```python
import torch

def _softmax(x, axis=-1):
    return torch.softmax(x, dim=axis)

def _gelu(x):
    return torch.nn.functional.gelu(x, approximate='tanh')

def _silu(x):
    return torch.nn.functional.silu(x)

def _sigmoid(x):
    return torch.sigmoid(x)

def _layernorm(x, axis=-1, eps=1e-05):
    m = x.mean(dim=axis, keepdim=True)
    v = x.var(dim=axis, keepdim=True, unbiased=False)
    return (x - m) / torch.sqrt(v + eps)

def _scatter_add(tgt, idx, src, axis=0):
    return tgt.clone().index_add_(axis, idx, src)

def _segment_sum(src, seg, n):
    out = torch.zeros((n,) + src.shape[1:], dtype=src.dtype)
    return out.index_add_(0, seg, src)

def _pad(x, pw):
    flat = tuple((v for pair in reversed(pw) for v in pair))
    return torch.nn.functional.pad(x, flat)
kernel_name = 'adaLN_cond__compressed_kv_cla__moe_arch_mod__prompt'

def setup_inputs():

    _w = lambda a: (lambda t: t.to(torch.bfloat16) if t.is_floating_point() else t)(torch.as_tensor(a))

    def _A_setup():
        B, H, Sq, Sk, D, M = (1, 32, 2048, 2048, 128, 512)
        Dc = 4 * D
        return {'x': _w((lambda *s: torch.randn(*s, dtype=torch.bfloat16) * 0.1)(B, Sq, M)), 'c_kv': _w((lambda *s: torch.randn(*s, dtype=torch.bfloat16) * 3.2)(B, Sk, Dc)), 'w_q': _w((lambda *s: torch.randn(*s, dtype=torch.bfloat16) * 0.8)(M, H, D) * M ** (-0.5)), 'w_uk': _w((lambda *s: torch.randn(*s, dtype=torch.bfloat16) * 0.8)(Dc, H, D) * Dc ** (-0.5)), 'w_uv': _w((lambda *s: torch.randn(*s, dtype=torch.bfloat16) * 3.2)(Dc, H, D) * Dc ** (-0.5)), 'w_o': _w((lambda *s: torch.randn(*s, dtype=torch.bfloat16) * 3.2)(H, D, M) * (H * D) ** (-0.5))}
    _A_in = _A_setup()

    def _B_setup():
        B, S, D, F, C = (1, 2048, 512, 1792, 1)
        return {'x': _w((lambda *s: torch.randn(*s, dtype=torch.bfloat16) * 0.1)(B, S, D)), 'w_r': _w((lambda *s: torch.randn(*s, dtype=torch.bfloat16) * 3.2)(D)), 'w_gate': _w((lambda *s: torch.randn(*s, dtype=torch.bfloat16) * 3.2)(D, F)), 'w_up': _w((lambda *s: torch.randn(*s, dtype=torch.bfloat16) * 3.2)(D, F)), 'w_down': _w((lambda *s: torch.randn(*s, dtype=torch.bfloat16) * 3.2)(F, D))}
    _B_in = _B_setup()
    return {'A_x': _A_in['x'], 'A_c_kv': _A_in['c_kv'], 'A_w_q': _A_in['w_q'], 'A_w_uk': _A_in['w_uk'], 'A_w_uv': _A_in['w_uv'], 'A_w_o': _A_in['w_o'], 'B_x': _B_in['x'], 'B_w_r': _B_in['w_r'], 'B_w_gate': _B_in['w_gate'], 'B_w_up': _B_in['w_up'], 'B_w_down': _B_in['w_down'], 'c': _w((lambda *s: torch.randn(*s, dtype=torch.bfloat16) * 0.2)(1, 512) * 8.0), 'w_mod': _w((lambda *s: torch.randn(*s, dtype=torch.bfloat16) * 0.2)(512, 6 * 512) * 512 ** (-0.5) * 8.0)}

def reference(A_x, A_c_kv, A_w_q, A_w_uk, A_w_uv, A_w_o, B_x, B_w_r, B_w_gate, B_w_up, B_w_down, c, w_mod):

    def _A_ref(x, c_kv, w_q, w_uk, w_uv, w_o):
        B, Sq, M = (x.shape[0], x.shape[1], x.shape[2])
        Sk = c_kv.shape[1]
        H, D = (w_q.shape[1], w_q.shape[2])
        q = torch.einsum('bqm,mhd->bhqd', x, w_q)
        k = torch.einsum('bkc,chd->bhkd', c_kv, w_uk)
        v = torch.einsum('bkc,chd->bhkd', c_kv, w_uv)
        scores = torch.einsum('bhqd,bhkd->bhqk', q, k) * D ** (-0.5)
        off = Sk - Sq
        qi = torch.arange(Sq)[:, None]
        kj = torch.arange(Sk)[None, :]
        cmask = kj <= qi + off
        scores = torch.where(cmask[None, None], scores, -1000000000.0)
        p = _softmax(scores, axis=-1)
        ctx = torch.einsum('bhqk,bhkd->bhqd', p, v)
        return torch.einsum('bhqd,hdm->bqm', ctx, w_o)

    def _B_ref(x, w_r, w_gate, w_up, w_down):
        B, S, D = x.shape
        C = 1
        r = x @ w_r
        idx = torch.argsort(-r, axis=-1)[:, :C]
        idx_e = (lambda x, n, axis: torch.repeat_interleave(x, n, dim=axis))(idx.reshape(B, C, 1), D, axis=2)
        x_sel = (lambda x, i, axis: torch.take_along_dim(x, i, dim=axis))(x, idx_e, axis=1)
        g = _silu(x_sel @ w_gate)
        u = x_sel @ w_up
        y = g * u @ w_down
        r_sel = _sigmoid((lambda x, i, axis: torch.take_along_dim(x, i, dim=axis))(r, idx, axis=1))
        y = y * r_sel.reshape(B, C, 1)
        b_off = (torch.arange(B) * S).reshape(B, 1)
        flat_idx = (idx + b_off).reshape(B * C)
        zero = (x * 0.0).reshape(B * S, D)
        upd = _scatter_add(zero, flat_idx, y.reshape(B * C, D), axis=0)
        return x + upd.reshape(B, S, D)
    x = A_x
    mod = (_silu(c) @ w_mod).reshape(c.shape[0], 6, 1, -1)
    sa, ca, ga, sb, cb, gb = (mod[:, 0].clone(), mod[:, 1].clone(), mod[:, 2].clone(), mod[:, 3].clone(), mod[:, 4].clone(), mod[:, 5].clone())
    h = _layernorm(x, axis=-1) * (1 + ca) + sa
    x = x + ga * _A_ref(h, A_c_kv, A_w_q, A_w_uk, A_w_uv, A_w_o)
    h = _layernorm(x, axis=-1) * (1 + cb) + sb
    x = x + gb * _B_ref(h, B_w_r, B_w_gate, B_w_up, B_w_down)
    return x
```

```cpp
#include <cuda.h>
#include <cuda_bf16.h>
#include <cuda_runtime.h>
#include <stdint.h>
#include <stdio.h>

namespace {

typedef __nv_bfloat16 bf16;
typedef unsigned long long u64;

constexpr int NCTA = 128, NSPARE = 4;
constexpr int SLOT = 32768;
constexpr int SM_BAR = 7 * SLOT;
constexpr int BAR_FULL = SM_BAR;
constexpr int BAR_EMPTY = BAR_FULL + 8 * 7;
constexpr int BAR_DONE = BAR_EMPTY + 8 * 7;
constexpr int BAR_FLAG = BAR_DONE + 8 * 9;
constexpr int BAR_PF = BAR_FLAG + 8 * 11;
constexpr int BAR_END = BAR_PF + 8;
constexpr int SM_EP = BAR_END + 8;
constexpr int SM_RED = SM_BAR + 384;
constexpr int SM_TAB = SM_BAR + 1024;
constexpr int SMEM_BYTES = SM_BAR + 3072;
constexpr int NFFN = 112;
#define HINT 29
constexpr u64 L2_NORMAL = 0x1000000000000000ull, L2_FIRST = 0x12F0000000000000ull;
#define PF0 0
#define PF1 13
#define PF2 11
#define EARLY 7
constexpr uint32_t SPIN_LIMIT = 1u << 22;
constexpr uint32_t ONE2 = 0x3f803f80u;

struct Sync {
    uint32_t modcnt[2 * 32];
    uint32_t hcnt[16 * 8];
    uint32_t kvcnt[32 * 2 * 8];
    uint32_t ctxcnt[16 * 32];
    uint32_t rdcnt[16 * 2 * 8];
    uint32_t epoch[32];
};

__device__ __align__(1024) uint8_t g_KV[16 * 16 * 2 * SLOT];
__device__ __align__(1024) uint8_t g_ctx[16 * 32 * SLOT];
__device__ __align__(1024) uint8_t g_h[16 * 4 * SLOT];
__device__ __align__(1024) uint4 g_part[128 * 1024];
__device__ __align__(1024) uint4 g_stat[2048 * 4];
__device__ __align__(1024) bf16 g_mod[3072];
__device__ __align__(1024) uint4 g_cand[128 * 192];
__device__ __align__(1024) uint32_t g_key[4 * 128];
__device__ __align__(1024) uint32_t g_act[1792];
__device__ __align__(1024) Sync g_sync;
#define TS(i)

#define PT()

struct Params {
    const bf16 *x, *ckv, *wo, *wr, *wgate, *wup, *wdown, *c;
    bf16* out;
    int by_smid;
};

__device__ __forceinline__ void mbar_init(uint32_t bar, uint32_t cnt) {
    asm volatile("mbarrier.init.shared::cta.b64 [%0], %1;" ::"r"(bar), "r"(cnt) : "memory");
}
__device__ __forceinline__ void mbar_wait(uint32_t bar, uint32_t parity) {
    asm volatile("{\n.reg .pred p;\nL_%=:\nmbarrier.try_wait.parity.shared::cta.b64 p, [%0], %1;\n@!p bra L_%=;\n}" ::"r"(bar), "r"(parity) : "memory");
}
__device__ __forceinline__ void mbar_watch(uint32_t bar, uint32_t parity) {
    asm volatile("{\n.reg .pred p;\n.reg .u32 n;\nmov.u32 n, 0;\n"
                 "L_%=:\nmbarrier.try_wait.parity.shared::cta.b64 p, [%0], %1;\n@p bra D_%=;\n"
                 "add.u32 n, n, 1;\nsetp.lt.u32 p, n, %2;\n@p bra L_%=;\ntrap;\nD_%=:\n}"
                 ::"r"(bar), "r"(parity), "n"(SPIN_LIMIT) : "memory");
}
__device__ __forceinline__ void mbar_arrive(uint32_t bar) {
    asm volatile("mbarrier.arrive.shared::cta.b64 _, [%0];" ::"r"(bar) : "memory");
}
__device__ __forceinline__ void mbar_arrive_if(uint32_t bar, bool on) {
    asm volatile("{\n.reg .pred p;\nsetp.ne.s32 p, %1, 0;\n@p mbarrier.arrive.shared::cta.b64 _, [%0];\n}" ::"r"(bar), "r"((int)on) : "memory");
}
__device__ __forceinline__ void mbar_expect(uint32_t bar, uint32_t bytes) {
    asm volatile("mbarrier.arrive.expect_tx.shared::cta.b64 _, [%0], %1;" ::"r"(bar), "r"(bytes) : "memory");
}
__device__ __forceinline__ void tma2d(uint32_t dst, const CUtensorMap* m, int c0, int c1, uint32_t bar) {
    asm volatile("cp.async.bulk.tensor.2d.shared::cluster.global.mbarrier::complete_tx::bytes [%0], [%1, {%3, %4}], [%2];"
                 ::"r"(dst), "l"(m), "r"(bar), "r"(c0), "r"(c1) : "memory");
}
__device__ __forceinline__ void tma3d_prefetch(const CUtensorMap* m, int row, int cb) {
    asm volatile("cp.async.bulk.prefetch.tensor.3d.L2.global [%0, {%1, %2, %3}];" ::"l"(m), "r"(0), "r"(row), "r"(cb) : "memory");
}
__device__ __forceinline__ void l2_prefetch(const void* p, uint32_t bytes) {
    asm volatile("cp.async.bulk.prefetch.L2.global [%0], %1;" ::"l"(p), "r"(bytes) : "memory");
}
__device__ __forceinline__ void flag_wait(const uint32_t* f, uint32_t target) {
    asm volatile("{\n.reg .pred p;\n.reg .u32 v;\n"
                 "L_%=:\nld.acquire.gpu.global.u32 v, [%0];\nsub.u32 v, v, %1;\nsetp.lt.s32 p, v, 0;\n@p nanosleep.u32 100;\n@p bra L_%=;\n}"
                 ::"l"(f), "r"(target) : "memory");
}
__device__ __forceinline__ uint4 ld_poll(const uint4* p) {
    uint4 v;
    asm volatile("ld.relaxed.gpu.global.v4.u32 {%0, %1, %2, %3}, [%4];" : "=r"(v.x), "=r"(v.y), "=r"(v.z), "=r"(v.w) : "l"(p) : "memory");
    return v;
}
__device__ __forceinline__ uint2 ld_poll(const uint2* p) {
    uint2 v;
    asm volatile("ld.relaxed.gpu.global.v2.u32 {%0, %1}, [%2];" : "=r"(v.x), "=r"(v.y) : "l"(p) : "memory");
    return v;
}
__device__ __forceinline__ void st_pub(uint4* p, uint4 v, bool on) {
    asm volatile("{\n.reg .pred p;\nsetp.ne.s32 p, %5, 0;\n@p st.relaxed.gpu.global.v4.u32 [%0], {%1, %2, %3, %4};\n}"
                 ::"l"(p), "r"(v.x), "r"(v.y), "r"(v.z), "r"(v.w), "r"((int)on) : "memory");
}
__device__ __forceinline__ void st_pub(uint32_t* p, uint32_t v, bool on) {
    asm volatile("{\n.reg .pred p;\nsetp.ne.s32 p, %2, 0;\n@p st.relaxed.gpu.global.u32 [%0], %1;\n}" ::"l"(p), "r"(v), "r"((int)on) : "memory");
}
__device__ __forceinline__ void flag_add(uint32_t* p) {
    asm volatile("red.release.gpu.global.add.u32 [%0], 1;" ::"l"(p) : "memory");
}
__device__ __forceinline__ uint32_t lds32(uint32_t a) {
    uint32_t v;
    asm volatile("ld.shared.u32 %0, [%1];" : "=r"(v) : "r"(a) : "memory");
    return v;
}
__device__ __forceinline__ void fence_async_global() { asm volatile("fence.proxy.async.global;" ::: "memory"); }
__device__ __forceinline__ void fence_async_smem() { asm volatile("fence.proxy.async.shared::cta;" ::: "memory"); }
__device__ __forceinline__ void bar_sync(int id, int n) { asm volatile("bar.sync %0, %1;" ::"r"(id), "r"(n) : "memory"); }
__device__ __forceinline__ void bar_arrive(int id, int n) { asm volatile("bar.arrive %0, %1;" ::"r"(id), "r"(n) : "memory"); }
__device__ __forceinline__ void wg_fence() { asm volatile("wgmma.fence.sync.aligned;" ::: "memory"); }
__device__ __forceinline__ void wg_commit() { asm volatile("wgmma.commit_group.sync.aligned;" ::: "memory"); }
template <int N> __device__ __forceinline__ void wg_wait() { asm volatile("wgmma.wait_group.sync.aligned %0;" ::"n"(N) : "memory"); }
template <int N> __device__ __forceinline__ void reg_fence(float (&d)[N]) {
#pragma unroll
    for (int i = 0; i < N; i++) asm volatile("" : "+f"(d[i])::"memory");
}
template <int N> __device__ __forceinline__ void reg_fence(uint32_t (&d)[N]) {
#pragma unroll
    for (int i = 0; i < N; i++) asm volatile("" : "+r"(d[i])::"memory");
}
__device__ __forceinline__ uint32_t desc_k(uint32_t a) { return (a >> 4) | (1u << 16); }
__device__ __forceinline__ uint32_t desc_mn(uint32_t a) { return (a >> 4) | (1024u << 16); }

template <int TB>
__device__ __forceinline__ void wgmma_ss128(float (&d)[64], uint32_t da, uint32_t db, int acc) {
    asm volatile("{\n.reg .pred p;\n.reg .b64 a, b;\nsetp.ne.b32 p, %66, 0;\nmov.b64 a, {%64, 0x40000040};\nmov.b64 b, {%65, 0x40000040};\n"
        "wgmma.mma_async.sync.aligned.m64n128k16.f32.bf16.bf16 {%0, %1, %2, %3, %4, %5, %6, %7, %8, %9, %10, %11, %12, %13, %14, %15, %16, %17, %18, %19, %20, %21, %22, %23, %24, %25, %26, %27, %28, %29, %30, %31, %32, %33, %34, %35, %36, %37, %38, %39, %40, %41, %42, %43, %44, %45, %46, %47, %48, %49, %50, %51, %52, %53, %54, %55, %56, %57, %58, %59, %60, %61, %62, %63}, a, b, p, 1, 1, 0, %67;\n}"
        : "+f"(d[0]), "+f"(d[1]), "+f"(d[2]), "+f"(d[3]), "+f"(d[4]), "+f"(d[5]), "+f"(d[6]), "+f"(d[7]), "+f"(d[8]), "+f"(d[9]), "+f"(d[10]), "+f"(d[11]), "+f"(d[12]), "+f"(d[13]), "+f"(d[14]), "+f"(d[15]), "+f"(d[16]), "+f"(d[17]), "+f"(d[18]), "+f"(d[19]), "+f"(d[20]), "+f"(d[21]), "+f"(d[22]), "+f"(d[23]), "+f"(d[24]), "+f"(d[25]), "+f"(d[26]), "+f"(d[27]), "+f"(d[28]), "+f"(d[29]), "+f"(d[30]), "+f"(d[31]), "+f"(d[32]), "+f"(d[33]), "+f"(d[34]), "+f"(d[35]), "+f"(d[36]), "+f"(d[37]), "+f"(d[38]), "+f"(d[39]), "+f"(d[40]), "+f"(d[41]), "+f"(d[42]), "+f"(d[43]), "+f"(d[44]), "+f"(d[45]), "+f"(d[46]), "+f"(d[47]), "+f"(d[48]), "+f"(d[49]), "+f"(d[50]), "+f"(d[51]), "+f"(d[52]), "+f"(d[53]), "+f"(d[54]), "+f"(d[55]), "+f"(d[56]), "+f"(d[57]), "+f"(d[58]), "+f"(d[59]), "+f"(d[60]), "+f"(d[61]), "+f"(d[62]), "+f"(d[63])
        : "r"(da), "r"(db), "r"(acc), "n"(TB));
}
template <int TB>
__device__ __forceinline__ void wgmma_ss128_init(float (&d)[64], uint32_t da, uint32_t db) {
    asm volatile("{\n.reg .pred p;\n.reg .b64 a, b;\nsetp.ne.b32 p, 0, 0;\nmov.b64 a, {%64, 0x40000040};\nmov.b64 b, {%65, 0x40000040};\n"
        "wgmma.mma_async.sync.aligned.m64n128k16.f32.bf16.bf16 {%0, %1, %2, %3, %4, %5, %6, %7, %8, %9, %10, %11, %12, %13, %14, %15, %16, %17, %18, %19, %20, %21, %22, %23, %24, %25, %26, %27, %28, %29, %30, %31, %32, %33, %34, %35, %36, %37, %38, %39, %40, %41, %42, %43, %44, %45, %46, %47, %48, %49, %50, %51, %52, %53, %54, %55, %56, %57, %58, %59, %60, %61, %62, %63}, a, b, p, 1, 1, 0, %66;\n}"
        : "=f"(d[0]), "=f"(d[1]), "=f"(d[2]), "=f"(d[3]), "=f"(d[4]), "=f"(d[5]), "=f"(d[6]), "=f"(d[7]), "=f"(d[8]), "=f"(d[9]), "=f"(d[10]), "=f"(d[11]), "=f"(d[12]), "=f"(d[13]), "=f"(d[14]), "=f"(d[15]), "=f"(d[16]), "=f"(d[17]), "=f"(d[18]), "=f"(d[19]), "=f"(d[20]), "=f"(d[21]), "=f"(d[22]), "=f"(d[23]), "=f"(d[24]), "=f"(d[25]), "=f"(d[26]), "=f"(d[27]), "=f"(d[28]), "=f"(d[29]), "=f"(d[30]), "=f"(d[31]), "=f"(d[32]), "=f"(d[33]), "=f"(d[34]), "=f"(d[35]), "=f"(d[36]), "=f"(d[37]), "=f"(d[38]), "=f"(d[39]), "=f"(d[40]), "=f"(d[41]), "=f"(d[42]), "=f"(d[43]), "=f"(d[44]), "=f"(d[45]), "=f"(d[46]), "=f"(d[47]), "=f"(d[48]), "=f"(d[49]), "=f"(d[50]), "=f"(d[51]), "=f"(d[52]), "=f"(d[53]), "=f"(d[54]), "=f"(d[55]), "=f"(d[56]), "=f"(d[57]), "=f"(d[58]), "=f"(d[59]), "=f"(d[60]), "=f"(d[61]), "=f"(d[62]), "=f"(d[63])
        : "r"(da), "r"(db), "n"(TB));
}
template <int TB>
__device__ __forceinline__ void wgmma_ss64(float (&d)[32], uint32_t da, uint32_t db, int acc) {
    asm volatile("{\n.reg .pred p;\n.reg .b64 a, b;\nsetp.ne.b32 p, %34, 0;\nmov.b64 a, {%32, 0x40000040};\nmov.b64 b, {%33, 0x40000040};\n"
        "wgmma.mma_async.sync.aligned.m64n64k16.f32.bf16.bf16 {%0, %1, %2, %3, %4, %5, %6, %7, %8, %9, %10, %11, %12, %13, %14, %15, %16, %17, %18, %19, %20, %21, %22, %23, %24, %25, %26, %27, %28, %29, %30, %31}, a, b, p, 1, 1, 0, %35;\n}"
        : "+f"(d[0]), "+f"(d[1]), "+f"(d[2]), "+f"(d[3]), "+f"(d[4]), "+f"(d[5]), "+f"(d[6]), "+f"(d[7]), "+f"(d[8]), "+f"(d[9]), "+f"(d[10]), "+f"(d[11]), "+f"(d[12]), "+f"(d[13]), "+f"(d[14]), "+f"(d[15]), "+f"(d[16]), "+f"(d[17]), "+f"(d[18]), "+f"(d[19]), "+f"(d[20]), "+f"(d[21]), "+f"(d[22]), "+f"(d[23]), "+f"(d[24]), "+f"(d[25]), "+f"(d[26]), "+f"(d[27]), "+f"(d[28]), "+f"(d[29]), "+f"(d[30]), "+f"(d[31])
        : "r"(da), "r"(db), "r"(acc), "n"(TB));
}
template <int TB>
__device__ __forceinline__ void wgmma_ss64_init(float (&d)[32], uint32_t da, uint32_t db) {
    asm volatile("{\n.reg .pred p;\n.reg .b64 a, b;\nsetp.ne.b32 p, 0, 0;\nmov.b64 a, {%32, 0x40000040};\nmov.b64 b, {%33, 0x40000040};\n"
        "wgmma.mma_async.sync.aligned.m64n64k16.f32.bf16.bf16 {%0, %1, %2, %3, %4, %5, %6, %7, %8, %9, %10, %11, %12, %13, %14, %15, %16, %17, %18, %19, %20, %21, %22, %23, %24, %25, %26, %27, %28, %29, %30, %31}, a, b, p, 1, 1, 0, %34;\n}"
        : "=f"(d[0]), "=f"(d[1]), "=f"(d[2]), "=f"(d[3]), "=f"(d[4]), "=f"(d[5]), "=f"(d[6]), "=f"(d[7]), "=f"(d[8]), "=f"(d[9]), "=f"(d[10]), "=f"(d[11]), "=f"(d[12]), "=f"(d[13]), "=f"(d[14]), "=f"(d[15]), "=f"(d[16]), "=f"(d[17]), "=f"(d[18]), "=f"(d[19]), "=f"(d[20]), "=f"(d[21]), "=f"(d[22]), "=f"(d[23]), "=f"(d[24]), "=f"(d[25]), "=f"(d[26]), "=f"(d[27]), "=f"(d[28]), "=f"(d[29]), "=f"(d[30]), "=f"(d[31])
        : "r"(da), "r"(db), "n"(TB));
}
__device__ __forceinline__ void wgmma_rs128(float (&d)[64], uint32_t a0, uint32_t a1, uint32_t a2, uint32_t a3, uint32_t db, int acc) {
    asm volatile("{\n.reg .pred p;\n.reg .b64 b;\nsetp.ne.b32 p, %69, 0;\nmov.b64 b, {%68, 0x40000040};\n"
        "wgmma.mma_async.sync.aligned.m64n128k16.f32.bf16.bf16 {%0, %1, %2, %3, %4, %5, %6, %7, %8, %9, %10, %11, %12, %13, %14, %15, %16, %17, %18, %19, %20, %21, %22, %23, %24, %25, %26, %27, %28, %29, %30, %31, %32, %33, %34, %35, %36, %37, %38, %39, %40, %41, %42, %43, %44, %45, %46, %47, %48, %49, %50, %51, %52, %53, %54, %55, %56, %57, %58, %59, %60, %61, %62, %63}, {%64, %65, %66, %67}, b, p, 1, 1, 1;\n}"
        : "+f"(d[0]), "+f"(d[1]), "+f"(d[2]), "+f"(d[3]), "+f"(d[4]), "+f"(d[5]), "+f"(d[6]), "+f"(d[7]), "+f"(d[8]), "+f"(d[9]), "+f"(d[10]), "+f"(d[11]), "+f"(d[12]), "+f"(d[13]), "+f"(d[14]), "+f"(d[15]), "+f"(d[16]), "+f"(d[17]), "+f"(d[18]), "+f"(d[19]), "+f"(d[20]), "+f"(d[21]), "+f"(d[22]), "+f"(d[23]), "+f"(d[24]), "+f"(d[25]), "+f"(d[26]), "+f"(d[27]), "+f"(d[28]), "+f"(d[29]), "+f"(d[30]), "+f"(d[31]), "+f"(d[32]), "+f"(d[33]), "+f"(d[34]), "+f"(d[35]), "+f"(d[36]), "+f"(d[37]), "+f"(d[38]), "+f"(d[39]), "+f"(d[40]), "+f"(d[41]), "+f"(d[42]), "+f"(d[43]), "+f"(d[44]), "+f"(d[45]), "+f"(d[46]), "+f"(d[47]), "+f"(d[48]), "+f"(d[49]), "+f"(d[50]), "+f"(d[51]), "+f"(d[52]), "+f"(d[53]), "+f"(d[54]), "+f"(d[55]), "+f"(d[56]), "+f"(d[57]), "+f"(d[58]), "+f"(d[59]), "+f"(d[60]), "+f"(d[61]), "+f"(d[62]), "+f"(d[63])
        : "r"(a0), "r"(a1), "r"(a2), "r"(a3), "r"(db), "r"(acc));
}

__device__ __forceinline__ uint32_t pack2(float lo, float hi) {
    uint32_t r;
    asm("cvt.rn.bf16x2.f32 %0, %1, %2;" : "=r"(r) : "f"(hi), "f"(lo));
    return r;
}
__device__ __forceinline__ float bf_lo(uint32_t v) { return __uint_as_float(v << 16); }
__device__ __forceinline__ float bf_hi(uint32_t v) { return __uint_as_float(v & 0xffff0000u); }
__device__ __forceinline__ float rbf(float v) { return bf_lo(pack2(v, v)); }
__device__ __forceinline__ uint32_t badd(uint32_t a, uint32_t b) {
    uint32_t r;
    asm("add.rn.bf16x2 %0, %1, %2;" : "=r"(r) : "r"(a), "r"(b));
    return r;
}
__device__ __forceinline__ uint32_t bsub(uint32_t a, uint32_t b) {
    uint32_t r;
    asm("sub.rn.bf16x2 %0, %1, %2;" : "=r"(r) : "r"(a), "r"(b));
    return r;
}
__device__ __forceinline__ uint32_t bmul(uint32_t a, uint32_t b) {
    uint32_t r;
    asm("mul.rn.bf16x2 %0, %1, %2;" : "=r"(r) : "r"(a), "r"(b));
    return r;
}
__device__ __forceinline__ uint32_t ln_apply(uint32_t x, uint32_t mb, float rs, uint32_t scale, uint32_t shift) {
    const uint32_t d = bsub(x, mb);
    return badd(bmul(pack2(bf_lo(d) * rs, bf_hi(d) * rs), scale), shift);
}
__device__ __forceinline__ float ex2(float v) {
    float r;
    asm("ex2.approx.ftz.f32 %0, %1;" : "=f"(r) : "f"(v));
    return r;
}
__device__ __forceinline__ float rcp(float v) {
    float r;
    asm("rcp.approx.ftz.f32 %0, %1;" : "=f"(r) : "f"(v));
    return r;
}
__device__ __forceinline__ float sqrt_fast(float v) {
    float r;
    asm("sqrt.approx.ftz.f32 %0, %1;" : "=f"(r) : "f"(v));
    return r;
}
__device__ __forceinline__ float ln_rstd(float var) { return rcp(rbf(sqrt_fast(rbf(rbf(var) + 1e-5f)))); }
__device__ __forceinline__ float sigmoid(float v) { return rcp(1.f + ex2(-1.4426950408889634f * v)); }
__device__ __forceinline__ float warp_sum(float v) {
#pragma unroll
    for (int o = 16; o > 0; o >>= 1) v += __shfl_xor_sync(0xffffffffu, v, o);
    return v;
}
__device__ __forceinline__ float quad_sum(float v) {
    v += __shfl_xor_sync(0xffffffffu, v, 1);
    return v + __shfl_xor_sync(0xffffffffu, v, 2);
}

template <int M, int RH>
__device__ __forceinline__ uint4 img_pack(const float (&d)[64], float s) {
    uint4 v;
    v.x = pack2(d[16 * M + 2 * RH] * s, d[16 * M + 2 * RH + 1] * s);
    v.y = pack2(d[16 * M + 4 + 2 * RH] * s, d[16 * M + 5 + 2 * RH] * s);
    v.z = pack2(d[16 * M + 8 + 2 * RH] * s, d[16 * M + 9 + 2 * RH] * s);
    v.w = pack2(d[16 * M + 12 + 2 * RH] * s, d[16 * M + 13 + 2 * RH] * s);
    return v;
}
template <int M, int RH>
__device__ __forceinline__ uint4 img_pack(const float (&d)[64]) {
    uint4 v;
    v.x = pack2(d[16 * M + 2 * RH], d[16 * M + 2 * RH + 1]);
    v.y = pack2(d[16 * M + 4 + 2 * RH], d[16 * M + 5 + 2 * RH]);
    v.z = pack2(d[16 * M + 8 + 2 * RH], d[16 * M + 9 + 2 * RH]);
    v.w = pack2(d[16 * M + 12 + 2 * RH], d[16 * M + 13 + 2 * RH]);
    return v;
}
template <int M, int RH>
__device__ __forceinline__ uint32_t img_off(uint32_t toff) { return (toff ^ ((M & 1) * 64)) + (M >> 1) * 16384 + RH * 1024; }
template <int M>
__device__ __forceinline__ void img_store_global(uint8_t* img, uint32_t toff, const float (&d)[64]) {
    uint4* p = reinterpret_cast<uint4*>(img + (toff ^ ((M & 1) * 64)));
    p[(M >> 1) * 1024] = img_pack<M, 0>(d);
    p[(M >> 1) * 1024 + 64] = img_pack<M, 1>(d);
}
__device__ __forceinline__ void sts128(uint32_t a, uint4 v) {
    asm volatile("st.shared.v4.b32 [%0], {%1, %2, %3, %4};" ::"r"(a), "r"(v.x), "r"(v.y), "r"(v.z), "r"(v.w) : "memory");
}
constexpr float SM_C = 0.08838834764831845f * 1.4426950408889634f;
template <int M>
__device__ __forceinline__ void q_store(uint32_t a, uint32_t toff, const float (&d)[64]) {
    sts128(a + img_off<M, 0>(toff), img_pack<M, 0>(d, SM_C));
    sts128(a + img_off<M, 1>(toff), img_pack<M, 1>(d, SM_C));
}
__device__ __forceinline__ void ctx_store(uint8_t* img, uint32_t toff, const float (&o)[64], float l0, float l1) {
    const float i0 = rcp(quad_sum(l0)), i1 = rcp(quad_sum(l1));
    asm volatile("" : "+r"(toff));
    uint4 *p0 = reinterpret_cast<uint4*>(img + toff), *p1 = reinterpret_cast<uint4*>(img + (toff ^ 64));
    p0[0] = img_pack<0, 0>(o, i0);
    p1[0] = img_pack<1, 0>(o, i0);
    p0[64] = img_pack<0, 1>(o, i1);
    p1[64] = img_pack<1, 1>(o, i1);
    p0[1024] = img_pack<2, 0>(o, i0);
    p1[1024] = img_pack<3, 0>(o, i0);
    p0[1088] = img_pack<2, 1>(o, i1);
    p1[1088] = img_pack<3, 1>(o, i1);
}

__device__ __forceinline__ void slot_wait(uint32_t bars, uint32_t& ph, uint32_t slot) {
    mbar_wait(bars + 8 * slot, (ph >> slot) & 1);
    ph ^= 1u << slot;
}
__device__ __forceinline__ void load_image(uint32_t sb, uint32_t& ph, uint32_t slot, const void* src, bool first) {
    slot_wait(sb + BAR_EMPTY, ph, slot);
    asm volatile("{\n.reg .pred p;\nelect.sync _|p, 0xffffffff;\n@p mbarrier.arrive.expect_tx.shared::cta.b64 _, [%2], 32768;\n"
                 "@p cp.async.bulk.shared::cluster.global.mbarrier::complete_tx::bytes.L2::cache_hint [%0], [%1], 32768, [%2], %3;\n}"
                 ::"r"(sb + slot * SLOT), "l"(src), "r"(sb + BAR_FULL + 8 * slot), "l"(first ? L2_FIRST : L2_NORMAL) : "memory");
}
__device__ __forceinline__ void load_tile(uint32_t sb, uint32_t& ph, uint32_t slot, const CUtensorMap* m, int row, int cb, bool first) {
    slot_wait(sb + BAR_EMPTY, ph, slot);
    asm volatile("{\n.reg .pred p;\nelect.sync _|p, 0xffffffff;\n@p mbarrier.arrive.expect_tx.shared::cta.b64 _, [%2], 32768;\n"
                 "@p cp.async.bulk.tensor.3d.shared::cluster.global.mbarrier::complete_tx::bytes.L2::cache_hint [%0], [%1, {%3, %4, %5}], [%2], %6;\n}"
                 ::"r"(sb + slot * SLOT), "l"(m), "r"(sb + BAR_FULL + 8 * slot), "r"(0), "r"(row), "r"(cb), "l"(first ? L2_FIRST : L2_NORMAL) : "memory");
}
__device__ __forceinline__ uint32_t ring_next(uint32_t r) { return r == 4 ? 0 : r + 1; }
__device__ __forceinline__ uint32_t w_table(int hp) { return hp ? 0x3104u : 0x4210u; }
__device__ __forceinline__ uint32_t a_table(int hp) { return hp ? 0x625u : 0x635u; }
__device__ __forceinline__ uint32_t a_next(uint32_t& t) {
    const uint32_t s = t & 15;
    t = (t >> 4) | (s << 8);
    return s;
}
constexpr uint32_t O_TABLE = 0x2160435u;
__device__ __forceinline__ uint32_t o_next(uint32_t& t) {
    const uint32_t s = t & 15;
    t = (t >> 4) | (s << 24);
    return s;
}
__device__ __forceinline__ int o_head(int i, int kh) { return i < 16 ? 4 * (i & 7) + 2 * (kh ^ 1) + (i >> 3) : 29 + 2 * kh; }

__device__ __forceinline__ void gemm_issue(float (&d)[64], uint32_t a, uint32_t b, int acc) {
    wg_fence();
#pragma unroll
    for (int k = 0; k < 8; k++) wgmma_ss128<1>(d, a + (k >> 2) * 1024 + (k & 3) * 2, b + k * 128, k ? 1 : acc);
    wg_commit();
}

template <bool ODD>
__device__ __forceinline__ void proj_tile(float (&acc)[64], float (&prev)[64], int t, uint32_t sb, int wg, bool elected, uint32_t& fph,
                                          uint32_t wtab, uint32_t& atab, uint8_t* prev_img, uint32_t toff, bool first,
                                          const bf16* x, int xrow) {
    const uint32_t a0 = desc_k(sb + (wg ^ (ODD && t == 5)) * 8192), b0 = desc_mn(sb);
    const int lane = threadIdx.x & 31;
    uint4 mv[4];
#pragma unroll
    for (int i = 0; i < 4; i++) mv[i] = make_uint4(0, 0, 0, 0);
    uint32_t xn[16];
#pragma unroll
    for (int i = 0; i < 4; i++) {
        uint4 v = make_uint4(0, 0, 0, 0);
        if (ODD && first) v = __ldg(reinterpret_cast<const uint4*>(x) + xrow * 64 + lane + 32 * i);
        xn[4 * i] = v.x; xn[4 * i + 1] = v.y; xn[4 * i + 2] = v.z; xn[4 * i + 3] = v.w;
    }
#pragma unroll 1
    for (int q = 0; q < 4; q++) {
        const uint32_t ws = (wtab >> (4 * q)) & 15, as = a_next(atab);
        if (!ODD && t != 2) slot_wait(sb + BAR_FULL, fph, ws);
        slot_wait(sb + BAR_FULL, fph, as);
        bar_sync(1 + wg, 256);
        gemm_issue(acc, a0 + as * (SLOT / 16), b0 + ws * (SLOT / 16), q);
        bar_arrive(2 - wg, 256);
        wg_wait<1>();
        reg_fence(prev);
        if (ODD && t == 5) {
            if (q == 2) { q_store<0>(sb + 5 * SLOT, toff ^ 8192, prev); q_store<1>(sb + 5 * SLOT, toff ^ 8192, prev); }
            if (q == 3) { q_store<2>(sb + 5 * SLOT, toff ^ 8192, prev); q_store<3>(sb + 5 * SLOT, toff ^ 8192, prev); fence_async_smem(); }
        } else if (ODD || t != 0) {
            if (q == 0) img_store_global<0>(prev_img, toff, prev);
            if (q == 1) img_store_global<1>(prev_img, toff, prev);
            if (q == 2) img_store_global<2>(prev_img, toff, prev);
            if (q == 3) img_store_global<3>(prev_img, toff, prev);
        }
        if (ODD && q == 1 && first) {
            mbar_wait(sb + BAR_FLAG + 8 * 8, 0);
#pragma unroll
            for (int i = 0; i < 4; i++) mv[i] = __ldcg(reinterpret_cast<const uint4*>(g_mod) + lane + 32 * i);
        }
        wg_wait<0>();
        mbar_arrive_if(sb + BAR_EMPTY + 8 * as, elected && !(ODD && (q & 1) && t == 5));
        if (ODD) mbar_arrive_if(sb + BAR_EMPTY + 8 * ws, elected && t != 1);
        if (ODD && q == 0 && first) {
            float sum[2] = {0.f, 0.f}, sq[2] = {0.f, 0.f};
#pragma unroll
            for (int k = 0; k < 16; k++) sum[k >> 3] += bf_lo(xn[k]) + bf_hi(xn[k]);
#pragma unroll
            for (int i = 0; i < 2; i++) sum[i] = warp_sum(sum[i]) * (1.f / 512.f);
#pragma unroll
            for (int k = 0; k < 16; k++) {
                const float d0 = bf_lo(xn[k]) - sum[k >> 3], d1 = bf_hi(xn[k]) - sum[k >> 3];
                sq[k >> 3] = fmaf(d0, d0, fmaf(d1, d1, sq[k >> 3]));
            }
#pragma unroll
            for (int i = 0; i < 2; i++) sq[i] = ln_rstd(warp_sum(sq[i]) * (1.f / 512.f));
#pragma unroll
            for (int k = 0; k < 16; k++) {
                const uint32_t d = bsub(xn[k], pack2(sum[k >> 3], sum[k >> 3]));
                xn[k] = pack2(bf_lo(d) * sq[k >> 3], bf_hi(d) * sq[k >> 3]);
            }
        }
        if (ODD && q == 2 && first) {
#pragma unroll
            for (int i = 0; i < 4; i++) {
                const int rin = (xrow + (i >> 1)) & 127;
                const uint4 a = mv[2 + (i & 1)], c = mv[i & 1];
                *reinterpret_cast<uint4*>(g_h + ((xrow >> 7) * 8 + (i & 1) * 4 + (lane >> 3)) * 16384 + rin * 128 + (((lane ^ rin) & 7) << 4)) =
                    make_uint4(badd(bmul(xn[4 * i], badd(a.x, ONE2)), c.x), badd(bmul(xn[4 * i + 1], badd(a.y, ONE2)), c.y),
                               badd(bmul(xn[4 * i + 2], badd(a.z, ONE2)), c.z), badd(bmul(xn[4 * i + 3], badd(a.w, ONE2)), c.w));
            }
            __syncwarp();
            mbar_arrive_if(sb + BAR_DONE, lane == 0);
        }
    }
    reg_fence(acc);
}

__device__ __forceinline__ void qk_issue(float (&s)[64], uint32_t q, uint32_t k) {
    wg_fence();
    wgmma_ss128_init<0>(s, q, k);
#pragma unroll
    for (int i = 1; i < 8; i++) wgmma_ss128<0>(s, q + (i >> 2) * 1024 + (i & 3) * 2, k + (i >> 2) * 1024 + (i & 3) * 2, 1);
    wg_commit();
}
__device__ __forceinline__ void qk_issue(float (&s)[32], uint32_t q, uint32_t k) {
    wg_fence();
    wgmma_ss64_init<0>(s, q, k);
#pragma unroll
    for (int i = 1; i < 8; i++) wgmma_ss64<0>(s, q + (i >> 2) * 1024 + (i & 3) * 2, k + (i >> 2) * 1024 + (i & 3) * 2, 1);
    wg_commit();
}
__device__ __forceinline__ void pv_issue(float (&o)[64], const uint32_t (&p)[32], uint32_t v, int acc, bool half) {
    if (half) {
        asm volatile("// half" ::: "memory");
        wg_fence();
#pragma unroll
        for (int i = 0; i < 4; i++) wgmma_rs128(o, p[4 * i], p[4 * i + 1], p[4 * i + 2], p[4 * i + 3], v + i * 128, i ? 1 : acc);
        wg_commit();
        asm volatile("// half" ::: "memory");
    } else {
        wg_fence();
#pragma unroll
        for (int i = 0; i < 8; i++) wgmma_rs128(o, p[4 * i], p[4 * i + 1], p[4 * i + 2], p[4 * i + 3], v + i * 128, i ? 1 : acc);
        wg_commit();
    }
}
template <int B, int N>
__device__ __forceinline__ void tri_mask(float (&s)[N], int x) {
#pragma unroll
    for (int k = 0; k < 7; k++)
        asm("{\n.reg .pred p, q;\nsetp.lt.s32 p, %4, %5;\nsetp.le.s32 q, %4, %5;\n"
            "@p mov.b32 %0, 0fFF800000;\n@q mov.b32 %1, 0fFF800000;\n@p mov.b32 %2, 0fFF800000;\n@q mov.b32 %3, 0fFF800000;\n}"
            : "+f"(s[B + 4 * k]), "+f"(s[B + 4 * k + 1]), "+f"(s[B + 4 * k + 6]), "+f"(s[B + 4 * k + 7]) : "r"(x), "r"(8 * k));
    asm("{\n.reg .pred p, q;\nsetp.lt.s32 p, %2, 56;\nsetp.le.s32 q, %2, 56;\n@p mov.b32 %0, 0fFF800000;\n@q mov.b32 %1, 0fFF800000;\n}"
        : "+f"(s[B + 28]), "+f"(s[B + 29]) : "r"(x));
}
__device__ __forceinline__ void tri_mask_copy(float (&s)[64], const float (&h)[32], int x) {
#pragma unroll
    for (int i = 0; i < 32; i++) {
        asm("{\n.reg .pred p;\nsetp.lt.s32 p, %2, %3;\nselp.f32 %0, 0fFF800000, %1, p;\n}"
            : "=f"(s[i]) : "f"(h[i]), "r"(x), "r"(8 * (i >> 2) - 4 * (i & 2) + (i & 1)));
        s[32 + i] = __uint_as_float(0xff800000u);
    }
}
constexpr float SM_HI = 1152921504606846976.f, SM_LO = 1.f / 1152921504606846976.f;
__device__ __forceinline__ bool softmax_unsafe(float t0, float t1, bool first) {
    bool bad = __any_sync(0xffffffffu, fmaxf(t0, t1) > SM_HI);
    if (first) {
        uint32_t a = __ballot_sync(0xffffffffu, t0 >= SM_LO), b = __ballot_sync(0xffffffffu, t1 >= SM_LO);
        a |= a >> 1;
        b |= b >> 1;
        bad |= ((a | (a >> 2)) & (b | (b >> 2)) & 0x11111111u) != 0x11111111u;
    }
    return bad;
}
__device__ __forceinline__ void softmax_shift(float (&s)[64], float d0, float d1) {
#pragma unroll
    for (int i = 0; i < 64; i++) s[i] -= (i & 2) ? d1 : d0;
}
__device__ __forceinline__ void softmax_remax(float (&s)[64], float (&m)[2], bool first, float& a0, float& a1) {
    float m0 = fmaxf(s[0], s[1]), m1 = fmaxf(s[2], s[3]);
#pragma unroll
    for (int k = 1; k < 16; k++) {
        m0 = fmaxf(m0, fmaxf(s[4 * k], s[4 * k + 1]));
        m1 = fmaxf(m1, fmaxf(s[4 * k + 2], s[4 * k + 3]));
    }
    m0 = fmaxf(m0, __shfl_xor_sync(0xffffffffu, m0, 1));
    m1 = fmaxf(m1, __shfl_xor_sync(0xffffffffu, m1, 1));
    m0 = fmaxf(m0, __shfl_xor_sync(0xffffffffu, m0, 2));
    m1 = fmaxf(m1, __shfl_xor_sync(0xffffffffu, m1, 2));
    if (!first) {
        m0 = fmaxf(m0, 0.f);
        m1 = fmaxf(m1, 0.f);
    }
    a0 = first ? 0.f : ex2(-m0);
    a1 = first ? 0.f : ex2(-m1);
    m[0] += m0;
    m[1] += m1;
    softmax_shift(s, m0, m1);
}
template <int J0, int J1>
__device__ __forceinline__ void softmax_exp(const float (&s)[64], uint32_t (&p)[32], float (&t)[4]) {
#pragma unroll
    for (int k = J0; k < J1; k++) {
        const float e0 = ex2(s[4 * k]), e1 = ex2(s[4 * k + 1]), e2 = ex2(s[4 * k + 2]), e3 = ex2(s[4 * k + 3]);
        if (k == 0) { t[0] = e0; t[1] = e1; t[2] = e2; t[3] = e3; }
        else { t[0] += e0; t[1] += e1; t[2] += e2; t[3] += e3; }
        p[2 * k] = pack2(e0, e1);
        p[2 * k + 1] = pack2(e2, e3);
    }
}
__device__ __forceinline__ void fma8(float (&acc)[8], float a, uint4 w) {
    acc[0] = fmaf(a, bf_lo(w.x), acc[0]); acc[1] = fmaf(a, bf_hi(w.x), acc[1]);
    acc[2] = fmaf(a, bf_lo(w.y), acc[2]); acc[3] = fmaf(a, bf_hi(w.y), acc[3]);
    acc[4] = fmaf(a, bf_lo(w.z), acc[4]); acc[5] = fmaf(a, bf_hi(w.z), acc[5]);
    acc[6] = fmaf(a, bf_lo(w.w), acc[6]); acc[7] = fmaf(a, bf_hi(w.w), acc[7]);
}
__device__ __forceinline__ void mma16816(float (&d)[4], const uint32_t* a, uint32_t b0, uint32_t b1) {
    asm("mma.sync.aligned.m16n8k16.row.col.f32.bf16.bf16.f32 {%0, %1, %2, %3}, {%4, %5, %6, %7}, {%8, %9}, {%0, %1, %2, %3};"
        : "+f"(d[0]), "+f"(d[1]), "+f"(d[2]), "+f"(d[3]) : "r"(a[0]), "r"(a[1]), "r"(a[2]), "r"(a[3]), "r"(b0), "r"(b1));
}
__device__ __forceinline__ uint32_t best_key(const uint32_t* keys, int lane, uint32_t ep) {
    uint32_t best;
#pragma unroll 1
    for (;;) {
        const uint4 k = ld_poll(reinterpret_cast<const uint4*>(keys) + lane);
        best = max(max(k.x, k.y), max(k.z, k.w));
        if (__all_sync(0xffffffffu, (((k.x ^ ep) | (k.y ^ ep) | (k.z ^ ep) | (k.w ^ ep)) & 31) == 0)) break;
    }
    return __reduce_max_sync(0xffffffffu, best);
}

__global__ void __launch_bounds__(384, 1)
fused_kernel(const __grid_constant__ CUtensorMap tm_ckv, const __grid_constant__ CUtensorMap tm_wq,
             const __grid_constant__ CUtensorMap tm_wuk, const __grid_constant__ CUtensorMap tm_wuv,
             const __grid_constant__ CUtensorMap tm_wo, const __grid_constant__ CUtensorMap tm_wg,
             const __grid_constant__ CUtensorMap tm_wu, const __grid_constant__ CUtensorMap tm_wd,
             const __grid_constant__ CUtensorMap tm_wm, const Params P) {
    extern __shared__ __align__(1024) uint8_t smem[];
    const uint32_t sb = (uint32_t)__cvta_generic_to_shared(smem);
    const int tid = threadIdx.x, lane = tid & 31, warp = __shfl_sync(0xffffffffu, tid >> 5, 0), wg = warp >> 2;
    uint32_t sm;
    asm("mov.u32 %0, %%smid;" : "=r"(sm));
    const uint32_t smq = ((sm - 64) * 147) >> 11;
    const int rb = !P.by_smid ? blockIdx.x : sm < 64 ? (sm & 14) * 8 + (sm >> 4) * 2 + (sm & 1)
                 : sm < 120 ? ((sm - 64 - smq * 14) & 14) * 8 + 24 + smq * 2 + (sm & 1) : sm < 124 ? sm + 8 : sm - 116;
    const int grp = rb >> 3, j = rb & 7, cq = j & 3, kh = grp & 1, ort = (grp & 14) + (j >> 2);
    if (warp == 0) TS(0);

    if (rb >= NCTA) {
        float* sc = reinterpret_cast<float*>(smem + 6 * SLOT);
        float* red = sc + 512;
        if (tid == 256) {
            for (int i = 0; i < 6; i++) { mbar_init(sb + BAR_FULL + 8 * i, 1); mbar_init(sb + BAR_EMPTY + 8 * i, 8); }
            fence_async_smem();
        }
        __syncthreads();
        uint32_t ph = 0, sl = 0;
        if (tid == 256) {
#pragma unroll 1
            for (int i = 0; i < 24; i++) {
                mbar_wait(sb + BAR_EMPTY + 8 * sl, ph ^ 1);
                mbar_expect(sb + BAR_FULL + 8 * sl, SLOT);
                tma2d(sb + sl * SLOT, &tm_wm, (i >> 3) * 1024 + (rb - NCTA) * 256, (i & 7) * 64, sb + BAR_FULL + 8 * sl);
                if (++sl == 6) { sl = 0; ph ^= 1; }
            }
        } else if (tid < 256) {
            const uint32_t c2 = __ldg(reinterpret_cast<const uint32_t*>(P.c) + tid);
            sc[2 * tid] = rbf(bf_lo(c2) * sigmoid(bf_lo(c2)));
            sc[2 * tid + 1] = rbf(bf_hi(c2) * sigmoid(bf_hi(c2)));
            bar_sync(1, 256);
#pragma unroll 1
            for (int ps = 0; ps < 3; ps++) {
                float acc[8] = {0.f, 0.f, 0.f, 0.f, 0.f, 0.f, 0.f, 0.f};
#pragma unroll 1
                for (int bt = 0; bt < 8; bt++) {
                    mbar_wait(sb + BAR_FULL + 8 * sl, ph);
#pragma unroll
                    for (int i = 0; i < 8; i++)
                        fma8(acc, sc[bt * 64 + warp * 8 + i], *reinterpret_cast<const uint4*>(smem + sl * SLOT + (warp * 8 + i) * 512 + lane * 16));
                    __syncwarp();
                    mbar_arrive_if(sb + BAR_EMPTY + 8 * sl, lane == 0);
                    if (++sl == 6) { sl = 0; ph ^= 1; }
                }
                *reinterpret_cast<float4*>(red + warp * 256 + lane * 8) = make_float4(acc[0], acc[1], acc[2], acc[3]);
                *reinterpret_cast<float4*>(red + warp * 256 + lane * 8 + 4) = make_float4(acc[4], acc[5], acc[6], acc[7]);
                bar_sync(1, 256);
                float v = 0.f;
#pragma unroll
                for (int i = 0; i < 8; i++) v += red[i * 256 + tid];
                g_mod[ps * 1024 + (rb - NCTA) * 256 + tid] = __float2bfloat16_rn(v);
                bar_sync(1, 256);
                if (tid == 0 && ps != 1) flag_add(&g_sync.modcnt[(ps >> 1) * 32]);
                if (warp == 0) TS(1 + ps);
            }
        }
        return;
    }

    if (tid == 256) {
        if (sb & 1023) __trap();
        asm volatile("prefetch.tensormap [%0];" ::"l"((j & 1) ? &tm_wuv : &tm_wuk) : "memory");
        asm volatile("prefetch.tensormap [%0];" ::"l"(&tm_ckv) : "memory");
        for (int i = 0; i < 7; i++) { mbar_init(sb + BAR_FULL + 8 * i, 1); mbar_init(sb + BAR_EMPTY + 8 * i, 2); }
        for (int i = 0; i < 9; i++) mbar_init(sb + BAR_DONE + 8 * i, 8);
        for (int i = 0; i < 12; i++) mbar_init(sb + BAR_FLAG + 8 * i, 1);
        mbar_init(sb + BAR_END, 8);
        fence_async_smem();
    }
    __syncthreads();

    if (wg == 2) {
        asm volatile("setmaxnreg.dec.sync.aligned.u32 40;");
        if (warp == 8) {
            uint32_t eph = 0x7f, r = 0;
            const CUtensorMap* tw = (j & 1) ? &tm_wuv : &tm_wuk;
#pragma unroll 1
            for (int hp = 0; hp < 2; hp++) {
                const int hc = 4 * grp + 2 * hp;
                uint32_t wtab = w_table(hp), atab = a_table(hp);
#pragma unroll 1
                for (int u = 0; u < 4; u++) {
                    load_tile(sb, eph, (wtab >> (4 * u)) & 15, tw, u * 128, hc, HINT & 1); PT();
                    load_tile(sb, eph, a_next(atab), &tm_ckv, (j >> 1) * 128, u * 2, (HINT & 8) && hp); PT();
                }
#pragma unroll 1
                for (int u = 4; u < 16; u++) {
                    if (hp == 1 && (u & 7) == 4) mbar_wait(sb + BAR_FLAG + 24 + (u & 8), 0);
                    load_tile(sb, eph, a_next(atab), &tm_ckv, ((u & 12) + (j >> 1)) * 128, (u & 3) * 2, (HINT & 8) && hp); PT();
                }
                mbar_wait(sb + BAR_FLAG, 0);
                fence_async_global();
#pragma unroll 1
                for (int u = 0; u < 4; u++) {
                    load_tile(sb, eph, (wtab >> (4 * u)) & 15, &tm_wq, u * 128, hc, HINT & 1); PT();
                    load_image(sb, eph, a_next(atab), g_h + ((15 - j) * 4 + u) * SLOT, (HINT & 8) && hp); PT();
                }
                mbar_wait(sb + BAR_FLAG + 8 + 32 * hp, 0);
                fence_async_global();
#pragma unroll 1
                for (int u = 0; u < 4; u++) { load_image(sb, eph, a_next(atab), g_h + (j * 4 + u) * SLOT, (HINT & 8) && hp); PT(); }
                const uint8_t* kv = g_KV + (size_t)(grp * 32 + 30 * hp) * SLOT;
                const int step = hp ? -2 * SLOT : 2 * SLOT;
                load_image(sb, eph, r, kv, HINT & 4); PT();
                r = ring_next(r);
#pragma unroll 1
                for (int n = 1; n <= 16; n++) {
                    if (n == 8) {
                        mbar_wait(sb + BAR_FLAG + 16 + 32 * hp, 0);
                        fence_async_global();
                    }
                    mbar_arrive_if(sb + BAR_PF, lane == 0 && (n == PF1 || n == PF2));
                    const uint8_t* v = kv + SLOT;
                    kv += n < 16 - j ? step : n == 16 - j ? (2 * j - 15) * step : -step;
                    load_image(sb, eph, r, kv, HINT & 4); PT();
                    r = ring_next(r);
                    load_image(sb, eph, r, v, HINT & 4); PT();
                    r = ring_next(r);
                }
                load_image(sb, eph, r, kv + SLOT, HINT & 4); PT();
                r = ring_next(r);
            }
            uint32_t otab = O_TABLE;
#pragma unroll 1
            for (int i = 0; i < 17; i++) {
                if ((i & 7) == 0) {
                    mbar_wait(sb + BAR_FLAG + 8 * 9 + (i ? 8 : 0), 0);
                    fence_async_global();
                }
                const int head = o_head(i, kh);
                load_image(sb, eph, o_next(otab), g_ctx + (size_t)(ort * 32 + head) * SLOT, HINT & 16); PT();
                load_tile(sb, eph, o_next(otab), &tm_wo, head * 128, cq * 2, HINT & 2); PT();
            }
            if (lane == 0) {
                const uint32_t s1 = o_next(otab), s2 = o_next(otab);
                if (rb < NFFN) {
                    slot_wait(sb + BAR_EMPTY, eph, s1);
                    const uint32_t f = sb + BAR_FULL + 8 * s1, d = sb + s1 * SLOT;
                    mbar_expect(f, SLOT);
                    tma2d(d, &tm_wg, rb * 16, 0, f);
                    tma2d(d + 8192, &tm_wg, rb * 16, 256, f);
                    tma2d(d + 16384, &tm_wu, rb * 16, 0, f);
                    tma2d(d + 24576, &tm_wu, rb * 16, 256, f);
                }
                slot_wait(sb + BAR_EMPTY, eph, s2);
                mbar_expect(sb + BAR_FULL + 8 * s2, 7 * 4096);
#pragma unroll 1
                for (int k = 0; k < 7; k++) tma2d(sb + s2 * SLOT + k * 4096, &tm_wd, (rb >> 1) * 8, k * 256, sb + BAR_FULL + 8 * s2);
            }
        } else {
            const int hw = warp - 9;
            if (hw == 1 && lane == 0) {
                mbar_watch(sb + BAR_FULL + 8 * PF0, 0);
                l2_prefetch(P.ckv + 512 * 512 + rb * 6144, 12288);
                l2_prefetch(P.x + rb * 8192, 16384);
                mbar_watch(sb + BAR_FULL + 8 * 4, 0);
                TS(40);
                if (j < 4) tma3d_prefetch(&tm_wq, j * 128, grp * 4);
                mbar_watch(sb + BAR_PF, 0);
                l2_prefetch(P.ckv + rb * 8192, 16384);
                l2_prefetch(g_h + rb * 16384, 16384);
                mbar_watch(sb + BAR_PF, 1);
                tma3d_prefetch((j & 1) ? &tm_wuv : &tm_wuk, (j >> 1) * 128, grp * 4 + 2);
                if (j < 4) tma3d_prefetch(&tm_wq, j * 128, grp * 4 + 2);
                mbar_watch(sb + BAR_PF, 0);
                l2_prefetch(g_ctx + (size_t)(ort * 32 + o_head(cq, kh)) * SLOT, SLOT);
                l2_prefetch(g_ctx + (size_t)(ort * 32 + o_head(cq + 4, kh)) * SLOT, SLOT);
                mbar_watch(sb + BAR_PF, 1);
                l2_prefetch(reinterpret_cast<const uint8_t*>(P.wo) + rb * 32768, 32768);
                l2_prefetch(reinterpret_cast<const uint8_t*>(P.wgate) + rb * 14336, 14336);
                l2_prefetch(reinterpret_cast<const uint8_t*>(P.wup) + rb * 14336, 14336);
                l2_prefetch(reinterpret_cast<const uint8_t*>(P.wdown) + rb * 14336, 14336);
                l2_prefetch(P.x + rb * 8192, 16384);
                mbar_watch(sb + BAR_END, 0);
            }
            if (hw == 0) {
#pragma unroll 1
                for (int i = 0; i < 9; i++) {
                    const int hp = i > 4, k = (i - 1) & 3;
                    if (lane == 0) {
                        mbar_wait(sb + BAR_DONE + 8 * i, 0);
                        if (i == 3 || i == 4) asm volatile("red.relaxed.gpu.global.add.u32 [%0], 1;" ::"l"(&g_sync.rdcnt[(grp * 2 + i - 3) * 8]) : "memory");
                        flag_add(i == 0 ? &g_sync.hcnt[grp * 8] : k < 2 ? &g_sync.kvcnt[((2 * grp + hp) * 2 + k) * 8]
                                                                        : &g_sync.ctxcnt[(k == 2 ? 15 - j : j) * 32 + 2 * grp + hp]);
                    }
                    if (i == 0) TS(43);
                    if (i == 4) {
                        __syncwarp();
#pragma unroll 1
                        for (int v = 0; v < 32; v++) g_part[rb * 1024 + v * 32 + lane] = make_uint4(0, 0, 0, 0);
                        __syncwarp();
                    }
                }
            }
            if (hw == 2) {
                const uint32_t ep = __ldcg(&g_sync.epoch[0]) + 1;
                if (lane == 0) {
                    asm volatile("st.shared.u32 [%0], %1;" ::"r"(sb + SM_EP), "r"(ep) : "memory");
                    flag_wait(&g_sync.modcnt[0], NSPARE * ep);
                    mbar_arrive(sb + BAR_FLAG + 8 * 8);
                }
                TS(42);
#pragma unroll 1
                for (int i = 0; i < 8; i++) {
                    if (lane == 0) mbar_wait(sb + BAR_DONE + 8 * (i == 7 ? 6 : i), 0);
                    __syncwarp();
                    const uint32_t* f = i == 0 ? &g_sync.hcnt[(lane ? j : 15 - j) * 8]
                                      : i == 3 || i == 4 ? &g_sync.rdcnt[(grp * 2 + i - 3) * 8]
                                      : i == 7 ? &g_sync.modcnt[32] : &g_sync.kvcnt[(4 * grp + (i > 4 ? i - 3 : i - 1)) * 8];
                    if (lane < (i ? 1 : 2)) flag_wait(f, i == 7 ? NSPARE * ep : 8 * ep);
                    __syncwarp();
                    if (i == 7) {
                        const uint32_t *mp = reinterpret_cast<const uint32_t*>(g_mod) + lane, *wp = reinterpret_cast<const uint32_t*>(P.wr) + lane;
                        float ra = 0.f, rs = 0.f;
#pragma unroll 1
                        for (int k = 0; k < 256; k += 32) {
                            const uint32_t ga = __ldcg(mp + 512 + k), sh = __ldcg(mp + 768 + k), c1 = badd(__ldcg(mp + 1024 + k), ONE2);
                            const uint32_t gb = __ldcg(mp + 1280 + k), ww = __ldg(wp + k);
                            const float a0 = bf_lo(c1) * bf_lo(ww), a1 = bf_hi(c1) * bf_hi(ww);
                            ra += a0 + a1;
                            rs = fmaf(bf_lo(sh), bf_lo(ww), fmaf(bf_hi(sh), bf_hi(ww), rs));
                            if (k >> 6 == cq) {
                                sts128(sb + SM_TAB + ((k & 32) + lane) * 16, make_uint4(ga << 16, ga & 0xffff0000u, __float_as_uint(a0), __float_as_uint(a1)));
                                sts128(sb + SM_TAB + 1024 + ((k & 32) + lane) * 16, make_uint4(c1, sh, gb, 0));
                            }
                        }
                        *reinterpret_cast<float2*>(smem + SM_EP + 8) = make_float2(warp_sum(ra), warp_sum(rs));
                        __syncwarp();
                    }
                    if (lane == 0) mbar_arrive(sb + BAR_FLAG + 8 * i);
                    TS(48 + i);
                }
#pragma unroll 1
                for (int i = 0; i < 2; i++) {
                    if (i) mbar_wait(sb + BAR_DONE + 8 * 7, 0);
                    if (lane < 8 + i) flag_wait(&g_sync.ctxcnt[ort * 32 + o_head(lane + 8 * i, kh)], ep);
                    __syncwarp();
                    if (lane == 0) mbar_arrive(sb + BAR_FLAG + 8 * (9 + i));
                    TS(44 + i);
                }
            }
        }
    } else {
        asm volatile("setmaxnreg.inc.sync.aligned.u32 232;");
        const bool elected = (tid & 127) == 0;
        const int g = lane >> 2, c4 = lane & 3;
        const uint32_t toff = (warp * 16 + g) * 128 + ((c4 ^ g) << 4);
        uint32_t fph = 0, r = 0;
        if (wg == 1) bar_arrive(1, 256);
        const uint32_t kd = desc_k(sb), vd = desc_mn(sb);
        const int nL = 16 - j, hn = nL - 1 + wg;
        {
        float s[64], o[64];
#pragma unroll 1
        for (int hp = 0; hp < 2; hp++) {
            {
                const int step = hp ? -8 * SLOT : 8 * SLOT;
                uint8_t* img = g_KV + (size_t)(grp * 32 + (hp ? j ^ 30 : j)) * SLOT - step;
                const uint32_t wtab = w_table(hp);
                uint32_t atab = a_table(hp);
#pragma unroll 1
                for (int t = 0; t < 6; t += 2) {
                    proj_tile<false>(s, o, t, sb, wg, elected, fph, wtab, atab, img, toff, (hp | t) == 0, P.x, rb * 16 + warp * 2);
                    __syncwarp();
                    mbar_arrive_if(sb + BAR_DONE + 4 * t + 32 * hp, lane == 0 && t != 0);
                    if (elected) TS(1 + 10 * hp + t + 20 * wg);
                    proj_tile<true>(o, s, t + 1, sb, wg, elected, fph, wtab, atab, img + step, toff, (hp | t) == 0, P.x, rb * 16 + warp * 2);
                    if (elected) TS(2 + 10 * hp + t + 20 * wg);
                    img += 2 * step;
                }
            }
            float m[2] = {0.f, 0.f}, l[2] = {0.f, 0.f}, t[4];
            bool shifted = false;
            uint32_t p[32];
            uint32_t qa = desc_k(sb + 5 * SLOT + (wg ^ 1) * 8192);
            uint8_t* img = g_ctx + (size_t)((15 - j) * 32 + 2 * grp + hp) * SLOT;
            slot_wait(sb + BAR_FULL, fph, r);
            bar_sync(1 + wg, 256);
            qk_issue(s, qa, kd + r * (SLOT / 16));
            bar_arrive(2 - wg, 256);
            reg_fence(o);
            q_store<0>(sb + 6 * SLOT, toff ^ 8192, o);
            q_store<1>(sb + 6 * SLOT, toff ^ 8192, o);
            q_store<2>(sb + 6 * SLOT, toff ^ 8192, o);
            q_store<3>(sb + 6 * SLOT, toff ^ 8192, o);
            fence_async_smem();
            wg_wait<0>();
            reg_fence(s);
            mbar_arrive_if(sb + BAR_EMPTY + 8 * r, elected);
            r = ring_next(r);
            slot_wait(sb + BAR_FULL, fph, r);
            int n = 0;
            bool bad = false;
#pragma unroll 1
            for (;;) {
                for (;;) {
                    if (bad) {
                        float a0, a1;
                        softmax_remax(s, m, n == 0 || n == nL, a0, a1);
                        shifted = true;
                        l[0] *= a0;
                        l[1] *= a1;
#pragma unroll
                        for (int i = 0; i < 64; i++) o[i] *= (i & 2) ? a1 : a0;
                    }
                    softmax_exp<0, 16>(s, p, t);
                    t[0] += t[1];
                    t[2] += t[3];
                    bad = !bad && softmax_unsafe(t[0], t[2], n == 0);
                    if (!bad) break;
                }
                bool plain = false;
#pragma unroll 1
                do {
                    l[0] += t[0];
                    l[1] += t[2];
                    if (++n > 16) break;
                    const uint32_t ks = r, vs = ring_next(r);
                    r = ring_next(vs);
                    bar_sync(1 + wg, 256);
                    if ((uint32_t)(n + 1 - nL) <= (uint32_t)(1 + wg)) {
                        const int x = (warp & 3) * 16 + g - 2 * c4;
                        if (n == hn) {
                            float sh[32];
                            qk_issue(sh, qa, kd + ks * (SLOT / 16));
                            slot_wait(sb + BAR_FULL, fph, vs);
                            pv_issue(o, p, vd + vs * (SLOT / 16), 1, false);
                            bar_arrive(2 - wg, 256);
                            wg_wait<1>();
                            reg_fence(sh);
                            tri_mask_copy(s, sh, x);
                        } else {
                            qk_issue(s, qa, kd + ks * (SLOT / 16));
                            slot_wait(sb + BAR_FULL, fph, vs);
                            pv_issue(o, p, vd + vs * (SLOT / 16), n != nL + 1, n == hn + 1);
                            bar_arrive(2 - wg, 256);
                            wg_wait<1>();
                            reg_fence(s);
                            if (n <= nL) tri_mask<32>(s, x);
                        }
                        mbar_arrive_if(sb + BAR_EMPTY + 8 * ks, elected);
                        mbar_arrive_if(sb + BAR_EMPTY + 8 * (n == 16 ? 6 : 5), elected && (n == 16 || n == nL - 1));
                        if (n == nL - 1) qa += SLOT / 16;
                        if (shifted) {
                            if (n == nL) {
                                m[0] = m[1] = 0.f;
                                shifted = false;
                            }
                            softmax_shift(s, m[0], m[1]);
                        }
                        float e[4 * EARLY];
#pragma unroll
                        for (int i = 0; i < 4 * EARLY; i++) {
                            e[i] = ex2(s[i]);
                            t[i & 3] = i < 4 ? e[i] : t[i & 3] + e[i];
                        }
                        reg_fence(e);
                        slot_wait(sb + BAR_FULL, fph, r);
                        wg_wait<0>();
                        reg_fence(o);
                        reg_fence(e);
                        mbar_arrive_if(sb + BAR_EMPTY + 8 * vs, elected);
#pragma unroll
                        for (int i = 0; i < 2 * EARLY; i++) p[i] = pack2(e[2 * i], e[2 * i + 1]);
                        softmax_exp<EARLY, 8>(s, p, t);
                        if (n == nL) {
                            ctx_store(img, toff, o, l[0], l[1]);
                            __syncwarp();
                            mbar_arrive_if(sb + BAR_DONE + 24 + 32 * hp, lane == 0);
                            if (elected) TS(7 + 10 * hp + 20 * wg);
                            l[0] = l[1] = 0.f;
                        }
                        if (n != hn) softmax_exp<8, 16>(s, p, t);
                        t[0] += t[1];
                        t[2] += t[3];
                        bad = softmax_unsafe(t[0], t[2], n == nL);
                        continue;
                    }
                    qk_issue(s, qa, kd + ks * (SLOT / 16));
                    slot_wait(sb + BAR_FULL, fph, vs);
                    pv_issue(o, p, vd + vs * (SLOT / 16), n != 1 && n != nL + 1, false);
                    bar_arrive(2 - wg, 256);
                    wg_wait<1>();
                    reg_fence(s);
                    mbar_arrive_if(sb + BAR_EMPTY + 8 * ks, elected);
                    mbar_arrive_if(sb + BAR_EMPTY + 8 * 6, elected && n == 16);
                    if (shifted) {
                        slot_wait(sb + BAR_FULL, fph, r);
                        wg_wait<0>();
                        reg_fence(o);
                        mbar_arrive_if(sb + BAR_EMPTY + 8 * vs, elected);
                        softmax_shift(s, m[0], m[1]);
                        plain = true;
                        break;
                    }
                    float e[4 * EARLY];
#pragma unroll
                    for (int i = 0; i < 4 * EARLY; i++) {
                        e[i] = ex2(s[i]);
                        t[i & 3] = i < 4 ? e[i] : t[i & 3] + e[i];
                    }
                    reg_fence(e);
                    slot_wait(sb + BAR_FULL, fph, r);
                    wg_wait<0>();
                    reg_fence(o);
                    reg_fence(e);
                    mbar_arrive_if(sb + BAR_EMPTY + 8 * vs, elected);
#pragma unroll
                    for (int i = 0; i < 2 * EARLY; i++) p[i] = pack2(e[2 * i], e[2 * i + 1]);
                    softmax_exp<EARLY, 16>(s, p, t);
                    t[0] += t[1];
                    t[2] += t[3];
                    bad = softmax_unsafe(t[0], t[2], false);
                } while (!bad);
                if (!bad && !plain) break;
            }
            bar_sync(1 + wg, 256);
            pv_issue(o, p, vd + r * (SLOT / 16), j, hn == 16);
            bar_arrive(2 - wg, 256);
            wg_wait<0>();
            reg_fence(o);
            mbar_arrive_if(sb + BAR_EMPTY + 8 * r, elected);
            r = ring_next(r);
            ctx_store(img + (ptrdiff_t)(2 * j - 15) * 32 * SLOT, toff ^ 8192, o, l[0], l[1]);
            __syncwarp();
            mbar_arrive_if(sb + BAR_DONE + 32 + 32 * hp, lane == 0);
            if (elected) TS(8 + 10 * hp + 20 * wg);
        }
        }
        float s[64], o[64];
        uint32_t otab = O_TABLE;
        const uint32_t oa = desc_k(sb + (wg ^ kh ^ 1) * 8192);
        const int t7 = tid & 127, w4 = warp & 3, row = ort * 128 + kh * 64 + w4 * 16 + g;
        uint32_t x2[32];
#pragma unroll
        for (int k = 0; k < 32; k++) x2[k] = 0;
#pragma unroll 1
        for (int i = 0; i < 15 - wg; i++) {
            const uint32_t as = o_next(otab), ws = o_next(otab);
            slot_wait(sb + BAR_FULL, fph, as);
            slot_wait(sb + BAR_FULL, fph, ws);
            bar_sync(1 + wg, 256);
            gemm_issue(s, oa + as * (SLOT / 16), vd + ws * (SLOT / 16), i);
            bar_arrive(2 - wg, 256);
            if (i == 12 && wg) {
                const uint32_t* xp = reinterpret_cast<const uint32_t*>(P.x) + row * 256 + cq * 64 + c4;
#pragma unroll
                for (int k = 0; k < 32; k++) x2[k] = __ldg(xp + (k & 1) * 2048 + (k >> 1) * 4);
            }
            wg_wait<0>();
            mbar_arrive_if(sb + BAR_EMPTY + 8 * as, elected);
            mbar_arrive_if(sb + BAR_EMPTY + 8 * ws, elected);
        }
        mbar_wait(sb + BAR_FLAG + 8 * 7, 0);
        const uint32_t ep = lds32(sb + SM_EP);
        if (wg == 0) {
            reg_fence(s);
            if (elected) TS(9);
#pragma unroll
            for (int v = 0; v < 8; v++)
                st_pub(g_part + rb * 1024 + v * 128 + t7, make_uint4(max(pack2(s[8 * v], s[8 * v + 1]), 1u), pack2(s[8 * v + 2], s[8 * v + 3]),
                                                                      pack2(s[8 * v + 4], s[8 * v + 5]), pack2(s[8 * v + 6], s[8 * v + 7])), true);
            o_next(otab); o_next(otab); o_next(otab); o_next(otab);
            const uint32_t s1 = o_next(otab), s2 = o_next(otab);
            uint32_t wf[64];
            float wd[56];
            if (rb < NFFN) {
                slot_wait(sb + BAR_FULL, fph, s1);
                const uint32_t a = sb + s1 * SLOT + (w4 * 128 + (lane >> 4) * 8 + (lane & 7)) * 32 + ((lane >> 3) & 1) * 16;
#pragma unroll
                for (int i = 0; i < 16; i++)
                    asm volatile("ldmatrix.sync.aligned.m8n8.x4.trans.shared.b16 {%0, %1, %2, %3}, [%4];"
                                 : "=r"(wf[4 * i]), "=r"(wf[4 * i + 1]), "=r"(wf[4 * i + 2]), "=r"(wf[4 * i + 3])
                                 : "r"(a + (i >> 3) * 16384 + (i & 7) * 512) : "memory");
            }
            slot_wait(sb + BAR_FULL, fph, s2);
#pragma unroll
            for (int i = 0; i < 14; i++) {
                const uint2 w = *reinterpret_cast<const uint2*>(smem + s2 * SLOT + (i >> 1) * 4096 + (2 * t7 + (i & 1)) * 16 + (rb & 1) * 8);
                wd[4 * i] = bf_lo(w.x); wd[4 * i + 1] = bf_hi(w.x); wd[4 * i + 2] = bf_lo(w.y); wd[4 * i + 3] = bf_hi(w.y);
            }
            const uint32_t gbf = __ldcg(reinterpret_cast<const uint32_t*>(g_mod) + 1280 + rb * 2 + (tid & 1));
            reg_fence(wd);
            if (elected) TS(10);
            const uint32_t best = best_key(g_key + cq * 128, lane, ep);
            const int sel = (~best >> 5) & 2047;
            if (elected) TS(19);
            const uint4* cp = g_cand + (sel >> 4) * 192;
            float* sred = reinterpret_cast<float*>(smem + SM_RED);
            const int pq = (2 * rb + (tid & 1)) & 63, pv = (pq >> 2) / 3;
            const uint4* fp = cp + (rb >> 5) * 24 + pv * 4 + (pq & 3);
            uint4 fh = ld_poll(fp), fx = ld_poll(fp + 96);
            if (rb < NFFN) {
                uint4 cv[6];
                for (;;) {
                    uint32_t bad = 0;
#pragma unroll
                    for (int v = 0; v < 6; v++) cv[v] = ld_poll(cp + w4 * 24 + v * 4 + c4);
#pragma unroll
                    for (int v = 0; v < 6; v++) bad |= cv[v].w ^ ep;
                    if (__all_sync(0xffffffffu, bad == 0)) break;
                }
                if (elected) TS(20);
                float d[4][4] = {};
#pragma unroll
                for (int k = 0; k < 8; k++) {
                    const uint32_t b0 = (&cv[(2 * k) / 3].x)[(2 * k) % 3], b1 = (&cv[(2 * k + 1) / 3].x)[(2 * k + 1) % 3];
                    mma16816(d[k & 1], wf + 4 * k, b0, b1);
                    mma16816(d[2 + (k & 1)], wf + 32 + 4 * k, b0, b1);
                }
                const float u = (c4 & 2) ? ((c4 & 1) ? d[2][2] + d[3][2] : d[2][0] + d[3][0]) : ((c4 & 1) ? d[0][2] + d[1][2] : d[0][0] + d[1][0]);
                sred[w4 * 32 + c4 * 8 + g] = u;
                bar_sync(3, 128);
                if (warp == 0) {
                    const float v = rbf((sred[lane] + sred[32 + lane]) + (sred[64 + lane] + sred[96 + lane]));
                    const float up = __shfl_down_sync(0xffffffffu, v, 16);
                    st_pub(g_act + rb * 16 + lane, (pack2(0.f, rbf(v * sigmoid(v)) * up) & 0xffff0000u) | (ep & 0xffffu), lane < 16);
                }
            }
            if (rb == 0 && tid == 0) g_sync.epoch[0] = ep;
            if (elected) TS(60);
            uint2 av[7];
            for (;;) {
                uint32_t bad = 0;
#pragma unroll
                for (int k = 0; k < 7; k++) av[k] = ld_poll(reinterpret_cast<const uint2*>(g_act) + t7 + 128 * k);
#pragma unroll
                for (int k = 0; k < 7; k++) bad |= (av[k].x ^ ep) | (av[k].y ^ ep);
                if (__all_sync(0xffffffffu, (bad & 0xffffu) == 0)) break;
            }
            if (elected) TS(61);
            float y[4] = {0.f, 0.f, 0.f, 0.f};
#pragma unroll
            for (int k = 0; k < 7; k++)
#pragma unroll
                for (int i = 0; i < 4; i++) y[i] = fmaf(bf_hi(av[k].y), wd[8 * k + 4 + i], fmaf(bf_hi(av[k].x), wd[8 * k + i], y[i]));
            const float z0 = ((lane & 16) ? y[2] : y[0]) + __shfl_xor_sync(0xffffffffu, (lane & 16) ? y[0] : y[2], 16);
            const float z1 = ((lane & 16) ? y[3] : y[1]) + __shfl_xor_sync(0xffffffffu, (lane & 16) ? y[1] : y[3], 16);
            float z = ((lane & 8) ? z1 : z0) + __shfl_xor_sync(0xffffffffu, (lane & 8) ? z0 : z1, 8);
            z += __shfl_xor_sync(0xffffffffu, z, 4);
            z = quad_sum(z);
            if ((lane & 7) == 0) sred[128 + (lane >> 3) * 4 + w4] = z;
            bar_sync(3, 128);
            if (tid < 2) {
                while (fh.w != ep || fx.w != ep) { fh = ld_poll(fp); fx = ld_poll(fp + 96); }
                const float4 y0 = *reinterpret_cast<const float4*>(sred + 128 + tid * 8), y1 = *reinterpret_cast<const float4*>(sred + 132 + tid * 8);
                const int cm = (pq >> 2) - 3 * pv;
                const uint32_t h2 = cm == 0 ? fh.x : cm == 1 ? fh.y : fh.z, x2 = cm == 0 ? fx.x : cm == 1 ? fx.y : fx.z;
                const float sg = sigmoid(bf_hi((best & 0x80000000u) ? (best ^ 0x80000000u) : ~best));
                reinterpret_cast<uint32_t*>(P.out)[sel * 256 + rb * 2 + tid] =
                    badd(x2, bmul(gbf, badd(h2, bmul(pack2((y0.x + y0.y) + (y0.z + y0.w), (y1.x + y1.y) + (y1.z + y1.w)), pack2(sg, sg)))));
            }
            if (elected) TS(62);
        } else {
            const float4* tf = reinterpret_cast<const float4*>(smem + SM_TAB) + c4;
            const uint32_t as14 = otab & 15;
            bar_sync(2, 256);
#pragma unroll 1
            for (int i = 14; i < 17; i++) {
                const uint32_t as = o_next(otab), ws = o_next(otab);
                slot_wait(sb + BAR_FULL, fph, as);
                slot_wait(sb + BAR_FULL, fph, ws);
                gemm_issue(s, oa + as * (SLOT / 16), vd + ws * (SLOT / 16), 1);
                wg_wait<1>();
                mbar_arrive_if(sb + BAR_EMPTY + 8 * as14, elected && i == 15);
            }
            if (elected) TS(29);
            {
                const uint4* pr = g_part + (rb ^ 8) * 1024 + t7;
                uint4 pa[8];
                for (;;) {
                    uint32_t ok = ~0u;
#pragma unroll
                    for (int v = 0; v < 8; v++) pa[v] = ld_poll(pr + v * 128);
#pragma unroll
                    for (int v = 0; v < 8; v++) ok = min(ok, pa[v].x);
                    if (__all_sync(0xffffffffu, ok != 0)) break;
                }
#pragma unroll
                for (int i = 0; i < 32; i++) {
                    const uint32_t w = (&pa[i >> 2].x)[i & 3];
                    const float2 ga = *reinterpret_cast<const float2*>(tf + (i >> 1) * 4);
                    o[2 * i] = fmaf(ga.x, bf_lo(w), bf_lo(x2[i]));
                    o[2 * i + 1] = fmaf(ga.y, bf_hi(w), bf_hi(x2[i]));
                }
            }
            reg_fence(o);
            if (elected) TS(30);
            wg_wait<0>();
            reg_fence(s);
            if (elected) TS(39);
            float st[6] = {0.f, 0.f, 0.f, 0.f, 0.f, 0.f};
#pragma unroll
            for (int k = 0; k < 16; k++) {
                const float4 c = tf[k * 4];
#pragma unroll
                for (int i = 4 * k; i < 4 * k + 4; i++) {
                    const int rh = (i >> 1) & 1;
                    const float v = fmaf((i & 1) ? c.y : c.x, s[i], o[i]);
                    s[i] = v;
                    st[rh] += v;
                    st[2 + rh] = fmaf(v, v, st[2 + rh]);
                    st[4 + rh] = fmaf(v, (i & 1) ? c.w : c.z, st[4 + rh]);
                }
            }
#pragma unroll
            for (int i = 0; i < 6; i++) st[i] = quad_sum(st[i]);
            st_pub(g_stat + (row + 8 * (c4 & 1)) * 4 + cq,
                   make_uint4(__float_as_uint((c4 & 1) ? st[1] : st[0]), __float_as_uint((c4 & 1) ? st[3] : st[2]),
                              __float_as_uint((c4 & 1) ? st[5] : st[4]), ep), c4 < 2);
            if (elected) TS(56);
            uint32_t cb[16], sh[16], gb[16];
#pragma unroll
            for (int i = 0; i < 16; i++) {
                const float4 c = tf[64 + i * 4];
                cb[i] = __float_as_uint(c.x); sh[i] = __float_as_uint(c.y); gb[i] = __float_as_uint(c.z);
            }
            const float ra = __uint_as_float(lds32(sb + SM_EP + 8)), rb0 = __uint_as_float(lds32(sb + SM_EP + 12));
#pragma unroll
            for (int i = 0; i < 32; i++) x2[i] = pack2(s[2 * i], s[2 * i + 1]);
            reg_fence(x2);
            uint4 r0, r1;
            for (;;) {
                r0 = ld_poll(g_stat + row * 4 + c4);
                r1 = ld_poll(g_stat + (row + 8) * 4 + c4);
                if (__all_sync(0xffffffffu, r0.w == ep && r1.w == ep)) break;
            }
            if (elected) TS(57);
            const float m0 = quad_sum(__uint_as_float(r0.x)) * (1.f / 512.f), m1 = quad_sum(__uint_as_float(r1.x)) * (1.f / 512.f);
            const float rs0 = ln_rstd(fmaxf(fmaf(-m0, m0, quad_sum(__uint_as_float(r0.y)) * (1.f / 512.f)), 0.f));
            const float rs1 = ln_rstd(fmaxf(fmaf(-m1, m1, quad_sum(__uint_as_float(r1.y)) * (1.f / 512.f)), 0.f));
            const uint32_t mb0 = pack2(m0, m0), mb1 = pack2(m1, m1);
            const uint32_t lg = pack2(fmaf(rs0, fmaf(-bf_lo(mb0), ra, quad_sum(__uint_as_float(r0.z))), rb0),
                                      fmaf(rs1, fmaf(-bf_lo(mb1), ra, quad_sum(__uint_as_float(r1.z))), rb0));
            const uint32_t u0 = lg << 16, u1 = lg & 0xffff0000u;
            const uint32_t k0 = ((u0 ^ (((int)u0 >> 31) | 0x80000000u)) & 0xffff0000u) | ((2047 - row) << 5) | (ep & 31);
            const uint32_t k1 = ((u1 ^ (((int)u1 >> 31) | 0x80000000u)) & 0xffff0000u) | ((2039 - row) << 5) | (ep & 31);
            const uint32_t kb = __reduce_max_sync(0xffffffffu, max(k0, k1));
            st_pub(g_key + cq * 128 + (row >> 4), kb, lane == 0);
            {
                uint32_t cx[18], ch[18];
#pragma unroll
                for (int i = 0; i < 16; i++) {
                    cx[i] = kb == k1 ? x2[2 * i + 1] : x2[2 * i];
                    ch[i] = ln_apply(cx[i], kb == k1 ? mb1 : mb0, kb == k1 ? rs1 : rs0, cb[i], sh[i]);
                }
                cx[16] = cx[17] = ch[16] = ch[17] = 0;
                uint4* cp = g_cand + (row >> 4) * 192 + cq * 24 + c4;
#pragma unroll
                for (int v = 0; v < 6; v++) st_pub(cp + v * 4, make_uint4(ch[3 * v], ch[3 * v + 1], ch[3 * v + 2], ep), kb == k0 || kb == k1);
#pragma unroll
                for (int v = 0; v < 6; v++) st_pub(cp + 96 + v * 4, make_uint4(cx[3 * v], cx[3 * v + 1], cx[3 * v + 2], ep), kb == k0 || kb == k1);
            }
            if (elected) TS(58);
            uint2 ov[16];
#pragma unroll
            for (int i = 0; i < 16; i++) {
                const int rh = i & 1, jj = i & 14;
                const uint32_t v0 = badd(x2[2 * jj + rh], bmul(gb[jj], ln_apply(x2[2 * jj + rh], rh ? mb1 : mb0, rh ? rs1 : rs0, cb[jj], sh[jj])));
                const uint32_t v1 = badd(x2[2 * jj + 2 + rh], bmul(gb[jj + 1], ln_apply(x2[2 * jj + 2 + rh], rh ? mb1 : mb0, rh ? rs1 : rs0, cb[jj + 1], sh[jj + 1])));
                const uint32_t rv = __shfl_xor_sync(0xffffffffu, (c4 & 1) ? v0 : v1, 1);
                ov[i] = (c4 & 1) ? make_uint2(rv, v1) : make_uint2(v0, rv);
            }
            uint2* op = reinterpret_cast<uint2*>(P.out) + row * 128 + cq * 32 + (c4 & 1) * 2 + (c4 >> 1);
#pragma unroll
            for (int i = 0; i < 16; i++)
                if (kb != ((i & 1) ? k1 : k0)) op[(i & 1) * 1024 + (i & 14) * 2] = ov[i];
            const uint32_t best = best_key(g_key + cq * 128, lane, ep);
            if (best != kb) {
#pragma unroll
                for (int i = 0; i < 16; i++)
                    if (kb == ((i & 1) ? k1 : k0)) op[(i & 1) * 1024 + (i & 14) * 2] = ov[i];
            }
            if (elected) TS(59);
        }
        mbar_arrive_if(sb + BAR_END, lane == 0);
    }
}

typedef CUresult (*EncodeFn)(CUtensorMap*, CUtensorMapDataType, cuuint32_t, void*, const cuuint64_t*, const cuuint64_t*,
                             const cuuint32_t*, const cuuint32_t*, CUtensorMapInterleave, CUtensorMapSwizzle,
                             CUtensorMapL2promotion, CUtensorMapFloatOOBfill);

void make_2d(EncodeFn fn, CUtensorMap* m, const void* p, uint64_t cols, uint64_t rows, uint32_t bc, uint32_t br) {
    cuuint64_t dims[2] = {cols, rows}, strides[1] = {cols * 2};
    cuuint32_t box[2] = {bc, br}, es[2] = {1, 1};
    fn(m, CU_TENSOR_MAP_DATA_TYPE_BFLOAT16, 2, const_cast<void*>(p), dims, strides, box, es, CU_TENSOR_MAP_INTERLEAVE_NONE,
       CU_TENSOR_MAP_SWIZZLE_NONE, CU_TENSOR_MAP_L2_PROMOTION_L2_128B, CU_TENSOR_MAP_FLOAT_OOB_FILL_NONE);
}
void make_3d(EncodeFn fn, CUtensorMap* m, const void* p, uint64_t cols, uint64_t rows) {
    cuuint64_t dims[3] = {64, rows, cols / 64}, strides[2] = {cols * 2, 128};
    cuuint32_t box[3] = {64, 128, 2}, es[3] = {1, 1, 1};
    fn(m, CU_TENSOR_MAP_DATA_TYPE_BFLOAT16, 3, const_cast<void*>(p), dims, strides, box, es, CU_TENSOR_MAP_INTERLEAVE_NONE,
       CU_TENSOR_MAP_SWIZZLE_128B, CU_TENSOR_MAP_L2_PROMOTION_L2_256B, CU_TENSOR_MAP_FLOAT_OOB_FILL_NONE);
}

}

extern "C" void kernel_launch(void* const* d_in, const int* in_sizes, int n_in, void* d_out, int out_size) {
    static EncodeFn fn = nullptr;
    static int sms = 0;
    if (!fn) {
        void* f = nullptr;
        cudaDriverEntryPointQueryResult st;
        cudaGetDriverEntryPoint("cuTensorMapEncodeTiled", &f, cudaEnableDefault, &st);
        fn = (EncodeFn)f;
        int dev = 0;
        cudaGetDevice(&dev);
        cudaDeviceGetAttribute(&sms, cudaDevAttrMultiProcessorCount, dev);
        cudaFuncSetAttribute(fused_kernel, cudaFuncAttributeMaxDynamicSharedMemorySize, SMEM_BYTES);
    }
    CUtensorMap ckv, wq, wuk, wuv, wo, wg, wu, wd, wm;
    make_3d(fn, &ckv, d_in[1], 512, 2048);
    make_3d(fn, &wq, d_in[2], 4096, 512);
    make_3d(fn, &wuk, d_in[3], 4096, 512);
    make_3d(fn, &wuv, d_in[4], 4096, 512);
    make_3d(fn, &wo, d_in[5], 512, 4096);
    make_2d(fn, &wg, d_in[8], 1792, 512, 16, 256);
    make_2d(fn, &wu, d_in[9], 1792, 512, 16, 256);
    make_2d(fn, &wd, d_in[10], 512, 1792, 8, 256);
    make_2d(fn, &wm, d_in[12], 3072, 512, 256, 64);
    Params p;
    p.x = (const bf16*)d_in[0];
    p.ckv = (const bf16*)d_in[1];
    p.wo = (const bf16*)d_in[5];
    p.wr = (const bf16*)d_in[7];
    p.wgate = (const bf16*)d_in[8];
    p.wup = (const bf16*)d_in[9];
    p.wdown = (const bf16*)d_in[10];
    p.c = (const bf16*)d_in[11];
    p.out = (bf16*)d_out;
    p.by_smid = sms == NCTA + NSPARE;
    fused_kernel<<<NCTA + NSPARE, 384, SMEM_BYTES>>>(ckv, wq, wuk, wuv, wo, wg, wu, wd, wm, p);
}
```

```cpp
#include <cuda.h>
#include <cuda_bf16.h>
#include <cuda_runtime.h>
#include <stdint.h>
#include <stdio.h>

namespace {

typedef __nv_bfloat16 bf16;
typedef unsigned long long u64;

constexpr int NCTA = 128, NSPARE = 4;
constexpr int SLOT = 32768;
constexpr int SM_BAR = 7 * SLOT;
constexpr int BAR_FULL = SM_BAR;
constexpr int BAR_EMPTY = BAR_FULL + 8 * 7;
constexpr int BAR_DONE = BAR_EMPTY + 8 * 7;
constexpr int BAR_FLAG = BAR_DONE + 8 * 9;
constexpr int BAR_PF = BAR_FLAG + 8 * 11;
constexpr int BAR_END = BAR_PF + 8;
constexpr int SM_EP = BAR_END + 8;
constexpr int SM_RED = SM_BAR + 384;
constexpr int SM_TAB = SM_BAR + 1024;
constexpr int SMEM_BYTES = SM_BAR + 3072;
constexpr int NFFN = 112;
#define HINT 29
constexpr u64 L2_NORMAL = 0x1000000000000000ull, L2_FIRST = 0x12F0000000000000ull;
#define PF0 0
#define PF1 13
#define PF2 11
#define UNR 4
#define LNQ 3
#define EARLY 7
constexpr uint32_t SPIN_LIMIT = 1u << 22;
constexpr uint32_t ONE2 = 0x3f803f80u;

struct Sync {
    uint32_t modcnt[2 * 32];
    uint32_t hcnt[16 * 8];
    uint32_t kvcnt[32 * 2 * 8];
    uint32_t ctxcnt[16 * 32];
    uint32_t rdcnt[16 * 2 * 8];
    uint32_t epoch[32];
};

__device__ __align__(1024) uint8_t g_KV[16 * 16 * 2 * SLOT];
__device__ __align__(1024) uint8_t g_ctx[16 * 32 * SLOT];
__device__ __align__(1024) uint8_t g_h[16 * 4 * SLOT];
__device__ __align__(1024) uint4 g_part[128 * 1024];
__device__ __align__(1024) uint4 g_stat[2048 * 4];
__device__ __align__(1024) bf16 g_mod[3072];
__device__ __align__(1024) uint4 g_cand[128 * 192];
__device__ __align__(1024) uint32_t g_key[4 * 128];
__device__ __align__(1024) uint32_t g_act[1792];
__device__ __align__(1024) Sync g_sync;
#define TS(i)

#define PT()

struct Params {
    const bf16 *x, *ckv, *wo, *wr, *wgate, *wup, *wdown, *c;
    bf16* out;
    int by_smid;
};

__device__ __forceinline__ void mbar_init(uint32_t bar, uint32_t cnt) {
    asm volatile("mbarrier.init.shared::cta.b64 [%0], %1;" ::"r"(bar), "r"(cnt) : "memory");
}
__device__ __forceinline__ void mbar_wait(uint32_t bar, uint32_t parity) {
    asm volatile("{\n.reg .pred p;\nL_%=:\nmbarrier.try_wait.parity.shared::cta.b64 p, [%0], %1;\n@!p bra L_%=;\n}" ::"r"(bar), "r"(parity) : "memory");
}
__device__ __forceinline__ void mbar_watch(uint32_t bar, uint32_t parity) {
    asm volatile("{\n.reg .pred p;\n.reg .u32 n;\nmov.u32 n, 0;\n"
                 "L_%=:\nmbarrier.try_wait.parity.shared::cta.b64 p, [%0], %1;\n@p bra D_%=;\n"
                 "add.u32 n, n, 1;\nsetp.lt.u32 p, n, %2;\n@p bra L_%=;\ntrap;\nD_%=:\n}"
                 ::"r"(bar), "r"(parity), "n"(SPIN_LIMIT) : "memory");
}
__device__ __forceinline__ void mbar_arrive(uint32_t bar) {
    asm volatile("mbarrier.arrive.shared::cta.b64 _, [%0];" ::"r"(bar) : "memory");
}
__device__ __forceinline__ void mbar_arrive_if(uint32_t bar, bool on) {
    asm volatile("{\n.reg .pred p;\nsetp.ne.s32 p, %1, 0;\n@p mbarrier.arrive.shared::cta.b64 _, [%0];\n}" ::"r"(bar), "r"((int)on) : "memory");
}
__device__ __forceinline__ void mbar_expect(uint32_t bar, uint32_t bytes) {
    asm volatile("mbarrier.arrive.expect_tx.shared::cta.b64 _, [%0], %1;" ::"r"(bar), "r"(bytes) : "memory");
}
__device__ __forceinline__ void tma2d(uint32_t dst, const CUtensorMap* m, int c0, int c1, uint32_t bar) {
    asm volatile("cp.async.bulk.tensor.2d.shared::cluster.global.mbarrier::complete_tx::bytes [%0], [%1, {%3, %4}], [%2];"
                 ::"r"(dst), "l"(m), "r"(bar), "r"(c0), "r"(c1) : "memory");
}
__device__ __forceinline__ void tma3d_prefetch(const CUtensorMap* m, int row, int cb) {
    asm volatile("cp.async.bulk.prefetch.tensor.3d.L2.global [%0, {%1, %2, %3}];" ::"l"(m), "r"(0), "r"(row), "r"(cb) : "memory");
}
__device__ __forceinline__ void l2_prefetch(const void* p, uint32_t bytes) {
    asm volatile("cp.async.bulk.prefetch.L2.global [%0], %1;" ::"l"(p), "r"(bytes) : "memory");
}
__device__ __forceinline__ void flag_wait(const uint32_t* f, uint32_t target) {
    asm volatile("{\n.reg .pred p;\n.reg .u32 v;\n"
                 "L_%=:\nld.acquire.gpu.global.u32 v, [%0];\nsub.u32 v, v, %1;\nsetp.lt.s32 p, v, 0;\n@p nanosleep.u32 100;\n@p bra L_%=;\n}"
                 ::"l"(f), "r"(target) : "memory");
}
__device__ __forceinline__ uint4 ld_poll(const uint4* p) {
    uint4 v;
    asm volatile("ld.relaxed.gpu.global.v4.u32 {%0, %1, %2, %3}, [%4];" : "=r"(v.x), "=r"(v.y), "=r"(v.z), "=r"(v.w) : "l"(p) : "memory");
    return v;
}
__device__ __forceinline__ uint2 ld_poll(const uint2* p) {
    uint2 v;
    asm volatile("ld.relaxed.gpu.global.v2.u32 {%0, %1}, [%2];" : "=r"(v.x), "=r"(v.y) : "l"(p) : "memory");
    return v;
}
__device__ __forceinline__ void st_pub(uint4* p, uint4 v, bool on) {
    asm volatile("{\n.reg .pred p;\nsetp.ne.s32 p, %5, 0;\n@p st.relaxed.gpu.global.v4.u32 [%0], {%1, %2, %3, %4};\n}"
                 ::"l"(p), "r"(v.x), "r"(v.y), "r"(v.z), "r"(v.w), "r"((int)on) : "memory");
}
__device__ __forceinline__ void st_pub(uint32_t* p, uint32_t v, bool on) {
    asm volatile("{\n.reg .pred p;\nsetp.ne.s32 p, %2, 0;\n@p st.relaxed.gpu.global.u32 [%0], %1;\n}" ::"l"(p), "r"(v), "r"((int)on) : "memory");
}
__device__ __forceinline__ void flag_add(uint32_t* p) {
    asm volatile("red.release.gpu.global.add.u32 [%0], 1;" ::"l"(p) : "memory");
}
__device__ __forceinline__ uint32_t lds32(uint32_t a) {
    uint32_t v;
    asm volatile("ld.shared.u32 %0, [%1];" : "=r"(v) : "r"(a) : "memory");
    return v;
}
__device__ __forceinline__ uint4 lds128(uint32_t a) {
    uint4 v;
    asm volatile("ld.shared.v4.u32 {%0, %1, %2, %3}, [%4];" : "=r"(v.x), "=r"(v.y), "=r"(v.z), "=r"(v.w) : "r"(a) : "memory");
    return v;
}
__device__ __forceinline__ void fence_async_global() { asm volatile("fence.proxy.async.global;" ::: "memory"); }
__device__ __forceinline__ void fence_async_smem() { asm volatile("fence.proxy.async.shared::cta;" ::: "memory"); }
__device__ __forceinline__ void bar_sync(int id, int n) { asm volatile("bar.sync %0, %1;" ::"r"(id), "r"(n) : "memory"); }
__device__ __forceinline__ void bar_arrive(int id, int n) { asm volatile("bar.arrive %0, %1;" ::"r"(id), "r"(n) : "memory"); }
__device__ __forceinline__ void wg_fence() { asm volatile("wgmma.fence.sync.aligned;" ::: "memory"); }
__device__ __forceinline__ void wg_commit() { asm volatile("wgmma.commit_group.sync.aligned;" ::: "memory"); }
template <int N> __device__ __forceinline__ void wg_wait() { asm volatile("wgmma.wait_group.sync.aligned %0;" ::"n"(N) : "memory"); }
template <int N> __device__ __forceinline__ void reg_fence(float (&d)[N]) {
#pragma unroll
    for (int i = 0; i < N; i++) asm volatile("" : "+f"(d[i])::"memory");
}
template <int N> __device__ __forceinline__ void reg_fence(uint32_t (&d)[N]) {
#pragma unroll
    for (int i = 0; i < N; i++) asm volatile("" : "+r"(d[i])::"memory");
}
__device__ __forceinline__ uint32_t desc_k(uint32_t a) { return (a >> 4) | (1u << 16); }
__device__ __forceinline__ uint32_t desc_mn(uint32_t a) { return (a >> 4) | (1024u << 16); }

template <int TB>
__device__ __forceinline__ void wgmma_ss128(float (&d)[64], uint32_t da, uint32_t db, int acc) {
    asm volatile("{\n.reg .pred p;\n.reg .b64 a, b;\nsetp.ne.b32 p, %66, 0;\nmov.b64 a, {%64, 0x40000040};\nmov.b64 b, {%65, 0x40000040};\n"
        "wgmma.mma_async.sync.aligned.m64n128k16.f32.bf16.bf16 {%0, %1, %2, %3, %4, %5, %6, %7, %8, %9, %10, %11, %12, %13, %14, %15, %16, %17, %18, %19, %20, %21, %22, %23, %24, %25, %26, %27, %28, %29, %30, %31, %32, %33, %34, %35, %36, %37, %38, %39, %40, %41, %42, %43, %44, %45, %46, %47, %48, %49, %50, %51, %52, %53, %54, %55, %56, %57, %58, %59, %60, %61, %62, %63}, a, b, p, 1, 1, 0, %67;\n}"
        : "+f"(d[0]), "+f"(d[1]), "+f"(d[2]), "+f"(d[3]), "+f"(d[4]), "+f"(d[5]), "+f"(d[6]), "+f"(d[7]), "+f"(d[8]), "+f"(d[9]), "+f"(d[10]), "+f"(d[11]), "+f"(d[12]), "+f"(d[13]), "+f"(d[14]), "+f"(d[15]), "+f"(d[16]), "+f"(d[17]), "+f"(d[18]), "+f"(d[19]), "+f"(d[20]), "+f"(d[21]), "+f"(d[22]), "+f"(d[23]), "+f"(d[24]), "+f"(d[25]), "+f"(d[26]), "+f"(d[27]), "+f"(d[28]), "+f"(d[29]), "+f"(d[30]), "+f"(d[31]), "+f"(d[32]), "+f"(d[33]), "+f"(d[34]), "+f"(d[35]), "+f"(d[36]), "+f"(d[37]), "+f"(d[38]), "+f"(d[39]), "+f"(d[40]), "+f"(d[41]), "+f"(d[42]), "+f"(d[43]), "+f"(d[44]), "+f"(d[45]), "+f"(d[46]), "+f"(d[47]), "+f"(d[48]), "+f"(d[49]), "+f"(d[50]), "+f"(d[51]), "+f"(d[52]), "+f"(d[53]), "+f"(d[54]), "+f"(d[55]), "+f"(d[56]), "+f"(d[57]), "+f"(d[58]), "+f"(d[59]), "+f"(d[60]), "+f"(d[61]), "+f"(d[62]), "+f"(d[63])
        : "r"(da), "r"(db), "r"(acc), "n"(TB));
}
template <int TB>
__device__ __forceinline__ void wgmma_ss128_init(float (&d)[64], uint32_t da, uint32_t db) {
    asm volatile("{\n.reg .pred p;\n.reg .b64 a, b;\nsetp.ne.b32 p, 0, 0;\nmov.b64 a, {%64, 0x40000040};\nmov.b64 b, {%65, 0x40000040};\n"
        "wgmma.mma_async.sync.aligned.m64n128k16.f32.bf16.bf16 {%0, %1, %2, %3, %4, %5, %6, %7, %8, %9, %10, %11, %12, %13, %14, %15, %16, %17, %18, %19, %20, %21, %22, %23, %24, %25, %26, %27, %28, %29, %30, %31, %32, %33, %34, %35, %36, %37, %38, %39, %40, %41, %42, %43, %44, %45, %46, %47, %48, %49, %50, %51, %52, %53, %54, %55, %56, %57, %58, %59, %60, %61, %62, %63}, a, b, p, 1, 1, 0, %66;\n}"
        : "=f"(d[0]), "=f"(d[1]), "=f"(d[2]), "=f"(d[3]), "=f"(d[4]), "=f"(d[5]), "=f"(d[6]), "=f"(d[7]), "=f"(d[8]), "=f"(d[9]), "=f"(d[10]), "=f"(d[11]), "=f"(d[12]), "=f"(d[13]), "=f"(d[14]), "=f"(d[15]), "=f"(d[16]), "=f"(d[17]), "=f"(d[18]), "=f"(d[19]), "=f"(d[20]), "=f"(d[21]), "=f"(d[22]), "=f"(d[23]), "=f"(d[24]), "=f"(d[25]), "=f"(d[26]), "=f"(d[27]), "=f"(d[28]), "=f"(d[29]), "=f"(d[30]), "=f"(d[31]), "=f"(d[32]), "=f"(d[33]), "=f"(d[34]), "=f"(d[35]), "=f"(d[36]), "=f"(d[37]), "=f"(d[38]), "=f"(d[39]), "=f"(d[40]), "=f"(d[41]), "=f"(d[42]), "=f"(d[43]), "=f"(d[44]), "=f"(d[45]), "=f"(d[46]), "=f"(d[47]), "=f"(d[48]), "=f"(d[49]), "=f"(d[50]), "=f"(d[51]), "=f"(d[52]), "=f"(d[53]), "=f"(d[54]), "=f"(d[55]), "=f"(d[56]), "=f"(d[57]), "=f"(d[58]), "=f"(d[59]), "=f"(d[60]), "=f"(d[61]), "=f"(d[62]), "=f"(d[63])
        : "r"(da), "r"(db), "n"(TB));
}
template <int TB>
__device__ __forceinline__ void wgmma_ss64(float (&d)[32], uint32_t da, uint32_t db, int acc) {
    asm volatile("{\n.reg .pred p;\n.reg .b64 a, b;\nsetp.ne.b32 p, %34, 0;\nmov.b64 a, {%32, 0x40000040};\nmov.b64 b, {%33, 0x40000040};\n"
        "wgmma.mma_async.sync.aligned.m64n64k16.f32.bf16.bf16 {%0, %1, %2, %3, %4, %5, %6, %7, %8, %9, %10, %11, %12, %13, %14, %15, %16, %17, %18, %19, %20, %21, %22, %23, %24, %25, %26, %27, %28, %29, %30, %31}, a, b, p, 1, 1, 0, %35;\n}"
        : "+f"(d[0]), "+f"(d[1]), "+f"(d[2]), "+f"(d[3]), "+f"(d[4]), "+f"(d[5]), "+f"(d[6]), "+f"(d[7]), "+f"(d[8]), "+f"(d[9]), "+f"(d[10]), "+f"(d[11]), "+f"(d[12]), "+f"(d[13]), "+f"(d[14]), "+f"(d[15]), "+f"(d[16]), "+f"(d[17]), "+f"(d[18]), "+f"(d[19]), "+f"(d[20]), "+f"(d[21]), "+f"(d[22]), "+f"(d[23]), "+f"(d[24]), "+f"(d[25]), "+f"(d[26]), "+f"(d[27]), "+f"(d[28]), "+f"(d[29]), "+f"(d[30]), "+f"(d[31])
        : "r"(da), "r"(db), "r"(acc), "n"(TB));
}
template <int TB>
__device__ __forceinline__ void wgmma_ss64_init(float (&d)[32], uint32_t da, uint32_t db) {
    asm volatile("{\n.reg .pred p;\n.reg .b64 a, b;\nsetp.ne.b32 p, 0, 0;\nmov.b64 a, {%32, 0x40000040};\nmov.b64 b, {%33, 0x40000040};\n"
        "wgmma.mma_async.sync.aligned.m64n64k16.f32.bf16.bf16 {%0, %1, %2, %3, %4, %5, %6, %7, %8, %9, %10, %11, %12, %13, %14, %15, %16, %17, %18, %19, %20, %21, %22, %23, %24, %25, %26, %27, %28, %29, %30, %31}, a, b, p, 1, 1, 0, %34;\n}"
        : "=f"(d[0]), "=f"(d[1]), "=f"(d[2]), "=f"(d[3]), "=f"(d[4]), "=f"(d[5]), "=f"(d[6]), "=f"(d[7]), "=f"(d[8]), "=f"(d[9]), "=f"(d[10]), "=f"(d[11]), "=f"(d[12]), "=f"(d[13]), "=f"(d[14]), "=f"(d[15]), "=f"(d[16]), "=f"(d[17]), "=f"(d[18]), "=f"(d[19]), "=f"(d[20]), "=f"(d[21]), "=f"(d[22]), "=f"(d[23]), "=f"(d[24]), "=f"(d[25]), "=f"(d[26]), "=f"(d[27]), "=f"(d[28]), "=f"(d[29]), "=f"(d[30]), "=f"(d[31])
        : "r"(da), "r"(db), "n"(TB));
}
__device__ __forceinline__ void wgmma_rs128(float (&d)[64], uint32_t a0, uint32_t a1, uint32_t a2, uint32_t a3, uint32_t db, int acc) {
    asm volatile("{\n.reg .pred p;\n.reg .b64 b;\nsetp.ne.b32 p, %69, 0;\nmov.b64 b, {%68, 0x40000040};\n"
        "wgmma.mma_async.sync.aligned.m64n128k16.f32.bf16.bf16 {%0, %1, %2, %3, %4, %5, %6, %7, %8, %9, %10, %11, %12, %13, %14, %15, %16, %17, %18, %19, %20, %21, %22, %23, %24, %25, %26, %27, %28, %29, %30, %31, %32, %33, %34, %35, %36, %37, %38, %39, %40, %41, %42, %43, %44, %45, %46, %47, %48, %49, %50, %51, %52, %53, %54, %55, %56, %57, %58, %59, %60, %61, %62, %63}, {%64, %65, %66, %67}, b, p, 1, 1, 1;\n}"
        : "+f"(d[0]), "+f"(d[1]), "+f"(d[2]), "+f"(d[3]), "+f"(d[4]), "+f"(d[5]), "+f"(d[6]), "+f"(d[7]), "+f"(d[8]), "+f"(d[9]), "+f"(d[10]), "+f"(d[11]), "+f"(d[12]), "+f"(d[13]), "+f"(d[14]), "+f"(d[15]), "+f"(d[16]), "+f"(d[17]), "+f"(d[18]), "+f"(d[19]), "+f"(d[20]), "+f"(d[21]), "+f"(d[22]), "+f"(d[23]), "+f"(d[24]), "+f"(d[25]), "+f"(d[26]), "+f"(d[27]), "+f"(d[28]), "+f"(d[29]), "+f"(d[30]), "+f"(d[31]), "+f"(d[32]), "+f"(d[33]), "+f"(d[34]), "+f"(d[35]), "+f"(d[36]), "+f"(d[37]), "+f"(d[38]), "+f"(d[39]), "+f"(d[40]), "+f"(d[41]), "+f"(d[42]), "+f"(d[43]), "+f"(d[44]), "+f"(d[45]), "+f"(d[46]), "+f"(d[47]), "+f"(d[48]), "+f"(d[49]), "+f"(d[50]), "+f"(d[51]), "+f"(d[52]), "+f"(d[53]), "+f"(d[54]), "+f"(d[55]), "+f"(d[56]), "+f"(d[57]), "+f"(d[58]), "+f"(d[59]), "+f"(d[60]), "+f"(d[61]), "+f"(d[62]), "+f"(d[63])
        : "r"(a0), "r"(a1), "r"(a2), "r"(a3), "r"(db), "r"(acc));
}

__device__ __forceinline__ uint32_t pack2(float lo, float hi) {
    uint32_t r;
    asm("cvt.rn.bf16x2.f32 %0, %1, %2;" : "=r"(r) : "f"(hi), "f"(lo));
    return r;
}
__device__ __forceinline__ float bf_lo(uint32_t v) { return __uint_as_float(v << 16); }
__device__ __forceinline__ float bf_hi(uint32_t v) { return __uint_as_float(v & 0xffff0000u); }
__device__ __forceinline__ float rbf(float v) { return bf_lo(pack2(v, v)); }
__device__ __forceinline__ uint32_t badd(uint32_t a, uint32_t b) {
    uint32_t r;
    asm("add.rn.bf16x2 %0, %1, %2;" : "=r"(r) : "r"(a), "r"(b));
    return r;
}
__device__ __forceinline__ uint32_t bsub(uint32_t a, uint32_t b) {
    uint32_t r;
    asm("sub.rn.bf16x2 %0, %1, %2;" : "=r"(r) : "r"(a), "r"(b));
    return r;
}
__device__ __forceinline__ uint32_t bmul(uint32_t a, uint32_t b) {
    uint32_t r;
    asm("mul.rn.bf16x2 %0, %1, %2;" : "=r"(r) : "r"(a), "r"(b));
    return r;
}
__device__ __forceinline__ uint32_t ln_apply(uint32_t x, uint32_t mb, float rs, uint32_t scale, uint32_t shift) {
    const uint32_t d = bsub(x, mb);
    return badd(bmul(pack2(bf_lo(d) * rs, bf_hi(d) * rs), scale), shift);
}
__device__ __forceinline__ float ex2(float v) {
    float r;
    asm("ex2.approx.ftz.f32 %0, %1;" : "=f"(r) : "f"(v));
    return r;
}
__device__ __forceinline__ float rcp(float v) {
    float r;
    asm("rcp.approx.ftz.f32 %0, %1;" : "=f"(r) : "f"(v));
    return r;
}
__device__ __forceinline__ float sqrt_fast(float v) {
    float r;
    asm("sqrt.approx.ftz.f32 %0, %1;" : "=f"(r) : "f"(v));
    return r;
}
__device__ __forceinline__ float ln_rstd(float var) { return rcp(rbf(sqrt_fast(rbf(rbf(var) + 1e-5f)))); }
__device__ __forceinline__ float sigmoid(float v) { return rcp(1.f + ex2(-1.4426950408889634f * v)); }
__device__ __forceinline__ float warp_sum(float v) {
#pragma unroll
    for (int o = 16; o > 0; o >>= 1) v += __shfl_xor_sync(0xffffffffu, v, o);
    return v;
}
__device__ __forceinline__ float quad_sum(float v) {
    v += __shfl_xor_sync(0xffffffffu, v, 1);
    return v + __shfl_xor_sync(0xffffffffu, v, 2);
}

template <int M, int RH>
__device__ __forceinline__ uint4 img_pack(const float (&d)[64], float s) {
    uint4 v;
    v.x = pack2(d[16 * M + 2 * RH] * s, d[16 * M + 2 * RH + 1] * s);
    v.y = pack2(d[16 * M + 4 + 2 * RH] * s, d[16 * M + 5 + 2 * RH] * s);
    v.z = pack2(d[16 * M + 8 + 2 * RH] * s, d[16 * M + 9 + 2 * RH] * s);
    v.w = pack2(d[16 * M + 12 + 2 * RH] * s, d[16 * M + 13 + 2 * RH] * s);
    return v;
}
template <int M, int RH>
__device__ __forceinline__ uint4 img_pack(const float (&d)[64]) {
    uint4 v;
    v.x = pack2(d[16 * M + 2 * RH], d[16 * M + 2 * RH + 1]);
    v.y = pack2(d[16 * M + 4 + 2 * RH], d[16 * M + 5 + 2 * RH]);
    v.z = pack2(d[16 * M + 8 + 2 * RH], d[16 * M + 9 + 2 * RH]);
    v.w = pack2(d[16 * M + 12 + 2 * RH], d[16 * M + 13 + 2 * RH]);
    return v;
}
template <int M, int RH>
__device__ __forceinline__ uint32_t img_off(uint32_t toff) { return (toff ^ ((M & 1) * 64)) + (M >> 1) * 16384 + RH * 1024; }
template <int M>
__device__ __forceinline__ void img_store_global(uint8_t* img, uint32_t toff, const float (&d)[64]) {
    uint4* p = reinterpret_cast<uint4*>(img + (toff ^ ((M & 1) * 64)));
    p[(M >> 1) * 1024] = img_pack<M, 0>(d);
    p[(M >> 1) * 1024 + 64] = img_pack<M, 1>(d);
}
__device__ __forceinline__ void sts128(uint32_t a, uint4 v) {
    asm volatile("st.shared.v4.b32 [%0], {%1, %2, %3, %4};" ::"r"(a), "r"(v.x), "r"(v.y), "r"(v.z), "r"(v.w) : "memory");
}
constexpr float SM_C = 0.08838834764831845f * 1.4426950408889634f;
__device__ __forceinline__ void q_store(uint32_t a, uint32_t toff, const float (&d)[64]) {
    sts128(a + img_off<0, 0>(toff), img_pack<0, 0>(d, SM_C)); sts128(a + img_off<0, 1>(toff), img_pack<0, 1>(d, SM_C));
    sts128(a + img_off<1, 0>(toff), img_pack<1, 0>(d, SM_C)); sts128(a + img_off<1, 1>(toff), img_pack<1, 1>(d, SM_C));
    sts128(a + img_off<2, 0>(toff), img_pack<2, 0>(d, SM_C)); sts128(a + img_off<2, 1>(toff), img_pack<2, 1>(d, SM_C));
    sts128(a + img_off<3, 0>(toff), img_pack<3, 0>(d, SM_C)); sts128(a + img_off<3, 1>(toff), img_pack<3, 1>(d, SM_C));
}
__device__ __forceinline__ void ctx_store(uint8_t* img, uint32_t toff, const float (&o)[64], float i0, float i1) {
    asm volatile("" : "+r"(toff));
    uint4 *p0 = reinterpret_cast<uint4*>(img + toff), *p1 = reinterpret_cast<uint4*>(img + (toff ^ 64));
    p0[0] = img_pack<0, 0>(o, i0);
    p1[0] = img_pack<1, 0>(o, i0);
    p0[64] = img_pack<0, 1>(o, i1);
    p1[64] = img_pack<1, 1>(o, i1);
    p0[1024] = img_pack<2, 0>(o, i0);
    p1[1024] = img_pack<3, 0>(o, i0);
    p0[1088] = img_pack<2, 1>(o, i1);
    p1[1088] = img_pack<3, 1>(o, i1);
}

__device__ __forceinline__ void slot_wait(uint32_t bars, uint32_t& ph, uint32_t slot) {
    mbar_wait(bars + 8 * slot, (ph >> slot) & 1);
    ph ^= 1u << slot;
}
__device__ __forceinline__ void load_image(uint32_t sb, uint32_t& ph, uint32_t slot, const void* src, bool first) {
    slot_wait(sb + BAR_EMPTY, ph, slot);
    asm volatile("{\n.reg .pred p;\nelect.sync _|p, 0xffffffff;\n@p mbarrier.arrive.expect_tx.shared::cta.b64 _, [%2], 32768;\n"
                 "@p cp.async.bulk.shared::cluster.global.mbarrier::complete_tx::bytes.L2::cache_hint [%0], [%1], 32768, [%2], %3;\n}"
                 ::"r"(sb + slot * SLOT), "l"(src), "r"(sb + BAR_FULL + 8 * slot), "l"(first ? L2_FIRST : L2_NORMAL) : "memory");
}
__device__ __forceinline__ void load_tile(uint32_t sb, uint32_t& ph, uint32_t slot, const CUtensorMap* m, int row, int cb, bool first) {
    slot_wait(sb + BAR_EMPTY, ph, slot);
    asm volatile("{\n.reg .pred p;\nelect.sync _|p, 0xffffffff;\n@p mbarrier.arrive.expect_tx.shared::cta.b64 _, [%2], 32768;\n"
                 "@p cp.async.bulk.tensor.3d.shared::cluster.global.mbarrier::complete_tx::bytes.L2::cache_hint [%0], [%1, {%3, %4, %5}], [%2], %6;\n}"
                 ::"r"(sb + slot * SLOT), "l"(m), "r"(sb + BAR_FULL + 8 * slot), "r"(0), "r"(row), "r"(cb), "l"(first ? L2_FIRST : L2_NORMAL) : "memory");
}
__device__ __forceinline__ uint32_t ring_next(uint32_t r) { return r == 4 ? 0 : r + 1; }
__device__ __forceinline__ uint32_t w_table(int hp) { return hp ? 0x3104u : 0x4210u; }
__device__ __forceinline__ uint32_t a_table(int hp) { return hp ? 0x625u : 0x635u; }
__device__ __forceinline__ uint32_t a_next(uint32_t& t) {
    const uint32_t s = t & 15;
    t = (t >> 4) | (s << 8);
    return s;
}
constexpr uint32_t O_TABLE = 0x2160435u;
__device__ __forceinline__ uint32_t o_next(uint32_t& t) {
    const uint32_t s = t & 15;
    t = (t >> 4) | (s << 24);
    return s;
}
__device__ __forceinline__ int o_head(int i, int kh) { return i < 16 ? 4 * (i & 7) + 2 * (kh ^ 1) + (i >> 3) : 29 + 2 * kh; }

__device__ __forceinline__ void gemm_issue(float (&d)[64], uint32_t a, uint32_t b, int acc) {
    wg_fence();
#pragma unroll
    for (int k = 0; k < 8; k++) wgmma_ss128<1>(d, a + (k >> 2) * 1024 + (k & 3) * 2, b + k * 128, k ? 1 : acc);
    wg_commit();
}

__device__ __forceinline__ void gemm_issue_init(float (&d)[64], uint32_t a, uint32_t b) {
    wg_fence();
    wgmma_ss128_init<1>(d, a, b);
#pragma unroll
    for (int k = 1; k < 8; k++) wgmma_ss128<1>(d, a + (k >> 2) * 1024 + (k & 3) * 2, b + k * 128, 1);
    wg_commit();
}

template <bool ODD>
__device__ __forceinline__ void proj_tile(float (&acc)[64], float (&prev)[64], int t, int q0, uint32_t sb, int wg, bool elected, uint32_t& fph,
                                          uint32_t wtab, uint32_t& atab, uint8_t* prev_img, uint32_t toff, bool first,
                                          const bf16* x, int xrow) {
    const uint32_t a0 = desc_k(sb + (wg ^ (ODD && t == 5)) * 8192), b0 = desc_mn(sb);
    const int lane = threadIdx.x & 31;
    uint32_t xn[16];
#pragma unroll
    for (int i = 0; i < 4; i++) {
        uint4 v = make_uint4(0, 0, 0, 0);
        if (ODD && first) v = __ldg(reinterpret_cast<const uint4*>(x) + xrow * 64 + lane + 32 * i);
        xn[4 * i] = v.x; xn[4 * i + 1] = v.y; xn[4 * i + 2] = v.z; xn[4 * i + 3] = v.w;
    }
    constexpr int U = ODD ? UNR : 1;
#pragma unroll U
    for (int q = ODD ? 0 : q0; q < 4; q++) {
        if (ODD && t == 5 && q == 3) break;
        const uint32_t ws = (wtab >> (4 * q)) & 15, as = a_next(atab);
        if (!ODD && t != 2) slot_wait(sb + BAR_FULL, fph, ws);
        slot_wait(sb + BAR_FULL, fph, as);
        bar_sync(1 + wg, 256);
        gemm_issue(acc, a0 + as * (SLOT / 16), b0 + ws * (SLOT / 16), q);
        bar_arrive(2 - wg, 256);
        wg_wait<1>();
        reg_fence(prev);
        if (ODD && t == 5) {
            if (q == 2) {
                q_store(sb + 5 * SLOT, toff ^ 8192, prev);
                fence_async_smem();
            }
        } else if (ODD || t != 0) {
            if (q == 0) img_store_global<0>(prev_img, toff, prev);
            if (q == 1) img_store_global<1>(prev_img, toff, prev);
            if (q == 2) img_store_global<2>(prev_img, toff, prev);
            if (q == 3) img_store_global<3>(prev_img, toff, prev);
        }
        if (ODD && q == 1 && first) {
            float sum[2] = {0.f, 0.f}, sq[2] = {0.f, 0.f};
#pragma unroll
            for (int k = 0; k < 16; k++) sum[k >> 3] += bf_lo(xn[k]) + bf_hi(xn[k]);
#pragma unroll
            for (int i = 0; i < 2; i++) sum[i] = warp_sum(sum[i]) * (1.f / 512.f);
#pragma unroll
            for (int k = 0; k < 16; k++) {
                const float d0 = bf_lo(xn[k]) - sum[k >> 3], d1 = bf_hi(xn[k]) - sum[k >> 3];
                sq[k >> 3] = fmaf(d0, d0, fmaf(d1, d1, sq[k >> 3]));
            }
#pragma unroll
            for (int i = 0; i < 2; i++) sq[i] = ln_rstd(warp_sum(sq[i]) * (1.f / 512.f));
#pragma unroll
            for (int k = 0; k < 16; k++) {
                const uint32_t d = bsub(xn[k], pack2(sum[k >> 3], sum[k >> 3]));
                xn[k] = pack2(bf_lo(d) * sq[k >> 3], bf_hi(d) * sq[k >> 3]);
            }
        }
        if (ODD && q == LNQ && first) {
            mbar_wait(sb + BAR_FLAG + 8 * 8, 0);
#pragma unroll
            for (int i = 0; i < 4; i++) {
                const int rin = (xrow + (i >> 1)) & 127;
                const uint4 a = lds128(sb + SM_TAB + 1024 + (i & 1) * 512 + lane * 16), c = lds128(sb + SM_TAB + (i & 1) * 512 + lane * 16);
                *reinterpret_cast<uint4*>(g_h + ((xrow >> 7) * 8 + (i & 1) * 4 + (lane >> 3)) * 16384 + rin * 128 + (((lane ^ rin) & 7) << 4)) =
                    make_uint4(badd(bmul(xn[4 * i], badd(a.x, ONE2)), c.x), badd(bmul(xn[4 * i + 1], badd(a.y, ONE2)), c.y),
                               badd(bmul(xn[4 * i + 2], badd(a.z, ONE2)), c.z), badd(bmul(xn[4 * i + 3], badd(a.w, ONE2)), c.w));
            }
            __syncwarp();
            mbar_arrive_if(sb + BAR_DONE, lane == 0);
        }
        wg_wait<0>();
        mbar_arrive_if(sb + BAR_EMPTY + 8 * as, elected && !(ODD && (q & 1) && t == 5));
        if (ODD) mbar_arrive_if(sb + BAR_EMPTY + 8 * ws, elected && t != 1);
    }
    reg_fence(acc);
}

__device__ __forceinline__ void qk_issue(float (&s)[64], uint32_t q, uint32_t k) {
    wg_fence();
    wgmma_ss128_init<0>(s, q, k);
#pragma unroll
    for (int i = 1; i < 8; i++) wgmma_ss128<0>(s, q + (i >> 2) * 1024 + (i & 3) * 2, k + (i >> 2) * 1024 + (i & 3) * 2, 1);
    wg_commit();
}
__device__ __forceinline__ void qk_issue(float (&s)[32], uint32_t q, uint32_t k) {
    wg_fence();
    wgmma_ss64_init<0>(s, q, k);
#pragma unroll
    for (int i = 1; i < 8; i++) wgmma_ss64<0>(s, q + (i >> 2) * 1024 + (i & 3) * 2, k + (i >> 2) * 1024 + (i & 3) * 2, 1);
    wg_commit();
}
__device__ __forceinline__ void pv_issue(float (&o)[64], const uint32_t (&p)[32], uint32_t v, int acc, bool half) {
    if (half) {
        asm volatile("// half" ::: "memory");
        wg_fence();
#pragma unroll
        for (int i = 0; i < 4; i++) wgmma_rs128(o, p[4 * i], p[4 * i + 1], p[4 * i + 2], p[4 * i + 3], v + i * 128, i ? 1 : acc);
        wg_commit();
        asm volatile("// half" ::: "memory");
    } else {
        wg_fence();
#pragma unroll
        for (int i = 0; i < 8; i++) wgmma_rs128(o, p[4 * i], p[4 * i + 1], p[4 * i + 2], p[4 * i + 3], v + i * 128, i ? 1 : acc);
        wg_commit();
    }
}
template <int B, int N>
__device__ __forceinline__ void tri_mask(float (&s)[N], int x) {
#pragma unroll
    for (int k = 0; k < 7; k++)
        asm("{\n.reg .pred p, q;\nsetp.lt.s32 p, %4, %5;\nsetp.le.s32 q, %4, %5;\n"
            "@p mov.b32 %0, 0fFF800000;\n@q mov.b32 %1, 0fFF800000;\n@p mov.b32 %2, 0fFF800000;\n@q mov.b32 %3, 0fFF800000;\n}"
            : "+f"(s[B + 4 * k]), "+f"(s[B + 4 * k + 1]), "+f"(s[B + 4 * k + 6]), "+f"(s[B + 4 * k + 7]) : "r"(x), "r"(8 * k));
    asm("{\n.reg .pred p, q;\nsetp.lt.s32 p, %2, 56;\nsetp.le.s32 q, %2, 56;\n@p mov.b32 %0, 0fFF800000;\n@q mov.b32 %1, 0fFF800000;\n}"
        : "+f"(s[B + 28]), "+f"(s[B + 29]) : "r"(x));
}
__device__ __forceinline__ void tri_mask_copy(float (&s)[64], const float (&h)[32], int x) {
#pragma unroll
    for (int i = 0; i < 32; i++) {
        asm("{\n.reg .pred p;\nsetp.lt.s32 p, %2, %3;\nselp.f32 %0, 0fFF800000, %1, p;\n}"
            : "=f"(s[i]) : "f"(h[i]), "r"(x), "r"(8 * (i >> 2) - 4 * (i & 2) + (i & 1)));
        s[32 + i] = __uint_as_float(0xff800000u);
    }
}
constexpr float SM_HI = 1152921504606846976.f, SM_LO = 1.f / 1152921504606846976.f;
__device__ __forceinline__ bool softmax_unsafe(float t0, float t1, bool first) {
    bool bad = __any_sync(0xffffffffu, fmaxf(t0, t1) > SM_HI);
    if (first) {
        uint32_t a = __ballot_sync(0xffffffffu, t0 >= SM_LO), b = __ballot_sync(0xffffffffu, t1 >= SM_LO);
        a |= a >> 1;
        b |= b >> 1;
        bad |= ((a | (a >> 2)) & (b | (b >> 2)) & 0x11111111u) != 0x11111111u;
    }
    return bad;
}
__device__ __forceinline__ void softmax_shift(float (&s)[64], float d0, float d1) {
#pragma unroll
    for (int i = 0; i < 64; i++) s[i] -= (i & 2) ? d1 : d0;
}
__device__ __forceinline__ void softmax_remax(float (&s)[64], float (&m)[2], bool first, float& a0, float& a1) {
    float m0 = fmaxf(s[0], s[1]), m1 = fmaxf(s[2], s[3]);
#pragma unroll
    for (int k = 1; k < 16; k++) {
        m0 = fmaxf(m0, fmaxf(s[4 * k], s[4 * k + 1]));
        m1 = fmaxf(m1, fmaxf(s[4 * k + 2], s[4 * k + 3]));
    }
    m0 = fmaxf(m0, __shfl_xor_sync(0xffffffffu, m0, 1));
    m1 = fmaxf(m1, __shfl_xor_sync(0xffffffffu, m1, 1));
    m0 = fmaxf(m0, __shfl_xor_sync(0xffffffffu, m0, 2));
    m1 = fmaxf(m1, __shfl_xor_sync(0xffffffffu, m1, 2));
    if (!first) {
        m0 = fmaxf(m0, 0.f);
        m1 = fmaxf(m1, 0.f);
    }
    a0 = first ? 1.f : ex2(-m0);
    a1 = first ? 1.f : ex2(-m1);
    m[0] += m0;
    m[1] += m1;
    softmax_shift(s, m0, m1);
}
template <int J0, int J1>
__device__ __forceinline__ void softmax_exp(const float (&s)[64], uint32_t (&p)[32], float (&t)[4]) {
#pragma unroll
    for (int k = J0; k < J1; k++) {
        const float e0 = ex2(s[4 * k]), e1 = ex2(s[4 * k + 1]), e2 = ex2(s[4 * k + 2]), e3 = ex2(s[4 * k + 3]);
        if (k == 0) { t[0] = e0; t[1] = e1; t[2] = e2; t[3] = e3; }
        else { t[0] += e0; t[1] += e1; t[2] += e2; t[3] += e3; }
        p[2 * k] = pack2(e0, e1);
        p[2 * k + 1] = pack2(e2, e3);
    }
}
__device__ __forceinline__ void fma8(float (&acc)[8], float a, uint4 w) {
    acc[0] = fmaf(a, bf_lo(w.x), acc[0]); acc[1] = fmaf(a, bf_hi(w.x), acc[1]);
    acc[2] = fmaf(a, bf_lo(w.y), acc[2]); acc[3] = fmaf(a, bf_hi(w.y), acc[3]);
    acc[4] = fmaf(a, bf_lo(w.z), acc[4]); acc[5] = fmaf(a, bf_hi(w.z), acc[5]);
    acc[6] = fmaf(a, bf_lo(w.w), acc[6]); acc[7] = fmaf(a, bf_hi(w.w), acc[7]);
}
__device__ __forceinline__ void mma16816(float (&d)[4], const uint32_t* a, uint32_t b0, uint32_t b1) {
    asm("mma.sync.aligned.m16n8k16.row.col.f32.bf16.bf16.f32 {%0, %1, %2, %3}, {%4, %5, %6, %7}, {%8, %9}, {%0, %1, %2, %3};"
        : "+f"(d[0]), "+f"(d[1]), "+f"(d[2]), "+f"(d[3]) : "r"(a[0]), "r"(a[1]), "r"(a[2]), "r"(a[3]), "r"(b0), "r"(b1));
}
__device__ __forceinline__ uint32_t best_key(const uint32_t* keys, int lane, uint32_t ep) {
    uint32_t best;
#pragma unroll 1
    for (;;) {
        const uint4 k = ld_poll(reinterpret_cast<const uint4*>(keys) + lane);
        best = max(max(k.x, k.y), max(k.z, k.w));
        if (__all_sync(0xffffffffu, (((k.x ^ ep) | (k.y ^ ep) | (k.z ^ ep) | (k.w ^ ep)) & 31) == 0)) break;
    }
    return __reduce_max_sync(0xffffffffu, best);
}

__global__ void __launch_bounds__(384, 1)
fused_kernel(const __grid_constant__ CUtensorMap tm_ckv, const __grid_constant__ CUtensorMap tm_wq,
             const __grid_constant__ CUtensorMap tm_wuk, const __grid_constant__ CUtensorMap tm_wuv,
             const __grid_constant__ CUtensorMap tm_wo, const __grid_constant__ CUtensorMap tm_wg,
             const __grid_constant__ CUtensorMap tm_wu, const __grid_constant__ CUtensorMap tm_wd,
             const __grid_constant__ CUtensorMap tm_wm, const Params P) {
    extern __shared__ __align__(1024) uint8_t smem[];
    const uint32_t sb = (uint32_t)__cvta_generic_to_shared(smem);
    const int tid = threadIdx.x, lane = tid & 31, warp = __shfl_sync(0xffffffffu, tid >> 5, 0), wg = warp >> 2;
    uint32_t sm;
    asm("mov.u32 %0, %%smid;" : "=r"(sm));
    const uint32_t smq = ((sm - 64) * 147) >> 11;
    const int rb = !P.by_smid ? blockIdx.x : sm < 64 ? (sm & 14) * 8 + (sm >> 4) * 2 + (sm & 1)
                 : sm < 120 ? ((sm - 64 - smq * 14) & 14) * 8 + 24 + smq * 2 + (sm & 1) : sm < 124 ? sm + 8 : sm - 116;
    const int grp = rb >> 3, j = rb & 7, cq = j & 3, kh = grp & 1, ort = (grp & 14) + (j >> 2);
    if (warp == 0) TS(0);

    if (rb >= NCTA) {
        float* sc = reinterpret_cast<float*>(smem + 6 * SLOT);
        float* red = sc + 512;
        if (tid == 256) {
            for (int i = 0; i < 6; i++) { mbar_init(sb + BAR_FULL + 8 * i, 1); mbar_init(sb + BAR_EMPTY + 8 * i, 8); }
            fence_async_smem();
        }
        __syncthreads();
        uint32_t ph = 0, sl = 0;
        if (tid == 256) {
#pragma unroll 1
            for (int i = 0; i < 24; i++) {
                mbar_wait(sb + BAR_EMPTY + 8 * sl, ph ^ 1);
                mbar_expect(sb + BAR_FULL + 8 * sl, SLOT);
                tma2d(sb + sl * SLOT, &tm_wm, (i >> 3) * 1024 + (rb - NCTA) * 256, (i & 7) * 64, sb + BAR_FULL + 8 * sl);
                if (++sl == 6) { sl = 0; ph ^= 1; }
            }
        } else if (tid < 256) {
            const uint32_t c2 = __ldg(reinterpret_cast<const uint32_t*>(P.c) + tid);
            sc[2 * tid] = rbf(bf_lo(c2) * sigmoid(bf_lo(c2)));
            sc[2 * tid + 1] = rbf(bf_hi(c2) * sigmoid(bf_hi(c2)));
            bar_sync(1, 256);
#pragma unroll 1
            for (int ps = 0; ps < 3; ps++) {
                float acc[8] = {0.f, 0.f, 0.f, 0.f, 0.f, 0.f, 0.f, 0.f};
#pragma unroll 1
                for (int bt = 0; bt < 8; bt++) {
                    mbar_wait(sb + BAR_FULL + 8 * sl, ph);
#pragma unroll
                    for (int i = 0; i < 8; i++)
                        fma8(acc, sc[bt * 64 + warp * 8 + i], *reinterpret_cast<const uint4*>(smem + sl * SLOT + (warp * 8 + i) * 512 + lane * 16));
                    __syncwarp();
                    mbar_arrive_if(sb + BAR_EMPTY + 8 * sl, lane == 0);
                    if (++sl == 6) { sl = 0; ph ^= 1; }
                }
                *reinterpret_cast<float4*>(red + warp * 256 + lane * 8) = make_float4(acc[0], acc[1], acc[2], acc[3]);
                *reinterpret_cast<float4*>(red + warp * 256 + lane * 8 + 4) = make_float4(acc[4], acc[5], acc[6], acc[7]);
                bar_sync(1, 256);
                float v = 0.f;
#pragma unroll
                for (int i = 0; i < 8; i++) v += red[i * 256 + tid];
                g_mod[ps * 1024 + (rb - NCTA) * 256 + tid] = __float2bfloat16_rn(v);
                bar_sync(1, 256);
                if (tid == 0 && ps != 1) flag_add(&g_sync.modcnt[(ps >> 1) * 32]);
                if (warp == 0) TS(1 + ps);
            }
        }
        return;
    }

    if (tid == 256) {
        if (sb & 1023) __trap();
        asm volatile("prefetch.tensormap [%0];" ::"l"((j & 1) ? &tm_wuv : &tm_wuk) : "memory");
        asm volatile("prefetch.tensormap [%0];" ::"l"(&tm_ckv) : "memory");
        for (int i = 0; i < 7; i++) { mbar_init(sb + BAR_FULL + 8 * i, 1); mbar_init(sb + BAR_EMPTY + 8 * i, 2); }
        for (int i = 0; i < 9; i++) mbar_init(sb + BAR_DONE + 8 * i, 8);
        for (int i = 0; i < 12; i++) mbar_init(sb + BAR_FLAG + 8 * i, 1);
        mbar_init(sb + BAR_END, 8);
        fence_async_smem();
    }
    __syncthreads();

    if (wg == 2) {
        asm volatile("setmaxnreg.dec.sync.aligned.u32 40;");
        if (warp == 8) {
            uint32_t eph = 0x7f, r = 0;
            const CUtensorMap* tw = (j & 1) ? &tm_wuv : &tm_wuk;
#pragma unroll 1
            for (int hp = 0; hp < 2; hp++) {
                const int hc = 4 * grp + 2 * hp;
                uint32_t wtab = w_table(hp), atab = a_table(hp);
#pragma unroll 1
                for (int u = 0; u < 4; u++) {
                    load_tile(sb, eph, (wtab >> (4 * u)) & 15, tw, u * 128, hc, HINT & 1); PT();
                    load_tile(sb, eph, a_next(atab), &tm_ckv, (j >> 1) * 128, u * 2, (HINT & 8) && hp); PT();
                    if (hp == 1 && (u & 1) && lane == 0) asm volatile("red.relaxed.gpu.global.add.u32 [%0], 1;" ::"l"(&g_sync.rdcnt[(grp * 2 + (u >> 1)) * 8]) : "memory");
                }
#pragma unroll 1
                for (int u = 4; u < 16; u++) {
                    if (hp == 1 && (u & 7) == 4) mbar_wait(sb + BAR_FLAG + 24 + (u & 8), 0);
                    load_tile(sb, eph, a_next(atab), &tm_ckv, ((u & 12) + (j >> 1)) * 128, (u & 3) * 2, (HINT & 8) && hp); PT();
                }
                mbar_wait(sb + BAR_FLAG, 0);
                fence_async_global();
#pragma unroll 1
                for (int u = 0; u < 4; u++) {
                    load_tile(sb, eph, (wtab >> (4 * u)) & 15, &tm_wq, u * 128, hc, HINT & 1); PT();
                    load_image(sb, eph, a_next(atab), g_h + ((15 - j) * 4 + u) * SLOT, (HINT & 8) && hp); PT();
                }
                mbar_wait(sb + BAR_FLAG + 8 + 32 * hp, 0);
                fence_async_global();
#pragma unroll 1
                for (int u = 0; u < 4; u++) { load_image(sb, eph, a_next(atab), g_h + (j * 4 + u) * SLOT, (HINT & 8) && hp); PT(); }
                const uint8_t* kv = g_KV + (size_t)(grp * 32 + 30 * hp) * SLOT;
                const int step = hp ? -2 * SLOT : 2 * SLOT;
                load_image(sb, eph, r, kv, HINT & 4); PT();
                r = ring_next(r);
#pragma unroll 1
                for (int n = 1; n <= 16; n++) {
                    if (n == 8) {
                        mbar_wait(sb + BAR_FLAG + 16 + 32 * hp, 0);
                        fence_async_global();
                    }
                    mbar_arrive_if(sb + BAR_PF, lane == 0 && (n == PF1 || n == PF2));
                    const uint8_t* v = kv + SLOT;
                    kv += n < 16 - j ? step : n == 16 - j ? (2 * j - 15) * step : -step;
                    load_image(sb, eph, r, kv, HINT & 4); PT();
                    r = ring_next(r);
                    load_image(sb, eph, r, v, HINT & 4); PT();
                    r = ring_next(r);
                }
                load_image(sb, eph, r, kv + SLOT, HINT & 4); PT();
                r = ring_next(r);
            }
            uint32_t otab = O_TABLE;
#pragma unroll 1
            for (int i = 0; i < 17; i++) {
                if ((i & 7) == 0) {
                    mbar_wait(sb + BAR_FLAG + 8 * 9 + (i ? 8 : 0), 0);
                    fence_async_global();
                }
                const int head = o_head(i, kh);
                load_image(sb, eph, o_next(otab), g_ctx + (size_t)(ort * 32 + head) * SLOT, HINT & 16); PT();
                load_tile(sb, eph, o_next(otab), &tm_wo, head * 128, cq * 2, HINT & 2); PT();
            }
            if (lane == 0) {
                const uint32_t s1 = o_next(otab), s2 = o_next(otab);
                if (rb < NFFN) {
                    slot_wait(sb + BAR_EMPTY, eph, s1);
                    const uint32_t f = sb + BAR_FULL + 8 * s1, d = sb + s1 * SLOT;
                    mbar_expect(f, SLOT);
                    tma2d(d, &tm_wg, rb * 16, 0, f);
                    tma2d(d + 8192, &tm_wg, rb * 16, 256, f);
                    tma2d(d + 16384, &tm_wu, rb * 16, 0, f);
                    tma2d(d + 24576, &tm_wu, rb * 16, 256, f);
                }
                slot_wait(sb + BAR_EMPTY, eph, s2);
                mbar_expect(sb + BAR_FULL + 8 * s2, 7 * 4096);
#pragma unroll 1
                for (int k = 0; k < 7; k++) tma2d(sb + s2 * SLOT + k * 4096, &tm_wd, (rb >> 1) * 8, k * 256, sb + BAR_FULL + 8 * s2);
            }
        } else {
            const int hw = warp - 9;
            if (hw == 1 && lane == 0) {
                mbar_watch(sb + BAR_FULL + 8 * PF0, 0);
                l2_prefetch(P.ckv + 512 * 512 + rb * 6144, 12288);
                l2_prefetch(P.x + rb * 8192, 16384);
                mbar_watch(sb + BAR_FULL + 8 * 4, 0);
                TS(40);
                if (j < 4) tma3d_prefetch(&tm_wq, j * 128, grp * 4);
                mbar_watch(sb + BAR_PF, 0);
                l2_prefetch(P.ckv + rb * 8192, 16384);
                l2_prefetch(g_h + rb * 16384, 16384);
                mbar_watch(sb + BAR_PF, 1);
                tma3d_prefetch((j & 1) ? &tm_wuv : &tm_wuk, (j >> 1) * 128, grp * 4 + 2);
                if (j < 4) tma3d_prefetch(&tm_wq, j * 128, grp * 4 + 2);
                mbar_watch(sb + BAR_PF, 0);
                l2_prefetch(g_ctx + (size_t)(ort * 32 + o_head(cq, kh)) * SLOT, SLOT);
                l2_prefetch(g_ctx + (size_t)(ort * 32 + o_head(cq + 4, kh)) * SLOT, SLOT);
                mbar_watch(sb + BAR_PF, 1);
                l2_prefetch(reinterpret_cast<const uint8_t*>(P.wo) + rb * 32768, 32768);
                l2_prefetch(reinterpret_cast<const uint8_t*>(P.wgate) + rb * 14336, 14336);
                l2_prefetch(reinterpret_cast<const uint8_t*>(P.wup) + rb * 14336, 14336);
                l2_prefetch(reinterpret_cast<const uint8_t*>(P.wdown) + rb * 14336, 14336);
                l2_prefetch(P.x + rb * 8192, 16384);
                mbar_watch(sb + BAR_END, 0);
            }
            if (hw == 0) {
#pragma unroll 1
                for (int i = 0; i < 9; i++) {
                    const int hp = i > 4, k = (i - 1) & 3;
                    if (lane == 0) {
                        mbar_wait(sb + BAR_DONE + 8 * i, 0);
                        flag_add(i == 0 ? &g_sync.hcnt[grp * 8] : k < 2 ? &g_sync.kvcnt[((2 * grp + hp) * 2 + k) * 8]
                                                                        : &g_sync.ctxcnt[(k == 2 ? 15 - j : j) * 32 + 2 * grp + hp]);
                    }
                    if (i == 0) TS(43);
                    if (i == 4) {
                        __syncwarp();
#pragma unroll 1
                        for (int v = 0; v < 32; v++) g_part[rb * 1024 + v * 32 + lane] = make_uint4(0, 0, 0, 0);
                        __syncwarp();
                    }
                }
            }
            if (hw == 2) {
                const uint32_t ep = __ldcg(&g_sync.epoch[0]) + 1;
                if (lane == 0) {
                    asm volatile("st.shared.u32 [%0], %1;" ::"r"(sb + SM_EP), "r"(ep) : "memory");
                    flag_wait(&g_sync.modcnt[0], NSPARE * ep);
                }
                __syncwarp();
#pragma unroll
                for (int i = 0; i < 4; i++) sts128(sb + SM_TAB + i * 512 + lane * 16, __ldcg(reinterpret_cast<const uint4*>(g_mod) + lane + 32 * i));
                __syncwarp();
                if (lane == 0) mbar_arrive(sb + BAR_FLAG + 8 * 8);
                TS(42);
#pragma unroll 1
                for (int i = 0; i < 8; i++) {
                    if (lane == 0) mbar_wait(sb + BAR_DONE + 8 * (i == 7 ? 6 : i), 0);
                    __syncwarp();
                    const uint32_t* f = i == 0 ? &g_sync.hcnt[(lane ? j : 15 - j) * 8]
                                      : i == 3 || i == 4 ? &g_sync.rdcnt[(grp * 2 + i - 3) * 8]
                                      : i == 7 ? &g_sync.modcnt[32] : &g_sync.kvcnt[(4 * grp + (i > 4 ? i - 3 : i - 1)) * 8];
                    if (lane < (i ? 1 : 2)) flag_wait(f, i == 7 ? NSPARE * ep : 8 * ep);
                    __syncwarp();
                    if (i == 7) {
                        const uint32_t *mp = reinterpret_cast<const uint32_t*>(g_mod) + lane, *wp = reinterpret_cast<const uint32_t*>(P.wr) + lane;
                        float ra = 0.f, rs = 0.f;
#pragma unroll 1
                        for (int k = 0; k < 256; k += 32) {
                            const uint32_t ga = __ldcg(mp + 512 + k), sh = __ldcg(mp + 768 + k), c1 = badd(__ldcg(mp + 1024 + k), ONE2);
                            const uint32_t gb = __ldcg(mp + 1280 + k), ww = __ldg(wp + k);
                            const float a0 = bf_lo(c1) * bf_lo(ww), a1 = bf_hi(c1) * bf_hi(ww);
                            ra += a0 + a1;
                            rs = fmaf(bf_lo(sh), bf_lo(ww), fmaf(bf_hi(sh), bf_hi(ww), rs));
                            if (k >> 6 == cq) {
                                sts128(sb + SM_TAB + ((k & 32) + lane) * 16, make_uint4(ga << 16, ga & 0xffff0000u, __float_as_uint(a0), __float_as_uint(a1)));
                                sts128(sb + SM_TAB + 1024 + ((k & 32) + lane) * 16, make_uint4(c1, sh, gb, 0));
                            }
                        }
                        *reinterpret_cast<float2*>(smem + SM_EP + 8) = make_float2(warp_sum(ra), warp_sum(rs));
                        __syncwarp();
                    }
                    if (lane == 0) mbar_arrive(sb + BAR_FLAG + 8 * i);
                    TS(48 + i);
                }
#pragma unroll 1
                for (int i = 0; i < 2; i++) {
                    if (i) mbar_wait(sb + BAR_DONE + 8 * 7, 0);
                    if (lane < 8 + i) flag_wait(&g_sync.ctxcnt[ort * 32 + o_head(lane + 8 * i, kh)], ep);
                    __syncwarp();
                    if (lane == 0) mbar_arrive(sb + BAR_FLAG + 8 * (9 + i));
                    TS(44 + i);
                }
            }
        }
    } else {
        asm volatile("setmaxnreg.inc.sync.aligned.u32 232;");
        const bool elected = (tid & 127) == 0;
        const int g = lane >> 2, c4 = lane & 3;
        const uint32_t toff = (warp * 16 + g) * 128 + ((c4 ^ g) << 4);
        uint32_t fph = 0, r = 0;
        if (wg == 1) bar_arrive(1, 256);
        const uint32_t kd = desc_k(sb), vd = desc_mn(sb);
        const int nL = 16 - j, hn = nL - 1 + wg;
        float s[64], o[64];
#pragma unroll 1
        for (int hp = 0; hp < 2; hp++) {
            {
                const int step = hp ? -8 * SLOT : 8 * SLOT;
                uint8_t* img = g_KV + (size_t)(grp * 32 + (hp ? j ^ 30 : j)) * SLOT - step;
                const uint32_t wtab = w_table(hp);
                uint32_t atab = hp ? 0x256u : a_table(0);
#pragma unroll 1
                for (int t = 0; t < 6; t += 2) {
                    proj_tile<false>(s, o, t, t ? 0 : 2 * hp, sb, wg, elected, fph, wtab, atab, img, toff, (hp | t) == 0, P.x, rb * 16 + warp * 2);
                    __syncwarp();
                    mbar_arrive_if(sb + BAR_DONE + 4 * t + 32 * hp, lane == 0 && t != 0);
                    if (elected) TS(1 + 10 * hp + t + 20 * wg);
                    proj_tile<true>(o, s, t + 1, 0, sb, wg, elected, fph, wtab, atab, img + step, toff, (hp | t) == 0, P.x, rb * 16 + warp * 2);
                    if (elected) TS(2 + 10 * hp + t + 20 * wg);
                    img += 2 * step;
                }
            }
            float m[2] = {0.f, 0.f}, l[2] = {0.f, 0.f}, li[2] = {0.f, 0.f}, t[4] = {0.f, 0.f, 0.f, 0.f};
            bool shifted = false, bad = false, plain = false;
            uint32_t p[32];
#pragma unroll
            for (int i = 0; i < 32; i++) p[i] = 0;
            uint32_t qa = desc_k(sb + 5 * SLOT + (wg ^ 1) * 8192);
            uint8_t* img = g_ctx + (size_t)((15 - j) * 32 + 2 * grp + hp) * SLOT;
            slot_wait(sb + BAR_FULL, fph, r);
            int n = -1;
#pragma unroll 1
            for (;;) {
                while (bad || plain) {
                    if (bad) {
                        float a0, a1;
                        softmax_remax(s, m, n == 0 || n == nL, a0, a1);
                        shifted = true;
                        l[0] *= a0;
                        l[1] *= a1;
#pragma unroll
                        for (int i = 0; i < 64; i++) o[i] *= (i & 2) ? a1 : a0;
                    }
                    softmax_exp<0, 16>(s, p, t);
                    t[0] += t[1];
                    t[2] += t[3];
                    bad = !bad && softmax_unsafe(t[0], t[2], false);
                    plain = false;
                }
#pragma unroll 1
                do {
                    l[0] += t[0];
                    l[1] += t[2];
                    if (++n > 16) break;
                    const uint32_t ks = r;
                    uint32_t vs = ring_next(r);
                    r = ring_next(vs);
                    bar_sync(1 + wg, 256);
                    if (n == 0 || (uint32_t)(n + 1 - nL) <= 2u) {
                        const int x = (warp & 3) * 16 + g - 2 * c4;
                        if (n == 0) {
                            r = vs;
                            vs = 4 - hp;
                            qk_issue(s, qa, kd + ks * (SLOT / 16));
                            slot_wait(sb + BAR_FULL, fph, 6);
                            gemm_issue(o, qa + SLOT / 16, vd + vs * (SLOT / 16), 1);
                            bar_arrive(2 - wg, 256);
                            wg_wait<1>();
                            reg_fence(s);
                        } else if (n == hn) {
                            float sh[32];
                            qk_issue(sh, qa, kd + ks * (SLOT / 16));
                            slot_wait(sb + BAR_FULL, fph, vs);
                            pv_issue(o, p, vd + vs * (SLOT / 16), 1, false);
                            bar_arrive(2 - wg, 256);
                            wg_wait<1>();
                            reg_fence(sh);
                            tri_mask_copy(s, sh, x);
                        } else {
                            qk_issue(s, qa, kd + ks * (SLOT / 16));
                            if (n == nL + 1) {
                                wg_wait<1>();
                                reg_fence(o);
                                ctx_store(img, toff, o, li[0], li[1]);
                                __syncwarp();
                                mbar_arrive_if(sb + BAR_DONE + 24 + 32 * hp, lane == 0);
                            }
                            slot_wait(sb + BAR_FULL, fph, vs);
                            pv_issue(o, p, vd + vs * (SLOT / 16), n != nL + 1, n == hn + 1);
                            bar_arrive(2 - wg, 256);
                            wg_wait<1>();
                            reg_fence(s);
                            if (n <= nL) tri_mask<32>(s, x);
                        }
                        mbar_arrive_if(sb + BAR_EMPTY + 8 * ks, elected);
                        mbar_arrive_if(sb + BAR_EMPTY + 8 * (n == 16 ? 6 : 5), elected && (n == 16 || n == nL - 1));
                        if (n == nL - 1) {
                            qa += SLOT / 16;
                            fence_async_smem();
                        }
                        if (shifted) {
                            if (n == nL) {
                                m[0] = m[1] = 0.f;
                                shifted = false;
                            }
                            softmax_shift(s, m[0], m[1]);
                        }
                        float e[4 * EARLY];
#pragma unroll
                        for (int i = 0; i < 4 * EARLY; i++) {
                            e[i] = ex2(s[i]);
                            t[i & 3] = i < 4 ? e[i] : t[i & 3] + e[i];
                        }
                        reg_fence(e);
                        slot_wait(sb + BAR_FULL, fph, r);
                        wg_wait<0>();
                        reg_fence(o);
                        reg_fence(e);
                        mbar_arrive_if(sb + BAR_EMPTY + 8 * vs, elected);
#pragma unroll
                        for (int i = 0; i < 2 * EARLY; i++) p[i] = pack2(e[2 * i], e[2 * i + 1]);
                        softmax_exp<EARLY, 8>(s, p, t);
                        if (n == 0) q_store(sb + 6 * SLOT, toff ^ 8192, o);
                        if (n == nL) {
                            li[0] = rcp(quad_sum(l[0]));
                            li[1] = rcp(quad_sum(l[1]));
                            l[0] = l[1] = 0.f;
                        }
                        if (n != hn) softmax_exp<8, 16>(s, p, t);
                        t[0] += t[1];
                        t[2] += t[3];
                        bad = softmax_unsafe(t[0], t[2], n == 0 || n == nL);
                        continue;
                    }
                    qk_issue(s, qa, kd + ks * (SLOT / 16));
                    slot_wait(sb + BAR_FULL, fph, vs);
                    pv_issue(o, p, vd + vs * (SLOT / 16), n != 1, false);
                    bar_arrive(2 - wg, 256);
                    wg_wait<1>();
                    reg_fence(s);
                    mbar_arrive_if(sb + BAR_EMPTY + 8 * ks, elected);
                    mbar_arrive_if(sb + BAR_EMPTY + 8 * 6, elected && n == 16);
                    if (shifted) {
                        slot_wait(sb + BAR_FULL, fph, r);
                        wg_wait<0>();
                        reg_fence(o);
                        mbar_arrive_if(sb + BAR_EMPTY + 8 * vs, elected);
                        softmax_shift(s, m[0], m[1]);
                        plain = true;
                        break;
                    }
                    float e[4 * EARLY];
#pragma unroll
                    for (int i = 0; i < 4 * EARLY; i++) {
                        e[i] = ex2(s[i]);
                        t[i & 3] = i < 4 ? e[i] : t[i & 3] + e[i];
                    }
                    reg_fence(e);
                    slot_wait(sb + BAR_FULL, fph, r);
                    wg_wait<0>();
                    reg_fence(o);
                    reg_fence(e);
                    mbar_arrive_if(sb + BAR_EMPTY + 8 * vs, elected);
#pragma unroll
                    for (int i = 0; i < 2 * EARLY; i++) p[i] = pack2(e[2 * i], e[2 * i + 1]);
                    softmax_exp<EARLY, 16>(s, p, t);
                    t[0] += t[1];
                    t[2] += t[3];
                    bad = softmax_unsafe(t[0], t[2], false);
                } while (!bad);
                if (!bad && !plain) break;
            }
            const uint32_t vs = r, ga = desc_k(sb + (hp ? wg ^ kh ^ 1 : wg) * 8192), as = 2 + 2 * hp;
            r = ring_next(r);
            slot_wait(sb + BAR_FULL, fph, 5);
            slot_wait(sb + BAR_FULL, fph, r);
            bar_sync(1 + wg, 256);
            gemm_issue_init(s, ga + 5 * (SLOT / 16), vd + r * (SLOT / 16));
            if (j == 0) {
                wg_wait<1>();
                reg_fence(o);
                ctx_store(img, toff, o, li[0], li[1]);
                __syncwarp();
                mbar_arrive_if(sb + BAR_DONE + 24 + 32 * hp, lane == 0);
            }
            pv_issue(o, p, vd + vs * (SLOT / 16), j, hn == 16);
            bar_arrive(2 - wg, 256);
            li[0] = rcp(quad_sum(l[0]));
            li[1] = rcp(quad_sum(l[1]));
            wg_wait<1>();
            mbar_arrive_if(sb + BAR_EMPTY + 8 * 5, elected);
            mbar_arrive_if(sb + BAR_EMPTY + 8 * r, elected && hp);
            wg_wait<0>();
            mbar_arrive_if(sb + BAR_EMPTY + 8 * vs, elected);
            slot_wait(sb + BAR_FULL, fph, as);
            slot_wait(sb + BAR_FULL, fph, 0);
            bar_sync(1 + wg, 256);
            gemm_issue(s, ga + as * (SLOT / 16), vd, 1);
            bar_arrive(2 - wg, 256);
            reg_fence(o);
            ctx_store(img + (ptrdiff_t)(2 * j - 15) * 32 * SLOT, toff ^ 8192, o, li[0], li[1]);
            __syncwarp();
            mbar_arrive_if(sb + BAR_DONE + 32 + 32 * hp, lane == 0);
            wg_wait<0>();
            mbar_arrive_if(sb + BAR_EMPTY + 8 * as, elected);
            mbar_arrive_if(sb + BAR_EMPTY, elected && hp);
            if (elected) TS(8 + 10 * hp + 20 * wg);
        }
        uint32_t otab = 0x0435216u;
        const uint32_t oa = desc_k(sb + (wg ^ kh ^ 1) * 8192);
        const int t7 = tid & 127, w4 = warp & 3, row = ort * 128 + kh * 64 + w4 * 16 + g;
        uint32_t x2[32];
#pragma unroll
        for (int k = 0; k < 32; k++) x2[k] = 0;
#pragma unroll 1
        for (int i = 2; i < 15 - wg; i++) {
            const uint32_t as = o_next(otab), ws = o_next(otab);
            slot_wait(sb + BAR_FULL, fph, as);
            slot_wait(sb + BAR_FULL, fph, ws);
            bar_sync(1 + wg, 256);
            gemm_issue(s, oa + as * (SLOT / 16), vd + ws * (SLOT / 16), 1);
            bar_arrive(2 - wg, 256);
            if (i == 12 && wg) {
                const uint32_t* xp = reinterpret_cast<const uint32_t*>(P.x) + row * 256 + cq * 64 + c4;
#pragma unroll
                for (int k = 0; k < 32; k++) x2[k] = __ldg(xp + (k & 1) * 2048 + (k >> 1) * 4);
            }
            wg_wait<0>();
            mbar_arrive_if(sb + BAR_EMPTY + 8 * as, elected);
            mbar_arrive_if(sb + BAR_EMPTY + 8 * ws, elected);
        }
        mbar_wait(sb + BAR_FLAG + 8 * 7, 0);
        const uint32_t ep = lds32(sb + SM_EP);
        if (wg == 0) {
            reg_fence(s);
            if (elected) TS(9);
#pragma unroll
            for (int v = 0; v < 8; v++)
                st_pub(g_part + rb * 1024 + v * 128 + t7, make_uint4(max(pack2(s[8 * v], s[8 * v + 1]), 1u), pack2(s[8 * v + 2], s[8 * v + 3]),
                                                                      pack2(s[8 * v + 4], s[8 * v + 5]), pack2(s[8 * v + 6], s[8 * v + 7])), true);
            o_next(otab); o_next(otab); o_next(otab); o_next(otab);
            const uint32_t s1 = o_next(otab), s2 = o_next(otab);
            uint32_t wf[64];
            float wd[56];
            if (rb < NFFN) {
                slot_wait(sb + BAR_FULL, fph, s1);
                const uint32_t a = sb + s1 * SLOT + (w4 * 128 + (lane >> 4) * 8 + (lane & 7)) * 32 + ((lane >> 3) & 1) * 16;
#pragma unroll
                for (int i = 0; i < 16; i++)
                    asm volatile("ldmatrix.sync.aligned.m8n8.x4.trans.shared.b16 {%0, %1, %2, %3}, [%4];"
                                 : "=r"(wf[4 * i]), "=r"(wf[4 * i + 1]), "=r"(wf[4 * i + 2]), "=r"(wf[4 * i + 3])
                                 : "r"(a + (i >> 3) * 16384 + (i & 7) * 512) : "memory");
            }
            slot_wait(sb + BAR_FULL, fph, s2);
#pragma unroll
            for (int i = 0; i < 14; i++) {
                const uint2 w = *reinterpret_cast<const uint2*>(smem + s2 * SLOT + (i >> 1) * 4096 + (2 * t7 + (i & 1)) * 16 + (rb & 1) * 8);
                wd[4 * i] = bf_lo(w.x); wd[4 * i + 1] = bf_hi(w.x); wd[4 * i + 2] = bf_lo(w.y); wd[4 * i + 3] = bf_hi(w.y);
            }
            const uint32_t gbf = __ldcg(reinterpret_cast<const uint32_t*>(g_mod) + 1280 + rb * 2 + (tid & 1));
            reg_fence(wd);
            if (elected) TS(10);
            const uint32_t best = best_key(g_key + cq * 128, lane, ep);
            const int sel = (~best >> 5) & 2047;
            if (elected) TS(19);
            const uint4* cp = g_cand + (sel >> 4) * 192;
            float* sred = reinterpret_cast<float*>(smem + SM_RED);
            const int pq = (2 * rb + (tid & 1)) & 63, pv = (pq >> 2) / 3;
            const uint4* fp = cp + (rb >> 5) * 24 + pv * 4 + (pq & 3);
            uint4 fh = ld_poll(fp), fx = ld_poll(fp + 96);
            if (rb < NFFN) {
                uint4 cv[6];
                for (;;) {
                    uint32_t bad = 0;
#pragma unroll
                    for (int v = 0; v < 6; v++) cv[v] = ld_poll(cp + w4 * 24 + v * 4 + c4);
#pragma unroll
                    for (int v = 0; v < 6; v++) bad |= cv[v].w ^ ep;
                    if (__all_sync(0xffffffffu, bad == 0)) break;
                }
                if (elected) TS(20);
                float d[4][4] = {};
#pragma unroll
                for (int k = 0; k < 8; k++) {
                    const uint32_t b0 = (&cv[(2 * k) / 3].x)[(2 * k) % 3], b1 = (&cv[(2 * k + 1) / 3].x)[(2 * k + 1) % 3];
                    mma16816(d[k & 1], wf + 4 * k, b0, b1);
                    mma16816(d[2 + (k & 1)], wf + 32 + 4 * k, b0, b1);
                }
                const float u = (c4 & 2) ? ((c4 & 1) ? d[2][2] + d[3][2] : d[2][0] + d[3][0]) : ((c4 & 1) ? d[0][2] + d[1][2] : d[0][0] + d[1][0]);
                sred[w4 * 32 + c4 * 8 + g] = u;
                bar_sync(3, 128);
                if (warp == 0) {
                    const float v = rbf((sred[lane] + sred[32 + lane]) + (sred[64 + lane] + sred[96 + lane]));
                    const float up = __shfl_down_sync(0xffffffffu, v, 16);
                    st_pub(g_act + rb * 16 + lane, (pack2(0.f, rbf(v * sigmoid(v)) * up) & 0xffff0000u) | (ep & 0xffffu), lane < 16);
                }
            }
            if (rb == 0 && tid == 0) g_sync.epoch[0] = ep;
            if (elected) TS(60);
            uint2 av[7];
            for (;;) {
                uint32_t bad = 0;
#pragma unroll
                for (int k = 0; k < 7; k++) av[k] = ld_poll(reinterpret_cast<const uint2*>(g_act) + t7 + 128 * k);
#pragma unroll
                for (int k = 0; k < 7; k++) bad |= (av[k].x ^ ep) | (av[k].y ^ ep);
                if (__all_sync(0xffffffffu, (bad & 0xffffu) == 0)) break;
            }
            if (elected) TS(61);
            float y[4] = {0.f, 0.f, 0.f, 0.f};
#pragma unroll
            for (int k = 0; k < 7; k++)
#pragma unroll
                for (int i = 0; i < 4; i++) y[i] = fmaf(bf_hi(av[k].y), wd[8 * k + 4 + i], fmaf(bf_hi(av[k].x), wd[8 * k + i], y[i]));
            const float z0 = ((lane & 16) ? y[2] : y[0]) + __shfl_xor_sync(0xffffffffu, (lane & 16) ? y[0] : y[2], 16);
            const float z1 = ((lane & 16) ? y[3] : y[1]) + __shfl_xor_sync(0xffffffffu, (lane & 16) ? y[1] : y[3], 16);
            float z = ((lane & 8) ? z1 : z0) + __shfl_xor_sync(0xffffffffu, (lane & 8) ? z0 : z1, 8);
            z += __shfl_xor_sync(0xffffffffu, z, 4);
            z = quad_sum(z);
            if ((lane & 7) == 0) sred[128 + (lane >> 3) * 4 + w4] = z;
            bar_sync(3, 128);
            if (tid < 2) {
                while (fh.w != ep || fx.w != ep) { fh = ld_poll(fp); fx = ld_poll(fp + 96); }
                const float4 y0 = *reinterpret_cast<const float4*>(sred + 128 + tid * 8), y1 = *reinterpret_cast<const float4*>(sred + 132 + tid * 8);
                const int cm = (pq >> 2) - 3 * pv;
                const uint32_t h2 = cm == 0 ? fh.x : cm == 1 ? fh.y : fh.z, x2 = cm == 0 ? fx.x : cm == 1 ? fx.y : fx.z;
                const float sg = sigmoid(bf_hi((best & 0x80000000u) ? (best ^ 0x80000000u) : ~best));
                reinterpret_cast<uint32_t*>(P.out)[sel * 256 + rb * 2 + tid] =
                    badd(x2, bmul(gbf, badd(h2, bmul(pack2((y0.x + y0.y) + (y0.z + y0.w), (y1.x + y1.y) + (y1.z + y1.w)), pack2(sg, sg)))));
            }
            if (elected) TS(62);
        } else {
            const float4* tf = reinterpret_cast<const float4*>(smem + SM_TAB) + c4;
            const uint32_t as14 = otab & 15;
            bar_sync(2, 256);
#pragma unroll 1
            for (int i = 14; i < 17; i++) {
                const uint32_t as = o_next(otab), ws = o_next(otab);
                slot_wait(sb + BAR_FULL, fph, as);
                slot_wait(sb + BAR_FULL, fph, ws);
                gemm_issue(s, oa + as * (SLOT / 16), vd + ws * (SLOT / 16), 1);
                wg_wait<1>();
                mbar_arrive_if(sb + BAR_EMPTY + 8 * as14, elected && i == 15);
            }
            if (elected) TS(29);
            {
                const uint4* pr = g_part + (rb ^ 8) * 1024 + t7;
                uint4 pa[8];
                for (;;) {
                    uint32_t ok = ~0u;
#pragma unroll
                    for (int v = 0; v < 8; v++) pa[v] = ld_poll(pr + v * 128);
#pragma unroll
                    for (int v = 0; v < 8; v++) ok = min(ok, pa[v].x);
                    if (__all_sync(0xffffffffu, ok != 0)) break;
                }
#pragma unroll
                for (int i = 0; i < 32; i++) {
                    const uint32_t w = (&pa[i >> 2].x)[i & 3];
                    const float2 ga = *reinterpret_cast<const float2*>(tf + (i >> 1) * 4);
                    o[2 * i] = fmaf(ga.x, bf_lo(w), bf_lo(x2[i]));
                    o[2 * i + 1] = fmaf(ga.y, bf_hi(w), bf_hi(x2[i]));
                }
            }
            reg_fence(o);
            if (elected) TS(30);
            wg_wait<0>();
            reg_fence(s);
            if (elected) TS(39);
            float st[6] = {0.f, 0.f, 0.f, 0.f, 0.f, 0.f};
#pragma unroll
            for (int k = 0; k < 16; k++) {
                const float4 c = tf[k * 4];
#pragma unroll
                for (int i = 4 * k; i < 4 * k + 4; i++) {
                    const int rh = (i >> 1) & 1;
                    const float v = fmaf((i & 1) ? c.y : c.x, s[i], o[i]);
                    s[i] = v;
                    st[rh] += v;
                    st[2 + rh] = fmaf(v, v, st[2 + rh]);
                    st[4 + rh] = fmaf(v, (i & 1) ? c.w : c.z, st[4 + rh]);
                }
            }
#pragma unroll
            for (int i = 0; i < 6; i++) st[i] = quad_sum(st[i]);
            st_pub(g_stat + (row + 8 * (c4 & 1)) * 4 + cq,
                   make_uint4(__float_as_uint((c4 & 1) ? st[1] : st[0]), __float_as_uint((c4 & 1) ? st[3] : st[2]),
                              __float_as_uint((c4 & 1) ? st[5] : st[4]), ep), c4 < 2);
            if (elected) TS(56);
            uint32_t cb[16], sh[16], gb[16];
#pragma unroll
            for (int i = 0; i < 16; i++) {
                const float4 c = tf[64 + i * 4];
                cb[i] = __float_as_uint(c.x); sh[i] = __float_as_uint(c.y); gb[i] = __float_as_uint(c.z);
            }
            const float ra = __uint_as_float(lds32(sb + SM_EP + 8)), rb0 = __uint_as_float(lds32(sb + SM_EP + 12));
#pragma unroll
            for (int i = 0; i < 32; i++) x2[i] = pack2(s[2 * i], s[2 * i + 1]);
            reg_fence(x2);
            uint4 r0, r1;
            for (;;) {
                r0 = ld_poll(g_stat + row * 4 + c4);
                r1 = ld_poll(g_stat + (row + 8) * 4 + c4);
                if (__all_sync(0xffffffffu, r0.w == ep && r1.w == ep)) break;
            }
            if (elected) TS(57);
            const float m0 = quad_sum(__uint_as_float(r0.x)) * (1.f / 512.f), m1 = quad_sum(__uint_as_float(r1.x)) * (1.f / 512.f);
            const float rs0 = ln_rstd(fmaxf(fmaf(-m0, m0, quad_sum(__uint_as_float(r0.y)) * (1.f / 512.f)), 0.f));
            const float rs1 = ln_rstd(fmaxf(fmaf(-m1, m1, quad_sum(__uint_as_float(r1.y)) * (1.f / 512.f)), 0.f));
            const uint32_t mb0 = pack2(m0, m0), mb1 = pack2(m1, m1);
            const uint32_t lg = pack2(fmaf(rs0, fmaf(-bf_lo(mb0), ra, quad_sum(__uint_as_float(r0.z))), rb0),
                                      fmaf(rs1, fmaf(-bf_lo(mb1), ra, quad_sum(__uint_as_float(r1.z))), rb0));
            const uint32_t u0 = lg << 16, u1 = lg & 0xffff0000u;
            const uint32_t k0 = ((u0 ^ (((int)u0 >> 31) | 0x80000000u)) & 0xffff0000u) | ((2047 - row) << 5) | (ep & 31);
            const uint32_t k1 = ((u1 ^ (((int)u1 >> 31) | 0x80000000u)) & 0xffff0000u) | ((2039 - row) << 5) | (ep & 31);
            const uint32_t kb = __reduce_max_sync(0xffffffffu, max(k0, k1));
            st_pub(g_key + cq * 128 + (row >> 4), kb, lane == 0);
            {
                uint32_t cx[18], ch[18];
#pragma unroll
                for (int i = 0; i < 16; i++) {
                    cx[i] = kb == k1 ? x2[2 * i + 1] : x2[2 * i];
                    ch[i] = ln_apply(cx[i], kb == k1 ? mb1 : mb0, kb == k1 ? rs1 : rs0, cb[i], sh[i]);
                }
                cx[16] = cx[17] = ch[16] = ch[17] = 0;
                uint4* cp = g_cand + (row >> 4) * 192 + cq * 24 + c4;
#pragma unroll
                for (int v = 0; v < 6; v++) st_pub(cp + v * 4, make_uint4(ch[3 * v], ch[3 * v + 1], ch[3 * v + 2], ep), kb == k0 || kb == k1);
#pragma unroll
                for (int v = 0; v < 6; v++) st_pub(cp + 96 + v * 4, make_uint4(cx[3 * v], cx[3 * v + 1], cx[3 * v + 2], ep), kb == k0 || kb == k1);
            }
            if (elected) TS(58);
            uint2 ov[16];
#pragma unroll
            for (int i = 0; i < 16; i++) {
                const int rh = i & 1, jj = i & 14;
                const uint32_t v0 = badd(x2[2 * jj + rh], bmul(gb[jj], ln_apply(x2[2 * jj + rh], rh ? mb1 : mb0, rh ? rs1 : rs0, cb[jj], sh[jj])));
                const uint32_t v1 = badd(x2[2 * jj + 2 + rh], bmul(gb[jj + 1], ln_apply(x2[2 * jj + 2 + rh], rh ? mb1 : mb0, rh ? rs1 : rs0, cb[jj + 1], sh[jj + 1])));
                const uint32_t rv = __shfl_xor_sync(0xffffffffu, (c4 & 1) ? v0 : v1, 1);
                ov[i] = (c4 & 1) ? make_uint2(rv, v1) : make_uint2(v0, rv);
            }
            uint2* op = reinterpret_cast<uint2*>(P.out) + row * 128 + cq * 32 + (c4 & 1) * 2 + (c4 >> 1);
#pragma unroll
            for (int i = 0; i < 16; i++)
                if (kb != ((i & 1) ? k1 : k0)) op[(i & 1) * 1024 + (i & 14) * 2] = ov[i];
            const uint32_t best = best_key(g_key + cq * 128, lane, ep);
            if (best != kb) {
#pragma unroll
                for (int i = 0; i < 16; i++)
                    if (kb == ((i & 1) ? k1 : k0)) op[(i & 1) * 1024 + (i & 14) * 2] = ov[i];
            }
            if (elected) TS(59);
        }
        mbar_arrive_if(sb + BAR_END, lane == 0);
    }
}

typedef CUresult (*EncodeFn)(CUtensorMap*, CUtensorMapDataType, cuuint32_t, void*, const cuuint64_t*, const cuuint64_t*,
                             const cuuint32_t*, const cuuint32_t*, CUtensorMapInterleave, CUtensorMapSwizzle,
                             CUtensorMapL2promotion, CUtensorMapFloatOOBfill);

void make_2d(EncodeFn fn, CUtensorMap* m, const void* p, uint64_t cols, uint64_t rows, uint32_t bc, uint32_t br) {
    cuuint64_t dims[2] = {cols, rows}, strides[1] = {cols * 2};
    cuuint32_t box[2] = {bc, br}, es[2] = {1, 1};
    fn(m, CU_TENSOR_MAP_DATA_TYPE_BFLOAT16, 2, const_cast<void*>(p), dims, strides, box, es, CU_TENSOR_MAP_INTERLEAVE_NONE,
       CU_TENSOR_MAP_SWIZZLE_NONE, CU_TENSOR_MAP_L2_PROMOTION_L2_128B, CU_TENSOR_MAP_FLOAT_OOB_FILL_NONE);
}
void make_3d(EncodeFn fn, CUtensorMap* m, const void* p, uint64_t cols, uint64_t rows) {
    cuuint64_t dims[3] = {64, rows, cols / 64}, strides[2] = {cols * 2, 128};
    cuuint32_t box[3] = {64, 128, 2}, es[3] = {1, 1, 1};
    fn(m, CU_TENSOR_MAP_DATA_TYPE_BFLOAT16, 3, const_cast<void*>(p), dims, strides, box, es, CU_TENSOR_MAP_INTERLEAVE_NONE,
       CU_TENSOR_MAP_SWIZZLE_128B, CU_TENSOR_MAP_L2_PROMOTION_L2_256B, CU_TENSOR_MAP_FLOAT_OOB_FILL_NONE);
}

}

extern "C" void kernel_launch(void* const* d_in, const int* in_sizes, int n_in, void* d_out, int out_size) {
    static EncodeFn fn = nullptr;
    static int sms = 0;
    if (!fn) {
        void* f = nullptr;
        cudaDriverEntryPointQueryResult st;
        cudaGetDriverEntryPoint("cuTensorMapEncodeTiled", &f, cudaEnableDefault, &st);
        fn = (EncodeFn)f;
        int dev = 0;
        cudaGetDevice(&dev);
        cudaDeviceGetAttribute(&sms, cudaDevAttrMultiProcessorCount, dev);
        cudaFuncSetAttribute(fused_kernel, cudaFuncAttributeMaxDynamicSharedMemorySize, SMEM_BYTES);
    }
    CUtensorMap ckv, wq, wuk, wuv, wo, wg, wu, wd, wm;
    make_3d(fn, &ckv, d_in[1], 512, 2048);
    make_3d(fn, &wq, d_in[2], 4096, 512);
    make_3d(fn, &wuk, d_in[3], 4096, 512);
    make_3d(fn, &wuv, d_in[4], 4096, 512);
    make_3d(fn, &wo, d_in[5], 512, 4096);
    make_2d(fn, &wg, d_in[8], 1792, 512, 16, 256);
    make_2d(fn, &wu, d_in[9], 1792, 512, 16, 256);
    make_2d(fn, &wd, d_in[10], 512, 1792, 8, 256);
    make_2d(fn, &wm, d_in[12], 3072, 512, 256, 64);
    Params p;
    p.x = (const bf16*)d_in[0];
    p.ckv = (const bf16*)d_in[1];
    p.wo = (const bf16*)d_in[5];
    p.wr = (const bf16*)d_in[7];
    p.wgate = (const bf16*)d_in[8];
    p.wup = (const bf16*)d_in[9];
    p.wdown = (const bf16*)d_in[10];
    p.c = (const bf16*)d_in[11];
    p.out = (bf16*)d_out;
    p.by_smid = sms == NCTA + NSPARE;
    fused_kernel<<<NCTA + NSPARE, 384, SMEM_BYTES>>>(ckv, wq, wuk, wuv, wo, wg, wu, wd, wm, p);
}
```

```cpp
#include <cuda.h>
#include <cuda_bf16.h>
#include <cuda_runtime.h>
#include <stdint.h>
#include <stdio.h>

namespace {

typedef __nv_bfloat16 bf16;
typedef unsigned long long u64;

constexpr int NCTA = 128, NSPARE = 4;
constexpr int SLOT = 32768;
constexpr int SM_BAR = 7 * SLOT;
constexpr int BAR_FULL = SM_BAR;
constexpr int BAR_EMPTY = BAR_FULL + 8 * 7;
constexpr int BAR_DONE = BAR_EMPTY + 8 * 7;
constexpr int BAR_FLAG = BAR_DONE + 8 * 9;
constexpr int BAR_PF = BAR_FLAG + 8 * 11;
constexpr int BAR_END = BAR_PF + 8;
constexpr int SM_EP = BAR_END + 8;
constexpr int SM_RED = SM_BAR + 384;
constexpr int SM_TAB = SM_BAR + 1024;
constexpr int SMEM_BYTES = SM_BAR + 3072;
constexpr int NFFN = 112;
#define HINT 29
constexpr u64 L2_NORMAL = 0x1000000000000000ull, L2_FIRST = 0x12F0000000000000ull;
#define PF0 0
#define PF1 13
#define PF2 11
#define UNR 4
#define LNQ 3
#define PARKS 7
#define EARLY 7
constexpr uint32_t SPIN_LIMIT = 1u << 22;
constexpr uint32_t ONE2 = 0x3f803f80u;

struct Sync {
    uint32_t modcnt[2 * 32];
    uint32_t hcnt[16 * 8];
    uint32_t kvcnt[32 * 2 * 8];
    uint32_t ctxcnt[16 * 32];
    uint32_t rdcnt[16 * 2 * 8];
    uint32_t epoch[32];
};

__device__ __align__(1024) uint8_t g_KV[16 * 16 * 2 * SLOT];
__device__ __align__(1024) uint8_t g_ctx[16 * 32 * SLOT];
__device__ __align__(1024) uint8_t g_h[16 * 4 * SLOT];
__device__ __align__(1024) uint4 g_part[128 * 1024];
__device__ __align__(1024) uint4 g_stat[2048 * 4];
__device__ __align__(1024) bf16 g_mod[3072];
__device__ __align__(1024) uint4 g_cand[128 * 192];
__device__ __align__(1024) uint32_t g_key[4 * 128];
__device__ __align__(1024) uint32_t g_act[1792];
__device__ __align__(1024) Sync g_sync;
#define TS(i)

#define PT()

struct Params {
    const bf16 *x, *ckv, *wo, *wr, *wgate, *wup, *wdown, *c;
    bf16* out;
    int by_smid;
};

__device__ __forceinline__ void mbar_init(uint32_t bar, uint32_t cnt) {
    asm volatile("mbarrier.init.shared::cta.b64 [%0], %1;" ::"r"(bar), "r"(cnt) : "memory");
}
__device__ __forceinline__ void mbar_wait(uint32_t bar, uint32_t parity) {
    asm volatile("{\n.reg .pred p;\nL_%=:\nmbarrier.try_wait.parity.shared::cta.b64 p, [%0], %1;\n@!p bra L_%=;\n}" ::"r"(bar), "r"(parity) : "memory");
}
__device__ __forceinline__ void mbar_watch(uint32_t bar, uint32_t parity) {
    asm volatile("{\n.reg .pred p;\n.reg .u32 n;\nmov.u32 n, 0;\n"
                 "L_%=:\nmbarrier.try_wait.parity.shared::cta.b64 p, [%0], %1;\n@p bra D_%=;\n"
                 "add.u32 n, n, 1;\nsetp.lt.u32 p, n, %2;\n@p bra L_%=;\ntrap;\nD_%=:\n}"
                 ::"r"(bar), "r"(parity), "n"(SPIN_LIMIT) : "memory");
}
__device__ __forceinline__ void mbar_arrive(uint32_t bar) {
    asm volatile("mbarrier.arrive.shared::cta.b64 _, [%0];" ::"r"(bar) : "memory");
}
__device__ __forceinline__ void mbar_arrive_if(uint32_t bar, bool on) {
    asm volatile("{\n.reg .pred p;\nsetp.ne.s32 p, %1, 0;\n@p mbarrier.arrive.shared::cta.b64 _, [%0];\n}" ::"r"(bar), "r"((int)on) : "memory");
}
__device__ __forceinline__ void mbar_expect(uint32_t bar, uint32_t bytes) {
    asm volatile("mbarrier.arrive.expect_tx.shared::cta.b64 _, [%0], %1;" ::"r"(bar), "r"(bytes) : "memory");
}
__device__ __forceinline__ void tma2d(uint32_t dst, const CUtensorMap* m, int c0, int c1, uint32_t bar) {
    asm volatile("cp.async.bulk.tensor.2d.shared::cluster.global.mbarrier::complete_tx::bytes [%0], [%1, {%3, %4}], [%2];"
                 ::"r"(dst), "l"(m), "r"(bar), "r"(c0), "r"(c1) : "memory");
}
__device__ __forceinline__ void tma3d_prefetch(const CUtensorMap* m, int row, int cb) {
    asm volatile("cp.async.bulk.prefetch.tensor.3d.L2.global [%0, {%1, %2, %3}];" ::"l"(m), "r"(0), "r"(row), "r"(cb) : "memory");
}
__device__ __forceinline__ void l2_prefetch(const void* p, uint32_t bytes) {
    asm volatile("cp.async.bulk.prefetch.L2.global [%0], %1;" ::"l"(p), "r"(bytes) : "memory");
}
__device__ __forceinline__ void flag_wait(const uint32_t* f, uint32_t target) {
    asm volatile("{\n.reg .pred p;\n.reg .u32 v;\n"
                 "L_%=:\nld.acquire.gpu.global.u32 v, [%0];\nsub.u32 v, v, %1;\nsetp.lt.s32 p, v, 0;\n@p nanosleep.u32 100;\n@p bra L_%=;\n}"
                 ::"l"(f), "r"(target) : "memory");
}
__device__ __forceinline__ uint4 ld_poll(const uint4* p) {
    uint4 v;
    asm volatile("ld.relaxed.gpu.global.v4.u32 {%0, %1, %2, %3}, [%4];" : "=r"(v.x), "=r"(v.y), "=r"(v.z), "=r"(v.w) : "l"(p) : "memory");
    return v;
}
__device__ __forceinline__ uint2 ld_poll(const uint2* p) {
    uint2 v;
    asm volatile("ld.relaxed.gpu.global.v2.u32 {%0, %1}, [%2];" : "=r"(v.x), "=r"(v.y) : "l"(p) : "memory");
    return v;
}
__device__ __forceinline__ void st_pub(uint4* p, uint4 v, bool on) {
    asm volatile("{\n.reg .pred p;\nsetp.ne.s32 p, %5, 0;\n@p st.relaxed.gpu.global.v4.u32 [%0], {%1, %2, %3, %4};\n}"
                 ::"l"(p), "r"(v.x), "r"(v.y), "r"(v.z), "r"(v.w), "r"((int)on) : "memory");
}
__device__ __forceinline__ void st_pub(uint32_t* p, uint32_t v, bool on) {
    asm volatile("{\n.reg .pred p;\nsetp.ne.s32 p, %2, 0;\n@p st.relaxed.gpu.global.u32 [%0], %1;\n}" ::"l"(p), "r"(v), "r"((int)on) : "memory");
}
__device__ __forceinline__ void flag_add(uint32_t* p) {
    asm volatile("red.release.gpu.global.add.u32 [%0], 1;" ::"l"(p) : "memory");
}
__device__ __forceinline__ uint32_t lds32(uint32_t a) {
    uint32_t v;
    asm volatile("ld.shared.u32 %0, [%1];" : "=r"(v) : "r"(a) : "memory");
    return v;
}
__device__ __forceinline__ uint4 lds128(uint32_t a) {
    uint4 v;
    asm volatile("ld.shared.v4.u32 {%0, %1, %2, %3}, [%4];" : "=r"(v.x), "=r"(v.y), "=r"(v.z), "=r"(v.w) : "r"(a) : "memory");
    return v;
}
__device__ __forceinline__ void fence_async_global() { asm volatile("fence.proxy.async.global;" ::: "memory"); }
__device__ __forceinline__ void fence_async_smem() { asm volatile("fence.proxy.async.shared::cta;" ::: "memory"); }
__device__ __forceinline__ void bar_sync(int id, int n) { asm volatile("bar.sync %0, %1;" ::"r"(id), "r"(n) : "memory"); }
__device__ __forceinline__ void bar_arrive(int id, int n) { asm volatile("bar.arrive %0, %1;" ::"r"(id), "r"(n) : "memory"); }
__device__ __forceinline__ void wg_fence() { asm volatile("wgmma.fence.sync.aligned;" ::: "memory"); }
__device__ __forceinline__ void wg_commit() { asm volatile("wgmma.commit_group.sync.aligned;" ::: "memory"); }
template <int N> __device__ __forceinline__ void wg_wait() { asm volatile("wgmma.wait_group.sync.aligned %0;" ::"n"(N) : "memory"); }
template <int N> __device__ __forceinline__ void reg_fence(float (&d)[N]) {
#pragma unroll
    for (int i = 0; i < N; i++) asm volatile("" : "+f"(d[i])::"memory");
}
template <int N> __device__ __forceinline__ void reg_fence(uint32_t (&d)[N]) {
#pragma unroll
    for (int i = 0; i < N; i++) asm volatile("" : "+r"(d[i])::"memory");
}
__device__ __forceinline__ uint32_t desc_k(uint32_t a) { return (a >> 4) | (1u << 16); }
__device__ __forceinline__ uint32_t desc_mn(uint32_t a) { return (a >> 4) | (1024u << 16); }

template <int TB>
__device__ __forceinline__ void wgmma_ss128(float (&d)[64], uint32_t da, uint32_t db, int acc, uint32_t ha = 0x40000040u, uint32_t hb = 0x40000040u) {
    asm volatile("{\n.reg .pred p;\n.reg .b64 a, b;\nsetp.ne.b32 p, %66, 0;\nmov.b64 a, {%64, %68};\nmov.b64 b, {%65, %69};\n"
        "wgmma.mma_async.sync.aligned.m64n128k16.f32.bf16.bf16 {%0, %1, %2, %3, %4, %5, %6, %7, %8, %9, %10, %11, %12, %13, %14, %15, %16, %17, %18, %19, %20, %21, %22, %23, %24, %25, %26, %27, %28, %29, %30, %31, %32, %33, %34, %35, %36, %37, %38, %39, %40, %41, %42, %43, %44, %45, %46, %47, %48, %49, %50, %51, %52, %53, %54, %55, %56, %57, %58, %59, %60, %61, %62, %63}, a, b, p, 1, 1, 0, %67;\n}"
        : "+f"(d[0]), "+f"(d[1]), "+f"(d[2]), "+f"(d[3]), "+f"(d[4]), "+f"(d[5]), "+f"(d[6]), "+f"(d[7]), "+f"(d[8]), "+f"(d[9]), "+f"(d[10]), "+f"(d[11]), "+f"(d[12]), "+f"(d[13]), "+f"(d[14]), "+f"(d[15]), "+f"(d[16]), "+f"(d[17]), "+f"(d[18]), "+f"(d[19]), "+f"(d[20]), "+f"(d[21]), "+f"(d[22]), "+f"(d[23]), "+f"(d[24]), "+f"(d[25]), "+f"(d[26]), "+f"(d[27]), "+f"(d[28]), "+f"(d[29]), "+f"(d[30]), "+f"(d[31]), "+f"(d[32]), "+f"(d[33]), "+f"(d[34]), "+f"(d[35]), "+f"(d[36]), "+f"(d[37]), "+f"(d[38]), "+f"(d[39]), "+f"(d[40]), "+f"(d[41]), "+f"(d[42]), "+f"(d[43]), "+f"(d[44]), "+f"(d[45]), "+f"(d[46]), "+f"(d[47]), "+f"(d[48]), "+f"(d[49]), "+f"(d[50]), "+f"(d[51]), "+f"(d[52]), "+f"(d[53]), "+f"(d[54]), "+f"(d[55]), "+f"(d[56]), "+f"(d[57]), "+f"(d[58]), "+f"(d[59]), "+f"(d[60]), "+f"(d[61]), "+f"(d[62]), "+f"(d[63])
        : "r"(da), "r"(db), "r"(acc), "n"(TB), "r"(ha), "r"(hb));
}
template <int TB>
__device__ __forceinline__ void wgmma_ss128_init(float (&d)[64], uint32_t da, uint32_t db, uint32_t ha = 0x40000040u, uint32_t hb = 0x40000040u) {
    asm volatile("{\n.reg .pred p;\n.reg .b64 a, b;\nsetp.ne.b32 p, 0, 0;\nmov.b64 a, {%64, %67};\nmov.b64 b, {%65, %68};\n"
        "wgmma.mma_async.sync.aligned.m64n128k16.f32.bf16.bf16 {%0, %1, %2, %3, %4, %5, %6, %7, %8, %9, %10, %11, %12, %13, %14, %15, %16, %17, %18, %19, %20, %21, %22, %23, %24, %25, %26, %27, %28, %29, %30, %31, %32, %33, %34, %35, %36, %37, %38, %39, %40, %41, %42, %43, %44, %45, %46, %47, %48, %49, %50, %51, %52, %53, %54, %55, %56, %57, %58, %59, %60, %61, %62, %63}, a, b, p, 1, 1, 0, %66;\n}"
        : "=f"(d[0]), "=f"(d[1]), "=f"(d[2]), "=f"(d[3]), "=f"(d[4]), "=f"(d[5]), "=f"(d[6]), "=f"(d[7]), "=f"(d[8]), "=f"(d[9]), "=f"(d[10]), "=f"(d[11]), "=f"(d[12]), "=f"(d[13]), "=f"(d[14]), "=f"(d[15]), "=f"(d[16]), "=f"(d[17]), "=f"(d[18]), "=f"(d[19]), "=f"(d[20]), "=f"(d[21]), "=f"(d[22]), "=f"(d[23]), "=f"(d[24]), "=f"(d[25]), "=f"(d[26]), "=f"(d[27]), "=f"(d[28]), "=f"(d[29]), "=f"(d[30]), "=f"(d[31]), "=f"(d[32]), "=f"(d[33]), "=f"(d[34]), "=f"(d[35]), "=f"(d[36]), "=f"(d[37]), "=f"(d[38]), "=f"(d[39]), "=f"(d[40]), "=f"(d[41]), "=f"(d[42]), "=f"(d[43]), "=f"(d[44]), "=f"(d[45]), "=f"(d[46]), "=f"(d[47]), "=f"(d[48]), "=f"(d[49]), "=f"(d[50]), "=f"(d[51]), "=f"(d[52]), "=f"(d[53]), "=f"(d[54]), "=f"(d[55]), "=f"(d[56]), "=f"(d[57]), "=f"(d[58]), "=f"(d[59]), "=f"(d[60]), "=f"(d[61]), "=f"(d[62]), "=f"(d[63])
        : "r"(da), "r"(db), "n"(TB), "r"(ha), "r"(hb));
}
template <int TB>
__device__ __forceinline__ void wgmma_ss64(float (&d)[32], uint32_t da, uint32_t db, int acc, uint32_t ha = 0x40000040u, uint32_t hb = 0x40000040u) {
    asm volatile("{\n.reg .pred p;\n.reg .b64 a, b;\nsetp.ne.b32 p, %34, 0;\nmov.b64 a, {%32, %36};\nmov.b64 b, {%33, %37};\n"
        "wgmma.mma_async.sync.aligned.m64n64k16.f32.bf16.bf16 {%0, %1, %2, %3, %4, %5, %6, %7, %8, %9, %10, %11, %12, %13, %14, %15, %16, %17, %18, %19, %20, %21, %22, %23, %24, %25, %26, %27, %28, %29, %30, %31}, a, b, p, 1, 1, 0, %35;\n}"
        : "+f"(d[0]), "+f"(d[1]), "+f"(d[2]), "+f"(d[3]), "+f"(d[4]), "+f"(d[5]), "+f"(d[6]), "+f"(d[7]), "+f"(d[8]), "+f"(d[9]), "+f"(d[10]), "+f"(d[11]), "+f"(d[12]), "+f"(d[13]), "+f"(d[14]), "+f"(d[15]), "+f"(d[16]), "+f"(d[17]), "+f"(d[18]), "+f"(d[19]), "+f"(d[20]), "+f"(d[21]), "+f"(d[22]), "+f"(d[23]), "+f"(d[24]), "+f"(d[25]), "+f"(d[26]), "+f"(d[27]), "+f"(d[28]), "+f"(d[29]), "+f"(d[30]), "+f"(d[31])
        : "r"(da), "r"(db), "r"(acc), "n"(TB), "r"(ha), "r"(hb));
}
template <int TB>
__device__ __forceinline__ void wgmma_ss64_init(float (&d)[32], uint32_t da, uint32_t db, uint32_t ha = 0x40000040u, uint32_t hb = 0x40000040u) {
    asm volatile("{\n.reg .pred p;\n.reg .b64 a, b;\nsetp.ne.b32 p, 0, 0;\nmov.b64 a, {%32, %35};\nmov.b64 b, {%33, %36};\n"
        "wgmma.mma_async.sync.aligned.m64n64k16.f32.bf16.bf16 {%0, %1, %2, %3, %4, %5, %6, %7, %8, %9, %10, %11, %12, %13, %14, %15, %16, %17, %18, %19, %20, %21, %22, %23, %24, %25, %26, %27, %28, %29, %30, %31}, a, b, p, 1, 1, 0, %34;\n}"
        : "=f"(d[0]), "=f"(d[1]), "=f"(d[2]), "=f"(d[3]), "=f"(d[4]), "=f"(d[5]), "=f"(d[6]), "=f"(d[7]), "=f"(d[8]), "=f"(d[9]), "=f"(d[10]), "=f"(d[11]), "=f"(d[12]), "=f"(d[13]), "=f"(d[14]), "=f"(d[15]), "=f"(d[16]), "=f"(d[17]), "=f"(d[18]), "=f"(d[19]), "=f"(d[20]), "=f"(d[21]), "=f"(d[22]), "=f"(d[23]), "=f"(d[24]), "=f"(d[25]), "=f"(d[26]), "=f"(d[27]), "=f"(d[28]), "=f"(d[29]), "=f"(d[30]), "=f"(d[31])
        : "r"(da), "r"(db), "n"(TB), "r"(ha), "r"(hb));
}
__device__ __forceinline__ void wgmma_rs128(float (&d)[64], uint32_t a0, uint32_t a1, uint32_t a2, uint32_t a3, uint32_t db, int acc, uint32_t hb = 0x40000040u) {
    asm volatile("{\n.reg .pred p;\n.reg .b64 b;\nsetp.ne.b32 p, %69, 0;\nmov.b64 b, {%68, %70};\n"
        "wgmma.mma_async.sync.aligned.m64n128k16.f32.bf16.bf16 {%0, %1, %2, %3, %4, %5, %6, %7, %8, %9, %10, %11, %12, %13, %14, %15, %16, %17, %18, %19, %20, %21, %22, %23, %24, %25, %26, %27, %28, %29, %30, %31, %32, %33, %34, %35, %36, %37, %38, %39, %40, %41, %42, %43, %44, %45, %46, %47, %48, %49, %50, %51, %52, %53, %54, %55, %56, %57, %58, %59, %60, %61, %62, %63}, {%64, %65, %66, %67}, b, p, 1, 1, 1;\n}"
        : "+f"(d[0]), "+f"(d[1]), "+f"(d[2]), "+f"(d[3]), "+f"(d[4]), "+f"(d[5]), "+f"(d[6]), "+f"(d[7]), "+f"(d[8]), "+f"(d[9]), "+f"(d[10]), "+f"(d[11]), "+f"(d[12]), "+f"(d[13]), "+f"(d[14]), "+f"(d[15]), "+f"(d[16]), "+f"(d[17]), "+f"(d[18]), "+f"(d[19]), "+f"(d[20]), "+f"(d[21]), "+f"(d[22]), "+f"(d[23]), "+f"(d[24]), "+f"(d[25]), "+f"(d[26]), "+f"(d[27]), "+f"(d[28]), "+f"(d[29]), "+f"(d[30]), "+f"(d[31]), "+f"(d[32]), "+f"(d[33]), "+f"(d[34]), "+f"(d[35]), "+f"(d[36]), "+f"(d[37]), "+f"(d[38]), "+f"(d[39]), "+f"(d[40]), "+f"(d[41]), "+f"(d[42]), "+f"(d[43]), "+f"(d[44]), "+f"(d[45]), "+f"(d[46]), "+f"(d[47]), "+f"(d[48]), "+f"(d[49]), "+f"(d[50]), "+f"(d[51]), "+f"(d[52]), "+f"(d[53]), "+f"(d[54]), "+f"(d[55]), "+f"(d[56]), "+f"(d[57]), "+f"(d[58]), "+f"(d[59]), "+f"(d[60]), "+f"(d[61]), "+f"(d[62]), "+f"(d[63])
        : "r"(a0), "r"(a1), "r"(a2), "r"(a3), "r"(db), "r"(acc), "r"(hb));
}

__device__ __forceinline__ uint32_t pack2(float lo, float hi) {
    uint32_t r;
    asm("cvt.rn.bf16x2.f32 %0, %1, %2;" : "=r"(r) : "f"(hi), "f"(lo));
    return r;
}
__device__ __forceinline__ float bf_lo(uint32_t v) { return __uint_as_float(v << 16); }
__device__ __forceinline__ float bf_hi(uint32_t v) { return __uint_as_float(v & 0xffff0000u); }
__device__ __forceinline__ float rbf(float v) { return bf_lo(pack2(v, v)); }
__device__ __forceinline__ uint32_t badd(uint32_t a, uint32_t b) {
    uint32_t r;
    asm("add.rn.bf16x2 %0, %1, %2;" : "=r"(r) : "r"(a), "r"(b));
    return r;
}
__device__ __forceinline__ uint32_t bsub(uint32_t a, uint32_t b) {
    uint32_t r;
    asm("sub.rn.bf16x2 %0, %1, %2;" : "=r"(r) : "r"(a), "r"(b));
    return r;
}
__device__ __forceinline__ uint32_t bmul(uint32_t a, uint32_t b) {
    uint32_t r;
    asm("mul.rn.bf16x2 %0, %1, %2;" : "=r"(r) : "r"(a), "r"(b));
    return r;
}
__device__ __forceinline__ uint32_t ln_apply(uint32_t x, uint32_t mb, float rs, uint32_t scale, uint32_t shift) {
    const uint32_t d = bsub(x, mb);
    return badd(bmul(pack2(bf_lo(d) * rs, bf_hi(d) * rs), scale), shift);
}
__device__ __forceinline__ float ex2(float v) {
    float r;
    asm("ex2.approx.ftz.f32 %0, %1;" : "=f"(r) : "f"(v));
    return r;
}
__device__ __forceinline__ float rcp(float v) {
    float r;
    asm("rcp.approx.ftz.f32 %0, %1;" : "=f"(r) : "f"(v));
    return r;
}
__device__ __forceinline__ float sqrt_fast(float v) {
    float r;
    asm("sqrt.approx.ftz.f32 %0, %1;" : "=f"(r) : "f"(v));
    return r;
}
__device__ __forceinline__ float ln_rstd(float var) { return rcp(rbf(sqrt_fast(rbf(rbf(var) + 1e-5f)))); }
__device__ __forceinline__ float sigmoid(float v) { return rcp(1.f + ex2(-1.4426950408889634f * v)); }
__device__ __forceinline__ float warp_sum(float v) {
#pragma unroll
    for (int o = 16; o > 0; o >>= 1) v += __shfl_xor_sync(0xffffffffu, v, o);
    return v;
}
__device__ __forceinline__ float quad_sum(float v) {
    v += __shfl_xor_sync(0xffffffffu, v, 1);
    return v + __shfl_xor_sync(0xffffffffu, v, 2);
}

constexpr uint32_t HI_128 = 0x40000040u, HI_IMG = 0x80000080u, HI_Q = 0x80000040u;
template <int M, int RH>
__device__ __forceinline__ uint4 img_pack(const float (&d)[64], float s) {
    uint4 v;
    v.x = pack2(d[16 * M + 2 * RH] * s, d[16 * M + 2 * RH + 1] * s);
    v.y = pack2(d[16 * M + 4 + 2 * RH] * s, d[16 * M + 5 + 2 * RH] * s);
    v.z = pack2(d[16 * M + 8 + 2 * RH] * s, d[16 * M + 9 + 2 * RH] * s);
    v.w = pack2(d[16 * M + 12 + 2 * RH] * s, d[16 * M + 13 + 2 * RH] * s);
    return v;
}
template <int M, int RH>
__device__ __forceinline__ uint4 img_pack(const float (&d)[64]) {
    uint4 v;
    v.x = pack2(d[16 * M + 2 * RH], d[16 * M + 2 * RH + 1]);
    v.y = pack2(d[16 * M + 4 + 2 * RH], d[16 * M + 5 + 2 * RH]);
    v.z = pack2(d[16 * M + 8 + 2 * RH], d[16 * M + 9 + 2 * RH]);
    v.w = pack2(d[16 * M + 12 + 2 * RH], d[16 * M + 13 + 2 * RH]);
    return v;
}
template <int M>
__device__ __forceinline__ void img_store_global(uint8_t* img, uint32_t toff, const float (&d)[64], float sc) {
    uint4* p = reinterpret_cast<uint4*>(img + toff) + M * 32;
    p[0] = img_pack<M, 0>(d, sc);
    p[128] = img_pack<M, 1>(d, sc);
}
__device__ __forceinline__ void sts128(uint32_t a, uint4 v) {
    asm volatile("st.shared.v4.b32 [%0], {%1, %2, %3, %4};" ::"r"(a), "r"(v.x), "r"(v.y), "r"(v.z), "r"(v.w) : "memory");
}
constexpr float SM_C = 0.08838834764831845f * 1.4426950408889634f;
__device__ __forceinline__ float pack2f(float lo, float hi) {
    float r;
    asm("{\n.reg .b32 t;\ncvt.rn.bf16x2.f32 t, %1, %2;\nmov.b32 %0, t;\n}" : "=f"(r) : "f"(hi), "f"(lo));
    return r;
}
template <int M, bool SCALE, bool PARK>
__device__ __forceinline__ void pack_group(float (&d)[64], float (&v)[8], float s0, float s1) {
#pragma unroll
    for (int i = 0; i < 8; i++) {
        const int k = 16 * M + 4 * (i & 3) + 2 * (i >> 2);
        v[i] = SCALE ? pack2f(d[k] * (i < 4 ? s0 : s1), d[k + 1] * (i < 4 ? s0 : s1)) : pack2f(d[k], d[k + 1]);
        if (PARK && M > 0) d[16 * (M > 0 ? M - 1 : 0) + i] = v[i];
    }
}
template <int M, bool PARK>
__device__ __forceinline__ void q_store_part(uint32_t a, float (&d)[64]) {
    float v[8];
    pack_group<M, false, PARK>(d, v, 0.f, 0.f);
#pragma unroll
    for (int h = 0; h < 2; h++)
        asm volatile("st.shared.v4.f32 [%0], {%1, %2, %3, %4};" ::"r"(a + (M >> 1) * 16384 + (M & 1) * 512 + h * 1024),
                     "f"(v[4 * h]), "f"(v[4 * h + 1]), "f"(v[4 * h + 2]), "f"(v[4 * h + 3]) : "memory");
}
template <bool PARK>
__device__ __forceinline__ void q_store(uint32_t a, uint32_t toff, float (&d)[64]) {
    a += (((toff >> 1) & ~2047u) ^ 8192) + (toff & 511);
    q_store_part<0, PARK>(a, d); q_store_part<1, PARK>(a, d); q_store_part<2, PARK>(a, d); q_store_part<3, PARK>(a, d);
}
template <int M, bool PARK>
__device__ __forceinline__ void ctx_store_part(float4* p, float (&d)[64], float i0, float i1) {
    float v[8];
    pack_group<M, true, PARK>(d, v, i0, i1);
    p[M * 32] = make_float4(v[0], v[1], v[2], v[3]);
    p[M * 32 + 128] = make_float4(v[4], v[5], v[6], v[7]);
}
template <bool PARK>
__device__ __forceinline__ void ctx_store(uint8_t* img, uint32_t toff, float (&o)[64], float l0, float l1) {
    const float i0 = rcp(quad_sum(l0)), i1 = rcp(quad_sum(l1));
    float4* p = reinterpret_cast<float4*>(img + toff);
    ctx_store_part<0, PARK>(p, o, i0, i1); ctx_store_part<1, PARK>(p, o, i0, i1); ctx_store_part<2, PARK>(p, o, i0, i1); ctx_store_part<3, PARK>(p, o, i0, i1);
}

__device__ __forceinline__ void slot_wait(uint32_t bars, uint32_t& ph, uint32_t slot) {
    mbar_wait(bars + 8 * slot, (ph >> slot) & 1);
    ph ^= 1u << slot;
}
__device__ __forceinline__ void load_image(uint32_t sb, uint32_t& ph, uint32_t slot, const void* src, bool first) {
    slot_wait(sb + BAR_EMPTY, ph, slot);
    asm volatile("{\n.reg .pred p;\nelect.sync _|p, 0xffffffff;\n@p mbarrier.arrive.expect_tx.shared::cta.b64 _, [%2], 32768;\n"
                 "@p cp.async.bulk.shared::cluster.global.mbarrier::complete_tx::bytes.L2::cache_hint [%0], [%1], 32768, [%2], %3;\n}"
                 ::"r"(sb + slot * SLOT), "l"(src), "r"(sb + BAR_FULL + 8 * slot), "l"(first ? L2_FIRST : L2_NORMAL) : "memory");
}
__device__ __forceinline__ void load_tile(uint32_t sb, uint32_t& ph, uint32_t slot, const CUtensorMap* m, int row, int cb, bool first) {
    slot_wait(sb + BAR_EMPTY, ph, slot);
    asm volatile("{\n.reg .pred p;\nelect.sync _|p, 0xffffffff;\n@p mbarrier.arrive.expect_tx.shared::cta.b64 _, [%2], 32768;\n"
                 "@p cp.async.bulk.tensor.3d.shared::cluster.global.mbarrier::complete_tx::bytes.L2::cache_hint [%0], [%1, {%3, %4, %5}], [%2], %6;\n}"
                 ::"r"(sb + slot * SLOT), "l"(m), "r"(sb + BAR_FULL + 8 * slot), "r"(0), "r"(row), "r"(cb), "l"(first ? L2_FIRST : L2_NORMAL) : "memory");
}
__device__ __forceinline__ uint32_t ring_next(uint32_t r) { return r == 4 ? 0 : r + 1; }
__device__ __forceinline__ uint32_t w_table(int hp) { return hp ? 0x3104u : 0x4210u; }
__device__ __forceinline__ uint32_t a_table(int hp) { return hp ? 0x625u : 0x635u; }
__device__ __forceinline__ uint32_t a_next(uint32_t& t) {
    const uint32_t s = t & 15;
    t = (t >> 4) | (s << 8);
    return s;
}
constexpr uint32_t O_TABLE = 0x2160435u;
__device__ __forceinline__ uint32_t o_next(uint32_t& t) {
    const uint32_t s = t & 15;
    t = (t >> 4) | (s << 24);
    return s;
}
__device__ __forceinline__ int o_head(int i, int kh) { return i < 16 ? 4 * (i & 7) + 2 * (kh ^ 1) + (i >> 3) : 29 + 2 * kh; }

template <bool INIT>
__device__ __forceinline__ void gemm_issue(float (&d)[64], uint32_t a, uint32_t b, int acc, bool img) {
    const uint32_t ha = img ? HI_IMG : HI_128, o2 = img ? 32 : 4, o4 = img ? 64 : 1024;
    wg_fence();
#pragma unroll
    for (int k = 0; k < 8; k++) {
        if (INIT && k == 0) wgmma_ss128_init<1>(d, a, b, ha);
        else wgmma_ss128<1>(d, a + (k >> 2) * o4 + ((k >> 1) & 1) * o2 + (k & 1) * 2, b + k * 128, k ? 1 : acc, ha);
    }
    wg_commit();
}

template <bool ODD>
__device__ __forceinline__ void proj_tile(float (&acc)[64], float (&prev)[64], int t, int q0, uint32_t sb, int wg, bool elected, uint32_t& fph,
                                          uint32_t wtab, uint32_t& atab, uint8_t* prev_img, uint32_t toff, bool first,
                                          const bf16* x, int xrow) {
    const uint32_t a0 = desc_k(sb + (wg ^ (ODD && t == 5)) * 8192), b0 = desc_mn(sb);
    const int lane = threadIdx.x & 31;
    const float sc = (xrow & 16) ? 1.f : SM_C;
    uint32_t xn[16];
#pragma unroll
    for (int i = 0; i < 4; i++) {
        uint4 v = make_uint4(0, 0, 0, 0);
        if (ODD && first) v = __ldg(reinterpret_cast<const uint4*>(x) + xrow * 64 + lane + 32 * i);
        xn[4 * i] = v.x; xn[4 * i + 1] = v.y; xn[4 * i + 2] = v.z; xn[4 * i + 3] = v.w;
    }
    constexpr int U = ODD ? UNR : 1;
#pragma unroll U
    for (int q = ODD ? 0 : q0; q < 4; q++) {
        if (ODD && t == 5 && q == 3) break;
        const uint32_t ws = (wtab >> (4 * q)) & 15, as = a_next(atab);
        if (!ODD && t != 2) slot_wait(sb + BAR_FULL, fph, ws);
        slot_wait(sb + BAR_FULL, fph, as);
        bar_sync(1 + wg, 256);
        gemm_issue<false>(acc, a0 + as * (SLOT / 16), b0 + ws * (SLOT / 16), q, false);
        bar_arrive(2 - wg, 256);
        wg_wait<1>();
        reg_fence(prev);
        if (ODD && t == 5) {
            if (q == 2) {
                q_store<false>(sb + 5 * SLOT, toff, prev);
                fence_async_smem();
            }
        } else if (ODD || t != 0) {
            if (q == 0) img_store_global<0>(prev_img, toff, prev, sc);
            if (q == 1) img_store_global<1>(prev_img, toff, prev, sc);
            if (q == 2) img_store_global<2>(prev_img, toff, prev, sc);
            if (q == 3) img_store_global<3>(prev_img, toff, prev, sc);
        }
        if (ODD && q == 1 && first) {
            float sum[2] = {0.f, 0.f}, sq[2] = {0.f, 0.f};
#pragma unroll
            for (int k = 0; k < 16; k++) sum[k >> 3] += bf_lo(xn[k]) + bf_hi(xn[k]);
#pragma unroll
            for (int i = 0; i < 2; i++) sum[i] = warp_sum(sum[i]) * (1.f / 512.f);
#pragma unroll
            for (int k = 0; k < 16; k++) {
                const float d0 = bf_lo(xn[k]) - sum[k >> 3], d1 = bf_hi(xn[k]) - sum[k >> 3];
                sq[k >> 3] = fmaf(d0, d0, fmaf(d1, d1, sq[k >> 3]));
            }
#pragma unroll
            for (int i = 0; i < 2; i++) sq[i] = ln_rstd(warp_sum(sq[i]) * (1.f / 512.f));
#pragma unroll
            for (int k = 0; k < 16; k++) {
                const uint32_t d = bsub(xn[k], pack2(sum[k >> 3], sum[k >> 3]));
                xn[k] = pack2(bf_lo(d) * sq[k >> 3], bf_hi(d) * sq[k >> 3]);
            }
        }
        if (ODD && q == LNQ && first) {
            mbar_wait(sb + BAR_FLAG + 8 * 8, 0);
#pragma unroll
            for (int i = 0; i < 4; i++) {
                const int rin = (xrow + (i >> 1)) & 127;
                const uint4 a = lds128(sb + SM_TAB + 1024 + (i & 1) * 512 + lane * 16), c = lds128(sb + SM_TAB + (i & 1) * 512 + lane * 16);
                *reinterpret_cast<uint4*>(g_h + ((xrow >> 7) * 8 + (i & 1) * 4 + (lane >> 3)) * 16384 + rin * 128 + (((lane ^ rin) & 7) << 4)) =
                    make_uint4(badd(bmul(xn[4 * i], badd(a.x, ONE2)), c.x), badd(bmul(xn[4 * i + 1], badd(a.y, ONE2)), c.y),
                               badd(bmul(xn[4 * i + 2], badd(a.z, ONE2)), c.z), badd(bmul(xn[4 * i + 3], badd(a.w, ONE2)), c.w));
            }
            __syncwarp();
            mbar_arrive_if(sb + BAR_DONE, lane == 0);
        }
        wg_wait<0>();
        mbar_arrive_if(sb + BAR_EMPTY + 8 * as, elected && !(ODD && (q & 1) && t == 5));
        if (ODD) mbar_arrive_if(sb + BAR_EMPTY + 8 * ws, elected && t != 1);
    }
    reg_fence(acc);
}

__device__ __forceinline__ void qk_issue(float (&s)[64], uint32_t q, uint32_t k) {
    wg_fence();
    wgmma_ss128_init<0>(s, q, k, HI_Q, HI_IMG);
#pragma unroll
    for (int i = 1; i < 8; i++) wgmma_ss128<0>(s, q + (i >> 2) * 1024 + (i & 2) * 16 + (i & 1) * 2, k + (i >> 1) * 32 + (i & 1) * 2, 1, HI_Q, HI_IMG);
    wg_commit();
}
__device__ __forceinline__ void qk_issue(float (&s)[32], uint32_t q, uint32_t k) {
    wg_fence();
    wgmma_ss64_init<0>(s, q, k, HI_Q, HI_IMG);
#pragma unroll
    for (int i = 1; i < 8; i++) wgmma_ss64<0>(s, q + (i >> 2) * 1024 + (i & 2) * 16 + (i & 1) * 2, k + (i >> 1) * 32 + (i & 1) * 2, 1, HI_Q, HI_IMG);
    wg_commit();
}
__device__ __forceinline__ void pv_issue(float (&o)[64], const uint32_t (&p)[32], uint32_t v, int acc, bool half) {
    if (half) {
        asm volatile("// half" ::: "memory");
        wg_fence();
#pragma unroll
        for (int i = 0; i < 4; i++) wgmma_rs128(o, p[4 * i], p[4 * i + 1], p[4 * i + 2], p[4 * i + 3], v + i * 256, i ? 1 : acc, HI_IMG);
        wg_commit();
        asm volatile("// half" ::: "memory");
    } else {
        wg_fence();
#pragma unroll
        for (int i = 0; i < 8; i++) wgmma_rs128(o, p[4 * i], p[4 * i + 1], p[4 * i + 2], p[4 * i + 3], v + i * 256, i ? 1 : acc, HI_IMG);
        wg_commit();
    }
}
template <int B, int N>
__device__ __forceinline__ void tri_mask(float (&s)[N], int x) {
#pragma unroll
    for (int k = 0; k < 7; k++)
        asm("{\n.reg .pred p, q;\nsetp.lt.s32 p, %4, %5;\nsetp.le.s32 q, %4, %5;\n"
            "@p mov.b32 %0, 0fFF800000;\n@q mov.b32 %1, 0fFF800000;\n@p mov.b32 %2, 0fFF800000;\n@q mov.b32 %3, 0fFF800000;\n}"
            : "+f"(s[B + 4 * k]), "+f"(s[B + 4 * k + 1]), "+f"(s[B + 4 * k + 6]), "+f"(s[B + 4 * k + 7]) : "r"(x), "r"(8 * k));
    asm("{\n.reg .pred p, q;\nsetp.lt.s32 p, %2, 56;\nsetp.le.s32 q, %2, 56;\n@p mov.b32 %0, 0fFF800000;\n@q mov.b32 %1, 0fFF800000;\n}"
        : "+f"(s[B + 28]), "+f"(s[B + 29]) : "r"(x));
}
__device__ __forceinline__ void tri_mask_copy(float (&s)[64], const float (&h)[32], int x) {
#pragma unroll
    for (int i = 0; i < 32; i++) {
        asm("{\n.reg .pred p;\nsetp.lt.s32 p, %2, %3;\nselp.f32 %0, 0fFF800000, %1, p;\n}"
            : "=f"(s[i]) : "f"(h[i]), "r"(x), "r"(8 * (i >> 2) - 4 * (i & 2) + (i & 1)));
        s[32 + i] = __uint_as_float(0xff800000u);
    }
}
constexpr float SM_HI = 1152921504606846976.f, SM_LO = 1.f / 1152921504606846976.f;
__device__ __forceinline__ bool softmax_unsafe(float t0, float t1, bool first) {
    bool bad = __any_sync(0xffffffffu, fmaxf(t0, t1) > SM_HI);
    if (first) {
        uint32_t a = __ballot_sync(0xffffffffu, t0 >= SM_LO), b = __ballot_sync(0xffffffffu, t1 >= SM_LO);
        a |= a >> 1;
        b |= b >> 1;
        bad |= ((a | (a >> 2)) & (b | (b >> 2)) & 0x11111111u) != 0x11111111u;
    }
    return bad;
}
__device__ __forceinline__ void softmax_shift(float (&s)[64], float d0, float d1) {
#pragma unroll
    for (int i = 0; i < 64; i++) s[i] -= (i & 2) ? d1 : d0;
}
__device__ __forceinline__ void softmax_remax(float (&s)[64], float (&m)[2], bool first, float& a0, float& a1) {
    float m0 = fmaxf(s[0], s[1]), m1 = fmaxf(s[2], s[3]);
#pragma unroll
    for (int k = 1; k < 16; k++) {
        m0 = fmaxf(m0, fmaxf(s[4 * k], s[4 * k + 1]));
        m1 = fmaxf(m1, fmaxf(s[4 * k + 2], s[4 * k + 3]));
    }
    m0 = fmaxf(m0, __shfl_xor_sync(0xffffffffu, m0, 1));
    m1 = fmaxf(m1, __shfl_xor_sync(0xffffffffu, m1, 1));
    m0 = fmaxf(m0, __shfl_xor_sync(0xffffffffu, m0, 2));
    m1 = fmaxf(m1, __shfl_xor_sync(0xffffffffu, m1, 2));
    if (!first) {
        m0 = fmaxf(m0, 0.f);
        m1 = fmaxf(m1, 0.f);
    }
    a0 = first ? 1.f : ex2(-m0);
    a1 = first ? 1.f : ex2(-m1);
    m[0] += m0;
    m[1] += m1;
    softmax_shift(s, m0, m1);
}
template <int J0, int J1>
__device__ __forceinline__ void softmax_exp(const float (&s)[64], uint32_t (&p)[32], float (&t)[4]) {
#pragma unroll
    for (int k = J0; k < J1; k++) {
        const float e0 = ex2(s[4 * k]), e1 = ex2(s[4 * k + 1]), e2 = ex2(s[4 * k + 2]), e3 = ex2(s[4 * k + 3]);
        if (k == 0) { t[0] = e0; t[1] = e1; t[2] = e2; t[3] = e3; }
        else { t[0] += e0; t[1] += e1; t[2] += e2; t[3] += e3; }
        p[2 * k] = pack2(e0, e1);
        p[2 * k + 1] = pack2(e2, e3);
    }
}
__device__ __forceinline__ void fma8(float (&acc)[8], float a, uint4 w) {
    acc[0] = fmaf(a, bf_lo(w.x), acc[0]); acc[1] = fmaf(a, bf_hi(w.x), acc[1]);
    acc[2] = fmaf(a, bf_lo(w.y), acc[2]); acc[3] = fmaf(a, bf_hi(w.y), acc[3]);
    acc[4] = fmaf(a, bf_lo(w.z), acc[4]); acc[5] = fmaf(a, bf_hi(w.z), acc[5]);
    acc[6] = fmaf(a, bf_lo(w.w), acc[6]); acc[7] = fmaf(a, bf_hi(w.w), acc[7]);
}
__device__ __forceinline__ void mma16816(float (&d)[4], const uint32_t* a, uint32_t b0, uint32_t b1) {
    asm("mma.sync.aligned.m16n8k16.row.col.f32.bf16.bf16.f32 {%0, %1, %2, %3}, {%4, %5, %6, %7}, {%8, %9}, {%0, %1, %2, %3};"
        : "+f"(d[0]), "+f"(d[1]), "+f"(d[2]), "+f"(d[3]) : "r"(a[0]), "r"(a[1]), "r"(a[2]), "r"(a[3]), "r"(b0), "r"(b1));
}
__device__ __forceinline__ uint32_t best_key(const uint32_t* keys, int lane, uint32_t ep) {
    uint32_t best;
#pragma unroll 1
    for (;;) {
        const uint4 k = ld_poll(reinterpret_cast<const uint4*>(keys) + lane);
        best = max(max(k.x, k.y), max(k.z, k.w));
        if (__all_sync(0xffffffffu, (((k.x ^ ep) | (k.y ^ ep) | (k.z ^ ep) | (k.w ^ ep)) & 31) == 0)) break;
    }
    return __reduce_max_sync(0xffffffffu, best);
}

__global__ void __launch_bounds__(384, 1)
fused_kernel(const __grid_constant__ CUtensorMap tm_ckv, const __grid_constant__ CUtensorMap tm_wq,
             const __grid_constant__ CUtensorMap tm_wuk, const __grid_constant__ CUtensorMap tm_wuv,
             const __grid_constant__ CUtensorMap tm_wo, const __grid_constant__ CUtensorMap tm_wg,
             const __grid_constant__ CUtensorMap tm_wu, const __grid_constant__ CUtensorMap tm_wd,
             const __grid_constant__ CUtensorMap tm_wm, const Params P) {
    extern __shared__ __align__(1024) uint8_t smem[];
    const uint32_t sb = (uint32_t)__cvta_generic_to_shared(smem);
    const int tid = threadIdx.x, lane = tid & 31, warp = __shfl_sync(0xffffffffu, tid >> 5, 0), wg = warp >> 2;
    uint32_t sm;
    asm("mov.u32 %0, %%smid;" : "=r"(sm));
    const uint32_t smq = ((sm - 64) * 147) >> 11;
    const int rb = !P.by_smid ? blockIdx.x : sm < 64 ? (sm & 14) * 8 + (sm >> 4) * 2 + (sm & 1)
                 : sm < 120 ? ((sm - 64 - smq * 14) & 14) * 8 + 24 + smq * 2 + (sm & 1) : sm < 124 ? sm + 8 : sm - 116;
    const int grp = rb >> 3, j = rb & 7, cq = j & 3, kh = grp & 1, ort = (grp & 14) + (j >> 2);
    if (warp == 0) TS(0);

    if (rb >= NCTA) {
        float* sc = reinterpret_cast<float*>(smem + 6 * SLOT);
        float* red = sc + 512;
        if (tid == 256) {
            for (int i = 0; i < 6; i++) { mbar_init(sb + BAR_FULL + 8 * i, 1); mbar_init(sb + BAR_EMPTY + 8 * i, 8); }
            fence_async_smem();
        }
        __syncthreads();
        uint32_t ph = 0, sl = 0;
        if (tid == 256) {
#pragma unroll 1
            for (int i = 0; i < 24; i++) {
                mbar_wait(sb + BAR_EMPTY + 8 * sl, ph ^ 1);
                mbar_expect(sb + BAR_FULL + 8 * sl, SLOT);
                tma2d(sb + sl * SLOT, &tm_wm, (i >> 3) * 1024 + (rb - NCTA) * 256, (i & 7) * 64, sb + BAR_FULL + 8 * sl);
                if (++sl == 6) { sl = 0; ph ^= 1; }
            }
        } else if (tid < 256) {
            const uint32_t c2 = __ldg(reinterpret_cast<const uint32_t*>(P.c) + tid);
            sc[2 * tid] = rbf(bf_lo(c2) * sigmoid(bf_lo(c2)));
            sc[2 * tid + 1] = rbf(bf_hi(c2) * sigmoid(bf_hi(c2)));
            bar_sync(1, 256);
#pragma unroll 1
            for (int ps = 0; ps < 3; ps++) {
                float acc[8] = {0.f, 0.f, 0.f, 0.f, 0.f, 0.f, 0.f, 0.f};
#pragma unroll 1
                for (int bt = 0; bt < 8; bt++) {
                    mbar_wait(sb + BAR_FULL + 8 * sl, ph);
#pragma unroll
                    for (int i = 0; i < 8; i++)
                        fma8(acc, sc[bt * 64 + warp * 8 + i], *reinterpret_cast<const uint4*>(smem + sl * SLOT + (warp * 8 + i) * 512 + lane * 16));
                    __syncwarp();
                    mbar_arrive_if(sb + BAR_EMPTY + 8 * sl, lane == 0);
                    if (++sl == 6) { sl = 0; ph ^= 1; }
                }
                *reinterpret_cast<float4*>(red + warp * 256 + lane * 8) = make_float4(acc[0], acc[1], acc[2], acc[3]);
                *reinterpret_cast<float4*>(red + warp * 256 + lane * 8 + 4) = make_float4(acc[4], acc[5], acc[6], acc[7]);
                bar_sync(1, 256);
                float v = 0.f;
#pragma unroll
                for (int i = 0; i < 8; i++) v += red[i * 256 + tid];
                g_mod[ps * 1024 + (rb - NCTA) * 256 + tid] = __float2bfloat16_rn(v);
                bar_sync(1, 256);
                if (tid == 0 && ps != 1) flag_add(&g_sync.modcnt[(ps >> 1) * 32]);
                if (warp == 0) TS(1 + ps);
            }
        }
        return;
    }

    if (tid == 256) {
        if (sb & 1023) __trap();
        asm volatile("prefetch.tensormap [%0];" ::"l"((j & 1) ? &tm_wuv : &tm_wuk) : "memory");
        asm volatile("prefetch.tensormap [%0];" ::"l"(&tm_ckv) : "memory");
        for (int i = 0; i < 7; i++) { mbar_init(sb + BAR_FULL + 8 * i, 1); mbar_init(sb + BAR_EMPTY + 8 * i, 2); }
        for (int i = 0; i < 9; i++) mbar_init(sb + BAR_DONE + 8 * i, 8);
        for (int i = 0; i < 12; i++) mbar_init(sb + BAR_FLAG + 8 * i, 1);
        mbar_init(sb + BAR_END, 8);
        fence_async_smem();
    }
    __syncthreads();

    if (wg == 2) {
        asm volatile("setmaxnreg.dec.sync.aligned.u32 40;");
        if (warp == 8) {
            uint32_t eph = 0x7f, r = 0;
            const CUtensorMap* tw = (j & 1) ? &tm_wuv : &tm_wuk;
#pragma unroll 1
            for (int hp = 0; hp < 2; hp++) {
                const int hc = 4 * grp + 2 * hp;
                uint32_t wtab = w_table(hp), atab = a_table(hp);
#pragma unroll 1
                for (int u = 0; u < 4; u++) {
                    load_tile(sb, eph, (wtab >> (4 * u)) & 15, tw, u * 128, hc, HINT & 1); PT();
                    load_tile(sb, eph, a_next(atab), &tm_ckv, (j >> 1) * 128, u * 2, (HINT & 8) && hp); PT();
                    if (hp == 1 && (u & 1) && lane == 0) asm volatile("red.relaxed.gpu.global.add.u32 [%0], 1;" ::"l"(&g_sync.rdcnt[(grp * 2 + (u >> 1)) * 8]) : "memory");
                }
#pragma unroll 1
                for (int u = 4; u < 16; u++) {
                    if (hp == 1 && (u & 7) == 4) mbar_wait(sb + BAR_FLAG + 24 + (u & 8), 0);
                    load_tile(sb, eph, a_next(atab), &tm_ckv, ((u & 12) + (j >> 1)) * 128, (u & 3) * 2, (HINT & 8) && hp); PT();
                }
                mbar_wait(sb + BAR_FLAG, 0);
                fence_async_global();
#pragma unroll 1
                for (int u = 0; u < 4; u++) {
                    load_tile(sb, eph, (wtab >> (4 * u)) & 15, &tm_wq, u * 128, hc, HINT & 1); PT();
                    load_image(sb, eph, a_next(atab), g_h + ((15 - j) * 4 + u) * SLOT, (HINT & 8) && hp); PT();
                }
                mbar_wait(sb + BAR_FLAG + 8 + 32 * hp, 0);
                fence_async_global();
#pragma unroll 1
                for (int u = 0; u < 4; u++) { load_image(sb, eph, a_next(atab), g_h + (j * 4 + u) * SLOT, (HINT & 8) && hp); PT(); }
                const uint8_t* kv = g_KV + (size_t)(grp * 32 + 30 * hp) * SLOT;
                const int step = hp ? -2 * SLOT : 2 * SLOT;
                load_image(sb, eph, r, kv, HINT & 4); PT();
                r = ring_next(r);
#pragma unroll 1
                for (int n = 1; n <= 16; n++) {
                    if (n == 8) {
                        mbar_wait(sb + BAR_FLAG + 16 + 32 * hp, 0);
                        fence_async_global();
                    }
                    mbar_arrive_if(sb + BAR_PF, lane == 0 && (n == PF1 || n == PF2));
                    const uint8_t* v = kv + SLOT;
                    kv += n < 16 - j ? step : n == 16 - j ? (2 * j - 15) * step : -step;
                    load_image(sb, eph, r, kv, HINT & 4); PT();
                    r = ring_next(r);
                    load_image(sb, eph, r, v, HINT & 4); PT();
                    r = ring_next(r);
                }
                load_image(sb, eph, r, kv + SLOT, HINT & 4); PT();
                r = ring_next(r);
            }
            uint32_t otab = O_TABLE;
#pragma unroll 1
            for (int i = 0; i < 17; i++) {
                if ((i & 7) == 0) {
                    mbar_wait(sb + BAR_FLAG + 8 * 9 + (i ? 8 : 0), 0);
                    fence_async_global();
                }
                const int head = o_head(i, kh);
                load_image(sb, eph, o_next(otab), g_ctx + (size_t)(ort * 32 + head) * SLOT, HINT & 16); PT();
                load_tile(sb, eph, o_next(otab), &tm_wo, head * 128, cq * 2, HINT & 2); PT();
            }
            if (lane == 0) {
                const uint32_t s1 = o_next(otab), s2 = o_next(otab);
                if (rb < NFFN) {
                    slot_wait(sb + BAR_EMPTY, eph, s1);
                    const uint32_t f = sb + BAR_FULL + 8 * s1, d = sb + s1 * SLOT;
                    mbar_expect(f, SLOT);
                    tma2d(d, &tm_wg, rb * 16, 0, f);
                    tma2d(d + 8192, &tm_wg, rb * 16, 256, f);
                    tma2d(d + 16384, &tm_wu, rb * 16, 0, f);
                    tma2d(d + 24576, &tm_wu, rb * 16, 256, f);
                }
                slot_wait(sb + BAR_EMPTY, eph, s2);
                mbar_expect(sb + BAR_FULL + 8 * s2, 7 * 4096);
#pragma unroll 1
                for (int k = 0; k < 7; k++) tma2d(sb + s2 * SLOT + k * 4096, &tm_wd, (rb >> 1) * 8, k * 256, sb + BAR_FULL + 8 * s2);
            }
        } else {
            const int hw = warp - 9;
            if (hw == 1 && lane == 0) {
                mbar_watch(sb + BAR_FULL + 8 * PF0, 0);
                l2_prefetch(P.ckv + 512 * 512 + rb * 6144, 12288);
                l2_prefetch(P.x + rb * 8192, 16384);
                mbar_watch(sb + BAR_FULL + 8 * 4, 0);
                TS(40);
                if (j < 4) tma3d_prefetch(&tm_wq, j * 128, grp * 4);
                mbar_watch(sb + BAR_PF, 0);
                l2_prefetch(P.ckv + rb * 8192, 16384);
                l2_prefetch(g_h + rb * 16384, 16384);
                mbar_watch(sb + BAR_PF, 1);
                tma3d_prefetch((j & 1) ? &tm_wuv : &tm_wuk, (j >> 1) * 128, grp * 4 + 2);
                if (j < 4) tma3d_prefetch(&tm_wq, j * 128, grp * 4 + 2);
                mbar_watch(sb + BAR_PF, 0);
                l2_prefetch(g_ctx + (size_t)(ort * 32 + o_head(cq, kh)) * SLOT, SLOT);
                l2_prefetch(g_ctx + (size_t)(ort * 32 + o_head(cq + 4, kh)) * SLOT, SLOT);
                mbar_watch(sb + BAR_PF, 1);
                l2_prefetch(reinterpret_cast<const uint8_t*>(P.wo) + rb * 32768, 32768);
                l2_prefetch(reinterpret_cast<const uint8_t*>(P.wgate) + rb * 14336, 14336);
                l2_prefetch(reinterpret_cast<const uint8_t*>(P.wup) + rb * 14336, 14336);
                l2_prefetch(reinterpret_cast<const uint8_t*>(P.wdown) + rb * 14336, 14336);
                l2_prefetch(P.x + rb * 8192, 16384);
                mbar_watch(sb + BAR_END, 0);
            }
            if (hw == 0) {
#pragma unroll 1
                for (int i = 0; i < 9; i++) {
                    const int hp = i > 4, k = (i - 1) & 3;
                    if (lane == 0) {
                        mbar_wait(sb + BAR_DONE + 8 * i, 0);
                        flag_add(i == 0 ? &g_sync.hcnt[grp * 8] : k < 2 ? &g_sync.kvcnt[((2 * grp + hp) * 2 + k) * 8]
                                                                        : &g_sync.ctxcnt[(k == 2 ? 15 - j : j) * 32 + 2 * grp + hp]);
                    }
                    if (i == 0) TS(43);
                }
            }
            if (hw == 2) {
                const uint32_t ep = __ldcg(&g_sync.epoch[0]) + 1;
                if (lane == 0) {
                    asm volatile("st.shared.u32 [%0], %1;" ::"r"(sb + SM_EP), "r"(ep) : "memory");
                    flag_wait(&g_sync.modcnt[0], NSPARE * ep);
                }
                __syncwarp();
#pragma unroll
                for (int i = 0; i < 4; i++) sts128(sb + SM_TAB + i * 512 + lane * 16, __ldcg(reinterpret_cast<const uint4*>(g_mod) + lane + 32 * i));
                __syncwarp();
                if (lane == 0) mbar_arrive(sb + BAR_FLAG + 8 * 8);
                TS(42);
#pragma unroll 1
                for (int i = 0; i < 8; i++) {
                    if (lane == 0) mbar_wait(sb + BAR_DONE + 8 * (i == 7 ? 6 : i), 0);
                    __syncwarp();
                    const uint32_t* f = i == 0 ? &g_sync.hcnt[(lane ? j : 15 - j) * 8]
                                      : i == 3 || i == 4 ? &g_sync.rdcnt[(grp * 2 + i - 3) * 8]
                                      : i == 7 ? &g_sync.modcnt[32] : &g_sync.kvcnt[(4 * grp + (i > 4 ? i - 3 : i - 1)) * 8];
                    if (lane < (i ? 1 : 2)) flag_wait(f, i == 7 ? NSPARE * ep : 8 * ep);
                    __syncwarp();
                    if (i == 7) {
                        const uint32_t *mp = reinterpret_cast<const uint32_t*>(g_mod) + lane, *wp = reinterpret_cast<const uint32_t*>(P.wr) + lane;
                        float ra = 0.f, rs = 0.f;
#pragma unroll 1
                        for (int k = 0; k < 256; k += 32) {
                            const uint32_t ga = __ldcg(mp + 512 + k), sh = __ldcg(mp + 768 + k), c1 = badd(__ldcg(mp + 1024 + k), ONE2);
                            const uint32_t gb = __ldcg(mp + 1280 + k), ww = __ldg(wp + k);
                            const float a0 = bf_lo(c1) * bf_lo(ww), a1 = bf_hi(c1) * bf_hi(ww);
                            ra += a0 + a1;
                            rs = fmaf(bf_lo(sh), bf_lo(ww), fmaf(bf_hi(sh), bf_hi(ww), rs));
                            if (k >> 6 == cq) {
                                sts128(sb + SM_TAB + ((k & 32) + lane) * 16, make_uint4(ga << 16, ga & 0xffff0000u, __float_as_uint(a0), __float_as_uint(a1)));
                                sts128(sb + SM_TAB + 1024 + ((k & 32) + lane) * 16, make_uint4(c1, sh, gb, 0));
                            }
                        }
                        *reinterpret_cast<float2*>(smem + SM_EP + 8) = make_float2(warp_sum(ra), warp_sum(rs));
                        __syncwarp();
                    }
                    if (lane == 0) mbar_arrive(sb + BAR_FLAG + 8 * i);
                    TS(48 + i);
                }
#pragma unroll 1
                for (int i = 0; i < 2; i++) {
                    if (i) mbar_wait(sb + BAR_DONE + 8 * 7, 0);
                    if (lane < 8 + i) flag_wait(&g_sync.ctxcnt[ort * 32 + o_head(lane + 8 * i, kh)], ep);
                    __syncwarp();
                    if (lane == 0) mbar_arrive(sb + BAR_FLAG + 8 * (9 + i));
                    TS(44 + i);
                }
            }
        }
    } else {
        asm volatile("setmaxnreg.inc.sync.aligned.u32 232;");
        const bool elected = (tid & 127) == 0;
        const int g = lane >> 2, c4 = lane & 3;
        const uint32_t toff = warp * 4096 + g * 64 + ((c4 ^ (g >> 1)) << 4);
        uint32_t fph = 0, r = 0;
        if (wg == 1) bar_arrive(1, 256);
        const uint32_t kd = desc_k(sb), wd = desc_mn(sb), vd = (sb >> 4) | (32u << 16);
        const int nL = 16 - j, hn = nL - 1 + wg;
        float s[64], o[64];
#pragma unroll 1
        for (int hp = 0; hp < 2; hp++) {
            {
                const int step = hp ? -8 * SLOT : 8 * SLOT;
                uint8_t* img = g_KV + (size_t)(grp * 32 + (hp ? j ^ 30 : j)) * SLOT - step;
                const uint32_t wtab = w_table(hp);
                uint32_t atab = hp ? 0x256u : a_table(0);
#pragma unroll 1
                for (int t = 0; t < 6; t += 2) {
                    proj_tile<false>(s, o, t, t ? 0 : 2 * hp, sb, wg, elected, fph, wtab, atab, img, toff, (hp | t) == 0, P.x, rb * 16 + warp * 2);
                    __syncwarp();
                    mbar_arrive_if(sb + BAR_DONE + 4 * t + 32 * hp, lane == 0 && t != 0);
                    if (elected) TS(1 + 10 * hp + t + 20 * wg);
                    proj_tile<true>(o, s, t + 1, 0, sb, wg, elected, fph, wtab, atab, img + step, toff, (hp | t) == 0, P.x, rb * 16 + warp * 2);
                    if (elected) TS(2 + 10 * hp + t + 20 * wg);
                    img += 2 * step;
                }
            }
            float m[2] = {0.f, 0.f}, l[2] = {0.f, 0.f}, t[4] = {0.f, 0.f, 0.f, 0.f};
            bool shifted = false, bad = false, plain = false;
            uint32_t p[32];
#pragma unroll
            for (int i = 0; i < 32; i++) p[i] = 0;
            uint32_t qa = desc_k(sb + 5 * SLOT + (wg ^ 1) * 8192);
            uint8_t* img = g_ctx + (size_t)((15 - j) * 32 + 2 * grp + hp) * SLOT;
            slot_wait(sb + BAR_FULL, fph, r);
            int n = -1;
#pragma unroll 1
            for (;;) {
                while (bad || plain) {
                    if (bad) {
                        float a0, a1;
                        softmax_remax(s, m, n == 0 || n == nL, a0, a1);
                        shifted = true;
                        l[0] *= a0;
                        l[1] *= a1;
#pragma unroll
                        for (int i = 0; i < 64; i++) o[i] *= (i & 2) ? a1 : a0;
                    }
                    softmax_exp<0, 16>(s, p, t);
                    t[0] += t[1];
                    t[2] += t[3];
                    bad = !bad && softmax_unsafe(t[0], t[2], false);
                    plain = false;
                }
#pragma unroll 1
                do {
                    l[0] += t[0];
                    l[1] += t[2];
                    if (++n > 16) break;
                    const uint32_t ks = r;
                    uint32_t vs = ring_next(r);
                    r = ring_next(vs);
                    bar_sync(1 + wg, 256);
                    if (n == 0 || (uint32_t)(n + 1 - nL) <= (uint32_t)(1 + wg)) {
                        const int x = (warp & 3) * 16 + g - 2 * c4;
                        if (n == 0) {
                            r = vs;
                            vs = 4 - hp;
                            qk_issue(s, qa, kd + ks * (SLOT / 16));
                            slot_wait(sb + BAR_FULL, fph, 6);
                            gemm_issue<false>(o, qa + SLOT / 16, wd + vs * (SLOT / 16), 1, false);
                            bar_arrive(2 - wg, 256);
                            wg_wait<1>();
                            reg_fence(s);
                        } else if (n == hn) {
                            float sh[32];
                            qk_issue(sh, qa, kd + ks * (SLOT / 16));
                            slot_wait(sb + BAR_FULL, fph, vs);
                            pv_issue(o, p, vd + vs * (SLOT / 16), 1, false);
                            bar_arrive(2 - wg, 256);
                            wg_wait<1>();
                            reg_fence(sh);
                            tri_mask_copy(s, sh, x);
                        } else {
                            qk_issue(s, qa, kd + ks * (SLOT / 16));
                            slot_wait(sb + BAR_FULL, fph, vs);
                            pv_issue(o, p, vd + vs * (SLOT / 16), n != nL + 1, n == hn + 1);
                            bar_arrive(2 - wg, 256);
                            wg_wait<1>();
                            reg_fence(s);
                            if (n <= nL) tri_mask<32>(s, x);
                        }
                        mbar_arrive_if(sb + BAR_EMPTY + 8 * ks, elected);
                        mbar_arrive_if(sb + BAR_EMPTY + 8 * (n == 16 ? 6 : 5), elected && (n == 16 || n == nL - 1));
                        if (n == nL - 1) {
                            qa += SLOT / 16;
                            fence_async_smem();
                        }
                        if (shifted) {
                            if (n == nL) {
                                m[0] = m[1] = 0.f;
                                shifted = false;
                            }
                            softmax_shift(s, m[0], m[1]);
                        }
                        float e[4 * EARLY];
#pragma unroll
                        for (int i = 0; i < 4 * EARLY; i++) {
                            e[i] = ex2(s[i]);
                            t[i & 3] = i < 4 ? e[i] : t[i & 3] + e[i];
                        }
                        reg_fence(e);
                        slot_wait(sb + BAR_FULL, fph, r);
                        wg_wait<0>();
                        reg_fence(o);
                        reg_fence(e);
                        mbar_arrive_if(sb + BAR_EMPTY + 8 * vs, elected);
#pragma unroll
                        for (int i = 0; i < 2 * EARLY; i++) p[i] = pack2(e[2 * i], e[2 * i + 1]);
                        softmax_exp<EARLY, 8>(s, p, t);
                        if (n == 0) q_store<(PARKS & 1) != 0>(sb + 6 * SLOT, toff, o);
                        if (n == nL) {
                            ctx_store<(PARKS & 2) != 0>(img, toff, o, l[0], l[1]);
                            __syncwarp();
                            mbar_arrive_if(sb + BAR_DONE + 24 + 32 * hp, lane == 0);
                            l[0] = l[1] = 0.f;
                        }
                        if (n != hn) softmax_exp<8, 16>(s, p, t);
                        t[0] += t[1];
                        t[2] += t[3];
                        bad = softmax_unsafe(t[0], t[2], n == 0 || n == nL);
                        continue;
                    }
                    qk_issue(s, qa, kd + ks * (SLOT / 16));
                    slot_wait(sb + BAR_FULL, fph, vs);
                    pv_issue(o, p, vd + vs * (SLOT / 16), n != 1 && n != nL + 1, false);
                    bar_arrive(2 - wg, 256);
                    wg_wait<1>();
                    reg_fence(s);
                    mbar_arrive_if(sb + BAR_EMPTY + 8 * ks, elected);
                    mbar_arrive_if(sb + BAR_EMPTY + 8 * 6, elected && n == 16);
                    if (shifted) {
                        slot_wait(sb + BAR_FULL, fph, r);
                        wg_wait<0>();
                        reg_fence(o);
                        mbar_arrive_if(sb + BAR_EMPTY + 8 * vs, elected);
                        softmax_shift(s, m[0], m[1]);
                        plain = true;
                        break;
                    }
                    float e[4 * EARLY];
#pragma unroll
                    for (int i = 0; i < 4 * EARLY; i++) {
                        e[i] = ex2(s[i]);
                        t[i & 3] = i < 4 ? e[i] : t[i & 3] + e[i];
                    }
                    reg_fence(e);
                    slot_wait(sb + BAR_FULL, fph, r);
                    wg_wait<0>();
                    reg_fence(o);
                    reg_fence(e);
                    mbar_arrive_if(sb + BAR_EMPTY + 8 * vs, elected);
#pragma unroll
                    for (int i = 0; i < 2 * EARLY; i++) p[i] = pack2(e[2 * i], e[2 * i + 1]);
                    softmax_exp<EARLY, 16>(s, p, t);
                    t[0] += t[1];
                    t[2] += t[3];
                    bad = softmax_unsafe(t[0], t[2], false);
                } while (!bad);
                if (!bad && !plain) break;
            }
            const uint32_t vs = r, ga = desc_k(sb + (hp ? 2 * (wg ^ kh ^ 1) : wg) * 8192), as = 2 + 2 * hp;
            r = ring_next(r);
            slot_wait(sb + BAR_FULL, fph, 5);
            slot_wait(sb + BAR_FULL, fph, r);
            bar_sync(1 + wg, 256);
            gemm_issue<true>(s, ga + 5 * (SLOT / 16), wd + r * (SLOT / 16), 0, hp);
            pv_issue(o, p, vd + vs * (SLOT / 16), j, hn == 16);
            bar_arrive(2 - wg, 256);
            wg_wait<1>();
            mbar_arrive_if(sb + BAR_EMPTY + 8 * 5, elected);
            mbar_arrive_if(sb + BAR_EMPTY + 8 * r, elected && hp);
            wg_wait<0>();
            mbar_arrive_if(sb + BAR_EMPTY + 8 * vs, elected);
            slot_wait(sb + BAR_FULL, fph, as);
            slot_wait(sb + BAR_FULL, fph, 0);
            bar_sync(1 + wg, 256);
            gemm_issue<false>(s, ga + as * (SLOT / 16), wd, 1, hp);
            bar_arrive(2 - wg, 256);
            reg_fence(o);
            ctx_store<(PARKS & 4) != 0>(img + (ptrdiff_t)(2 * j - 15) * 32 * SLOT, toff ^ 16384, o, l[0], l[1]);
            __syncwarp();
            mbar_arrive_if(sb + BAR_DONE + 32 + 32 * hp, lane == 0);
            wg_wait<0>();
            mbar_arrive_if(sb + BAR_EMPTY + 8 * as, elected);
            mbar_arrive_if(sb + BAR_EMPTY, elected && hp);
            if (elected) TS(8 + 10 * hp + 20 * wg);
        }
        uint32_t otab = 0x0435216u;
        const uint32_t oa = desc_k(sb + (wg ^ kh ^ 1) * 16384);
        const int t7 = tid & 127, w4 = warp & 3, row = ort * 128 + kh * 64 + w4 * 16 + g;
        uint32_t x2[32];
#pragma unroll
        for (int k = 0; k < 32; k++) x2[k] = 0;
#pragma unroll 1
        for (int i = 2; i < 15 - wg; i++) {
            const uint32_t as = o_next(otab), ws = o_next(otab);
            slot_wait(sb + BAR_FULL, fph, as);
            slot_wait(sb + BAR_FULL, fph, ws);
            bar_sync(1 + wg, 256);
            gemm_issue<false>(s, oa + as * (SLOT / 16), wd + ws * (SLOT / 16), 1, true);
            bar_arrive(2 - wg, 256);
            if (i == 12 && wg) {
                const uint32_t* xp = reinterpret_cast<const uint32_t*>(P.x) + row * 256 + cq * 64 + c4;
#pragma unroll
                for (int k = 0; k < 32; k++) x2[k] = __ldg(xp + (k & 1) * 2048 + (k >> 1) * 4);
            }
            wg_wait<0>();
            mbar_arrive_if(sb + BAR_EMPTY + 8 * as, elected);
            mbar_arrive_if(sb + BAR_EMPTY + 8 * ws, elected);
        }
        mbar_wait(sb + BAR_FLAG + 8 * 7, 0);
        const uint32_t ep = lds32(sb + SM_EP);
        if (wg == 0) {
            reg_fence(s);
            if (elected) TS(9);
#pragma unroll
            for (int v = 0; v < 8; v++)
                st_pub(g_part + rb * 1024 + v * 128 + t7, make_uint4((pack2(s[8 * v], s[8 * v + 1]) & ~1u) | (ep & 1), pack2(s[8 * v + 2], s[8 * v + 3]),
                                                                      pack2(s[8 * v + 4], s[8 * v + 5]), pack2(s[8 * v + 6], s[8 * v + 7])), true);
            o_next(otab); o_next(otab); o_next(otab); o_next(otab);
            const uint32_t s1 = o_next(otab), s2 = o_next(otab);
            uint32_t wf[64];
            float wn[56];
            if (rb < NFFN) {
                slot_wait(sb + BAR_FULL, fph, s1);
                const uint32_t a = sb + s1 * SLOT + (w4 * 128 + (lane >> 4) * 8 + (lane & 7)) * 32 + ((lane >> 3) & 1) * 16;
#pragma unroll
                for (int i = 0; i < 16; i++)
                    asm volatile("ldmatrix.sync.aligned.m8n8.x4.trans.shared.b16 {%0, %1, %2, %3}, [%4];"
                                 : "=r"(wf[4 * i]), "=r"(wf[4 * i + 1]), "=r"(wf[4 * i + 2]), "=r"(wf[4 * i + 3])
                                 : "r"(a + (i >> 3) * 16384 + (i & 7) * 512) : "memory");
            }
            slot_wait(sb + BAR_FULL, fph, s2);
#pragma unroll
            for (int i = 0; i < 14; i++) {
                const uint2 w = *reinterpret_cast<const uint2*>(smem + s2 * SLOT + (i >> 1) * 4096 + (2 * t7 + (i & 1)) * 16 + (rb & 1) * 8);
                wn[4 * i] = bf_lo(w.x); wn[4 * i + 1] = bf_hi(w.x); wn[4 * i + 2] = bf_lo(w.y); wn[4 * i + 3] = bf_hi(w.y);
            }
            const uint32_t gbf = __ldcg(reinterpret_cast<const uint32_t*>(g_mod) + 1280 + rb * 2 + (tid & 1));
            reg_fence(wn);
            if (elected) TS(10);
            const uint32_t best = best_key(g_key + cq * 128, lane, ep);
            const int sel = (~best >> 5) & 2047;
            if (elected) TS(19);
            const uint4* cp = g_cand + (sel >> 4) * 192;
            float* sred = reinterpret_cast<float*>(smem + SM_RED);
            const int pq = (2 * rb + (tid & 1)) & 63, pv = (pq >> 2) / 3;
            const uint4* fp = cp + (rb >> 5) * 24 + pv * 4 + (pq & 3);
            uint4 fh = ld_poll(fp), fx = ld_poll(fp + 96);
            if (rb < NFFN) {
                uint4 cv[6];
                for (;;) {
                    uint32_t bad = 0;
#pragma unroll
                    for (int v = 0; v < 6; v++) cv[v] = ld_poll(cp + w4 * 24 + v * 4 + c4);
#pragma unroll
                    for (int v = 0; v < 6; v++) bad |= cv[v].w ^ ep;
                    if (__all_sync(0xffffffffu, bad == 0)) break;
                }
                if (elected) TS(20);
                float d[4][4] = {};
#pragma unroll
                for (int k = 0; k < 8; k++) {
                    const uint32_t b0 = (&cv[(2 * k) / 3].x)[(2 * k) % 3], b1 = (&cv[(2 * k + 1) / 3].x)[(2 * k + 1) % 3];
                    mma16816(d[k & 1], wf + 4 * k, b0, b1);
                    mma16816(d[2 + (k & 1)], wf + 32 + 4 * k, b0, b1);
                }
                const float u = (c4 & 2) ? ((c4 & 1) ? d[2][2] + d[3][2] : d[2][0] + d[3][0]) : ((c4 & 1) ? d[0][2] + d[1][2] : d[0][0] + d[1][0]);
                sred[w4 * 32 + c4 * 8 + g] = u;
                bar_sync(3, 128);
                if (warp == 0) {
                    const float v = rbf((sred[lane] + sred[32 + lane]) + (sred[64 + lane] + sred[96 + lane]));
                    const float up = __shfl_down_sync(0xffffffffu, v, 16);
                    st_pub(g_act + rb * 16 + lane, (pack2(0.f, rbf(v * sigmoid(v)) * up) & 0xffff0000u) | (ep & 0xffffu), lane < 16);
                }
            }
            if (rb == 0 && tid == 0) g_sync.epoch[0] = ep;
            if (elected) TS(60);
            uint2 av[7];
            for (;;) {
                uint32_t bad = 0;
#pragma unroll
                for (int k = 0; k < 7; k++) av[k] = ld_poll(reinterpret_cast<const uint2*>(g_act) + t7 + 128 * k);
#pragma unroll
                for (int k = 0; k < 7; k++) bad |= (av[k].x ^ ep) | (av[k].y ^ ep);
                if (__all_sync(0xffffffffu, (bad & 0xffffu) == 0)) break;
            }
            if (elected) TS(61);
            float y[4] = {0.f, 0.f, 0.f, 0.f};
#pragma unroll
            for (int k = 0; k < 7; k++)
#pragma unroll
                for (int i = 0; i < 4; i++) y[i] = fmaf(bf_hi(av[k].y), wn[8 * k + 4 + i], fmaf(bf_hi(av[k].x), wn[8 * k + i], y[i]));
            const float z0 = ((lane & 16) ? y[2] : y[0]) + __shfl_xor_sync(0xffffffffu, (lane & 16) ? y[0] : y[2], 16);
            const float z1 = ((lane & 16) ? y[3] : y[1]) + __shfl_xor_sync(0xffffffffu, (lane & 16) ? y[1] : y[3], 16);
            float z = ((lane & 8) ? z1 : z0) + __shfl_xor_sync(0xffffffffu, (lane & 8) ? z0 : z1, 8);
            z += __shfl_xor_sync(0xffffffffu, z, 4);
            z = quad_sum(z);
            if ((lane & 7) == 0) sred[128 + (lane >> 3) * 4 + w4] = z;
            bar_sync(3, 128);
            if (tid < 2) {
                while (fh.w != ep || fx.w != ep) { fh = ld_poll(fp); fx = ld_poll(fp + 96); }
                const float4 y0 = *reinterpret_cast<const float4*>(sred + 128 + tid * 8), y1 = *reinterpret_cast<const float4*>(sred + 132 + tid * 8);
                const int cm = (pq >> 2) - 3 * pv;
                const uint32_t h2 = cm == 0 ? fh.x : cm == 1 ? fh.y : fh.z, x2 = cm == 0 ? fx.x : cm == 1 ? fx.y : fx.z;
                const float sg = sigmoid(bf_hi((best & 0x80000000u) ? (best ^ 0x80000000u) : ~best));
                reinterpret_cast<uint32_t*>(P.out)[sel * 256 + rb * 2 + tid] =
                    badd(x2, bmul(gbf, badd(h2, bmul(pack2((y0.x + y0.y) + (y0.z + y0.w), (y1.x + y1.y) + (y1.z + y1.w)), pack2(sg, sg)))));
            }
            if (elected) TS(62);
        } else {
            const float4* tf = reinterpret_cast<const float4*>(smem + SM_TAB) + c4;
            const uint32_t as14 = otab & 15;
            bar_sync(2, 256);
#pragma unroll 1
            for (int i = 14; i < 17; i++) {
                const uint32_t as = o_next(otab), ws = o_next(otab);
                slot_wait(sb + BAR_FULL, fph, as);
                slot_wait(sb + BAR_FULL, fph, ws);
                gemm_issue<false>(s, oa + as * (SLOT / 16), wd + ws * (SLOT / 16), 1, true);
                wg_wait<1>();
                mbar_arrive_if(sb + BAR_EMPTY + 8 * as14, elected && i == 15);
            }
            if (elected) TS(29);
            {
                const uint4* pr = g_part + (rb ^ 8) * 1024 + t7;
                uint4 pa[8];
                for (;;) {
                    uint32_t bad = 0;
#pragma unroll
                    for (int v = 0; v < 8; v++) pa[v] = ld_poll(pr + v * 128);
#pragma unroll
                    for (int v = 0; v < 8; v++) bad |= pa[v].x ^ ep;
                    if (__all_sync(0xffffffffu, (bad & 1) == 0)) break;
                }
#pragma unroll
                for (int i = 0; i < 32; i++) {
                    const uint32_t w = (&pa[i >> 2].x)[i & 3];
                    const float2 ga = *reinterpret_cast<const float2*>(tf + (i >> 1) * 4);
                    o[2 * i] = fmaf(ga.x, bf_lo(w), bf_lo(x2[i]));
                    o[2 * i + 1] = fmaf(ga.y, bf_hi(w), bf_hi(x2[i]));
                }
            }
            reg_fence(o);
            if (elected) TS(30);
            wg_wait<0>();
            reg_fence(s);
            if (elected) TS(39);
            float st[6] = {0.f, 0.f, 0.f, 0.f, 0.f, 0.f};
#pragma unroll
            for (int k = 0; k < 16; k++) {
                const float4 c = tf[k * 4];
#pragma unroll
                for (int i = 4 * k; i < 4 * k + 4; i++) {
                    const int rh = (i >> 1) & 1;
                    const float v = fmaf((i & 1) ? c.y : c.x, s[i], o[i]);
                    s[i] = v;
                    st[rh] += v;
                    st[2 + rh] = fmaf(v, v, st[2 + rh]);
                    st[4 + rh] = fmaf(v, (i & 1) ? c.w : c.z, st[4 + rh]);
                }
            }
#pragma unroll
            for (int i = 0; i < 6; i++) st[i] = quad_sum(st[i]);
            st_pub(g_stat + (row + 8 * (c4 & 1)) * 4 + cq,
                   make_uint4(__float_as_uint((c4 & 1) ? st[1] : st[0]), __float_as_uint((c4 & 1) ? st[3] : st[2]),
                              __float_as_uint((c4 & 1) ? st[5] : st[4]), ep), c4 < 2);
            if (elected) TS(56);
            uint32_t cb[16], sh[16], gb[16];
#pragma unroll
            for (int i = 0; i < 16; i++) {
                const float4 c = tf[64 + i * 4];
                cb[i] = __float_as_uint(c.x); sh[i] = __float_as_uint(c.y); gb[i] = __float_as_uint(c.z);
            }
            const float ra = __uint_as_float(lds32(sb + SM_EP + 8)), rb0 = __uint_as_float(lds32(sb + SM_EP + 12));
#pragma unroll
            for (int i = 0; i < 32; i++) x2[i] = pack2(s[2 * i], s[2 * i + 1]);
            reg_fence(x2);
            uint4 r0, r1;
            for (;;) {
                r0 = ld_poll(g_stat + row * 4 + c4);
                r1 = ld_poll(g_stat + (row + 8) * 4 + c4);
                if (__all_sync(0xffffffffu, r0.w == ep && r1.w == ep)) break;
            }
            if (elected) TS(57);
            const float m0 = quad_sum(__uint_as_float(r0.x)) * (1.f / 512.f), m1 = quad_sum(__uint_as_float(r1.x)) * (1.f / 512.f);
            const float rs0 = ln_rstd(fmaxf(fmaf(-m0, m0, quad_sum(__uint_as_float(r0.y)) * (1.f / 512.f)), 0.f));
            const float rs1 = ln_rstd(fmaxf(fmaf(-m1, m1, quad_sum(__uint_as_float(r1.y)) * (1.f / 512.f)), 0.f));
            const uint32_t mb0 = pack2(m0, m0), mb1 = pack2(m1, m1);
            const uint32_t lg = pack2(fmaf(rs0, fmaf(-bf_lo(mb0), ra, quad_sum(__uint_as_float(r0.z))), rb0),
                                      fmaf(rs1, fmaf(-bf_lo(mb1), ra, quad_sum(__uint_as_float(r1.z))), rb0));
            const uint32_t u0 = lg << 16, u1 = lg & 0xffff0000u;
            const uint32_t k0 = ((u0 ^ (((int)u0 >> 31) | 0x80000000u)) & 0xffff0000u) | ((2047 - row) << 5) | (ep & 31);
            const uint32_t k1 = ((u1 ^ (((int)u1 >> 31) | 0x80000000u)) & 0xffff0000u) | ((2039 - row) << 5) | (ep & 31);
            const uint32_t kb = __reduce_max_sync(0xffffffffu, max(k0, k1));
            st_pub(g_key + cq * 128 + (row >> 4), kb, lane == 0);
            {
                uint32_t cx[18], ch[18];
#pragma unroll
                for (int i = 0; i < 16; i++) {
                    cx[i] = kb == k1 ? x2[2 * i + 1] : x2[2 * i];
                    ch[i] = ln_apply(cx[i], kb == k1 ? mb1 : mb0, kb == k1 ? rs1 : rs0, cb[i], sh[i]);
                }
                cx[16] = cx[17] = ch[16] = ch[17] = 0;
                uint4* cp = g_cand + (row >> 4) * 192 + cq * 24 + c4;
#pragma unroll
                for (int v = 0; v < 6; v++) st_pub(cp + v * 4, make_uint4(ch[3 * v], ch[3 * v + 1], ch[3 * v + 2], ep), kb == k0 || kb == k1);
#pragma unroll
                for (int v = 0; v < 6; v++) st_pub(cp + 96 + v * 4, make_uint4(cx[3 * v], cx[3 * v + 1], cx[3 * v + 2], ep), kb == k0 || kb == k1);
            }
            if (elected) TS(58);
            uint2 ov[16];
#pragma unroll
            for (int i = 0; i < 16; i++) {
                const int rh = i & 1, jj = i & 14;
                const uint32_t v0 = badd(x2[2 * jj + rh], bmul(gb[jj], ln_apply(x2[2 * jj + rh], rh ? mb1 : mb0, rh ? rs1 : rs0, cb[jj], sh[jj])));
                const uint32_t v1 = badd(x2[2 * jj + 2 + rh], bmul(gb[jj + 1], ln_apply(x2[2 * jj + 2 + rh], rh ? mb1 : mb0, rh ? rs1 : rs0, cb[jj + 1], sh[jj + 1])));
                const uint32_t rv = __shfl_xor_sync(0xffffffffu, (c4 & 1) ? v0 : v1, 1);
                ov[i] = (c4 & 1) ? make_uint2(rv, v1) : make_uint2(v0, rv);
            }
            uint2* op = reinterpret_cast<uint2*>(P.out) + row * 128 + cq * 32 + (c4 & 1) * 2 + (c4 >> 1);
#pragma unroll
            for (int i = 0; i < 16; i++)
                if (kb != ((i & 1) ? k1 : k0)) op[(i & 1) * 1024 + (i & 14) * 2] = ov[i];
            const uint32_t best = best_key(g_key + cq * 128, lane, ep);
            if (best != kb) {
#pragma unroll
                for (int i = 0; i < 16; i++)
                    if (kb == ((i & 1) ? k1 : k0)) op[(i & 1) * 1024 + (i & 14) * 2] = ov[i];
            }
            if (elected) TS(59);
        }
        mbar_arrive_if(sb + BAR_END, lane == 0);
    }
}

typedef CUresult (*EncodeFn)(CUtensorMap*, CUtensorMapDataType, cuuint32_t, void*, const cuuint64_t*, const cuuint64_t*,
                             const cuuint32_t*, const cuuint32_t*, CUtensorMapInterleave, CUtensorMapSwizzle,
                             CUtensorMapL2promotion, CUtensorMapFloatOOBfill);

void make_2d(EncodeFn fn, CUtensorMap* m, const void* p, uint64_t cols, uint64_t rows, uint32_t bc, uint32_t br) {
    cuuint64_t dims[2] = {cols, rows}, strides[1] = {cols * 2};
    cuuint32_t box[2] = {bc, br}, es[2] = {1, 1};
    fn(m, CU_TENSOR_MAP_DATA_TYPE_BFLOAT16, 2, const_cast<void*>(p), dims, strides, box, es, CU_TENSOR_MAP_INTERLEAVE_NONE,
       CU_TENSOR_MAP_SWIZZLE_NONE, CU_TENSOR_MAP_L2_PROMOTION_L2_128B, CU_TENSOR_MAP_FLOAT_OOB_FILL_NONE);
}
void make_3d(EncodeFn fn, CUtensorMap* m, const void* p, uint64_t cols, uint64_t rows) {
    cuuint64_t dims[3] = {64, rows, cols / 64}, strides[2] = {cols * 2, 128};
    cuuint32_t box[3] = {64, 128, 2}, es[3] = {1, 1, 1};
    fn(m, CU_TENSOR_MAP_DATA_TYPE_BFLOAT16, 3, const_cast<void*>(p), dims, strides, box, es, CU_TENSOR_MAP_INTERLEAVE_NONE,
       CU_TENSOR_MAP_SWIZZLE_128B, CU_TENSOR_MAP_L2_PROMOTION_L2_256B, CU_TENSOR_MAP_FLOAT_OOB_FILL_NONE);
}

}

extern "C" void kernel_launch(void* const* d_in, const int* in_sizes, int n_in, void* d_out, int out_size) {
    static EncodeFn fn = nullptr;
    static int sms = 0;
    if (!fn) {
        void* f = nullptr;
        cudaDriverEntryPointQueryResult st;
        cudaGetDriverEntryPoint("cuTensorMapEncodeTiled", &f, cudaEnableDefault, &st);
        fn = (EncodeFn)f;
        int dev = 0;
        cudaGetDevice(&dev);
        cudaDeviceGetAttribute(&sms, cudaDevAttrMultiProcessorCount, dev);
        cudaFuncSetAttribute(fused_kernel, cudaFuncAttributeMaxDynamicSharedMemorySize, SMEM_BYTES);
    }
    CUtensorMap ckv, wq, wuk, wuv, wo, wg, wu, wd, wm;
    make_3d(fn, &ckv, d_in[1], 512, 2048);
    make_3d(fn, &wq, d_in[2], 4096, 512);
    make_3d(fn, &wuk, d_in[3], 4096, 512);
    make_3d(fn, &wuv, d_in[4], 4096, 512);
    make_3d(fn, &wo, d_in[5], 512, 4096);
    make_2d(fn, &wg, d_in[8], 1792, 512, 16, 256);
    make_2d(fn, &wu, d_in[9], 1792, 512, 16, 256);
    make_2d(fn, &wd, d_in[10], 512, 1792, 8, 256);
    make_2d(fn, &wm, d_in[12], 3072, 512, 256, 64);
    Params p;
    p.x = (const bf16*)d_in[0];
    p.ckv = (const bf16*)d_in[1];
    p.wo = (const bf16*)d_in[5];
    p.wr = (const bf16*)d_in[7];
    p.wgate = (const bf16*)d_in[8];
    p.wup = (const bf16*)d_in[9];
    p.wdown = (const bf16*)d_in[10];
    p.c = (const bf16*)d_in[11];
    p.out = (bf16*)d_out;
    p.by_smid = sms == NCTA + NSPARE;
    fused_kernel<<<NCTA + NSPARE, 384, SMEM_BYTES>>>(ckv, wq, wuk, wuv, wo, wg, wu, wd, wm, p);
}
```

```cpp
#include <cuda.h>
#include <cuda_bf16.h>
#include <cuda_runtime.h>
#include <stdint.h>
#include <stdio.h>

namespace {

typedef __nv_bfloat16 bf16;
typedef unsigned long long u64;

constexpr int NCTA = 128, NSPARE = 4;
constexpr int SLOT = 32768;
constexpr int SM_BAR = 7 * SLOT;
constexpr int BAR_FULL = SM_BAR;
constexpr int BAR_EMPTY = BAR_FULL + 8 * 7;
constexpr int BAR_DONE = BAR_EMPTY + 8 * 7;
constexpr int BAR_FLAG = BAR_DONE + 8 * 9;
constexpr int BAR_PF = BAR_FLAG + 8 * 11;
constexpr int BAR_END = BAR_PF + 8;
constexpr int SM_EP = BAR_END + 8;
constexpr int SM_RED = SM_BAR + 384;
constexpr int SM_TAB = SM_BAR + 1024;
constexpr int SMEM_BYTES = SM_BAR + 3072;
constexpr int NFFN = 112;
#define HINT 29
constexpr u64 L2_NORMAL = 0x1000000000000000ull, L2_FIRST = 0x12F0000000000000ull;
#define PF0 0
#define PF1 13
#define PF2 11
#define UNR 4
#define PARKS 7
#define EARLY 7
constexpr uint32_t SPIN_LIMIT = 1u << 22;
constexpr uint32_t ONE2 = 0x3f803f80u;

struct Sync {
    uint32_t modcnt[2 * 32];
    uint32_t hcnt[16 * 8];
    uint32_t kvcnt[32 * 2 * 8];
    uint32_t ctxcnt[16 * 32];
    uint32_t rdcnt[16 * 2 * 8];
    uint32_t epoch[32];
};

__device__ __align__(1024) uint8_t g_KV[16 * 16 * 2 * SLOT];
__device__ __align__(1024) uint8_t g_ctx[16 * 32 * SLOT];
__device__ __align__(1024) uint8_t g_h[16 * 4 * SLOT];
__device__ __align__(1024) uint4 g_part[128 * 1024];
__device__ __align__(1024) uint4 g_stat[2048 * 4];
__device__ __align__(1024) bf16 g_mod[3072];
__device__ __align__(1024) uint4 g_cand[128 * 192];
__device__ __align__(1024) uint32_t g_key[4 * 128];
__device__ __align__(1024) uint32_t g_act[1792];
__device__ __align__(1024) Sync g_sync;
#define TS(i)

#define PT()

struct Params {
    const bf16 *x, *ckv, *wo, *wr, *wgate, *wup, *wdown, *c;
    bf16* out;
    int by_smid;
};

__device__ __forceinline__ void mbar_init(uint32_t bar, uint32_t cnt) {
    asm volatile("mbarrier.init.shared::cta.b64 [%0], %1;" ::"r"(bar), "r"(cnt) : "memory");
}
__device__ __forceinline__ void mbar_wait(uint32_t bar, uint32_t parity) {
    asm volatile("{\n.reg .pred p;\nL_%=:\nmbarrier.try_wait.parity.shared::cta.b64 p, [%0], %1;\n@!p bra L_%=;\n}" ::"r"(bar), "r"(parity) : "memory");
}
__device__ __forceinline__ void mbar_watch(uint32_t bar, uint32_t parity) {
    asm volatile("{\n.reg .pred p;\n.reg .u32 n;\nmov.u32 n, 0;\n"
                 "L_%=:\nmbarrier.try_wait.parity.shared::cta.b64 p, [%0], %1;\n@p bra D_%=;\n"
                 "add.u32 n, n, 1;\nsetp.lt.u32 p, n, %2;\n@p bra L_%=;\ntrap;\nD_%=:\n}"
                 ::"r"(bar), "r"(parity), "n"(SPIN_LIMIT) : "memory");
}
__device__ __forceinline__ void mbar_arrive(uint32_t bar) {
    asm volatile("mbarrier.arrive.shared::cta.b64 _, [%0];" ::"r"(bar) : "memory");
}
__device__ __forceinline__ void mbar_arrive_if(uint32_t bar, bool on) {
    asm volatile("{\n.reg .pred p;\nsetp.ne.s32 p, %1, 0;\n@p mbarrier.arrive.shared::cta.b64 _, [%0];\n}" ::"r"(bar), "r"((int)on) : "memory");
}
__device__ __forceinline__ void mbar_expect(uint32_t bar, uint32_t bytes) {
    asm volatile("mbarrier.arrive.expect_tx.shared::cta.b64 _, [%0], %1;" ::"r"(bar), "r"(bytes) : "memory");
}
__device__ __forceinline__ void tma2d(uint32_t dst, const CUtensorMap* m, int c0, int c1, uint32_t bar) {
    asm volatile("cp.async.bulk.tensor.2d.shared::cluster.global.mbarrier::complete_tx::bytes [%0], [%1, {%3, %4}], [%2];"
                 ::"r"(dst), "l"(m), "r"(bar), "r"(c0), "r"(c1) : "memory");
}
__device__ __forceinline__ void tma3d_prefetch(const CUtensorMap* m, int row, int cb) {
    asm volatile("cp.async.bulk.prefetch.tensor.3d.L2.global [%0, {%1, %2, %3}];" ::"l"(m), "r"(0), "r"(row), "r"(cb) : "memory");
}
__device__ __forceinline__ void l2_prefetch(const void* p, uint32_t bytes) {
    asm volatile("cp.async.bulk.prefetch.L2.global [%0], %1;" ::"l"(p), "r"(bytes) : "memory");
}
__device__ __forceinline__ void flag_wait(const uint32_t* f, uint32_t target) {
    asm volatile("{\n.reg .pred p;\n.reg .u32 v;\n"
                 "L_%=:\nld.acquire.gpu.global.u32 v, [%0];\nsub.u32 v, v, %1;\nsetp.lt.s32 p, v, 0;\n@p nanosleep.u32 100;\n@p bra L_%=;\n}"
                 ::"l"(f), "r"(target) : "memory");
}
__device__ __forceinline__ uint4 ld_poll(const uint4* p) {
    uint4 v;
    asm volatile("ld.relaxed.gpu.global.v4.u32 {%0, %1, %2, %3}, [%4];" : "=r"(v.x), "=r"(v.y), "=r"(v.z), "=r"(v.w) : "l"(p) : "memory");
    return v;
}
__device__ __forceinline__ uint2 ld_poll(const uint2* p) {
    uint2 v;
    asm volatile("ld.relaxed.gpu.global.v2.u32 {%0, %1}, [%2];" : "=r"(v.x), "=r"(v.y) : "l"(p) : "memory");
    return v;
}
__device__ __forceinline__ void st_pub(uint4* p, uint4 v, bool on) {
    asm volatile("{\n.reg .pred p;\nsetp.ne.s32 p, %5, 0;\n@p st.relaxed.gpu.global.v4.u32 [%0], {%1, %2, %3, %4};\n}"
                 ::"l"(p), "r"(v.x), "r"(v.y), "r"(v.z), "r"(v.w), "r"((int)on) : "memory");
}
__device__ __forceinline__ void st_pub(uint32_t* p, uint32_t v, bool on) {
    asm volatile("{\n.reg .pred p;\nsetp.ne.s32 p, %2, 0;\n@p st.relaxed.gpu.global.u32 [%0], %1;\n}" ::"l"(p), "r"(v), "r"((int)on) : "memory");
}
__device__ __forceinline__ void flag_add(uint32_t* p) {
    asm volatile("red.release.gpu.global.add.u32 [%0], 1;" ::"l"(p) : "memory");
}
__device__ __forceinline__ uint32_t lds32(uint32_t a) {
    uint32_t v;
    asm volatile("ld.shared.u32 %0, [%1];" : "=r"(v) : "r"(a) : "memory");
    return v;
}
__device__ __forceinline__ uint4 lds128(uint32_t a) {
    uint4 v;
    asm volatile("ld.shared.v4.u32 {%0, %1, %2, %3}, [%4];" : "=r"(v.x), "=r"(v.y), "=r"(v.z), "=r"(v.w) : "r"(a) : "memory");
    return v;
}
__device__ __forceinline__ void fence_async_global() { asm volatile("fence.proxy.async.global;" ::: "memory"); }
__device__ __forceinline__ void fence_async_smem() { asm volatile("fence.proxy.async.shared::cta;" ::: "memory"); }
__device__ __forceinline__ void bar_sync(int id, int n) { asm volatile("bar.sync %0, %1;" ::"r"(id), "r"(n) : "memory"); }
__device__ __forceinline__ void bar_arrive(int id, int n) { asm volatile("bar.arrive %0, %1;" ::"r"(id), "r"(n) : "memory"); }
__device__ __forceinline__ void wg_fence() { asm volatile("wgmma.fence.sync.aligned;" ::: "memory"); }
__device__ __forceinline__ void wg_commit() { asm volatile("wgmma.commit_group.sync.aligned;" ::: "memory"); }
template <int N> __device__ __forceinline__ void wg_wait() { asm volatile("wgmma.wait_group.sync.aligned %0;" ::"n"(N) : "memory"); }
template <int N> __device__ __forceinline__ void reg_fence(float (&d)[N]) {
#pragma unroll
    for (int i = 0; i < N; i++) asm volatile("" : "+f"(d[i])::"memory");
}
template <int N> __device__ __forceinline__ void reg_fence(uint32_t (&d)[N]) {
#pragma unroll
    for (int i = 0; i < N; i++) asm volatile("" : "+r"(d[i])::"memory");
}
__device__ __forceinline__ uint32_t desc_k(uint32_t a) { return (a >> 4) | (1u << 16); }
__device__ __forceinline__ uint32_t desc_mn(uint32_t a) { return (a >> 4) | (1024u << 16); }

template <int TB>
__device__ __forceinline__ void wgmma_ss128(float (&d)[64], uint32_t da, uint32_t db, int acc, uint32_t ha = 0x40000040u, uint32_t hb = 0x40000040u) {
    asm volatile("{\n.reg .pred p;\n.reg .b64 a, b;\nsetp.ne.b32 p, %66, 0;\nmov.b64 a, {%64, %68};\nmov.b64 b, {%65, %69};\n"
        "wgmma.mma_async.sync.aligned.m64n128k16.f32.bf16.bf16 {%0, %1, %2, %3, %4, %5, %6, %7, %8, %9, %10, %11, %12, %13, %14, %15, %16, %17, %18, %19, %20, %21, %22, %23, %24, %25, %26, %27, %28, %29, %30, %31, %32, %33, %34, %35, %36, %37, %38, %39, %40, %41, %42, %43, %44, %45, %46, %47, %48, %49, %50, %51, %52, %53, %54, %55, %56, %57, %58, %59, %60, %61, %62, %63}, a, b, p, 1, 1, 0, %67;\n}"
        : "+f"(d[0]), "+f"(d[1]), "+f"(d[2]), "+f"(d[3]), "+f"(d[4]), "+f"(d[5]), "+f"(d[6]), "+f"(d[7]), "+f"(d[8]), "+f"(d[9]), "+f"(d[10]), "+f"(d[11]), "+f"(d[12]), "+f"(d[13]), "+f"(d[14]), "+f"(d[15]), "+f"(d[16]), "+f"(d[17]), "+f"(d[18]), "+f"(d[19]), "+f"(d[20]), "+f"(d[21]), "+f"(d[22]), "+f"(d[23]), "+f"(d[24]), "+f"(d[25]), "+f"(d[26]), "+f"(d[27]), "+f"(d[28]), "+f"(d[29]), "+f"(d[30]), "+f"(d[31]), "+f"(d[32]), "+f"(d[33]), "+f"(d[34]), "+f"(d[35]), "+f"(d[36]), "+f"(d[37]), "+f"(d[38]), "+f"(d[39]), "+f"(d[40]), "+f"(d[41]), "+f"(d[42]), "+f"(d[43]), "+f"(d[44]), "+f"(d[45]), "+f"(d[46]), "+f"(d[47]), "+f"(d[48]), "+f"(d[49]), "+f"(d[50]), "+f"(d[51]), "+f"(d[52]), "+f"(d[53]), "+f"(d[54]), "+f"(d[55]), "+f"(d[56]), "+f"(d[57]), "+f"(d[58]), "+f"(d[59]), "+f"(d[60]), "+f"(d[61]), "+f"(d[62]), "+f"(d[63])
        : "r"(da), "r"(db), "r"(acc), "n"(TB), "r"(ha), "r"(hb));
}
template <int TB>
__device__ __forceinline__ void wgmma_ss128_init(float (&d)[64], uint32_t da, uint32_t db, uint32_t ha = 0x40000040u, uint32_t hb = 0x40000040u) {
    asm volatile("{\n.reg .pred p;\n.reg .b64 a, b;\nsetp.ne.b32 p, 0, 0;\nmov.b64 a, {%64, %67};\nmov.b64 b, {%65, %68};\n"
        "wgmma.mma_async.sync.aligned.m64n128k16.f32.bf16.bf16 {%0, %1, %2, %3, %4, %5, %6, %7, %8, %9, %10, %11, %12, %13, %14, %15, %16, %17, %18, %19, %20, %21, %22, %23, %24, %25, %26, %27, %28, %29, %30, %31, %32, %33, %34, %35, %36, %37, %38, %39, %40, %41, %42, %43, %44, %45, %46, %47, %48, %49, %50, %51, %52, %53, %54, %55, %56, %57, %58, %59, %60, %61, %62, %63}, a, b, p, 1, 1, 0, %66;\n}"
        : "=f"(d[0]), "=f"(d[1]), "=f"(d[2]), "=f"(d[3]), "=f"(d[4]), "=f"(d[5]), "=f"(d[6]), "=f"(d[7]), "=f"(d[8]), "=f"(d[9]), "=f"(d[10]), "=f"(d[11]), "=f"(d[12]), "=f"(d[13]), "=f"(d[14]), "=f"(d[15]), "=f"(d[16]), "=f"(d[17]), "=f"(d[18]), "=f"(d[19]), "=f"(d[20]), "=f"(d[21]), "=f"(d[22]), "=f"(d[23]), "=f"(d[24]), "=f"(d[25]), "=f"(d[26]), "=f"(d[27]), "=f"(d[28]), "=f"(d[29]), "=f"(d[30]), "=f"(d[31]), "=f"(d[32]), "=f"(d[33]), "=f"(d[34]), "=f"(d[35]), "=f"(d[36]), "=f"(d[37]), "=f"(d[38]), "=f"(d[39]), "=f"(d[40]), "=f"(d[41]), "=f"(d[42]), "=f"(d[43]), "=f"(d[44]), "=f"(d[45]), "=f"(d[46]), "=f"(d[47]), "=f"(d[48]), "=f"(d[49]), "=f"(d[50]), "=f"(d[51]), "=f"(d[52]), "=f"(d[53]), "=f"(d[54]), "=f"(d[55]), "=f"(d[56]), "=f"(d[57]), "=f"(d[58]), "=f"(d[59]), "=f"(d[60]), "=f"(d[61]), "=f"(d[62]), "=f"(d[63])
        : "r"(da), "r"(db), "n"(TB), "r"(ha), "r"(hb));
}
template <int TB>
__device__ __forceinline__ void wgmma_ss64(float (&d)[32], uint32_t da, uint32_t db, int acc, uint32_t ha = 0x40000040u, uint32_t hb = 0x40000040u) {
    asm volatile("{\n.reg .pred p;\n.reg .b64 a, b;\nsetp.ne.b32 p, %34, 0;\nmov.b64 a, {%32, %36};\nmov.b64 b, {%33, %37};\n"
        "wgmma.mma_async.sync.aligned.m64n64k16.f32.bf16.bf16 {%0, %1, %2, %3, %4, %5, %6, %7, %8, %9, %10, %11, %12, %13, %14, %15, %16, %17, %18, %19, %20, %21, %22, %23, %24, %25, %26, %27, %28, %29, %30, %31}, a, b, p, 1, 1, 0, %35;\n}"
        : "+f"(d[0]), "+f"(d[1]), "+f"(d[2]), "+f"(d[3]), "+f"(d[4]), "+f"(d[5]), "+f"(d[6]), "+f"(d[7]), "+f"(d[8]), "+f"(d[9]), "+f"(d[10]), "+f"(d[11]), "+f"(d[12]), "+f"(d[13]), "+f"(d[14]), "+f"(d[15]), "+f"(d[16]), "+f"(d[17]), "+f"(d[18]), "+f"(d[19]), "+f"(d[20]), "+f"(d[21]), "+f"(d[22]), "+f"(d[23]), "+f"(d[24]), "+f"(d[25]), "+f"(d[26]), "+f"(d[27]), "+f"(d[28]), "+f"(d[29]), "+f"(d[30]), "+f"(d[31])
        : "r"(da), "r"(db), "r"(acc), "n"(TB), "r"(ha), "r"(hb));
}
template <int TB>
__device__ __forceinline__ void wgmma_ss64_init(float (&d)[32], uint32_t da, uint32_t db, uint32_t ha = 0x40000040u, uint32_t hb = 0x40000040u) {
    asm volatile("{\n.reg .pred p;\n.reg .b64 a, b;\nsetp.ne.b32 p, 0, 0;\nmov.b64 a, {%32, %35};\nmov.b64 b, {%33, %36};\n"
        "wgmma.mma_async.sync.aligned.m64n64k16.f32.bf16.bf16 {%0, %1, %2, %3, %4, %5, %6, %7, %8, %9, %10, %11, %12, %13, %14, %15, %16, %17, %18, %19, %20, %21, %22, %23, %24, %25, %26, %27, %28, %29, %30, %31}, a, b, p, 1, 1, 0, %34;\n}"
        : "=f"(d[0]), "=f"(d[1]), "=f"(d[2]), "=f"(d[3]), "=f"(d[4]), "=f"(d[5]), "=f"(d[6]), "=f"(d[7]), "=f"(d[8]), "=f"(d[9]), "=f"(d[10]), "=f"(d[11]), "=f"(d[12]), "=f"(d[13]), "=f"(d[14]), "=f"(d[15]), "=f"(d[16]), "=f"(d[17]), "=f"(d[18]), "=f"(d[19]), "=f"(d[20]), "=f"(d[21]), "=f"(d[22]), "=f"(d[23]), "=f"(d[24]), "=f"(d[25]), "=f"(d[26]), "=f"(d[27]), "=f"(d[28]), "=f"(d[29]), "=f"(d[30]), "=f"(d[31])
        : "r"(da), "r"(db), "n"(TB), "r"(ha), "r"(hb));
}
__device__ __forceinline__ void wgmma_rs128(float (&d)[64], uint32_t a0, uint32_t a1, uint32_t a2, uint32_t a3, uint32_t db, int acc, uint32_t hb = 0x40000040u) {
    asm volatile("{\n.reg .pred p;\n.reg .b64 b;\nsetp.ne.b32 p, %69, 0;\nmov.b64 b, {%68, %70};\n"
        "wgmma.mma_async.sync.aligned.m64n128k16.f32.bf16.bf16 {%0, %1, %2, %3, %4, %5, %6, %7, %8, %9, %10, %11, %12, %13, %14, %15, %16, %17, %18, %19, %20, %21, %22, %23, %24, %25, %26, %27, %28, %29, %30, %31, %32, %33, %34, %35, %36, %37, %38, %39, %40, %41, %42, %43, %44, %45, %46, %47, %48, %49, %50, %51, %52, %53, %54, %55, %56, %57, %58, %59, %60, %61, %62, %63}, {%64, %65, %66, %67}, b, p, 1, 1, 1;\n}"
        : "+f"(d[0]), "+f"(d[1]), "+f"(d[2]), "+f"(d[3]), "+f"(d[4]), "+f"(d[5]), "+f"(d[6]), "+f"(d[7]), "+f"(d[8]), "+f"(d[9]), "+f"(d[10]), "+f"(d[11]), "+f"(d[12]), "+f"(d[13]), "+f"(d[14]), "+f"(d[15]), "+f"(d[16]), "+f"(d[17]), "+f"(d[18]), "+f"(d[19]), "+f"(d[20]), "+f"(d[21]), "+f"(d[22]), "+f"(d[23]), "+f"(d[24]), "+f"(d[25]), "+f"(d[26]), "+f"(d[27]), "+f"(d[28]), "+f"(d[29]), "+f"(d[30]), "+f"(d[31]), "+f"(d[32]), "+f"(d[33]), "+f"(d[34]), "+f"(d[35]), "+f"(d[36]), "+f"(d[37]), "+f"(d[38]), "+f"(d[39]), "+f"(d[40]), "+f"(d[41]), "+f"(d[42]), "+f"(d[43]), "+f"(d[44]), "+f"(d[45]), "+f"(d[46]), "+f"(d[47]), "+f"(d[48]), "+f"(d[49]), "+f"(d[50]), "+f"(d[51]), "+f"(d[52]), "+f"(d[53]), "+f"(d[54]), "+f"(d[55]), "+f"(d[56]), "+f"(d[57]), "+f"(d[58]), "+f"(d[59]), "+f"(d[60]), "+f"(d[61]), "+f"(d[62]), "+f"(d[63])
        : "r"(a0), "r"(a1), "r"(a2), "r"(a3), "r"(db), "r"(acc), "r"(hb));
}

__device__ __forceinline__ uint32_t pack2(float lo, float hi) {
    uint32_t r;
    asm("cvt.rn.bf16x2.f32 %0, %1, %2;" : "=r"(r) : "f"(hi), "f"(lo));
    return r;
}
__device__ __forceinline__ float bf_lo(uint32_t v) { return __uint_as_float(v << 16); }
__device__ __forceinline__ float bf_hi(uint32_t v) { return __uint_as_float(v & 0xffff0000u); }
__device__ __forceinline__ float rbf(float v) { return bf_lo(pack2(v, v)); }
__device__ __forceinline__ uint32_t badd(uint32_t a, uint32_t b) {
    uint32_t r;
    asm("add.rn.bf16x2 %0, %1, %2;" : "=r"(r) : "r"(a), "r"(b));
    return r;
}
__device__ __forceinline__ uint32_t bsub(uint32_t a, uint32_t b) {
    uint32_t r;
    asm("sub.rn.bf16x2 %0, %1, %2;" : "=r"(r) : "r"(a), "r"(b));
    return r;
}
__device__ __forceinline__ uint32_t bmul(uint32_t a, uint32_t b) {
    uint32_t r;
    asm("mul.rn.bf16x2 %0, %1, %2;" : "=r"(r) : "r"(a), "r"(b));
    return r;
}
__device__ __forceinline__ uint32_t ln_apply(uint32_t x, uint32_t mb, float rs, uint32_t scale, uint32_t shift) {
    const uint32_t d = bsub(x, mb);
    return badd(bmul(pack2(bf_lo(d) * rs, bf_hi(d) * rs), scale), shift);
}
__device__ __forceinline__ float ex2(float v) {
    float r;
    asm("ex2.approx.ftz.f32 %0, %1;" : "=f"(r) : "f"(v));
    return r;
}
__device__ __forceinline__ float rcp(float v) {
    float r;
    asm("rcp.approx.ftz.f32 %0, %1;" : "=f"(r) : "f"(v));
    return r;
}
__device__ __forceinline__ float sqrt_fast(float v) {
    float r;
    asm("sqrt.approx.ftz.f32 %0, %1;" : "=f"(r) : "f"(v));
    return r;
}
__device__ __forceinline__ float ln_rstd(float var) { return rcp(rbf(sqrt_fast(rbf(rbf(var) + 1e-5f)))); }
__device__ __forceinline__ float sigmoid(float v) { return rcp(1.f + ex2(-1.4426950408889634f * v)); }
__device__ __forceinline__ float warp_sum(float v) {
#pragma unroll
    for (int o = 16; o > 0; o >>= 1) v += __shfl_xor_sync(0xffffffffu, v, o);
    return v;
}
__device__ __forceinline__ float quad_sum(float v) {
    v += __shfl_xor_sync(0xffffffffu, v, 1);
    return v + __shfl_xor_sync(0xffffffffu, v, 2);
}

constexpr uint32_t HI_128 = 0x40000040u, HI_IMG = 0x80000080u, HI_Q = 0x80000040u;
template <int M, int RH>
__device__ __forceinline__ uint4 img_pack(const float (&d)[64], float s) {
    uint4 v;
    v.x = pack2(d[16 * M + 2 * RH] * s, d[16 * M + 2 * RH + 1] * s);
    v.y = pack2(d[16 * M + 4 + 2 * RH] * s, d[16 * M + 5 + 2 * RH] * s);
    v.z = pack2(d[16 * M + 8 + 2 * RH] * s, d[16 * M + 9 + 2 * RH] * s);
    v.w = pack2(d[16 * M + 12 + 2 * RH] * s, d[16 * M + 13 + 2 * RH] * s);
    return v;
}
template <int M, int RH>
__device__ __forceinline__ uint4 img_pack(const float (&d)[64]) {
    uint4 v;
    v.x = pack2(d[16 * M + 2 * RH], d[16 * M + 2 * RH + 1]);
    v.y = pack2(d[16 * M + 4 + 2 * RH], d[16 * M + 5 + 2 * RH]);
    v.z = pack2(d[16 * M + 8 + 2 * RH], d[16 * M + 9 + 2 * RH]);
    v.w = pack2(d[16 * M + 12 + 2 * RH], d[16 * M + 13 + 2 * RH]);
    return v;
}
template <int M>
__device__ __forceinline__ void img_store_global(uint8_t* img, uint32_t toff, const float (&d)[64], float s0, float s1) {
    uint4* p = reinterpret_cast<uint4*>(img + toff) + M * 32;
    p[0] = img_pack<M, 0>(d, s0);
    p[128] = img_pack<M, 1>(d, s1);
}
__device__ __forceinline__ void sts128(uint32_t a, uint4 v) {
    asm volatile("st.shared.v4.b32 [%0], {%1, %2, %3, %4};" ::"r"(a), "r"(v.x), "r"(v.y), "r"(v.z), "r"(v.w) : "memory");
}
constexpr float SM_C = 0.08838834764831845f * 1.4426950408889634f;
__device__ __forceinline__ float pack2f(float lo, float hi) {
    float r;
    asm("{\n.reg .b32 t;\ncvt.rn.bf16x2.f32 t, %1, %2;\nmov.b32 %0, t;\n}" : "=f"(r) : "f"(hi), "f"(lo));
    return r;
}
template <int M, bool SCALE, bool PARK>
__device__ __forceinline__ void pack_group(float (&d)[64], float (&v)[8], float s0, float s1) {
#pragma unroll
    for (int i = 0; i < 8; i++) {
        const int k = 16 * M + 4 * (i & 3) + 2 * (i >> 2);
        v[i] = SCALE ? pack2f(d[k] * (i < 4 ? s0 : s1), d[k + 1] * (i < 4 ? s0 : s1)) : pack2f(d[k], d[k + 1]);
        if (PARK && M > 0) d[16 * (M > 0 ? M - 1 : 0) + i] = v[i];
    }
}
template <int M, bool PARK>
__device__ __forceinline__ void q_store_part(uint32_t a, float (&d)[64]) {
    float v[8];
    pack_group<M, false, PARK>(d, v, 0.f, 0.f);
#pragma unroll
    for (int h = 0; h < 2; h++)
        asm volatile("st.shared.v4.f32 [%0], {%1, %2, %3, %4};" ::"r"(a + (M >> 1) * 16384 + (M & 1) * 512 + h * 1024),
                     "f"(v[4 * h]), "f"(v[4 * h + 1]), "f"(v[4 * h + 2]), "f"(v[4 * h + 3]) : "memory");
}
template <bool PARK>
__device__ __forceinline__ void q_store(uint32_t a, uint32_t toff, float (&d)[64]) {
    a += (((toff >> 1) & ~2047u) ^ 8192) + (toff & 511);
    q_store_part<0, PARK>(a, d); q_store_part<1, PARK>(a, d); q_store_part<2, PARK>(a, d); q_store_part<3, PARK>(a, d);
}
template <int M, bool PARK>
__device__ __forceinline__ void ctx_store_part(float4* p, float (&d)[64], float i0, float i1) {
    float v[8];
    pack_group<M, true, PARK>(d, v, i0, i1);
    p[M * 32] = make_float4(v[0], v[1], v[2], v[3]);
    p[M * 32 + 128] = make_float4(v[4], v[5], v[6], v[7]);
}
template <bool PARK>
__device__ __forceinline__ void ctx_store(uint8_t* img, uint32_t toff, float (&o)[64], float l0, float l1) {
    const float i0 = rcp(quad_sum(l0)), i1 = rcp(quad_sum(l1));
    float4* p = reinterpret_cast<float4*>(img + toff);
    ctx_store_part<0, PARK>(p, o, i0, i1); ctx_store_part<1, PARK>(p, o, i0, i1); ctx_store_part<2, PARK>(p, o, i0, i1); ctx_store_part<3, PARK>(p, o, i0, i1);
}

__device__ __forceinline__ void slot_wait(uint32_t bars, uint32_t& ph, uint32_t slot) {
    mbar_wait(bars + 8 * slot, (ph >> slot) & 1);
    ph ^= 1u << slot;
}
__device__ __forceinline__ void load_image(uint32_t sb, uint32_t& ph, uint32_t slot, const void* src, bool first) {
    slot_wait(sb + BAR_EMPTY, ph, slot);
    asm volatile("{\n.reg .pred p;\nelect.sync _|p, 0xffffffff;\n@p mbarrier.arrive.expect_tx.shared::cta.b64 _, [%2], 32768;\n"
                 "@p cp.async.bulk.shared::cluster.global.mbarrier::complete_tx::bytes.L2::cache_hint [%0], [%1], 32768, [%2], %3;\n}"
                 ::"r"(sb + slot * SLOT), "l"(src), "r"(sb + BAR_FULL + 8 * slot), "l"(first ? L2_FIRST : L2_NORMAL) : "memory");
}
__device__ __forceinline__ void load_tile(uint32_t sb, uint32_t& ph, uint32_t slot, const CUtensorMap* m, int row, int cb, bool first) {
    slot_wait(sb + BAR_EMPTY, ph, slot);
    asm volatile("{\n.reg .pred p;\nelect.sync _|p, 0xffffffff;\n@p mbarrier.arrive.expect_tx.shared::cta.b64 _, [%2], 32768;\n"
                 "@p cp.async.bulk.tensor.3d.shared::cluster.global.mbarrier::complete_tx::bytes.L2::cache_hint [%0], [%1, {%3, %4, %5}], [%2], %6;\n}"
                 ::"r"(sb + slot * SLOT), "l"(m), "r"(sb + BAR_FULL + 8 * slot), "r"(0), "r"(row), "r"(cb), "l"(first ? L2_FIRST : L2_NORMAL) : "memory");
}
__device__ __forceinline__ uint32_t ring_next(uint32_t r) { return r == 4 ? 0 : r + 1; }
__device__ __forceinline__ uint32_t w_table(int hp) { return hp ? 0x3104u : 0x4210u; }
__device__ __forceinline__ uint32_t a_table(int hp) { return hp ? 0x625u : 0x635u; }
__device__ __forceinline__ uint32_t a_next(uint32_t& t) {
    const uint32_t s = t & 15;
    t = (t >> 4) | (s << 8);
    return s;
}
constexpr uint32_t O_TABLE = 0x2160435u;
__device__ __forceinline__ uint32_t o_next(uint32_t& t) {
    const uint32_t s = t & 15;
    t = (t >> 4) | (s << 24);
    return s;
}
__device__ __forceinline__ int o_head(int i, int kh) { return i < 16 ? 4 * (i & 7) + 2 * (kh ^ 1) + (i >> 3) : 29 + 2 * kh; }

template <bool INIT>
__device__ __forceinline__ void gemm_issue(float (&d)[64], uint32_t a, uint32_t b, int acc, bool img) {
    const uint32_t ha = img ? HI_IMG : HI_128, o2 = img ? 32 : 4, o4 = img ? 64 : 1024;
    wg_fence();
#pragma unroll
    for (int k = 0; k < 8; k++) {
        if (INIT && k == 0) wgmma_ss128_init<1>(d, a, b, ha);
        else wgmma_ss128<1>(d, a + (k >> 2) * o4 + ((k >> 1) & 1) * o2 + (k & 1) * 2, b + k * 128, k ? 1 : acc, ha);
    }
    wg_commit();
}

__device__ __forceinline__ void h_store(const uint32_t* x, float mean, float sq, uint32_t sb, int row) {
    const int lane = threadIdx.x & 31;
    const float rs = ln_rstd(sq * (1.f / 512.f));
    const uint32_t mb = pack2(mean, mean);
    uint8_t* p = g_h + ((row >> 7) * 8 + (lane >> 3)) * 16384 + (row & 127) * 128 + (((lane ^ row) & 7) << 4);
#pragma unroll
    for (int i = 0; i < 2; i++) {
        const uint4 a = lds128(sb + SM_TAB + 1024 + i * 512 + lane * 16), c = lds128(sb + SM_TAB + i * 512 + lane * 16);
        *reinterpret_cast<uint4*>(p + i * 65536) = make_uint4(ln_apply(x[4 * i], mb, rs, a.x, c.x), ln_apply(x[4 * i + 1], mb, rs, a.y, c.y),
                                                              ln_apply(x[4 * i + 2], mb, rs, a.z, c.z), ln_apply(x[4 * i + 3], mb, rs, a.w, c.w));
    }
}

template <bool ODD>
__device__ __forceinline__ void proj_tile(float (&acc)[64], float (&prev)[64], int t, int q0, uint32_t sb, int wg, bool elected, uint32_t& fph,
                                          uint32_t wtab, uint32_t& atab, uint8_t* prev_img, uint32_t toff, float s0, float s1, bool first,
                                          const bf16* x, int xrow) {
    const uint32_t a0 = desc_k(sb + (wg ^ (ODD && t == 5)) * 8192), b0 = desc_mn(sb);
    const int lane = threadIdx.x & 31;
    float mean[2] = {0.f, 0.f}, rstd[2] = {0.f, 0.f};
    uint32_t xn[16];
#pragma unroll
    for (int i = 0; i < 4; i++) {
        uint4 v = make_uint4(0, 0, 0, 0);
        if (ODD && first) v = __ldg(reinterpret_cast<const uint4*>(x) + xrow * 64 + lane + 32 * i);
        xn[4 * i] = v.x; xn[4 * i + 1] = v.y; xn[4 * i + 2] = v.z; xn[4 * i + 3] = v.w;
    }
    constexpr int U = ODD ? UNR : 1;
#pragma unroll U
    for (int q = ODD ? 0 : q0; q < 4; q++) {
        if (ODD && t == 5 && q == 3) break;
        const uint32_t ws = (wtab >> (4 * q)) & 15, as = a_next(atab);
        if (!ODD && t != 2) slot_wait(sb + BAR_FULL, fph, ws);
        slot_wait(sb + BAR_FULL, fph, as);
        bar_sync(1 + wg, 256);
        gemm_issue<false>(acc, a0 + as * (SLOT / 16), b0 + ws * (SLOT / 16), q, false);
        bar_arrive(2 - wg, 256);
        wg_wait<1>();
        reg_fence(prev);
        if (ODD && t == 5) {
            if (q == 2) {
                q_store<false>(sb + 5 * SLOT, toff, prev);
                fence_async_smem();
            }
        } else if (ODD || !first) {
            if (q == 0) img_store_global<0>(prev_img, toff, prev, s0, s1);
            if (q == 1) img_store_global<1>(prev_img, toff, prev, s0, s1);
            if (q == 2) img_store_global<2>(prev_img, toff, prev, s0, s1);
            if (q == 3) img_store_global<3>(prev_img, toff, prev, s0, s1);
        }
        if (ODD && q == 1 && first) {
#pragma unroll
            for (int k = 0; k < 16; k++) mean[k >> 3] += bf_lo(xn[k]) + bf_hi(xn[k]);
#pragma unroll
            for (int i = 0; i < 2; i++) mean[i] = warp_sum(mean[i]) * (1.f / 512.f);
        }
        if (ODD && q == 2 && first) {
#pragma unroll
            for (int k = 0; k < 16; k++) {
                const float d0 = bf_lo(xn[k]) - mean[k >> 3], d1 = bf_hi(xn[k]) - mean[k >> 3];
                rstd[k >> 3] = fmaf(d0, d0, fmaf(d1, d1, rstd[k >> 3]));
            }
#pragma unroll
            for (int i = 0; i < 2; i++) rstd[i] = warp_sum(rstd[i]);
        }
        if (ODD && q == 3 && first) {
            mbar_wait(sb + BAR_FLAG + 8 * 8, 0);
            h_store(xn, mean[0], rstd[0], sb, xrow);
        }
        wg_wait<0>();
        mbar_arrive_if(sb + BAR_EMPTY + 8 * as, elected && !(ODD && (q & 1) && t == 5));
        if (ODD) mbar_arrive_if(sb + BAR_EMPTY + 8 * ws, elected && t != 1);
        if (ODD && q == 3 && first) {
            h_store(xn + 8, mean[1], rstd[1], sb, xrow + 1);
            __syncwarp();
            mbar_arrive_if(sb + BAR_DONE, lane == 0);
        }
    }
    reg_fence(acc);
}

__device__ __forceinline__ void qk_issue(float (&s)[64], uint32_t q, uint32_t k) {
    wg_fence();
    wgmma_ss128_init<0>(s, q, k, HI_Q, HI_IMG);
#pragma unroll
    for (int i = 1; i < 8; i++) wgmma_ss128<0>(s, q + (i >> 2) * 1024 + (i & 2) * 16 + (i & 1) * 2, k + (i >> 1) * 32 + (i & 1) * 2, 1, HI_Q, HI_IMG);
    wg_commit();
}
__device__ __forceinline__ void qk_issue(float (&s)[32], uint32_t q, uint32_t k) {
    wg_fence();
    wgmma_ss64_init<0>(s, q, k, HI_Q, HI_IMG);
#pragma unroll
    for (int i = 1; i < 8; i++) wgmma_ss64<0>(s, q + (i >> 2) * 1024 + (i & 2) * 16 + (i & 1) * 2, k + (i >> 1) * 32 + (i & 1) * 2, 1, HI_Q, HI_IMG);
    wg_commit();
}
__device__ __forceinline__ void pv_issue(float (&o)[64], const uint32_t (&p)[32], uint32_t v, int acc, bool half) {
    if (half) {
        asm volatile("// half" ::: "memory");
        wg_fence();
#pragma unroll
        for (int i = 0; i < 4; i++) wgmma_rs128(o, p[4 * i], p[4 * i + 1], p[4 * i + 2], p[4 * i + 3], v + i * 256, i ? 1 : acc, HI_IMG);
        wg_commit();
        asm volatile("// half" ::: "memory");
    } else {
        wg_fence();
#pragma unroll
        for (int i = 0; i < 8; i++) wgmma_rs128(o, p[4 * i], p[4 * i + 1], p[4 * i + 2], p[4 * i + 3], v + i * 256, i ? 1 : acc, HI_IMG);
        wg_commit();
    }
}
template <int B, int N>
__device__ __forceinline__ void tri_mask(float (&s)[N], int x) {
#pragma unroll
    for (int k = 0; k < 7; k++)
        asm("{\n.reg .pred p, q;\nsetp.lt.s32 p, %4, %5;\nsetp.le.s32 q, %4, %5;\n"
            "@p mov.b32 %0, 0fFF800000;\n@q mov.b32 %1, 0fFF800000;\n@p mov.b32 %2, 0fFF800000;\n@q mov.b32 %3, 0fFF800000;\n}"
            : "+f"(s[B + 4 * k]), "+f"(s[B + 4 * k + 1]), "+f"(s[B + 4 * k + 6]), "+f"(s[B + 4 * k + 7]) : "r"(x), "r"(8 * k));
    asm("{\n.reg .pred p, q;\nsetp.lt.s32 p, %2, 56;\nsetp.le.s32 q, %2, 56;\n@p mov.b32 %0, 0fFF800000;\n@q mov.b32 %1, 0fFF800000;\n}"
        : "+f"(s[B + 28]), "+f"(s[B + 29]) : "r"(x));
}
__device__ __forceinline__ void tri_mask_copy(float (&s)[64], const float (&h)[32], int x) {
#pragma unroll
    for (int i = 0; i < 32; i++) {
        asm("{\n.reg .pred p;\nsetp.lt.s32 p, %2, %3;\nselp.f32 %0, 0fFF800000, %1, p;\n}"
            : "=f"(s[i]) : "f"(h[i]), "r"(x), "r"(8 * (i >> 2) - 4 * (i & 2) + (i & 1)));
        s[32 + i] = __uint_as_float(0xff800000u);
    }
}
constexpr float SM_HI = 1152921504606846976.f, SM_LO = 1.f / 1152921504606846976.f;
__device__ __forceinline__ bool softmax_unsafe(float t0, float t1, bool first) {
    bool bad = __any_sync(0xffffffffu, fmaxf(t0, t1) > SM_HI);
    if (first) {
        uint32_t a = __ballot_sync(0xffffffffu, t0 >= SM_LO), b = __ballot_sync(0xffffffffu, t1 >= SM_LO);
        a |= a >> 1;
        b |= b >> 1;
        bad |= ((a | (a >> 2)) & (b | (b >> 2)) & 0x11111111u) != 0x11111111u;
    }
    return bad;
}
__device__ __forceinline__ void softmax_shift(float (&s)[64], float d0, float d1) {
#pragma unroll
    for (int i = 0; i < 64; i++) s[i] -= (i & 2) ? d1 : d0;
}
__device__ __forceinline__ void softmax_remax(float (&s)[64], float (&m)[2], bool first, float& a0, float& a1) {
    float m0 = fmaxf(s[0], s[1]), m1 = fmaxf(s[2], s[3]);
#pragma unroll
    for (int k = 1; k < 16; k++) {
        m0 = fmaxf(m0, fmaxf(s[4 * k], s[4 * k + 1]));
        m1 = fmaxf(m1, fmaxf(s[4 * k + 2], s[4 * k + 3]));
    }
    m0 = fmaxf(m0, __shfl_xor_sync(0xffffffffu, m0, 1));
    m1 = fmaxf(m1, __shfl_xor_sync(0xffffffffu, m1, 1));
    m0 = fmaxf(m0, __shfl_xor_sync(0xffffffffu, m0, 2));
    m1 = fmaxf(m1, __shfl_xor_sync(0xffffffffu, m1, 2));
    if (!first) {
        m0 = fmaxf(m0, 0.f);
        m1 = fmaxf(m1, 0.f);
    }
    a0 = first ? 1.f : ex2(-m0);
    a1 = first ? 1.f : ex2(-m1);
    m[0] += m0;
    m[1] += m1;
    softmax_shift(s, m0, m1);
}
template <int J0, int J1>
__device__ __forceinline__ void softmax_exp(const float (&s)[64], uint32_t (&p)[32], float (&t)[4]) {
#pragma unroll
    for (int k = J0; k < J1; k++) {
        const float e0 = ex2(s[4 * k]), e1 = ex2(s[4 * k + 1]), e2 = ex2(s[4 * k + 2]), e3 = ex2(s[4 * k + 3]);
        if (k == 0) { t[0] = e0; t[1] = e1; t[2] = e2; t[3] = e3; }
        else { t[0] += e0; t[1] += e1; t[2] += e2; t[3] += e3; }
        p[2 * k] = pack2(e0, e1);
        p[2 * k + 1] = pack2(e2, e3);
    }
}
__device__ __forceinline__ void fma8(float (&acc)[8], float a, uint4 w) {
    acc[0] = fmaf(a, bf_lo(w.x), acc[0]); acc[1] = fmaf(a, bf_hi(w.x), acc[1]);
    acc[2] = fmaf(a, bf_lo(w.y), acc[2]); acc[3] = fmaf(a, bf_hi(w.y), acc[3]);
    acc[4] = fmaf(a, bf_lo(w.z), acc[4]); acc[5] = fmaf(a, bf_hi(w.z), acc[5]);
    acc[6] = fmaf(a, bf_lo(w.w), acc[6]); acc[7] = fmaf(a, bf_hi(w.w), acc[7]);
}
__device__ __forceinline__ void mma16816(float (&d)[4], const uint32_t* a, uint32_t b0, uint32_t b1) {
    asm("mma.sync.aligned.m16n8k16.row.col.f32.bf16.bf16.f32 {%0, %1, %2, %3}, {%4, %5, %6, %7}, {%8, %9}, {%0, %1, %2, %3};"
        : "+f"(d[0]), "+f"(d[1]), "+f"(d[2]), "+f"(d[3]) : "r"(a[0]), "r"(a[1]), "r"(a[2]), "r"(a[3]), "r"(b0), "r"(b1));
}
__device__ __forceinline__ uint32_t best_key(const uint32_t* keys, int lane, uint32_t ep) {
    uint32_t best;
#pragma unroll 1
    for (;;) {
        const uint4 k = ld_poll(reinterpret_cast<const uint4*>(keys) + lane);
        best = max(max(k.x, k.y), max(k.z, k.w));
        if (__all_sync(0xffffffffu, (((k.x ^ ep) | (k.y ^ ep) | (k.z ^ ep) | (k.w ^ ep)) & 31) == 0)) break;
    }
    return __reduce_max_sync(0xffffffffu, best);
}

__global__ void __launch_bounds__(384, 1)
fused_kernel(const __grid_constant__ CUtensorMap tm_ckv, const __grid_constant__ CUtensorMap tm_wq,
             const __grid_constant__ CUtensorMap tm_wuk, const __grid_constant__ CUtensorMap tm_wuv,
             const __grid_constant__ CUtensorMap tm_wo, const __grid_constant__ CUtensorMap tm_wg,
             const __grid_constant__ CUtensorMap tm_wu, const __grid_constant__ CUtensorMap tm_wd,
             const __grid_constant__ CUtensorMap tm_wm, const __grid_constant__ CUtensorMap tm_x, const Params P) {
    extern __shared__ __align__(1024) uint8_t smem[];
    const uint32_t sb = (uint32_t)__cvta_generic_to_shared(smem);
    const int tid = threadIdx.x, lane = tid & 31, warp = __shfl_sync(0xffffffffu, tid >> 5, 0), wg = warp >> 2;
    uint32_t sm;
    asm("mov.u32 %0, %%smid;" : "=r"(sm));
    const uint32_t smq = ((sm - 64) * 147) >> 11;
    const int rb = !P.by_smid ? blockIdx.x : sm < 64 ? (sm & 14) * 8 + (sm >> 4) * 2 + (sm & 1)
                 : sm < 120 ? ((sm - 64 - smq * 14) & 14) * 8 + 24 + smq * 2 + (sm & 1) : sm < 124 ? sm + 8 : sm - 116;
    const int grp = rb >> 3, j = rb & 7, cq = j & 3, kh = grp & 1, ort = (grp & 14) + (j >> 2);
    if (warp == 0) TS(0);

    if (rb >= NCTA) {
        float* sc = reinterpret_cast<float*>(smem + 6 * SLOT);
        float* red = sc + 512;
        if (tid == 256) {
            for (int i = 0; i < 6; i++) { mbar_init(sb + BAR_FULL + 8 * i, 1); mbar_init(sb + BAR_EMPTY + 8 * i, 8); }
            fence_async_smem();
        }
        __syncthreads();
        uint32_t ph = 0, sl = 0;
        if (tid == 256) {
#pragma unroll 1
            for (int i = 0; i < 24; i++) {
                mbar_wait(sb + BAR_EMPTY + 8 * sl, ph ^ 1);
                mbar_expect(sb + BAR_FULL + 8 * sl, SLOT);
                tma2d(sb + sl * SLOT, &tm_wm, (i >> 3) * 1024 + (rb - NCTA) * 256, (i & 7) * 64, sb + BAR_FULL + 8 * sl);
                if (++sl == 6) { sl = 0; ph ^= 1; }
            }
        } else if (tid < 256) {
            const uint32_t c2 = __ldg(reinterpret_cast<const uint32_t*>(P.c) + tid);
            sc[2 * tid] = rbf(bf_lo(c2) * sigmoid(bf_lo(c2)));
            sc[2 * tid + 1] = rbf(bf_hi(c2) * sigmoid(bf_hi(c2)));
            bar_sync(1, 256);
#pragma unroll 1
            for (int ps = 0; ps < 3; ps++) {
                float acc[8] = {0.f, 0.f, 0.f, 0.f, 0.f, 0.f, 0.f, 0.f};
#pragma unroll 1
                for (int bt = 0; bt < 8; bt++) {
                    mbar_wait(sb + BAR_FULL + 8 * sl, ph);
#pragma unroll
                    for (int i = 0; i < 8; i++)
                        fma8(acc, sc[bt * 64 + warp * 8 + i], *reinterpret_cast<const uint4*>(smem + sl * SLOT + (warp * 8 + i) * 512 + lane * 16));
                    __syncwarp();
                    mbar_arrive_if(sb + BAR_EMPTY + 8 * sl, lane == 0);
                    if (++sl == 6) { sl = 0; ph ^= 1; }
                }
                *reinterpret_cast<float4*>(red + warp * 256 + lane * 8) = make_float4(acc[0], acc[1], acc[2], acc[3]);
                *reinterpret_cast<float4*>(red + warp * 256 + lane * 8 + 4) = make_float4(acc[4], acc[5], acc[6], acc[7]);
                bar_sync(1, 256);
                float v = 0.f;
#pragma unroll
                for (int i = 0; i < 8; i++) v += red[i * 256 + tid];
                g_mod[ps * 1024 + (rb - NCTA) * 256 + tid] = __float2bfloat16_rn(v);
                bar_sync(1, 256);
                if (tid == 0 && ps != 1) flag_add(&g_sync.modcnt[(ps >> 1) * 32]);
                if (warp == 0) TS(1 + ps);
            }
        }
        return;
    }

    if (tid == 256) {
        if (sb & 1023) __trap();
        asm volatile("prefetch.tensormap [%0];" ::"l"((j & 1) ? &tm_wuv : &tm_wuk) : "memory");
        asm volatile("prefetch.tensormap [%0];" ::"l"(&tm_ckv) : "memory");
        for (int i = 0; i < 7; i++) { mbar_init(sb + BAR_FULL + 8 * i, 1); mbar_init(sb + BAR_EMPTY + 8 * i, 2); }
        for (int i = 0; i < 9; i++) mbar_init(sb + BAR_DONE + 8 * i, 8);
        for (int i = 0; i < 12; i++) mbar_init(sb + BAR_FLAG + 8 * i, 1);
        mbar_init(sb + BAR_END, 8);
        fence_async_smem();
    }
    __syncthreads();

    if (wg == 2) {
        asm volatile("setmaxnreg.dec.sync.aligned.u32 40;");
        if (warp == 8) {
            uint32_t eph = 0x7f, r = 0;
            const CUtensorMap* tw = (j & 1) ? &tm_wuv : &tm_wuk;
#pragma unroll 1
            for (int hp = 0; hp < 2; hp++) {
                const int hc = 4 * grp + 2 * hp;
                uint32_t wtab = w_table(hp), atab = a_table(hp);
#pragma unroll 1
                for (int u = 0; u < 4; u++) {
                    load_tile(sb, eph, (wtab >> (4 * u)) & 15, tw, u * 128, hc, HINT & 1); PT();
                    load_tile(sb, eph, a_next(atab), &tm_ckv, (j >> 1) * 128, u * 2, (HINT & 8) && hp); PT();
                    if (hp == 1 && (u & 1) && lane == 0) asm volatile("red.relaxed.gpu.global.add.u32 [%0], 1;" ::"l"(&g_sync.rdcnt[(grp * 2 + (u >> 1)) * 8]) : "memory");
                }
#pragma unroll 1
                for (int u = 4; u < 16; u++) {
                    if (hp == 1 && (u & 7) == 4) mbar_wait(sb + BAR_FLAG + 24 + (u & 8), 0);
                    load_tile(sb, eph, a_next(atab), &tm_ckv, ((u & 12) + (j >> 1)) * 128, (u & 3) * 2, (HINT & 8) && hp); PT();
                }
                mbar_wait(sb + BAR_FLAG, 0);
                fence_async_global();
#pragma unroll 1
                for (int u = 0; u < 4; u++) {
                    load_tile(sb, eph, (wtab >> (4 * u)) & 15, &tm_wq, u * 128, hc, HINT & 1); PT();
                    load_image(sb, eph, a_next(atab), g_h + ((15 - j) * 4 + u) * SLOT, (HINT & 8) && hp); PT();
                }
                mbar_wait(sb + BAR_FLAG + 8 + 32 * hp, 0);
                fence_async_global();
#pragma unroll 1
                for (int u = 0; u < 4; u++) { load_image(sb, eph, a_next(atab), g_h + (j * 4 + u) * SLOT, (HINT & 8) && hp); PT(); }
                const uint8_t* kv = g_KV + (size_t)(grp * 32 + 30 * hp) * SLOT;
                const int step = hp ? -2 * SLOT : 2 * SLOT;
                load_image(sb, eph, r, kv, HINT & 4); PT();
                r = ring_next(r);
#pragma unroll 1
                for (int n = 1; n <= 16; n++) {
                    if (n == 8) {
                        mbar_wait(sb + BAR_FLAG + 16 + 32 * hp, 0);
                        fence_async_global();
                    }
                    mbar_arrive_if(sb + BAR_PF, lane == 0 && (n == PF1 || n == PF2));
                    const uint8_t* v = kv + SLOT;
                    kv += n < 16 - j ? step : n == 16 - j ? (2 * j - 15) * step : -step;
                    load_image(sb, eph, r, kv, HINT & 4); PT();
                    r = ring_next(r);
                    load_image(sb, eph, r, v, HINT & 4); PT();
                    r = ring_next(r);
                }
                load_image(sb, eph, r, kv + SLOT, HINT & 4); PT();
                r = ring_next(r);
            }
            uint32_t otab = O_TABLE;
#pragma unroll 1
            for (int i = 0; i < 17; i++) {
                if ((i & 7) == 0) {
                    mbar_wait(sb + BAR_FLAG + 8 * 9 + (i ? 8 : 0), 0);
                    fence_async_global();
                }
                const int head = o_head(i, kh);
                const uint8_t* src = g_ctx + (size_t)(ort * 32 + head) * SLOT;
                if (i < 15) {
                    load_image(sb, eph, o_next(otab), src, HINT & 16);
                } else {
                    const uint32_t as = o_next(otab), d = sb + as * SLOT;
                    slot_wait(sb + BAR_EMPTY, eph, as);
                    asm volatile("{\n.reg .pred p, q;\nelect.sync _|p, 0xffffffff;\n@p mbarrier.arrive.expect_tx.shared::cta.b64 _, [%2], %3;\n"
                                 "@p cp.async.bulk.shared::cluster.global.mbarrier::complete_tx::bytes [%0], [%1], 16384, [%2];\n}"
                                 ::"r"(d + kh * 16384), "l"(src + kh * 16384), "r"(sb + BAR_FULL + 8 * as), "r"(i == 15 ? 32768 : 16384) : "memory");
                    if (i == 15)
                        asm volatile("{\n.reg .pred p;\nelect.sync _|p, 0xffffffff;\n"
                                     "@p cp.async.bulk.tensor.3d.shared::cluster.global.mbarrier::complete_tx::bytes [%0], [%1, {%3, %4, %5}], [%2];\n}"
                                     ::"r"(d + (kh ^ 1) * 16384), "l"(&tm_x), "r"(sb + BAR_FULL + 8 * as), "r"(0), "r"(ort * 128 + kh * 64), "r"(cq * 2) : "memory");
                }
                PT();
                load_tile(sb, eph, o_next(otab), &tm_wo, head * 128, cq * 2, HINT & 2); PT();
            }
            if (lane == 0) {
                const uint32_t s1 = o_next(otab), s2 = o_next(otab);
                if (rb < NFFN) {
                    slot_wait(sb + BAR_EMPTY, eph, s1);
                    const uint32_t f = sb + BAR_FULL + 8 * s1, d = sb + s1 * SLOT;
                    mbar_expect(f, SLOT);
                    tma2d(d, &tm_wg, rb * 16, 0, f);
                    tma2d(d + 8192, &tm_wg, rb * 16, 256, f);
                    tma2d(d + 16384, &tm_wu, rb * 16, 0, f);
                    tma2d(d + 24576, &tm_wu, rb * 16, 256, f);
                }
                slot_wait(sb + BAR_EMPTY, eph, s2);
                mbar_expect(sb + BAR_FULL + 8 * s2, 7 * 4096);
#pragma unroll 1
                for (int k = 0; k < 7; k++) tma2d(sb + s2 * SLOT + k * 4096, &tm_wd, (rb >> 1) * 8, k * 256, sb + BAR_FULL + 8 * s2);
            }
        } else {
            const int hw = warp - 9;
            if (hw == 1 && lane == 0) {
                l2_prefetch(P.ckv + rb * 2048, 4096);
                mbar_watch(sb + BAR_FULL + 8 * PF0, 0);
                l2_prefetch(P.ckv + 512 * 512 + rb * 2048, 4096);
                mbar_watch(sb + BAR_FULL + 8 * 4, 0);
                l2_prefetch(P.x + rb * 8192, 16384);
                l2_prefetch(P.ckv + 1024 * 512 + rb * 4096, 8192);
                TS(40);
                if (j < 4) tma3d_prefetch(&tm_wq, j * 128, grp * 4);
                mbar_watch(sb + BAR_PF, 0);
                l2_prefetch(P.ckv + rb * 8192, 16384);
                l2_prefetch(g_h + rb * 16384, 16384);
                mbar_watch(sb + BAR_PF, 1);
                tma3d_prefetch((j & 1) ? &tm_wuv : &tm_wuk, (j >> 1) * 128, grp * 4 + 2);
                if (j < 4) tma3d_prefetch(&tm_wq, j * 128, grp * 4 + 2);
                mbar_watch(sb + BAR_PF, 0);
                l2_prefetch(g_ctx + (size_t)(ort * 32 + o_head(cq, kh)) * SLOT, SLOT);
                l2_prefetch(g_ctx + (size_t)(ort * 32 + o_head(cq + 4, kh)) * SLOT, SLOT);
                mbar_watch(sb + BAR_PF, 1);
                l2_prefetch(reinterpret_cast<const uint8_t*>(P.wo) + rb * 32768, 32768);
                l2_prefetch(reinterpret_cast<const uint8_t*>(P.wgate) + rb * 14336, 14336);
                l2_prefetch(reinterpret_cast<const uint8_t*>(P.wup) + rb * 14336, 14336);
                l2_prefetch(reinterpret_cast<const uint8_t*>(P.wdown) + rb * 14336, 14336);
                l2_prefetch(P.x + rb * 8192, 16384);
                mbar_watch(sb + BAR_END, 0);
            }
            if (hw == 0) {
#pragma unroll 1
                for (int i = 0; i < 9; i++) {
                    const int hp = i > 4, k = (i - 1) & 3;
                    if (lane == 0) {
                        mbar_wait(sb + BAR_DONE + 8 * i, 0);
                        flag_add(i == 0 ? &g_sync.hcnt[grp * 8] : k < 2 ? &g_sync.kvcnt[((2 * grp + hp) * 2 + k) * 8]
                                                                        : &g_sync.ctxcnt[(k == 2 ? 15 - j : j) * 32 + 2 * grp + hp]);
                    }
                    if (i == 0) TS(43);
                }
            }
            if (hw == 2) {
                const uint32_t ep = __ldcg(&g_sync.epoch[0]) + 1;
                if (lane == 0) {
                    asm volatile("st.shared.u32 [%0], %1;" ::"r"(sb + SM_EP), "r"(ep) : "memory");
                    flag_wait(&g_sync.modcnt[0], NSPARE * ep);
                }
                __syncwarp();
#pragma unroll
                for (int i = 0; i < 4; i++) {
                    uint4 v = __ldcg(reinterpret_cast<const uint4*>(g_mod) + lane + 32 * i);
                    if (i >= 2) v = make_uint4(badd(v.x, ONE2), badd(v.y, ONE2), badd(v.z, ONE2), badd(v.w, ONE2));
                    sts128(sb + SM_TAB + i * 512 + lane * 16, v);
                }
                __syncwarp();
                if (lane == 0) mbar_arrive(sb + BAR_FLAG + 8 * 8);
                TS(42);
#pragma unroll 1
                for (int i = 0; i < 8; i++) {
                    if (lane == 0) mbar_wait(sb + BAR_DONE + 8 * (i == 7 ? 6 : i == 4 ? 3 : i), 0);
                    __syncwarp();
                    const uint32_t* f = i == 0 ? &g_sync.hcnt[(lane ? j : 15 - j) * 8]
                                      : i == 3 || i == 4 ? &g_sync.rdcnt[(grp * 2 + i - 3) * 8]
                                      : i == 7 ? &g_sync.modcnt[32] : &g_sync.kvcnt[(4 * grp + (i > 4 ? i - 3 : i - 1)) * 8];
                    if (lane < (i ? 1 : 2)) flag_wait(f, i == 7 ? NSPARE * ep : 8 * ep);
                    __syncwarp();
                    if (i == 7) {
                        const uint32_t *mp = reinterpret_cast<const uint32_t*>(g_mod) + lane, *wp = reinterpret_cast<const uint32_t*>(P.wr) + lane;
                        float ra = 0.f, rs = 0.f;
#pragma unroll 1
                        for (int k = 0; k < 256; k += 32) {
                            const uint32_t ga = __ldcg(mp + 512 + k), sh = __ldcg(mp + 768 + k), c1 = badd(__ldcg(mp + 1024 + k), ONE2);
                            const uint32_t gb = __ldcg(mp + 1280 + k), ww = __ldg(wp + k);
                            const float a0 = bf_lo(c1) * bf_lo(ww), a1 = bf_hi(c1) * bf_hi(ww);
                            ra += a0 + a1;
                            rs = fmaf(bf_lo(sh), bf_lo(ww), fmaf(bf_hi(sh), bf_hi(ww), rs));
                            if (k >> 6 == cq) {
                                sts128(sb + SM_TAB + ((k & 32) + lane) * 16, make_uint4(ga << 16, ga & 0xffff0000u, __float_as_uint(a0), __float_as_uint(a1)));
                                sts128(sb + SM_TAB + 1024 + ((k & 32) + lane) * 16, make_uint4(c1, sh, gb, 0));
                            }
                        }
                        *reinterpret_cast<float2*>(smem + SM_EP + 8) = make_float2(warp_sum(ra), warp_sum(rs));
                        __syncwarp();
                    }
                    if (lane == 0) mbar_arrive(sb + BAR_FLAG + 8 * i);
                    TS(48 + i);
                }
#pragma unroll 1
                for (int i = 0; i < 2; i++) {
                    if (i) mbar_wait(sb + BAR_DONE + 8 * 7, 0);
                    if (lane < 8 + i) flag_wait(&g_sync.ctxcnt[ort * 32 + o_head(lane + 8 * i, kh)], ep);
                    __syncwarp();
                    if (lane == 0) mbar_arrive(sb + BAR_FLAG + 8 * (9 + i));
                    TS(44 + i);
                }
            }
        }
    } else {
        asm volatile("setmaxnreg.inc.sync.aligned.u32 232;");
        const bool elected = (tid & 127) == 0;
        const int g = lane >> 2, c4 = lane & 3;
        const uint32_t toff = warp * 4096 + g * 64 + ((c4 ^ (g >> 1)) << 4);
        uint32_t fph = 0, r = 0;
        if (wg == 1) bar_arrive(1, 256);
        const uint32_t kd = desc_k(sb), wd = desc_mn(sb), vd = (sb >> 4) | (32u << 16);
        const int nL = 16 - j, hn = nL - 1 + wg;
        float s[64], o[64], li[2] = {0.f, 0.f};
        uint8_t* cimg = g_ctx;
#pragma unroll 1
        for (int hp = 0; hp < 2; hp++) {
            {
                const int step = hp ? -8 * SLOT : 8 * SLOT;
                uint8_t* img = g_KV + (size_t)(grp * 32 + (hp ? j ^ 30 : j)) * SLOT - step;
                const float sc = (j & 1) ? 1.f : SM_C;
                const uint32_t wtab = w_table(hp);
                uint32_t atab = hp ? 0x256u : a_table(0);
#pragma unroll 1
                for (int t = 0; t < 6; t += 2) {
                    proj_tile<false>(s, o, t, t ? 0 : 2 * hp, sb, wg, elected, fph, wtab, atab, t ? img : cimg, toff, t ? sc : li[0], t ? sc : li[1], (hp | t) == 0, P.x, rb * 16 + warp * 2);
                    __syncwarp();
                    mbar_arrive_if(sb + BAR_DONE + 4 * t + 32 * hp, lane == 0 && (hp | t) != 0);
                    if (elected) TS(1 + 10 * hp + t + 20 * wg);
                    proj_tile<true>(o, s, t + 1, 0, sb, wg, elected, fph, wtab, atab, img + step, toff, sc, sc, (hp | t) == 0, P.x, rb * 16 + warp * 2);
                    if (elected) TS(2 + 10 * hp + t + 20 * wg);
                    img += 2 * step;
                }
            }
            float m[2] = {0.f, 0.f}, l[2] = {0.f, 0.f}, t[4] = {0.f, 0.f, 0.f, 0.f};
            bool shifted = false, bad = false, plain = false;
            uint32_t p[32];
#pragma unroll
            for (int i = 0; i < 32; i++) p[i] = 0;
            uint32_t qa = desc_k(sb + 5 * SLOT + (wg ^ 1) * 8192);
            uint8_t* img = g_ctx + (size_t)((15 - j) * 32 + 2 * grp + hp) * SLOT;
            slot_wait(sb + BAR_FULL, fph, r);
            int n = -1;
#pragma unroll 1
            for (;;) {
                while (bad || plain) {
                    if (bad) {
                        float a0, a1;
                        softmax_remax(s, m, n == 0 || n == nL, a0, a1);
                        shifted = true;
                        l[0] *= a0;
                        l[1] *= a1;
#pragma unroll
                        for (int i = 0; i < 64; i++) o[i] *= (i & 2) ? a1 : a0;
                    }
                    softmax_exp<0, 16>(s, p, t);
                    t[0] += t[1];
                    t[2] += t[3];
                    bad = !bad && softmax_unsafe(t[0], t[2], false);
                    plain = false;
                }
#pragma unroll 1
                do {
                    l[0] += t[0];
                    l[1] += t[2];
                    if (++n > 16) break;
                    const uint32_t ks = r;
                    uint32_t vs = ring_next(r);
                    r = ring_next(vs);
                    bar_sync(1 + wg, 256);
                    if (n == 0 || (uint32_t)(n + 1 - nL) <= (uint32_t)(1 + wg)) {
                        const int x = (warp & 3) * 16 + g - 2 * c4;
                        if (n == 0) {
                            r = vs;
                            vs = 4 - hp;
                            qk_issue(s, qa, kd + ks * (SLOT / 16));
                            slot_wait(sb + BAR_FULL, fph, 6);
                            gemm_issue<false>(o, qa + SLOT / 16, wd + vs * (SLOT / 16), 1, false);
                            bar_arrive(2 - wg, 256);
                            wg_wait<1>();
                            reg_fence(s);
                        } else if (n == hn) {
                            float sh[32];
                            qk_issue(sh, qa, kd + ks * (SLOT / 16));
                            slot_wait(sb + BAR_FULL, fph, vs);
                            pv_issue(o, p, vd + vs * (SLOT / 16), 1, false);
                            bar_arrive(2 - wg, 256);
                            wg_wait<1>();
                            reg_fence(sh);
                            tri_mask_copy(s, sh, x);
                        } else {
                            qk_issue(s, qa, kd + ks * (SLOT / 16));
                            slot_wait(sb + BAR_FULL, fph, vs);
                            pv_issue(o, p, vd + vs * (SLOT / 16), n != nL + 1, n == hn + 1);
                            bar_arrive(2 - wg, 256);
                            wg_wait<1>();
                            reg_fence(s);
                            if (n <= nL) tri_mask<32>(s, x);
                        }
                        mbar_arrive_if(sb + BAR_EMPTY + 8 * ks, elected);
                        mbar_arrive_if(sb + BAR_EMPTY + 8 * (n == 16 ? 6 : 5), elected && (n == 16 || n == nL - 1));
                        if (n == nL - 1) {
                            qa += SLOT / 16;
                            fence_async_smem();
                        }
                        if (shifted) {
                            if (n == nL) {
                                m[0] = m[1] = 0.f;
                                shifted = false;
                            }
                            softmax_shift(s, m[0], m[1]);
                        }
                        float e[4 * EARLY];
#pragma unroll
                        for (int i = 0; i < 4 * EARLY; i++) {
                            e[i] = ex2(s[i]);
                            t[i & 3] = i < 4 ? e[i] : t[i & 3] + e[i];
                        }
                        reg_fence(e);
                        slot_wait(sb + BAR_FULL, fph, r);
                        wg_wait<0>();
                        reg_fence(o);
                        reg_fence(e);
                        mbar_arrive_if(sb + BAR_EMPTY + 8 * vs, elected);
#pragma unroll
                        for (int i = 0; i < 2 * EARLY; i++) p[i] = pack2(e[2 * i], e[2 * i + 1]);
                        softmax_exp<EARLY, 8>(s, p, t);
                        if (n == 0) q_store<(PARKS & 1) != 0>(sb + 6 * SLOT, toff, o);
                        if (n == nL) {
                            ctx_store<(PARKS & 2) != 0>(img, toff, o, l[0], l[1]);
                            __syncwarp();
                            mbar_arrive_if(sb + BAR_DONE + 24 + 32 * hp, lane == 0);
                            l[0] = l[1] = 0.f;
                        }
                        if (n != hn) softmax_exp<8, 16>(s, p, t);
                        t[0] += t[1];
                        t[2] += t[3];
                        bad = softmax_unsafe(t[0], t[2], n == 0 || n == nL);
                        continue;
                    }
                    qk_issue(s, qa, kd + ks * (SLOT / 16));
                    slot_wait(sb + BAR_FULL, fph, vs);
                    pv_issue(o, p, vd + vs * (SLOT / 16), n != 1 && n != nL + 1, false);
                    bar_arrive(2 - wg, 256);
                    wg_wait<1>();
                    reg_fence(s);
                    mbar_arrive_if(sb + BAR_EMPTY + 8 * ks, elected);
                    mbar_arrive_if(sb + BAR_EMPTY + 8 * 6, elected && n == 16);
                    if (shifted) {
                        slot_wait(sb + BAR_FULL, fph, r);
                        wg_wait<0>();
                        reg_fence(o);
                        mbar_arrive_if(sb + BAR_EMPTY + 8 * vs, elected);
                        softmax_shift(s, m[0], m[1]);
                        plain = true;
                        break;
                    }
                    float e[4 * EARLY];
#pragma unroll
                    for (int i = 0; i < 4 * EARLY; i++) {
                        e[i] = ex2(s[i]);
                        t[i & 3] = i < 4 ? e[i] : t[i & 3] + e[i];
                    }
                    reg_fence(e);
                    slot_wait(sb + BAR_FULL, fph, r);
                    wg_wait<0>();
                    reg_fence(o);
                    reg_fence(e);
                    mbar_arrive_if(sb + BAR_EMPTY + 8 * vs, elected);
#pragma unroll
                    for (int i = 0; i < 2 * EARLY; i++) p[i] = pack2(e[2 * i], e[2 * i + 1]);
                    softmax_exp<EARLY, 16>(s, p, t);
                    t[0] += t[1];
                    t[2] += t[3];
                    bad = softmax_unsafe(t[0], t[2], false);
                } while (!bad);
                if (!bad && !plain) break;
            }
            const uint32_t vs = r, ga = desc_k(sb + (hp ? 2 * (wg ^ kh ^ 1) : wg) * 8192), as = 2 + 2 * hp;
            r = ring_next(r);
            slot_wait(sb + BAR_FULL, fph, 5);
            slot_wait(sb + BAR_FULL, fph, r);
            bar_sync(1 + wg, 256);
            gemm_issue<true>(s, ga + 5 * (SLOT / 16), wd + r * (SLOT / 16), 0, hp);
            pv_issue(o, p, vd + vs * (SLOT / 16), j, hn == 16);
            bar_arrive(2 - wg, 256);
            li[0] = rcp(quad_sum(l[0]));
            li[1] = rcp(quad_sum(l[1]));
            cimg = img + (ptrdiff_t)(2 * j - 15) * 32 * SLOT + (wg ? -16384 : 16384);
            wg_wait<1>();
            mbar_arrive_if(sb + BAR_EMPTY + 8 * 5, elected);
            mbar_arrive_if(sb + BAR_EMPTY + 8 * r, elected && hp);
            wg_wait<0>();
            mbar_arrive_if(sb + BAR_EMPTY + 8 * vs, elected);
            reg_fence(o);
            img_store_global<0>(cimg, toff, o, li[0], li[1]);
            slot_wait(sb + BAR_FULL, fph, as);
            slot_wait(sb + BAR_FULL, fph, 0);
            bar_sync(1 + wg, 256);
            gemm_issue<false>(s, ga + as * (SLOT / 16), wd, 1, hp);
            bar_arrive(2 - wg, 256);
            reg_fence(o);
            img_store_global<1>(cimg, toff, o, li[0], li[1]);
            wg_wait<0>();
            mbar_arrive_if(sb + BAR_EMPTY + 8 * as, elected);
            mbar_arrive_if(sb + BAR_EMPTY, elected && hp);
            if (elected) TS(8 + 10 * hp + 20 * wg);
        }
        uint32_t otab = 0x0435216u;
        const uint32_t oa = desc_k(sb + (wg ^ kh ^ 1) * 16384);
        const int t7 = tid & 127, w4 = warp & 3, row = ort * 128 + kh * 64 + w4 * 16 + g;
#pragma unroll 1
        for (int i = 2; i < 15 - wg; i++) {
            const uint32_t as = o_next(otab), ws = o_next(otab);
            slot_wait(sb + BAR_FULL, fph, as);
            slot_wait(sb + BAR_FULL, fph, ws);
            bar_sync(1 + wg, 256);
            gemm_issue<false>(s, oa + as * (SLOT / 16), wd + ws * (SLOT / 16), 1, true);
            bar_arrive(2 - wg, 256);
            wg_wait<1>();
            reg_fence(o);
            if (i == 2) img_store_global<2>(cimg, toff, o, li[0], li[1]);
            if (i == 3) {
                img_store_global<3>(cimg, toff, o, li[0], li[1]);
                __syncwarp();
                mbar_arrive_if(sb + BAR_DONE + 64, lane == 0);
            }
            wg_wait<0>();
            mbar_arrive_if(sb + BAR_EMPTY + 8 * as, elected);
            mbar_arrive_if(sb + BAR_EMPTY + 8 * ws, elected);
        }
        mbar_wait(sb + BAR_FLAG + 8 * 7, 0);
        const uint32_t ep = lds32(sb + SM_EP);
        if (wg == 0) {
            reg_fence(s);
            if (elected) TS(9);
#pragma unroll
            for (int v = 0; v < 8; v++)
                st_pub(g_part + rb * 1024 + v * 128 + t7, make_uint4((pack2(s[8 * v], s[8 * v + 1]) & ~1u) | (ep & 1), pack2(s[8 * v + 2], s[8 * v + 3]),
                                                                      pack2(s[8 * v + 4], s[8 * v + 5]), pack2(s[8 * v + 6], s[8 * v + 7])), true);
            o_next(otab); o_next(otab); o_next(otab); o_next(otab);
            const uint32_t s1 = o_next(otab), s2 = o_next(otab);
            uint32_t wf[64];
            float wn[56];
            if (rb < NFFN) {
                slot_wait(sb + BAR_FULL, fph, s1);
                const uint32_t a = sb + s1 * SLOT + (w4 * 128 + (lane >> 4) * 8 + (lane & 7)) * 32 + ((lane >> 3) & 1) * 16;
#pragma unroll
                for (int i = 0; i < 16; i++)
                    asm volatile("ldmatrix.sync.aligned.m8n8.x4.trans.shared.b16 {%0, %1, %2, %3}, [%4];"
                                 : "=r"(wf[4 * i]), "=r"(wf[4 * i + 1]), "=r"(wf[4 * i + 2]), "=r"(wf[4 * i + 3])
                                 : "r"(a + (i >> 3) * 16384 + (i & 7) * 512) : "memory");
            }
            const uint32_t gbf = __ldcg(reinterpret_cast<const uint32_t*>(g_mod) + 1280 + rb * 2 + (tid & 1));
            if (elected) TS(10);
            const uint32_t best = best_key(g_key + cq * 128, lane, ep);
            const int sel = (~best >> 5) & 2047;
            if (elected) TS(19);
            const uint4* cp = g_cand + (sel >> 4) * 192;
            float* sred = reinterpret_cast<float*>(smem + SM_RED);
            const int pq = (2 * rb + (tid & 1)) & 63, pv = (pq >> 2) / 3;
            const uint4* fp = cp + (rb >> 5) * 24 + pv * 4 + (pq & 3);
            uint4 fh = ld_poll(fp), fx = ld_poll(fp + 96);
            if (rb < NFFN) {
                uint4 cv[6];
                for (;;) {
                    uint32_t bad = 0;
#pragma unroll
                    for (int v = 0; v < 6; v++) cv[v] = ld_poll(cp + w4 * 24 + v * 4 + c4);
#pragma unroll
                    for (int v = 0; v < 6; v++) bad |= cv[v].w ^ ep;
                    if (__all_sync(0xffffffffu, bad == 0)) break;
                }
                if (elected) TS(20);
                float d[4][4] = {};
#pragma unroll
                for (int k = 0; k < 8; k++) {
                    const uint32_t b0 = (&cv[(2 * k) / 3].x)[(2 * k) % 3], b1 = (&cv[(2 * k + 1) / 3].x)[(2 * k + 1) % 3];
                    mma16816(d[k & 1], wf + 4 * k, b0, b1);
                    mma16816(d[2 + (k & 1)], wf + 32 + 4 * k, b0, b1);
                }
                const float u = (c4 & 2) ? ((c4 & 1) ? d[2][2] + d[3][2] : d[2][0] + d[3][0]) : ((c4 & 1) ? d[0][2] + d[1][2] : d[0][0] + d[1][0]);
                sred[w4 * 32 + c4 * 8 + g] = u;
                bar_sync(3, 128);
                if (warp == 0) {
                    const float v = rbf((sred[lane] + sred[32 + lane]) + (sred[64 + lane] + sred[96 + lane]));
                    const float up = __shfl_down_sync(0xffffffffu, v, 16);
                    st_pub(g_act + rb * 16 + lane, (pack2(0.f, rbf(v * sigmoid(v)) * up) & 0xffff0000u) | (ep & 0xffffu), lane < 16);
                }
            }
            if (rb == 0 && tid == 0) g_sync.epoch[0] = ep;
            if (elected) TS(60);
            slot_wait(sb + BAR_FULL, fph, s2);
#pragma unroll
            for (int i = 0; i < 14; i++) {
                const uint2 w = *reinterpret_cast<const uint2*>(smem + s2 * SLOT + (i >> 1) * 4096 + (2 * t7 + (i & 1)) * 16 + (rb & 1) * 8);
                wn[4 * i] = bf_lo(w.x); wn[4 * i + 1] = bf_hi(w.x); wn[4 * i + 2] = bf_lo(w.y); wn[4 * i + 3] = bf_hi(w.y);
            }
            reg_fence(wn);
            uint2 av[7];
            for (;;) {
                uint32_t bad = 0;
#pragma unroll
                for (int k = 0; k < 7; k++) av[k] = ld_poll(reinterpret_cast<const uint2*>(g_act) + t7 + 128 * k);
#pragma unroll
                for (int k = 0; k < 7; k++) bad |= (av[k].x ^ ep) | (av[k].y ^ ep);
                if (__all_sync(0xffffffffu, (bad & 0xffffu) == 0)) break;
            }
            if (elected) TS(61);
            float y[4] = {0.f, 0.f, 0.f, 0.f};
#pragma unroll
            for (int k = 0; k < 7; k++)
#pragma unroll
                for (int i = 0; i < 4; i++) y[i] = fmaf(bf_hi(av[k].y), wn[8 * k + 4 + i], fmaf(bf_hi(av[k].x), wn[8 * k + i], y[i]));
            const float z0 = ((lane & 16) ? y[2] : y[0]) + __shfl_xor_sync(0xffffffffu, (lane & 16) ? y[0] : y[2], 16);
            const float z1 = ((lane & 16) ? y[3] : y[1]) + __shfl_xor_sync(0xffffffffu, (lane & 16) ? y[1] : y[3], 16);
            float z = ((lane & 8) ? z1 : z0) + __shfl_xor_sync(0xffffffffu, (lane & 8) ? z0 : z1, 8);
            z += __shfl_xor_sync(0xffffffffu, z, 4);
            z = quad_sum(z);
            if ((lane & 7) == 0) sred[128 + (lane >> 3) * 4 + w4] = z;
            bar_sync(3, 128);
            if (tid < 2) {
                while (fh.w != ep || fx.w != ep) { fh = ld_poll(fp); fx = ld_poll(fp + 96); }
                const float4 y0 = *reinterpret_cast<const float4*>(sred + 128 + tid * 8), y1 = *reinterpret_cast<const float4*>(sred + 132 + tid * 8);
                const int cm = (pq >> 2) - 3 * pv;
                const uint32_t h2 = cm == 0 ? fh.x : cm == 1 ? fh.y : fh.z, x2 = cm == 0 ? fx.x : cm == 1 ? fx.y : fx.z;
                const float sg = sigmoid(bf_hi((best & 0x80000000u) ? (best ^ 0x80000000u) : ~best));
                reinterpret_cast<uint32_t*>(P.out)[sel * 256 + rb * 2 + tid] =
                    badd(x2, bmul(gbf, badd(h2, bmul(pack2((y0.x + y0.y) + (y0.z + y0.w), (y1.x + y1.y) + (y1.z + y1.w)), pack2(sg, sg)))));
            }
            if (elected) TS(62);
        } else {
            const float4* tf = reinterpret_cast<const float4*>(smem + SM_TAB) + c4;
            const uint32_t as14 = otab & 15, xa = sb + ((otab >> 8) & 15) * SLOT + (kh ^ 1) * 16384 + (w4 * 16 + (lane & 15)) * 128;
            uint32_t x2[32];
            bar_sync(2, 256);
#pragma unroll 1
            for (int i = 14; i < 17; i++) {
                const uint32_t as = o_next(otab), ws = o_next(otab);
                slot_wait(sb + BAR_FULL, fph, as);
                slot_wait(sb + BAR_FULL, fph, ws);
                gemm_issue<false>(s, oa + as * (SLOT / 16), wd + ws * (SLOT / 16), 1, true);
                wg_wait<1>();
                mbar_arrive_if(sb + BAR_EMPTY + 8 * as14, elected && i == 15);
            }
            if (elected) TS(29);
            {
#pragma unroll
                for (int k = 0; k < 8; k++)
                    asm volatile("ldmatrix.sync.aligned.m8n8.x4.shared.b16 {%0, %1, %2, %3}, [%4];"
                                 : "=r"(x2[4 * k]), "=r"(x2[4 * k + 1]), "=r"(x2[4 * k + 2]), "=r"(x2[4 * k + 3])
                                 : "r"(xa + (k >> 2) * 8192 + (((2 * (k & 3) + (lane >> 4)) ^ (lane & 7)) << 4)) : "memory");
                const uint4* pr = g_part + (rb ^ 8) * 1024 + t7;
                uint4 pa[8];
                for (;;) {
                    uint32_t bad = 0;
#pragma unroll
                    for (int v = 0; v < 8; v++) pa[v] = ld_poll(pr + v * 128);
#pragma unroll
                    for (int v = 0; v < 8; v++) bad |= pa[v].x ^ ep;
                    if (__all_sync(0xffffffffu, (bad & 1) == 0)) break;
                }
#pragma unroll
                for (int i = 0; i < 32; i++) {
                    const uint32_t w = (&pa[i >> 2].x)[i & 3];
                    const float2 ga = *reinterpret_cast<const float2*>(tf + (i >> 1) * 4);
                    o[2 * i] = fmaf(ga.x, bf_lo(w), bf_lo(x2[i]));
                    o[2 * i + 1] = fmaf(ga.y, bf_hi(w), bf_hi(x2[i]));
                }
            }
            reg_fence(o);
            if (elected) TS(30);
            wg_wait<0>();
            reg_fence(s);
            if (elected) TS(39);
            float st[6] = {0.f, 0.f, 0.f, 0.f, 0.f, 0.f};
#pragma unroll
            for (int k = 0; k < 16; k++) {
                const float4 c = tf[k * 4];
#pragma unroll
                for (int i = 4 * k; i < 4 * k + 4; i++) {
                    const int rh = (i >> 1) & 1;
                    const float v = fmaf((i & 1) ? c.y : c.x, s[i], o[i]);
                    s[i] = v;
                    st[rh] += v;
                    st[2 + rh] = fmaf(v, v, st[2 + rh]);
                    st[4 + rh] = fmaf(v, (i & 1) ? c.w : c.z, st[4 + rh]);
                }
            }
#pragma unroll
            for (int i = 0; i < 6; i++) st[i] = quad_sum(st[i]);
            st_pub(g_stat + (row + 8 * (c4 & 1)) * 4 + cq,
                   make_uint4(__float_as_uint((c4 & 1) ? st[1] : st[0]), __float_as_uint((c4 & 1) ? st[3] : st[2]),
                              __float_as_uint((c4 & 1) ? st[5] : st[4]), ep), c4 < 2);
            if (elected) TS(56);
            uint32_t cb[16], sh[16], gb[16];
#pragma unroll
            for (int i = 0; i < 16; i++) {
                const float4 c = tf[64 + i * 4];
                cb[i] = __float_as_uint(c.x); sh[i] = __float_as_uint(c.y); gb[i] = __float_as_uint(c.z);
            }
            const float ra = __uint_as_float(lds32(sb + SM_EP + 8)), rb0 = __uint_as_float(lds32(sb + SM_EP + 12));
#pragma unroll
            for (int i = 0; i < 32; i++) x2[i] = pack2(s[2 * i], s[2 * i + 1]);
            reg_fence(x2);
            uint4 r0, r1;
            for (;;) {
                r0 = ld_poll(g_stat + row * 4 + c4);
                r1 = ld_poll(g_stat + (row + 8) * 4 + c4);
                if (__all_sync(0xffffffffu, r0.w == ep && r1.w == ep)) break;
            }
            if (elected) TS(57);
            const float m0 = quad_sum(__uint_as_float(r0.x)) * (1.f / 512.f), m1 = quad_sum(__uint_as_float(r1.x)) * (1.f / 512.f);
            const float rs0 = ln_rstd(fmaxf(fmaf(-m0, m0, quad_sum(__uint_as_float(r0.y)) * (1.f / 512.f)), 0.f));
            const float rs1 = ln_rstd(fmaxf(fmaf(-m1, m1, quad_sum(__uint_as_float(r1.y)) * (1.f / 512.f)), 0.f));
            const uint32_t mb0 = pack2(m0, m0), mb1 = pack2(m1, m1);
            const uint32_t lg = pack2(fmaf(rs0, fmaf(-bf_lo(mb0), ra, quad_sum(__uint_as_float(r0.z))), rb0),
                                      fmaf(rs1, fmaf(-bf_lo(mb1), ra, quad_sum(__uint_as_float(r1.z))), rb0));
            const uint32_t u0 = lg << 16, u1 = lg & 0xffff0000u;
            const uint32_t k0 = ((u0 ^ (((int)u0 >> 31) | 0x80000000u)) & 0xffff0000u) | ((2047 - row) << 5) | (ep & 31);
            const uint32_t k1 = ((u1 ^ (((int)u1 >> 31) | 0x80000000u)) & 0xffff0000u) | ((2039 - row) << 5) | (ep & 31);
            const uint32_t kb = __reduce_max_sync(0xffffffffu, max(k0, k1));
            st_pub(g_key + cq * 128 + (row >> 4), kb, lane == 0);
            {
                uint32_t cx[18], ch[18];
#pragma unroll
                for (int i = 0; i < 16; i++) {
                    cx[i] = kb == k1 ? x2[2 * i + 1] : x2[2 * i];
                    ch[i] = ln_apply(cx[i], kb == k1 ? mb1 : mb0, kb == k1 ? rs1 : rs0, cb[i], sh[i]);
                }
                cx[16] = cx[17] = ch[16] = ch[17] = 0;
                uint4* cp = g_cand + (row >> 4) * 192 + cq * 24 + c4;
#pragma unroll
                for (int v = 0; v < 6; v++) st_pub(cp + v * 4, make_uint4(ch[3 * v], ch[3 * v + 1], ch[3 * v + 2], ep), kb == k0 || kb == k1);
#pragma unroll
                for (int v = 0; v < 6; v++) st_pub(cp + 96 + v * 4, make_uint4(cx[3 * v], cx[3 * v + 1], cx[3 * v + 2], ep), kb == k0 || kb == k1);
            }
            if (elected) TS(58);
            uint2 ov[16];
#pragma unroll
            for (int i = 0; i < 16; i++) {
                const int rh = i & 1, jj = i & 14;
                const uint32_t v0 = badd(x2[2 * jj + rh], bmul(gb[jj], ln_apply(x2[2 * jj + rh], rh ? mb1 : mb0, rh ? rs1 : rs0, cb[jj], sh[jj])));
                const uint32_t v1 = badd(x2[2 * jj + 2 + rh], bmul(gb[jj + 1], ln_apply(x2[2 * jj + 2 + rh], rh ? mb1 : mb0, rh ? rs1 : rs0, cb[jj + 1], sh[jj + 1])));
                const uint32_t rv = __shfl_xor_sync(0xffffffffu, (c4 & 1) ? v0 : v1, 1);
                ov[i] = (c4 & 1) ? make_uint2(rv, v1) : make_uint2(v0, rv);
            }
            uint2* op = reinterpret_cast<uint2*>(P.out) + row * 128 + cq * 32 + (c4 & 1) * 2 + (c4 >> 1);
#pragma unroll
            for (int i = 0; i < 16; i++)
                if (kb != ((i & 1) ? k1 : k0)) op[(i & 1) * 1024 + (i & 14) * 2] = ov[i];
            const uint32_t best = best_key(g_key + cq * 128, lane, ep);
            if (best != kb) {
#pragma unroll
                for (int i = 0; i < 16; i++)
                    if (kb == ((i & 1) ? k1 : k0)) op[(i & 1) * 1024 + (i & 14) * 2] = ov[i];
            }
            if (elected) TS(59);
        }
        mbar_arrive_if(sb + BAR_END, lane == 0);
    }
}

typedef CUresult (*EncodeFn)(CUtensorMap*, CUtensorMapDataType, cuuint32_t, void*, const cuuint64_t*, const cuuint64_t*,
                             const cuuint32_t*, const cuuint32_t*, CUtensorMapInterleave, CUtensorMapSwizzle,
                             CUtensorMapL2promotion, CUtensorMapFloatOOBfill);

void make_2d(EncodeFn fn, CUtensorMap* m, const void* p, uint64_t cols, uint64_t rows, uint32_t bc, uint32_t br) {
    cuuint64_t dims[2] = {cols, rows}, strides[1] = {cols * 2};
    cuuint32_t box[2] = {bc, br}, es[2] = {1, 1};
    fn(m, CU_TENSOR_MAP_DATA_TYPE_BFLOAT16, 2, const_cast<void*>(p), dims, strides, box, es, CU_TENSOR_MAP_INTERLEAVE_NONE,
       CU_TENSOR_MAP_SWIZZLE_NONE, CU_TENSOR_MAP_L2_PROMOTION_L2_128B, CU_TENSOR_MAP_FLOAT_OOB_FILL_NONE);
}
void make_3d(EncodeFn fn, CUtensorMap* m, const void* p, uint64_t cols, uint64_t rows, uint32_t br = 128) {
    cuuint64_t dims[3] = {64, rows, cols / 64}, strides[2] = {cols * 2, 128};
    cuuint32_t box[3] = {64, br, 2}, es[3] = {1, 1, 1};
    fn(m, CU_TENSOR_MAP_DATA_TYPE_BFLOAT16, 3, const_cast<void*>(p), dims, strides, box, es, CU_TENSOR_MAP_INTERLEAVE_NONE,
       CU_TENSOR_MAP_SWIZZLE_128B, CU_TENSOR_MAP_L2_PROMOTION_L2_256B, CU_TENSOR_MAP_FLOAT_OOB_FILL_NONE);
}

}

extern "C" void kernel_launch(void* const* d_in, const int* in_sizes, int n_in, void* d_out, int out_size) {
    static EncodeFn fn = nullptr;
    static int sms = 0;
    if (!fn) {
        void* f = nullptr;
        cudaDriverEntryPointQueryResult st;
        cudaGetDriverEntryPoint("cuTensorMapEncodeTiled", &f, cudaEnableDefault, &st);
        fn = (EncodeFn)f;
        int dev = 0;
        cudaGetDevice(&dev);
        cudaDeviceGetAttribute(&sms, cudaDevAttrMultiProcessorCount, dev);
        cudaFuncSetAttribute(fused_kernel, cudaFuncAttributeMaxDynamicSharedMemorySize, SMEM_BYTES);
    }
    CUtensorMap ckv, wq, wuk, wuv, wo, wg, wu, wd, wm, xm;
    make_3d(fn, &ckv, d_in[1], 512, 2048);
    make_3d(fn, &xm, d_in[0], 512, 2048, 64);
    make_3d(fn, &wq, d_in[2], 4096, 512);
    make_3d(fn, &wuk, d_in[3], 4096, 512);
    make_3d(fn, &wuv, d_in[4], 4096, 512);
    make_3d(fn, &wo, d_in[5], 512, 4096);
    make_2d(fn, &wg, d_in[8], 1792, 512, 16, 256);
    make_2d(fn, &wu, d_in[9], 1792, 512, 16, 256);
    make_2d(fn, &wd, d_in[10], 512, 1792, 8, 256);
    make_2d(fn, &wm, d_in[12], 3072, 512, 256, 64);
    Params p;
    p.x = (const bf16*)d_in[0];
    p.ckv = (const bf16*)d_in[1];
    p.wo = (const bf16*)d_in[5];
    p.wr = (const bf16*)d_in[7];
    p.wgate = (const bf16*)d_in[8];
    p.wup = (const bf16*)d_in[9];
    p.wdown = (const bf16*)d_in[10];
    p.c = (const bf16*)d_in[11];
    p.out = (bf16*)d_out;
    p.by_smid = sms == NCTA + NSPARE;
    fused_kernel<<<NCTA + NSPARE, 384, SMEM_BYTES>>>(ckv, wq, wuk, wuv, wo, wg, wu, wd, wm, xm, p);
}
```

```cpp
#include <cuda.h>
#include <cuda_bf16.h>
#include <cuda_runtime.h>
#include <stdint.h>
#include <stdio.h>

namespace {

typedef __nv_bfloat16 bf16;
typedef unsigned long long u64;

constexpr int NCTA = 128, NSPARE = 4;
constexpr int SLOT = 32768;
constexpr int SM_BAR = 7 * SLOT;
constexpr int BAR_FULL = SM_BAR;
constexpr int BAR_EMPTY = BAR_FULL + 8 * 7;
constexpr int BAR_DONE = BAR_EMPTY + 8 * 7;
constexpr int BAR_FLAG = BAR_DONE + 8 * 9;
constexpr int BAR_PF = BAR_FLAG + 8 * 9;
constexpr int BAR_END = BAR_PF + 8;
constexpr int SM_EP = BAR_END + 8;
constexpr int SM_RED = SM_BAR + 384;
constexpr int SM_TAB = SM_BAR + 1024;
constexpr int SMEM_BYTES = SM_BAR + 3072;
constexpr int NFFN = 112;
#define HINT 29
constexpr u64 L2_NORMAL = 0x1000000000000000ull, L2_FIRST = 0x12F0000000000000ull;
#define PF0 0
#define PF1 13
#define PF2 11
#define UNR 4
#define PARKS 7
#define POLL_NS 50
#define CLAST 2
#define EARLY 7
constexpr uint32_t SPIN_LIMIT = 1u << 22;
constexpr uint32_t ONE2 = 0x3f803f80u;

struct Sync {
    uint32_t modcnt[2 * 32];
    uint32_t hcnt[16 * 8];
    uint32_t kvcnt[32 * 2 * 8];
    uint32_t ctxcnt[16 * 32];
    uint32_t rdcnt[16 * 2 * 8];
    uint32_t epoch[32];
};

__device__ __align__(1024) uint8_t g_KV[16 * 16 * 2 * SLOT];
__device__ __align__(1024) uint8_t g_ctx[16 * 32 * SLOT];
__device__ __align__(1024) uint8_t g_h[16 * 4 * SLOT];
__device__ __align__(1024) uint4 g_part[128 * 1024];
__device__ __align__(1024) uint4 g_stat[2048 * 4];
__device__ __align__(1024) bf16 g_mod[3072];
__device__ __align__(1024) uint4 g_cand[128 * 192];
__device__ __align__(1024) uint32_t g_key[4 * 128];
__device__ __align__(1024) uint32_t g_act[1792];
__device__ __align__(1024) Sync g_sync;
#define TS(i)

#define PT()

struct Params {
    const bf16 *x, *ckv, *wo, *wr, *wgate, *wup, *wdown, *c;
    bf16* out;
    int by_smid;
};

__device__ __forceinline__ void mbar_init(uint32_t bar, uint32_t cnt) {
    asm volatile("mbarrier.init.shared::cta.b64 [%0], %1;" ::"r"(bar), "r"(cnt) : "memory");
}
__device__ __forceinline__ void mbar_wait(uint32_t bar, uint32_t parity) {
    asm volatile("{\n.reg .pred p;\nL_%=:\nmbarrier.try_wait.parity.shared::cta.b64 p, [%0], %1;\n@!p bra L_%=;\n}" ::"r"(bar), "r"(parity) : "memory");
}
__device__ __forceinline__ void mbar_watch(uint32_t bar, uint32_t parity) {
    asm volatile("{\n.reg .pred p;\n.reg .u32 n;\nmov.u32 n, 0;\n"
                 "L_%=:\nmbarrier.try_wait.parity.shared::cta.b64 p, [%0], %1;\n@p bra D_%=;\n"
                 "add.u32 n, n, 1;\nsetp.lt.u32 p, n, %2;\n@p bra L_%=;\ntrap;\nD_%=:\n}"
                 ::"r"(bar), "r"(parity), "n"(SPIN_LIMIT) : "memory");
}
__device__ __forceinline__ void mbar_arrive(uint32_t bar) {
    asm volatile("mbarrier.arrive.shared::cta.b64 _, [%0];" ::"r"(bar) : "memory");
}
__device__ __forceinline__ void mbar_arrive_if(uint32_t bar, bool on) {
    asm volatile("{\n.reg .pred p;\nsetp.ne.s32 p, %1, 0;\n@p mbarrier.arrive.shared::cta.b64 _, [%0];\n}" ::"r"(bar), "r"((int)on) : "memory");
}
__device__ __forceinline__ void mbar_expect(uint32_t bar, uint32_t bytes) {
    asm volatile("mbarrier.arrive.expect_tx.shared::cta.b64 _, [%0], %1;" ::"r"(bar), "r"(bytes) : "memory");
}
__device__ __forceinline__ void tma2d(uint32_t dst, const CUtensorMap* m, int c0, int c1, uint32_t bar) {
    asm volatile("cp.async.bulk.tensor.2d.shared::cluster.global.mbarrier::complete_tx::bytes [%0], [%1, {%3, %4}], [%2];"
                 ::"r"(dst), "l"(m), "r"(bar), "r"(c0), "r"(c1) : "memory");
}
__device__ __forceinline__ void tma3d_prefetch(const CUtensorMap* m, int row, int cb) {
    asm volatile("cp.async.bulk.prefetch.tensor.3d.L2.global [%0, {%1, %2, %3}];" ::"l"(m), "r"(0), "r"(row), "r"(cb) : "memory");
}
__device__ __forceinline__ void l2_prefetch(const void* p, uint32_t bytes) {
    asm volatile("cp.async.bulk.prefetch.L2.global [%0], %1;" ::"l"(p), "r"(bytes) : "memory");
}
__device__ __forceinline__ void flag_wait(const uint32_t* f, uint32_t target) {
    asm volatile("{\n.reg .pred p;\n.reg .u32 v;\n"
                 "L_%=:\nld.acquire.gpu.global.u32 v, [%0];\nsub.u32 v, v, %1;\nsetp.lt.s32 p, v, 0;\n@p nanosleep.u32 100;\n@p bra L_%=;\n}"
                 ::"l"(f), "r"(target) : "memory");
}
__device__ __forceinline__ uint4 ld_poll(const uint4* p) {
    uint4 v;
    asm volatile("ld.relaxed.gpu.global.v4.u32 {%0, %1, %2, %3}, [%4];" : "=r"(v.x), "=r"(v.y), "=r"(v.z), "=r"(v.w) : "l"(p) : "memory");
    return v;
}
__device__ __forceinline__ uint2 ld_poll(const uint2* p) {
    uint2 v;
    asm volatile("ld.relaxed.gpu.global.v2.u32 {%0, %1}, [%2];" : "=r"(v.x), "=r"(v.y) : "l"(p) : "memory");
    return v;
}
__device__ __forceinline__ void st_pub(uint4* p, uint4 v, bool on) {
    asm volatile("{\n.reg .pred p;\nsetp.ne.s32 p, %5, 0;\n@p st.relaxed.gpu.global.v4.u32 [%0], {%1, %2, %3, %4};\n}"
                 ::"l"(p), "r"(v.x), "r"(v.y), "r"(v.z), "r"(v.w), "r"((int)on) : "memory");
}
__device__ __forceinline__ void st_pub(uint32_t* p, uint32_t v, bool on) {
    asm volatile("{\n.reg .pred p;\nsetp.ne.s32 p, %2, 0;\n@p st.relaxed.gpu.global.u32 [%0], %1;\n}" ::"l"(p), "r"(v), "r"((int)on) : "memory");
}
__device__ __forceinline__ void flag_add(uint32_t* p) {
    asm volatile("red.release.gpu.global.add.u32 [%0], 1;" ::"l"(p) : "memory");
}
__device__ __forceinline__ uint32_t lds32(uint32_t a) {
    uint32_t v;
    asm volatile("ld.shared.u32 %0, [%1];" : "=r"(v) : "r"(a) : "memory");
    return v;
}
__device__ __forceinline__ uint4 lds128(uint32_t a) {
    uint4 v;
    asm volatile("ld.shared.v4.u32 {%0, %1, %2, %3}, [%4];" : "=r"(v.x), "=r"(v.y), "=r"(v.z), "=r"(v.w) : "r"(a) : "memory");
    return v;
}
__device__ __forceinline__ void fence_async_global() { asm volatile("fence.proxy.async.global;" ::: "memory"); }
__device__ __forceinline__ void fence_async_smem() { asm volatile("fence.proxy.async.shared::cta;" ::: "memory"); }
__device__ __forceinline__ void bar_sync(int id, int n) { asm volatile("bar.sync %0, %1;" ::"r"(id), "r"(n) : "memory"); }
__device__ __forceinline__ void bar_arrive(int id, int n) { asm volatile("bar.arrive %0, %1;" ::"r"(id), "r"(n) : "memory"); }
__device__ __forceinline__ void wg_fence() { asm volatile("wgmma.fence.sync.aligned;" ::: "memory"); }
__device__ __forceinline__ void wg_commit() { asm volatile("wgmma.commit_group.sync.aligned;" ::: "memory"); }
template <int N> __device__ __forceinline__ void wg_wait() { asm volatile("wgmma.wait_group.sync.aligned %0;" ::"n"(N) : "memory"); }
template <int N> __device__ __forceinline__ void reg_fence(float (&d)[N]) {
#pragma unroll
    for (int i = 0; i < N; i++) asm volatile("" : "+f"(d[i])::"memory");
}
template <int N> __device__ __forceinline__ void reg_fence(uint32_t (&d)[N]) {
#pragma unroll
    for (int i = 0; i < N; i++) asm volatile("" : "+r"(d[i])::"memory");
}
__device__ __forceinline__ uint32_t desc_k(uint32_t a) { return (a >> 4) | (1u << 16); }
__device__ __forceinline__ uint32_t desc_mn(uint32_t a) { return (a >> 4) | (1024u << 16); }

template <int TB>
__device__ __forceinline__ void wgmma_ss128(float (&d)[64], uint32_t da, uint32_t db, int acc, uint32_t ha = 0x40000040u, uint32_t hb = 0x40000040u) {
    asm volatile("{\n.reg .pred p;\n.reg .b64 a, b;\nsetp.ne.b32 p, %66, 0;\nmov.b64 a, {%64, %68};\nmov.b64 b, {%65, %69};\n"
        "wgmma.mma_async.sync.aligned.m64n128k16.f32.bf16.bf16 {%0, %1, %2, %3, %4, %5, %6, %7, %8, %9, %10, %11, %12, %13, %14, %15, %16, %17, %18, %19, %20, %21, %22, %23, %24, %25, %26, %27, %28, %29, %30, %31, %32, %33, %34, %35, %36, %37, %38, %39, %40, %41, %42, %43, %44, %45, %46, %47, %48, %49, %50, %51, %52, %53, %54, %55, %56, %57, %58, %59, %60, %61, %62, %63}, a, b, p, 1, 1, 0, %67;\n}"
        : "+f"(d[0]), "+f"(d[1]), "+f"(d[2]), "+f"(d[3]), "+f"(d[4]), "+f"(d[5]), "+f"(d[6]), "+f"(d[7]), "+f"(d[8]), "+f"(d[9]), "+f"(d[10]), "+f"(d[11]), "+f"(d[12]), "+f"(d[13]), "+f"(d[14]), "+f"(d[15]), "+f"(d[16]), "+f"(d[17]), "+f"(d[18]), "+f"(d[19]), "+f"(d[20]), "+f"(d[21]), "+f"(d[22]), "+f"(d[23]), "+f"(d[24]), "+f"(d[25]), "+f"(d[26]), "+f"(d[27]), "+f"(d[28]), "+f"(d[29]), "+f"(d[30]), "+f"(d[31]), "+f"(d[32]), "+f"(d[33]), "+f"(d[34]), "+f"(d[35]), "+f"(d[36]), "+f"(d[37]), "+f"(d[38]), "+f"(d[39]), "+f"(d[40]), "+f"(d[41]), "+f"(d[42]), "+f"(d[43]), "+f"(d[44]), "+f"(d[45]), "+f"(d[46]), "+f"(d[47]), "+f"(d[48]), "+f"(d[49]), "+f"(d[50]), "+f"(d[51]), "+f"(d[52]), "+f"(d[53]), "+f"(d[54]), "+f"(d[55]), "+f"(d[56]), "+f"(d[57]), "+f"(d[58]), "+f"(d[59]), "+f"(d[60]), "+f"(d[61]), "+f"(d[62]), "+f"(d[63])
        : "r"(da), "r"(db), "r"(acc), "n"(TB), "r"(ha), "r"(hb));
}
template <int TB>
__device__ __forceinline__ void wgmma_ss128_init(float (&d)[64], uint32_t da, uint32_t db, uint32_t ha = 0x40000040u, uint32_t hb = 0x40000040u) {
    asm volatile("{\n.reg .pred p;\n.reg .b64 a, b;\nsetp.ne.b32 p, 0, 0;\nmov.b64 a, {%64, %67};\nmov.b64 b, {%65, %68};\n"
        "wgmma.mma_async.sync.aligned.m64n128k16.f32.bf16.bf16 {%0, %1, %2, %3, %4, %5, %6, %7, %8, %9, %10, %11, %12, %13, %14, %15, %16, %17, %18, %19, %20, %21, %22, %23, %24, %25, %26, %27, %28, %29, %30, %31, %32, %33, %34, %35, %36, %37, %38, %39, %40, %41, %42, %43, %44, %45, %46, %47, %48, %49, %50, %51, %52, %53, %54, %55, %56, %57, %58, %59, %60, %61, %62, %63}, a, b, p, 1, 1, 0, %66;\n}"
        : "=f"(d[0]), "=f"(d[1]), "=f"(d[2]), "=f"(d[3]), "=f"(d[4]), "=f"(d[5]), "=f"(d[6]), "=f"(d[7]), "=f"(d[8]), "=f"(d[9]), "=f"(d[10]), "=f"(d[11]), "=f"(d[12]), "=f"(d[13]), "=f"(d[14]), "=f"(d[15]), "=f"(d[16]), "=f"(d[17]), "=f"(d[18]), "=f"(d[19]), "=f"(d[20]), "=f"(d[21]), "=f"(d[22]), "=f"(d[23]), "=f"(d[24]), "=f"(d[25]), "=f"(d[26]), "=f"(d[27]), "=f"(d[28]), "=f"(d[29]), "=f"(d[30]), "=f"(d[31]), "=f"(d[32]), "=f"(d[33]), "=f"(d[34]), "=f"(d[35]), "=f"(d[36]), "=f"(d[37]), "=f"(d[38]), "=f"(d[39]), "=f"(d[40]), "=f"(d[41]), "=f"(d[42]), "=f"(d[43]), "=f"(d[44]), "=f"(d[45]), "=f"(d[46]), "=f"(d[47]), "=f"(d[48]), "=f"(d[49]), "=f"(d[50]), "=f"(d[51]), "=f"(d[52]), "=f"(d[53]), "=f"(d[54]), "=f"(d[55]), "=f"(d[56]), "=f"(d[57]), "=f"(d[58]), "=f"(d[59]), "=f"(d[60]), "=f"(d[61]), "=f"(d[62]), "=f"(d[63])
        : "r"(da), "r"(db), "n"(TB), "r"(ha), "r"(hb));
}
template <int TB>
__device__ __forceinline__ void wgmma_ss64(float (&d)[32], uint32_t da, uint32_t db, int acc, uint32_t ha = 0x40000040u, uint32_t hb = 0x40000040u) {
    asm volatile("{\n.reg .pred p;\n.reg .b64 a, b;\nsetp.ne.b32 p, %34, 0;\nmov.b64 a, {%32, %36};\nmov.b64 b, {%33, %37};\n"
        "wgmma.mma_async.sync.aligned.m64n64k16.f32.bf16.bf16 {%0, %1, %2, %3, %4, %5, %6, %7, %8, %9, %10, %11, %12, %13, %14, %15, %16, %17, %18, %19, %20, %21, %22, %23, %24, %25, %26, %27, %28, %29, %30, %31}, a, b, p, 1, 1, 0, %35;\n}"
        : "+f"(d[0]), "+f"(d[1]), "+f"(d[2]), "+f"(d[3]), "+f"(d[4]), "+f"(d[5]), "+f"(d[6]), "+f"(d[7]), "+f"(d[8]), "+f"(d[9]), "+f"(d[10]), "+f"(d[11]), "+f"(d[12]), "+f"(d[13]), "+f"(d[14]), "+f"(d[15]), "+f"(d[16]), "+f"(d[17]), "+f"(d[18]), "+f"(d[19]), "+f"(d[20]), "+f"(d[21]), "+f"(d[22]), "+f"(d[23]), "+f"(d[24]), "+f"(d[25]), "+f"(d[26]), "+f"(d[27]), "+f"(d[28]), "+f"(d[29]), "+f"(d[30]), "+f"(d[31])
        : "r"(da), "r"(db), "r"(acc), "n"(TB), "r"(ha), "r"(hb));
}
template <int TB>
__device__ __forceinline__ void wgmma_ss64_init(float (&d)[32], uint32_t da, uint32_t db, uint32_t ha = 0x40000040u, uint32_t hb = 0x40000040u) {
    asm volatile("{\n.reg .pred p;\n.reg .b64 a, b;\nsetp.ne.b32 p, 0, 0;\nmov.b64 a, {%32, %35};\nmov.b64 b, {%33, %36};\n"
        "wgmma.mma_async.sync.aligned.m64n64k16.f32.bf16.bf16 {%0, %1, %2, %3, %4, %5, %6, %7, %8, %9, %10, %11, %12, %13, %14, %15, %16, %17, %18, %19, %20, %21, %22, %23, %24, %25, %26, %27, %28, %29, %30, %31}, a, b, p, 1, 1, 0, %34;\n}"
        : "=f"(d[0]), "=f"(d[1]), "=f"(d[2]), "=f"(d[3]), "=f"(d[4]), "=f"(d[5]), "=f"(d[6]), "=f"(d[7]), "=f"(d[8]), "=f"(d[9]), "=f"(d[10]), "=f"(d[11]), "=f"(d[12]), "=f"(d[13]), "=f"(d[14]), "=f"(d[15]), "=f"(d[16]), "=f"(d[17]), "=f"(d[18]), "=f"(d[19]), "=f"(d[20]), "=f"(d[21]), "=f"(d[22]), "=f"(d[23]), "=f"(d[24]), "=f"(d[25]), "=f"(d[26]), "=f"(d[27]), "=f"(d[28]), "=f"(d[29]), "=f"(d[30]), "=f"(d[31])
        : "r"(da), "r"(db), "n"(TB), "r"(ha), "r"(hb));
}
__device__ __forceinline__ void wgmma_rs128(float (&d)[64], uint32_t a0, uint32_t a1, uint32_t a2, uint32_t a3, uint32_t db, int acc, uint32_t hb = 0x40000040u) {
    asm volatile("{\n.reg .pred p;\n.reg .b64 b;\nsetp.ne.b32 p, %69, 0;\nmov.b64 b, {%68, %70};\n"
        "wgmma.mma_async.sync.aligned.m64n128k16.f32.bf16.bf16 {%0, %1, %2, %3, %4, %5, %6, %7, %8, %9, %10, %11, %12, %13, %14, %15, %16, %17, %18, %19, %20, %21, %22, %23, %24, %25, %26, %27, %28, %29, %30, %31, %32, %33, %34, %35, %36, %37, %38, %39, %40, %41, %42, %43, %44, %45, %46, %47, %48, %49, %50, %51, %52, %53, %54, %55, %56, %57, %58, %59, %60, %61, %62, %63}, {%64, %65, %66, %67}, b, p, 1, 1, 1;\n}"
        : "+f"(d[0]), "+f"(d[1]), "+f"(d[2]), "+f"(d[3]), "+f"(d[4]), "+f"(d[5]), "+f"(d[6]), "+f"(d[7]), "+f"(d[8]), "+f"(d[9]), "+f"(d[10]), "+f"(d[11]), "+f"(d[12]), "+f"(d[13]), "+f"(d[14]), "+f"(d[15]), "+f"(d[16]), "+f"(d[17]), "+f"(d[18]), "+f"(d[19]), "+f"(d[20]), "+f"(d[21]), "+f"(d[22]), "+f"(d[23]), "+f"(d[24]), "+f"(d[25]), "+f"(d[26]), "+f"(d[27]), "+f"(d[28]), "+f"(d[29]), "+f"(d[30]), "+f"(d[31]), "+f"(d[32]), "+f"(d[33]), "+f"(d[34]), "+f"(d[35]), "+f"(d[36]), "+f"(d[37]), "+f"(d[38]), "+f"(d[39]), "+f"(d[40]), "+f"(d[41]), "+f"(d[42]), "+f"(d[43]), "+f"(d[44]), "+f"(d[45]), "+f"(d[46]), "+f"(d[47]), "+f"(d[48]), "+f"(d[49]), "+f"(d[50]), "+f"(d[51]), "+f"(d[52]), "+f"(d[53]), "+f"(d[54]), "+f"(d[55]), "+f"(d[56]), "+f"(d[57]), "+f"(d[58]), "+f"(d[59]), "+f"(d[60]), "+f"(d[61]), "+f"(d[62]), "+f"(d[63])
        : "r"(a0), "r"(a1), "r"(a2), "r"(a3), "r"(db), "r"(acc), "r"(hb));
}

__device__ __forceinline__ uint32_t pack2(float lo, float hi) {
    uint32_t r;
    asm("cvt.rn.bf16x2.f32 %0, %1, %2;" : "=r"(r) : "f"(hi), "f"(lo));
    return r;
}
__device__ __forceinline__ float bf_lo(uint32_t v) { return __uint_as_float(v << 16); }
__device__ __forceinline__ float bf_hi(uint32_t v) { return __uint_as_float(v & 0xffff0000u); }
__device__ __forceinline__ float rbf(float v) { return bf_lo(pack2(v, v)); }
__device__ __forceinline__ uint32_t badd(uint32_t a, uint32_t b) {
    uint32_t r;
    asm("add.rn.bf16x2 %0, %1, %2;" : "=r"(r) : "r"(a), "r"(b));
    return r;
}
__device__ __forceinline__ uint32_t bsub(uint32_t a, uint32_t b) {
    uint32_t r;
    asm("sub.rn.bf16x2 %0, %1, %2;" : "=r"(r) : "r"(a), "r"(b));
    return r;
}
__device__ __forceinline__ uint32_t bmul(uint32_t a, uint32_t b) {
    uint32_t r;
    asm("mul.rn.bf16x2 %0, %1, %2;" : "=r"(r) : "r"(a), "r"(b));
    return r;
}
__device__ __forceinline__ uint32_t ln_apply(uint32_t x, uint32_t mb, float rs, uint32_t scale, uint32_t shift) {
    const uint32_t d = bsub(x, mb);
    return badd(bmul(pack2(bf_lo(d) * rs, bf_hi(d) * rs), scale), shift);
}
__device__ __forceinline__ float ex2(float v) {
    float r;
    asm("ex2.approx.ftz.f32 %0, %1;" : "=f"(r) : "f"(v));
    return r;
}
__device__ __forceinline__ float rcp(float v) {
    float r;
    asm("rcp.approx.ftz.f32 %0, %1;" : "=f"(r) : "f"(v));
    return r;
}
__device__ __forceinline__ float sqrt_fast(float v) {
    float r;
    asm("sqrt.approx.ftz.f32 %0, %1;" : "=f"(r) : "f"(v));
    return r;
}
__device__ __forceinline__ float ln_rstd(float var) { return rcp(rbf(sqrt_fast(rbf(rbf(var) + 1e-5f)))); }
__device__ __forceinline__ float sigmoid(float v) { return rcp(1.f + ex2(-1.4426950408889634f * v)); }
__device__ __forceinline__ float warp_sum(float v) {
#pragma unroll
    for (int o = 16; o > 0; o >>= 1) v += __shfl_xor_sync(0xffffffffu, v, o);
    return v;
}
__device__ __forceinline__ float quad_sum(float v) {
    v += __shfl_xor_sync(0xffffffffu, v, 1);
    return v + __shfl_xor_sync(0xffffffffu, v, 2);
}

constexpr uint32_t HI_128 = 0x40000040u, HI_IMG = 0x80000080u, HI_Q = 0x80000040u;
template <int M, int RH>
__device__ __forceinline__ uint4 img_pack(const float (&d)[64], float s) {
    uint4 v;
    v.x = pack2(d[16 * M + 2 * RH] * s, d[16 * M + 2 * RH + 1] * s);
    v.y = pack2(d[16 * M + 4 + 2 * RH] * s, d[16 * M + 5 + 2 * RH] * s);
    v.z = pack2(d[16 * M + 8 + 2 * RH] * s, d[16 * M + 9 + 2 * RH] * s);
    v.w = pack2(d[16 * M + 12 + 2 * RH] * s, d[16 * M + 13 + 2 * RH] * s);
    return v;
}
template <int M, int RH>
__device__ __forceinline__ uint4 img_pack(const float (&d)[64]) {
    uint4 v;
    v.x = pack2(d[16 * M + 2 * RH], d[16 * M + 2 * RH + 1]);
    v.y = pack2(d[16 * M + 4 + 2 * RH], d[16 * M + 5 + 2 * RH]);
    v.z = pack2(d[16 * M + 8 + 2 * RH], d[16 * M + 9 + 2 * RH]);
    v.w = pack2(d[16 * M + 12 + 2 * RH], d[16 * M + 13 + 2 * RH]);
    return v;
}
template <int M>
__device__ __forceinline__ void img_store_global(uint8_t* img, uint32_t toff, const float (&d)[64], float s0, float s1) {
    uint4* p = reinterpret_cast<uint4*>(img + toff) + M * 32;
    p[0] = img_pack<M, 0>(d, s0);
    p[128] = img_pack<M, 1>(d, s1);
}
__device__ __forceinline__ void sts128(uint32_t a, uint4 v) {
    asm volatile("st.shared.v4.b32 [%0], {%1, %2, %3, %4};" ::"r"(a), "r"(v.x), "r"(v.y), "r"(v.z), "r"(v.w) : "memory");
}
constexpr float SM_C = 0.08838834764831845f * 1.4426950408889634f;
__device__ __forceinline__ float pack2f(float lo, float hi) {
    float r;
    asm("{\n.reg .b32 t;\ncvt.rn.bf16x2.f32 t, %1, %2;\nmov.b32 %0, t;\n}" : "=f"(r) : "f"(hi), "f"(lo));
    return r;
}
template <int M, bool SCALE, bool PARK>
__device__ __forceinline__ void pack_group(float (&d)[64], float (&v)[8], float s0, float s1) {
#pragma unroll
    for (int i = 0; i < 8; i++) {
        const int k = 16 * M + 4 * (i & 3) + 2 * (i >> 2);
        v[i] = SCALE ? pack2f(d[k] * (i < 4 ? s0 : s1), d[k + 1] * (i < 4 ? s0 : s1)) : pack2f(d[k], d[k + 1]);
        if (PARK && M > 0) d[16 * (M > 0 ? M - 1 : 0) + i] = v[i];
    }
}
template <int M, bool PARK>
__device__ __forceinline__ void q_store_part(uint32_t a, float (&d)[64]) {
    float v[8];
    pack_group<M, false, PARK>(d, v, 0.f, 0.f);
#pragma unroll
    for (int h = 0; h < 2; h++)
        asm volatile("st.shared.v4.f32 [%0], {%1, %2, %3, %4};" ::"r"(a + (M >> 1) * 16384 + (M & 1) * 512 + h * 1024),
                     "f"(v[4 * h]), "f"(v[4 * h + 1]), "f"(v[4 * h + 2]), "f"(v[4 * h + 3]) : "memory");
}
template <bool PARK>
__device__ __forceinline__ void q_store(uint32_t a, uint32_t toff, float (&d)[64]) {
    a += (((toff >> 1) & ~2047u) ^ 8192) + (toff & 511);
    q_store_part<0, PARK>(a, d); q_store_part<1, PARK>(a, d); q_store_part<2, PARK>(a, d); q_store_part<3, PARK>(a, d);
}
template <int M, bool PARK>
__device__ __forceinline__ void ctx_store_part(float4* p, float (&d)[64], float i0, float i1) {
    float v[8];
    pack_group<M, true, PARK>(d, v, i0, i1);
    p[M * 32] = make_float4(v[0], v[1], v[2], v[3]);
    p[M * 32 + 128] = make_float4(v[4], v[5], v[6], v[7]);
}
template <bool PARK>
__device__ __forceinline__ void ctx_store(uint8_t* img, uint32_t toff, float (&o)[64], float l0, float l1) {
    const float i0 = rcp(quad_sum(l0)), i1 = rcp(quad_sum(l1));
    float4* p = reinterpret_cast<float4*>(img + toff);
    ctx_store_part<0, PARK>(p, o, i0, i1); ctx_store_part<1, PARK>(p, o, i0, i1); ctx_store_part<2, PARK>(p, o, i0, i1); ctx_store_part<3, PARK>(p, o, i0, i1);
}

__device__ __forceinline__ void slot_wait(uint32_t bars, uint32_t& ph, uint32_t slot) {
    mbar_wait(bars + 8 * slot, (ph >> slot) & 1);
    ph ^= 1u << slot;
}
__device__ __forceinline__ void load_image(uint32_t sb, uint32_t& ph, uint32_t slot, const void* src, bool first) {
    slot_wait(sb + BAR_EMPTY, ph, slot);
    asm volatile("{\n.reg .pred p;\nelect.sync _|p, 0xffffffff;\n@p mbarrier.arrive.expect_tx.shared::cta.b64 _, [%2], 32768;\n"
                 "@p cp.async.bulk.shared::cluster.global.mbarrier::complete_tx::bytes.L2::cache_hint [%0], [%1], 32768, [%2], %3;\n}"
                 ::"r"(sb + slot * SLOT), "l"(src), "r"(sb + BAR_FULL + 8 * slot), "l"(first ? L2_FIRST : L2_NORMAL) : "memory");
}
__device__ __forceinline__ void load_tile(uint32_t sb, uint32_t& ph, uint32_t slot, const CUtensorMap* m, int row, int cb, bool first) {
    slot_wait(sb + BAR_EMPTY, ph, slot);
    asm volatile("{\n.reg .pred p;\nelect.sync _|p, 0xffffffff;\n@p mbarrier.arrive.expect_tx.shared::cta.b64 _, [%2], 32768;\n"
                 "@p cp.async.bulk.tensor.3d.shared::cluster.global.mbarrier::complete_tx::bytes.L2::cache_hint [%0], [%1, {%3, %4, %5}], [%2], %6;\n}"
                 ::"r"(sb + slot * SLOT), "l"(m), "r"(sb + BAR_FULL + 8 * slot), "r"(0), "r"(row), "r"(cb), "l"(first ? L2_FIRST : L2_NORMAL) : "memory");
}
__device__ __forceinline__ uint32_t ring_next(uint32_t r) { return r == 4 ? 0 : r + 1; }
__device__ __forceinline__ uint32_t w_table(int hp) { return hp ? 0x3104u : 0x4210u; }
__device__ __forceinline__ uint32_t a_table(int hp) { return hp ? 0x625u : 0x635u; }
__device__ __forceinline__ uint32_t a_next(uint32_t& t) {
    const uint32_t s = t & 15;
    t = (t >> 4) | (s << 8);
    return s;
}
constexpr uint32_t O_TABLE = 0x2160435u;
__device__ __forceinline__ uint32_t o_next(uint32_t& t) {
    const uint32_t s = t & 15;
    t = (t >> 4) | (s << 24);
    return s;
}
__device__ __forceinline__ int o_head(int i, int kh) { return i < 16 ? 4 * (i & 7) + 2 * (kh ^ 1) + (i >> 3) : 29 + 2 * kh; }

template <bool INIT>
__device__ __forceinline__ void gemm_issue(float (&d)[64], uint32_t a, uint32_t b, int acc, bool img) {
    const uint32_t ha = img ? HI_IMG : HI_128, o2 = img ? 32 : 4, o4 = img ? 64 : 1024;
    wg_fence();
#pragma unroll
    for (int k = 0; k < 8; k++) {
        if (INIT && k == 0) wgmma_ss128_init<1>(d, a, b, ha);
        else wgmma_ss128<1>(d, a + (k >> 2) * o4 + ((k >> 1) & 1) * o2 + (k & 1) * 2, b + k * 128, k ? 1 : acc, ha);
    }
    wg_commit();
}

__device__ __forceinline__ void h_store(const uint32_t* x, float mean, float sq, uint32_t sb, int row) {
    const int lane = threadIdx.x & 31;
    const float rs = ln_rstd(sq * (1.f / 512.f));
    const uint32_t mb = pack2(mean, mean);
    uint8_t* p = g_h + ((row >> 7) * 8 + (lane >> 3)) * 16384 + (row & 127) * 128 + (((lane ^ row) & 7) << 4);
#pragma unroll
    for (int i = 0; i < 2; i++) {
        const uint4 a = lds128(sb + SM_TAB + 1024 + i * 512 + lane * 16), c = lds128(sb + SM_TAB + i * 512 + lane * 16);
        *reinterpret_cast<uint4*>(p + i * 65536) = make_uint4(ln_apply(x[4 * i], mb, rs, a.x, c.x), ln_apply(x[4 * i + 1], mb, rs, a.y, c.y),
                                                              ln_apply(x[4 * i + 2], mb, rs, a.z, c.z), ln_apply(x[4 * i + 3], mb, rs, a.w, c.w));
    }
}

template <bool ODD>
__device__ __forceinline__ void proj_tile(float (&acc)[64], float (&prev)[64], int t, int q0, uint32_t sb, int wg, bool elected, uint32_t& fph,
                                          uint32_t wtab, uint32_t& atab, uint8_t* prev_img, uint32_t toff, float s0, float s1, bool first,
                                          const bf16* x, int xrow) {
    const uint32_t a0 = desc_k(sb + (wg ^ (ODD && t == 5)) * 8192), b0 = desc_mn(sb);
    const int lane = threadIdx.x & 31;
    float mean[2] = {0.f, 0.f}, rstd[2] = {0.f, 0.f};
    uint32_t xn[16];
#pragma unroll
    for (int i = 0; i < 4; i++) {
        uint4 v = make_uint4(0, 0, 0, 0);
        if (ODD && first) v = __ldg(reinterpret_cast<const uint4*>(x) + xrow * 64 + lane + 32 * i);
        xn[4 * i] = v.x; xn[4 * i + 1] = v.y; xn[4 * i + 2] = v.z; xn[4 * i + 3] = v.w;
    }
    constexpr int U = ODD ? UNR : 1;
#pragma unroll U
    for (int q = ODD ? 0 : q0; q < 4; q++) {
        if (ODD && t == 5 && q == 3) break;
        const uint32_t ws = (wtab >> (4 * q)) & 15, as = a_next(atab);
        if (!ODD && t != 2) slot_wait(sb + BAR_FULL, fph, ws);
        slot_wait(sb + BAR_FULL, fph, as);
        bar_sync(1 + wg, 256);
        gemm_issue<false>(acc, a0 + as * (SLOT / 16), b0 + ws * (SLOT / 16), q, false);
        bar_arrive(2 - wg, 256);
        wg_wait<1>();
        reg_fence(prev);
        if (ODD && t == 5) {
            if (q == 2) {
                q_store<false>(sb + 5 * SLOT, toff, prev);
                fence_async_smem();
            }
        } else if (ODD || !first) {
            if (q == 0) img_store_global<0>(prev_img, toff, prev, s0, s1);
            if (q == 1) img_store_global<1>(prev_img, toff, prev, s0, s1);
            if (q == 2) img_store_global<2>(prev_img, toff, prev, s0, s1);
            if (q == 3) img_store_global<3>(prev_img, toff, prev, s0, s1);
        }
        if (ODD && q == 1 && first) {
#pragma unroll
            for (int k = 0; k < 16; k++) mean[k >> 3] += bf_lo(xn[k]) + bf_hi(xn[k]);
#pragma unroll
            for (int i = 0; i < 2; i++) mean[i] = warp_sum(mean[i]) * (1.f / 512.f);
        }
        if (ODD && q == 2 && first) {
#pragma unroll
            for (int k = 0; k < 16; k++) {
                const float d0 = bf_lo(xn[k]) - mean[k >> 3], d1 = bf_hi(xn[k]) - mean[k >> 3];
                rstd[k >> 3] = fmaf(d0, d0, fmaf(d1, d1, rstd[k >> 3]));
            }
#pragma unroll
            for (int i = 0; i < 2; i++) rstd[i] = warp_sum(rstd[i]);
        }
        if (ODD && q == 3 && first) {
            mbar_wait(sb + BAR_FLAG + 8 * 8, 0);
            h_store(xn, mean[0], rstd[0], sb, xrow);
        }
        wg_wait<0>();
        mbar_arrive_if(sb + BAR_EMPTY + 8 * as, elected && !(ODD && (q & 1) && t == 5));
        if (ODD) mbar_arrive_if(sb + BAR_EMPTY + 8 * ws, elected && t != 1);
        if (ODD && q == 3 && first) {
            h_store(xn + 8, mean[1], rstd[1], sb, xrow + 1);
            __syncwarp();
            mbar_arrive_if(sb + BAR_DONE, lane == 0);
        }
    }
    reg_fence(acc);
}

__device__ __forceinline__ void qk_issue(float (&s)[64], uint32_t q, uint32_t k) {
    wg_fence();
    wgmma_ss128_init<0>(s, q, k, HI_Q, HI_IMG);
#pragma unroll
    for (int i = 1; i < 8; i++) wgmma_ss128<0>(s, q + (i >> 2) * 1024 + (i & 2) * 16 + (i & 1) * 2, k + (i >> 1) * 32 + (i & 1) * 2, 1, HI_Q, HI_IMG);
    wg_commit();
}
__device__ __forceinline__ void qk_issue(float (&s)[32], uint32_t q, uint32_t k) {
    wg_fence();
    wgmma_ss64_init<0>(s, q, k, HI_Q, HI_IMG);
#pragma unroll
    for (int i = 1; i < 8; i++) wgmma_ss64<0>(s, q + (i >> 2) * 1024 + (i & 2) * 16 + (i & 1) * 2, k + (i >> 1) * 32 + (i & 1) * 2, 1, HI_Q, HI_IMG);
    wg_commit();
}
__device__ __forceinline__ void pv_issue(float (&o)[64], const uint32_t (&p)[32], uint32_t v, int acc, bool half) {
    if (half) {
        asm volatile("// half" ::: "memory");
        wg_fence();
#pragma unroll
        for (int i = 0; i < 4; i++) wgmma_rs128(o, p[4 * i], p[4 * i + 1], p[4 * i + 2], p[4 * i + 3], v + i * 256, i ? 1 : acc, HI_IMG);
        wg_commit();
        asm volatile("// half" ::: "memory");
    } else {
        wg_fence();
#pragma unroll
        for (int i = 0; i < 8; i++) wgmma_rs128(o, p[4 * i], p[4 * i + 1], p[4 * i + 2], p[4 * i + 3], v + i * 256, i ? 1 : acc, HI_IMG);
        wg_commit();
    }
}
template <int B, int N>
__device__ __forceinline__ void tri_mask(float (&s)[N], int x) {
#pragma unroll
    for (int k = 0; k < 7; k++)
        asm("{\n.reg .pred p, q;\nsetp.lt.s32 p, %4, %5;\nsetp.le.s32 q, %4, %5;\n"
            "@p mov.b32 %0, 0fFF800000;\n@q mov.b32 %1, 0fFF800000;\n@p mov.b32 %2, 0fFF800000;\n@q mov.b32 %3, 0fFF800000;\n}"
            : "+f"(s[B + 4 * k]), "+f"(s[B + 4 * k + 1]), "+f"(s[B + 4 * k + 6]), "+f"(s[B + 4 * k + 7]) : "r"(x), "r"(8 * k));
    asm("{\n.reg .pred p, q;\nsetp.lt.s32 p, %2, 56;\nsetp.le.s32 q, %2, 56;\n@p mov.b32 %0, 0fFF800000;\n@q mov.b32 %1, 0fFF800000;\n}"
        : "+f"(s[B + 28]), "+f"(s[B + 29]) : "r"(x));
}
__device__ __forceinline__ void tri_mask_copy(float (&s)[64], const float (&h)[32], int x) {
#pragma unroll
    for (int i = 0; i < 32; i++) {
        asm("{\n.reg .pred p;\nsetp.lt.s32 p, %2, %3;\nselp.f32 %0, 0fFF800000, %1, p;\n}"
            : "=f"(s[i]) : "f"(h[i]), "r"(x), "r"(8 * (i >> 2) - 4 * (i & 2) + (i & 1)));
        s[32 + i] = __uint_as_float(0xff800000u);
    }
}
constexpr float SM_HI = 1152921504606846976.f, SM_LO = 1.f / 1152921504606846976.f;
__device__ __forceinline__ bool softmax_unsafe(float t0, float t1, bool first) {
    bool bad = __any_sync(0xffffffffu, fmaxf(t0, t1) > SM_HI);
    if (first) {
        uint32_t a = __ballot_sync(0xffffffffu, t0 >= SM_LO), b = __ballot_sync(0xffffffffu, t1 >= SM_LO);
        a |= a >> 1;
        b |= b >> 1;
        bad |= ((a | (a >> 2)) & (b | (b >> 2)) & 0x11111111u) != 0x11111111u;
    }
    return bad;
}
__device__ __forceinline__ void softmax_shift(float (&s)[64], float d0, float d1) {
#pragma unroll
    for (int i = 0; i < 64; i++) s[i] -= (i & 2) ? d1 : d0;
}
__device__ __forceinline__ void softmax_remax(float (&s)[64], float (&m)[2], bool first, float& a0, float& a1) {
    float m0 = fmaxf(s[0], s[1]), m1 = fmaxf(s[2], s[3]);
#pragma unroll
    for (int k = 1; k < 16; k++) {
        m0 = fmaxf(m0, fmaxf(s[4 * k], s[4 * k + 1]));
        m1 = fmaxf(m1, fmaxf(s[4 * k + 2], s[4 * k + 3]));
    }
    m0 = fmaxf(m0, __shfl_xor_sync(0xffffffffu, m0, 1));
    m1 = fmaxf(m1, __shfl_xor_sync(0xffffffffu, m1, 1));
    m0 = fmaxf(m0, __shfl_xor_sync(0xffffffffu, m0, 2));
    m1 = fmaxf(m1, __shfl_xor_sync(0xffffffffu, m1, 2));
    if (!first) {
        m0 = fmaxf(m0, 0.f);
        m1 = fmaxf(m1, 0.f);
    }
    a0 = first ? 1.f : ex2(-m0);
    a1 = first ? 1.f : ex2(-m1);
    m[0] += m0;
    m[1] += m1;
    softmax_shift(s, m0, m1);
}
template <int J0, int J1>
__device__ __forceinline__ void softmax_exp(const float (&s)[64], uint32_t (&p)[32], float (&t)[4]) {
#pragma unroll
    for (int k = J0; k < J1; k++) {
        const float e0 = ex2(s[4 * k]), e1 = ex2(s[4 * k + 1]), e2 = ex2(s[4 * k + 2]), e3 = ex2(s[4 * k + 3]);
        if (k == 0) { t[0] = e0; t[1] = e1; t[2] = e2; t[3] = e3; }
        else { t[0] += e0; t[1] += e1; t[2] += e2; t[3] += e3; }
        p[2 * k] = pack2(e0, e1);
        p[2 * k + 1] = pack2(e2, e3);
    }
}
__device__ __forceinline__ void fma8(float (&acc)[8], float a, uint4 w) {
    acc[0] = fmaf(a, bf_lo(w.x), acc[0]); acc[1] = fmaf(a, bf_hi(w.x), acc[1]);
    acc[2] = fmaf(a, bf_lo(w.y), acc[2]); acc[3] = fmaf(a, bf_hi(w.y), acc[3]);
    acc[4] = fmaf(a, bf_lo(w.z), acc[4]); acc[5] = fmaf(a, bf_hi(w.z), acc[5]);
    acc[6] = fmaf(a, bf_lo(w.w), acc[6]); acc[7] = fmaf(a, bf_hi(w.w), acc[7]);
}
__device__ __forceinline__ void mma16816(float (&d)[4], const uint32_t* a, uint32_t b0, uint32_t b1) {
    asm("mma.sync.aligned.m16n8k16.row.col.f32.bf16.bf16.f32 {%0, %1, %2, %3}, {%4, %5, %6, %7}, {%8, %9}, {%0, %1, %2, %3};"
        : "+f"(d[0]), "+f"(d[1]), "+f"(d[2]), "+f"(d[3]) : "r"(a[0]), "r"(a[1]), "r"(a[2]), "r"(a[3]), "r"(b0), "r"(b1));
}
__device__ __forceinline__ uint32_t best_key(const uint32_t* keys, int lane, uint32_t ep) {
    uint32_t best;
#pragma unroll 1
    for (;;) {
        const uint4 k = ld_poll(reinterpret_cast<const uint4*>(keys) + lane);
        best = max(max(k.x, k.y), max(k.z, k.w));
        if (__all_sync(0xffffffffu, (((k.x ^ ep) | (k.y ^ ep) | (k.z ^ ep) | (k.w ^ ep)) & 31) == 0)) break;
    }
    return __reduce_max_sync(0xffffffffu, best);
}

__global__ void __launch_bounds__(384, 1)
fused_kernel(const __grid_constant__ CUtensorMap tm_ckv, const __grid_constant__ CUtensorMap tm_wq,
             const __grid_constant__ CUtensorMap tm_wuk, const __grid_constant__ CUtensorMap tm_wuv,
             const __grid_constant__ CUtensorMap tm_wo, const __grid_constant__ CUtensorMap tm_wg,
             const __grid_constant__ CUtensorMap tm_wu, const __grid_constant__ CUtensorMap tm_wd,
             const __grid_constant__ CUtensorMap tm_wm, const __grid_constant__ CUtensorMap tm_x, const Params P) {
    extern __shared__ __align__(1024) uint8_t smem[];
    const uint32_t sb = (uint32_t)__cvta_generic_to_shared(smem);
    const int tid = threadIdx.x, lane = tid & 31, warp = __shfl_sync(0xffffffffu, tid >> 5, 0), wg = warp >> 2;
    uint32_t sm;
    asm("mov.u32 %0, %%smid;" : "=r"(sm));
    const uint32_t smq = ((sm - 64) * 147) >> 11;
    const int rb = !P.by_smid ? blockIdx.x : sm < 64 ? (sm & 14) * 8 + (sm >> 4) * 2 + (sm & 1)
                 : sm < 120 ? ((sm - 64 - smq * 14) & 14) * 8 + 24 + smq * 2 + (sm & 1) : sm < 124 ? sm + 8 : sm - 116;
    const int grp = rb >> 3, j = rb & 7, cq = j & 3, kh = grp & 1, ort = (grp & 14) + (j >> 2);
    if (warp == 0) TS(0);

    if (rb >= NCTA) {
        float* sc = reinterpret_cast<float*>(smem + 6 * SLOT);
        float* red = sc + 512;
        if (tid == 256) {
            for (int i = 0; i < 6; i++) { mbar_init(sb + BAR_FULL + 8 * i, 1); mbar_init(sb + BAR_EMPTY + 8 * i, 8); }
            fence_async_smem();
        }
        __syncthreads();
        uint32_t ph = 0, sl = 0;
        if (tid == 256) {
#pragma unroll 1
            for (int i = 0; i < 24; i++) {
                mbar_wait(sb + BAR_EMPTY + 8 * sl, ph ^ 1);
                mbar_expect(sb + BAR_FULL + 8 * sl, SLOT);
                tma2d(sb + sl * SLOT, &tm_wm, (i >> 3) * 1024 + (rb - NCTA) * 256, (i & 7) * 64, sb + BAR_FULL + 8 * sl);
                if (++sl == 6) { sl = 0; ph ^= 1; }
            }
        } else if (tid < 256) {
            const uint32_t c2 = __ldg(reinterpret_cast<const uint32_t*>(P.c) + tid);
            sc[2 * tid] = rbf(bf_lo(c2) * sigmoid(bf_lo(c2)));
            sc[2 * tid + 1] = rbf(bf_hi(c2) * sigmoid(bf_hi(c2)));
            bar_sync(1, 256);
#pragma unroll 1
            for (int ps = 0; ps < 3; ps++) {
                float acc[8] = {0.f, 0.f, 0.f, 0.f, 0.f, 0.f, 0.f, 0.f};
#pragma unroll 1
                for (int bt = 0; bt < 8; bt++) {
                    mbar_wait(sb + BAR_FULL + 8 * sl, ph);
#pragma unroll
                    for (int i = 0; i < 8; i++)
                        fma8(acc, sc[bt * 64 + warp * 8 + i], *reinterpret_cast<const uint4*>(smem + sl * SLOT + (warp * 8 + i) * 512 + lane * 16));
                    __syncwarp();
                    mbar_arrive_if(sb + BAR_EMPTY + 8 * sl, lane == 0);
                    if (++sl == 6) { sl = 0; ph ^= 1; }
                }
                *reinterpret_cast<float4*>(red + warp * 256 + lane * 8) = make_float4(acc[0], acc[1], acc[2], acc[3]);
                *reinterpret_cast<float4*>(red + warp * 256 + lane * 8 + 4) = make_float4(acc[4], acc[5], acc[6], acc[7]);
                bar_sync(1, 256);
                float v = 0.f;
#pragma unroll
                for (int i = 0; i < 8; i++) v += red[i * 256 + tid];
                g_mod[ps * 1024 + (rb - NCTA) * 256 + tid] = __float2bfloat16_rn(v);
                bar_sync(1, 256);
                if (tid == 0 && ps != 1) flag_add(&g_sync.modcnt[(ps >> 1) * 32]);
                if (warp == 0) TS(1 + ps);
            }
        }
        return;
    }

    if (tid == 256) {
        if (sb & 1023) __trap();
        asm volatile("prefetch.tensormap [%0];" ::"l"((j & 1) ? &tm_wuv : &tm_wuk) : "memory");
        asm volatile("prefetch.tensormap [%0];" ::"l"(&tm_ckv) : "memory");
        for (int i = 0; i < 7; i++) { mbar_init(sb + BAR_FULL + 8 * i, 1); mbar_init(sb + BAR_EMPTY + 8 * i, 2); }
        for (int i = 0; i < 9; i++) mbar_init(sb + BAR_DONE + 8 * i, 8);
        for (int i = 0; i < 10; i++) mbar_init(sb + BAR_FLAG + 8 * i, 1);
        *reinterpret_cast<uint32_t*>(smem + SM_EP + 4) = 0;
        mbar_init(sb + BAR_END, 8);
        fence_async_smem();
    }
    __syncthreads();

    if (wg == 2) {
        asm volatile("setmaxnreg.dec.sync.aligned.u32 40;");
        if (warp == 8) {
            uint32_t eph = 0x7f, r = 0;
            const CUtensorMap* tw = (j & 1) ? &tm_wuv : &tm_wuk;
#pragma unroll 1
            for (int hp = 0; hp < 2; hp++) {
                const int hc = 4 * grp + 2 * hp;
                uint32_t wtab = w_table(hp), atab = a_table(hp);
#pragma unroll 1
                for (int u = 0; u < 4; u++) {
                    load_tile(sb, eph, (wtab >> (4 * u)) & 15, tw, u * 128, hc, HINT & 1); PT();
                    load_tile(sb, eph, a_next(atab), &tm_ckv, (j >> 1) * 128, u * 2, (HINT & 8) && hp); PT();
                    if (hp == 1 && (u & 1) && lane == 0) asm volatile("red.relaxed.gpu.global.add.u32 [%0], 1;" ::"l"(&g_sync.rdcnt[(grp * 2 + (u >> 1)) * 8]) : "memory");
                }
#pragma unroll 1
                for (int u = 4; u < 16; u++) {
                    if (hp == 1 && (u & 7) == 4) mbar_wait(sb + BAR_FLAG + 24 + (u & 8), 0);
                    load_tile(sb, eph, a_next(atab), &tm_ckv, ((u & 12) + (j >> 1)) * 128, (u & 3) * 2, (HINT & 8) && hp); PT();
                }
                mbar_wait(sb + BAR_FLAG, 0);
                fence_async_global();
#pragma unroll 1
                for (int u = 0; u < 4; u++) {
                    load_tile(sb, eph, (wtab >> (4 * u)) & 15, &tm_wq, u * 128, hc, HINT & 1); PT();
                    load_image(sb, eph, a_next(atab), g_h + ((15 - j) * 4 + u) * SLOT, (HINT & 8) && hp); PT();
                }
                mbar_wait(sb + BAR_FLAG + 8 + 32 * hp, 0);
                fence_async_global();
#pragma unroll 1
                for (int u = 0; u < 4; u++) { load_image(sb, eph, a_next(atab), g_h + (j * 4 + u) * SLOT, (HINT & 8) && hp); PT(); }
                const uint8_t* kv = g_KV + (size_t)(grp * 32 + 30 * hp) * SLOT;
                const int step = hp ? -2 * SLOT : 2 * SLOT;
                load_image(sb, eph, r, kv, HINT & 4); PT();
                r = ring_next(r);
#pragma unroll 1
                for (int n = 1; n <= 16; n++) {
                    if (n == 8) {
                        mbar_wait(sb + BAR_FLAG + 16 + 32 * hp, 0);
                        fence_async_global();
                    }
                    mbar_arrive_if(sb + BAR_PF, lane == 0 && (n == PF1 || n == PF2));
                    const uint8_t* v = kv + SLOT;
                    kv += n < 16 - j ? step : n == 16 - j ? (2 * j - 15) * step : -step;
                    load_image(sb, eph, r, kv, HINT & 4); PT();
                    r = ring_next(r);
                    load_image(sb, eph, r, v, HINT & 4); PT();
                    r = ring_next(r);
                }
                load_image(sb, eph, r, kv + SLOT, HINT & 4); PT();
                r = ring_next(r);
            }
            uint32_t otab = O_TABLE, ready = 0, todo = 0x7f00;
#pragma unroll 1
            for (int i = 0; i < 17; i++) {
                const uint32_t want = i >= 8 && i < 15 ? todo : 1u << i;
                if (!(ready & want)) {
                    do {
                        asm volatile("ld.acquire.cta.shared.u32 %0, [%1];" : "=r"(ready) : "r"(sb + SM_EP + 4) : "memory");
                        ready = __shfl_sync(0xffffffffu, ready, 0);
                    } while (!(ready & want));
                    fence_async_global();
                }
                const int pick = __ffs(ready & want) - 1;
                todo &= ~(1u << pick);
                const int head = o_head(pick, kh);
                const uint8_t* src = g_ctx + (size_t)(ort * 32 + head) * SLOT;
                if (i < 15) {
                    load_image(sb, eph, o_next(otab), src, HINT & 16);
                } else {
                    const uint32_t as = o_next(otab), d = sb + as * SLOT;
                    slot_wait(sb + BAR_EMPTY, eph, as);
                    asm volatile("{\n.reg .pred p, q;\nelect.sync _|p, 0xffffffff;\n@p mbarrier.arrive.expect_tx.shared::cta.b64 _, [%2], %3;\n"
                                 "@p cp.async.bulk.shared::cluster.global.mbarrier::complete_tx::bytes [%0], [%1], 16384, [%2];\n}"
                                 ::"r"(d + kh * 16384), "l"(src + kh * 16384), "r"(sb + BAR_FULL + 8 * as), "r"(i == 15 ? 32768 : 16384) : "memory");
                    if (i == 15)
                        asm volatile("{\n.reg .pred p;\nelect.sync _|p, 0xffffffff;\n"
                                     "@p cp.async.bulk.tensor.3d.shared::cluster.global.mbarrier::complete_tx::bytes [%0], [%1, {%3, %4, %5}], [%2];\n}"
                                     ::"r"(d + (kh ^ 1) * 16384), "l"(&tm_x), "r"(sb + BAR_FULL + 8 * as), "r"(0), "r"(ort * 128 + kh * 64), "r"(cq * 2) : "memory");
                }
                PT();
                load_tile(sb, eph, o_next(otab), &tm_wo, head * 128, cq * 2, HINT & 2); PT();
            }
            if (lane == 0) {
                const uint32_t s1 = o_next(otab), s2 = o_next(otab);
                if (rb < NFFN) {
                    slot_wait(sb + BAR_EMPTY, eph, s1);
                    const uint32_t f = sb + BAR_FULL + 8 * s1, d = sb + s1 * SLOT;
                    mbar_expect(f, SLOT);
                    tma2d(d, &tm_wg, rb * 16, 0, f);
                    tma2d(d + 8192, &tm_wg, rb * 16, 256, f);
                    tma2d(d + 16384, &tm_wu, rb * 16, 0, f);
                    tma2d(d + 24576, &tm_wu, rb * 16, 256, f);
                }
                slot_wait(sb + BAR_EMPTY, eph, s2);
                mbar_expect(sb + BAR_FULL + 8 * s2, 7 * 4096);
#pragma unroll 1
                for (int k = 0; k < 7; k++) tma2d(sb + s2 * SLOT + k * 4096, &tm_wd, (rb >> 1) * 8, k * 256, sb + BAR_FULL + 8 * s2);
            }
        } else {
            const int hw = warp - 9;
            if (hw == 1 && lane == 0) {
                l2_prefetch(P.ckv + rb * 2048, 4096);
                mbar_watch(sb + BAR_FULL + 8 * PF0, 0);
                l2_prefetch(P.ckv + 512 * 512 + rb * 2048, 4096);
                mbar_watch(sb + BAR_FULL + 8 * 4, 0);
                l2_prefetch(P.x + rb * 8192, 16384);
                l2_prefetch(P.ckv + 1024 * 512 + rb * 4096, 8192);
                TS(40);
                if (j < 4) tma3d_prefetch(&tm_wq, j * 128, grp * 4);
                mbar_watch(sb + BAR_PF, 0);
                l2_prefetch(P.ckv + rb * 8192, 16384);
                l2_prefetch(g_h + rb * 16384, 16384);
                mbar_watch(sb + BAR_PF, 1);
                tma3d_prefetch((j & 1) ? &tm_wuv : &tm_wuk, (j >> 1) * 128, grp * 4 + 2);
                if (j < 4) tma3d_prefetch(&tm_wq, j * 128, grp * 4 + 2);
                mbar_watch(sb + BAR_PF, 0);
                l2_prefetch(g_ctx + (size_t)(ort * 32 + o_head(cq, kh)) * SLOT, SLOT);
                l2_prefetch(g_ctx + (size_t)(ort * 32 + o_head(cq + 4, kh)) * SLOT, SLOT);
                mbar_watch(sb + BAR_PF, 1);
                l2_prefetch(reinterpret_cast<const uint8_t*>(P.wo) + rb * 32768, 32768);
                l2_prefetch(reinterpret_cast<const uint8_t*>(P.wgate) + rb * 14336, 14336);
                l2_prefetch(reinterpret_cast<const uint8_t*>(P.wup) + rb * 14336, 14336);
                l2_prefetch(reinterpret_cast<const uint8_t*>(P.wdown) + rb * 14336, 14336);
                l2_prefetch(P.x + rb * 8192, 16384);
                mbar_watch(sb + BAR_END, 0);
            }
            if (hw == 0) {
#pragma unroll 1
                for (int i = 0; i < 9; i++) {
                    const int hp = i > 4, k = (i - 1) & 3;
                    if (lane == 0) {
                        mbar_wait(sb + BAR_DONE + 8 * i, 0);
                        flag_add(i == 0 ? &g_sync.hcnt[grp * 8] : k < 2 ? &g_sync.kvcnt[((2 * grp + hp) * 2 + k) * 8]
                                                                        : &g_sync.ctxcnt[(k == 2 ? 15 - j : j) * 32 + 2 * grp + hp]);
                    }
                    if (i == 0) TS(43);
                }
            }
            if (hw == 2) {
                const uint32_t ep = __ldcg(&g_sync.epoch[0]) + 1;
                if (lane == 0) {
                    asm volatile("st.shared.u32 [%0], %1;" ::"r"(sb + SM_EP), "r"(ep) : "memory");
                    flag_wait(&g_sync.modcnt[0], NSPARE * ep);
                }
                __syncwarp();
#pragma unroll
                for (int i = 0; i < 4; i++) {
                    uint4 v = __ldcg(reinterpret_cast<const uint4*>(g_mod) + lane + 32 * i);
                    if (i >= 2) v = make_uint4(badd(v.x, ONE2), badd(v.y, ONE2), badd(v.z, ONE2), badd(v.w, ONE2));
                    sts128(sb + SM_TAB + i * 512 + lane * 16, v);
                }
                __syncwarp();
                if (lane == 0) mbar_arrive(sb + BAR_FLAG + 8 * 8);
                TS(42);
#pragma unroll 1
                for (int i = 0; i < 8; i++) {
                    if (lane == 0) mbar_wait(sb + BAR_DONE + 8 * (i == 7 ? 6 : i == 4 ? 3 : i), 0);
                    __syncwarp();
                    const uint32_t* f = i == 0 ? &g_sync.hcnt[(lane ? j : 15 - j) * 8]
                                      : i == 3 || i == 4 ? &g_sync.rdcnt[(grp * 2 + i - 3) * 8]
                                      : i == 7 ? &g_sync.modcnt[32] : &g_sync.kvcnt[(4 * grp + (i > 4 ? i - 3 : i - 1)) * 8];
                    if (lane < (i ? 1 : 2)) flag_wait(f, i == 7 ? NSPARE * ep : 8 * ep);
                    __syncwarp();
                    if (i == 7) {
                        const uint32_t *mp = reinterpret_cast<const uint32_t*>(g_mod) + lane, *wp = reinterpret_cast<const uint32_t*>(P.wr) + lane;
                        float ra = 0.f, rs = 0.f;
#pragma unroll 1
                        for (int k = 0; k < 256; k += 32) {
                            const uint32_t ga = __ldcg(mp + 512 + k), sh = __ldcg(mp + 768 + k), c1 = badd(__ldcg(mp + 1024 + k), ONE2);
                            const uint32_t gb = __ldcg(mp + 1280 + k), ww = __ldg(wp + k);
                            const float a0 = bf_lo(c1) * bf_lo(ww), a1 = bf_hi(c1) * bf_hi(ww);
                            ra += a0 + a1;
                            rs = fmaf(bf_lo(sh), bf_lo(ww), fmaf(bf_hi(sh), bf_hi(ww), rs));
                            if (k >> 6 == cq) {
                                sts128(sb + SM_TAB + ((k & 32) + lane) * 16, make_uint4(ga << 16, ga & 0xffff0000u, __float_as_uint(a0), __float_as_uint(a1)));
                                sts128(sb + SM_TAB + 1024 + ((k & 32) + lane) * 16, make_uint4(c1, sh, gb, 0));
                            }
                        }
                        *reinterpret_cast<float2*>(smem + SM_EP + 8) = make_float2(warp_sum(ra), warp_sum(rs));
                        __syncwarp();
                    }
                    if (lane == 0) mbar_arrive(sb + BAR_FLAG + 8 * i);
                    TS(48 + i);
                }
                const uint32_t* f = &g_sync.ctxcnt[ort * 32 + o_head(min(lane, 16), kh)];
                uint32_t ready = 0;
                while (ready != ~0u) {
                    uint32_t v;
                    asm volatile("ld.acquire.gpu.global.u32 %0, [%1];" : "=r"(v) : "l"(f) : "memory");
                    const uint32_t now = __ballot_sync(0xffffffffu, (int)(v - ep) >= 0);
                    if (now != ready && lane == 0) asm volatile("st.release.cta.shared.u32 [%0], %1;" ::"r"(sb + SM_EP + 4), "r"(now) : "memory");
                    if ((now & 0xff) == 0xff) mbar_wait(sb + BAR_DONE + 8 * 7, 0);
                    ready = now;
                    __nanosleep(POLL_NS);
                }
                TS(45);
            }
        }
    } else {
        asm volatile("setmaxnreg.inc.sync.aligned.u32 232;");
        const bool elected = (tid & 127) == 0;
        const int g = lane >> 2, c4 = lane & 3;
        const uint32_t toff = warp * 4096 + g * 64 + ((c4 ^ (g >> 1)) << 4);
        uint32_t fph = 0, r = 0;
        if (wg == 1) bar_arrive(1, 256);
        const uint32_t kd = desc_k(sb), wd = desc_mn(sb), vd = (sb >> 4) | (32u << 16);
        const int nL = 16 - j, hn = nL - 1 + wg;
        float s[64], o[64], li[2] = {0.f, 0.f};
        uint8_t* cimg = g_ctx;
#pragma unroll 1
        for (int hp = 0; hp < 2; hp++) {
            {
                const int step = hp ? -8 * SLOT : 8 * SLOT;
                uint8_t* img = g_KV + (size_t)(grp * 32 + (hp ? j ^ 30 : j)) * SLOT - step;
                const float sc = (j & 1) ? 1.f : SM_C;
                const uint32_t wtab = w_table(hp);
                uint32_t atab = hp ? 0x256u : a_table(0);
#pragma unroll 1
                for (int t = 0; t < 6; t += 2) {
                    proj_tile<false>(s, o, t, t ? 0 : 2 * hp, sb, wg, elected, fph, wtab, atab, t ? img : cimg, toff, t ? sc : li[0], t ? sc : li[1], (hp | t) == 0, P.x, rb * 16 + warp * 2);
                    __syncwarp();
                    mbar_arrive_if(sb + BAR_DONE + 4 * t + 32 * hp, lane == 0 && (hp | t) != 0);
                    if (elected) TS(1 + 10 * hp + t + 20 * wg);
                    proj_tile<true>(o, s, t + 1, 0, sb, wg, elected, fph, wtab, atab, img + step, toff, sc, sc, (hp | t) == 0, P.x, rb * 16 + warp * 2);
                    if (elected) TS(2 + 10 * hp + t + 20 * wg);
                    img += 2 * step;
                }
            }
            float m[2] = {0.f, 0.f}, l[2] = {0.f, 0.f}, t[4] = {0.f, 0.f, 0.f, 0.f};
            bool shifted = false, bad = false, plain = false;
            uint32_t p[32];
#pragma unroll
            for (int i = 0; i < 32; i++) p[i] = 0;
            uint32_t qa = desc_k(sb + 5 * SLOT + (wg ^ 1) * 8192);
            uint8_t* img = g_ctx + (size_t)((15 - j) * 32 + 2 * grp + hp) * SLOT;
            slot_wait(sb + BAR_FULL, fph, r);
            int n = -1;
#pragma unroll 1
            for (;;) {
                while (bad || plain) {
                    if (bad) {
                        float a0, a1;
                        softmax_remax(s, m, n == 0 || n == nL, a0, a1);
                        shifted = true;
                        l[0] *= a0;
                        l[1] *= a1;
#pragma unroll
                        for (int i = 0; i < 64; i++) o[i] *= (i & 2) ? a1 : a0;
                    }
                    softmax_exp<0, 16>(s, p, t);
                    t[0] += t[1];
                    t[2] += t[3];
                    bad = !bad && softmax_unsafe(t[0], t[2], false);
                    plain = false;
                }
#pragma unroll 1
                do {
                    l[0] += t[0];
                    l[1] += t[2];
                    if (++n > 16) break;
                    const uint32_t ks = r;
                    uint32_t vs = ring_next(r);
                    r = ring_next(vs);
                    bar_sync(1 + wg, 256);
                    if (n == 0 || (uint32_t)(n + 1 - nL) <= (uint32_t)(1 + wg)) {
                        const int x = (warp & 3) * 16 + g - 2 * c4;
                        if (n == 0) {
                            r = vs;
                            vs = 4 - hp;
                            qk_issue(s, qa, kd + ks * (SLOT / 16));
                            slot_wait(sb + BAR_FULL, fph, 6);
                            gemm_issue<false>(o, qa + SLOT / 16, wd + vs * (SLOT / 16), 1, false);
                            bar_arrive(2 - wg, 256);
                            wg_wait<1>();
                            reg_fence(s);
                        } else if (n == hn) {
                            float sh[32];
                            qk_issue(sh, qa, kd + ks * (SLOT / 16));
                            slot_wait(sb + BAR_FULL, fph, vs);
                            pv_issue(o, p, vd + vs * (SLOT / 16), 1, false);
                            bar_arrive(2 - wg, 256);
                            wg_wait<1>();
                            reg_fence(sh);
                            tri_mask_copy(s, sh, x);
                        } else {
                            qk_issue(s, qa, kd + ks * (SLOT / 16));
                            slot_wait(sb + BAR_FULL, fph, vs);
                            pv_issue(o, p, vd + vs * (SLOT / 16), n != nL + 1, n == hn + 1);
                            bar_arrive(2 - wg, 256);
                            wg_wait<1>();
                            reg_fence(s);
                            if (n <= nL) tri_mask<32>(s, x);
                        }
                        mbar_arrive_if(sb + BAR_EMPTY + 8 * ks, elected);
                        mbar_arrive_if(sb + BAR_EMPTY + 8 * (n == 16 ? 6 : 5), elected && (n == 16 || n == nL - 1));
                        if (n == nL - 1) {
                            qa += SLOT / 16;
                            fence_async_smem();
                        }
                        if (shifted) {
                            if (n == nL) {
                                m[0] = m[1] = 0.f;
                                shifted = false;
                            }
                            softmax_shift(s, m[0], m[1]);
                        }
                        float e[4 * EARLY];
#pragma unroll
                        for (int i = 0; i < 4 * EARLY; i++) {
                            e[i] = ex2(s[i]);
                            t[i & 3] = i < 4 ? e[i] : t[i & 3] + e[i];
                        }
                        reg_fence(e);
                        slot_wait(sb + BAR_FULL, fph, r);
                        wg_wait<0>();
                        reg_fence(o);
                        reg_fence(e);
                        mbar_arrive_if(sb + BAR_EMPTY + 8 * vs, elected);
#pragma unroll
                        for (int i = 0; i < 2 * EARLY; i++) p[i] = pack2(e[2 * i], e[2 * i + 1]);
                        softmax_exp<EARLY, 8>(s, p, t);
                        if (n == 0) q_store<(PARKS & 1) != 0>(sb + 6 * SLOT, toff, o);
                        if (n == nL) {
                            ctx_store<(PARKS & 2) != 0>(img, toff, o, l[0], l[1]);
                            __syncwarp();
                            mbar_arrive_if(sb + BAR_DONE + 24 + 32 * hp, lane == 0);
                            l[0] = l[1] = 0.f;
                        }
                        if (n != hn) softmax_exp<8, 16>(s, p, t);
                        t[0] += t[1];
                        t[2] += t[3];
                        bad = softmax_unsafe(t[0], t[2], n == 0 || n == nL);
                        continue;
                    }
                    qk_issue(s, qa, kd + ks * (SLOT / 16));
                    slot_wait(sb + BAR_FULL, fph, vs);
                    pv_issue(o, p, vd + vs * (SLOT / 16), n != 1 && n != nL + 1, false);
                    bar_arrive(2 - wg, 256);
                    wg_wait<1>();
                    reg_fence(s);
                    mbar_arrive_if(sb + BAR_EMPTY + 8 * ks, elected);
                    mbar_arrive_if(sb + BAR_EMPTY + 8 * 6, elected && n == 16);
                    if (shifted) {
                        slot_wait(sb + BAR_FULL, fph, r);
                        wg_wait<0>();
                        reg_fence(o);
                        mbar_arrive_if(sb + BAR_EMPTY + 8 * vs, elected);
                        softmax_shift(s, m[0], m[1]);
                        plain = true;
                        break;
                    }
                    float e[4 * EARLY];
#pragma unroll
                    for (int i = 0; i < 4 * EARLY; i++) {
                        e[i] = ex2(s[i]);
                        t[i & 3] = i < 4 ? e[i] : t[i & 3] + e[i];
                    }
                    reg_fence(e);
                    slot_wait(sb + BAR_FULL, fph, r);
                    wg_wait<0>();
                    reg_fence(o);
                    reg_fence(e);
                    mbar_arrive_if(sb + BAR_EMPTY + 8 * vs, elected);
#pragma unroll
                    for (int i = 0; i < 2 * EARLY; i++) p[i] = pack2(e[2 * i], e[2 * i + 1]);
                    softmax_exp<EARLY, 16>(s, p, t);
                    t[0] += t[1];
                    t[2] += t[3];
                    bad = softmax_unsafe(t[0], t[2], false);
                } while (!bad);
                if (!bad && !plain) break;
            }
            const uint32_t vs = r, ga = desc_k(sb + (hp ? 2 * (wg ^ kh ^ 1) : wg) * 8192), as = 2 + 2 * hp;
            r = ring_next(r);
            slot_wait(sb + BAR_FULL, fph, 5);
            slot_wait(sb + BAR_FULL, fph, r);
            bar_sync(1 + wg, 256);
            gemm_issue<true>(s, ga + 5 * (SLOT / 16), wd + r * (SLOT / 16), 0, hp);
            pv_issue(o, p, vd + vs * (SLOT / 16), j, hn == 16);
            bar_arrive(2 - wg, 256);
            li[0] = rcp(quad_sum(l[0]));
            li[1] = rcp(quad_sum(l[1]));
            cimg = img + (ptrdiff_t)(2 * j - 15) * 32 * SLOT + (wg ? -16384 : 16384);
            wg_wait<1>();
            mbar_arrive_if(sb + BAR_EMPTY + 8 * 5, elected);
            mbar_arrive_if(sb + BAR_EMPTY + 8 * r, elected && hp);
            wg_wait<0>();
            mbar_arrive_if(sb + BAR_EMPTY + 8 * vs, elected);
            reg_fence(o);
            img_store_global<0>(cimg, toff, o, li[0], li[1]);
            slot_wait(sb + BAR_FULL, fph, as);
            slot_wait(sb + BAR_FULL, fph, 0);
            bar_sync(1 + wg, 256);
            gemm_issue<false>(s, ga + as * (SLOT / 16), wd, 1, hp);
            bar_arrive(2 - wg, 256);
            reg_fence(o);
            img_store_global<1>(cimg, toff, o, li[0], li[1]);
            wg_wait<0>();
            mbar_arrive_if(sb + BAR_EMPTY + 8 * as, elected);
            mbar_arrive_if(sb + BAR_EMPTY, elected && hp);
            if (elected) TS(8 + 10 * hp + 20 * wg);
        }
        uint32_t otab = 0x0435216u;
        const uint32_t oa = desc_k(sb + (wg ^ kh ^ 1) * 16384);
        const int t7 = tid & 127, w4 = warp & 3, row = ort * 128 + kh * 64 + w4 * 16 + g;
#pragma unroll 1
        for (int i = 2; i < 15 - wg; i++) {
            const uint32_t as = o_next(otab), ws = o_next(otab);
            slot_wait(sb + BAR_FULL, fph, as);
            slot_wait(sb + BAR_FULL, fph, ws);
            bar_sync(1 + wg, 256);
            gemm_issue<false>(s, oa + as * (SLOT / 16), wd + ws * (SLOT / 16), 1, true);
            bar_arrive(2 - wg, 256);
            wg_wait<1>();
            reg_fence(o);
            if (i == 2) img_store_global<2>(cimg, toff, o, li[0], li[1]);
            if (i == CLAST) {
                img_store_global<3>(cimg, toff, o, li[0], li[1]);
                __syncwarp();
                mbar_arrive_if(sb + BAR_DONE + 64, lane == 0);
            }
            wg_wait<0>();
            mbar_arrive_if(sb + BAR_EMPTY + 8 * as, elected);
            mbar_arrive_if(sb + BAR_EMPTY + 8 * ws, elected);
        }
        mbar_wait(sb + BAR_FLAG + 8 * 7, 0);
        const uint32_t ep = lds32(sb + SM_EP);
        if (wg == 0) {
            reg_fence(s);
            if (elected) TS(9);
#pragma unroll
            for (int v = 0; v < 8; v++)
                st_pub(g_part + rb * 1024 + v * 128 + t7, make_uint4((pack2(s[8 * v], s[8 * v + 1]) & ~1u) | (ep & 1), pack2(s[8 * v + 2], s[8 * v + 3]),
                                                                      pack2(s[8 * v + 4], s[8 * v + 5]), pack2(s[8 * v + 6], s[8 * v + 7])), true);
            o_next(otab); o_next(otab); o_next(otab); o_next(otab);
            const uint32_t s1 = o_next(otab), s2 = o_next(otab);
            uint32_t wf[64];
            float wn[56];
            if (rb < NFFN) {
                slot_wait(sb + BAR_FULL, fph, s1);
                const uint32_t a = sb + s1 * SLOT + (w4 * 128 + (lane >> 4) * 8 + (lane & 7)) * 32 + ((lane >> 3) & 1) * 16;
#pragma unroll
                for (int i = 0; i < 16; i++)
                    asm volatile("ldmatrix.sync.aligned.m8n8.x4.trans.shared.b16 {%0, %1, %2, %3}, [%4];"
                                 : "=r"(wf[4 * i]), "=r"(wf[4 * i + 1]), "=r"(wf[4 * i + 2]), "=r"(wf[4 * i + 3])
                                 : "r"(a + (i >> 3) * 16384 + (i & 7) * 512) : "memory");
            }
            const uint32_t gbf = __ldcg(reinterpret_cast<const uint32_t*>(g_mod) + 1280 + rb * 2 + (tid & 1));
            if (elected) TS(10);
            const uint32_t best = best_key(g_key + cq * 128, lane, ep);
            const int sel = (~best >> 5) & 2047;
            if (elected) TS(19);
            const uint4* cp = g_cand + (sel >> 4) * 192;
            float* sred = reinterpret_cast<float*>(smem + SM_RED);
            const int pq = (2 * rb + (tid & 1)) & 63, pv = (pq >> 2) / 3;
            const uint4* fp = cp + (rb >> 5) * 24 + pv * 4 + (pq & 3);
            uint4 fh = ld_poll(fp), fx = ld_poll(fp + 96);
            if (rb < NFFN) {
                uint4 cv[6];
                for (;;) {
                    uint32_t bad = 0;
#pragma unroll
                    for (int v = 0; v < 6; v++) cv[v] = ld_poll(cp + w4 * 24 + v * 4 + c4);
#pragma unroll
                    for (int v = 0; v < 6; v++) bad |= cv[v].w ^ ep;
                    if (__all_sync(0xffffffffu, bad == 0)) break;
                }
                if (elected) TS(20);
                float d[4][4] = {};
#pragma unroll
                for (int k = 0; k < 8; k++) {
                    const uint32_t b0 = (&cv[(2 * k) / 3].x)[(2 * k) % 3], b1 = (&cv[(2 * k + 1) / 3].x)[(2 * k + 1) % 3];
                    mma16816(d[k & 1], wf + 4 * k, b0, b1);
                    mma16816(d[2 + (k & 1)], wf + 32 + 4 * k, b0, b1);
                }
                const float u = (c4 & 2) ? ((c4 & 1) ? d[2][2] + d[3][2] : d[2][0] + d[3][0]) : ((c4 & 1) ? d[0][2] + d[1][2] : d[0][0] + d[1][0]);
                sred[w4 * 32 + c4 * 8 + g] = u;
                bar_sync(3, 128);
                if (warp == 0) {
                    const float v = rbf((sred[lane] + sred[32 + lane]) + (sred[64 + lane] + sred[96 + lane]));
                    const float up = __shfl_down_sync(0xffffffffu, v, 16);
                    st_pub(g_act + rb * 16 + lane, (pack2(0.f, rbf(v * sigmoid(v)) * up) & 0xffff0000u) | (ep & 0xffffu), lane < 16);
                }
            }
            if (rb == 0 && tid == 0) g_sync.epoch[0] = ep;
            if (elected) TS(60);
            slot_wait(sb + BAR_FULL, fph, s2);
#pragma unroll
            for (int i = 0; i < 14; i++) {
                const uint2 w = *reinterpret_cast<const uint2*>(smem + s2 * SLOT + (i >> 1) * 4096 + (2 * t7 + (i & 1)) * 16 + (rb & 1) * 8);
                wn[4 * i] = bf_lo(w.x); wn[4 * i + 1] = bf_hi(w.x); wn[4 * i + 2] = bf_lo(w.y); wn[4 * i + 3] = bf_hi(w.y);
            }
            reg_fence(wn);
            uint2 av[7];
            for (;;) {
                uint32_t bad = 0;
#pragma unroll
                for (int k = 0; k < 7; k++) av[k] = ld_poll(reinterpret_cast<const uint2*>(g_act) + t7 + 128 * k);
#pragma unroll
                for (int k = 0; k < 7; k++) bad |= (av[k].x ^ ep) | (av[k].y ^ ep);
                if (__all_sync(0xffffffffu, (bad & 0xffffu) == 0)) break;
            }
            if (elected) TS(61);
            float y[4] = {0.f, 0.f, 0.f, 0.f};
#pragma unroll
            for (int k = 0; k < 7; k++)
#pragma unroll
                for (int i = 0; i < 4; i++) y[i] = fmaf(bf_hi(av[k].y), wn[8 * k + 4 + i], fmaf(bf_hi(av[k].x), wn[8 * k + i], y[i]));
            const float z0 = ((lane & 16) ? y[2] : y[0]) + __shfl_xor_sync(0xffffffffu, (lane & 16) ? y[0] : y[2], 16);
            const float z1 = ((lane & 16) ? y[3] : y[1]) + __shfl_xor_sync(0xffffffffu, (lane & 16) ? y[1] : y[3], 16);
            float z = ((lane & 8) ? z1 : z0) + __shfl_xor_sync(0xffffffffu, (lane & 8) ? z0 : z1, 8);
            z += __shfl_xor_sync(0xffffffffu, z, 4);
            z = quad_sum(z);
            if ((lane & 7) == 0) sred[128 + (lane >> 3) * 4 + w4] = z;
            bar_sync(3, 128);
            if (tid < 2) {
                while (fh.w != ep || fx.w != ep) { fh = ld_poll(fp); fx = ld_poll(fp + 96); }
                const float4 y0 = *reinterpret_cast<const float4*>(sred + 128 + tid * 8), y1 = *reinterpret_cast<const float4*>(sred + 132 + tid * 8);
                const int cm = (pq >> 2) - 3 * pv;
                const uint32_t h2 = cm == 0 ? fh.x : cm == 1 ? fh.y : fh.z, x2 = cm == 0 ? fx.x : cm == 1 ? fx.y : fx.z;
                const float sg = sigmoid(bf_hi((best & 0x80000000u) ? (best ^ 0x80000000u) : ~best));
                reinterpret_cast<uint32_t*>(P.out)[sel * 256 + rb * 2 + tid] =
                    badd(x2, bmul(gbf, badd(h2, bmul(pack2((y0.x + y0.y) + (y0.z + y0.w), (y1.x + y1.y) + (y1.z + y1.w)), pack2(sg, sg)))));
            }
            if (elected) TS(62);
        } else {
            const float4* tf = reinterpret_cast<const float4*>(smem + SM_TAB) + c4;
            const uint32_t as14 = otab & 15, xa = sb + ((otab >> 8) & 15) * SLOT + (kh ^ 1) * 16384 + (w4 * 16 + (lane & 15)) * 128;
            uint32_t x2[32];
            bar_sync(2, 256);
#pragma unroll 1
            for (int i = 14; i < 17; i++) {
                const uint32_t as = o_next(otab), ws = o_next(otab);
                slot_wait(sb + BAR_FULL, fph, as);
                slot_wait(sb + BAR_FULL, fph, ws);
                gemm_issue<false>(s, oa + as * (SLOT / 16), wd + ws * (SLOT / 16), 1, true);
                wg_wait<1>();
                mbar_arrive_if(sb + BAR_EMPTY + 8 * as14, elected && i == 15);
            }
            if (elected) TS(29);
            {
#pragma unroll
                for (int k = 0; k < 8; k++)
                    asm volatile("ldmatrix.sync.aligned.m8n8.x4.shared.b16 {%0, %1, %2, %3}, [%4];"
                                 : "=r"(x2[4 * k]), "=r"(x2[4 * k + 1]), "=r"(x2[4 * k + 2]), "=r"(x2[4 * k + 3])
                                 : "r"(xa + (k >> 2) * 8192 + (((2 * (k & 3) + (lane >> 4)) ^ (lane & 7)) << 4)) : "memory");
                const uint4* pr = g_part + (rb ^ 8) * 1024 + t7;
                uint4 pa[8];
                for (;;) {
                    uint32_t bad = 0;
#pragma unroll
                    for (int v = 0; v < 8; v++) pa[v] = ld_poll(pr + v * 128);
#pragma unroll
                    for (int v = 0; v < 8; v++) bad |= pa[v].x ^ ep;
                    if (__all_sync(0xffffffffu, (bad & 1) == 0)) break;
                }
#pragma unroll
                for (int i = 0; i < 32; i++) {
                    const uint32_t w = (&pa[i >> 2].x)[i & 3];
                    const float2 ga = *reinterpret_cast<const float2*>(tf + (i >> 1) * 4);
                    o[2 * i] = fmaf(ga.x, bf_lo(w), bf_lo(x2[i]));
                    o[2 * i + 1] = fmaf(ga.y, bf_hi(w), bf_hi(x2[i]));
                }
            }
            reg_fence(o);
            if (elected) TS(30);
            wg_wait<0>();
            reg_fence(s);
            if (elected) TS(39);
            float st[6] = {0.f, 0.f, 0.f, 0.f, 0.f, 0.f};
#pragma unroll
            for (int k = 0; k < 16; k++) {
                const float4 c = tf[k * 4];
#pragma unroll
                for (int i = 4 * k; i < 4 * k + 4; i++) {
                    const int rh = (i >> 1) & 1;
                    const float v = fmaf((i & 1) ? c.y : c.x, s[i], o[i]);
                    s[i] = v;
                    st[rh] += v;
                    st[2 + rh] = fmaf(v, v, st[2 + rh]);
                    st[4 + rh] = fmaf(v, (i & 1) ? c.w : c.z, st[4 + rh]);
                }
            }
#pragma unroll
            for (int i = 0; i < 6; i++) st[i] = quad_sum(st[i]);
            st_pub(g_stat + (row + 8 * (c4 & 1)) * 4 + cq,
                   make_uint4(__float_as_uint((c4 & 1) ? st[1] : st[0]), __float_as_uint((c4 & 1) ? st[3] : st[2]),
                              __float_as_uint((c4 & 1) ? st[5] : st[4]), ep), c4 < 2);
            if (elected) TS(56);
            uint32_t cb[16], sh[16], gb[16];
#pragma unroll
            for (int i = 0; i < 16; i++) {
                const float4 c = tf[64 + i * 4];
                cb[i] = __float_as_uint(c.x); sh[i] = __float_as_uint(c.y); gb[i] = __float_as_uint(c.z);
            }
            const float ra = __uint_as_float(lds32(sb + SM_EP + 8)), rb0 = __uint_as_float(lds32(sb + SM_EP + 12));
#pragma unroll
            for (int i = 0; i < 32; i++) x2[i] = pack2(s[2 * i], s[2 * i + 1]);
            reg_fence(x2);
            uint4 r0, r1;
            for (;;) {
                r0 = ld_poll(g_stat + row * 4 + c4);
                r1 = ld_poll(g_stat + (row + 8) * 4 + c4);
                if (__all_sync(0xffffffffu, r0.w == ep && r1.w == ep)) break;
            }
            if (elected) TS(57);
            const float m0 = quad_sum(__uint_as_float(r0.x)) * (1.f / 512.f), m1 = quad_sum(__uint_as_float(r1.x)) * (1.f / 512.f);
            const float rs0 = ln_rstd(fmaxf(fmaf(-m0, m0, quad_sum(__uint_as_float(r0.y)) * (1.f / 512.f)), 0.f));
            const float rs1 = ln_rstd(fmaxf(fmaf(-m1, m1, quad_sum(__uint_as_float(r1.y)) * (1.f / 512.f)), 0.f));
            const uint32_t mb0 = pack2(m0, m0), mb1 = pack2(m1, m1);
            const uint32_t lg = pack2(fmaf(rs0, fmaf(-bf_lo(mb0), ra, quad_sum(__uint_as_float(r0.z))), rb0),
                                      fmaf(rs1, fmaf(-bf_lo(mb1), ra, quad_sum(__uint_as_float(r1.z))), rb0));
            const uint32_t u0 = lg << 16, u1 = lg & 0xffff0000u;
            const uint32_t k0 = ((u0 ^ (((int)u0 >> 31) | 0x80000000u)) & 0xffff0000u) | ((2047 - row) << 5) | (ep & 31);
            const uint32_t k1 = ((u1 ^ (((int)u1 >> 31) | 0x80000000u)) & 0xffff0000u) | ((2039 - row) << 5) | (ep & 31);
            const uint32_t kb = __reduce_max_sync(0xffffffffu, max(k0, k1));
            st_pub(g_key + cq * 128 + (row >> 4), kb, lane == 0);
            {
                uint32_t cx[18], ch[18];
#pragma unroll
                for (int i = 0; i < 16; i++) {
                    cx[i] = kb == k1 ? x2[2 * i + 1] : x2[2 * i];
                    ch[i] = ln_apply(cx[i], kb == k1 ? mb1 : mb0, kb == k1 ? rs1 : rs0, cb[i], sh[i]);
                }
                cx[16] = cx[17] = ch[16] = ch[17] = 0;
                uint4* cp = g_cand + (row >> 4) * 192 + cq * 24 + c4;
#pragma unroll
                for (int v = 0; v < 6; v++) st_pub(cp + v * 4, make_uint4(ch[3 * v], ch[3 * v + 1], ch[3 * v + 2], ep), kb == k0 || kb == k1);
#pragma unroll
                for (int v = 0; v < 6; v++) st_pub(cp + 96 + v * 4, make_uint4(cx[3 * v], cx[3 * v + 1], cx[3 * v + 2], ep), kb == k0 || kb == k1);
            }
            if (elected) TS(58);
            uint2 ov[16];
#pragma unroll
            for (int i = 0; i < 16; i++) {
                const int rh = i & 1, jj = i & 14;
                const uint32_t v0 = badd(x2[2 * jj + rh], bmul(gb[jj], ln_apply(x2[2 * jj + rh], rh ? mb1 : mb0, rh ? rs1 : rs0, cb[jj], sh[jj])));
                const uint32_t v1 = badd(x2[2 * jj + 2 + rh], bmul(gb[jj + 1], ln_apply(x2[2 * jj + 2 + rh], rh ? mb1 : mb0, rh ? rs1 : rs0, cb[jj + 1], sh[jj + 1])));
                const uint32_t rv = __shfl_xor_sync(0xffffffffu, (c4 & 1) ? v0 : v1, 1);
                ov[i] = (c4 & 1) ? make_uint2(rv, v1) : make_uint2(v0, rv);
            }
            uint2* op = reinterpret_cast<uint2*>(P.out) + row * 128 + cq * 32 + (c4 & 1) * 2 + (c4 >> 1);
#pragma unroll
            for (int i = 0; i < 16; i++)
                if (kb != ((i & 1) ? k1 : k0)) op[(i & 1) * 1024 + (i & 14) * 2] = ov[i];
            const uint32_t best = best_key(g_key + cq * 128, lane, ep);
            if (best != kb) {
#pragma unroll
                for (int i = 0; i < 16; i++)
                    if (kb == ((i & 1) ? k1 : k0)) op[(i & 1) * 1024 + (i & 14) * 2] = ov[i];
            }
            if (elected) TS(59);
        }
        mbar_arrive_if(sb + BAR_END, lane == 0);
    }
}

typedef CUresult (*EncodeFn)(CUtensorMap*, CUtensorMapDataType, cuuint32_t, void*, const cuuint64_t*, const cuuint64_t*,
                             const cuuint32_t*, const cuuint32_t*, CUtensorMapInterleave, CUtensorMapSwizzle,
                             CUtensorMapL2promotion, CUtensorMapFloatOOBfill);

void make_2d(EncodeFn fn, CUtensorMap* m, const void* p, uint64_t cols, uint64_t rows, uint32_t bc, uint32_t br) {
    cuuint64_t dims[2] = {cols, rows}, strides[1] = {cols * 2};
    cuuint32_t box[2] = {bc, br}, es[2] = {1, 1};
    fn(m, CU_TENSOR_MAP_DATA_TYPE_BFLOAT16, 2, const_cast<void*>(p), dims, strides, box, es, CU_TENSOR_MAP_INTERLEAVE_NONE,
       CU_TENSOR_MAP_SWIZZLE_NONE, CU_TENSOR_MAP_L2_PROMOTION_L2_128B, CU_TENSOR_MAP_FLOAT_OOB_FILL_NONE);
}
void make_3d(EncodeFn fn, CUtensorMap* m, const void* p, uint64_t cols, uint64_t rows, uint32_t br = 128) {
    cuuint64_t dims[3] = {64, rows, cols / 64}, strides[2] = {cols * 2, 128};
    cuuint32_t box[3] = {64, br, 2}, es[3] = {1, 1, 1};
    fn(m, CU_TENSOR_MAP_DATA_TYPE_BFLOAT16, 3, const_cast<void*>(p), dims, strides, box, es, CU_TENSOR_MAP_INTERLEAVE_NONE,
       CU_TENSOR_MAP_SWIZZLE_128B, CU_TENSOR_MAP_L2_PROMOTION_L2_256B, CU_TENSOR_MAP_FLOAT_OOB_FILL_NONE);
}

}

extern "C" void kernel_launch(void* const* d_in, const int* in_sizes, int n_in, void* d_out, int out_size) {
    static EncodeFn fn = nullptr;
    static int sms = 0;
    if (!fn) {
        void* f = nullptr;
        cudaDriverEntryPointQueryResult st;
        cudaGetDriverEntryPoint("cuTensorMapEncodeTiled", &f, cudaEnableDefault, &st);
        fn = (EncodeFn)f;
        int dev = 0;
        cudaGetDevice(&dev);
        cudaDeviceGetAttribute(&sms, cudaDevAttrMultiProcessorCount, dev);
        cudaFuncSetAttribute(fused_kernel, cudaFuncAttributeMaxDynamicSharedMemorySize, SMEM_BYTES);
    }
    CUtensorMap ckv, wq, wuk, wuv, wo, wg, wu, wd, wm, xm;
    make_3d(fn, &ckv, d_in[1], 512, 2048);
    make_3d(fn, &xm, d_in[0], 512, 2048, 64);
    make_3d(fn, &wq, d_in[2], 4096, 512);
    make_3d(fn, &wuk, d_in[3], 4096, 512);
    make_3d(fn, &wuv, d_in[4], 4096, 512);
    make_3d(fn, &wo, d_in[5], 512, 4096);
    make_2d(fn, &wg, d_in[8], 1792, 512, 16, 256);
    make_2d(fn, &wu, d_in[9], 1792, 512, 16, 256);
    make_2d(fn, &wd, d_in[10], 512, 1792, 8, 256);
    make_2d(fn, &wm, d_in[12], 3072, 512, 256, 64);
    Params p;
    p.x = (const bf16*)d_in[0];
    p.ckv = (const bf16*)d_in[1];
    p.wo = (const bf16*)d_in[5];
    p.wr = (const bf16*)d_in[7];
    p.wgate = (const bf16*)d_in[8];
    p.wup = (const bf16*)d_in[9];
    p.wdown = (const bf16*)d_in[10];
    p.c = (const bf16*)d_in[11];
    p.out = (bf16*)d_out;
    p.by_smid = sms == NCTA + NSPARE;
    fused_kernel<<<NCTA + NSPARE, 384, SMEM_BYTES>>>(ckv, wq, wuk, wuv, wo, wg, wu, wd, wm, xm, p);
}
```

```cpp
#include <cuda.h>
#include <cuda_bf16.h>
#include <cuda_runtime.h>
#include <stdint.h>
#include <stdio.h>

namespace {

typedef __nv_bfloat16 bf16;
typedef unsigned long long u64;

constexpr int NCTA = 128, NSPARE = 4;
constexpr int SLOT = 32768;
constexpr int SM_BAR = 7 * SLOT;
constexpr int BAR_FULL = SM_BAR;
constexpr int BAR_EMPTY = BAR_FULL + 8 * 7;
constexpr int BAR_DONE = BAR_EMPTY + 8 * 7;
constexpr int BAR_FLAG = BAR_DONE + 8 * 9;
constexpr int BAR_PF = BAR_FLAG + 8 * 9;
constexpr int BAR_END = BAR_PF + 8;
constexpr int SM_EP = BAR_END + 8;
constexpr int SM_RED = SM_BAR + 384;
constexpr int SM_TAB = SM_BAR + 1024;
constexpr int SMEM_BYTES = SM_BAR + 3072;
constexpr int NFFN = 112;
#define HINT 29
constexpr u64 L2_NORMAL = 0x1000000000000000ull, L2_FIRST = 0x12F0000000000000ull;
#define PF0 0
#define PF1 13
#define PF2 11
#define UNR 4
#define PARKS 7
#define POLL_NS 50
#define CLAST 2
#define OBINIT 1
#define EARLY 7
constexpr uint32_t SPIN_LIMIT = 1u << 22;
constexpr uint32_t ONE2 = 0x3f803f80u;

struct Sync {
    uint32_t modcnt[2 * 32];
    uint32_t hcnt[16 * 8];
    uint32_t kvcnt[32 * 2 * 8];
    uint32_t ctxcnt[16 * 32];
    uint32_t rdcnt[16 * 2 * 8];
    uint32_t epoch[32];
};

__device__ __align__(1024) uint8_t g_KV[16 * 16 * 2 * SLOT];
__device__ __align__(1024) uint8_t g_ctx[16 * 32 * SLOT];
__device__ __align__(1024) uint8_t g_h[16 * 4 * SLOT];
constexpr int OB = 1216, OB_STAT = 1024, OB_Y = 1088;
__device__ __align__(1024) uint4 g_out[128 * OB];
__device__ __align__(1024) bf16 g_mod[3072];
__device__ __align__(1024) uint4 g_cand[128 * 192];
__device__ __align__(1024) uint32_t g_key[4 * 128];
__device__ __align__(1024) uint8_t g_wf[NFFN * SLOT];
__device__ __align__(1024) Sync g_sync;
#define TS(i)

#define PT()

struct Params {
    const bf16 *x, *ckv, *wo, *wr, *wdown, *c;
    bf16* out;
    int by_smid;
};

__device__ __forceinline__ void mbar_init(uint32_t bar, uint32_t cnt) {
    asm volatile("mbarrier.init.shared::cta.b64 [%0], %1;" ::"r"(bar), "r"(cnt) : "memory");
}
__device__ __forceinline__ void mbar_wait(uint32_t bar, uint32_t parity) {
    asm volatile("{\n.reg .pred p;\nL_%=:\nmbarrier.try_wait.parity.shared::cta.b64 p, [%0], %1;\n@!p bra L_%=;\n}" ::"r"(bar), "r"(parity) : "memory");
}
__device__ __forceinline__ void mbar_watch(uint32_t bar, uint32_t parity) {
    asm volatile("{\n.reg .pred p;\n.reg .u32 n;\nmov.u32 n, 0;\n"
                 "L_%=:\nmbarrier.try_wait.parity.shared::cta.b64 p, [%0], %1;\n@p bra D_%=;\n"
                 "add.u32 n, n, 1;\nsetp.lt.u32 p, n, %2;\n@p bra L_%=;\ntrap;\nD_%=:\n}"
                 ::"r"(bar), "r"(parity), "n"(SPIN_LIMIT) : "memory");
}
__device__ __forceinline__ void mbar_arrive(uint32_t bar) {
    asm volatile("mbarrier.arrive.shared::cta.b64 _, [%0];" ::"r"(bar) : "memory");
}
__device__ __forceinline__ void mbar_arrive_if(uint32_t bar, bool on) {
    asm volatile("{\n.reg .pred p;\nsetp.ne.s32 p, %1, 0;\n@p mbarrier.arrive.shared::cta.b64 _, [%0];\n}" ::"r"(bar), "r"((int)on) : "memory");
}
__device__ __forceinline__ void mbar_expect(uint32_t bar, uint32_t bytes) {
    asm volatile("mbarrier.arrive.expect_tx.shared::cta.b64 _, [%0], %1;" ::"r"(bar), "r"(bytes) : "memory");
}
__device__ __forceinline__ void tma2d(uint32_t dst, const CUtensorMap* m, int c0, int c1, uint32_t bar) {
    asm volatile("cp.async.bulk.tensor.2d.shared::cluster.global.mbarrier::complete_tx::bytes [%0], [%1, {%3, %4}], [%2];"
                 ::"r"(dst), "l"(m), "r"(bar), "r"(c0), "r"(c1) : "memory");
}
__device__ __forceinline__ void tma3d_prefetch(const CUtensorMap* m, int row, int cb) {
    asm volatile("cp.async.bulk.prefetch.tensor.3d.L2.global [%0, {%1, %2, %3}];" ::"l"(m), "r"(0), "r"(row), "r"(cb) : "memory");
}
__device__ __forceinline__ void l2_prefetch(const void* p, uint32_t bytes) {
    asm volatile("cp.async.bulk.prefetch.L2.global [%0], %1;" ::"l"(p), "r"(bytes) : "memory");
}
__device__ __forceinline__ void flag_wait(const uint32_t* f, uint32_t target) {
    asm volatile("{\n.reg .pred p;\n.reg .u32 v;\n"
                 "L_%=:\nld.acquire.gpu.global.u32 v, [%0];\nsub.u32 v, v, %1;\nsetp.lt.s32 p, v, 0;\n@p nanosleep.u32 100;\n@p bra L_%=;\n}"
                 ::"l"(f), "r"(target) : "memory");
}
__device__ __forceinline__ uint4 ld_poll(const uint4* p) {
    uint4 v;
    asm volatile("ld.relaxed.gpu.global.v4.u32 {%0, %1, %2, %3}, [%4];" : "=r"(v.x), "=r"(v.y), "=r"(v.z), "=r"(v.w) : "l"(p) : "memory");
    return v;
}
__device__ __forceinline__ void st_pub(uint4* p, uint4 v, bool on) {
    asm volatile("{\n.reg .pred p;\nsetp.ne.s32 p, %5, 0;\n@p st.relaxed.gpu.global.v4.u32 [%0], {%1, %2, %3, %4};\n}"
                 ::"l"(p), "r"(v.x), "r"(v.y), "r"(v.z), "r"(v.w), "r"((int)on) : "memory");
}
__device__ __forceinline__ void st_pub(uint32_t* p, uint32_t v, bool on) {
    asm volatile("{\n.reg .pred p;\nsetp.ne.s32 p, %2, 0;\n@p st.relaxed.gpu.global.u32 [%0], %1;\n}" ::"l"(p), "r"(v), "r"((int)on) : "memory");
}
__device__ __forceinline__ void flag_add(uint32_t* p) {
    asm volatile("red.release.gpu.global.add.u32 [%0], 1;" ::"l"(p) : "memory");
}
__device__ __forceinline__ uint32_t lds32(uint32_t a) {
    uint32_t v;
    asm volatile("ld.shared.u32 %0, [%1];" : "=r"(v) : "r"(a) : "memory");
    return v;
}
__device__ __forceinline__ uint4 lds128(uint32_t a) {
    uint4 v;
    asm volatile("ld.shared.v4.u32 {%0, %1, %2, %3}, [%4];" : "=r"(v.x), "=r"(v.y), "=r"(v.z), "=r"(v.w) : "r"(a) : "memory");
    return v;
}
__device__ __forceinline__ void fence_async_global() { asm volatile("fence.proxy.async.global;" ::: "memory"); }
__device__ __forceinline__ void fence_async_smem() { asm volatile("fence.proxy.async.shared::cta;" ::: "memory"); }
__device__ __forceinline__ void bar_sync(int id, int n) { asm volatile("bar.sync %0, %1;" ::"r"(id), "r"(n) : "memory"); }
__device__ __forceinline__ void bar_arrive(int id, int n) { asm volatile("bar.arrive %0, %1;" ::"r"(id), "r"(n) : "memory"); }
__device__ __forceinline__ void wg_fence() { asm volatile("wgmma.fence.sync.aligned;" ::: "memory"); }
__device__ __forceinline__ void wg_commit() { asm volatile("wgmma.commit_group.sync.aligned;" ::: "memory"); }
template <int N> __device__ __forceinline__ void wg_wait() { asm volatile("wgmma.wait_group.sync.aligned %0;" ::"n"(N) : "memory"); }
template <int N> __device__ __forceinline__ void reg_fence(float (&d)[N]) {
#pragma unroll
    for (int i = 0; i < N; i++) asm volatile("" : "+f"(d[i])::"memory");
}
template <int N> __device__ __forceinline__ void reg_fence(uint32_t (&d)[N]) {
#pragma unroll
    for (int i = 0; i < N; i++) asm volatile("" : "+r"(d[i])::"memory");
}
__device__ __forceinline__ uint32_t desc_k(uint32_t a) { return (a >> 4) | (1u << 16); }
__device__ __forceinline__ uint32_t desc_mn(uint32_t a) { return (a >> 4) | (1024u << 16); }

template <int TB>
__device__ __forceinline__ void wgmma_ss128(float (&d)[64], uint32_t da, uint32_t db, int acc, uint32_t ha = 0x40000040u, uint32_t hb = 0x40000040u) {
    asm volatile("{\n.reg .pred p;\n.reg .b64 a, b;\nsetp.ne.b32 p, %66, 0;\nmov.b64 a, {%64, %68};\nmov.b64 b, {%65, %69};\n"
        "wgmma.mma_async.sync.aligned.m64n128k16.f32.bf16.bf16 {%0, %1, %2, %3, %4, %5, %6, %7, %8, %9, %10, %11, %12, %13, %14, %15, %16, %17, %18, %19, %20, %21, %22, %23, %24, %25, %26, %27, %28, %29, %30, %31, %32, %33, %34, %35, %36, %37, %38, %39, %40, %41, %42, %43, %44, %45, %46, %47, %48, %49, %50, %51, %52, %53, %54, %55, %56, %57, %58, %59, %60, %61, %62, %63}, a, b, p, 1, 1, 0, %67;\n}"
        : "+f"(d[0]), "+f"(d[1]), "+f"(d[2]), "+f"(d[3]), "+f"(d[4]), "+f"(d[5]), "+f"(d[6]), "+f"(d[7]), "+f"(d[8]), "+f"(d[9]), "+f"(d[10]), "+f"(d[11]), "+f"(d[12]), "+f"(d[13]), "+f"(d[14]), "+f"(d[15]), "+f"(d[16]), "+f"(d[17]), "+f"(d[18]), "+f"(d[19]), "+f"(d[20]), "+f"(d[21]), "+f"(d[22]), "+f"(d[23]), "+f"(d[24]), "+f"(d[25]), "+f"(d[26]), "+f"(d[27]), "+f"(d[28]), "+f"(d[29]), "+f"(d[30]), "+f"(d[31]), "+f"(d[32]), "+f"(d[33]), "+f"(d[34]), "+f"(d[35]), "+f"(d[36]), "+f"(d[37]), "+f"(d[38]), "+f"(d[39]), "+f"(d[40]), "+f"(d[41]), "+f"(d[42]), "+f"(d[43]), "+f"(d[44]), "+f"(d[45]), "+f"(d[46]), "+f"(d[47]), "+f"(d[48]), "+f"(d[49]), "+f"(d[50]), "+f"(d[51]), "+f"(d[52]), "+f"(d[53]), "+f"(d[54]), "+f"(d[55]), "+f"(d[56]), "+f"(d[57]), "+f"(d[58]), "+f"(d[59]), "+f"(d[60]), "+f"(d[61]), "+f"(d[62]), "+f"(d[63])
        : "r"(da), "r"(db), "r"(acc), "n"(TB), "r"(ha), "r"(hb));
}
template <int TB>
__device__ __forceinline__ void wgmma_ss128_init(float (&d)[64], uint32_t da, uint32_t db, uint32_t ha = 0x40000040u, uint32_t hb = 0x40000040u) {
    asm volatile("{\n.reg .pred p;\n.reg .b64 a, b;\nsetp.ne.b32 p, 0, 0;\nmov.b64 a, {%64, %67};\nmov.b64 b, {%65, %68};\n"
        "wgmma.mma_async.sync.aligned.m64n128k16.f32.bf16.bf16 {%0, %1, %2, %3, %4, %5, %6, %7, %8, %9, %10, %11, %12, %13, %14, %15, %16, %17, %18, %19, %20, %21, %22, %23, %24, %25, %26, %27, %28, %29, %30, %31, %32, %33, %34, %35, %36, %37, %38, %39, %40, %41, %42, %43, %44, %45, %46, %47, %48, %49, %50, %51, %52, %53, %54, %55, %56, %57, %58, %59, %60, %61, %62, %63}, a, b, p, 1, 1, 0, %66;\n}"
        : "=f"(d[0]), "=f"(d[1]), "=f"(d[2]), "=f"(d[3]), "=f"(d[4]), "=f"(d[5]), "=f"(d[6]), "=f"(d[7]), "=f"(d[8]), "=f"(d[9]), "=f"(d[10]), "=f"(d[11]), "=f"(d[12]), "=f"(d[13]), "=f"(d[14]), "=f"(d[15]), "=f"(d[16]), "=f"(d[17]), "=f"(d[18]), "=f"(d[19]), "=f"(d[20]), "=f"(d[21]), "=f"(d[22]), "=f"(d[23]), "=f"(d[24]), "=f"(d[25]), "=f"(d[26]), "=f"(d[27]), "=f"(d[28]), "=f"(d[29]), "=f"(d[30]), "=f"(d[31]), "=f"(d[32]), "=f"(d[33]), "=f"(d[34]), "=f"(d[35]), "=f"(d[36]), "=f"(d[37]), "=f"(d[38]), "=f"(d[39]), "=f"(d[40]), "=f"(d[41]), "=f"(d[42]), "=f"(d[43]), "=f"(d[44]), "=f"(d[45]), "=f"(d[46]), "=f"(d[47]), "=f"(d[48]), "=f"(d[49]), "=f"(d[50]), "=f"(d[51]), "=f"(d[52]), "=f"(d[53]), "=f"(d[54]), "=f"(d[55]), "=f"(d[56]), "=f"(d[57]), "=f"(d[58]), "=f"(d[59]), "=f"(d[60]), "=f"(d[61]), "=f"(d[62]), "=f"(d[63])
        : "r"(da), "r"(db), "n"(TB), "r"(ha), "r"(hb));
}
template <int TB>
__device__ __forceinline__ void wgmma_ss64(float (&d)[32], uint32_t da, uint32_t db, int acc, uint32_t ha = 0x40000040u, uint32_t hb = 0x40000040u) {
    asm volatile("{\n.reg .pred p;\n.reg .b64 a, b;\nsetp.ne.b32 p, %34, 0;\nmov.b64 a, {%32, %36};\nmov.b64 b, {%33, %37};\n"
        "wgmma.mma_async.sync.aligned.m64n64k16.f32.bf16.bf16 {%0, %1, %2, %3, %4, %5, %6, %7, %8, %9, %10, %11, %12, %13, %14, %15, %16, %17, %18, %19, %20, %21, %22, %23, %24, %25, %26, %27, %28, %29, %30, %31}, a, b, p, 1, 1, 0, %35;\n}"
        : "+f"(d[0]), "+f"(d[1]), "+f"(d[2]), "+f"(d[3]), "+f"(d[4]), "+f"(d[5]), "+f"(d[6]), "+f"(d[7]), "+f"(d[8]), "+f"(d[9]), "+f"(d[10]), "+f"(d[11]), "+f"(d[12]), "+f"(d[13]), "+f"(d[14]), "+f"(d[15]), "+f"(d[16]), "+f"(d[17]), "+f"(d[18]), "+f"(d[19]), "+f"(d[20]), "+f"(d[21]), "+f"(d[22]), "+f"(d[23]), "+f"(d[24]), "+f"(d[25]), "+f"(d[26]), "+f"(d[27]), "+f"(d[28]), "+f"(d[29]), "+f"(d[30]), "+f"(d[31])
        : "r"(da), "r"(db), "r"(acc), "n"(TB), "r"(ha), "r"(hb));
}
template <int TB>
__device__ __forceinline__ void wgmma_ss64_init(float (&d)[32], uint32_t da, uint32_t db, uint32_t ha = 0x40000040u, uint32_t hb = 0x40000040u) {
    asm volatile("{\n.reg .pred p;\n.reg .b64 a, b;\nsetp.ne.b32 p, 0, 0;\nmov.b64 a, {%32, %35};\nmov.b64 b, {%33, %36};\n"
        "wgmma.mma_async.sync.aligned.m64n64k16.f32.bf16.bf16 {%0, %1, %2, %3, %4, %5, %6, %7, %8, %9, %10, %11, %12, %13, %14, %15, %16, %17, %18, %19, %20, %21, %22, %23, %24, %25, %26, %27, %28, %29, %30, %31}, a, b, p, 1, 1, 0, %34;\n}"
        : "=f"(d[0]), "=f"(d[1]), "=f"(d[2]), "=f"(d[3]), "=f"(d[4]), "=f"(d[5]), "=f"(d[6]), "=f"(d[7]), "=f"(d[8]), "=f"(d[9]), "=f"(d[10]), "=f"(d[11]), "=f"(d[12]), "=f"(d[13]), "=f"(d[14]), "=f"(d[15]), "=f"(d[16]), "=f"(d[17]), "=f"(d[18]), "=f"(d[19]), "=f"(d[20]), "=f"(d[21]), "=f"(d[22]), "=f"(d[23]), "=f"(d[24]), "=f"(d[25]), "=f"(d[26]), "=f"(d[27]), "=f"(d[28]), "=f"(d[29]), "=f"(d[30]), "=f"(d[31])
        : "r"(da), "r"(db), "n"(TB), "r"(ha), "r"(hb));
}
__device__ __forceinline__ void wgmma_rs128(float (&d)[64], uint32_t a0, uint32_t a1, uint32_t a2, uint32_t a3, uint32_t db, int acc, uint32_t hb = 0x40000040u) {
    asm volatile("{\n.reg .pred p;\n.reg .b64 b;\nsetp.ne.b32 p, %69, 0;\nmov.b64 b, {%68, %70};\n"
        "wgmma.mma_async.sync.aligned.m64n128k16.f32.bf16.bf16 {%0, %1, %2, %3, %4, %5, %6, %7, %8, %9, %10, %11, %12, %13, %14, %15, %16, %17, %18, %19, %20, %21, %22, %23, %24, %25, %26, %27, %28, %29, %30, %31, %32, %33, %34, %35, %36, %37, %38, %39, %40, %41, %42, %43, %44, %45, %46, %47, %48, %49, %50, %51, %52, %53, %54, %55, %56, %57, %58, %59, %60, %61, %62, %63}, {%64, %65, %66, %67}, b, p, 1, 1, 1;\n}"
        : "+f"(d[0]), "+f"(d[1]), "+f"(d[2]), "+f"(d[3]), "+f"(d[4]), "+f"(d[5]), "+f"(d[6]), "+f"(d[7]), "+f"(d[8]), "+f"(d[9]), "+f"(d[10]), "+f"(d[11]), "+f"(d[12]), "+f"(d[13]), "+f"(d[14]), "+f"(d[15]), "+f"(d[16]), "+f"(d[17]), "+f"(d[18]), "+f"(d[19]), "+f"(d[20]), "+f"(d[21]), "+f"(d[22]), "+f"(d[23]), "+f"(d[24]), "+f"(d[25]), "+f"(d[26]), "+f"(d[27]), "+f"(d[28]), "+f"(d[29]), "+f"(d[30]), "+f"(d[31]), "+f"(d[32]), "+f"(d[33]), "+f"(d[34]), "+f"(d[35]), "+f"(d[36]), "+f"(d[37]), "+f"(d[38]), "+f"(d[39]), "+f"(d[40]), "+f"(d[41]), "+f"(d[42]), "+f"(d[43]), "+f"(d[44]), "+f"(d[45]), "+f"(d[46]), "+f"(d[47]), "+f"(d[48]), "+f"(d[49]), "+f"(d[50]), "+f"(d[51]), "+f"(d[52]), "+f"(d[53]), "+f"(d[54]), "+f"(d[55]), "+f"(d[56]), "+f"(d[57]), "+f"(d[58]), "+f"(d[59]), "+f"(d[60]), "+f"(d[61]), "+f"(d[62]), "+f"(d[63])
        : "r"(a0), "r"(a1), "r"(a2), "r"(a3), "r"(db), "r"(acc), "r"(hb));
}

__device__ __forceinline__ uint32_t pack2(float lo, float hi) {
    uint32_t r;
    asm("cvt.rn.bf16x2.f32 %0, %1, %2;" : "=r"(r) : "f"(hi), "f"(lo));
    return r;
}
__device__ __forceinline__ float bf_lo(uint32_t v) { return __uint_as_float(v << 16); }
__device__ __forceinline__ float bf_hi(uint32_t v) { return __uint_as_float(v & 0xffff0000u); }
__device__ __forceinline__ float rbf(float v) { return bf_lo(pack2(v, v)); }
__device__ __forceinline__ uint32_t badd(uint32_t a, uint32_t b) {
    uint32_t r;
    asm("add.rn.bf16x2 %0, %1, %2;" : "=r"(r) : "r"(a), "r"(b));
    return r;
}
__device__ __forceinline__ uint32_t bsub(uint32_t a, uint32_t b) {
    uint32_t r;
    asm("sub.rn.bf16x2 %0, %1, %2;" : "=r"(r) : "r"(a), "r"(b));
    return r;
}
__device__ __forceinline__ uint32_t bmul(uint32_t a, uint32_t b) {
    uint32_t r;
    asm("mul.rn.bf16x2 %0, %1, %2;" : "=r"(r) : "r"(a), "r"(b));
    return r;
}
__device__ __forceinline__ uint32_t ln_apply(uint32_t x, uint32_t mb, float rs, uint32_t scale, uint32_t shift) {
    const uint32_t d = bsub(x, mb);
    return badd(bmul(pack2(bf_lo(d) * rs, bf_hi(d) * rs), scale), shift);
}
__device__ __forceinline__ float ex2(float v) {
    float r;
    asm("ex2.approx.ftz.f32 %0, %1;" : "=f"(r) : "f"(v));
    return r;
}
__device__ __forceinline__ float rcp(float v) {
    float r;
    asm("rcp.approx.ftz.f32 %0, %1;" : "=f"(r) : "f"(v));
    return r;
}
__device__ __forceinline__ float sqrt_fast(float v) {
    float r;
    asm("sqrt.approx.ftz.f32 %0, %1;" : "=f"(r) : "f"(v));
    return r;
}
__device__ __forceinline__ float ln_rstd(float var) { return rcp(rbf(sqrt_fast(rbf(rbf(var) + 1e-5f)))); }
__device__ __forceinline__ float sigmoid(float v) { return rcp(1.f + ex2(-1.4426950408889634f * v)); }
__device__ __forceinline__ float warp_sum(float v) {
#pragma unroll
    for (int o = 16; o > 0; o >>= 1) v += __shfl_xor_sync(0xffffffffu, v, o);
    return v;
}
__device__ __forceinline__ float quad_sum(float v) {
    v += __shfl_xor_sync(0xffffffffu, v, 1);
    return v + __shfl_xor_sync(0xffffffffu, v, 2);
}

constexpr uint32_t HI_128 = 0x40000040u, HI_IMG = 0x80000080u, HI_Q = 0x80000040u;
template <int M, int RH>
__device__ __forceinline__ uint4 img_pack(const float (&d)[64], float s) {
    uint4 v;
    v.x = pack2(d[16 * M + 2 * RH] * s, d[16 * M + 2 * RH + 1] * s);
    v.y = pack2(d[16 * M + 4 + 2 * RH] * s, d[16 * M + 5 + 2 * RH] * s);
    v.z = pack2(d[16 * M + 8 + 2 * RH] * s, d[16 * M + 9 + 2 * RH] * s);
    v.w = pack2(d[16 * M + 12 + 2 * RH] * s, d[16 * M + 13 + 2 * RH] * s);
    return v;
}
template <int M, int RH>
__device__ __forceinline__ uint4 img_pack(const float (&d)[64]) {
    uint4 v;
    v.x = pack2(d[16 * M + 2 * RH], d[16 * M + 2 * RH + 1]);
    v.y = pack2(d[16 * M + 4 + 2 * RH], d[16 * M + 5 + 2 * RH]);
    v.z = pack2(d[16 * M + 8 + 2 * RH], d[16 * M + 9 + 2 * RH]);
    v.w = pack2(d[16 * M + 12 + 2 * RH], d[16 * M + 13 + 2 * RH]);
    return v;
}
template <int M>
__device__ __forceinline__ void img_store_global(uint8_t* img, uint32_t toff, const float (&d)[64], float s0, float s1) {
    uint4* p = reinterpret_cast<uint4*>(img + toff) + M * 32;
    p[0] = img_pack<M, 0>(d, s0);
    p[128] = img_pack<M, 1>(d, s1);
}
__device__ __forceinline__ void sts128(uint32_t a, uint4 v) {
    asm volatile("st.shared.v4.b32 [%0], {%1, %2, %3, %4};" ::"r"(a), "r"(v.x), "r"(v.y), "r"(v.z), "r"(v.w) : "memory");
}
constexpr float SM_C = 0.08838834764831845f * 1.4426950408889634f;
__device__ __forceinline__ float pack2f(float lo, float hi) {
    float r;
    asm("{\n.reg .b32 t;\ncvt.rn.bf16x2.f32 t, %1, %2;\nmov.b32 %0, t;\n}" : "=f"(r) : "f"(hi), "f"(lo));
    return r;
}
template <int M, bool SCALE, bool PARK>
__device__ __forceinline__ void pack_group(float (&d)[64], float (&v)[8], float s0, float s1) {
#pragma unroll
    for (int i = 0; i < 8; i++) {
        const int k = 16 * M + 4 * (i & 3) + 2 * (i >> 2);
        v[i] = SCALE ? pack2f(d[k] * (i < 4 ? s0 : s1), d[k + 1] * (i < 4 ? s0 : s1)) : pack2f(d[k], d[k + 1]);
        if (PARK && M > 0) d[16 * (M > 0 ? M - 1 : 0) + i] = v[i];
    }
}
template <int M, bool PARK>
__device__ __forceinline__ void q_store_part(uint32_t a, float (&d)[64]) {
    float v[8];
    pack_group<M, false, PARK>(d, v, 0.f, 0.f);
#pragma unroll
    for (int h = 0; h < 2; h++)
        asm volatile("st.shared.v4.f32 [%0], {%1, %2, %3, %4};" ::"r"(a + (M >> 1) * 16384 + (M & 1) * 512 + h * 1024),
                     "f"(v[4 * h]), "f"(v[4 * h + 1]), "f"(v[4 * h + 2]), "f"(v[4 * h + 3]) : "memory");
}
template <bool PARK>
__device__ __forceinline__ void q_store(uint32_t a, uint32_t toff, float (&d)[64]) {
    a += (((toff >> 1) & ~2047u) ^ 8192) + (toff & 511);
    q_store_part<0, PARK>(a, d); q_store_part<1, PARK>(a, d); q_store_part<2, PARK>(a, d); q_store_part<3, PARK>(a, d);
}
template <int M, bool PARK>
__device__ __forceinline__ void ctx_store_part(float4* p, float (&d)[64], float i0, float i1) {
    float v[8];
    pack_group<M, true, PARK>(d, v, i0, i1);
    p[M * 32] = make_float4(v[0], v[1], v[2], v[3]);
    p[M * 32 + 128] = make_float4(v[4], v[5], v[6], v[7]);
}
template <bool PARK>
__device__ __forceinline__ void ctx_store(uint8_t* img, uint32_t toff, float (&o)[64], float l0, float l1) {
    const float i0 = rcp(quad_sum(l0)), i1 = rcp(quad_sum(l1));
    float4* p = reinterpret_cast<float4*>(img + toff);
    ctx_store_part<0, PARK>(p, o, i0, i1); ctx_store_part<1, PARK>(p, o, i0, i1); ctx_store_part<2, PARK>(p, o, i0, i1); ctx_store_part<3, PARK>(p, o, i0, i1);
}

__device__ __forceinline__ void slot_wait(uint32_t bars, uint32_t& ph, uint32_t slot) {
    mbar_wait(bars + 8 * slot, (ph >> slot) & 1);
    ph ^= 1u << slot;
}
__device__ __forceinline__ void load_image(uint32_t sb, uint32_t& ph, uint32_t slot, const void* src, bool first) {
    slot_wait(sb + BAR_EMPTY, ph, slot);
    asm volatile("{\n.reg .pred p;\nelect.sync _|p, 0xffffffff;\n@p mbarrier.arrive.expect_tx.shared::cta.b64 _, [%2], 32768;\n"
                 "@p cp.async.bulk.shared::cluster.global.mbarrier::complete_tx::bytes.L2::cache_hint [%0], [%1], 32768, [%2], %3;\n}"
                 ::"r"(sb + slot * SLOT), "l"(src), "r"(sb + BAR_FULL + 8 * slot), "l"(first ? L2_FIRST : L2_NORMAL) : "memory");
}
__device__ __forceinline__ void load_tile(uint32_t sb, uint32_t& ph, uint32_t slot, const CUtensorMap* m, int row, int cb, bool first) {
    slot_wait(sb + BAR_EMPTY, ph, slot);
    asm volatile("{\n.reg .pred p;\nelect.sync _|p, 0xffffffff;\n@p mbarrier.arrive.expect_tx.shared::cta.b64 _, [%2], 32768;\n"
                 "@p cp.async.bulk.tensor.3d.shared::cluster.global.mbarrier::complete_tx::bytes.L2::cache_hint [%0], [%1, {%3, %4, %5}], [%2], %6;\n}"
                 ::"r"(sb + slot * SLOT), "l"(m), "r"(sb + BAR_FULL + 8 * slot), "r"(0), "r"(row), "r"(cb), "l"(first ? L2_FIRST : L2_NORMAL) : "memory");
}
__device__ __forceinline__ uint32_t ring_next(uint32_t r) { return r == 4 ? 0 : r + 1; }
__device__ __forceinline__ uint32_t w_table(int hp) { return hp ? 0x3104u : 0x4210u; }
__device__ __forceinline__ uint32_t a_table(int hp) { return hp ? 0x625u : 0x635u; }
__device__ __forceinline__ uint32_t a_next(uint32_t& t) {
    const uint32_t s = t & 15;
    t = (t >> 4) | (s << 8);
    return s;
}
constexpr uint32_t O_TABLE = 0x2160435u;
__device__ __forceinline__ uint32_t o_next(uint32_t& t) {
    const uint32_t s = t & 15;
    t = (t >> 4) | (s << 24);
    return s;
}
__device__ __forceinline__ int o_head(int i, int kh) { return i < 16 ? 4 * (i & 7) + 2 * (kh ^ 1) + (i >> 3) : 29 + 2 * kh; }

template <bool INIT>
__device__ __forceinline__ void gemm_issue(float (&d)[64], uint32_t a, uint32_t b, int acc, bool img) {
    const uint32_t ha = img ? HI_IMG : HI_128, o2 = img ? 32 : 4, o4 = img ? 64 : 1024;
    wg_fence();
#pragma unroll
    for (int k = 0; k < 8; k++) {
        if (INIT && k == 0) wgmma_ss128_init<1>(d, a, b, ha);
        else wgmma_ss128<1>(d, a + (k >> 2) * o4 + ((k >> 1) & 1) * o2 + (k & 1) * 2, b + k * 128, k ? 1 : acc, ha);
    }
    wg_commit();
}

__device__ __forceinline__ void h_store(const uint32_t* x, float mean, float sq, uint32_t sb, int row) {
    const int lane = threadIdx.x & 31;
    const float rs = ln_rstd(sq * (1.f / 512.f));
    const uint32_t mb = pack2(mean, mean);
    uint8_t* p = g_h + ((row >> 7) * 8 + (lane >> 3)) * 16384 + (row & 127) * 128 + (((lane ^ row) & 7) << 4);
#pragma unroll
    for (int i = 0; i < 2; i++) {
        const uint4 a = lds128(sb + SM_TAB + 1024 + i * 512 + lane * 16), c = lds128(sb + SM_TAB + i * 512 + lane * 16);
        *reinterpret_cast<uint4*>(p + i * 65536) = make_uint4(ln_apply(x[4 * i], mb, rs, a.x, c.x), ln_apply(x[4 * i + 1], mb, rs, a.y, c.y),
                                                              ln_apply(x[4 * i + 2], mb, rs, a.z, c.z), ln_apply(x[4 * i + 3], mb, rs, a.w, c.w));
    }
}

template <bool ODD>
__device__ __forceinline__ void proj_tile(float (&acc)[64], float (&prev)[64], int t, int q0, uint32_t sb, int wg, bool elected, uint32_t& fph,
                                          uint32_t wtab, uint32_t& atab, uint8_t* prev_img, uint32_t toff, float s0, float s1, bool first,
                                          const bf16* x, int xrow) {
    const uint32_t a0 = desc_k(sb + (wg ^ (ODD && t == 5)) * 8192), b0 = desc_mn(sb);
    const int lane = threadIdx.x & 31;
    float mean[2] = {0.f, 0.f}, rstd[2] = {0.f, 0.f};
    uint32_t xn[16];
#pragma unroll
    for (int i = 0; i < 4; i++) {
        uint4 v = make_uint4(0, 0, 0, 0);
        if (ODD && first) v = __ldg(reinterpret_cast<const uint4*>(x) + xrow * 64 + lane + 32 * i);
        xn[4 * i] = v.x; xn[4 * i + 1] = v.y; xn[4 * i + 2] = v.z; xn[4 * i + 3] = v.w;
    }
    constexpr int U = ODD ? UNR : 1;
#pragma unroll U
    for (int q = ODD ? 0 : q0; q < 4; q++) {
        if (ODD && t == 5 && q == 3) break;
        const uint32_t ws = (wtab >> (4 * q)) & 15, as = a_next(atab);
        if (!ODD && t != 2) slot_wait(sb + BAR_FULL, fph, ws);
        slot_wait(sb + BAR_FULL, fph, as);
        bar_sync(1 + wg, 256);
        gemm_issue<false>(acc, a0 + as * (SLOT / 16), b0 + ws * (SLOT / 16), q, false);
        bar_arrive(2 - wg, 256);
        wg_wait<1>();
        reg_fence(prev);
        if (ODD && t == 5) {
            if (q == 2) {
                q_store<false>(sb + 5 * SLOT, toff, prev);
                fence_async_smem();
            }
        } else if (ODD || !first) {
            if (q == 0) img_store_global<0>(prev_img, toff, prev, s0, s1);
            if (q == 1) img_store_global<1>(prev_img, toff, prev, s0, s1);
            if (q == 2) img_store_global<2>(prev_img, toff, prev, s0, s1);
            if (q == 3) img_store_global<3>(prev_img, toff, prev, s0, s1);
        }
        if (ODD && q == 1 && first) {
#pragma unroll
            for (int k = 0; k < 16; k++) mean[k >> 3] += bf_lo(xn[k]) + bf_hi(xn[k]);
#pragma unroll
            for (int i = 0; i < 2; i++) mean[i] = warp_sum(mean[i]) * (1.f / 512.f);
        }
        if (ODD && q == 2 && first) {
#pragma unroll
            for (int k = 0; k < 16; k++) {
                const float d0 = bf_lo(xn[k]) - mean[k >> 3], d1 = bf_hi(xn[k]) - mean[k >> 3];
                rstd[k >> 3] = fmaf(d0, d0, fmaf(d1, d1, rstd[k >> 3]));
            }
#pragma unroll
            for (int i = 0; i < 2; i++) rstd[i] = warp_sum(rstd[i]);
        }
        if (ODD && q == 3 && first) {
            mbar_wait(sb + BAR_FLAG + 8 * 8, 0);
            h_store(xn, mean[0], rstd[0], sb, xrow);
        }
        wg_wait<0>();
        mbar_arrive_if(sb + BAR_EMPTY + 8 * as, elected && !(ODD && (q & 1) && t == 5));
        if (ODD) mbar_arrive_if(sb + BAR_EMPTY + 8 * ws, elected && t != 1);
        if (ODD && q == 3 && first) {
            h_store(xn + 8, mean[1], rstd[1], sb, xrow + 1);
            __syncwarp();
            mbar_arrive_if(sb + BAR_DONE, lane == 0);
        }
    }
    reg_fence(acc);
}

__device__ __forceinline__ void qk_issue(float (&s)[64], uint32_t q, uint32_t k) {
    wg_fence();
    wgmma_ss128_init<0>(s, q, k, HI_Q, HI_IMG);
#pragma unroll
    for (int i = 1; i < 8; i++) wgmma_ss128<0>(s, q + (i >> 2) * 1024 + (i & 2) * 16 + (i & 1) * 2, k + (i >> 1) * 32 + (i & 1) * 2, 1, HI_Q, HI_IMG);
    wg_commit();
}
__device__ __forceinline__ void qk_issue(float (&s)[32], uint32_t q, uint32_t k) {
    wg_fence();
    wgmma_ss64_init<0>(s, q, k, HI_Q, HI_IMG);
#pragma unroll
    for (int i = 1; i < 8; i++) wgmma_ss64<0>(s, q + (i >> 2) * 1024 + (i & 2) * 16 + (i & 1) * 2, k + (i >> 1) * 32 + (i & 1) * 2, 1, HI_Q, HI_IMG);
    wg_commit();
}
__device__ __forceinline__ void pv_issue(float (&o)[64], const uint32_t (&p)[32], uint32_t v, int acc, bool half) {
    if (half) {
        asm volatile("// half" ::: "memory");
        wg_fence();
#pragma unroll
        for (int i = 0; i < 4; i++) wgmma_rs128(o, p[4 * i], p[4 * i + 1], p[4 * i + 2], p[4 * i + 3], v + i * 256, i ? 1 : acc, HI_IMG);
        wg_commit();
        asm volatile("// half" ::: "memory");
    } else {
        wg_fence();
#pragma unroll
        for (int i = 0; i < 8; i++) wgmma_rs128(o, p[4 * i], p[4 * i + 1], p[4 * i + 2], p[4 * i + 3], v + i * 256, i ? 1 : acc, HI_IMG);
        wg_commit();
    }
}
template <int B, int N>
__device__ __forceinline__ void tri_mask(float (&s)[N], int x) {
#pragma unroll
    for (int k = 0; k < 7; k++)
        asm("{\n.reg .pred p, q;\nsetp.lt.s32 p, %4, %5;\nsetp.le.s32 q, %4, %5;\n"
            "@p mov.b32 %0, 0fFF800000;\n@q mov.b32 %1, 0fFF800000;\n@p mov.b32 %2, 0fFF800000;\n@q mov.b32 %3, 0fFF800000;\n}"
            : "+f"(s[B + 4 * k]), "+f"(s[B + 4 * k + 1]), "+f"(s[B + 4 * k + 6]), "+f"(s[B + 4 * k + 7]) : "r"(x), "r"(8 * k));
    asm("{\n.reg .pred p, q;\nsetp.lt.s32 p, %2, 56;\nsetp.le.s32 q, %2, 56;\n@p mov.b32 %0, 0fFF800000;\n@q mov.b32 %1, 0fFF800000;\n}"
        : "+f"(s[B + 28]), "+f"(s[B + 29]) : "r"(x));
}
__device__ __forceinline__ void tri_mask_copy(float (&s)[64], const float (&h)[32], int x) {
#pragma unroll
    for (int i = 0; i < 32; i++) {
        asm("{\n.reg .pred p;\nsetp.lt.s32 p, %2, %3;\nselp.f32 %0, 0fFF800000, %1, p;\n}"
            : "=f"(s[i]) : "f"(h[i]), "r"(x), "r"(8 * (i >> 2) - 4 * (i & 2) + (i & 1)));
        s[32 + i] = __uint_as_float(0xff800000u);
    }
}
constexpr float SM_HI = 1152921504606846976.f, SM_LO = 1.f / 1152921504606846976.f;
__device__ __forceinline__ bool softmax_unsafe(float t0, float t1, bool first) {
    bool bad = __any_sync(0xffffffffu, fmaxf(t0, t1) > SM_HI);
    if (first) {
        uint32_t a = __ballot_sync(0xffffffffu, t0 >= SM_LO), b = __ballot_sync(0xffffffffu, t1 >= SM_LO);
        a |= a >> 1;
        b |= b >> 1;
        bad |= ((a | (a >> 2)) & (b | (b >> 2)) & 0x11111111u) != 0x11111111u;
    }
    return bad;
}
__device__ __forceinline__ void softmax_shift(float (&s)[64], float d0, float d1) {
#pragma unroll
    for (int i = 0; i < 64; i++) s[i] -= (i & 2) ? d1 : d0;
}
__device__ __forceinline__ void softmax_remax(float (&s)[64], float (&m)[2], bool first, float& a0, float& a1) {
    float m0 = fmaxf(s[0], s[1]), m1 = fmaxf(s[2], s[3]);
#pragma unroll
    for (int k = 1; k < 16; k++) {
        m0 = fmaxf(m0, fmaxf(s[4 * k], s[4 * k + 1]));
        m1 = fmaxf(m1, fmaxf(s[4 * k + 2], s[4 * k + 3]));
    }
    m0 = fmaxf(m0, __shfl_xor_sync(0xffffffffu, m0, 1));
    m1 = fmaxf(m1, __shfl_xor_sync(0xffffffffu, m1, 1));
    m0 = fmaxf(m0, __shfl_xor_sync(0xffffffffu, m0, 2));
    m1 = fmaxf(m1, __shfl_xor_sync(0xffffffffu, m1, 2));
    if (!first) {
        m0 = fmaxf(m0, 0.f);
        m1 = fmaxf(m1, 0.f);
    }
    a0 = first ? 1.f : ex2(-m0);
    a1 = first ? 1.f : ex2(-m1);
    m[0] += m0;
    m[1] += m1;
    softmax_shift(s, m0, m1);
}
template <int J0, int J1>
__device__ __forceinline__ void softmax_exp(const float (&s)[64], uint32_t (&p)[32], float (&t)[4]) {
#pragma unroll
    for (int k = J0; k < J1; k++) {
        const float e0 = ex2(s[4 * k]), e1 = ex2(s[4 * k + 1]), e2 = ex2(s[4 * k + 2]), e3 = ex2(s[4 * k + 3]);
        if (k == 0) { t[0] = e0; t[1] = e1; t[2] = e2; t[3] = e3; }
        else { t[0] += e0; t[1] += e1; t[2] += e2; t[3] += e3; }
        p[2 * k] = pack2(e0, e1);
        p[2 * k + 1] = pack2(e2, e3);
    }
}
__device__ __forceinline__ void fma8(float (&acc)[8], float a, uint4 w) {
    acc[0] = fmaf(a, bf_lo(w.x), acc[0]); acc[1] = fmaf(a, bf_hi(w.x), acc[1]);
    acc[2] = fmaf(a, bf_lo(w.y), acc[2]); acc[3] = fmaf(a, bf_hi(w.y), acc[3]);
    acc[4] = fmaf(a, bf_lo(w.z), acc[4]); acc[5] = fmaf(a, bf_hi(w.z), acc[5]);
    acc[6] = fmaf(a, bf_lo(w.w), acc[6]); acc[7] = fmaf(a, bf_hi(w.w), acc[7]);
}
__device__ __forceinline__ void mma16816(float (&d)[4], const uint32_t* a, uint32_t b0, uint32_t b1) {
    asm("mma.sync.aligned.m16n8k16.row.col.f32.bf16.bf16.f32 {%0, %1, %2, %3}, {%4, %5, %6, %7}, {%8, %9}, {%0, %1, %2, %3};"
        : "+f"(d[0]), "+f"(d[1]), "+f"(d[2]), "+f"(d[3]) : "r"(a[0]), "r"(a[1]), "r"(a[2]), "r"(a[3]), "r"(b0), "r"(b1));
}
__device__ __forceinline__ uint32_t best_key(const uint32_t* keys, int lane, uint32_t ep) {
    uint32_t best;
#pragma unroll 1
    for (;;) {
        const uint4 k = ld_poll(reinterpret_cast<const uint4*>(keys) + lane);
        best = max(max(k.x, k.y), max(k.z, k.w));
        if (__all_sync(0xffffffffu, (((k.x ^ ep) | (k.y ^ ep) | (k.z ^ ep) | (k.w ^ ep)) & 31) == 0)) break;
    }
    return __reduce_max_sync(0xffffffffu, best);
}

__global__ void __launch_bounds__(384, 1)
fused_kernel(const __grid_constant__ CUtensorMap tm_ckv, const __grid_constant__ CUtensorMap tm_wq,
             const __grid_constant__ CUtensorMap tm_wuk, const __grid_constant__ CUtensorMap tm_wuv,
             const __grid_constant__ CUtensorMap tm_wo, const __grid_constant__ CUtensorMap tm_wg,
             const __grid_constant__ CUtensorMap tm_wu,
             const __grid_constant__ CUtensorMap tm_wm, const __grid_constant__ CUtensorMap tm_x, const Params P) {
    extern __shared__ __align__(1024) uint8_t smem[];
    const uint32_t sb = (uint32_t)__cvta_generic_to_shared(smem);
    const int tid = threadIdx.x, lane = tid & 31, warp = __shfl_sync(0xffffffffu, tid >> 5, 0), wg = warp >> 2;
    uint32_t sm;
    asm("mov.u32 %0, %%smid;" : "=r"(sm));
    const uint32_t smq = ((sm - 64) * 147) >> 11;
    const int rb = !P.by_smid ? blockIdx.x : sm < 64 ? (sm & 14) * 8 + (sm >> 4) * 2 + (sm & 1)
                 : sm < 120 ? ((sm - 64 - smq * 14) & 14) * 8 + 24 + smq * 2 + (sm & 1) : sm < 124 ? sm + 8 : sm - 116;
    const int grp = rb >> 3, j = rb & 7, cq = j & 3, kh = grp & 1, ort = (grp & 14) + (j >> 2);
    if (warp == 0) TS(0);

    if (rb >= NCTA) {
        float* sc = reinterpret_cast<float*>(smem + 6 * SLOT);
        float* red = sc + 512;
        if (tid == 256) {
            for (int i = 0; i < 6; i++) { mbar_init(sb + BAR_FULL + 8 * i, 1); mbar_init(sb + BAR_EMPTY + 8 * i, 8); }
            fence_async_smem();
        }
        __syncthreads();
        uint32_t ph = 0, sl = 0;
        if (tid == 256) {
#pragma unroll 1
            for (int i = 0; i < 24; i++) {
                mbar_wait(sb + BAR_EMPTY + 8 * sl, ph ^ 1);
                mbar_expect(sb + BAR_FULL + 8 * sl, SLOT);
                tma2d(sb + sl * SLOT, &tm_wm, (i >> 3) * 1024 + (rb - NCTA) * 256, (i & 7) * 64, sb + BAR_FULL + 8 * sl);
                if (++sl == 6) { sl = 0; ph ^= 1; }
            }
            mbar_wait(sb + BAR_EMPTY, 1);
            mbar_wait(sb + BAR_EMPTY + 8, 1);
#pragma unroll 1
            for (int i = 0; i <= NFFN / NSPARE; i++) {
                const int b = (rb - NCTA) * (NFFN / NSPARE) + i;
                if (i < NFFN / NSPARE) {
                    const uint32_t f = sb + BAR_FULL + 8 * (i & 1), d = sb + (i & 1) * SLOT;
                    asm volatile("cp.async.bulk.wait_group.read 0;" ::: "memory");
                    mbar_expect(f, SLOT);
                    tma2d(d, &tm_wg, b * 16, 0, f);
                    tma2d(d + 8192, &tm_wg, b * 16, 256, f);
                    tma2d(d + 16384, &tm_wu, b * 16, 0, f);
                    tma2d(d + 24576, &tm_wu, b * 16, 256, f);
                }
                if (i) {
                    mbar_wait(sb + BAR_FULL + 8 * (~i & 1), ((i - 1) >> 1) & 1);
                    asm volatile("cp.async.bulk.global.shared::cta.bulk_group [%0], [%1], 32768;\ncp.async.bulk.commit_group;"
                                 ::"l"(g_wf + (b - 1) * SLOT), "r"(sb + (~i & 1) * SLOT) : "memory");
                }
            }
            asm volatile("cp.async.bulk.wait_group 0;" ::: "memory");
            fence_async_global();
            flag_add(&g_sync.modcnt[32]);
            TS(4);
        } else if (tid < 256) {
            const uint32_t c2 = __ldg(reinterpret_cast<const uint32_t*>(P.c) + tid);
            sc[2 * tid] = rbf(bf_lo(c2) * sigmoid(bf_lo(c2)));
            sc[2 * tid + 1] = rbf(bf_hi(c2) * sigmoid(bf_hi(c2)));
            bar_sync(1, 256);
#pragma unroll 1
            for (int ps = 0; ps < 3; ps++) {
                float acc[8] = {0.f, 0.f, 0.f, 0.f, 0.f, 0.f, 0.f, 0.f};
#pragma unroll 1
                for (int bt = 0; bt < 8; bt++) {
                    mbar_wait(sb + BAR_FULL + 8 * sl, ph);
#pragma unroll
                    for (int i = 0; i < 8; i++)
                        fma8(acc, sc[bt * 64 + warp * 8 + i], *reinterpret_cast<const uint4*>(smem + sl * SLOT + (warp * 8 + i) * 512 + lane * 16));
                    __syncwarp();
                    mbar_arrive_if(sb + BAR_EMPTY + 8 * sl, lane == 0);
                    if (++sl == 6) { sl = 0; ph ^= 1; }
                }
                *reinterpret_cast<float4*>(red + warp * 256 + lane * 8) = make_float4(acc[0], acc[1], acc[2], acc[3]);
                *reinterpret_cast<float4*>(red + warp * 256 + lane * 8 + 4) = make_float4(acc[4], acc[5], acc[6], acc[7]);
                bar_sync(1, 256);
                float v = 0.f;
#pragma unroll
                for (int i = 0; i < 8; i++) v += red[i * 256 + tid];
                g_mod[ps * 1024 + (rb - NCTA) * 256 + tid] = __float2bfloat16_rn(v);
                bar_sync(1, 256);
                if (tid == 0 && ps != 1) flag_add(&g_sync.modcnt[(ps >> 1) * 32]);
                if (warp == 0) TS(1 + ps);
            }
        }
        return;
    }

    if (tid == 256) {
        if (sb & 1023) __trap();
        asm volatile("prefetch.tensormap [%0];" ::"l"((j & 1) ? &tm_wuv : &tm_wuk) : "memory");
        asm volatile("prefetch.tensormap [%0];" ::"l"(&tm_ckv) : "memory");
        for (int i = 0; i < 7; i++) { mbar_init(sb + BAR_FULL + 8 * i, 1); mbar_init(sb + BAR_EMPTY + 8 * i, 2); }
        for (int i = 0; i < 9; i++) mbar_init(sb + BAR_DONE + 8 * i, 8);
        for (int i = 0; i < 10; i++) mbar_init(sb + BAR_FLAG + 8 * i, 1);
        *reinterpret_cast<uint32_t*>(smem + SM_EP + 4) = 0;
        mbar_init(sb + BAR_END, 8);
        fence_async_smem();
    }
    __syncthreads();

    if (wg == 2) {
        asm volatile("setmaxnreg.dec.sync.aligned.u32 40;");
        if (warp == 8) {
            uint32_t eph = 0x7f, r = 0;
            const CUtensorMap* tw = (j & 1) ? &tm_wuv : &tm_wuk;
#pragma unroll 1
            for (int hp = 0; hp < 2; hp++) {
                const int hc = 4 * grp + 2 * hp;
                uint32_t wtab = w_table(hp), atab = a_table(hp);
#pragma unroll 1
                for (int u = 0; u < 4; u++) {
                    load_tile(sb, eph, (wtab >> (4 * u)) & 15, tw, u * 128, hc, HINT & 1); PT();
                    load_tile(sb, eph, a_next(atab), &tm_ckv, (j >> 1) * 128, u * 2, (HINT & 8) && hp); PT();
                    if (hp == 1 && (u & 1) && lane == 0) asm volatile("red.relaxed.gpu.global.add.u32 [%0], 1;" ::"l"(&g_sync.rdcnt[(grp * 2 + (u >> 1)) * 8]) : "memory");
                }
#pragma unroll 1
                for (int u = 4; u < 16; u++) {
                    if (hp == 1 && (u & 7) == 4) mbar_wait(sb + BAR_FLAG + 24 + (u & 8), 0);
                    load_tile(sb, eph, a_next(atab), &tm_ckv, ((u & 12) + (j >> 1)) * 128, (u & 3) * 2, (HINT & 8) && hp); PT();
                }
                mbar_wait(sb + BAR_FLAG, 0);
                fence_async_global();
#pragma unroll 1
                for (int u = 0; u < 4; u++) {
                    load_tile(sb, eph, (wtab >> (4 * u)) & 15, &tm_wq, u * 128, hc, HINT & 1); PT();
                    load_image(sb, eph, a_next(atab), g_h + ((15 - j) * 4 + u) * SLOT, (HINT & 8) && hp); PT();
                }
                mbar_wait(sb + BAR_FLAG + 8 + 32 * hp, 0);
                fence_async_global();
#pragma unroll 1
                for (int u = 0; u < 4; u++) { load_image(sb, eph, a_next(atab), g_h + (j * 4 + u) * SLOT, (HINT & 8) && hp); PT(); }
                const uint8_t* kv = g_KV + (size_t)(grp * 32 + 30 * hp) * SLOT;
                const int step = hp ? -2 * SLOT : 2 * SLOT;
                load_image(sb, eph, r, kv, HINT & 4); PT();
                r = ring_next(r);
#pragma unroll 1
                for (int n = 1; n <= 16; n++) {
                    if (n == 8) {
                        mbar_wait(sb + BAR_FLAG + 16 + 32 * hp, 0);
                        fence_async_global();
                    }
                    mbar_arrive_if(sb + BAR_PF, lane == 0 && (n == PF1 || n == PF2));
                    const uint8_t* v = kv + SLOT;
                    kv += n < 16 - j ? step : n == 16 - j ? (2 * j - 15) * step : -step;
                    load_image(sb, eph, r, kv, HINT & 4); PT();
                    r = ring_next(r);
                    load_image(sb, eph, r, v, HINT & 4); PT();
                    r = ring_next(r);
                }
                load_image(sb, eph, r, kv + SLOT, HINT & 4); PT();
                r = ring_next(r);
            }
            uint32_t otab = O_TABLE, ready = 0, todo = 0x7f00;
#pragma unroll 1
            for (int i = 0; i < 17; i++) {
                const uint32_t want = i >= 8 && i < 15 ? todo : 1u << i;
                if (!(ready & want)) {
                    do {
                        asm volatile("ld.acquire.cta.shared.u32 %0, [%1];" : "=r"(ready) : "r"(sb + SM_EP + 4) : "memory");
                        ready = __shfl_sync(0xffffffffu, ready, 0);
                    } while (!(ready & want));
                    fence_async_global();
                }
                const int pick = __ffs(ready & want) - 1;
                todo &= ~(1u << pick);
                const int head = o_head(pick, kh);
                const uint8_t* src = g_ctx + (size_t)(ort * 32 + head) * SLOT;
                if (i < 15) {
                    load_image(sb, eph, o_next(otab), src, HINT & 16);
                } else {
                    const uint32_t as = o_next(otab), d = sb + as * SLOT;
                    slot_wait(sb + BAR_EMPTY, eph, as);
                    asm volatile("{\n.reg .pred p, q;\nelect.sync _|p, 0xffffffff;\n@p mbarrier.arrive.expect_tx.shared::cta.b64 _, [%2], %3;\n"
                                 "@p cp.async.bulk.shared::cluster.global.mbarrier::complete_tx::bytes [%0], [%1], 16384, [%2];\n}"
                                 ::"r"(d + kh * 16384), "l"(src + kh * 16384), "r"(sb + BAR_FULL + 8 * as), "r"(i == 15 ? 32768 : 16384) : "memory");
                    if (i == 15)
                        asm volatile("{\n.reg .pred p;\nelect.sync _|p, 0xffffffff;\n"
                                     "@p cp.async.bulk.tensor.3d.shared::cluster.global.mbarrier::complete_tx::bytes [%0], [%1, {%3, %4, %5}], [%2];\n}"
                                     ::"r"(d + (kh ^ 1) * 16384), "l"(&tm_x), "r"(sb + BAR_FULL + 8 * as), "r"(0), "r"(ort * 128 + kh * 64), "r"(cq * 2) : "memory");
                }
                PT();
                load_tile(sb, eph, o_next(otab), &tm_wo, head * 128, cq * 2, HINT & 2); PT();
            }
            if (rb < NFFN) {
                load_image(sb, eph, o_next(otab), g_wf + rb * SLOT, false);
                const uint32_t s2 = o_next(otab);
                slot_wait(sb + BAR_EMPTY, eph, s2);
                asm volatile("{\n.reg .pred p;\nelect.sync _|p, 0xffffffff;\n@p mbarrier.arrive.expect_tx.shared::cta.b64 _, [%2], 16384;\n"
                             "@p cp.async.bulk.shared::cluster.global.mbarrier::complete_tx::bytes [%0], [%1], 16384, [%2];\n}"
                             ::"r"(sb + s2 * SLOT), "l"(P.wdown + rb * 8192), "r"(sb + BAR_FULL + 8 * s2) : "memory");
            }
        } else {
            const int hw = warp - 9;
            if (hw == 1 && lane == 0) {
                l2_prefetch(P.ckv + rb * 2048, 4096);
                mbar_watch(sb + BAR_FULL + 8 * PF0, 0);
                l2_prefetch(P.ckv + 512 * 512 + rb * 2048, 4096);
                mbar_watch(sb + BAR_FULL + 8 * 4, 0);
                l2_prefetch(P.x + rb * 8192, 16384);
                l2_prefetch(P.ckv + 1024 * 512 + rb * 4096, 8192);
                TS(40);
                if (j < 4) tma3d_prefetch(&tm_wq, j * 128, grp * 4);
                mbar_watch(sb + BAR_PF, 0);
                l2_prefetch(P.ckv + rb * 8192, 16384);
                l2_prefetch(g_h + rb * 16384, 16384);
                mbar_watch(sb + BAR_PF, 1);
                tma3d_prefetch((j & 1) ? &tm_wuv : &tm_wuk, (j >> 1) * 128, grp * 4 + 2);
                if (j < 4) tma3d_prefetch(&tm_wq, j * 128, grp * 4 + 2);
                mbar_watch(sb + BAR_PF, 0);
                l2_prefetch(g_ctx + (size_t)(ort * 32 + o_head(cq, kh)) * SLOT, SLOT);
                l2_prefetch(g_ctx + (size_t)(ort * 32 + o_head(cq + 4, kh)) * SLOT, SLOT);
                mbar_watch(sb + BAR_PF, 1);
                l2_prefetch(reinterpret_cast<const uint8_t*>(P.wo) + rb * 32768, 32768);
                mbar_watch(sb + BAR_FLAG + 8 * 7, 0);
                if (rb < NFFN) {
                    l2_prefetch(g_wf + rb * SLOT, SLOT);
                    l2_prefetch(P.wdown + rb * 8192, 16384);
                }
                l2_prefetch(P.x + rb * 8192, 16384);
                if (OBINIT) {
                    const uint32_t v = lds32(sb + SM_EP) - 1;
#pragma unroll 1
                    for (int i = 0; i < 32; i++) sts128(sb + SM_RED + i * 16, make_uint4(v, v, v, v));
                    fence_async_smem();
#pragma unroll 1
                    for (int i = 0; i < OB / 32; i++)
                        asm volatile("cp.async.bulk.global.shared::cta.bulk_group [%0], [%1], 512;" ::"l"(g_out + rb * OB + i * 32), "r"(sb + SM_RED) : "memory");
                    asm volatile("cp.async.bulk.commit_group;\ncp.async.bulk.wait_group 0;" ::: "memory");
                    fence_async_global();
                }
                mbar_arrive(sb + BAR_PF);
                mbar_watch(sb + BAR_END, 0);
            }
            if (hw == 0) {
#pragma unroll 1
                for (int i = 0; i < 9; i++) {
                    const int hp = i > 4, k = (i - 1) & 3;
                    if (lane == 0) {
                        mbar_wait(sb + BAR_DONE + 8 * i, 0);
                        flag_add(i == 0 ? &g_sync.hcnt[grp * 8] : k < 2 ? &g_sync.kvcnt[((2 * grp + hp) * 2 + k) * 8]
                                                                        : &g_sync.ctxcnt[(k == 2 ? 15 - j : j) * 32 + 2 * grp + hp]);
                    }
                    if (i == 0) TS(43);
                }
            }
            if (hw == 2) {
                const uint32_t ep = __ldcg(&g_sync.epoch[0]) + 1;
                if (lane == 0) {
                    asm volatile("st.shared.u32 [%0], %1;" ::"r"(sb + SM_EP), "r"(ep) : "memory");
                    flag_wait(&g_sync.modcnt[0], NSPARE * ep);
                }
                __syncwarp();
#pragma unroll
                for (int i = 0; i < 4; i++) {
                    uint4 v = __ldcg(reinterpret_cast<const uint4*>(g_mod) + lane + 32 * i);
                    if (i >= 2) v = make_uint4(badd(v.x, ONE2), badd(v.y, ONE2), badd(v.z, ONE2), badd(v.w, ONE2));
                    sts128(sb + SM_TAB + i * 512 + lane * 16, v);
                }
                __syncwarp();
                if (lane == 0) mbar_arrive(sb + BAR_FLAG + 8 * 8);
                TS(42);
#pragma unroll 1
                for (int i = 0; i < 8; i++) {
                    if (lane == 0) mbar_wait(sb + BAR_DONE + 8 * (i == 7 ? 6 : i == 4 ? 3 : i), 0);
                    __syncwarp();
                    const uint32_t* f = i == 0 ? &g_sync.hcnt[(lane ? j : 15 - j) * 8]
                                      : i == 3 || i == 4 ? &g_sync.rdcnt[(grp * 2 + i - 3) * 8]
                                      : i == 7 ? &g_sync.modcnt[32] : &g_sync.kvcnt[(4 * grp + (i > 4 ? i - 3 : i - 1)) * 8];
                    if (lane < (i ? 1 : 2)) flag_wait(f, 8 * ep);
                    __syncwarp();
                    if (i == 7) {
                        const uint32_t *mp = reinterpret_cast<const uint32_t*>(g_mod) + lane, *wp = reinterpret_cast<const uint32_t*>(P.wr) + lane;
                        float ra = 0.f, rs = 0.f;
#pragma unroll 1
                        for (int k = 0; k < 256; k += 32) {
                            const uint32_t ga = __ldcg(mp + 512 + k), sh = __ldcg(mp + 768 + k), c1 = badd(__ldcg(mp + 1024 + k), ONE2);
                            const uint32_t gb = __ldcg(mp + 1280 + k), ww = __ldg(wp + k);
                            const float a0 = bf_lo(c1) * bf_lo(ww), a1 = bf_hi(c1) * bf_hi(ww);
                            ra += a0 + a1;
                            rs = fmaf(bf_lo(sh), bf_lo(ww), fmaf(bf_hi(sh), bf_hi(ww), rs));
                            if (k >> 6 == cq) {
                                sts128(sb + SM_TAB + ((k & 32) + lane) * 16, make_uint4(ga << 16, ga & 0xffff0000u, __float_as_uint(a0), __float_as_uint(a1)));
                                sts128(sb + SM_TAB + 1024 + ((k & 32) + lane) * 16, make_uint4(c1, sh, gb, 0));
                            }
                        }
                        *reinterpret_cast<float2*>(smem + SM_EP + 8) = make_float2(warp_sum(ra), warp_sum(rs));
                        __syncwarp();
                    }
                    if (lane == 0) mbar_arrive(sb + BAR_FLAG + 8 * i);
                    TS(48 + i);
                }
                const uint32_t* f = &g_sync.ctxcnt[ort * 32 + o_head(min(lane, 16), kh)];
                uint32_t ready = 0;
                while (ready != ~0u) {
                    uint32_t v;
                    asm volatile("ld.acquire.gpu.global.u32 %0, [%1];" : "=r"(v) : "l"(f) : "memory");
                    const uint32_t now = __ballot_sync(0xffffffffu, (int)(v - ep) >= 0);
                    if (now != ready && lane == 0) asm volatile("st.release.cta.shared.u32 [%0], %1;" ::"r"(sb + SM_EP + 4), "r"(now) : "memory");
                    if ((now & 0xff) == 0xff) mbar_wait(sb + BAR_DONE + 8 * 7, 0);
                    ready = now;
                    __nanosleep(POLL_NS);
                }
                TS(45);
            }
        }
    } else {
        asm volatile("setmaxnreg.inc.sync.aligned.u32 232;");
        const bool elected = (tid & 127) == 0;
        const int g = lane >> 2, c4 = lane & 3;
        const uint32_t toff = warp * 4096 + g * 64 + ((c4 ^ (g >> 1)) << 4);
        uint32_t fph = 0, r = 0;
        if (wg == 1) bar_arrive(1, 256);
        const uint32_t kd = desc_k(sb), wd = desc_mn(sb), vd = (sb >> 4) | (32u << 16);
        const int nL = 16 - j, hn = nL - 1 + wg;
        float s[64], o[64], li[2] = {0.f, 0.f};
        uint8_t* cimg = g_ctx;
#pragma unroll 1
        for (int hp = 0; hp < 2; hp++) {
            {
                const int step = hp ? -8 * SLOT : 8 * SLOT;
                uint8_t* img = g_KV + (size_t)(grp * 32 + (hp ? j ^ 30 : j)) * SLOT - step;
                const float sc = (j & 1) ? 1.f : SM_C;
                const uint32_t wtab = w_table(hp);
                uint32_t atab = hp ? 0x256u : a_table(0);
#pragma unroll 1
                for (int t = 0; t < 6; t += 2) {
                    proj_tile<false>(s, o, t, t ? 0 : 2 * hp, sb, wg, elected, fph, wtab, atab, t ? img : cimg, toff, t ? sc : li[0], t ? sc : li[1], (hp | t) == 0, P.x, rb * 16 + warp * 2);
                    __syncwarp();
                    mbar_arrive_if(sb + BAR_DONE + 4 * t + 32 * hp, lane == 0 && (hp | t) != 0);
                    if (elected) TS(1 + 10 * hp + t + 20 * wg);
                    proj_tile<true>(o, s, t + 1, 0, sb, wg, elected, fph, wtab, atab, img + step, toff, sc, sc, (hp | t) == 0, P.x, rb * 16 + warp * 2);
                    if (elected) TS(2 + 10 * hp + t + 20 * wg);
                    img += 2 * step;
                }
            }
            float m[2] = {0.f, 0.f}, l[2] = {0.f, 0.f}, t[4] = {0.f, 0.f, 0.f, 0.f};
            bool shifted = false, bad = false, plain = false;
            uint32_t p[32];
#pragma unroll
            for (int i = 0; i < 32; i++) p[i] = 0;
            uint32_t qa = desc_k(sb + 5 * SLOT + (wg ^ 1) * 8192);
            uint8_t* img = g_ctx + (size_t)((15 - j) * 32 + 2 * grp + hp) * SLOT;
            slot_wait(sb + BAR_FULL, fph, r);
            int n = -1;
#pragma unroll 1
            for (;;) {
                while (bad || plain) {
                    if (bad) {
                        float a0, a1;
                        softmax_remax(s, m, n == 0 || n == nL, a0, a1);
                        shifted = true;
                        l[0] *= a0;
                        l[1] *= a1;
#pragma unroll
                        for (int i = 0; i < 64; i++) o[i] *= (i & 2) ? a1 : a0;
                    }
                    softmax_exp<0, 16>(s, p, t);
                    t[0] += t[1];
                    t[2] += t[3];
                    bad = !bad && softmax_unsafe(t[0], t[2], false);
                    plain = false;
                }
#pragma unroll 1
                do {
                    l[0] += t[0];
                    l[1] += t[2];
                    if (++n > 16) break;
                    const uint32_t ks = r;
                    uint32_t vs = ring_next(r);
                    r = ring_next(vs);
                    bar_sync(1 + wg, 256);
                    if (n == 0 || (uint32_t)(n + 1 - nL) <= (uint32_t)(1 + wg)) {
                        const int x = (warp & 3) * 16 + g - 2 * c4;
                        if (n == 0) {
                            r = vs;
                            vs = 4 - hp;
                            qk_issue(s, qa, kd + ks * (SLOT / 16));
                            slot_wait(sb + BAR_FULL, fph, 6);
                            gemm_issue<false>(o, qa + SLOT / 16, wd + vs * (SLOT / 16), 1, false);
                            bar_arrive(2 - wg, 256);
                            wg_wait<1>();
                            reg_fence(s);
                        } else if (n == hn) {
                            float sh[32];
                            qk_issue(sh, qa, kd + ks * (SLOT / 16));
                            slot_wait(sb + BAR_FULL, fph, vs);
                            pv_issue(o, p, vd + vs * (SLOT / 16), 1, false);
                            bar_arrive(2 - wg, 256);
                            wg_wait<1>();
                            reg_fence(sh);
                            tri_mask_copy(s, sh, x);
                        } else {
                            qk_issue(s, qa, kd + ks * (SLOT / 16));
                            slot_wait(sb + BAR_FULL, fph, vs);
                            pv_issue(o, p, vd + vs * (SLOT / 16), n != nL + 1, n == hn + 1);
                            bar_arrive(2 - wg, 256);
                            wg_wait<1>();
                            reg_fence(s);
                            if (n <= nL) tri_mask<32>(s, x);
                        }
                        mbar_arrive_if(sb + BAR_EMPTY + 8 * ks, elected);
                        mbar_arrive_if(sb + BAR_EMPTY + 8 * (n == 16 ? 6 : 5), elected && (n == 16 || n == nL - 1));
                        if (n == nL - 1) {
                            qa += SLOT / 16;
                            fence_async_smem();
                        }
                        if (shifted) {
                            if (n == nL) {
                                m[0] = m[1] = 0.f;
                                shifted = false;
                            }
                            softmax_shift(s, m[0], m[1]);
                        }
                        float e[4 * EARLY];
#pragma unroll
                        for (int i = 0; i < 4 * EARLY; i++) {
                            e[i] = ex2(s[i]);
                            t[i & 3] = i < 4 ? e[i] : t[i & 3] + e[i];
                        }
                        reg_fence(e);
                        slot_wait(sb + BAR_FULL, fph, r);
                        wg_wait<0>();
                        reg_fence(o);
                        reg_fence(e);
                        mbar_arrive_if(sb + BAR_EMPTY + 8 * vs, elected);
#pragma unroll
                        for (int i = 0; i < 2 * EARLY; i++) p[i] = pack2(e[2 * i], e[2 * i + 1]);
                        softmax_exp<EARLY, 8>(s, p, t);
                        if (n == 0) q_store<(PARKS & 1) != 0>(sb + 6 * SLOT, toff, o);
                        if (n == nL) {
                            ctx_store<(PARKS & 2) != 0>(img, toff, o, l[0], l[1]);
                            __syncwarp();
                            mbar_arrive_if(sb + BAR_DONE + 24 + 32 * hp, lane == 0);
                            l[0] = l[1] = 0.f;
                        }
                        if (n != hn) softmax_exp<8, 16>(s, p, t);
                        t[0] += t[1];
                        t[2] += t[3];
                        bad = softmax_unsafe(t[0], t[2], n == 0 || n == nL);
                        continue;
                    }
                    qk_issue(s, qa, kd + ks * (SLOT / 16));
                    slot_wait(sb + BAR_FULL, fph, vs);
                    pv_issue(o, p, vd + vs * (SLOT / 16), n != 1 && n != nL + 1, false);
                    bar_arrive(2 - wg, 256);
                    wg_wait<1>();
                    reg_fence(s);
                    mbar_arrive_if(sb + BAR_EMPTY + 8 * ks, elected);
                    mbar_arrive_if(sb + BAR_EMPTY + 8 * 6, elected && n == 16);
                    if (shifted) {
                        slot_wait(sb + BAR_FULL, fph, r);
                        wg_wait<0>();
                        reg_fence(o);
                        mbar_arrive_if(sb + BAR_EMPTY + 8 * vs, elected);
                        softmax_shift(s, m[0], m[1]);
                        plain = true;
                        break;
                    }
                    float e[4 * EARLY];
#pragma unroll
                    for (int i = 0; i < 4 * EARLY; i++) {
                        e[i] = ex2(s[i]);
                        t[i & 3] = i < 4 ? e[i] : t[i & 3] + e[i];
                    }
                    reg_fence(e);
                    slot_wait(sb + BAR_FULL, fph, r);
                    wg_wait<0>();
                    reg_fence(o);
                    reg_fence(e);
                    mbar_arrive_if(sb + BAR_EMPTY + 8 * vs, elected);
#pragma unroll
                    for (int i = 0; i < 2 * EARLY; i++) p[i] = pack2(e[2 * i], e[2 * i + 1]);
                    softmax_exp<EARLY, 16>(s, p, t);
                    t[0] += t[1];
                    t[2] += t[3];
                    bad = softmax_unsafe(t[0], t[2], false);
                } while (!bad);
                if (!bad && !plain) break;
            }
            const uint32_t vs = r, ga = desc_k(sb + (hp ? 2 * (wg ^ kh ^ 1) : wg) * 8192), as = 2 + 2 * hp;
            r = ring_next(r);
            slot_wait(sb + BAR_FULL, fph, 5);
            slot_wait(sb + BAR_FULL, fph, r);
            bar_sync(1 + wg, 256);
            gemm_issue<true>(s, ga + 5 * (SLOT / 16), wd + r * (SLOT / 16), 0, hp);
            pv_issue(o, p, vd + vs * (SLOT / 16), j, hn == 16);
            bar_arrive(2 - wg, 256);
            li[0] = rcp(quad_sum(l[0]));
            li[1] = rcp(quad_sum(l[1]));
            cimg = img + (ptrdiff_t)(2 * j - 15) * 32 * SLOT + (wg ? -16384 : 16384);
            wg_wait<1>();
            mbar_arrive_if(sb + BAR_EMPTY + 8 * 5, elected);
            mbar_arrive_if(sb + BAR_EMPTY + 8 * r, elected && hp);
            wg_wait<0>();
            mbar_arrive_if(sb + BAR_EMPTY + 8 * vs, elected);
            reg_fence(o);
            img_store_global<0>(cimg, toff, o, li[0], li[1]);
            slot_wait(sb + BAR_FULL, fph, as);
            slot_wait(sb + BAR_FULL, fph, 0);
            bar_sync(1 + wg, 256);
            gemm_issue<false>(s, ga + as * (SLOT / 16), wd, 1, hp);
            bar_arrive(2 - wg, 256);
            reg_fence(o);
            img_store_global<1>(cimg, toff, o, li[0], li[1]);
            wg_wait<0>();
            mbar_arrive_if(sb + BAR_EMPTY + 8 * as, elected);
            mbar_arrive_if(sb + BAR_EMPTY, elected && hp);
            if (elected) TS(8 + 10 * hp + 20 * wg);
        }
        uint32_t otab = 0x0435216u;
        const uint32_t oa = desc_k(sb + (wg ^ kh ^ 1) * 16384);
        const int t7 = tid & 127, w4 = warp & 3, row = ort * 128 + kh * 64 + w4 * 16 + g;
#pragma unroll 1
        for (int i = 2; i < 15 - wg; i++) {
            const uint32_t as = o_next(otab), ws = o_next(otab);
            slot_wait(sb + BAR_FULL, fph, as);
            slot_wait(sb + BAR_FULL, fph, ws);
            bar_sync(1 + wg, 256);
            gemm_issue<false>(s, oa + as * (SLOT / 16), wd + ws * (SLOT / 16), 1, true);
            bar_arrive(2 - wg, 256);
            wg_wait<1>();
            reg_fence(o);
            if (i == 2) img_store_global<2>(cimg, toff, o, li[0], li[1]);
            if (i == CLAST) {
                img_store_global<3>(cimg, toff, o, li[0], li[1]);
                __syncwarp();
                mbar_arrive_if(sb + BAR_DONE + 64, lane == 0);
            }
            wg_wait<0>();
            mbar_arrive_if(sb + BAR_EMPTY + 8 * as, elected);
            mbar_arrive_if(sb + BAR_EMPTY + 8 * ws, elected);
        }
        mbar_wait(sb + BAR_PF, 0);
        const uint32_t ep = lds32(sb + SM_EP);
        if (wg == 0) {
            reg_fence(s);
            if (elected) TS(9);
#pragma unroll
            for (int v = 0; v < 8; v++)
                st_pub(g_out + rb * OB + v * 128 + t7, make_uint4((pack2(s[8 * v], s[8 * v + 1]) & ~1u) | (ep & 1), pack2(s[8 * v + 2], s[8 * v + 3]),
                                                                      pack2(s[8 * v + 4], s[8 * v + 5]), pack2(s[8 * v + 6], s[8 * v + 7])), true);
            o_next(otab); o_next(otab); o_next(otab); o_next(otab);
            const uint32_t s1 = o_next(otab), s2 = o_next(otab);
            bar_sync(4, 256);
            uint32_t wf[64];
            float wn[64];
            if (rb < NFFN) {
                slot_wait(sb + BAR_FULL, fph, s1);
                const uint32_t a = sb + s1 * SLOT + (w4 * 128 + (lane >> 4) * 8 + (lane & 7)) * 32 + ((lane >> 3) & 1) * 16;
#pragma unroll
                for (int i = 0; i < 16; i++)
                    asm volatile("ldmatrix.sync.aligned.m8n8.x4.trans.shared.b16 {%0, %1, %2, %3}, [%4];"
                                 : "=r"(wf[4 * i]), "=r"(wf[4 * i + 1]), "=r"(wf[4 * i + 2]), "=r"(wf[4 * i + 3])
                                 : "r"(a + (i >> 3) * 16384 + (i & 7) * 512) : "memory");
                slot_wait(sb + BAR_FULL, fph, s2);
#pragma unroll
                for (int i = 0; i < 16; i++) {
                    const uint2 w = *reinterpret_cast<const uint2*>(smem + s2 * SLOT + i * 1024 + t7 * 8);
                    wn[4 * i] = bf_lo(w.x); wn[4 * i + 1] = bf_hi(w.x); wn[4 * i + 2] = bf_lo(w.y); wn[4 * i + 3] = bf_hi(w.y);
                }
                reg_fence(wn);
            }
            const uint32_t gbf = __ldcg(reinterpret_cast<const uint32_t*>(g_mod) + 1280 + rb * 2 + (tid & 1));
            if (elected) TS(10);
            const uint32_t best = best_key(g_key + cq * 128, lane, ep);
            const int sel = (~best >> 5) & 2047;
            if (elected) TS(19);
            const uint4* cp = g_cand + (sel >> 4) * 192;
            float* sred = reinterpret_cast<float*>(smem + SM_RED);
            const int pq = (2 * rb + (tid & 1)) & 63, pv = (pq >> 2) / 3;
            const uint4* fp = cp + (rb >> 5) * 24 + pv * 4 + (pq & 3);
            uint4 fh = ld_poll(fp), fx = ld_poll(fp + 96);
            if (rb < NFFN) {
                uint4 cv[6];
                for (;;) {
                    uint32_t bad = 0;
#pragma unroll
                    for (int v = 0; v < 6; v++) cv[v] = ld_poll(cp + w4 * 24 + v * 4 + c4);
#pragma unroll
                    for (int v = 0; v < 6; v++) bad |= cv[v].w ^ ep;
                    if (__all_sync(0xffffffffu, bad == 0)) break;
                }
                if (elected) TS(20);
                float d[4][4] = {};
#pragma unroll
                for (int k = 0; k < 8; k++) {
                    const uint32_t b0 = (&cv[(2 * k) / 3].x)[(2 * k) % 3], b1 = (&cv[(2 * k + 1) / 3].x)[(2 * k + 1) % 3];
                    mma16816(d[k & 1], wf + 4 * k, b0, b1);
                    mma16816(d[2 + (k & 1)], wf + 32 + 4 * k, b0, b1);
                }
                const float u = (c4 & 2) ? ((c4 & 1) ? d[2][2] + d[3][2] : d[2][0] + d[3][0]) : ((c4 & 1) ? d[0][2] + d[1][2] : d[0][0] + d[1][0]);
                sred[w4 * 32 + c4 * 8 + g] = u;
                bar_sync(3, 128);
                const float v = rbf((sred[lane] + sred[32 + lane]) + (sred[64 + lane] + sred[96 + lane]));
                const float act = rbf(rbf(v * sigmoid(v)) * __shfl_down_sync(0xffffffffu, v, 16));
                float y[4] = {0.f, 0.f, 0.f, 0.f};
#pragma unroll
                for (int k = 0; k < 16; k++) {
                    const float a = __shfl_sync(0xffffffffu, act, k);
#pragma unroll
                    for (int i = 0; i < 4; i++) y[i] = fmaf(a, wn[4 * k + i], y[i]);
                }
                st_pub(g_out + rb * OB + OB_Y + t7, make_uint4((__float_as_uint(y[0]) & ~15u) | (ep & 15), __float_as_uint(y[1]), __float_as_uint(y[2]), __float_as_uint(y[3])), true);
            }
            if (rb == 0 && tid == 0) g_sync.epoch[0] = ep;
            if (elected) TS(60);
            uint4 yv;
            do yv = ld_poll(g_out + min(t7, NFFN - 1) * OB + OB_Y + rb);
            while (!__all_sync(0xffffffffu, ((yv.x ^ ep) & 15) == 0));
            if (elected) TS(61);
            float y[4] = {0.f, 0.f, 0.f, 0.f};
            if (t7 < NFFN) { y[0] = __uint_as_float(yv.x); y[1] = __uint_as_float(yv.y); y[2] = __uint_as_float(yv.z); y[3] = __uint_as_float(yv.w); }
            const float z0 = ((lane & 16) ? y[2] : y[0]) + __shfl_xor_sync(0xffffffffu, (lane & 16) ? y[0] : y[2], 16);
            const float z1 = ((lane & 16) ? y[3] : y[1]) + __shfl_xor_sync(0xffffffffu, (lane & 16) ? y[1] : y[3], 16);
            float z = ((lane & 8) ? z1 : z0) + __shfl_xor_sync(0xffffffffu, (lane & 8) ? z0 : z1, 8);
            z += __shfl_xor_sync(0xffffffffu, z, 4);
            z = quad_sum(z);
            if ((lane & 7) == 0) sred[128 + (lane >> 3) * 4 + w4] = z;
            bar_sync(3, 128);
            if (tid < 2) {
                while (fh.w != ep || fx.w != ep) { fh = ld_poll(fp); fx = ld_poll(fp + 96); }
                const float4 y0 = *reinterpret_cast<const float4*>(sred + 128 + tid * 8), y1 = *reinterpret_cast<const float4*>(sred + 132 + tid * 8);
                const int cm = (pq >> 2) - 3 * pv;
                const uint32_t h2 = cm == 0 ? fh.x : cm == 1 ? fh.y : fh.z, x2 = cm == 0 ? fx.x : cm == 1 ? fx.y : fx.z;
                const float sg = sigmoid(bf_hi((best & 0x80000000u) ? (best ^ 0x80000000u) : ~best));
                reinterpret_cast<uint32_t*>(P.out)[sel * 256 + rb * 2 + tid] =
                    badd(x2, bmul(gbf, badd(h2, bmul(pack2((y0.x + y0.y) + (y0.z + y0.w), (y1.x + y1.y) + (y1.z + y1.w)), pack2(sg, sg)))));
            }
            if (elected) TS(62);
        } else {
            const float4* tf = reinterpret_cast<const float4*>(smem + SM_TAB) + c4;
            const uint32_t as14 = otab & 15, xa = sb + ((otab >> 8) & 15) * SLOT + (kh ^ 1) * 16384 + (w4 * 16 + (lane & 15)) * 128;
            uint32_t x2[32];
            bar_sync(2, 256);
#pragma unroll 1
            for (int i = 14; i < 17; i++) {
                const uint32_t as = o_next(otab), ws = o_next(otab);
                slot_wait(sb + BAR_FULL, fph, as);
                slot_wait(sb + BAR_FULL, fph, ws);
                gemm_issue<false>(s, oa + as * (SLOT / 16), wd + ws * (SLOT / 16), 1, true);
                wg_wait<1>();
                mbar_arrive_if(sb + BAR_EMPTY + 8 * as14, elected && i == 15);
            }
            if (elected) TS(29);
            {
#pragma unroll
                for (int k = 0; k < 8; k++)
                    asm volatile("ldmatrix.sync.aligned.m8n8.x4.shared.b16 {%0, %1, %2, %3}, [%4];"
                                 : "=r"(x2[4 * k]), "=r"(x2[4 * k + 1]), "=r"(x2[4 * k + 2]), "=r"(x2[4 * k + 3])
                                 : "r"(xa + (k >> 2) * 8192 + (((2 * (k & 3) + (lane >> 4)) ^ (lane & 7)) << 4)) : "memory");
            }
            wg_wait<0>();
            reg_fence(s);
            bar_arrive(4, 256);
            if (elected) TS(39);
            const uint4* pr = g_out + (rb ^ 8) * OB + t7;
            uint4 pa[8];
#pragma unroll
            for (int v = 0; v < 8; v++) pa[v] = ld_poll(pr + v * 128);
            float4 tc[16];
#pragma unroll
            for (int k = 0; k < 16; k++) {
                tc[k] = tf[k * 4];
#pragma unroll
                for (int i = 4 * k; i < 4 * k + 4; i++) s[i] = fmaf((i & 1) ? tc[k].y : tc[k].x, s[i], (i & 1) ? bf_hi(x2[i >> 1]) : bf_lo(x2[i >> 1]));
            }
            reg_fence(s);
            for (;;) {
                uint32_t bad = 0;
#pragma unroll
                for (int v = 0; v < 8; v++) bad |= pa[v].x ^ ep;
                if (__all_sync(0xffffffffu, (bad & 1) == 0)) break;
#pragma unroll
                for (int v = 0; v < 8; v++) pa[v] = ld_poll(pr + v * 128);
            }
            if (elected) TS(30);
            float st[6] = {0.f, 0.f, 0.f, 0.f, 0.f, 0.f};
#pragma unroll
            for (int i = 0; i < 64; i++) {
                const int rh = (i >> 1) & 1;
                const uint32_t w = (&pa[i >> 3].x)[(i >> 1) & 3];
                const float v = fmaf((i & 1) ? tc[i >> 2].y : tc[i >> 2].x, (i & 1) ? bf_hi(w) : bf_lo(w), s[i]);
                s[i] = v;
                st[rh] += v;
                st[2 + rh] = fmaf(v, v, st[2 + rh]);
                st[4 + rh] = fmaf(v, (i & 1) ? tc[i >> 2].w : tc[i >> 2].z, st[4 + rh]);
            }
#pragma unroll
            for (int i = 0; i < 6; i++) st[i] = quad_sum(st[i]);
            st_pub(g_out + rb * OB + OB_STAT + (w4 * 8 + g) * 2 + (c4 & 1),
                   make_uint4(__float_as_uint((c4 & 1) ? st[1] : st[0]), __float_as_uint((c4 & 1) ? st[3] : st[2]),
                              __float_as_uint((c4 & 1) ? st[5] : st[4]), ep), c4 < 2);
            if (elected) TS(56);
            uint32_t cb[16], sh[16], gb[16];
#pragma unroll
            for (int i = 0; i < 16; i++) {
                const float4 c = tf[64 + i * 4];
                cb[i] = __float_as_uint(c.x); sh[i] = __float_as_uint(c.y); gb[i] = __float_as_uint(c.z);
            }
            const float ra = __uint_as_float(lds32(sb + SM_EP + 8)), rb0 = __uint_as_float(lds32(sb + SM_EP + 12));
#pragma unroll
            for (int i = 0; i < 32; i++) x2[i] = pack2(s[2 * i], s[2 * i + 1]);
            reg_fence(x2);
            uint4 r0, r1;
            for (;;) {
                r0 = ld_poll(g_out + ((rb & ~3) + c4) * OB + OB_STAT + (w4 * 8 + g) * 2);
                r1 = ld_poll(g_out + ((rb & ~3) + c4) * OB + OB_STAT + (w4 * 8 + g) * 2 + 1);
                if (__all_sync(0xffffffffu, r0.w == ep && r1.w == ep)) break;
            }
            if (elected) TS(57);
            const float m0 = quad_sum(__uint_as_float(r0.x)) * (1.f / 512.f), m1 = quad_sum(__uint_as_float(r1.x)) * (1.f / 512.f);
            const float rs0 = ln_rstd(fmaxf(fmaf(-m0, m0, quad_sum(__uint_as_float(r0.y)) * (1.f / 512.f)), 0.f));
            const float rs1 = ln_rstd(fmaxf(fmaf(-m1, m1, quad_sum(__uint_as_float(r1.y)) * (1.f / 512.f)), 0.f));
            const uint32_t mb0 = pack2(m0, m0), mb1 = pack2(m1, m1);
            const uint32_t lg = pack2(fmaf(rs0, fmaf(-bf_lo(mb0), ra, quad_sum(__uint_as_float(r0.z))), rb0),
                                      fmaf(rs1, fmaf(-bf_lo(mb1), ra, quad_sum(__uint_as_float(r1.z))), rb0));
            const uint32_t u0 = lg << 16, u1 = lg & 0xffff0000u;
            const uint32_t k0 = ((u0 ^ (((int)u0 >> 31) | 0x80000000u)) & 0xffff0000u) | ((2047 - row) << 5) | (ep & 31);
            const uint32_t k1 = ((u1 ^ (((int)u1 >> 31) | 0x80000000u)) & 0xffff0000u) | ((2039 - row) << 5) | (ep & 31);
            const uint32_t kb = __reduce_max_sync(0xffffffffu, max(k0, k1));
            st_pub(g_key + cq * 128 + (row >> 4), kb, lane == 0);
            {
                uint32_t cx[18], ch[18];
#pragma unroll
                for (int i = 0; i < 16; i++) {
                    cx[i] = kb == k1 ? x2[2 * i + 1] : x2[2 * i];
                    ch[i] = ln_apply(cx[i], kb == k1 ? mb1 : mb0, kb == k1 ? rs1 : rs0, cb[i], sh[i]);
                }
                cx[16] = cx[17] = ch[16] = ch[17] = 0;
                uint4* cp = g_cand + (row >> 4) * 192 + cq * 24 + c4;
#pragma unroll
                for (int v = 0; v < 6; v++) st_pub(cp + v * 4, make_uint4(ch[3 * v], ch[3 * v + 1], ch[3 * v + 2], ep), kb == k0 || kb == k1);
#pragma unroll
                for (int v = 0; v < 6; v++) st_pub(cp + 96 + v * 4, make_uint4(cx[3 * v], cx[3 * v + 1], cx[3 * v + 2], ep), kb == k0 || kb == k1);
            }
            if (elected) TS(58);
            uint2 ov[16];
#pragma unroll
            for (int i = 0; i < 16; i++) {
                const int rh = i & 1, jj = i & 14;
                const uint32_t v0 = badd(x2[2 * jj + rh], bmul(gb[jj], ln_apply(x2[2 * jj + rh], rh ? mb1 : mb0, rh ? rs1 : rs0, cb[jj], sh[jj])));
                const uint32_t v1 = badd(x2[2 * jj + 2 + rh], bmul(gb[jj + 1], ln_apply(x2[2 * jj + 2 + rh], rh ? mb1 : mb0, rh ? rs1 : rs0, cb[jj + 1], sh[jj + 1])));
                const uint32_t rv = __shfl_xor_sync(0xffffffffu, (c4 & 1) ? v0 : v1, 1);
                ov[i] = (c4 & 1) ? make_uint2(rv, v1) : make_uint2(v0, rv);
            }
            uint2* op = reinterpret_cast<uint2*>(P.out) + row * 128 + cq * 32 + (c4 & 1) * 2 + (c4 >> 1);
#pragma unroll
            for (int i = 0; i < 16; i++)
                if (kb != ((i & 1) ? k1 : k0)) op[(i & 1) * 1024 + (i & 14) * 2] = ov[i];
            const uint32_t best = best_key(g_key + cq * 128, lane, ep);
            if (best != kb) {
#pragma unroll
                for (int i = 0; i < 16; i++)
                    if (kb == ((i & 1) ? k1 : k0)) op[(i & 1) * 1024 + (i & 14) * 2] = ov[i];
            }
            if (elected) TS(59);
        }
        mbar_arrive_if(sb + BAR_END, lane == 0);
    }
}

typedef CUresult (*EncodeFn)(CUtensorMap*, CUtensorMapDataType, cuuint32_t, void*, const cuuint64_t*, const cuuint64_t*,
                             const cuuint32_t*, const cuuint32_t*, CUtensorMapInterleave, CUtensorMapSwizzle,
                             CUtensorMapL2promotion, CUtensorMapFloatOOBfill);

void make_2d(EncodeFn fn, CUtensorMap* m, const void* p, uint64_t cols, uint64_t rows, uint32_t bc, uint32_t br) {
    cuuint64_t dims[2] = {cols, rows}, strides[1] = {cols * 2};
    cuuint32_t box[2] = {bc, br}, es[2] = {1, 1};
    fn(m, CU_TENSOR_MAP_DATA_TYPE_BFLOAT16, 2, const_cast<void*>(p), dims, strides, box, es, CU_TENSOR_MAP_INTERLEAVE_NONE,
       CU_TENSOR_MAP_SWIZZLE_NONE, CU_TENSOR_MAP_L2_PROMOTION_L2_128B, CU_TENSOR_MAP_FLOAT_OOB_FILL_NONE);
}
void make_3d(EncodeFn fn, CUtensorMap* m, const void* p, uint64_t cols, uint64_t rows, uint32_t br = 128) {
    cuuint64_t dims[3] = {64, rows, cols / 64}, strides[2] = {cols * 2, 128};
    cuuint32_t box[3] = {64, br, 2}, es[3] = {1, 1, 1};
    fn(m, CU_TENSOR_MAP_DATA_TYPE_BFLOAT16, 3, const_cast<void*>(p), dims, strides, box, es, CU_TENSOR_MAP_INTERLEAVE_NONE,
       CU_TENSOR_MAP_SWIZZLE_128B, CU_TENSOR_MAP_L2_PROMOTION_L2_256B, CU_TENSOR_MAP_FLOAT_OOB_FILL_NONE);
}

}

extern "C" void kernel_launch(void* const* d_in, const int* in_sizes, int n_in, void* d_out, int out_size) {
    static EncodeFn fn = nullptr;
    static int sms = 0;
    if (!fn) {
        void* f = nullptr;
        cudaDriverEntryPointQueryResult st;
        cudaGetDriverEntryPoint("cuTensorMapEncodeTiled", &f, cudaEnableDefault, &st);
        fn = (EncodeFn)f;
        int dev = 0;
        cudaGetDevice(&dev);
        cudaDeviceGetAttribute(&sms, cudaDevAttrMultiProcessorCount, dev);
        cudaFuncSetAttribute(fused_kernel, cudaFuncAttributeMaxDynamicSharedMemorySize, SMEM_BYTES);
    }
    CUtensorMap ckv, wq, wuk, wuv, wo, wg, wu, wm, xm;
    make_3d(fn, &ckv, d_in[1], 512, 2048);
    make_3d(fn, &xm, d_in[0], 512, 2048, 64);
    make_3d(fn, &wq, d_in[2], 4096, 512);
    make_3d(fn, &wuk, d_in[3], 4096, 512);
    make_3d(fn, &wuv, d_in[4], 4096, 512);
    make_3d(fn, &wo, d_in[5], 512, 4096);
    make_2d(fn, &wg, d_in[8], 1792, 512, 16, 256);
    make_2d(fn, &wu, d_in[9], 1792, 512, 16, 256);
    make_2d(fn, &wm, d_in[12], 3072, 512, 256, 64);
    Params p;
    p.x = (const bf16*)d_in[0];
    p.ckv = (const bf16*)d_in[1];
    p.wo = (const bf16*)d_in[5];
    p.wr = (const bf16*)d_in[7];
    p.wdown = (const bf16*)d_in[10];
    p.c = (const bf16*)d_in[11];
    p.out = (bf16*)d_out;
    p.by_smid = sms == NCTA + NSPARE;
    fused_kernel<<<NCTA + NSPARE, 384, SMEM_BYTES>>>(ckv, wq, wuk, wuv, wo, wg, wu, wm, xm, p);
}
```

```cpp
#include <cuda.h>
#include <cuda_bf16.h>
#include <cuda_runtime.h>
#include <stdint.h>
#include <stdio.h>

namespace {

typedef __nv_bfloat16 bf16;
typedef unsigned long long u64;

constexpr int NCTA = 128, NSPARE = 4;
constexpr int SLOT = 32768;
constexpr int SM_BAR = 7 * SLOT;
constexpr int BAR_FULL = SM_BAR;
constexpr int BAR_EMPTY = BAR_FULL + 8 * 7;
constexpr int BAR_DONE = BAR_EMPTY + 8 * 7;
constexpr int BAR_FLAG = BAR_DONE + 8 * 9;
constexpr int BAR_PF = BAR_FLAG + 8 * 9;
constexpr int BAR_END = BAR_PF + 8;
constexpr int SM_EP = BAR_END + 8;
constexpr int SM_RED = SM_BAR + 384;
constexpr int SM_TAB = SM_BAR + 1024;
constexpr int SMEM_BYTES = SM_BAR + 3072;
constexpr int NFFN = 112;
#define HINT 29
constexpr u64 L2_NORMAL = 0x1000000000000000ull, L2_FIRST = 0x12F0000000000000ull;
#define PF0 0
#define PF1 13
#define PF2 11
#define UNR 4
#define PARKS 7
#define POLL_NS 50
#define CLAST 2
#define OBINIT 1
#define MC 15
#define EARLY 7
constexpr uint32_t SPIN_LIMIT = 1u << 22;
constexpr uint32_t ONE2 = 0x3f803f80u;

struct Sync {
    uint32_t modcnt[2 * 32];
    uint32_t hcnt[16 * 8];
    uint32_t kvcnt[32 * 2 * 8];
    uint32_t ctxcnt[16 * 32];
    uint32_t rdcnt[16 * 2 * 8];
    uint32_t epoch[32];
};

__device__ __align__(1024) uint8_t g_KV[16 * 16 * 2 * SLOT];
__device__ __align__(1024) uint8_t g_ctx[16 * 32 * SLOT];
__device__ __align__(1024) uint8_t g_h[16 * 4 * SLOT];
constexpr int OB = 1216, OB_STAT = 1024, OB_Y = 1088;
__device__ __align__(1024) uint4 g_out[128 * OB];
__device__ __align__(1024) bf16 g_mod[3072];
__device__ __align__(1024) uint4 g_cand[128 * 192];
__device__ __align__(1024) uint32_t g_key[4 * 128];
__device__ __align__(1024) uint8_t g_wf[NFFN * SLOT];
__device__ __align__(1024) Sync g_sync;
#define TS(i)

#define PT()

struct Params {
    const bf16 *x, *ckv, *wo, *wr, *wdown, *c;
    bf16* out;
    int by_smid;
};

__device__ __forceinline__ void mbar_init(uint32_t bar, uint32_t cnt) {
    asm volatile("mbarrier.init.shared::cta.b64 [%0], %1;" ::"r"(bar), "r"(cnt) : "memory");
}
__device__ __forceinline__ void mbar_wait(uint32_t bar, uint32_t parity) {
    asm volatile("{\n.reg .pred p;\nL_%=:\nmbarrier.try_wait.parity.shared::cta.b64 p, [%0], %1;\n@!p bra L_%=;\n}" ::"r"(bar), "r"(parity) : "memory");
}
__device__ __forceinline__ void mbar_watch(uint32_t bar, uint32_t parity) {
    asm volatile("{\n.reg .pred p;\n.reg .u32 n;\nmov.u32 n, 0;\n"
                 "L_%=:\nmbarrier.try_wait.parity.shared::cta.b64 p, [%0], %1;\n@p bra D_%=;\n"
                 "add.u32 n, n, 1;\nsetp.lt.u32 p, n, %2;\n@p bra L_%=;\ntrap;\nD_%=:\n}"
                 ::"r"(bar), "r"(parity), "n"(SPIN_LIMIT) : "memory");
}
__device__ __forceinline__ void mbar_arrive(uint32_t bar) {
    asm volatile("mbarrier.arrive.shared::cta.b64 _, [%0];" ::"r"(bar) : "memory");
}
__device__ __forceinline__ void mbar_arrive_if(uint32_t bar, bool on) {
    asm volatile("{\n.reg .pred p;\nsetp.ne.s32 p, %1, 0;\n@p mbarrier.arrive.shared::cta.b64 _, [%0];\n}" ::"r"(bar), "r"((int)on) : "memory");
}
__device__ __forceinline__ void mbar_expect(uint32_t bar, uint32_t bytes) {
    asm volatile("mbarrier.arrive.expect_tx.shared::cta.b64 _, [%0], %1;" ::"r"(bar), "r"(bytes) : "memory");
}
__device__ __forceinline__ void tma2d(uint32_t dst, const CUtensorMap* m, int c0, int c1, uint32_t bar) {
    asm volatile("cp.async.bulk.tensor.2d.shared::cluster.global.mbarrier::complete_tx::bytes [%0], [%1, {%3, %4}], [%2];"
                 ::"r"(dst), "l"(m), "r"(bar), "r"(c0), "r"(c1) : "memory");
}
__device__ __forceinline__ void tma3d_prefetch(const CUtensorMap* m, int row, int cb) {
    asm volatile("cp.async.bulk.prefetch.tensor.3d.L2.global [%0, {%1, %2, %3}];" ::"l"(m), "r"(0), "r"(row), "r"(cb) : "memory");
}
__device__ __forceinline__ void l2_prefetch(const void* p, uint32_t bytes) {
    asm volatile("cp.async.bulk.prefetch.L2.global [%0], %1;" ::"l"(p), "r"(bytes) : "memory");
}
__device__ __forceinline__ void flag_wait(const uint32_t* f, uint32_t target) {
    asm volatile("{\n.reg .pred p;\n.reg .u32 v;\n"
                 "L_%=:\nld.acquire.gpu.global.u32 v, [%0];\nsub.u32 v, v, %1;\nsetp.lt.s32 p, v, 0;\n@p nanosleep.u32 100;\n@p bra L_%=;\n}"
                 ::"l"(f), "r"(target) : "memory");
}
__device__ __forceinline__ uint4 ld_poll(const uint4* p) {
    uint4 v;
    asm volatile("ld.relaxed.gpu.global.v4.u32 {%0, %1, %2, %3}, [%4];" : "=r"(v.x), "=r"(v.y), "=r"(v.z), "=r"(v.w) : "l"(p) : "memory");
    return v;
}
__device__ __forceinline__ void st_pub(uint4* p, uint4 v, bool on) {
    asm volatile("{\n.reg .pred p;\nsetp.ne.s32 p, %5, 0;\n@p st.relaxed.gpu.global.v4.u32 [%0], {%1, %2, %3, %4};\n}"
                 ::"l"(p), "r"(v.x), "r"(v.y), "r"(v.z), "r"(v.w), "r"((int)on) : "memory");
}
__device__ __forceinline__ void st_pub(uint32_t* p, uint32_t v, bool on) {
    asm volatile("{\n.reg .pred p;\nsetp.ne.s32 p, %2, 0;\n@p st.relaxed.gpu.global.u32 [%0], %1;\n}" ::"l"(p), "r"(v), "r"((int)on) : "memory");
}
__device__ __forceinline__ void flag_add(uint32_t* p) {
    asm volatile("red.release.gpu.global.add.u32 [%0], 1;" ::"l"(p) : "memory");
}
__device__ __forceinline__ uint32_t lds32(uint32_t a) {
    uint32_t v;
    asm volatile("ld.shared.u32 %0, [%1];" : "=r"(v) : "r"(a) : "memory");
    return v;
}
__device__ __forceinline__ uint4 lds128(uint32_t a) {
    uint4 v;
    asm volatile("ld.shared.v4.u32 {%0, %1, %2, %3}, [%4];" : "=r"(v.x), "=r"(v.y), "=r"(v.z), "=r"(v.w) : "r"(a) : "memory");
    return v;
}
__device__ __forceinline__ void fence_async_global() { asm volatile("fence.proxy.async.global;" ::: "memory"); }
__device__ __forceinline__ void fence_async_smem() { asm volatile("fence.proxy.async.shared::cta;" ::: "memory"); }
__device__ __forceinline__ void bar_sync(int id, int n) { asm volatile("bar.sync %0, %1;" ::"r"(id), "r"(n) : "memory"); }
__device__ __forceinline__ void bar_arrive(int id, int n) { asm volatile("bar.arrive %0, %1;" ::"r"(id), "r"(n) : "memory"); }
__device__ __forceinline__ void wg_fence() { asm volatile("wgmma.fence.sync.aligned;" ::: "memory"); }
__device__ __forceinline__ void wg_commit() { asm volatile("wgmma.commit_group.sync.aligned;" ::: "memory"); }
template <int N> __device__ __forceinline__ void wg_wait() { asm volatile("wgmma.wait_group.sync.aligned %0;" ::"n"(N) : "memory"); }
template <int N> __device__ __forceinline__ void reg_fence(float (&d)[N]) {
#pragma unroll
    for (int i = 0; i < N; i++) asm volatile("" : "+f"(d[i])::"memory");
}
template <int N> __device__ __forceinline__ void reg_fence(uint32_t (&d)[N]) {
#pragma unroll
    for (int i = 0; i < N; i++) asm volatile("" : "+r"(d[i])::"memory");
}
__device__ __forceinline__ uint32_t desc_k(uint32_t a) { return ((a & 0x3ffff) >> 4) | (1u << 16); }
__device__ __forceinline__ uint32_t desc_mn(uint32_t a) { return ((a & 0x3ffff) >> 4) | (1024u << 16); }

template <int TB>
__device__ __forceinline__ void wgmma_ss128(float (&d)[64], uint32_t da, uint32_t db, int acc, uint32_t ha = 0x40000040u, uint32_t hb = 0x40000040u) {
    asm volatile("{\n.reg .pred p;\n.reg .b64 a, b;\nsetp.ne.b32 p, %66, 0;\nmov.b64 a, {%64, %68};\nmov.b64 b, {%65, %69};\n"
        "wgmma.mma_async.sync.aligned.m64n128k16.f32.bf16.bf16 {%0, %1, %2, %3, %4, %5, %6, %7, %8, %9, %10, %11, %12, %13, %14, %15, %16, %17, %18, %19, %20, %21, %22, %23, %24, %25, %26, %27, %28, %29, %30, %31, %32, %33, %34, %35, %36, %37, %38, %39, %40, %41, %42, %43, %44, %45, %46, %47, %48, %49, %50, %51, %52, %53, %54, %55, %56, %57, %58, %59, %60, %61, %62, %63}, a, b, p, 1, 1, 0, %67;\n}"
        : "+f"(d[0]), "+f"(d[1]), "+f"(d[2]), "+f"(d[3]), "+f"(d[4]), "+f"(d[5]), "+f"(d[6]), "+f"(d[7]), "+f"(d[8]), "+f"(d[9]), "+f"(d[10]), "+f"(d[11]), "+f"(d[12]), "+f"(d[13]), "+f"(d[14]), "+f"(d[15]), "+f"(d[16]), "+f"(d[17]), "+f"(d[18]), "+f"(d[19]), "+f"(d[20]), "+f"(d[21]), "+f"(d[22]), "+f"(d[23]), "+f"(d[24]), "+f"(d[25]), "+f"(d[26]), "+f"(d[27]), "+f"(d[28]), "+f"(d[29]), "+f"(d[30]), "+f"(d[31]), "+f"(d[32]), "+f"(d[33]), "+f"(d[34]), "+f"(d[35]), "+f"(d[36]), "+f"(d[37]), "+f"(d[38]), "+f"(d[39]), "+f"(d[40]), "+f"(d[41]), "+f"(d[42]), "+f"(d[43]), "+f"(d[44]), "+f"(d[45]), "+f"(d[46]), "+f"(d[47]), "+f"(d[48]), "+f"(d[49]), "+f"(d[50]), "+f"(d[51]), "+f"(d[52]), "+f"(d[53]), "+f"(d[54]), "+f"(d[55]), "+f"(d[56]), "+f"(d[57]), "+f"(d[58]), "+f"(d[59]), "+f"(d[60]), "+f"(d[61]), "+f"(d[62]), "+f"(d[63])
        : "r"(da), "r"(db), "r"(acc), "n"(TB), "r"(ha), "r"(hb));
}
template <int TB>
__device__ __forceinline__ void wgmma_ss128_init(float (&d)[64], uint32_t da, uint32_t db, uint32_t ha = 0x40000040u, uint32_t hb = 0x40000040u) {
    asm volatile("{\n.reg .pred p;\n.reg .b64 a, b;\nsetp.ne.b32 p, 0, 0;\nmov.b64 a, {%64, %67};\nmov.b64 b, {%65, %68};\n"
        "wgmma.mma_async.sync.aligned.m64n128k16.f32.bf16.bf16 {%0, %1, %2, %3, %4, %5, %6, %7, %8, %9, %10, %11, %12, %13, %14, %15, %16, %17, %18, %19, %20, %21, %22, %23, %24, %25, %26, %27, %28, %29, %30, %31, %32, %33, %34, %35, %36, %37, %38, %39, %40, %41, %42, %43, %44, %45, %46, %47, %48, %49, %50, %51, %52, %53, %54, %55, %56, %57, %58, %59, %60, %61, %62, %63}, a, b, p, 1, 1, 0, %66;\n}"
        : "=f"(d[0]), "=f"(d[1]), "=f"(d[2]), "=f"(d[3]), "=f"(d[4]), "=f"(d[5]), "=f"(d[6]), "=f"(d[7]), "=f"(d[8]), "=f"(d[9]), "=f"(d[10]), "=f"(d[11]), "=f"(d[12]), "=f"(d[13]), "=f"(d[14]), "=f"(d[15]), "=f"(d[16]), "=f"(d[17]), "=f"(d[18]), "=f"(d[19]), "=f"(d[20]), "=f"(d[21]), "=f"(d[22]), "=f"(d[23]), "=f"(d[24]), "=f"(d[25]), "=f"(d[26]), "=f"(d[27]), "=f"(d[28]), "=f"(d[29]), "=f"(d[30]), "=f"(d[31]), "=f"(d[32]), "=f"(d[33]), "=f"(d[34]), "=f"(d[35]), "=f"(d[36]), "=f"(d[37]), "=f"(d[38]), "=f"(d[39]), "=f"(d[40]), "=f"(d[41]), "=f"(d[42]), "=f"(d[43]), "=f"(d[44]), "=f"(d[45]), "=f"(d[46]), "=f"(d[47]), "=f"(d[48]), "=f"(d[49]), "=f"(d[50]), "=f"(d[51]), "=f"(d[52]), "=f"(d[53]), "=f"(d[54]), "=f"(d[55]), "=f"(d[56]), "=f"(d[57]), "=f"(d[58]), "=f"(d[59]), "=f"(d[60]), "=f"(d[61]), "=f"(d[62]), "=f"(d[63])
        : "r"(da), "r"(db), "n"(TB), "r"(ha), "r"(hb));
}
template <int TB>
__device__ __forceinline__ void wgmma_ss64(float (&d)[32], uint32_t da, uint32_t db, int acc, uint32_t ha = 0x40000040u, uint32_t hb = 0x40000040u) {
    asm volatile("{\n.reg .pred p;\n.reg .b64 a, b;\nsetp.ne.b32 p, %34, 0;\nmov.b64 a, {%32, %36};\nmov.b64 b, {%33, %37};\n"
        "wgmma.mma_async.sync.aligned.m64n64k16.f32.bf16.bf16 {%0, %1, %2, %3, %4, %5, %6, %7, %8, %9, %10, %11, %12, %13, %14, %15, %16, %17, %18, %19, %20, %21, %22, %23, %24, %25, %26, %27, %28, %29, %30, %31}, a, b, p, 1, 1, 0, %35;\n}"
        : "+f"(d[0]), "+f"(d[1]), "+f"(d[2]), "+f"(d[3]), "+f"(d[4]), "+f"(d[5]), "+f"(d[6]), "+f"(d[7]), "+f"(d[8]), "+f"(d[9]), "+f"(d[10]), "+f"(d[11]), "+f"(d[12]), "+f"(d[13]), "+f"(d[14]), "+f"(d[15]), "+f"(d[16]), "+f"(d[17]), "+f"(d[18]), "+f"(d[19]), "+f"(d[20]), "+f"(d[21]), "+f"(d[22]), "+f"(d[23]), "+f"(d[24]), "+f"(d[25]), "+f"(d[26]), "+f"(d[27]), "+f"(d[28]), "+f"(d[29]), "+f"(d[30]), "+f"(d[31])
        : "r"(da), "r"(db), "r"(acc), "n"(TB), "r"(ha), "r"(hb));
}
template <int TB>
__device__ __forceinline__ void wgmma_ss64_init(float (&d)[32], uint32_t da, uint32_t db, uint32_t ha = 0x40000040u, uint32_t hb = 0x40000040u) {
    asm volatile("{\n.reg .pred p;\n.reg .b64 a, b;\nsetp.ne.b32 p, 0, 0;\nmov.b64 a, {%32, %35};\nmov.b64 b, {%33, %36};\n"
        "wgmma.mma_async.sync.aligned.m64n64k16.f32.bf16.bf16 {%0, %1, %2, %3, %4, %5, %6, %7, %8, %9, %10, %11, %12, %13, %14, %15, %16, %17, %18, %19, %20, %21, %22, %23, %24, %25, %26, %27, %28, %29, %30, %31}, a, b, p, 1, 1, 0, %34;\n}"
        : "=f"(d[0]), "=f"(d[1]), "=f"(d[2]), "=f"(d[3]), "=f"(d[4]), "=f"(d[5]), "=f"(d[6]), "=f"(d[7]), "=f"(d[8]), "=f"(d[9]), "=f"(d[10]), "=f"(d[11]), "=f"(d[12]), "=f"(d[13]), "=f"(d[14]), "=f"(d[15]), "=f"(d[16]), "=f"(d[17]), "=f"(d[18]), "=f"(d[19]), "=f"(d[20]), "=f"(d[21]), "=f"(d[22]), "=f"(d[23]), "=f"(d[24]), "=f"(d[25]), "=f"(d[26]), "=f"(d[27]), "=f"(d[28]), "=f"(d[29]), "=f"(d[30]), "=f"(d[31])
        : "r"(da), "r"(db), "n"(TB), "r"(ha), "r"(hb));
}
__device__ __forceinline__ void wgmma_rs128(float (&d)[64], uint32_t a0, uint32_t a1, uint32_t a2, uint32_t a3, uint32_t db, int acc, uint32_t hb = 0x40000040u) {
    asm volatile("{\n.reg .pred p;\n.reg .b64 b;\nsetp.ne.b32 p, %69, 0;\nmov.b64 b, {%68, %70};\n"
        "wgmma.mma_async.sync.aligned.m64n128k16.f32.bf16.bf16 {%0, %1, %2, %3, %4, %5, %6, %7, %8, %9, %10, %11, %12, %13, %14, %15, %16, %17, %18, %19, %20, %21, %22, %23, %24, %25, %26, %27, %28, %29, %30, %31, %32, %33, %34, %35, %36, %37, %38, %39, %40, %41, %42, %43, %44, %45, %46, %47, %48, %49, %50, %51, %52, %53, %54, %55, %56, %57, %58, %59, %60, %61, %62, %63}, {%64, %65, %66, %67}, b, p, 1, 1, 1;\n}"
        : "+f"(d[0]), "+f"(d[1]), "+f"(d[2]), "+f"(d[3]), "+f"(d[4]), "+f"(d[5]), "+f"(d[6]), "+f"(d[7]), "+f"(d[8]), "+f"(d[9]), "+f"(d[10]), "+f"(d[11]), "+f"(d[12]), "+f"(d[13]), "+f"(d[14]), "+f"(d[15]), "+f"(d[16]), "+f"(d[17]), "+f"(d[18]), "+f"(d[19]), "+f"(d[20]), "+f"(d[21]), "+f"(d[22]), "+f"(d[23]), "+f"(d[24]), "+f"(d[25]), "+f"(d[26]), "+f"(d[27]), "+f"(d[28]), "+f"(d[29]), "+f"(d[30]), "+f"(d[31]), "+f"(d[32]), "+f"(d[33]), "+f"(d[34]), "+f"(d[35]), "+f"(d[36]), "+f"(d[37]), "+f"(d[38]), "+f"(d[39]), "+f"(d[40]), "+f"(d[41]), "+f"(d[42]), "+f"(d[43]), "+f"(d[44]), "+f"(d[45]), "+f"(d[46]), "+f"(d[47]), "+f"(d[48]), "+f"(d[49]), "+f"(d[50]), "+f"(d[51]), "+f"(d[52]), "+f"(d[53]), "+f"(d[54]), "+f"(d[55]), "+f"(d[56]), "+f"(d[57]), "+f"(d[58]), "+f"(d[59]), "+f"(d[60]), "+f"(d[61]), "+f"(d[62]), "+f"(d[63])
        : "r"(a0), "r"(a1), "r"(a2), "r"(a3), "r"(db), "r"(acc), "r"(hb));
}

__device__ __forceinline__ uint32_t pack2(float lo, float hi) {
    uint32_t r;
    asm("cvt.rn.bf16x2.f32 %0, %1, %2;" : "=r"(r) : "f"(hi), "f"(lo));
    return r;
}
__device__ __forceinline__ float bf_lo(uint32_t v) { return __uint_as_float(v << 16); }
__device__ __forceinline__ float bf_hi(uint32_t v) { return __uint_as_float(v & 0xffff0000u); }
__device__ __forceinline__ float rbf(float v) { return bf_lo(pack2(v, v)); }
__device__ __forceinline__ uint32_t badd(uint32_t a, uint32_t b) {
    uint32_t r;
    asm("add.rn.bf16x2 %0, %1, %2;" : "=r"(r) : "r"(a), "r"(b));
    return r;
}
__device__ __forceinline__ uint32_t bsub(uint32_t a, uint32_t b) {
    uint32_t r;
    asm("sub.rn.bf16x2 %0, %1, %2;" : "=r"(r) : "r"(a), "r"(b));
    return r;
}
__device__ __forceinline__ uint32_t bmul(uint32_t a, uint32_t b) {
    uint32_t r;
    asm("mul.rn.bf16x2 %0, %1, %2;" : "=r"(r) : "r"(a), "r"(b));
    return r;
}
__device__ __forceinline__ uint32_t ln_apply(uint32_t x, uint32_t mb, float rs, uint32_t scale, uint32_t shift) {
    const uint32_t d = bsub(x, mb);
    return badd(bmul(pack2(bf_lo(d) * rs, bf_hi(d) * rs), scale), shift);
}
__device__ __forceinline__ float ex2(float v) {
    float r;
    asm("ex2.approx.ftz.f32 %0, %1;" : "=f"(r) : "f"(v));
    return r;
}
__device__ __forceinline__ float rcp(float v) {
    float r;
    asm("rcp.approx.ftz.f32 %0, %1;" : "=f"(r) : "f"(v));
    return r;
}
__device__ __forceinline__ float sqrt_fast(float v) {
    float r;
    asm("sqrt.approx.ftz.f32 %0, %1;" : "=f"(r) : "f"(v));
    return r;
}
__device__ __forceinline__ float ln_rstd(float var) { return rcp(rbf(sqrt_fast(rbf(rbf(var) + 1e-5f)))); }
__device__ __forceinline__ float sigmoid(float v) { return rcp(1.f + ex2(-1.4426950408889634f * v)); }
__device__ __forceinline__ float warp_sum(float v) {
#pragma unroll
    for (int o = 16; o > 0; o >>= 1) v += __shfl_xor_sync(0xffffffffu, v, o);
    return v;
}
__device__ __forceinline__ float quad_sum(float v) {
    v += __shfl_xor_sync(0xffffffffu, v, 1);
    return v + __shfl_xor_sync(0xffffffffu, v, 2);
}

constexpr uint32_t HI_128 = 0x40000040u, HI_IMG = 0x80000080u, HI_Q = 0x80000040u;
template <int M, int RH>
__device__ __forceinline__ uint4 img_pack(const float (&d)[64], float s) {
    uint4 v;
    v.x = pack2(d[16 * M + 2 * RH] * s, d[16 * M + 2 * RH + 1] * s);
    v.y = pack2(d[16 * M + 4 + 2 * RH] * s, d[16 * M + 5 + 2 * RH] * s);
    v.z = pack2(d[16 * M + 8 + 2 * RH] * s, d[16 * M + 9 + 2 * RH] * s);
    v.w = pack2(d[16 * M + 12 + 2 * RH] * s, d[16 * M + 13 + 2 * RH] * s);
    return v;
}
template <int M, int RH>
__device__ __forceinline__ uint4 img_pack(const float (&d)[64]) {
    uint4 v;
    v.x = pack2(d[16 * M + 2 * RH], d[16 * M + 2 * RH + 1]);
    v.y = pack2(d[16 * M + 4 + 2 * RH], d[16 * M + 5 + 2 * RH]);
    v.z = pack2(d[16 * M + 8 + 2 * RH], d[16 * M + 9 + 2 * RH]);
    v.w = pack2(d[16 * M + 12 + 2 * RH], d[16 * M + 13 + 2 * RH]);
    return v;
}
template <int M>
__device__ __forceinline__ void img_store_global(uint8_t* img, uint32_t toff, const float (&d)[64], float s0, float s1) {
    uint4* p = reinterpret_cast<uint4*>(img + toff) + M * 32;
    p[0] = img_pack<M, 0>(d, s0);
    p[128] = img_pack<M, 1>(d, s1);
}
__device__ __forceinline__ void sts128(uint32_t a, uint4 v) {
    asm volatile("st.shared.v4.b32 [%0], {%1, %2, %3, %4};" ::"r"(a), "r"(v.x), "r"(v.y), "r"(v.z), "r"(v.w) : "memory");
}
constexpr float SM_C = 0.08838834764831845f * 1.4426950408889634f;
__device__ __forceinline__ float pack2f(float lo, float hi) {
    float r;
    asm("{\n.reg .b32 t;\ncvt.rn.bf16x2.f32 t, %1, %2;\nmov.b32 %0, t;\n}" : "=f"(r) : "f"(hi), "f"(lo));
    return r;
}
template <int M, bool SCALE, bool PARK>
__device__ __forceinline__ void pack_group(float (&d)[64], float (&v)[8], float s0, float s1) {
#pragma unroll
    for (int i = 0; i < 8; i++) {
        const int k = 16 * M + 4 * (i & 3) + 2 * (i >> 2);
        v[i] = SCALE ? pack2f(d[k] * (i < 4 ? s0 : s1), d[k + 1] * (i < 4 ? s0 : s1)) : pack2f(d[k], d[k + 1]);
        if (PARK && M > 0) d[16 * (M > 0 ? M - 1 : 0) + i] = v[i];
    }
}
template <int M, bool PARK>
__device__ __forceinline__ void q_store_part(uint32_t a, float (&d)[64]) {
    float v[8];
    pack_group<M, false, PARK>(d, v, 0.f, 0.f);
#pragma unroll
    for (int h = 0; h < 2; h++)
        asm volatile("st.shared.v4.f32 [%0], {%1, %2, %3, %4};" ::"r"(a + (M >> 1) * 16384 + (M & 1) * 512 + h * 1024),
                     "f"(v[4 * h]), "f"(v[4 * h + 1]), "f"(v[4 * h + 2]), "f"(v[4 * h + 3]) : "memory");
}
template <bool PARK>
__device__ __forceinline__ void q_store(uint32_t a, uint32_t toff, float (&d)[64]) {
    a += (((toff >> 1) & ~2047u) ^ 8192) + (toff & 511);
    q_store_part<0, PARK>(a, d); q_store_part<1, PARK>(a, d); q_store_part<2, PARK>(a, d); q_store_part<3, PARK>(a, d);
}
template <int M, bool PARK>
__device__ __forceinline__ void ctx_store_part(float4* p, float (&d)[64], float i0, float i1) {
    float v[8];
    pack_group<M, true, PARK>(d, v, i0, i1);
    p[M * 32] = make_float4(v[0], v[1], v[2], v[3]);
    p[M * 32 + 128] = make_float4(v[4], v[5], v[6], v[7]);
}
template <bool PARK>
__device__ __forceinline__ void ctx_store(uint8_t* img, uint32_t toff, float (&o)[64], float l0, float l1) {
    const float i0 = rcp(quad_sum(l0)), i1 = rcp(quad_sum(l1));
    float4* p = reinterpret_cast<float4*>(img + toff);
    ctx_store_part<0, PARK>(p, o, i0, i1); ctx_store_part<1, PARK>(p, o, i0, i1); ctx_store_part<2, PARK>(p, o, i0, i1); ctx_store_part<3, PARK>(p, o, i0, i1);
}

__device__ __forceinline__ void slot_wait(uint32_t bars, uint32_t& ph, uint32_t slot) {
    mbar_wait(bars + 8 * slot, (ph >> slot) & 1);
    ph ^= 1u << slot;
}
__device__ __forceinline__ void release_if(uint32_t eb, uint32_t slot, bool on) {
    asm volatile("{\n.reg .pred p;\nsetp.ne.s32 p, %1, 0;\n@p mbarrier.arrive.shared::cluster.b64 _, [%0];\n}" ::"r"(eb + 8 * slot), "r"((int)on) : "memory");
}
__device__ __forceinline__ void load_image_mc(uint32_t sb, uint32_t& ph, uint32_t slot, const uint8_t* src, int rank, bool first) {
    slot_wait(sb + BAR_EMPTY, ph, slot);
    asm volatile("{\n.reg .pred p;\nelect.sync _|p, 0xffffffff;\n@p mbarrier.arrive.expect_tx.shared::cta.b64 _, [%2], 32768;\n"
                 "@p cp.async.bulk.shared::cluster.global.mbarrier::complete_tx::bytes.multicast::cluster.L2::cache_hint [%0], [%1], 16384, [%2], %4, %3;\n}"
                 ::"r"(sb + slot * SLOT + rank * 16384), "l"(src + rank * 16384), "r"(sb + BAR_FULL + 8 * slot), "l"(first ? L2_FIRST : L2_NORMAL),
                 "h"((uint16_t)3) : "memory");
}
__device__ __forceinline__ void load_tile_mc(uint32_t sb, uint32_t& ph, uint32_t slot, const CUtensorMap* m, int row, int cb, int rank, bool first) {
    slot_wait(sb + BAR_EMPTY, ph, slot);
    asm volatile("{\n.reg .pred p;\nelect.sync _|p, 0xffffffff;\n@p mbarrier.arrive.expect_tx.shared::cta.b64 _, [%2], 32768;\n"
                 "@p cp.async.bulk.tensor.3d.shared::cluster.global.mbarrier::complete_tx::bytes.multicast::cluster.L2::cache_hint [%0], [%1, {%3, %4, %5}], [%2], %7, %6;\n}"
                 ::"r"(sb + slot * SLOT + rank * 16384), "l"(m), "r"(sb + BAR_FULL + 8 * slot), "r"(0), "r"(row), "r"(cb + rank),
                 "l"(first ? L2_FIRST : L2_NORMAL), "h"((uint16_t)3) : "memory");
}
__device__ __forceinline__ void load_image(uint32_t sb, uint32_t& ph, uint32_t slot, const void* src, bool first) {
    slot_wait(sb + BAR_EMPTY, ph, slot);
    asm volatile("{\n.reg .pred p;\nelect.sync _|p, 0xffffffff;\n@p mbarrier.arrive.expect_tx.shared::cta.b64 _, [%2], 32768;\n"
                 "@p cp.async.bulk.shared::cluster.global.mbarrier::complete_tx::bytes.L2::cache_hint [%0], [%1], 32768, [%2], %3;\n}"
                 ::"r"(sb + slot * SLOT), "l"(src), "r"(sb + BAR_FULL + 8 * slot), "l"(first ? L2_FIRST : L2_NORMAL) : "memory");
}
__device__ __forceinline__ void load_tile(uint32_t sb, uint32_t& ph, uint32_t slot, const CUtensorMap* m, int row, int cb, bool first) {
    slot_wait(sb + BAR_EMPTY, ph, slot);
    asm volatile("{\n.reg .pred p;\nelect.sync _|p, 0xffffffff;\n@p mbarrier.arrive.expect_tx.shared::cta.b64 _, [%2], 32768;\n"
                 "@p cp.async.bulk.tensor.3d.shared::cluster.global.mbarrier::complete_tx::bytes.L2::cache_hint [%0], [%1, {%3, %4, %5}], [%2], %6;\n}"
                 ::"r"(sb + slot * SLOT), "l"(m), "r"(sb + BAR_FULL + 8 * slot), "r"(0), "r"(row), "r"(cb), "l"(first ? L2_FIRST : L2_NORMAL) : "memory");
}
__device__ __forceinline__ uint32_t ring_next(uint32_t r) { return r == 4 ? 0 : r + 1; }
__device__ __forceinline__ uint32_t w_table(int hp) { return hp ? 0x3104u : 0x4210u; }
__device__ __forceinline__ uint32_t a_table(int hp) { return hp ? 0x625u : 0x635u; }
__device__ __forceinline__ uint32_t a_next(uint32_t& t) {
    const uint32_t s = t & 15;
    t = (t >> 4) | (s << 8);
    return s;
}
constexpr uint32_t O_TABLE = 0x2160435u;
__device__ __forceinline__ uint32_t o_next(uint32_t& t) {
    const uint32_t s = t & 15;
    t = (t >> 4) | (s << 24);
    return s;
}
__device__ __forceinline__ int o_head(int i, int kh) { return i < 16 ? 4 * (i & 7) + 2 * (kh ^ 1) + (i >> 3) : 29 + 2 * kh; }

template <bool INIT>
__device__ __forceinline__ void gemm_issue(float (&d)[64], uint32_t a, uint32_t b, int acc, bool img) {
    const uint32_t ha = img ? HI_IMG : HI_128, o2 = img ? 32 : 4, o4 = img ? 64 : 1024;
    wg_fence();
#pragma unroll
    for (int k = 0; k < 8; k++) {
        if (INIT && k == 0) wgmma_ss128_init<1>(d, a, b, ha);
        else wgmma_ss128<1>(d, a + (k >> 2) * o4 + ((k >> 1) & 1) * o2 + (k & 1) * 2, b + k * 128, k ? 1 : acc, ha);
    }
    wg_commit();
}

__device__ __forceinline__ void h_store(const uint32_t* x, float mean, float sq, uint32_t sb, int row) {
    const int lane = threadIdx.x & 31;
    const float rs = ln_rstd(sq * (1.f / 512.f));
    const uint32_t mb = pack2(mean, mean);
    uint8_t* p = g_h + ((row >> 7) * 8 + (lane >> 3)) * 16384 + (row & 127) * 128 + (((lane ^ row) & 7) << 4);
#pragma unroll
    for (int i = 0; i < 2; i++) {
        const uint4 a = lds128(sb + SM_TAB + 1024 + i * 512 + lane * 16), c = lds128(sb + SM_TAB + i * 512 + lane * 16);
        *reinterpret_cast<uint4*>(p + i * 65536) = make_uint4(ln_apply(x[4 * i], mb, rs, a.x, c.x), ln_apply(x[4 * i + 1], mb, rs, a.y, c.y),
                                                              ln_apply(x[4 * i + 2], mb, rs, a.z, c.z), ln_apply(x[4 * i + 3], mb, rs, a.w, c.w));
    }
}

template <bool ODD>
__device__ __forceinline__ void proj_tile(float (&acc)[64], float (&prev)[64], int t, int q0, uint32_t sb, int wg, uint32_t eb, bool rel, uint32_t& fph,
                                          uint32_t wtab, uint32_t& atab, uint8_t* prev_img, uint32_t toff, float s0, float s1, bool first,
                                          const bf16* x, int xrow) {
    const uint32_t a0 = desc_k(sb + (wg ^ (ODD && t == 5)) * 8192), b0 = desc_mn(sb);
    const int lane = threadIdx.x & 31;
    float mean[2] = {0.f, 0.f}, rstd[2] = {0.f, 0.f};
    uint32_t xn[16];
#pragma unroll
    for (int i = 0; i < 4; i++) {
        uint4 v = make_uint4(0, 0, 0, 0);
        if (ODD && first) v = __ldg(reinterpret_cast<const uint4*>(x) + xrow * 64 + lane + 32 * i);
        xn[4 * i] = v.x; xn[4 * i + 1] = v.y; xn[4 * i + 2] = v.z; xn[4 * i + 3] = v.w;
    }
    constexpr int U = ODD ? UNR : 1;
#pragma unroll U
    for (int q = ODD ? 0 : q0; q < 4; q++) {
        if (ODD && t == 5 && q == 3) break;
        const uint32_t ws = (wtab >> (4 * q)) & 15, as = a_next(atab);
        if (!ODD && t != 2) slot_wait(sb + BAR_FULL, fph, ws);
        slot_wait(sb + BAR_FULL, fph, as);
        bar_sync(1 + wg, 256);
        gemm_issue<false>(acc, a0 + as * (SLOT / 16), b0 + ws * (SLOT / 16), q, false);
        bar_arrive(2 - wg, 256);
        wg_wait<1>();
        reg_fence(prev);
        if (ODD && t == 5) {
            if (q == 2) {
                q_store<false>(sb + 5 * SLOT, toff, prev);
                fence_async_smem();
            }
        } else if (ODD || !first) {
            if (q == 0) img_store_global<0>(prev_img, toff, prev, s0, s1);
            if (q == 1) img_store_global<1>(prev_img, toff, prev, s0, s1);
            if (q == 2) img_store_global<2>(prev_img, toff, prev, s0, s1);
            if (q == 3) img_store_global<3>(prev_img, toff, prev, s0, s1);
        }
        if (ODD && q == 1 && first) {
#pragma unroll
            for (int k = 0; k < 16; k++) mean[k >> 3] += bf_lo(xn[k]) + bf_hi(xn[k]);
#pragma unroll
            for (int i = 0; i < 2; i++) mean[i] = warp_sum(mean[i]) * (1.f / 512.f);
        }
        if (ODD && q == 2 && first) {
#pragma unroll
            for (int k = 0; k < 16; k++) {
                const float d0 = bf_lo(xn[k]) - mean[k >> 3], d1 = bf_hi(xn[k]) - mean[k >> 3];
                rstd[k >> 3] = fmaf(d0, d0, fmaf(d1, d1, rstd[k >> 3]));
            }
#pragma unroll
            for (int i = 0; i < 2; i++) rstd[i] = warp_sum(rstd[i]);
        }
        if (ODD && q == 3 && first) {
            mbar_wait(sb + BAR_FLAG + 8 * 8, 0);
            h_store(xn, mean[0], rstd[0], sb, xrow);
        }
        wg_wait<0>();
        release_if(eb, as, rel && !(ODD && (q & 1) && t == 5));
        if (ODD) release_if(eb, ws, rel && t != 1);
        if (ODD && q == 3 && first) {
            h_store(xn + 8, mean[1], rstd[1], sb, xrow + 1);
            __syncwarp();
            mbar_arrive_if(sb + BAR_DONE, lane == 0);
        }
    }
    reg_fence(acc);
}

__device__ __forceinline__ void qk_issue(float (&s)[64], uint32_t q, uint32_t k) {
    wg_fence();
    wgmma_ss128_init<0>(s, q, k, HI_Q, HI_IMG);
#pragma unroll
    for (int i = 1; i < 8; i++) wgmma_ss128<0>(s, q + (i >> 2) * 1024 + (i & 2) * 16 + (i & 1) * 2, k + (i >> 1) * 32 + (i & 1) * 2, 1, HI_Q, HI_IMG);
    wg_commit();
}
__device__ __forceinline__ void qk_issue(float (&s)[32], uint32_t q, uint32_t k) {
    wg_fence();
    wgmma_ss64_init<0>(s, q, k, HI_Q, HI_IMG);
#pragma unroll
    for (int i = 1; i < 8; i++) wgmma_ss64<0>(s, q + (i >> 2) * 1024 + (i & 2) * 16 + (i & 1) * 2, k + (i >> 1) * 32 + (i & 1) * 2, 1, HI_Q, HI_IMG);
    wg_commit();
}
__device__ __forceinline__ void pv_issue(float (&o)[64], const uint32_t (&p)[32], uint32_t v, int acc, bool half) {
    if (half) {
        asm volatile("// half" ::: "memory");
        wg_fence();
#pragma unroll
        for (int i = 0; i < 4; i++) wgmma_rs128(o, p[4 * i], p[4 * i + 1], p[4 * i + 2], p[4 * i + 3], v + i * 256, i ? 1 : acc, HI_IMG);
        wg_commit();
        asm volatile("// half" ::: "memory");
    } else {
        wg_fence();
#pragma unroll
        for (int i = 0; i < 8; i++) wgmma_rs128(o, p[4 * i], p[4 * i + 1], p[4 * i + 2], p[4 * i + 3], v + i * 256, i ? 1 : acc, HI_IMG);
        wg_commit();
    }
}
template <int B, int N>
__device__ __forceinline__ void tri_mask(float (&s)[N], int x) {
#pragma unroll
    for (int k = 0; k < 7; k++)
        asm("{\n.reg .pred p, q;\nsetp.lt.s32 p, %4, %5;\nsetp.le.s32 q, %4, %5;\n"
            "@p mov.b32 %0, 0fFF800000;\n@q mov.b32 %1, 0fFF800000;\n@p mov.b32 %2, 0fFF800000;\n@q mov.b32 %3, 0fFF800000;\n}"
            : "+f"(s[B + 4 * k]), "+f"(s[B + 4 * k + 1]), "+f"(s[B + 4 * k + 6]), "+f"(s[B + 4 * k + 7]) : "r"(x), "r"(8 * k));
    asm("{\n.reg .pred p, q;\nsetp.lt.s32 p, %2, 56;\nsetp.le.s32 q, %2, 56;\n@p mov.b32 %0, 0fFF800000;\n@q mov.b32 %1, 0fFF800000;\n}"
        : "+f"(s[B + 28]), "+f"(s[B + 29]) : "r"(x));
}
__device__ __forceinline__ void tri_mask_copy(float (&s)[64], const float (&h)[32], int x) {
#pragma unroll
    for (int i = 0; i < 32; i++) {
        asm("{\n.reg .pred p;\nsetp.lt.s32 p, %2, %3;\nselp.f32 %0, 0fFF800000, %1, p;\n}"
            : "=f"(s[i]) : "f"(h[i]), "r"(x), "r"(8 * (i >> 2) - 4 * (i & 2) + (i & 1)));
        s[32 + i] = __uint_as_float(0xff800000u);
    }
}
constexpr float SM_HI = 1152921504606846976.f, SM_LO = 1.f / 1152921504606846976.f;
__device__ __forceinline__ bool softmax_unsafe(float t0, float t1, bool first) {
    bool bad = __any_sync(0xffffffffu, fmaxf(t0, t1) > SM_HI);
    if (first) {
        uint32_t a = __ballot_sync(0xffffffffu, t0 >= SM_LO), b = __ballot_sync(0xffffffffu, t1 >= SM_LO);
        a |= a >> 1;
        b |= b >> 1;
        bad |= ((a | (a >> 2)) & (b | (b >> 2)) & 0x11111111u) != 0x11111111u;
    }
    return bad;
}
__device__ __forceinline__ void softmax_shift(float (&s)[64], float d0, float d1) {
#pragma unroll
    for (int i = 0; i < 64; i++) s[i] -= (i & 2) ? d1 : d0;
}
__device__ __forceinline__ void softmax_remax(float (&s)[64], float (&m)[2], bool first, float& a0, float& a1) {
    float m0 = fmaxf(s[0], s[1]), m1 = fmaxf(s[2], s[3]);
#pragma unroll
    for (int k = 1; k < 16; k++) {
        m0 = fmaxf(m0, fmaxf(s[4 * k], s[4 * k + 1]));
        m1 = fmaxf(m1, fmaxf(s[4 * k + 2], s[4 * k + 3]));
    }
    m0 = fmaxf(m0, __shfl_xor_sync(0xffffffffu, m0, 1));
    m1 = fmaxf(m1, __shfl_xor_sync(0xffffffffu, m1, 1));
    m0 = fmaxf(m0, __shfl_xor_sync(0xffffffffu, m0, 2));
    m1 = fmaxf(m1, __shfl_xor_sync(0xffffffffu, m1, 2));
    if (!first) {
        m0 = fmaxf(m0, 0.f);
        m1 = fmaxf(m1, 0.f);
    }
    a0 = first ? 1.f : ex2(-m0);
    a1 = first ? 1.f : ex2(-m1);
    m[0] += m0;
    m[1] += m1;
    softmax_shift(s, m0, m1);
}
template <int J0, int J1>
__device__ __forceinline__ void softmax_exp(const float (&s)[64], uint32_t (&p)[32], float (&t)[4]) {
#pragma unroll
    for (int k = J0; k < J1; k++) {
        const float e0 = ex2(s[4 * k]), e1 = ex2(s[4 * k + 1]), e2 = ex2(s[4 * k + 2]), e3 = ex2(s[4 * k + 3]);
        if (k == 0) { t[0] = e0; t[1] = e1; t[2] = e2; t[3] = e3; }
        else { t[0] += e0; t[1] += e1; t[2] += e2; t[3] += e3; }
        p[2 * k] = pack2(e0, e1);
        p[2 * k + 1] = pack2(e2, e3);
    }
}
__device__ __forceinline__ void fma8(float (&acc)[8], float a, uint4 w) {
    acc[0] = fmaf(a, bf_lo(w.x), acc[0]); acc[1] = fmaf(a, bf_hi(w.x), acc[1]);
    acc[2] = fmaf(a, bf_lo(w.y), acc[2]); acc[3] = fmaf(a, bf_hi(w.y), acc[3]);
    acc[4] = fmaf(a, bf_lo(w.z), acc[4]); acc[5] = fmaf(a, bf_hi(w.z), acc[5]);
    acc[6] = fmaf(a, bf_lo(w.w), acc[6]); acc[7] = fmaf(a, bf_hi(w.w), acc[7]);
}
__device__ __forceinline__ void mma16816(float (&d)[4], const uint32_t* a, uint32_t b0, uint32_t b1) {
    asm("mma.sync.aligned.m16n8k16.row.col.f32.bf16.bf16.f32 {%0, %1, %2, %3}, {%4, %5, %6, %7}, {%8, %9}, {%0, %1, %2, %3};"
        : "+f"(d[0]), "+f"(d[1]), "+f"(d[2]), "+f"(d[3]) : "r"(a[0]), "r"(a[1]), "r"(a[2]), "r"(a[3]), "r"(b0), "r"(b1));
}
__device__ __forceinline__ uint32_t best_key(const uint32_t* keys, int lane, uint32_t ep) {
    uint32_t best;
#pragma unroll 1
    for (;;) {
        const uint4 k = ld_poll(reinterpret_cast<const uint4*>(keys) + lane);
        best = max(max(k.x, k.y), max(k.z, k.w));
        if (__all_sync(0xffffffffu, (((k.x ^ ep) | (k.y ^ ep) | (k.z ^ ep) | (k.w ^ ep)) & 31) == 0)) break;
    }
    return __reduce_max_sync(0xffffffffu, best);
}

__global__ void __cluster_dims__(2, 1, 1) __launch_bounds__(384, 1)
fused_kernel(const __grid_constant__ CUtensorMap tm_ckv, const __grid_constant__ CUtensorMap tm_wq,
             const __grid_constant__ CUtensorMap tm_wuk, const __grid_constant__ CUtensorMap tm_wuv,
             const __grid_constant__ CUtensorMap tm_wo, const __grid_constant__ CUtensorMap tm_wg,
             const __grid_constant__ CUtensorMap tm_wu,
             const __grid_constant__ CUtensorMap tm_wm, const __grid_constant__ CUtensorMap tm_x, const Params P) {
    extern __shared__ __align__(1024) uint8_t smem[];
    const uint32_t sb = (uint32_t)__cvta_generic_to_shared(smem);
    const int tid = threadIdx.x, lane = tid & 31, warp = __shfl_sync(0xffffffffu, tid >> 5, 0), wg = warp >> 2;
    uint32_t sm;
    asm("mov.u32 %0, %%smid;" : "=r"(sm));
    if (MC) sm = blockIdx.x < 8 ? blockIdx.x + 124 : blockIdx.x - 8;
    const uint32_t smq = ((sm - 64) * 147) >> 11;
    const int rb = !P.by_smid ? blockIdx.x : sm < 64 ? (sm & 14) * 8 + (sm >> 4) * 2 + (sm & 1)
                 : sm < 120 ? ((sm - 64 - smq * 14) & 14) * 8 + 24 + smq * 2 + (sm & 1) : sm < 124 ? sm + 8 : sm - 116;
    const int grp = rb >> 3, j = rb & 7, cq = j & 3, kh = grp & 1, ort = (grp & 14) + (j >> 2);
    if (warp == 0) TS(0);

    if (rb >= NCTA) {
        float* sc = reinterpret_cast<float*>(smem + 6 * SLOT);
        float* red = sc + 512;
        if (tid == 256) {
            for (int i = 0; i < 6; i++) { mbar_init(sb + BAR_FULL + 8 * i, 1); mbar_init(sb + BAR_EMPTY + 8 * i, 8); }
            fence_async_smem();
        }
        __syncthreads();
        uint32_t ph = 0, sl = 0;
        if (tid == 256) {
#pragma unroll 1
            for (int i = 0; i < 24; i++) {
                mbar_wait(sb + BAR_EMPTY + 8 * sl, ph ^ 1);
                mbar_expect(sb + BAR_FULL + 8 * sl, SLOT);
                tma2d(sb + sl * SLOT, &tm_wm, (i >> 3) * 1024 + (rb - NCTA) * 256, (i & 7) * 64, sb + BAR_FULL + 8 * sl);
                if (++sl == 6) { sl = 0; ph ^= 1; }
            }
            mbar_wait(sb + BAR_EMPTY, 1);
            mbar_wait(sb + BAR_EMPTY + 8, 1);
#pragma unroll 1
            for (int i = 0; i <= NFFN / NSPARE; i++) {
                const int b = (rb - NCTA) * (NFFN / NSPARE) + i;
                if (i < NFFN / NSPARE) {
                    const uint32_t f = sb + BAR_FULL + 8 * (i & 1), d = sb + (i & 1) * SLOT;
                    asm volatile("cp.async.bulk.wait_group.read 0;" ::: "memory");
                    mbar_expect(f, SLOT);
                    tma2d(d, &tm_wg, b * 16, 0, f);
                    tma2d(d + 8192, &tm_wg, b * 16, 256, f);
                    tma2d(d + 16384, &tm_wu, b * 16, 0, f);
                    tma2d(d + 24576, &tm_wu, b * 16, 256, f);
                }
                if (i) {
                    mbar_wait(sb + BAR_FULL + 8 * (~i & 1), ((i - 1) >> 1) & 1);
                    asm volatile("cp.async.bulk.global.shared::cta.bulk_group [%0], [%1], 32768;\ncp.async.bulk.commit_group;"
                                 ::"l"(g_wf + (b - 1) * SLOT), "r"(sb + (~i & 1) * SLOT) : "memory");
                }
            }
            asm volatile("cp.async.bulk.wait_group 0;" ::: "memory");
            fence_async_global();
            flag_add(&g_sync.modcnt[32]);
            TS(4);
        } else if (tid < 256) {
            const uint32_t c2 = __ldg(reinterpret_cast<const uint32_t*>(P.c) + tid);
            sc[2 * tid] = rbf(bf_lo(c2) * sigmoid(bf_lo(c2)));
            sc[2 * tid + 1] = rbf(bf_hi(c2) * sigmoid(bf_hi(c2)));
            bar_sync(1, 256);
#pragma unroll 1
            for (int ps = 0; ps < 3; ps++) {
                float acc[8] = {0.f, 0.f, 0.f, 0.f, 0.f, 0.f, 0.f, 0.f};
#pragma unroll 1
                for (int bt = 0; bt < 8; bt++) {
                    mbar_wait(sb + BAR_FULL + 8 * sl, ph);
#pragma unroll
                    for (int i = 0; i < 8; i++)
                        fma8(acc, sc[bt * 64 + warp * 8 + i], *reinterpret_cast<const uint4*>(smem + sl * SLOT + (warp * 8 + i) * 512 + lane * 16));
                    __syncwarp();
                    mbar_arrive_if(sb + BAR_EMPTY + 8 * sl, lane == 0);
                    if (++sl == 6) { sl = 0; ph ^= 1; }
                }
                *reinterpret_cast<float4*>(red + warp * 256 + lane * 8) = make_float4(acc[0], acc[1], acc[2], acc[3]);
                *reinterpret_cast<float4*>(red + warp * 256 + lane * 8 + 4) = make_float4(acc[4], acc[5], acc[6], acc[7]);
                bar_sync(1, 256);
                float v = 0.f;
#pragma unroll
                for (int i = 0; i < 8; i++) v += red[i * 256 + tid];
                g_mod[ps * 1024 + (rb - NCTA) * 256 + tid] = __float2bfloat16_rn(v);
                bar_sync(1, 256);
                if (tid == 0 && ps != 1) flag_add(&g_sync.modcnt[(ps >> 1) * 32]);
                if (warp == 0) TS(1 + ps);
            }
        }
        return;
    }

    if (tid == 256) {
        if (sb & 1023) __trap();
        asm volatile("prefetch.tensormap [%0];" ::"l"((j & 1) ? &tm_wuv : &tm_wuk) : "memory");
        asm volatile("prefetch.tensormap [%0];" ::"l"(&tm_ckv) : "memory");
        for (int i = 0; i < 7; i++) { mbar_init(sb + BAR_FULL + 8 * i, 1); mbar_init(sb + BAR_EMPTY + 8 * i, MC ? 4 : 2); }
        for (int i = 0; i < 9; i++) mbar_init(sb + BAR_DONE + 8 * i, 8);
        for (int i = 0; i < 10; i++) mbar_init(sb + BAR_FLAG + 8 * i, 1);
        *reinterpret_cast<uint32_t*>(smem + SM_EP + 4) = 0;
        mbar_init(sb + BAR_END, 8);
        fence_async_smem();
        if (MC) asm volatile("fence.mbarrier_init.release.cluster;" ::: "memory");
    }
    __syncthreads();
    if (MC) asm volatile("barrier.cluster.arrive.relaxed.aligned;\nbarrier.cluster.wait.aligned;" ::: "memory");

    if (wg == 2) {
        asm volatile("setmaxnreg.dec.sync.aligned.u32 40;");
        if (warp == 8) {
            uint32_t eph = 0x7f, r = 0;
            const CUtensorMap* tw = (j & 1) ? &tm_wuv : &tm_wuk;
#pragma unroll 1
            for (int hp = 0; hp < 2; hp++) {
                const int hc = 4 * grp + 2 * hp;
                uint32_t wtab = w_table(hp), atab = a_table(hp);
#pragma unroll 1
                for (int u = 0; u < 4; u++) {
                    load_tile(sb, eph, (wtab >> (4 * u)) & 15, tw, u * 128, hc, HINT & 1); PT();
                    if (MC & 1) load_tile_mc(sb, eph, a_next(atab), &tm_ckv, (j >> 1) * 128, u * 2, j & 1, (HINT & 8) && hp);
                    else load_tile(sb, eph, a_next(atab), &tm_ckv, (j >> 1) * 128, u * 2, (HINT & 8) && hp);
                    PT();
                    if (hp == 1 && (u & 1) && lane == 0) asm volatile("red.relaxed.gpu.global.add.u32 [%0], 1;" ::"l"(&g_sync.rdcnt[(grp * 2 + (u >> 1)) * 8]) : "memory");
                }
#pragma unroll 1
                for (int u = 4; u < 16; u++) {
                    if (hp == 1 && (u & 7) == 4) mbar_wait(sb + BAR_FLAG + 24 + (u & 8), 0);
                    if (MC & 1) load_tile_mc(sb, eph, a_next(atab), &tm_ckv, ((u & 12) + (j >> 1)) * 128, (u & 3) * 2, j & 1, (HINT & 8) && hp);
                    else load_tile(sb, eph, a_next(atab), &tm_ckv, ((u & 12) + (j >> 1)) * 128, (u & 3) * 2, (HINT & 8) && hp);
                    PT();
                }
                mbar_wait(sb + BAR_FLAG, 0);
                fence_async_global();
#pragma unroll 1
                for (int u = 0; u < 4; u++) {
                    if (MC & 2) load_tile_mc(sb, eph, (wtab >> (4 * u)) & 15, &tm_wq, u * 128, hc, j & 1, HINT & 1);
                    else load_tile(sb, eph, (wtab >> (4 * u)) & 15, &tm_wq, u * 128, hc, HINT & 1);
                    PT();
                    load_image(sb, eph, a_next(atab), g_h + ((15 - j) * 4 + u) * SLOT, (HINT & 8) && hp); PT();
                }
                mbar_wait(sb + BAR_FLAG + 8 + 32 * hp, 0);
                fence_async_global();
#pragma unroll 1
                for (int u = 0; u < 4; u++) { load_image(sb, eph, a_next(atab), g_h + (j * 4 + u) * SLOT, (HINT & 8) && hp); PT(); }
                const uint8_t* kv = g_KV + (size_t)(grp * 32 + 30 * hp) * SLOT;
                const int step = hp ? -2 * SLOT : 2 * SLOT;
                if (MC & 4) load_image_mc(sb, eph, r, kv, j & 1, HINT & 4);
                else load_image(sb, eph, r, kv, HINT & 4);
                PT();
                r = ring_next(r);
#pragma unroll 1
                for (int n = 1; n <= 16; n++) {
                    if (n == 8) {
                        mbar_wait(sb + BAR_FLAG + 16 + 32 * hp, 0);
                        fence_async_global();
                    }
                    mbar_arrive_if(sb + BAR_PF, lane == 0 && (n == PF1 || n == PF2));
                    const uint8_t* v = kv + SLOT;
                    kv += n < 16 - j ? step : n == 16 - j ? (2 * j - 15) * step : -step;
                    if ((MC & 4) && n != 15 - (j & 6)) load_image_mc(sb, eph, r, kv, j & 1, HINT & 4);
                    else load_image(sb, eph, r, kv, HINT & 4);
                    PT();
                    r = ring_next(r);
                    if ((MC & 4) && n != 16 - (j & 6)) load_image_mc(sb, eph, r, v, j & 1, HINT & 4);
                    else load_image(sb, eph, r, v, HINT & 4);
                    PT();
                    r = ring_next(r);
                }
                if (MC & 4) load_image_mc(sb, eph, r, kv + SLOT, j & 1, HINT & 4);
                else load_image(sb, eph, r, kv + SLOT, HINT & 4);
                PT();
                r = ring_next(r);
            }
            uint32_t otab = O_TABLE, ready = 0;
#pragma unroll 1
            for (int i = 0; i < 17; i++) {
                const bool dyn = i >= 8 && i < 15;
                const uint32_t want = dyn ? 15u << (4 * (i - 8)) : 1u << max(i + 14, 28);
                if (!(ready & want)) {
                    do {
                        asm volatile("ld.acquire.cta.shared.u32 %0, [%1];" : "=r"(ready) : "r"(sb + SM_EP + 4) : "memory");
                        ready = __shfl_sync(0xffffffffu, ready, 0);
                    } while (!(ready & want));
                    fence_async_global();
                }
                const int head = o_head(dyn ? (ready >> (4 * (i - 8))) & 15 : i, kh);
                const uint8_t* src = g_ctx + (size_t)(ort * 32 + head) * SLOT;
                if (i < 15) {
                    if (MC & 8) load_image_mc(sb, eph, o_next(otab), src, j & 1, HINT & 16);
                    else load_image(sb, eph, o_next(otab), src, HINT & 16);
                } else {
                    const uint32_t as = o_next(otab), d = sb + as * SLOT;
                    slot_wait(sb + BAR_EMPTY, eph, as);
                    asm volatile("{\n.reg .pred p, q;\nelect.sync _|p, 0xffffffff;\n@p mbarrier.arrive.expect_tx.shared::cta.b64 _, [%2], %3;\n"
                                 "@p cp.async.bulk.shared::cluster.global.mbarrier::complete_tx::bytes [%0], [%1], 16384, [%2];\n}"
                                 ::"r"(d + kh * 16384), "l"(src + kh * 16384), "r"(sb + BAR_FULL + 8 * as), "r"(i == 15 ? 32768 : 16384) : "memory");
                    if (i == 15)
                        asm volatile("{\n.reg .pred p;\nelect.sync _|p, 0xffffffff;\n"
                                     "@p cp.async.bulk.tensor.3d.shared::cluster.global.mbarrier::complete_tx::bytes [%0], [%1, {%3, %4, %5}], [%2];\n}"
                                     ::"r"(d + (kh ^ 1) * 16384), "l"(&tm_x), "r"(sb + BAR_FULL + 8 * as), "r"(0), "r"(ort * 128 + kh * 64), "r"(cq * 2) : "memory");
                }
                PT();
                load_tile(sb, eph, o_next(otab), &tm_wo, head * 128, cq * 2, HINT & 2); PT();
            }
            if (rb < NFFN) {
                load_image(sb, eph, o_next(otab), g_wf + rb * SLOT, false);
                const uint32_t s2 = o_next(otab);
                slot_wait(sb + BAR_EMPTY, eph, s2);
                asm volatile("{\n.reg .pred p;\nelect.sync _|p, 0xffffffff;\n@p mbarrier.arrive.expect_tx.shared::cta.b64 _, [%2], 16384;\n"
                             "@p cp.async.bulk.shared::cluster.global.mbarrier::complete_tx::bytes [%0], [%1], 16384, [%2];\n}"
                             ::"r"(sb + s2 * SLOT), "l"(P.wdown + rb * 8192), "r"(sb + BAR_FULL + 8 * s2) : "memory");
            }
        } else {
            const int hw = warp - 9;
            if (hw == 1 && lane == 0) {
                l2_prefetch(P.ckv + rb * 2048, 4096);
                mbar_watch(sb + BAR_FULL + 8 * PF0, 0);
                l2_prefetch(P.ckv + 512 * 512 + rb * 2048, 4096);
                mbar_watch(sb + BAR_FULL + 8 * 4, 0);
                l2_prefetch(P.x + rb * 8192, 16384);
                l2_prefetch(P.ckv + 1024 * 512 + rb * 4096, 8192);
                TS(40);
                if (MC & 2) tma3d_prefetch(&tm_wq, (j >> 1) * 128, grp * 4 + (j & 1));
                else if (j < 4) tma3d_prefetch(&tm_wq, j * 128, grp * 4);
                mbar_watch(sb + BAR_PF, 0);
                l2_prefetch(P.ckv + rb * 8192, 16384);
                l2_prefetch(g_h + rb * 16384, 16384);
                mbar_watch(sb + BAR_PF, 1);
                tma3d_prefetch((j & 1) ? &tm_wuv : &tm_wuk, (j >> 1) * 128, grp * 4 + 2);
                if (MC & 2) tma3d_prefetch(&tm_wq, (j >> 1) * 128, grp * 4 + 2 + (j & 1));
                else if (j < 4) tma3d_prefetch(&tm_wq, j * 128, grp * 4 + 2);
                mbar_watch(sb + BAR_PF, 0);
                l2_prefetch(g_ctx + (size_t)(ort * 32 + o_head(cq, kh)) * SLOT, SLOT);
                l2_prefetch(g_ctx + (size_t)(ort * 32 + o_head(cq + 4, kh)) * SLOT, SLOT);
                mbar_watch(sb + BAR_PF, 1);
                l2_prefetch(reinterpret_cast<const uint8_t*>(P.wo) + rb * 32768, 32768);
                mbar_watch(sb + BAR_FLAG + 8 * 7, 0);
                if (rb < NFFN) {
                    l2_prefetch(g_wf + rb * SLOT, SLOT);
                    l2_prefetch(P.wdown + rb * 8192, 16384);
                }
                l2_prefetch(P.x + rb * 8192, 16384);
                if (OBINIT) {
                    const uint32_t v = lds32(sb + SM_EP) - 1;
#pragma unroll 1
                    for (int i = 0; i < 32; i++) sts128(sb + SM_RED + i * 16, make_uint4(v, v, v, v));
                    fence_async_smem();
#pragma unroll 1
                    for (int i = 0; i < OB / 32; i++)
                        asm volatile("cp.async.bulk.global.shared::cta.bulk_group [%0], [%1], 512;" ::"l"(g_out + rb * OB + i * 32), "r"(sb + SM_RED) : "memory");
                    asm volatile("cp.async.bulk.commit_group;\ncp.async.bulk.wait_group 0;" ::: "memory");
                    fence_async_global();
                }
                mbar_arrive(sb + BAR_PF);
                mbar_watch(sb + BAR_END, 0);
            }
            if (hw == 0) {
#pragma unroll 1
                for (int i = 0; i < 9; i++) {
                    const int hp = i > 4, k = (i - 1) & 3;
                    if (lane == 0) {
                        mbar_wait(sb + BAR_DONE + 8 * i, 0);
                        flag_add(i == 0 ? &g_sync.hcnt[grp * 8] : k < 2 ? &g_sync.kvcnt[((2 * grp + hp) * 2 + k) * 8]
                                                                        : &g_sync.ctxcnt[(k == 2 ? 15 - j : j) * 32 + 2 * grp + hp]);
                    }
                    if (i == 0) TS(43);
                }
            }
            if (hw == 2) {
                const uint32_t ep = __ldcg(&g_sync.epoch[0]) + 1;
                if (lane == 0) {
                    asm volatile("st.shared.u32 [%0], %1;" ::"r"(sb + SM_EP), "r"(ep) : "memory");
                    flag_wait(&g_sync.modcnt[0], NSPARE * ep);
                }
                __syncwarp();
#pragma unroll
                for (int i = 0; i < 4; i++) {
                    uint4 v = __ldcg(reinterpret_cast<const uint4*>(g_mod) + lane + 32 * i);
                    if (i >= 2) v = make_uint4(badd(v.x, ONE2), badd(v.y, ONE2), badd(v.z, ONE2), badd(v.w, ONE2));
                    sts128(sb + SM_TAB + i * 512 + lane * 16, v);
                }
                __syncwarp();
                if (lane == 0) mbar_arrive(sb + BAR_FLAG + 8 * 8);
                TS(42);
#pragma unroll 1
                for (int i = 0; i < 8; i++) {
                    if (lane == 0) mbar_wait(sb + BAR_DONE + 8 * (i == 7 ? 6 : i == 4 ? 3 : i), 0);
                    __syncwarp();
                    const uint32_t* f = i == 0 ? &g_sync.hcnt[(lane ? j : 15 - j) * 8]
                                      : i == 3 || i == 4 ? &g_sync.rdcnt[(grp * 2 + i - 3) * 8]
                                      : i == 7 ? &g_sync.modcnt[32] : &g_sync.kvcnt[(4 * grp + (i > 4 ? i - 3 : i - 1)) * 8];
                    if (lane < (i ? 1 : 2)) flag_wait(f, 8 * ep);
                    __syncwarp();
                    if (i == 7) {
                        const uint32_t *mp = reinterpret_cast<const uint32_t*>(g_mod) + lane, *wp = reinterpret_cast<const uint32_t*>(P.wr) + lane;
                        float ra = 0.f, rs = 0.f;
#pragma unroll 1
                        for (int k = 0; k < 256; k += 32) {
                            const uint32_t ga = __ldcg(mp + 512 + k), sh = __ldcg(mp + 768 + k), c1 = badd(__ldcg(mp + 1024 + k), ONE2);
                            const uint32_t gb = __ldcg(mp + 1280 + k), ww = __ldg(wp + k);
                            const float a0 = bf_lo(c1) * bf_lo(ww), a1 = bf_hi(c1) * bf_hi(ww);
                            ra += a0 + a1;
                            rs = fmaf(bf_lo(sh), bf_lo(ww), fmaf(bf_hi(sh), bf_hi(ww), rs));
                            if (k >> 6 == cq) {
                                sts128(sb + SM_TAB + ((k & 32) + lane) * 16, make_uint4(ga << 16, ga & 0xffff0000u, __float_as_uint(a0), __float_as_uint(a1)));
                                sts128(sb + SM_TAB + 1024 + ((k & 32) + lane) * 16, make_uint4(c1, sh, gb, 0));
                            }
                        }
                        *reinterpret_cast<float2*>(smem + SM_EP + 8) = make_float2(warp_sum(ra), warp_sum(rs));
                        __syncwarp();
                    }
                    if (lane == 0) mbar_arrive(sb + BAR_FLAG + 8 * i);
                    TS(48 + i);
                }
                const uint32_t* f = &g_sync.ctxcnt[ort * 32 + o_head(min(lane, 16), kh)];
                uint32_t ready = (MC & 8) && (j & 1) ? ~0u : 0u, list = 0, sh = 0, qa = sb + SM_EP + 4;
                if (MC & 8) asm("mapa.shared::cluster.u32 %0, %1, %2;" : "=r"(qa) : "r"(sb + SM_EP + 4), "r"(lane & 1));
                while (ready != ~0u) {
                    uint32_t v;
                    asm volatile("ld.acquire.gpu.global.u32 %0, [%1];" : "=r"(v) : "l"(f) : "memory");
                    const uint32_t now = __ballot_sync(0xffffffffu, (int)(v - ep) >= 0);
                    for (uint32_t fresh = now & ~ready & 0x7f00; fresh; fresh &= fresh - 1, sh += 4) list |= (__ffs(fresh) - 1) << sh;
                    list |= (((now & 0xff) + 1) >> 8 << 28) | ((now & 0x18000) << 14);
                    if (now != ready && lane < ((MC & 8) ? 2 : 1)) asm volatile("st.relaxed.cluster.shared::cluster.u32 [%0], %1;" ::"r"(qa), "r"(list) : "memory");
                    if ((now & 0xff) == 0xff) mbar_wait(sb + BAR_DONE + 8 * 7, 0);
                    ready = now;
                    __nanosleep(POLL_NS);
                }
                TS(45);
            }
        }
    } else {
        asm volatile("setmaxnreg.inc.sync.aligned.u32 232;");
        const bool elected = (tid & 127) == 0, rel = MC ? (tid & 95) == 0 : elected;
        uint32_t eb = sb + BAR_EMPTY;
        if (MC) asm("mapa.shared::cluster.u32 %0, %1, %2;" : "=r"(eb) : "r"(sb + BAR_EMPTY), "r"(warp & 1));
        const int g = lane >> 2, c4 = lane & 3;
        const uint32_t toff = warp * 4096 + g * 64 + ((c4 ^ (g >> 1)) << 4);
        uint32_t fph = 0, r = 0;
        if (wg == 1) bar_arrive(1, 256);
        const uint32_t kd = desc_k(sb), wd = desc_mn(sb), vd = ((sb & 0x3ffff) >> 4) | (32u << 16);
        const int nL = 16 - j, hn = nL - 1 + wg;
        float s[64], o[64], li[2] = {0.f, 0.f};
        uint8_t* cimg = g_ctx;
#pragma unroll 1
        for (int hp = 0; hp < 2; hp++) {
            {
                const int step = hp ? -8 * SLOT : 8 * SLOT;
                uint8_t* img = g_KV + (size_t)(grp * 32 + (hp ? j ^ 30 : j)) * SLOT - step;
                const float sc = (j & 1) ? 1.f : SM_C;
                const uint32_t wtab = w_table(hp);
                uint32_t atab = hp ? 0x256u : a_table(0);
#pragma unroll 1
                for (int t = 0; t < 6; t += 2) {
                    proj_tile<false>(s, o, t, t ? 0 : 2 * hp, sb, wg, eb, rel, fph, wtab, atab, t ? img : cimg, toff, t ? sc : li[0], t ? sc : li[1], (hp | t) == 0, P.x, rb * 16 + warp * 2);
                    __syncwarp();
                    mbar_arrive_if(sb + BAR_DONE + 4 * t + 32 * hp, lane == 0 && (hp | t) != 0);
                    if (elected) TS(1 + 10 * hp + t + 20 * wg);
                    proj_tile<true>(o, s, t + 1, 0, sb, wg, eb, rel, fph, wtab, atab, img + step, toff, sc, sc, (hp | t) == 0, P.x, rb * 16 + warp * 2);
                    if (elected) TS(2 + 10 * hp + t + 20 * wg);
                    img += 2 * step;
                }
            }
            float m[2] = {0.f, 0.f}, l[2] = {0.f, 0.f}, t[4] = {0.f, 0.f, 0.f, 0.f};
            bool shifted = false, bad = false, plain = false;
            uint32_t p[32];
#pragma unroll
            for (int i = 0; i < 32; i++) p[i] = 0;
            uint32_t qa = desc_k(sb + 5 * SLOT + (wg ^ 1) * 8192);
            uint8_t* img = g_ctx + (size_t)((15 - j) * 32 + 2 * grp + hp) * SLOT;
            slot_wait(sb + BAR_FULL, fph, r);
            int n = -1;
#pragma unroll 1
            for (;;) {
                while (bad || plain) {
                    if (bad) {
                        float a0, a1;
                        softmax_remax(s, m, n == 0 || n == nL, a0, a1);
                        shifted = true;
                        l[0] *= a0;
                        l[1] *= a1;
#pragma unroll
                        for (int i = 0; i < 64; i++) o[i] *= (i & 2) ? a1 : a0;
                    }
                    softmax_exp<0, 16>(s, p, t);
                    t[0] += t[1];
                    t[2] += t[3];
                    bad = !bad && softmax_unsafe(t[0], t[2], false);
                    plain = false;
                }
#pragma unroll 1
                do {
                    l[0] += t[0];
                    l[1] += t[2];
                    if (++n > 16) break;
                    const uint32_t ks = r;
                    uint32_t vs = ring_next(r);
                    r = ring_next(vs);
                    bar_sync(1 + wg, 256);
                    if (n == 0 || (uint32_t)(n + 1 - nL) <= (uint32_t)(1 + wg)) {
                        const int x = (warp & 3) * 16 + g - 2 * c4;
                        if (n == 0) {
                            r = vs;
                            vs = 4 - hp;
                            qk_issue(s, qa, kd + ks * (SLOT / 16));
                            slot_wait(sb + BAR_FULL, fph, 6);
                            gemm_issue<false>(o, qa + SLOT / 16, wd + vs * (SLOT / 16), 1, false);
                            bar_arrive(2 - wg, 256);
                            wg_wait<1>();
                            reg_fence(s);
                        } else if (n == hn) {
                            float sh[32];
                            qk_issue(sh, qa, kd + ks * (SLOT / 16));
                            slot_wait(sb + BAR_FULL, fph, vs);
                            pv_issue(o, p, vd + vs * (SLOT / 16), 1, false);
                            bar_arrive(2 - wg, 256);
                            wg_wait<1>();
                            reg_fence(sh);
                            tri_mask_copy(s, sh, x);
                        } else {
                            qk_issue(s, qa, kd + ks * (SLOT / 16));
                            slot_wait(sb + BAR_FULL, fph, vs);
                            pv_issue(o, p, vd + vs * (SLOT / 16), n != nL + 1, n == hn + 1);
                            bar_arrive(2 - wg, 256);
                            wg_wait<1>();
                            reg_fence(s);
                            if (n <= nL) tri_mask<32>(s, x);
                        }
                        release_if(eb, ks, rel);
                        release_if(eb, (n == 16 ? 6 : 5), rel && (n == 16 || n == nL - 1));
                        if (n == nL - 1) {
                            qa += SLOT / 16;
                            fence_async_smem();
                        }
                        if (shifted) {
                            if (n == nL) {
                                m[0] = m[1] = 0.f;
                                shifted = false;
                            }
                            softmax_shift(s, m[0], m[1]);
                        }
                        float e[4 * EARLY];
#pragma unroll
                        for (int i = 0; i < 4 * EARLY; i++) {
                            e[i] = ex2(s[i]);
                            t[i & 3] = i < 4 ? e[i] : t[i & 3] + e[i];
                        }
                        reg_fence(e);
                        slot_wait(sb + BAR_FULL, fph, r);
                        wg_wait<0>();
                        reg_fence(o);
                        reg_fence(e);
                        release_if(eb, vs, rel);
#pragma unroll
                        for (int i = 0; i < 2 * EARLY; i++) p[i] = pack2(e[2 * i], e[2 * i + 1]);
                        softmax_exp<EARLY, 8>(s, p, t);
                        if (n == 0) q_store<(PARKS & 1) != 0>(sb + 6 * SLOT, toff, o);
                        if (n == nL) {
                            ctx_store<(PARKS & 2) != 0>(img, toff, o, l[0], l[1]);
                            __syncwarp();
                            mbar_arrive_if(sb + BAR_DONE + 24 + 32 * hp, lane == 0);
                            l[0] = l[1] = 0.f;
                        }
                        if (n != hn) softmax_exp<8, 16>(s, p, t);
                        t[0] += t[1];
                        t[2] += t[3];
                        bad = softmax_unsafe(t[0], t[2], n == 0 || n == nL);
                        continue;
                    }
                    qk_issue(s, qa, kd + ks * (SLOT / 16));
                    slot_wait(sb + BAR_FULL, fph, vs);
                    pv_issue(o, p, vd + vs * (SLOT / 16), n != 1 && n != nL + 1, false);
                    bar_arrive(2 - wg, 256);
                    wg_wait<1>();
                    reg_fence(s);
                    release_if(eb, ks, rel);
                    release_if(eb, 6, rel && n == 16);
                    if (shifted) {
                        slot_wait(sb + BAR_FULL, fph, r);
                        wg_wait<0>();
                        reg_fence(o);
                        release_if(eb, vs, rel);
                        softmax_shift(s, m[0], m[1]);
                        plain = true;
                        break;
                    }
                    float e[4 * EARLY];
#pragma unroll
                    for (int i = 0; i < 4 * EARLY; i++) {
                        e[i] = ex2(s[i]);
                        t[i & 3] = i < 4 ? e[i] : t[i & 3] + e[i];
                    }
                    reg_fence(e);
                    slot_wait(sb + BAR_FULL, fph, r);
                    wg_wait<0>();
                    reg_fence(o);
                    reg_fence(e);
                    release_if(eb, vs, rel);
#pragma unroll
                    for (int i = 0; i < 2 * EARLY; i++) p[i] = pack2(e[2 * i], e[2 * i + 1]);
                    softmax_exp<EARLY, 16>(s, p, t);
                    t[0] += t[1];
                    t[2] += t[3];
                    bad = softmax_unsafe(t[0], t[2], false);
                } while (!bad);
                if (!bad && !plain) break;
            }
            const uint32_t vs = r, ga = desc_k(sb + (hp ? 2 * (wg ^ kh ^ 1) : wg) * 8192), as = 2 + 2 * hp;
            r = ring_next(r);
            slot_wait(sb + BAR_FULL, fph, 5);
            slot_wait(sb + BAR_FULL, fph, r);
            bar_sync(1 + wg, 256);
            gemm_issue<true>(s, ga + 5 * (SLOT / 16), wd + r * (SLOT / 16), 0, hp);
            pv_issue(o, p, vd + vs * (SLOT / 16), j, hn == 16);
            bar_arrive(2 - wg, 256);
            li[0] = rcp(quad_sum(l[0]));
            li[1] = rcp(quad_sum(l[1]));
            cimg = img + (ptrdiff_t)(2 * j - 15) * 32 * SLOT + (wg ? -16384 : 16384);
            wg_wait<1>();
            release_if(eb, 5, rel);
            release_if(eb, r, rel && hp);
            wg_wait<0>();
            release_if(eb, vs, rel);
            reg_fence(o);
            img_store_global<0>(cimg, toff, o, li[0], li[1]);
            slot_wait(sb + BAR_FULL, fph, as);
            slot_wait(sb + BAR_FULL, fph, 0);
            bar_sync(1 + wg, 256);
            gemm_issue<false>(s, ga + as * (SLOT / 16), wd, 1, hp);
            bar_arrive(2 - wg, 256);
            reg_fence(o);
            img_store_global<1>(cimg, toff, o, li[0], li[1]);
            wg_wait<0>();
            release_if(eb, as, rel);
            release_if(eb, 0, rel && hp);
            if (elected) TS(8 + 10 * hp + 20 * wg);
        }
        uint32_t otab = 0x0435216u;
        const uint32_t oa = desc_k(sb + (wg ^ kh ^ 1) * 16384);
        const int t7 = tid & 127, w4 = warp & 3, row = ort * 128 + kh * 64 + w4 * 16 + g;
#pragma unroll 1
        for (int i = 2; i < 15 - wg; i++) {
            const uint32_t as = o_next(otab), ws = o_next(otab);
            slot_wait(sb + BAR_FULL, fph, as);
            slot_wait(sb + BAR_FULL, fph, ws);
            bar_sync(1 + wg, 256);
            gemm_issue<false>(s, oa + as * (SLOT / 16), wd + ws * (SLOT / 16), 1, true);
            bar_arrive(2 - wg, 256);
            wg_wait<1>();
            reg_fence(o);
            if (i == 2) img_store_global<2>(cimg, toff, o, li[0], li[1]);
            if (i == CLAST) {
                img_store_global<3>(cimg, toff, o, li[0], li[1]);
                __syncwarp();
                mbar_arrive_if(sb + BAR_DONE + 64, lane == 0);
            }
            wg_wait<0>();
            release_if(eb, as, rel);
            release_if(eb, ws, rel);
        }
        mbar_wait(sb + BAR_PF, 0);
        const uint32_t ep = lds32(sb + SM_EP);
        if (wg == 0) {
            reg_fence(s);
            if (elected) TS(9);
#pragma unroll
            for (int v = 0; v < 8; v++)
                st_pub(g_out + rb * OB + v * 128 + t7, make_uint4((pack2(s[8 * v], s[8 * v + 1]) & ~1u) | (ep & 1), pack2(s[8 * v + 2], s[8 * v + 3]),
                                                                      pack2(s[8 * v + 4], s[8 * v + 5]), pack2(s[8 * v + 6], s[8 * v + 7])), true);
            o_next(otab); o_next(otab); o_next(otab); o_next(otab);
            const uint32_t s1 = o_next(otab), s2 = o_next(otab);
            bar_sync(4, 256);
            uint32_t wf[64];
            float wn[64];
            if (rb < NFFN) {
                slot_wait(sb + BAR_FULL, fph, s1);
                const uint32_t a = sb + s1 * SLOT + (w4 * 128 + (lane >> 4) * 8 + (lane & 7)) * 32 + ((lane >> 3) & 1) * 16;
#pragma unroll
                for (int i = 0; i < 16; i++)
                    asm volatile("ldmatrix.sync.aligned.m8n8.x4.trans.shared.b16 {%0, %1, %2, %3}, [%4];"
                                 : "=r"(wf[4 * i]), "=r"(wf[4 * i + 1]), "=r"(wf[4 * i + 2]), "=r"(wf[4 * i + 3])
                                 : "r"(a + (i >> 3) * 16384 + (i & 7) * 512) : "memory");
                slot_wait(sb + BAR_FULL, fph, s2);
#pragma unroll
                for (int i = 0; i < 16; i++) {
                    const uint2 w = *reinterpret_cast<const uint2*>(smem + s2 * SLOT + i * 1024 + t7 * 8);
                    wn[4 * i] = bf_lo(w.x); wn[4 * i + 1] = bf_hi(w.x); wn[4 * i + 2] = bf_lo(w.y); wn[4 * i + 3] = bf_hi(w.y);
                }
                reg_fence(wn);
            }
            const uint32_t gbf = __ldcg(reinterpret_cast<const uint32_t*>(g_mod) + 1280 + rb * 2 + (tid & 1));
            if (elected) TS(10);
            const uint32_t best = best_key(g_key + cq * 128, lane, ep);
            const int sel = (~best >> 5) & 2047;
            if (elected) TS(19);
            const uint4* cp = g_cand + (sel >> 4) * 192;
            float* sred = reinterpret_cast<float*>(smem + SM_RED);
            const int pq = (2 * rb + (tid & 1)) & 63, pv = (pq >> 2) / 3;
            const uint4* fp = cp + (rb >> 5) * 24 + pv * 4 + (pq & 3);
            uint4 fh = ld_poll(fp), fx = ld_poll(fp + 96);
            if (rb < NFFN) {
                uint4 cv[6];
                for (;;) {
                    uint32_t bad = 0;
#pragma unroll
                    for (int v = 0; v < 6; v++) cv[v] = ld_poll(cp + w4 * 24 + v * 4 + c4);
#pragma unroll
                    for (int v = 0; v < 6; v++) bad |= cv[v].w ^ ep;
                    if (__all_sync(0xffffffffu, bad == 0)) break;
                }
                if (elected) TS(20);
                float d[4][4] = {};
#pragma unroll
                for (int k = 0; k < 8; k++) {
                    const uint32_t b0 = (&cv[(2 * k) / 3].x)[(2 * k) % 3], b1 = (&cv[(2 * k + 1) / 3].x)[(2 * k + 1) % 3];
                    mma16816(d[k & 1], wf + 4 * k, b0, b1);
                    mma16816(d[2 + (k & 1)], wf + 32 + 4 * k, b0, b1);
                }
                const float u = (c4 & 2) ? ((c4 & 1) ? d[2][2] + d[3][2] : d[2][0] + d[3][0]) : ((c4 & 1) ? d[0][2] + d[1][2] : d[0][0] + d[1][0]);
                sred[w4 * 32 + c4 * 8 + g] = u;
                bar_sync(3, 128);
                const float v = rbf((sred[lane] + sred[32 + lane]) + (sred[64 + lane] + sred[96 + lane]));
                const float act = rbf(rbf(v * sigmoid(v)) * __shfl_down_sync(0xffffffffu, v, 16));
                float y[4] = {0.f, 0.f, 0.f, 0.f};
#pragma unroll
                for (int k = 0; k < 16; k++) {
                    const float a = __shfl_sync(0xffffffffu, act, k);
#pragma unroll
                    for (int i = 0; i < 4; i++) y[i] = fmaf(a, wn[4 * k + i], y[i]);
                }
                st_pub(g_out + rb * OB + OB_Y + t7, make_uint4((__float_as_uint(y[0]) & ~15u) | (ep & 15), __float_as_uint(y[1]), __float_as_uint(y[2]), __float_as_uint(y[3])), true);
            }
            if (rb == 0 && tid == 0) g_sync.epoch[0] = ep;
            if (elected) TS(60);
            uint4 yv;
            do yv = ld_poll(g_out + min(t7, NFFN - 1) * OB + OB_Y + rb);
            while (!__all_sync(0xffffffffu, ((yv.x ^ ep) & 15) == 0));
            if (elected) TS(61);
            float y[4] = {0.f, 0.f, 0.f, 0.f};
            if (t7 < NFFN) { y[0] = __uint_as_float(yv.x); y[1] = __uint_as_float(yv.y); y[2] = __uint_as_float(yv.z); y[3] = __uint_as_float(yv.w); }
            const float z0 = ((lane & 16) ? y[2] : y[0]) + __shfl_xor_sync(0xffffffffu, (lane & 16) ? y[0] : y[2], 16);
            const float z1 = ((lane & 16) ? y[3] : y[1]) + __shfl_xor_sync(0xffffffffu, (lane & 16) ? y[1] : y[3], 16);
            float z = ((lane & 8) ? z1 : z0) + __shfl_xor_sync(0xffffffffu, (lane & 8) ? z0 : z1, 8);
            z += __shfl_xor_sync(0xffffffffu, z, 4);
            z = quad_sum(z);
            if ((lane & 7) == 0) sred[128 + (lane >> 3) * 4 + w4] = z;
            bar_sync(3, 128);
            if (tid < 2) {
                while (fh.w != ep || fx.w != ep) { fh = ld_poll(fp); fx = ld_poll(fp + 96); }
                const float4 y0 = *reinterpret_cast<const float4*>(sred + 128 + tid * 8), y1 = *reinterpret_cast<const float4*>(sred + 132 + tid * 8);
                const int cm = (pq >> 2) - 3 * pv;
                const uint32_t h2 = cm == 0 ? fh.x : cm == 1 ? fh.y : fh.z, x2 = cm == 0 ? fx.x : cm == 1 ? fx.y : fx.z;
                const float sg = sigmoid(bf_hi((best & 0x80000000u) ? (best ^ 0x80000000u) : ~best));
                reinterpret_cast<uint32_t*>(P.out)[sel * 256 + rb * 2 + tid] =
                    badd(x2, bmul(gbf, badd(h2, bmul(pack2((y0.x + y0.y) + (y0.z + y0.w), (y1.x + y1.y) + (y1.z + y1.w)), pack2(sg, sg)))));
            }
            if (elected) TS(62);
        } else {
            const float4* tf = reinterpret_cast<const float4*>(smem + SM_TAB) + c4;
            const uint32_t as14 = otab & 15, xa = sb + ((otab >> 8) & 15) * SLOT + (kh ^ 1) * 16384 + (w4 * 16 + (lane & 15)) * 128;
            uint32_t x2[32];
            bar_sync(2, 256);
#pragma unroll 1
            for (int i = 14; i < 17; i++) {
                const uint32_t as = o_next(otab), ws = o_next(otab);
                slot_wait(sb + BAR_FULL, fph, as);
                slot_wait(sb + BAR_FULL, fph, ws);
                gemm_issue<false>(s, oa + as * (SLOT / 16), wd + ws * (SLOT / 16), 1, true);
                wg_wait<1>();
                release_if(eb, as14, rel && i == 15);
            }
            if (elected) TS(29);
            {
#pragma unroll
                for (int k = 0; k < 8; k++)
                    asm volatile("ldmatrix.sync.aligned.m8n8.x4.shared.b16 {%0, %1, %2, %3}, [%4];"
                                 : "=r"(x2[4 * k]), "=r"(x2[4 * k + 1]), "=r"(x2[4 * k + 2]), "=r"(x2[4 * k + 3])
                                 : "r"(xa + (k >> 2) * 8192 + (((2 * (k & 3) + (lane >> 4)) ^ (lane & 7)) << 4)) : "memory");
            }
            wg_wait<0>();
            reg_fence(s);
            bar_arrive(4, 256);
            if (elected) TS(39);
            const uint4* pr = g_out + (rb ^ 8) * OB + t7;
            uint4 pa[8];
#pragma unroll
            for (int v = 0; v < 8; v++) pa[v] = ld_poll(pr + v * 128);
            float4 tc[16];
#pragma unroll
            for (int k = 0; k < 16; k++) {
                tc[k] = tf[k * 4];
#pragma unroll
                for (int i = 4 * k; i < 4 * k + 4; i++) s[i] = fmaf((i & 1) ? tc[k].y : tc[k].x, s[i], (i & 1) ? bf_hi(x2[i >> 1]) : bf_lo(x2[i >> 1]));
            }
            reg_fence(s);
            for (;;) {
                uint32_t bad = 0;
#pragma unroll
                for (int v = 0; v < 8; v++) bad |= pa[v].x ^ ep;
                if (__all_sync(0xffffffffu, (bad & 1) == 0)) break;
#pragma unroll
                for (int v = 0; v < 8; v++) pa[v] = ld_poll(pr + v * 128);
            }
            if (elected) TS(30);
            float st[6] = {0.f, 0.f, 0.f, 0.f, 0.f, 0.f};
#pragma unroll
            for (int i = 0; i < 64; i++) {
                const int rh = (i >> 1) & 1;
                const uint32_t w = (&pa[i >> 3].x)[(i >> 1) & 3];
                const float v = fmaf((i & 1) ? tc[i >> 2].y : tc[i >> 2].x, (i & 1) ? bf_hi(w) : bf_lo(w), s[i]);
                s[i] = v;
                st[rh] += v;
                st[2 + rh] = fmaf(v, v, st[2 + rh]);
                st[4 + rh] = fmaf(v, (i & 1) ? tc[i >> 2].w : tc[i >> 2].z, st[4 + rh]);
            }
#pragma unroll
            for (int i = 0; i < 6; i++) st[i] = quad_sum(st[i]);
            st_pub(g_out + rb * OB + OB_STAT + (w4 * 8 + g) * 2 + (c4 & 1),
                   make_uint4(__float_as_uint((c4 & 1) ? st[1] : st[0]), __float_as_uint((c4 & 1) ? st[3] : st[2]),
                              __float_as_uint((c4 & 1) ? st[5] : st[4]), ep), c4 < 2);
            if (elected) TS(56);
            uint32_t cb[16], sh[16], gb[16];
#pragma unroll
            for (int i = 0; i < 16; i++) {
                const float4 c = tf[64 + i * 4];
                cb[i] = __float_as_uint(c.x); sh[i] = __float_as_uint(c.y); gb[i] = __float_as_uint(c.z);
            }
            const float ra = __uint_as_float(lds32(sb + SM_EP + 8)), rb0 = __uint_as_float(lds32(sb + SM_EP + 12));
#pragma unroll
            for (int i = 0; i < 32; i++) x2[i] = pack2(s[2 * i], s[2 * i + 1]);
            reg_fence(x2);
            uint4 r0, r1;
            for (;;) {
                r0 = ld_poll(g_out + ((rb & ~3) + c4) * OB + OB_STAT + (w4 * 8 + g) * 2);
                r1 = ld_poll(g_out + ((rb & ~3) + c4) * OB + OB_STAT + (w4 * 8 + g) * 2 + 1);
                if (__all_sync(0xffffffffu, r0.w == ep && r1.w == ep)) break;
            }
            if (elected) TS(57);
            const float m0 = quad_sum(__uint_as_float(r0.x)) * (1.f / 512.f), m1 = quad_sum(__uint_as_float(r1.x)) * (1.f / 512.f);
            const float rs0 = ln_rstd(fmaxf(fmaf(-m0, m0, quad_sum(__uint_as_float(r0.y)) * (1.f / 512.f)), 0.f));
            const float rs1 = ln_rstd(fmaxf(fmaf(-m1, m1, quad_sum(__uint_as_float(r1.y)) * (1.f / 512.f)), 0.f));
            const uint32_t mb0 = pack2(m0, m0), mb1 = pack2(m1, m1);
            const uint32_t lg = pack2(fmaf(rs0, fmaf(-bf_lo(mb0), ra, quad_sum(__uint_as_float(r0.z))), rb0),
                                      fmaf(rs1, fmaf(-bf_lo(mb1), ra, quad_sum(__uint_as_float(r1.z))), rb0));
            const uint32_t u0 = lg << 16, u1 = lg & 0xffff0000u;
            const uint32_t k0 = ((u0 ^ (((int)u0 >> 31) | 0x80000000u)) & 0xffff0000u) | ((2047 - row) << 5) | (ep & 31);
            const uint32_t k1 = ((u1 ^ (((int)u1 >> 31) | 0x80000000u)) & 0xffff0000u) | ((2039 - row) << 5) | (ep & 31);
            const uint32_t kb = __reduce_max_sync(0xffffffffu, max(k0, k1));
            st_pub(g_key + cq * 128 + (row >> 4), kb, lane == 0);
            {
                uint32_t cx[18], ch[18];
#pragma unroll
                for (int i = 0; i < 16; i++) {
                    cx[i] = kb == k1 ? x2[2 * i + 1] : x2[2 * i];
                    ch[i] = ln_apply(cx[i], kb == k1 ? mb1 : mb0, kb == k1 ? rs1 : rs0, cb[i], sh[i]);
                }
                cx[16] = cx[17] = ch[16] = ch[17] = 0;
                uint4* cp = g_cand + (row >> 4) * 192 + cq * 24 + c4;
#pragma unroll
                for (int v = 0; v < 6; v++) st_pub(cp + v * 4, make_uint4(ch[3 * v], ch[3 * v + 1], ch[3 * v + 2], ep), kb == k0 || kb == k1);
#pragma unroll
                for (int v = 0; v < 6; v++) st_pub(cp + 96 + v * 4, make_uint4(cx[3 * v], cx[3 * v + 1], cx[3 * v + 2], ep), kb == k0 || kb == k1);
            }
            if (elected) TS(58);
            uint2 ov[16];
#pragma unroll
            for (int i = 0; i < 16; i++) {
                const int rh = i & 1, jj = i & 14;
                const uint32_t v0 = badd(x2[2 * jj + rh], bmul(gb[jj], ln_apply(x2[2 * jj + rh], rh ? mb1 : mb0, rh ? rs1 : rs0, cb[jj], sh[jj])));
                const uint32_t v1 = badd(x2[2 * jj + 2 + rh], bmul(gb[jj + 1], ln_apply(x2[2 * jj + 2 + rh], rh ? mb1 : mb0, rh ? rs1 : rs0, cb[jj + 1], sh[jj + 1])));
                const uint32_t rv = __shfl_xor_sync(0xffffffffu, (c4 & 1) ? v0 : v1, 1);
                ov[i] = (c4 & 1) ? make_uint2(rv, v1) : make_uint2(v0, rv);
            }
            uint2* op = reinterpret_cast<uint2*>(P.out) + row * 128 + cq * 32 + (c4 & 1) * 2 + (c4 >> 1);
#pragma unroll
            for (int i = 0; i < 16; i++)
                if (kb != ((i & 1) ? k1 : k0)) op[(i & 1) * 1024 + (i & 14) * 2] = ov[i];
            const uint32_t best = best_key(g_key + cq * 128, lane, ep);
            if (best != kb) {
#pragma unroll
                for (int i = 0; i < 16; i++)
                    if (kb == ((i & 1) ? k1 : k0)) op[(i & 1) * 1024 + (i & 14) * 2] = ov[i];
            }
            if (elected) TS(59);
        }
        mbar_arrive_if(sb + BAR_END, lane == 0);
    }
}

typedef CUresult (*EncodeFn)(CUtensorMap*, CUtensorMapDataType, cuuint32_t, void*, const cuuint64_t*, const cuuint64_t*,
                             const cuuint32_t*, const cuuint32_t*, CUtensorMapInterleave, CUtensorMapSwizzle,
                             CUtensorMapL2promotion, CUtensorMapFloatOOBfill);

void make_2d(EncodeFn fn, CUtensorMap* m, const void* p, uint64_t cols, uint64_t rows, uint32_t bc, uint32_t br) {
    cuuint64_t dims[2] = {cols, rows}, strides[1] = {cols * 2};
    cuuint32_t box[2] = {bc, br}, es[2] = {1, 1};
    fn(m, CU_TENSOR_MAP_DATA_TYPE_BFLOAT16, 2, const_cast<void*>(p), dims, strides, box, es, CU_TENSOR_MAP_INTERLEAVE_NONE,
       CU_TENSOR_MAP_SWIZZLE_NONE, CU_TENSOR_MAP_L2_PROMOTION_L2_128B, CU_TENSOR_MAP_FLOAT_OOB_FILL_NONE);
}
void make_3d(EncodeFn fn, CUtensorMap* m, const void* p, uint64_t cols, uint64_t rows, uint32_t br = 128, uint32_t nb = 2) {
    cuuint64_t dims[3] = {64, rows, cols / 64}, strides[2] = {cols * 2, 128};
    cuuint32_t box[3] = {64, br, nb}, es[3] = {1, 1, 1};
    fn(m, CU_TENSOR_MAP_DATA_TYPE_BFLOAT16, 3, const_cast<void*>(p), dims, strides, box, es, CU_TENSOR_MAP_INTERLEAVE_NONE,
       CU_TENSOR_MAP_SWIZZLE_128B, CU_TENSOR_MAP_L2_PROMOTION_L2_256B, CU_TENSOR_MAP_FLOAT_OOB_FILL_NONE);
}

}

extern "C" void kernel_launch(void* const* d_in, const int* in_sizes, int n_in, void* d_out, int out_size) {
    static EncodeFn fn = nullptr;
    static int sms = 0;
    if (!fn) {
        void* f = nullptr;
        cudaDriverEntryPointQueryResult st;
        cudaGetDriverEntryPoint("cuTensorMapEncodeTiled", &f, cudaEnableDefault, &st);
        fn = (EncodeFn)f;
        int dev = 0;
        cudaGetDevice(&dev);
        cudaDeviceGetAttribute(&sms, cudaDevAttrMultiProcessorCount, dev);
        cudaFuncSetAttribute(fused_kernel, cudaFuncAttributeMaxDynamicSharedMemorySize, SMEM_BYTES);
    }
    CUtensorMap ckv, wq, wuk, wuv, wo, wg, wu, wm, xm;
    make_3d(fn, &ckv, d_in[1], 512, 2048, 128, (MC & 1) ? 1 : 2);
    make_3d(fn, &xm, d_in[0], 512, 2048, 64);
    make_3d(fn, &wq, d_in[2], 4096, 512, 128, (MC & 2) ? 1 : 2);
    make_3d(fn, &wuk, d_in[3], 4096, 512);
    make_3d(fn, &wuv, d_in[4], 4096, 512);
    make_3d(fn, &wo, d_in[5], 512, 4096);
    make_2d(fn, &wg, d_in[8], 1792, 512, 16, 256);
    make_2d(fn, &wu, d_in[9], 1792, 512, 16, 256);
    make_2d(fn, &wm, d_in[12], 3072, 512, 256, 64);
    Params p;
    p.x = (const bf16*)d_in[0];
    p.ckv = (const bf16*)d_in[1];
    p.wo = (const bf16*)d_in[5];
    p.wr = (const bf16*)d_in[7];
    p.wdown = (const bf16*)d_in[10];
    p.c = (const bf16*)d_in[11];
    p.out = (bf16*)d_out;
    p.by_smid = sms == NCTA + NSPARE;
    fused_kernel<<<NCTA + NSPARE, 384, SMEM_BYTES>>>(ckv, wq, wuk, wuv, wo, wg, wu, wm, xm, p);
}
```

```cpp
#include <cuda.h>
#include <cuda_bf16.h>
#include <cuda_runtime.h>
#include <stdint.h>
#include <stdio.h>

namespace {

typedef __nv_bfloat16 bf16;
typedef unsigned long long u64;

constexpr int NCTA = 128, NSPARE = 4;
constexpr int SLOT = 32768;
constexpr int SM_BAR = 7 * SLOT;
constexpr int BAR_FULL = SM_BAR;
constexpr int BAR_EMPTY = BAR_FULL + 8 * 7;
constexpr int BAR_DONE = BAR_EMPTY + 8 * 7;
constexpr int BAR_FLAG = BAR_DONE + 8 * 9;
constexpr int BAR_PF = BAR_FLAG + 8 * 9;
constexpr int BAR_END = BAR_PF + 8;
constexpr int SM_EP = BAR_END + 8;
constexpr int SM_RED = SM_BAR + 384;
constexpr int SM_TAB = SM_BAR + 1024;
constexpr int SMEM_BYTES = SM_BAR + 3072;
constexpr int NFFN = 112;
#define HINT 29
constexpr u64 L2_NORMAL = 0x1000000000000000ull, L2_FIRST = 0x12F0000000000000ull;
#define PF0 0
#define PFA 9
#define PFB 6
#define PFC 12
#define PFMASK 1023
#define UNR 4
#define PARKS 7
#define POLL_NS 50
#define CLAST 2
#define OBINIT 1
#define MC 15
#define EARLY 7
constexpr uint32_t SPIN_LIMIT = 1u << 22;
constexpr uint32_t ONE2 = 0x3f803f80u;

struct Sync {
    uint32_t modcnt[2 * 32];
    uint32_t hcnt[16 * 8];
    uint32_t kvcnt[32 * 2 * 8];
    uint32_t ctxcnt[16 * 32];
    uint32_t rdcnt[16 * 2 * 8];
    uint32_t epoch[32];
};

__device__ __align__(1024) uint8_t g_KV[16 * 16 * 2 * SLOT];
__device__ __align__(1024) uint8_t g_ctx[16 * 32 * SLOT];
__device__ __align__(1024) uint8_t g_h[16 * 4 * SLOT];
constexpr int OB = 1216, OB_STAT = 1024, OB_Y = 1088;
__device__ __align__(1024) uint4 g_out[128 * OB];
__device__ __align__(1024) bf16 g_mod[3072];
__device__ __align__(1024) uint4 g_cand[128 * 192];
__device__ __align__(1024) uint32_t g_key[4 * 128];
__device__ __align__(1024) uint8_t g_wf[NFFN * SLOT];
__device__ __align__(1024) Sync g_sync;
#define TS(i)

#define PT()

struct Params {
    const bf16 *x, *ckv, *wo, *wr, *wdown, *c;
    bf16* out;
    int by_smid;
};

__device__ __forceinline__ void mbar_init(uint32_t bar, uint32_t cnt) {
    asm volatile("mbarrier.init.shared::cta.b64 [%0], %1;" ::"r"(bar), "r"(cnt) : "memory");
}
__device__ __forceinline__ void mbar_wait(uint32_t bar, uint32_t parity) {
    asm volatile("{\n.reg .pred p;\nL_%=:\nmbarrier.try_wait.parity.shared::cta.b64 p, [%0], %1;\n@!p bra L_%=;\n}" ::"r"(bar), "r"(parity) : "memory");
}
__device__ __forceinline__ void mbar_watch(uint32_t bar, uint32_t parity) {
    asm volatile("{\n.reg .pred p;\n.reg .u32 n;\nmov.u32 n, 0;\n"
                 "L_%=:\nmbarrier.try_wait.parity.shared::cta.b64 p, [%0], %1;\n@p bra D_%=;\n"
                 "add.u32 n, n, 1;\nsetp.lt.u32 p, n, %2;\n@p bra L_%=;\ntrap;\nD_%=:\n}"
                 ::"r"(bar), "r"(parity), "n"(SPIN_LIMIT) : "memory");
}
__device__ __forceinline__ void step_watch(uint32_t a, uint32_t step) {
    asm volatile("{\n.reg .pred p;\n.reg .u32 n, v;\nmov.u32 n, 0;\n"
                 "L_%=:\nld.volatile.shared.u32 v, [%0];\nsetp.ge.u32 p, v, %1;\n@p bra D_%=;\nnanosleep.u32 200;\n"
                 "add.u32 n, n, 1;\nsetp.lt.u32 p, n, %2;\n@p bra L_%=;\ntrap;\nD_%=:\n}"
                 ::"r"(a), "r"(step), "n"(SPIN_LIMIT) : "memory");
}
__device__ __forceinline__ void mbar_arrive(uint32_t bar) {
    asm volatile("mbarrier.arrive.shared::cta.b64 _, [%0];" ::"r"(bar) : "memory");
}
__device__ __forceinline__ void mbar_arrive_if(uint32_t bar, bool on) {
    asm volatile("{\n.reg .pred p;\nsetp.ne.s32 p, %1, 0;\n@p mbarrier.arrive.shared::cta.b64 _, [%0];\n}" ::"r"(bar), "r"((int)on) : "memory");
}
__device__ __forceinline__ void mbar_expect(uint32_t bar, uint32_t bytes) {
    asm volatile("mbarrier.arrive.expect_tx.shared::cta.b64 _, [%0], %1;" ::"r"(bar), "r"(bytes) : "memory");
}
__device__ __forceinline__ void tma2d(uint32_t dst, const CUtensorMap* m, int c0, int c1, uint32_t bar) {
    asm volatile("cp.async.bulk.tensor.2d.shared::cluster.global.mbarrier::complete_tx::bytes [%0], [%1, {%3, %4}], [%2];"
                 ::"r"(dst), "l"(m), "r"(bar), "r"(c0), "r"(c1) : "memory");
}
__device__ __forceinline__ void tma3d_prefetch(const CUtensorMap* m, int row, int cb) {
    asm volatile("cp.async.bulk.prefetch.tensor.3d.L2.global [%0, {%1, %2, %3}];" ::"l"(m), "r"(0), "r"(row), "r"(cb) : "memory");
}
__device__ __forceinline__ void l2_prefetch(const void* p, uint32_t bytes) {
    asm volatile("cp.async.bulk.prefetch.L2.global [%0], %1;" ::"l"(p), "r"(bytes) : "memory");
}
__device__ __forceinline__ void flag_wait(const uint32_t* f, uint32_t target) {
    asm volatile("{\n.reg .pred p;\n.reg .u32 v;\n"
                 "L_%=:\nld.acquire.gpu.global.u32 v, [%0];\nsub.u32 v, v, %1;\nsetp.lt.s32 p, v, 0;\n@p nanosleep.u32 100;\n@p bra L_%=;\n}"
                 ::"l"(f), "r"(target) : "memory");
}
__device__ __forceinline__ uint4 ld_poll(const uint4* p) {
    uint4 v;
    asm volatile("ld.relaxed.gpu.global.v4.u32 {%0, %1, %2, %3}, [%4];" : "=r"(v.x), "=r"(v.y), "=r"(v.z), "=r"(v.w) : "l"(p) : "memory");
    return v;
}
__device__ __forceinline__ void st_pub(uint4* p, uint4 v, bool on) {
    asm volatile("{\n.reg .pred p;\nsetp.ne.s32 p, %5, 0;\n@p st.relaxed.gpu.global.v4.u32 [%0], {%1, %2, %3, %4};\n}"
                 ::"l"(p), "r"(v.x), "r"(v.y), "r"(v.z), "r"(v.w), "r"((int)on) : "memory");
}
__device__ __forceinline__ void st_pub(uint32_t* p, uint32_t v, bool on) {
    asm volatile("{\n.reg .pred p;\nsetp.ne.s32 p, %2, 0;\n@p st.relaxed.gpu.global.u32 [%0], %1;\n}" ::"l"(p), "r"(v), "r"((int)on) : "memory");
}
__device__ __forceinline__ void flag_add(uint32_t* p) {
    asm volatile("red.release.gpu.global.add.u32 [%0], 1;" ::"l"(p) : "memory");
}
__device__ __forceinline__ uint32_t lds32(uint32_t a) {
    uint32_t v;
    asm volatile("ld.shared.u32 %0, [%1];" : "=r"(v) : "r"(a) : "memory");
    return v;
}
__device__ __forceinline__ uint4 lds128(uint32_t a) {
    uint4 v;
    asm volatile("ld.shared.v4.u32 {%0, %1, %2, %3}, [%4];" : "=r"(v.x), "=r"(v.y), "=r"(v.z), "=r"(v.w) : "r"(a) : "memory");
    return v;
}
__device__ __forceinline__ void fence_async_global() { asm volatile("fence.proxy.async.global;" ::: "memory"); }
__device__ __forceinline__ void fence_async_smem() { asm volatile("fence.proxy.async.shared::cta;" ::: "memory"); }
__device__ __forceinline__ void bar_sync(int id, int n) { asm volatile("bar.sync %0, %1;" ::"r"(id), "r"(n) : "memory"); }
__device__ __forceinline__ void bar_arrive(int id, int n) { asm volatile("bar.arrive %0, %1;" ::"r"(id), "r"(n) : "memory"); }
__device__ __forceinline__ void wg_fence() { asm volatile("wgmma.fence.sync.aligned;" ::: "memory"); }
__device__ __forceinline__ void wg_commit() { asm volatile("wgmma.commit_group.sync.aligned;" ::: "memory"); }
template <int N> __device__ __forceinline__ void wg_wait() { asm volatile("wgmma.wait_group.sync.aligned %0;" ::"n"(N) : "memory"); }
template <int N> __device__ __forceinline__ void reg_fence(float (&d)[N]) {
#pragma unroll
    for (int i = 0; i < N; i++) asm volatile("" : "+f"(d[i])::"memory");
}
template <int N> __device__ __forceinline__ void reg_fence(uint32_t (&d)[N]) {
#pragma unroll
    for (int i = 0; i < N; i++) asm volatile("" : "+r"(d[i])::"memory");
}
__device__ __forceinline__ uint32_t desc_k(uint32_t a) { return ((a & 0x3ffff) >> 4) | (1u << 16); }
__device__ __forceinline__ uint32_t desc_mn(uint32_t a) { return ((a & 0x3ffff) >> 4) | (1024u << 16); }

template <int TB>
__device__ __forceinline__ void wgmma_ss128(float (&d)[64], uint32_t da, uint32_t db, int acc, uint32_t ha = 0x40000040u, uint32_t hb = 0x40000040u) {
    asm volatile("{\n.reg .pred p;\n.reg .b64 a, b;\nsetp.ne.b32 p, %66, 0;\nmov.b64 a, {%64, %68};\nmov.b64 b, {%65, %69};\n"
        "wgmma.mma_async.sync.aligned.m64n128k16.f32.bf16.bf16 {%0, %1, %2, %3, %4, %5, %6, %7, %8, %9, %10, %11, %12, %13, %14, %15, %16, %17, %18, %19, %20, %21, %22, %23, %24, %25, %26, %27, %28, %29, %30, %31, %32, %33, %34, %35, %36, %37, %38, %39, %40, %41, %42, %43, %44, %45, %46, %47, %48, %49, %50, %51, %52, %53, %54, %55, %56, %57, %58, %59, %60, %61, %62, %63}, a, b, p, 1, 1, 0, %67;\n}"
        : "+f"(d[0]), "+f"(d[1]), "+f"(d[2]), "+f"(d[3]), "+f"(d[4]), "+f"(d[5]), "+f"(d[6]), "+f"(d[7]), "+f"(d[8]), "+f"(d[9]), "+f"(d[10]), "+f"(d[11]), "+f"(d[12]), "+f"(d[13]), "+f"(d[14]), "+f"(d[15]), "+f"(d[16]), "+f"(d[17]), "+f"(d[18]), "+f"(d[19]), "+f"(d[20]), "+f"(d[21]), "+f"(d[22]), "+f"(d[23]), "+f"(d[24]), "+f"(d[25]), "+f"(d[26]), "+f"(d[27]), "+f"(d[28]), "+f"(d[29]), "+f"(d[30]), "+f"(d[31]), "+f"(d[32]), "+f"(d[33]), "+f"(d[34]), "+f"(d[35]), "+f"(d[36]), "+f"(d[37]), "+f"(d[38]), "+f"(d[39]), "+f"(d[40]), "+f"(d[41]), "+f"(d[42]), "+f"(d[43]), "+f"(d[44]), "+f"(d[45]), "+f"(d[46]), "+f"(d[47]), "+f"(d[48]), "+f"(d[49]), "+f"(d[50]), "+f"(d[51]), "+f"(d[52]), "+f"(d[53]), "+f"(d[54]), "+f"(d[55]), "+f"(d[56]), "+f"(d[57]), "+f"(d[58]), "+f"(d[59]), "+f"(d[60]), "+f"(d[61]), "+f"(d[62]), "+f"(d[63])
        : "r"(da), "r"(db), "r"(acc), "n"(TB), "r"(ha), "r"(hb));
}
template <int TB>
__device__ __forceinline__ void wgmma_ss128_init(float (&d)[64], uint32_t da, uint32_t db, uint32_t ha = 0x40000040u, uint32_t hb = 0x40000040u) {
    asm volatile("{\n.reg .pred p;\n.reg .b64 a, b;\nsetp.ne.b32 p, 0, 0;\nmov.b64 a, {%64, %67};\nmov.b64 b, {%65, %68};\n"
        "wgmma.mma_async.sync.aligned.m64n128k16.f32.bf16.bf16 {%0, %1, %2, %3, %4, %5, %6, %7, %8, %9, %10, %11, %12, %13, %14, %15, %16, %17, %18, %19, %20, %21, %22, %23, %24, %25, %26, %27, %28, %29, %30, %31, %32, %33, %34, %35, %36, %37, %38, %39, %40, %41, %42, %43, %44, %45, %46, %47, %48, %49, %50, %51, %52, %53, %54, %55, %56, %57, %58, %59, %60, %61, %62, %63}, a, b, p, 1, 1, 0, %66;\n}"
        : "=f"(d[0]), "=f"(d[1]), "=f"(d[2]), "=f"(d[3]), "=f"(d[4]), "=f"(d[5]), "=f"(d[6]), "=f"(d[7]), "=f"(d[8]), "=f"(d[9]), "=f"(d[10]), "=f"(d[11]), "=f"(d[12]), "=f"(d[13]), "=f"(d[14]), "=f"(d[15]), "=f"(d[16]), "=f"(d[17]), "=f"(d[18]), "=f"(d[19]), "=f"(d[20]), "=f"(d[21]), "=f"(d[22]), "=f"(d[23]), "=f"(d[24]), "=f"(d[25]), "=f"(d[26]), "=f"(d[27]), "=f"(d[28]), "=f"(d[29]), "=f"(d[30]), "=f"(d[31]), "=f"(d[32]), "=f"(d[33]), "=f"(d[34]), "=f"(d[35]), "=f"(d[36]), "=f"(d[37]), "=f"(d[38]), "=f"(d[39]), "=f"(d[40]), "=f"(d[41]), "=f"(d[42]), "=f"(d[43]), "=f"(d[44]), "=f"(d[45]), "=f"(d[46]), "=f"(d[47]), "=f"(d[48]), "=f"(d[49]), "=f"(d[50]), "=f"(d[51]), "=f"(d[52]), "=f"(d[53]), "=f"(d[54]), "=f"(d[55]), "=f"(d[56]), "=f"(d[57]), "=f"(d[58]), "=f"(d[59]), "=f"(d[60]), "=f"(d[61]), "=f"(d[62]), "=f"(d[63])
        : "r"(da), "r"(db), "n"(TB), "r"(ha), "r"(hb));
}
template <int TB>
__device__ __forceinline__ void wgmma_ss64(float (&d)[32], uint32_t da, uint32_t db, int acc, uint32_t ha = 0x40000040u, uint32_t hb = 0x40000040u) {
    asm volatile("{\n.reg .pred p;\n.reg .b64 a, b;\nsetp.ne.b32 p, %34, 0;\nmov.b64 a, {%32, %36};\nmov.b64 b, {%33, %37};\n"
        "wgmma.mma_async.sync.aligned.m64n64k16.f32.bf16.bf16 {%0, %1, %2, %3, %4, %5, %6, %7, %8, %9, %10, %11, %12, %13, %14, %15, %16, %17, %18, %19, %20, %21, %22, %23, %24, %25, %26, %27, %28, %29, %30, %31}, a, b, p, 1, 1, 0, %35;\n}"
        : "+f"(d[0]), "+f"(d[1]), "+f"(d[2]), "+f"(d[3]), "+f"(d[4]), "+f"(d[5]), "+f"(d[6]), "+f"(d[7]), "+f"(d[8]), "+f"(d[9]), "+f"(d[10]), "+f"(d[11]), "+f"(d[12]), "+f"(d[13]), "+f"(d[14]), "+f"(d[15]), "+f"(d[16]), "+f"(d[17]), "+f"(d[18]), "+f"(d[19]), "+f"(d[20]), "+f"(d[21]), "+f"(d[22]), "+f"(d[23]), "+f"(d[24]), "+f"(d[25]), "+f"(d[26]), "+f"(d[27]), "+f"(d[28]), "+f"(d[29]), "+f"(d[30]), "+f"(d[31])
        : "r"(da), "r"(db), "r"(acc), "n"(TB), "r"(ha), "r"(hb));
}
template <int TB>
__device__ __forceinline__ void wgmma_ss64_init(float (&d)[32], uint32_t da, uint32_t db, uint32_t ha = 0x40000040u, uint32_t hb = 0x40000040u) {
    asm volatile("{\n.reg .pred p;\n.reg .b64 a, b;\nsetp.ne.b32 p, 0, 0;\nmov.b64 a, {%32, %35};\nmov.b64 b, {%33, %36};\n"
        "wgmma.mma_async.sync.aligned.m64n64k16.f32.bf16.bf16 {%0, %1, %2, %3, %4, %5, %6, %7, %8, %9, %10, %11, %12, %13, %14, %15, %16, %17, %18, %19, %20, %21, %22, %23, %24, %25, %26, %27, %28, %29, %30, %31}, a, b, p, 1, 1, 0, %34;\n}"
        : "=f"(d[0]), "=f"(d[1]), "=f"(d[2]), "=f"(d[3]), "=f"(d[4]), "=f"(d[5]), "=f"(d[6]), "=f"(d[7]), "=f"(d[8]), "=f"(d[9]), "=f"(d[10]), "=f"(d[11]), "=f"(d[12]), "=f"(d[13]), "=f"(d[14]), "=f"(d[15]), "=f"(d[16]), "=f"(d[17]), "=f"(d[18]), "=f"(d[19]), "=f"(d[20]), "=f"(d[21]), "=f"(d[22]), "=f"(d[23]), "=f"(d[24]), "=f"(d[25]), "=f"(d[26]), "=f"(d[27]), "=f"(d[28]), "=f"(d[29]), "=f"(d[30]), "=f"(d[31])
        : "r"(da), "r"(db), "n"(TB), "r"(ha), "r"(hb));
}
__device__ __forceinline__ void wgmma_rs128(float (&d)[64], uint32_t a0, uint32_t a1, uint32_t a2, uint32_t a3, uint32_t db, int acc, uint32_t hb = 0x40000040u) {
    asm volatile("{\n.reg .pred p;\n.reg .b64 b;\nsetp.ne.b32 p, %69, 0;\nmov.b64 b, {%68, %70};\n"
        "wgmma.mma_async.sync.aligned.m64n128k16.f32.bf16.bf16 {%0, %1, %2, %3, %4, %5, %6, %7, %8, %9, %10, %11, %12, %13, %14, %15, %16, %17, %18, %19, %20, %21, %22, %23, %24, %25, %26, %27, %28, %29, %30, %31, %32, %33, %34, %35, %36, %37, %38, %39, %40, %41, %42, %43, %44, %45, %46, %47, %48, %49, %50, %51, %52, %53, %54, %55, %56, %57, %58, %59, %60, %61, %62, %63}, {%64, %65, %66, %67}, b, p, 1, 1, 1;\n}"
        : "+f"(d[0]), "+f"(d[1]), "+f"(d[2]), "+f"(d[3]), "+f"(d[4]), "+f"(d[5]), "+f"(d[6]), "+f"(d[7]), "+f"(d[8]), "+f"(d[9]), "+f"(d[10]), "+f"(d[11]), "+f"(d[12]), "+f"(d[13]), "+f"(d[14]), "+f"(d[15]), "+f"(d[16]), "+f"(d[17]), "+f"(d[18]), "+f"(d[19]), "+f"(d[20]), "+f"(d[21]), "+f"(d[22]), "+f"(d[23]), "+f"(d[24]), "+f"(d[25]), "+f"(d[26]), "+f"(d[27]), "+f"(d[28]), "+f"(d[29]), "+f"(d[30]), "+f"(d[31]), "+f"(d[32]), "+f"(d[33]), "+f"(d[34]), "+f"(d[35]), "+f"(d[36]), "+f"(d[37]), "+f"(d[38]), "+f"(d[39]), "+f"(d[40]), "+f"(d[41]), "+f"(d[42]), "+f"(d[43]), "+f"(d[44]), "+f"(d[45]), "+f"(d[46]), "+f"(d[47]), "+f"(d[48]), "+f"(d[49]), "+f"(d[50]), "+f"(d[51]), "+f"(d[52]), "+f"(d[53]), "+f"(d[54]), "+f"(d[55]), "+f"(d[56]), "+f"(d[57]), "+f"(d[58]), "+f"(d[59]), "+f"(d[60]), "+f"(d[61]), "+f"(d[62]), "+f"(d[63])
        : "r"(a0), "r"(a1), "r"(a2), "r"(a3), "r"(db), "r"(acc), "r"(hb));
}

__device__ __forceinline__ uint32_t pack2(float lo, float hi) {
    uint32_t r;
    asm("cvt.rn.bf16x2.f32 %0, %1, %2;" : "=r"(r) : "f"(hi), "f"(lo));
    return r;
}
__device__ __forceinline__ float bf_lo(uint32_t v) { return __uint_as_float(v << 16); }
__device__ __forceinline__ float bf_hi(uint32_t v) { return __uint_as_float(v & 0xffff0000u); }
__device__ __forceinline__ float rbf(float v) { return bf_lo(pack2(v, v)); }
__device__ __forceinline__ uint32_t badd(uint32_t a, uint32_t b) {
    uint32_t r;
    asm("add.rn.bf16x2 %0, %1, %2;" : "=r"(r) : "r"(a), "r"(b));
    return r;
}
__device__ __forceinline__ uint32_t bsub(uint32_t a, uint32_t b) {
    uint32_t r;
    asm("sub.rn.bf16x2 %0, %1, %2;" : "=r"(r) : "r"(a), "r"(b));
    return r;
}
__device__ __forceinline__ uint32_t bmul(uint32_t a, uint32_t b) {
    uint32_t r;
    asm("mul.rn.bf16x2 %0, %1, %2;" : "=r"(r) : "r"(a), "r"(b));
    return r;
}
__device__ __forceinline__ uint32_t ln_apply(uint32_t x, uint32_t mb, float rs, uint32_t scale, uint32_t shift) {
    const uint32_t d = bsub(x, mb);
    return badd(bmul(pack2(bf_lo(d) * rs, bf_hi(d) * rs), scale), shift);
}
__device__ __forceinline__ float ex2(float v) {
    float r;
    asm("ex2.approx.ftz.f32 %0, %1;" : "=f"(r) : "f"(v));
    return r;
}
__device__ __forceinline__ float rcp(float v) {
    float r;
    asm("rcp.approx.ftz.f32 %0, %1;" : "=f"(r) : "f"(v));
    return r;
}
__device__ __forceinline__ float sqrt_fast(float v) {
    float r;
    asm("sqrt.approx.ftz.f32 %0, %1;" : "=f"(r) : "f"(v));
    return r;
}
__device__ __forceinline__ float ln_rstd(float var) { return rcp(rbf(sqrt_fast(rbf(rbf(var) + 1e-5f)))); }
__device__ __forceinline__ float sigmoid(float v) { return rcp(1.f + ex2(-1.4426950408889634f * v)); }
__device__ __forceinline__ float warp_sum(float v) {
#pragma unroll
    for (int o = 16; o > 0; o >>= 1) v += __shfl_xor_sync(0xffffffffu, v, o);
    return v;
}
__device__ __forceinline__ float quad_sum(float v) {
    v += __shfl_xor_sync(0xffffffffu, v, 1);
    return v + __shfl_xor_sync(0xffffffffu, v, 2);
}

constexpr uint32_t HI_128 = 0x40000040u, HI_IMG = 0x80000080u, HI_Q = 0x80000040u;
template <int M, int RH>
__device__ __forceinline__ uint4 img_pack(const float (&d)[64], float s) {
    uint4 v;
    v.x = pack2(d[16 * M + 2 * RH] * s, d[16 * M + 2 * RH + 1] * s);
    v.y = pack2(d[16 * M + 4 + 2 * RH] * s, d[16 * M + 5 + 2 * RH] * s);
    v.z = pack2(d[16 * M + 8 + 2 * RH] * s, d[16 * M + 9 + 2 * RH] * s);
    v.w = pack2(d[16 * M + 12 + 2 * RH] * s, d[16 * M + 13 + 2 * RH] * s);
    return v;
}
template <int M, int RH>
__device__ __forceinline__ uint4 img_pack(const float (&d)[64]) {
    uint4 v;
    v.x = pack2(d[16 * M + 2 * RH], d[16 * M + 2 * RH + 1]);
    v.y = pack2(d[16 * M + 4 + 2 * RH], d[16 * M + 5 + 2 * RH]);
    v.z = pack2(d[16 * M + 8 + 2 * RH], d[16 * M + 9 + 2 * RH]);
    v.w = pack2(d[16 * M + 12 + 2 * RH], d[16 * M + 13 + 2 * RH]);
    return v;
}
template <int M>
__device__ __forceinline__ void img_store_global(uint8_t* img, uint32_t toff, const float (&d)[64], float s0, float s1) {
    uint4* p = reinterpret_cast<uint4*>(img + toff) + M * 32;
    p[0] = img_pack<M, 0>(d, s0);
    p[128] = img_pack<M, 1>(d, s1);
}
__device__ __forceinline__ void sts128(uint32_t a, uint4 v) {
    asm volatile("st.shared.v4.b32 [%0], {%1, %2, %3, %4};" ::"r"(a), "r"(v.x), "r"(v.y), "r"(v.z), "r"(v.w) : "memory");
}
constexpr float SM_C = 0.08838834764831845f * 1.4426950408889634f;
__device__ __forceinline__ float pack2f(float lo, float hi) {
    float r;
    asm("{\n.reg .b32 t;\ncvt.rn.bf16x2.f32 t, %1, %2;\nmov.b32 %0, t;\n}" : "=f"(r) : "f"(hi), "f"(lo));
    return r;
}
template <int M, bool SCALE, bool PARK>
__device__ __forceinline__ void pack_group(float (&d)[64], float (&v)[8], float s0, float s1) {
#pragma unroll
    for (int i = 0; i < 8; i++) {
        const int k = 16 * M + 4 * (i & 3) + 2 * (i >> 2);
        v[i] = SCALE ? pack2f(d[k] * (i < 4 ? s0 : s1), d[k + 1] * (i < 4 ? s0 : s1)) : pack2f(d[k], d[k + 1]);
        if (PARK && M > 0) d[16 * (M > 0 ? M - 1 : 0) + i] = v[i];
    }
}
template <int M, bool PARK>
__device__ __forceinline__ void q_store_part(uint32_t a, float (&d)[64]) {
    float v[8];
    pack_group<M, false, PARK>(d, v, 0.f, 0.f);
#pragma unroll
    for (int h = 0; h < 2; h++)
        asm volatile("st.shared.v4.f32 [%0], {%1, %2, %3, %4};" ::"r"(a + (M >> 1) * 16384 + (M & 1) * 512 + h * 1024),
                     "f"(v[4 * h]), "f"(v[4 * h + 1]), "f"(v[4 * h + 2]), "f"(v[4 * h + 3]) : "memory");
}
template <bool PARK>
__device__ __forceinline__ void q_store(uint32_t a, uint32_t toff, float (&d)[64]) {
    a += (((toff >> 1) & ~2047u) ^ 8192) + (toff & 511);
    q_store_part<0, PARK>(a, d); q_store_part<1, PARK>(a, d); q_store_part<2, PARK>(a, d); q_store_part<3, PARK>(a, d);
}
template <int M, bool PARK>
__device__ __forceinline__ void ctx_store_part(float4* p, float (&d)[64], float i0, float i1) {
    float v[8];
    pack_group<M, true, PARK>(d, v, i0, i1);
    p[M * 32] = make_float4(v[0], v[1], v[2], v[3]);
    p[M * 32 + 128] = make_float4(v[4], v[5], v[6], v[7]);
}
template <bool PARK>
__device__ __forceinline__ void ctx_store(uint8_t* img, uint32_t toff, float (&o)[64], float l0, float l1) {
    const float i0 = rcp(quad_sum(l0)), i1 = rcp(quad_sum(l1));
    float4* p = reinterpret_cast<float4*>(img + toff);
    ctx_store_part<0, PARK>(p, o, i0, i1); ctx_store_part<1, PARK>(p, o, i0, i1); ctx_store_part<2, PARK>(p, o, i0, i1); ctx_store_part<3, PARK>(p, o, i0, i1);
}

__device__ __forceinline__ void slot_wait(uint32_t bars, uint32_t& ph, uint32_t slot) {
    mbar_wait(bars + 8 * slot, (ph >> slot) & 1);
    ph ^= 1u << slot;
}
__device__ __forceinline__ void release_if(uint32_t eb, uint32_t slot, bool on) {
    asm volatile("{\n.reg .pred p;\nsetp.ne.s32 p, %1, 0;\n@p mbarrier.arrive.shared::cluster.b64 _, [%0];\n}" ::"r"(eb + 8 * slot), "r"((int)on) : "memory");
}
__device__ __forceinline__ void load_image_mc(uint32_t sb, uint32_t& ph, uint32_t slot, const uint8_t* src, int rank, bool first) {
    slot_wait(sb + BAR_EMPTY, ph, slot);
    asm volatile("{\n.reg .pred p;\nelect.sync _|p, 0xffffffff;\n@p mbarrier.arrive.expect_tx.shared::cta.b64 _, [%2], 32768;\n"
                 "@p cp.async.bulk.shared::cluster.global.mbarrier::complete_tx::bytes.multicast::cluster.L2::cache_hint [%0], [%1], 16384, [%2], %4, %3;\n}"
                 ::"r"(sb + slot * SLOT + rank * 16384), "l"(src + rank * 16384), "r"(sb + BAR_FULL + 8 * slot), "l"(first ? L2_FIRST : L2_NORMAL),
                 "h"((uint16_t)3) : "memory");
}
__device__ __forceinline__ void load_tile_mc(uint32_t sb, uint32_t& ph, uint32_t slot, const CUtensorMap* m, int row, int cb, int rank, bool first) {
    slot_wait(sb + BAR_EMPTY, ph, slot);
    asm volatile("{\n.reg .pred p;\nelect.sync _|p, 0xffffffff;\n@p mbarrier.arrive.expect_tx.shared::cta.b64 _, [%2], 32768;\n"
                 "@p cp.async.bulk.tensor.3d.shared::cluster.global.mbarrier::complete_tx::bytes.multicast::cluster.L2::cache_hint [%0], [%1, {%3, %4, %5}], [%2], %7, %6;\n}"
                 ::"r"(sb + slot * SLOT + rank * 16384), "l"(m), "r"(sb + BAR_FULL + 8 * slot), "r"(0), "r"(row), "r"(cb + rank),
                 "l"(first ? L2_FIRST : L2_NORMAL), "h"((uint16_t)3) : "memory");
}
__device__ __forceinline__ void load_image(uint32_t sb, uint32_t& ph, uint32_t slot, const void* src, bool first) {
    slot_wait(sb + BAR_EMPTY, ph, slot);
    asm volatile("{\n.reg .pred p;\nelect.sync _|p, 0xffffffff;\n@p mbarrier.arrive.expect_tx.shared::cta.b64 _, [%2], 32768;\n"
                 "@p cp.async.bulk.shared::cluster.global.mbarrier::complete_tx::bytes.L2::cache_hint [%0], [%1], 32768, [%2], %3;\n}"
                 ::"r"(sb + slot * SLOT), "l"(src), "r"(sb + BAR_FULL + 8 * slot), "l"(first ? L2_FIRST : L2_NORMAL) : "memory");
}
__device__ __forceinline__ void load_tile(uint32_t sb, uint32_t& ph, uint32_t slot, const CUtensorMap* m, int row, int cb, bool first) {
    slot_wait(sb + BAR_EMPTY, ph, slot);
    asm volatile("{\n.reg .pred p;\nelect.sync _|p, 0xffffffff;\n@p mbarrier.arrive.expect_tx.shared::cta.b64 _, [%2], 32768;\n"
                 "@p cp.async.bulk.tensor.3d.shared::cluster.global.mbarrier::complete_tx::bytes.L2::cache_hint [%0], [%1, {%3, %4, %5}], [%2], %6;\n}"
                 ::"r"(sb + slot * SLOT), "l"(m), "r"(sb + BAR_FULL + 8 * slot), "r"(0), "r"(row), "r"(cb), "l"(first ? L2_FIRST : L2_NORMAL) : "memory");
}
__device__ __forceinline__ uint32_t ring_next(uint32_t r) { return r == 4 ? 0 : r + 1; }
__device__ __forceinline__ uint32_t w_table(int hp) { return hp ? 0x3104u : 0x4210u; }
__device__ __forceinline__ uint32_t a_table(int hp) { return hp ? 0x625u : 0x635u; }
__device__ __forceinline__ uint32_t a_next(uint32_t& t) {
    const uint32_t s = t & 15;
    t = (t >> 4) | (s << 8);
    return s;
}
constexpr uint32_t O_TABLE = 0x2160435u;
__device__ __forceinline__ uint32_t o_next(uint32_t& t) {
    const uint32_t s = t & 15;
    t = (t >> 4) | (s << 24);
    return s;
}
__device__ __forceinline__ int o_head(int i, int kh) { return i < 16 ? 4 * (i & 7) + 2 * (kh ^ 1) + (i >> 3) : 29 + 2 * kh; }

template <bool INIT>
__device__ __forceinline__ void gemm_issue(float (&d)[64], uint32_t a, uint32_t b, int acc, bool img) {
    const uint32_t ha = img ? HI_IMG : HI_128, o2 = img ? 32 : 4, o4 = img ? 64 : 1024;
    wg_fence();
#pragma unroll
    for (int k = 0; k < 8; k++) {
        if (INIT && k == 0) wgmma_ss128_init<1>(d, a, b, ha);
        else wgmma_ss128<1>(d, a + (k >> 2) * o4 + ((k >> 1) & 1) * o2 + (k & 1) * 2, b + k * 128, k ? 1 : acc, ha);
    }
    wg_commit();
}

__device__ __forceinline__ void h_store(const uint32_t* x, float mean, float sq, uint32_t sb, int row) {
    const int lane = threadIdx.x & 31;
    const float rs = ln_rstd(sq * (1.f / 512.f));
    const uint32_t mb = pack2(mean, mean);
    uint8_t* p = g_h + ((row >> 7) * 8 + (lane >> 3)) * 16384 + (row & 127) * 128 + (((lane ^ row) & 7) << 4);
#pragma unroll
    for (int i = 0; i < 2; i++) {
        const uint4 a = lds128(sb + SM_TAB + 1024 + i * 512 + lane * 16), c = lds128(sb + SM_TAB + i * 512 + lane * 16);
        *reinterpret_cast<uint4*>(p + i * 65536) = make_uint4(ln_apply(x[4 * i], mb, rs, a.x, c.x), ln_apply(x[4 * i + 1], mb, rs, a.y, c.y),
                                                              ln_apply(x[4 * i + 2], mb, rs, a.z, c.z), ln_apply(x[4 * i + 3], mb, rs, a.w, c.w));
    }
}

template <bool ODD>
__device__ __forceinline__ void proj_tile(float (&acc)[64], float (&prev)[64], int t, int q0, uint32_t sb, int wg, uint32_t eb, bool rel, uint32_t& fph,
                                          uint32_t wtab, uint32_t& atab, uint8_t* prev_img, uint32_t toff, float s0, float s1, bool first,
                                          const bf16* x, int xrow) {
    const uint32_t a0 = desc_k(sb + (wg ^ (ODD && t == 5)) * 8192), b0 = desc_mn(sb);
    const int lane = threadIdx.x & 31;
    float mean[2] = {0.f, 0.f}, rstd[2] = {0.f, 0.f};
    uint32_t xn[16];
#pragma unroll
    for (int i = 0; i < 4; i++) {
        uint4 v = make_uint4(0, 0, 0, 0);
        if (ODD && first) v = __ldg(reinterpret_cast<const uint4*>(x) + xrow * 64 + lane + 32 * i);
        xn[4 * i] = v.x; xn[4 * i + 1] = v.y; xn[4 * i + 2] = v.z; xn[4 * i + 3] = v.w;
    }
    constexpr int U = ODD ? UNR : 1;
#pragma unroll U
    for (int q = ODD ? 0 : q0; q < 4; q++) {
        if (ODD && t == 5 && q == 3) break;
        const uint32_t ws = (wtab >> (4 * q)) & 15, as = a_next(atab);
        if (!ODD && t != 2) slot_wait(sb + BAR_FULL, fph, ws);
        slot_wait(sb + BAR_FULL, fph, as);
        bar_sync(1 + wg, 256);
        gemm_issue<false>(acc, a0 + as * (SLOT / 16), b0 + ws * (SLOT / 16), q, false);
        bar_arrive(2 - wg, 256);
        wg_wait<1>();
        reg_fence(prev);
        if (ODD && t == 5) {
            if (q == 2) {
                q_store<false>(sb + 5 * SLOT, toff, prev);
                fence_async_smem();
            }
        } else if (ODD || !first) {
            if (q == 0) img_store_global<0>(prev_img, toff, prev, s0, s1);
            if (q == 1) img_store_global<1>(prev_img, toff, prev, s0, s1);
            if (q == 2) img_store_global<2>(prev_img, toff, prev, s0, s1);
            if (q == 3) img_store_global<3>(prev_img, toff, prev, s0, s1);
        }
        if (ODD && q == 1 && first) {
#pragma unroll
            for (int k = 0; k < 16; k++) mean[k >> 3] += bf_lo(xn[k]) + bf_hi(xn[k]);
#pragma unroll
            for (int i = 0; i < 2; i++) mean[i] = warp_sum(mean[i]) * (1.f / 512.f);
        }
        if (ODD && q == 2 && first) {
#pragma unroll
            for (int k = 0; k < 16; k++) {
                const float d0 = bf_lo(xn[k]) - mean[k >> 3], d1 = bf_hi(xn[k]) - mean[k >> 3];
                rstd[k >> 3] = fmaf(d0, d0, fmaf(d1, d1, rstd[k >> 3]));
            }
#pragma unroll
            for (int i = 0; i < 2; i++) rstd[i] = warp_sum(rstd[i]);
        }
        if (ODD && q == 3 && first) {
            mbar_wait(sb + BAR_FLAG + 8 * 8, 0);
            h_store(xn, mean[0], rstd[0], sb, xrow);
        }
        wg_wait<0>();
        release_if(eb, as, rel && !(ODD && (q & 1) && t == 5));
        if (ODD) release_if(eb, ws, rel && t != 1);
        if (ODD && q == 3 && first) {
            h_store(xn + 8, mean[1], rstd[1], sb, xrow + 1);
            __syncwarp();
            mbar_arrive_if(sb + BAR_DONE, lane == 0);
        }
    }
    reg_fence(acc);
}

__device__ __forceinline__ void qk_issue(float (&s)[64], uint32_t q, uint32_t k) {
    wg_fence();
    wgmma_ss128_init<0>(s, q, k, HI_Q, HI_IMG);
#pragma unroll
    for (int i = 1; i < 8; i++) wgmma_ss128<0>(s, q + (i >> 2) * 1024 + (i & 2) * 16 + (i & 1) * 2, k + (i >> 1) * 32 + (i & 1) * 2, 1, HI_Q, HI_IMG);
    wg_commit();
}
__device__ __forceinline__ void qk_issue(float (&s)[32], uint32_t q, uint32_t k) {
    wg_fence();
    wgmma_ss64_init<0>(s, q, k, HI_Q, HI_IMG);
#pragma unroll
    for (int i = 1; i < 8; i++) wgmma_ss64<0>(s, q + (i >> 2) * 1024 + (i & 2) * 16 + (i & 1) * 2, k + (i >> 1) * 32 + (i & 1) * 2, 1, HI_Q, HI_IMG);
    wg_commit();
}
__device__ __forceinline__ void pv_issue(float (&o)[64], const uint32_t (&p)[32], uint32_t v, int acc, bool half) {
    if (half) {
        asm volatile("// half" ::: "memory");
        wg_fence();
#pragma unroll
        for (int i = 0; i < 4; i++) wgmma_rs128(o, p[4 * i], p[4 * i + 1], p[4 * i + 2], p[4 * i + 3], v + i * 256, i ? 1 : acc, HI_IMG);
        wg_commit();
        asm volatile("// half" ::: "memory");
    } else {
        wg_fence();
#pragma unroll
        for (int i = 0; i < 8; i++) wgmma_rs128(o, p[4 * i], p[4 * i + 1], p[4 * i + 2], p[4 * i + 3], v + i * 256, i ? 1 : acc, HI_IMG);
        wg_commit();
    }
}
template <int B, int N>
__device__ __forceinline__ void tri_mask(float (&s)[N], int x) {
#pragma unroll
    for (int k = 0; k < 7; k++)
        asm("{\n.reg .pred p, q;\nsetp.lt.s32 p, %4, %5;\nsetp.le.s32 q, %4, %5;\n"
            "@p mov.b32 %0, 0fFF800000;\n@q mov.b32 %1, 0fFF800000;\n@p mov.b32 %2, 0fFF800000;\n@q mov.b32 %3, 0fFF800000;\n}"
            : "+f"(s[B + 4 * k]), "+f"(s[B + 4 * k + 1]), "+f"(s[B + 4 * k + 6]), "+f"(s[B + 4 * k + 7]) : "r"(x), "r"(8 * k));
    asm("{\n.reg .pred p, q;\nsetp.lt.s32 p, %2, 56;\nsetp.le.s32 q, %2, 56;\n@p mov.b32 %0, 0fFF800000;\n@q mov.b32 %1, 0fFF800000;\n}"
        : "+f"(s[B + 28]), "+f"(s[B + 29]) : "r"(x));
}
__device__ __forceinline__ void tri_mask_copy(float (&s)[64], const float (&h)[32], int x) {
#pragma unroll
    for (int i = 0; i < 32; i++) {
        asm("{\n.reg .pred p;\nsetp.lt.s32 p, %2, %3;\nselp.f32 %0, 0fFF800000, %1, p;\n}"
            : "=f"(s[i]) : "f"(h[i]), "r"(x), "r"(8 * (i >> 2) - 4 * (i & 2) + (i & 1)));
        s[32 + i] = __uint_as_float(0xff800000u);
    }
}
constexpr float SM_HI = 1152921504606846976.f, SM_LO = 1.f / 1152921504606846976.f;
__device__ __forceinline__ bool softmax_unsafe(float t0, float t1, bool first) {
    bool bad = __any_sync(0xffffffffu, fmaxf(t0, t1) > SM_HI);
    if (first) {
        uint32_t a = __ballot_sync(0xffffffffu, t0 >= SM_LO), b = __ballot_sync(0xffffffffu, t1 >= SM_LO);
        a |= a >> 1;
        b |= b >> 1;
        bad |= ((a | (a >> 2)) & (b | (b >> 2)) & 0x11111111u) != 0x11111111u;
    }
    return bad;
}
__device__ __forceinline__ void softmax_shift(float (&s)[64], float d0, float d1) {
#pragma unroll
    for (int i = 0; i < 64; i++) s[i] -= (i & 2) ? d1 : d0;
}
__device__ __forceinline__ void softmax_remax(float (&s)[64], float (&m)[2], bool first, float& a0, float& a1) {
    float m0 = fmaxf(s[0], s[1]), m1 = fmaxf(s[2], s[3]);
#pragma unroll
    for (int k = 1; k < 16; k++) {
        m0 = fmaxf(m0, fmaxf(s[4 * k], s[4 * k + 1]));
        m1 = fmaxf(m1, fmaxf(s[4 * k + 2], s[4 * k + 3]));
    }
    m0 = fmaxf(m0, __shfl_xor_sync(0xffffffffu, m0, 1));
    m1 = fmaxf(m1, __shfl_xor_sync(0xffffffffu, m1, 1));
    m0 = fmaxf(m0, __shfl_xor_sync(0xffffffffu, m0, 2));
    m1 = fmaxf(m1, __shfl_xor_sync(0xffffffffu, m1, 2));
    if (!first) {
        m0 = fmaxf(m0, 0.f);
        m1 = fmaxf(m1, 0.f);
    }
    a0 = first ? 1.f : ex2(-m0);
    a1 = first ? 1.f : ex2(-m1);
    m[0] += m0;
    m[1] += m1;
    softmax_shift(s, m0, m1);
}
template <int J0, int J1>
__device__ __forceinline__ void softmax_exp(const float (&s)[64], uint32_t (&p)[32], float (&t)[4]) {
#pragma unroll
    for (int k = J0; k < J1; k++) {
        const float e0 = ex2(s[4 * k]), e1 = ex2(s[4 * k + 1]), e2 = ex2(s[4 * k + 2]), e3 = ex2(s[4 * k + 3]);
        if (k == 0) { t[0] = e0; t[1] = e1; t[2] = e2; t[3] = e3; }
        else { t[0] += e0; t[1] += e1; t[2] += e2; t[3] += e3; }
        p[2 * k] = pack2(e0, e1);
        p[2 * k + 1] = pack2(e2, e3);
    }
}
__device__ __forceinline__ void fma8(float (&acc)[8], float a, uint4 w) {
    acc[0] = fmaf(a, bf_lo(w.x), acc[0]); acc[1] = fmaf(a, bf_hi(w.x), acc[1]);
    acc[2] = fmaf(a, bf_lo(w.y), acc[2]); acc[3] = fmaf(a, bf_hi(w.y), acc[3]);
    acc[4] = fmaf(a, bf_lo(w.z), acc[4]); acc[5] = fmaf(a, bf_hi(w.z), acc[5]);
    acc[6] = fmaf(a, bf_lo(w.w), acc[6]); acc[7] = fmaf(a, bf_hi(w.w), acc[7]);
}
__device__ __forceinline__ void mma16816(float (&d)[4], const uint32_t* a, uint32_t b0, uint32_t b1) {
    asm("mma.sync.aligned.m16n8k16.row.col.f32.bf16.bf16.f32 {%0, %1, %2, %3}, {%4, %5, %6, %7}, {%8, %9}, {%0, %1, %2, %3};"
        : "+f"(d[0]), "+f"(d[1]), "+f"(d[2]), "+f"(d[3]) : "r"(a[0]), "r"(a[1]), "r"(a[2]), "r"(a[3]), "r"(b0), "r"(b1));
}
__device__ __forceinline__ uint32_t best_key(const uint32_t* keys, int lane, uint32_t ep) {
    uint32_t best;
#pragma unroll 1
    for (;;) {
        const uint4 k = ld_poll(reinterpret_cast<const uint4*>(keys) + lane);
        best = max(max(k.x, k.y), max(k.z, k.w));
        if (__all_sync(0xffffffffu, (((k.x ^ ep) | (k.y ^ ep) | (k.z ^ ep) | (k.w ^ ep)) & 31) == 0)) break;
    }
    return __reduce_max_sync(0xffffffffu, best);
}

__global__ void __cluster_dims__(2, 1, 1) __launch_bounds__(384, 1)
fused_kernel(const __grid_constant__ CUtensorMap tm_ckv, const __grid_constant__ CUtensorMap tm_wq,
             const __grid_constant__ CUtensorMap tm_wuk, const __grid_constant__ CUtensorMap tm_wuv,
             const __grid_constant__ CUtensorMap tm_wo, const __grid_constant__ CUtensorMap tm_wg,
             const __grid_constant__ CUtensorMap tm_wu,
             const __grid_constant__ CUtensorMap tm_wm, const __grid_constant__ CUtensorMap tm_x, const Params P) {
    extern __shared__ __align__(1024) uint8_t smem[];
    const uint32_t sb = (uint32_t)__cvta_generic_to_shared(smem);
    const int tid = threadIdx.x, lane = tid & 31, warp = __shfl_sync(0xffffffffu, tid >> 5, 0), wg = warp >> 2;
    uint32_t sm;
    asm("mov.u32 %0, %%smid;" : "=r"(sm));
    if (MC) sm = blockIdx.x < 8 ? blockIdx.x + 124 : blockIdx.x - 8;
    const uint32_t smq = ((sm - 64) * 147) >> 11;
    const int rb = !P.by_smid ? blockIdx.x : sm < 64 ? (sm & 14) * 8 + (sm >> 4) * 2 + (sm & 1)
                 : sm < 120 ? ((sm - 64 - smq * 14) & 14) * 8 + 24 + smq * 2 + (sm & 1) : sm < 124 ? sm + 8 : sm - 116;
    const int grp = rb >> 3, j = rb & 7, cq = j & 3, kh = grp & 1, ort = (grp & 14) + (j >> 2);
    if (warp == 0) TS(0);

    if (rb >= NCTA) {
        float* sc = reinterpret_cast<float*>(smem + 6 * SLOT);
        float* red = sc + 512;
        if (tid == 256) {
            for (int i = 0; i < 6; i++) { mbar_init(sb + BAR_FULL + 8 * i, 1); mbar_init(sb + BAR_EMPTY + 8 * i, 8); }
            fence_async_smem();
        }
        __syncthreads();
        uint32_t ph = 0, sl = 0;
        if (tid == 256) {
#pragma unroll 1
            for (int i = 0; i < 24; i++) {
                mbar_wait(sb + BAR_EMPTY + 8 * sl, ph ^ 1);
                mbar_expect(sb + BAR_FULL + 8 * sl, SLOT);
                tma2d(sb + sl * SLOT, &tm_wm, (i >> 3) * 1024 + (rb - NCTA) * 256, (i & 7) * 64, sb + BAR_FULL + 8 * sl);
                if (++sl == 6) { sl = 0; ph ^= 1; }
            }
            mbar_wait(sb + BAR_EMPTY, 1);
            mbar_wait(sb + BAR_EMPTY + 8, 1);
#pragma unroll 1
            for (int i = 0; i <= NFFN / NSPARE; i++) {
                const int b = (rb - NCTA) * (NFFN / NSPARE) + i;
                if (i < NFFN / NSPARE) {
                    const uint32_t f = sb + BAR_FULL + 8 * (i & 1), d = sb + (i & 1) * SLOT;
                    asm volatile("cp.async.bulk.wait_group.read 0;" ::: "memory");
                    mbar_expect(f, SLOT);
                    tma2d(d, &tm_wg, b * 16, 0, f);
                    tma2d(d + 8192, &tm_wg, b * 16, 256, f);
                    tma2d(d + 16384, &tm_wu, b * 16, 0, f);
                    tma2d(d + 24576, &tm_wu, b * 16, 256, f);
                }
                if (i) {
                    mbar_wait(sb + BAR_FULL + 8 * (~i & 1), ((i - 1) >> 1) & 1);
                    asm volatile("cp.async.bulk.global.shared::cta.bulk_group [%0], [%1], 32768;\ncp.async.bulk.commit_group;"
                                 ::"l"(g_wf + (b - 1) * SLOT), "r"(sb + (~i & 1) * SLOT) : "memory");
                }
            }
            asm volatile("cp.async.bulk.wait_group 0;" ::: "memory");
            fence_async_global();
            flag_add(&g_sync.modcnt[32]);
            TS(4);
        } else if (tid < 256) {
            const uint32_t c2 = __ldg(reinterpret_cast<const uint32_t*>(P.c) + tid);
            sc[2 * tid] = rbf(bf_lo(c2) * sigmoid(bf_lo(c2)));
            sc[2 * tid + 1] = rbf(bf_hi(c2) * sigmoid(bf_hi(c2)));
            bar_sync(1, 256);
#pragma unroll 1
            for (int ps = 0; ps < 3; ps++) {
                float acc[8] = {0.f, 0.f, 0.f, 0.f, 0.f, 0.f, 0.f, 0.f};
#pragma unroll 1
                for (int bt = 0; bt < 8; bt++) {
                    mbar_wait(sb + BAR_FULL + 8 * sl, ph);
#pragma unroll
                    for (int i = 0; i < 8; i++)
                        fma8(acc, sc[bt * 64 + warp * 8 + i], *reinterpret_cast<const uint4*>(smem + sl * SLOT + (warp * 8 + i) * 512 + lane * 16));
                    __syncwarp();
                    mbar_arrive_if(sb + BAR_EMPTY + 8 * sl, lane == 0);
                    if (++sl == 6) { sl = 0; ph ^= 1; }
                }
                *reinterpret_cast<float4*>(red + warp * 256 + lane * 8) = make_float4(acc[0], acc[1], acc[2], acc[3]);
                *reinterpret_cast<float4*>(red + warp * 256 + lane * 8 + 4) = make_float4(acc[4], acc[5], acc[6], acc[7]);
                bar_sync(1, 256);
                float v = 0.f;
#pragma unroll
                for (int i = 0; i < 8; i++) v += red[i * 256 + tid];
                g_mod[ps * 1024 + (rb - NCTA) * 256 + tid] = __float2bfloat16_rn(v);
                bar_sync(1, 256);
                if (tid == 0 && ps != 1) flag_add(&g_sync.modcnt[(ps >> 1) * 32]);
                if (warp == 0) TS(1 + ps);
            }
        }
        return;
    }

    if (tid == 256) {
        if (sb & 1023) __trap();
        asm volatile("prefetch.tensormap [%0];" ::"l"((j & 1) ? &tm_wuv : &tm_wuk) : "memory");
        asm volatile("prefetch.tensormap [%0];" ::"l"(&tm_ckv) : "memory");
        for (int i = 0; i < 7; i++) { mbar_init(sb + BAR_FULL + 8 * i, 1); mbar_init(sb + BAR_EMPTY + 8 * i, MC ? 4 : 2); }
        for (int i = 0; i < 9; i++) mbar_init(sb + BAR_DONE + 8 * i, 8);
        for (int i = 0; i < 10; i++) mbar_init(sb + BAR_FLAG + 8 * i, 1);
        *reinterpret_cast<uint32_t*>(smem + SM_EP + 4) = 0;
        *reinterpret_cast<uint32_t*>(smem + SM_EP + 16) = 0;
        mbar_init(sb + BAR_END, 8);
        fence_async_smem();
        if (MC) asm volatile("fence.mbarrier_init.release.cluster;" ::: "memory");
    }
    __syncthreads();
    if (MC) asm volatile("barrier.cluster.arrive.relaxed.aligned;\nbarrier.cluster.wait.aligned;" ::: "memory");

    if (wg == 2) {
        asm volatile("setmaxnreg.dec.sync.aligned.u32 40;");
        if (warp == 8) {
            uint32_t eph = 0x7f, r = 0;
            const CUtensorMap* tw = (j & 1) ? &tm_wuv : &tm_wuk;
#pragma unroll 1
            for (int hp = 0; hp < 2; hp++) {
                const int hc = 4 * grp + 2 * hp;
                uint32_t wtab = w_table(hp), atab = a_table(hp);
#pragma unroll 1
                for (int u = 0; u < 4; u++) {
                    load_tile(sb, eph, (wtab >> (4 * u)) & 15, tw, u * 128, hc, HINT & 1); PT();
                    if (MC & 1) load_tile_mc(sb, eph, a_next(atab), &tm_ckv, (j >> 1) * 128, u * 2, j & 1, (HINT & 8) && hp);
                    else load_tile(sb, eph, a_next(atab), &tm_ckv, (j >> 1) * 128, u * 2, (HINT & 8) && hp);
                    PT();
                    if (hp == 1 && (u & 1) && lane == 0) asm volatile("red.relaxed.gpu.global.add.u32 [%0], 1;" ::"l"(&g_sync.rdcnt[(grp * 2 + (u >> 1)) * 8]) : "memory");
                }
#pragma unroll 1
                for (int u = 4; u < 16; u++) {
                    if (hp == 1 && (u & 7) == 4) mbar_wait(sb + BAR_FLAG + 24 + (u & 8), 0);
                    if (MC & 1) load_tile_mc(sb, eph, a_next(atab), &tm_ckv, ((u & 12) + (j >> 1)) * 128, (u & 3) * 2, j & 1, (HINT & 8) && hp);
                    else load_tile(sb, eph, a_next(atab), &tm_ckv, ((u & 12) + (j >> 1)) * 128, (u & 3) * 2, (HINT & 8) && hp);
                    PT();
                }
                mbar_wait(sb + BAR_FLAG, 0);
                fence_async_global();
#pragma unroll 1
                for (int u = 0; u < 4; u++) {
                    if (MC & 2) load_tile_mc(sb, eph, (wtab >> (4 * u)) & 15, &tm_wq, u * 128, hc, j & 1, HINT & 1);
                    else load_tile(sb, eph, (wtab >> (4 * u)) & 15, &tm_wq, u * 128, hc, HINT & 1);
                    PT();
                    load_image(sb, eph, a_next(atab), g_h + ((15 - j) * 4 + u) * SLOT, (HINT & 8) && hp); PT();
                }
                mbar_wait(sb + BAR_FLAG + 8 + 32 * hp, 0);
                fence_async_global();
#pragma unroll 1
                for (int u = 0; u < 4; u++) { load_image(sb, eph, a_next(atab), g_h + (j * 4 + u) * SLOT, (HINT & 8) && hp); PT(); }
                const uint8_t* kv = g_KV + (size_t)(grp * 32 + 30 * hp) * SLOT;
                const int step = hp ? -2 * SLOT : 2 * SLOT;
                if (MC & 4) load_image_mc(sb, eph, r, kv, j & 1, HINT & 4);
                else load_image(sb, eph, r, kv, HINT & 4);
                PT();
                r = ring_next(r);
#pragma unroll 1
                for (int n = 1; n <= 16; n++) {
                    if (n == 8) {
                        mbar_wait(sb + BAR_FLAG + 16 + 32 * hp, 0);
                        fence_async_global();
                    }
                    asm volatile("st.volatile.shared.u32 [%0], %1;" ::"r"(sb + SM_EP + 16), "r"(16 * hp + n) : "memory");
                    const uint8_t* v = kv + SLOT;
                    kv += n < 16 - j ? step : n == 16 - j ? (2 * j - 15) * step : -step;
                    if ((MC & 4) && n != 15 - (j & 6)) load_image_mc(sb, eph, r, kv, j & 1, HINT & 4);
                    else load_image(sb, eph, r, kv, HINT & 4);
                    PT();
                    r = ring_next(r);
                    if ((MC & 4) && n != 16 - (j & 6)) load_image_mc(sb, eph, r, v, j & 1, HINT & 4);
                    else load_image(sb, eph, r, v, HINT & 4);
                    PT();
                    r = ring_next(r);
                }
                if (MC & 4) load_image_mc(sb, eph, r, kv + SLOT, j & 1, HINT & 4);
                else load_image(sb, eph, r, kv + SLOT, HINT & 4);
                PT();
                r = ring_next(r);
            }
            uint32_t otab = O_TABLE, ready = 0;
#pragma unroll 1
            for (int i = 0; i < 17; i++) {
                asm volatile("st.volatile.shared.u32 [%0], %1;" ::"r"(sb + SM_EP + 16), "r"(33 + i) : "memory");
                const bool dyn = i >= 8 && i < 15;
                const uint32_t want = dyn ? 15u << (4 * (i - 8)) : 1u << max(i + 14, 28);
                if (!(ready & want)) {
                    do {
                        asm volatile("ld.acquire.cta.shared.u32 %0, [%1];" : "=r"(ready) : "r"(sb + SM_EP + 4) : "memory");
                        ready = __shfl_sync(0xffffffffu, ready, 0);
                    } while (!(ready & want));
                    fence_async_global();
                }
                const int head = o_head(dyn ? (ready >> (4 * (i - 8))) & 15 : i, kh);
                const uint8_t* src = g_ctx + (size_t)(ort * 32 + head) * SLOT;
                if (i < 15) {
                    if (MC & 8) load_image_mc(sb, eph, o_next(otab), src, j & 1, HINT & 16);
                    else load_image(sb, eph, o_next(otab), src, HINT & 16);
                } else {
                    const uint32_t as = o_next(otab), d = sb + as * SLOT;
                    slot_wait(sb + BAR_EMPTY, eph, as);
                    asm volatile("{\n.reg .pred p, q;\nelect.sync _|p, 0xffffffff;\n@p mbarrier.arrive.expect_tx.shared::cta.b64 _, [%2], %3;\n"
                                 "@p cp.async.bulk.shared::cluster.global.mbarrier::complete_tx::bytes [%0], [%1], 16384, [%2];\n}"
                                 ::"r"(d + kh * 16384), "l"(src + kh * 16384), "r"(sb + BAR_FULL + 8 * as), "r"(i == 15 ? 32768 : 16384) : "memory");
                    if (i == 15)
                        asm volatile("{\n.reg .pred p;\nelect.sync _|p, 0xffffffff;\n"
                                     "@p cp.async.bulk.tensor.3d.shared::cluster.global.mbarrier::complete_tx::bytes [%0], [%1, {%3, %4, %5}], [%2];\n}"
                                     ::"r"(d + (kh ^ 1) * 16384), "l"(&tm_x), "r"(sb + BAR_FULL + 8 * as), "r"(0), "r"(ort * 128 + kh * 64), "r"(cq * 2) : "memory");
                }
                PT();
                load_tile(sb, eph, o_next(otab), &tm_wo, head * 128, cq * 2, HINT & 2); PT();
            }
            if (rb < NFFN) {
                load_image(sb, eph, o_next(otab), g_wf + rb * SLOT, false);
                const uint32_t s2 = o_next(otab);
                slot_wait(sb + BAR_EMPTY, eph, s2);
                asm volatile("{\n.reg .pred p;\nelect.sync _|p, 0xffffffff;\n@p mbarrier.arrive.expect_tx.shared::cta.b64 _, [%2], 16384;\n"
                             "@p cp.async.bulk.shared::cluster.global.mbarrier::complete_tx::bytes [%0], [%1], 16384, [%2];\n}"
                             ::"r"(sb + s2 * SLOT), "l"(P.wdown + rb * 8192), "r"(sb + BAR_FULL + 8 * s2) : "memory");
            }
        } else {
            const int hw = warp - 9;
            if (hw == 1 && lane == 0) {
                l2_prefetch(P.ckv + rb * 2048, 4096);
                mbar_watch(sb + BAR_FULL + 8 * PF0, 0);
                l2_prefetch(P.ckv + 512 * 512 + rb * 2048, 4096);
                mbar_watch(sb + BAR_FULL + 8 * 4, 0);
                l2_prefetch(P.x + rb * 8192, 16384);
                l2_prefetch(P.ckv + 1024 * 512 + rb * 4096, 8192);
                TS(40);
                if (MC & 2) tma3d_prefetch(&tm_wq, (j >> 1) * 128, grp * 4 + (j & 1));
                else if (j < 4) tma3d_prefetch(&tm_wq, j * 128, grp * 4);
                step_watch(sb + SM_EP + 16, PFA);
                tma3d_prefetch((j & 1) ? &tm_wuv : &tm_wuk, (j >> 1) * 128, grp * 4 + 2);
                step_watch(sb + SM_EP + 16, PFA + 2);
                l2_prefetch(P.ckv + rb * 8192, 16384);
                step_watch(sb + SM_EP + 16, PFA + 3);
                l2_prefetch(g_h + rb * 16384, 16384);
                step_watch(sb + SM_EP + 16, PFA + 4);
                if (MC & 2) tma3d_prefetch(&tm_wq, (j >> 1) * 128, grp * 4 + 2 + (j & 1));
                else if (j < 4) tma3d_prefetch(&tm_wq, j * 128, grp * 4 + 2);
#pragma unroll 1
                for (int i = 0; i < 10; i++) {
                    step_watch(sb + SM_EP + 16, i < 6 ? 16 + PFB + i : 16 + PFC + i - 6);
                    if (i == 7) mbar_watch(sb + BAR_FLAG + 8 * 7, 0);
                    const uint8_t* p = i < 4 ? g_ctx + (size_t)(ort * 32 + o_head(cq + 2 * (i & 2), kh)) * SLOT + (i & 1) * 16384
                                     : i < 6 ? reinterpret_cast<const uint8_t*>(P.wo) + ((rb >> 3) * 16 + (i & 1) * 8 + (rb & 7)) * 16384
                                     : i == 6 ? reinterpret_cast<const uint8_t*>(P.x) + rb * 16384
                                     : i == 7 ? reinterpret_cast<const uint8_t*>(P.wdown) + rb * 16384 : g_wf + rb * SLOT + (i & 1) * 16384;
                    if ((i < 7 || rb < NFFN) && ((PFMASK >> i) & 1)) l2_prefetch(p, 16384);
                }
                step_watch(sb + SM_EP + 16, 16 + PFC + 4);
                if (OBINIT) {
                    const uint32_t v = lds32(sb + SM_EP) - 1;
#pragma unroll 1
                    for (int i = 0; i < 32; i++) sts128(sb + SM_RED + i * 16, make_uint4(v, v, v, v));
                    fence_async_smem();
#pragma unroll 1
                    for (int i = 0; i < OB / 32; i++)
                        asm volatile("cp.async.bulk.global.shared::cta.bulk_group [%0], [%1], 512;" ::"l"(g_out + rb * OB + i * 32), "r"(sb + SM_RED) : "memory");
                    asm volatile("cp.async.bulk.commit_group;\ncp.async.bulk.wait_group 0;" ::: "memory");
                    fence_async_global();
                }
                mbar_arrive(sb + BAR_PF);
                mbar_watch(sb + BAR_END, 0);
            }
            if (hw == 0) {
#pragma unroll 1
                for (int i = 0; i < 9; i++) {
                    const int hp = i > 4, k = (i - 1) & 3;
                    if (lane == 0) {
                        mbar_wait(sb + BAR_DONE + 8 * i, 0);
                        flag_add(i == 0 ? &g_sync.hcnt[grp * 8] : k < 2 ? &g_sync.kvcnt[((2 * grp + hp) * 2 + k) * 8]
                                                                        : &g_sync.ctxcnt[(k == 2 ? 15 - j : j) * 32 + 2 * grp + hp]);
                    }
                    if (i == 0) TS(43);
                }
            }
            if (hw == 2) {
                const uint32_t ep = __ldcg(&g_sync.epoch[0]) + 1;
                if (lane == 0) {
                    asm volatile("st.shared.u32 [%0], %1;" ::"r"(sb + SM_EP), "r"(ep) : "memory");
                    flag_wait(&g_sync.modcnt[0], NSPARE * ep);
                }
                __syncwarp();
#pragma unroll
                for (int i = 0; i < 4; i++) {
                    uint4 v = __ldcg(reinterpret_cast<const uint4*>(g_mod) + lane + 32 * i);
                    if (i >= 2) v = make_uint4(badd(v.x, ONE2), badd(v.y, ONE2), badd(v.z, ONE2), badd(v.w, ONE2));
                    sts128(sb + SM_TAB + i * 512 + lane * 16, v);
                }
                __syncwarp();
                if (lane == 0) mbar_arrive(sb + BAR_FLAG + 8 * 8);
                TS(42);
#pragma unroll 1
                for (int i = 0; i < 8; i++) {
                    if (lane == 0) mbar_wait(sb + BAR_DONE + 8 * (i == 7 ? 6 : i == 4 ? 3 : i), 0);
                    __syncwarp();
                    const uint32_t* f = i == 0 ? &g_sync.hcnt[(lane ? j : 15 - j) * 8]
                                      : i == 3 || i == 4 ? &g_sync.rdcnt[(grp * 2 + i - 3) * 8]
                                      : i == 7 ? &g_sync.modcnt[32] : &g_sync.kvcnt[(4 * grp + (i > 4 ? i - 3 : i - 1)) * 8];
                    if (lane < (i ? 1 : 2)) flag_wait(f, 8 * ep);
                    __syncwarp();
                    if (i == 7) {
                        const uint32_t *mp = reinterpret_cast<const uint32_t*>(g_mod) + lane, *wp = reinterpret_cast<const uint32_t*>(P.wr) + lane;
                        float ra = 0.f, rs = 0.f;
#pragma unroll 1
                        for (int k = 0; k < 256; k += 32) {
                            const uint32_t ga = __ldcg(mp + 512 + k), sh = __ldcg(mp + 768 + k), c1 = badd(__ldcg(mp + 1024 + k), ONE2);
                            const uint32_t gb = __ldcg(mp + 1280 + k), ww = __ldg(wp + k);
                            const float a0 = bf_lo(c1) * bf_lo(ww), a1 = bf_hi(c1) * bf_hi(ww);
                            ra += a0 + a1;
                            rs = fmaf(bf_lo(sh), bf_lo(ww), fmaf(bf_hi(sh), bf_hi(ww), rs));
                            if (k >> 6 == cq) {
                                sts128(sb + SM_TAB + ((k & 32) + lane) * 16, make_uint4(ga << 16, ga & 0xffff0000u, __float_as_uint(a0), __float_as_uint(a1)));
                                sts128(sb + SM_TAB + 1024 + ((k & 32) + lane) * 16, make_uint4(c1, sh, gb, 0));
                            }
                        }
                        *reinterpret_cast<float2*>(smem + SM_EP + 8) = make_float2(warp_sum(ra), warp_sum(rs));
                        __syncwarp();
                    }
                    if (lane == 0) mbar_arrive(sb + BAR_FLAG + 8 * i);
                    TS(48 + i);
                }
                const uint32_t* f = &g_sync.ctxcnt[ort * 32 + o_head(min(lane, 16), kh)];
                uint32_t ready = (MC & 8) && (j & 1) ? ~0u : 0u, list = 0, sh = 0, qa = sb + SM_EP + 4;
                if (MC & 8) asm("mapa.shared::cluster.u32 %0, %1, %2;" : "=r"(qa) : "r"(sb + SM_EP + 4), "r"(lane & 1));
                while (ready != ~0u) {
                    uint32_t v;
                    asm volatile("ld.acquire.gpu.global.u32 %0, [%1];" : "=r"(v) : "l"(f) : "memory");
                    const uint32_t now = __ballot_sync(0xffffffffu, (int)(v - ep) >= 0);
                    for (uint32_t fresh = now & ~ready & 0x7f00; fresh; fresh &= fresh - 1, sh += 4) list |= (__ffs(fresh) - 1) << sh;
                    list |= (((now & 0xff) + 1) >> 8 << 28) | ((now & 0x18000) << 14);
                    if (now != ready && lane < ((MC & 8) ? 2 : 1)) asm volatile("st.relaxed.cluster.shared::cluster.u32 [%0], %1;" ::"r"(qa), "r"(list) : "memory");
                    if ((now & 0xff) == 0xff) mbar_wait(sb + BAR_DONE + 8 * 7, 0);
                    ready = now;
                    __nanosleep(POLL_NS);
                }
                TS(45);
            }
        }
    } else {
        asm volatile("setmaxnreg.inc.sync.aligned.u32 232;");
        const bool elected = (tid & 127) == 0, rel = MC ? (tid & 95) == 0 : elected;
        uint32_t eb = sb + BAR_EMPTY;
        if (MC) asm("mapa.shared::cluster.u32 %0, %1, %2;" : "=r"(eb) : "r"(sb + BAR_EMPTY), "r"(warp & 1));
        const int g = lane >> 2, c4 = lane & 3;
        const uint32_t toff = warp * 4096 + g * 64 + ((c4 ^ (g >> 1)) << 4);
        uint32_t fph = 0, r = 0;
        if (wg == 1) bar_arrive(1, 256);
        const uint32_t kd = desc_k(sb), wd = desc_mn(sb), vd = ((sb & 0x3ffff) >> 4) | (32u << 16);
        const int nL = 16 - j, hn = nL - 1 + wg;
        float s[64], o[64], li[2] = {0.f, 0.f};
        uint8_t* cimg = g_ctx;
#pragma unroll 1
        for (int hp = 0; hp < 2; hp++) {
            {
                const int step = hp ? -8 * SLOT : 8 * SLOT;
                uint8_t* img = g_KV + (size_t)(grp * 32 + (hp ? j ^ 30 : j)) * SLOT - step;
                const float sc = (j & 1) ? 1.f : SM_C;
                const uint32_t wtab = w_table(hp);
                uint32_t atab = hp ? 0x256u : a_table(0);
#pragma unroll 1
                for (int t = 0; t < 6; t += 2) {
                    proj_tile<false>(s, o, t, t ? 0 : 2 * hp, sb, wg, eb, rel, fph, wtab, atab, t ? img : cimg, toff, t ? sc : li[0], t ? sc : li[1], (hp | t) == 0, P.x, rb * 16 + warp * 2);
                    __syncwarp();
                    mbar_arrive_if(sb + BAR_DONE + 4 * t + 32 * hp, lane == 0 && (hp | t) != 0);
                    if (elected) TS(1 + 10 * hp + t + 20 * wg);
                    proj_tile<true>(o, s, t + 1, 0, sb, wg, eb, rel, fph, wtab, atab, img + step, toff, sc, sc, (hp | t) == 0, P.x, rb * 16 + warp * 2);
                    if (elected) TS(2 + 10 * hp + t + 20 * wg);
                    img += 2 * step;
                }
            }
            float m[2] = {0.f, 0.f}, l[2] = {0.f, 0.f}, t[4] = {0.f, 0.f, 0.f, 0.f};
            bool shifted = false, bad = false, plain = false;
            uint32_t p[32];
#pragma unroll
            for (int i = 0; i < 32; i++) p[i] = 0;
            uint32_t qa = desc_k(sb + 5 * SLOT + (wg ^ 1) * 8192);
            uint8_t* img = g_ctx + (size_t)((15 - j) * 32 + 2 * grp + hp) * SLOT;
            slot_wait(sb + BAR_FULL, fph, r);
            int n = -1;
#pragma unroll 1
            for (;;) {
                while (bad || plain) {
                    if (bad) {
                        float a0, a1;
                        softmax_remax(s, m, n == 0 || n == nL, a0, a1);
                        shifted = true;
                        l[0] *= a0;
                        l[1] *= a1;
#pragma unroll
                        for (int i = 0; i < 64; i++) o[i] *= (i & 2) ? a1 : a0;
                    }
                    softmax_exp<0, 16>(s, p, t);
                    t[0] += t[1];
                    t[2] += t[3];
                    bad = !bad && softmax_unsafe(t[0], t[2], false);
                    plain = false;
                }
#pragma unroll 1
                do {
                    l[0] += t[0];
                    l[1] += t[2];
                    if (++n > 16) break;
                    const uint32_t ks = r;
                    uint32_t vs = ring_next(r);
                    r = ring_next(vs);
                    bar_sync(1 + wg, 256);
                    if (n == 0 || (uint32_t)(n + 1 - nL) <= (uint32_t)(1 + wg)) {
                        const int x = (warp & 3) * 16 + g - 2 * c4;
                        if (n == 0) {
                            r = vs;
                            vs = 4 - hp;
                            qk_issue(s, qa, kd + ks * (SLOT / 16));
                            slot_wait(sb + BAR_FULL, fph, 6);
                            gemm_issue<false>(o, qa + SLOT / 16, wd + vs * (SLOT / 16), 1, false);
                            bar_arrive(2 - wg, 256);
                            wg_wait<1>();
                            reg_fence(s);
                        } else if (n == hn) {
                            float sh[32];
                            qk_issue(sh, qa, kd + ks * (SLOT / 16));
                            slot_wait(sb + BAR_FULL, fph, vs);
                            pv_issue(o, p, vd + vs * (SLOT / 16), 1, false);
                            bar_arrive(2 - wg, 256);
                            wg_wait<1>();
                            reg_fence(sh);
                            tri_mask_copy(s, sh, x);
                        } else {
                            qk_issue(s, qa, kd + ks * (SLOT / 16));
                            slot_wait(sb + BAR_FULL, fph, vs);
                            pv_issue(o, p, vd + vs * (SLOT / 16), n != nL + 1, n == hn + 1);
                            bar_arrive(2 - wg, 256);
                            wg_wait<1>();
                            reg_fence(s);
                            if (n <= nL) tri_mask<32>(s, x);
                        }
                        release_if(eb, ks, rel);
                        release_if(eb, (n == 16 ? 6 : 5), rel && (n == 16 || n == nL - 1));
                        if (n == nL - 1) {
                            qa += SLOT / 16;
                            fence_async_smem();
                        }
                        if (shifted) {
                            if (n == nL) {
                                m[0] = m[1] = 0.f;
                                shifted = false;
                            }
                            softmax_shift(s, m[0], m[1]);
                        }
                        float e[4 * EARLY];
#pragma unroll
                        for (int i = 0; i < 4 * EARLY; i++) {
                            e[i] = ex2(s[i]);
                            t[i & 3] = i < 4 ? e[i] : t[i & 3] + e[i];
                        }
                        reg_fence(e);
                        slot_wait(sb + BAR_FULL, fph, r);
                        wg_wait<0>();
                        reg_fence(o);
                        reg_fence(e);
                        release_if(eb, vs, rel);
#pragma unroll
                        for (int i = 0; i < 2 * EARLY; i++) p[i] = pack2(e[2 * i], e[2 * i + 1]);
                        softmax_exp<EARLY, 8>(s, p, t);
                        if (n == 0) q_store<(PARKS & 1) != 0>(sb + 6 * SLOT, toff, o);
                        if (n == nL) {
                            ctx_store<(PARKS & 2) != 0>(img, toff, o, l[0], l[1]);
                            __syncwarp();
                            mbar_arrive_if(sb + BAR_DONE + 24 + 32 * hp, lane == 0);
                            l[0] = l[1] = 0.f;
                        }
                        if (n != hn) softmax_exp<8, 16>(s, p, t);
                        t[0] += t[1];
                        t[2] += t[3];
                        bad = softmax_unsafe(t[0], t[2], n == 0 || n == nL);
                        continue;
                    }
                    qk_issue(s, qa, kd + ks * (SLOT / 16));
                    slot_wait(sb + BAR_FULL, fph, vs);
                    pv_issue(o, p, vd + vs * (SLOT / 16), n != 1 && n != nL + 1, false);
                    bar_arrive(2 - wg, 256);
                    wg_wait<1>();
                    reg_fence(s);
                    release_if(eb, ks, rel);
                    release_if(eb, 6, rel && n == 16);
                    if (shifted) {
                        slot_wait(sb + BAR_FULL, fph, r);
                        wg_wait<0>();
                        reg_fence(o);
                        release_if(eb, vs, rel);
                        softmax_shift(s, m[0], m[1]);
                        plain = true;
                        break;
                    }
                    float e[4 * EARLY];
#pragma unroll
                    for (int i = 0; i < 4 * EARLY; i++) {
                        e[i] = ex2(s[i]);
                        t[i & 3] = i < 4 ? e[i] : t[i & 3] + e[i];
                    }
                    reg_fence(e);
                    slot_wait(sb + BAR_FULL, fph, r);
                    wg_wait<0>();
                    reg_fence(o);
                    reg_fence(e);
                    release_if(eb, vs, rel);
#pragma unroll
                    for (int i = 0; i < 2 * EARLY; i++) p[i] = pack2(e[2 * i], e[2 * i + 1]);
                    softmax_exp<EARLY, 16>(s, p, t);
                    t[0] += t[1];
                    t[2] += t[3];
                    bad = softmax_unsafe(t[0], t[2], false);
                } while (!bad);
                if (!bad && !plain) break;
            }
            const uint32_t vs = r, ga = desc_k(sb + (hp ? 2 * (wg ^ kh ^ 1) : wg) * 8192), as = 2 + 2 * hp;
            r = ring_next(r);
            slot_wait(sb + BAR_FULL, fph, 5);
            slot_wait(sb + BAR_FULL, fph, r);
            bar_sync(1 + wg, 256);
            gemm_issue<true>(s, ga + 5 * (SLOT / 16), wd + r * (SLOT / 16), 0, hp);
            pv_issue(o, p, vd + vs * (SLOT / 16), j, hn == 16);
            bar_arrive(2 - wg, 256);
            li[0] = rcp(quad_sum(l[0]));
            li[1] = rcp(quad_sum(l[1]));
            cimg = img + (ptrdiff_t)(2 * j - 15) * 32 * SLOT + (wg ? -16384 : 16384);
            wg_wait<1>();
            release_if(eb, 5, rel);
            release_if(eb, r, rel && hp);
            wg_wait<0>();
            release_if(eb, vs, rel);
            reg_fence(o);
            img_store_global<0>(cimg, toff, o, li[0], li[1]);
            slot_wait(sb + BAR_FULL, fph, as);
            slot_wait(sb + BAR_FULL, fph, 0);
            bar_sync(1 + wg, 256);
            gemm_issue<false>(s, ga + as * (SLOT / 16), wd, 1, hp);
            bar_arrive(2 - wg, 256);
            reg_fence(o);
            img_store_global<1>(cimg, toff, o, li[0], li[1]);
            wg_wait<0>();
            release_if(eb, as, rel);
            release_if(eb, 0, rel && hp);
            if (elected) TS(8 + 10 * hp + 20 * wg);
        }
        uint32_t otab = 0x0435216u;
        const uint32_t oa = desc_k(sb + (wg ^ kh ^ 1) * 16384);
        const int t7 = tid & 127, w4 = warp & 3, row = ort * 128 + kh * 64 + w4 * 16 + g;
#pragma unroll 1
        for (int i = 2; i < 15 - wg; i++) {
            const uint32_t as = o_next(otab), ws = o_next(otab);
            slot_wait(sb + BAR_FULL, fph, as);
            slot_wait(sb + BAR_FULL, fph, ws);
            bar_sync(1 + wg, 256);
            gemm_issue<false>(s, oa + as * (SLOT / 16), wd + ws * (SLOT / 16), 1, true);
            bar_arrive(2 - wg, 256);
            wg_wait<1>();
            reg_fence(o);
            if (i == 2) img_store_global<2>(cimg, toff, o, li[0], li[1]);
            if (i == CLAST) {
                img_store_global<3>(cimg, toff, o, li[0], li[1]);
                __syncwarp();
                mbar_arrive_if(sb + BAR_DONE + 64, lane == 0);
            }
            wg_wait<0>();
            release_if(eb, as, rel);
            release_if(eb, ws, rel);
        }
        mbar_wait(sb + BAR_PF, 0);
        const uint32_t ep = lds32(sb + SM_EP);
        if (wg == 0) {
            reg_fence(s);
            if (elected) TS(9);
#pragma unroll
            for (int v = 0; v < 8; v++)
                st_pub(g_out + rb * OB + v * 128 + t7, make_uint4((pack2(s[8 * v], s[8 * v + 1]) & ~1u) | (ep & 1), pack2(s[8 * v + 2], s[8 * v + 3]),
                                                                      pack2(s[8 * v + 4], s[8 * v + 5]), pack2(s[8 * v + 6], s[8 * v + 7])), true);
            o_next(otab); o_next(otab); o_next(otab); o_next(otab);
            const uint32_t s1 = o_next(otab), s2 = o_next(otab);
            bar_sync(4, 256);
            uint32_t wf[64];
            float wn[64];
            if (rb < NFFN) {
                slot_wait(sb + BAR_FULL, fph, s1);
                const uint32_t a = sb + s1 * SLOT + (w4 * 128 + (lane >> 4) * 8 + (lane & 7)) * 32 + ((lane >> 3) & 1) * 16;
#pragma unroll
                for (int i = 0; i < 16; i++)
                    asm volatile("ldmatrix.sync.aligned.m8n8.x4.trans.shared.b16 {%0, %1, %2, %3}, [%4];"
                                 : "=r"(wf[4 * i]), "=r"(wf[4 * i + 1]), "=r"(wf[4 * i + 2]), "=r"(wf[4 * i + 3])
                                 : "r"(a + (i >> 3) * 16384 + (i & 7) * 512) : "memory");
                slot_wait(sb + BAR_FULL, fph, s2);
#pragma unroll
                for (int i = 0; i < 16; i++) {
                    const uint2 w = *reinterpret_cast<const uint2*>(smem + s2 * SLOT + i * 1024 + t7 * 8);
                    wn[4 * i] = bf_lo(w.x); wn[4 * i + 1] = bf_hi(w.x); wn[4 * i + 2] = bf_lo(w.y); wn[4 * i + 3] = bf_hi(w.y);
                }
                reg_fence(wn);
            }
            const uint32_t gbf = __ldcg(reinterpret_cast<const uint32_t*>(g_mod) + 1280 + rb * 2 + (tid & 1));
            if (elected) TS(10);
            const uint32_t best = best_key(g_key + cq * 128, lane, ep);
            const int sel = (~best >> 5) & 2047;
            if (elected) TS(19);
            const uint4* cp = g_cand + (sel >> 4) * 192;
            float* sred = reinterpret_cast<float*>(smem + SM_RED);
            const int pq = (2 * rb + (tid & 1)) & 63, pv = (pq >> 2) / 3;
            const uint4* fp = cp + (rb >> 5) * 24 + pv * 4 + (pq & 3);
            uint4 fh = ld_poll(fp), fx = ld_poll(fp + 96);
            if (rb < NFFN) {
                uint4 cv[6];
                for (;;) {
                    uint32_t bad = 0;
#pragma unroll
                    for (int v = 0; v < 6; v++) cv[v] = ld_poll(cp + w4 * 24 + v * 4 + c4);
#pragma unroll
                    for (int v = 0; v < 6; v++) bad |= cv[v].w ^ ep;
                    if (__all_sync(0xffffffffu, bad == 0)) break;
                }
                if (elected) TS(20);
                float d[4][4] = {};
#pragma unroll
                for (int k = 0; k < 8; k++) {
                    const uint32_t b0 = (&cv[(2 * k) / 3].x)[(2 * k) % 3], b1 = (&cv[(2 * k + 1) / 3].x)[(2 * k + 1) % 3];
                    mma16816(d[k & 1], wf + 4 * k, b0, b1);
                    mma16816(d[2 + (k & 1)], wf + 32 + 4 * k, b0, b1);
                }
                const float u = (c4 & 2) ? ((c4 & 1) ? d[2][2] + d[3][2] : d[2][0] + d[3][0]) : ((c4 & 1) ? d[0][2] + d[1][2] : d[0][0] + d[1][0]);
                sred[w4 * 32 + c4 * 8 + g] = u;
                bar_sync(3, 128);
                const float v = rbf((sred[lane] + sred[32 + lane]) + (sred[64 + lane] + sred[96 + lane]));
                const float act = rbf(rbf(v * sigmoid(v)) * __shfl_down_sync(0xffffffffu, v, 16));
                float y[4] = {0.f, 0.f, 0.f, 0.f};
#pragma unroll
                for (int k = 0; k < 16; k++) {
                    const float a = __shfl_sync(0xffffffffu, act, k);
#pragma unroll
                    for (int i = 0; i < 4; i++) y[i] = fmaf(a, wn[4 * k + i], y[i]);
                }
                st_pub(g_out + rb * OB + OB_Y + t7, make_uint4((__float_as_uint(y[0]) & ~15u) | (ep & 15), __float_as_uint(y[1]), __float_as_uint(y[2]), __float_as_uint(y[3])), true);
            }
            if (rb == 0 && tid == 0) g_sync.epoch[0] = ep;
            if (elected) TS(60);
            uint4 yv;
            do yv = ld_poll(g_out + min(t7, NFFN - 1) * OB + OB_Y + rb);
            while (!__all_sync(0xffffffffu, ((yv.x ^ ep) & 15) == 0));
            if (elected) TS(61);
            float y[4] = {0.f, 0.f, 0.f, 0.f};
            if (t7 < NFFN) { y[0] = __uint_as_float(yv.x); y[1] = __uint_as_float(yv.y); y[2] = __uint_as_float(yv.z); y[3] = __uint_as_float(yv.w); }
            const float z0 = ((lane & 16) ? y[2] : y[0]) + __shfl_xor_sync(0xffffffffu, (lane & 16) ? y[0] : y[2], 16);
            const float z1 = ((lane & 16) ? y[3] : y[1]) + __shfl_xor_sync(0xffffffffu, (lane & 16) ? y[1] : y[3], 16);
            float z = ((lane & 8) ? z1 : z0) + __shfl_xor_sync(0xffffffffu, (lane & 8) ? z0 : z1, 8);
            z += __shfl_xor_sync(0xffffffffu, z, 4);
            z = quad_sum(z);
            if ((lane & 7) == 0) sred[128 + (lane >> 3) * 4 + w4] = z;
            bar_sync(3, 128);
            if (tid < 2) {
                while (fh.w != ep || fx.w != ep) { fh = ld_poll(fp); fx = ld_poll(fp + 96); }
                const float4 y0 = *reinterpret_cast<const float4*>(sred + 128 + tid * 8), y1 = *reinterpret_cast<const float4*>(sred + 132 + tid * 8);
                const int cm = (pq >> 2) - 3 * pv;
                const uint32_t h2 = cm == 0 ? fh.x : cm == 1 ? fh.y : fh.z, x2 = cm == 0 ? fx.x : cm == 1 ? fx.y : fx.z;
                const float sg = sigmoid(bf_hi((best & 0x80000000u) ? (best ^ 0x80000000u) : ~best));
                reinterpret_cast<uint32_t*>(P.out)[sel * 256 + rb * 2 + tid] =
                    badd(x2, bmul(gbf, badd(h2, bmul(pack2((y0.x + y0.y) + (y0.z + y0.w), (y1.x + y1.y) + (y1.z + y1.w)), pack2(sg, sg)))));
            }
            if (elected) TS(62);
        } else {
            const float4* tf = reinterpret_cast<const float4*>(smem + SM_TAB) + c4;
            const uint32_t as14 = otab & 15, xa = sb + ((otab >> 8) & 15) * SLOT + (kh ^ 1) * 16384 + (w4 * 16 + (lane & 15)) * 128;
            uint32_t x2[32];
            bar_sync(2, 256);
#pragma unroll 1
            for (int i = 14; i < 17; i++) {
                const uint32_t as = o_next(otab), ws = o_next(otab);
                slot_wait(sb + BAR_FULL, fph, as);
                slot_wait(sb + BAR_FULL, fph, ws);
                gemm_issue<false>(s, oa + as * (SLOT / 16), wd + ws * (SLOT / 16), 1, true);
                wg_wait<1>();
                release_if(eb, as14, rel && i == 15);
            }
            if (elected) TS(29);
            {
#pragma unroll
                for (int k = 0; k < 8; k++)
                    asm volatile("ldmatrix.sync.aligned.m8n8.x4.shared.b16 {%0, %1, %2, %3}, [%4];"
                                 : "=r"(x2[4 * k]), "=r"(x2[4 * k + 1]), "=r"(x2[4 * k + 2]), "=r"(x2[4 * k + 3])
                                 : "r"(xa + (k >> 2) * 8192 + (((2 * (k & 3) + (lane >> 4)) ^ (lane & 7)) << 4)) : "memory");
            }
            wg_wait<0>();
            reg_fence(s);
            bar_arrive(4, 256);
            if (elected) TS(39);
            const uint4* pr = g_out + (rb ^ 8) * OB + t7;
            uint4 pa[8];
#pragma unroll
            for (int v = 0; v < 8; v++) pa[v] = ld_poll(pr + v * 128);
            float4 tc[16];
#pragma unroll
            for (int k = 0; k < 16; k++) {
                tc[k] = tf[k * 4];
#pragma unroll
                for (int i = 4 * k; i < 4 * k + 4; i++) s[i] = fmaf((i & 1) ? tc[k].y : tc[k].x, s[i], (i & 1) ? bf_hi(x2[i >> 1]) : bf_lo(x2[i >> 1]));
            }
            reg_fence(s);
            for (;;) {
                uint32_t bad = 0;
#pragma unroll
                for (int v = 0; v < 8; v++) bad |= pa[v].x ^ ep;
                if (__all_sync(0xffffffffu, (bad & 1) == 0)) break;
#pragma unroll
                for (int v = 0; v < 8; v++) pa[v] = ld_poll(pr + v * 128);
            }
            if (elected) TS(30);
            float st[6] = {0.f, 0.f, 0.f, 0.f, 0.f, 0.f};
#pragma unroll
            for (int i = 0; i < 64; i++) {
                const int rh = (i >> 1) & 1;
                const uint32_t w = (&pa[i >> 3].x)[(i >> 1) & 3];
                const float v = fmaf((i & 1) ? tc[i >> 2].y : tc[i >> 2].x, (i & 1) ? bf_hi(w) : bf_lo(w), s[i]);
                s[i] = v;
                st[rh] += v;
                st[2 + rh] = fmaf(v, v, st[2 + rh]);
                st[4 + rh] = fmaf(v, (i & 1) ? tc[i >> 2].w : tc[i >> 2].z, st[4 + rh]);
            }
#pragma unroll
            for (int i = 0; i < 6; i++) st[i] = quad_sum(st[i]);
            st_pub(g_out + rb * OB + OB_STAT + (w4 * 8 + g) * 2 + (c4 & 1),
                   make_uint4(__float_as_uint((c4 & 1) ? st[1] : st[0]), __float_as_uint((c4 & 1) ? st[3] : st[2]),
                              __float_as_uint((c4 & 1) ? st[5] : st[4]), ep), c4 < 2);
            if (elected) TS(56);
            uint32_t cb[16], sh[16], gb[16];
#pragma unroll
            for (int i = 0; i < 16; i++) {
                const float4 c = tf[64 + i * 4];
                cb[i] = __float_as_uint(c.x); sh[i] = __float_as_uint(c.y); gb[i] = __float_as_uint(c.z);
            }
            const float ra = __uint_as_float(lds32(sb + SM_EP + 8)), rb0 = __uint_as_float(lds32(sb + SM_EP + 12));
#pragma unroll
            for (int i = 0; i < 32; i++) x2[i] = pack2(s[2 * i], s[2 * i + 1]);
            reg_fence(x2);
            uint4 r0, r1;
            for (;;) {
                r0 = ld_poll(g_out + ((rb & ~3) + c4) * OB + OB_STAT + (w4 * 8 + g) * 2);
                r1 = ld_poll(g_out + ((rb & ~3) + c4) * OB + OB_STAT + (w4 * 8 + g) * 2 + 1);
                if (__all_sync(0xffffffffu, r0.w == ep && r1.w == ep)) break;
            }
            if (elected) TS(57);
            const float m0 = quad_sum(__uint_as_float(r0.x)) * (1.f / 512.f), m1 = quad_sum(__uint_as_float(r1.x)) * (1.f / 512.f);
            const float rs0 = ln_rstd(fmaxf(fmaf(-m0, m0, quad_sum(__uint_as_float(r0.y)) * (1.f / 512.f)), 0.f));
            const float rs1 = ln_rstd(fmaxf(fmaf(-m1, m1, quad_sum(__uint_as_float(r1.y)) * (1.f / 512.f)), 0.f));
            const uint32_t mb0 = pack2(m0, m0), mb1 = pack2(m1, m1);
            const uint32_t lg = pack2(fmaf(rs0, fmaf(-bf_lo(mb0), ra, quad_sum(__uint_as_float(r0.z))), rb0),
                                      fmaf(rs1, fmaf(-bf_lo(mb1), ra, quad_sum(__uint_as_float(r1.z))), rb0));
            const uint32_t u0 = lg << 16, u1 = lg & 0xffff0000u;
            const uint32_t k0 = ((u0 ^ (((int)u0 >> 31) | 0x80000000u)) & 0xffff0000u) | ((2047 - row) << 5) | (ep & 31);
            const uint32_t k1 = ((u1 ^ (((int)u1 >> 31) | 0x80000000u)) & 0xffff0000u) | ((2039 - row) << 5) | (ep & 31);
            const uint32_t kb = __reduce_max_sync(0xffffffffu, max(k0, k1));
            st_pub(g_key + cq * 128 + (row >> 4), kb, lane == 0);
            {
                uint32_t cx[18], ch[18];
#pragma unroll
                for (int i = 0; i < 16; i++) {
                    cx[i] = kb == k1 ? x2[2 * i + 1] : x2[2 * i];
                    ch[i] = ln_apply(cx[i], kb == k1 ? mb1 : mb0, kb == k1 ? rs1 : rs0, cb[i], sh[i]);
                }
                cx[16] = cx[17] = ch[16] = ch[17] = 0;
                uint4* cp = g_cand + (row >> 4) * 192 + cq * 24 + c4;
#pragma unroll
                for (int v = 0; v < 6; v++) st_pub(cp + v * 4, make_uint4(ch[3 * v], ch[3 * v + 1], ch[3 * v + 2], ep), kb == k0 || kb == k1);
#pragma unroll
                for (int v = 0; v < 6; v++) st_pub(cp + 96 + v * 4, make_uint4(cx[3 * v], cx[3 * v + 1], cx[3 * v + 2], ep), kb == k0 || kb == k1);
            }
            if (elected) TS(58);
            uint2 ov[16];
#pragma unroll
            for (int i = 0; i < 16; i++) {
                const int rh = i & 1, jj = i & 14;
                const uint32_t v0 = badd(x2[2 * jj + rh], bmul(gb[jj], ln_apply(x2[2 * jj + rh], rh ? mb1 : mb0, rh ? rs1 : rs0, cb[jj], sh[jj])));
                const uint32_t v1 = badd(x2[2 * jj + 2 + rh], bmul(gb[jj + 1], ln_apply(x2[2 * jj + 2 + rh], rh ? mb1 : mb0, rh ? rs1 : rs0, cb[jj + 1], sh[jj + 1])));
                const uint32_t rv = __shfl_xor_sync(0xffffffffu, (c4 & 1) ? v0 : v1, 1);
                ov[i] = (c4 & 1) ? make_uint2(rv, v1) : make_uint2(v0, rv);
            }
            uint2* op = reinterpret_cast<uint2*>(P.out) + row * 128 + cq * 32 + (c4 & 1) * 2 + (c4 >> 1);
#pragma unroll
            for (int i = 0; i < 16; i++)
                if (kb != ((i & 1) ? k1 : k0)) op[(i & 1) * 1024 + (i & 14) * 2] = ov[i];
            const uint32_t best = best_key(g_key + cq * 128, lane, ep);
            if (best != kb) {
#pragma unroll
                for (int i = 0; i < 16; i++)
                    if (kb == ((i & 1) ? k1 : k0)) op[(i & 1) * 1024 + (i & 14) * 2] = ov[i];
            }
            if (elected) TS(59);
        }
        mbar_arrive_if(sb + BAR_END, lane == 0);
    }
}

typedef CUresult (*EncodeFn)(CUtensorMap*, CUtensorMapDataType, cuuint32_t, void*, const cuuint64_t*, const cuuint64_t*,
                             const cuuint32_t*, const cuuint32_t*, CUtensorMapInterleave, CUtensorMapSwizzle,
                             CUtensorMapL2promotion, CUtensorMapFloatOOBfill);

void make_2d(EncodeFn fn, CUtensorMap* m, const void* p, uint64_t cols, uint64_t rows, uint32_t bc, uint32_t br) {
    cuuint64_t dims[2] = {cols, rows}, strides[1] = {cols * 2};
    cuuint32_t box[2] = {bc, br}, es[2] = {1, 1};
    fn(m, CU_TENSOR_MAP_DATA_TYPE_BFLOAT16, 2, const_cast<void*>(p), dims, strides, box, es, CU_TENSOR_MAP_INTERLEAVE_NONE,
       CU_TENSOR_MAP_SWIZZLE_NONE, CU_TENSOR_MAP_L2_PROMOTION_L2_128B, CU_TENSOR_MAP_FLOAT_OOB_FILL_NONE);
}
void make_3d(EncodeFn fn, CUtensorMap* m, const void* p, uint64_t cols, uint64_t rows, uint32_t br = 128, uint32_t nb = 2) {
    cuuint64_t dims[3] = {64, rows, cols / 64}, strides[2] = {cols * 2, 128};
    cuuint32_t box[3] = {64, br, nb}, es[3] = {1, 1, 1};
    fn(m, CU_TENSOR_MAP_DATA_TYPE_BFLOAT16, 3, const_cast<void*>(p), dims, strides, box, es, CU_TENSOR_MAP_INTERLEAVE_NONE,
       CU_TENSOR_MAP_SWIZZLE_128B, CU_TENSOR_MAP_L2_PROMOTION_L2_256B, CU_TENSOR_MAP_FLOAT_OOB_FILL_NONE);
}

}

extern "C" void kernel_launch(void* const* d_in, const int* in_sizes, int n_in, void* d_out, int out_size) {
    static EncodeFn fn = nullptr;
    static int sms = 0;
    if (!fn) {
        void* f = nullptr;
        cudaDriverEntryPointQueryResult st;
        cudaGetDriverEntryPoint("cuTensorMapEncodeTiled", &f, cudaEnableDefault, &st);
        fn = (EncodeFn)f;
        int dev = 0;
        cudaGetDevice(&dev);
        cudaDeviceGetAttribute(&sms, cudaDevAttrMultiProcessorCount, dev);
        cudaFuncSetAttribute(fused_kernel, cudaFuncAttributeMaxDynamicSharedMemorySize, SMEM_BYTES);
    }
    CUtensorMap ckv, wq, wuk, wuv, wo, wg, wu, wm, xm;
    make_3d(fn, &ckv, d_in[1], 512, 2048, 128, (MC & 1) ? 1 : 2);
    make_3d(fn, &xm, d_in[0], 512, 2048, 64);
    make_3d(fn, &wq, d_in[2], 4096, 512, 128, (MC & 2) ? 1 : 2);
    make_3d(fn, &wuk, d_in[3], 4096, 512);
    make_3d(fn, &wuv, d_in[4], 4096, 512);
    make_3d(fn, &wo, d_in[5], 512, 4096);
    make_2d(fn, &wg, d_in[8], 1792, 512, 16, 256);
    make_2d(fn, &wu, d_in[9], 1792, 512, 16, 256);
    make_2d(fn, &wm, d_in[12], 3072, 512, 256, 64);
    Params p;
    p.x = (const bf16*)d_in[0];
    p.ckv = (const bf16*)d_in[1];
    p.wo = (const bf16*)d_in[5];
    p.wr = (const bf16*)d_in[7];
    p.wdown = (const bf16*)d_in[10];
    p.c = (const bf16*)d_in[11];
    p.out = (bf16*)d_out;
    p.by_smid = sms == NCTA + NSPARE;
    fused_kernel<<<NCTA + NSPARE, 384, SMEM_BYTES>>>(ckv, wq, wuk, wuv, wo, wg, wu, wm, xm, p);
}
```

```cpp
#include <cuda.h>
#include <cuda_bf16.h>
#include <cuda_runtime.h>
#include <stdint.h>
#include <stdio.h>

namespace {

typedef __nv_bfloat16 bf16;
typedef unsigned long long u64;

constexpr int NCTA = 128, NSPARE = 4;
constexpr int SLOT = 32768;
constexpr int SM_BAR = 7 * SLOT;
constexpr int BAR_FULL = SM_BAR;
constexpr int BAR_EMPTY = BAR_FULL + 8 * 7;
constexpr int BAR_DONE = BAR_EMPTY + 8 * 7;
constexpr int BAR_FLAG = BAR_DONE + 8 * 9;
constexpr int BAR_PF = BAR_FLAG + 8 * 9;
constexpr int BAR_END = BAR_PF + 8;
constexpr int SM_EP = BAR_END + 8;
constexpr int SM_RED = SM_BAR + 384;
constexpr int SM_TAB = SM_BAR + 1024;
constexpr int SMEM_BYTES = SM_BAR + 3072;
constexpr int NFFN = 112;
#define HINT 31
constexpr u64 L2_NORMAL = 0x1000000000000000ull, L2_FIRST = 0x12F0000000000000ull;
#define PF0 0
#define PFA 9
#define PFB 6
#define PFC 12
#define PFMASK 1023
#define UNR 4
#define PARKS 7
#define POLL_NS 50
#define CLAST 2
#define OBINIT 1
#define MC 15
#define EARLY 7
constexpr uint32_t SPIN_LIMIT = 1u << 22;
constexpr uint32_t ONE2 = 0x3f803f80u;

struct Sync {
    uint32_t modcnt[2 * 32];
    uint32_t hcnt[16 * 8];
    uint32_t kvcnt[32 * 2 * 8];
    uint32_t ctxcnt[16 * 32];
    uint32_t rdcnt[16 * 2 * 8];
    uint32_t epoch[32];
};

__device__ __align__(1024) uint8_t g_KV[16 * 16 * 2 * SLOT];
__device__ __align__(1024) uint8_t g_ctx[16 * 32 * SLOT];
__device__ __align__(1024) uint8_t g_h[16 * 4 * SLOT];
constexpr int OB = 1216, OB_STAT = 1024, OB_Y = 1088;
__device__ __align__(1024) uint4 g_out[128 * OB];
__device__ __align__(1024) bf16 g_mod[3072];
__device__ __align__(1024) uint4 g_cand[128 * 192];
__device__ __align__(1024) uint32_t g_key[4 * 128];
__device__ __align__(1024) uint8_t g_wf[NFFN * SLOT];
__device__ __align__(1024) Sync g_sync;
#define TS(i)

#define PT()

struct Params {
    const bf16 *x, *ckv, *wo, *wr, *wdown, *c;
    bf16* out;
    int by_smid;
};

__device__ __forceinline__ void mbar_init(uint32_t bar, uint32_t cnt) {
    asm volatile("mbarrier.init.shared::cta.b64 [%0], %1;" ::"r"(bar), "r"(cnt) : "memory");
}
__device__ __forceinline__ void mbar_wait(uint32_t bar, uint32_t parity) {
    asm volatile("{\n.reg .pred p;\nL_%=:\nmbarrier.try_wait.parity.shared::cta.b64 p, [%0], %1;\n@!p bra L_%=;\n}" ::"r"(bar), "r"(parity) : "memory");
}
__device__ __forceinline__ void mbar_watch(uint32_t bar, uint32_t parity) {
    asm volatile("{\n.reg .pred p;\n.reg .u32 n;\nmov.u32 n, 0;\n"
                 "L_%=:\nmbarrier.try_wait.parity.shared::cta.b64 p, [%0], %1;\n@p bra D_%=;\n"
                 "add.u32 n, n, 1;\nsetp.lt.u32 p, n, %2;\n@p bra L_%=;\ntrap;\nD_%=:\n}"
                 ::"r"(bar), "r"(parity), "n"(SPIN_LIMIT) : "memory");
}
__device__ __forceinline__ void step_watch(uint32_t a, uint32_t step) {
    asm volatile("{\n.reg .pred p;\n.reg .u32 n, v;\nmov.u32 n, 0;\n"
                 "L_%=:\nld.volatile.shared.u32 v, [%0];\nsetp.ge.u32 p, v, %1;\n@p bra D_%=;\nnanosleep.u32 200;\n"
                 "add.u32 n, n, 1;\nsetp.lt.u32 p, n, %2;\n@p bra L_%=;\ntrap;\nD_%=:\n}"
                 ::"r"(a), "r"(step), "n"(SPIN_LIMIT) : "memory");
}
__device__ __forceinline__ void mbar_arrive(uint32_t bar) {
    asm volatile("mbarrier.arrive.shared::cta.b64 _, [%0];" ::"r"(bar) : "memory");
}
__device__ __forceinline__ void mbar_arrive_if(uint32_t bar, bool on) {
    asm volatile("{\n.reg .pred p;\nsetp.ne.s32 p, %1, 0;\n@p mbarrier.arrive.shared::cta.b64 _, [%0];\n}" ::"r"(bar), "r"((int)on) : "memory");
}
__device__ __forceinline__ void mbar_expect(uint32_t bar, uint32_t bytes) {
    asm volatile("mbarrier.arrive.expect_tx.shared::cta.b64 _, [%0], %1;" ::"r"(bar), "r"(bytes) : "memory");
}
__device__ __forceinline__ void tma2d(uint32_t dst, const CUtensorMap* m, int c0, int c1, uint32_t bar) {
    asm volatile("cp.async.bulk.tensor.2d.shared::cluster.global.mbarrier::complete_tx::bytes [%0], [%1, {%3, %4}], [%2];"
                 ::"r"(dst), "l"(m), "r"(bar), "r"(c0), "r"(c1) : "memory");
}
__device__ __forceinline__ void tma3d_prefetch(const CUtensorMap* m, int row, int cb) {
    asm volatile("cp.async.bulk.prefetch.tensor.3d.L2.global [%0, {%1, %2, %3}];" ::"l"(m), "r"(0), "r"(row), "r"(cb) : "memory");
}
__device__ __forceinline__ void l2_prefetch(const void* p, uint32_t bytes) {
    asm volatile("cp.async.bulk.prefetch.L2.global [%0], %1;" ::"l"(p), "r"(bytes) : "memory");
}
__device__ __forceinline__ void flag_wait(const uint32_t* f, uint32_t target) {
    asm volatile("{\n.reg .pred p;\n.reg .u32 v;\n"
                 "L_%=:\nld.acquire.gpu.global.u32 v, [%0];\nsub.u32 v, v, %1;\nsetp.lt.s32 p, v, 0;\n@p nanosleep.u32 100;\n@p bra L_%=;\n}"
                 ::"l"(f), "r"(target) : "memory");
}
__device__ __forceinline__ uint4 ld_poll(const uint4* p) {
    uint4 v;
    asm volatile("ld.relaxed.gpu.global.v4.u32 {%0, %1, %2, %3}, [%4];" : "=r"(v.x), "=r"(v.y), "=r"(v.z), "=r"(v.w) : "l"(p) : "memory");
    return v;
}
__device__ __forceinline__ void st_pub(uint4* p, uint4 v, bool on) {
    asm volatile("{\n.reg .pred p;\nsetp.ne.s32 p, %5, 0;\n@p st.relaxed.gpu.global.v4.u32 [%0], {%1, %2, %3, %4};\n}"
                 ::"l"(p), "r"(v.x), "r"(v.y), "r"(v.z), "r"(v.w), "r"((int)on) : "memory");
}
__device__ __forceinline__ void st_pub(uint32_t* p, uint32_t v, bool on) {
    asm volatile("{\n.reg .pred p;\nsetp.ne.s32 p, %2, 0;\n@p st.relaxed.gpu.global.u32 [%0], %1;\n}" ::"l"(p), "r"(v), "r"((int)on) : "memory");
}
__device__ __forceinline__ void flag_add(uint32_t* p) {
    asm volatile("red.release.gpu.global.add.u32 [%0], 1;" ::"l"(p) : "memory");
}
__device__ __forceinline__ uint32_t lds32(uint32_t a) {
    uint32_t v;
    asm volatile("ld.shared.u32 %0, [%1];" : "=r"(v) : "r"(a) : "memory");
    return v;
}
__device__ __forceinline__ uint4 lds128(uint32_t a) {
    uint4 v;
    asm volatile("ld.shared.v4.u32 {%0, %1, %2, %3}, [%4];" : "=r"(v.x), "=r"(v.y), "=r"(v.z), "=r"(v.w) : "r"(a) : "memory");
    return v;
}
__device__ __forceinline__ void fence_async_global() { asm volatile("fence.proxy.async.global;" ::: "memory"); }
__device__ __forceinline__ void fence_async_smem() { asm volatile("fence.proxy.async.shared::cta;" ::: "memory"); }
__device__ __forceinline__ void bar_sync(int id, int n) { asm volatile("bar.sync %0, %1;" ::"r"(id), "r"(n) : "memory"); }
__device__ __forceinline__ void bar_arrive(int id, int n) { asm volatile("bar.arrive %0, %1;" ::"r"(id), "r"(n) : "memory"); }
__device__ __forceinline__ void wg_fence() { asm volatile("wgmma.fence.sync.aligned;" ::: "memory"); }
__device__ __forceinline__ void wg_commit() { asm volatile("wgmma.commit_group.sync.aligned;" ::: "memory"); }
template <int N> __device__ __forceinline__ void wg_wait() { asm volatile("wgmma.wait_group.sync.aligned %0;" ::"n"(N) : "memory"); }
template <int N> __device__ __forceinline__ void reg_fence(float (&d)[N]) {
#pragma unroll
    for (int i = 0; i < N; i++) asm volatile("" : "+f"(d[i])::"memory");
}
template <int N> __device__ __forceinline__ void reg_fence(uint32_t (&d)[N]) {
#pragma unroll
    for (int i = 0; i < N; i++) asm volatile("" : "+r"(d[i])::"memory");
}
__device__ __forceinline__ uint32_t desc_k(uint32_t a) { return ((a & 0x3ffff) >> 4) | (1u << 16); }
__device__ __forceinline__ uint32_t desc_mn(uint32_t a) { return ((a & 0x3ffff) >> 4) | (1024u << 16); }

template <int TB>
__device__ __forceinline__ void wgmma_ss128(float (&d)[64], uint32_t da, uint32_t db, int acc, uint32_t ha = 0x40000040u, uint32_t hb = 0x40000040u) {
    asm volatile("{\n.reg .pred p;\n.reg .b64 a, b;\nsetp.ne.b32 p, %66, 0;\nmov.b64 a, {%64, %68};\nmov.b64 b, {%65, %69};\n"
        "wgmma.mma_async.sync.aligned.m64n128k16.f32.bf16.bf16 {%0, %1, %2, %3, %4, %5, %6, %7, %8, %9, %10, %11, %12, %13, %14, %15, %16, %17, %18, %19, %20, %21, %22, %23, %24, %25, %26, %27, %28, %29, %30, %31, %32, %33, %34, %35, %36, %37, %38, %39, %40, %41, %42, %43, %44, %45, %46, %47, %48, %49, %50, %51, %52, %53, %54, %55, %56, %57, %58, %59, %60, %61, %62, %63}, a, b, p, 1, 1, 0, %67;\n}"
        : "+f"(d[0]), "+f"(d[1]), "+f"(d[2]), "+f"(d[3]), "+f"(d[4]), "+f"(d[5]), "+f"(d[6]), "+f"(d[7]), "+f"(d[8]), "+f"(d[9]), "+f"(d[10]), "+f"(d[11]), "+f"(d[12]), "+f"(d[13]), "+f"(d[14]), "+f"(d[15]), "+f"(d[16]), "+f"(d[17]), "+f"(d[18]), "+f"(d[19]), "+f"(d[20]), "+f"(d[21]), "+f"(d[22]), "+f"(d[23]), "+f"(d[24]), "+f"(d[25]), "+f"(d[26]), "+f"(d[27]), "+f"(d[28]), "+f"(d[29]), "+f"(d[30]), "+f"(d[31]), "+f"(d[32]), "+f"(d[33]), "+f"(d[34]), "+f"(d[35]), "+f"(d[36]), "+f"(d[37]), "+f"(d[38]), "+f"(d[39]), "+f"(d[40]), "+f"(d[41]), "+f"(d[42]), "+f"(d[43]), "+f"(d[44]), "+f"(d[45]), "+f"(d[46]), "+f"(d[47]), "+f"(d[48]), "+f"(d[49]), "+f"(d[50]), "+f"(d[51]), "+f"(d[52]), "+f"(d[53]), "+f"(d[54]), "+f"(d[55]), "+f"(d[56]), "+f"(d[57]), "+f"(d[58]), "+f"(d[59]), "+f"(d[60]), "+f"(d[61]), "+f"(d[62]), "+f"(d[63])
        : "r"(da), "r"(db), "r"(acc), "n"(TB), "r"(ha), "r"(hb));
}
template <int TB>
__device__ __forceinline__ void wgmma_ss128_init(float (&d)[64], uint32_t da, uint32_t db, uint32_t ha = 0x40000040u, uint32_t hb = 0x40000040u) {
    asm volatile("{\n.reg .pred p;\n.reg .b64 a, b;\nsetp.ne.b32 p, 0, 0;\nmov.b64 a, {%64, %67};\nmov.b64 b, {%65, %68};\n"
        "wgmma.mma_async.sync.aligned.m64n128k16.f32.bf16.bf16 {%0, %1, %2, %3, %4, %5, %6, %7, %8, %9, %10, %11, %12, %13, %14, %15, %16, %17, %18, %19, %20, %21, %22, %23, %24, %25, %26, %27, %28, %29, %30, %31, %32, %33, %34, %35, %36, %37, %38, %39, %40, %41, %42, %43, %44, %45, %46, %47, %48, %49, %50, %51, %52, %53, %54, %55, %56, %57, %58, %59, %60, %61, %62, %63}, a, b, p, 1, 1, 0, %66;\n}"
        : "=f"(d[0]), "=f"(d[1]), "=f"(d[2]), "=f"(d[3]), "=f"(d[4]), "=f"(d[5]), "=f"(d[6]), "=f"(d[7]), "=f"(d[8]), "=f"(d[9]), "=f"(d[10]), "=f"(d[11]), "=f"(d[12]), "=f"(d[13]), "=f"(d[14]), "=f"(d[15]), "=f"(d[16]), "=f"(d[17]), "=f"(d[18]), "=f"(d[19]), "=f"(d[20]), "=f"(d[21]), "=f"(d[22]), "=f"(d[23]), "=f"(d[24]), "=f"(d[25]), "=f"(d[26]), "=f"(d[27]), "=f"(d[28]), "=f"(d[29]), "=f"(d[30]), "=f"(d[31]), "=f"(d[32]), "=f"(d[33]), "=f"(d[34]), "=f"(d[35]), "=f"(d[36]), "=f"(d[37]), "=f"(d[38]), "=f"(d[39]), "=f"(d[40]), "=f"(d[41]), "=f"(d[42]), "=f"(d[43]), "=f"(d[44]), "=f"(d[45]), "=f"(d[46]), "=f"(d[47]), "=f"(d[48]), "=f"(d[49]), "=f"(d[50]), "=f"(d[51]), "=f"(d[52]), "=f"(d[53]), "=f"(d[54]), "=f"(d[55]), "=f"(d[56]), "=f"(d[57]), "=f"(d[58]), "=f"(d[59]), "=f"(d[60]), "=f"(d[61]), "=f"(d[62]), "=f"(d[63])
        : "r"(da), "r"(db), "n"(TB), "r"(ha), "r"(hb));
}
template <int TB>
__device__ __forceinline__ void wgmma_ss64(float (&d)[32], uint32_t da, uint32_t db, int acc, uint32_t ha = 0x40000040u, uint32_t hb = 0x40000040u) {
    asm volatile("{\n.reg .pred p;\n.reg .b64 a, b;\nsetp.ne.b32 p, %34, 0;\nmov.b64 a, {%32, %36};\nmov.b64 b, {%33, %37};\n"
        "wgmma.mma_async.sync.aligned.m64n64k16.f32.bf16.bf16 {%0, %1, %2, %3, %4, %5, %6, %7, %8, %9, %10, %11, %12, %13, %14, %15, %16, %17, %18, %19, %20, %21, %22, %23, %24, %25, %26, %27, %28, %29, %30, %31}, a, b, p, 1, 1, 0, %35;\n}"
        : "+f"(d[0]), "+f"(d[1]), "+f"(d[2]), "+f"(d[3]), "+f"(d[4]), "+f"(d[5]), "+f"(d[6]), "+f"(d[7]), "+f"(d[8]), "+f"(d[9]), "+f"(d[10]), "+f"(d[11]), "+f"(d[12]), "+f"(d[13]), "+f"(d[14]), "+f"(d[15]), "+f"(d[16]), "+f"(d[17]), "+f"(d[18]), "+f"(d[19]), "+f"(d[20]), "+f"(d[21]), "+f"(d[22]), "+f"(d[23]), "+f"(d[24]), "+f"(d[25]), "+f"(d[26]), "+f"(d[27]), "+f"(d[28]), "+f"(d[29]), "+f"(d[30]), "+f"(d[31])
        : "r"(da), "r"(db), "r"(acc), "n"(TB), "r"(ha), "r"(hb));
}
template <int TB>
__device__ __forceinline__ void wgmma_ss64_init(float (&d)[32], uint32_t da, uint32_t db, uint32_t ha = 0x40000040u, uint32_t hb = 0x40000040u) {
    asm volatile("{\n.reg .pred p;\n.reg .b64 a, b;\nsetp.ne.b32 p, 0, 0;\nmov.b64 a, {%32, %35};\nmov.b64 b, {%33, %36};\n"
        "wgmma.mma_async.sync.aligned.m64n64k16.f32.bf16.bf16 {%0, %1, %2, %3, %4, %5, %6, %7, %8, %9, %10, %11, %12, %13, %14, %15, %16, %17, %18, %19, %20, %21, %22, %23, %24, %25, %26, %27, %28, %29, %30, %31}, a, b, p, 1, 1, 0, %34;\n}"
        : "=f"(d[0]), "=f"(d[1]), "=f"(d[2]), "=f"(d[3]), "=f"(d[4]), "=f"(d[5]), "=f"(d[6]), "=f"(d[7]), "=f"(d[8]), "=f"(d[9]), "=f"(d[10]), "=f"(d[11]), "=f"(d[12]), "=f"(d[13]), "=f"(d[14]), "=f"(d[15]), "=f"(d[16]), "=f"(d[17]), "=f"(d[18]), "=f"(d[19]), "=f"(d[20]), "=f"(d[21]), "=f"(d[22]), "=f"(d[23]), "=f"(d[24]), "=f"(d[25]), "=f"(d[26]), "=f"(d[27]), "=f"(d[28]), "=f"(d[29]), "=f"(d[30]), "=f"(d[31])
        : "r"(da), "r"(db), "n"(TB), "r"(ha), "r"(hb));
}
__device__ __forceinline__ void wgmma_rs128(float (&d)[64], uint32_t a0, uint32_t a1, uint32_t a2, uint32_t a3, uint32_t db, int acc, uint32_t hb = 0x40000040u) {
    asm volatile("{\n.reg .pred p;\n.reg .b64 b;\nsetp.ne.b32 p, %69, 0;\nmov.b64 b, {%68, %70};\n"
        "wgmma.mma_async.sync.aligned.m64n128k16.f32.bf16.bf16 {%0, %1, %2, %3, %4, %5, %6, %7, %8, %9, %10, %11, %12, %13, %14, %15, %16, %17, %18, %19, %20, %21, %22, %23, %24, %25, %26, %27, %28, %29, %30, %31, %32, %33, %34, %35, %36, %37, %38, %39, %40, %41, %42, %43, %44, %45, %46, %47, %48, %49, %50, %51, %52, %53, %54, %55, %56, %57, %58, %59, %60, %61, %62, %63}, {%64, %65, %66, %67}, b, p, 1, 1, 1;\n}"
        : "+f"(d[0]), "+f"(d[1]), "+f"(d[2]), "+f"(d[3]), "+f"(d[4]), "+f"(d[5]), "+f"(d[6]), "+f"(d[7]), "+f"(d[8]), "+f"(d[9]), "+f"(d[10]), "+f"(d[11]), "+f"(d[12]), "+f"(d[13]), "+f"(d[14]), "+f"(d[15]), "+f"(d[16]), "+f"(d[17]), "+f"(d[18]), "+f"(d[19]), "+f"(d[20]), "+f"(d[21]), "+f"(d[22]), "+f"(d[23]), "+f"(d[24]), "+f"(d[25]), "+f"(d[26]), "+f"(d[27]), "+f"(d[28]), "+f"(d[29]), "+f"(d[30]), "+f"(d[31]), "+f"(d[32]), "+f"(d[33]), "+f"(d[34]), "+f"(d[35]), "+f"(d[36]), "+f"(d[37]), "+f"(d[38]), "+f"(d[39]), "+f"(d[40]), "+f"(d[41]), "+f"(d[42]), "+f"(d[43]), "+f"(d[44]), "+f"(d[45]), "+f"(d[46]), "+f"(d[47]), "+f"(d[48]), "+f"(d[49]), "+f"(d[50]), "+f"(d[51]), "+f"(d[52]), "+f"(d[53]), "+f"(d[54]), "+f"(d[55]), "+f"(d[56]), "+f"(d[57]), "+f"(d[58]), "+f"(d[59]), "+f"(d[60]), "+f"(d[61]), "+f"(d[62]), "+f"(d[63])
        : "r"(a0), "r"(a1), "r"(a2), "r"(a3), "r"(db), "r"(acc), "r"(hb));
}

__device__ __forceinline__ uint32_t pack2(float lo, float hi) {
    uint32_t r;
    asm("cvt.rn.bf16x2.f32 %0, %1, %2;" : "=r"(r) : "f"(hi), "f"(lo));
    return r;
}
__device__ __forceinline__ float bf_lo(uint32_t v) { return __uint_as_float(v << 16); }
__device__ __forceinline__ float bf_hi(uint32_t v) { return __uint_as_float(v & 0xffff0000u); }
__device__ __forceinline__ float rbf(float v) { return bf_lo(pack2(v, v)); }
__device__ __forceinline__ uint32_t badd(uint32_t a, uint32_t b) {
    uint32_t r;
    asm("add.rn.bf16x2 %0, %1, %2;" : "=r"(r) : "r"(a), "r"(b));
    return r;
}
__device__ __forceinline__ uint32_t bsub(uint32_t a, uint32_t b) {
    uint32_t r;
    asm("sub.rn.bf16x2 %0, %1, %2;" : "=r"(r) : "r"(a), "r"(b));
    return r;
}
__device__ __forceinline__ uint32_t bmul(uint32_t a, uint32_t b) {
    uint32_t r;
    asm("mul.rn.bf16x2 %0, %1, %2;" : "=r"(r) : "r"(a), "r"(b));
    return r;
}
__device__ __forceinline__ uint32_t ln_apply(uint32_t x, uint32_t mb, float rs, uint32_t scale, uint32_t shift) {
    const uint32_t d = bsub(x, mb);
    return badd(bmul(pack2(bf_lo(d) * rs, bf_hi(d) * rs), scale), shift);
}
__device__ __forceinline__ float ex2(float v) {
    float r;
    asm("ex2.approx.ftz.f32 %0, %1;" : "=f"(r) : "f"(v));
    return r;
}
__device__ __forceinline__ float rcp(float v) {
    float r;
    asm("rcp.approx.ftz.f32 %0, %1;" : "=f"(r) : "f"(v));
    return r;
}
__device__ __forceinline__ float sqrt_fast(float v) {
    float r;
    asm("sqrt.approx.ftz.f32 %0, %1;" : "=f"(r) : "f"(v));
    return r;
}
__device__ __forceinline__ float ln_rstd(float var) { return rcp(rbf(sqrt_fast(rbf(rbf(var) + 1e-5f)))); }
__device__ __forceinline__ float sigmoid(float v) { return rcp(1.f + ex2(-1.4426950408889634f * v)); }
__device__ __forceinline__ float warp_sum(float v) {
#pragma unroll
    for (int o = 16; o > 0; o >>= 1) v += __shfl_xor_sync(0xffffffffu, v, o);
    return v;
}
__device__ __forceinline__ float quad_sum(float v) {
    v += __shfl_xor_sync(0xffffffffu, v, 1);
    return v + __shfl_xor_sync(0xffffffffu, v, 2);
}

constexpr uint32_t HI_128 = 0x40000040u, HI_IMG = 0x80000080u, HI_Q = 0x80000040u;
template <int M, int RH>
__device__ __forceinline__ uint4 img_pack(const float (&d)[64], float s) {
    uint4 v;
    v.x = pack2(d[16 * M + 2 * RH] * s, d[16 * M + 2 * RH + 1] * s);
    v.y = pack2(d[16 * M + 4 + 2 * RH] * s, d[16 * M + 5 + 2 * RH] * s);
    v.z = pack2(d[16 * M + 8 + 2 * RH] * s, d[16 * M + 9 + 2 * RH] * s);
    v.w = pack2(d[16 * M + 12 + 2 * RH] * s, d[16 * M + 13 + 2 * RH] * s);
    return v;
}
template <int M, int RH>
__device__ __forceinline__ uint4 img_pack(const float (&d)[64]) {
    uint4 v;
    v.x = pack2(d[16 * M + 2 * RH], d[16 * M + 2 * RH + 1]);
    v.y = pack2(d[16 * M + 4 + 2 * RH], d[16 * M + 5 + 2 * RH]);
    v.z = pack2(d[16 * M + 8 + 2 * RH], d[16 * M + 9 + 2 * RH]);
    v.w = pack2(d[16 * M + 12 + 2 * RH], d[16 * M + 13 + 2 * RH]);
    return v;
}
template <int M>
__device__ __forceinline__ void img_store_global(uint8_t* img, uint32_t toff, const float (&d)[64], float s0, float s1) {
    uint4* p = reinterpret_cast<uint4*>(img + toff) + M * 32;
    p[0] = img_pack<M, 0>(d, s0);
    p[128] = img_pack<M, 1>(d, s1);
}
__device__ __forceinline__ void sts128(uint32_t a, uint4 v) {
    asm volatile("st.shared.v4.b32 [%0], {%1, %2, %3, %4};" ::"r"(a), "r"(v.x), "r"(v.y), "r"(v.z), "r"(v.w) : "memory");
}
constexpr float SM_C = 0.08838834764831845f * 1.4426950408889634f;
__device__ __forceinline__ float pack2f(float lo, float hi) {
    float r;
    asm("{\n.reg .b32 t;\ncvt.rn.bf16x2.f32 t, %1, %2;\nmov.b32 %0, t;\n}" : "=f"(r) : "f"(hi), "f"(lo));
    return r;
}
template <int M, bool SCALE, bool PARK>
__device__ __forceinline__ void pack_group(float (&d)[64], float (&v)[8], float s0, float s1) {
#pragma unroll
    for (int i = 0; i < 8; i++) {
        const int k = 16 * M + 4 * (i & 3) + 2 * (i >> 2);
        v[i] = SCALE ? pack2f(d[k] * (i < 4 ? s0 : s1), d[k + 1] * (i < 4 ? s0 : s1)) : pack2f(d[k], d[k + 1]);
        if (PARK && M > 0) d[16 * (M > 0 ? M - 1 : 0) + i] = v[i];
    }
}
template <int M, bool PARK>
__device__ __forceinline__ void q_store_part(uint32_t a, float (&d)[64]) {
    float v[8];
    pack_group<M, false, PARK>(d, v, 0.f, 0.f);
#pragma unroll
    for (int h = 0; h < 2; h++)
        asm volatile("st.shared.v4.f32 [%0], {%1, %2, %3, %4};" ::"r"(a + (M >> 1) * 16384 + (M & 1) * 512 + h * 1024),
                     "f"(v[4 * h]), "f"(v[4 * h + 1]), "f"(v[4 * h + 2]), "f"(v[4 * h + 3]) : "memory");
}
template <bool PARK>
__device__ __forceinline__ void q_store(uint32_t a, uint32_t toff, float (&d)[64]) {
    a += (((toff >> 1) & ~2047u) ^ 8192) + (toff & 511);
    q_store_part<0, PARK>(a, d); q_store_part<1, PARK>(a, d); q_store_part<2, PARK>(a, d); q_store_part<3, PARK>(a, d);
}
template <int M, bool PARK>
__device__ __forceinline__ void ctx_store_part(float4* p, float (&d)[64], float i0, float i1) {
    float v[8];
    pack_group<M, true, PARK>(d, v, i0, i1);
    p[M * 32] = make_float4(v[0], v[1], v[2], v[3]);
    p[M * 32 + 128] = make_float4(v[4], v[5], v[6], v[7]);
}
template <bool PARK>
__device__ __forceinline__ void ctx_store(uint8_t* img, uint32_t toff, float (&o)[64], float l0, float l1) {
    const float i0 = rcp(quad_sum(l0)), i1 = rcp(quad_sum(l1));
    float4* p = reinterpret_cast<float4*>(img + toff);
    ctx_store_part<0, PARK>(p, o, i0, i1); ctx_store_part<1, PARK>(p, o, i0, i1); ctx_store_part<2, PARK>(p, o, i0, i1); ctx_store_part<3, PARK>(p, o, i0, i1);
}

__device__ __forceinline__ void slot_wait(uint32_t bars, uint32_t& ph, uint32_t slot) {
    mbar_wait(bars + 8 * slot, (ph >> slot) & 1);
    ph ^= 1u << slot;
}
__device__ __forceinline__ void release_if(uint32_t eb, uint32_t slot, bool on) {
    asm volatile("{\n.reg .pred p;\nsetp.ne.s32 p, %1, 0;\n@p mbarrier.arrive.shared::cluster.b64 _, [%0];\n}" ::"r"(eb + 8 * slot), "r"((int)on) : "memory");
}
__device__ __forceinline__ void load_image_mc(uint32_t sb, uint32_t& ph, uint32_t slot, const uint8_t* src, int rank, bool first) {
    slot_wait(sb + BAR_EMPTY, ph, slot);
    asm volatile("{\n.reg .pred p;\nelect.sync _|p, 0xffffffff;\n@p mbarrier.arrive.expect_tx.shared::cta.b64 _, [%2], 32768;\n"
                 "@p cp.async.bulk.shared::cluster.global.mbarrier::complete_tx::bytes.multicast::cluster.L2::cache_hint [%0], [%1], 16384, [%2], %4, %3;\n}"
                 ::"r"(sb + slot * SLOT + rank * 16384), "l"(src + rank * 16384), "r"(sb + BAR_FULL + 8 * slot), "l"(first ? L2_FIRST : L2_NORMAL),
                 "h"((uint16_t)3) : "memory");
}
__device__ __forceinline__ void load_tile_mc(uint32_t sb, uint32_t& ph, uint32_t slot, const CUtensorMap* m, int row, int cb, int rank, bool first) {
    slot_wait(sb + BAR_EMPTY, ph, slot);
    asm volatile("{\n.reg .pred p;\nelect.sync _|p, 0xffffffff;\n@p mbarrier.arrive.expect_tx.shared::cta.b64 _, [%2], 32768;\n"
                 "@p cp.async.bulk.tensor.3d.shared::cluster.global.mbarrier::complete_tx::bytes.multicast::cluster.L2::cache_hint [%0], [%1, {%3, %4, %5}], [%2], %7, %6;\n}"
                 ::"r"(sb + slot * SLOT + rank * 16384), "l"(m), "r"(sb + BAR_FULL + 8 * slot), "r"(0), "r"(row), "r"(cb + rank),
                 "l"(first ? L2_FIRST : L2_NORMAL), "h"((uint16_t)3) : "memory");
}
__device__ __forceinline__ void load_image(uint32_t sb, uint32_t& ph, uint32_t slot, const void* src, bool first) {
    slot_wait(sb + BAR_EMPTY, ph, slot);
    asm volatile("{\n.reg .pred p;\nelect.sync _|p, 0xffffffff;\n@p mbarrier.arrive.expect_tx.shared::cta.b64 _, [%2], 32768;\n"
                 "@p cp.async.bulk.shared::cluster.global.mbarrier::complete_tx::bytes.L2::cache_hint [%0], [%1], 32768, [%2], %3;\n}"
                 ::"r"(sb + slot * SLOT), "l"(src), "r"(sb + BAR_FULL + 8 * slot), "l"(first ? L2_FIRST : L2_NORMAL) : "memory");
}
__device__ __forceinline__ void load_tile(uint32_t sb, uint32_t& ph, uint32_t slot, const CUtensorMap* m, int row, int cb, bool first) {
    slot_wait(sb + BAR_EMPTY, ph, slot);
    asm volatile("{\n.reg .pred p;\nelect.sync _|p, 0xffffffff;\n@p mbarrier.arrive.expect_tx.shared::cta.b64 _, [%2], 32768;\n"
                 "@p cp.async.bulk.tensor.3d.shared::cluster.global.mbarrier::complete_tx::bytes.L2::cache_hint [%0], [%1, {%3, %4, %5}], [%2], %6;\n}"
                 ::"r"(sb + slot * SLOT), "l"(m), "r"(sb + BAR_FULL + 8 * slot), "r"(0), "r"(row), "r"(cb), "l"(first ? L2_FIRST : L2_NORMAL) : "memory");
}
__device__ __forceinline__ uint32_t ring_next(uint32_t r) { return r == 4 ? 0 : r + 1; }
__device__ __forceinline__ uint32_t w_table(int hp) { return hp ? 0x3104u : 0x4210u; }
__device__ __forceinline__ uint32_t a_table(int hp) { return hp ? 0x625u : 0x635u; }
__device__ __forceinline__ uint32_t a_next(uint32_t& t) {
    const uint32_t s = t & 15;
    t = (t >> 4) | (s << 8);
    return s;
}
constexpr uint32_t O_TABLE = 0x1604235u;
__device__ __forceinline__ uint32_t o_next(uint32_t& t) {
    const uint32_t s = t & 15;
    t = (t >> 4) | (s << 24);
    return s;
}
__device__ __forceinline__ int o_head(int i, int kh) { return i < 16 ? 4 * (i & 7) + 2 * (kh ^ 1) + (i >> 3) : 29 + 2 * kh; }

template <bool INIT>
__device__ __forceinline__ void gemm_issue(float (&d)[64], uint32_t a, uint32_t b, int acc, bool img) {
    const uint32_t ha = img ? HI_IMG : HI_128, o2 = img ? 32 : 4, o4 = img ? 64 : 1024;
    wg_fence();
#pragma unroll
    for (int k = 0; k < 8; k++) {
        if (INIT && k == 0) wgmma_ss128_init<1>(d, a, b, ha);
        else wgmma_ss128<1>(d, a + (k >> 2) * o4 + ((k >> 1) & 1) * o2 + (k & 1) * 2, b + k * 128, k ? 1 : acc, ha);
    }
    wg_commit();
}

__device__ __forceinline__ void h_store(const uint32_t* x, float mean, float sq, uint32_t sb, int row) {
    const int lane = threadIdx.x & 31;
    const float rs = ln_rstd(sq * (1.f / 512.f));
    const uint32_t mb = pack2(mean, mean);
    uint8_t* p = g_h + ((row >> 7) * 8 + (lane >> 3)) * 16384 + (row & 127) * 128 + (((lane ^ row) & 7) << 4);
#pragma unroll
    for (int i = 0; i < 2; i++) {
        const uint4 a = lds128(sb + SM_TAB + 1024 + i * 512 + lane * 16), c = lds128(sb + SM_TAB + i * 512 + lane * 16);
        *reinterpret_cast<uint4*>(p + i * 65536) = make_uint4(ln_apply(x[4 * i], mb, rs, a.x, c.x), ln_apply(x[4 * i + 1], mb, rs, a.y, c.y),
                                                              ln_apply(x[4 * i + 2], mb, rs, a.z, c.z), ln_apply(x[4 * i + 3], mb, rs, a.w, c.w));
    }
}

template <bool ODD>
__device__ __forceinline__ void proj_tile(float (&acc)[64], float (&prev)[64], int t, int q0, uint32_t sb, int wg, uint32_t eb, bool rel, uint32_t& fph,
                                          uint32_t wtab, uint32_t& atab, uint8_t* prev_img, uint32_t toff, float s0, float s1, bool first,
                                          const bf16* x, int xrow) {
    const uint32_t a0 = desc_k(sb + (wg ^ (ODD && t == 5)) * 8192), b0 = desc_mn(sb);
    const int lane = threadIdx.x & 31;
    float mean[2] = {0.f, 0.f}, rstd[2] = {0.f, 0.f};
    uint32_t xn[16];
#pragma unroll
    for (int i = 0; i < 4; i++) {
        uint4 v = make_uint4(0, 0, 0, 0);
        if (ODD && first) v = __ldg(reinterpret_cast<const uint4*>(x) + xrow * 64 + lane + 32 * i);
        xn[4 * i] = v.x; xn[4 * i + 1] = v.y; xn[4 * i + 2] = v.z; xn[4 * i + 3] = v.w;
    }
    constexpr int U = ODD ? UNR : 1;
#pragma unroll U
    for (int q = ODD ? 0 : q0; q < 4; q++) {
        if (ODD && t == 5 && q == 3) break;
        const uint32_t ws = (wtab >> (4 * q)) & 15, as = a_next(atab);
        if (!ODD && t != 2) slot_wait(sb + BAR_FULL, fph, ws);
        slot_wait(sb + BAR_FULL, fph, as);
        bar_sync(1 + wg, 256);
        gemm_issue<false>(acc, a0 + as * (SLOT / 16), b0 + ws * (SLOT / 16), q, false);
        bar_arrive(2 - wg, 256);
        wg_wait<1>();
        reg_fence(prev);
        if (ODD && t == 5) {
            if (q == 2) {
                q_store<false>(sb + 5 * SLOT, toff, prev);
                fence_async_smem();
            }
        } else if (ODD || !first) {
            if (q == 0) img_store_global<0>(prev_img, toff, prev, s0, s1);
            if (q == 1) img_store_global<1>(prev_img, toff, prev, s0, s1);
            if (q == 2) img_store_global<2>(prev_img, toff, prev, s0, s1);
            if (q == 3) img_store_global<3>(prev_img, toff, prev, s0, s1);
        }
        if (ODD && q == 1 && first) {
#pragma unroll
            for (int k = 0; k < 16; k++) mean[k >> 3] += bf_lo(xn[k]) + bf_hi(xn[k]);
#pragma unroll
            for (int i = 0; i < 2; i++) mean[i] = warp_sum(mean[i]) * (1.f / 512.f);
        }
        if (ODD && q == 2 && first) {
#pragma unroll
            for (int k = 0; k < 16; k++) {
                const float d0 = bf_lo(xn[k]) - mean[k >> 3], d1 = bf_hi(xn[k]) - mean[k >> 3];
                rstd[k >> 3] = fmaf(d0, d0, fmaf(d1, d1, rstd[k >> 3]));
            }
#pragma unroll
            for (int i = 0; i < 2; i++) rstd[i] = warp_sum(rstd[i]);
        }
        if (ODD && q == 3 && first) {
            mbar_wait(sb + BAR_FLAG + 8 * 8, 0);
            h_store(xn, mean[0], rstd[0], sb, xrow);
        }
        wg_wait<0>();
        release_if(eb, as, rel && !(ODD && (q & 1) && t == 5));
        if (ODD) release_if(eb, ws, rel && t != 1);
        if (ODD && q == 3 && first) {
            h_store(xn + 8, mean[1], rstd[1], sb, xrow + 1);
            __syncwarp();
            mbar_arrive_if(sb + BAR_DONE, lane == 0);
        }
    }
    reg_fence(acc);
}

__device__ __forceinline__ void qk_issue(float (&s)[64], uint32_t q, uint32_t k) {
    wg_fence();
    wgmma_ss128_init<0>(s, q, k, HI_Q, HI_IMG);
#pragma unroll
    for (int i = 1; i < 8; i++) wgmma_ss128<0>(s, q + (i >> 2) * 1024 + (i & 2) * 16 + (i & 1) * 2, k + (i >> 1) * 32 + (i & 1) * 2, 1, HI_Q, HI_IMG);
    wg_commit();
}
__device__ __forceinline__ void qk_issue(float (&s)[32], uint32_t q, uint32_t k) {
    wg_fence();
    wgmma_ss64_init<0>(s, q, k, HI_Q, HI_IMG);
#pragma unroll
    for (int i = 1; i < 8; i++) wgmma_ss64<0>(s, q + (i >> 2) * 1024 + (i & 2) * 16 + (i & 1) * 2, k + (i >> 1) * 32 + (i & 1) * 2, 1, HI_Q, HI_IMG);
    wg_commit();
}
__device__ __forceinline__ void pv_issue(float (&o)[64], const uint32_t (&p)[32], uint32_t v, int acc, bool half) {
    if (half) {
        asm volatile("// half" ::: "memory");
        wg_fence();
#pragma unroll
        for (int i = 0; i < 4; i++) wgmma_rs128(o, p[4 * i], p[4 * i + 1], p[4 * i + 2], p[4 * i + 3], v + i * 256, i ? 1 : acc, HI_IMG);
        wg_commit();
        asm volatile("// half" ::: "memory");
    } else {
        wg_fence();
#pragma unroll
        for (int i = 0; i < 8; i++) wgmma_rs128(o, p[4 * i], p[4 * i + 1], p[4 * i + 2], p[4 * i + 3], v + i * 256, i ? 1 : acc, HI_IMG);
        wg_commit();
    }
}
template <int B, int N>
__device__ __forceinline__ void tri_mask(float (&s)[N], int x) {
#pragma unroll
    for (int k = 0; k < 7; k++)
        asm("{\n.reg .pred p, q;\nsetp.lt.s32 p, %4, %5;\nsetp.le.s32 q, %4, %5;\n"
            "@p mov.b32 %0, 0fFF800000;\n@q mov.b32 %1, 0fFF800000;\n@p mov.b32 %2, 0fFF800000;\n@q mov.b32 %3, 0fFF800000;\n}"
            : "+f"(s[B + 4 * k]), "+f"(s[B + 4 * k + 1]), "+f"(s[B + 4 * k + 6]), "+f"(s[B + 4 * k + 7]) : "r"(x), "r"(8 * k));
    asm("{\n.reg .pred p, q;\nsetp.lt.s32 p, %2, 56;\nsetp.le.s32 q, %2, 56;\n@p mov.b32 %0, 0fFF800000;\n@q mov.b32 %1, 0fFF800000;\n}"
        : "+f"(s[B + 28]), "+f"(s[B + 29]) : "r"(x));
}
__device__ __forceinline__ void tri_mask_copy(float (&s)[64], const float (&h)[32], int x) {
#pragma unroll
    for (int i = 0; i < 32; i++) {
        asm("{\n.reg .pred p;\nsetp.lt.s32 p, %2, %3;\nselp.f32 %0, 0fFF800000, %1, p;\n}"
            : "=f"(s[i]) : "f"(h[i]), "r"(x), "r"(8 * (i >> 2) - 4 * (i & 2) + (i & 1)));
        s[32 + i] = __uint_as_float(0xff800000u);
    }
}
constexpr float SM_HI = 1152921504606846976.f, SM_LO = 1.f / 1152921504606846976.f;
__device__ __forceinline__ bool softmax_unsafe(float t0, float t1, bool first) {
    bool bad = __any_sync(0xffffffffu, fmaxf(t0, t1) > SM_HI);
    if (first) {
        uint32_t a = __ballot_sync(0xffffffffu, t0 >= SM_LO), b = __ballot_sync(0xffffffffu, t1 >= SM_LO);
        a |= a >> 1;
        b |= b >> 1;
        bad |= ((a | (a >> 2)) & (b | (b >> 2)) & 0x11111111u) != 0x11111111u;
    }
    return bad;
}
__device__ __forceinline__ void softmax_shift(float (&s)[64], float d0, float d1) {
#pragma unroll
    for (int i = 0; i < 64; i++) s[i] -= (i & 2) ? d1 : d0;
}
__device__ __forceinline__ void softmax_remax(float (&s)[64], float (&m)[2], bool first, float& a0, float& a1) {
    float m0 = fmaxf(s[0], s[1]), m1 = fmaxf(s[2], s[3]);
#pragma unroll
    for (int k = 1; k < 16; k++) {
        m0 = fmaxf(m0, fmaxf(s[4 * k], s[4 * k + 1]));
        m1 = fmaxf(m1, fmaxf(s[4 * k + 2], s[4 * k + 3]));
    }
    m0 = fmaxf(m0, __shfl_xor_sync(0xffffffffu, m0, 1));
    m1 = fmaxf(m1, __shfl_xor_sync(0xffffffffu, m1, 1));
    m0 = fmaxf(m0, __shfl_xor_sync(0xffffffffu, m0, 2));
    m1 = fmaxf(m1, __shfl_xor_sync(0xffffffffu, m1, 2));
    if (!first) {
        m0 = fmaxf(m0, 0.f);
        m1 = fmaxf(m1, 0.f);
    }
    a0 = first ? 1.f : ex2(-m0);
    a1 = first ? 1.f : ex2(-m1);
    m[0] += m0;
    m[1] += m1;
    softmax_shift(s, m0, m1);
}
template <int J0, int J1>
__device__ __forceinline__ void softmax_exp(const float (&s)[64], uint32_t (&p)[32], float (&t)[4]) {
#pragma unroll
    for (int k = J0; k < J1; k++) {
        const float e0 = ex2(s[4 * k]), e1 = ex2(s[4 * k + 1]), e2 = ex2(s[4 * k + 2]), e3 = ex2(s[4 * k + 3]);
        if (k == 0) { t[0] = e0; t[1] = e1; t[2] = e2; t[3] = e3; }
        else { t[0] += e0; t[1] += e1; t[2] += e2; t[3] += e3; }
        p[2 * k] = pack2(e0, e1);
        p[2 * k + 1] = pack2(e2, e3);
    }
}
__device__ __forceinline__ void fma8(float (&acc)[8], float a, uint4 w) {
    acc[0] = fmaf(a, bf_lo(w.x), acc[0]); acc[1] = fmaf(a, bf_hi(w.x), acc[1]);
    acc[2] = fmaf(a, bf_lo(w.y), acc[2]); acc[3] = fmaf(a, bf_hi(w.y), acc[3]);
    acc[4] = fmaf(a, bf_lo(w.z), acc[4]); acc[5] = fmaf(a, bf_hi(w.z), acc[5]);
    acc[6] = fmaf(a, bf_lo(w.w), acc[6]); acc[7] = fmaf(a, bf_hi(w.w), acc[7]);
}
__device__ __forceinline__ void mma16816(float (&d)[4], const uint32_t* a, uint32_t b0, uint32_t b1) {
    asm("mma.sync.aligned.m16n8k16.row.col.f32.bf16.bf16.f32 {%0, %1, %2, %3}, {%4, %5, %6, %7}, {%8, %9}, {%0, %1, %2, %3};"
        : "+f"(d[0]), "+f"(d[1]), "+f"(d[2]), "+f"(d[3]) : "r"(a[0]), "r"(a[1]), "r"(a[2]), "r"(a[3]), "r"(b0), "r"(b1));
}
__device__ __forceinline__ uint32_t best_key(const uint32_t* keys, int lane, uint32_t ep) {
    uint32_t best;
#pragma unroll 1
    for (;;) {
        const uint4 k = ld_poll(reinterpret_cast<const uint4*>(keys) + lane);
        best = max(max(k.x, k.y), max(k.z, k.w));
        if (__all_sync(0xffffffffu, (((k.x ^ ep) | (k.y ^ ep) | (k.z ^ ep) | (k.w ^ ep)) & 31) == 0)) break;
    }
    return __reduce_max_sync(0xffffffffu, best);
}

__global__ void __cluster_dims__(2, 1, 1) __launch_bounds__(384, 1)
fused_kernel(const __grid_constant__ CUtensorMap tm_ckv, const __grid_constant__ CUtensorMap tm_wq,
             const __grid_constant__ CUtensorMap tm_wuk, const __grid_constant__ CUtensorMap tm_wuv,
             const __grid_constant__ CUtensorMap tm_wo, const __grid_constant__ CUtensorMap tm_wg,
             const __grid_constant__ CUtensorMap tm_wu,
             const __grid_constant__ CUtensorMap tm_wm, const __grid_constant__ CUtensorMap tm_x, const Params P) {
    extern __shared__ __align__(1024) uint8_t smem[];
    const uint32_t sb = (uint32_t)__cvta_generic_to_shared(smem);
    const int tid = threadIdx.x, lane = tid & 31, warp = __shfl_sync(0xffffffffu, tid >> 5, 0), wg = warp >> 2;
    uint32_t sm;
    asm("mov.u32 %0, %%smid;" : "=r"(sm));
    if (MC) sm = blockIdx.x < 8 ? blockIdx.x + 124 : blockIdx.x - 8;
    const uint32_t smq = ((sm - 64) * 147) >> 11;
    const int rb = !P.by_smid ? blockIdx.x : sm < 64 ? (sm & 14) * 8 + (sm >> 4) * 2 + (sm & 1)
                 : sm < 120 ? ((sm - 64 - smq * 14) & 14) * 8 + 24 + smq * 2 + (sm & 1) : sm < 124 ? sm + 8 : sm - 116;
    const int grp = rb >> 3, j = rb & 7, cq = j & 3, kh = grp & 1, ort = (grp & 14) + (j >> 2);
    if (warp == 0) TS(0);

    if (rb >= NCTA) {
        float* sc = reinterpret_cast<float*>(smem + 6 * SLOT);
        float* red = sc + 512;
        if (tid == 256) {
            for (int i = 0; i < 6; i++) { mbar_init(sb + BAR_FULL + 8 * i, 1); mbar_init(sb + BAR_EMPTY + 8 * i, 8); }
            fence_async_smem();
        }
        __syncthreads();
        uint32_t ph = 0, sl = 0;
        if (tid == 256) {
#pragma unroll 1
            for (int i = 0; i < 24; i++) {
                mbar_wait(sb + BAR_EMPTY + 8 * sl, ph ^ 1);
                mbar_expect(sb + BAR_FULL + 8 * sl, SLOT);
                tma2d(sb + sl * SLOT, &tm_wm, (i >> 3) * 1024 + (rb - NCTA) * 256, (i & 7) * 64, sb + BAR_FULL + 8 * sl);
                if (++sl == 6) { sl = 0; ph ^= 1; }
            }
            mbar_wait(sb + BAR_EMPTY, 1);
            mbar_wait(sb + BAR_EMPTY + 8, 1);
#pragma unroll 1
            for (int i = 0; i <= NFFN / NSPARE; i++) {
                const int b = (rb - NCTA) * (NFFN / NSPARE) + i;
                if (i < NFFN / NSPARE) {
                    const uint32_t f = sb + BAR_FULL + 8 * (i & 1), d = sb + (i & 1) * SLOT;
                    asm volatile("cp.async.bulk.wait_group.read 0;" ::: "memory");
                    mbar_expect(f, SLOT);
                    tma2d(d, &tm_wg, b * 16, 0, f);
                    tma2d(d + 8192, &tm_wg, b * 16, 256, f);
                    tma2d(d + 16384, &tm_wu, b * 16, 0, f);
                    tma2d(d + 24576, &tm_wu, b * 16, 256, f);
                }
                if (i) {
                    mbar_wait(sb + BAR_FULL + 8 * (~i & 1), ((i - 1) >> 1) & 1);
                    asm volatile("cp.async.bulk.global.shared::cta.bulk_group [%0], [%1], 32768;\ncp.async.bulk.commit_group;"
                                 ::"l"(g_wf + (b - 1) * SLOT), "r"(sb + (~i & 1) * SLOT) : "memory");
                }
            }
            asm volatile("cp.async.bulk.wait_group 0;" ::: "memory");
            fence_async_global();
            flag_add(&g_sync.modcnt[32]);
            TS(4);
        } else if (tid < 256) {
            const uint32_t c2 = __ldg(reinterpret_cast<const uint32_t*>(P.c) + tid);
            sc[2 * tid] = rbf(bf_lo(c2) * sigmoid(bf_lo(c2)));
            sc[2 * tid + 1] = rbf(bf_hi(c2) * sigmoid(bf_hi(c2)));
            bar_sync(1, 256);
#pragma unroll 1
            for (int ps = 0; ps < 3; ps++) {
                float acc[8] = {0.f, 0.f, 0.f, 0.f, 0.f, 0.f, 0.f, 0.f};
#pragma unroll 1
                for (int bt = 0; bt < 8; bt++) {
                    mbar_wait(sb + BAR_FULL + 8 * sl, ph);
#pragma unroll
                    for (int i = 0; i < 8; i++)
                        fma8(acc, sc[bt * 64 + warp * 8 + i], *reinterpret_cast<const uint4*>(smem + sl * SLOT + (warp * 8 + i) * 512 + lane * 16));
                    __syncwarp();
                    mbar_arrive_if(sb + BAR_EMPTY + 8 * sl, lane == 0);
                    if (++sl == 6) { sl = 0; ph ^= 1; }
                }
                *reinterpret_cast<float4*>(red + warp * 256 + lane * 8) = make_float4(acc[0], acc[1], acc[2], acc[3]);
                *reinterpret_cast<float4*>(red + warp * 256 + lane * 8 + 4) = make_float4(acc[4], acc[5], acc[6], acc[7]);
                bar_sync(1, 256);
                float v = 0.f;
#pragma unroll
                for (int i = 0; i < 8; i++) v += red[i * 256 + tid];
                g_mod[ps * 1024 + (rb - NCTA) * 256 + tid] = __float2bfloat16_rn(v);
                bar_sync(1, 256);
                if (tid == 0 && ps != 1) flag_add(&g_sync.modcnt[(ps >> 1) * 32]);
                if (warp == 0) TS(1 + ps);
            }
        }
        return;
    }

    if (tid == 256) {
        if (sb & 1023) __trap();
        asm volatile("prefetch.tensormap [%0];" ::"l"((j & 1) ? &tm_wuv : &tm_wuk) : "memory");
        asm volatile("prefetch.tensormap [%0];" ::"l"(&tm_ckv) : "memory");
        for (int i = 0; i < 7; i++) { mbar_init(sb + BAR_FULL + 8 * i, 1); mbar_init(sb + BAR_EMPTY + 8 * i, MC ? 4 : 2); }
        for (int i = 0; i < 9; i++) mbar_init(sb + BAR_DONE + 8 * i, 8);
        for (int i = 0; i < 10; i++) mbar_init(sb + BAR_FLAG + 8 * i, 1);
        *reinterpret_cast<uint32_t*>(smem + SM_EP + 4) = 0;
        *reinterpret_cast<uint32_t*>(smem + SM_EP + 16) = 0;
        mbar_init(sb + BAR_END, 8);
        fence_async_smem();
        if (MC) asm volatile("fence.mbarrier_init.release.cluster;" ::: "memory");
    }
    __syncthreads();
    if (MC) asm volatile("barrier.cluster.arrive.relaxed.aligned;\nbarrier.cluster.wait.aligned;" ::: "memory");

    if (wg == 2) {
        asm volatile("setmaxnreg.dec.sync.aligned.u32 40;");
        if (warp == 8) {
            uint32_t eph = 0x7f, r = 0;
            const CUtensorMap* tw = (j & 1) ? &tm_wuv : &tm_wuk;
#pragma unroll 1
            for (int hp = 0; hp < 2; hp++) {
                const int hc = 4 * grp + 2 * hp;
                uint32_t wtab = w_table(hp), atab = a_table(hp);
#pragma unroll 1
                for (int u = 0; u < 4; u++) {
                    load_tile(sb, eph, (wtab >> (4 * u)) & 15, tw, u * 128, hc, HINT & 1); PT();
                    if (MC & 1) load_tile_mc(sb, eph, a_next(atab), &tm_ckv, (j >> 1) * 128, u * 2, j & 1, (HINT & 8) && hp);
                    else load_tile(sb, eph, a_next(atab), &tm_ckv, (j >> 1) * 128, u * 2, (HINT & 8) && hp);
                    PT();
                    if (hp == 1 && (u & 1) && lane == 0) asm volatile("red.relaxed.gpu.global.add.u32 [%0], 1;" ::"l"(&g_sync.rdcnt[(grp * 2 + (u >> 1)) * 8]) : "memory");
                }
#pragma unroll 1
                for (int u = 4; u < 16; u++) {
                    if (hp == 1 && (u & 7) == 4) mbar_wait(sb + BAR_FLAG + 24 + (u & 8), 0);
                    if (MC & 1) load_tile_mc(sb, eph, a_next(atab), &tm_ckv, ((u & 12) + (j >> 1)) * 128, (u & 3) * 2, j & 1, (HINT & 8) && hp);
                    else load_tile(sb, eph, a_next(atab), &tm_ckv, ((u & 12) + (j >> 1)) * 128, (u & 3) * 2, (HINT & 8) && hp);
                    PT();
                }
                mbar_wait(sb + BAR_FLAG, 0);
                fence_async_global();
#pragma unroll 1
                for (int u = 0; u < 4; u++) {
                    if (MC & 2) load_tile_mc(sb, eph, (wtab >> (4 * u)) & 15, &tm_wq, u * 128, hc, j & 1, HINT & 1);
                    else load_tile(sb, eph, (wtab >> (4 * u)) & 15, &tm_wq, u * 128, hc, HINT & 1);
                    PT();
                    load_image(sb, eph, a_next(atab), g_h + ((15 - j) * 4 + u) * SLOT, (HINT & 8) && hp); PT();
                }
                mbar_wait(sb + BAR_FLAG + 8 + 32 * hp, 0);
                fence_async_global();
#pragma unroll 1
                for (int u = 0; u < 4; u++) { load_image(sb, eph, a_next(atab), g_h + (j * 4 + u) * SLOT, (HINT & 8) && hp); PT(); }
                const uint8_t* kv = g_KV + (size_t)(grp * 32 + 30 * hp) * SLOT;
                const int step = hp ? -2 * SLOT : 2 * SLOT;
                if (MC & 4) load_image_mc(sb, eph, r, kv, j & 1, HINT & 4);
                else load_image(sb, eph, r, kv, HINT & 4);
                PT();
                r = ring_next(r);
#pragma unroll 1
                for (int n = 1; n <= 16; n++) {
                    if (n == 8) {
                        mbar_wait(sb + BAR_FLAG + 16 + 32 * hp, 0);
                        fence_async_global();
                    }
                    asm volatile("st.volatile.shared.u32 [%0], %1;" ::"r"(sb + SM_EP + 16), "r"(16 * hp + n) : "memory");
                    const uint8_t* v = kv + SLOT;
                    kv += n < 16 - j ? step : n == 16 - j ? (2 * j - 15) * step : -step;
                    if ((MC & 4) && n != 15 - (j & 6)) load_image_mc(sb, eph, r, kv, j & 1, HINT & 4);
                    else load_image(sb, eph, r, kv, HINT & 4);
                    PT();
                    r = ring_next(r);
                    if ((MC & 4) && n != 16 - (j & 6)) load_image_mc(sb, eph, r, v, j & 1, HINT & 4);
                    else load_image(sb, eph, r, v, HINT & 4);
                    PT();
                    r = ring_next(r);
                }
                if (MC & 4) load_image_mc(sb, eph, r, kv + SLOT, j & 1, HINT & 4);
                else load_image(sb, eph, r, kv + SLOT, HINT & 4);
                PT();
                r = ring_next(r);
            }
            uint32_t otab = O_TABLE, ready = 0;
#pragma unroll 1
            for (int i = 0; i < 17; i++) {
                asm volatile("st.volatile.shared.u32 [%0], %1;" ::"r"(sb + SM_EP + 16), "r"(33 + i) : "memory");
                const bool dyn = i >= 8 && i < 15;
                const uint32_t want = dyn ? 15u << (4 * (i - 8)) : 1u << max(i + 14, 28);
                if (!(ready & want)) {
                    do {
                        asm volatile("ld.acquire.cta.shared.u32 %0, [%1];" : "=r"(ready) : "r"(sb + SM_EP + 4) : "memory");
                        ready = __shfl_sync(0xffffffffu, ready, 0);
                    } while (!(ready & want));
                    fence_async_global();
                }
                const int head = o_head(dyn ? (ready >> (4 * (i - 8))) & 15 : i, kh);
                const uint8_t* src = g_ctx + (size_t)(ort * 32 + head) * SLOT;
                if (i < 15) {
                    if (MC & 8) load_image_mc(sb, eph, o_next(otab), src, j & 1, HINT & 16);
                    else load_image(sb, eph, o_next(otab), src, HINT & 16);
                } else {
                    const uint32_t as = o_next(otab), d = sb + as * SLOT;
                    slot_wait(sb + BAR_EMPTY, eph, as);
                    asm volatile("{\n.reg .pred p, q;\nelect.sync _|p, 0xffffffff;\n@p mbarrier.arrive.expect_tx.shared::cta.b64 _, [%2], %3;\n"
                                 "@p cp.async.bulk.shared::cluster.global.mbarrier::complete_tx::bytes [%0], [%1], 16384, [%2];\n}"
                                 ::"r"(d + kh * 16384), "l"(src + kh * 16384), "r"(sb + BAR_FULL + 8 * as), "r"(i == 15 ? 32768 : 16384) : "memory");
                    if (i == 15)
                        asm volatile("{\n.reg .pred p;\nelect.sync _|p, 0xffffffff;\n"
                                     "@p cp.async.bulk.tensor.3d.shared::cluster.global.mbarrier::complete_tx::bytes [%0], [%1, {%3, %4, %5}], [%2];\n}"
                                     ::"r"(d + (kh ^ 1) * 16384), "l"(&tm_x), "r"(sb + BAR_FULL + 8 * as), "r"(0), "r"(ort * 128 + kh * 64), "r"(cq * 2) : "memory");
                }
                PT();
                load_tile(sb, eph, o_next(otab), &tm_wo, head * 128, cq * 2, HINT & 2); PT();
                if (i == 0) o_next(otab);
            }
            if (rb < NFFN) {
                load_image(sb, eph, o_next(otab), g_wf + rb * SLOT, false);
                const uint32_t s2 = o_next(otab);
                slot_wait(sb + BAR_EMPTY, eph, s2);
                asm volatile("{\n.reg .pred p;\nelect.sync _|p, 0xffffffff;\n@p mbarrier.arrive.expect_tx.shared::cta.b64 _, [%2], 16384;\n"
                             "@p cp.async.bulk.shared::cluster.global.mbarrier::complete_tx::bytes [%0], [%1], 16384, [%2];\n}"
                             ::"r"(sb + s2 * SLOT), "l"(P.wdown + rb * 8192), "r"(sb + BAR_FULL + 8 * s2) : "memory");
            }
        } else {
            const int hw = warp - 9;
            if (hw == 1 && lane == 0) {
                l2_prefetch(P.ckv + rb * 2048, 4096);
                mbar_watch(sb + BAR_FULL + 8 * PF0, 0);
                l2_prefetch(P.ckv + 512 * 512 + rb * 2048, 4096);
                mbar_watch(sb + BAR_FULL + 8 * 4, 0);
                l2_prefetch(P.x + rb * 8192, 16384);
                l2_prefetch(P.ckv + 1024 * 512 + rb * 4096, 8192);
                TS(40);
                if (MC & 2) tma3d_prefetch(&tm_wq, (j >> 1) * 128, grp * 4 + (j & 1));
                else if (j < 4) tma3d_prefetch(&tm_wq, j * 128, grp * 4);
                step_watch(sb + SM_EP + 16, PFA);
                tma3d_prefetch((j & 1) ? &tm_wuv : &tm_wuk, (j >> 1) * 128, grp * 4 + 2);
                step_watch(sb + SM_EP + 16, PFA + 2);
                l2_prefetch(P.ckv + rb * 8192, 16384);
                step_watch(sb + SM_EP + 16, PFA + 3);
                l2_prefetch(g_h + rb * 16384, 16384);
                step_watch(sb + SM_EP + 16, PFA + 4);
                if (MC & 2) tma3d_prefetch(&tm_wq, (j >> 1) * 128, grp * 4 + 2 + (j & 1));
                else if (j < 4) tma3d_prefetch(&tm_wq, j * 128, grp * 4 + 2);
#pragma unroll 1
                for (int i = 0; i < 10; i++) {
                    step_watch(sb + SM_EP + 16, i < 6 ? 16 + PFB + i : 16 + PFC + i - 6);
                    if (i == 7) mbar_watch(sb + BAR_FLAG + 8 * 7, 0);
                    const uint8_t* p = i < 4 ? g_ctx + (size_t)(ort * 32 + o_head(cq + 2 * (i & 2), kh)) * SLOT + (i & 1) * 16384
                                     : i < 6 ? reinterpret_cast<const uint8_t*>(P.wo) + ((rb >> 3) * 16 + (i & 1) * 8 + (rb & 7)) * 16384
                                     : i == 6 ? reinterpret_cast<const uint8_t*>(P.x) + rb * 16384
                                     : i == 7 ? reinterpret_cast<const uint8_t*>(P.wdown) + rb * 16384 : g_wf + rb * SLOT + (i & 1) * 16384;
                    if ((i < 7 || rb < NFFN) && ((PFMASK >> i) & 1)) l2_prefetch(p, 16384);
                }
                step_watch(sb + SM_EP + 16, 16 + PFC + 4);
                if (OBINIT) {
                    const uint32_t v = lds32(sb + SM_EP) - 1;
#pragma unroll 1
                    for (int i = 0; i < 32; i++) sts128(sb + SM_RED + i * 16, make_uint4(v, v, v, v));
                    fence_async_smem();
#pragma unroll 1
                    for (int i = 0; i < OB / 32; i++)
                        asm volatile("cp.async.bulk.global.shared::cta.bulk_group [%0], [%1], 512;" ::"l"(g_out + rb * OB + i * 32), "r"(sb + SM_RED) : "memory");
                    asm volatile("cp.async.bulk.commit_group;\ncp.async.bulk.wait_group 0;" ::: "memory");
                    fence_async_global();
                }
                mbar_arrive(sb + BAR_PF);
                mbar_watch(sb + BAR_END, 0);
            }
            if (hw == 0) {
#pragma unroll 1
                for (int i = 0; i < 9; i++) {
                    const int hp = i > 4, k = (i - 1) & 3;
                    if (lane == 0) {
                        mbar_wait(sb + BAR_DONE + 8 * i, 0);
                        flag_add(i == 0 ? &g_sync.hcnt[grp * 8] : k < 2 ? &g_sync.kvcnt[((2 * grp + hp) * 2 + k) * 8]
                                                                        : &g_sync.ctxcnt[(k == 2 ? 15 - j : j) * 32 + 2 * grp + hp]);
                    }
                    if (i == 0) TS(43);
                }
            }
            if (hw == 2) {
                const uint32_t ep = __ldcg(&g_sync.epoch[0]) + 1;
                if (lane == 0) {
                    asm volatile("st.shared.u32 [%0], %1;" ::"r"(sb + SM_EP), "r"(ep) : "memory");
                    flag_wait(&g_sync.modcnt[0], NSPARE * ep);
                }
                __syncwarp();
#pragma unroll
                for (int i = 0; i < 4; i++) {
                    uint4 v = __ldcg(reinterpret_cast<const uint4*>(g_mod) + lane + 32 * i);
                    if (i >= 2) v = make_uint4(badd(v.x, ONE2), badd(v.y, ONE2), badd(v.z, ONE2), badd(v.w, ONE2));
                    sts128(sb + SM_TAB + i * 512 + lane * 16, v);
                }
                __syncwarp();
                if (lane == 0) mbar_arrive(sb + BAR_FLAG + 8 * 8);
                TS(42);
#pragma unroll 1
                for (int i = 0; i < 8; i++) {
                    if (lane == 0) mbar_wait(sb + BAR_DONE + 8 * (i == 7 ? 6 : i == 4 ? 3 : i), 0);
                    __syncwarp();
                    const uint32_t* f = i == 0 ? &g_sync.hcnt[(lane ? j : 15 - j) * 8]
                                      : i == 3 || i == 4 ? &g_sync.rdcnt[(grp * 2 + i - 3) * 8]
                                      : i == 7 ? &g_sync.modcnt[32] : &g_sync.kvcnt[(4 * grp + (i > 4 ? i - 3 : i - 1)) * 8];
                    if (lane < (i ? 1 : 2)) flag_wait(f, 8 * ep);
                    __syncwarp();
                    if (i == 7) {
                        const uint32_t *mp = reinterpret_cast<const uint32_t*>(g_mod) + lane, *wp = reinterpret_cast<const uint32_t*>(P.wr) + lane;
                        float ra = 0.f, rs = 0.f;
#pragma unroll 1
                        for (int k = 0; k < 256; k += 32) {
                            const uint32_t ga = __ldcg(mp + 512 + k), sh = __ldcg(mp + 768 + k), c1 = badd(__ldcg(mp + 1024 + k), ONE2);
                            const uint32_t gb = __ldcg(mp + 1280 + k), ww = __ldg(wp + k);
                            const float a0 = bf_lo(c1) * bf_lo(ww), a1 = bf_hi(c1) * bf_hi(ww);
                            ra += a0 + a1;
                            rs = fmaf(bf_lo(sh), bf_lo(ww), fmaf(bf_hi(sh), bf_hi(ww), rs));
                            if (k >> 6 == cq) {
                                sts128(sb + SM_TAB + ((k & 32) + lane) * 16, make_uint4(ga << 16, ga & 0xffff0000u, __float_as_uint(a0), __float_as_uint(a1)));
                                sts128(sb + SM_TAB + 1024 + ((k & 32) + lane) * 16, make_uint4(c1, sh, gb, 0));
                            }
                        }
                        *reinterpret_cast<float2*>(smem + SM_EP + 8) = make_float2(warp_sum(ra), warp_sum(rs));
                        __syncwarp();
                    }
                    if (lane == 0) mbar_arrive(sb + BAR_FLAG + 8 * i);
                    TS(48 + i);
                }
                const uint32_t* f = &g_sync.ctxcnt[ort * 32 + o_head(min(lane, 16), kh)];
                uint32_t ready = (MC & 8) && (j & 1) ? ~0u : 0u, list = 0, sh = 0, qa = sb + SM_EP + 4;
                if (MC & 8) asm("mapa.shared::cluster.u32 %0, %1, %2;" : "=r"(qa) : "r"(sb + SM_EP + 4), "r"(lane & 1));
                while (ready != ~0u) {
                    uint32_t v;
                    asm volatile("ld.acquire.gpu.global.u32 %0, [%1];" : "=r"(v) : "l"(f) : "memory");
                    const uint32_t now = __ballot_sync(0xffffffffu, (int)(v - ep) >= 0);
                    for (uint32_t fresh = now & ~ready & 0x7f00; fresh; fresh &= fresh - 1, sh += 4) list |= (__ffs(fresh) - 1) << sh;
                    list |= (((now & 0xff) + 1) >> 8 << 28) | ((now & 0x18000) << 14);
                    if (now != ready && lane < ((MC & 8) ? 2 : 1)) asm volatile("st.relaxed.cluster.shared::cluster.u32 [%0], %1;" ::"r"(qa), "r"(list) : "memory");
                    if ((now & 0xff) == 0xff) mbar_wait(sb + BAR_DONE + 8 * 7, 0);
                    ready = now;
                    __nanosleep(POLL_NS);
                }
                TS(45);
            }
        }
    } else {
        asm volatile("setmaxnreg.inc.sync.aligned.u32 232;");
        const bool elected = (tid & 127) == 0, rel = MC ? (tid & 95) == 0 : elected;
        uint32_t eb = sb + BAR_EMPTY;
        if (MC) asm("mapa.shared::cluster.u32 %0, %1, %2;" : "=r"(eb) : "r"(sb + BAR_EMPTY), "r"(warp & 1));
        const int g = lane >> 2, c4 = lane & 3;
        const uint32_t toff = warp * 4096 + g * 64 + ((c4 ^ (g >> 1)) << 4);
        uint32_t fph = 0, r = 0;
        if (wg == 1) bar_arrive(1, 256);
        const uint32_t kd = desc_k(sb), wd = desc_mn(sb), vd = ((sb & 0x3ffff) >> 4) | (32u << 16);
        const int nL = 16 - j, hn = nL - 1 + wg;
        float s[64], o[64], li[2] = {0.f, 0.f};
        uint8_t* cimg = g_ctx;
#pragma unroll 1
        for (int hp = 0; hp < 2; hp++) {
            {
                const int step = hp ? -8 * SLOT : 8 * SLOT;
                uint8_t* img = g_KV + (size_t)(grp * 32 + (hp ? j ^ 30 : j)) * SLOT - step;
                const float sc = (j & 1) ? 1.f : SM_C;
                const uint32_t wtab = w_table(hp);
                uint32_t atab = hp ? 0x256u : a_table(0);
#pragma unroll 1
                for (int t = 0; t < 6; t += 2) {
                    proj_tile<false>(s, o, t, t ? 0 : 2 * hp, sb, wg, eb, rel, fph, wtab, atab, t ? img : cimg, toff, t ? sc : li[0], t ? sc : li[1], (hp | t) == 0, P.x, rb * 16 + warp * 2);
                    __syncwarp();
                    mbar_arrive_if(sb + BAR_DONE + 4 * t + 32 * hp, lane == 0 && (hp | t) != 0);
                    if (elected) TS(1 + 10 * hp + t + 20 * wg);
                    proj_tile<true>(o, s, t + 1, 0, sb, wg, eb, rel, fph, wtab, atab, img + step, toff, sc, sc, (hp | t) == 0, P.x, rb * 16 + warp * 2);
                    if (elected) TS(2 + 10 * hp + t + 20 * wg);
                    img += 2 * step;
                }
            }
            float m[2] = {0.f, 0.f}, l[2] = {0.f, 0.f}, t[4] = {0.f, 0.f, 0.f, 0.f};
            bool shifted = false, bad = false, plain = false;
            uint32_t p[32];
#pragma unroll
            for (int i = 0; i < 32; i++) p[i] = 0;
            uint32_t qa = desc_k(sb + 5 * SLOT + (wg ^ 1) * 8192);
            uint8_t* img = g_ctx + (size_t)((15 - j) * 32 + 2 * grp + hp) * SLOT;
            slot_wait(sb + BAR_FULL, fph, r);
            int n = -1;
#pragma unroll 1
            for (;;) {
                while (bad || plain) {
                    if (bad) {
                        float a0, a1;
                        softmax_remax(s, m, n == 0 || n == nL, a0, a1);
                        shifted = true;
                        l[0] *= a0;
                        l[1] *= a1;
#pragma unroll
                        for (int i = 0; i < 64; i++) o[i] *= (i & 2) ? a1 : a0;
                    }
                    softmax_exp<0, 16>(s, p, t);
                    t[0] += t[1];
                    t[2] += t[3];
                    bad = !bad && softmax_unsafe(t[0], t[2], false);
                    plain = false;
                }
#pragma unroll 1
                do {
                    l[0] += t[0];
                    l[1] += t[2];
                    if (++n > 16) break;
                    const uint32_t ks = r;
                    uint32_t vs = ring_next(r);
                    r = ring_next(vs);
                    bar_sync(1 + wg, 256);
                    if (n == 0 || (uint32_t)(n + 1 - nL) <= (uint32_t)(1 + wg)) {
                        const int x = (warp & 3) * 16 + g - 2 * c4;
                        if (n == 0) {
                            r = vs;
                            vs = 4 - hp;
                            qk_issue(s, qa, kd + ks * (SLOT / 16));
                            slot_wait(sb + BAR_FULL, fph, 6);
                            gemm_issue<false>(o, qa + SLOT / 16, wd + vs * (SLOT / 16), 1, false);
                            bar_arrive(2 - wg, 256);
                            wg_wait<1>();
                            reg_fence(s);
                        } else if (n == hn) {
                            float sh[32];
                            qk_issue(sh, qa, kd + ks * (SLOT / 16));
                            slot_wait(sb + BAR_FULL, fph, vs);
                            pv_issue(o, p, vd + vs * (SLOT / 16), 1, false);
                            bar_arrive(2 - wg, 256);
                            wg_wait<1>();
                            reg_fence(sh);
                            tri_mask_copy(s, sh, x);
                        } else {
                            qk_issue(s, qa, kd + ks * (SLOT / 16));
                            slot_wait(sb + BAR_FULL, fph, vs);
                            pv_issue(o, p, vd + vs * (SLOT / 16), n != nL + 1, n == hn + 1);
                            bar_arrive(2 - wg, 256);
                            wg_wait<1>();
                            reg_fence(s);
                            if (n <= nL) tri_mask<32>(s, x);
                        }
                        release_if(eb, ks, rel);
                        release_if(eb, (n == 16 ? 6 : 5), rel && (n == 16 || n == nL - 1));
                        if (n == nL - 1) {
                            qa += SLOT / 16;
                            fence_async_smem();
                        }
                        if (shifted) {
                            if (n == nL) {
                                m[0] = m[1] = 0.f;
                                shifted = false;
                            }
                            softmax_shift(s, m[0], m[1]);
                        }
                        float e[4 * EARLY];
#pragma unroll
                        for (int i = 0; i < 4 * EARLY; i++) {
                            e[i] = ex2(s[i]);
                            t[i & 3] = i < 4 ? e[i] : t[i & 3] + e[i];
                        }
                        reg_fence(e);
                        slot_wait(sb + BAR_FULL, fph, r);
                        wg_wait<0>();
                        reg_fence(o);
                        reg_fence(e);
                        release_if(eb, vs, rel);
#pragma unroll
                        for (int i = 0; i < 2 * EARLY; i++) p[i] = pack2(e[2 * i], e[2 * i + 1]);
                        softmax_exp<EARLY, 8>(s, p, t);
                        if (n == 0) q_store<(PARKS & 1) != 0>(sb + 6 * SLOT, toff, o);
                        if (n == nL) {
                            ctx_store<(PARKS & 2) != 0>(img, toff, o, l[0], l[1]);
                            __syncwarp();
                            mbar_arrive_if(sb + BAR_DONE + 24 + 32 * hp, lane == 0);
                            l[0] = l[1] = 0.f;
                        }
                        if (n != hn) softmax_exp<8, 16>(s, p, t);
                        t[0] += t[1];
                        t[2] += t[3];
                        bad = softmax_unsafe(t[0], t[2], n == 0 || n == nL);
                        continue;
                    }
                    qk_issue(s, qa, kd + ks * (SLOT / 16));
                    slot_wait(sb + BAR_FULL, fph, vs);
                    pv_issue(o, p, vd + vs * (SLOT / 16), n != 1 && n != nL + 1, false);
                    bar_arrive(2 - wg, 256);
                    wg_wait<1>();
                    reg_fence(s);
                    release_if(eb, ks, rel);
                    release_if(eb, 6, rel && n == 16);
                    if (shifted) {
                        slot_wait(sb + BAR_FULL, fph, r);
                        wg_wait<0>();
                        reg_fence(o);
                        release_if(eb, vs, rel);
                        softmax_shift(s, m[0], m[1]);
                        plain = true;
                        break;
                    }
                    float e[4 * EARLY];
#pragma unroll
                    for (int i = 0; i < 4 * EARLY; i++) {
                        e[i] = ex2(s[i]);
                        t[i & 3] = i < 4 ? e[i] : t[i & 3] + e[i];
                    }
                    reg_fence(e);
                    slot_wait(sb + BAR_FULL, fph, r);
                    wg_wait<0>();
                    reg_fence(o);
                    reg_fence(e);
                    release_if(eb, vs, rel);
#pragma unroll
                    for (int i = 0; i < 2 * EARLY; i++) p[i] = pack2(e[2 * i], e[2 * i + 1]);
                    softmax_exp<EARLY, 16>(s, p, t);
                    t[0] += t[1];
                    t[2] += t[3];
                    bad = softmax_unsafe(t[0], t[2], false);
                } while (!bad);
                if (!bad && !plain) break;
            }
            const uint32_t vs = r, ga = desc_k(sb + (hp ? 2 * (wg ^ kh ^ 1) : wg) * 8192), as = 2 + 2 * hp;
            r = ring_next(r);
            slot_wait(sb + BAR_FULL, fph, 5);
            slot_wait(sb + BAR_FULL, fph, r);
            bar_sync(1 + wg, 256);
            gemm_issue<true>(s, ga + 5 * (SLOT / 16), wd + r * (SLOT / 16), 0, hp);
            pv_issue(o, p, vd + vs * (SLOT / 16), j, hn == 16);
            bar_arrive(2 - wg, 256);
            li[0] = rcp(quad_sum(l[0]));
            li[1] = rcp(quad_sum(l[1]));
            cimg = img + (ptrdiff_t)(2 * j - 15) * 32 * SLOT + (wg ? -16384 : 16384);
            wg_wait<1>();
            release_if(eb, 5, rel);
            release_if(eb, r, rel && hp);
            wg_wait<0>();
            release_if(eb, vs, rel);
            reg_fence(o);
            img_store_global<0>(cimg, toff, o, li[0], li[1]);
            slot_wait(sb + BAR_FULL, fph, as);
            slot_wait(sb + BAR_FULL, fph, 0);
            bar_sync(1 + wg, 256);
            gemm_issue<false>(s, ga + as * (SLOT / 16), wd, 1, hp);
            bar_arrive(2 - wg, 256);
            reg_fence(o);
            img_store_global<1>(cimg, toff, o, li[0], li[1]);
            wg_wait<0>();
            release_if(eb, as, rel);
            release_if(eb, 0, rel && hp);
            if (elected) TS(8 + 10 * hp + 20 * wg);
        }
        uint32_t otab = 0x0423516u;
        const uint32_t oa = desc_k(sb + (wg ^ kh ^ 1) * 16384);
        const int t7 = tid & 127, w4 = warp & 3, row = ort * 128 + kh * 64 + w4 * 16 + g;
#pragma unroll 1
        for (int i = 2; i < 15 - wg; i++) {
            const uint32_t as = o_next(otab), ws = o_next(otab);
            slot_wait(sb + BAR_FULL, fph, as);
            slot_wait(sb + BAR_FULL, fph, ws);
            bar_sync(1 + wg, 256);
            gemm_issue<false>(s, oa + as * (SLOT / 16), wd + ws * (SLOT / 16), 1, true);
            bar_arrive(2 - wg, 256);
            wg_wait<1>();
            reg_fence(o);
            if (i == 2) img_store_global<2>(cimg, toff, o, li[0], li[1]);
            if (i == CLAST) {
                img_store_global<3>(cimg, toff, o, li[0], li[1]);
                __syncwarp();
                mbar_arrive_if(sb + BAR_DONE + 64, lane == 0);
            }
            wg_wait<0>();
            release_if(eb, as, rel);
            release_if(eb, ws, rel);
        }
        mbar_wait(sb + BAR_PF, 0);
        const uint32_t ep = lds32(sb + SM_EP);
        if (wg == 0) {
            reg_fence(s);
            if (elected) TS(9);
#pragma unroll
            for (int v = 0; v < 8; v++)
                st_pub(g_out + rb * OB + v * 128 + t7, make_uint4((pack2(s[8 * v], s[8 * v + 1]) & ~1u) | (ep & 1), pack2(s[8 * v + 2], s[8 * v + 3]),
                                                                      pack2(s[8 * v + 4], s[8 * v + 5]), pack2(s[8 * v + 6], s[8 * v + 7])), true);
            o_next(otab); o_next(otab); o_next(otab); o_next(otab);
            const uint32_t s1 = o_next(otab), s2 = o_next(otab);
            bar_sync(4, 256);
            uint32_t wf[64];
            float wn[64];
            if (rb < NFFN) {
                slot_wait(sb + BAR_FULL, fph, s1);
                const uint32_t a = sb + s1 * SLOT + (w4 * 128 + (lane >> 4) * 8 + (lane & 7)) * 32 + ((lane >> 3) & 1) * 16;
#pragma unroll
                for (int i = 0; i < 16; i++)
                    asm volatile("ldmatrix.sync.aligned.m8n8.x4.trans.shared.b16 {%0, %1, %2, %3}, [%4];"
                                 : "=r"(wf[4 * i]), "=r"(wf[4 * i + 1]), "=r"(wf[4 * i + 2]), "=r"(wf[4 * i + 3])
                                 : "r"(a + (i >> 3) * 16384 + (i & 7) * 512) : "memory");
                slot_wait(sb + BAR_FULL, fph, s2);
#pragma unroll
                for (int i = 0; i < 16; i++) {
                    const uint2 w = *reinterpret_cast<const uint2*>(smem + s2 * SLOT + i * 1024 + t7 * 8);
                    wn[4 * i] = bf_lo(w.x); wn[4 * i + 1] = bf_hi(w.x); wn[4 * i + 2] = bf_lo(w.y); wn[4 * i + 3] = bf_hi(w.y);
                }
                reg_fence(wn);
            }
            const uint32_t gbf = __ldcg(reinterpret_cast<const uint32_t*>(g_mod) + 1280 + rb * 2 + (tid & 1));
            if (elected) TS(10);
            const uint32_t best = best_key(g_key + cq * 128, lane, ep);
            const int sel = (~best >> 5) & 2047;
            if (elected) TS(19);
            const uint4* cp = g_cand + (sel >> 4) * 192;
            float* sred = reinterpret_cast<float*>(smem + SM_RED);
            const int pq = (2 * rb + (tid & 1)) & 63, pv = (pq >> 2) / 3;
            const uint4* fp = cp + (rb >> 5) * 24 + pv * 4 + (pq & 3);
            uint4 fh = ld_poll(fp), fx = ld_poll(fp + 96);
            if (rb < NFFN) {
                uint4 cv[6];
                for (;;) {
                    uint32_t bad = 0;
#pragma unroll
                    for (int v = 0; v < 6; v++) cv[v] = ld_poll(cp + w4 * 24 + v * 4 + c4);
#pragma unroll
                    for (int v = 0; v < 6; v++) bad |= cv[v].w ^ ep;
                    if (__all_sync(0xffffffffu, bad == 0)) break;
                }
                if (elected) TS(20);
                float d[4][4] = {};
#pragma unroll
                for (int k = 0; k < 8; k++) {
                    const uint32_t b0 = (&cv[(2 * k) / 3].x)[(2 * k) % 3], b1 = (&cv[(2 * k + 1) / 3].x)[(2 * k + 1) % 3];
                    mma16816(d[k & 1], wf + 4 * k, b0, b1);
                    mma16816(d[2 + (k & 1)], wf + 32 + 4 * k, b0, b1);
                }
                const float u = (c4 & 2) ? ((c4 & 1) ? d[2][2] + d[3][2] : d[2][0] + d[3][0]) : ((c4 & 1) ? d[0][2] + d[1][2] : d[0][0] + d[1][0]);
                sred[w4 * 32 + c4 * 8 + g] = u;
                bar_sync(3, 128);
                const float v = rbf((sred[lane] + sred[32 + lane]) + (sred[64 + lane] + sred[96 + lane]));
                const float act = rbf(rbf(v * sigmoid(v)) * __shfl_down_sync(0xffffffffu, v, 16));
                float y[4] = {0.f, 0.f, 0.f, 0.f};
#pragma unroll
                for (int k = 0; k < 16; k++) {
                    const float a = __shfl_sync(0xffffffffu, act, k);
#pragma unroll
                    for (int i = 0; i < 4; i++) y[i] = fmaf(a, wn[4 * k + i], y[i]);
                }
                st_pub(g_out + rb * OB + OB_Y + t7, make_uint4((__float_as_uint(y[0]) & ~15u) | (ep & 15), __float_as_uint(y[1]), __float_as_uint(y[2]), __float_as_uint(y[3])), true);
            }
            if (rb == 0 && tid == 0) g_sync.epoch[0] = ep;
            if (elected) TS(60);
            uint4 yv;
            do yv = ld_poll(g_out + min(t7, NFFN - 1) * OB + OB_Y + rb);
            while (!__all_sync(0xffffffffu, ((yv.x ^ ep) & 15) == 0));
            if (elected) TS(61);
            float y[4] = {0.f, 0.f, 0.f, 0.f};
            if (t7 < NFFN) { y[0] = __uint_as_float(yv.x); y[1] = __uint_as_float(yv.y); y[2] = __uint_as_float(yv.z); y[3] = __uint_as_float(yv.w); }
            const float z0 = ((lane & 16) ? y[2] : y[0]) + __shfl_xor_sync(0xffffffffu, (lane & 16) ? y[0] : y[2], 16);
            const float z1 = ((lane & 16) ? y[3] : y[1]) + __shfl_xor_sync(0xffffffffu, (lane & 16) ? y[1] : y[3], 16);
            float z = ((lane & 8) ? z1 : z0) + __shfl_xor_sync(0xffffffffu, (lane & 8) ? z0 : z1, 8);
            z += __shfl_xor_sync(0xffffffffu, z, 4);
            z = quad_sum(z);
            if ((lane & 7) == 0) sred[128 + (lane >> 3) * 4 + w4] = z;
            bar_sync(3, 128);
            if (tid < 2) {
                while (fh.w != ep || fx.w != ep) { fh = ld_poll(fp); fx = ld_poll(fp + 96); }
                const float4 y0 = *reinterpret_cast<const float4*>(sred + 128 + tid * 8), y1 = *reinterpret_cast<const float4*>(sred + 132 + tid * 8);
                const int cm = (pq >> 2) - 3 * pv;
                const uint32_t h2 = cm == 0 ? fh.x : cm == 1 ? fh.y : fh.z, x2 = cm == 0 ? fx.x : cm == 1 ? fx.y : fx.z;
                const float sg = sigmoid(bf_hi((best & 0x80000000u) ? (best ^ 0x80000000u) : ~best));
                reinterpret_cast<uint32_t*>(P.out)[sel * 256 + rb * 2 + tid] =
                    badd(x2, bmul(gbf, badd(h2, bmul(pack2((y0.x + y0.y) + (y0.z + y0.w), (y1.x + y1.y) + (y1.z + y1.w)), pack2(sg, sg)))));
            }
            if (elected) TS(62);
        } else {
            const float4* tf = reinterpret_cast<const float4*>(smem + SM_TAB) + c4;
            const uint32_t as14 = otab & 15, xa = sb + ((otab >> 8) & 15) * SLOT + (kh ^ 1) * 16384 + (w4 * 16 + (lane & 15)) * 128;
            uint32_t x2[32];
            bar_sync(2, 256);
#pragma unroll 1
            for (int i = 14; i < 17; i++) {
                const uint32_t as = o_next(otab), ws = o_next(otab);
                slot_wait(sb + BAR_FULL, fph, as);
                slot_wait(sb + BAR_FULL, fph, ws);
                gemm_issue<false>(s, oa + as * (SLOT / 16), wd + ws * (SLOT / 16), 1, true);
                wg_wait<1>();
                release_if(eb, as14, rel && i == 15);
            }
            if (elected) TS(29);
            {
#pragma unroll
                for (int k = 0; k < 8; k++)
                    asm volatile("ldmatrix.sync.aligned.m8n8.x4.shared.b16 {%0, %1, %2, %3}, [%4];"
                                 : "=r"(x2[4 * k]), "=r"(x2[4 * k + 1]), "=r"(x2[4 * k + 2]), "=r"(x2[4 * k + 3])
                                 : "r"(xa + (k >> 2) * 8192 + (((2 * (k & 3) + (lane >> 4)) ^ (lane & 7)) << 4)) : "memory");
            }
            wg_wait<0>();
            reg_fence(s);
            bar_arrive(4, 256);
            if (elected) TS(39);
            const uint4* pr = g_out + (rb ^ 8) * OB + t7;
            uint4 pa[8];
#pragma unroll
            for (int v = 0; v < 8; v++) pa[v] = ld_poll(pr + v * 128);
            float4 tc[16];
#pragma unroll
            for (int k = 0; k < 16; k++) {
                tc[k] = tf[k * 4];
#pragma unroll
                for (int i = 4 * k; i < 4 * k + 4; i++) s[i] = fmaf((i & 1) ? tc[k].y : tc[k].x, s[i], (i & 1) ? bf_hi(x2[i >> 1]) : bf_lo(x2[i >> 1]));
            }
            reg_fence(s);
            for (;;) {
                uint32_t bad = 0;
#pragma unroll
                for (int v = 0; v < 8; v++) bad |= pa[v].x ^ ep;
                if (__all_sync(0xffffffffu, (bad & 1) == 0)) break;
#pragma unroll
                for (int v = 0; v < 8; v++) pa[v] = ld_poll(pr + v * 128);
            }
            if (elected) TS(30);
            float st[6] = {0.f, 0.f, 0.f, 0.f, 0.f, 0.f};
#pragma unroll
            for (int i = 0; i < 64; i++) {
                const int rh = (i >> 1) & 1;
                const uint32_t w = (&pa[i >> 3].x)[(i >> 1) & 3];
                const float v = fmaf((i & 1) ? tc[i >> 2].y : tc[i >> 2].x, (i & 1) ? bf_hi(w) : bf_lo(w), s[i]);
                s[i] = v;
                st[rh] += v;
                st[2 + rh] = fmaf(v, v, st[2 + rh]);
                st[4 + rh] = fmaf(v, (i & 1) ? tc[i >> 2].w : tc[i >> 2].z, st[4 + rh]);
            }
#pragma unroll
            for (int i = 0; i < 6; i++) st[i] = quad_sum(st[i]);
            st_pub(g_out + rb * OB + OB_STAT + (w4 * 8 + g) * 2 + (c4 & 1),
                   make_uint4(__float_as_uint((c4 & 1) ? st[1] : st[0]), __float_as_uint((c4 & 1) ? st[3] : st[2]),
                              __float_as_uint((c4 & 1) ? st[5] : st[4]), ep), c4 < 2);
            if (elected) TS(56);
            uint32_t cb[16], sh[16], gb[16];
#pragma unroll
            for (int i = 0; i < 16; i++) {
                const float4 c = tf[64 + i * 4];
                cb[i] = __float_as_uint(c.x); sh[i] = __float_as_uint(c.y); gb[i] = __float_as_uint(c.z);
            }
            const float ra = __uint_as_float(lds32(sb + SM_EP + 8)), rb0 = __uint_as_float(lds32(sb + SM_EP + 12));
#pragma unroll
            for (int i = 0; i < 32; i++) x2[i] = pack2(s[2 * i], s[2 * i + 1]);
            reg_fence(x2);
            uint4 r0, r1;
            for (;;) {
                r0 = ld_poll(g_out + ((rb & ~3) + c4) * OB + OB_STAT + (w4 * 8 + g) * 2);
                r1 = ld_poll(g_out + ((rb & ~3) + c4) * OB + OB_STAT + (w4 * 8 + g) * 2 + 1);
                if (__all_sync(0xffffffffu, r0.w == ep && r1.w == ep)) break;
            }
            if (elected) TS(57);
            const float m0 = quad_sum(__uint_as_float(r0.x)) * (1.f / 512.f), m1 = quad_sum(__uint_as_float(r1.x)) * (1.f / 512.f);
            const float rs0 = ln_rstd(fmaxf(fmaf(-m0, m0, quad_sum(__uint_as_float(r0.y)) * (1.f / 512.f)), 0.f));
            const float rs1 = ln_rstd(fmaxf(fmaf(-m1, m1, quad_sum(__uint_as_float(r1.y)) * (1.f / 512.f)), 0.f));
            const uint32_t mb0 = pack2(m0, m0), mb1 = pack2(m1, m1);
            const uint32_t lg = pack2(fmaf(rs0, fmaf(-bf_lo(mb0), ra, quad_sum(__uint_as_float(r0.z))), rb0),
                                      fmaf(rs1, fmaf(-bf_lo(mb1), ra, quad_sum(__uint_as_float(r1.z))), rb0));
            const uint32_t u0 = lg << 16, u1 = lg & 0xffff0000u;
            const uint32_t k0 = ((u0 ^ (((int)u0 >> 31) | 0x80000000u)) & 0xffff0000u) | ((2047 - row) << 5) | (ep & 31);
            const uint32_t k1 = ((u1 ^ (((int)u1 >> 31) | 0x80000000u)) & 0xffff0000u) | ((2039 - row) << 5) | (ep & 31);
            const uint32_t kb = __reduce_max_sync(0xffffffffu, max(k0, k1));
            st_pub(g_key + cq * 128 + (row >> 4), kb, lane == 0);
            {
                uint32_t cx[18], ch[18];
#pragma unroll
                for (int i = 0; i < 16; i++) {
                    cx[i] = kb == k1 ? x2[2 * i + 1] : x2[2 * i];
                    ch[i] = ln_apply(cx[i], kb == k1 ? mb1 : mb0, kb == k1 ? rs1 : rs0, cb[i], sh[i]);
                }
                cx[16] = cx[17] = ch[16] = ch[17] = 0;
                uint4* cp = g_cand + (row >> 4) * 192 + cq * 24 + c4;
#pragma unroll
                for (int v = 0; v < 6; v++) st_pub(cp + v * 4, make_uint4(ch[3 * v], ch[3 * v + 1], ch[3 * v + 2], ep), kb == k0 || kb == k1);
#pragma unroll
                for (int v = 0; v < 6; v++) st_pub(cp + 96 + v * 4, make_uint4(cx[3 * v], cx[3 * v + 1], cx[3 * v + 2], ep), kb == k0 || kb == k1);
            }
            if (elected) TS(58);
            uint2 ov[16];
#pragma unroll
            for (int i = 0; i < 16; i++) {
                const int rh = i & 1, jj = i & 14;
                const uint32_t v0 = badd(x2[2 * jj + rh], bmul(gb[jj], ln_apply(x2[2 * jj + rh], rh ? mb1 : mb0, rh ? rs1 : rs0, cb[jj], sh[jj])));
                const uint32_t v1 = badd(x2[2 * jj + 2 + rh], bmul(gb[jj + 1], ln_apply(x2[2 * jj + 2 + rh], rh ? mb1 : mb0, rh ? rs1 : rs0, cb[jj + 1], sh[jj + 1])));
                const uint32_t rv = __shfl_xor_sync(0xffffffffu, (c4 & 1) ? v0 : v1, 1);
                ov[i] = (c4 & 1) ? make_uint2(rv, v1) : make_uint2(v0, rv);
            }
            uint2* op = reinterpret_cast<uint2*>(P.out) + row * 128 + cq * 32 + (c4 & 1) * 2 + (c4 >> 1);
#pragma unroll
            for (int i = 0; i < 16; i++)
                if (kb != ((i & 1) ? k1 : k0)) op[(i & 1) * 1024 + (i & 14) * 2] = ov[i];
            const uint32_t best = best_key(g_key + cq * 128, lane, ep);
            if (best != kb) {
#pragma unroll
                for (int i = 0; i < 16; i++)
                    if (kb == ((i & 1) ? k1 : k0)) op[(i & 1) * 1024 + (i & 14) * 2] = ov[i];
            }
            if (elected) TS(59);
        }
        mbar_arrive_if(sb + BAR_END, lane == 0);
    }
}

typedef CUresult (*EncodeFn)(CUtensorMap*, CUtensorMapDataType, cuuint32_t, void*, const cuuint64_t*, const cuuint64_t*,
                             const cuuint32_t*, const cuuint32_t*, CUtensorMapInterleave, CUtensorMapSwizzle,
                             CUtensorMapL2promotion, CUtensorMapFloatOOBfill);

void make_2d(EncodeFn fn, CUtensorMap* m, const void* p, uint64_t cols, uint64_t rows, uint32_t bc, uint32_t br) {
    cuuint64_t dims[2] = {cols, rows}, strides[1] = {cols * 2};
    cuuint32_t box[2] = {bc, br}, es[2] = {1, 1};
    fn(m, CU_TENSOR_MAP_DATA_TYPE_BFLOAT16, 2, const_cast<void*>(p), dims, strides, box, es, CU_TENSOR_MAP_INTERLEAVE_NONE,
       CU_TENSOR_MAP_SWIZZLE_NONE, CU_TENSOR_MAP_L2_PROMOTION_L2_128B, CU_TENSOR_MAP_FLOAT_OOB_FILL_NONE);
}
void make_3d(EncodeFn fn, CUtensorMap* m, const void* p, uint64_t cols, uint64_t rows, uint32_t br = 128, uint32_t nb = 2) {
    cuuint64_t dims[3] = {64, rows, cols / 64}, strides[2] = {cols * 2, 128};
    cuuint32_t box[3] = {64, br, nb}, es[3] = {1, 1, 1};
    fn(m, CU_TENSOR_MAP_DATA_TYPE_BFLOAT16, 3, const_cast<void*>(p), dims, strides, box, es, CU_TENSOR_MAP_INTERLEAVE_NONE,
       CU_TENSOR_MAP_SWIZZLE_128B, CU_TENSOR_MAP_L2_PROMOTION_L2_256B, CU_TENSOR_MAP_FLOAT_OOB_FILL_NONE);
}

}

extern "C" void kernel_launch(void* const* d_in, const int* in_sizes, int n_in, void* d_out, int out_size) {
    static EncodeFn fn = nullptr;
    static int sms = 0;
    if (!fn) {
        void* f = nullptr;
        cudaDriverEntryPointQueryResult st;
        cudaGetDriverEntryPoint("cuTensorMapEncodeTiled", &f, cudaEnableDefault, &st);
        fn = (EncodeFn)f;
        int dev = 0;
        cudaGetDevice(&dev);
        cudaDeviceGetAttribute(&sms, cudaDevAttrMultiProcessorCount, dev);
        cudaFuncSetAttribute(fused_kernel, cudaFuncAttributeMaxDynamicSharedMemorySize, SMEM_BYTES);
    }
    CUtensorMap ckv, wq, wuk, wuv, wo, wg, wu, wm, xm;
    make_3d(fn, &ckv, d_in[1], 512, 2048, 128, (MC & 1) ? 1 : 2);
    make_3d(fn, &xm, d_in[0], 512, 2048, 64);
    make_3d(fn, &wq, d_in[2], 4096, 512, 128, (MC & 2) ? 1 : 2);
    make_3d(fn, &wuk, d_in[3], 4096, 512);
    make_3d(fn, &wuv, d_in[4], 4096, 512);
    make_3d(fn, &wo, d_in[5], 512, 4096);
    make_2d(fn, &wg, d_in[8], 1792, 512, 16, 256);
    make_2d(fn, &wu, d_in[9], 1792, 512, 16, 256);
    make_2d(fn, &wm, d_in[12], 3072, 512, 256, 64);
    Params p;
    p.x = (const bf16*)d_in[0];
    p.ckv = (const bf16*)d_in[1];
    p.wo = (const bf16*)d_in[5];
    p.wr = (const bf16*)d_in[7];
    p.wdown = (const bf16*)d_in[10];
    p.c = (const bf16*)d_in[11];
    p.out = (bf16*)d_out;
    p.by_smid = sms == NCTA + NSPARE;
    fused_kernel<<<NCTA + NSPARE, 384, SMEM_BYTES>>>(ckv, wq, wuk, wuv, wo, wg, wu, wm, xm, p);
}
```

```cpp
#include <cuda.h>
#include <cuda_bf16.h>
#include <cuda_runtime.h>
#include <stdint.h>
#include <stdio.h>

namespace {

typedef __nv_bfloat16 bf16;
typedef unsigned long long u64;

constexpr int NCTA = 128, NSPARE = 4;
constexpr int SLOT = 32768;
constexpr int SM_BAR = 7 * SLOT;
constexpr int BAR_FULL = SM_BAR;
constexpr int BAR_EMPTY = BAR_FULL + 8 * 7;
constexpr int BAR_DONE = BAR_EMPTY + 8 * 7;
constexpr int BAR_FLAG = BAR_DONE + 8 * 9;
constexpr int BAR_PF = BAR_FLAG + 8 * 9;
constexpr int BAR_END = BAR_PF + 8;
constexpr int SM_EP = BAR_END + 8;
constexpr int SM_RED = SM_BAR + 384;
constexpr int SM_TAB = SM_BAR + 1024;
constexpr int SMEM_BYTES = SM_BAR + 3072;
constexpr int NFFN = 112;
#define HINT 31
constexpr u64 L2_NORMAL = 0x1000000000000000ull, L2_FIRST = 0x12F0000000000000ull;
#define PF0 0
#define PFA 9
#define PFB 6
#define PFC 12
#define PFMASK 1023
#define UNR 4
#define POLL_NS 50
#define CLAST 2
#define OBINIT 1
#define MC 15
#define EARLY 7
constexpr uint32_t SPIN_LIMIT = 1u << 22;
constexpr uint32_t ONE2 = 0x3f803f80u;

struct Sync {
    uint32_t modcnt[2 * 32];
    uint32_t hcnt[16 * 8];
    uint32_t kvcnt[32 * 2 * 8];
    uint32_t ctxcnt[16 * 32];
    uint32_t rdcnt[16 * 2 * 8];
    uint32_t epoch[32];
};

__device__ __align__(1024) uint8_t g_KV[16 * 16 * 2 * SLOT];
__device__ __align__(1024) uint8_t g_ctx[16 * 32 * SLOT];
__device__ __align__(1024) uint8_t g_h[16 * 4 * SLOT];
constexpr int OB = 1216, OB_STAT = 1024, OB_Y = 1088;
__device__ __align__(1024) uint4 g_out[128 * OB];
__device__ __align__(1024) bf16 g_mod[3072];
__device__ __align__(1024) uint4 g_cand[128 * 192];
__device__ __align__(1024) uint32_t g_key[4 * 128];
__device__ __align__(1024) uint8_t g_wf[NFFN * SLOT];
__device__ __align__(1024) Sync g_sync;
#define TS(i)

#define PT()

struct Params {
    const bf16 *x, *ckv, *wo, *wr, *wdown, *c;
    bf16* out;
    int by_smid;
};

__device__ __forceinline__ void mbar_init(uint32_t bar, uint32_t cnt) {
    asm volatile("mbarrier.init.shared::cta.b64 [%0], %1;" ::"r"(bar), "r"(cnt) : "memory");
}
__device__ __forceinline__ void mbar_wait(uint32_t bar, uint32_t parity) {
    asm volatile("{\n.reg .pred p;\nL_%=:\nmbarrier.try_wait.parity.shared::cta.b64 p, [%0], %1;\n@!p bra L_%=;\n}" ::"r"(bar), "r"(parity) : "memory");
}
__device__ __forceinline__ void mbar_watch(uint32_t bar, uint32_t parity) {
    asm volatile("{\n.reg .pred p;\n.reg .u32 n;\nmov.u32 n, 0;\n"
                 "L_%=:\nmbarrier.try_wait.parity.shared::cta.b64 p, [%0], %1;\n@p bra D_%=;\n"
                 "add.u32 n, n, 1;\nsetp.lt.u32 p, n, %2;\n@p bra L_%=;\ntrap;\nD_%=:\n}"
                 ::"r"(bar), "r"(parity), "n"(SPIN_LIMIT) : "memory");
}
__device__ __forceinline__ void step_watch(uint32_t a, uint32_t step) {
    asm volatile("{\n.reg .pred p;\n.reg .u32 n, v;\nmov.u32 n, 0;\n"
                 "L_%=:\nld.volatile.shared.u32 v, [%0];\nsetp.ge.u32 p, v, %1;\n@p bra D_%=;\nnanosleep.u32 200;\n"
                 "add.u32 n, n, 1;\nsetp.lt.u32 p, n, %2;\n@p bra L_%=;\ntrap;\nD_%=:\n}"
                 ::"r"(a), "r"(step), "n"(SPIN_LIMIT) : "memory");
}
__device__ __forceinline__ void mbar_arrive(uint32_t bar) {
    asm volatile("mbarrier.arrive.shared::cta.b64 _, [%0];" ::"r"(bar) : "memory");
}
__device__ __forceinline__ void mbar_arrive_if(uint32_t bar, bool on) {
    asm volatile("{\n.reg .pred p;\nsetp.ne.s32 p, %1, 0;\n@p mbarrier.arrive.shared::cta.b64 _, [%0];\n}" ::"r"(bar), "r"((int)on) : "memory");
}
__device__ __forceinline__ void mbar_expect(uint32_t bar, uint32_t bytes) {
    asm volatile("mbarrier.arrive.expect_tx.shared::cta.b64 _, [%0], %1;" ::"r"(bar), "r"(bytes) : "memory");
}
__device__ __forceinline__ void tma2d(uint32_t dst, const CUtensorMap* m, int c0, int c1, uint32_t bar) {
    asm volatile("cp.async.bulk.tensor.2d.shared::cluster.global.mbarrier::complete_tx::bytes [%0], [%1, {%3, %4}], [%2];"
                 ::"r"(dst), "l"(m), "r"(bar), "r"(c0), "r"(c1) : "memory");
}
__device__ __forceinline__ void tma3d_prefetch(const CUtensorMap* m, int row, int cb) {
    asm volatile("cp.async.bulk.prefetch.tensor.3d.L2.global [%0, {%1, %2, %3}];" ::"l"(m), "r"(0), "r"(row), "r"(cb) : "memory");
}
__device__ __forceinline__ void l2_prefetch(const void* p, uint32_t bytes) {
    asm volatile("cp.async.bulk.prefetch.L2.global [%0], %1;" ::"l"(p), "r"(bytes) : "memory");
}
__device__ __forceinline__ void flag_wait(const uint32_t* f, uint32_t target) {
    asm volatile("{\n.reg .pred p;\n.reg .u32 v;\n"
                 "L_%=:\nld.acquire.gpu.global.u32 v, [%0];\nsub.u32 v, v, %1;\nsetp.lt.s32 p, v, 0;\n@p nanosleep.u32 100;\n@p bra L_%=;\n}"
                 ::"l"(f), "r"(target) : "memory");
}
__device__ __forceinline__ uint4 ld_poll(const uint4* p) {
    uint4 v;
    asm volatile("{\n.reg .b128 t;\nld.relaxed.gpu.global.b128 t, [%4];\nmov.b128 {%0, %1, %2, %3}, t;\n}"
                 : "=r"(v.x), "=r"(v.y), "=r"(v.z), "=r"(v.w) : "l"(p) : "memory");
    return v;
}
__device__ __forceinline__ void st_pub(uint4* p, uint4 v, bool on) {
    asm volatile("{\n.reg .pred p;\n.reg .b128 t;\nsetp.ne.s32 p, %5, 0;\nmov.b128 t, {%1, %2, %3, %4};\n@p st.relaxed.gpu.global.b128 [%0], t;\n}"
                 ::"l"(p), "r"(v.x), "r"(v.y), "r"(v.z), "r"(v.w), "r"((int)on) : "memory");
}
__device__ __forceinline__ void st_pub(uint32_t* p, uint32_t v, bool on) {
    asm volatile("{\n.reg .pred p;\nsetp.ne.s32 p, %2, 0;\n@p st.relaxed.gpu.global.u32 [%0], %1;\n}" ::"l"(p), "r"(v), "r"((int)on) : "memory");
}
__device__ __forceinline__ void flag_add(uint32_t* p) {
    asm volatile("red.release.gpu.global.add.u32 [%0], 1;" ::"l"(p) : "memory");
}
__device__ __forceinline__ uint32_t lds32(uint32_t a) {
    uint32_t v;
    asm volatile("ld.shared.u32 %0, [%1];" : "=r"(v) : "r"(a) : "memory");
    return v;
}
__device__ __forceinline__ uint4 lds128(uint32_t a) {
    uint4 v;
    asm volatile("ld.shared.v4.u32 {%0, %1, %2, %3}, [%4];" : "=r"(v.x), "=r"(v.y), "=r"(v.z), "=r"(v.w) : "r"(a) : "memory");
    return v;
}
__device__ __forceinline__ void fence_async_global() { asm volatile("fence.proxy.async.global;" ::: "memory"); }
__device__ __forceinline__ void fence_async_smem() { asm volatile("fence.proxy.async.shared::cta;" ::: "memory"); }
__device__ __forceinline__ void bar_sync(int id, int n) { asm volatile("bar.sync %0, %1;" ::"r"(id), "r"(n) : "memory"); }
__device__ __forceinline__ void bar_arrive(int id, int n) { asm volatile("bar.arrive %0, %1;" ::"r"(id), "r"(n) : "memory"); }
__device__ __forceinline__ void wg_fence() { asm volatile("wgmma.fence.sync.aligned;" ::: "memory"); }
__device__ __forceinline__ void wg_commit() { asm volatile("wgmma.commit_group.sync.aligned;" ::: "memory"); }
template <int N> __device__ __forceinline__ void wg_wait() { asm volatile("wgmma.wait_group.sync.aligned %0;" ::"n"(N) : "memory"); }
template <int N> __device__ __forceinline__ void reg_fence(float (&d)[N]) {
#pragma unroll
    for (int i = 0; i < N; i++) asm volatile("" : "+f"(d[i])::"memory");
}
template <int N> __device__ __forceinline__ void reg_fence(uint32_t (&d)[N]) {
#pragma unroll
    for (int i = 0; i < N; i++) asm volatile("" : "+r"(d[i])::"memory");
}
__device__ __forceinline__ uint32_t desc_k(uint32_t a) { return ((a & 0x3ffff) >> 4) | (1u << 16); }
__device__ __forceinline__ uint32_t desc_mn(uint32_t a) { return ((a & 0x3ffff) >> 4) | (1024u << 16); }

template <int TB>
__device__ __forceinline__ void wgmma_ss128(float (&d)[64], uint32_t da, uint32_t db, int acc, uint32_t ha = 0x40000040u, uint32_t hb = 0x40000040u) {
    asm volatile("{\n.reg .pred p;\n.reg .b64 a, b;\nsetp.ne.b32 p, %66, 0;\nmov.b64 a, {%64, %68};\nmov.b64 b, {%65, %69};\n"
        "wgmma.mma_async.sync.aligned.m64n128k16.f32.bf16.bf16 {%0, %1, %2, %3, %4, %5, %6, %7, %8, %9, %10, %11, %12, %13, %14, %15, %16, %17, %18, %19, %20, %21, %22, %23, %24, %25, %26, %27, %28, %29, %30, %31, %32, %33, %34, %35, %36, %37, %38, %39, %40, %41, %42, %43, %44, %45, %46, %47, %48, %49, %50, %51, %52, %53, %54, %55, %56, %57, %58, %59, %60, %61, %62, %63}, a, b, p, 1, 1, 0, %67;\n}"
        : "+f"(d[0]), "+f"(d[1]), "+f"(d[2]), "+f"(d[3]), "+f"(d[4]), "+f"(d[5]), "+f"(d[6]), "+f"(d[7]), "+f"(d[8]), "+f"(d[9]), "+f"(d[10]), "+f"(d[11]), "+f"(d[12]), "+f"(d[13]), "+f"(d[14]), "+f"(d[15]), "+f"(d[16]), "+f"(d[17]), "+f"(d[18]), "+f"(d[19]), "+f"(d[20]), "+f"(d[21]), "+f"(d[22]), "+f"(d[23]), "+f"(d[24]), "+f"(d[25]), "+f"(d[26]), "+f"(d[27]), "+f"(d[28]), "+f"(d[29]), "+f"(d[30]), "+f"(d[31]), "+f"(d[32]), "+f"(d[33]), "+f"(d[34]), "+f"(d[35]), "+f"(d[36]), "+f"(d[37]), "+f"(d[38]), "+f"(d[39]), "+f"(d[40]), "+f"(d[41]), "+f"(d[42]), "+f"(d[43]), "+f"(d[44]), "+f"(d[45]), "+f"(d[46]), "+f"(d[47]), "+f"(d[48]), "+f"(d[49]), "+f"(d[50]), "+f"(d[51]), "+f"(d[52]), "+f"(d[53]), "+f"(d[54]), "+f"(d[55]), "+f"(d[56]), "+f"(d[57]), "+f"(d[58]), "+f"(d[59]), "+f"(d[60]), "+f"(d[61]), "+f"(d[62]), "+f"(d[63])
        : "r"(da), "r"(db), "r"(acc), "n"(TB), "r"(ha), "r"(hb));
}
template <int TB>
__device__ __forceinline__ void wgmma_ss128_init(float (&d)[64], uint32_t da, uint32_t db, uint32_t ha = 0x40000040u, uint32_t hb = 0x40000040u) {
    asm volatile("{\n.reg .pred p;\n.reg .b64 a, b;\nsetp.ne.b32 p, 0, 0;\nmov.b64 a, {%64, %67};\nmov.b64 b, {%65, %68};\n"
        "wgmma.mma_async.sync.aligned.m64n128k16.f32.bf16.bf16 {%0, %1, %2, %3, %4, %5, %6, %7, %8, %9, %10, %11, %12, %13, %14, %15, %16, %17, %18, %19, %20, %21, %22, %23, %24, %25, %26, %27, %28, %29, %30, %31, %32, %33, %34, %35, %36, %37, %38, %39, %40, %41, %42, %43, %44, %45, %46, %47, %48, %49, %50, %51, %52, %53, %54, %55, %56, %57, %58, %59, %60, %61, %62, %63}, a, b, p, 1, 1, 0, %66;\n}"
        : "=f"(d[0]), "=f"(d[1]), "=f"(d[2]), "=f"(d[3]), "=f"(d[4]), "=f"(d[5]), "=f"(d[6]), "=f"(d[7]), "=f"(d[8]), "=f"(d[9]), "=f"(d[10]), "=f"(d[11]), "=f"(d[12]), "=f"(d[13]), "=f"(d[14]), "=f"(d[15]), "=f"(d[16]), "=f"(d[17]), "=f"(d[18]), "=f"(d[19]), "=f"(d[20]), "=f"(d[21]), "=f"(d[22]), "=f"(d[23]), "=f"(d[24]), "=f"(d[25]), "=f"(d[26]), "=f"(d[27]), "=f"(d[28]), "=f"(d[29]), "=f"(d[30]), "=f"(d[31]), "=f"(d[32]), "=f"(d[33]), "=f"(d[34]), "=f"(d[35]), "=f"(d[36]), "=f"(d[37]), "=f"(d[38]), "=f"(d[39]), "=f"(d[40]), "=f"(d[41]), "=f"(d[42]), "=f"(d[43]), "=f"(d[44]), "=f"(d[45]), "=f"(d[46]), "=f"(d[47]), "=f"(d[48]), "=f"(d[49]), "=f"(d[50]), "=f"(d[51]), "=f"(d[52]), "=f"(d[53]), "=f"(d[54]), "=f"(d[55]), "=f"(d[56]), "=f"(d[57]), "=f"(d[58]), "=f"(d[59]), "=f"(d[60]), "=f"(d[61]), "=f"(d[62]), "=f"(d[63])
        : "r"(da), "r"(db), "n"(TB), "r"(ha), "r"(hb));
}
template <int TB>
__device__ __forceinline__ void wgmma_ss64(float (&d)[32], uint32_t da, uint32_t db, int acc, uint32_t ha = 0x40000040u, uint32_t hb = 0x40000040u) {
    asm volatile("{\n.reg .pred p;\n.reg .b64 a, b;\nsetp.ne.b32 p, %34, 0;\nmov.b64 a, {%32, %36};\nmov.b64 b, {%33, %37};\n"
        "wgmma.mma_async.sync.aligned.m64n64k16.f32.bf16.bf16 {%0, %1, %2, %3, %4, %5, %6, %7, %8, %9, %10, %11, %12, %13, %14, %15, %16, %17, %18, %19, %20, %21, %22, %23, %24, %25, %26, %27, %28, %29, %30, %31}, a, b, p, 1, 1, 0, %35;\n}"
        : "+f"(d[0]), "+f"(d[1]), "+f"(d[2]), "+f"(d[3]), "+f"(d[4]), "+f"(d[5]), "+f"(d[6]), "+f"(d[7]), "+f"(d[8]), "+f"(d[9]), "+f"(d[10]), "+f"(d[11]), "+f"(d[12]), "+f"(d[13]), "+f"(d[14]), "+f"(d[15]), "+f"(d[16]), "+f"(d[17]), "+f"(d[18]), "+f"(d[19]), "+f"(d[20]), "+f"(d[21]), "+f"(d[22]), "+f"(d[23]), "+f"(d[24]), "+f"(d[25]), "+f"(d[26]), "+f"(d[27]), "+f"(d[28]), "+f"(d[29]), "+f"(d[30]), "+f"(d[31])
        : "r"(da), "r"(db), "r"(acc), "n"(TB), "r"(ha), "r"(hb));
}
template <int TB>
__device__ __forceinline__ void wgmma_ss64_init(float (&d)[32], uint32_t da, uint32_t db, uint32_t ha = 0x40000040u, uint32_t hb = 0x40000040u) {
    asm volatile("{\n.reg .pred p;\n.reg .b64 a, b;\nsetp.ne.b32 p, 0, 0;\nmov.b64 a, {%32, %35};\nmov.b64 b, {%33, %36};\n"
        "wgmma.mma_async.sync.aligned.m64n64k16.f32.bf16.bf16 {%0, %1, %2, %3, %4, %5, %6, %7, %8, %9, %10, %11, %12, %13, %14, %15, %16, %17, %18, %19, %20, %21, %22, %23, %24, %25, %26, %27, %28, %29, %30, %31}, a, b, p, 1, 1, 0, %34;\n}"
        : "=f"(d[0]), "=f"(d[1]), "=f"(d[2]), "=f"(d[3]), "=f"(d[4]), "=f"(d[5]), "=f"(d[6]), "=f"(d[7]), "=f"(d[8]), "=f"(d[9]), "=f"(d[10]), "=f"(d[11]), "=f"(d[12]), "=f"(d[13]), "=f"(d[14]), "=f"(d[15]), "=f"(d[16]), "=f"(d[17]), "=f"(d[18]), "=f"(d[19]), "=f"(d[20]), "=f"(d[21]), "=f"(d[22]), "=f"(d[23]), "=f"(d[24]), "=f"(d[25]), "=f"(d[26]), "=f"(d[27]), "=f"(d[28]), "=f"(d[29]), "=f"(d[30]), "=f"(d[31])
        : "r"(da), "r"(db), "n"(TB), "r"(ha), "r"(hb));
}
__device__ __forceinline__ void wgmma_rs128(float (&d)[64], uint32_t a0, uint32_t a1, uint32_t a2, uint32_t a3, uint32_t db, int acc, uint32_t hb = 0x40000040u) {
    asm volatile("{\n.reg .pred p;\n.reg .b64 b;\nsetp.ne.b32 p, %69, 0;\nmov.b64 b, {%68, %70};\n"
        "wgmma.mma_async.sync.aligned.m64n128k16.f32.bf16.bf16 {%0, %1, %2, %3, %4, %5, %6, %7, %8, %9, %10, %11, %12, %13, %14, %15, %16, %17, %18, %19, %20, %21, %22, %23, %24, %25, %26, %27, %28, %29, %30, %31, %32, %33, %34, %35, %36, %37, %38, %39, %40, %41, %42, %43, %44, %45, %46, %47, %48, %49, %50, %51, %52, %53, %54, %55, %56, %57, %58, %59, %60, %61, %62, %63}, {%64, %65, %66, %67}, b, p, 1, 1, 1;\n}"
        : "+f"(d[0]), "+f"(d[1]), "+f"(d[2]), "+f"(d[3]), "+f"(d[4]), "+f"(d[5]), "+f"(d[6]), "+f"(d[7]), "+f"(d[8]), "+f"(d[9]), "+f"(d[10]), "+f"(d[11]), "+f"(d[12]), "+f"(d[13]), "+f"(d[14]), "+f"(d[15]), "+f"(d[16]), "+f"(d[17]), "+f"(d[18]), "+f"(d[19]), "+f"(d[20]), "+f"(d[21]), "+f"(d[22]), "+f"(d[23]), "+f"(d[24]), "+f"(d[25]), "+f"(d[26]), "+f"(d[27]), "+f"(d[28]), "+f"(d[29]), "+f"(d[30]), "+f"(d[31]), "+f"(d[32]), "+f"(d[33]), "+f"(d[34]), "+f"(d[35]), "+f"(d[36]), "+f"(d[37]), "+f"(d[38]), "+f"(d[39]), "+f"(d[40]), "+f"(d[41]), "+f"(d[42]), "+f"(d[43]), "+f"(d[44]), "+f"(d[45]), "+f"(d[46]), "+f"(d[47]), "+f"(d[48]), "+f"(d[49]), "+f"(d[50]), "+f"(d[51]), "+f"(d[52]), "+f"(d[53]), "+f"(d[54]), "+f"(d[55]), "+f"(d[56]), "+f"(d[57]), "+f"(d[58]), "+f"(d[59]), "+f"(d[60]), "+f"(d[61]), "+f"(d[62]), "+f"(d[63])
        : "r"(a0), "r"(a1), "r"(a2), "r"(a3), "r"(db), "r"(acc), "r"(hb));
}

__device__ __forceinline__ uint32_t pack2(float lo, float hi) {
    uint32_t r;
    asm("cvt.rn.bf16x2.f32 %0, %1, %2;" : "=r"(r) : "f"(hi), "f"(lo));
    return r;
}
__device__ __forceinline__ float bf_lo(uint32_t v) { return __uint_as_float(v << 16); }
__device__ __forceinline__ float bf_hi(uint32_t v) { return __uint_as_float(v & 0xffff0000u); }
__device__ __forceinline__ float rbf(float v) { return bf_lo(pack2(v, v)); }
__device__ __forceinline__ uint32_t badd(uint32_t a, uint32_t b) {
    uint32_t r;
    asm("add.rn.bf16x2 %0, %1, %2;" : "=r"(r) : "r"(a), "r"(b));
    return r;
}
__device__ __forceinline__ uint32_t bsub(uint32_t a, uint32_t b) {
    uint32_t r;
    asm("sub.rn.bf16x2 %0, %1, %2;" : "=r"(r) : "r"(a), "r"(b));
    return r;
}
__device__ __forceinline__ uint32_t bmul(uint32_t a, uint32_t b) {
    uint32_t r;
    asm("mul.rn.bf16x2 %0, %1, %2;" : "=r"(r) : "r"(a), "r"(b));
    return r;
}
__device__ __forceinline__ uint32_t ln_apply(uint32_t x, uint32_t mb, float rs, uint32_t scale, uint32_t shift) {
    const uint32_t d = bsub(x, mb);
    return badd(bmul(pack2(bf_lo(d) * rs, bf_hi(d) * rs), scale), shift);
}
__device__ __forceinline__ float ex2(float v) {
    float r;
    asm("ex2.approx.ftz.f32 %0, %1;" : "=f"(r) : "f"(v));
    return r;
}
__device__ __forceinline__ float rcp(float v) {
    float r;
    asm("rcp.approx.ftz.f32 %0, %1;" : "=f"(r) : "f"(v));
    return r;
}
__device__ __forceinline__ float sqrt_fast(float v) {
    float r;
    asm("sqrt.approx.ftz.f32 %0, %1;" : "=f"(r) : "f"(v));
    return r;
}
__device__ __forceinline__ float ln_rstd(float var) { return rcp(rbf(sqrt_fast(rbf(rbf(var) + 1e-5f)))); }
__device__ __forceinline__ float sigmoid(float v) { return rcp(1.f + ex2(-1.4426950408889634f * v)); }
__device__ __forceinline__ float warp_sum(float v) {
#pragma unroll
    for (int o = 16; o > 0; o >>= 1) v += __shfl_xor_sync(0xffffffffu, v, o);
    return v;
}
__device__ __forceinline__ float quad_sum(float v) {
    v += __shfl_xor_sync(0xffffffffu, v, 1);
    return v + __shfl_xor_sync(0xffffffffu, v, 2);
}

constexpr uint32_t HI_128 = 0x40000040u, HI_IMG = 0x80000080u, HI_Q = 0x80000040u;
template <int M, int RH>
__device__ __forceinline__ uint4 img_pack(const float (&d)[64], float s) {
    uint4 v;
    v.x = pack2(d[16 * M + 2 * RH] * s, d[16 * M + 2 * RH + 1] * s);
    v.y = pack2(d[16 * M + 4 + 2 * RH] * s, d[16 * M + 5 + 2 * RH] * s);
    v.z = pack2(d[16 * M + 8 + 2 * RH] * s, d[16 * M + 9 + 2 * RH] * s);
    v.w = pack2(d[16 * M + 12 + 2 * RH] * s, d[16 * M + 13 + 2 * RH] * s);
    return v;
}
template <int M, int RH>
__device__ __forceinline__ uint4 img_pack(const float (&d)[64]) {
    uint4 v;
    v.x = pack2(d[16 * M + 2 * RH], d[16 * M + 2 * RH + 1]);
    v.y = pack2(d[16 * M + 4 + 2 * RH], d[16 * M + 5 + 2 * RH]);
    v.z = pack2(d[16 * M + 8 + 2 * RH], d[16 * M + 9 + 2 * RH]);
    v.w = pack2(d[16 * M + 12 + 2 * RH], d[16 * M + 13 + 2 * RH]);
    return v;
}
template <int M>
__device__ __forceinline__ void img_store_global(uint8_t* img, uint32_t toff, const float (&d)[64], float s0, float s1) {
    uint4* p = reinterpret_cast<uint4*>(img + toff) + M * 32;
    p[0] = img_pack<M, 0>(d, s0);
    p[128] = img_pack<M, 1>(d, s1);
}
__device__ __forceinline__ void sts128(uint32_t a, uint4 v) {
    asm volatile("st.shared.v4.b32 [%0], {%1, %2, %3, %4};" ::"r"(a), "r"(v.x), "r"(v.y), "r"(v.z), "r"(v.w) : "memory");
}
constexpr float SM_C = 0.08838834764831845f * 1.4426950408889634f;
__device__ __forceinline__ float pack2f(float lo, float hi) {
    float r;
    asm("{\n.reg .b32 t;\ncvt.rn.bf16x2.f32 t, %1, %2;\nmov.b32 %0, t;\n}" : "=f"(r) : "f"(hi), "f"(lo));
    return r;
}
template <int M, bool SCALE, bool PARK>
__device__ __forceinline__ void pack_group(float (&d)[64], float (&v)[8], float s0, float s1) {
#pragma unroll
    for (int i = 0; i < 8; i++) {
        const int k = 16 * M + 4 * (i & 3) + 2 * (i >> 2);
        v[i] = SCALE ? pack2f(d[k] * (i < 4 ? s0 : s1), d[k + 1] * (i < 4 ? s0 : s1)) : pack2f(d[k], d[k + 1]);
        if (PARK && M > 0) d[16 * (M > 0 ? M - 1 : 0) + i] = v[i];
    }
}
template <int M, bool PARK>
__device__ __forceinline__ void q_store_part(uint32_t a, float (&d)[64]) {
    float v[8];
    pack_group<M, false, PARK>(d, v, 0.f, 0.f);
#pragma unroll
    for (int h = 0; h < 2; h++)
        asm volatile("st.shared.v4.f32 [%0], {%1, %2, %3, %4};" ::"r"(a + (M >> 1) * 16384 + (M & 1) * 512 + h * 1024),
                     "f"(v[4 * h]), "f"(v[4 * h + 1]), "f"(v[4 * h + 2]), "f"(v[4 * h + 3]) : "memory");
}
template <bool PARK>
__device__ __forceinline__ void q_store(uint32_t a, uint32_t toff, float (&d)[64]) {
    a += (((toff >> 1) & ~2047u) ^ 8192) + (toff & 511);
    q_store_part<0, PARK>(a, d); q_store_part<1, PARK>(a, d); q_store_part<2, PARK>(a, d); q_store_part<3, PARK>(a, d);
}
template <int M, bool PARK>
__device__ __forceinline__ void ctx_store_part(float4* p, float (&d)[64], float i0, float i1) {
    float v[8];
    pack_group<M, true, PARK>(d, v, i0, i1);
    p[M * 32] = make_float4(v[0], v[1], v[2], v[3]);
    p[M * 32 + 128] = make_float4(v[4], v[5], v[6], v[7]);
}
template <bool PARK>
__device__ __forceinline__ void ctx_store(uint8_t* img, uint32_t toff, float (&o)[64], float l0, float l1) {
    const float i0 = rcp(quad_sum(l0)), i1 = rcp(quad_sum(l1));
    float4* p = reinterpret_cast<float4*>(img + toff);
    ctx_store_part<0, PARK>(p, o, i0, i1); ctx_store_part<1, PARK>(p, o, i0, i1); ctx_store_part<2, PARK>(p, o, i0, i1); ctx_store_part<3, PARK>(p, o, i0, i1);
}

template <int M>
__device__ __forceinline__ void tile_store_part(float4* p, uint32_t a, float (&d)[64], float i0, float i1, int ctx) {
    float v[8];
    pack_group<M, true, true>(d, v, i0, i1);
#pragma unroll
    for (int h = 0; h < 2; h++)
        asm volatile("{\n.reg .pred p;\nsetp.ne.s32 p, %6, 0;\n@p st.global.v4.f32 [%0], {%2, %3, %4, %5};\n@!p st.shared.v4.f32 [%1], {%2, %3, %4, %5};\n}"
                     ::"l"(p + M * 32 + h * 128), "r"(a + (M >> 1) * 16384 + (M & 1) * 512 + h * 1024),
                     "f"(v[4 * h]), "f"(v[4 * h + 1]), "f"(v[4 * h + 2]), "f"(v[4 * h + 3]), "r"(ctx) : "memory");
}
__device__ __forceinline__ void tile_store(uint8_t* img, uint32_t a, uint32_t toff, float (&d)[64], float i0, float i1, int ctx) {
    float4* p = reinterpret_cast<float4*>(img + toff);
    a += (((toff >> 1) & ~2047u) ^ 8192) + (toff & 511);
    tile_store_part<0>(p, a, d, i0, i1, ctx); tile_store_part<1>(p, a, d, i0, i1, ctx);
    tile_store_part<2>(p, a, d, i0, i1, ctx); tile_store_part<3>(p, a, d, i0, i1, ctx);
}

__device__ __forceinline__ void slot_wait(uint32_t bars, uint32_t& ph, uint32_t slot) {
    mbar_wait(bars + 8 * slot, (ph >> slot) & 1);
    ph ^= 1u << slot;
}
__device__ __forceinline__ void release_if(uint32_t eb, uint32_t slot, bool on) {
    asm volatile("{\n.reg .pred p;\nsetp.ne.s32 p, %1, 0;\n@p mbarrier.arrive.shared::cluster.b64 _, [%0];\n}" ::"r"(eb + 8 * slot), "r"((int)on) : "memory");
}
__device__ __forceinline__ void load_image_mc(uint32_t sb, uint32_t& ph, uint32_t slot, const uint8_t* src, int rank, bool first) {
    slot_wait(sb + BAR_EMPTY, ph, slot);
    asm volatile("{\n.reg .pred p;\nelect.sync _|p, 0xffffffff;\n@p mbarrier.arrive.expect_tx.shared::cta.b64 _, [%2], 32768;\n"
                 "@p cp.async.bulk.shared::cluster.global.mbarrier::complete_tx::bytes.multicast::cluster.L2::cache_hint [%0], [%1], 16384, [%2], %4, %3;\n}"
                 ::"r"(sb + slot * SLOT + rank * 16384), "l"(src + rank * 16384), "r"(sb + BAR_FULL + 8 * slot), "l"(first ? L2_FIRST : L2_NORMAL),
                 "h"((uint16_t)3) : "memory");
}
__device__ __forceinline__ void load_tile_mc(uint32_t sb, uint32_t& ph, uint32_t slot, const CUtensorMap* m, int row, int cb, int rank, bool first) {
    slot_wait(sb + BAR_EMPTY, ph, slot);
    asm volatile("{\n.reg .pred p;\nelect.sync _|p, 0xffffffff;\n@p mbarrier.arrive.expect_tx.shared::cta.b64 _, [%2], 32768;\n"
                 "@p cp.async.bulk.tensor.3d.shared::cluster.global.mbarrier::complete_tx::bytes.multicast::cluster.L2::cache_hint [%0], [%1, {%3, %4, %5}], [%2], %7, %6;\n}"
                 ::"r"(sb + slot * SLOT + rank * 16384), "l"(m), "r"(sb + BAR_FULL + 8 * slot), "r"(0), "r"(row), "r"(cb + rank),
                 "l"(first ? L2_FIRST : L2_NORMAL), "h"((uint16_t)3) : "memory");
}
__device__ __forceinline__ void load_image(uint32_t sb, uint32_t& ph, uint32_t slot, const void* src, bool first) {
    slot_wait(sb + BAR_EMPTY, ph, slot);
    asm volatile("{\n.reg .pred p;\nelect.sync _|p, 0xffffffff;\n@p mbarrier.arrive.expect_tx.shared::cta.b64 _, [%2], 32768;\n"
                 "@p cp.async.bulk.shared::cluster.global.mbarrier::complete_tx::bytes.L2::cache_hint [%0], [%1], 32768, [%2], %3;\n}"
                 ::"r"(sb + slot * SLOT), "l"(src), "r"(sb + BAR_FULL + 8 * slot), "l"(first ? L2_FIRST : L2_NORMAL) : "memory");
}
__device__ __forceinline__ void load_tile(uint32_t sb, uint32_t& ph, uint32_t slot, const CUtensorMap* m, int row, int cb, bool first) {
    slot_wait(sb + BAR_EMPTY, ph, slot);
    asm volatile("{\n.reg .pred p;\nelect.sync _|p, 0xffffffff;\n@p mbarrier.arrive.expect_tx.shared::cta.b64 _, [%2], 32768;\n"
                 "@p cp.async.bulk.tensor.3d.shared::cluster.global.mbarrier::complete_tx::bytes.L2::cache_hint [%0], [%1, {%3, %4, %5}], [%2], %6;\n}"
                 ::"r"(sb + slot * SLOT), "l"(m), "r"(sb + BAR_FULL + 8 * slot), "r"(0), "r"(row), "r"(cb), "l"(first ? L2_FIRST : L2_NORMAL) : "memory");
}
__device__ __forceinline__ uint32_t ring_next(uint32_t r) { return r == 4 ? 0 : r + 1; }
__device__ __forceinline__ uint32_t w_table(int hp) { return hp ? 0x3104u : 0x4210u; }
__device__ __forceinline__ uint32_t a_table(int hp) { return hp ? 0x625u : 0x635u; }
__device__ __forceinline__ uint32_t a_next(uint32_t& t) {
    const uint32_t s = t & 15;
    t = (t >> 4) | (s << 8);
    return s;
}
constexpr uint32_t O_TABLE = 0x1604235u;
__device__ __forceinline__ uint32_t o_next(uint32_t& t) {
    const uint32_t s = t & 15;
    t = (t >> 4) | (s << 24);
    return s;
}
__device__ __forceinline__ int o_head(int i, int kh) { return i < 16 ? 4 * (i & 7) + 2 * (kh ^ 1) + (i >> 3) : 29 + 2 * kh; }

template <bool INIT>
__device__ __forceinline__ void gemm_issue(float (&d)[64], uint32_t a, uint32_t b, int acc, bool img) {
    const uint32_t ha = img ? HI_IMG : HI_128, o2 = img ? 32 : 4, o4 = img ? 64 : 1024;
    wg_fence();
#pragma unroll
    for (int k = 0; k < 8; k++) {
        if (INIT && k == 0) wgmma_ss128_init<1>(d, a, b, ha);
        else wgmma_ss128<1>(d, a + (k >> 2) * o4 + ((k >> 1) & 1) * o2 + (k & 1) * 2, b + k * 128, k ? 1 : acc, ha);
    }
    wg_commit();
}

__device__ __forceinline__ void h_store(const uint32_t* x, float mean, float sq, uint32_t sb, int row) {
    const int lane = threadIdx.x & 31;
    const float rs = ln_rstd(sq * (1.f / 512.f));
    const uint32_t mb = pack2(mean, mean);
    uint8_t* p = g_h + ((row >> 7) * 8 + (lane >> 3)) * 16384 + (row & 127) * 128 + (((lane ^ row) & 7) << 4);
#pragma unroll
    for (int i = 0; i < 2; i++) {
        const uint4 a = lds128(sb + SM_TAB + 1024 + i * 512 + lane * 16), c = lds128(sb + SM_TAB + i * 512 + lane * 16);
        *reinterpret_cast<uint4*>(p + i * 65536) = make_uint4(ln_apply(x[4 * i], mb, rs, a.x, c.x), ln_apply(x[4 * i + 1], mb, rs, a.y, c.y),
                                                              ln_apply(x[4 * i + 2], mb, rs, a.z, c.z), ln_apply(x[4 * i + 3], mb, rs, a.w, c.w));
    }
}

template <bool ODD>
__device__ __forceinline__ void proj_tile(float (&acc)[64], float (&prev)[64], int t, int q0, uint32_t sb, int wg, uint32_t eb, bool rel, uint32_t& fph,
                                          uint32_t wtab, uint32_t& atab, uint8_t* prev_img, uint32_t toff, float s0, float s1, bool first,
                                          const bf16* x, int xrow) {
    const uint32_t a0 = desc_k(sb + (wg ^ (ODD && t == 5)) * 8192), b0 = desc_mn(sb);
    const int lane = threadIdx.x & 31;
    float mean[2] = {0.f, 0.f}, rstd[2] = {0.f, 0.f};
    uint32_t xn[16];
#pragma unroll
    for (int i = 0; i < 4; i++) {
        uint4 v = make_uint4(0, 0, 0, 0);
        if (ODD && first) v = __ldg(reinterpret_cast<const uint4*>(x) + xrow * 64 + lane + 32 * i);
        xn[4 * i] = v.x; xn[4 * i + 1] = v.y; xn[4 * i + 2] = v.z; xn[4 * i + 3] = v.w;
    }
    constexpr int U = ODD ? UNR : 1;
#pragma unroll U
    for (int q = ODD ? 0 : q0; q < 4; q++) {
        if (ODD && t == 5 && q == 3) break;
        const uint32_t ws = (wtab >> (4 * q)) & 15, as = a_next(atab);
        if (!ODD && t != 2) slot_wait(sb + BAR_FULL, fph, ws);
        slot_wait(sb + BAR_FULL, fph, as);
        bar_sync(1 + wg, 256);
        gemm_issue<false>(acc, a0 + as * (SLOT / 16), b0 + ws * (SLOT / 16), q, false);
        bar_arrive(2 - wg, 256);
        wg_wait<1>();
        reg_fence(prev);
        if (ODD && t == 5) {
            if (q == 2) {
                q_store<false>(sb + 5 * SLOT, toff, prev);
                fence_async_smem();
            }
        } else if (ODD || !first) {
            if (q == 0) img_store_global<0>(prev_img, toff, prev, s0, s1);
            if (q == 1) img_store_global<1>(prev_img, toff, prev, s0, s1);
            if (q == 2) img_store_global<2>(prev_img, toff, prev, s0, s1);
            if (q == 3) img_store_global<3>(prev_img, toff, prev, s0, s1);
        }
        if (ODD && q == 1 && first) {
#pragma unroll
            for (int k = 0; k < 16; k++) mean[k >> 3] += bf_lo(xn[k]) + bf_hi(xn[k]);
#pragma unroll
            for (int i = 0; i < 2; i++) mean[i] = warp_sum(mean[i]) * (1.f / 512.f);
        }
        if (ODD && q == 2 && first) {
#pragma unroll
            for (int k = 0; k < 16; k++) {
                const float d0 = bf_lo(xn[k]) - mean[k >> 3], d1 = bf_hi(xn[k]) - mean[k >> 3];
                rstd[k >> 3] = fmaf(d0, d0, fmaf(d1, d1, rstd[k >> 3]));
            }
#pragma unroll
            for (int i = 0; i < 2; i++) rstd[i] = warp_sum(rstd[i]);
        }
        if (ODD && q == 3 && first) {
            mbar_wait(sb + BAR_FLAG + 8 * 8, 0);
            h_store(xn, mean[0], rstd[0], sb, xrow);
        }
        wg_wait<0>();
        release_if(eb, as, rel && !(ODD && (q & 1) && t == 5));
        if (ODD) release_if(eb, ws, rel && t != 1);
        if (ODD && q == 3 && first) {
            h_store(xn + 8, mean[1], rstd[1], sb, xrow + 1);
            __syncwarp();
            mbar_arrive_if(sb + BAR_DONE, lane == 0);
        }
    }
    reg_fence(acc);
}

__device__ __forceinline__ void qk_issue(float (&s)[64], uint32_t q, uint32_t k) {
    wg_fence();
    wgmma_ss128_init<0>(s, q, k, HI_Q, HI_IMG);
#pragma unroll
    for (int i = 1; i < 8; i++) wgmma_ss128<0>(s, q + (i >> 2) * 1024 + (i & 2) * 16 + (i & 1) * 2, k + (i >> 1) * 32 + (i & 1) * 2, 1, HI_Q, HI_IMG);
    wg_commit();
}
__device__ __forceinline__ void qk_issue(float (&s)[32], uint32_t q, uint32_t k) {
    wg_fence();
    wgmma_ss64_init<0>(s, q, k, HI_Q, HI_IMG);
#pragma unroll
    for (int i = 1; i < 8; i++) wgmma_ss64<0>(s, q + (i >> 2) * 1024 + (i & 2) * 16 + (i & 1) * 2, k + (i >> 1) * 32 + (i & 1) * 2, 1, HI_Q, HI_IMG);
    wg_commit();
}
__device__ __forceinline__ void pv_issue(float (&o)[64], const uint32_t (&p)[32], uint32_t v, int acc, bool half) {
    if (half) {
        asm volatile("// half" ::: "memory");
        wg_fence();
#pragma unroll
        for (int i = 0; i < 4; i++) wgmma_rs128(o, p[4 * i], p[4 * i + 1], p[4 * i + 2], p[4 * i + 3], v + i * 256, i ? 1 : acc, HI_IMG);
        wg_commit();
        asm volatile("// half" ::: "memory");
    } else {
        wg_fence();
#pragma unroll
        for (int i = 0; i < 8; i++) wgmma_rs128(o, p[4 * i], p[4 * i + 1], p[4 * i + 2], p[4 * i + 3], v + i * 256, i ? 1 : acc, HI_IMG);
        wg_commit();
    }
}
template <int B, int N>
__device__ __forceinline__ void tri_mask(float (&s)[N], int x) {
#pragma unroll
    for (int k = 0; k < 7; k++)
        asm("{\n.reg .pred p, q;\nsetp.lt.s32 p, %4, %5;\nsetp.le.s32 q, %4, %5;\n"
            "@p mov.b32 %0, 0fFF800000;\n@q mov.b32 %1, 0fFF800000;\n@p mov.b32 %2, 0fFF800000;\n@q mov.b32 %3, 0fFF800000;\n}"
            : "+f"(s[B + 4 * k]), "+f"(s[B + 4 * k + 1]), "+f"(s[B + 4 * k + 6]), "+f"(s[B + 4 * k + 7]) : "r"(x), "r"(8 * k));
    asm("{\n.reg .pred p, q;\nsetp.lt.s32 p, %2, 56;\nsetp.le.s32 q, %2, 56;\n@p mov.b32 %0, 0fFF800000;\n@q mov.b32 %1, 0fFF800000;\n}"
        : "+f"(s[B + 28]), "+f"(s[B + 29]) : "r"(x));
}
__device__ __forceinline__ void tri_mask_copy(float (&s)[64], const float (&h)[32], int x) {
#pragma unroll
    for (int i = 0; i < 32; i++) {
        asm("{\n.reg .pred p;\nsetp.lt.s32 p, %2, %3;\nselp.f32 %0, 0fFF800000, %1, p;\n}"
            : "=f"(s[i]) : "f"(h[i]), "r"(x), "r"(8 * (i >> 2) - 4 * (i & 2) + (i & 1)));
        s[32 + i] = __uint_as_float(0xff800000u);
    }
}
constexpr float SM_HI = 1152921504606846976.f, SM_LO = 1.f / 1152921504606846976.f;
__device__ __forceinline__ bool softmax_unsafe(float t0, float t1, bool first) {
    bool bad = __any_sync(0xffffffffu, fmaxf(t0, t1) > SM_HI);
    if (first) {
        uint32_t a = __ballot_sync(0xffffffffu, t0 >= SM_LO), b = __ballot_sync(0xffffffffu, t1 >= SM_LO);
        a |= a >> 1;
        b |= b >> 1;
        bad |= ((a | (a >> 2)) & (b | (b >> 2)) & 0x11111111u) != 0x11111111u;
    }
    return bad;
}
__device__ __forceinline__ void softmax_shift(float (&s)[64], float d0, float d1) {
#pragma unroll
    for (int i = 0; i < 64; i++) s[i] -= (i & 2) ? d1 : d0;
}
__device__ __forceinline__ void softmax_remax(float (&s)[64], float (&m)[2], bool first, float& a0, float& a1) {
    float m0 = fmaxf(s[0], s[1]), m1 = fmaxf(s[2], s[3]);
#pragma unroll
    for (int k = 1; k < 16; k++) {
        m0 = fmaxf(m0, fmaxf(s[4 * k], s[4 * k + 1]));
        m1 = fmaxf(m1, fmaxf(s[4 * k + 2], s[4 * k + 3]));
    }
    m0 = fmaxf(m0, __shfl_xor_sync(0xffffffffu, m0, 1));
    m1 = fmaxf(m1, __shfl_xor_sync(0xffffffffu, m1, 1));
    m0 = fmaxf(m0, __shfl_xor_sync(0xffffffffu, m0, 2));
    m1 = fmaxf(m1, __shfl_xor_sync(0xffffffffu, m1, 2));
    if (!first) {
        m0 = fmaxf(m0, 0.f);
        m1 = fmaxf(m1, 0.f);
    }
    a0 = first ? 1.f : ex2(-m0);
    a1 = first ? 1.f : ex2(-m1);
    m[0] += m0;
    m[1] += m1;
    softmax_shift(s, m0, m1);
}
template <int J0, int J1>
__device__ __forceinline__ void softmax_exp(const float (&s)[64], uint32_t (&p)[32], float (&t)[4]) {
#pragma unroll
    for (int k = J0; k < J1; k++) {
        const float e0 = ex2(s[4 * k]), e1 = ex2(s[4 * k + 1]), e2 = ex2(s[4 * k + 2]), e3 = ex2(s[4 * k + 3]);
        if (k == 0) { t[0] = e0; t[1] = e1; t[2] = e2; t[3] = e3; }
        else { t[0] += e0; t[1] += e1; t[2] += e2; t[3] += e3; }
        p[2 * k] = pack2(e0, e1);
        p[2 * k + 1] = pack2(e2, e3);
    }
}
__device__ __forceinline__ void fma8(float (&acc)[8], float a, uint4 w) {
    acc[0] = fmaf(a, bf_lo(w.x), acc[0]); acc[1] = fmaf(a, bf_hi(w.x), acc[1]);
    acc[2] = fmaf(a, bf_lo(w.y), acc[2]); acc[3] = fmaf(a, bf_hi(w.y), acc[3]);
    acc[4] = fmaf(a, bf_lo(w.z), acc[4]); acc[5] = fmaf(a, bf_hi(w.z), acc[5]);
    acc[6] = fmaf(a, bf_lo(w.w), acc[6]); acc[7] = fmaf(a, bf_hi(w.w), acc[7]);
}
__device__ __forceinline__ void mma16816(float (&d)[4], const uint32_t* a, uint32_t b0, uint32_t b1) {
    asm("mma.sync.aligned.m16n8k16.row.col.f32.bf16.bf16.f32 {%0, %1, %2, %3}, {%4, %5, %6, %7}, {%8, %9}, {%0, %1, %2, %3};"
        : "+f"(d[0]), "+f"(d[1]), "+f"(d[2]), "+f"(d[3]) : "r"(a[0]), "r"(a[1]), "r"(a[2]), "r"(a[3]), "r"(b0), "r"(b1));
}
__device__ __forceinline__ uint32_t best_key(const uint32_t* keys, int lane, uint32_t ep) {
    uint32_t best;
#pragma unroll 1
    for (;;) {
        const uint4 k = ld_poll(reinterpret_cast<const uint4*>(keys) + lane);
        best = max(max(k.x, k.y), max(k.z, k.w));
        if (__all_sync(0xffffffffu, (((k.x ^ ep) | (k.y ^ ep) | (k.z ^ ep) | (k.w ^ ep)) & 31) == 0)) break;
    }
    return __reduce_max_sync(0xffffffffu, best);
}

__global__ void __cluster_dims__(2, 1, 1) __launch_bounds__(384, 1)
fused_kernel(const __grid_constant__ CUtensorMap tm_ckv, const __grid_constant__ CUtensorMap tm_wq,
             const __grid_constant__ CUtensorMap tm_wuk, const __grid_constant__ CUtensorMap tm_wuv,
             const __grid_constant__ CUtensorMap tm_wo, const __grid_constant__ CUtensorMap tm_wg,
             const __grid_constant__ CUtensorMap tm_wu,
             const __grid_constant__ CUtensorMap tm_wm, const __grid_constant__ CUtensorMap tm_x, const Params P) {
    extern __shared__ __align__(1024) uint8_t smem[];
    const uint32_t sb = (uint32_t)__cvta_generic_to_shared(smem);
    const int tid = threadIdx.x, lane = tid & 31, warp = __shfl_sync(0xffffffffu, tid >> 5, 0), wg = warp >> 2;
    uint32_t sm;
    asm("mov.u32 %0, %%smid;" : "=r"(sm));
    if (MC) sm = blockIdx.x < 8 ? blockIdx.x + 124 : blockIdx.x - 8;
    const uint32_t smq = ((sm - 64) * 147) >> 11;
    const int rb = !P.by_smid ? blockIdx.x : sm < 64 ? (sm & 14) * 8 + (sm >> 4) * 2 + (sm & 1)
                 : sm < 120 ? ((sm - 64 - smq * 14) & 14) * 8 + 24 + smq * 2 + (sm & 1) : sm < 124 ? sm + 8 : sm - 116;
    const int grp = rb >> 3, j = rb & 7, cq = j & 3, kh = grp & 1, ort = (grp & 14) + (j >> 2);
    if (warp == 0) TS(0);

    if (rb >= NCTA) {
        float* sc = reinterpret_cast<float*>(smem + 6 * SLOT);
        float* red = sc + 512;
        if (tid == 256) {
            for (int i = 0; i < 6; i++) { mbar_init(sb + BAR_FULL + 8 * i, 1); mbar_init(sb + BAR_EMPTY + 8 * i, 8); }
            fence_async_smem();
        }
        __syncthreads();
        uint32_t ph = 0, sl = 0;
        if (tid == 256) {
#pragma unroll 1
            for (int i = 0; i < 24; i++) {
                mbar_wait(sb + BAR_EMPTY + 8 * sl, ph ^ 1);
                mbar_expect(sb + BAR_FULL + 8 * sl, SLOT);
                tma2d(sb + sl * SLOT, &tm_wm, (i >> 3) * 1024 + (rb - NCTA) * 256, (i & 7) * 64, sb + BAR_FULL + 8 * sl);
                if (++sl == 6) { sl = 0; ph ^= 1; }
            }
            mbar_wait(sb + BAR_EMPTY, 1);
            mbar_wait(sb + BAR_EMPTY + 8, 1);
#pragma unroll 1
            for (int i = 0; i <= NFFN / NSPARE; i++) {
                const int b = (rb - NCTA) * (NFFN / NSPARE) + i;
                if (i < NFFN / NSPARE) {
                    const uint32_t f = sb + BAR_FULL + 8 * (i & 1), d = sb + (i & 1) * SLOT;
                    asm volatile("cp.async.bulk.wait_group.read 0;" ::: "memory");
                    mbar_expect(f, SLOT);
                    tma2d(d, &tm_wg, b * 16, 0, f);
                    tma2d(d + 8192, &tm_wg, b * 16, 256, f);
                    tma2d(d + 16384, &tm_wu, b * 16, 0, f);
                    tma2d(d + 24576, &tm_wu, b * 16, 256, f);
                }
                if (i) {
                    mbar_wait(sb + BAR_FULL + 8 * (~i & 1), ((i - 1) >> 1) & 1);
                    asm volatile("cp.async.bulk.global.shared::cta.bulk_group [%0], [%1], 32768;\ncp.async.bulk.commit_group;"
                                 ::"l"(g_wf + (b - 1) * SLOT), "r"(sb + (~i & 1) * SLOT) : "memory");
                }
            }
            asm volatile("cp.async.bulk.wait_group 0;" ::: "memory");
            fence_async_global();
            flag_add(&g_sync.modcnt[32]);
            TS(4);
        } else if (tid < 256) {
            const uint32_t c2 = __ldg(reinterpret_cast<const uint32_t*>(P.c) + tid);
            sc[2 * tid] = rbf(bf_lo(c2) * sigmoid(bf_lo(c2)));
            sc[2 * tid + 1] = rbf(bf_hi(c2) * sigmoid(bf_hi(c2)));
            bar_sync(1, 256);
#pragma unroll 1
            for (int ps = 0; ps < 3; ps++) {
                float acc[8] = {0.f, 0.f, 0.f, 0.f, 0.f, 0.f, 0.f, 0.f};
#pragma unroll 1
                for (int bt = 0; bt < 8; bt++) {
                    mbar_wait(sb + BAR_FULL + 8 * sl, ph);
#pragma unroll
                    for (int i = 0; i < 8; i++)
                        fma8(acc, sc[bt * 64 + warp * 8 + i], *reinterpret_cast<const uint4*>(smem + sl * SLOT + (warp * 8 + i) * 512 + lane * 16));
                    __syncwarp();
                    mbar_arrive_if(sb + BAR_EMPTY + 8 * sl, lane == 0);
                    if (++sl == 6) { sl = 0; ph ^= 1; }
                }
                *reinterpret_cast<float4*>(red + warp * 256 + lane * 8) = make_float4(acc[0], acc[1], acc[2], acc[3]);
                *reinterpret_cast<float4*>(red + warp * 256 + lane * 8 + 4) = make_float4(acc[4], acc[5], acc[6], acc[7]);
                bar_sync(1, 256);
                float v = 0.f;
#pragma unroll
                for (int i = 0; i < 8; i++) v += red[i * 256 + tid];
                g_mod[ps * 1024 + (rb - NCTA) * 256 + tid] = __float2bfloat16_rn(v);
                bar_sync(1, 256);
                if (tid == 0 && ps != 1) flag_add(&g_sync.modcnt[(ps >> 1) * 32]);
                if (warp == 0) TS(1 + ps);
            }
        }
        return;
    }

    if (tid == 256) {
        if (sb & 1023) __trap();
        asm volatile("prefetch.tensormap [%0];" ::"l"((j & 1) ? &tm_wuv : &tm_wuk) : "memory");
        asm volatile("prefetch.tensormap [%0];" ::"l"(&tm_ckv) : "memory");
        for (int i = 0; i < 7; i++) { mbar_init(sb + BAR_FULL + 8 * i, 1); mbar_init(sb + BAR_EMPTY + 8 * i, MC ? 4 : 2); }
        for (int i = 0; i < 9; i++) mbar_init(sb + BAR_DONE + 8 * i, 8);
        for (int i = 0; i < 10; i++) mbar_init(sb + BAR_FLAG + 8 * i, 1);
        *reinterpret_cast<uint32_t*>(smem + SM_EP + 4) = 0;
        *reinterpret_cast<uint32_t*>(smem + SM_EP + 16) = 0;
        mbar_init(sb + BAR_END, 8);
        fence_async_smem();
        if (MC) asm volatile("fence.mbarrier_init.release.cluster;" ::: "memory");
    }
    __syncthreads();
    if (MC) asm volatile("barrier.cluster.arrive.relaxed.aligned;\nbarrier.cluster.wait.aligned;" ::: "memory");

    if (wg == 2) {
        asm volatile("setmaxnreg.dec.sync.aligned.u32 40;");
        if (warp == 8) {
            uint32_t eph = 0x7f, r = 0;
            const CUtensorMap* tw = (j & 1) ? &tm_wuv : &tm_wuk;
#pragma unroll 1
            for (int hp = 0; hp < 2; hp++) {
                const int hc = 4 * grp + 2 * hp;
                uint32_t wtab = w_table(hp), atab = a_table(hp);
#pragma unroll 1
                for (int u = 0; u < 4; u++) {
                    load_tile(sb, eph, (wtab >> (4 * u)) & 15, tw, u * 128, hc, HINT & 1); PT();
                    if (MC & 1) load_tile_mc(sb, eph, a_next(atab), &tm_ckv, (j >> 1) * 128, u * 2, j & 1, (HINT & 8) && hp);
                    else load_tile(sb, eph, a_next(atab), &tm_ckv, (j >> 1) * 128, u * 2, (HINT & 8) && hp);
                    PT();
                    if (hp == 1 && (u & 1) && lane == 0) asm volatile("red.relaxed.gpu.global.add.u32 [%0], 1;" ::"l"(&g_sync.rdcnt[(grp * 2 + (u >> 1)) * 8]) : "memory");
                }
#pragma unroll 1
                for (int u = 4; u < 16; u++) {
                    if (hp == 1 && (u & 7) == 4) mbar_wait(sb + BAR_FLAG + 24 + (u & 8), 0);
                    if (MC & 1) load_tile_mc(sb, eph, a_next(atab), &tm_ckv, ((u & 12) + (j >> 1)) * 128, (u & 3) * 2, j & 1, (HINT & 8) && hp);
                    else load_tile(sb, eph, a_next(atab), &tm_ckv, ((u & 12) + (j >> 1)) * 128, (u & 3) * 2, (HINT & 8) && hp);
                    PT();
                }
                mbar_wait(sb + BAR_FLAG, 0);
                fence_async_global();
#pragma unroll 1
                for (int u = 0; u < 4; u++) {
                    if (MC & 2) load_tile_mc(sb, eph, (wtab >> (4 * u)) & 15, &tm_wq, u * 128, hc, j & 1, HINT & 1);
                    else load_tile(sb, eph, (wtab >> (4 * u)) & 15, &tm_wq, u * 128, hc, HINT & 1);
                    PT();
                    load_image(sb, eph, a_next(atab), g_h + ((15 - j) * 4 + u) * SLOT, (HINT & 8) && hp); PT();
                }
                mbar_wait(sb + BAR_FLAG + 8 + 32 * hp, 0);
                fence_async_global();
#pragma unroll 1
                for (int u = 0; u < 4; u++) { load_image(sb, eph, a_next(atab), g_h + (j * 4 + u) * SLOT, (HINT & 8) && hp); PT(); }
                const uint8_t* kv = g_KV + (size_t)(grp * 32 + 30 * hp) * SLOT;
                const int step = hp ? -2 * SLOT : 2 * SLOT;
                if (MC & 4) load_image_mc(sb, eph, r, kv, j & 1, HINT & 4);
                else load_image(sb, eph, r, kv, HINT & 4);
                PT();
                r = ring_next(r);
#pragma unroll 1
                for (int n = 1; n <= 16; n++) {
                    if (n == 8) {
                        mbar_wait(sb + BAR_FLAG + 16 + 32 * hp, 0);
                        fence_async_global();
                    }
                    asm volatile("st.volatile.shared.u32 [%0], %1;" ::"r"(sb + SM_EP + 16), "r"(16 * hp + n) : "memory");
                    const uint8_t* v = kv + SLOT;
                    kv += n < 16 - j ? step : n == 16 - j ? (2 * j - 15) * step : -step;
                    if ((MC & 4) && n != 15 - (j & 6)) load_image_mc(sb, eph, r, kv, j & 1, HINT & 4);
                    else load_image(sb, eph, r, kv, HINT & 4);
                    PT();
                    r = ring_next(r);
                    if ((MC & 4) && n != 16 - (j & 6)) load_image_mc(sb, eph, r, v, j & 1, HINT & 4);
                    else load_image(sb, eph, r, v, HINT & 4);
                    PT();
                    r = ring_next(r);
                }
                if (MC & 4) load_image_mc(sb, eph, r, kv + SLOT, j & 1, HINT & 4);
                else load_image(sb, eph, r, kv + SLOT, HINT & 4);
                PT();
                r = ring_next(r);
            }
            uint32_t otab = O_TABLE, ready = 0;
#pragma unroll 1
            for (int i = 0; i < 17; i++) {
                asm volatile("st.volatile.shared.u32 [%0], %1;" ::"r"(sb + SM_EP + 16), "r"(33 + i) : "memory");
                const bool dyn = i >= 8 && i < 15;
                const uint32_t want = dyn ? 15u << (4 * (i - 8)) : 1u << max(i + 14, 28);
                if (!(ready & want)) {
                    do {
                        asm volatile("ld.acquire.cta.shared.u32 %0, [%1];" : "=r"(ready) : "r"(sb + SM_EP + 4) : "memory");
                        ready = __shfl_sync(0xffffffffu, ready, 0);
                    } while (!(ready & want));
                    fence_async_global();
                }
                const int head = o_head(dyn ? (ready >> (4 * (i - 8))) & 15 : i, kh);
                const uint8_t* src = g_ctx + (size_t)(ort * 32 + head) * SLOT;
                if (i < 15) {
                    if (MC & 8) load_image_mc(sb, eph, o_next(otab), src, j & 1, HINT & 16);
                    else load_image(sb, eph, o_next(otab), src, HINT & 16);
                } else {
                    const uint32_t as = o_next(otab), d = sb + as * SLOT;
                    slot_wait(sb + BAR_EMPTY, eph, as);
                    asm volatile("{\n.reg .pred p, q;\nelect.sync _|p, 0xffffffff;\n@p mbarrier.arrive.expect_tx.shared::cta.b64 _, [%2], %3;\n"
                                 "@p cp.async.bulk.shared::cluster.global.mbarrier::complete_tx::bytes [%0], [%1], 16384, [%2];\n}"
                                 ::"r"(d + kh * 16384), "l"(src + kh * 16384), "r"(sb + BAR_FULL + 8 * as), "r"(i == 15 ? 32768 : 16384) : "memory");
                    if (i == 15)
                        asm volatile("{\n.reg .pred p;\nelect.sync _|p, 0xffffffff;\n"
                                     "@p cp.async.bulk.tensor.3d.shared::cluster.global.mbarrier::complete_tx::bytes [%0], [%1, {%3, %4, %5}], [%2];\n}"
                                     ::"r"(d + (kh ^ 1) * 16384), "l"(&tm_x), "r"(sb + BAR_FULL + 8 * as), "r"(0), "r"(ort * 128 + kh * 64), "r"(cq * 2) : "memory");
                }
                PT();
                load_tile(sb, eph, o_next(otab), &tm_wo, head * 128, cq * 2, HINT & 2); PT();
                if (i == 0) o_next(otab);
            }
            if (rb < NFFN) {
                load_image(sb, eph, o_next(otab), g_wf + rb * SLOT, false);
                const uint32_t s2 = o_next(otab);
                slot_wait(sb + BAR_EMPTY, eph, s2);
                asm volatile("{\n.reg .pred p;\nelect.sync _|p, 0xffffffff;\n@p mbarrier.arrive.expect_tx.shared::cta.b64 _, [%2], 16384;\n"
                             "@p cp.async.bulk.shared::cluster.global.mbarrier::complete_tx::bytes [%0], [%1], 16384, [%2];\n}"
                             ::"r"(sb + s2 * SLOT), "l"(P.wdown + rb * 8192), "r"(sb + BAR_FULL + 8 * s2) : "memory");
            }
        } else {
            const int hw = warp - 9;
            if (hw == 1 && lane == 0) {
                l2_prefetch(P.ckv + rb * 2048, 4096);
                mbar_watch(sb + BAR_FULL + 8 * PF0, 0);
                l2_prefetch(P.ckv + 512 * 512 + rb * 2048, 4096);
                mbar_watch(sb + BAR_FULL + 8 * 4, 0);
                l2_prefetch(P.x + rb * 8192, 16384);
                l2_prefetch(P.ckv + 1024 * 512 + rb * 4096, 8192);
                TS(40);
                if (MC & 2) tma3d_prefetch(&tm_wq, (j >> 1) * 128, grp * 4 + (j & 1));
                else if (j < 4) tma3d_prefetch(&tm_wq, j * 128, grp * 4);
                step_watch(sb + SM_EP + 16, PFA);
                tma3d_prefetch((j & 1) ? &tm_wuv : &tm_wuk, (j >> 1) * 128, grp * 4 + 2);
                step_watch(sb + SM_EP + 16, PFA + 2);
                l2_prefetch(P.ckv + rb * 8192, 16384);
                step_watch(sb + SM_EP + 16, PFA + 3);
                l2_prefetch(g_h + rb * 16384, 16384);
                step_watch(sb + SM_EP + 16, PFA + 4);
                if (MC & 2) tma3d_prefetch(&tm_wq, (j >> 1) * 128, grp * 4 + 2 + (j & 1));
                else if (j < 4) tma3d_prefetch(&tm_wq, j * 128, grp * 4 + 2);
#pragma unroll 1
                for (int i = 0; i < 10; i++) {
                    step_watch(sb + SM_EP + 16, i < 6 ? 16 + PFB + i : 16 + PFC + i - 6);
                    if (i == 7) mbar_watch(sb + BAR_FLAG + 8 * 7, 0);
                    const uint8_t* p = i < 4 ? g_ctx + (size_t)(ort * 32 + o_head(cq + 2 * (i & 2), kh)) * SLOT + (i & 1) * 16384
                                     : i < 6 ? reinterpret_cast<const uint8_t*>(P.wo) + ((rb >> 3) * 16 + (i & 1) * 8 + (rb & 7)) * 16384
                                     : i == 6 ? reinterpret_cast<const uint8_t*>(P.x) + rb * 16384
                                     : i == 7 ? reinterpret_cast<const uint8_t*>(P.wdown) + rb * 16384 : g_wf + rb * SLOT + (i & 1) * 16384;
                    if ((i < 7 || rb < NFFN) && ((PFMASK >> i) & 1)) l2_prefetch(p, 16384);
                }
                step_watch(sb + SM_EP + 16, 16 + PFC + 4);
                if (OBINIT) {
                    const uint32_t v = lds32(sb + SM_EP) - 1;
#pragma unroll 1
                    for (int i = 0; i < 32; i++) sts128(sb + SM_RED + i * 16, make_uint4(v, v, v, v));
                    fence_async_smem();
#pragma unroll 1
                    for (int i = 0; i < OB / 32; i++)
                        asm volatile("cp.async.bulk.global.shared::cta.bulk_group [%0], [%1], 512;" ::"l"(g_out + rb * OB + i * 32), "r"(sb + SM_RED) : "memory");
                    asm volatile("cp.async.bulk.commit_group;\ncp.async.bulk.wait_group 0;" ::: "memory");
                    fence_async_global();
                }
                mbar_arrive(sb + BAR_PF);
                mbar_watch(sb + BAR_END, 0);
            }
            if (hw == 0) {
#pragma unroll 1
                for (int i = 0; i < 9; i++) {
                    const int hp = i > 4, k = (i - 1) & 3;
                    if (lane == 0) {
                        mbar_wait(sb + BAR_DONE + 8 * i, 0);
                        flag_add(i == 0 ? &g_sync.hcnt[grp * 8] : k < 2 ? &g_sync.kvcnt[((2 * grp + hp) * 2 + k) * 8]
                                                                        : &g_sync.ctxcnt[(k == 2 ? 15 - j : j) * 32 + 2 * grp + hp]);
                    }
                    if (i == 0) TS(43);
                }
            }
            if (hw == 2) {
                const uint32_t ep = __ldcg(&g_sync.epoch[0]) + 1;
                if (lane == 0) {
                    asm volatile("st.shared.u32 [%0], %1;" ::"r"(sb + SM_EP), "r"(ep) : "memory");
                    flag_wait(&g_sync.modcnt[0], NSPARE * ep);
                }
                __syncwarp();
#pragma unroll
                for (int i = 0; i < 4; i++) {
                    uint4 v = __ldcg(reinterpret_cast<const uint4*>(g_mod) + lane + 32 * i);
                    if (i >= 2) v = make_uint4(badd(v.x, ONE2), badd(v.y, ONE2), badd(v.z, ONE2), badd(v.w, ONE2));
                    sts128(sb + SM_TAB + i * 512 + lane * 16, v);
                }
                __syncwarp();
                if (lane == 0) mbar_arrive(sb + BAR_FLAG + 8 * 8);
                TS(42);
#pragma unroll 1
                for (int i = 0; i < 8; i++) {
                    if (lane == 0) mbar_wait(sb + BAR_DONE + 8 * (i == 7 ? 6 : i == 4 ? 3 : i), 0);
                    __syncwarp();
                    const uint32_t* f = i == 0 ? &g_sync.hcnt[(lane ? j : 15 - j) * 8]
                                      : i == 3 || i == 4 ? &g_sync.rdcnt[(grp * 2 + i - 3) * 8]
                                      : i == 7 ? &g_sync.modcnt[32] : &g_sync.kvcnt[(4 * grp + (i > 4 ? i - 3 : i - 1)) * 8];
                    if (lane < (i ? 1 : 2)) flag_wait(f, 8 * ep);
                    __syncwarp();
                    if (i == 7) {
                        const uint32_t *mp = reinterpret_cast<const uint32_t*>(g_mod) + lane, *wp = reinterpret_cast<const uint32_t*>(P.wr) + lane;
                        float ra = 0.f, rs = 0.f;
#pragma unroll 1
                        for (int k = 0; k < 256; k += 32) {
                            const uint32_t ga = __ldcg(mp + 512 + k), sh = __ldcg(mp + 768 + k), c1 = badd(__ldcg(mp + 1024 + k), ONE2);
                            const uint32_t gb = __ldcg(mp + 1280 + k), ww = __ldg(wp + k);
                            const float a0 = bf_lo(c1) * bf_lo(ww), a1 = bf_hi(c1) * bf_hi(ww);
                            ra += a0 + a1;
                            rs = fmaf(bf_lo(sh), bf_lo(ww), fmaf(bf_hi(sh), bf_hi(ww), rs));
                            if (k >> 6 == cq) {
                                sts128(sb + SM_TAB + ((k & 32) + lane) * 16, make_uint4(ga << 16, ga & 0xffff0000u, __float_as_uint(a0), __float_as_uint(a1)));
                                sts128(sb + SM_TAB + 1024 + ((k & 32) + lane) * 16, make_uint4(c1, sh, gb, 0));
                            }
                        }
                        *reinterpret_cast<float2*>(smem + SM_EP + 8) = make_float2(warp_sum(ra), warp_sum(rs));
                        __syncwarp();
                    }
                    if (lane == 0) mbar_arrive(sb + BAR_FLAG + 8 * i);
                    TS(48 + i);
                }
                const uint32_t* f = &g_sync.ctxcnt[ort * 32 + o_head(min(lane, 16), kh)];
                uint32_t ready = (MC & 8) && (j & 1) ? ~0u : 0u, list = 0, sh = 0, qa = sb + SM_EP + 4;
                if (MC & 8) asm("mapa.shared::cluster.u32 %0, %1, %2;" : "=r"(qa) : "r"(sb + SM_EP + 4), "r"(lane & 1));
                while (ready != ~0u) {
                    uint32_t v;
                    asm volatile("ld.acquire.gpu.global.u32 %0, [%1];" : "=r"(v) : "l"(f) : "memory");
                    const uint32_t now = __ballot_sync(0xffffffffu, (int)(v - ep) >= 0);
                    for (uint32_t fresh = now & ~ready & 0x7f00; fresh; fresh &= fresh - 1, sh += 4) list |= (__ffs(fresh) - 1) << sh;
                    list |= (((now & 0xff) + 1) >> 8 << 28) | ((now & 0x18000) << 14);
                    if (now != ready && lane < ((MC & 8) ? 2 : 1)) asm volatile("st.relaxed.cluster.shared::cluster.u32 [%0], %1;" ::"r"(qa), "r"(list) : "memory");
                    if ((now & 0xff) == 0xff) mbar_wait(sb + BAR_DONE + 8 * 7, 0);
                    ready = now;
                    __nanosleep(POLL_NS);
                }
                TS(45);
            }
        }
    } else {
        asm volatile("setmaxnreg.inc.sync.aligned.u32 232;");
        const bool elected = (tid & 127) == 0, rel = MC ? (tid & 95) == 0 : elected;
        uint32_t eb = sb + BAR_EMPTY;
        if (MC) asm("mapa.shared::cluster.u32 %0, %1, %2;" : "=r"(eb) : "r"(sb + BAR_EMPTY), "r"(warp & 1));
        const int g = lane >> 2, c4 = lane & 3;
        const uint32_t toff = warp * 4096 + g * 64 + ((c4 ^ (g >> 1)) << 4);
        uint32_t fph = 0, r = 0;
        if (wg == 1) bar_arrive(1, 256);
        const uint32_t kd = desc_k(sb), wd = desc_mn(sb), vd = ((sb & 0x3ffff) >> 4) | (32u << 16);
        const int nL = 16 - j, hn = nL - 1 + wg;
        float s[64], o[64], li[2] = {0.f, 0.f};
        uint8_t* cimg = g_ctx;
#pragma unroll 1
        for (int hp = 0; hp < 2; hp++) {
            {
                const int step = hp ? -8 * SLOT : 8 * SLOT;
                uint8_t* img = g_KV + (size_t)(grp * 32 + (hp ? j ^ 30 : j)) * SLOT - step;
                const float sc = (j & 1) ? 1.f : SM_C;
                const uint32_t wtab = w_table(hp);
                uint32_t atab = hp ? 0x256u : a_table(0);
#pragma unroll 1
                for (int t = 0; t < 6; t += 2) {
                    proj_tile<false>(s, o, t, t ? 0 : 2 * hp, sb, wg, eb, rel, fph, wtab, atab, t ? img : cimg, toff, t ? sc : li[0], t ? sc : li[1], (hp | t) == 0, P.x, rb * 16 + warp * 2);
                    __syncwarp();
                    mbar_arrive_if(sb + BAR_DONE + 4 * t + 32 * hp, lane == 0 && (hp | t) != 0);
                    if (elected) TS(1 + 10 * hp + t + 20 * wg);
                    proj_tile<true>(o, s, t + 1, 0, sb, wg, eb, rel, fph, wtab, atab, img + step, toff, sc, sc, (hp | t) == 0, P.x, rb * 16 + warp * 2);
                    if (elected) TS(2 + 10 * hp + t + 20 * wg);
                    img += 2 * step;
                }
            }
            float m[2] = {0.f, 0.f}, l[2] = {0.f, 0.f}, t[4] = {0.f, 0.f, 0.f, 0.f};
            bool shifted = false, bad = false, plain = false;
            uint32_t p[32];
#pragma unroll
            for (int i = 0; i < 32; i++) p[i] = 0;
            uint32_t qa = desc_k(sb + 5 * SLOT + (wg ^ 1) * 8192);
            uint8_t* img = g_ctx + (size_t)((15 - j) * 32 + 2 * grp + hp) * SLOT;
            slot_wait(sb + BAR_FULL, fph, r);
            int n = -1;
#pragma unroll 1
            for (;;) {
                while (bad || plain) {
                    if (bad) {
                        float a0, a1;
                        softmax_remax(s, m, n == 0 || n == nL, a0, a1);
                        shifted = true;
                        l[0] *= a0;
                        l[1] *= a1;
#pragma unroll
                        for (int i = 0; i < 64; i++) o[i] *= (i & 2) ? a1 : a0;
                    }
                    softmax_exp<0, 16>(s, p, t);
                    t[0] += t[1];
                    t[2] += t[3];
                    bad = !bad && softmax_unsafe(t[0], t[2], false);
                    plain = false;
                }
#pragma unroll 1
                do {
                    l[0] += t[0];
                    l[1] += t[2];
                    if (++n > 16) break;
                    const uint32_t ks = r;
                    uint32_t vs = ring_next(r);
                    r = ring_next(vs);
                    bar_sync(1 + wg, 256);
                    const int x = (warp & 3) * 16 + g - 2 * c4;
                    if (n == hn) {
                        float sh[32];
                        qk_issue(sh, qa, kd + ks * (SLOT / 16));
                        slot_wait(sb + BAR_FULL, fph, vs);
                        pv_issue(o, p, vd + vs * (SLOT / 16), 1, false);
                        bar_arrive(2 - wg, 256);
                        wg_wait<1>();
                        reg_fence(sh);
                        tri_mask_copy(s, sh, x);
                        release_if(eb, ks, rel);
                        release_if(eb, 5 + wg, rel && (!wg || n == 16));
                        if (!wg) {
                            qa += SLOT / 16;
                            fence_async_smem();
                            if (shifted) softmax_shift(s, m[0], m[1]);
                        }
                        float e[4 * EARLY];
#pragma unroll
                        for (int i = 0; i < 4 * EARLY; i++) {
                            e[i] = ex2(s[i]);
                            t[i & 3] = i < 4 ? e[i] : t[i & 3] + e[i];
                        }
                        reg_fence(e);
                        slot_wait(sb + BAR_FULL, fph, r);
                        wg_wait<0>();
                        reg_fence(o);
                        reg_fence(e);
                        release_if(eb, vs, rel);
#pragma unroll
                        for (int i = 0; i < 2 * EARLY; i++) p[i] = pack2(e[2 * i], e[2 * i + 1]);
                        softmax_exp<EARLY, 8>(s, p, t);
                        if (wg) {
                            ctx_store<true>(img, toff, o, l[0], l[1]);
                            __syncwarp();
                            mbar_arrive_if(sb + BAR_DONE + 24 + 32 * hp, lane == 0);
                            l[0] = l[1] = m[0] = m[1] = 0.f;
                            shifted = false;
                        }
                        t[0] += t[1];
                        t[2] += t[3];
                        bad = softmax_unsafe(t[0], t[2], wg);
                        continue;
                    }
                    if (n == 0 || n == nL) {
                        qk_issue(s, qa, kd + ks * (SLOT / 16));
                        if (n == 0) {
                            r = vs;
                            vs = 4 - hp;
                            slot_wait(sb + BAR_FULL, fph, 6);
                            gemm_issue<false>(o, qa + SLOT / 16, wd + vs * (SLOT / 16), 1, false);
                        } else {
                            slot_wait(sb + BAR_FULL, fph, vs);
                            pv_issue(o, p, vd + vs * (SLOT / 16), 1, true);
                        }
                        bar_arrive(2 - wg, 256);
                        const float i0 = n ? rcp(quad_sum(l[0])) : 1.f, i1 = n ? rcp(quad_sum(l[1])) : 1.f;
                        wg_wait<1>();
                        reg_fence(s);
                        release_if(eb, ks, rel);
                        release_if(eb, 6, rel && n == 16);
                        tri_mask<32>(s, n ? x : 64);
                        float e[4 * EARLY];
#pragma unroll
                        for (int i = 0; i < 4 * EARLY; i++) {
                            e[i] = ex2(s[i]);
                            t[i & 3] = i < 4 ? e[i] : t[i & 3] + e[i];
                        }
                        reg_fence(e);
                        slot_wait(sb + BAR_FULL, fph, r);
                        wg_wait<0>();
                        reg_fence(o);
                        reg_fence(e);
                        release_if(eb, vs, rel);
#pragma unroll
                        for (int i = 0; i < 2 * EARLY; i++) p[i] = pack2(e[2 * i], e[2 * i + 1]);
                        tile_store(img, sb + 6 * SLOT, toff, o, i0, i1, n);
                        softmax_exp<EARLY, 16>(s, p, t);
                        __syncwarp();
                        mbar_arrive_if(sb + BAR_DONE + 24 + 32 * hp, lane == 0 && n);
                        l[0] = l[1] = m[0] = m[1] = 0.f;
                        shifted = false;
                        t[0] += t[1];
                        t[2] += t[3];
                        bad = softmax_unsafe(t[0], t[2], true);
                        continue;
                    }
                    qk_issue(s, qa, kd + ks * (SLOT / 16));
                    slot_wait(sb + BAR_FULL, fph, vs);
                    pv_issue(o, p, vd + vs * (SLOT / 16), n != 1 && n != nL + 1, n == hn + 1);
                    bar_arrive(2 - wg, 256);
                    wg_wait<1>();
                    reg_fence(s);
                    release_if(eb, ks, rel);
                    release_if(eb, 6, rel && n == 16);
                    if (n == nL - 1) {
                        tri_mask<32>(s, x);
                        release_if(eb, 5, rel);
                        qa += SLOT / 16;
                        fence_async_smem();
                    }
                    if (shifted) {
                        slot_wait(sb + BAR_FULL, fph, r);
                        wg_wait<0>();
                        reg_fence(o);
                        release_if(eb, vs, rel);
                        softmax_shift(s, m[0], m[1]);
                        plain = true;
                        break;
                    }
                    float e[4 * EARLY];
#pragma unroll
                    for (int i = 0; i < 4 * EARLY; i++) {
                        e[i] = ex2(s[i]);
                        t[i & 3] = i < 4 ? e[i] : t[i & 3] + e[i];
                    }
                    reg_fence(e);
                    slot_wait(sb + BAR_FULL, fph, r);
                    wg_wait<0>();
                    reg_fence(o);
                    reg_fence(e);
                    release_if(eb, vs, rel);
#pragma unroll
                    for (int i = 0; i < 2 * EARLY; i++) p[i] = pack2(e[2 * i], e[2 * i + 1]);
                    softmax_exp<EARLY, 16>(s, p, t);
                    t[0] += t[1];
                    t[2] += t[3];
                    bad = softmax_unsafe(t[0], t[2], false);
                } while (!bad);
                if (!bad && !plain) break;
            }
            const uint32_t vs = r, ga = desc_k(sb + (hp ? 2 * (wg ^ kh ^ 1) : wg) * 8192), as = 2 + 2 * hp;
            r = ring_next(r);
            slot_wait(sb + BAR_FULL, fph, 5);
            slot_wait(sb + BAR_FULL, fph, r);
            bar_sync(1 + wg, 256);
            gemm_issue<true>(s, ga + 5 * (SLOT / 16), wd + r * (SLOT / 16), 0, hp);
            pv_issue(o, p, vd + vs * (SLOT / 16), j, hn == 16);
            bar_arrive(2 - wg, 256);
            li[0] = rcp(quad_sum(l[0]));
            li[1] = rcp(quad_sum(l[1]));
            cimg = img + (ptrdiff_t)(2 * j - 15) * 32 * SLOT + (wg ? -16384 : 16384);
            wg_wait<1>();
            release_if(eb, 5, rel);
            release_if(eb, r, rel && hp);
            wg_wait<0>();
            release_if(eb, vs, rel);
            reg_fence(o);
            img_store_global<0>(cimg, toff, o, li[0], li[1]);
            slot_wait(sb + BAR_FULL, fph, as);
            slot_wait(sb + BAR_FULL, fph, 0);
            bar_sync(1 + wg, 256);
            gemm_issue<false>(s, ga + as * (SLOT / 16), wd, 1, hp);
            bar_arrive(2 - wg, 256);
            reg_fence(o);
            img_store_global<1>(cimg, toff, o, li[0], li[1]);
            wg_wait<0>();
            release_if(eb, as, rel);
            release_if(eb, 0, rel && hp);
            if (elected) TS(8 + 10 * hp + 20 * wg);
        }
        uint32_t otab = 0x0423516u;
        const uint32_t oa = desc_k(sb + (wg ^ kh ^ 1) * 16384);
        const int t7 = tid & 127, w4 = warp & 3, row = ort * 128 + kh * 64 + w4 * 16 + g;
#pragma unroll 1
        for (int i = 2; i < 15 - wg; i++) {
            const uint32_t as = o_next(otab), ws = o_next(otab);
            slot_wait(sb + BAR_FULL, fph, as);
            slot_wait(sb + BAR_FULL, fph, ws);
            bar_sync(1 + wg, 256);
            gemm_issue<false>(s, oa + as * (SLOT / 16), wd + ws * (SLOT / 16), 1, true);
            bar_arrive(2 - wg, 256);
            wg_wait<1>();
            reg_fence(o);
            if (i == 2) img_store_global<2>(cimg, toff, o, li[0], li[1]);
            if (i == CLAST) {
                img_store_global<3>(cimg, toff, o, li[0], li[1]);
                __syncwarp();
                mbar_arrive_if(sb + BAR_DONE + 64, lane == 0);
            }
            wg_wait<0>();
            release_if(eb, as, rel);
            release_if(eb, ws, rel);
        }
        mbar_wait(sb + BAR_PF, 0);
        const uint32_t ep = lds32(sb + SM_EP);
        if (wg == 0) {
            reg_fence(s);
            if (elected) TS(9);
#pragma unroll
            for (int v = 0; v < 8; v++)
                st_pub(g_out + rb * OB + v * 128 + t7, make_uint4((pack2(s[8 * v], s[8 * v + 1]) & ~1u) | (ep & 1), pack2(s[8 * v + 2], s[8 * v + 3]),
                                                                      pack2(s[8 * v + 4], s[8 * v + 5]), pack2(s[8 * v + 6], s[8 * v + 7])), true);
            o_next(otab); o_next(otab); o_next(otab); o_next(otab);
            const uint32_t s1 = o_next(otab), s2 = o_next(otab);
            bar_sync(4, 256);
            uint32_t wf[64];
            float wn[64];
            if (rb < NFFN) {
                slot_wait(sb + BAR_FULL, fph, s1);
                const uint32_t a = sb + s1 * SLOT + (w4 * 128 + (lane >> 4) * 8 + (lane & 7)) * 32 + ((lane >> 3) & 1) * 16;
#pragma unroll
                for (int i = 0; i < 16; i++)
                    asm volatile("ldmatrix.sync.aligned.m8n8.x4.trans.shared.b16 {%0, %1, %2, %3}, [%4];"
                                 : "=r"(wf[4 * i]), "=r"(wf[4 * i + 1]), "=r"(wf[4 * i + 2]), "=r"(wf[4 * i + 3])
                                 : "r"(a + (i >> 3) * 16384 + (i & 7) * 512) : "memory");
                slot_wait(sb + BAR_FULL, fph, s2);
#pragma unroll
                for (int i = 0; i < 16; i++) {
                    const uint2 w = *reinterpret_cast<const uint2*>(smem + s2 * SLOT + i * 1024 + t7 * 8);
                    wn[4 * i] = bf_lo(w.x); wn[4 * i + 1] = bf_hi(w.x); wn[4 * i + 2] = bf_lo(w.y); wn[4 * i + 3] = bf_hi(w.y);
                }
                reg_fence(wn);
            }
            const uint32_t gbf = __ldcg(reinterpret_cast<const uint32_t*>(g_mod) + 1280 + rb * 2 + (tid & 1));
            if (elected) TS(10);
            const uint32_t best = best_key(g_key + cq * 128, lane, ep);
            const int sel = (~best >> 5) & 2047;
            if (elected) TS(19);
            const uint4* cp = g_cand + (sel >> 4) * 192;
            float* sred = reinterpret_cast<float*>(smem + SM_RED);
            const int pq = (2 * rb + (tid & 1)) & 63, pv = (pq >> 2) / 3;
            const uint4* fp = cp + (rb >> 5) * 24 + pv * 4 + (pq & 3);
            uint4 fh = ld_poll(fp), fx = ld_poll(fp + 96);
            if (rb < NFFN) {
                uint4 cv[6];
                for (;;) {
                    uint32_t bad = 0;
#pragma unroll
                    for (int v = 0; v < 6; v++) cv[v] = ld_poll(cp + w4 * 24 + v * 4 + c4);
#pragma unroll
                    for (int v = 0; v < 6; v++) bad |= cv[v].w ^ ep;
                    if (__all_sync(0xffffffffu, bad == 0)) break;
                }
                if (elected) TS(20);
                float d[4][4] = {};
#pragma unroll
                for (int k = 0; k < 8; k++) {
                    const uint32_t b0 = (&cv[(2 * k) / 3].x)[(2 * k) % 3], b1 = (&cv[(2 * k + 1) / 3].x)[(2 * k + 1) % 3];
                    mma16816(d[k & 1], wf + 4 * k, b0, b1);
                    mma16816(d[2 + (k & 1)], wf + 32 + 4 * k, b0, b1);
                }
                const float u = (c4 & 2) ? ((c4 & 1) ? d[2][2] + d[3][2] : d[2][0] + d[3][0]) : ((c4 & 1) ? d[0][2] + d[1][2] : d[0][0] + d[1][0]);
                sred[w4 * 32 + c4 * 8 + g] = u;
                bar_sync(3, 128);
                const float v = rbf((sred[lane] + sred[32 + lane]) + (sred[64 + lane] + sred[96 + lane]));
                const float act = rbf(rbf(v * sigmoid(v)) * __shfl_down_sync(0xffffffffu, v, 16));
                float y[4] = {0.f, 0.f, 0.f, 0.f};
#pragma unroll
                for (int k = 0; k < 16; k++) {
                    const float a = __shfl_sync(0xffffffffu, act, k);
#pragma unroll
                    for (int i = 0; i < 4; i++) y[i] = fmaf(a, wn[4 * k + i], y[i]);
                }
                st_pub(g_out + rb * OB + OB_Y + t7, make_uint4((__float_as_uint(y[0]) & ~15u) | (ep & 15), __float_as_uint(y[1]), __float_as_uint(y[2]), __float_as_uint(y[3])), true);
            }
            if (rb == 0 && tid == 0) g_sync.epoch[0] = ep;
            if (elected) TS(60);
            uint4 yv;
            do yv = ld_poll(g_out + min(t7, NFFN - 1) * OB + OB_Y + rb);
            while (!__all_sync(0xffffffffu, ((yv.x ^ ep) & 15) == 0));
            if (elected) TS(61);
            float y[4] = {0.f, 0.f, 0.f, 0.f};
            if (t7 < NFFN) { y[0] = __uint_as_float(yv.x); y[1] = __uint_as_float(yv.y); y[2] = __uint_as_float(yv.z); y[3] = __uint_as_float(yv.w); }
            const float z0 = ((lane & 16) ? y[2] : y[0]) + __shfl_xor_sync(0xffffffffu, (lane & 16) ? y[0] : y[2], 16);
            const float z1 = ((lane & 16) ? y[3] : y[1]) + __shfl_xor_sync(0xffffffffu, (lane & 16) ? y[1] : y[3], 16);
            float z = ((lane & 8) ? z1 : z0) + __shfl_xor_sync(0xffffffffu, (lane & 8) ? z0 : z1, 8);
            z += __shfl_xor_sync(0xffffffffu, z, 4);
            z = quad_sum(z);
            if ((lane & 7) == 0) sred[128 + (lane >> 3) * 4 + w4] = z;
            bar_sync(3, 128);
            if (tid < 2) {
                while (fh.w != ep || fx.w != ep) { fh = ld_poll(fp); fx = ld_poll(fp + 96); }
                const float4 y0 = *reinterpret_cast<const float4*>(sred + 128 + tid * 8), y1 = *reinterpret_cast<const float4*>(sred + 132 + tid * 8);
                const int cm = (pq >> 2) - 3 * pv;
                const uint32_t h2 = cm == 0 ? fh.x : cm == 1 ? fh.y : fh.z, x2 = cm == 0 ? fx.x : cm == 1 ? fx.y : fx.z;
                const float sg = sigmoid(bf_hi((best & 0x80000000u) ? (best ^ 0x80000000u) : ~best));
                reinterpret_cast<uint32_t*>(P.out)[sel * 256 + rb * 2 + tid] =
                    badd(x2, bmul(gbf, badd(h2, bmul(pack2((y0.x + y0.y) + (y0.z + y0.w), (y1.x + y1.y) + (y1.z + y1.w)), pack2(sg, sg)))));
            }
            if (elected) TS(62);
        } else {
            const float4* tf = reinterpret_cast<const float4*>(smem + SM_TAB) + c4;
            const uint32_t as14 = otab & 15, xa = sb + ((otab >> 8) & 15) * SLOT + (kh ^ 1) * 16384 + (w4 * 16 + (lane & 15)) * 128;
            uint32_t x2[32];
            bar_sync(2, 256);
#pragma unroll 1
            for (int i = 14; i < 17; i++) {
                const uint32_t as = o_next(otab), ws = o_next(otab);
                slot_wait(sb + BAR_FULL, fph, as);
                slot_wait(sb + BAR_FULL, fph, ws);
                gemm_issue<false>(s, oa + as * (SLOT / 16), wd + ws * (SLOT / 16), 1, true);
                wg_wait<1>();
                release_if(eb, as14, rel && i == 15);
            }
            if (elected) TS(29);
            {
#pragma unroll
                for (int k = 0; k < 8; k++)
                    asm volatile("ldmatrix.sync.aligned.m8n8.x4.shared.b16 {%0, %1, %2, %3}, [%4];"
                                 : "=r"(x2[4 * k]), "=r"(x2[4 * k + 1]), "=r"(x2[4 * k + 2]), "=r"(x2[4 * k + 3])
                                 : "r"(xa + (k >> 2) * 8192 + (((2 * (k & 3) + (lane >> 4)) ^ (lane & 7)) << 4)) : "memory");
            }
            wg_wait<0>();
            reg_fence(s);
            bar_arrive(4, 256);
            if (elected) TS(39);
            const uint4* pr = g_out + (rb ^ 8) * OB + t7;
            uint4 pa[8];
#pragma unroll
            for (int v = 0; v < 8; v++) pa[v] = ld_poll(pr + v * 128);
            float4 tc[16];
#pragma unroll
            for (int k = 0; k < 16; k++) {
                tc[k] = tf[k * 4];
#pragma unroll
                for (int i = 4 * k; i < 4 * k + 4; i++) s[i] = fmaf((i & 1) ? tc[k].y : tc[k].x, s[i], (i & 1) ? bf_hi(x2[i >> 1]) : bf_lo(x2[i >> 1]));
            }
            reg_fence(s);
            for (;;) {
                uint32_t bad = 0;
#pragma unroll
                for (int v = 0; v < 8; v++) bad |= pa[v].x ^ ep;
                if (__all_sync(0xffffffffu, (bad & 1) == 0)) break;
#pragma unroll
                for (int v = 0; v < 8; v++) pa[v] = ld_poll(pr + v * 128);
            }
            if (elected) TS(30);
            float st[6] = {0.f, 0.f, 0.f, 0.f, 0.f, 0.f};
#pragma unroll
            for (int i = 0; i < 64; i++) {
                const int rh = (i >> 1) & 1;
                const uint32_t w = (&pa[i >> 3].x)[(i >> 1) & 3];
                const float v = fmaf((i & 1) ? tc[i >> 2].y : tc[i >> 2].x, (i & 1) ? bf_hi(w) : bf_lo(w), s[i]);
                s[i] = v;
                st[rh] += v;
                st[2 + rh] = fmaf(v, v, st[2 + rh]);
                st[4 + rh] = fmaf(v, (i & 1) ? tc[i >> 2].w : tc[i >> 2].z, st[4 + rh]);
            }
#pragma unroll
            for (int i = 0; i < 6; i++) st[i] = quad_sum(st[i]);
            st_pub(g_out + rb * OB + OB_STAT + (w4 * 8 + g) * 2 + (c4 & 1),
                   make_uint4(__float_as_uint((c4 & 1) ? st[1] : st[0]), __float_as_uint((c4 & 1) ? st[3] : st[2]),
                              __float_as_uint((c4 & 1) ? st[5] : st[4]), ep), c4 < 2);
            if (elected) TS(56);
            uint32_t cb[16], sh[16], gb[16];
#pragma unroll
            for (int i = 0; i < 16; i++) {
                const float4 c = tf[64 + i * 4];
                cb[i] = __float_as_uint(c.x); sh[i] = __float_as_uint(c.y); gb[i] = __float_as_uint(c.z);
            }
            const float ra = __uint_as_float(lds32(sb + SM_EP + 8)), rb0 = __uint_as_float(lds32(sb + SM_EP + 12));
#pragma unroll
            for (int i = 0; i < 32; i++) x2[i] = pack2(s[2 * i], s[2 * i + 1]);
            reg_fence(x2);
            uint4 r0, r1;
            for (;;) {
                r0 = ld_poll(g_out + ((rb & ~3) + c4) * OB + OB_STAT + (w4 * 8 + g) * 2);
                r1 = ld_poll(g_out + ((rb & ~3) + c4) * OB + OB_STAT + (w4 * 8 + g) * 2 + 1);
                if (__all_sync(0xffffffffu, r0.w == ep && r1.w == ep)) break;
            }
            if (elected) TS(57);
            const float m0 = quad_sum(__uint_as_float(r0.x)) * (1.f / 512.f), m1 = quad_sum(__uint_as_float(r1.x)) * (1.f / 512.f);
            const float rs0 = ln_rstd(fmaxf(fmaf(-m0, m0, quad_sum(__uint_as_float(r0.y)) * (1.f / 512.f)), 0.f));
            const float rs1 = ln_rstd(fmaxf(fmaf(-m1, m1, quad_sum(__uint_as_float(r1.y)) * (1.f / 512.f)), 0.f));
            const uint32_t mb0 = pack2(m0, m0), mb1 = pack2(m1, m1);
            const uint32_t lg = pack2(fmaf(rs0, fmaf(-bf_lo(mb0), ra, quad_sum(__uint_as_float(r0.z))), rb0),
                                      fmaf(rs1, fmaf(-bf_lo(mb1), ra, quad_sum(__uint_as_float(r1.z))), rb0));
            const uint32_t u0 = lg << 16, u1 = lg & 0xffff0000u;
            const uint32_t k0 = ((u0 ^ (((int)u0 >> 31) | 0x80000000u)) & 0xffff0000u) | ((2047 - row) << 5) | (ep & 31);
            const uint32_t k1 = ((u1 ^ (((int)u1 >> 31) | 0x80000000u)) & 0xffff0000u) | ((2039 - row) << 5) | (ep & 31);
            const uint32_t kb = __reduce_max_sync(0xffffffffu, max(k0, k1));
            st_pub(g_key + cq * 128 + (row >> 4), kb, lane == 0);
            {
                uint32_t cx[18], ch[18];
#pragma unroll
                for (int i = 0; i < 16; i++) {
                    cx[i] = kb == k1 ? x2[2 * i + 1] : x2[2 * i];
                    ch[i] = ln_apply(cx[i], kb == k1 ? mb1 : mb0, kb == k1 ? rs1 : rs0, cb[i], sh[i]);
                }
                cx[16] = cx[17] = ch[16] = ch[17] = 0;
                uint4* cp = g_cand + (row >> 4) * 192 + cq * 24 + c4;
#pragma unroll
                for (int v = 0; v < 6; v++) st_pub(cp + v * 4, make_uint4(ch[3 * v], ch[3 * v + 1], ch[3 * v + 2], ep), kb == k0 || kb == k1);
#pragma unroll
                for (int v = 0; v < 6; v++) st_pub(cp + 96 + v * 4, make_uint4(cx[3 * v], cx[3 * v + 1], cx[3 * v + 2], ep), kb == k0 || kb == k1);
            }
            if (elected) TS(58);
            uint2 ov[16];
#pragma unroll
            for (int i = 0; i < 16; i++) {
                const int rh = i & 1, jj = i & 14;
                const uint32_t v0 = badd(x2[2 * jj + rh], bmul(gb[jj], ln_apply(x2[2 * jj + rh], rh ? mb1 : mb0, rh ? rs1 : rs0, cb[jj], sh[jj])));
                const uint32_t v1 = badd(x2[2 * jj + 2 + rh], bmul(gb[jj + 1], ln_apply(x2[2 * jj + 2 + rh], rh ? mb1 : mb0, rh ? rs1 : rs0, cb[jj + 1], sh[jj + 1])));
                const uint32_t rv = __shfl_xor_sync(0xffffffffu, (c4 & 1) ? v0 : v1, 1);
                ov[i] = (c4 & 1) ? make_uint2(rv, v1) : make_uint2(v0, rv);
            }
            uint2* op = reinterpret_cast<uint2*>(P.out) + row * 128 + cq * 32 + (c4 & 1) * 2 + (c4 >> 1);
#pragma unroll
            for (int i = 0; i < 16; i++)
                if (kb != ((i & 1) ? k1 : k0)) op[(i & 1) * 1024 + (i & 14) * 2] = ov[i];
            const uint32_t best = best_key(g_key + cq * 128, lane, ep);
            if (best != kb) {
#pragma unroll
                for (int i = 0; i < 16; i++)
                    if (kb == ((i & 1) ? k1 : k0)) op[(i & 1) * 1024 + (i & 14) * 2] = ov[i];
            }
            if (elected) TS(59);
        }
        mbar_arrive_if(sb + BAR_END, lane == 0);
    }
}

typedef CUresult (*EncodeFn)(CUtensorMap*, CUtensorMapDataType, cuuint32_t, void*, const cuuint64_t*, const cuuint64_t*,
                             const cuuint32_t*, const cuuint32_t*, CUtensorMapInterleave, CUtensorMapSwizzle,
                             CUtensorMapL2promotion, CUtensorMapFloatOOBfill);

void make_2d(EncodeFn fn, CUtensorMap* m, const void* p, uint64_t cols, uint64_t rows, uint32_t bc, uint32_t br) {
    cuuint64_t dims[2] = {cols, rows}, strides[1] = {cols * 2};
    cuuint32_t box[2] = {bc, br}, es[2] = {1, 1};
    fn(m, CU_TENSOR_MAP_DATA_TYPE_BFLOAT16, 2, const_cast<void*>(p), dims, strides, box, es, CU_TENSOR_MAP_INTERLEAVE_NONE,
       CU_TENSOR_MAP_SWIZZLE_NONE, CU_TENSOR_MAP_L2_PROMOTION_L2_128B, CU_TENSOR_MAP_FLOAT_OOB_FILL_NONE);
}
void make_3d(EncodeFn fn, CUtensorMap* m, const void* p, uint64_t cols, uint64_t rows, uint32_t br = 128, uint32_t nb = 2) {
    cuuint64_t dims[3] = {64, rows, cols / 64}, strides[2] = {cols * 2, 128};
    cuuint32_t box[3] = {64, br, nb}, es[3] = {1, 1, 1};
    fn(m, CU_TENSOR_MAP_DATA_TYPE_BFLOAT16, 3, const_cast<void*>(p), dims, strides, box, es, CU_TENSOR_MAP_INTERLEAVE_NONE,
       CU_TENSOR_MAP_SWIZZLE_128B, CU_TENSOR_MAP_L2_PROMOTION_L2_256B, CU_TENSOR_MAP_FLOAT_OOB_FILL_NONE);
}

}

extern "C" void kernel_launch(void* const* d_in, const int* in_sizes, int n_in, void* d_out, int out_size) {
    static EncodeFn fn = nullptr;
    static int sms = 0;
    if (!fn) {
        void* f = nullptr;
        cudaDriverEntryPointQueryResult st;
        cudaGetDriverEntryPoint("cuTensorMapEncodeTiled", &f, cudaEnableDefault, &st);
        fn = (EncodeFn)f;
        int dev = 0;
        cudaGetDevice(&dev);
        cudaDeviceGetAttribute(&sms, cudaDevAttrMultiProcessorCount, dev);
        cudaFuncSetAttribute(fused_kernel, cudaFuncAttributeMaxDynamicSharedMemorySize, SMEM_BYTES);
    }
    CUtensorMap ckv, wq, wuk, wuv, wo, wg, wu, wm, xm;
    make_3d(fn, &ckv, d_in[1], 512, 2048, 128, (MC & 1) ? 1 : 2);
    make_3d(fn, &xm, d_in[0], 512, 2048, 64);
    make_3d(fn, &wq, d_in[2], 4096, 512, 128, (MC & 2) ? 1 : 2);
    make_3d(fn, &wuk, d_in[3], 4096, 512);
    make_3d(fn, &wuv, d_in[4], 4096, 512);
    make_3d(fn, &wo, d_in[5], 512, 4096);
    make_2d(fn, &wg, d_in[8], 1792, 512, 16, 256);
    make_2d(fn, &wu, d_in[9], 1792, 512, 16, 256);
    make_2d(fn, &wm, d_in[12], 3072, 512, 256, 64);
    Params p;
    p.x = (const bf16*)d_in[0];
    p.ckv = (const bf16*)d_in[1];
    p.wo = (const bf16*)d_in[5];
    p.wr = (const bf16*)d_in[7];
    p.wdown = (const bf16*)d_in[10];
    p.c = (const bf16*)d_in[11];
    p.out = (bf16*)d_out;
    p.by_smid = sms == NCTA + NSPARE;
    fused_kernel<<<NCTA + NSPARE, 384, SMEM_BYTES>>>(ckv, wq, wuk, wuv, wo, wg, wu, wm, xm, p);
}
```

```cpp
#include <cuda.h>
#include <cuda_bf16.h>
#include <cuda_runtime.h>
#include <stdint.h>
#include <stdio.h>

namespace {

typedef __nv_bfloat16 bf16;
typedef unsigned long long u64;

constexpr int NCTA = 128, NSPARE = 4;
constexpr int SLOT = 32768;
constexpr int SM_BAR = 7 * SLOT;
constexpr int BAR_FULL = SM_BAR;
constexpr int BAR_EMPTY = BAR_FULL + 8 * 7;
constexpr int BAR_DONE = BAR_EMPTY + 8 * 7;
constexpr int BAR_FLAG = BAR_DONE + 8 * 9;
constexpr int BAR_PF = BAR_FLAG + 8 * 9;
constexpr int BAR_END = BAR_PF + 8;
constexpr int SM_EP = BAR_END + 8;
constexpr int SM_RED = SM_BAR + 384;
constexpr int SM_TAB = SM_BAR + 1024;
constexpr int SMEM_BYTES = SM_BAR + 3072;
constexpr int NFFN = 112;
#define HINT 31
constexpr u64 L2_NORMAL = 0x1000000000000000ull, L2_FIRST = 0x12F0000000000000ull;
#define PF0 0
#define PFA 9
#define PFB 6
#define PFC 12
#define PFMASK 1023
#define UNR 4
#define POLL_NS 50
#define CLAST 2
#define OBINIT 1
#define MC 15
#define LATEMASK 1
#define EARLY 7
constexpr uint32_t SPIN_LIMIT = 1u << 22;
constexpr uint32_t ONE2 = 0x3f803f80u;

struct Sync {
    uint32_t modcnt[2 * 32];
    uint32_t hcnt[16 * 8];
    uint32_t kvcnt[32 * 2 * 8];
    uint32_t ctxcnt[16 * 32];
    uint32_t rdcnt[16 * 2 * 8];
    uint32_t epoch[32];
};

__device__ __align__(1024) uint8_t g_KV[16 * 16 * 2 * SLOT];
__device__ __align__(1024) uint8_t g_ctx[16 * 32 * SLOT];
__device__ __align__(1024) uint8_t g_h[16 * 4 * SLOT];
constexpr int OB = 1216, OB_STAT = 1024, OB_Y = 1088;
__device__ __align__(1024) uint4 g_out[128 * OB];
__device__ __align__(1024) bf16 g_mod[3072];
__device__ __align__(1024) uint4 g_cand[128 * 192];
__device__ __align__(1024) uint32_t g_key[4 * 128];
__device__ __align__(1024) uint8_t g_wf[NFFN * SLOT];
__device__ __align__(1024) Sync g_sync;
#define TS(i)

#define PT()

struct Params {
    const bf16 *x, *ckv, *wo, *wr, *wdown, *c;
    bf16* out;
    int by_smid, zero;
};

__device__ __forceinline__ void mbar_init(uint32_t bar, uint32_t cnt) {
    asm volatile("mbarrier.init.shared::cta.b64 [%0], %1;" ::"r"(bar), "r"(cnt) : "memory");
}
__device__ __forceinline__ void mbar_wait(uint32_t bar, uint32_t parity) {
    asm volatile("{\n.reg .pred p;\nL_%=:\nmbarrier.try_wait.parity.shared::cta.b64 p, [%0], %1;\n@!p bra L_%=;\n}" ::"r"(bar), "r"(parity) : "memory");
}
__device__ __forceinline__ void mbar_watch(uint32_t bar, uint32_t parity) {
    asm volatile("{\n.reg .pred p;\n.reg .u32 n;\nmov.u32 n, 0;\n"
                 "L_%=:\nmbarrier.try_wait.parity.shared::cta.b64 p, [%0], %1;\n@p bra D_%=;\n"
                 "add.u32 n, n, 1;\nsetp.lt.u32 p, n, %2;\n@p bra L_%=;\ntrap;\nD_%=:\n}"
                 ::"r"(bar), "r"(parity), "n"(SPIN_LIMIT) : "memory");
}
__device__ __forceinline__ void step_watch(uint32_t a, uint32_t step) {
    asm volatile("{\n.reg .pred p;\n.reg .u32 n, v;\nmov.u32 n, 0;\n"
                 "L_%=:\nld.volatile.shared.u32 v, [%0];\nsetp.ge.u32 p, v, %1;\n@p bra D_%=;\nnanosleep.u32 200;\n"
                 "add.u32 n, n, 1;\nsetp.lt.u32 p, n, %2;\n@p bra L_%=;\ntrap;\nD_%=:\n}"
                 ::"r"(a), "r"(step), "n"(SPIN_LIMIT) : "memory");
}
__device__ __forceinline__ void mbar_arrive(uint32_t bar) {
    asm volatile("mbarrier.arrive.shared::cta.b64 _, [%0];" ::"r"(bar) : "memory");
}
__device__ __forceinline__ void mbar_arrive_if(uint32_t bar, bool on) {
    asm volatile("{\n.reg .pred p;\nsetp.ne.s32 p, %1, 0;\n@p mbarrier.arrive.shared::cta.b64 _, [%0];\n}" ::"r"(bar), "r"((int)on) : "memory");
}
__device__ __forceinline__ void mbar_expect(uint32_t bar, uint32_t bytes) {
    asm volatile("mbarrier.arrive.expect_tx.shared::cta.b64 _, [%0], %1;" ::"r"(bar), "r"(bytes) : "memory");
}
__device__ __forceinline__ void tma2d(uint32_t dst, const CUtensorMap* m, int c0, int c1, uint32_t bar) {
    asm volatile("cp.async.bulk.tensor.2d.shared::cluster.global.mbarrier::complete_tx::bytes [%0], [%1, {%3, %4}], [%2];"
                 ::"r"(dst), "l"(m), "r"(bar), "r"(c0), "r"(c1) : "memory");
}
__device__ __forceinline__ void tma3d_prefetch(const CUtensorMap* m, int row, int cb) {
    asm volatile("cp.async.bulk.prefetch.tensor.3d.L2.global [%0, {%1, %2, %3}];" ::"l"(m), "r"(0), "r"(row), "r"(cb) : "memory");
}
__device__ __forceinline__ void l2_prefetch(const void* p, uint32_t bytes) {
    asm volatile("cp.async.bulk.prefetch.L2.global [%0], %1;" ::"l"(p), "r"(bytes) : "memory");
}
__device__ __forceinline__ void flag_wait(const uint32_t* f, uint32_t target) {
    asm volatile("{\n.reg .pred p;\n.reg .u32 v;\n"
                 "L_%=:\nld.acquire.gpu.global.u32 v, [%0];\nsub.u32 v, v, %1;\nsetp.lt.s32 p, v, 0;\n@p nanosleep.u32 100;\n@p bra L_%=;\n}"
                 ::"l"(f), "r"(target) : "memory");
}
__device__ __forceinline__ uint4 ld_poll(const uint4* p) {
    uint4 v;
    asm volatile("{\n.reg .b128 t;\nld.relaxed.gpu.global.b128 t, [%4];\nmov.b128 {%0, %1, %2, %3}, t;\n}"
                 : "=r"(v.x), "=r"(v.y), "=r"(v.z), "=r"(v.w) : "l"(p) : "memory");
    return v;
}
__device__ __forceinline__ void st_pub(uint4* p, uint4 v, bool on) {
    asm volatile("{\n.reg .pred p;\n.reg .b128 t;\nsetp.ne.s32 p, %5, 0;\nmov.b128 t, {%1, %2, %3, %4};\n@p st.relaxed.gpu.global.b128 [%0], t;\n}"
                 ::"l"(p), "r"(v.x), "r"(v.y), "r"(v.z), "r"(v.w), "r"((int)on) : "memory");
}
__device__ __forceinline__ void st_pub(uint32_t* p, uint32_t v, bool on) {
    asm volatile("{\n.reg .pred p;\nsetp.ne.s32 p, %2, 0;\n@p st.relaxed.gpu.global.u32 [%0], %1;\n}" ::"l"(p), "r"(v), "r"((int)on) : "memory");
}
__device__ __forceinline__ void flag_add(uint32_t* p) {
    asm volatile("red.release.gpu.global.add.u32 [%0], 1;" ::"l"(p) : "memory");
}
__device__ __forceinline__ uint32_t lds32(uint32_t a) {
    uint32_t v;
    asm volatile("ld.shared.u32 %0, [%1];" : "=r"(v) : "r"(a) : "memory");
    return v;
}
__device__ __forceinline__ uint4 lds128(uint32_t a) {
    uint4 v;
    asm volatile("ld.shared.v4.u32 {%0, %1, %2, %3}, [%4];" : "=r"(v.x), "=r"(v.y), "=r"(v.z), "=r"(v.w) : "r"(a) : "memory");
    return v;
}
__device__ __forceinline__ void fence_async_global() { asm volatile("fence.proxy.async.global;" ::: "memory"); }
__device__ __forceinline__ void fence_async_smem() { asm volatile("fence.proxy.async.shared::cta;" ::: "memory"); }
__device__ __forceinline__ void bar_sync(int id, int n) { asm volatile("bar.sync %0, %1;" ::"r"(id), "r"(n) : "memory"); }
__device__ __forceinline__ void bar_arrive(int id, int n) { asm volatile("bar.arrive %0, %1;" ::"r"(id), "r"(n) : "memory"); }
__device__ __forceinline__ void wg_fence() { asm volatile("wgmma.fence.sync.aligned;" ::: "memory"); }
__device__ __forceinline__ void wg_commit() { asm volatile("wgmma.commit_group.sync.aligned;" ::: "memory"); }
template <int N> __device__ __forceinline__ void wg_wait() { asm volatile("wgmma.wait_group.sync.aligned %0;" ::"n"(N) : "memory"); }
template <int N> __device__ __forceinline__ void reg_fence(float (&d)[N]) {
#pragma unroll
    for (int i = 0; i < N; i++) asm volatile("" : "+f"(d[i])::"memory");
}
template <int N> __device__ __forceinline__ void reg_fence(uint32_t (&d)[N]) {
#pragma unroll
    for (int i = 0; i < N; i++) asm volatile("" : "+r"(d[i])::"memory");
}
__device__ __forceinline__ uint32_t desc_k(uint32_t a) { return ((a & 0x3ffff) >> 4) | (1u << 16); }
__device__ __forceinline__ uint32_t desc_mn(uint32_t a) { return ((a & 0x3ffff) >> 4) | (1024u << 16); }

template <int TB>
__device__ __forceinline__ void wgmma_ss128(float (&d)[64], uint32_t da, uint32_t db, int acc, uint32_t ha = 0x40000040u, uint32_t hb = 0x40000040u) {
    asm volatile("{\n.reg .pred p;\n.reg .b64 a, b;\nsetp.ne.b32 p, %66, 0;\nmov.b64 a, {%64, %68};\nmov.b64 b, {%65, %69};\n"
        "wgmma.mma_async.sync.aligned.m64n128k16.f32.bf16.bf16 {%0, %1, %2, %3, %4, %5, %6, %7, %8, %9, %10, %11, %12, %13, %14, %15, %16, %17, %18, %19, %20, %21, %22, %23, %24, %25, %26, %27, %28, %29, %30, %31, %32, %33, %34, %35, %36, %37, %38, %39, %40, %41, %42, %43, %44, %45, %46, %47, %48, %49, %50, %51, %52, %53, %54, %55, %56, %57, %58, %59, %60, %61, %62, %63}, a, b, p, 1, 1, 0, %67;\n}"
        : "+f"(d[0]), "+f"(d[1]), "+f"(d[2]), "+f"(d[3]), "+f"(d[4]), "+f"(d[5]), "+f"(d[6]), "+f"(d[7]), "+f"(d[8]), "+f"(d[9]), "+f"(d[10]), "+f"(d[11]), "+f"(d[12]), "+f"(d[13]), "+f"(d[14]), "+f"(d[15]), "+f"(d[16]), "+f"(d[17]), "+f"(d[18]), "+f"(d[19]), "+f"(d[20]), "+f"(d[21]), "+f"(d[22]), "+f"(d[23]), "+f"(d[24]), "+f"(d[25]), "+f"(d[26]), "+f"(d[27]), "+f"(d[28]), "+f"(d[29]), "+f"(d[30]), "+f"(d[31]), "+f"(d[32]), "+f"(d[33]), "+f"(d[34]), "+f"(d[35]), "+f"(d[36]), "+f"(d[37]), "+f"(d[38]), "+f"(d[39]), "+f"(d[40]), "+f"(d[41]), "+f"(d[42]), "+f"(d[43]), "+f"(d[44]), "+f"(d[45]), "+f"(d[46]), "+f"(d[47]), "+f"(d[48]), "+f"(d[49]), "+f"(d[50]), "+f"(d[51]), "+f"(d[52]), "+f"(d[53]), "+f"(d[54]), "+f"(d[55]), "+f"(d[56]), "+f"(d[57]), "+f"(d[58]), "+f"(d[59]), "+f"(d[60]), "+f"(d[61]), "+f"(d[62]), "+f"(d[63])
        : "r"(da), "r"(db), "r"(acc), "n"(TB), "r"(ha), "r"(hb));
}
template <int TB>
__device__ __forceinline__ void wgmma_ss128_init(float (&d)[64], uint32_t da, uint32_t db, uint32_t ha = 0x40000040u, uint32_t hb = 0x40000040u) {
    asm volatile("{\n.reg .pred p;\n.reg .b64 a, b;\nsetp.ne.b32 p, 0, 0;\nmov.b64 a, {%64, %67};\nmov.b64 b, {%65, %68};\n"
        "wgmma.mma_async.sync.aligned.m64n128k16.f32.bf16.bf16 {%0, %1, %2, %3, %4, %5, %6, %7, %8, %9, %10, %11, %12, %13, %14, %15, %16, %17, %18, %19, %20, %21, %22, %23, %24, %25, %26, %27, %28, %29, %30, %31, %32, %33, %34, %35, %36, %37, %38, %39, %40, %41, %42, %43, %44, %45, %46, %47, %48, %49, %50, %51, %52, %53, %54, %55, %56, %57, %58, %59, %60, %61, %62, %63}, a, b, p, 1, 1, 0, %66;\n}"
        : "=f"(d[0]), "=f"(d[1]), "=f"(d[2]), "=f"(d[3]), "=f"(d[4]), "=f"(d[5]), "=f"(d[6]), "=f"(d[7]), "=f"(d[8]), "=f"(d[9]), "=f"(d[10]), "=f"(d[11]), "=f"(d[12]), "=f"(d[13]), "=f"(d[14]), "=f"(d[15]), "=f"(d[16]), "=f"(d[17]), "=f"(d[18]), "=f"(d[19]), "=f"(d[20]), "=f"(d[21]), "=f"(d[22]), "=f"(d[23]), "=f"(d[24]), "=f"(d[25]), "=f"(d[26]), "=f"(d[27]), "=f"(d[28]), "=f"(d[29]), "=f"(d[30]), "=f"(d[31]), "=f"(d[32]), "=f"(d[33]), "=f"(d[34]), "=f"(d[35]), "=f"(d[36]), "=f"(d[37]), "=f"(d[38]), "=f"(d[39]), "=f"(d[40]), "=f"(d[41]), "=f"(d[42]), "=f"(d[43]), "=f"(d[44]), "=f"(d[45]), "=f"(d[46]), "=f"(d[47]), "=f"(d[48]), "=f"(d[49]), "=f"(d[50]), "=f"(d[51]), "=f"(d[52]), "=f"(d[53]), "=f"(d[54]), "=f"(d[55]), "=f"(d[56]), "=f"(d[57]), "=f"(d[58]), "=f"(d[59]), "=f"(d[60]), "=f"(d[61]), "=f"(d[62]), "=f"(d[63])
        : "r"(da), "r"(db), "n"(TB), "r"(ha), "r"(hb));
}
template <int TB>
__device__ __forceinline__ void wgmma_ss64(float (&d)[32], uint32_t da, uint32_t db, int acc, uint32_t ha = 0x40000040u, uint32_t hb = 0x40000040u) {
    asm volatile("{\n.reg .pred p;\n.reg .b64 a, b;\nsetp.ne.b32 p, %34, 0;\nmov.b64 a, {%32, %36};\nmov.b64 b, {%33, %37};\n"
        "wgmma.mma_async.sync.aligned.m64n64k16.f32.bf16.bf16 {%0, %1, %2, %3, %4, %5, %6, %7, %8, %9, %10, %11, %12, %13, %14, %15, %16, %17, %18, %19, %20, %21, %22, %23, %24, %25, %26, %27, %28, %29, %30, %31}, a, b, p, 1, 1, 0, %35;\n}"
        : "+f"(d[0]), "+f"(d[1]), "+f"(d[2]), "+f"(d[3]), "+f"(d[4]), "+f"(d[5]), "+f"(d[6]), "+f"(d[7]), "+f"(d[8]), "+f"(d[9]), "+f"(d[10]), "+f"(d[11]), "+f"(d[12]), "+f"(d[13]), "+f"(d[14]), "+f"(d[15]), "+f"(d[16]), "+f"(d[17]), "+f"(d[18]), "+f"(d[19]), "+f"(d[20]), "+f"(d[21]), "+f"(d[22]), "+f"(d[23]), "+f"(d[24]), "+f"(d[25]), "+f"(d[26]), "+f"(d[27]), "+f"(d[28]), "+f"(d[29]), "+f"(d[30]), "+f"(d[31])
        : "r"(da), "r"(db), "r"(acc), "n"(TB), "r"(ha), "r"(hb));
}
template <int TB>
__device__ __forceinline__ void wgmma_ss64_init(float (&d)[32], uint32_t da, uint32_t db, uint32_t ha = 0x40000040u, uint32_t hb = 0x40000040u) {
    asm volatile("{\n.reg .pred p;\n.reg .b64 a, b;\nsetp.ne.b32 p, 0, 0;\nmov.b64 a, {%32, %35};\nmov.b64 b, {%33, %36};\n"
        "wgmma.mma_async.sync.aligned.m64n64k16.f32.bf16.bf16 {%0, %1, %2, %3, %4, %5, %6, %7, %8, %9, %10, %11, %12, %13, %14, %15, %16, %17, %18, %19, %20, %21, %22, %23, %24, %25, %26, %27, %28, %29, %30, %31}, a, b, p, 1, 1, 0, %34;\n}"
        : "=f"(d[0]), "=f"(d[1]), "=f"(d[2]), "=f"(d[3]), "=f"(d[4]), "=f"(d[5]), "=f"(d[6]), "=f"(d[7]), "=f"(d[8]), "=f"(d[9]), "=f"(d[10]), "=f"(d[11]), "=f"(d[12]), "=f"(d[13]), "=f"(d[14]), "=f"(d[15]), "=f"(d[16]), "=f"(d[17]), "=f"(d[18]), "=f"(d[19]), "=f"(d[20]), "=f"(d[21]), "=f"(d[22]), "=f"(d[23]), "=f"(d[24]), "=f"(d[25]), "=f"(d[26]), "=f"(d[27]), "=f"(d[28]), "=f"(d[29]), "=f"(d[30]), "=f"(d[31])
        : "r"(da), "r"(db), "n"(TB), "r"(ha), "r"(hb));
}
__device__ __forceinline__ void wgmma_rs128(float (&d)[64], uint32_t a0, uint32_t a1, uint32_t a2, uint32_t a3, uint32_t db, int acc, uint32_t hb = 0x40000040u) {
    asm volatile("{\n.reg .pred p;\n.reg .b64 b;\nsetp.ne.b32 p, %69, 0;\nmov.b64 b, {%68, %70};\n"
        "wgmma.mma_async.sync.aligned.m64n128k16.f32.bf16.bf16 {%0, %1, %2, %3, %4, %5, %6, %7, %8, %9, %10, %11, %12, %13, %14, %15, %16, %17, %18, %19, %20, %21, %22, %23, %24, %25, %26, %27, %28, %29, %30, %31, %32, %33, %34, %35, %36, %37, %38, %39, %40, %41, %42, %43, %44, %45, %46, %47, %48, %49, %50, %51, %52, %53, %54, %55, %56, %57, %58, %59, %60, %61, %62, %63}, {%64, %65, %66, %67}, b, p, 1, 1, 1;\n}"
        : "+f"(d[0]), "+f"(d[1]), "+f"(d[2]), "+f"(d[3]), "+f"(d[4]), "+f"(d[5]), "+f"(d[6]), "+f"(d[7]), "+f"(d[8]), "+f"(d[9]), "+f"(d[10]), "+f"(d[11]), "+f"(d[12]), "+f"(d[13]), "+f"(d[14]), "+f"(d[15]), "+f"(d[16]), "+f"(d[17]), "+f"(d[18]), "+f"(d[19]), "+f"(d[20]), "+f"(d[21]), "+f"(d[22]), "+f"(d[23]), "+f"(d[24]), "+f"(d[25]), "+f"(d[26]), "+f"(d[27]), "+f"(d[28]), "+f"(d[29]), "+f"(d[30]), "+f"(d[31]), "+f"(d[32]), "+f"(d[33]), "+f"(d[34]), "+f"(d[35]), "+f"(d[36]), "+f"(d[37]), "+f"(d[38]), "+f"(d[39]), "+f"(d[40]), "+f"(d[41]), "+f"(d[42]), "+f"(d[43]), "+f"(d[44]), "+f"(d[45]), "+f"(d[46]), "+f"(d[47]), "+f"(d[48]), "+f"(d[49]), "+f"(d[50]), "+f"(d[51]), "+f"(d[52]), "+f"(d[53]), "+f"(d[54]), "+f"(d[55]), "+f"(d[56]), "+f"(d[57]), "+f"(d[58]), "+f"(d[59]), "+f"(d[60]), "+f"(d[61]), "+f"(d[62]), "+f"(d[63])
        : "r"(a0), "r"(a1), "r"(a2), "r"(a3), "r"(db), "r"(acc), "r"(hb));
}

__device__ __forceinline__ uint32_t pack2(float lo, float hi) {
    uint32_t r;
    asm("cvt.rn.bf16x2.f32 %0, %1, %2;" : "=r"(r) : "f"(hi), "f"(lo));
    return r;
}
__device__ __forceinline__ float bf_lo(uint32_t v) { return __uint_as_float(v << 16); }
__device__ __forceinline__ float bf_hi(uint32_t v) { return __uint_as_float(v & 0xffff0000u); }
__device__ __forceinline__ float rbf(float v) { return bf_lo(pack2(v, v)); }
__device__ __forceinline__ uint32_t badd(uint32_t a, uint32_t b) {
    uint32_t r;
    asm("add.rn.bf16x2 %0, %1, %2;" : "=r"(r) : "r"(a), "r"(b));
    return r;
}
__device__ __forceinline__ uint32_t bsub(uint32_t a, uint32_t b) {
    uint32_t r;
    asm("sub.rn.bf16x2 %0, %1, %2;" : "=r"(r) : "r"(a), "r"(b));
    return r;
}
__device__ __forceinline__ uint32_t bmul(uint32_t a, uint32_t b) {
    uint32_t r;
    asm("mul.rn.bf16x2 %0, %1, %2;" : "=r"(r) : "r"(a), "r"(b));
    return r;
}
__device__ __forceinline__ uint32_t ln_apply(uint32_t x, uint32_t mb, float rs, uint32_t scale, uint32_t shift) {
    const uint32_t d = bsub(x, mb);
    return badd(bmul(pack2(bf_lo(d) * rs, bf_hi(d) * rs), scale), shift);
}
__device__ __forceinline__ float ex2(float v) {
    float r;
    asm("ex2.approx.ftz.f32 %0, %1;" : "=f"(r) : "f"(v));
    return r;
}
__device__ __forceinline__ float rcp(float v) {
    float r;
    asm("rcp.approx.ftz.f32 %0, %1;" : "=f"(r) : "f"(v));
    return r;
}
__device__ __forceinline__ float sqrt_fast(float v) {
    float r;
    asm("sqrt.approx.ftz.f32 %0, %1;" : "=f"(r) : "f"(v));
    return r;
}
__device__ __forceinline__ float ln_rstd(float var) { return rcp(rbf(sqrt_fast(rbf(rbf(var) + 1e-5f)))); }
__device__ __forceinline__ float sigmoid(float v) { return rcp(1.f + ex2(-1.4426950408889634f * v)); }
__device__ __forceinline__ float warp_sum(float v) {
#pragma unroll
    for (int o = 16; o > 0; o >>= 1) v += __shfl_xor_sync(0xffffffffu, v, o);
    return v;
}
__device__ __forceinline__ float quad_sum(float v) {
    v += __shfl_xor_sync(0xffffffffu, v, 1);
    return v + __shfl_xor_sync(0xffffffffu, v, 2);
}

constexpr uint32_t HI_128 = 0x40000040u, HI_IMG = 0x80000080u, HI_Q = 0x80000040u;
template <int M, int RH>
__device__ __forceinline__ uint4 img_pack(const float (&d)[64], float s) {
    uint4 v;
    v.x = pack2(d[16 * M + 2 * RH] * s, d[16 * M + 2 * RH + 1] * s);
    v.y = pack2(d[16 * M + 4 + 2 * RH] * s, d[16 * M + 5 + 2 * RH] * s);
    v.z = pack2(d[16 * M + 8 + 2 * RH] * s, d[16 * M + 9 + 2 * RH] * s);
    v.w = pack2(d[16 * M + 12 + 2 * RH] * s, d[16 * M + 13 + 2 * RH] * s);
    return v;
}
template <int M, int RH>
__device__ __forceinline__ uint4 img_pack(const float (&d)[64]) {
    uint4 v;
    v.x = pack2(d[16 * M + 2 * RH], d[16 * M + 2 * RH + 1]);
    v.y = pack2(d[16 * M + 4 + 2 * RH], d[16 * M + 5 + 2 * RH]);
    v.z = pack2(d[16 * M + 8 + 2 * RH], d[16 * M + 9 + 2 * RH]);
    v.w = pack2(d[16 * M + 12 + 2 * RH], d[16 * M + 13 + 2 * RH]);
    return v;
}
template <int M>
__device__ __forceinline__ void img_store_global(uint8_t* img, uint32_t toff, const float (&d)[64], float s0, float s1) {
    uint4* p = reinterpret_cast<uint4*>(img + toff) + M * 32;
    p[0] = img_pack<M, 0>(d, s0);
    p[128] = img_pack<M, 1>(d, s1);
}
__device__ __forceinline__ void sts128(uint32_t a, uint4 v) {
    asm volatile("st.shared.v4.b32 [%0], {%1, %2, %3, %4};" ::"r"(a), "r"(v.x), "r"(v.y), "r"(v.z), "r"(v.w) : "memory");
}
constexpr float SM_C = 0.08838834764831845f * 1.4426950408889634f;
__device__ __forceinline__ float pack2f(float lo, float hi) {
    float r;
    asm("{\n.reg .b32 t;\ncvt.rn.bf16x2.f32 t, %1, %2;\nmov.b32 %0, t;\n}" : "=f"(r) : "f"(hi), "f"(lo));
    return r;
}
template <int M, bool SCALE, bool PARK>
__device__ __forceinline__ void pack_group(float (&d)[64], float (&v)[8], float s0, float s1) {
#pragma unroll
    for (int i = 0; i < 8; i++) {
        const int k = 16 * M + 4 * (i & 3) + 2 * (i >> 2);
        v[i] = SCALE ? pack2f(d[k] * (i < 4 ? s0 : s1), d[k + 1] * (i < 4 ? s0 : s1)) : pack2f(d[k], d[k + 1]);
        if (PARK && M > 0) d[16 * (M > 0 ? M - 1 : 0) + i] = v[i];
    }
}
__device__ __forceinline__ uint32_t q_off(uint32_t toff) { return (((toff >> 1) & ~2047u) ^ 8192) + (toff & 511); }
template <int M, bool PARK>
__device__ __forceinline__ void ctx_store_part(float4* p, float (&d)[64], float i0, float i1) {
    float v[8];
    pack_group<M, true, PARK>(d, v, i0, i1);
    p[M * 32] = make_float4(v[0], v[1], v[2], v[3]);
    p[M * 32 + 128] = make_float4(v[4], v[5], v[6], v[7]);
}
template <bool PARK>
__device__ __forceinline__ void ctx_store(uint8_t* img, uint32_t toff, float (&o)[64], float l0, float l1) {
    const float i0 = rcp(quad_sum(l0)), i1 = rcp(quad_sum(l1));
    float4* p = reinterpret_cast<float4*>(img + toff);
    ctx_store_part<0, PARK>(p, o, i0, i1); ctx_store_part<1, PARK>(p, o, i0, i1); ctx_store_part<2, PARK>(p, o, i0, i1); ctx_store_part<3, PARK>(p, o, i0, i1);
}

template <int M>
__device__ __forceinline__ void tile_store_part(float4* p, uint32_t a, float (&d)[64], float i0, float i1, int ctx) {
    float v[8];
    pack_group<M, true, true>(d, v, i0, i1);
#pragma unroll
    for (int h = 0; h < 2; h++)
        asm volatile("{\n.reg .pred p;\nsetp.ne.s32 p, %6, 0;\n@p st.global.v4.f32 [%0], {%2, %3, %4, %5};\n@!p st.shared.v4.f32 [%1], {%2, %3, %4, %5};\n}"
                     ::"l"(p + M * 32 + h * 128), "r"(a + (M >> 1) * 16384 + (M & 1) * 512 + h * 1024),
                     "f"(v[4 * h]), "f"(v[4 * h + 1]), "f"(v[4 * h + 2]), "f"(v[4 * h + 3]), "r"(ctx) : "memory");
}
__device__ __forceinline__ void tile_store(uint8_t* img, uint32_t a, uint32_t toff, float (&d)[64], float i0, float i1, int ctx) {
    float4* p = reinterpret_cast<float4*>(img + toff);
    a += q_off(toff);
    tile_store_part<0>(p, a, d, i0, i1, ctx); tile_store_part<1>(p, a, d, i0, i1, ctx);
    tile_store_part<2>(p, a, d, i0, i1, ctx); tile_store_part<3>(p, a, d, i0, i1, ctx);
}

__device__ __forceinline__ void slot_wait(uint32_t bars, uint32_t& ph, uint32_t slot) {
    mbar_wait(bars + 8 * slot, (ph >> slot) & 1);
    ph ^= 1u << slot;
}
__device__ __forceinline__ void release_if(uint32_t eb, uint32_t slot, bool on) {
    asm volatile("{\n.reg .pred p;\nsetp.ne.s32 p, %1, 0;\n@p mbarrier.arrive.shared::cluster.b64 _, [%0];\n}" ::"r"(eb + 8 * slot), "r"((int)on) : "memory");
}
__device__ __forceinline__ void load_image_mc(uint32_t sb, uint32_t& ph, uint32_t slot, const uint8_t* src, int rank, bool first) {
    slot_wait(sb + BAR_EMPTY, ph, slot);
    asm volatile("{\n.reg .pred p;\nelect.sync _|p, 0xffffffff;\n@p mbarrier.arrive.expect_tx.shared::cta.b64 _, [%2], 32768;\n"
                 "@p cp.async.bulk.shared::cluster.global.mbarrier::complete_tx::bytes.multicast::cluster.L2::cache_hint [%0], [%1], 16384, [%2], %4, %3;\n}"
                 ::"r"(sb + slot * SLOT + rank * 16384), "l"(src + rank * 16384), "r"(sb + BAR_FULL + 8 * slot), "l"(first ? L2_FIRST : L2_NORMAL),
                 "h"((uint16_t)3) : "memory");
}
__device__ __forceinline__ void load_tile_mc(uint32_t sb, uint32_t& ph, uint32_t slot, const CUtensorMap* m, int row, int cb, int rank, bool first) {
    slot_wait(sb + BAR_EMPTY, ph, slot);
    asm volatile("{\n.reg .pred p;\nelect.sync _|p, 0xffffffff;\n@p mbarrier.arrive.expect_tx.shared::cta.b64 _, [%2], 32768;\n"
                 "@p cp.async.bulk.tensor.3d.shared::cluster.global.mbarrier::complete_tx::bytes.multicast::cluster.L2::cache_hint [%0], [%1, {%3, %4, %5}], [%2], %7, %6;\n}"
                 ::"r"(sb + slot * SLOT + rank * 16384), "l"(m), "r"(sb + BAR_FULL + 8 * slot), "r"(0), "r"(row), "r"(cb + rank),
                 "l"(first ? L2_FIRST : L2_NORMAL), "h"((uint16_t)3) : "memory");
}
__device__ __forceinline__ void load_image(uint32_t sb, uint32_t& ph, uint32_t slot, const void* src, bool first) {
    slot_wait(sb + BAR_EMPTY, ph, slot);
    asm volatile("{\n.reg .pred p;\nelect.sync _|p, 0xffffffff;\n@p mbarrier.arrive.expect_tx.shared::cta.b64 _, [%2], 32768;\n"
                 "@p cp.async.bulk.shared::cluster.global.mbarrier::complete_tx::bytes.L2::cache_hint [%0], [%1], 32768, [%2], %3;\n}"
                 ::"r"(sb + slot * SLOT), "l"(src), "r"(sb + BAR_FULL + 8 * slot), "l"(first ? L2_FIRST : L2_NORMAL) : "memory");
}
__device__ __forceinline__ void load_tile(uint32_t sb, uint32_t& ph, uint32_t slot, const CUtensorMap* m, int row, int cb, bool first) {
    slot_wait(sb + BAR_EMPTY, ph, slot);
    asm volatile("{\n.reg .pred p;\nelect.sync _|p, 0xffffffff;\n@p mbarrier.arrive.expect_tx.shared::cta.b64 _, [%2], 32768;\n"
                 "@p cp.async.bulk.tensor.3d.shared::cluster.global.mbarrier::complete_tx::bytes.L2::cache_hint [%0], [%1, {%3, %4, %5}], [%2], %6;\n}"
                 ::"r"(sb + slot * SLOT), "l"(m), "r"(sb + BAR_FULL + 8 * slot), "r"(0), "r"(row), "r"(cb), "l"(first ? L2_FIRST : L2_NORMAL) : "memory");
}
__device__ __forceinline__ uint32_t ring_next(uint32_t r) { return r == 4 ? 0 : r + 1; }
__device__ __forceinline__ uint32_t w_table(int hp) { return hp ? 0x3104u : 0x4210u; }
__device__ __forceinline__ uint32_t a_table(int hp) { return hp ? 0x625u : 0x635u; }
__device__ __forceinline__ uint32_t a_next(uint32_t& t) {
    const uint32_t s = t & 15;
    t = (t >> 4) | (s << 8);
    return s;
}
constexpr uint32_t O_TABLE = 0x1604235u;
__device__ __forceinline__ uint32_t o_next(uint32_t& t) {
    const uint32_t s = t & 15;
    t = (t >> 4) | (s << 24);
    return s;
}
__device__ __forceinline__ int o_head(int i, int kh) { return i < 16 ? 4 * (i & 7) + 2 * (kh ^ 1) + (i >> 3) : 29 + 2 * kh; }

template <bool INIT>
__device__ __forceinline__ void gemm_issue(float (&d)[64], uint32_t a, uint32_t b, int acc, bool img) {
    const uint32_t ha = img ? HI_IMG : HI_128, o2 = img ? 32 : 4, o4 = img ? 64 : 1024;
    wg_fence();
#pragma unroll
    for (int k = 0; k < 8; k++) {
        if (INIT && k == 0) wgmma_ss128_init<1>(d, a, b, ha);
        else wgmma_ss128<1>(d, a + (k >> 2) * o4 + ((k >> 1) & 1) * o2 + (k & 1) * 2, b + k * 128, k ? 1 : acc, ha);
    }
    wg_commit();
}

__device__ __forceinline__ void h_store(const uint32_t* x, float mean, float sq, uint32_t sb, int row) {
    const int lane = threadIdx.x & 31;
    const float rs = ln_rstd(sq * (1.f / 512.f));
    const uint32_t mb = pack2(mean, mean);
    uint8_t* p = g_h + ((row >> 7) * 8 + (lane >> 3)) * 16384 + (row & 127) * 128 + (((lane ^ row) & 7) << 4);
#pragma unroll
    for (int i = 0; i < 2; i++) {
        const uint4 a = lds128(sb + SM_TAB + 1024 + i * 512 + lane * 16), c = lds128(sb + SM_TAB + i * 512 + lane * 16);
        *reinterpret_cast<uint4*>(p + i * 65536) = make_uint4(ln_apply(x[4 * i], mb, rs, a.x, c.x), ln_apply(x[4 * i + 1], mb, rs, a.y, c.y),
                                                              ln_apply(x[4 * i + 2], mb, rs, a.z, c.z), ln_apply(x[4 * i + 3], mb, rs, a.w, c.w));
    }
}

template <bool ODD>
__device__ __forceinline__ bool proj_tile(float (&acc)[64], float (&prev)[64], int t, int q0, uint32_t sb, int wg, uint32_t eb, bool rel, uint32_t& fph,
                                          uint32_t wtab, uint32_t& atab, uint8_t* prev_img, uint32_t toff, float s0, float s1, bool first,
                                          const bf16* x, int xrow) {
    const uint32_t a0 = desc_k(sb + (wg ^ (ODD && t == 5)) * 8192), b0 = desc_mn(sb);
    const int lane = threadIdx.x & 31;
    float mean[2] = {0.f, 0.f}, rstd[2] = {0.f, 0.f};
    uint32_t xn[16];
#pragma unroll
    for (int i = 0; i < 4; i++) {
        uint4 v = make_uint4(0, 0, 0, 0);
        if (ODD && first) v = __ldg(reinterpret_cast<const uint4*>(x) + xrow * 64 + lane + 32 * i);
        xn[4 * i] = v.x; xn[4 * i + 1] = v.y; xn[4 * i + 2] = v.z; xn[4 * i + 3] = v.w;
    }
    constexpr int U = ODD ? UNR : 1;
#pragma unroll U
    for (int q = ODD ? 0 : q0; q < 4; q++) {
        const uint32_t ws = (wtab >> (4 * q)) & 15, as = a_next(atab);
        if (!ODD && t != 2) slot_wait(sb + BAR_FULL, fph, ws);
        slot_wait(sb + BAR_FULL, fph, as);
        bar_sync(1 + wg, 256);
        gemm_issue<false>(acc, a0 + as * (SLOT / 16), b0 + ws * (SLOT / 16), q, false);
        bar_arrive(2 - wg, 256);
        wg_wait<1>();
        reg_fence(prev);
        if (ODD && t == 5) {
            if (q == 1) {
                uint4 v[8] = {img_pack<0, 0>(prev), img_pack<0, 1>(prev), img_pack<1, 0>(prev), img_pack<1, 1>(prev),
                              img_pack<2, 0>(prev), img_pack<2, 1>(prev), img_pack<3, 0>(prev), img_pack<3, 1>(prev)};
                wg_wait<0>();
#pragma unroll
                for (int i = 0; i < 8; i++) sts128(sb + 5 * SLOT + q_off(toff) + (i >> 2) * 16384 + (i & 2) * 256 + (i & 1) * 1024, v[i]);
            }
            if (q == 2) {
                fence_async_smem();
                slot_wait(sb + BAR_FULL, fph, wtab & 15);
                wg_wait<0>();
                release_if(eb, as, rel);
                release_if(eb, ws, rel);
                reg_fence(acc);
                return true;
            }
        } else if (ODD || !first) {
            if (q == 0) img_store_global<0>(prev_img, toff, prev, s0, s1);
            if (q == 1) img_store_global<1>(prev_img, toff, prev, s0, s1);
            if (q == 2) img_store_global<2>(prev_img, toff, prev, s0, s1);
            if (q == 3) img_store_global<3>(prev_img, toff, prev, s0, s1);
        }
        if (ODD && q == 1 && first) {
#pragma unroll
            for (int k = 0; k < 16; k++) mean[k >> 3] += bf_lo(xn[k]) + bf_hi(xn[k]);
#pragma unroll
            for (int i = 0; i < 2; i++) mean[i] = warp_sum(mean[i]) * (1.f / 512.f);
        }
        if (ODD && q == 2 && first) {
#pragma unroll
            for (int k = 0; k < 16; k++) {
                const float d0 = bf_lo(xn[k]) - mean[k >> 3], d1 = bf_hi(xn[k]) - mean[k >> 3];
                rstd[k >> 3] = fmaf(d0, d0, fmaf(d1, d1, rstd[k >> 3]));
            }
#pragma unroll
            for (int i = 0; i < 2; i++) rstd[i] = warp_sum(rstd[i]);
        }
        if (ODD && q == 3 && first) {
            mbar_wait(sb + BAR_FLAG + 8 * 8, 0);
            h_store(xn, mean[0], rstd[0], sb, xrow);
        }
        wg_wait<0>();
        release_if(eb, as, rel && !(ODD && (q & 1) && t == 5));
        if (ODD) release_if(eb, ws, rel && t != 1);
        if (ODD && q == 3 && first) {
            h_store(xn + 8, mean[1], rstd[1], sb, xrow + 1);
            __syncwarp();
            mbar_arrive_if(sb + BAR_DONE, lane == 0);
        }
    }
    reg_fence(acc);
    return false;
}

__device__ __forceinline__ void qk_issue(float (&s)[64], uint32_t q, uint32_t k) {
    wg_fence();
    wgmma_ss128_init<0>(s, q, k, HI_Q, HI_IMG);
#pragma unroll
    for (int i = 1; i < 8; i++) wgmma_ss128<0>(s, q + (i >> 2) * 1024 + (i & 2) * 16 + (i & 1) * 2, k + (i >> 1) * 32 + (i & 1) * 2, 1, HI_Q, HI_IMG);
    wg_commit();
}
__device__ __forceinline__ void qk_issue(float (&s)[32], uint32_t q, uint32_t k) {
    wg_fence();
    wgmma_ss64_init<0>(s, q, k, HI_Q, HI_IMG);
#pragma unroll
    for (int i = 1; i < 8; i++) wgmma_ss64<0>(s, q + (i >> 2) * 1024 + (i & 2) * 16 + (i & 1) * 2, k + (i >> 1) * 32 + (i & 1) * 2, 1, HI_Q, HI_IMG);
    wg_commit();
}
__device__ __forceinline__ void pv_issue(float (&o)[64], const uint32_t (&p)[32], uint32_t v, int acc, bool half) {
    if (half) {
        asm volatile("// half" ::: "memory");
        wg_fence();
#pragma unroll
        for (int i = 0; i < 4; i++) wgmma_rs128(o, p[4 * i], p[4 * i + 1], p[4 * i + 2], p[4 * i + 3], v + i * 256, i ? 1 : acc, HI_IMG);
        wg_commit();
        asm volatile("// half" ::: "memory");
    } else {
        wg_fence();
#pragma unroll
        for (int i = 0; i < 8; i++) wgmma_rs128(o, p[4 * i], p[4 * i + 1], p[4 * i + 2], p[4 * i + 3], v + i * 256, i ? 1 : acc, HI_IMG);
        wg_commit();
    }
}
template <int B, int N>
__device__ __forceinline__ void tri_mask(float (&s)[N], int x) {
#pragma unroll
    for (int k = 0; k < 7; k++)
        asm("{\n.reg .pred p, q;\nsetp.lt.s32 p, %4, %5;\nsetp.le.s32 q, %4, %5;\n"
            "@p mov.b32 %0, 0fFF800000;\n@q mov.b32 %1, 0fFF800000;\n@p mov.b32 %2, 0fFF800000;\n@q mov.b32 %3, 0fFF800000;\n}"
            : "+f"(s[B + 4 * k]), "+f"(s[B + 4 * k + 1]), "+f"(s[B + 4 * k + 6]), "+f"(s[B + 4 * k + 7]) : "r"(x), "r"(8 * k));
    asm("{\n.reg .pred p, q;\nsetp.lt.s32 p, %2, 56;\nsetp.le.s32 q, %2, 56;\n@p mov.b32 %0, 0fFF800000;\n@q mov.b32 %1, 0fFF800000;\n}"
        : "+f"(s[B + 28]), "+f"(s[B + 29]) : "r"(x));
}
__device__ __forceinline__ void tri_mask_copy(float (&s)[64], const float (&h)[32], int x) {
#pragma unroll
    for (int i = 0; i < 32; i++) {
        asm("{\n.reg .pred p;\nsetp.lt.s32 p, %2, %3;\nselp.f32 %0, 0fFF800000, %1, p;\n}"
            : "=f"(s[i]) : "f"(h[i]), "r"(x), "r"(8 * (i >> 2) - 4 * (i & 2) + (i & 1)));
        s[32 + i] = __uint_as_float(0xff800000u);
    }
}
constexpr float SM_HI = 1152921504606846976.f, SM_LO = 1.f / 1152921504606846976.f;
__device__ __forceinline__ bool softmax_unsafe(float t0, float t1, bool first) {
    bool bad = __any_sync(0xffffffffu, fmaxf(t0, t1) > SM_HI);
    if (first) {
        uint32_t a = __ballot_sync(0xffffffffu, t0 >= SM_LO), b = __ballot_sync(0xffffffffu, t1 >= SM_LO);
        a |= a >> 1;
        b |= b >> 1;
        bad |= ((a | (a >> 2)) & (b | (b >> 2)) & 0x11111111u) != 0x11111111u;
    }
    return bad;
}
__device__ __forceinline__ void softmax_shift(float (&s)[64], float d0, float d1) {
#pragma unroll
    for (int i = 0; i < 64; i++) s[i] -= (i & 2) ? d1 : d0;
}
__device__ __forceinline__ void softmax_remax(float (&s)[64], float (&m)[2], bool first, float& a0, float& a1) {
    float m0 = fmaxf(s[0], s[1]), m1 = fmaxf(s[2], s[3]);
#pragma unroll
    for (int k = 1; k < 16; k++) {
        m0 = fmaxf(m0, fmaxf(s[4 * k], s[4 * k + 1]));
        m1 = fmaxf(m1, fmaxf(s[4 * k + 2], s[4 * k + 3]));
    }
    m0 = fmaxf(m0, __shfl_xor_sync(0xffffffffu, m0, 1));
    m1 = fmaxf(m1, __shfl_xor_sync(0xffffffffu, m1, 1));
    m0 = fmaxf(m0, __shfl_xor_sync(0xffffffffu, m0, 2));
    m1 = fmaxf(m1, __shfl_xor_sync(0xffffffffu, m1, 2));
    if (!first) {
        m0 = fmaxf(m0, 0.f);
        m1 = fmaxf(m1, 0.f);
    }
    a0 = first ? 1.f : ex2(-m0);
    a1 = first ? 1.f : ex2(-m1);
    m[0] += m0;
    m[1] += m1;
    softmax_shift(s, m0, m1);
}
template <int J0, int J1>
__device__ __forceinline__ void softmax_exp(const float (&s)[64], uint32_t (&p)[32], float (&t)[4]) {
#pragma unroll
    for (int k = J0; k < J1; k++) {
        const float e0 = ex2(s[4 * k]), e1 = ex2(s[4 * k + 1]), e2 = ex2(s[4 * k + 2]), e3 = ex2(s[4 * k + 3]);
        if (k == 0) { t[0] = e0; t[1] = e1; t[2] = e2; t[3] = e3; }
        else { t[0] += e0; t[1] += e1; t[2] += e2; t[3] += e3; }
        p[2 * k] = pack2(e0, e1);
        p[2 * k + 1] = pack2(e2, e3);
    }
}
__device__ __forceinline__ void fma8(float (&acc)[8], float a, uint4 w) {
    acc[0] = fmaf(a, bf_lo(w.x), acc[0]); acc[1] = fmaf(a, bf_hi(w.x), acc[1]);
    acc[2] = fmaf(a, bf_lo(w.y), acc[2]); acc[3] = fmaf(a, bf_hi(w.y), acc[3]);
    acc[4] = fmaf(a, bf_lo(w.z), acc[4]); acc[5] = fmaf(a, bf_hi(w.z), acc[5]);
    acc[6] = fmaf(a, bf_lo(w.w), acc[6]); acc[7] = fmaf(a, bf_hi(w.w), acc[7]);
}
__device__ __forceinline__ void mma16816(float (&d)[4], const uint32_t* a, uint32_t b0, uint32_t b1) {
    asm("mma.sync.aligned.m16n8k16.row.col.f32.bf16.bf16.f32 {%0, %1, %2, %3}, {%4, %5, %6, %7}, {%8, %9}, {%0, %1, %2, %3};"
        : "+f"(d[0]), "+f"(d[1]), "+f"(d[2]), "+f"(d[3]) : "r"(a[0]), "r"(a[1]), "r"(a[2]), "r"(a[3]), "r"(b0), "r"(b1));
}
__device__ __forceinline__ uint32_t best_key(const uint32_t* keys, int lane, uint32_t ep) {
    uint32_t best;
#pragma unroll 1
    for (;;) {
        const uint4 k = ld_poll(reinterpret_cast<const uint4*>(keys) + lane);
        best = max(max(k.x, k.y), max(k.z, k.w));
        if (__all_sync(0xffffffffu, (((k.x ^ ep) | (k.y ^ ep) | (k.z ^ ep) | (k.w ^ ep)) & 31) == 0)) break;
    }
    return __reduce_max_sync(0xffffffffu, best);
}

__global__ void __cluster_dims__(2, 1, 1) __launch_bounds__(384, 1)
fused_kernel(const __grid_constant__ CUtensorMap tm_ckv, const __grid_constant__ CUtensorMap tm_wq,
             const __grid_constant__ CUtensorMap tm_wuk, const __grid_constant__ CUtensorMap tm_wuv,
             const __grid_constant__ CUtensorMap tm_wo, const __grid_constant__ CUtensorMap tm_wg,
             const __grid_constant__ CUtensorMap tm_wu,
             const __grid_constant__ CUtensorMap tm_wm, const __grid_constant__ CUtensorMap tm_x, const Params P) {
    extern __shared__ __align__(1024) uint8_t smem[];
    const uint32_t sb = (uint32_t)__cvta_generic_to_shared(smem);
    const int tid = threadIdx.x, lane = tid & 31, warp = __shfl_sync(0xffffffffu, tid >> 5, 0), wg = warp >> 2;
    uint32_t sm;
    asm("mov.u32 %0, %%smid;" : "=r"(sm));
    if (MC) sm = blockIdx.x < 8 ? blockIdx.x + 124 : blockIdx.x - 8;
    const uint32_t smq = ((sm - 64) * 147) >> 11;
    const int rb = !P.by_smid ? blockIdx.x : sm < 64 ? (sm & 14) * 8 + (sm >> 4) * 2 + (sm & 1)
                 : sm < 120 ? ((sm - 64 - smq * 14) & 14) * 8 + 24 + smq * 2 + (sm & 1) : sm < 124 ? sm + 8 : sm - 116;
    const int grp = rb >> 3, j = rb & 7, cq = j & 3, kh = grp & 1, ort = (grp & 14) + (j >> 2);
    if (warp == 0) TS(0);

    if (rb >= NCTA) {
        float* sc = reinterpret_cast<float*>(smem + 6 * SLOT);
        float* red = sc + 512;
        if (tid == 256) {
            for (int i = 0; i < 6; i++) { mbar_init(sb + BAR_FULL + 8 * i, 1); mbar_init(sb + BAR_EMPTY + 8 * i, 8); }
            fence_async_smem();
        }
        __syncthreads();
        uint32_t ph = 0, sl = 0;
        if (tid == 256) {
#pragma unroll 1
            for (int i = 0; i < 24; i++) {
                mbar_wait(sb + BAR_EMPTY + 8 * sl, ph ^ 1);
                mbar_expect(sb + BAR_FULL + 8 * sl, SLOT);
                tma2d(sb + sl * SLOT, &tm_wm, (i >> 3) * 1024 + (rb - NCTA) * 256, (i & 7) * 64, sb + BAR_FULL + 8 * sl);
                if (++sl == 6) { sl = 0; ph ^= 1; }
            }
            mbar_wait(sb + BAR_EMPTY, 1);
            mbar_wait(sb + BAR_EMPTY + 8, 1);
#pragma unroll 1
            for (int i = 0; i <= NFFN / NSPARE; i++) {
                const int b = (rb - NCTA) * (NFFN / NSPARE) + i;
                if (i < NFFN / NSPARE) {
                    const uint32_t f = sb + BAR_FULL + 8 * (i & 1), d = sb + (i & 1) * SLOT;
                    asm volatile("cp.async.bulk.wait_group.read 0;" ::: "memory");
                    mbar_expect(f, SLOT);
                    tma2d(d, &tm_wg, b * 16, 0, f);
                    tma2d(d + 8192, &tm_wg, b * 16, 256, f);
                    tma2d(d + 16384, &tm_wu, b * 16, 0, f);
                    tma2d(d + 24576, &tm_wu, b * 16, 256, f);
                }
                if (i) {
                    mbar_wait(sb + BAR_FULL + 8 * (~i & 1), ((i - 1) >> 1) & 1);
                    asm volatile("cp.async.bulk.global.shared::cta.bulk_group [%0], [%1], 32768;\ncp.async.bulk.commit_group;"
                                 ::"l"(g_wf + (b - 1) * SLOT), "r"(sb + (~i & 1) * SLOT) : "memory");
                }
            }
            asm volatile("cp.async.bulk.wait_group 0;" ::: "memory");
            fence_async_global();
            flag_add(&g_sync.modcnt[32]);
            TS(4);
        } else if (tid < 256) {
            const uint32_t c2 = __ldg(reinterpret_cast<const uint32_t*>(P.c) + tid);
            sc[2 * tid] = rbf(bf_lo(c2) * sigmoid(bf_lo(c2)));
            sc[2 * tid + 1] = rbf(bf_hi(c2) * sigmoid(bf_hi(c2)));
            bar_sync(1, 256);
#pragma unroll 1
            for (int ps = 0; ps < 3; ps++) {
                float acc[8] = {0.f, 0.f, 0.f, 0.f, 0.f, 0.f, 0.f, 0.f};
#pragma unroll 1
                for (int bt = 0; bt < 8; bt++) {
                    mbar_wait(sb + BAR_FULL + 8 * sl, ph);
#pragma unroll
                    for (int i = 0; i < 8; i++)
                        fma8(acc, sc[bt * 64 + warp * 8 + i], *reinterpret_cast<const uint4*>(smem + sl * SLOT + (warp * 8 + i) * 512 + lane * 16));
                    __syncwarp();
                    mbar_arrive_if(sb + BAR_EMPTY + 8 * sl, lane == 0);
                    if (++sl == 6) { sl = 0; ph ^= 1; }
                }
                *reinterpret_cast<float4*>(red + warp * 256 + lane * 8) = make_float4(acc[0], acc[1], acc[2], acc[3]);
                *reinterpret_cast<float4*>(red + warp * 256 + lane * 8 + 4) = make_float4(acc[4], acc[5], acc[6], acc[7]);
                bar_sync(1, 256);
                float v = 0.f;
#pragma unroll
                for (int i = 0; i < 8; i++) v += red[i * 256 + tid];
                g_mod[ps * 1024 + (rb - NCTA) * 256 + tid] = __float2bfloat16_rn(v);
                bar_sync(1, 256);
                if (tid == 0 && ps != 1) flag_add(&g_sync.modcnt[(ps >> 1) * 32]);
                if (warp == 0) TS(1 + ps);
            }
        }
        return;
    }

    if (tid == 256) {
        if (sb & 1023) __trap();
        asm volatile("prefetch.tensormap [%0];" ::"l"((j & 1) ? &tm_wuv : &tm_wuk) : "memory");
        asm volatile("prefetch.tensormap [%0];" ::"l"(&tm_ckv) : "memory");
        for (int i = 0; i < 7; i++) { mbar_init(sb + BAR_FULL + 8 * i, 1); mbar_init(sb + BAR_EMPTY + 8 * i, MC ? 4 : 2); }
        for (int i = 0; i < 9; i++) mbar_init(sb + BAR_DONE + 8 * i, 8);
        for (int i = 0; i < 10; i++) mbar_init(sb + BAR_FLAG + 8 * i, 1);
        *reinterpret_cast<uint32_t*>(smem + SM_EP + 4) = 0;
        *reinterpret_cast<uint32_t*>(smem + SM_EP + 16) = 0;
        mbar_init(sb + BAR_END, 8);
        fence_async_smem();
        if (MC) asm volatile("fence.mbarrier_init.release.cluster;" ::: "memory");
    }
    __syncthreads();
    if (MC) asm volatile("barrier.cluster.arrive.relaxed.aligned;\nbarrier.cluster.wait.aligned;" ::: "memory");

    if (wg == 2) {
        asm volatile("setmaxnreg.dec.sync.aligned.u32 40;");
        if (warp == 8) {
            uint32_t eph = 0x7f, r = 0;
            const CUtensorMap* tw = (j & 1) ? &tm_wuv : &tm_wuk;
#pragma unroll 1
            for (int hp = 0; hp < 2; hp++) {
                const int hc = 4 * grp + 2 * hp;
                uint32_t wtab = w_table(hp), atab = a_table(hp);
#pragma unroll 1
                for (int u = 0; u < 4; u++) {
                    load_tile(sb, eph, (wtab >> (4 * u)) & 15, tw, u * 128, hc, HINT & 1); PT();
                    if (MC & 1) load_tile_mc(sb, eph, a_next(atab), &tm_ckv, (j >> 1) * 128, u * 2, j & 1, (HINT & 8) && hp);
                    else load_tile(sb, eph, a_next(atab), &tm_ckv, (j >> 1) * 128, u * 2, (HINT & 8) && hp);
                    PT();
                    if (hp == 1 && (u & 1) && lane == 0) asm volatile("red.relaxed.gpu.global.add.u32 [%0], 1;" ::"l"(&g_sync.rdcnt[(grp * 2 + (u >> 1)) * 8]) : "memory");
                }
#pragma unroll 1
                for (int u = 4; u < 16; u++) {
                    if (hp == 1 && (u & 7) == 4) mbar_wait(sb + BAR_FLAG + 24 + (u & 8), 0);
                    if (MC & 1) load_tile_mc(sb, eph, a_next(atab), &tm_ckv, ((u & 12) + (j >> 1)) * 128, (u & 3) * 2, j & 1, (HINT & 8) && hp);
                    else load_tile(sb, eph, a_next(atab), &tm_ckv, ((u & 12) + (j >> 1)) * 128, (u & 3) * 2, (HINT & 8) && hp);
                    PT();
                }
                mbar_wait(sb + BAR_FLAG, 0);
                fence_async_global();
#pragma unroll 1
                for (int u = 0; u < 4; u++) {
                    if (MC & 2) load_tile_mc(sb, eph, (wtab >> (4 * u)) & 15, &tm_wq, u * 128, hc, j & 1, HINT & 1);
                    else load_tile(sb, eph, (wtab >> (4 * u)) & 15, &tm_wq, u * 128, hc, HINT & 1);
                    PT();
                    load_image(sb, eph, a_next(atab), g_h + ((15 - j) * 4 + u) * SLOT, (HINT & 8) && hp); PT();
                }
                mbar_wait(sb + BAR_FLAG + 8 + 32 * hp, 0);
                fence_async_global();
#pragma unroll 1
                for (int u = 0; u < 4; u++) { load_image(sb, eph, a_next(atab), g_h + (j * 4 + u) * SLOT, (HINT & 8) && hp); PT(); }
                const uint8_t* kv = g_KV + (size_t)(grp * 32 + 30 * hp) * SLOT;
                const int step = hp ? -2 * SLOT : 2 * SLOT;
                if (MC & 4) load_image_mc(sb, eph, r, kv, j & 1, HINT & 4);
                else load_image(sb, eph, r, kv, HINT & 4);
                PT();
                r = ring_next(r);
#pragma unroll 1
                for (int n = 1; n <= 16; n++) {
                    if (n == 8) {
                        mbar_wait(sb + BAR_FLAG + 16 + 32 * hp, 0);
                        fence_async_global();
                    }
                    asm volatile("st.volatile.shared.u32 [%0], %1;" ::"r"(sb + SM_EP + 16), "r"(16 * hp + n) : "memory");
                    const uint8_t* v = kv + SLOT;
                    kv += n < 16 - j ? step : n == 16 - j ? (2 * j - 15) * step : -step;
                    if ((MC & 4) && n != 15 - (j & 6)) load_image_mc(sb, eph, r, kv, j & 1, HINT & 4);
                    else load_image(sb, eph, r, kv, HINT & 4);
                    PT();
                    r = ring_next(r);
                    if ((MC & 4) && n != 16 - (j & 6)) load_image_mc(sb, eph, r, v, j & 1, HINT & 4);
                    else load_image(sb, eph, r, v, HINT & 4);
                    PT();
                    r = ring_next(r);
                }
                if (MC & 4) load_image_mc(sb, eph, r, kv + SLOT, j & 1, HINT & 4);
                else load_image(sb, eph, r, kv + SLOT, HINT & 4);
                PT();
                r = ring_next(r);
            }
            uint32_t otab = O_TABLE, ready = 0;
#pragma unroll 1
            for (int i = 0; i < 17; i++) {
                asm volatile("st.volatile.shared.u32 [%0], %1;" ::"r"(sb + SM_EP + 16), "r"(33 + i) : "memory");
                const bool dyn = i >= 8 && i < 15;
                const uint32_t want = dyn ? 15u << (4 * (i - 8)) : 1u << max(i + 14, 28);
                if (!(ready & want)) {
                    do {
                        asm volatile("ld.acquire.cta.shared.u32 %0, [%1];" : "=r"(ready) : "r"(sb + SM_EP + 4) : "memory");
                        ready = __shfl_sync(0xffffffffu, ready, 0);
                    } while (!(ready & want));
                    fence_async_global();
                }
                const int head = o_head(dyn ? (ready >> (4 * (i - 8))) & 15 : i, kh);
                const uint8_t* src = g_ctx + (size_t)(ort * 32 + head) * SLOT;
                if (i < 15) {
                    if (MC & 8) load_image_mc(sb, eph, o_next(otab), src, j & 1, HINT & 16);
                    else load_image(sb, eph, o_next(otab), src, HINT & 16);
                } else {
                    const uint32_t as = o_next(otab), d = sb + as * SLOT;
                    slot_wait(sb + BAR_EMPTY, eph, as);
                    asm volatile("{\n.reg .pred p, q;\nelect.sync _|p, 0xffffffff;\n@p mbarrier.arrive.expect_tx.shared::cta.b64 _, [%2], %3;\n"
                                 "@p cp.async.bulk.shared::cluster.global.mbarrier::complete_tx::bytes [%0], [%1], 16384, [%2];\n}"
                                 ::"r"(d + kh * 16384), "l"(src + kh * 16384), "r"(sb + BAR_FULL + 8 * as), "r"(i == 15 ? 32768 : 16384) : "memory");
                    if (i == 15)
                        asm volatile("{\n.reg .pred p;\nelect.sync _|p, 0xffffffff;\n"
                                     "@p cp.async.bulk.tensor.3d.shared::cluster.global.mbarrier::complete_tx::bytes [%0], [%1, {%3, %4, %5}], [%2];\n}"
                                     ::"r"(d + (kh ^ 1) * 16384), "l"(&tm_x), "r"(sb + BAR_FULL + 8 * as), "r"(0), "r"(ort * 128 + kh * 64), "r"(cq * 2) : "memory");
                }
                PT();
                load_tile(sb, eph, o_next(otab), &tm_wo, head * 128, cq * 2, HINT & 2); PT();
                if (i == 0) o_next(otab);
            }
            if (rb < NFFN) {
                load_image(sb, eph, o_next(otab), g_wf + rb * SLOT, false);
                const uint32_t s2 = o_next(otab);
                slot_wait(sb + BAR_EMPTY, eph, s2);
                asm volatile("{\n.reg .pred p;\nelect.sync _|p, 0xffffffff;\n@p mbarrier.arrive.expect_tx.shared::cta.b64 _, [%2], 16384;\n"
                             "@p cp.async.bulk.shared::cluster.global.mbarrier::complete_tx::bytes [%0], [%1], 16384, [%2];\n}"
                             ::"r"(sb + s2 * SLOT), "l"(P.wdown + rb * 8192), "r"(sb + BAR_FULL + 8 * s2) : "memory");
            }
        } else {
            const int hw = warp - 9;
            if (hw == 1 && lane == 0) {
                l2_prefetch(P.ckv + rb * 2048, 4096);
                mbar_watch(sb + BAR_FULL + 8 * PF0, 0);
                l2_prefetch(P.ckv + 512 * 512 + rb * 2048, 4096);
                mbar_watch(sb + BAR_FULL + 8 * 4, 0);
                l2_prefetch(P.x + rb * 8192, 16384);
                l2_prefetch(P.ckv + 1024 * 512 + rb * 4096, 8192);
                TS(40);
                if (MC & 2) tma3d_prefetch(&tm_wq, (j >> 1) * 128, grp * 4 + (j & 1));
                else if (j < 4) tma3d_prefetch(&tm_wq, j * 128, grp * 4);
                step_watch(sb + SM_EP + 16, PFA);
                tma3d_prefetch((j & 1) ? &tm_wuv : &tm_wuk, (j >> 1) * 128, grp * 4 + 2);
                step_watch(sb + SM_EP + 16, PFA + 2);
                l2_prefetch(P.ckv + rb * 8192, 16384);
                step_watch(sb + SM_EP + 16, PFA + 3);
                l2_prefetch(g_h + rb * 16384, 16384);
                step_watch(sb + SM_EP + 16, PFA + 4);
                if (MC & 2) tma3d_prefetch(&tm_wq, (j >> 1) * 128, grp * 4 + 2 + (j & 1));
                else if (j < 4) tma3d_prefetch(&tm_wq, j * 128, grp * 4 + 2);
#pragma unroll 1
                for (int i = 0; i < 10; i++) {
                    step_watch(sb + SM_EP + 16, i < 6 ? 16 + PFB + i : 16 + PFC + i - 6);
                    if (i == 7) mbar_watch(sb + BAR_FLAG + 8 * 7, 0);
                    const uint8_t* p = i < 4 ? g_ctx + (size_t)(ort * 32 + o_head(cq + 2 * (i & 2), kh)) * SLOT + (i & 1) * 16384
                                     : i < 6 ? reinterpret_cast<const uint8_t*>(P.wo) + ((rb >> 3) * 16 + (i & 1) * 8 + (rb & 7)) * 16384
                                     : i == 6 ? reinterpret_cast<const uint8_t*>(P.x) + rb * 16384
                                     : i == 7 ? reinterpret_cast<const uint8_t*>(P.wdown) + rb * 16384 : g_wf + rb * SLOT + (i & 1) * 16384;
                    if ((i < 7 || rb < NFFN) && ((PFMASK >> i) & 1)) l2_prefetch(p, 16384);
                }
                step_watch(sb + SM_EP + 16, 16 + PFC + 4);
                if (OBINIT) {
                    const uint32_t v = lds32(sb + SM_EP) - 1;
#pragma unroll 1
                    for (int i = 0; i < 32; i++) sts128(sb + SM_RED + i * 16, make_uint4(v, v, v, v));
                    fence_async_smem();
#pragma unroll 1
                    for (int i = 0; i < OB / 32; i++)
                        asm volatile("cp.async.bulk.global.shared::cta.bulk_group [%0], [%1], 512;" ::"l"(g_out + rb * OB + i * 32), "r"(sb + SM_RED) : "memory");
                    asm volatile("cp.async.bulk.commit_group;\ncp.async.bulk.wait_group 0;" ::: "memory");
                    fence_async_global();
                }
                mbar_arrive(sb + BAR_PF);
                mbar_watch(sb + BAR_END, 0);
            }
            if (hw == 0) {
#pragma unroll 1
                for (int i = 0; i < 9; i++) {
                    const int hp = i > 4, k = (i - 1) & 3;
                    if (lane == 0) {
                        mbar_wait(sb + BAR_DONE + 8 * i, 0);
                        flag_add(i == 0 ? &g_sync.hcnt[grp * 8] : k < 2 ? &g_sync.kvcnt[((2 * grp + hp) * 2 + k) * 8]
                                                                        : &g_sync.ctxcnt[(k == 2 ? 15 - j : j) * 32 + 2 * grp + hp]);
                    }
                    if (i == 0) TS(43);
                }
            }
            if (hw == 2) {
                const uint32_t ep = __ldcg(&g_sync.epoch[0]) + 1;
                if (lane == 0) {
                    asm volatile("st.shared.u32 [%0], %1;" ::"r"(sb + SM_EP), "r"(ep) : "memory");
                    flag_wait(&g_sync.modcnt[0], NSPARE * ep);
                }
                __syncwarp();
#pragma unroll
                for (int i = 0; i < 4; i++) {
                    uint4 v = __ldcg(reinterpret_cast<const uint4*>(g_mod) + lane + 32 * i);
                    if (i >= 2) v = make_uint4(badd(v.x, ONE2), badd(v.y, ONE2), badd(v.z, ONE2), badd(v.w, ONE2));
                    sts128(sb + SM_TAB + i * 512 + lane * 16, v);
                }
                __syncwarp();
                if (lane == 0) mbar_arrive(sb + BAR_FLAG + 8 * 8);
                TS(42);
#pragma unroll 1
                for (int i = 0; i < 8; i++) {
                    if (lane == 0) mbar_wait(sb + BAR_DONE + 8 * (i == 7 ? 6 : i == 4 ? 3 : i), 0);
                    __syncwarp();
                    const uint32_t* f = i == 0 ? &g_sync.hcnt[(lane ? j : 15 - j) * 8]
                                      : i == 3 || i == 4 ? &g_sync.rdcnt[(grp * 2 + i - 3) * 8]
                                      : i == 7 ? &g_sync.modcnt[32] : &g_sync.kvcnt[(4 * grp + (i > 4 ? i - 3 : i - 1)) * 8];
                    if (lane < (i ? 1 : 2)) flag_wait(f, 8 * ep);
                    __syncwarp();
                    if (i == 7) {
                        const uint32_t *mp = reinterpret_cast<const uint32_t*>(g_mod) + lane, *wp = reinterpret_cast<const uint32_t*>(P.wr) + lane;
                        float ra = 0.f, rs = 0.f;
#pragma unroll 1
                        for (int k = 0; k < 256; k += 32) {
                            const uint32_t ga = __ldcg(mp + 512 + k), sh = __ldcg(mp + 768 + k), c1 = badd(__ldcg(mp + 1024 + k), ONE2);
                            const uint32_t gb = __ldcg(mp + 1280 + k), ww = __ldg(wp + k);
                            const float a0 = bf_lo(c1) * bf_lo(ww), a1 = bf_hi(c1) * bf_hi(ww);
                            ra += a0 + a1;
                            rs = fmaf(bf_lo(sh), bf_lo(ww), fmaf(bf_hi(sh), bf_hi(ww), rs));
                            if (k >> 6 == cq) {
                                sts128(sb + SM_TAB + ((k & 32) + lane) * 16, make_uint4(ga << 16, ga & 0xffff0000u, __float_as_uint(a0), __float_as_uint(a1)));
                                sts128(sb + SM_TAB + 1024 + ((k & 32) + lane) * 16, make_uint4(c1, sh, gb, 0));
                            }
                        }
                        *reinterpret_cast<float2*>(smem + SM_EP + 8) = make_float2(warp_sum(ra), warp_sum(rs));
                        __syncwarp();
                    }
                    if (lane == 0) mbar_arrive(sb + BAR_FLAG + 8 * i);
                    TS(48 + i);
                }
                const uint32_t* f = &g_sync.ctxcnt[ort * 32 + o_head(min(lane, 16), kh)];
                uint32_t ready = (MC & 8) && (j & 1) ? ~0u : 0u, list = 0, sh = 0, qa = sb + SM_EP + 4;
                if (MC & 8) asm("mapa.shared::cluster.u32 %0, %1, %2;" : "=r"(qa) : "r"(sb + SM_EP + 4), "r"(lane & 1));
                while (ready != ~0u) {
                    uint32_t v;
                    asm volatile("ld.acquire.gpu.global.u32 %0, [%1];" : "=r"(v) : "l"(f) : "memory");
                    const uint32_t now = __ballot_sync(0xffffffffu, (int)(v - ep) >= 0);
                    for (uint32_t fresh = now & ~ready & 0x7f00; fresh; fresh &= fresh - 1, sh += 4) list |= (__ffs(fresh) - 1) << sh;
                    list |= (((now & 0xff) + 1) >> 8 << 28) | ((now & 0x18000) << 14);
                    if (now != ready && lane < ((MC & 8) ? 2 : 1)) asm volatile("st.relaxed.cluster.shared::cluster.u32 [%0], %1;" ::"r"(qa), "r"(list) : "memory");
                    if ((now & 0xff) == 0xff) mbar_wait(sb + BAR_DONE + 8 * 7, 0);
                    ready = now;
                    __nanosleep(POLL_NS);
                }
                TS(45);
            }
        }
    } else {
        asm volatile("setmaxnreg.inc.sync.aligned.u32 232;");
        const bool elected = (tid & 127) == 0, rel = MC ? (tid & 95) == 0 : elected;
        uint32_t eb = sb + BAR_EMPTY;
        if (MC) asm("mapa.shared::cluster.u32 %0, %1, %2;" : "=r"(eb) : "r"(sb + BAR_EMPTY), "r"(warp & 1));
        const int g = lane >> 2, c4 = lane & 3;
        const uint32_t toff = warp * 4096 + g * 64 + ((c4 ^ (g >> 1)) << 4);
        uint32_t fph = 0, r = 0;
        if (wg == 1) bar_arrive(1, 256);
        const uint32_t kd = desc_k(sb), wd = desc_mn(sb), vd = ((sb & 0x3ffff) >> 4) | (32u << 16);
        const int nL = 16 - j, hn = nL - 1 + wg;
        float s[64], o[64], li[2] = {0.f, 0.f};
        uint8_t* cimg = g_ctx;
#pragma unroll 1
        for (int hp = 0; hp < 2; hp++) {
            {
                const int step = hp ? -8 * SLOT : 8 * SLOT;
                uint8_t* img = g_KV + (size_t)(grp * 32 + (hp ? j ^ 30 : j)) * SLOT - step;
                const float sc = (j & 1) ? 1.f : SM_C;
                const uint32_t wtab = w_table(hp);
                uint32_t atab = hp ? 0x256u : a_table(0);
#pragma unroll 1
                for (int t = 0;; t += 2) {
                    proj_tile<false>(s, o, t, t ? 0 : 2 * hp, sb, wg, eb, rel, fph, wtab, atab, t ? img : cimg, toff, t ? sc : li[0], t ? sc : li[1], (hp | t) == 0, P.x, rb * 16 + warp * 2);
                    __syncwarp();
                    mbar_arrive_if(sb + BAR_DONE + 4 * t + 32 * hp, lane == 0 && (hp | t) != 0);
                    if (elected) TS(1 + 10 * hp + t + 20 * wg);
                    if (proj_tile<true>(o, s, t + 1, 0, sb, wg, eb, rel, fph, wtab, atab, img + step, toff, sc, sc, (hp | t) == 0, P.x, rb * 16 + warp * 2)) break;
                    if (elected) TS(2 + 10 * hp + t + 20 * wg);
                    img += 2 * step;
                }
            }
            float m[2] = {0.f, 0.f}, l[2] = {0.f, 0.f}, t[4] = {0.f, 0.f, 0.f, 0.f};
            bool shifted = false, bad = false, plain = false;
            uint32_t p[32];
#pragma unroll
            for (int i = 0; i < 32; i++) p[i] = 0;
            uint32_t qa = desc_k(sb + 5 * SLOT + (wg ^ 1) * 8192);
            uint8_t* img = g_ctx + (size_t)((15 - j) * 32 + 2 * grp + hp) * SLOT;
            if (elected) TS(6 + 10 * hp + 20 * wg);
            int n = -1;
#pragma unroll 1
            for (;;) {
                while (bad || plain) {
                    if (bad) {
                        float a0, a1;
                        softmax_remax(s, m, n == 0 || n == nL, a0, a1);
                        shifted = true;
                        l[0] *= a0;
                        l[1] *= a1;
#pragma unroll
                        for (int i = 0; i < 64; i++) o[i] *= (i & 2) ? a1 : a0;
                    }
                    softmax_exp<0, 16>(s, p, t);
                    t[0] += t[1];
                    t[2] += t[3];
                    bad = !bad && softmax_unsafe(t[0], t[2], false);
                    plain = false;
                }
#pragma unroll 1
                do {
                    l[0] += t[0];
                    l[1] += t[2];
                    if (++n > 16) break;
                    const uint32_t ks = r;
                    uint32_t vs = ring_next(r);
                    r = ring_next(vs);
                    bar_sync(1 + wg, 256);
                    const int x = (warp & 3) * 16 + g - 2 * c4;
                    if (n == hn) {
                        float sh[32];
                        qk_issue(sh, qa, kd + ks * (SLOT / 16));
                        slot_wait(sb + BAR_FULL, fph, vs);
                        pv_issue(o, p, vd + vs * (SLOT / 16), 1, false);
                        bar_arrive(2 - wg, 256);
                        wg_wait<1>();
                        reg_fence(sh);
                        tri_mask_copy(s, sh, x);
                        release_if(eb, ks, rel);
                        release_if(eb, 5 + wg, rel && (!wg || n == 16));
                        if (!wg) {
                            qa += SLOT / 16;
                            fence_async_smem();
                            if (shifted) softmax_shift(s, m[0], m[1]);
                        }
                        float e[4 * EARLY];
#pragma unroll
                        for (int i = 0; i < 4 * EARLY; i++) {
                            e[i] = ex2(s[i]);
                            t[i & 3] = i < 4 ? e[i] : t[i & 3] + e[i];
                        }
                        reg_fence(e);
                        slot_wait(sb + BAR_FULL, fph, r);
                        wg_wait<0>();
                        reg_fence(o);
                        reg_fence(e);
                        release_if(eb, vs, rel);
#pragma unroll
                        for (int i = 0; i < 2 * EARLY; i++) p[i] = pack2(e[2 * i], e[2 * i + 1]);
                        softmax_exp<EARLY, 8>(s, p, t);
                        if (wg) {
                            ctx_store<true>(img, toff, o, l[0], l[1]);
                            __syncwarp();
                            mbar_arrive_if(sb + BAR_DONE + 24 + 32 * hp, lane == 0);
                            l[0] = l[1] = m[0] = m[1] = 0.f;
                            shifted = false;
                        }
                        t[0] += t[1];
                        t[2] += t[3];
                        bad = softmax_unsafe(t[0], t[2], wg);
                        continue;
                    }
                    if (n == 0 || n == nL) {
                        qk_issue(s, qa, kd + ks * (SLOT / 16));
                        if (n == 0) {
                            r = vs;
                            vs = 4 - hp;
                            slot_wait(sb + BAR_FULL, fph, 6);
                            gemm_issue<false>(o, qa + SLOT / 16, wd + vs * (SLOT / 16), 1, false);
                        } else {
                            slot_wait(sb + BAR_FULL, fph, vs);
                            pv_issue(o, p, vd + vs * (SLOT / 16), 1, true);
                        }
                        bar_arrive(2 - wg, 256);
                        const float i0 = n ? rcp(quad_sum(l[0])) : 1.f, i1 = n ? rcp(quad_sum(l[1])) : 1.f;
                        wg_wait<1>();
                        reg_fence(s);
                        release_if(eb, ks, rel);
                        release_if(eb, 6, rel && n == 16);
                        if (!LATEMASK) tri_mask<32>(s, n ? x : 64);
                        float e[4 * EARLY];
#pragma unroll
                        for (int i = 0; i < 4 * EARLY; i++) {
                            e[i] = ex2(s[i]);
                            t[i & 3] = i < 4 ? e[i] : t[i & 3] + e[i];
                        }
                        reg_fence(e);
                        slot_wait(sb + BAR_FULL, fph, r);
                        wg_wait<0>();
                        reg_fence(o);
                        reg_fence(e);
                        release_if(eb, vs, rel);
#pragma unroll
                        for (int i = 0; i < 2 * EARLY; i++) p[i] = pack2(e[2 * i], e[2 * i + 1]);
                        if (LATEMASK) tri_mask<32>(s, (n ? x : 64) + (__float_as_int(o[63]) & P.zero));
                        tile_store(img, sb + 6 * SLOT, toff, o, i0, i1, n);
                        softmax_exp<EARLY, 16>(s, p, t);
                        __syncwarp();
                        mbar_arrive_if(sb + BAR_DONE + 24 + 32 * hp, lane == 0 && n);
                        l[0] = l[1] = m[0] = m[1] = 0.f;
                        shifted = false;
                        t[0] += t[1];
                        t[2] += t[3];
                        bad = softmax_unsafe(t[0], t[2], true);
                        continue;
                    }
                    qk_issue(s, qa, kd + ks * (SLOT / 16));
                    slot_wait(sb + BAR_FULL, fph, vs);
                    pv_issue(o, p, vd + vs * (SLOT / 16), n != 1 && n != nL + 1, n == hn + 1);
                    bar_arrive(2 - wg, 256);
                    wg_wait<1>();
                    reg_fence(s);
                    release_if(eb, ks, rel);
                    release_if(eb, 6, rel && n == 16);
                    if (n == nL - 1) {
                        tri_mask<32>(s, x);
                        release_if(eb, 5, rel);
                        qa += SLOT / 16;
                        fence_async_smem();
                    }
                    if (shifted) {
                        slot_wait(sb + BAR_FULL, fph, r);
                        wg_wait<0>();
                        reg_fence(o);
                        release_if(eb, vs, rel);
                        softmax_shift(s, m[0], m[1]);
                        plain = true;
                        break;
                    }
                    float e[4 * EARLY];
#pragma unroll
                    for (int i = 0; i < 4 * EARLY; i++) {
                        e[i] = ex2(s[i]);
                        t[i & 3] = i < 4 ? e[i] : t[i & 3] + e[i];
                    }
                    reg_fence(e);
                    slot_wait(sb + BAR_FULL, fph, r);
                    wg_wait<0>();
                    reg_fence(o);
                    reg_fence(e);
                    release_if(eb, vs, rel);
#pragma unroll
                    for (int i = 0; i < 2 * EARLY; i++) p[i] = pack2(e[2 * i], e[2 * i + 1]);
                    softmax_exp<EARLY, 16>(s, p, t);
                    t[0] += t[1];
                    t[2] += t[3];
                    bad = softmax_unsafe(t[0], t[2], false);
                } while (!bad);
                if (!bad && !plain) break;
            }
            const uint32_t vs = r, ga = desc_k(sb + (hp ? 2 * (wg ^ kh ^ 1) : wg) * 8192), as = 2 + 2 * hp;
            r = ring_next(r);
            slot_wait(sb + BAR_FULL, fph, 5);
            slot_wait(sb + BAR_FULL, fph, r);
            bar_sync(1 + wg, 256);
            gemm_issue<true>(s, ga + 5 * (SLOT / 16), wd + r * (SLOT / 16), 0, hp);
            pv_issue(o, p, vd + vs * (SLOT / 16), j, hn == 16);
            bar_arrive(2 - wg, 256);
            li[0] = rcp(quad_sum(l[0]));
            li[1] = rcp(quad_sum(l[1]));
            cimg = img + (ptrdiff_t)(2 * j - 15) * 32 * SLOT + (wg ? -16384 : 16384);
            wg_wait<1>();
            release_if(eb, 5, rel);
            release_if(eb, r, rel && hp);
            wg_wait<0>();
            release_if(eb, vs, rel);
            reg_fence(o);
            img_store_global<0>(cimg, toff, o, li[0], li[1]);
            slot_wait(sb + BAR_FULL, fph, as);
            slot_wait(sb + BAR_FULL, fph, 0);
            bar_sync(1 + wg, 256);
            gemm_issue<false>(s, ga + as * (SLOT / 16), wd, 1, hp);
            bar_arrive(2 - wg, 256);
            reg_fence(o);
            img_store_global<1>(cimg, toff, o, li[0], li[1]);
            wg_wait<0>();
            release_if(eb, as, rel);
            release_if(eb, 0, rel && hp);
            if (elected) TS(8 + 10 * hp + 20 * wg);
        }
        uint32_t otab = 0x0423516u;
        const uint32_t oa = desc_k(sb + (wg ^ kh ^ 1) * 16384);
        const int t7 = tid & 127, w4 = warp & 3, row = ort * 128 + kh * 64 + w4 * 16 + g;
#pragma unroll 1
        for (int i = 2; i < 15 - wg; i++) {
            const uint32_t as = o_next(otab), ws = o_next(otab);
            slot_wait(sb + BAR_FULL, fph, as);
            slot_wait(sb + BAR_FULL, fph, ws);
            bar_sync(1 + wg, 256);
            gemm_issue<false>(s, oa + as * (SLOT / 16), wd + ws * (SLOT / 16), 1, true);
            bar_arrive(2 - wg, 256);
            wg_wait<1>();
            reg_fence(o);
            if (i == 2) img_store_global<2>(cimg, toff, o, li[0], li[1]);
            if (i == CLAST) {
                img_store_global<3>(cimg, toff, o, li[0], li[1]);
                __syncwarp();
                mbar_arrive_if(sb + BAR_DONE + 64, lane == 0);
            }
            wg_wait<0>();
            release_if(eb, as, rel);
            release_if(eb, ws, rel);
        }
        mbar_wait(sb + BAR_PF, 0);
        const uint32_t ep = lds32(sb + SM_EP);
        if (wg == 0) {
            reg_fence(s);
            if (elected) TS(9);
#pragma unroll
            for (int v = 0; v < 8; v++)
                st_pub(g_out + rb * OB + v * 128 + t7, make_uint4((pack2(s[8 * v], s[8 * v + 1]) & ~1u) | (ep & 1), pack2(s[8 * v + 2], s[8 * v + 3]),
                                                                      pack2(s[8 * v + 4], s[8 * v + 5]), pack2(s[8 * v + 6], s[8 * v + 7])), true);
            o_next(otab); o_next(otab); o_next(otab); o_next(otab);
            const uint32_t s1 = o_next(otab), s2 = o_next(otab);
            bar_sync(4, 256);
            uint32_t wf[64];
            float wn[64];
            if (rb < NFFN) {
                slot_wait(sb + BAR_FULL, fph, s1);
                const uint32_t a = sb + s1 * SLOT + (w4 * 128 + (lane >> 4) * 8 + (lane & 7)) * 32 + ((lane >> 3) & 1) * 16;
#pragma unroll
                for (int i = 0; i < 16; i++)
                    asm volatile("ldmatrix.sync.aligned.m8n8.x4.trans.shared.b16 {%0, %1, %2, %3}, [%4];"
                                 : "=r"(wf[4 * i]), "=r"(wf[4 * i + 1]), "=r"(wf[4 * i + 2]), "=r"(wf[4 * i + 3])
                                 : "r"(a + (i >> 3) * 16384 + (i & 7) * 512) : "memory");
                slot_wait(sb + BAR_FULL, fph, s2);
#pragma unroll
                for (int i = 0; i < 16; i++) {
                    const uint2 w = *reinterpret_cast<const uint2*>(smem + s2 * SLOT + i * 1024 + t7 * 8);
                    wn[4 * i] = bf_lo(w.x); wn[4 * i + 1] = bf_hi(w.x); wn[4 * i + 2] = bf_lo(w.y); wn[4 * i + 3] = bf_hi(w.y);
                }
                reg_fence(wn);
            }
            const uint32_t gbf = __ldcg(reinterpret_cast<const uint32_t*>(g_mod) + 1280 + rb * 2 + (tid & 1));
            if (elected) TS(10);
            const uint32_t best = best_key(g_key + cq * 128, lane, ep);
            const int sel = (~best >> 5) & 2047;
            if (elected) TS(19);
            const uint4* cp = g_cand + (sel >> 4) * 192;
            float* sred = reinterpret_cast<float*>(smem + SM_RED);
            const int pq = (2 * rb + (tid & 1)) & 63, pv = (pq >> 2) / 3;
            const uint4* fp = cp + (rb >> 5) * 24 + pv * 4 + (pq & 3);
            uint4 fh = ld_poll(fp), fx = ld_poll(fp + 96);
            if (rb < NFFN) {
                uint4 cv[6];
                for (;;) {
                    uint32_t bad = 0;
#pragma unroll
                    for (int v = 0; v < 6; v++) cv[v] = ld_poll(cp + w4 * 24 + v * 4 + c4);
#pragma unroll
                    for (int v = 0; v < 6; v++) bad |= cv[v].w ^ ep;
                    if (__all_sync(0xffffffffu, bad == 0)) break;
                }
                if (elected) TS(20);
                float d[4][4] = {};
#pragma unroll
                for (int k = 0; k < 8; k++) {
                    const uint32_t b0 = (&cv[(2 * k) / 3].x)[(2 * k) % 3], b1 = (&cv[(2 * k + 1) / 3].x)[(2 * k + 1) % 3];
                    mma16816(d[k & 1], wf + 4 * k, b0, b1);
                    mma16816(d[2 + (k & 1)], wf + 32 + 4 * k, b0, b1);
                }
                const float u = (c4 & 2) ? ((c4 & 1) ? d[2][2] + d[3][2] : d[2][0] + d[3][0]) : ((c4 & 1) ? d[0][2] + d[1][2] : d[0][0] + d[1][0]);
                sred[w4 * 32 + c4 * 8 + g] = u;
                bar_sync(3, 128);
                const float v = rbf((sred[lane] + sred[32 + lane]) + (sred[64 + lane] + sred[96 + lane]));
                const float act = rbf(rbf(v * sigmoid(v)) * __shfl_down_sync(0xffffffffu, v, 16));
                float y[4] = {0.f, 0.f, 0.f, 0.f};
#pragma unroll
                for (int k = 0; k < 16; k++) {
                    const float a = __shfl_sync(0xffffffffu, act, k);
#pragma unroll
                    for (int i = 0; i < 4; i++) y[i] = fmaf(a, wn[4 * k + i], y[i]);
                }
                st_pub(g_out + rb * OB + OB_Y + t7, make_uint4((__float_as_uint(y[0]) & ~15u) | (ep & 15), __float_as_uint(y[1]), __float_as_uint(y[2]), __float_as_uint(y[3])), true);
            }
            if (rb == 0 && tid == 0) g_sync.epoch[0] = ep;
            if (elected) TS(60);
            uint4 yv;
            do yv = ld_poll(g_out + min(t7, NFFN - 1) * OB + OB_Y + rb);
            while (!__all_sync(0xffffffffu, ((yv.x ^ ep) & 15) == 0));
            if (elected) TS(61);
            float y[4] = {0.f, 0.f, 0.f, 0.f};
            if (t7 < NFFN) { y[0] = __uint_as_float(yv.x); y[1] = __uint_as_float(yv.y); y[2] = __uint_as_float(yv.z); y[3] = __uint_as_float(yv.w); }
            const float z0 = ((lane & 16) ? y[2] : y[0]) + __shfl_xor_sync(0xffffffffu, (lane & 16) ? y[0] : y[2], 16);
            const float z1 = ((lane & 16) ? y[3] : y[1]) + __shfl_xor_sync(0xffffffffu, (lane & 16) ? y[1] : y[3], 16);
            float z = ((lane & 8) ? z1 : z0) + __shfl_xor_sync(0xffffffffu, (lane & 8) ? z0 : z1, 8);
            z += __shfl_xor_sync(0xffffffffu, z, 4);
            z = quad_sum(z);
            if ((lane & 7) == 0) sred[128 + (lane >> 3) * 4 + w4] = z;
            bar_sync(3, 128);
            if (tid < 2) {
                while (fh.w != ep || fx.w != ep) { fh = ld_poll(fp); fx = ld_poll(fp + 96); }
                const float4 y0 = *reinterpret_cast<const float4*>(sred + 128 + tid * 8), y1 = *reinterpret_cast<const float4*>(sred + 132 + tid * 8);
                const int cm = (pq >> 2) - 3 * pv;
                const uint32_t h2 = cm == 0 ? fh.x : cm == 1 ? fh.y : fh.z, x2 = cm == 0 ? fx.x : cm == 1 ? fx.y : fx.z;
                const float sg = sigmoid(bf_hi((best & 0x80000000u) ? (best ^ 0x80000000u) : ~best));
                reinterpret_cast<uint32_t*>(P.out)[sel * 256 + rb * 2 + tid] =
                    badd(x2, bmul(gbf, badd(h2, bmul(pack2((y0.x + y0.y) + (y0.z + y0.w), (y1.x + y1.y) + (y1.z + y1.w)), pack2(sg, sg)))));
            }
            if (elected) TS(62);
        } else {
            const float4* tf = reinterpret_cast<const float4*>(smem + SM_TAB) + c4;
            const uint32_t as14 = otab & 15, xa = sb + ((otab >> 8) & 15) * SLOT + (kh ^ 1) * 16384 + (w4 * 16 + (lane & 15)) * 128;
            uint32_t x2[32];
            bar_sync(2, 256);
#pragma unroll 1
            for (int i = 14; i < 17; i++) {
                const uint32_t as = o_next(otab), ws = o_next(otab);
                slot_wait(sb + BAR_FULL, fph, as);
                slot_wait(sb + BAR_FULL, fph, ws);
                gemm_issue<false>(s, oa + as * (SLOT / 16), wd + ws * (SLOT / 16), 1, true);
                wg_wait<1>();
                release_if(eb, as14, rel && i == 15);
            }
            if (elected) TS(29);
            {
#pragma unroll
                for (int k = 0; k < 8; k++)
                    asm volatile("ldmatrix.sync.aligned.m8n8.x4.shared.b16 {%0, %1, %2, %3}, [%4];"
                                 : "=r"(x2[4 * k]), "=r"(x2[4 * k + 1]), "=r"(x2[4 * k + 2]), "=r"(x2[4 * k + 3])
                                 : "r"(xa + (k >> 2) * 8192 + (((2 * (k & 3) + (lane >> 4)) ^ (lane & 7)) << 4)) : "memory");
            }
            wg_wait<0>();
            reg_fence(s);
            bar_arrive(4, 256);
            if (elected) TS(39);
            const uint4* pr = g_out + (rb ^ 8) * OB + t7;
            uint4 pa[8];
#pragma unroll
            for (int v = 0; v < 8; v++) pa[v] = ld_poll(pr + v * 128);
            float4 tc[16];
#pragma unroll
            for (int k = 0; k < 16; k++) {
                tc[k] = tf[k * 4];
#pragma unroll
                for (int i = 4 * k; i < 4 * k + 4; i++) s[i] = fmaf((i & 1) ? tc[k].y : tc[k].x, s[i], (i & 1) ? bf_hi(x2[i >> 1]) : bf_lo(x2[i >> 1]));
            }
            reg_fence(s);
            for (;;) {
                uint32_t bad = 0;
#pragma unroll
                for (int v = 0; v < 8; v++) bad |= pa[v].x ^ ep;
                if (__all_sync(0xffffffffu, (bad & 1) == 0)) break;
#pragma unroll
                for (int v = 0; v < 8; v++) pa[v] = ld_poll(pr + v * 128);
            }
            if (elected) TS(30);
            float st[6] = {0.f, 0.f, 0.f, 0.f, 0.f, 0.f};
#pragma unroll
            for (int i = 0; i < 64; i++) {
                const int rh = (i >> 1) & 1;
                const uint32_t w = (&pa[i >> 3].x)[(i >> 1) & 3];
                const float v = fmaf((i & 1) ? tc[i >> 2].y : tc[i >> 2].x, (i & 1) ? bf_hi(w) : bf_lo(w), s[i]);
                s[i] = v;
                st[rh] += v;
                st[2 + rh] = fmaf(v, v, st[2 + rh]);
                st[4 + rh] = fmaf(v, (i & 1) ? tc[i >> 2].w : tc[i >> 2].z, st[4 + rh]);
            }
#pragma unroll
            for (int i = 0; i < 6; i++) st[i] = quad_sum(st[i]);
            st_pub(g_out + rb * OB + OB_STAT + (w4 * 8 + g) * 2 + (c4 & 1),
                   make_uint4(__float_as_uint((c4 & 1) ? st[1] : st[0]), __float_as_uint((c4 & 1) ? st[3] : st[2]),
                              __float_as_uint((c4 & 1) ? st[5] : st[4]), ep), c4 < 2);
            if (elected) TS(56);
            uint32_t cb[16], sh[16], gb[16];
#pragma unroll
            for (int i = 0; i < 16; i++) {
                const float4 c = tf[64 + i * 4];
                cb[i] = __float_as_uint(c.x); sh[i] = __float_as_uint(c.y); gb[i] = __float_as_uint(c.z);
            }
            const float ra = __uint_as_float(lds32(sb + SM_EP + 8)), rb0 = __uint_as_float(lds32(sb + SM_EP + 12));
#pragma unroll
            for (int i = 0; i < 32; i++) x2[i] = pack2(s[2 * i], s[2 * i + 1]);
            reg_fence(x2);
            uint4 r0, r1;
            for (;;) {
                r0 = ld_poll(g_out + ((rb & ~3) + c4) * OB + OB_STAT + (w4 * 8 + g) * 2);
                r1 = ld_poll(g_out + ((rb & ~3) + c4) * OB + OB_STAT + (w4 * 8 + g) * 2 + 1);
                if (__all_sync(0xffffffffu, r0.w == ep && r1.w == ep)) break;
            }
            if (elected) TS(57);
            const float m0 = quad_sum(__uint_as_float(r0.x)) * (1.f / 512.f), m1 = quad_sum(__uint_as_float(r1.x)) * (1.f / 512.f);
            const float rs0 = ln_rstd(fmaxf(fmaf(-m0, m0, quad_sum(__uint_as_float(r0.y)) * (1.f / 512.f)), 0.f));
            const float rs1 = ln_rstd(fmaxf(fmaf(-m1, m1, quad_sum(__uint_as_float(r1.y)) * (1.f / 512.f)), 0.f));
            const uint32_t mb0 = pack2(m0, m0), mb1 = pack2(m1, m1);
            const uint32_t lg = pack2(fmaf(rs0, fmaf(-bf_lo(mb0), ra, quad_sum(__uint_as_float(r0.z))), rb0),
                                      fmaf(rs1, fmaf(-bf_lo(mb1), ra, quad_sum(__uint_as_float(r1.z))), rb0));
            const uint32_t u0 = lg << 16, u1 = lg & 0xffff0000u;
            const uint32_t k0 = ((u0 ^ (((int)u0 >> 31) | 0x80000000u)) & 0xffff0000u) | ((2047 - row) << 5) | (ep & 31);
            const uint32_t k1 = ((u1 ^ (((int)u1 >> 31) | 0x80000000u)) & 0xffff0000u) | ((2039 - row) << 5) | (ep & 31);
            const uint32_t kb = __reduce_max_sync(0xffffffffu, max(k0, k1));
            st_pub(g_key + cq * 128 + (row >> 4), kb, lane == 0);
            {
                uint32_t cx[18], ch[18];
#pragma unroll
                for (int i = 0; i < 16; i++) {
                    cx[i] = kb == k1 ? x2[2 * i + 1] : x2[2 * i];
                    ch[i] = ln_apply(cx[i], kb == k1 ? mb1 : mb0, kb == k1 ? rs1 : rs0, cb[i], sh[i]);
                }
                cx[16] = cx[17] = ch[16] = ch[17] = 0;
                uint4* cp = g_cand + (row >> 4) * 192 + cq * 24 + c4;
#pragma unroll
                for (int v = 0; v < 6; v++) st_pub(cp + v * 4, make_uint4(ch[3 * v], ch[3 * v + 1], ch[3 * v + 2], ep), kb == k0 || kb == k1);
#pragma unroll
                for (int v = 0; v < 6; v++) st_pub(cp + 96 + v * 4, make_uint4(cx[3 * v], cx[3 * v + 1], cx[3 * v + 2], ep), kb == k0 || kb == k1);
            }
            if (elected) TS(58);
            uint2 ov[16];
#pragma unroll
            for (int i = 0; i < 16; i++) {
                const int rh = i & 1, jj = i & 14;
                const uint32_t v0 = badd(x2[2 * jj + rh], bmul(gb[jj], ln_apply(x2[2 * jj + rh], rh ? mb1 : mb0, rh ? rs1 : rs0, cb[jj], sh[jj])));
                const uint32_t v1 = badd(x2[2 * jj + 2 + rh], bmul(gb[jj + 1], ln_apply(x2[2 * jj + 2 + rh], rh ? mb1 : mb0, rh ? rs1 : rs0, cb[jj + 1], sh[jj + 1])));
                const uint32_t rv = __shfl_xor_sync(0xffffffffu, (c4 & 1) ? v0 : v1, 1);
                ov[i] = (c4 & 1) ? make_uint2(rv, v1) : make_uint2(v0, rv);
            }
            uint2* op = reinterpret_cast<uint2*>(P.out) + row * 128 + cq * 32 + (c4 & 1) * 2 + (c4 >> 1);
#pragma unroll
            for (int i = 0; i < 16; i++)
                if (kb != ((i & 1) ? k1 : k0)) op[(i & 1) * 1024 + (i & 14) * 2] = ov[i];
            const uint32_t best = best_key(g_key + cq * 128, lane, ep);
            if (best != kb) {
#pragma unroll
                for (int i = 0; i < 16; i++)
                    if (kb == ((i & 1) ? k1 : k0)) op[(i & 1) * 1024 + (i & 14) * 2] = ov[i];
            }
            if (elected) TS(59);
        }
        mbar_arrive_if(sb + BAR_END, lane == 0);
    }
}

typedef CUresult (*EncodeFn)(CUtensorMap*, CUtensorMapDataType, cuuint32_t, void*, const cuuint64_t*, const cuuint64_t*,
                             const cuuint32_t*, const cuuint32_t*, CUtensorMapInterleave, CUtensorMapSwizzle,
                             CUtensorMapL2promotion, CUtensorMapFloatOOBfill);

void make_2d(EncodeFn fn, CUtensorMap* m, const void* p, uint64_t cols, uint64_t rows, uint32_t bc, uint32_t br) {
    cuuint64_t dims[2] = {cols, rows}, strides[1] = {cols * 2};
    cuuint32_t box[2] = {bc, br}, es[2] = {1, 1};
    fn(m, CU_TENSOR_MAP_DATA_TYPE_BFLOAT16, 2, const_cast<void*>(p), dims, strides, box, es, CU_TENSOR_MAP_INTERLEAVE_NONE,
       CU_TENSOR_MAP_SWIZZLE_NONE, CU_TENSOR_MAP_L2_PROMOTION_L2_128B, CU_TENSOR_MAP_FLOAT_OOB_FILL_NONE);
}
void make_3d(EncodeFn fn, CUtensorMap* m, const void* p, uint64_t cols, uint64_t rows, uint32_t br = 128, uint32_t nb = 2) {
    cuuint64_t dims[3] = {64, rows, cols / 64}, strides[2] = {cols * 2, 128};
    cuuint32_t box[3] = {64, br, nb}, es[3] = {1, 1, 1};
    fn(m, CU_TENSOR_MAP_DATA_TYPE_BFLOAT16, 3, const_cast<void*>(p), dims, strides, box, es, CU_TENSOR_MAP_INTERLEAVE_NONE,
       CU_TENSOR_MAP_SWIZZLE_128B, CU_TENSOR_MAP_L2_PROMOTION_L2_256B, CU_TENSOR_MAP_FLOAT_OOB_FILL_NONE);
}

}

extern "C" void kernel_launch(void* const* d_in, const int* in_sizes, int n_in, void* d_out, int out_size) {
    static EncodeFn fn = nullptr;
    static int sms = 0;
    if (!fn) {
        void* f = nullptr;
        cudaDriverEntryPointQueryResult st;
        cudaGetDriverEntryPoint("cuTensorMapEncodeTiled", &f, cudaEnableDefault, &st);
        fn = (EncodeFn)f;
        int dev = 0;
        cudaGetDevice(&dev);
        cudaDeviceGetAttribute(&sms, cudaDevAttrMultiProcessorCount, dev);
        cudaFuncSetAttribute(fused_kernel, cudaFuncAttributeMaxDynamicSharedMemorySize, SMEM_BYTES);
    }
    CUtensorMap ckv, wq, wuk, wuv, wo, wg, wu, wm, xm;
    make_3d(fn, &ckv, d_in[1], 512, 2048, 128, (MC & 1) ? 1 : 2);
    make_3d(fn, &xm, d_in[0], 512, 2048, 64);
    make_3d(fn, &wq, d_in[2], 4096, 512, 128, (MC & 2) ? 1 : 2);
    make_3d(fn, &wuk, d_in[3], 4096, 512);
    make_3d(fn, &wuv, d_in[4], 4096, 512);
    make_3d(fn, &wo, d_in[5], 512, 4096);
    make_2d(fn, &wg, d_in[8], 1792, 512, 16, 256);
    make_2d(fn, &wu, d_in[9], 1792, 512, 16, 256);
    make_2d(fn, &wm, d_in[12], 3072, 512, 256, 64);
    Params p;
    p.x = (const bf16*)d_in[0];
    p.ckv = (const bf16*)d_in[1];
    p.wo = (const bf16*)d_in[5];
    p.wr = (const bf16*)d_in[7];
    p.wdown = (const bf16*)d_in[10];
    p.c = (const bf16*)d_in[11];
    p.out = (bf16*)d_out;
    p.zero = 0;
    p.by_smid = sms == NCTA + NSPARE;
    fused_kernel<<<NCTA + NSPARE, 384, SMEM_BYTES>>>(ckv, wq, wuk, wuv, wo, wg, wu, wm, xm, p);
}
```

```cpp
#include <cuda.h>
#include <cuda_bf16.h>
#include <cuda_runtime.h>
#include <stdint.h>
#include <stdio.h>

namespace {

typedef __nv_bfloat16 bf16;
typedef unsigned long long u64;

constexpr int NCTA = 128, NSPARE = 4;
constexpr int SLOT = 32768;
constexpr int SM_BAR = 7 * SLOT;
constexpr int BAR_FULL = SM_BAR;
constexpr int BAR_EMPTY = BAR_FULL + 8 * 7;
constexpr int BAR_DONE = BAR_EMPTY + 8 * 7;
constexpr int BAR_FLAG = BAR_DONE + 8 * 9;
constexpr int BAR_PF = BAR_FLAG + 8 * 9;
constexpr int BAR_END = BAR_PF + 8;
constexpr int SM_EP = BAR_END + 8;
constexpr int SM_RED = SM_BAR + 384;
constexpr int SM_TAB = SM_BAR + 1024;
constexpr int SMEM_BYTES = SM_BAR + 3072;
constexpr int NFFN = 112;
#define HINT 31
constexpr u64 L2_NORMAL = 0x1000000000000000ull, L2_FIRST = 0x12F0000000000000ull;
#define PF0 0
#define PFA 9
#define PFB 6
#define PFC 12
#define PFMASK 1023
#define UNR 4
#define POLL_NS 50
#define CLAST 2
#define OBINIT 1
#define MC 15
#define MSPLIT 13
#define SF 3
#define EARLY 7
constexpr uint32_t SPIN_LIMIT = 1u << 22;
constexpr uint32_t ONE2 = 0x3f803f80u;

struct Sync {
    uint32_t modcnt[2 * 32];
    uint32_t hcnt[16 * 8];
    uint32_t kvcnt[32 * 2 * 8];
    uint32_t ctxcnt[16 * 32];
    uint32_t rdcnt[16 * 2 * 8];
    uint32_t epoch[32];
};

__device__ __align__(1024) uint8_t g_KV[16 * 16 * 2 * SLOT];
__device__ __align__(1024) uint8_t g_ctx[16 * 32 * SLOT];
__device__ __align__(1024) uint8_t g_h[16 * 4 * SLOT];
constexpr int OB = 1216, OB_STAT = 1024, OB_Y = 1088;
__device__ __align__(1024) uint4 g_out[128 * OB];
__device__ __align__(1024) bf16 g_mod[3072];
__device__ __align__(1024) uint4 g_cand[128 * 192];
__device__ __align__(1024) uint32_t g_key[4 * 128];
__device__ __align__(1024) uint8_t g_wf[NFFN * SLOT];
__device__ __align__(1024) Sync g_sync;
#define TS(i)

#define PT()
#define CDEF
#define CT(i)
#define COUT(b, k)

struct Params {
    const bf16 *x, *ckv, *wo, *wr, *wdown, *c;
    bf16* out;
    int by_smid, zero;
};

__device__ __forceinline__ void mbar_init(uint32_t bar, uint32_t cnt) {
    asm volatile("mbarrier.init.shared::cta.b64 [%0], %1;" ::"r"(bar), "r"(cnt) : "memory");
}
__device__ __forceinline__ void mbar_wait(uint32_t bar, uint32_t parity) {
    asm volatile("{\n.reg .pred p;\nL_%=:\nmbarrier.try_wait.parity.shared::cta.b64 p, [%0], %1;\n@!p bra L_%=;\n}" ::"r"(bar), "r"(parity) : "memory");
}
__device__ __forceinline__ void mbar_watch(uint32_t bar, uint32_t parity) {
    asm volatile("{\n.reg .pred p;\n.reg .u32 n;\nmov.u32 n, 0;\n"
                 "L_%=:\nmbarrier.try_wait.parity.shared::cta.b64 p, [%0], %1;\n@p bra D_%=;\n"
                 "add.u32 n, n, 1;\nsetp.lt.u32 p, n, %2;\n@p bra L_%=;\ntrap;\nD_%=:\n}"
                 ::"r"(bar), "r"(parity), "n"(SPIN_LIMIT) : "memory");
}
__device__ __forceinline__ void step_watch(uint32_t a, uint32_t step) {
    asm volatile("{\n.reg .pred p;\n.reg .u32 n, v;\nmov.u32 n, 0;\n"
                 "L_%=:\nld.volatile.shared.u32 v, [%0];\nsetp.ge.u32 p, v, %1;\n@p bra D_%=;\nnanosleep.u32 200;\n"
                 "add.u32 n, n, 1;\nsetp.lt.u32 p, n, %2;\n@p bra L_%=;\ntrap;\nD_%=:\n}"
                 ::"r"(a), "r"(step), "n"(SPIN_LIMIT) : "memory");
}
__device__ __forceinline__ void mbar_arrive(uint32_t bar) {
    asm volatile("mbarrier.arrive.shared::cta.b64 _, [%0];" ::"r"(bar) : "memory");
}
__device__ __forceinline__ void mbar_arrive_if(uint32_t bar, bool on) {
    asm volatile("{\n.reg .pred p;\nsetp.ne.s32 p, %1, 0;\n@p mbarrier.arrive.shared::cta.b64 _, [%0];\n}" ::"r"(bar), "r"((int)on) : "memory");
}
__device__ __forceinline__ void mbar_expect(uint32_t bar, uint32_t bytes) {
    asm volatile("mbarrier.arrive.expect_tx.shared::cta.b64 _, [%0], %1;" ::"r"(bar), "r"(bytes) : "memory");
}
__device__ __forceinline__ void tma2d(uint32_t dst, const CUtensorMap* m, int c0, int c1, uint32_t bar) {
    asm volatile("cp.async.bulk.tensor.2d.shared::cluster.global.mbarrier::complete_tx::bytes [%0], [%1, {%3, %4}], [%2];"
                 ::"r"(dst), "l"(m), "r"(bar), "r"(c0), "r"(c1) : "memory");
}
__device__ __forceinline__ void tma3d_prefetch(const CUtensorMap* m, int row, int cb) {
    asm volatile("cp.async.bulk.prefetch.tensor.3d.L2.global [%0, {%1, %2, %3}];" ::"l"(m), "r"(0), "r"(row), "r"(cb) : "memory");
}
__device__ __forceinline__ void l2_prefetch(const void* p, uint32_t bytes) {
    asm volatile("cp.async.bulk.prefetch.L2.global [%0], %1;" ::"l"(p), "r"(bytes) : "memory");
}
__device__ __forceinline__ void flag_wait(const uint32_t* f, uint32_t target) {
    asm volatile("{\n.reg .pred p;\n.reg .u32 v;\n"
                 "L_%=:\nld.acquire.gpu.global.u32 v, [%0];\nsub.u32 v, v, %1;\nsetp.lt.s32 p, v, 0;\n@p nanosleep.u32 100;\n@p bra L_%=;\n}"
                 ::"l"(f), "r"(target) : "memory");
}
__device__ __forceinline__ uint4 ld_poll(const uint4* p) {
    uint4 v;
    asm volatile("{\n.reg .b128 t;\nld.relaxed.gpu.global.b128 t, [%4];\nmov.b128 {%0, %1, %2, %3}, t;\n}"
                 : "=r"(v.x), "=r"(v.y), "=r"(v.z), "=r"(v.w) : "l"(p) : "memory");
    return v;
}
__device__ __forceinline__ void st_pub(uint4* p, uint4 v, bool on) {
    asm volatile("{\n.reg .pred p;\n.reg .b128 t;\nsetp.ne.s32 p, %5, 0;\nmov.b128 t, {%1, %2, %3, %4};\n@p st.relaxed.gpu.global.b128 [%0], t;\n}"
                 ::"l"(p), "r"(v.x), "r"(v.y), "r"(v.z), "r"(v.w), "r"((int)on) : "memory");
}
__device__ __forceinline__ void st_pub(uint32_t* p, uint32_t v, bool on) {
    asm volatile("{\n.reg .pred p;\nsetp.ne.s32 p, %2, 0;\n@p st.relaxed.gpu.global.u32 [%0], %1;\n}" ::"l"(p), "r"(v), "r"((int)on) : "memory");
}
__device__ __forceinline__ void flag_add(uint32_t* p) {
    asm volatile("red.release.gpu.global.add.u32 [%0], 1;" ::"l"(p) : "memory");
}
__device__ __forceinline__ uint32_t lds32(uint32_t a) {
    uint32_t v;
    asm volatile("ld.shared.u32 %0, [%1];" : "=r"(v) : "r"(a) : "memory");
    return v;
}
__device__ __forceinline__ uint4 lds128(uint32_t a) {
    uint4 v;
    asm volatile("ld.shared.v4.u32 {%0, %1, %2, %3}, [%4];" : "=r"(v.x), "=r"(v.y), "=r"(v.z), "=r"(v.w) : "r"(a) : "memory");
    return v;
}
__device__ __forceinline__ void sched_fence(uint32_t& v, uint32_t z) {
    uint32_t ck;
    asm volatile("mov.u32 %0, %%clock;" : "=r"(ck)::"memory");
    v ^= ck & z;
}
__device__ __forceinline__ void fence_async_global() { asm volatile("fence.proxy.async.global;" ::: "memory"); }
__device__ __forceinline__ void fence_async_smem() { asm volatile("fence.proxy.async.shared::cta;" ::: "memory"); }
__device__ __forceinline__ void bar_sync(int id, int n) { asm volatile("bar.sync %0, %1;" ::"r"(id), "r"(n) : "memory"); }
__device__ __forceinline__ void bar_arrive(int id, int n) { asm volatile("bar.arrive %0, %1;" ::"r"(id), "r"(n) : "memory"); }
__device__ __forceinline__ void wg_fence() { asm volatile("wgmma.fence.sync.aligned;" ::: "memory"); }
__device__ __forceinline__ void wg_commit() { asm volatile("wgmma.commit_group.sync.aligned;" ::: "memory"); }
template <int N> __device__ __forceinline__ void wg_wait() { asm volatile("wgmma.wait_group.sync.aligned %0;" ::"n"(N) : "memory"); }
template <int N> __device__ __forceinline__ void reg_fence(float (&d)[N]) {
#pragma unroll
    for (int i = 0; i < N; i++) asm volatile("" : "+f"(d[i])::"memory");
}
template <int N> __device__ __forceinline__ void reg_fence(uint32_t (&d)[N]) {
#pragma unroll
    for (int i = 0; i < N; i++) asm volatile("" : "+r"(d[i])::"memory");
}
__device__ __forceinline__ uint32_t desc_k(uint32_t a) { return ((a & 0x3ffff) >> 4) | (1u << 16); }
__device__ __forceinline__ uint32_t desc_mn(uint32_t a) { return ((a & 0x3ffff) >> 4) | (1024u << 16); }

template <int TB>
__device__ __forceinline__ void wgmma_ss128(float (&d)[64], uint32_t da, uint32_t db, int acc, uint32_t ha = 0x40000040u, uint32_t hb = 0x40000040u) {
    asm volatile("{\n.reg .pred p;\n.reg .b64 a, b;\nsetp.ne.b32 p, %66, 0;\nmov.b64 a, {%64, %68};\nmov.b64 b, {%65, %69};\n"
        "wgmma.mma_async.sync.aligned.m64n128k16.f32.bf16.bf16 {%0, %1, %2, %3, %4, %5, %6, %7, %8, %9, %10, %11, %12, %13, %14, %15, %16, %17, %18, %19, %20, %21, %22, %23, %24, %25, %26, %27, %28, %29, %30, %31, %32, %33, %34, %35, %36, %37, %38, %39, %40, %41, %42, %43, %44, %45, %46, %47, %48, %49, %50, %51, %52, %53, %54, %55, %56, %57, %58, %59, %60, %61, %62, %63}, a, b, p, 1, 1, 0, %67;\n}"
        : "+f"(d[0]), "+f"(d[1]), "+f"(d[2]), "+f"(d[3]), "+f"(d[4]), "+f"(d[5]), "+f"(d[6]), "+f"(d[7]), "+f"(d[8]), "+f"(d[9]), "+f"(d[10]), "+f"(d[11]), "+f"(d[12]), "+f"(d[13]), "+f"(d[14]), "+f"(d[15]), "+f"(d[16]), "+f"(d[17]), "+f"(d[18]), "+f"(d[19]), "+f"(d[20]), "+f"(d[21]), "+f"(d[22]), "+f"(d[23]), "+f"(d[24]), "+f"(d[25]), "+f"(d[26]), "+f"(d[27]), "+f"(d[28]), "+f"(d[29]), "+f"(d[30]), "+f"(d[31]), "+f"(d[32]), "+f"(d[33]), "+f"(d[34]), "+f"(d[35]), "+f"(d[36]), "+f"(d[37]), "+f"(d[38]), "+f"(d[39]), "+f"(d[40]), "+f"(d[41]), "+f"(d[42]), "+f"(d[43]), "+f"(d[44]), "+f"(d[45]), "+f"(d[46]), "+f"(d[47]), "+f"(d[48]), "+f"(d[49]), "+f"(d[50]), "+f"(d[51]), "+f"(d[52]), "+f"(d[53]), "+f"(d[54]), "+f"(d[55]), "+f"(d[56]), "+f"(d[57]), "+f"(d[58]), "+f"(d[59]), "+f"(d[60]), "+f"(d[61]), "+f"(d[62]), "+f"(d[63])
        : "r"(da), "r"(db), "r"(acc), "n"(TB), "r"(ha), "r"(hb));
}
template <int TB>
__device__ __forceinline__ void wgmma_ss128_init(float (&d)[64], uint32_t da, uint32_t db, uint32_t ha = 0x40000040u, uint32_t hb = 0x40000040u) {
    asm volatile("{\n.reg .pred p;\n.reg .b64 a, b;\nsetp.ne.b32 p, 0, 0;\nmov.b64 a, {%64, %67};\nmov.b64 b, {%65, %68};\n"
        "wgmma.mma_async.sync.aligned.m64n128k16.f32.bf16.bf16 {%0, %1, %2, %3, %4, %5, %6, %7, %8, %9, %10, %11, %12, %13, %14, %15, %16, %17, %18, %19, %20, %21, %22, %23, %24, %25, %26, %27, %28, %29, %30, %31, %32, %33, %34, %35, %36, %37, %38, %39, %40, %41, %42, %43, %44, %45, %46, %47, %48, %49, %50, %51, %52, %53, %54, %55, %56, %57, %58, %59, %60, %61, %62, %63}, a, b, p, 1, 1, 0, %66;\n}"
        : "=f"(d[0]), "=f"(d[1]), "=f"(d[2]), "=f"(d[3]), "=f"(d[4]), "=f"(d[5]), "=f"(d[6]), "=f"(d[7]), "=f"(d[8]), "=f"(d[9]), "=f"(d[10]), "=f"(d[11]), "=f"(d[12]), "=f"(d[13]), "=f"(d[14]), "=f"(d[15]), "=f"(d[16]), "=f"(d[17]), "=f"(d[18]), "=f"(d[19]), "=f"(d[20]), "=f"(d[21]), "=f"(d[22]), "=f"(d[23]), "=f"(d[24]), "=f"(d[25]), "=f"(d[26]), "=f"(d[27]), "=f"(d[28]), "=f"(d[29]), "=f"(d[30]), "=f"(d[31]), "=f"(d[32]), "=f"(d[33]), "=f"(d[34]), "=f"(d[35]), "=f"(d[36]), "=f"(d[37]), "=f"(d[38]), "=f"(d[39]), "=f"(d[40]), "=f"(d[41]), "=f"(d[42]), "=f"(d[43]), "=f"(d[44]), "=f"(d[45]), "=f"(d[46]), "=f"(d[47]), "=f"(d[48]), "=f"(d[49]), "=f"(d[50]), "=f"(d[51]), "=f"(d[52]), "=f"(d[53]), "=f"(d[54]), "=f"(d[55]), "=f"(d[56]), "=f"(d[57]), "=f"(d[58]), "=f"(d[59]), "=f"(d[60]), "=f"(d[61]), "=f"(d[62]), "=f"(d[63])
        : "r"(da), "r"(db), "n"(TB), "r"(ha), "r"(hb));
}
template <int TB>
__device__ __forceinline__ void wgmma_ss64(float (&d)[32], uint32_t da, uint32_t db, int acc, uint32_t ha = 0x40000040u, uint32_t hb = 0x40000040u) {
    asm volatile("{\n.reg .pred p;\n.reg .b64 a, b;\nsetp.ne.b32 p, %34, 0;\nmov.b64 a, {%32, %36};\nmov.b64 b, {%33, %37};\n"
        "wgmma.mma_async.sync.aligned.m64n64k16.f32.bf16.bf16 {%0, %1, %2, %3, %4, %5, %6, %7, %8, %9, %10, %11, %12, %13, %14, %15, %16, %17, %18, %19, %20, %21, %22, %23, %24, %25, %26, %27, %28, %29, %30, %31}, a, b, p, 1, 1, 0, %35;\n}"
        : "+f"(d[0]), "+f"(d[1]), "+f"(d[2]), "+f"(d[3]), "+f"(d[4]), "+f"(d[5]), "+f"(d[6]), "+f"(d[7]), "+f"(d[8]), "+f"(d[9]), "+f"(d[10]), "+f"(d[11]), "+f"(d[12]), "+f"(d[13]), "+f"(d[14]), "+f"(d[15]), "+f"(d[16]), "+f"(d[17]), "+f"(d[18]), "+f"(d[19]), "+f"(d[20]), "+f"(d[21]), "+f"(d[22]), "+f"(d[23]), "+f"(d[24]), "+f"(d[25]), "+f"(d[26]), "+f"(d[27]), "+f"(d[28]), "+f"(d[29]), "+f"(d[30]), "+f"(d[31])
        : "r"(da), "r"(db), "r"(acc), "n"(TB), "r"(ha), "r"(hb));
}
template <int TB>
__device__ __forceinline__ void wgmma_ss64_init(float (&d)[32], uint32_t da, uint32_t db, uint32_t ha = 0x40000040u, uint32_t hb = 0x40000040u) {
    asm volatile("{\n.reg .pred p;\n.reg .b64 a, b;\nsetp.ne.b32 p, 0, 0;\nmov.b64 a, {%32, %35};\nmov.b64 b, {%33, %36};\n"
        "wgmma.mma_async.sync.aligned.m64n64k16.f32.bf16.bf16 {%0, %1, %2, %3, %4, %5, %6, %7, %8, %9, %10, %11, %12, %13, %14, %15, %16, %17, %18, %19, %20, %21, %22, %23, %24, %25, %26, %27, %28, %29, %30, %31}, a, b, p, 1, 1, 0, %34;\n}"
        : "=f"(d[0]), "=f"(d[1]), "=f"(d[2]), "=f"(d[3]), "=f"(d[4]), "=f"(d[5]), "=f"(d[6]), "=f"(d[7]), "=f"(d[8]), "=f"(d[9]), "=f"(d[10]), "=f"(d[11]), "=f"(d[12]), "=f"(d[13]), "=f"(d[14]), "=f"(d[15]), "=f"(d[16]), "=f"(d[17]), "=f"(d[18]), "=f"(d[19]), "=f"(d[20]), "=f"(d[21]), "=f"(d[22]), "=f"(d[23]), "=f"(d[24]), "=f"(d[25]), "=f"(d[26]), "=f"(d[27]), "=f"(d[28]), "=f"(d[29]), "=f"(d[30]), "=f"(d[31])
        : "r"(da), "r"(db), "n"(TB), "r"(ha), "r"(hb));
}
__device__ __forceinline__ void wgmma_rs128(float (&d)[64], uint32_t a0, uint32_t a1, uint32_t a2, uint32_t a3, uint32_t db, int acc, uint32_t hb = 0x40000040u) {
    asm volatile("{\n.reg .pred p;\n.reg .b64 b;\nsetp.ne.b32 p, %69, 0;\nmov.b64 b, {%68, %70};\n"
        "wgmma.mma_async.sync.aligned.m64n128k16.f32.bf16.bf16 {%0, %1, %2, %3, %4, %5, %6, %7, %8, %9, %10, %11, %12, %13, %14, %15, %16, %17, %18, %19, %20, %21, %22, %23, %24, %25, %26, %27, %28, %29, %30, %31, %32, %33, %34, %35, %36, %37, %38, %39, %40, %41, %42, %43, %44, %45, %46, %47, %48, %49, %50, %51, %52, %53, %54, %55, %56, %57, %58, %59, %60, %61, %62, %63}, {%64, %65, %66, %67}, b, p, 1, 1, 1;\n}"
        : "+f"(d[0]), "+f"(d[1]), "+f"(d[2]), "+f"(d[3]), "+f"(d[4]), "+f"(d[5]), "+f"(d[6]), "+f"(d[7]), "+f"(d[8]), "+f"(d[9]), "+f"(d[10]), "+f"(d[11]), "+f"(d[12]), "+f"(d[13]), "+f"(d[14]), "+f"(d[15]), "+f"(d[16]), "+f"(d[17]), "+f"(d[18]), "+f"(d[19]), "+f"(d[20]), "+f"(d[21]), "+f"(d[22]), "+f"(d[23]), "+f"(d[24]), "+f"(d[25]), "+f"(d[26]), "+f"(d[27]), "+f"(d[28]), "+f"(d[29]), "+f"(d[30]), "+f"(d[31]), "+f"(d[32]), "+f"(d[33]), "+f"(d[34]), "+f"(d[35]), "+f"(d[36]), "+f"(d[37]), "+f"(d[38]), "+f"(d[39]), "+f"(d[40]), "+f"(d[41]), "+f"(d[42]), "+f"(d[43]), "+f"(d[44]), "+f"(d[45]), "+f"(d[46]), "+f"(d[47]), "+f"(d[48]), "+f"(d[49]), "+f"(d[50]), "+f"(d[51]), "+f"(d[52]), "+f"(d[53]), "+f"(d[54]), "+f"(d[55]), "+f"(d[56]), "+f"(d[57]), "+f"(d[58]), "+f"(d[59]), "+f"(d[60]), "+f"(d[61]), "+f"(d[62]), "+f"(d[63])
        : "r"(a0), "r"(a1), "r"(a2), "r"(a3), "r"(db), "r"(acc), "r"(hb));
}

__device__ __forceinline__ uint32_t pack2(float lo, float hi) {
    uint32_t r;
    asm("cvt.rn.bf16x2.f32 %0, %1, %2;" : "=r"(r) : "f"(hi), "f"(lo));
    return r;
}
__device__ __forceinline__ float bf_lo(uint32_t v) { return __uint_as_float(v << 16); }
__device__ __forceinline__ float bf_hi(uint32_t v) { return __uint_as_float(v & 0xffff0000u); }
__device__ __forceinline__ float rbf(float v) { return bf_lo(pack2(v, v)); }
__device__ __forceinline__ uint32_t badd(uint32_t a, uint32_t b) {
    uint32_t r;
    asm("add.rn.bf16x2 %0, %1, %2;" : "=r"(r) : "r"(a), "r"(b));
    return r;
}
__device__ __forceinline__ uint32_t bsub(uint32_t a, uint32_t b) {
    uint32_t r;
    asm("sub.rn.bf16x2 %0, %1, %2;" : "=r"(r) : "r"(a), "r"(b));
    return r;
}
__device__ __forceinline__ uint32_t bmul(uint32_t a, uint32_t b) {
    uint32_t r;
    asm("mul.rn.bf16x2 %0, %1, %2;" : "=r"(r) : "r"(a), "r"(b));
    return r;
}
__device__ __forceinline__ uint32_t ln_apply(uint32_t x, uint32_t mb, float rs, uint32_t scale, uint32_t shift) {
    const uint32_t d = bsub(x, mb);
    return badd(bmul(pack2(bf_lo(d) * rs, bf_hi(d) * rs), scale), shift);
}
__device__ __forceinline__ float ex2(float v) {
    float r;
    asm("ex2.approx.ftz.f32 %0, %1;" : "=f"(r) : "f"(v));
    return r;
}
__device__ __forceinline__ float rcp(float v) {
    float r;
    asm("rcp.approx.ftz.f32 %0, %1;" : "=f"(r) : "f"(v));
    return r;
}
__device__ __forceinline__ float sqrt_fast(float v) {
    float r;
    asm("sqrt.approx.ftz.f32 %0, %1;" : "=f"(r) : "f"(v));
    return r;
}
__device__ __forceinline__ float ln_rstd(float var) { return rcp(rbf(sqrt_fast(rbf(rbf(var) + 1e-5f)))); }
__device__ __forceinline__ float sigmoid(float v) { return rcp(1.f + ex2(-1.4426950408889634f * v)); }
__device__ __forceinline__ float warp_sum(float v) {
#pragma unroll
    for (int o = 16; o > 0; o >>= 1) v += __shfl_xor_sync(0xffffffffu, v, o);
    return v;
}
__device__ __forceinline__ float quad_sum(float v) {
    v += __shfl_xor_sync(0xffffffffu, v, 1);
    return v + __shfl_xor_sync(0xffffffffu, v, 2);
}

constexpr uint32_t HI_128 = 0x40000040u, HI_IMG = 0x80000080u, HI_Q = 0x80000040u;
template <int M, int RH>
__device__ __forceinline__ uint4 img_pack(const float (&d)[64], float s) {
    uint4 v;
    v.x = pack2(d[16 * M + 2 * RH] * s, d[16 * M + 2 * RH + 1] * s);
    v.y = pack2(d[16 * M + 4 + 2 * RH] * s, d[16 * M + 5 + 2 * RH] * s);
    v.z = pack2(d[16 * M + 8 + 2 * RH] * s, d[16 * M + 9 + 2 * RH] * s);
    v.w = pack2(d[16 * M + 12 + 2 * RH] * s, d[16 * M + 13 + 2 * RH] * s);
    return v;
}
template <int M, int RH>
__device__ __forceinline__ uint4 img_pack(const float (&d)[64]) {
    uint4 v;
    v.x = pack2(d[16 * M + 2 * RH], d[16 * M + 2 * RH + 1]);
    v.y = pack2(d[16 * M + 4 + 2 * RH], d[16 * M + 5 + 2 * RH]);
    v.z = pack2(d[16 * M + 8 + 2 * RH], d[16 * M + 9 + 2 * RH]);
    v.w = pack2(d[16 * M + 12 + 2 * RH], d[16 * M + 13 + 2 * RH]);
    return v;
}
template <int M>
__device__ __forceinline__ void img_store_global(uint8_t* img, uint32_t toff, const float (&d)[64], float s0, float s1) {
    uint4* p = reinterpret_cast<uint4*>(img + toff) + M * 32;
    p[0] = img_pack<M, 0>(d, s0);
    p[128] = img_pack<M, 1>(d, s1);
}
__device__ __forceinline__ void sts128(uint32_t a, uint4 v) {
    asm volatile("st.shared.v4.b32 [%0], {%1, %2, %3, %4};" ::"r"(a), "r"(v.x), "r"(v.y), "r"(v.z), "r"(v.w) : "memory");
}
constexpr float SM_C = 0.08838834764831845f * 1.4426950408889634f;
__device__ __forceinline__ float pack2f(float lo, float hi) {
    float r;
    asm("{\n.reg .b32 t;\ncvt.rn.bf16x2.f32 t, %1, %2;\nmov.b32 %0, t;\n}" : "=f"(r) : "f"(hi), "f"(lo));
    return r;
}
template <int M, bool SCALE, bool PARK>
__device__ __forceinline__ void pack_group(float (&d)[64], float (&v)[8], float s0, float s1) {
#pragma unroll
    for (int i = 0; i < 8; i++) {
        const int k = 16 * M + 4 * (i & 3) + 2 * (i >> 2);
        v[i] = SCALE ? pack2f(d[k] * (i < 4 ? s0 : s1), d[k + 1] * (i < 4 ? s0 : s1)) : pack2f(d[k], d[k + 1]);
        if (PARK && M > 0) d[16 * (M > 0 ? M - 1 : 0) + i] = v[i];
    }
}
__device__ __forceinline__ uint32_t q_off(uint32_t toff) { return (((toff >> 1) & ~2047u) ^ 8192) + (toff & 511); }
template <int M, bool PARK>
__device__ __forceinline__ void ctx_store_part(float4* p, float (&d)[64], float i0, float i1) {
    float v[8];
    pack_group<M, true, PARK>(d, v, i0, i1);
    p[M * 32] = make_float4(v[0], v[1], v[2], v[3]);
    p[M * 32 + 128] = make_float4(v[4], v[5], v[6], v[7]);
}
template <bool PARK>
__device__ __forceinline__ void ctx_store(uint8_t* img, uint32_t toff, float (&o)[64], float l0, float l1) {
    const float i0 = rcp(quad_sum(l0)), i1 = rcp(quad_sum(l1));
    float4* p = reinterpret_cast<float4*>(img + toff);
    ctx_store_part<0, PARK>(p, o, i0, i1); ctx_store_part<1, PARK>(p, o, i0, i1); ctx_store_part<2, PARK>(p, o, i0, i1); ctx_store_part<3, PARK>(p, o, i0, i1);
}

template <int M>
__device__ __forceinline__ void tile_store_part(float4* p, uint32_t a, float (&d)[64], float i0, float i1, int ctx) {
    float v[8];
    pack_group<M, true, true>(d, v, i0, i1);
#pragma unroll
    for (int h = 0; h < 2; h++)
        asm volatile("{\n.reg .pred p;\nsetp.ne.s32 p, %6, 0;\n@p st.global.v4.f32 [%0], {%2, %3, %4, %5};\n@!p st.shared.v4.f32 [%1], {%2, %3, %4, %5};\n}"
                     ::"l"(p + M * 32 + h * 128), "r"(a + (M >> 1) * 16384 + (M & 1) * 512 + h * 1024),
                     "f"(v[4 * h]), "f"(v[4 * h + 1]), "f"(v[4 * h + 2]), "f"(v[4 * h + 3]), "r"(ctx) : "memory");
}
__device__ __forceinline__ void tile_store(uint8_t* img, uint32_t a, uint32_t toff, float (&d)[64], float i0, float i1, int ctx) {
    float4* p = reinterpret_cast<float4*>(img + toff);
    a += q_off(toff);
    tile_store_part<0>(p, a, d, i0, i1, ctx); tile_store_part<1>(p, a, d, i0, i1, ctx);
    tile_store_part<2>(p, a, d, i0, i1, ctx); tile_store_part<3>(p, a, d, i0, i1, ctx);
}

__device__ __forceinline__ void slot_wait(uint32_t bars, uint32_t& ph, uint32_t slot) {
    mbar_wait(bars + 8 * slot, (ph >> slot) & 1);
    ph ^= 1u << slot;
}
__device__ __forceinline__ void release_if(uint32_t eb, uint32_t slot, bool on) {
    asm volatile("{\n.reg .pred p;\nsetp.ne.s32 p, %1, 0;\n@p mbarrier.arrive.shared::cluster.b64 _, [%0];\n}" ::"r"(eb + 8 * slot), "r"((int)on) : "memory");
}
__device__ __forceinline__ void load_image_mc(uint32_t sb, uint32_t& ph, uint32_t slot, const uint8_t* src, int rank, bool first) {
    slot_wait(sb + BAR_EMPTY, ph, slot);
    asm volatile("{\n.reg .pred p;\nelect.sync _|p, 0xffffffff;\n@p mbarrier.arrive.expect_tx.shared::cta.b64 _, [%2], 32768;\n"
                 "@p cp.async.bulk.shared::cluster.global.mbarrier::complete_tx::bytes.multicast::cluster.L2::cache_hint [%0], [%1], 16384, [%2], %4, %3;\n}"
                 ::"r"(sb + slot * SLOT + rank * 16384), "l"(src + rank * 16384), "r"(sb + BAR_FULL + 8 * slot), "l"(first ? L2_FIRST : L2_NORMAL),
                 "h"((uint16_t)3) : "memory");
}
__device__ __forceinline__ void load_tile_mc(uint32_t sb, uint32_t& ph, uint32_t slot, const CUtensorMap* m, int row, int cb, int rank, bool first) {
    slot_wait(sb + BAR_EMPTY, ph, slot);
    asm volatile("{\n.reg .pred p;\nelect.sync _|p, 0xffffffff;\n@p mbarrier.arrive.expect_tx.shared::cta.b64 _, [%2], 32768;\n"
                 "@p cp.async.bulk.tensor.3d.shared::cluster.global.mbarrier::complete_tx::bytes.multicast::cluster.L2::cache_hint [%0], [%1, {%3, %4, %5}], [%2], %7, %6;\n}"
                 ::"r"(sb + slot * SLOT + rank * 16384), "l"(m), "r"(sb + BAR_FULL + 8 * slot), "r"(0), "r"(row), "r"(cb + rank),
                 "l"(first ? L2_FIRST : L2_NORMAL), "h"((uint16_t)3) : "memory");
}
__device__ __forceinline__ void load_image(uint32_t sb, uint32_t& ph, uint32_t slot, const void* src, bool first) {
    slot_wait(sb + BAR_EMPTY, ph, slot);
    asm volatile("{\n.reg .pred p;\nelect.sync _|p, 0xffffffff;\n@p mbarrier.arrive.expect_tx.shared::cta.b64 _, [%2], 32768;\n"
                 "@p cp.async.bulk.shared::cluster.global.mbarrier::complete_tx::bytes.L2::cache_hint [%0], [%1], 32768, [%2], %3;\n}"
                 ::"r"(sb + slot * SLOT), "l"(src), "r"(sb + BAR_FULL + 8 * slot), "l"(first ? L2_FIRST : L2_NORMAL) : "memory");
}
__device__ __forceinline__ void load_tile(uint32_t sb, uint32_t& ph, uint32_t slot, const CUtensorMap* m, int row, int cb, bool first) {
    slot_wait(sb + BAR_EMPTY, ph, slot);
    asm volatile("{\n.reg .pred p;\nelect.sync _|p, 0xffffffff;\n@p mbarrier.arrive.expect_tx.shared::cta.b64 _, [%2], 32768;\n"
                 "@p cp.async.bulk.tensor.3d.shared::cluster.global.mbarrier::complete_tx::bytes.L2::cache_hint [%0], [%1, {%3, %4, %5}], [%2], %6;\n}"
                 ::"r"(sb + slot * SLOT), "l"(m), "r"(sb + BAR_FULL + 8 * slot), "r"(0), "r"(row), "r"(cb), "l"(first ? L2_FIRST : L2_NORMAL) : "memory");
}
__device__ __forceinline__ uint32_t ring_next(uint32_t r) { return r == 4 ? 0 : r + 1; }
__device__ __forceinline__ uint32_t w_table(int hp) { return hp ? 0x3104u : 0x4210u; }
__device__ __forceinline__ uint32_t a_table(int hp) { return hp ? 0x625u : 0x635u; }
__device__ __forceinline__ uint32_t a_next(uint32_t& t) {
    const uint32_t s = t & 15;
    t = (t >> 4) | (s << 8);
    return s;
}
constexpr uint32_t O_TABLE = 0x1604235u;
__device__ __forceinline__ uint32_t o_next(uint32_t& t) {
    const uint32_t s = t & 15;
    t = (t >> 4) | (s << 24);
    return s;
}
__device__ __forceinline__ int o_head(int i, int kh) { return i < 16 ? 4 * (i & 7) + 2 * (kh ^ 1) + (i >> 3) : 29 + 2 * kh; }

template <bool INIT>
__device__ __forceinline__ void gemm_issue(float (&d)[64], uint32_t a, uint32_t b, int acc, bool img) {
    const uint32_t ha = img ? HI_IMG : HI_128, o2 = img ? 32 : 4, o4 = img ? 64 : 1024;
    wg_fence();
#pragma unroll
    for (int k = 0; k < 8; k++) {
        if (INIT && k == 0) wgmma_ss128_init<1>(d, a, b, ha);
        else wgmma_ss128<1>(d, a + (k >> 2) * o4 + ((k >> 1) & 1) * o2 + (k & 1) * 2, b + k * 128, k ? 1 : acc, ha);
    }
    wg_commit();
}

__device__ __forceinline__ void h_store(const uint32_t* x, float piv, float sum, float sq, uint32_t sb, int row) {
    const int lane = threadIdx.x & 31;
    const float d = sum * (1.f / 512.f), rs = ln_rstd(fmaxf(fmaf(-d, d, sq * (1.f / 512.f)), 0.f));
    const uint32_t mb = pack2(piv + d, piv + d);
    uint8_t* p = g_h + ((row >> 7) * 8 + (lane >> 3)) * 16384 + (row & 127) * 128 + (((lane ^ row) & 7) << 4);
#pragma unroll
    for (int i = 0; i < 2; i++) {
        const uint4 a = lds128(sb + SM_TAB + 1024 + i * 512 + lane * 16), c = lds128(sb + SM_TAB + i * 512 + lane * 16);
        *reinterpret_cast<uint4*>(p + i * 65536) = make_uint4(ln_apply(x[4 * i], mb, rs, a.x, c.x), ln_apply(x[4 * i + 1], mb, rs, a.y, c.y),
                                                              ln_apply(x[4 * i + 2], mb, rs, a.z, c.z), ln_apply(x[4 * i + 3], mb, rs, a.w, c.w));
    }
}

template <bool ODD>
__device__ __forceinline__ bool proj_tile(float (&acc)[64], float (&prev)[64], int t, int q0, uint32_t sb, int wg, uint32_t eb, bool rel, uint32_t& fph,
                                          uint32_t wtab, uint32_t& atab, uint8_t* prev_img, uint32_t toff, float s0, float s1, bool first,
                                          const bf16* x, int xrow) {
    const uint32_t a0 = desc_k(sb + (wg ^ (ODD && t == 5)) * 8192), b0 = desc_mn(sb);
    const int lane = threadIdx.x & 31;
    float st[4] = {0.f, 0.f, 0.f, 0.f}, piv[2] = {0.f, 0.f};
    uint4 v[8] = {};
    uint32_t xn[16];
#pragma unroll
    for (int i = 0; i < 4; i++) {
        uint4 u = make_uint4(0, 0, 0, 0);
        if (ODD && first) u = __ldg(reinterpret_cast<const uint4*>(x) + xrow * 64 + lane + 32 * i);
        xn[4 * i] = u.x; xn[4 * i + 1] = u.y; xn[4 * i + 2] = u.z; xn[4 * i + 3] = u.w;
    }
    uint32_t x0[2] = {0, 0};
    if (ODD && first) {
        x0[0] = __ldg(reinterpret_cast<const uint32_t*>(x) + xrow * 256);
        x0[1] = __ldg(reinterpret_cast<const uint32_t*>(x) + xrow * 256 + 256);
    }
    constexpr int U = ODD ? UNR : 1;
#pragma unroll U
    for (int q = ODD ? 0 : q0; q < 4; q++) {
        const uint32_t ws = (wtab >> (4 * q)) & 15, as = a_next(atab);
        if (!ODD && t != 2) slot_wait(sb + BAR_FULL, fph, ws);
        slot_wait(sb + BAR_FULL, fph, as);
        if (ODD && q == 2 && t == 5) {
#pragma unroll
            for (int i = 0; i < 8; i++) sts128(sb + 5 * SLOT + q_off(toff) + (i >> 2) * 16384 + (i & 2) * 256 + (i & 1) * 1024, v[i]);
        }
        bar_sync(1 + wg, 256);
        gemm_issue<false>(acc, a0 + as * (SLOT / 16), b0 + ws * (SLOT / 16), q, false);
        bar_arrive(2 - wg, 256);
        wg_wait<1>();
        reg_fence(prev);
        if (ODD && t == 5) {
            if (q == 0) {
                v[0] = img_pack<0, 0>(prev); v[1] = img_pack<0, 1>(prev); v[2] = img_pack<1, 0>(prev); v[3] = img_pack<1, 1>(prev);
                v[4] = img_pack<2, 0>(prev); v[5] = img_pack<2, 1>(prev); v[6] = img_pack<3, 0>(prev); v[7] = img_pack<3, 1>(prev);
            }
            if (q == 2) {
                CDEF;
                CT(0);
                fence_async_smem();
                CT(1);
                slot_wait(sb + BAR_FULL, fph, wtab & 15);
                CT(2);
                COUT(xrow >> 4, 0);
                wg_wait<0>();
                release_if(eb, as, rel);
                release_if(eb, ws, rel);
                reg_fence(acc);
                return true;
            }
        } else if (ODD || !first) {
            if (q == 0) img_store_global<0>(prev_img, toff, prev, s0, s1);
            if (q == 1) img_store_global<1>(prev_img, toff, prev, s0, s1);
            if (q == 2) img_store_global<2>(prev_img, toff, prev, s0, s1);
            if (q == 3) img_store_global<3>(prev_img, toff, prev, s0, s1);
        }
        if (ODD && q == 1 && first) {
            piv[0] = bf_lo(x0[0]);
            piv[1] = bf_lo(x0[1]);
#pragma unroll
            for (int k = 0; k < 16; k++) {
                const float d0 = bf_lo(xn[k]) - piv[k >> 3], d1 = bf_hi(xn[k]) - piv[k >> 3];
                st[k >> 3] += d0 + d1;
                st[2 + (k >> 3)] = fmaf(d0, d0, fmaf(d1, d1, st[2 + (k >> 3)]));
            }
        }
        if (ODD && q == 2 && first) {
#pragma unroll
            for (int i = 0; i < 12; i++) st[i & 3] += __shfl_xor_sync(0xffffffffu, st[i & 3], 4 << (i >> 2));
        }
        if (ODD && q == 3 && first) h_store(xn + 8, piv[1], st[1], st[3], sb, xrow + 1);
        wg_wait<0>();
        release_if(eb, as, rel && !(ODD && (q & 1) && t == 5));
        if (ODD) release_if(eb, ws, rel && t != 1);
        if (ODD && q == 1 && first) {
#pragma unroll
            for (int i = 0; i < 4; i++) st[i] = quad_sum(st[i]);
        }
        if (ODD && q == 2 && first) {
            mbar_wait(sb + BAR_FLAG + 8 * 8, 0);
            h_store(xn, piv[0], st[0], st[2], sb, xrow);
        }
        if (ODD && q == 3 && first) {
            __syncwarp();
            mbar_arrive_if(sb + BAR_DONE, lane == 0);
        }
    }
    reg_fence(acc);
    return false;
}

__device__ __forceinline__ void qk_issue(float (&s)[64], uint32_t q, uint32_t k) {
    wg_fence();
    wgmma_ss128_init<0>(s, q, k, HI_Q, HI_IMG);
#pragma unroll
    for (int i = 1; i < 8; i++) wgmma_ss128<0>(s, q + (i >> 2) * 1024 + (i & 2) * 16 + (i & 1) * 2, k + (i >> 1) * 32 + (i & 1) * 2, 1, HI_Q, HI_IMG);
    wg_commit();
}
__device__ __forceinline__ void qk_issue(float (&s)[32], uint32_t q, uint32_t k) {
    wg_fence();
    wgmma_ss64_init<0>(s, q, k, HI_Q, HI_IMG);
#pragma unroll
    for (int i = 1; i < 8; i++) wgmma_ss64<0>(s, q + (i >> 2) * 1024 + (i & 2) * 16 + (i & 1) * 2, k + (i >> 1) * 32 + (i & 1) * 2, 1, HI_Q, HI_IMG);
    wg_commit();
}
__device__ __forceinline__ void pv_issue(float (&o)[64], const uint32_t (&p)[32], uint32_t v, int acc, bool half) {
    if (half) {
        asm volatile("// half" ::: "memory");
        wg_fence();
#pragma unroll
        for (int i = 0; i < 4; i++) wgmma_rs128(o, p[4 * i], p[4 * i + 1], p[4 * i + 2], p[4 * i + 3], v + i * 256, i ? 1 : acc, HI_IMG);
        wg_commit();
        asm volatile("// half" ::: "memory");
    } else {
        wg_fence();
#pragma unroll
        for (int i = 0; i < 8; i++) wgmma_rs128(o, p[4 * i], p[4 * i + 1], p[4 * i + 2], p[4 * i + 3], v + i * 256, i ? 1 : acc, HI_IMG);
        wg_commit();
    }
}
__device__ __forceinline__ void tri_mask(float (&s)[64], float x) {
#pragma unroll
    for (int k = 0; k < 16; k++) {
        float b;
        asm("sub.sat.f32 %0, %1, %2;" : "=f"(b) : "f"((float)(8 * (k >> 1) + (k & 1))), "f"(x));
        const int i = 32 + 4 * (k >> 1) + (k & 1);
        asm("fma.rn.f32 %0, %1, 0fFF61B1E6, %0;" : "+f"(s[i]) : "f"(b));
        if (k < 14) asm("fma.rn.f32 %0, %1, 0fFF61B1E6, %0;" : "+f"(s[i + 6]) : "f"(b));
    }
}
__device__ __forceinline__ void tri_mask_copy(float (&s)[64], const float (&h)[32], float x) {
#pragma unroll
    for (int i = 0; i < 32; i++) {
        asm("{\n.reg .pred p;\nsetp.lt.f32 p, %2, %3;\nselp.f32 %0, 0fFF800000, %1, p;\n}"
            : "=f"(s[i]) : "f"(h[i]), "f"(x), "f"((float)(8 * (i >> 2) - 4 * (i & 2) + (i & 1))));
        s[32 + i] = __uint_as_float(0xff800000u);
    }
}
constexpr float SM_HI = 1152921504606846976.f, SM_LO = 1.f / 1152921504606846976.f;
__device__ __forceinline__ bool softmax_unsafe(float t0, float t1, bool first) {
    bool bad = __any_sync(0xffffffffu, fmaxf(t0, t1) > SM_HI);
    if (first) {
        uint32_t a = __ballot_sync(0xffffffffu, t0 >= SM_LO), b = __ballot_sync(0xffffffffu, t1 >= SM_LO);
        a |= a >> 1;
        b |= b >> 1;
        bad |= ((a | (a >> 2)) & (b | (b >> 2)) & 0x11111111u) != 0x11111111u;
    }
    return bad;
}
__device__ __forceinline__ void softmax_shift(float (&s)[64], float d0, float d1) {
#pragma unroll
    for (int i = 0; i < 64; i++) s[i] -= (i & 2) ? d1 : d0;
}
__device__ __forceinline__ void softmax_remax(float (&s)[64], float (&m)[2], bool first, float& a0, float& a1) {
    float m0 = fmaxf(s[0], s[1]), m1 = fmaxf(s[2], s[3]);
#pragma unroll
    for (int k = 1; k < 16; k++) {
        m0 = fmaxf(m0, fmaxf(s[4 * k], s[4 * k + 1]));
        m1 = fmaxf(m1, fmaxf(s[4 * k + 2], s[4 * k + 3]));
    }
    m0 = fmaxf(m0, __shfl_xor_sync(0xffffffffu, m0, 1));
    m1 = fmaxf(m1, __shfl_xor_sync(0xffffffffu, m1, 1));
    m0 = fmaxf(m0, __shfl_xor_sync(0xffffffffu, m0, 2));
    m1 = fmaxf(m1, __shfl_xor_sync(0xffffffffu, m1, 2));
    if (!first) {
        m0 = fmaxf(m0, 0.f);
        m1 = fmaxf(m1, 0.f);
    }
    a0 = first ? 1.f : ex2(-m0);
    a1 = first ? 1.f : ex2(-m1);
    m[0] += m0;
    m[1] += m1;
    softmax_shift(s, m0, m1);
}
template <int J0, int J1>
__device__ __forceinline__ void softmax_exp(const float (&s)[64], uint32_t (&p)[32], float (&t)[4]) {
#pragma unroll
    for (int k = J0; k < J1; k++) {
        const float e0 = ex2(s[4 * k]), e1 = ex2(s[4 * k + 1]), e2 = ex2(s[4 * k + 2]), e3 = ex2(s[4 * k + 3]);
        if (k == 0) { t[0] = e0; t[1] = e1; t[2] = e2; t[3] = e3; }
        else { t[0] += e0; t[1] += e1; t[2] += e2; t[3] += e3; }
        p[2 * k] = pack2(e0, e1);
        p[2 * k + 1] = pack2(e2, e3);
    }
}
__device__ __forceinline__ void fma8(float (&acc)[8], float a, uint4 w) {
    acc[0] = fmaf(a, bf_lo(w.x), acc[0]); acc[1] = fmaf(a, bf_hi(w.x), acc[1]);
    acc[2] = fmaf(a, bf_lo(w.y), acc[2]); acc[3] = fmaf(a, bf_hi(w.y), acc[3]);
    acc[4] = fmaf(a, bf_lo(w.z), acc[4]); acc[5] = fmaf(a, bf_hi(w.z), acc[5]);
    acc[6] = fmaf(a, bf_lo(w.w), acc[6]); acc[7] = fmaf(a, bf_hi(w.w), acc[7]);
}
__device__ __forceinline__ void mma16816(float (&d)[4], const uint32_t* a, uint32_t b0, uint32_t b1) {
    asm("mma.sync.aligned.m16n8k16.row.col.f32.bf16.bf16.f32 {%0, %1, %2, %3}, {%4, %5, %6, %7}, {%8, %9}, {%0, %1, %2, %3};"
        : "+f"(d[0]), "+f"(d[1]), "+f"(d[2]), "+f"(d[3]) : "r"(a[0]), "r"(a[1]), "r"(a[2]), "r"(a[3]), "r"(b0), "r"(b1));
}
__device__ __forceinline__ uint32_t best_key(const uint32_t* keys, int lane, uint32_t ep) {
    uint32_t best;
#pragma unroll 1
    for (;;) {
        const uint4 k = ld_poll(reinterpret_cast<const uint4*>(keys) + lane);
        best = max(max(k.x, k.y), max(k.z, k.w));
        if (__all_sync(0xffffffffu, (((k.x ^ ep) | (k.y ^ ep) | (k.z ^ ep) | (k.w ^ ep)) & 31) == 0)) break;
    }
    return __reduce_max_sync(0xffffffffu, best);
}

__global__ void __cluster_dims__(2, 1, 1) __launch_bounds__(384, 1)
fused_kernel(const __grid_constant__ CUtensorMap tm_ckv, const __grid_constant__ CUtensorMap tm_wq,
             const __grid_constant__ CUtensorMap tm_wuk, const __grid_constant__ CUtensorMap tm_wuv,
             const __grid_constant__ CUtensorMap tm_wo, const __grid_constant__ CUtensorMap tm_wg,
             const __grid_constant__ CUtensorMap tm_wu,
             const __grid_constant__ CUtensorMap tm_wm, const __grid_constant__ CUtensorMap tm_x, const Params P) {
    extern __shared__ __align__(1024) uint8_t smem[];
    const uint32_t sb = (uint32_t)__cvta_generic_to_shared(smem);
    const int tid = threadIdx.x, lane = tid & 31, warp = __shfl_sync(0xffffffffu, tid >> 5, 0), wg = warp >> 2;
    uint32_t sm;
    asm("mov.u32 %0, %%smid;" : "=r"(sm));
    if (MC) sm = blockIdx.x < 8 ? blockIdx.x + 124 : blockIdx.x - 8;
    const uint32_t smq = ((sm - 64) * 147) >> 11;
    const int rb = !P.by_smid ? blockIdx.x : sm < 64 ? (sm & 14) * 8 + (sm >> 4) * 2 + (sm & 1)
                 : sm < 120 ? ((sm - 64 - smq * 14) & 14) * 8 + 24 + smq * 2 + (sm & 1) : sm < 124 ? sm + 8 : sm - 116;
    const int grp = rb >> 3, j = rb & 7, cq = j & 3, kh = grp & 1, ort = (grp & 14) + (j >> 2);
    if (warp == 0) TS(0);

    if (rb >= NCTA) {
        float* sc = reinterpret_cast<float*>(smem + 6 * SLOT);
        float* red = sc + 512;
        if (tid == 256) {
            for (int i = 0; i < 6; i++) { mbar_init(sb + BAR_FULL + 8 * i, 1); mbar_init(sb + BAR_EMPTY + 8 * i, 8); }
            fence_async_smem();
        }
        __syncthreads();
        uint32_t ph = 0, sl = 0;
        if (tid == 256) {
#pragma unroll 1
            for (int i = 0; i < 24; i++) {
                mbar_wait(sb + BAR_EMPTY + 8 * sl, ph ^ 1);
                mbar_expect(sb + BAR_FULL + 8 * sl, SLOT);
                tma2d(sb + sl * SLOT, &tm_wm, (i >> 3) * 1024 + (rb - NCTA) * 256, (i & 7) * 64, sb + BAR_FULL + 8 * sl);
                if (++sl == 6) { sl = 0; ph ^= 1; }
            }
            mbar_wait(sb + BAR_EMPTY, 1);
            mbar_wait(sb + BAR_EMPTY + 8, 1);
#pragma unroll 1
            for (int i = 0; i <= NFFN / NSPARE; i++) {
                const int b = (rb - NCTA) * (NFFN / NSPARE) + i;
                if (i < NFFN / NSPARE) {
                    const uint32_t f = sb + BAR_FULL + 8 * (i & 1), d = sb + (i & 1) * SLOT;
                    asm volatile("cp.async.bulk.wait_group.read 0;" ::: "memory");
                    mbar_expect(f, SLOT);
                    tma2d(d, &tm_wg, b * 16, 0, f);
                    tma2d(d + 8192, &tm_wg, b * 16, 256, f);
                    tma2d(d + 16384, &tm_wu, b * 16, 0, f);
                    tma2d(d + 24576, &tm_wu, b * 16, 256, f);
                }
                if (i) {
                    mbar_wait(sb + BAR_FULL + 8 * (~i & 1), ((i - 1) >> 1) & 1);
                    asm volatile("cp.async.bulk.global.shared::cta.bulk_group [%0], [%1], 32768;\ncp.async.bulk.commit_group;"
                                 ::"l"(g_wf + (b - 1) * SLOT), "r"(sb + (~i & 1) * SLOT) : "memory");
                }
            }
            asm volatile("cp.async.bulk.wait_group 0;" ::: "memory");
            fence_async_global();
            flag_add(&g_sync.modcnt[32]);
            TS(4);
        } else if (tid < 256) {
            const uint32_t c2 = __ldg(reinterpret_cast<const uint32_t*>(P.c) + tid);
            sc[2 * tid] = rbf(bf_lo(c2) * sigmoid(bf_lo(c2)));
            sc[2 * tid + 1] = rbf(bf_hi(c2) * sigmoid(bf_hi(c2)));
            bar_sync(1, 256);
#pragma unroll 1
            for (int ps = 0; ps < 3; ps++) {
                float acc[8] = {0.f, 0.f, 0.f, 0.f, 0.f, 0.f, 0.f, 0.f};
#pragma unroll 1
                for (int bt = 0; bt < 8; bt++) {
                    mbar_wait(sb + BAR_FULL + 8 * sl, ph);
#pragma unroll
                    for (int i = 0; i < 8; i++)
                        fma8(acc, sc[bt * 64 + warp * 8 + i], *reinterpret_cast<const uint4*>(smem + sl * SLOT + (warp * 8 + i) * 512 + lane * 16));
                    __syncwarp();
                    mbar_arrive_if(sb + BAR_EMPTY + 8 * sl, lane == 0);
                    if (++sl == 6) { sl = 0; ph ^= 1; }
                }
                *reinterpret_cast<float4*>(red + warp * 256 + lane * 8) = make_float4(acc[0], acc[1], acc[2], acc[3]);
                *reinterpret_cast<float4*>(red + warp * 256 + lane * 8 + 4) = make_float4(acc[4], acc[5], acc[6], acc[7]);
                bar_sync(1, 256);
                float v = 0.f;
#pragma unroll
                for (int i = 0; i < 8; i++) v += red[i * 256 + tid];
                g_mod[ps * 1024 + (rb - NCTA) * 256 + tid] = __float2bfloat16_rn(v);
                bar_sync(1, 256);
                if (tid == 0 && ps != 1) flag_add(&g_sync.modcnt[(ps >> 1) * 32]);
                if (warp == 0) TS(1 + ps);
            }
        }
        return;
    }

    if (tid == 256) {
        if (sb & 1023) __trap();
        asm volatile("prefetch.tensormap [%0];" ::"l"((j & 1) ? &tm_wuv : &tm_wuk) : "memory");
        asm volatile("prefetch.tensormap [%0];" ::"l"(&tm_ckv) : "memory");
        for (int i = 0; i < 7; i++) { mbar_init(sb + BAR_FULL + 8 * i, 1); mbar_init(sb + BAR_EMPTY + 8 * i, MC ? 4 : 2); }
        for (int i = 0; i < 9; i++) mbar_init(sb + BAR_DONE + 8 * i, 8);
        for (int i = 0; i < 10; i++) mbar_init(sb + BAR_FLAG + 8 * i, 1);
        *reinterpret_cast<uint32_t*>(smem + SM_EP + 4) = 0;
        *reinterpret_cast<uint32_t*>(smem + SM_EP + 16) = 0;
        mbar_init(sb + BAR_END, 8);
        fence_async_smem();
        if (MC) asm volatile("fence.mbarrier_init.release.cluster;" ::: "memory");
    }
    __syncthreads();
    if (MC) asm volatile("barrier.cluster.arrive.relaxed.aligned;\nbarrier.cluster.wait.aligned;" ::: "memory");

    if (wg == 2) {
        asm volatile("setmaxnreg.dec.sync.aligned.u32 40;");
        if (warp == 8) {
            uint32_t eph = 0x7f, r = 0;
            const CUtensorMap* tw = (j & 1) ? &tm_wuv : &tm_wuk;
#pragma unroll 1
            for (int hp = 0; hp < 2; hp++) {
                const int hc = 4 * grp + 2 * hp;
                uint32_t wtab = w_table(hp), atab = a_table(hp);
#pragma unroll 1
                for (int u = 0; u < 4; u++) {
                    load_tile(sb, eph, (wtab >> (4 * u)) & 15, tw, u * 128, hc, HINT & 1); PT();
                    if (MC & 1) load_tile_mc(sb, eph, a_next(atab), &tm_ckv, (j >> 1) * 128, u * 2, j & 1, (HINT & 8) && hp);
                    else load_tile(sb, eph, a_next(atab), &tm_ckv, (j >> 1) * 128, u * 2, (HINT & 8) && hp);
                    PT();
                    if (hp == 1 && (u & 1) && lane == 0) asm volatile("red.relaxed.gpu.global.add.u32 [%0], 1;" ::"l"(&g_sync.rdcnt[(grp * 2 + (u >> 1)) * 8]) : "memory");
                }
#pragma unroll 1
                for (int u = 4; u < 16; u++) {
                    if (hp == 1 && (u & 7) == 4) mbar_wait(sb + BAR_FLAG + 24 + (u & 8), 0);
                    if (MC & 1) load_tile_mc(sb, eph, a_next(atab), &tm_ckv, ((u & 12) + (j >> 1)) * 128, (u & 3) * 2, j & 1, (HINT & 8) && hp);
                    else load_tile(sb, eph, a_next(atab), &tm_ckv, ((u & 12) + (j >> 1)) * 128, (u & 3) * 2, (HINT & 8) && hp);
                    PT();
                }
                mbar_wait(sb + BAR_FLAG, 0);
                fence_async_global();
#pragma unroll 1
                for (int u = 0; u < 4; u++) {
                    if (MC & 2) load_tile_mc(sb, eph, (wtab >> (4 * u)) & 15, &tm_wq, u * 128, hc, j & 1, HINT & 1);
                    else load_tile(sb, eph, (wtab >> (4 * u)) & 15, &tm_wq, u * 128, hc, HINT & 1);
                    PT();
                    load_image(sb, eph, a_next(atab), g_h + ((15 - j) * 4 + u) * SLOT, (HINT & 8) && hp); PT();
                }
                mbar_wait(sb + BAR_FLAG + 8 + 32 * hp, 0);
                fence_async_global();
#pragma unroll 1
                for (int u = 0; u < 4; u++) { load_image(sb, eph, a_next(atab), g_h + (j * 4 + u) * SLOT, (HINT & 8) && hp); PT(); }
                const uint8_t* kv = g_KV + (size_t)(grp * 32 + 30 * hp) * SLOT;
                const int step = hp ? -2 * SLOT : 2 * SLOT;
                if (MC & 4) load_image_mc(sb, eph, r, kv, j & 1, HINT & 4);
                else load_image(sb, eph, r, kv, HINT & 4);
                PT();
                r = ring_next(r);
#pragma unroll 1
                for (int n = 1; n <= 16; n++) {
                    if (n == 8) {
                        mbar_wait(sb + BAR_FLAG + 16 + 32 * hp, 0);
                        fence_async_global();
                    }
                    asm volatile("st.volatile.shared.u32 [%0], %1;" ::"r"(sb + SM_EP + 16), "r"(16 * hp + n) : "memory");
                    const uint8_t* v = kv + SLOT;
                    kv += n < 16 - j ? step : n == 16 - j ? (2 * j - 15) * step : -step;
                    if ((MC & 4) && n != 15 - (j & 6)) load_image_mc(sb, eph, r, kv, j & 1, HINT & 4);
                    else load_image(sb, eph, r, kv, HINT & 4);
                    PT();
                    r = ring_next(r);
                    if ((MC & 4) && n != 16 - (j & 6)) load_image_mc(sb, eph, r, v, j & 1, HINT & 4);
                    else load_image(sb, eph, r, v, HINT & 4);
                    PT();
                    r = ring_next(r);
                }
                if (MC & 4) load_image_mc(sb, eph, r, kv + SLOT, j & 1, HINT & 4);
                else load_image(sb, eph, r, kv + SLOT, HINT & 4);
                PT();
                r = ring_next(r);
            }
            uint32_t otab = O_TABLE, ready = 0;
#pragma unroll 1
            for (int i = 0; i < 17; i++) {
                asm volatile("st.volatile.shared.u32 [%0], %1;" ::"r"(sb + SM_EP + 16), "r"(33 + i) : "memory");
                const bool dyn = i >= 8 && i < 15;
                const uint32_t want = dyn ? 15u << (4 * (i - 8)) : 1u << max(i + 14, 28);
                if (!(ready & want)) {
                    do {
                        asm volatile("ld.acquire.cta.shared.u32 %0, [%1];" : "=r"(ready) : "r"(sb + SM_EP + 4) : "memory");
                        ready = __shfl_sync(0xffffffffu, ready, 0);
                    } while (!(ready & want));
                    fence_async_global();
                }
                const int head = o_head(dyn ? (ready >> (4 * (i - 8))) & 15 : i, kh);
                const uint8_t* src = g_ctx + (size_t)(ort * 32 + head) * SLOT;
                if (i < 15) {
                    if (MC & 8) load_image_mc(sb, eph, o_next(otab), src, j & 1, HINT & 16);
                    else load_image(sb, eph, o_next(otab), src, HINT & 16);
                } else {
                    const uint32_t as = o_next(otab), d = sb + as * SLOT;
                    slot_wait(sb + BAR_EMPTY, eph, as);
                    asm volatile("{\n.reg .pred p, q;\nelect.sync _|p, 0xffffffff;\n@p mbarrier.arrive.expect_tx.shared::cta.b64 _, [%2], %3;\n"
                                 "@p cp.async.bulk.shared::cluster.global.mbarrier::complete_tx::bytes [%0], [%1], 16384, [%2];\n}"
                                 ::"r"(d + kh * 16384), "l"(src + kh * 16384), "r"(sb + BAR_FULL + 8 * as), "r"(i == 15 ? 32768 : 16384) : "memory");
                    if (i == 15)
                        asm volatile("{\n.reg .pred p;\nelect.sync _|p, 0xffffffff;\n"
                                     "@p cp.async.bulk.tensor.3d.shared::cluster.global.mbarrier::complete_tx::bytes [%0], [%1, {%3, %4, %5}], [%2];\n}"
                                     ::"r"(d + (kh ^ 1) * 16384), "l"(&tm_x), "r"(sb + BAR_FULL + 8 * as), "r"(0), "r"(ort * 128 + kh * 64), "r"(cq * 2) : "memory");
                }
                PT();
                load_tile(sb, eph, o_next(otab), &tm_wo, head * 128, cq * 2, HINT & 2); PT();
                if (i == 0) o_next(otab);
            }
            if (rb < NFFN) {
                load_image(sb, eph, o_next(otab), g_wf + rb * SLOT, false);
                const uint32_t s2 = o_next(otab);
                slot_wait(sb + BAR_EMPTY, eph, s2);
                asm volatile("{\n.reg .pred p;\nelect.sync _|p, 0xffffffff;\n@p mbarrier.arrive.expect_tx.shared::cta.b64 _, [%2], 16384;\n"
                             "@p cp.async.bulk.shared::cluster.global.mbarrier::complete_tx::bytes [%0], [%1], 16384, [%2];\n}"
                             ::"r"(sb + s2 * SLOT), "l"(P.wdown + rb * 8192), "r"(sb + BAR_FULL + 8 * s2) : "memory");
            }
        } else {
            const int hw = warp - 9;
            if (hw == 1 && lane == 0) {
                l2_prefetch(P.ckv + rb * 2048, 4096);
                mbar_watch(sb + BAR_FULL + 8 * PF0, 0);
                l2_prefetch(P.ckv + 512 * 512 + rb * 2048, 4096);
                mbar_watch(sb + BAR_FULL + 8 * 4, 0);
                l2_prefetch(P.x + rb * 8192, 16384);
                l2_prefetch(P.ckv + 1024 * 512 + rb * 4096, 8192);
                TS(40);
                if (MC & 2) tma3d_prefetch(&tm_wq, (j >> 1) * 128, grp * 4 + (j & 1));
                else if (j < 4) tma3d_prefetch(&tm_wq, j * 128, grp * 4);
                step_watch(sb + SM_EP + 16, PFA);
                tma3d_prefetch((j & 1) ? &tm_wuv : &tm_wuk, (j >> 1) * 128, grp * 4 + 2);
                step_watch(sb + SM_EP + 16, PFA + 2);
                l2_prefetch(P.ckv + rb * 8192, 16384);
                step_watch(sb + SM_EP + 16, PFA + 3);
                l2_prefetch(g_h + rb * 16384, 16384);
                step_watch(sb + SM_EP + 16, PFA + 4);
                if (MC & 2) tma3d_prefetch(&tm_wq, (j >> 1) * 128, grp * 4 + 2 + (j & 1));
                else if (j < 4) tma3d_prefetch(&tm_wq, j * 128, grp * 4 + 2);
#pragma unroll 1
                for (int i = 0; i < 10; i++) {
                    step_watch(sb + SM_EP + 16, i < 6 ? 16 + PFB + i : 16 + PFC + i - 6);
                    if (i == 7) mbar_watch(sb + BAR_FLAG + 8 * 7, 0);
                    const uint8_t* p = i < 4 ? g_ctx + (size_t)(ort * 32 + o_head(cq + 2 * (i & 2), kh)) * SLOT + (i & 1) * 16384
                                     : i < 6 ? reinterpret_cast<const uint8_t*>(P.wo) + ((rb >> 3) * 16 + (i & 1) * 8 + (rb & 7)) * 16384
                                     : i == 6 ? reinterpret_cast<const uint8_t*>(P.x) + rb * 16384
                                     : i == 7 ? reinterpret_cast<const uint8_t*>(P.wdown) + rb * 16384 : g_wf + rb * SLOT + (i & 1) * 16384;
                    if ((i < 7 || rb < NFFN) && ((PFMASK >> i) & 1)) l2_prefetch(p, 16384);
                }
                step_watch(sb + SM_EP + 16, 16 + PFC + 4);
                if (OBINIT) {
                    const uint32_t v = lds32(sb + SM_EP) - 1;
#pragma unroll 1
                    for (int i = 0; i < 32; i++) sts128(sb + SM_RED + i * 16, make_uint4(v, v, v, v));
                    fence_async_smem();
#pragma unroll 1
                    for (int i = 0; i < OB / 32; i++)
                        asm volatile("cp.async.bulk.global.shared::cta.bulk_group [%0], [%1], 512;" ::"l"(g_out + rb * OB + i * 32), "r"(sb + SM_RED) : "memory");
                    asm volatile("cp.async.bulk.commit_group;\ncp.async.bulk.wait_group 0;" ::: "memory");
                    fence_async_global();
                }
                mbar_arrive(sb + BAR_PF);
                mbar_watch(sb + BAR_END, 0);
            }
            if (hw == 0) {
#pragma unroll 1
                for (int i = 0; i < 9; i++) {
                    const int hp = i > 4, k = (i - 1) & 3;
                    if (lane == 0) {
                        mbar_wait(sb + BAR_DONE + 8 * i, 0);
                        flag_add(i == 0 ? &g_sync.hcnt[grp * 8] : k < 2 ? &g_sync.kvcnt[((2 * grp + hp) * 2 + k) * 8]
                                                                        : &g_sync.ctxcnt[(k == 2 ? 15 - j : j) * 32 + 2 * grp + hp]);
                    }
                    if (i == 0) TS(43);
                }
            }
            if (hw == 2) {
                const uint32_t ep = __ldcg(&g_sync.epoch[0]) + 1;
                if (lane == 0) {
                    asm volatile("st.shared.u32 [%0], %1;" ::"r"(sb + SM_EP), "r"(ep) : "memory");
                    flag_wait(&g_sync.modcnt[0], NSPARE * ep);
                }
                __syncwarp();
#pragma unroll
                for (int i = 0; i < 4; i++) {
                    uint4 v = __ldcg(reinterpret_cast<const uint4*>(g_mod) + lane + 32 * i);
                    if (i >= 2) v = make_uint4(badd(v.x, ONE2), badd(v.y, ONE2), badd(v.z, ONE2), badd(v.w, ONE2));
                    sts128(sb + SM_TAB + i * 512 + lane * 16, v);
                }
                __syncwarp();
                if (lane == 0) mbar_arrive(sb + BAR_FLAG + 8 * 8);
                TS(42);
#pragma unroll 1
                for (int i = 0; i < 8; i++) {
                    if (lane == 0) mbar_wait(sb + BAR_DONE + 8 * (i == 7 ? 6 : i == 4 ? 3 : i), 0);
                    __syncwarp();
                    const uint32_t* f = i == 0 ? &g_sync.hcnt[(lane ? j : 15 - j) * 8]
                                      : i == 3 || i == 4 ? &g_sync.rdcnt[(grp * 2 + i - 3) * 8]
                                      : i == 7 ? &g_sync.modcnt[32] : &g_sync.kvcnt[(4 * grp + (i > 4 ? i - 3 : i - 1)) * 8];
                    if (lane < (i ? 1 : 2)) flag_wait(f, 8 * ep);
                    __syncwarp();
                    if (i == 7) {
                        const uint32_t *mp = reinterpret_cast<const uint32_t*>(g_mod) + lane, *wp = reinterpret_cast<const uint32_t*>(P.wr) + lane;
                        float ra = 0.f, rs = 0.f;
#pragma unroll 1
                        for (int k = 0; k < 256; k += 32) {
                            const uint32_t ga = __ldcg(mp + 512 + k), sh = __ldcg(mp + 768 + k), c1 = badd(__ldcg(mp + 1024 + k), ONE2);
                            const uint32_t gb = __ldcg(mp + 1280 + k), ww = __ldg(wp + k);
                            const float a0 = bf_lo(c1) * bf_lo(ww), a1 = bf_hi(c1) * bf_hi(ww);
                            ra += a0 + a1;
                            rs = fmaf(bf_lo(sh), bf_lo(ww), fmaf(bf_hi(sh), bf_hi(ww), rs));
                            if (k >> 6 == cq) {
                                sts128(sb + SM_TAB + ((k & 32) + lane) * 16, make_uint4(ga << 16, ga & 0xffff0000u, __float_as_uint(a0), __float_as_uint(a1)));
                                sts128(sb + SM_TAB + 1024 + ((k & 32) + lane) * 16, make_uint4(c1, sh, gb, 0));
                            }
                        }
                        *reinterpret_cast<float2*>(smem + SM_EP + 8) = make_float2(warp_sum(ra), warp_sum(rs));
                        __syncwarp();
                    }
                    if (lane == 0) mbar_arrive(sb + BAR_FLAG + 8 * i);
                    TS(48 + i);
                }
                const uint32_t* f = &g_sync.ctxcnt[ort * 32 + o_head(min(lane, 16), kh)];
                uint32_t ready = (MC & 8) && (j & 1) ? ~0u : 0u, list = 0, sh = 0, qa = sb + SM_EP + 4;
                if (MC & 8) asm("mapa.shared::cluster.u32 %0, %1, %2;" : "=r"(qa) : "r"(sb + SM_EP + 4), "r"(lane & 1));
                while (ready != ~0u) {
                    uint32_t v;
                    asm volatile("ld.acquire.gpu.global.u32 %0, [%1];" : "=r"(v) : "l"(f) : "memory");
                    const uint32_t now = __ballot_sync(0xffffffffu, (int)(v - ep) >= 0);
                    for (uint32_t fresh = now & ~ready & 0x7f00; fresh; fresh &= fresh - 1, sh += 4) list |= (__ffs(fresh) - 1) << sh;
                    list |= (((now & 0xff) + 1) >> 8 << 28) | ((now & 0x18000) << 14);
                    if (now != ready && lane < ((MC & 8) ? 2 : 1)) asm volatile("st.relaxed.cluster.shared::cluster.u32 [%0], %1;" ::"r"(qa), "r"(list) : "memory");
                    if ((now & 0xff) == 0xff) mbar_wait(sb + BAR_DONE + 8 * 7, 0);
                    ready = now;
                    __nanosleep(POLL_NS);
                }
                TS(45);
            }
        }
    } else {
        asm volatile("setmaxnreg.inc.sync.aligned.u32 232;");
        const bool elected = (tid & 127) == 0, rel = MC ? (tid & 95) == 0 : elected;
        uint32_t eb = sb + BAR_EMPTY;
        if (MC) asm("mapa.shared::cluster.u32 %0, %1, %2;" : "=r"(eb) : "r"(sb + BAR_EMPTY), "r"(warp & 1));
        const int g = lane >> 2, c4 = lane & 3;
        const uint32_t toff = warp * 4096 + g * 64 + ((c4 ^ (g >> 1)) << 4);
        uint32_t fph = 0, r = 0;
        if (wg == 1) bar_arrive(1, 256);
        const uint32_t kd = desc_k(sb), wd = desc_mn(sb), vd = ((sb & 0x3ffff) >> 4) | (32u << 16);
        const int nL = 16 - j, hn = nL - 1 + wg;
        float s[64], o[64], li[2] = {0.f, 0.f};
        uint8_t* cimg = g_ctx;
#pragma unroll 1
        for (int hp = 0; hp < 2; hp++) {
            float m[2] = {0.f, 0.f}, l[2] = {0.f, 0.f}, t[4] = {0.f, 0.f, 0.f, 0.f};
            bool shifted = false, bad = false, plain = false;
            uint32_t p[32];
#pragma unroll
            for (int i = 0; i < 32; i++) p[i] = 0;
            uint32_t qa = desc_k(sb + 5 * SLOT + (wg ^ 1) * 8192);
            uint8_t* limg = g_ctx + (size_t)((15 - j) * 32 + 2 * grp + hp) * SLOT;
            reg_fence(p);
            {
                const int step = hp ? -8 * SLOT : 8 * SLOT;
                uint8_t* img = g_KV + (size_t)(grp * 32 + (hp ? j ^ 30 : j)) * SLOT - step;
                const float sc = (j & 1) ? 1.f : SM_C;
                const uint32_t wtab = w_table(hp);
                uint32_t atab = hp ? 0x256u : a_table(0);
#pragma unroll 1
                for (int u = 0;; u += 2) {
                    proj_tile<false>(s, o, u, u ? 0 : 2 * hp, sb, wg, eb, rel, fph, wtab, atab, u ? img : cimg, toff, u ? sc : li[0], u ? sc : li[1], (hp | u) == 0, P.x, rb * 16 + warp * 2);
                    __syncwarp();
                    mbar_arrive_if(sb + BAR_DONE + 4 * u + 32 * hp, lane == 0 && (hp | u) != 0);
                    if (elected) TS(1 + 10 * hp + u + 20 * wg);
                    if (proj_tile<true>(o, s, u + 1, 0, sb, wg, eb, rel, fph, wtab, atab, img + step, toff, sc, sc, (hp | u) == 0, P.x, rb * 16 + warp * 2)) break;
                    if (elected) TS(2 + 10 * hp + u + 20 * wg);
                    img += 2 * step;
                }
            }
            if (elected) TS(6 + 10 * hp + 20 * wg);
            int n = -1;
#pragma unroll 1
            for (;;) {
                while (bad || plain) {
                    if (bad) {
                        float a0, a1;
                        softmax_remax(s, m, n == 0 || n == nL, a0, a1);
                        shifted = true;
                        l[0] *= a0;
                        l[1] *= a1;
#pragma unroll
                        for (int i = 0; i < 64; i++) o[i] *= (i & 2) ? a1 : a0;
                    }
                    softmax_exp<0, 16>(s, p, t);
                    t[0] += t[1];
                    t[2] += t[3];
                    bad = !bad && softmax_unsafe(t[0], t[2], false);
                    plain = false;
                }
#pragma unroll 1
                do {
                    l[0] += t[0];
                    l[1] += t[2];
                    if (++n > 16) break;
                    const uint32_t ks = r;
                    uint32_t vs = ring_next(r);
                    r = ring_next(vs);
                    bar_sync(1 + wg, 256);
                    const float x = (float)((warp & 3) * 16 + g - 2 * c4);
                    if (n == hn) {
                        float sh[32];
                        qk_issue(sh, qa, kd + ks * (SLOT / 16));
                        slot_wait(sb + BAR_FULL, fph, vs);
                        pv_issue(o, p, vd + vs * (SLOT / 16), 1, false);
                        bar_arrive(2 - wg, 256);
                        wg_wait<1>();
                        reg_fence(sh);
                        tri_mask_copy(s, sh, x);
                        release_if(eb, ks, rel);
                        release_if(eb, 5 + wg, rel && (!wg || n == 16));
                        if (!wg) {
                            qa += SLOT / 16;
                            fence_async_smem();
                            if (shifted) softmax_shift(s, m[0], m[1]);
                        }
                        float e[4 * EARLY];
#pragma unroll
                        for (int i = 0; i < 4 * EARLY; i++) {
                            e[i] = ex2(s[i]);
                            t[i & 3] = i < 4 ? e[i] : t[i & 3] + e[i];
                        }
                        reg_fence(e);
                        slot_wait(sb + BAR_FULL, fph, r);
                        wg_wait<0>();
                        reg_fence(o);
                        reg_fence(e);
                        release_if(eb, vs, rel);
#pragma unroll
                        for (int i = 0; i < 2 * EARLY; i++) p[i] = pack2(e[2 * i], e[2 * i + 1]);
                        softmax_exp<EARLY, 8>(s, p, t);
                        if (wg) {
                            ctx_store<true>(limg, toff, o, l[0], l[1]);
                            __syncwarp();
                            mbar_arrive_if(sb + BAR_DONE + 24 + 32 * hp, lane == 0);
                            l[0] = l[1] = m[0] = m[1] = 0.f;
                            shifted = false;
                        }
                        t[0] += t[1];
                        t[2] += t[3];
                        bad = softmax_unsafe(t[0], t[2], wg);
                        continue;
                    }
                    if (n == 0 || n == nL) {
                        CDEF;
                        CT(0);
                        qk_issue(s, qa, kd + ks * (SLOT / 16));
                        if (n == 0) {
                            r = vs;
                            vs = 4 - hp;
                            slot_wait(sb + BAR_FULL, fph, 6);
                            gemm_issue<false>(o, qa + SLOT / 16, wd + vs * (SLOT / 16), 1, false);
                        } else {
                            slot_wait(sb + BAR_FULL, fph, vs);
                            pv_issue(o, p, vd + vs * (SLOT / 16), 1, true);
                        }
                        bar_arrive(2 - wg, 256);
                        const float i0 = n ? rcp(quad_sum(l[0])) : 1.f, i1 = n ? rcp(quad_sum(l[1])) : 1.f;
                        wg_wait<1>();
                        reg_fence(s);
                        release_if(eb, ks, rel);
                        release_if(eb, 6, rel && n == 16);
                        CT(1);
                        tri_mask(s, n ? x : 64.f);
                        float e[4 * EARLY];
#pragma unroll
                        for (int i = 0; i < 4 * EARLY; i++) {
                            e[i] = ex2(s[i]);
                            t[i & 3] = i < 4 ? e[i] : t[i & 3] + e[i];
                        }
                        reg_fence(e);
                        reg_fence(s);
                        reg_fence(t);
                        slot_wait(sb + BAR_FULL, fph, r);
                        if (SF & 1) sched_fence(fph, P.zero);
                        CT(2);
                        wg_wait<0>();
                        CT(3);
                        reg_fence(o);
                        reg_fence(e);
                        release_if(eb, vs, rel);
#pragma unroll
                        for (int i = 0; i < 2 * EARLY; i++) p[i] = pack2(e[2 * i], e[2 * i + 1]);
                        softmax_exp<EARLY, MSPLIT>(s, p, t);
                        tile_store(limg, sb + 6 * SLOT, toff, o, i0, i1, n);
                        reg_fence(t);
                        if (SF & 2) sched_fence(fph, P.zero);
                        CT(4);
                        reg_fence(s);
                        softmax_exp<MSPLIT, 16>(s, p, t);
                        __syncwarp();
                        mbar_arrive_if(sb + BAR_DONE + 24 + 32 * hp, lane == 0 && n);
                        l[0] = l[1] = m[0] = m[1] = 0.f;
                        shifted = false;
                        t[0] += t[1];
                        t[2] += t[3];
                        bad = __any_sync(0xffffffffu, fmaxf(t[0], t[2]) > SM_HI || fminf(t[0], t[2]) < SM_LO);
                        CT(5);
                        COUT(rb, n ? 2 : 1);
                        continue;
                    }
                    qk_issue(s, qa, kd + ks * (SLOT / 16));
                    slot_wait(sb + BAR_FULL, fph, vs);
                    pv_issue(o, p, vd + vs * (SLOT / 16), n != 1 && n != nL + 1, n == hn + 1);
                    bar_arrive(2 - wg, 256);
                    wg_wait<1>();
                    reg_fence(s);
                    release_if(eb, ks, rel);
                    release_if(eb, 6, rel && n == 16);
                    if (n == nL - 1) {
                        tri_mask(s, x);
                        release_if(eb, 5, rel);
                        qa += SLOT / 16;
                        fence_async_smem();
                    }
                    if (shifted) {
                        slot_wait(sb + BAR_FULL, fph, r);
                        wg_wait<0>();
                        reg_fence(o);
                        release_if(eb, vs, rel);
                        softmax_shift(s, m[0], m[1]);
                        plain = true;
                        break;
                    }
                    float e[4 * EARLY];
#pragma unroll
                    for (int i = 0; i < 4 * EARLY; i++) {
                        e[i] = ex2(s[i]);
                        t[i & 3] = i < 4 ? e[i] : t[i & 3] + e[i];
                    }
                    reg_fence(e);
                    slot_wait(sb + BAR_FULL, fph, r);
                    wg_wait<0>();
                    reg_fence(o);
                    reg_fence(e);
                    release_if(eb, vs, rel);
#pragma unroll
                    for (int i = 0; i < 2 * EARLY; i++) p[i] = pack2(e[2 * i], e[2 * i + 1]);
                    softmax_exp<EARLY, 16>(s, p, t);
                    t[0] += t[1];
                    t[2] += t[3];
                    bad = softmax_unsafe(t[0], t[2], false);
                } while (!bad);
                if (!bad && !plain) break;
            }
            const uint32_t vs = r, ga = desc_k(sb + (hp ? 2 * (wg ^ kh ^ 1) : wg) * 8192), as = 2 + 2 * hp;
            r = ring_next(r);
            slot_wait(sb + BAR_FULL, fph, 5);
            slot_wait(sb + BAR_FULL, fph, r);
            bar_sync(1 + wg, 256);
            gemm_issue<true>(s, ga + 5 * (SLOT / 16), wd + r * (SLOT / 16), 0, hp);
            pv_issue(o, p, vd + vs * (SLOT / 16), j, hn == 16);
            bar_arrive(2 - wg, 256);
            li[0] = rcp(quad_sum(l[0]));
            li[1] = rcp(quad_sum(l[1]));
            cimg = limg + (ptrdiff_t)(2 * j - 15) * 32 * SLOT + (wg ? -16384 : 16384);
            wg_wait<1>();
            release_if(eb, 5, rel);
            release_if(eb, r, rel && hp);
            wg_wait<0>();
            release_if(eb, vs, rel);
            reg_fence(o);
            img_store_global<0>(cimg, toff, o, li[0], li[1]);
            slot_wait(sb + BAR_FULL, fph, as);
            slot_wait(sb + BAR_FULL, fph, 0);
            bar_sync(1 + wg, 256);
            gemm_issue<false>(s, ga + as * (SLOT / 16), wd, 1, hp);
            bar_arrive(2 - wg, 256);
            reg_fence(o);
            img_store_global<1>(cimg, toff, o, li[0], li[1]);
            wg_wait<0>();
            release_if(eb, as, rel);
            release_if(eb, 0, rel && hp);
            if (elected) TS(8 + 10 * hp + 20 * wg);
        }
        uint32_t otab = 0x0423516u;
        const uint32_t oa = desc_k(sb + (wg ^ kh ^ 1) * 16384);
        const int t7 = tid & 127, w4 = warp & 3, row = ort * 128 + kh * 64 + w4 * 16 + g;
#pragma unroll 1
        for (int i = 2; i < 15 - wg; i++) {
            const uint32_t as = o_next(otab), ws = o_next(otab);
            slot_wait(sb + BAR_FULL, fph, as);
            slot_wait(sb + BAR_FULL, fph, ws);
            bar_sync(1 + wg, 256);
            gemm_issue<false>(s, oa + as * (SLOT / 16), wd + ws * (SLOT / 16), 1, true);
            bar_arrive(2 - wg, 256);
            wg_wait<1>();
            reg_fence(o);
            if (i == 2) img_store_global<2>(cimg, toff, o, li[0], li[1]);
            if (i == CLAST) {
                img_store_global<3>(cimg, toff, o, li[0], li[1]);
                __syncwarp();
                mbar_arrive_if(sb + BAR_DONE + 64, lane == 0);
            }
            wg_wait<0>();
            release_if(eb, as, rel);
            release_if(eb, ws, rel);
        }
        mbar_wait(sb + BAR_PF, 0);
        const uint32_t ep = lds32(sb + SM_EP);
        if (wg == 0) {
            reg_fence(s);
            if (elected) TS(9);
#pragma unroll
            for (int v = 0; v < 8; v++)
                st_pub(g_out + rb * OB + v * 128 + t7, make_uint4((pack2(s[8 * v], s[8 * v + 1]) & ~1u) | (ep & 1), pack2(s[8 * v + 2], s[8 * v + 3]),
                                                                      pack2(s[8 * v + 4], s[8 * v + 5]), pack2(s[8 * v + 6], s[8 * v + 7])), true);
            o_next(otab); o_next(otab); o_next(otab); o_next(otab);
            const uint32_t s1 = o_next(otab), s2 = o_next(otab);
            bar_sync(4, 256);
            uint32_t wf[64];
            float wn[64];
            if (rb < NFFN) {
                slot_wait(sb + BAR_FULL, fph, s1);
                const uint32_t a = sb + s1 * SLOT + (w4 * 128 + (lane >> 4) * 8 + (lane & 7)) * 32 + ((lane >> 3) & 1) * 16;
#pragma unroll
                for (int i = 0; i < 16; i++)
                    asm volatile("ldmatrix.sync.aligned.m8n8.x4.trans.shared.b16 {%0, %1, %2, %3}, [%4];"
                                 : "=r"(wf[4 * i]), "=r"(wf[4 * i + 1]), "=r"(wf[4 * i + 2]), "=r"(wf[4 * i + 3])
                                 : "r"(a + (i >> 3) * 16384 + (i & 7) * 512) : "memory");
                slot_wait(sb + BAR_FULL, fph, s2);
#pragma unroll
                for (int i = 0; i < 16; i++) {
                    const uint2 w = *reinterpret_cast<const uint2*>(smem + s2 * SLOT + i * 1024 + t7 * 8);
                    wn[4 * i] = bf_lo(w.x); wn[4 * i + 1] = bf_hi(w.x); wn[4 * i + 2] = bf_lo(w.y); wn[4 * i + 3] = bf_hi(w.y);
                }
                reg_fence(wn);
            }
            const uint32_t gbf = __ldcg(reinterpret_cast<const uint32_t*>(g_mod) + 1280 + rb * 2 + (tid & 1));
            if (elected) TS(10);
            const uint32_t best = best_key(g_key + cq * 128, lane, ep);
            const int sel = (~best >> 5) & 2047;
            if (elected) TS(19);
            const uint4* cp = g_cand + (sel >> 4) * 192;
            float* sred = reinterpret_cast<float*>(smem + SM_RED);
            const int pq = (2 * rb + (tid & 1)) & 63, pv = (pq >> 2) / 3;
            const uint4* fp = cp + (rb >> 5) * 24 + pv * 4 + (pq & 3);
            uint4 fh = ld_poll(fp), fx = ld_poll(fp + 96);
            if (rb < NFFN) {
                uint4 cv[6];
                for (;;) {
                    uint32_t bad = 0;
#pragma unroll
                    for (int v = 0; v < 6; v++) cv[v] = ld_poll(cp + w4 * 24 + v * 4 + c4);
#pragma unroll
                    for (int v = 0; v < 6; v++) bad |= cv[v].w ^ ep;
                    if (__all_sync(0xffffffffu, bad == 0)) break;
                }
                if (elected) TS(20);
                float d[4][4] = {};
#pragma unroll
                for (int k = 0; k < 8; k++) {
                    const uint32_t b0 = (&cv[(2 * k) / 3].x)[(2 * k) % 3], b1 = (&cv[(2 * k + 1) / 3].x)[(2 * k + 1) % 3];
                    mma16816(d[k & 1], wf + 4 * k, b0, b1);
                    mma16816(d[2 + (k & 1)], wf + 32 + 4 * k, b0, b1);
                }
                const float u = (c4 & 2) ? ((c4 & 1) ? d[2][2] + d[3][2] : d[2][0] + d[3][0]) : ((c4 & 1) ? d[0][2] + d[1][2] : d[0][0] + d[1][0]);
                sred[w4 * 32 + c4 * 8 + g] = u;
                bar_sync(3, 128);
                const float v = rbf((sred[lane] + sred[32 + lane]) + (sred[64 + lane] + sred[96 + lane]));
                const float act = rbf(rbf(v * sigmoid(v)) * __shfl_down_sync(0xffffffffu, v, 16));
                float y[4] = {0.f, 0.f, 0.f, 0.f};
#pragma unroll
                for (int k = 0; k < 16; k++) {
                    const float a = __shfl_sync(0xffffffffu, act, k);
#pragma unroll
                    for (int i = 0; i < 4; i++) y[i] = fmaf(a, wn[4 * k + i], y[i]);
                }
                st_pub(g_out + rb * OB + OB_Y + t7, make_uint4((__float_as_uint(y[0]) & ~15u) | (ep & 15), __float_as_uint(y[1]), __float_as_uint(y[2]), __float_as_uint(y[3])), true);
            }
            if (rb == 0 && tid == 0) g_sync.epoch[0] = ep;
            if (elected) TS(60);
            uint4 yv;
            do yv = ld_poll(g_out + min(t7, NFFN - 1) * OB + OB_Y + rb);
            while (!__all_sync(0xffffffffu, ((yv.x ^ ep) & 15) == 0));
            if (elected) TS(61);
            float y[4] = {0.f, 0.f, 0.f, 0.f};
            if (t7 < NFFN) { y[0] = __uint_as_float(yv.x); y[1] = __uint_as_float(yv.y); y[2] = __uint_as_float(yv.z); y[3] = __uint_as_float(yv.w); }
            const float z0 = ((lane & 16) ? y[2] : y[0]) + __shfl_xor_sync(0xffffffffu, (lane & 16) ? y[0] : y[2], 16);
            const float z1 = ((lane & 16) ? y[3] : y[1]) + __shfl_xor_sync(0xffffffffu, (lane & 16) ? y[1] : y[3], 16);
            float z = ((lane & 8) ? z1 : z0) + __shfl_xor_sync(0xffffffffu, (lane & 8) ? z0 : z1, 8);
            z += __shfl_xor_sync(0xffffffffu, z, 4);
            z = quad_sum(z);
            if ((lane & 7) == 0) sred[128 + (lane >> 3) * 4 + w4] = z;
            bar_sync(3, 128);
            if (tid < 2) {
                while (fh.w != ep || fx.w != ep) { fh = ld_poll(fp); fx = ld_poll(fp + 96); }
                const float4 y0 = *reinterpret_cast<const float4*>(sred + 128 + tid * 8), y1 = *reinterpret_cast<const float4*>(sred + 132 + tid * 8);
                const int cm = (pq >> 2) - 3 * pv;
                const uint32_t h2 = cm == 0 ? fh.x : cm == 1 ? fh.y : fh.z, x2 = cm == 0 ? fx.x : cm == 1 ? fx.y : fx.z;
                const float sg = sigmoid(bf_hi((best & 0x80000000u) ? (best ^ 0x80000000u) : ~best));
                reinterpret_cast<uint32_t*>(P.out)[sel * 256 + rb * 2 + tid] =
                    badd(x2, bmul(gbf, badd(h2, bmul(pack2((y0.x + y0.y) + (y0.z + y0.w), (y1.x + y1.y) + (y1.z + y1.w)), pack2(sg, sg)))));
            }
            if (elected) TS(62);
        } else {
            const float4* tf = reinterpret_cast<const float4*>(smem + SM_TAB) + c4;
            const uint32_t as14 = otab & 15, xa = sb + ((otab >> 8) & 15) * SLOT + (kh ^ 1) * 16384 + (w4 * 16 + (lane & 15)) * 128;
            uint32_t x2[32];
            bar_sync(2, 256);
#pragma unroll 1
            for (int i = 14; i < 17; i++) {
                const uint32_t as = o_next(otab), ws = o_next(otab);
                slot_wait(sb + BAR_FULL, fph, as);
                slot_wait(sb + BAR_FULL, fph, ws);
                gemm_issue<false>(s, oa + as * (SLOT / 16), wd + ws * (SLOT / 16), 1, true);
                wg_wait<1>();
                release_if(eb, as14, rel && i == 15);
            }
            if (elected) TS(29);
            {
#pragma unroll
                for (int k = 0; k < 8; k++)
                    asm volatile("ldmatrix.sync.aligned.m8n8.x4.shared.b16 {%0, %1, %2, %3}, [%4];"
                                 : "=r"(x2[4 * k]), "=r"(x2[4 * k + 1]), "=r"(x2[4 * k + 2]), "=r"(x2[4 * k + 3])
                                 : "r"(xa + (k >> 2) * 8192 + (((2 * (k & 3) + (lane >> 4)) ^ (lane & 7)) << 4)) : "memory");
            }
            wg_wait<0>();
            reg_fence(s);
            bar_arrive(4, 256);
            if (elected) TS(39);
            const uint4* pr = g_out + (rb ^ 8) * OB + t7;
            uint4 pa[8];
#pragma unroll
            for (int v = 0; v < 8; v++) pa[v] = ld_poll(pr + v * 128);
            float4 tc[16];
#pragma unroll
            for (int k = 0; k < 16; k++) {
                tc[k] = tf[k * 4];
#pragma unroll
                for (int i = 4 * k; i < 4 * k + 4; i++) s[i] = fmaf((i & 1) ? tc[k].y : tc[k].x, s[i], (i & 1) ? bf_hi(x2[i >> 1]) : bf_lo(x2[i >> 1]));
            }
            reg_fence(s);
            for (;;) {
                uint32_t bad = 0;
#pragma unroll
                for (int v = 0; v < 8; v++) bad |= pa[v].x ^ ep;
                if (__all_sync(0xffffffffu, (bad & 1) == 0)) break;
#pragma unroll
                for (int v = 0; v < 8; v++) pa[v] = ld_poll(pr + v * 128);
            }
            if (elected) TS(30);
            float st[6] = {0.f, 0.f, 0.f, 0.f, 0.f, 0.f};
#pragma unroll
            for (int i = 0; i < 64; i++) {
                const int rh = (i >> 1) & 1;
                const uint32_t w = (&pa[i >> 3].x)[(i >> 1) & 3];
                const float v = fmaf((i & 1) ? tc[i >> 2].y : tc[i >> 2].x, (i & 1) ? bf_hi(w) : bf_lo(w), s[i]);
                s[i] = v;
                st[rh] += v;
                st[2 + rh] = fmaf(v, v, st[2 + rh]);
                st[4 + rh] = fmaf(v, (i & 1) ? tc[i >> 2].w : tc[i >> 2].z, st[4 + rh]);
            }
#pragma unroll
            for (int i = 0; i < 6; i++) st[i] = quad_sum(st[i]);
            st_pub(g_out + rb * OB + OB_STAT + (w4 * 8 + g) * 2 + (c4 & 1),
                   make_uint4(__float_as_uint((c4 & 1) ? st[1] : st[0]), __float_as_uint((c4 & 1) ? st[3] : st[2]),
                              __float_as_uint((c4 & 1) ? st[5] : st[4]), ep), c4 < 2);
            if (elected) TS(56);
            uint32_t cb[16], sh[16], gb[16];
#pragma unroll
            for (int i = 0; i < 16; i++) {
                const float4 c = tf[64 + i * 4];
                cb[i] = __float_as_uint(c.x); sh[i] = __float_as_uint(c.y); gb[i] = __float_as_uint(c.z);
            }
            const float ra = __uint_as_float(lds32(sb + SM_EP + 8)), rb0 = __uint_as_float(lds32(sb + SM_EP + 12));
#pragma unroll
            for (int i = 0; i < 32; i++) x2[i] = pack2(s[2 * i], s[2 * i + 1]);
            reg_fence(x2);
            uint4 r0, r1;
            for (;;) {
                r0 = ld_poll(g_out + ((rb & ~3) + c4) * OB + OB_STAT + (w4 * 8 + g) * 2);
                r1 = ld_poll(g_out + ((rb & ~3) + c4) * OB + OB_STAT + (w4 * 8 + g) * 2 + 1);
                if (__all_sync(0xffffffffu, r0.w == ep && r1.w == ep)) break;
            }
            if (elected) TS(57);
            const float m0 = quad_sum(__uint_as_float(r0.x)) * (1.f / 512.f), m1 = quad_sum(__uint_as_float(r1.x)) * (1.f / 512.f);
            const float rs0 = ln_rstd(fmaxf(fmaf(-m0, m0, quad_sum(__uint_as_float(r0.y)) * (1.f / 512.f)), 0.f));
            const float rs1 = ln_rstd(fmaxf(fmaf(-m1, m1, quad_sum(__uint_as_float(r1.y)) * (1.f / 512.f)), 0.f));
            const uint32_t mb0 = pack2(m0, m0), mb1 = pack2(m1, m1);
            const uint32_t lg = pack2(fmaf(rs0, fmaf(-bf_lo(mb0), ra, quad_sum(__uint_as_float(r0.z))), rb0),
                                      fmaf(rs1, fmaf(-bf_lo(mb1), ra, quad_sum(__uint_as_float(r1.z))), rb0));
            const uint32_t u0 = lg << 16, u1 = lg & 0xffff0000u;
            const uint32_t k0 = ((u0 ^ (((int)u0 >> 31) | 0x80000000u)) & 0xffff0000u) | ((2047 - row) << 5) | (ep & 31);
            const uint32_t k1 = ((u1 ^ (((int)u1 >> 31) | 0x80000000u)) & 0xffff0000u) | ((2039 - row) << 5) | (ep & 31);
            const uint32_t kb = __reduce_max_sync(0xffffffffu, max(k0, k1));
            st_pub(g_key + cq * 128 + (row >> 4), kb, lane == 0);
            {
                uint32_t cx[18], ch[18];
#pragma unroll
                for (int i = 0; i < 16; i++) {
                    cx[i] = kb == k1 ? x2[2 * i + 1] : x2[2 * i];
                    ch[i] = ln_apply(cx[i], kb == k1 ? mb1 : mb0, kb == k1 ? rs1 : rs0, cb[i], sh[i]);
                }
                cx[16] = cx[17] = ch[16] = ch[17] = 0;
                uint4* cp = g_cand + (row >> 4) * 192 + cq * 24 + c4;
#pragma unroll
                for (int v = 0; v < 6; v++) st_pub(cp + v * 4, make_uint4(ch[3 * v], ch[3 * v + 1], ch[3 * v + 2], ep), kb == k0 || kb == k1);
#pragma unroll
                for (int v = 0; v < 6; v++) st_pub(cp + 96 + v * 4, make_uint4(cx[3 * v], cx[3 * v + 1], cx[3 * v + 2], ep), kb == k0 || kb == k1);
            }
            if (elected) TS(58);
            uint2 ov[16];
#pragma unroll
            for (int i = 0; i < 16; i++) {
                const int rh = i & 1, jj = i & 14;
                const uint32_t v0 = badd(x2[2 * jj + rh], bmul(gb[jj], ln_apply(x2[2 * jj + rh], rh ? mb1 : mb0, rh ? rs1 : rs0, cb[jj], sh[jj])));
                const uint32_t v1 = badd(x2[2 * jj + 2 + rh], bmul(gb[jj + 1], ln_apply(x2[2 * jj + 2 + rh], rh ? mb1 : mb0, rh ? rs1 : rs0, cb[jj + 1], sh[jj + 1])));
                const uint32_t rv = __shfl_xor_sync(0xffffffffu, (c4 & 1) ? v0 : v1, 1);
                ov[i] = (c4 & 1) ? make_uint2(rv, v1) : make_uint2(v0, rv);
            }
            uint2* op = reinterpret_cast<uint2*>(P.out) + row * 128 + cq * 32 + (c4 & 1) * 2 + (c4 >> 1);
#pragma unroll
            for (int i = 0; i < 16; i++)
                if (kb != ((i & 1) ? k1 : k0)) op[(i & 1) * 1024 + (i & 14) * 2] = ov[i];
            const uint32_t best = best_key(g_key + cq * 128, lane, ep);
            if (best != kb) {
#pragma unroll
                for (int i = 0; i < 16; i++)
                    if (kb == ((i & 1) ? k1 : k0)) op[(i & 1) * 1024 + (i & 14) * 2] = ov[i];
            }
            if (elected) TS(59);
        }
        mbar_arrive_if(sb + BAR_END, lane == 0);
    }
}

typedef CUresult (*EncodeFn)(CUtensorMap*, CUtensorMapDataType, cuuint32_t, void*, const cuuint64_t*, const cuuint64_t*,
                             const cuuint32_t*, const cuuint32_t*, CUtensorMapInterleave, CUtensorMapSwizzle,
                             CUtensorMapL2promotion, CUtensorMapFloatOOBfill);

void make_2d(EncodeFn fn, CUtensorMap* m, const void* p, uint64_t cols, uint64_t rows, uint32_t bc, uint32_t br) {
    cuuint64_t dims[2] = {cols, rows}, strides[1] = {cols * 2};
    cuuint32_t box[2] = {bc, br}, es[2] = {1, 1};
    fn(m, CU_TENSOR_MAP_DATA_TYPE_BFLOAT16, 2, const_cast<void*>(p), dims, strides, box, es, CU_TENSOR_MAP_INTERLEAVE_NONE,
       CU_TENSOR_MAP_SWIZZLE_NONE, CU_TENSOR_MAP_L2_PROMOTION_L2_128B, CU_TENSOR_MAP_FLOAT_OOB_FILL_NONE);
}
void make_3d(EncodeFn fn, CUtensorMap* m, const void* p, uint64_t cols, uint64_t rows, uint32_t br = 128, uint32_t nb = 2) {
    cuuint64_t dims[3] = {64, rows, cols / 64}, strides[2] = {cols * 2, 128};
    cuuint32_t box[3] = {64, br, nb}, es[3] = {1, 1, 1};
    fn(m, CU_TENSOR_MAP_DATA_TYPE_BFLOAT16, 3, const_cast<void*>(p), dims, strides, box, es, CU_TENSOR_MAP_INTERLEAVE_NONE,
       CU_TENSOR_MAP_SWIZZLE_128B, CU_TENSOR_MAP_L2_PROMOTION_L2_256B, CU_TENSOR_MAP_FLOAT_OOB_FILL_NONE);
}

}

extern "C" void kernel_launch(void* const* d_in, const int* in_sizes, int n_in, void* d_out, int out_size) {
    static EncodeFn fn = nullptr;
    static int sms = 0;
    if (!fn) {
        void* f = nullptr;
        cudaDriverEntryPointQueryResult st;
        cudaGetDriverEntryPoint("cuTensorMapEncodeTiled", &f, cudaEnableDefault, &st);
        fn = (EncodeFn)f;
        int dev = 0;
        cudaGetDevice(&dev);
        cudaDeviceGetAttribute(&sms, cudaDevAttrMultiProcessorCount, dev);
        cudaFuncSetAttribute(fused_kernel, cudaFuncAttributeMaxDynamicSharedMemorySize, SMEM_BYTES);
    }
    CUtensorMap ckv, wq, wuk, wuv, wo, wg, wu, wm, xm;
    make_3d(fn, &ckv, d_in[1], 512, 2048, 128, (MC & 1) ? 1 : 2);
    make_3d(fn, &xm, d_in[0], 512, 2048, 64);
    make_3d(fn, &wq, d_in[2], 4096, 512, 128, (MC & 2) ? 1 : 2);
    make_3d(fn, &wuk, d_in[3], 4096, 512);
    make_3d(fn, &wuv, d_in[4], 4096, 512);
    make_3d(fn, &wo, d_in[5], 512, 4096);
    make_2d(fn, &wg, d_in[8], 1792, 512, 16, 256);
    make_2d(fn, &wu, d_in[9], 1792, 512, 16, 256);
    make_2d(fn, &wm, d_in[12], 3072, 512, 256, 64);
    Params p;
    p.x = (const bf16*)d_in[0];
    p.ckv = (const bf16*)d_in[1];
    p.wo = (const bf16*)d_in[5];
    p.wr = (const bf16*)d_in[7];
    p.wdown = (const bf16*)d_in[10];
    p.c = (const bf16*)d_in[11];
    p.out = (bf16*)d_out;
    p.zero = 0;
    p.by_smid = sms == NCTA + NSPARE;
    fused_kernel<<<NCTA + NSPARE, 384, SMEM_BYTES>>>(ckv, wq, wuk, wuv, wo, wg, wu, wm, xm, p);
}
```

```cpp
#include <cuda.h>
#include <cuda_bf16.h>
#include <cuda_runtime.h>
#include <stdint.h>
#include <stdio.h>

namespace {

typedef __nv_bfloat16 bf16;
typedef unsigned long long u64;

constexpr int NCTA = 128, NSPARE = 4;
constexpr int SLOT = 32768;
constexpr int SM_BAR = 7 * SLOT;
constexpr int BAR_FULL = SM_BAR;
constexpr int BAR_EMPTY = BAR_FULL + 8 * 7;
constexpr int BAR_DONE = BAR_EMPTY + 8 * 7;
constexpr int BAR_FLAG = BAR_DONE + 8 * 9;
constexpr int BAR_PF = BAR_FLAG + 8 * 9;
constexpr int BAR_END = BAR_PF + 8;
constexpr int SM_EP = BAR_END + 24;
constexpr int SM_RED = SM_BAR + 384;
constexpr int SM_TAB = SM_BAR + 1024;
constexpr int SMEM_BYTES = SM_BAR + 3072;
constexpr int NFFN = 112;
#define HINT 31
constexpr u64 L2_NORMAL = 0x1000000000000000ull, L2_FIRST = 0x12F0000000000000ull;
#define PFA 8
#define PFB 6
#define UNR 1
#define POLL_NS 50
#define MSPLIT 13
#define SF 3
#define XQ 0
#define EARLY 7
constexpr uint32_t SPIN_LIMIT = 1u << 22;
constexpr uint32_t ONE2 = 0x3f803f80u;

struct Sync {
    uint32_t cnt[16 * 8 * 8];
    uint32_t ctxcnt[16 * 32];
    uint32_t epoch[32];
};

__device__ __align__(1024) uint8_t g_KV[16 * 16 * 2 * SLOT];
__device__ __align__(1024) uint8_t g_ctx[16 * 32 * SLOT];
__device__ __align__(1024) uint8_t g_h[16 * 4 * SLOT];
constexpr int OB = 1216, OB_STAT = 1024, OB_Y = 1088;
__device__ __align__(1024) uint4 g_out[128 * OB];
__device__ __align__(1024) bf16 g_mod[3072];
__device__ __align__(1024) uint32_t g_mod1[1024];
__device__ __align__(1024) uint4 g_cand[128 * 192];
__device__ __align__(1024) uint32_t g_key[4 * 128];
__device__ __align__(1024) uint8_t g_wf[NFFN * SLOT];
__device__ __align__(1024) Sync g_sync;
#define TS(i)

#define PT()

struct Params {
    const bf16 *x, *ckv, *wo, *wr, *wdown, *c;
    bf16* out;
    int zero;
};

__device__ __forceinline__ void mbar_init(uint32_t bar, uint32_t cnt) {
    asm volatile("mbarrier.init.shared::cta.b64 [%0], %1;" ::"r"(bar), "r"(cnt) : "memory");
}
__device__ __forceinline__ void mbar_wait(uint32_t bar, uint32_t parity) {
    asm volatile("{\n.reg .pred p;\nL_%=:\nmbarrier.try_wait.parity.shared::cta.b64 p, [%0], %1;\n@!p bra L_%=;\n}" ::"r"(bar), "r"(parity) : "memory");
}
__device__ __forceinline__ void mbar_sleep(uint32_t bar) {
    if ((threadIdx.x & 31) == 0)
        asm volatile("{\n.reg .pred p;\nL_%=:\nmbarrier.try_wait.parity.shared::cta.b64 p, [%0], 0, 100000;\n@!p bra L_%=;\n}" ::"r"(bar) : "memory");
    __syncwarp();
}
__device__ __forceinline__ void mbar_watch(uint32_t bar, uint32_t parity) {
    asm volatile("{\n.reg .pred p;\n.reg .u32 n;\nmov.u32 n, 0;\n"
                 "L_%=:\nmbarrier.try_wait.parity.shared::cta.b64 p, [%0], %1;\n@p bra D_%=;\n"
                 "add.u32 n, n, 1;\nsetp.lt.u32 p, n, %2;\n@p bra L_%=;\ntrap;\nD_%=:\n}"
                 ::"r"(bar), "r"(parity), "n"(SPIN_LIMIT) : "memory");
}
__device__ __forceinline__ void step_watch(uint32_t a, uint32_t step) {
    asm volatile("{\n.reg .pred p;\n.reg .u32 n, v;\nmov.u32 n, 0;\n"
                 "L_%=:\nld.volatile.shared.u32 v, [%0];\nsetp.ge.u32 p, v, %1;\n@p bra D_%=;\nnanosleep.u32 400;\n"
                 "add.u32 n, n, 1;\nsetp.lt.u32 p, n, %2;\n@p bra L_%=;\ntrap;\nD_%=:\n}"
                 ::"r"(a), "r"(step), "n"(SPIN_LIMIT) : "memory");
}
__device__ __forceinline__ void mbar_arrive_if(uint32_t bar, bool on) {
    asm volatile("{\n.reg .pred p;\nsetp.ne.s32 p, %1, 0;\n@p mbarrier.arrive.shared::cta.b64 _, [%0];\n}" ::"r"(bar), "r"((int)on) : "memory");
}
__device__ __forceinline__ void tma2d(uint32_t dst, const CUtensorMap* m, int c0, int c1, uint32_t bar) {
    asm volatile("{\n.reg .pred p;\nelect.sync _|p, 0xffffffff;\n"
                 "@p cp.async.bulk.tensor.2d.shared::cluster.global.mbarrier::complete_tx::bytes [%0], [%1, {%3, %4}], [%2];\n}"
                 ::"r"(dst), "l"(m), "r"(bar), "r"(c0), "r"(c1) : "memory");
}
__device__ __forceinline__ void tma3d_prefetch(const CUtensorMap* m, int row, int cb) {
    asm volatile("{\n.reg .pred p;\nelect.sync _|p, 0xffffffff;\n@p cp.async.bulk.prefetch.tensor.3d.L2.global [%0, {%1, %2, %3}];\n}"
                 ::"l"(m), "r"(0), "r"(row), "r"(cb) : "memory");
}
__device__ __forceinline__ void l2_prefetch(const void* p, uint32_t bytes) {
    asm volatile("{\n.reg .pred p;\nelect.sync _|p, 0xffffffff;\n@p cp.async.bulk.prefetch.L2.global [%0], %1;\n}" ::"l"(p), "r"(bytes) : "memory");
}
__device__ __forceinline__ void bulk_store(void* dst, uint32_t src, uint32_t bytes) {
    asm volatile("{\n.reg .pred p;\nelect.sync _|p, 0xffffffff;\n@p cp.async.bulk.global.shared::cta.bulk_group [%0], [%1], %2;\n}"
                 ::"l"(dst), "r"(src), "r"(bytes) : "memory");
}
__device__ __forceinline__ void flag_wait(const uint32_t* f, uint32_t target) {
    asm volatile("{\n.reg .pred p;\n.reg .u32 v;\n"
                 "L_%=:\nld.acquire.gpu.global.u32 v, [%0];\nsub.u32 v, v, %1;\nsetp.lt.s32 p, v, 0;\n@p nanosleep.u32 100;\n@p bra L_%=;\n}"
                 ::"l"(f), "r"(target) : "memory");
}
__device__ __forceinline__ uint4 ld_poll(const uint4* p) {
    uint4 v;
    asm volatile("{\n.reg .b128 t;\nld.relaxed.gpu.global.b128 t, [%4];\nmov.b128 {%0, %1, %2, %3}, t;\n}"
                 : "=r"(v.x), "=r"(v.y), "=r"(v.z), "=r"(v.w) : "l"(p) : "memory");
    return v;
}
__device__ __forceinline__ void st_pub(uint4* p, uint4 v, bool on) {
    asm volatile("{\n.reg .pred p;\n.reg .b128 t;\nsetp.ne.s32 p, %5, 0;\nmov.b128 t, {%1, %2, %3, %4};\n@p st.relaxed.gpu.global.b128 [%0], t;\n}"
                 ::"l"(p), "r"(v.x), "r"(v.y), "r"(v.z), "r"(v.w), "r"((int)on) : "memory");
}
__device__ __forceinline__ void st_pub(uint32_t* p, uint32_t v, bool on) {
    asm volatile("{\n.reg .pred p;\nsetp.ne.s32 p, %2, 0;\n@p st.relaxed.gpu.global.u32 [%0], %1;\n}" ::"l"(p), "r"(v), "r"((int)on) : "memory");
}
__device__ __forceinline__ void flag_add(uint32_t* p) {
    asm volatile("red.release.gpu.global.add.u32 [%0], 1;" ::"l"(p) : "memory");
}
__device__ __forceinline__ uint32_t lds32(uint32_t a) {
    uint32_t v;
    asm volatile("ld.shared.u32 %0, [%1];" : "=r"(v) : "r"(a) : "memory");
    return v;
}
__device__ __forceinline__ uint4 lds128(uint32_t a) {
    uint4 v;
    asm volatile("ld.shared.v4.u32 {%0, %1, %2, %3}, [%4];" : "=r"(v.x), "=r"(v.y), "=r"(v.z), "=r"(v.w) : "r"(a) : "memory");
    return v;
}
__device__ __forceinline__ void sched_fence(uint32_t& v, uint32_t z) {
    uint32_t ck;
    asm volatile("mov.u32 %0, %%clock;" : "=r"(ck)::"memory");
    v ^= ck & z;
}
__device__ __forceinline__ void fence_async_global() { asm volatile("fence.proxy.async.global;" ::: "memory"); }
__device__ __forceinline__ void fence_async_smem() { asm volatile("fence.proxy.async.shared::cta;" ::: "memory"); }
__device__ __forceinline__ void bar_sync(int id, int n) { asm volatile("bar.sync %0, %1;" ::"r"(id), "r"(n) : "memory"); }
__device__ __forceinline__ void bar_arrive(int id, int n) { asm volatile("bar.arrive %0, %1;" ::"r"(id), "r"(n) : "memory"); }
__device__ __forceinline__ void wg_fence() { asm volatile("wgmma.fence.sync.aligned;" ::: "memory"); }
__device__ __forceinline__ void wg_commit() { asm volatile("wgmma.commit_group.sync.aligned;" ::: "memory"); }
template <int N> __device__ __forceinline__ void wg_wait() { asm volatile("wgmma.wait_group.sync.aligned %0;" ::"n"(N) : "memory"); }
template <int N> __device__ __forceinline__ void reg_fence(float (&d)[N]) {
#pragma unroll
    for (int i = 0; i < N; i++) asm volatile("" : "+f"(d[i])::"memory");
}
template <int N> __device__ __forceinline__ void reg_fence(uint32_t (&d)[N]) {
#pragma unroll
    for (int i = 0; i < N; i++) asm volatile("" : "+r"(d[i])::"memory");
}
__device__ __forceinline__ uint32_t desc_k(uint32_t a) { return ((a & 0x3ffff) >> 4) | (1u << 16); }
__device__ __forceinline__ uint32_t desc_mn(uint32_t a) { return ((a & 0x3ffff) >> 4) | (1024u << 16); }

template <int TB>
__device__ __forceinline__ void wgmma_ss128(float (&d)[64], uint32_t da, uint32_t db, int acc, uint32_t ha = 0x40000040u, uint32_t hb = 0x40000040u) {
    asm volatile("{\n.reg .pred p;\n.reg .b64 a, b;\nsetp.ne.b32 p, %66, 0;\nmov.b64 a, {%64, %68};\nmov.b64 b, {%65, %69};\n"
        "wgmma.mma_async.sync.aligned.m64n128k16.f32.bf16.bf16 {%0, %1, %2, %3, %4, %5, %6, %7, %8, %9, %10, %11, %12, %13, %14, %15, %16, %17, %18, %19, %20, %21, %22, %23, %24, %25, %26, %27, %28, %29, %30, %31, %32, %33, %34, %35, %36, %37, %38, %39, %40, %41, %42, %43, %44, %45, %46, %47, %48, %49, %50, %51, %52, %53, %54, %55, %56, %57, %58, %59, %60, %61, %62, %63}, a, b, p, 1, 1, 0, %67;\n}"
        : "+f"(d[0]), "+f"(d[1]), "+f"(d[2]), "+f"(d[3]), "+f"(d[4]), "+f"(d[5]), "+f"(d[6]), "+f"(d[7]), "+f"(d[8]), "+f"(d[9]), "+f"(d[10]), "+f"(d[11]), "+f"(d[12]), "+f"(d[13]), "+f"(d[14]), "+f"(d[15]), "+f"(d[16]), "+f"(d[17]), "+f"(d[18]), "+f"(d[19]), "+f"(d[20]), "+f"(d[21]), "+f"(d[22]), "+f"(d[23]), "+f"(d[24]), "+f"(d[25]), "+f"(d[26]), "+f"(d[27]), "+f"(d[28]), "+f"(d[29]), "+f"(d[30]), "+f"(d[31]), "+f"(d[32]), "+f"(d[33]), "+f"(d[34]), "+f"(d[35]), "+f"(d[36]), "+f"(d[37]), "+f"(d[38]), "+f"(d[39]), "+f"(d[40]), "+f"(d[41]), "+f"(d[42]), "+f"(d[43]), "+f"(d[44]), "+f"(d[45]), "+f"(d[46]), "+f"(d[47]), "+f"(d[48]), "+f"(d[49]), "+f"(d[50]), "+f"(d[51]), "+f"(d[52]), "+f"(d[53]), "+f"(d[54]), "+f"(d[55]), "+f"(d[56]), "+f"(d[57]), "+f"(d[58]), "+f"(d[59]), "+f"(d[60]), "+f"(d[61]), "+f"(d[62]), "+f"(d[63])
        : "r"(da), "r"(db), "r"(acc), "n"(TB), "r"(ha), "r"(hb));
}
template <int TB>
__device__ __forceinline__ void wgmma_ss128_init(float (&d)[64], uint32_t da, uint32_t db, uint32_t ha = 0x40000040u, uint32_t hb = 0x40000040u) {
    asm volatile("{\n.reg .pred p;\n.reg .b64 a, b;\nsetp.ne.b32 p, 0, 0;\nmov.b64 a, {%64, %67};\nmov.b64 b, {%65, %68};\n"
        "wgmma.mma_async.sync.aligned.m64n128k16.f32.bf16.bf16 {%0, %1, %2, %3, %4, %5, %6, %7, %8, %9, %10, %11, %12, %13, %14, %15, %16, %17, %18, %19, %20, %21, %22, %23, %24, %25, %26, %27, %28, %29, %30, %31, %32, %33, %34, %35, %36, %37, %38, %39, %40, %41, %42, %43, %44, %45, %46, %47, %48, %49, %50, %51, %52, %53, %54, %55, %56, %57, %58, %59, %60, %61, %62, %63}, a, b, p, 1, 1, 0, %66;\n}"
        : "=f"(d[0]), "=f"(d[1]), "=f"(d[2]), "=f"(d[3]), "=f"(d[4]), "=f"(d[5]), "=f"(d[6]), "=f"(d[7]), "=f"(d[8]), "=f"(d[9]), "=f"(d[10]), "=f"(d[11]), "=f"(d[12]), "=f"(d[13]), "=f"(d[14]), "=f"(d[15]), "=f"(d[16]), "=f"(d[17]), "=f"(d[18]), "=f"(d[19]), "=f"(d[20]), "=f"(d[21]), "=f"(d[22]), "=f"(d[23]), "=f"(d[24]), "=f"(d[25]), "=f"(d[26]), "=f"(d[27]), "=f"(d[28]), "=f"(d[29]), "=f"(d[30]), "=f"(d[31]), "=f"(d[32]), "=f"(d[33]), "=f"(d[34]), "=f"(d[35]), "=f"(d[36]), "=f"(d[37]), "=f"(d[38]), "=f"(d[39]), "=f"(d[40]), "=f"(d[41]), "=f"(d[42]), "=f"(d[43]), "=f"(d[44]), "=f"(d[45]), "=f"(d[46]), "=f"(d[47]), "=f"(d[48]), "=f"(d[49]), "=f"(d[50]), "=f"(d[51]), "=f"(d[52]), "=f"(d[53]), "=f"(d[54]), "=f"(d[55]), "=f"(d[56]), "=f"(d[57]), "=f"(d[58]), "=f"(d[59]), "=f"(d[60]), "=f"(d[61]), "=f"(d[62]), "=f"(d[63])
        : "r"(da), "r"(db), "n"(TB), "r"(ha), "r"(hb));
}
template <int TB>
__device__ __forceinline__ void wgmma_ss64(float (&d)[32], uint32_t da, uint32_t db, int acc, uint32_t ha = 0x40000040u, uint32_t hb = 0x40000040u) {
    asm volatile("{\n.reg .pred p;\n.reg .b64 a, b;\nsetp.ne.b32 p, %34, 0;\nmov.b64 a, {%32, %36};\nmov.b64 b, {%33, %37};\n"
        "wgmma.mma_async.sync.aligned.m64n64k16.f32.bf16.bf16 {%0, %1, %2, %3, %4, %5, %6, %7, %8, %9, %10, %11, %12, %13, %14, %15, %16, %17, %18, %19, %20, %21, %22, %23, %24, %25, %26, %27, %28, %29, %30, %31}, a, b, p, 1, 1, 0, %35;\n}"
        : "+f"(d[0]), "+f"(d[1]), "+f"(d[2]), "+f"(d[3]), "+f"(d[4]), "+f"(d[5]), "+f"(d[6]), "+f"(d[7]), "+f"(d[8]), "+f"(d[9]), "+f"(d[10]), "+f"(d[11]), "+f"(d[12]), "+f"(d[13]), "+f"(d[14]), "+f"(d[15]), "+f"(d[16]), "+f"(d[17]), "+f"(d[18]), "+f"(d[19]), "+f"(d[20]), "+f"(d[21]), "+f"(d[22]), "+f"(d[23]), "+f"(d[24]), "+f"(d[25]), "+f"(d[26]), "+f"(d[27]), "+f"(d[28]), "+f"(d[29]), "+f"(d[30]), "+f"(d[31])
        : "r"(da), "r"(db), "r"(acc), "n"(TB), "r"(ha), "r"(hb));
}
template <int TB>
__device__ __forceinline__ void wgmma_ss64_init(float (&d)[32], uint32_t da, uint32_t db, uint32_t ha = 0x40000040u, uint32_t hb = 0x40000040u) {
    asm volatile("{\n.reg .pred p;\n.reg .b64 a, b;\nsetp.ne.b32 p, 0, 0;\nmov.b64 a, {%32, %35};\nmov.b64 b, {%33, %36};\n"
        "wgmma.mma_async.sync.aligned.m64n64k16.f32.bf16.bf16 {%0, %1, %2, %3, %4, %5, %6, %7, %8, %9, %10, %11, %12, %13, %14, %15, %16, %17, %18, %19, %20, %21, %22, %23, %24, %25, %26, %27, %28, %29, %30, %31}, a, b, p, 1, 1, 0, %34;\n}"
        : "=f"(d[0]), "=f"(d[1]), "=f"(d[2]), "=f"(d[3]), "=f"(d[4]), "=f"(d[5]), "=f"(d[6]), "=f"(d[7]), "=f"(d[8]), "=f"(d[9]), "=f"(d[10]), "=f"(d[11]), "=f"(d[12]), "=f"(d[13]), "=f"(d[14]), "=f"(d[15]), "=f"(d[16]), "=f"(d[17]), "=f"(d[18]), "=f"(d[19]), "=f"(d[20]), "=f"(d[21]), "=f"(d[22]), "=f"(d[23]), "=f"(d[24]), "=f"(d[25]), "=f"(d[26]), "=f"(d[27]), "=f"(d[28]), "=f"(d[29]), "=f"(d[30]), "=f"(d[31])
        : "r"(da), "r"(db), "n"(TB), "r"(ha), "r"(hb));
}
__device__ __forceinline__ void wgmma_rs128(float (&d)[64], uint32_t a0, uint32_t a1, uint32_t a2, uint32_t a3, uint32_t db, int acc, uint32_t hb = 0x40000040u) {
    asm volatile("{\n.reg .pred p;\n.reg .b64 b;\nsetp.ne.b32 p, %69, 0;\nmov.b64 b, {%68, %70};\n"
        "wgmma.mma_async.sync.aligned.m64n128k16.f32.bf16.bf16 {%0, %1, %2, %3, %4, %5, %6, %7, %8, %9, %10, %11, %12, %13, %14, %15, %16, %17, %18, %19, %20, %21, %22, %23, %24, %25, %26, %27, %28, %29, %30, %31, %32, %33, %34, %35, %36, %37, %38, %39, %40, %41, %42, %43, %44, %45, %46, %47, %48, %49, %50, %51, %52, %53, %54, %55, %56, %57, %58, %59, %60, %61, %62, %63}, {%64, %65, %66, %67}, b, p, 1, 1, 1;\n}"
        : "+f"(d[0]), "+f"(d[1]), "+f"(d[2]), "+f"(d[3]), "+f"(d[4]), "+f"(d[5]), "+f"(d[6]), "+f"(d[7]), "+f"(d[8]), "+f"(d[9]), "+f"(d[10]), "+f"(d[11]), "+f"(d[12]), "+f"(d[13]), "+f"(d[14]), "+f"(d[15]), "+f"(d[16]), "+f"(d[17]), "+f"(d[18]), "+f"(d[19]), "+f"(d[20]), "+f"(d[21]), "+f"(d[22]), "+f"(d[23]), "+f"(d[24]), "+f"(d[25]), "+f"(d[26]), "+f"(d[27]), "+f"(d[28]), "+f"(d[29]), "+f"(d[30]), "+f"(d[31]), "+f"(d[32]), "+f"(d[33]), "+f"(d[34]), "+f"(d[35]), "+f"(d[36]), "+f"(d[37]), "+f"(d[38]), "+f"(d[39]), "+f"(d[40]), "+f"(d[41]), "+f"(d[42]), "+f"(d[43]), "+f"(d[44]), "+f"(d[45]), "+f"(d[46]), "+f"(d[47]), "+f"(d[48]), "+f"(d[49]), "+f"(d[50]), "+f"(d[51]), "+f"(d[52]), "+f"(d[53]), "+f"(d[54]), "+f"(d[55]), "+f"(d[56]), "+f"(d[57]), "+f"(d[58]), "+f"(d[59]), "+f"(d[60]), "+f"(d[61]), "+f"(d[62]), "+f"(d[63])
        : "r"(a0), "r"(a1), "r"(a2), "r"(a3), "r"(db), "r"(acc), "r"(hb));
}

__device__ __forceinline__ uint32_t pack2(float lo, float hi) {
    uint32_t r;
    asm("cvt.rn.bf16x2.f32 %0, %1, %2;" : "=r"(r) : "f"(hi), "f"(lo));
    return r;
}
__device__ __forceinline__ float bf_lo(uint32_t v) { return __uint_as_float(v << 16); }
__device__ __forceinline__ float bf_hi(uint32_t v) { return __uint_as_float(v & 0xffff0000u); }
__device__ __forceinline__ float rbf(float v) { return bf_lo(pack2(v, v)); }
__device__ __forceinline__ uint32_t badd(uint32_t a, uint32_t b) {
    uint32_t r;
    asm("add.rn.bf16x2 %0, %1, %2;" : "=r"(r) : "r"(a), "r"(b));
    return r;
}
__device__ __forceinline__ uint32_t bsub(uint32_t a, uint32_t b) {
    uint32_t r;
    asm("sub.rn.bf16x2 %0, %1, %2;" : "=r"(r) : "r"(a), "r"(b));
    return r;
}
__device__ __forceinline__ uint32_t bmul(uint32_t a, uint32_t b) {
    uint32_t r;
    asm("mul.rn.bf16x2 %0, %1, %2;" : "=r"(r) : "r"(a), "r"(b));
    return r;
}
__device__ __forceinline__ uint32_t ln_apply(uint32_t x, uint32_t mb, float rs, uint32_t scale, uint32_t shift) {
    const uint32_t d = bsub(x, mb);
    return badd(bmul(pack2(bf_lo(d) * rs, bf_hi(d) * rs), scale), shift);
}
__device__ __forceinline__ float ex2(float v) {
    float r;
    asm("ex2.approx.ftz.f32 %0, %1;" : "=f"(r) : "f"(v));
    return r;
}
__device__ __forceinline__ float rcp(float v) {
    float r;
    asm("rcp.approx.ftz.f32 %0, %1;" : "=f"(r) : "f"(v));
    return r;
}
__device__ __forceinline__ float sqrt_fast(float v) {
    float r;
    asm("sqrt.approx.ftz.f32 %0, %1;" : "=f"(r) : "f"(v));
    return r;
}
__device__ __forceinline__ float ln_rstd(float var) { return rcp(rbf(sqrt_fast(rbf(rbf(var) + 1e-5f)))); }
__device__ __forceinline__ float sigmoid(float v) { return rcp(1.f + ex2(-1.4426950408889634f * v)); }
__device__ __forceinline__ float quad_sum(float v) {
    v += __shfl_xor_sync(0xffffffffu, v, 1);
    return v + __shfl_xor_sync(0xffffffffu, v, 2);
}

constexpr uint32_t HI_128 = 0x40000040u, HI_IMG = 0x80000080u, HI_Q = 0x80000040u;
template <int M, int RH>
__device__ __forceinline__ uint4 img_pack(const float (&d)[64], float s) {
    uint4 v;
    v.x = pack2(d[16 * M + 2 * RH] * s, d[16 * M + 2 * RH + 1] * s);
    v.y = pack2(d[16 * M + 4 + 2 * RH] * s, d[16 * M + 5 + 2 * RH] * s);
    v.z = pack2(d[16 * M + 8 + 2 * RH] * s, d[16 * M + 9 + 2 * RH] * s);
    v.w = pack2(d[16 * M + 12 + 2 * RH] * s, d[16 * M + 13 + 2 * RH] * s);
    return v;
}
template <int M>
__device__ __forceinline__ void img_store_global(uint8_t* img, uint32_t toff, const float (&d)[64], float s0, float s1) {
    uint4* p = reinterpret_cast<uint4*>(img + toff) + M * 32;
    p[0] = img_pack<M, 0>(d, s0);
    p[128] = img_pack<M, 1>(d, s1);
}
__device__ __forceinline__ void sts128(uint32_t a, uint4 v) {
    asm volatile("st.shared.v4.b32 [%0], {%1, %2, %3, %4};" ::"r"(a), "r"(v.x), "r"(v.y), "r"(v.z), "r"(v.w) : "memory");
}
constexpr float SM_C = 0.08838834764831845f * 1.4426950408889634f;
__device__ __forceinline__ float pack2f(float lo, float hi) {
    float r;
    asm("{\n.reg .b32 t;\ncvt.rn.bf16x2.f32 t, %1, %2;\nmov.b32 %0, t;\n}" : "=f"(r) : "f"(hi), "f"(lo));
    return r;
}
template <int M, bool SCALE, bool PARK>
__device__ __forceinline__ void pack_group(float (&d)[64], float (&v)[8], float s0, float s1) {
#pragma unroll
    for (int i = 0; i < 8; i++) {
        const int k = 16 * M + 4 * (i & 3) + 2 * (i >> 2);
        v[i] = SCALE ? pack2f(d[k] * (i < 4 ? s0 : s1), d[k + 1] * (i < 4 ? s0 : s1)) : pack2f(d[k], d[k + 1]);
        if (PARK && M > 0) d[16 * (M > 0 ? M - 1 : 0) + i] = v[i];
    }
}
__device__ __forceinline__ uint32_t q_off(uint32_t toff) { return (((toff >> 1) & ~2047u) ^ 8192) + (toff & 511); }
template <int M, bool PARK>
__device__ __forceinline__ void ctx_store_part(float4* p, float (&d)[64], float i0, float i1) {
    float v[8];
    pack_group<M, true, PARK>(d, v, i0, i1);
    p[M * 32] = make_float4(v[0], v[1], v[2], v[3]);
    p[M * 32 + 128] = make_float4(v[4], v[5], v[6], v[7]);
}
template <bool PARK>
__device__ __forceinline__ void ctx_store(uint8_t* img, uint32_t toff, float (&o)[64], float l0, float l1) {
    const float i0 = rcp(quad_sum(l0)), i1 = rcp(quad_sum(l1));
    float4* p = reinterpret_cast<float4*>(img + toff);
    ctx_store_part<0, PARK>(p, o, i0, i1); ctx_store_part<1, PARK>(p, o, i0, i1); ctx_store_part<2, PARK>(p, o, i0, i1); ctx_store_part<3, PARK>(p, o, i0, i1);
}

template <int M>
__device__ __forceinline__ void tile_store_part(float4* p, uint32_t a, float (&d)[64], float i0, float i1, int ctx) {
    float v[8];
    pack_group<M, true, true>(d, v, i0, i1);
#pragma unroll
    for (int h = 0; h < 2; h++)
        asm volatile("{\n.reg .pred p;\nsetp.ne.s32 p, %6, 0;\n@p st.global.v4.f32 [%0], {%2, %3, %4, %5};\n@!p st.shared.v4.f32 [%1], {%2, %3, %4, %5};\n}"
                     ::"l"(p + M * 32 + h * 128), "r"(a + (M >> 1) * 16384 + (M & 1) * 512 + h * 1024),
                     "f"(v[4 * h]), "f"(v[4 * h + 1]), "f"(v[4 * h + 2]), "f"(v[4 * h + 3]), "r"(ctx) : "memory");
}
__device__ __forceinline__ void tile_store(uint8_t* img, uint32_t a, uint32_t toff, float (&d)[64], float i0, float i1, int ctx) {
    float4* p = reinterpret_cast<float4*>(img + toff);
    a += q_off(toff);
    tile_store_part<0>(p, a, d, i0, i1, ctx); tile_store_part<1>(p, a, d, i0, i1, ctx);
    tile_store_part<2>(p, a, d, i0, i1, ctx); tile_store_part<3>(p, a, d, i0, i1, ctx);
}

__device__ __forceinline__ void slot_wait(uint32_t bars, uint32_t& ph, uint32_t slot) {
    mbar_wait(bars + 8 * slot, (ph >> slot) & 1);
    ph ^= 1u << slot;
}
__device__ __forceinline__ void release_if(uint32_t eb, uint32_t slot, bool on) {
    asm volatile("{\n.reg .pred p;\nsetp.ne.s32 p, %1, 0;\n@p mbarrier.arrive.shared::cluster.b64 _, [%0];\n}" ::"r"(eb + 8 * slot), "r"((int)on) : "memory");
}
__device__ __forceinline__ void slot_acquire(uint32_t sb, uint32_t& ph, uint32_t slot) {
    slot_wait(sb + BAR_EMPTY, ph, slot);
    asm volatile("{\n.reg .pred p;\nelect.sync _|p, 0xffffffff;\n@p mbarrier.arrive.expect_tx.shared::cta.b64 _, [%0], 32768;\n}"
                 ::"r"(sb + BAR_FULL + 8 * slot) : "memory");
}
__device__ __forceinline__ void load_bulk(uint32_t sb, uint32_t slot, uint32_t off, const void* src, uint32_t bytes, bool both, bool first) {
    if (both)
        asm volatile("{\n.reg .pred p;\nelect.sync _|p, 0xffffffff;\n"
                     "@p cp.async.bulk.shared::cluster.global.mbarrier::complete_tx::bytes.multicast::cluster.L2::cache_hint [%0], [%1], %5, [%2], %4, %3;\n}"
                     ::"r"(sb + slot * SLOT + off), "l"(src), "r"(sb + BAR_FULL + 8 * slot), "l"(first ? L2_FIRST : L2_NORMAL), "h"((uint16_t)3),
                     "r"(bytes) : "memory");
    else
        asm volatile("{\n.reg .pred p;\nelect.sync _|p, 0xffffffff;\n"
                     "@p cp.async.bulk.shared::cluster.global.mbarrier::complete_tx::bytes.L2::cache_hint [%0], [%1], %4, [%2], %3;\n}"
                     ::"r"(sb + slot * SLOT + off), "l"(src), "r"(sb + BAR_FULL + 8 * slot), "l"(first ? L2_FIRST : L2_NORMAL), "r"(bytes) : "memory");
}
__device__ __forceinline__ void load_tile(uint32_t sb, uint32_t slot, uint32_t off, const CUtensorMap* m, int row, int cb, bool both, bool first) {
    if (both)
        asm volatile("{\n.reg .pred p;\nelect.sync _|p, 0xffffffff;\n"
                     "@p cp.async.bulk.tensor.3d.shared::cluster.global.mbarrier::complete_tx::bytes.multicast::cluster.L2::cache_hint [%0], [%1, {%3, %4, %5}], [%2], %7, %6;\n}"
                     ::"r"(sb + slot * SLOT + off), "l"(m), "r"(sb + BAR_FULL + 8 * slot), "r"(0), "r"(row), "r"(cb),
                     "l"(first ? L2_FIRST : L2_NORMAL), "h"((uint16_t)3) : "memory");
    else
        asm volatile("{\n.reg .pred p;\nelect.sync _|p, 0xffffffff;\n"
                     "@p cp.async.bulk.tensor.3d.shared::cluster.global.mbarrier::complete_tx::bytes.L2::cache_hint [%0], [%1, {%3, %4, %5}], [%2], %6;\n}"
                     ::"r"(sb + slot * SLOT + off), "l"(m), "r"(sb + BAR_FULL + 8 * slot), "r"(0), "r"(row), "r"(cb),
                     "l"(first ? L2_FIRST : L2_NORMAL) : "memory");
}
__device__ __forceinline__ uint32_t ring_next(uint32_t r) { return r == 4 ? 0 : r + 1; }
__device__ __forceinline__ uint32_t w_table(int hp) { return hp ? 0x3104u : 0x4210u; }
__device__ __forceinline__ uint32_t a_table(int hp) { return hp ? 0x625u : 0x635u; }
__device__ __forceinline__ uint32_t a_next(uint32_t& t) {
    const uint32_t s = t & 15;
    t = (t >> 4) | (s << 8);
    return s;
}
constexpr uint32_t O_TABLE = 0x1604235u;
__device__ __forceinline__ uint32_t o_next(uint32_t& t) {
    const uint32_t s = t & 15;
    t = (t >> 4) | (s << 24);
    return s;
}
__device__ __forceinline__ int o_head(int i, int kh) { return i < 16 ? 4 * (i & 7) + 2 * (kh ^ 1) + (i >> 3) : 29 + 2 * kh; }

template <bool INIT>
__device__ __forceinline__ void gemm_issue(float (&d)[64], uint32_t a, uint32_t b, int acc, bool img) {
    const uint32_t ha = img ? HI_IMG : HI_128, o2 = img ? 32 : 4, o4 = img ? 64 : 1024;
    wg_fence();
#pragma unroll
    for (int k = 0; k < 8; k++) {
        if (INIT && k == 0) wgmma_ss128_init<1>(d, a, b, ha);
        else wgmma_ss128<1>(d, a + (k >> 2) * o4 + ((k >> 1) & 1) * o2 + (k & 1) * 2, b + k * 128, k ? 1 : acc, ha);
    }
    wg_commit();
}

template <bool ODD>
__device__ __forceinline__ bool proj_tile(float (&acc)[64], float (&prev)[64], int t, int q0, uint32_t sb, int wg, uint32_t eb, bool rel, uint32_t& fph,
                                          uint32_t wtab, uint32_t& atab, uint8_t* prev_img, uint32_t toff, float s0, float s1, bool first,
                                          const bf16* x, int xrow, uint32_t (&v)[32]) {
    const uint32_t a0 = desc_k(sb + (wg ^ (ODD && t == 5)) * 8192), b0 = desc_mn(sb);
    const int lane = threadIdx.x & 31;
    constexpr int U = ODD ? UNR : 1;
#pragma unroll U
    for (int q = ODD ? 0 : q0; q < 4; q++) {
        const uint32_t ws = (wtab >> (4 * q)) & 15, as = a_next(atab);
        if (!ODD && t != 2) slot_wait(sb + BAR_FULL, fph, ws);
        slot_wait(sb + BAR_FULL, fph, as);
        if (ODD && q == 2 && t == 5) {
#pragma unroll
            for (int i = 0; i < 8; i++) sts128(sb + 5 * SLOT + q_off(toff) + (i >> 2) * 16384 + (i & 2) * 256 + (i & 1) * 1024, make_uint4(v[4 * i], v[4 * i + 1], v[4 * i + 2], v[4 * i + 3]));
        }
        bar_sync(1 + wg, 256);
        gemm_issue<false>(acc, a0 + as * (SLOT / 16), b0 + ws * (SLOT / 16), q, false);
        bar_arrive(2 - wg, 256);
        wg_wait<1>();
        reg_fence(prev);
        if (ODD && t == 5) {
            if (q == 0) {
#pragma unroll
                for (int i = 0; i < 32; i++) {
                    const int k = 16 * (i >> 3) + 4 * (i & 3) + ((i >> 1) & 2);
                    v[i] = pack2(prev[k], prev[k + 1]);
                }
            }
            if (q == 2) {
                fence_async_smem();
                slot_wait(sb + BAR_FULL, fph, wtab & 15);
                wg_wait<0>();
                release_if(eb, as, rel);
                release_if(eb, ws, rel);
                reg_fence(acc);
                return true;
            }
        } else {
            if (first) {
                const uint4* xp = reinterpret_cast<const uint4*>(x) + xrow * 64;
                if (!ODD) {
                    if (q == XQ && lane < 16) asm volatile("prefetch.global.L1 [%0];" ::"l"(xp + lane * 8) : "memory");
                    if (q == 3) {
#pragma unroll
                        for (int i = 0; i < 4; i++) {
                            const uint4 u = __ldg(xp + lane + 32 * i);
                            v[4 * i] = u.x; v[4 * i + 1] = u.y; v[4 * i + 2] = u.z; v[4 * i + 3] = u.w;
                        }
                        v[16] = __ldg(&xp[0].x) << 16;
                        v[17] = __ldg(&xp[64].x) << 16;
                        float st[4] = {0.f, 0.f, 0.f, 0.f};
#pragma unroll
                        for (int k = 0; k < 16; k++) {
                            const float d0 = bf_lo(v[k]) - __uint_as_float(v[16 + (k >> 3)]), d1 = bf_hi(v[k]) - __uint_as_float(v[16 + (k >> 3)]);
                            st[k >> 3] += d0 + d1;
                            st[2 + (k >> 3)] = fmaf(d0, d0, fmaf(d1, d1, st[2 + (k >> 3)]));
                        }
#pragma unroll
                        for (int i = 0; i < 4; i++) v[20 + i] = __float_as_uint(st[i]);
                    }
                } else if (q == 0) {
#pragma unroll
                    for (int i = 0; i < 20; i++)
                        v[20 + (i & 3)] = __float_as_uint(__uint_as_float(v[20 + (i & 3)]) + __uint_as_float(__shfl_xor_sync(0xffffffffu, v[20 + (i & 3)], 1 << (i >> 2))));
                } else if (q == 1) {
#pragma unroll
                    for (int i = 0; i < 2; i++) {
                        const float d = __uint_as_float(v[20 + i]) * (1.f / 512.f);
                        const float rs = ln_rstd(fmaxf(fmaf(-d, d, __uint_as_float(v[22 + i]) * (1.f / 512.f)), 0.f));
                        const uint32_t mb = pack2(__uint_as_float(v[16 + i]) + d, __uint_as_float(v[16 + i]) + d);
#pragma unroll
                        for (int k = 8 * i; k < 8 * i + 8; k++) {
                            const uint32_t y = bsub(v[k], mb);
                            v[k] = pack2(bf_lo(y) * rs, bf_hi(y) * rs);
                        }
                    }
                } else {
                    mbar_wait(sb + BAR_FLAG + 8 * 8, 0);
                    const uint4 a = lds128(sb + SM_TAB + q * 512 + lane * 16), c = lds128(sb + SM_TAB - 1024 + q * 512 + lane * 16);
                    uint8_t* p = g_h + ((xrow >> 7) * 8 + (q & 1) * 4 + (lane >> 3)) * 16384 + (xrow & 127) * 128;
#pragma unroll
                    for (int i = 0; i < 2; i++) {
                        *reinterpret_cast<uint4*>(p + i * 128 + (((lane ^ xrow ^ i) & 7) << 4)) =
                            make_uint4(badd(bmul(v[8 * i], a.x), c.x), badd(bmul(v[8 * i + 1], a.y), c.y),
                                       badd(bmul(v[8 * i + 2], a.z), c.z), badd(bmul(v[8 * i + 3], a.w), c.w));
#pragma unroll
                        for (int k = 0; k < 4; k++) v[8 * i + k] = v[8 * i + 4 + k];
                    }
                    __syncwarp();
                    mbar_arrive_if(sb + BAR_DONE, lane == 0 && q == 3);
                }
            }
            if (ODD || !first) {
                if (q == 0) img_store_global<0>(prev_img, toff, prev, s0, s1);
                if (q == 1) img_store_global<1>(prev_img, toff, prev, s0, s1);
                if (q == 2) img_store_global<2>(prev_img, toff, prev, s0, s1);
                if (q == 3) img_store_global<3>(prev_img, toff, prev, s0, s1);
            }
        }
        wg_wait<0>();
        release_if(eb, as, rel && !(ODD && (q & 1) && t == 5));
        if (ODD) release_if(eb, ws, rel && t != 1);
    }
    reg_fence(acc);
    return false;
}

__device__ __forceinline__ void qk_issue(float (&s)[64], uint32_t q, uint32_t k) {
    wg_fence();
    wgmma_ss128_init<0>(s, q, k, HI_Q, HI_IMG);
#pragma unroll
    for (int i = 1; i < 8; i++) wgmma_ss128<0>(s, q + (i >> 2) * 1024 + (i & 2) * 16 + (i & 1) * 2, k + (i >> 1) * 32 + (i & 1) * 2, 1, HI_Q, HI_IMG);
    wg_commit();
}
__device__ __forceinline__ void qk_issue(float (&s)[32], uint32_t q, uint32_t k) {
    wg_fence();
    wgmma_ss64_init<0>(s, q, k, HI_Q, HI_IMG);
#pragma unroll
    for (int i = 1; i < 8; i++) wgmma_ss64<0>(s, q + (i >> 2) * 1024 + (i & 2) * 16 + (i & 1) * 2, k + (i >> 1) * 32 + (i & 1) * 2, 1, HI_Q, HI_IMG);
    wg_commit();
}
__device__ __forceinline__ void pv_issue(float (&o)[64], const uint32_t (&p)[32], uint32_t v, int acc, bool half) {
    if (half) {
        asm volatile("// half" ::: "memory");
        wg_fence();
#pragma unroll
        for (int i = 0; i < 4; i++) wgmma_rs128(o, p[4 * i], p[4 * i + 1], p[4 * i + 2], p[4 * i + 3], v + i * 256, i ? 1 : acc, HI_IMG);
        wg_commit();
        asm volatile("// half" ::: "memory");
    } else {
        wg_fence();
#pragma unroll
        for (int i = 0; i < 8; i++) wgmma_rs128(o, p[4 * i], p[4 * i + 1], p[4 * i + 2], p[4 * i + 3], v + i * 256, i ? 1 : acc, HI_IMG);
        wg_commit();
    }
}
__device__ __forceinline__ void tri_mask(float (&s)[64], float x) {
#pragma unroll
    for (int k = 0; k < 16; k++) {
        float b;
        asm("sub.sat.f32 %0, %1, %2;" : "=f"(b) : "f"((float)(8 * (k >> 1) + (k & 1))), "f"(x));
        const int i = 32 + 4 * (k >> 1) + (k & 1);
        asm("fma.rn.f32 %0, %1, 0fFF61B1E6, %0;" : "+f"(s[i]) : "f"(b));
        if (k < 14) asm("fma.rn.f32 %0, %1, 0fFF61B1E6, %0;" : "+f"(s[i + 6]) : "f"(b));
    }
}
__device__ __forceinline__ void tri_mask_copy(float (&s)[64], const float (&h)[32], float x) {
#pragma unroll
    for (int i = 0; i < 32; i++) {
        asm("{\n.reg .pred p;\nsetp.lt.f32 p, %2, %3;\nselp.f32 %0, 0fFF800000, %1, p;\n}"
            : "=f"(s[i]) : "f"(h[i]), "f"(x), "f"((float)(8 * (i >> 2) - 4 * (i & 2) + (i & 1))));
        s[32 + i] = __uint_as_float(0xff800000u);
    }
}
constexpr float SM_HI = 1152921504606846976.f, SM_LO = 1.f / 1152921504606846976.f;
__device__ __forceinline__ bool softmax_unsafe(float t0, float t1, bool first) {
    bool bad = __any_sync(0xffffffffu, fmaxf(t0, t1) > SM_HI);
    if (first) {
        uint32_t a = __ballot_sync(0xffffffffu, t0 >= SM_LO), b = __ballot_sync(0xffffffffu, t1 >= SM_LO);
        a |= a >> 1;
        b |= b >> 1;
        bad |= ((a | (a >> 2)) & (b | (b >> 2)) & 0x11111111u) != 0x11111111u;
    }
    return bad;
}
__device__ __forceinline__ void softmax_shift(float (&s)[64], float d0, float d1) {
#pragma unroll
    for (int i = 0; i < 64; i++) s[i] -= (i & 2) ? d1 : d0;
}
__device__ __forceinline__ void softmax_remax(float (&s)[64], float (&m)[2], bool first, float& a0, float& a1) {
    float m0 = fmaxf(s[0], s[1]), m1 = fmaxf(s[2], s[3]);
#pragma unroll
    for (int k = 1; k < 16; k++) {
        m0 = fmaxf(m0, fmaxf(s[4 * k], s[4 * k + 1]));
        m1 = fmaxf(m1, fmaxf(s[4 * k + 2], s[4 * k + 3]));
    }
    m0 = fmaxf(m0, __shfl_xor_sync(0xffffffffu, m0, 1));
    m1 = fmaxf(m1, __shfl_xor_sync(0xffffffffu, m1, 1));
    m0 = fmaxf(m0, __shfl_xor_sync(0xffffffffu, m0, 2));
    m1 = fmaxf(m1, __shfl_xor_sync(0xffffffffu, m1, 2));
    if (!first) {
        m0 = fmaxf(m0, 0.f);
        m1 = fmaxf(m1, 0.f);
    }
    a0 = first ? 1.f : ex2(-m0);
    a1 = first ? 1.f : ex2(-m1);
    m[0] += m0;
    m[1] += m1;
    softmax_shift(s, m0, m1);
}
template <int J0, int J1>
__device__ __forceinline__ void softmax_exp(const float (&s)[64], uint32_t (&p)[32], float (&t)[4]) {
#pragma unroll
    for (int k = J0; k < J1; k++) {
        const float e0 = ex2(s[4 * k]), e1 = ex2(s[4 * k + 1]), e2 = ex2(s[4 * k + 2]), e3 = ex2(s[4 * k + 3]);
        if (k == 0) { t[0] = e0; t[1] = e1; t[2] = e2; t[3] = e3; }
        else { t[0] += e0; t[1] += e1; t[2] += e2; t[3] += e3; }
        p[2 * k] = pack2(e0, e1);
        p[2 * k + 1] = pack2(e2, e3);
    }
}
__device__ __forceinline__ void fma8(float (&acc)[8], float a, uint4 w) {
    acc[0] = fmaf(a, bf_lo(w.x), acc[0]); acc[1] = fmaf(a, bf_hi(w.x), acc[1]);
    acc[2] = fmaf(a, bf_lo(w.y), acc[2]); acc[3] = fmaf(a, bf_hi(w.y), acc[3]);
    acc[4] = fmaf(a, bf_lo(w.z), acc[4]); acc[5] = fmaf(a, bf_hi(w.z), acc[5]);
    acc[6] = fmaf(a, bf_lo(w.w), acc[6]); acc[7] = fmaf(a, bf_hi(w.w), acc[7]);
}
__device__ __forceinline__ void mma16816(float (&d)[4], const uint32_t* a, uint32_t b0, uint32_t b1) {
    asm("mma.sync.aligned.m16n8k16.row.col.f32.bf16.bf16.f32 {%0, %1, %2, %3}, {%4, %5, %6, %7}, {%8, %9}, {%0, %1, %2, %3};"
        : "+f"(d[0]), "+f"(d[1]), "+f"(d[2]), "+f"(d[3]) : "r"(a[0]), "r"(a[1]), "r"(a[2]), "r"(a[3]), "r"(b0), "r"(b1));
}
__device__ __forceinline__ uint32_t best_key(const uint32_t* keys, int lane, uint32_t ep) {
    uint32_t best;
#pragma unroll 1
    for (;;) {
        const uint4 k = ld_poll(reinterpret_cast<const uint4*>(keys) + lane);
        best = max(max(k.x, k.y), max(k.z, k.w));
        if (__all_sync(0xffffffffu, (((k.x ^ ep) | (k.y ^ ep) | (k.z ^ ep) | (k.w ^ ep)) & 31) == 0)) break;
    }
    return __reduce_max_sync(0xffffffffu, best);
}

__global__ void __cluster_dims__(2, 1, 1) __launch_bounds__(384, 1)
fused_kernel(const __grid_constant__ CUtensorMap tm_ckv, const __grid_constant__ CUtensorMap tm_wq,
             const __grid_constant__ CUtensorMap tm_wuk, const __grid_constant__ CUtensorMap tm_wuv,
             const __grid_constant__ CUtensorMap tm_wo, const __grid_constant__ CUtensorMap tm_wg,
             const __grid_constant__ CUtensorMap tm_wu,
             const __grid_constant__ CUtensorMap tm_wm, const __grid_constant__ CUtensorMap tm_x, const Params P) {
    extern __shared__ __align__(1024) uint8_t smem[];
    const uint32_t sb = (uint32_t)__cvta_generic_to_shared(smem);
    const int tid = threadIdx.x, lane = tid & 31, warp = __shfl_sync(0xffffffffu, tid >> 5, 0), wg = warp >> 2;
    const uint32_t sm = blockIdx.x < 8 ? blockIdx.x + 124 : blockIdx.x - 8, smq = ((sm - 64) * 147) >> 11;
    const int rb = sm < 64 ? (sm & 14) * 8 + (sm >> 4) * 2 + (sm & 1)
                 : sm < 120 ? ((sm - 64 - smq * 14) & 14) * 8 + 24 + smq * 2 + (sm & 1) : sm < 124 ? sm + 8 : sm - 116;
    const int grp = rb >> 3, j = rb & 7, cq = j & 3, kh = grp & 1, ort = (grp & 14) + (j >> 2);
    if (warp == 0) TS(0);

    if (lane == 0) {
        if (warp == 8) {
            asm volatile("prefetch.tensormap [%0];" ::"l"(rb >= NCTA ? &tm_wm : (j & 1) ? &tm_wuv : &tm_wuk) : "memory");
            asm volatile("prefetch.tensormap [%0];" ::"l"(&tm_ckv) : "memory");
            *reinterpret_cast<uint2*>(smem + SM_EP + 16) = make_uint2(0, 0);
        }
        const u64 cnt = (warp < 5 ? (rb < NCTA ? 0x844444441111111ull : 0x888888881111111ull) : warp < 10 ? 0x111111188888888ull : 0x118121ull) >> (12 * (warp % 5));
#pragma unroll
        for (int i = 0; i < 3; i++) mbar_init(sb + SM_BAR + 24 * warp + 8 * i, ((uint32_t)cnt >> (4 * i)) & 15);
        fence_async_smem();
        asm volatile("fence.mbarrier_init.release.cluster;" ::: "memory");
    }
    __syncthreads();
    asm volatile("barrier.cluster.arrive.relaxed.aligned;\nbarrier.cluster.wait.aligned;" ::: "memory");

    if (rb >= NCTA) {
        float* sc = reinterpret_cast<float*>(smem + 6 * SLOT);
        float* red = sc + 512;
        uint32_t ph = 0x7f, sl = 0;
        if (warp == 8) {
#pragma unroll 1
            for (int i = 0; i < 24; i++) {
                slot_acquire(sb, ph, sl);
                tma2d(sb + sl * SLOT, &tm_wm, (i >> 3) * 1024 + (rb - NCTA) * 256, (i & 7) * 64, sb + BAR_FULL + 8 * sl);
                if (++sl == 6) sl = 0;
            }
#pragma unroll 1
            for (int i = 0; i <= NFFN / NSPARE; i++) {
                const int b = (rb - NCTA) * (NFFN / NSPARE) + i;
                if (i < NFFN / NSPARE) {
                    asm volatile("cp.async.bulk.wait_group.read 0;" ::: "memory");
                    uint32_t done = 0x7f;
                    slot_acquire(sb, done, i & 1);
#pragma unroll 1
                    for (int k = 0; k < 4; k++) tma2d(sb + (i & 1) * SLOT + k * 8192, k < 2 ? &tm_wg : &tm_wu, b * 16, (k & 1) * 256, sb + BAR_FULL + 8 * (i & 1));
                }
                if (i) {
                    mbar_wait(sb + BAR_FULL + 8 * (~i & 1), ((i - 1) >> 1) & 1);
                    bulk_store(g_wf + (b - 1) * SLOT, sb + (~i & 1) * SLOT, SLOT);
                    asm volatile("cp.async.bulk.commit_group;" ::: "memory");
                }
            }
            asm volatile("cp.async.bulk.wait_group 0;" ::: "memory");
            fence_async_global();
            TS(4);
        } else if (warp < 8) {
            const uint32_t c2 = __ldg(reinterpret_cast<const uint32_t*>(P.c) + tid), ep = __ldcg(&g_sync.epoch[0]) + 1;
            sc[2 * tid] = rbf(bf_lo(c2) * sigmoid(bf_lo(c2)));
            sc[2 * tid + 1] = rbf(bf_hi(c2) * sigmoid(bf_hi(c2)));
            ph = 0;
#pragma unroll 1
            for (int ps = 0; ps < 3; ps++) {
                bar_sync(1, 256);
                float acc[8] = {0.f, 0.f, 0.f, 0.f, 0.f, 0.f, 0.f, 0.f};
#pragma unroll 1
                for (int bt = 0; bt < 8; bt++) {
                    slot_wait(sb + BAR_FULL, ph, sl);
#pragma unroll 4
                    for (int i = 0; i < 8; i++)
                        fma8(acc, sc[bt * 64 + warp * 8 + i], *reinterpret_cast<const uint4*>(smem + sl * SLOT + (warp * 8 + i) * 512 + lane * 16));
                    __syncwarp();
                    mbar_arrive_if(sb + BAR_EMPTY + 8 * sl, lane == 0);
                    if (++sl == 6) sl = 0;
                }
                *reinterpret_cast<float4*>(red + warp * 256 + lane * 8) = make_float4(acc[0], acc[1], acc[2], acc[3]);
                *reinterpret_cast<float4*>(red + warp * 256 + lane * 8 + 4) = make_float4(acc[4], acc[5], acc[6], acc[7]);
                bar_sync(1, 256);
                float v = 0.f;
#pragma unroll
                for (int i = 0; i < 8; i++) v += red[i * 256 + tid];
                if (ps == 0) st_pub(g_mod1 + (rb - NCTA) * 256 + tid, (pack2(0.f, v) & 0xffff0000u) | (ep & 0xffffu), true);
                else g_mod[ps * 1024 + (rb - NCTA) * 256 + tid] = __float2bfloat16_rn(v);
                if (warp == 0) TS(1 + ps);
            }
        }
        __syncthreads();
        if (tid < 2) flag_add(&g_sync.cnt[7 * 8]);
        return;
    }

    if (wg == 2) {
        asm volatile("setmaxnreg.dec.sync.aligned.u32 40;");
        const CUtensorMap* tw = (j & 1) ? &tm_wuv : &tm_wuk;
        if (warp == 8) {
            const uint32_t rank = j & 1, half = rank * 16384;
            uint32_t eph = 0x7f, r = 0;
#pragma unroll 1
            for (int hp = 0; hp < 2; hp++) {
                uint32_t wtab = w_table(hp), atab = a_table(hp);
                const int hc = 4 * grp + 2 * hp;
#pragma unroll 1
                for (int u = 0; u < 16; u++) {
                    if (u < 4) {
                        const uint32_t ws = (wtab >> (4 * u)) & 15;
                        slot_acquire(sb, eph, ws);
                        load_tile(sb, ws, 0, tw, u * 128, hc, false, HINT & 1);
                        PT();
                    }
                    if (hp == 1 && (u & 7) == 4) mbar_wait(sb + BAR_FLAG + 24 + (u & 8), 0);
                    const uint32_t as = a_next(atab);
                    slot_acquire(sb, eph, as);
                    load_tile(sb, as, half, &tm_ckv, ((u & 12) + (j >> 1)) * 128, (u & 3) * 2 + rank, true, (HINT & 8) && hp);
                    PT();
                    if (hp == 1 && (u | 2) == 3 && lane == 0)
                        asm volatile("red.relaxed.gpu.global.add.u32 [%0], 1;" ::"l"(&g_sync.cnt[(grp * 8 + 3 + (u >> 1)) * 8]) : "memory");
                }
                const uint8_t* src = g_h + (15 - j) * 4 * SLOT;
#pragma unroll 1
                for (int u = 0; u < 8; u++) {
                    if ((u & 3) == 0) {
                        mbar_wait(sb + BAR_FLAG + (2 + 8 * hp) * u, 0);
                        fence_async_global();
                    }
                    if (u < 4) {
                        const uint32_t ws = (wtab >> (4 * u)) & 15;
                        slot_acquire(sb, eph, ws);
                        load_tile(sb, ws, half, &tm_wq, u * 128, hc + rank, true, HINT & 1);
                        PT();
                    }
                    const uint32_t as = a_next(atab);
                    slot_acquire(sb, eph, as);
                    load_bulk(sb, as, 0, src, SLOT, false, (HINT & 8) && hp);
                    PT();
                    src += u == 3 ? (8 * j - 63) * SLOT : SLOT;
                }
                const int step = hp ? -2 * SLOT : 2 * SLOT;
                src = g_KV + (size_t)(grp * 32 + 30 * hp) * SLOT + half - step;
#pragma unroll 1
                for (int n = 0; n <= 17; n++) {
                    if (n == 8) {
                        mbar_wait(sb + BAR_FLAG + 16 + 32 * hp, 0);
                        fence_async_global();
                    }
                    const uint8_t* v = src + SLOT;
                    src += n < 16 - j ? step : n == 16 - j ? (2 * j - 15) * step : -step;
                    if (n < 17) {
                        slot_acquire(sb, eph, r);
                        if (n != 15 - (j & 6)) load_bulk(sb, r, half, src, SLOT / 2, true, HINT & 4);
                        else load_bulk(sb, r, 0, src - half, SLOT, false, HINT & 4);
                        PT();
                        r = ring_next(r);
                    }
                    if (n) {
                        slot_acquire(sb, eph, r);
                        if (n != 16 - (j & 6)) load_bulk(sb, r, half, v, SLOT / 2, true, HINT & 4);
                        else load_bulk(sb, r, 0, v - half, SLOT, false, HINT & 4);
                        PT();
                        r = ring_next(r);
                    }
                    asm volatile("st.volatile.shared.u32 [%0], %1;" ::"r"(sb + SM_EP + 16), "r"(18 * hp + n + 1) : "memory");
                }
            }
            uint32_t otab = O_TABLE, ready = 0;
#pragma unroll 1
            for (int i = 0; i < 17; i++) {
                const bool dyn = i >= 8 && i < 15;
                const uint32_t want = dyn ? 15u << (4 * (i - 8)) : 1u << max(i + 14, 28);
                if (!(ready & want)) {
                    do {
                        asm volatile("ld.acquire.cta.shared.u32 %0, [%1];" : "=r"(ready) : "r"(sb + SM_EP + 20) : "memory");
                        ready = __shfl_sync(0xffffffffu, ready, 0);
                    } while (!(ready & want));
                    fence_async_global();
                }
                const int head = o_head(dyn ? (ready >> (4 * (i - 8))) & 15 : i, kh);
                const uint32_t as = o_next(otab), ws = o_next(otab), off = i < 15 ? half : kh * 16384;
                slot_acquire(sb, eph, as);
                load_bulk(sb, as, off, g_ctx + (size_t)(ort * 32 + head) * SLOT + off, SLOT / 2, i < 15, HINT & 16);
                if (i == 15) load_tile(sb, as, off ^ 16384, &tm_x, ort * 128 + kh * 64, cq * 2, false, false);
                if (i == 16) load_bulk(sb, as, off ^ 16384, P.wdown + min(rb, NFFN - 1) * 8192, SLOT / 2, false, false);
                PT();
                slot_acquire(sb, eph, ws);
                load_tile(sb, ws, 0, &tm_wo, head * 128, cq * 2, false, HINT & 2);
                PT();
                if (i == 0) o_next(otab);
            }
            if (rb < NFFN) {
                slot_acquire(sb, eph, 5);
                load_bulk(sb, 5, 0, g_wf + rb * SLOT, SLOT, false, false);
            }
        } else if (warp == 9) {
            l2_prefetch(P.ckv + rb * 2048, 4096);
            mbar_watch(sb + BAR_FULL, 0);
            l2_prefetch(P.ckv + 512 * 512 + rb * 2048, 4096);
            mbar_watch(sb + BAR_FULL + 8 * 4, 0);
            l2_prefetch(P.ckv + 1024 * 512 + rb * 4096, 8192);
            TS(40);
#pragma unroll 1
            for (int i = 0; i < 15; i++) {
                step_watch(sb + SM_EP + 16, i == 0 ? 0 : i < 5 ? PFA + i : 13 + PFB + i);
                if (i == 12) mbar_watch(sb + BAR_FLAG + 8 * 7, 0);
                const int rf = min(rb, NFFN - 1);
                const uint8_t* p = i == 3 ? reinterpret_cast<const uint8_t*>(P.ckv) + rb * 16384
                                 : i == 4 ? g_h + rb * 16384
                                 : i < 9 ? g_ctx + (size_t)(ort * 32 + o_head(cq + 2 * ((i - 5) & 2), kh)) * SLOT + (i & 1) * 16384
                                 : i < 11 ? reinterpret_cast<const uint8_t*>(P.wo) + (grp * 16 + (~i & 1) * 8 + j) * 16384
                                 : i == 11 ? reinterpret_cast<const uint8_t*>(P.x) + rb * 16384
                                 : i == 12 ? reinterpret_cast<const uint8_t*>(P.wdown) + rf * 16384 : g_wf + rf * SLOT + (i & 1) * 16384;
                if (i < 3) tma3d_prefetch(i == 1 ? tw : &tm_wq, (j >> 1) * 128, grp * 4 + (i == 1 ? 2 : i + (j & 1)));
                else l2_prefetch(p, 16384);
            }
            const uint32_t v = lds32(sb + SM_EP) - 1;
            sts128(sb + SM_RED + lane * 16, make_uint4(v, v, v, v));
            fence_async_smem();
            __syncwarp();
#pragma unroll 1
            for (int i = 0; i < OB / 32; i++) bulk_store(g_out + rb * OB + i * 32, sb + SM_RED, 512);
            asm volatile("cp.async.bulk.commit_group;\ncp.async.bulk.wait_group 0;" ::: "memory");
            fence_async_global();
            __syncwarp();
            mbar_arrive_if(sb + BAR_PF, lane == 0);
            if (lane == 0) mbar_watch(sb + BAR_END, 0);
        } else {
            const uint32_t ep = __ldcg(&g_sync.epoch[0]) + 1;
            asm volatile("st.shared.u32 [%0], %1;" ::"r"(sb + SM_EP), "r"(ep) : "memory");
            mbar_wait(sb + BAR_FULL + 8 * 4, 0);
            {
                uint4 v[4];
                for (;;) {
                    uint32_t bad = 0;
#pragma unroll
                    for (int k = 0; k < 4; k++) v[k] = ld_poll(reinterpret_cast<const uint4*>(g_mod1) + (warp & 1) * 128 + k * 32 + lane);
#pragma unroll
                    for (int k = 0; k < 4; k++) bad |= (v[k].x ^ ep) | (v[k].y ^ ep) | (v[k].z ^ ep) | (v[k].w ^ ep);
                    if (__all_sync(0xffffffffu, (bad & 0xffff) == 0)) break;
                    __nanosleep(100);
                }
                const uint32_t one = (warp & 1) ? ONE2 : 0x80008000u;
#pragma unroll
                for (int k = 0; k < 4; k++)
                    *reinterpret_cast<uint2*>(smem + SM_TAB + (warp & 1) * 1024 + k * 256 + lane * 8) =
                        make_uint2(badd(__byte_perm(v[k].x, v[k].y, 0x7632), one), badd(__byte_perm(v[k].z, v[k].w, 0x7632), one));
            }
            __syncwarp();
            mbar_arrive_if(sb + BAR_FLAG + 8 * 8, lane == 0);
            if (warp == 10) {
#pragma unroll 1
                for (int i = 0; i < 9; i++) {
                    mbar_sleep(sb + BAR_DONE + 8 * i);
                    if (lane == 0) flag_add(i && ((i - 1) & 2) ? &g_sync.ctxcnt[((i & 1) ? 15 - j : j) * 32 + 2 * grp + (i > 4)] : &g_sync.cnt[(grp * 8 + i) * 8]);
                    if (i == 0) TS(43);
                }
            } else {
                TS(42);
#pragma unroll 1
                for (int i = 0; i < 8; i++) {
                    mbar_sleep(sb + BAR_DONE + 8 * (i == 7 ? 6 : i == 4 ? 3 : i));
                    if (lane < 2) flag_wait(&g_sync.cnt[((i == 0 ? (lane ? j : 15 - j) : i == 7 ? 0 : grp) * 8 + i) * 8], 8 * ep);
                    __syncwarp();
                    mbar_arrive_if(sb + BAR_FLAG + 8 * i, lane == 0 && i < 7);
                    TS(48 + i);
                }
                const uint32_t *mp = reinterpret_cast<const uint32_t*>(g_mod) + lane, *wp = reinterpret_cast<const uint32_t*>(P.wr) + lane;
                float ra = 0.f, rs = 0.f;
#pragma unroll 1
                for (int k = 0; k < 256; k += 32) {
                    const uint32_t ga = __ldcg(mp + 512 + k), sh = __ldcg(mp + 768 + k), c1 = badd(__ldcg(mp + 1024 + k), ONE2);
                    const uint32_t gb = __ldcg(mp + 1280 + k), ww = __ldg(wp + k);
                    const float a0 = bf_lo(c1) * bf_lo(ww), a1 = bf_hi(c1) * bf_hi(ww);
                    ra += a0 + a1;
                    rs = fmaf(bf_lo(sh), bf_lo(ww), fmaf(bf_hi(sh), bf_hi(ww), rs));
                    if (k >> 6 == cq) {
                        sts128(sb + SM_TAB + ((k & 32) + lane) * 16, make_uint4(ga << 16, ga & 0xffff0000u, __float_as_uint(a0), __float_as_uint(a1)));
                        sts128(sb + SM_TAB + 1024 + ((k & 32) + lane) * 16, make_uint4(c1, sh, gb, 0));
                    }
                }
#pragma unroll 1
                for (int o = 16; o > 0; o >>= 1) {
                    ra += __shfl_xor_sync(0xffffffffu, ra, o);
                    rs += __shfl_xor_sync(0xffffffffu, rs, o);
                }
                *reinterpret_cast<float2*>(smem + SM_EP + 8) = make_float2(ra, rs);
                __syncwarp();
                mbar_arrive_if(sb + BAR_FLAG + 8 * 7, lane == 0);
                const uint32_t* f = &g_sync.ctxcnt[ort * 32 + o_head(min(lane, 16), kh)];
                uint32_t ready = -(j & 1), list = 0, sh = 0, qa;
                asm("mapa.shared::cluster.u32 %0, %1, %2;" : "=r"(qa) : "r"(sb + SM_EP + 20), "r"(lane & 1));
                while (ready != ~0u) {
                    uint32_t v;
                    asm volatile("ld.acquire.gpu.global.u32 %0, [%1];" : "=r"(v) : "l"(f) : "memory");
                    const uint32_t now = __ballot_sync(0xffffffffu, (int)(v - ep) >= 0);
#pragma unroll 1
                    for (uint32_t fresh = now & ~ready & 0x7f00; fresh; fresh &= fresh - 1, sh += 4) list |= (__ffs(fresh) - 1) << sh;
                    list |= (((now & 0xff) + 1) >> 8 << 28) | ((now & 0x18000) << 14);
                    if (now != ready && lane < 2) asm volatile("st.relaxed.cluster.shared::cluster.u32 [%0], %1;" ::"r"(qa), "r"(list) : "memory");
                    if ((now & 0xff) == 0xff) mbar_sleep(sb + BAR_DONE + 8 * 7);
                    ready = now;
                    __nanosleep(POLL_NS);
                }
                TS(45);
            }
        }
    } else {
        asm volatile("setmaxnreg.inc.sync.aligned.u32 232;");
        const bool elected = (tid & 127) == 0, rel = (tid & 95) == 0;
        uint32_t eb;
        asm("mapa.shared::cluster.u32 %0, %1, %2;" : "=r"(eb) : "r"(sb + BAR_EMPTY), "r"(warp & 1));
        const int g = lane >> 2, c4 = lane & 3;
        const uint32_t toff = warp * 4096 + g * 64 + ((c4 ^ (g >> 1)) << 4);
        uint32_t fph = 0, r = 0;
        if (wg == 1) bar_arrive(1, 256);
        const uint32_t kd = desc_k(sb), wd = desc_mn(sb), vd = ((sb & 0x3ffff) >> 4) | (32u << 16);
        const int nL = 16 - j, hn = nL - 1 + wg;
        float s[64], o[64], li[2] = {0.f, 0.f};
        uint8_t* cimg = g_ctx;
        uint32_t p[32] = {};
#pragma unroll 1
        for (int hp = 0; hp < 2; hp++) {
            float m[2] = {0.f, 0.f}, l[2] = {0.f, 0.f}, t[4] = {0.f, 0.f, 0.f, 0.f};
            bool shifted = false, bad = false, plain = false;
            uint32_t qa = desc_k(sb + 5 * SLOT + (wg ^ 1) * 8192);
            uint8_t* limg = g_ctx + (size_t)((15 - j) * 32 + 2 * grp + hp) * SLOT;
            {
                const int step = hp ? -8 * SLOT : 8 * SLOT;
                uint8_t* img = g_KV + (size_t)(grp * 32 + (hp ? j ^ 30 : j)) * SLOT - step;
                const float sc = (j & 1) ? 1.f : SM_C;
                const uint32_t wtab = w_table(hp);
                uint32_t atab = hp ? 0x562u : a_table(0);
#pragma unroll 1
                for (int u = 0;; u += 2) {
                    proj_tile<false>(s, o, u, u ? 0 : hp, sb, wg, eb, rel, fph, wtab, atab, u ? img : cimg, toff, u ? sc : li[0], u ? sc : li[1], (hp | u) == 0, P.x, rb * 16 + warp * 2, p);
                    __syncwarp();
                    mbar_arrive_if(sb + BAR_DONE + 4 * u + 32 * hp, lane == 0 && (hp | u) != 0);
                    if (elected) TS(1 + 10 * hp + u + 20 * wg);
                    if (proj_tile<true>(o, s, u + 1, 0, sb, wg, eb, rel, fph, wtab, atab, img + step, toff, sc, sc, (hp | u) == 0, P.x, rb * 16 + warp * 2, p)) break;
                    if (elected) TS(2 + 10 * hp + u + 20 * wg);
                    img += 2 * step;
                }
            }
            if (elected) TS(6 + 10 * hp + 20 * wg);
            int n = -1;
#pragma unroll 1
            for (;;) {
                while (bad || plain) {
                    if (bad) {
                        float a0, a1;
                        softmax_remax(s, m, n == 0 || n == nL, a0, a1);
                        shifted = true;
                        l[0] *= a0;
                        l[1] *= a1;
#pragma unroll
                        for (int i = 0; i < 64; i++) o[i] *= (i & 2) ? a1 : a0;
                    }
                    softmax_exp<0, 16>(s, p, t);
                    t[0] += t[1];
                    t[2] += t[3];
                    bad = !bad && softmax_unsafe(t[0], t[2], false);
                    plain = false;
                }
#pragma unroll 1
                do {
                    l[0] += t[0];
                    l[1] += t[2];
                    if (++n > 16) break;
                    const uint32_t ks = r;
                    uint32_t vs = ring_next(r);
                    r = ring_next(vs);
                    bar_sync(1 + wg, 256);
                    const float x = (float)((warp & 3) * 16 + g - 2 * c4);
                    if (n == hn) {
                        float sh[32];
                        qk_issue(sh, qa, kd + ks * (SLOT / 16));
                        slot_wait(sb + BAR_FULL, fph, vs);
                        pv_issue(o, p, vd + vs * (SLOT / 16), 1, false);
                        bar_arrive(2 - wg, 256);
                        wg_wait<1>();
                        reg_fence(sh);
                        tri_mask_copy(s, sh, x);
                        release_if(eb, ks, rel);
                        release_if(eb, 5 + wg, rel && (!wg || n == 16));
                        if (!wg) {
                            qa += SLOT / 16;
                            fence_async_smem();
                            if (shifted) softmax_shift(s, m[0], m[1]);
                        }
                        float e[4 * EARLY];
#pragma unroll
                        for (int i = 0; i < 4 * EARLY; i++) {
                            e[i] = ex2(s[i]);
                            t[i & 3] = i < 4 ? e[i] : t[i & 3] + e[i];
                        }
                        reg_fence(e);
                        slot_wait(sb + BAR_FULL, fph, r);
                        wg_wait<0>();
                        reg_fence(o);
                        reg_fence(e);
                        release_if(eb, vs, rel);
#pragma unroll
                        for (int i = 0; i < 2 * EARLY; i++) p[i] = pack2(e[2 * i], e[2 * i + 1]);
                        softmax_exp<EARLY, 8>(s, p, t);
                        if (wg) {
                            ctx_store<true>(limg, toff, o, l[0], l[1]);
                            __syncwarp();
                            mbar_arrive_if(sb + BAR_DONE + 24 + 32 * hp, lane == 0);
                            l[0] = l[1] = m[0] = m[1] = 0.f;
                            shifted = false;
                        }
                        t[0] += t[1];
                        t[2] += t[3];
                        bad = softmax_unsafe(t[0], t[2], wg);
                        continue;
                    }
                    if (n == 0 || n == nL) {
                        qk_issue(s, qa, kd + ks * (SLOT / 16));
                        if (n == 0) {
                            r = vs;
                            vs = 4 - hp;
                            slot_wait(sb + BAR_FULL, fph, 6);
                            gemm_issue<false>(o, qa + SLOT / 16, wd + vs * (SLOT / 16), 1, false);
                        } else {
                            slot_wait(sb + BAR_FULL, fph, vs);
                            pv_issue(o, p, vd + vs * (SLOT / 16), 1, true);
                        }
                        bar_arrive(2 - wg, 256);
                        const float i0 = n ? rcp(quad_sum(l[0])) : 1.f, i1 = n ? rcp(quad_sum(l[1])) : 1.f;
                        wg_wait<1>();
                        reg_fence(s);
                        release_if(eb, ks, rel);
                        release_if(eb, 6, rel && n == 16);
                        tri_mask(s, n ? x : 64.f);
                        float e[4 * EARLY];
#pragma unroll
                        for (int i = 0; i < 4 * EARLY; i++) {
                            e[i] = ex2(s[i]);
                            t[i & 3] = i < 4 ? e[i] : t[i & 3] + e[i];
                        }
                        reg_fence(e);
                        reg_fence(s);
                        reg_fence(t);
                        slot_wait(sb + BAR_FULL, fph, r);
                        if (SF & 1) sched_fence(fph, P.zero);
                        wg_wait<0>();
                        reg_fence(o);
                        reg_fence(e);
                        release_if(eb, vs, rel);
#pragma unroll
                        for (int i = 0; i < 2 * EARLY; i++) p[i] = pack2(e[2 * i], e[2 * i + 1]);
                        softmax_exp<EARLY, MSPLIT>(s, p, t);
                        tile_store(limg, sb + 6 * SLOT, toff, o, i0, i1, n);
                        reg_fence(t);
                        if (SF & 2) sched_fence(fph, P.zero);
                        reg_fence(s);
                        softmax_exp<MSPLIT, 16>(s, p, t);
                        __syncwarp();
                        mbar_arrive_if(sb + BAR_DONE + 24 + 32 * hp, lane == 0 && n);
                        l[0] = l[1] = m[0] = m[1] = 0.f;
                        shifted = false;
                        t[0] += t[1];
                        t[2] += t[3];
                        bad = __any_sync(0xffffffffu, fmaxf(t[0], t[2]) > SM_HI || fminf(t[0], t[2]) < SM_LO);
                        continue;
                    }
                    qk_issue(s, qa, kd + ks * (SLOT / 16));
                    slot_wait(sb + BAR_FULL, fph, vs);
                    pv_issue(o, p, vd + vs * (SLOT / 16), n != 1 && n != nL + 1, n == hn + 1);
                    bar_arrive(2 - wg, 256);
                    wg_wait<1>();
                    reg_fence(s);
                    release_if(eb, ks, rel);
                    release_if(eb, 6, rel && n == 16);
                    if (n == nL - 1) {
                        tri_mask(s, x);
                        release_if(eb, 5, rel);
                        qa += SLOT / 16;
                        fence_async_smem();
                    }
                    if (shifted) {
                        slot_wait(sb + BAR_FULL, fph, r);
                        wg_wait<0>();
                        reg_fence(o);
                        release_if(eb, vs, rel);
                        softmax_shift(s, m[0], m[1]);
                        plain = true;
                        break;
                    }
                    float e[4 * EARLY];
#pragma unroll
                    for (int i = 0; i < 4 * EARLY; i++) {
                        e[i] = ex2(s[i]);
                        t[i & 3] = i < 4 ? e[i] : t[i & 3] + e[i];
                    }
                    reg_fence(e);
                    slot_wait(sb + BAR_FULL, fph, r);
                    wg_wait<0>();
                    reg_fence(o);
                    reg_fence(e);
                    release_if(eb, vs, rel);
#pragma unroll
                    for (int i = 0; i < 2 * EARLY; i++) p[i] = pack2(e[2 * i], e[2 * i + 1]);
                    softmax_exp<EARLY, 16>(s, p, t);
                    t[0] += t[1];
                    t[2] += t[3];
                    bad = softmax_unsafe(t[0], t[2], false);
                } while (!bad);
                if (!bad && !plain) break;
            }
            const uint32_t vs = r, ga = desc_k(sb + (hp ? 2 * (wg ^ kh ^ 1) : wg) * 8192);
            r = ring_next(r);
            slot_wait(sb + BAR_FULL, fph, 5);
            slot_wait(sb + BAR_FULL, fph, r);
            bar_sync(1 + wg, 256);
            gemm_issue<true>(s, ga + 5 * (SLOT / 16), wd + r * (SLOT / 16), 0, hp);
            pv_issue(o, p, vd + vs * (SLOT / 16), j, hn == 16);
            bar_arrive(2 - wg, 256);
            li[0] = rcp(quad_sum(l[0]));
            li[1] = rcp(quad_sum(l[1]));
            cimg = limg + (ptrdiff_t)(2 * j - 15) * 32 * SLOT + (wg ? -16384 : 16384);
            wg_wait<1>();
            release_if(eb, 5, rel);
            release_if(eb, r, rel && hp);
            wg_wait<0>();
            release_if(eb, vs, rel);
            reg_fence(o);
            img_store_global<0>(cimg, toff, o, li[0], li[1]);
            if (elected) TS(8 + 10 * hp + 20 * wg);
        }
        uint32_t otab = 0x2351604u;
        const uint32_t oa = desc_k(sb + (wg ^ kh ^ 1) * 16384);
        const int t7 = tid & 127, w4 = warp & 3, row = ort * 128 + kh * 64 + w4 * 16 + g;
#pragma unroll 1
        for (int i = 1; i < 15 - wg; i++) {
            const uint32_t as = o_next(otab), ws = o_next(otab);
            slot_wait(sb + BAR_FULL, fph, as);
            slot_wait(sb + BAR_FULL, fph, ws);
            bar_sync(1 + wg, 256);
            gemm_issue<false>(s, oa + as * (SLOT / 16), wd + ws * (SLOT / 16), 1, true);
            bar_arrive(2 - wg, 256);
            wg_wait<1>();
            reg_fence(o);
            if (i == 1) img_store_global<1>(cimg, toff, o, li[0], li[1]);
            if (i == 2) {
                img_store_global<2>(cimg, toff, o, li[0], li[1]);
                img_store_global<3>(cimg, toff, o, li[0], li[1]);
                __syncwarp();
                mbar_arrive_if(sb + BAR_DONE + 64, lane == 0);
            }
            wg_wait<0>();
            release_if(eb, as, rel);
            release_if(eb, ws, rel);
        }
        mbar_wait(sb + BAR_PF, 0);
        const uint32_t ep = lds32(sb + SM_EP);
        if (wg == 0) {
            reg_fence(s);
            if (elected) TS(9);
#pragma unroll
            for (int v = 0; v < 8; v++)
                st_pub(g_out + rb * OB + v * 128 + t7, make_uint4((pack2(s[8 * v], s[8 * v + 1]) & ~1u) | (ep & 1), pack2(s[8 * v + 2], s[8 * v + 3]),
                                                                      pack2(s[8 * v + 4], s[8 * v + 5]), pack2(s[8 * v + 6], s[8 * v + 7])), true);
            constexpr uint32_t s1 = 5, s2 = 6;
            bar_sync(4, 256);
            uint32_t wf[64];
            float wn[64];
            if (rb < NFFN) {
                slot_wait(sb + BAR_FULL, fph, s1);
                const uint32_t a = sb + s1 * SLOT + (w4 * 128 + (lane >> 4) * 8 + (lane & 7)) * 32 + ((lane >> 3) & 1) * 16;
#pragma unroll
                for (int i = 0; i < 16; i++)
                    asm volatile("ldmatrix.sync.aligned.m8n8.x4.trans.shared.b16 {%0, %1, %2, %3}, [%4];"
                                 : "=r"(wf[4 * i]), "=r"(wf[4 * i + 1]), "=r"(wf[4 * i + 2]), "=r"(wf[4 * i + 3])
                                 : "r"(a + (i >> 3) * 16384 + (i & 7) * 512) : "memory");
                slot_wait(sb + BAR_FULL, fph, s2);
#pragma unroll
                for (int i = 0; i < 16; i++) {
                    const uint2 w = *reinterpret_cast<const uint2*>(smem + s2 * SLOT + (kh ^ 1) * 16384 + i * 1024 + t7 * 8);
                    wn[4 * i] = bf_lo(w.x); wn[4 * i + 1] = bf_hi(w.x); wn[4 * i + 2] = bf_lo(w.y); wn[4 * i + 3] = bf_hi(w.y);
                }
                reg_fence(wn);
            }
            const uint32_t gbf = __ldcg(reinterpret_cast<const uint32_t*>(g_mod) + 1280 + rb * 2 + (tid & 1));
            if (elected) TS(10);
            const uint32_t best = best_key(g_key + cq * 128, lane, ep);
            const int sel = (~best >> 5) & 2047;
            if (elected) TS(19);
            const uint4* cp = g_cand + (sel >> 4) * 192;
            float* sred = reinterpret_cast<float*>(smem + SM_RED);
            const int pq = (2 * rb + (tid & 1)) & 63, pv = (pq >> 2) / 3;
            const uint4* fp = cp + (rb >> 5) * 24 + pv * 4 + (pq & 3);
            uint4 fh = ld_poll(fp), fx = ld_poll(fp + 96);
            if (rb < NFFN) {
                uint4 cv[6];
                for (;;) {
                    uint32_t bad = 0;
#pragma unroll
                    for (int v = 0; v < 6; v++) cv[v] = ld_poll(cp + w4 * 24 + v * 4 + c4);
#pragma unroll
                    for (int v = 0; v < 6; v++) bad |= cv[v].w ^ ep;
                    if (__all_sync(0xffffffffu, bad == 0)) break;
                }
                if (elected) TS(20);
                float d[4][4] = {};
#pragma unroll
                for (int k = 0; k < 8; k++) {
                    const uint32_t b0 = (&cv[(2 * k) / 3].x)[(2 * k) % 3], b1 = (&cv[(2 * k + 1) / 3].x)[(2 * k + 1) % 3];
                    mma16816(d[k & 1], wf + 4 * k, b0, b1);
                    mma16816(d[2 + (k & 1)], wf + 32 + 4 * k, b0, b1);
                }
                const float u = (c4 & 2) ? ((c4 & 1) ? d[2][2] + d[3][2] : d[2][0] + d[3][0]) : ((c4 & 1) ? d[0][2] + d[1][2] : d[0][0] + d[1][0]);
                sred[w4 * 32 + c4 * 8 + g] = u;
                bar_sync(3, 128);
                const float v = rbf((sred[lane] + sred[32 + lane]) + (sred[64 + lane] + sred[96 + lane]));
                const float act = rbf(rbf(v * sigmoid(v)) * __shfl_down_sync(0xffffffffu, v, 16));
                float y[4] = {0.f, 0.f, 0.f, 0.f};
#pragma unroll
                for (int k = 0; k < 16; k++) {
                    const float a = __shfl_sync(0xffffffffu, act, k);
#pragma unroll
                    for (int i = 0; i < 4; i++) y[i] = fmaf(a, wn[4 * k + i], y[i]);
                }
                st_pub(g_out + rb * OB + OB_Y + t7, make_uint4((__float_as_uint(y[0]) & ~15u) | (ep & 15), __float_as_uint(y[1]), __float_as_uint(y[2]), __float_as_uint(y[3])), true);
            }
            if (rb == 0 && tid == 0) g_sync.epoch[0] = ep;
            if (elected) TS(60);
            uint4 yv;
            do yv = ld_poll(g_out + min(t7, NFFN - 1) * OB + OB_Y + rb);
            while (!__all_sync(0xffffffffu, ((yv.x ^ ep) & 15) == 0));
            if (elected) TS(61);
            float y[4] = {0.f, 0.f, 0.f, 0.f};
            if (t7 < NFFN) { y[0] = __uint_as_float(yv.x); y[1] = __uint_as_float(yv.y); y[2] = __uint_as_float(yv.z); y[3] = __uint_as_float(yv.w); }
            const float z0 = ((lane & 16) ? y[2] : y[0]) + __shfl_xor_sync(0xffffffffu, (lane & 16) ? y[0] : y[2], 16);
            const float z1 = ((lane & 16) ? y[3] : y[1]) + __shfl_xor_sync(0xffffffffu, (lane & 16) ? y[1] : y[3], 16);
            float z = ((lane & 8) ? z1 : z0) + __shfl_xor_sync(0xffffffffu, (lane & 8) ? z0 : z1, 8);
            z += __shfl_xor_sync(0xffffffffu, z, 4);
            z = quad_sum(z);
            if ((lane & 7) == 0) sred[128 + (lane >> 3) * 4 + w4] = z;
            bar_sync(3, 128);
            if (tid < 2) {
                while (fh.w != ep || fx.w != ep) { fh = ld_poll(fp); fx = ld_poll(fp + 96); }
                const float4 y0 = *reinterpret_cast<const float4*>(sred + 128 + tid * 8), y1 = *reinterpret_cast<const float4*>(sred + 132 + tid * 8);
                const int cm = (pq >> 2) - 3 * pv;
                const uint32_t h2 = cm == 0 ? fh.x : cm == 1 ? fh.y : fh.z, x2 = cm == 0 ? fx.x : cm == 1 ? fx.y : fx.z;
                const float sg = sigmoid(bf_hi((best & 0x80000000u) ? (best ^ 0x80000000u) : ~best));
                reinterpret_cast<uint32_t*>(P.out)[sel * 256 + rb * 2 + tid] =
                    badd(x2, bmul(gbf, badd(h2, bmul(pack2((y0.x + y0.y) + (y0.z + y0.w), (y1.x + y1.y) + (y1.z + y1.w)), pack2(sg, sg)))));
            }
            if (elected) TS(62);
        } else {
            const float4* tf = reinterpret_cast<const float4*>(smem + SM_TAB) + c4;
            const uint32_t xa = sb + 4 * SLOT + (kh ^ 1) * 16384 + (w4 * 16 + (lane & 15)) * 128;
            uint32_t x2[32];
            bar_sync(2, 256);
#pragma unroll 1
            for (int i = 14; i < 17; i++) {
                const uint32_t as = o_next(otab), ws = o_next(otab);
                slot_wait(sb + BAR_FULL, fph, as);
                slot_wait(sb + BAR_FULL, fph, ws);
                gemm_issue<false>(s, oa + as * (SLOT / 16), wd + ws * (SLOT / 16), 1, true);
                wg_wait<1>();
            }
            if (elected) TS(29);
            {
#pragma unroll
                for (int k = 0; k < 8; k++)
                    asm volatile("ldmatrix.sync.aligned.m8n8.x4.shared.b16 {%0, %1, %2, %3}, [%4];"
                                 : "=r"(x2[4 * k]), "=r"(x2[4 * k + 1]), "=r"(x2[4 * k + 2]), "=r"(x2[4 * k + 3])
                                 : "r"(xa + (k >> 2) * 8192 + (((2 * (k & 3) + (lane >> 4)) ^ (lane & 7)) << 4)) : "memory");
            }
            wg_wait<0>();
            reg_fence(s);
            bar_arrive(4, 256);
            if (elected) TS(39);
            const uint4* pr = g_out + (rb ^ 8) * OB + t7;
            uint4 pa[8];
#pragma unroll
            for (int v = 0; v < 8; v++) pa[v] = ld_poll(pr + v * 128);
            float4 tc[16];
#pragma unroll
            for (int k = 0; k < 16; k++) {
                tc[k] = tf[k * 4];
#pragma unroll
                for (int i = 4 * k; i < 4 * k + 4; i++) s[i] = fmaf((i & 1) ? tc[k].y : tc[k].x, s[i], (i & 1) ? bf_hi(x2[i >> 1]) : bf_lo(x2[i >> 1]));
            }
            reg_fence(s);
            for (;;) {
                uint32_t bad = 0;
#pragma unroll
                for (int v = 0; v < 8; v++) bad |= pa[v].x ^ ep;
                if (__all_sync(0xffffffffu, (bad & 1) == 0)) break;
#pragma unroll
                for (int v = 0; v < 8; v++) pa[v] = ld_poll(pr + v * 128);
            }
            if (elected) TS(30);
            float st[6] = {0.f, 0.f, 0.f, 0.f, 0.f, 0.f};
#pragma unroll
            for (int i = 0; i < 64; i++) {
                const int rh = (i >> 1) & 1;
                const uint32_t w = (&pa[i >> 3].x)[(i >> 1) & 3];
                const float v = fmaf((i & 1) ? tc[i >> 2].y : tc[i >> 2].x, (i & 1) ? bf_hi(w) : bf_lo(w), s[i]);
                s[i] = v;
                st[rh] += v;
                st[2 + rh] = fmaf(v, v, st[2 + rh]);
                st[4 + rh] = fmaf(v, (i & 1) ? tc[i >> 2].w : tc[i >> 2].z, st[4 + rh]);
            }
#pragma unroll
            for (int i = 0; i < 6; i++) st[i] = quad_sum(st[i]);
            st_pub(g_out + rb * OB + OB_STAT + (w4 * 8 + g) * 2 + (c4 & 1),
                   make_uint4(__float_as_uint((c4 & 1) ? st[1] : st[0]), __float_as_uint((c4 & 1) ? st[3] : st[2]),
                              __float_as_uint((c4 & 1) ? st[5] : st[4]), ep), c4 < 2);
            if (elected) TS(56);
            uint32_t cb[16], sh[16], gb[16];
#pragma unroll
            for (int i = 0; i < 16; i++) {
                const float4 c = tf[64 + i * 4];
                cb[i] = __float_as_uint(c.x); sh[i] = __float_as_uint(c.y); gb[i] = __float_as_uint(c.z);
            }
            const float ra = __uint_as_float(lds32(sb + SM_EP + 8)), rb0 = __uint_as_float(lds32(sb + SM_EP + 12));
#pragma unroll
            for (int i = 0; i < 32; i++) x2[i] = pack2(s[2 * i], s[2 * i + 1]);
            reg_fence(x2);
            uint4 r0, r1;
            for (;;) {
                r0 = ld_poll(g_out + ((rb & ~3) + c4) * OB + OB_STAT + (w4 * 8 + g) * 2);
                r1 = ld_poll(g_out + ((rb & ~3) + c4) * OB + OB_STAT + (w4 * 8 + g) * 2 + 1);
                if (__all_sync(0xffffffffu, r0.w == ep && r1.w == ep)) break;
            }
            if (elected) TS(57);
            const float m0 = quad_sum(__uint_as_float(r0.x)) * (1.f / 512.f), m1 = quad_sum(__uint_as_float(r1.x)) * (1.f / 512.f);
            const float rs0 = ln_rstd(fmaxf(fmaf(-m0, m0, quad_sum(__uint_as_float(r0.y)) * (1.f / 512.f)), 0.f));
            const float rs1 = ln_rstd(fmaxf(fmaf(-m1, m1, quad_sum(__uint_as_float(r1.y)) * (1.f / 512.f)), 0.f));
            const uint32_t mb0 = pack2(m0, m0), mb1 = pack2(m1, m1);
            const uint32_t lg = pack2(fmaf(rs0, fmaf(-bf_lo(mb0), ra, quad_sum(__uint_as_float(r0.z))), rb0),
                                      fmaf(rs1, fmaf(-bf_lo(mb1), ra, quad_sum(__uint_as_float(r1.z))), rb0));
            const uint32_t u0 = lg << 16, u1 = lg & 0xffff0000u;
            const uint32_t k0 = ((u0 ^ (((int)u0 >> 31) | 0x80000000u)) & 0xffff0000u) | ((2047 - row) << 5) | (ep & 31);
            const uint32_t k1 = ((u1 ^ (((int)u1 >> 31) | 0x80000000u)) & 0xffff0000u) | ((2039 - row) << 5) | (ep & 31);
            const uint32_t kb = __reduce_max_sync(0xffffffffu, max(k0, k1));
            st_pub(g_key + cq * 128 + (row >> 4), kb, lane == 0);
            {
                uint32_t cx[18], ch[18];
#pragma unroll
                for (int i = 0; i < 16; i++) {
                    cx[i] = kb == k1 ? x2[2 * i + 1] : x2[2 * i];
                    ch[i] = ln_apply(cx[i], kb == k1 ? mb1 : mb0, kb == k1 ? rs1 : rs0, cb[i], sh[i]);
                }
                cx[16] = cx[17] = ch[16] = ch[17] = 0;
                uint4* cp = g_cand + (row >> 4) * 192 + cq * 24 + c4;
#pragma unroll
                for (int v = 0; v < 6; v++) st_pub(cp + v * 4, make_uint4(ch[3 * v], ch[3 * v + 1], ch[3 * v + 2], ep), kb == k0 || kb == k1);
#pragma unroll
                for (int v = 0; v < 6; v++) st_pub(cp + 96 + v * 4, make_uint4(cx[3 * v], cx[3 * v + 1], cx[3 * v + 2], ep), kb == k0 || kb == k1);
            }
            if (elected) TS(58);
            uint2 ov[16];
#pragma unroll
            for (int i = 0; i < 16; i++) {
                const int rh = i & 1, jj = i & 14;
                const uint32_t v0 = badd(x2[2 * jj + rh], bmul(gb[jj], ln_apply(x2[2 * jj + rh], rh ? mb1 : mb0, rh ? rs1 : rs0, cb[jj], sh[jj])));
                const uint32_t v1 = badd(x2[2 * jj + 2 + rh], bmul(gb[jj + 1], ln_apply(x2[2 * jj + 2 + rh], rh ? mb1 : mb0, rh ? rs1 : rs0, cb[jj + 1], sh[jj + 1])));
                const uint32_t rv = __shfl_xor_sync(0xffffffffu, (c4 & 1) ? v0 : v1, 1);
                ov[i] = (c4 & 1) ? make_uint2(rv, v1) : make_uint2(v0, rv);
            }
            uint2* op = reinterpret_cast<uint2*>(P.out) + row * 128 + cq * 32 + (c4 & 1) * 2 + (c4 >> 1);
#pragma unroll
            for (int i = 0; i < 16; i++)
                if (kb != ((i & 1) ? k1 : k0)) op[(i & 1) * 1024 + (i & 14) * 2] = ov[i];
            const uint32_t best = best_key(g_key + cq * 128, lane, ep);
            if (best != kb) {
#pragma unroll
                for (int i = 0; i < 16; i++)
                    if (kb == ((i & 1) ? k1 : k0)) op[(i & 1) * 1024 + (i & 14) * 2] = ov[i];
            }
            if (elected) TS(59);
        }
        mbar_arrive_if(sb + BAR_END, lane == 0);
    }
}

typedef CUresult (*EncodeFn)(CUtensorMap*, CUtensorMapDataType, cuuint32_t, void*, const cuuint64_t*, const cuuint64_t*,
                             const cuuint32_t*, const cuuint32_t*, CUtensorMapInterleave, CUtensorMapSwizzle,
                             CUtensorMapL2promotion, CUtensorMapFloatOOBfill);

void make_2d(EncodeFn fn, CUtensorMap* m, const void* p, uint64_t cols, uint64_t rows, uint32_t bc, uint32_t br) {
    cuuint64_t dims[2] = {cols, rows}, strides[1] = {cols * 2};
    cuuint32_t box[2] = {bc, br}, es[2] = {1, 1};
    fn(m, CU_TENSOR_MAP_DATA_TYPE_BFLOAT16, 2, const_cast<void*>(p), dims, strides, box, es, CU_TENSOR_MAP_INTERLEAVE_NONE,
       CU_TENSOR_MAP_SWIZZLE_NONE, CU_TENSOR_MAP_L2_PROMOTION_L2_128B, CU_TENSOR_MAP_FLOAT_OOB_FILL_NONE);
}
void make_3d(EncodeFn fn, CUtensorMap* m, const void* p, uint64_t cols, uint64_t rows, uint32_t br = 128, uint32_t nb = 2) {
    cuuint64_t dims[3] = {64, rows, cols / 64}, strides[2] = {cols * 2, 128};
    cuuint32_t box[3] = {64, br, nb}, es[3] = {1, 1, 1};
    fn(m, CU_TENSOR_MAP_DATA_TYPE_BFLOAT16, 3, const_cast<void*>(p), dims, strides, box, es, CU_TENSOR_MAP_INTERLEAVE_NONE,
       CU_TENSOR_MAP_SWIZZLE_128B, CU_TENSOR_MAP_L2_PROMOTION_L2_256B, CU_TENSOR_MAP_FLOAT_OOB_FILL_NONE);
}

}

extern "C" void kernel_launch(void* const* d_in, const int* in_sizes, int n_in, void* d_out, int out_size) {
    static EncodeFn fn = nullptr;
    if (!fn) {
        void* f = nullptr;
        cudaDriverEntryPointQueryResult st;
        cudaGetDriverEntryPoint("cuTensorMapEncodeTiled", &f, cudaEnableDefault, &st);
        fn = (EncodeFn)f;
        cudaFuncSetAttribute(fused_kernel, cudaFuncAttributeMaxDynamicSharedMemorySize, SMEM_BYTES);
    }
    CUtensorMap ckv, wq, wuk, wuv, wo, wg, wu, wm, xm;
    make_3d(fn, &ckv, d_in[1], 512, 2048, 128, 1);
    make_3d(fn, &xm, d_in[0], 512, 2048, 64);
    make_3d(fn, &wq, d_in[2], 4096, 512, 128, 1);
    make_3d(fn, &wuk, d_in[3], 4096, 512);
    make_3d(fn, &wuv, d_in[4], 4096, 512);
    make_3d(fn, &wo, d_in[5], 512, 4096);
    make_2d(fn, &wg, d_in[8], 1792, 512, 16, 256);
    make_2d(fn, &wu, d_in[9], 1792, 512, 16, 256);
    make_2d(fn, &wm, d_in[12], 3072, 512, 256, 64);
    Params p;
    p.x = (const bf16*)d_in[0];
    p.ckv = (const bf16*)d_in[1];
    p.wo = (const bf16*)d_in[5];
    p.wr = (const bf16*)d_in[7];
    p.wdown = (const bf16*)d_in[10];
    p.c = (const bf16*)d_in[11];
    p.out = (bf16*)d_out;
    p.zero = 0;
    fused_kernel<<<NCTA + NSPARE, 384, SMEM_BYTES>>>(ckv, wq, wuk, wuv, wo, wg, wu, wm, xm, p);
}
```

```cpp
#include <cuda.h>
#include <cuda_bf16.h>
#include <cuda_runtime.h>
#include <stdint.h>
#include <stdio.h>

namespace {

typedef __nv_bfloat16 bf16;
typedef unsigned long long u64;

constexpr int NCTA = 128, NSPARE = 4;
constexpr int SLOT = 32768;
constexpr int SM_BAR = 7 * SLOT;
constexpr int BAR_FULL = SM_BAR;
constexpr int BAR_EMPTY = BAR_FULL + 8 * 7;
constexpr int BAR_DONE = BAR_EMPTY + 8 * 7;
constexpr int BAR_FLAG = BAR_DONE + 8 * 9;
constexpr int BAR_PF = BAR_FLAG + 8 * 9;
constexpr int BAR_END = BAR_PF + 8;
constexpr int BAR_BEST = BAR_END + 8;
constexpr int SM_EP = BAR_END + 24;
constexpr int SM_RED = SM_BAR + 384;
constexpr int SM_TAB = SM_BAR + 1024;
constexpr int SMEM_BYTES = SM_BAR + 3072;
constexpr int NFFN = 112;
#define HINT 31
constexpr u64 L2_NORMAL = 0x1000000000000000ull, L2_FIRST = 0x12F0000000000000ull;
#define PFA 8
#define PFB 6
#define UNR 1
#define POLL_NS 50
#define MSPLIT 13
#define SF 3
#define XQ 0
#define KGATE 0
#define TF 7
#define KALL 0
#define EARLY 7
constexpr uint32_t SPIN_LIMIT = 1u << 22;
constexpr uint32_t ONE2 = 0x3f803f80u;

struct Sync {
    uint32_t cnt[16 * 8 * 8];
    uint32_t ctxcnt[16 * 32];
    uint32_t epoch[32];
};

__device__ __align__(1024) uint8_t g_KV[16 * 16 * 2 * SLOT];
__device__ __align__(1024) uint8_t g_ctx[16 * 32 * SLOT];
__device__ __align__(1024) uint8_t g_h[16 * 4 * SLOT];
constexpr int OB = 1216, OB_STAT = 1024, OB_Y = 1088;
__device__ __align__(1024) uint4 g_out[128 * OB];
__device__ __align__(1024) bf16 g_mod[3072];
__device__ __align__(1024) uint32_t g_mod1[1024];
__device__ __align__(1024) uint4 g_cand[128 * 192];
__device__ __align__(1024) uint32_t g_key[4 * 128];
__device__ __align__(1024) uint8_t g_wf[NFFN * SLOT];
__device__ __align__(1024) Sync g_sync;
#define TS(i)

#define TT(i)
#define PT()

struct Params {
    const bf16 *x, *ckv, *wo, *wr, *wdown, *c;
    bf16* out;
    int zero;
};

__device__ __forceinline__ void mbar_init(uint32_t bar, uint32_t cnt) {
    asm volatile("mbarrier.init.shared::cta.b64 [%0], %1;" ::"r"(bar), "r"(cnt) : "memory");
}
__device__ __forceinline__ void mbar_wait(uint32_t bar, uint32_t parity) {
    asm volatile("{\n.reg .pred p;\nL_%=:\nmbarrier.try_wait.parity.shared::cta.b64 p, [%0], %1;\n@!p bra L_%=;\n}" ::"r"(bar), "r"(parity) : "memory");
}
__device__ __forceinline__ void mbar_sleep(uint32_t bar) {
    if ((threadIdx.x & 31) == 0)
        asm volatile("{\n.reg .pred p;\nL_%=:\nmbarrier.try_wait.parity.shared::cta.b64 p, [%0], 0, 100000;\n@!p bra L_%=;\n}" ::"r"(bar) : "memory");
    __syncwarp();
}
__device__ __forceinline__ void mbar_watch(uint32_t bar, uint32_t parity) {
    asm volatile("{\n.reg .pred p;\n.reg .u32 n;\nmov.u32 n, 0;\n"
                 "L_%=:\nmbarrier.try_wait.parity.shared::cta.b64 p, [%0], %1;\n@p bra D_%=;\n"
                 "add.u32 n, n, 1;\nsetp.lt.u32 p, n, %2;\n@p bra L_%=;\ntrap;\nD_%=:\n}"
                 ::"r"(bar), "r"(parity), "n"(SPIN_LIMIT) : "memory");
}
__device__ __forceinline__ void step_watch(uint32_t a, uint32_t step) {
    asm volatile("{\n.reg .pred p;\n.reg .u32 n, v;\nmov.u32 n, 0;\n"
                 "L_%=:\nld.volatile.shared.u32 v, [%0];\nsetp.ge.u32 p, v, %1;\n@p bra D_%=;\nnanosleep.u32 400;\n"
                 "add.u32 n, n, 1;\nsetp.lt.u32 p, n, %2;\n@p bra L_%=;\ntrap;\nD_%=:\n}"
                 ::"r"(a), "r"(step), "n"(SPIN_LIMIT) : "memory");
}
__device__ __forceinline__ void mbar_arrive_if(uint32_t bar, bool on) {
    asm volatile("{\n.reg .pred p;\nsetp.ne.s32 p, %1, 0;\n@p mbarrier.arrive.shared::cta.b64 _, [%0];\n}" ::"r"(bar), "r"((int)on) : "memory");
}
__device__ __forceinline__ void tma2d(uint32_t dst, const CUtensorMap* m, int c0, int c1, uint32_t bar) {
    asm volatile("{\n.reg .pred p;\nelect.sync _|p, 0xffffffff;\n"
                 "@p cp.async.bulk.tensor.2d.shared::cluster.global.mbarrier::complete_tx::bytes [%0], [%1, {%3, %4}], [%2];\n}"
                 ::"r"(dst), "l"(m), "r"(bar), "r"(c0), "r"(c1) : "memory");
}
__device__ __forceinline__ void tma3d_prefetch(const CUtensorMap* m, int row, int cb) {
    asm volatile("{\n.reg .pred p;\nelect.sync _|p, 0xffffffff;\n@p cp.async.bulk.prefetch.tensor.3d.L2.global [%0, {%1, %2, %3}];\n}"
                 ::"l"(m), "r"(0), "r"(row), "r"(cb) : "memory");
}
__device__ __forceinline__ void l2_prefetch(const void* p, uint32_t bytes) {
    asm volatile("{\n.reg .pred p;\nelect.sync _|p, 0xffffffff;\n@p cp.async.bulk.prefetch.L2.global [%0], %1;\n}" ::"l"(p), "r"(bytes) : "memory");
}
__device__ __forceinline__ void bulk_store(void* dst, uint32_t src, uint32_t bytes) {
    asm volatile("{\n.reg .pred p;\nelect.sync _|p, 0xffffffff;\n@p cp.async.bulk.global.shared::cta.bulk_group [%0], [%1], %2;\n}"
                 ::"l"(dst), "r"(src), "r"(bytes) : "memory");
}
__device__ __forceinline__ void flag_wait(const uint32_t* f, uint32_t target) {
    asm volatile("{\n.reg .pred p;\n.reg .u32 v;\n"
                 "L_%=:\nld.acquire.gpu.global.u32 v, [%0];\nsub.u32 v, v, %1;\nsetp.lt.s32 p, v, 0;\n@p nanosleep.u32 100;\n@p bra L_%=;\n}"
                 ::"l"(f), "r"(target) : "memory");
}
__device__ __forceinline__ uint4 ld_poll(const uint4* p) {
    uint4 v;
    asm volatile("{\n.reg .b128 t;\nld.relaxed.gpu.global.b128 t, [%4];\nmov.b128 {%0, %1, %2, %3}, t;\n}"
                 : "=r"(v.x), "=r"(v.y), "=r"(v.z), "=r"(v.w) : "l"(p) : "memory");
    return v;
}
__device__ __forceinline__ void st_pub(uint4* p, uint4 v, bool on) {
    asm volatile("{\n.reg .pred p;\n.reg .b128 t;\nsetp.ne.s32 p, %5, 0;\nmov.b128 t, {%1, %2, %3, %4};\n@p st.relaxed.gpu.global.b128 [%0], t;\n}"
                 ::"l"(p), "r"(v.x), "r"(v.y), "r"(v.z), "r"(v.w), "r"((int)on) : "memory");
}
__device__ __forceinline__ void st_pub(uint32_t* p, uint32_t v, bool on) {
    asm volatile("{\n.reg .pred p;\nsetp.ne.s32 p, %2, 0;\n@p st.relaxed.gpu.global.u32 [%0], %1;\n}" ::"l"(p), "r"(v), "r"((int)on) : "memory");
}
__device__ __forceinline__ void flag_add(uint32_t* p) {
    asm volatile("red.release.gpu.global.add.u32 [%0], 1;" ::"l"(p) : "memory");
}
__device__ __forceinline__ uint32_t lds32(uint32_t a) {
    uint32_t v;
    asm volatile("ld.shared.u32 %0, [%1];" : "=r"(v) : "r"(a) : "memory");
    return v;
}
__device__ __forceinline__ uint4 lds128(uint32_t a) {
    uint4 v;
    asm volatile("ld.shared.v4.u32 {%0, %1, %2, %3}, [%4];" : "=r"(v.x), "=r"(v.y), "=r"(v.z), "=r"(v.w) : "r"(a) : "memory");
    return v;
}
__device__ __forceinline__ void sched_fence(uint32_t& v, uint32_t z) {
    uint32_t ck;
    asm volatile("mov.u32 %0, %%clock;" : "=r"(ck)::"memory");
    v ^= ck & z;
}
__device__ __forceinline__ void fence_async_global() { asm volatile("fence.proxy.async.global;" ::: "memory"); }
__device__ __forceinline__ void fence_async_smem() { asm volatile("fence.proxy.async.shared::cta;" ::: "memory"); }
__device__ __forceinline__ void bar_sync(int id, int n) { asm volatile("bar.sync %0, %1;" ::"r"(id), "r"(n) : "memory"); }
__device__ __forceinline__ void bar_arrive(int id, int n) { asm volatile("bar.arrive %0, %1;" ::"r"(id), "r"(n) : "memory"); }
__device__ __forceinline__ void wg_fence() { asm volatile("wgmma.fence.sync.aligned;" ::: "memory"); }
__device__ __forceinline__ void wg_commit() { asm volatile("wgmma.commit_group.sync.aligned;" ::: "memory"); }
template <int N> __device__ __forceinline__ void wg_wait() { asm volatile("wgmma.wait_group.sync.aligned %0;" ::"n"(N) : "memory"); }
template <int N> __device__ __forceinline__ void reg_fence(float (&d)[N]) {
#pragma unroll
    for (int i = 0; i < N; i++) asm volatile("" : "+f"(d[i])::"memory");
}
template <int N> __device__ __forceinline__ void reg_fence(uint32_t (&d)[N]) {
#pragma unroll
    for (int i = 0; i < N; i++) asm volatile("" : "+r"(d[i])::"memory");
}
__device__ __forceinline__ uint32_t desc_k(uint32_t a) { return ((a & 0x3ffff) >> 4) | (1u << 16); }
__device__ __forceinline__ uint32_t desc_mn(uint32_t a) { return ((a & 0x3ffff) >> 4) | (1024u << 16); }

template <int TB>
__device__ __forceinline__ void wgmma_ss128(float (&d)[64], uint32_t da, uint32_t db, int acc, uint32_t ha = 0x40000040u, uint32_t hb = 0x40000040u) {
    asm volatile("{\n.reg .pred p;\n.reg .b64 a, b;\nsetp.ne.b32 p, %66, 0;\nmov.b64 a, {%64, %68};\nmov.b64 b, {%65, %69};\n"
        "wgmma.mma_async.sync.aligned.m64n128k16.f32.bf16.bf16 {%0, %1, %2, %3, %4, %5, %6, %7, %8, %9, %10, %11, %12, %13, %14, %15, %16, %17, %18, %19, %20, %21, %22, %23, %24, %25, %26, %27, %28, %29, %30, %31, %32, %33, %34, %35, %36, %37, %38, %39, %40, %41, %42, %43, %44, %45, %46, %47, %48, %49, %50, %51, %52, %53, %54, %55, %56, %57, %58, %59, %60, %61, %62, %63}, a, b, p, 1, 1, 0, %67;\n}"
        : "+f"(d[0]), "+f"(d[1]), "+f"(d[2]), "+f"(d[3]), "+f"(d[4]), "+f"(d[5]), "+f"(d[6]), "+f"(d[7]), "+f"(d[8]), "+f"(d[9]), "+f"(d[10]), "+f"(d[11]), "+f"(d[12]), "+f"(d[13]), "+f"(d[14]), "+f"(d[15]), "+f"(d[16]), "+f"(d[17]), "+f"(d[18]), "+f"(d[19]), "+f"(d[20]), "+f"(d[21]), "+f"(d[22]), "+f"(d[23]), "+f"(d[24]), "+f"(d[25]), "+f"(d[26]), "+f"(d[27]), "+f"(d[28]), "+f"(d[29]), "+f"(d[30]), "+f"(d[31]), "+f"(d[32]), "+f"(d[33]), "+f"(d[34]), "+f"(d[35]), "+f"(d[36]), "+f"(d[37]), "+f"(d[38]), "+f"(d[39]), "+f"(d[40]), "+f"(d[41]), "+f"(d[42]), "+f"(d[43]), "+f"(d[44]), "+f"(d[45]), "+f"(d[46]), "+f"(d[47]), "+f"(d[48]), "+f"(d[49]), "+f"(d[50]), "+f"(d[51]), "+f"(d[52]), "+f"(d[53]), "+f"(d[54]), "+f"(d[55]), "+f"(d[56]), "+f"(d[57]), "+f"(d[58]), "+f"(d[59]), "+f"(d[60]), "+f"(d[61]), "+f"(d[62]), "+f"(d[63])
        : "r"(da), "r"(db), "r"(acc), "n"(TB), "r"(ha), "r"(hb));
}
template <int TB>
__device__ __forceinline__ void wgmma_ss128_init(float (&d)[64], uint32_t da, uint32_t db, uint32_t ha = 0x40000040u, uint32_t hb = 0x40000040u) {
    asm volatile("{\n.reg .pred p;\n.reg .b64 a, b;\nsetp.ne.b32 p, 0, 0;\nmov.b64 a, {%64, %67};\nmov.b64 b, {%65, %68};\n"
        "wgmma.mma_async.sync.aligned.m64n128k16.f32.bf16.bf16 {%0, %1, %2, %3, %4, %5, %6, %7, %8, %9, %10, %11, %12, %13, %14, %15, %16, %17, %18, %19, %20, %21, %22, %23, %24, %25, %26, %27, %28, %29, %30, %31, %32, %33, %34, %35, %36, %37, %38, %39, %40, %41, %42, %43, %44, %45, %46, %47, %48, %49, %50, %51, %52, %53, %54, %55, %56, %57, %58, %59, %60, %61, %62, %63}, a, b, p, 1, 1, 0, %66;\n}"
        : "=f"(d[0]), "=f"(d[1]), "=f"(d[2]), "=f"(d[3]), "=f"(d[4]), "=f"(d[5]), "=f"(d[6]), "=f"(d[7]), "=f"(d[8]), "=f"(d[9]), "=f"(d[10]), "=f"(d[11]), "=f"(d[12]), "=f"(d[13]), "=f"(d[14]), "=f"(d[15]), "=f"(d[16]), "=f"(d[17]), "=f"(d[18]), "=f"(d[19]), "=f"(d[20]), "=f"(d[21]), "=f"(d[22]), "=f"(d[23]), "=f"(d[24]), "=f"(d[25]), "=f"(d[26]), "=f"(d[27]), "=f"(d[28]), "=f"(d[29]), "=f"(d[30]), "=f"(d[31]), "=f"(d[32]), "=f"(d[33]), "=f"(d[34]), "=f"(d[35]), "=f"(d[36]), "=f"(d[37]), "=f"(d[38]), "=f"(d[39]), "=f"(d[40]), "=f"(d[41]), "=f"(d[42]), "=f"(d[43]), "=f"(d[44]), "=f"(d[45]), "=f"(d[46]), "=f"(d[47]), "=f"(d[48]), "=f"(d[49]), "=f"(d[50]), "=f"(d[51]), "=f"(d[52]), "=f"(d[53]), "=f"(d[54]), "=f"(d[55]), "=f"(d[56]), "=f"(d[57]), "=f"(d[58]), "=f"(d[59]), "=f"(d[60]), "=f"(d[61]), "=f"(d[62]), "=f"(d[63])
        : "r"(da), "r"(db), "n"(TB), "r"(ha), "r"(hb));
}
template <int TB>
__device__ __forceinline__ void wgmma_ss64(float (&d)[32], uint32_t da, uint32_t db, int acc, uint32_t ha = 0x40000040u, uint32_t hb = 0x40000040u) {
    asm volatile("{\n.reg .pred p;\n.reg .b64 a, b;\nsetp.ne.b32 p, %34, 0;\nmov.b64 a, {%32, %36};\nmov.b64 b, {%33, %37};\n"
        "wgmma.mma_async.sync.aligned.m64n64k16.f32.bf16.bf16 {%0, %1, %2, %3, %4, %5, %6, %7, %8, %9, %10, %11, %12, %13, %14, %15, %16, %17, %18, %19, %20, %21, %22, %23, %24, %25, %26, %27, %28, %29, %30, %31}, a, b, p, 1, 1, 0, %35;\n}"
        : "+f"(d[0]), "+f"(d[1]), "+f"(d[2]), "+f"(d[3]), "+f"(d[4]), "+f"(d[5]), "+f"(d[6]), "+f"(d[7]), "+f"(d[8]), "+f"(d[9]), "+f"(d[10]), "+f"(d[11]), "+f"(d[12]), "+f"(d[13]), "+f"(d[14]), "+f"(d[15]), "+f"(d[16]), "+f"(d[17]), "+f"(d[18]), "+f"(d[19]), "+f"(d[20]), "+f"(d[21]), "+f"(d[22]), "+f"(d[23]), "+f"(d[24]), "+f"(d[25]), "+f"(d[26]), "+f"(d[27]), "+f"(d[28]), "+f"(d[29]), "+f"(d[30]), "+f"(d[31])
        : "r"(da), "r"(db), "r"(acc), "n"(TB), "r"(ha), "r"(hb));
}
template <int TB>
__device__ __forceinline__ void wgmma_ss64_init(float (&d)[32], uint32_t da, uint32_t db, uint32_t ha = 0x40000040u, uint32_t hb = 0x40000040u) {
    asm volatile("{\n.reg .pred p;\n.reg .b64 a, b;\nsetp.ne.b32 p, 0, 0;\nmov.b64 a, {%32, %35};\nmov.b64 b, {%33, %36};\n"
        "wgmma.mma_async.sync.aligned.m64n64k16.f32.bf16.bf16 {%0, %1, %2, %3, %4, %5, %6, %7, %8, %9, %10, %11, %12, %13, %14, %15, %16, %17, %18, %19, %20, %21, %22, %23, %24, %25, %26, %27, %28, %29, %30, %31}, a, b, p, 1, 1, 0, %34;\n}"
        : "=f"(d[0]), "=f"(d[1]), "=f"(d[2]), "=f"(d[3]), "=f"(d[4]), "=f"(d[5]), "=f"(d[6]), "=f"(d[7]), "=f"(d[8]), "=f"(d[9]), "=f"(d[10]), "=f"(d[11]), "=f"(d[12]), "=f"(d[13]), "=f"(d[14]), "=f"(d[15]), "=f"(d[16]), "=f"(d[17]), "=f"(d[18]), "=f"(d[19]), "=f"(d[20]), "=f"(d[21]), "=f"(d[22]), "=f"(d[23]), "=f"(d[24]), "=f"(d[25]), "=f"(d[26]), "=f"(d[27]), "=f"(d[28]), "=f"(d[29]), "=f"(d[30]), "=f"(d[31])
        : "r"(da), "r"(db), "n"(TB), "r"(ha), "r"(hb));
}
__device__ __forceinline__ void wgmma_rs128(float (&d)[64], uint32_t a0, uint32_t a1, uint32_t a2, uint32_t a3, uint32_t db, int acc, uint32_t hb = 0x40000040u) {
    asm volatile("{\n.reg .pred p;\n.reg .b64 b;\nsetp.ne.b32 p, %69, 0;\nmov.b64 b, {%68, %70};\n"
        "wgmma.mma_async.sync.aligned.m64n128k16.f32.bf16.bf16 {%0, %1, %2, %3, %4, %5, %6, %7, %8, %9, %10, %11, %12, %13, %14, %15, %16, %17, %18, %19, %20, %21, %22, %23, %24, %25, %26, %27, %28, %29, %30, %31, %32, %33, %34, %35, %36, %37, %38, %39, %40, %41, %42, %43, %44, %45, %46, %47, %48, %49, %50, %51, %52, %53, %54, %55, %56, %57, %58, %59, %60, %61, %62, %63}, {%64, %65, %66, %67}, b, p, 1, 1, 1;\n}"
        : "+f"(d[0]), "+f"(d[1]), "+f"(d[2]), "+f"(d[3]), "+f"(d[4]), "+f"(d[5]), "+f"(d[6]), "+f"(d[7]), "+f"(d[8]), "+f"(d[9]), "+f"(d[10]), "+f"(d[11]), "+f"(d[12]), "+f"(d[13]), "+f"(d[14]), "+f"(d[15]), "+f"(d[16]), "+f"(d[17]), "+f"(d[18]), "+f"(d[19]), "+f"(d[20]), "+f"(d[21]), "+f"(d[22]), "+f"(d[23]), "+f"(d[24]), "+f"(d[25]), "+f"(d[26]), "+f"(d[27]), "+f"(d[28]), "+f"(d[29]), "+f"(d[30]), "+f"(d[31]), "+f"(d[32]), "+f"(d[33]), "+f"(d[34]), "+f"(d[35]), "+f"(d[36]), "+f"(d[37]), "+f"(d[38]), "+f"(d[39]), "+f"(d[40]), "+f"(d[41]), "+f"(d[42]), "+f"(d[43]), "+f"(d[44]), "+f"(d[45]), "+f"(d[46]), "+f"(d[47]), "+f"(d[48]), "+f"(d[49]), "+f"(d[50]), "+f"(d[51]), "+f"(d[52]), "+f"(d[53]), "+f"(d[54]), "+f"(d[55]), "+f"(d[56]), "+f"(d[57]), "+f"(d[58]), "+f"(d[59]), "+f"(d[60]), "+f"(d[61]), "+f"(d[62]), "+f"(d[63])
        : "r"(a0), "r"(a1), "r"(a2), "r"(a3), "r"(db), "r"(acc), "r"(hb));
}

__device__ __forceinline__ uint32_t pack2(float lo, float hi) {
    uint32_t r;
    asm("cvt.rn.bf16x2.f32 %0, %1, %2;" : "=r"(r) : "f"(hi), "f"(lo));
    return r;
}
__device__ __forceinline__ float bf_lo(uint32_t v) { return __uint_as_float(v << 16); }
__device__ __forceinline__ float bf_hi(uint32_t v) { return __uint_as_float(v & 0xffff0000u); }
__device__ __forceinline__ float rbf(float v) { return bf_lo(pack2(v, v)); }
__device__ __forceinline__ uint32_t badd(uint32_t a, uint32_t b) {
    uint32_t r;
    asm("add.rn.bf16x2 %0, %1, %2;" : "=r"(r) : "r"(a), "r"(b));
    return r;
}
__device__ __forceinline__ uint32_t bsub(uint32_t a, uint32_t b) {
    uint32_t r;
    asm("sub.rn.bf16x2 %0, %1, %2;" : "=r"(r) : "r"(a), "r"(b));
    return r;
}
__device__ __forceinline__ uint32_t bmul(uint32_t a, uint32_t b) {
    uint32_t r;
    asm("mul.rn.bf16x2 %0, %1, %2;" : "=r"(r) : "r"(a), "r"(b));
    return r;
}
__device__ __forceinline__ uint32_t ln_apply(uint32_t x, uint32_t mb, float rs, uint32_t scale, uint32_t shift) {
    const uint32_t d = bsub(x, mb);
    return badd(bmul(pack2(bf_lo(d) * rs, bf_hi(d) * rs), scale), shift);
}
__device__ __forceinline__ float ex2(float v) {
    float r;
    asm("ex2.approx.ftz.f32 %0, %1;" : "=f"(r) : "f"(v));
    return r;
}
__device__ __forceinline__ float rcp(float v) {
    float r;
    asm("rcp.approx.ftz.f32 %0, %1;" : "=f"(r) : "f"(v));
    return r;
}
__device__ __forceinline__ float sqrt_fast(float v) {
    float r;
    asm("sqrt.approx.ftz.f32 %0, %1;" : "=f"(r) : "f"(v));
    return r;
}
__device__ __forceinline__ float ln_rstd(float var) { return rcp(rbf(sqrt_fast(rbf(rbf(var) + 1e-5f)))); }
__device__ __forceinline__ float sigmoid(float v) { return rcp(1.f + ex2(-1.4426950408889634f * v)); }
__device__ __forceinline__ float quad_sum(float v) {
    v += __shfl_xor_sync(0xffffffffu, v, 1);
    return v + __shfl_xor_sync(0xffffffffu, v, 2);
}

constexpr uint32_t HI_128 = 0x40000040u, HI_IMG = 0x80000080u, HI_Q = 0x80000040u;
template <int M, int RH>
__device__ __forceinline__ uint4 img_pack(const float (&d)[64], float s) {
    uint4 v;
    v.x = pack2(d[16 * M + 2 * RH] * s, d[16 * M + 2 * RH + 1] * s);
    v.y = pack2(d[16 * M + 4 + 2 * RH] * s, d[16 * M + 5 + 2 * RH] * s);
    v.z = pack2(d[16 * M + 8 + 2 * RH] * s, d[16 * M + 9 + 2 * RH] * s);
    v.w = pack2(d[16 * M + 12 + 2 * RH] * s, d[16 * M + 13 + 2 * RH] * s);
    return v;
}
template <int M>
__device__ __forceinline__ void img_store_global(uint8_t* img, uint32_t toff, const float (&d)[64], float s0, float s1) {
    uint4* p = reinterpret_cast<uint4*>(img + toff) + M * 32;
    p[0] = img_pack<M, 0>(d, s0);
    p[128] = img_pack<M, 1>(d, s1);
}
__device__ __forceinline__ void sts128(uint32_t a, uint4 v) {
    asm volatile("st.shared.v4.b32 [%0], {%1, %2, %3, %4};" ::"r"(a), "r"(v.x), "r"(v.y), "r"(v.z), "r"(v.w) : "memory");
}
constexpr float SM_C = 0.08838834764831845f * 1.4426950408889634f;
__device__ __forceinline__ float pack2f(float lo, float hi) {
    float r;
    asm("{\n.reg .b32 t;\ncvt.rn.bf16x2.f32 t, %1, %2;\nmov.b32 %0, t;\n}" : "=f"(r) : "f"(hi), "f"(lo));
    return r;
}
template <int M, bool SCALE, bool PARK>
__device__ __forceinline__ void pack_group(float (&d)[64], float (&v)[8], float s0, float s1) {
#pragma unroll
    for (int i = 0; i < 8; i++) {
        const int k = 16 * M + 4 * (i & 3) + 2 * (i >> 2);
        v[i] = SCALE ? pack2f(d[k] * (i < 4 ? s0 : s1), d[k + 1] * (i < 4 ? s0 : s1)) : pack2f(d[k], d[k + 1]);
        if (PARK && M > 0) d[16 * (M > 0 ? M - 1 : 0) + i] = v[i];
    }
}
__device__ __forceinline__ uint32_t q_off(uint32_t toff) { return (((toff >> 1) & ~2047u) ^ 8192) + (toff & 511); }
template <int M, bool PARK>
__device__ __forceinline__ void ctx_store_part(float4* p, float (&d)[64], float i0, float i1) {
    float v[8];
    pack_group<M, true, PARK>(d, v, i0, i1);
    p[M * 32] = make_float4(v[0], v[1], v[2], v[3]);
    p[M * 32 + 128] = make_float4(v[4], v[5], v[6], v[7]);
}
template <bool PARK>
__device__ __forceinline__ void ctx_store(uint8_t* img, uint32_t toff, float (&o)[64], float l0, float l1) {
    const float i0 = rcp(quad_sum(l0)), i1 = rcp(quad_sum(l1));
    float4* p = reinterpret_cast<float4*>(img + toff);
    ctx_store_part<0, PARK>(p, o, i0, i1); ctx_store_part<1, PARK>(p, o, i0, i1); ctx_store_part<2, PARK>(p, o, i0, i1); ctx_store_part<3, PARK>(p, o, i0, i1);
}

template <int M>
__device__ __forceinline__ void tile_store_part(float4* p, uint32_t a, float (&d)[64], float i0, float i1, int ctx) {
    float v[8];
    pack_group<M, true, true>(d, v, i0, i1);
#pragma unroll
    for (int h = 0; h < 2; h++)
        asm volatile("{\n.reg .pred p;\nsetp.ne.s32 p, %6, 0;\n@p st.global.v4.f32 [%0], {%2, %3, %4, %5};\n@!p st.shared.v4.f32 [%1], {%2, %3, %4, %5};\n}"
                     ::"l"(p + M * 32 + h * 128), "r"(a + (M >> 1) * 16384 + (M & 1) * 512 + h * 1024),
                     "f"(v[4 * h]), "f"(v[4 * h + 1]), "f"(v[4 * h + 2]), "f"(v[4 * h + 3]), "r"(ctx) : "memory");
}
__device__ __forceinline__ void tile_store(uint8_t* img, uint32_t a, uint32_t toff, float (&d)[64], float i0, float i1, int ctx) {
    float4* p = reinterpret_cast<float4*>(img + toff);
    a += q_off(toff);
    tile_store_part<0>(p, a, d, i0, i1, ctx); tile_store_part<1>(p, a, d, i0, i1, ctx);
    tile_store_part<2>(p, a, d, i0, i1, ctx); tile_store_part<3>(p, a, d, i0, i1, ctx);
}

__device__ __forceinline__ void slot_wait(uint32_t bars, uint32_t& ph, uint32_t slot) {
    mbar_wait(bars + 8 * slot, (ph >> slot) & 1);
    ph ^= 1u << slot;
}
__device__ __forceinline__ void release_if(uint32_t eb, uint32_t slot, bool on) {
    asm volatile("{\n.reg .pred p;\nsetp.ne.s32 p, %1, 0;\n@p mbarrier.arrive.shared::cluster.b64 _, [%0];\n}" ::"r"(eb + 8 * slot), "r"((int)on) : "memory");
}
__device__ __forceinline__ void slot_acquire(uint32_t sb, uint32_t& ph, uint32_t slot) {
    slot_wait(sb + BAR_EMPTY, ph, slot);
    asm volatile("{\n.reg .pred p;\nelect.sync _|p, 0xffffffff;\n@p mbarrier.arrive.expect_tx.shared::cta.b64 _, [%0], 32768;\n}"
                 ::"r"(sb + BAR_FULL + 8 * slot) : "memory");
}
__device__ __forceinline__ void load_bulk(uint32_t sb, uint32_t slot, uint32_t off, const void* src, uint32_t bytes, bool both, bool first) {
    if (both)
        asm volatile("{\n.reg .pred p;\nelect.sync _|p, 0xffffffff;\n"
                     "@p cp.async.bulk.shared::cluster.global.mbarrier::complete_tx::bytes.multicast::cluster.L2::cache_hint [%0], [%1], %5, [%2], %4, %3;\n}"
                     ::"r"(sb + slot * SLOT + off), "l"(src), "r"(sb + BAR_FULL + 8 * slot), "l"(first ? L2_FIRST : L2_NORMAL), "h"((uint16_t)3),
                     "r"(bytes) : "memory");
    else
        asm volatile("{\n.reg .pred p;\nelect.sync _|p, 0xffffffff;\n"
                     "@p cp.async.bulk.shared::cluster.global.mbarrier::complete_tx::bytes.L2::cache_hint [%0], [%1], %4, [%2], %3;\n}"
                     ::"r"(sb + slot * SLOT + off), "l"(src), "r"(sb + BAR_FULL + 8 * slot), "l"(first ? L2_FIRST : L2_NORMAL), "r"(bytes) : "memory");
}
__device__ __forceinline__ void load_tile(uint32_t sb, uint32_t slot, uint32_t off, const CUtensorMap* m, int row, int cb, bool both, bool first) {
    if (both)
        asm volatile("{\n.reg .pred p;\nelect.sync _|p, 0xffffffff;\n"
                     "@p cp.async.bulk.tensor.3d.shared::cluster.global.mbarrier::complete_tx::bytes.multicast::cluster.L2::cache_hint [%0], [%1, {%3, %4, %5}], [%2], %7, %6;\n}"
                     ::"r"(sb + slot * SLOT + off), "l"(m), "r"(sb + BAR_FULL + 8 * slot), "r"(0), "r"(row), "r"(cb),
                     "l"(first ? L2_FIRST : L2_NORMAL), "h"((uint16_t)3) : "memory");
    else
        asm volatile("{\n.reg .pred p;\nelect.sync _|p, 0xffffffff;\n"
                     "@p cp.async.bulk.tensor.3d.shared::cluster.global.mbarrier::complete_tx::bytes.L2::cache_hint [%0], [%1, {%3, %4, %5}], [%2], %6;\n}"
                     ::"r"(sb + slot * SLOT + off), "l"(m), "r"(sb + BAR_FULL + 8 * slot), "r"(0), "r"(row), "r"(cb),
                     "l"(first ? L2_FIRST : L2_NORMAL) : "memory");
}
__device__ __forceinline__ uint32_t ring_next(uint32_t r) { return r == 4 ? 0 : r + 1; }
__device__ __forceinline__ uint32_t w_table(int hp) { return hp ? 0x3104u : 0x4210u; }
__device__ __forceinline__ uint32_t a_table(int hp) { return hp ? 0x625u : 0x635u; }
__device__ __forceinline__ uint32_t a_next(uint32_t& t) {
    const uint32_t s = t & 15;
    t = (t >> 4) | (s << 8);
    return s;
}
constexpr uint32_t O_TABLE = 0x1604235u;
__device__ __forceinline__ uint32_t o_next(uint32_t& t) {
    const uint32_t s = t & 15;
    t = (t >> 4) | (s << 24);
    return s;
}
__device__ __forceinline__ int o_head(int i, int kh) { return i < 16 ? 4 * (i & 7) + 2 * (kh ^ 1) + (i >> 3) : 29 + 2 * kh; }

template <bool INIT>
__device__ __forceinline__ void gemm_issue(float (&d)[64], uint32_t a, uint32_t b, int acc, bool img) {
    const uint32_t ha = img ? HI_IMG : HI_128, o2 = img ? 32 : 4, o4 = img ? 64 : 1024;
    wg_fence();
#pragma unroll
    for (int k = 0; k < 8; k++) {
        if (INIT && k == 0) wgmma_ss128_init<1>(d, a, b, ha);
        else wgmma_ss128<1>(d, a + (k >> 2) * o4 + ((k >> 1) & 1) * o2 + (k & 1) * 2, b + k * 128, k ? 1 : acc, ha);
    }
    wg_commit();
}

template <bool ODD>
__device__ __forceinline__ bool proj_tile(float (&acc)[64], float (&prev)[64], int t, int q0, uint32_t sb, int wg, uint32_t eb, bool rel, uint32_t& fph,
                                          uint32_t wtab, uint32_t& atab, uint8_t* prev_img, uint32_t toff, float s0, float s1, bool first,
                                          const bf16* x, int xrow, uint32_t (&v)[32]) {
    const uint32_t a0 = desc_k(sb + (wg ^ (ODD && t == 5)) * 8192), b0 = desc_mn(sb);
    const int lane = threadIdx.x & 31;
    constexpr int U = ODD ? UNR : 1;
#pragma unroll U
    for (int q = ODD ? 0 : q0; q < 4; q++) {
        const uint32_t ws = (wtab >> (4 * q)) & 15, as = a_next(atab);
        if (!ODD && t != 2) slot_wait(sb + BAR_FULL, fph, ws);
        slot_wait(sb + BAR_FULL, fph, as);
        if (ODD && q == 2 && t == 5) {
#pragma unroll
            for (int i = 0; i < 8; i++) sts128(sb + 5 * SLOT + q_off(toff) + (i >> 2) * 16384 + (i & 2) * 256 + (i & 1) * 1024, make_uint4(v[4 * i], v[4 * i + 1], v[4 * i + 2], v[4 * i + 3]));
        }
        bar_sync(1 + wg, 256);
        gemm_issue<false>(acc, a0 + as * (SLOT / 16), b0 + ws * (SLOT / 16), q, false);
        bar_arrive(2 - wg, 256);
        wg_wait<1>();
        reg_fence(prev);
        if (ODD && t == 5) {
            if (q == 0) {
#pragma unroll
                for (int i = 0; i < 32; i++) {
                    const int k = 16 * (i >> 3) + 4 * (i & 3) + ((i >> 1) & 2);
                    v[i] = pack2(prev[k], prev[k + 1]);
                }
            }
            if (q == 2) {
                fence_async_smem();
                slot_wait(sb + BAR_FULL, fph, wtab & 15);
                wg_wait<0>();
                release_if(eb, as, rel);
                release_if(eb, ws, rel);
                reg_fence(acc);
                return true;
            }
        } else {
            if (first) {
                const uint4* xp = reinterpret_cast<const uint4*>(x) + xrow * 64;
                if (!ODD) {
                    if (q == XQ && lane < 16) asm volatile("prefetch.global.L1 [%0];" ::"l"(xp + lane * 8) : "memory");
                    if (q == 3) {
#pragma unroll
                        for (int i = 0; i < 4; i++) {
                            const uint4 u = __ldg(xp + lane + 32 * i);
                            v[4 * i] = u.x; v[4 * i + 1] = u.y; v[4 * i + 2] = u.z; v[4 * i + 3] = u.w;
                        }
                        v[16] = __ldg(&xp[0].x) << 16;
                        v[17] = __ldg(&xp[64].x) << 16;
                        float st[4] = {0.f, 0.f, 0.f, 0.f};
#pragma unroll
                        for (int k = 0; k < 16; k++) {
                            const float d0 = bf_lo(v[k]) - __uint_as_float(v[16 + (k >> 3)]), d1 = bf_hi(v[k]) - __uint_as_float(v[16 + (k >> 3)]);
                            st[k >> 3] += d0 + d1;
                            st[2 + (k >> 3)] = fmaf(d0, d0, fmaf(d1, d1, st[2 + (k >> 3)]));
                        }
#pragma unroll
                        for (int i = 0; i < 4; i++) v[20 + i] = __float_as_uint(st[i]);
                    }
                } else if (q == 0) {
#pragma unroll
                    for (int i = 0; i < 20; i++)
                        v[20 + (i & 3)] = __float_as_uint(__uint_as_float(v[20 + (i & 3)]) + __uint_as_float(__shfl_xor_sync(0xffffffffu, v[20 + (i & 3)], 1 << (i >> 2))));
                } else if (q == 1) {
#pragma unroll
                    for (int i = 0; i < 2; i++) {
                        const float d = __uint_as_float(v[20 + i]) * (1.f / 512.f);
                        const float rs = ln_rstd(fmaxf(fmaf(-d, d, __uint_as_float(v[22 + i]) * (1.f / 512.f)), 0.f));
                        const uint32_t mb = pack2(__uint_as_float(v[16 + i]) + d, __uint_as_float(v[16 + i]) + d);
#pragma unroll
                        for (int k = 8 * i; k < 8 * i + 8; k++) {
                            const uint32_t y = bsub(v[k], mb);
                            v[k] = pack2(bf_lo(y) * rs, bf_hi(y) * rs);
                        }
                    }
                } else {
                    mbar_wait(sb + BAR_FLAG + 8 * 8, 0);
                    const uint4 a = lds128(sb + SM_TAB + q * 512 + lane * 16), c = lds128(sb + SM_TAB - 1024 + q * 512 + lane * 16);
                    uint8_t* p = g_h + ((xrow >> 7) * 8 + (q & 1) * 4 + (lane >> 3)) * 16384 + (xrow & 127) * 128;
#pragma unroll
                    for (int i = 0; i < 2; i++) {
                        *reinterpret_cast<uint4*>(p + i * 128 + (((lane ^ xrow ^ i) & 7) << 4)) =
                            make_uint4(badd(bmul(v[8 * i], a.x), c.x), badd(bmul(v[8 * i + 1], a.y), c.y),
                                       badd(bmul(v[8 * i + 2], a.z), c.z), badd(bmul(v[8 * i + 3], a.w), c.w));
#pragma unroll
                        for (int k = 0; k < 4; k++) v[8 * i + k] = v[8 * i + 4 + k];
                    }
                    __syncwarp();
                    mbar_arrive_if(sb + BAR_DONE, lane == 0 && q == 3);
                }
            }
            if (ODD || !first) {
                if (q == 0) img_store_global<0>(prev_img, toff, prev, s0, s1);
                if (q == 1) img_store_global<1>(prev_img, toff, prev, s0, s1);
                if (q == 2) img_store_global<2>(prev_img, toff, prev, s0, s1);
                if (q == 3) img_store_global<3>(prev_img, toff, prev, s0, s1);
            }
        }
        wg_wait<0>();
        release_if(eb, as, rel && !(ODD && (q & 1) && t == 5));
        if (ODD) release_if(eb, ws, rel && t != 1);
    }
    reg_fence(acc);
    return false;
}

__device__ __forceinline__ void qk_issue(float (&s)[64], uint32_t q, uint32_t k) {
    wg_fence();
    wgmma_ss128_init<0>(s, q, k, HI_Q, HI_IMG);
#pragma unroll
    for (int i = 1; i < 8; i++) wgmma_ss128<0>(s, q + (i >> 2) * 1024 + (i & 2) * 16 + (i & 1) * 2, k + (i >> 1) * 32 + (i & 1) * 2, 1, HI_Q, HI_IMG);
    wg_commit();
}
__device__ __forceinline__ void qk_issue(float (&s)[32], uint32_t q, uint32_t k) {
    wg_fence();
    wgmma_ss64_init<0>(s, q, k, HI_Q, HI_IMG);
#pragma unroll
    for (int i = 1; i < 8; i++) wgmma_ss64<0>(s, q + (i >> 2) * 1024 + (i & 2) * 16 + (i & 1) * 2, k + (i >> 1) * 32 + (i & 1) * 2, 1, HI_Q, HI_IMG);
    wg_commit();
}
__device__ __forceinline__ void pv_issue(float (&o)[64], const uint32_t (&p)[32], uint32_t v, int acc, bool half) {
    if (half) {
        asm volatile("// half" ::: "memory");
        wg_fence();
#pragma unroll
        for (int i = 0; i < 4; i++) wgmma_rs128(o, p[4 * i], p[4 * i + 1], p[4 * i + 2], p[4 * i + 3], v + i * 256, i ? 1 : acc, HI_IMG);
        wg_commit();
        asm volatile("// half" ::: "memory");
    } else {
        wg_fence();
#pragma unroll
        for (int i = 0; i < 8; i++) wgmma_rs128(o, p[4 * i], p[4 * i + 1], p[4 * i + 2], p[4 * i + 3], v + i * 256, i ? 1 : acc, HI_IMG);
        wg_commit();
    }
}
__device__ __forceinline__ void tri_mask(float (&s)[64], float x) {
#pragma unroll
    for (int k = 0; k < 16; k++) {
        float b;
        asm("sub.sat.f32 %0, %1, %2;" : "=f"(b) : "f"((float)(8 * (k >> 1) + (k & 1))), "f"(x));
        const int i = 32 + 4 * (k >> 1) + (k & 1);
        asm("fma.rn.f32 %0, %1, 0fFF61B1E6, %0;" : "+f"(s[i]) : "f"(b));
        if (k < 14) asm("fma.rn.f32 %0, %1, 0fFF61B1E6, %0;" : "+f"(s[i + 6]) : "f"(b));
    }
}
__device__ __forceinline__ void tri_mask_copy(float (&s)[64], const float (&h)[32], float x) {
#pragma unroll
    for (int i = 0; i < 32; i++) {
        asm("{\n.reg .pred p;\nsetp.lt.f32 p, %2, %3;\nselp.f32 %0, 0fFF800000, %1, p;\n}"
            : "=f"(s[i]) : "f"(h[i]), "f"(x), "f"((float)(8 * (i >> 2) - 4 * (i & 2) + (i & 1))));
        s[32 + i] = __uint_as_float(0xff800000u);
    }
}
constexpr float SM_HI = 1152921504606846976.f, SM_LO = 1.f / 1152921504606846976.f;
__device__ __forceinline__ bool softmax_unsafe(float t0, float t1, bool first) {
    bool bad = __any_sync(0xffffffffu, fmaxf(t0, t1) > SM_HI);
    if (first) {
        uint32_t a = __ballot_sync(0xffffffffu, t0 >= SM_LO), b = __ballot_sync(0xffffffffu, t1 >= SM_LO);
        a |= a >> 1;
        b |= b >> 1;
        bad |= ((a | (a >> 2)) & (b | (b >> 2)) & 0x11111111u) != 0x11111111u;
    }
    return bad;
}
__device__ __forceinline__ void softmax_shift(float (&s)[64], float d0, float d1) {
#pragma unroll
    for (int i = 0; i < 64; i++) s[i] -= (i & 2) ? d1 : d0;
}
__device__ __forceinline__ void softmax_remax(float (&s)[64], float (&m)[2], bool first, float& a0, float& a1) {
    float m0 = fmaxf(s[0], s[1]), m1 = fmaxf(s[2], s[3]);
#pragma unroll
    for (int k = 1; k < 16; k++) {
        m0 = fmaxf(m0, fmaxf(s[4 * k], s[4 * k + 1]));
        m1 = fmaxf(m1, fmaxf(s[4 * k + 2], s[4 * k + 3]));
    }
    m0 = fmaxf(m0, __shfl_xor_sync(0xffffffffu, m0, 1));
    m1 = fmaxf(m1, __shfl_xor_sync(0xffffffffu, m1, 1));
    m0 = fmaxf(m0, __shfl_xor_sync(0xffffffffu, m0, 2));
    m1 = fmaxf(m1, __shfl_xor_sync(0xffffffffu, m1, 2));
    if (!first) {
        m0 = fmaxf(m0, 0.f);
        m1 = fmaxf(m1, 0.f);
    }
    a0 = first ? 1.f : ex2(-m0);
    a1 = first ? 1.f : ex2(-m1);
    m[0] += m0;
    m[1] += m1;
    softmax_shift(s, m0, m1);
}
template <int J0, int J1>
__device__ __forceinline__ void softmax_exp(const float (&s)[64], uint32_t (&p)[32], float (&t)[4]) {
#pragma unroll
    for (int k = J0; k < J1; k++) {
        const float e0 = ex2(s[4 * k]), e1 = ex2(s[4 * k + 1]), e2 = ex2(s[4 * k + 2]), e3 = ex2(s[4 * k + 3]);
        if (k == 0) { t[0] = e0; t[1] = e1; t[2] = e2; t[3] = e3; }
        else { t[0] += e0; t[1] += e1; t[2] += e2; t[3] += e3; }
        p[2 * k] = pack2(e0, e1);
        p[2 * k + 1] = pack2(e2, e3);
    }
}
__device__ __forceinline__ void fma8(float (&acc)[8], float a, uint4 w) {
    acc[0] = fmaf(a, bf_lo(w.x), acc[0]); acc[1] = fmaf(a, bf_hi(w.x), acc[1]);
    acc[2] = fmaf(a, bf_lo(w.y), acc[2]); acc[3] = fmaf(a, bf_hi(w.y), acc[3]);
    acc[4] = fmaf(a, bf_lo(w.z), acc[4]); acc[5] = fmaf(a, bf_hi(w.z), acc[5]);
    acc[6] = fmaf(a, bf_lo(w.w), acc[6]); acc[7] = fmaf(a, bf_hi(w.w), acc[7]);
}
__device__ __forceinline__ void mma16816(float (&d)[4], const uint32_t* a, uint32_t b0, uint32_t b1) {
    asm("mma.sync.aligned.m16n8k16.row.col.f32.bf16.bf16.f32 {%0, %1, %2, %3}, {%4, %5, %6, %7}, {%8, %9}, {%0, %1, %2, %3};"
        : "+f"(d[0]), "+f"(d[1]), "+f"(d[2]), "+f"(d[3]) : "r"(a[0]), "r"(a[1]), "r"(a[2]), "r"(a[3]), "r"(b0), "r"(b1));
}
__device__ __forceinline__ uint32_t best_key(const uint32_t* keys, int lane, uint32_t ep) {
    uint32_t best;
#pragma unroll 1
    for (;;) {
        const uint4 k = ld_poll(reinterpret_cast<const uint4*>(keys) + lane);
        best = max(max(k.x, k.y), max(k.z, k.w));
        if (__all_sync(0xffffffffu, (((k.x ^ ep) | (k.y ^ ep) | (k.z ^ ep) | (k.w ^ ep)) & 31) == 0)) break;
    }
    return __reduce_max_sync(0xffffffffu, best);
}

__global__ void __cluster_dims__(2, 1, 1) __launch_bounds__(384, 1)
fused_kernel(const __grid_constant__ CUtensorMap tm_ckv, const __grid_constant__ CUtensorMap tm_wq,
             const __grid_constant__ CUtensorMap tm_wuk, const __grid_constant__ CUtensorMap tm_wuv,
             const __grid_constant__ CUtensorMap tm_wo, const __grid_constant__ CUtensorMap tm_wg,
             const __grid_constant__ CUtensorMap tm_wu,
             const __grid_constant__ CUtensorMap tm_wm, const __grid_constant__ CUtensorMap tm_x, const Params P) {
    extern __shared__ __align__(1024) uint8_t smem[];
    const uint32_t sb = (uint32_t)__cvta_generic_to_shared(smem);
    const int tid = threadIdx.x, lane = tid & 31, warp = __shfl_sync(0xffffffffu, tid >> 5, 0), wg = warp >> 2;
    const uint32_t sm = blockIdx.x < 8 ? blockIdx.x + 124 : blockIdx.x - 8, smq = ((sm - 64) * 147) >> 11;
    const int rb = sm < 64 ? (sm & 14) * 8 + (sm >> 4) * 2 + (sm & 1)
                 : sm < 120 ? ((sm - 64 - smq * 14) & 14) * 8 + 24 + smq * 2 + (sm & 1) : sm < 124 ? sm + 8 : sm - 116;
    const int grp = rb >> 3, j = rb & 7, cq = j & 3, kh = grp & 1, ort = (grp & 14) + (j >> 2);
    if (warp == 0) TS(0);

    if (lane == 0) {
        if (warp == 8) {
            asm volatile("prefetch.tensormap [%0];" ::"l"(rb >= NCTA ? &tm_wm : (j & 1) ? &tm_wuv : &tm_wuk) : "memory");
            asm volatile("prefetch.tensormap [%0];" ::"l"(&tm_ckv) : "memory");
            *reinterpret_cast<uint2*>(smem + SM_EP + 16) = make_uint2(0, 0);
        }
        const u64 cnt = (warp < 5 ? (rb < NCTA ? 0x844444441111111ull : 0x888888881111111ull) : warp < 10 ? 0x111111188888888ull : 0x118121ull) >> (12 * (warp % 5));
#pragma unroll
        for (int i = 0; i < 3; i++) mbar_init(sb + SM_BAR + 24 * warp + 8 * i, ((uint32_t)cnt >> (4 * i)) & 15);
        fence_async_smem();
        asm volatile("fence.mbarrier_init.release.cluster;" ::: "memory");
    }
    __syncthreads();
    asm volatile("barrier.cluster.arrive.relaxed.aligned;\nbarrier.cluster.wait.aligned;" ::: "memory");

    if (rb >= NCTA) {
        float* sc = reinterpret_cast<float*>(smem + 6 * SLOT);
        float* red = sc + 512;
        uint32_t ph = 0x7f, sl = 0;
        if (warp == 8) {
#pragma unroll 1
            for (int i = 0; i < 24; i++) {
                slot_acquire(sb, ph, sl);
                tma2d(sb + sl * SLOT, &tm_wm, (i >> 3) * 1024 + (rb - NCTA) * 256, (i & 7) * 64, sb + BAR_FULL + 8 * sl);
                if (++sl == 6) sl = 0;
            }
#pragma unroll 1
            for (int i = 0; i <= NFFN / NSPARE; i++) {
                const int b = (rb - NCTA) * (NFFN / NSPARE) + i;
                if (i < NFFN / NSPARE) {
                    asm volatile("cp.async.bulk.wait_group.read 0;" ::: "memory");
                    uint32_t done = 0x7f;
                    slot_acquire(sb, done, i & 1);
#pragma unroll 1
                    for (int k = 0; k < 4; k++) tma2d(sb + (i & 1) * SLOT + k * 8192, k < 2 ? &tm_wg : &tm_wu, b * 16, (k & 1) * 256, sb + BAR_FULL + 8 * (i & 1));
                }
                if (i) {
                    mbar_wait(sb + BAR_FULL + 8 * (~i & 1), ((i - 1) >> 1) & 1);
                    bulk_store(g_wf + (b - 1) * SLOT, sb + (~i & 1) * SLOT, SLOT);
                    asm volatile("cp.async.bulk.commit_group;" ::: "memory");
                }
            }
            asm volatile("cp.async.bulk.wait_group 0;" ::: "memory");
            fence_async_global();
            TS(4);
        } else if (warp < 8) {
            const uint32_t c2 = __ldg(reinterpret_cast<const uint32_t*>(P.c) + tid), ep = __ldcg(&g_sync.epoch[0]) + 1;
            sc[2 * tid] = rbf(bf_lo(c2) * sigmoid(bf_lo(c2)));
            sc[2 * tid + 1] = rbf(bf_hi(c2) * sigmoid(bf_hi(c2)));
            ph = 0;
#pragma unroll 1
            for (int ps = 0; ps < 3; ps++) {
                bar_sync(1, 256);
                float acc[8] = {0.f, 0.f, 0.f, 0.f, 0.f, 0.f, 0.f, 0.f};
#pragma unroll 1
                for (int bt = 0; bt < 8; bt++) {
                    slot_wait(sb + BAR_FULL, ph, sl);
#pragma unroll 4
                    for (int i = 0; i < 8; i++)
                        fma8(acc, sc[bt * 64 + warp * 8 + i], *reinterpret_cast<const uint4*>(smem + sl * SLOT + (warp * 8 + i) * 512 + lane * 16));
                    __syncwarp();
                    mbar_arrive_if(sb + BAR_EMPTY + 8 * sl, lane == 0);
                    if (++sl == 6) sl = 0;
                }
                *reinterpret_cast<float4*>(red + warp * 256 + lane * 8) = make_float4(acc[0], acc[1], acc[2], acc[3]);
                *reinterpret_cast<float4*>(red + warp * 256 + lane * 8 + 4) = make_float4(acc[4], acc[5], acc[6], acc[7]);
                bar_sync(1, 256);
                float v = 0.f;
#pragma unroll
                for (int i = 0; i < 8; i++) v += red[i * 256 + tid];
                if (ps == 0) st_pub(g_mod1 + (rb - NCTA) * 256 + tid, (pack2(0.f, v) & 0xffff0000u) | (ep & 0xffffu), true);
                else g_mod[ps * 1024 + (rb - NCTA) * 256 + tid] = __float2bfloat16_rn(v);
                if (warp == 0) TS(1 + ps);
            }
        }
        __syncthreads();
        if (tid < 2) flag_add(&g_sync.cnt[7 * 8]);
        return;
    }

    if (wg == 2) {
        asm volatile("setmaxnreg.dec.sync.aligned.u32 40;");
        const CUtensorMap* tw = (j & 1) ? &tm_wuv : &tm_wuk;
        if (warp == 8) {
            const uint32_t rank = j & 1, half = rank * 16384;
            uint32_t eph = 0x7f, r = 0;
#pragma unroll 1
            for (int hp = 0; hp < 2; hp++) {
                uint32_t wtab = w_table(hp), atab = a_table(hp);
                const int hc = 4 * grp + 2 * hp;
#pragma unroll 1
                for (int u = 0; u < 16; u++) {
                    if (u < 4) {
                        const uint32_t ws = (wtab >> (4 * u)) & 15;
                        slot_acquire(sb, eph, ws);
                        load_tile(sb, ws, 0, tw, u * 128, hc, false, HINT & 1);
                        PT();
                    }
                    if (hp == 1 && (u & 7) == 4) mbar_wait(sb + BAR_FLAG + 24 + (u & 8), 0);
                    const uint32_t as = a_next(atab);
                    slot_acquire(sb, eph, as);
                    load_tile(sb, as, half, &tm_ckv, ((u & 12) + (j >> 1)) * 128, (u & 3) * 2 + rank, true, (HINT & 8) && hp);
                    PT();
                    if (hp == 1 && (u | 2) == 3 && lane == 0)
                        asm volatile("red.relaxed.gpu.global.add.u32 [%0], 1;" ::"l"(&g_sync.cnt[(grp * 8 + 3 + (u >> 1)) * 8]) : "memory");
                }
                const uint8_t* src = g_h + (15 - j) * 4 * SLOT;
#pragma unroll 1
                for (int u = 0; u < 8; u++) {
                    if ((u & 3) == 0) {
                        mbar_wait(sb + BAR_FLAG + (2 + 8 * hp) * u, 0);
                        fence_async_global();
                    }
                    if (u < 4) {
                        const uint32_t ws = (wtab >> (4 * u)) & 15;
                        slot_acquire(sb, eph, ws);
                        load_tile(sb, ws, half, &tm_wq, u * 128, hc + rank, true, HINT & 1);
                        PT();
                    }
                    const uint32_t as = a_next(atab);
                    slot_acquire(sb, eph, as);
                    load_bulk(sb, as, 0, src, SLOT, false, (HINT & 8) && hp);
                    PT();
                    src += u == 3 ? (8 * j - 63) * SLOT : SLOT;
                }
                const int step = hp ? -2 * SLOT : 2 * SLOT;
                src = g_KV + (size_t)(grp * 32 + 30 * hp) * SLOT + half - step;
#pragma unroll 1
                for (int n = 0; n <= 17; n++) {
                    if (n == 8) {
                        mbar_wait(sb + BAR_FLAG + 16 + 32 * hp, 0);
                        fence_async_global();
                    }
                    const uint8_t* v = src + SLOT;
                    src += n < 16 - j ? step : n == 16 - j ? (2 * j - 15) * step : -step;
                    if (n < 17) {
                        slot_acquire(sb, eph, r);
                        if (n != 15 - (j & 6)) load_bulk(sb, r, half, src, SLOT / 2, true, (HINT & 4) && (hp || !(HINT & 32)));
                        else load_bulk(sb, r, 0, src - half, SLOT, false, (HINT & 4) && (hp || !(HINT & 32)));
                        PT();
                        r = ring_next(r);
                    }
                    if (n) {
                        slot_acquire(sb, eph, r);
                        if (n != 16 - (j & 6)) load_bulk(sb, r, half, v, SLOT / 2, true, (HINT & 4) && (hp || !(HINT & 32)));
                        else load_bulk(sb, r, 0, v - half, SLOT, false, (HINT & 4) && (hp || !(HINT & 32)));
                        PT();
                        r = ring_next(r);
                    }
                    asm volatile("st.volatile.shared.u32 [%0], %1;" ::"r"(sb + SM_EP + 16), "r"(18 * hp + n + 1) : "memory");
                }
            }
            uint32_t otab = O_TABLE, ready = 0;
#pragma unroll 1
            for (int i = 0; i < 17; i++) {
                const bool dyn = i >= 8 && i < 15;
                const uint32_t want = dyn ? 15u << (4 * (i - 8)) : 1u << max(i + 14, 28);
                if (!(ready & want)) {
                    do {
                        asm volatile("ld.acquire.cta.shared.u32 %0, [%1];" : "=r"(ready) : "r"(sb + SM_EP + 20) : "memory");
                        ready = __shfl_sync(0xffffffffu, ready, 0);
                    } while (!(ready & want));
                    fence_async_global();
                }
                const int head = o_head(dyn ? (ready >> (4 * (i - 8))) & 15 : i, kh);
                const uint32_t as = o_next(otab), ws = o_next(otab), off = i < 15 ? half : kh * 16384;
                slot_acquire(sb, eph, as);
                load_bulk(sb, as, off, g_ctx + (size_t)(ort * 32 + head) * SLOT + off, SLOT / 2, i < 15, HINT & 16);
                if (i == 15) load_tile(sb, as, off ^ 16384, &tm_x, ort * 128 + kh * 64, cq * 2, false, false);
                if (i == 16) load_bulk(sb, as, off ^ 16384, P.wdown + min(rb, NFFN - 1) * 8192, SLOT / 2, false, false);
                PT();
                slot_acquire(sb, eph, ws);
                load_tile(sb, ws, 0, &tm_wo, head * 128, cq * 2, false, HINT & 2);
                PT();
                if (i == 0) o_next(otab);
            }
            if (rb < NFFN) {
                slot_acquire(sb, eph, 5);
                load_bulk(sb, 5, 0, g_wf + rb * SLOT, SLOT, false, false);
            }
        } else if (warp == 9) {
            l2_prefetch(P.ckv + rb * 2048, 4096);
            mbar_watch(sb + BAR_FULL, 0);
            l2_prefetch(P.ckv + 512 * 512 + rb * 2048, 4096);
            mbar_watch(sb + BAR_FULL + 8 * 4, 0);
            l2_prefetch(P.ckv + 1024 * 512 + rb * 4096, 8192);
            TS(40);
#pragma unroll 1
            for (int i = 0; i < 15; i++) {
                step_watch(sb + SM_EP + 16, i == 0 ? 0 : i < 5 ? PFA + i : 13 + PFB + i);
                if (i == 12) mbar_watch(sb + BAR_FLAG + 8 * 7, 0);
                const int rf = min(rb, NFFN - 1);
                const uint8_t* p = i == 3 ? reinterpret_cast<const uint8_t*>(P.ckv) + rb * 16384
                                 : i == 4 ? g_h + rb * 16384
                                 : i < 9 ? g_ctx + (size_t)(ort * 32 + o_head(cq + 2 * ((i - 5) & 2), kh)) * SLOT + (i & 1) * 16384
                                 : i < 11 ? reinterpret_cast<const uint8_t*>(P.wo) + (grp * 16 + (~i & 1) * 8 + j) * 16384
                                 : i == 11 ? reinterpret_cast<const uint8_t*>(P.x) + rb * 16384
                                 : i == 12 ? reinterpret_cast<const uint8_t*>(P.wdown) + rf * 16384 : g_wf + rf * SLOT + (i & 1) * 16384;
                if (i < 3) tma3d_prefetch(i == 1 ? tw : &tm_wq, (j >> 1) * 128, grp * 4 + (i == 1 ? 2 : i + (j & 1)));
                else l2_prefetch(p, 16384);
            }
            const uint32_t v = lds32(sb + SM_EP) - 1;
            sts128(sb + SM_RED + lane * 16, make_uint4(v, v, v, v));
            fence_async_smem();
            __syncwarp();
#pragma unroll 1
            for (int i = 0; i < OB / 32; i++) bulk_store(g_out + rb * OB + i * 32, sb + SM_RED, 512);
            asm volatile("cp.async.bulk.commit_group;\ncp.async.bulk.wait_group 0;" ::: "memory");
            fence_async_global();
            __syncwarp();
            mbar_arrive_if(sb + BAR_PF, lane == 0);
            if (lane == 0) mbar_watch(sb + BAR_END, 0);
        } else {
            const uint32_t ep = __ldcg(&g_sync.epoch[0]) + 1;
            asm volatile("st.shared.u32 [%0], %1;" ::"r"(sb + SM_EP), "r"(ep) : "memory");
            mbar_wait(sb + BAR_FULL + 8 * 4, 0);
            {
                uint4 v[4];
                for (;;) {
                    uint32_t bad = 0;
#pragma unroll
                    for (int k = 0; k < 4; k++) v[k] = ld_poll(reinterpret_cast<const uint4*>(g_mod1) + (warp & 1) * 128 + k * 32 + lane);
#pragma unroll
                    for (int k = 0; k < 4; k++) bad |= (v[k].x ^ ep) | (v[k].y ^ ep) | (v[k].z ^ ep) | (v[k].w ^ ep);
                    if (__all_sync(0xffffffffu, (bad & 0xffff) == 0)) break;
                    __nanosleep(100);
                }
                const uint32_t one = (warp & 1) ? ONE2 : 0x80008000u;
#pragma unroll
                for (int k = 0; k < 4; k++)
                    *reinterpret_cast<uint2*>(smem + SM_TAB + (warp & 1) * 1024 + k * 256 + lane * 8) =
                        make_uint2(badd(__byte_perm(v[k].x, v[k].y, 0x7632), one), badd(__byte_perm(v[k].z, v[k].w, 0x7632), one));
            }
            __syncwarp();
            mbar_arrive_if(sb + BAR_FLAG + 8 * 8, lane == 0);
            if (warp == 10) {
#pragma unroll 1
                for (int i = 0; i < 9; i++) {
                    mbar_sleep(sb + BAR_DONE + 8 * i);
                    if (lane == 0) flag_add(i && ((i - 1) & 2) ? &g_sync.ctxcnt[((i & 1) ? 15 - j : j) * 32 + 2 * grp + (i > 4)] : &g_sync.cnt[(grp * 8 + i) * 8]);
                    if (i == 0) TS(43);
                }
            } else {
                TS(42);
#pragma unroll 1
                for (int i = 0; i < 8; i++) {
                    mbar_sleep(sb + BAR_DONE + 8 * (i == 7 ? 6 : i == 4 ? 3 : i));
                    if (lane < 2) flag_wait(&g_sync.cnt[((i == 0 ? (lane ? j : 15 - j) : i == 7 ? 0 : grp) * 8 + i) * 8], 8 * ep);
                    __syncwarp();
                    mbar_arrive_if(sb + BAR_FLAG + 8 * i, lane == 0 && i < 7);
                    TS(48 + i);
                }
                const uint32_t *mp = reinterpret_cast<const uint32_t*>(g_mod) + lane, *wp = reinterpret_cast<const uint32_t*>(P.wr) + lane;
                float ra = 0.f, rs = 0.f;
#pragma unroll 1
                for (int k = 0; k < 256; k += 32) {
                    const uint32_t ga = __ldcg(mp + 512 + k), sh = __ldcg(mp + 768 + k), c1 = badd(__ldcg(mp + 1024 + k), ONE2);
                    const uint32_t gb = __ldcg(mp + 1280 + k), ww = __ldg(wp + k);
                    const float a0 = bf_lo(c1) * bf_lo(ww), a1 = bf_hi(c1) * bf_hi(ww);
                    ra += a0 + a1;
                    rs = fmaf(bf_lo(sh), bf_lo(ww), fmaf(bf_hi(sh), bf_hi(ww), rs));
                    if (k >> 6 == cq) {
                        sts128(sb + SM_TAB + ((k & 32) + lane) * 16, make_uint4(ga << 16, ga & 0xffff0000u, __float_as_uint(a0), __float_as_uint(a1)));
                        sts128(sb + SM_TAB + 1024 + ((k & 32) + lane) * 16, make_uint4(c1, sh, gb, 0));
                    }
                }
#pragma unroll 1
                for (int o = 16; o > 0; o >>= 1) {
                    ra += __shfl_xor_sync(0xffffffffu, ra, o);
                    rs += __shfl_xor_sync(0xffffffffu, rs, o);
                }
                *reinterpret_cast<float2*>(smem + SM_EP + 8) = make_float2(ra, rs);
                __syncwarp();
                mbar_arrive_if(sb + BAR_FLAG + 8 * 7, lane == 0);
                const uint32_t* f = &g_sync.ctxcnt[ort * 32 + o_head(min(lane, 16), kh)];
                uint32_t ready = -(j & 1), list = 0, sh = 0, qa;
                asm("mapa.shared::cluster.u32 %0, %1, %2;" : "=r"(qa) : "r"(sb + SM_EP + 20), "r"(lane & 1));
                while (ready != ~0u) {
                    uint32_t v;
                    asm volatile("ld.acquire.gpu.global.u32 %0, [%1];" : "=r"(v) : "l"(f) : "memory");
                    const uint32_t now = __ballot_sync(0xffffffffu, (int)(v - ep) >= 0);
#pragma unroll 1
                    for (uint32_t fresh = now & ~ready & 0x7f00; fresh; fresh &= fresh - 1, sh += 4) list |= (__ffs(fresh) - 1) << sh;
                    list |= (((now & 0xff) + 1) >> 8 << 28) | ((now & 0x18000) << 14);
                    if (now != ready && lane < 2) asm volatile("st.relaxed.cluster.shared::cluster.u32 [%0], %1;" ::"r"(qa), "r"(list) : "memory");
                    if ((now & 0xff) == 0xff) mbar_sleep(sb + BAR_DONE + 8 * 7);
                    ready = now;
                    __nanosleep(POLL_NS);
                }
                TS(45);
            }
        }
    } else {
        asm volatile("setmaxnreg.inc.sync.aligned.u32 232;");
        const bool elected = (tid & 127) == 0, rel = (tid & 95) == 0;
        uint32_t eb;
        asm("mapa.shared::cluster.u32 %0, %1, %2;" : "=r"(eb) : "r"(sb + BAR_EMPTY), "r"(warp & 1));
        const int g = lane >> 2, c4 = lane & 3;
        const uint32_t toff = warp * 4096 + g * 64 + ((c4 ^ (g >> 1)) << 4);
        uint32_t fph = 0, r = 0;
        if (wg == 1) bar_arrive(1, 256);
        const uint32_t kd = desc_k(sb), wd = desc_mn(sb), vd = ((sb & 0x3ffff) >> 4) | (32u << 16);
        const int nL = 16 - j, hn = nL - 1 + wg;
        float s[64], o[64], li[2] = {0.f, 0.f};
        uint8_t* cimg = g_ctx;
        uint32_t p[32] = {};
#pragma unroll 1
        for (int hp = 0; hp < 2; hp++) {
            float m[2] = {0.f, 0.f}, l[2] = {0.f, 0.f}, t[4] = {0.f, 0.f, 0.f, 0.f};
            bool shifted = false, bad = false, plain = false;
            uint32_t qa = desc_k(sb + 5 * SLOT + (wg ^ 1) * 8192);
            uint8_t* limg = g_ctx + (size_t)((15 - j) * 32 + 2 * grp + hp) * SLOT;
            {
                const int step = hp ? -8 * SLOT : 8 * SLOT;
                uint8_t* img = g_KV + (size_t)(grp * 32 + (hp ? j ^ 30 : j)) * SLOT - step;
                const float sc = (j & 1) ? 1.f : SM_C;
                const uint32_t wtab = w_table(hp);
                uint32_t atab = hp ? 0x562u : a_table(0);
#pragma unroll 1
                for (int u = 0;; u += 2) {
                    proj_tile<false>(s, o, u, u ? 0 : hp, sb, wg, eb, rel, fph, wtab, atab, u ? img : cimg, toff, u ? sc : li[0], u ? sc : li[1], (hp | u) == 0, P.x, rb * 16 + warp * 2, p);
                    __syncwarp();
                    mbar_arrive_if(sb + BAR_DONE + 4 * u + 32 * hp, lane == 0 && (hp | u) != 0);
                    if (elected) TS(1 + 10 * hp + u + 20 * wg);
                    if (proj_tile<true>(o, s, u + 1, 0, sb, wg, eb, rel, fph, wtab, atab, img + step, toff, sc, sc, (hp | u) == 0, P.x, rb * 16 + warp * 2, p)) break;
                    if (elected) TS(2 + 10 * hp + u + 20 * wg);
                    img += 2 * step;
                }
            }
            if (elected) TS(6 + 10 * hp + 20 * wg);
            int n = -1;
#pragma unroll 1
            for (;;) {
                while (bad || plain) {
                    if (bad) {
                        float a0, a1;
                        softmax_remax(s, m, n == 0 || n == nL, a0, a1);
                        shifted = true;
                        l[0] *= a0;
                        l[1] *= a1;
#pragma unroll
                        for (int i = 0; i < 64; i++) o[i] *= (i & 2) ? a1 : a0;
                    }
                    softmax_exp<0, 16>(s, p, t);
                    t[0] += t[1];
                    t[2] += t[3];
                    bad = !bad && softmax_unsafe(t[0], t[2], false);
                    plain = false;
                }
#pragma unroll 1
                do {
                    l[0] += t[0];
                    l[1] += t[2];
                    if (++n > 16) break;
                    const uint32_t ks = r;
                    uint32_t vs = ring_next(r);
                    r = ring_next(vs);
                    bar_sync(1 + wg, 256);
                    const float x = (float)((warp & 3) * 16 + g - 2 * c4);
                    if (n == hn) {
                        float sh[32];
                        qk_issue(sh, qa, kd + ks * (SLOT / 16));
                        slot_wait(sb + BAR_FULL, fph, vs);
                        pv_issue(o, p, vd + vs * (SLOT / 16), 1, false);
                        bar_arrive(2 - wg, 256);
                        wg_wait<1>();
                        reg_fence(sh);
                        tri_mask_copy(s, sh, x);
                        release_if(eb, ks, rel);
                        release_if(eb, 5 + wg, rel && (!wg || n == 16));
                        if (!wg) {
                            qa += SLOT / 16;
                            fence_async_smem();
                            if (shifted) softmax_shift(s, m[0], m[1]);
                        }
                        float e[4 * EARLY];
#pragma unroll
                        for (int i = 0; i < 4 * EARLY; i++) {
                            e[i] = ex2(s[i]);
                            t[i & 3] = i < 4 ? e[i] : t[i & 3] + e[i];
                        }
                        reg_fence(e);
                        slot_wait(sb + BAR_FULL, fph, r);
                        wg_wait<0>();
                        reg_fence(o);
                        reg_fence(e);
                        release_if(eb, vs, rel);
#pragma unroll
                        for (int i = 0; i < 2 * EARLY; i++) p[i] = pack2(e[2 * i], e[2 * i + 1]);
                        softmax_exp<EARLY, 8>(s, p, t);
                        if (wg) {
                            ctx_store<true>(limg, toff, o, l[0], l[1]);
                            __syncwarp();
                            mbar_arrive_if(sb + BAR_DONE + 24 + 32 * hp, lane == 0);
                            l[0] = l[1] = m[0] = m[1] = 0.f;
                            shifted = false;
                        }
                        t[0] += t[1];
                        t[2] += t[3];
                        bad = softmax_unsafe(t[0], t[2], wg);
                        continue;
                    }
                    if (n == 0 || n == nL) {
                        qk_issue(s, qa, kd + ks * (SLOT / 16));
                        if (n == 0) {
                            r = vs;
                            vs = 4 - hp;
                            slot_wait(sb + BAR_FULL, fph, 6);
                            gemm_issue<false>(o, qa + SLOT / 16, wd + vs * (SLOT / 16), 1, false);
                        } else {
                            slot_wait(sb + BAR_FULL, fph, vs);
                            pv_issue(o, p, vd + vs * (SLOT / 16), 1, true);
                        }
                        bar_arrive(2 - wg, 256);
                        const float i0 = n ? rcp(quad_sum(l[0])) : 1.f, i1 = n ? rcp(quad_sum(l[1])) : 1.f;
                        wg_wait<1>();
                        reg_fence(s);
                        release_if(eb, ks, rel);
                        release_if(eb, 6, rel && n == 16);
                        tri_mask(s, n ? x : 64.f);
                        float e[4 * EARLY];
#pragma unroll
                        for (int i = 0; i < 4 * EARLY; i++) {
                            e[i] = ex2(s[i]);
                            t[i & 3] = i < 4 ? e[i] : t[i & 3] + e[i];
                        }
                        reg_fence(e);
                        reg_fence(s);
                        reg_fence(t);
                        slot_wait(sb + BAR_FULL, fph, r);
                        if (SF & 1) sched_fence(fph, P.zero);
                        wg_wait<0>();
                        reg_fence(o);
                        reg_fence(e);
                        release_if(eb, vs, rel);
#pragma unroll
                        for (int i = 0; i < 2 * EARLY; i++) p[i] = pack2(e[2 * i], e[2 * i + 1]);
                        softmax_exp<EARLY, MSPLIT>(s, p, t);
                        tile_store(limg, sb + 6 * SLOT, toff, o, i0, i1, n);
                        reg_fence(t);
                        if (SF & 2) sched_fence(fph, P.zero);
                        reg_fence(s);
                        softmax_exp<MSPLIT, 16>(s, p, t);
                        __syncwarp();
                        mbar_arrive_if(sb + BAR_DONE + 24 + 32 * hp, lane == 0 && n);
                        l[0] = l[1] = m[0] = m[1] = 0.f;
                        shifted = false;
                        t[0] += t[1];
                        t[2] += t[3];
                        bad = __any_sync(0xffffffffu, fmaxf(t[0], t[2]) > SM_HI || fminf(t[0], t[2]) < SM_LO);
                        continue;
                    }
                    qk_issue(s, qa, kd + ks * (SLOT / 16));
                    slot_wait(sb + BAR_FULL, fph, vs);
                    pv_issue(o, p, vd + vs * (SLOT / 16), n != 1 && n != nL + 1, n == hn + 1);
                    bar_arrive(2 - wg, 256);
                    wg_wait<1>();
                    reg_fence(s);
                    release_if(eb, ks, rel);
                    release_if(eb, 6, rel && n == 16);
                    if (n == nL - 1) {
                        tri_mask(s, x);
                        release_if(eb, 5, rel);
                        qa += SLOT / 16;
                        fence_async_smem();
                    }
                    if (shifted) {
                        slot_wait(sb + BAR_FULL, fph, r);
                        wg_wait<0>();
                        reg_fence(o);
                        release_if(eb, vs, rel);
                        softmax_shift(s, m[0], m[1]);
                        plain = true;
                        break;
                    }
                    float e[4 * EARLY];
#pragma unroll
                    for (int i = 0; i < 4 * EARLY; i++) {
                        e[i] = ex2(s[i]);
                        t[i & 3] = i < 4 ? e[i] : t[i & 3] + e[i];
                    }
                    reg_fence(e);
                    slot_wait(sb + BAR_FULL, fph, r);
                    wg_wait<0>();
                    reg_fence(o);
                    reg_fence(e);
                    release_if(eb, vs, rel);
#pragma unroll
                    for (int i = 0; i < 2 * EARLY; i++) p[i] = pack2(e[2 * i], e[2 * i + 1]);
                    softmax_exp<EARLY, 16>(s, p, t);
                    t[0] += t[1];
                    t[2] += t[3];
                    bad = softmax_unsafe(t[0], t[2], false);
                } while (!bad);
                if (!bad && !plain) break;
            }
            const uint32_t vs = r, ga = desc_k(sb + (hp ? 2 * (wg ^ kh ^ 1) : wg) * 8192);
            r = ring_next(r);
            slot_wait(sb + BAR_FULL, fph, 5);
            slot_wait(sb + BAR_FULL, fph, r);
            bar_sync(1 + wg, 256);
            gemm_issue<true>(s, ga + 5 * (SLOT / 16), wd + r * (SLOT / 16), 0, hp);
            pv_issue(o, p, vd + vs * (SLOT / 16), j, hn == 16);
            bar_arrive(2 - wg, 256);
            li[0] = rcp(quad_sum(l[0]));
            li[1] = rcp(quad_sum(l[1]));
            cimg = limg + (ptrdiff_t)(2 * j - 15) * 32 * SLOT + (wg ? -16384 : 16384);
            wg_wait<1>();
            release_if(eb, 5, rel);
            release_if(eb, r, rel && hp);
            wg_wait<0>();
            release_if(eb, vs, rel);
            reg_fence(o);
            img_store_global<0>(cimg, toff, o, li[0], li[1]);
            if (elected) TS(8 + 10 * hp + 20 * wg);
        }
        uint32_t otab = 0x2351604u;
        const uint32_t oa = desc_k(sb + (wg ^ kh ^ 1) * 16384);
        const int t7 = tid & 127, w4 = warp & 3, row = ort * 128 + kh * 64 + w4 * 16 + g;
#pragma unroll 1
        for (int i = 1; i < 15 - wg; i++) {
            const uint32_t as = o_next(otab), ws = o_next(otab);
            slot_wait(sb + BAR_FULL, fph, as);
            slot_wait(sb + BAR_FULL, fph, ws);
            bar_sync(1 + wg, 256);
            gemm_issue<false>(s, oa + as * (SLOT / 16), wd + ws * (SLOT / 16), 1, true);
            bar_arrive(2 - wg, 256);
            wg_wait<1>();
            reg_fence(o);
            if (i == 1) img_store_global<1>(cimg, toff, o, li[0], li[1]);
            if (i == 2) {
                img_store_global<2>(cimg, toff, o, li[0], li[1]);
                img_store_global<3>(cimg, toff, o, li[0], li[1]);
                __syncwarp();
                mbar_arrive_if(sb + BAR_DONE + 64, lane == 0);
            }
            wg_wait<0>();
            release_if(eb, as, rel);
            release_if(eb, ws, rel);
        }
        mbar_wait(sb + BAR_PF, 0);
        const uint32_t ep = lds32(sb + SM_EP);
        uint32_t eb2 = sb + BAR_END;
        if (wg == 0) {
            reg_fence(s);
            if (elected) TS(9);
            TT(1);
#pragma unroll
            for (int v = 0; v < 8; v++)
                st_pub(g_out + rb * OB + v * 128 + t7, make_uint4((pack2(s[8 * v], s[8 * v + 1]) & ~1u) | (ep & 1), pack2(s[8 * v + 2], s[8 * v + 3]),
                                                                      pack2(s[8 * v + 4], s[8 * v + 5]), pack2(s[8 * v + 6], s[8 * v + 7])), true);
            constexpr uint32_t s1 = 5, s2 = 6;
            bar_sync(4, 256);
            uint32_t wf[64];
            float wn[64];
            if (rb < NFFN) {
                slot_wait(sb + BAR_FULL, fph, s1);
                const uint32_t a = sb + s1 * SLOT + (w4 * 128 + (lane >> 4) * 8 + (lane & 7)) * 32 + ((lane >> 3) & 1) * 16;
#pragma unroll
                for (int i = 0; i < 16; i++)
                    asm volatile("ldmatrix.sync.aligned.m8n8.x4.trans.shared.b16 {%0, %1, %2, %3}, [%4];"
                                 : "=r"(wf[4 * i]), "=r"(wf[4 * i + 1]), "=r"(wf[4 * i + 2]), "=r"(wf[4 * i + 3])
                                 : "r"(a + (i >> 3) * 16384 + (i & 7) * 512) : "memory");
                slot_wait(sb + BAR_FULL, fph, s2);
#pragma unroll
                for (int i = 0; i < 16; i++) {
                    const uint2 w = *reinterpret_cast<const uint2*>(smem + s2 * SLOT + (kh ^ 1) * 16384 + i * 1024 + t7 * 8);
                    wn[4 * i] = bf_lo(w.x); wn[4 * i + 1] = bf_hi(w.x); wn[4 * i + 2] = bf_lo(w.y); wn[4 * i + 3] = bf_hi(w.y);
                }
                reg_fence(wn);
            }
            const uint32_t gbf = __ldcg(reinterpret_cast<const uint32_t*>(g_mod) + 1280 + rb * 2 + (tid & 1));
            if (elected) TS(10);
            TT(2);
            uint32_t best;
            if (KALL) best = best_key(g_key + cq * 128, lane, ep);
            if (warp == 0) {
                if (KGATE) bar_sync(5, 160);
                const uint32_t k = KALL ? best : best_key(g_key + cq * 128, lane, ep);
                if (lane == 0) asm volatile("st.shared.u32 [%0], %1;" ::"r"(sb + SM_EP + 4), "r"(k) : "memory");
                mbar_arrive_if(sb + BAR_BEST, lane == 0);
            }
            if (!KALL) {
                mbar_wait(sb + BAR_BEST, 0);
                best = lds32(sb + SM_EP + 4);
            }
            const int sel = (~best >> 5) & 2047;
            if (elected) TS(19);
            TT(3);
            const uint4* cp = g_cand + (sel >> 4) * 192;
            float* sred = reinterpret_cast<float*>(smem + SM_RED);
            const int pq = (2 * rb + (tid & 1)) & 63, pv = (pq >> 2) / 3;
            const uint4* fp = cp + (rb >> 5) * 24 + pv * 4 + (pq & 3);
            uint4 fh = ld_poll(fp), fx = ld_poll(fp + 96);
            if (rb < NFFN) {
                uint4 cv[6];
                for (;;) {
                    uint32_t bad = 0;
#pragma unroll
                    for (int v = 0; v < 6; v++) cv[v] = ld_poll(cp + w4 * 24 + v * 4 + c4);
#pragma unroll
                    for (int v = 0; v < 6; v++) bad |= cv[v].w ^ ep;
                    if (__all_sync(0xffffffffu, bad == 0)) break;
                }
                if (elected) TS(20);
            TT(4);
                float d[4][4] = {};
#pragma unroll
                for (int k = 0; k < 8; k++) {
                    const uint32_t b0 = (&cv[(2 * k) / 3].x)[(2 * k) % 3], b1 = (&cv[(2 * k + 1) / 3].x)[(2 * k + 1) % 3];
                    mma16816(d[k & 1], wf + 4 * k, b0, b1);
                    mma16816(d[2 + (k & 1)], wf + 32 + 4 * k, b0, b1);
                }
                const float u = (c4 & 2) ? ((c4 & 1) ? d[2][2] + d[3][2] : d[2][0] + d[3][0]) : ((c4 & 1) ? d[0][2] + d[1][2] : d[0][0] + d[1][0]);
                sred[w4 * 32 + c4 * 8 + g] = u;
                bar_sync(3, 128);
                const float v = rbf((sred[lane] + sred[32 + lane]) + (sred[64 + lane] + sred[96 + lane]));
                const float act = rbf(rbf(v * sigmoid(v)) * __shfl_down_sync(0xffffffffu, v, 16));
                float y[4] = {0.f, 0.f, 0.f, 0.f};
#pragma unroll
                for (int k = 0; k < 16; k++) {
                    const float a = __shfl_sync(0xffffffffu, act, k);
#pragma unroll
                    for (int i = 0; i < 4; i++) y[i] = fmaf(a, wn[4 * k + i], y[i]);
                }
                st_pub(g_out + rb * OB + OB_Y + t7, make_uint4((__float_as_uint(y[0]) & ~15u) | (ep & 15), __float_as_uint(y[1]), __float_as_uint(y[2]), __float_as_uint(y[3])), true);
            }
            if (rb == 0 && tid == 0) g_sync.epoch[0] = ep;
            if (elected) TS(60);
            TT(5);
            uint4 yv;
            do yv = ld_poll(g_out + min(t7, NFFN - 1) * OB + OB_Y + rb);
            while (!__all_sync(0xffffffffu, ((yv.x ^ ep) & 15) == 0));
            if (elected) TS(61);
            TT(6);
            float y[4] = {0.f, 0.f, 0.f, 0.f};
            if (t7 < NFFN) { y[0] = __uint_as_float(yv.x); y[1] = __uint_as_float(yv.y); y[2] = __uint_as_float(yv.z); y[3] = __uint_as_float(yv.w); }
            const float z0 = ((lane & 16) ? y[2] : y[0]) + __shfl_xor_sync(0xffffffffu, (lane & 16) ? y[0] : y[2], 16);
            const float z1 = ((lane & 16) ? y[3] : y[1]) + __shfl_xor_sync(0xffffffffu, (lane & 16) ? y[1] : y[3], 16);
            float z = ((lane & 8) ? z1 : z0) + __shfl_xor_sync(0xffffffffu, (lane & 8) ? z0 : z1, 8);
            z += __shfl_xor_sync(0xffffffffu, z, 4);
            z = quad_sum(z);
            if ((lane & 7) == 0) sred[128 + (lane >> 3) * 4 + w4] = z;
            bar_sync(3, 128);
            if (tid < 2) {
                while (fh.w != ep || fx.w != ep) { fh = ld_poll(fp); fx = ld_poll(fp + 96); }
                const float4 y0 = *reinterpret_cast<const float4*>(sred + 128 + tid * 8), y1 = *reinterpret_cast<const float4*>(sred + 132 + tid * 8);
                const int cm = (pq >> 2) - 3 * pv;
                const uint32_t h2 = cm == 0 ? fh.x : cm == 1 ? fh.y : fh.z, x2 = cm == 0 ? fx.x : cm == 1 ? fx.y : fx.z;
                const float sg = sigmoid(bf_hi((best & 0x80000000u) ? (best ^ 0x80000000u) : ~best));
                reinterpret_cast<uint32_t*>(P.out)[sel * 256 + rb * 2 + tid] =
                    badd(x2, bmul(gbf, badd(h2, bmul(pack2((y0.x + y0.y) + (y0.z + y0.w), (y1.x + y1.y) + (y1.z + y1.w)), pack2(sg, sg)))));
            }
            if (elected) TS(62);
            TT(7);
        } else {
            const float4* tf = reinterpret_cast<const float4*>(smem + SM_TAB) + c4;
            const uint32_t xa = sb + 4 * SLOT + (kh ^ 1) * 16384 + (w4 * 16 + (lane & 15)) * 128;
            uint32_t x2[32];
            bar_sync(2, 256);
#pragma unroll 1
            for (int i = 14; i < 17; i++) {
                const uint32_t as = o_next(otab), ws = o_next(otab);
                slot_wait(sb + BAR_FULL, fph, as);
                slot_wait(sb + BAR_FULL, fph, ws);
                gemm_issue<false>(s, oa + as * (SLOT / 16), wd + ws * (SLOT / 16), 1, true);
                wg_wait<1>();
            }
            if (elected) TS(29);
            TT(1);
            {
#pragma unroll
                for (int k = 0; k < 8; k++)
                    asm volatile("ldmatrix.sync.aligned.m8n8.x4.shared.b16 {%0, %1, %2, %3}, [%4];"
                                 : "=r"(x2[4 * k]), "=r"(x2[4 * k + 1]), "=r"(x2[4 * k + 2]), "=r"(x2[4 * k + 3])
                                 : "r"(xa + (k >> 2) * 8192 + (((2 * (k & 3) + (lane >> 4)) ^ (lane & 7)) << 4)) : "memory");
            }
            wg_wait<0>();
            reg_fence(s);
            bar_arrive(4, 256);
            if (elected) TS(39);
            TT(2);
            const uint4* pr = g_out + (rb ^ 8) * OB + t7;
            uint4 pa[8];
#pragma unroll
            for (int v = 0; v < 8; v++) pa[v] = ld_poll(pr + v * 128);
            float4 tc[16];
#pragma unroll
            for (int k = 0; k < 16; k++) {
                tc[k] = tf[k * 4];
#pragma unroll
                for (int i = 4 * k; i < 4 * k + 4; i++) s[i] = fmaf((i & 1) ? tc[k].y : tc[k].x, s[i], (i & 1) ? bf_hi(x2[i >> 1]) : bf_lo(x2[i >> 1]));
            }
            reg_fence(s);
            for (;;) {
                uint32_t bad = 0;
#pragma unroll
                for (int v = 0; v < 8; v++) bad |= pa[v].x ^ ep;
                if (__all_sync(0xffffffffu, (bad & 1) == 0)) break;
#pragma unroll
                for (int v = 0; v < 8; v++) pa[v] = ld_poll(pr + v * 128);
            }
            if (elected) TS(30);
            TT(3);
            float st[6] = {0.f, 0.f, 0.f, 0.f, 0.f, 0.f};
#pragma unroll
            for (int i = 0; i < 64; i++) {
                const int rh = (i >> 1) & 1;
                const uint32_t w = (&pa[i >> 3].x)[(i >> 1) & 3];
                const float v = fmaf((i & 1) ? tc[i >> 2].y : tc[i >> 2].x, (i & 1) ? bf_hi(w) : bf_lo(w), s[i]);
                s[i] = v;
                st[rh] += v;
                st[2 + rh] = fmaf(v, v, st[2 + rh]);
                st[4 + rh] = fmaf(v, (i & 1) ? tc[i >> 2].w : tc[i >> 2].z, st[4 + rh]);
            }
#pragma unroll
            for (int i = 0; i < 6; i++) st[i] = quad_sum(st[i]);
            st_pub(g_out + rb * OB + OB_STAT + (w4 * 8 + g) * 2 + (c4 & 1),
                   make_uint4(__float_as_uint((c4 & 1) ? st[1] : st[0]), __float_as_uint((c4 & 1) ? st[3] : st[2]),
                              __float_as_uint((c4 & 1) ? st[5] : st[4]), ep), c4 < 2);
            if (TF & 1) sched_fence(eb2, P.zero);
            if (elected) TS(56);
            TT(4);
            uint32_t cb[16], sh[16], gb[16];
#pragma unroll
            for (int i = 0; i < 16; i++) {
                const float4 c = tf[64 + i * 4];
                cb[i] = __float_as_uint(c.x); sh[i] = __float_as_uint(c.y); gb[i] = __float_as_uint(c.z);
            }
            const float ra = __uint_as_float(lds32(sb + SM_EP + 8)), rb0 = __uint_as_float(lds32(sb + SM_EP + 12));
#pragma unroll
            for (int i = 0; i < 32; i++) x2[i] = pack2(s[2 * i], s[2 * i + 1]);
            reg_fence(x2);
            uint4 r0, r1;
            for (;;) {
                r0 = ld_poll(g_out + ((rb & ~3) + c4) * OB + OB_STAT + (w4 * 8 + g) * 2);
                r1 = ld_poll(g_out + ((rb & ~3) + c4) * OB + OB_STAT + (w4 * 8 + g) * 2 + 1);
                if (__all_sync(0xffffffffu, r0.w == ep && r1.w == ep)) break;
            }
            if (elected) TS(57);
            TT(5);
            const float m0 = quad_sum(__uint_as_float(r0.x)) * (1.f / 512.f), m1 = quad_sum(__uint_as_float(r1.x)) * (1.f / 512.f);
            const float rs0 = ln_rstd(fmaxf(fmaf(-m0, m0, quad_sum(__uint_as_float(r0.y)) * (1.f / 512.f)), 0.f));
            const float rs1 = ln_rstd(fmaxf(fmaf(-m1, m1, quad_sum(__uint_as_float(r1.y)) * (1.f / 512.f)), 0.f));
            const uint32_t mb0 = pack2(m0, m0), mb1 = pack2(m1, m1);
            const uint32_t lg = pack2(fmaf(rs0, fmaf(-bf_lo(mb0), ra, quad_sum(__uint_as_float(r0.z))), rb0),
                                      fmaf(rs1, fmaf(-bf_lo(mb1), ra, quad_sum(__uint_as_float(r1.z))), rb0));
            const uint32_t u0 = lg << 16, u1 = lg & 0xffff0000u;
            const uint32_t k0 = ((u0 ^ (((int)u0 >> 31) | 0x80000000u)) & 0xffff0000u) | ((2047 - row) << 5) | (ep & 31);
            const uint32_t k1 = ((u1 ^ (((int)u1 >> 31) | 0x80000000u)) & 0xffff0000u) | ((2039 - row) << 5) | (ep & 31);
            const uint32_t kb = __reduce_max_sync(0xffffffffu, max(k0, k1));
            st_pub(g_key + cq * 128 + (row >> 4), kb, lane == 0);
            if (KGATE) bar_arrive(5, 160);
            if (TF & 2) sched_fence(eb2, P.zero);
            {
                uint32_t cx[18], ch[18];
#pragma unroll
                for (int i = 0; i < 16; i++) {
                    cx[i] = kb == k1 ? x2[2 * i + 1] : x2[2 * i];
                    ch[i] = ln_apply(cx[i], kb == k1 ? mb1 : mb0, kb == k1 ? rs1 : rs0, cb[i], sh[i]);
                }
                cx[16] = cx[17] = ch[16] = ch[17] = 0;
                uint4* cp = g_cand + (row >> 4) * 192 + cq * 24 + c4;
#pragma unroll
                for (int v = 0; v < 6; v++) st_pub(cp + v * 4, make_uint4(ch[3 * v], ch[3 * v + 1], ch[3 * v + 2], ep), kb == k0 || kb == k1);
                if (TF & 4) sched_fence(eb2, P.zero);
#pragma unroll
                for (int v = 0; v < 6; v++) st_pub(cp + 96 + v * 4, make_uint4(cx[3 * v], cx[3 * v + 1], cx[3 * v + 2], ep), kb == k0 || kb == k1);
            }
            if (elected) TS(58);
            TT(6);
            uint2 ov[16];
#pragma unroll
            for (int i = 0; i < 16; i++) {
                const int rh = i & 1, jj = i & 14;
                const uint32_t v0 = badd(x2[2 * jj + rh], bmul(gb[jj], ln_apply(x2[2 * jj + rh], rh ? mb1 : mb0, rh ? rs1 : rs0, cb[jj], sh[jj])));
                const uint32_t v1 = badd(x2[2 * jj + 2 + rh], bmul(gb[jj + 1], ln_apply(x2[2 * jj + 2 + rh], rh ? mb1 : mb0, rh ? rs1 : rs0, cb[jj + 1], sh[jj + 1])));
                const uint32_t rv = __shfl_xor_sync(0xffffffffu, (c4 & 1) ? v0 : v1, 1);
                ov[i] = (c4 & 1) ? make_uint2(rv, v1) : make_uint2(v0, rv);
            }
            uint2* op = reinterpret_cast<uint2*>(P.out) + row * 128 + cq * 32 + (c4 & 1) * 2 + (c4 >> 1);
#pragma unroll
            for (int i = 0; i < 16; i++)
                if (kb != ((i & 1) ? k1 : k0)) op[(i & 1) * 1024 + (i & 14) * 2] = ov[i];
            mbar_wait(sb + BAR_BEST, 0);
            if (lds32(sb + SM_EP + 4) != kb) {
#pragma unroll
                for (int i = 0; i < 16; i++)
                    if (kb == ((i & 1) ? k1 : k0)) op[(i & 1) * 1024 + (i & 14) * 2] = ov[i];
            }
            if (elected) TS(59);
            TT(7);
        }
        mbar_arrive_if(eb2, lane == 0);
    }
}

typedef CUresult (*EncodeFn)(CUtensorMap*, CUtensorMapDataType, cuuint32_t, void*, const cuuint64_t*, const cuuint64_t*,
                             const cuuint32_t*, const cuuint32_t*, CUtensorMapInterleave, CUtensorMapSwizzle,
                             CUtensorMapL2promotion, CUtensorMapFloatOOBfill);

void make_2d(EncodeFn fn, CUtensorMap* m, const void* p, uint64_t cols, uint64_t rows, uint32_t bc, uint32_t br) {
    cuuint64_t dims[2] = {cols, rows}, strides[1] = {cols * 2};
    cuuint32_t box[2] = {bc, br}, es[2] = {1, 1};
    fn(m, CU_TENSOR_MAP_DATA_TYPE_BFLOAT16, 2, const_cast<void*>(p), dims, strides, box, es, CU_TENSOR_MAP_INTERLEAVE_NONE,
       CU_TENSOR_MAP_SWIZZLE_NONE, CU_TENSOR_MAP_L2_PROMOTION_L2_128B, CU_TENSOR_MAP_FLOAT_OOB_FILL_NONE);
}
void make_3d(EncodeFn fn, CUtensorMap* m, const void* p, uint64_t cols, uint64_t rows, uint32_t br = 128, uint32_t nb = 2) {
    cuuint64_t dims[3] = {64, rows, cols / 64}, strides[2] = {cols * 2, 128};
    cuuint32_t box[3] = {64, br, nb}, es[3] = {1, 1, 1};
    fn(m, CU_TENSOR_MAP_DATA_TYPE_BFLOAT16, 3, const_cast<void*>(p), dims, strides, box, es, CU_TENSOR_MAP_INTERLEAVE_NONE,
       CU_TENSOR_MAP_SWIZZLE_128B, CU_TENSOR_MAP_L2_PROMOTION_L2_256B, CU_TENSOR_MAP_FLOAT_OOB_FILL_NONE);
}

}

extern "C" void kernel_launch(void* const* d_in, const int* in_sizes, int n_in, void* d_out, int out_size) {
    static EncodeFn fn = nullptr;
    if (!fn) {
        void* f = nullptr;
        cudaDriverEntryPointQueryResult st;
        cudaGetDriverEntryPoint("cuTensorMapEncodeTiled", &f, cudaEnableDefault, &st);
        fn = (EncodeFn)f;
        cudaFuncSetAttribute(fused_kernel, cudaFuncAttributeMaxDynamicSharedMemorySize, SMEM_BYTES);
    }
    CUtensorMap ckv, wq, wuk, wuv, wo, wg, wu, wm, xm;
    make_3d(fn, &ckv, d_in[1], 512, 2048, 128, 1);
    make_3d(fn, &xm, d_in[0], 512, 2048, 64);
    make_3d(fn, &wq, d_in[2], 4096, 512, 128, 1);
    make_3d(fn, &wuk, d_in[3], 4096, 512);
    make_3d(fn, &wuv, d_in[4], 4096, 512);
    make_3d(fn, &wo, d_in[5], 512, 4096);
    make_2d(fn, &wg, d_in[8], 1792, 512, 16, 256);
    make_2d(fn, &wu, d_in[9], 1792, 512, 16, 256);
    make_2d(fn, &wm, d_in[12], 3072, 512, 256, 64);
    Params p;
    p.x = (const bf16*)d_in[0];
    p.ckv = (const bf16*)d_in[1];
    p.wo = (const bf16*)d_in[5];
    p.wr = (const bf16*)d_in[7];
    p.wdown = (const bf16*)d_in[10];
    p.c = (const bf16*)d_in[11];
    p.out = (bf16*)d_out;
    p.zero = 0;
    fused_kernel<<<NCTA + NSPARE, 384, SMEM_BYTES>>>(ckv, wq, wuk, wuv, wo, wg, wu, wm, xm, p);
}
```

```cpp
#include <cuda.h>
#include <cuda_bf16.h>
#include <cuda_runtime.h>
#include <stdint.h>
#include <stdio.h>

namespace {

typedef __nv_bfloat16 bf16;
typedef unsigned long long u64;

constexpr int NCTA = 128, NSPARE = 4;
constexpr int SLOT = 32768;
constexpr int SM_BAR = 7 * SLOT;
constexpr int BAR_FULL = SM_BAR;
constexpr int BAR_EMPTY = BAR_FULL + 8 * 7;
constexpr int BAR_DONE = BAR_EMPTY + 8 * 7;
constexpr int BAR_FLAG = BAR_DONE + 8 * 9;
constexpr int BAR_PF = BAR_FLAG + 8 * 9;
constexpr int BAR_END = BAR_PF + 8;
constexpr int BAR_BEST = BAR_END + 8;
constexpr int SM_EP = BAR_END + 24;
constexpr int SM_RED = SM_BAR + 384;
constexpr int SM_TAB = SM_BAR + 1024;
constexpr int SMEM_BYTES = SM_BAR + 3072;
constexpr int NFFN = 112;
#define HINT 31
constexpr u64 L2_NORMAL = 0x1000000000000000ull, L2_FIRST = 0x12F0000000000000ull;
#define PFA 8
#define PFB 6
#define UNR 1
#define POLL_NS 50
#define MSPLIT 13
#define SF 3
#define XQ 0
#define KGATE 1
#define TF 7
#define KALL 0
#define OUTLATE 0
#define KSLEEP 150
#define YSLEEP 50
#define YPRE 150
#define SSLEEP 50
#define SPRE 0
#define PSLEEP 0
#define CSLEEP 0
#define EARLY 7
constexpr uint32_t SPIN_LIMIT = 1u << 22;
constexpr uint32_t ONE2 = 0x3f803f80u;

struct Sync {
    uint32_t cnt[16 * 8 * 8];
    uint32_t ctxcnt[16 * 32];
    uint32_t epoch[32];
};

__device__ __align__(1024) uint8_t g_KV[16 * 16 * 2 * SLOT];
__device__ __align__(1024) uint8_t g_ctx[16 * 32 * SLOT];
__device__ __align__(1024) uint8_t g_h[16 * 4 * SLOT];
constexpr int OB = 1216, OB_STAT = 1024, OB_Y = 1088;
__device__ __align__(1024) uint4 g_out[128 * OB];
__device__ __align__(1024) bf16 g_mod[3072];
__device__ __align__(1024) uint32_t g_mod1[1024];
__device__ __align__(1024) uint4 g_cand[128 * 192];
__device__ __align__(1024) uint32_t g_key[4 * 128];
__device__ __align__(1024) uint8_t g_wf[NFFN * SLOT];
__device__ __align__(1024) Sync g_sync;
#define TS(i)

#define TT(i)
#define PT()

struct Params {
    const bf16 *x, *ckv, *wo, *wr, *wdown, *c;
    bf16* out;
    int zero;
};

__device__ __forceinline__ void mbar_init(uint32_t bar, uint32_t cnt) {
    asm volatile("mbarrier.init.shared::cta.b64 [%0], %1;" ::"r"(bar), "r"(cnt) : "memory");
}
__device__ __forceinline__ void mbar_wait(uint32_t bar, uint32_t parity) {
    asm volatile("{\n.reg .pred p;\nL_%=:\nmbarrier.try_wait.parity.shared::cta.b64 p, [%0], %1;\n@!p bra L_%=;\n}" ::"r"(bar), "r"(parity) : "memory");
}
__device__ __forceinline__ void mbar_sleep(uint32_t bar) {
    if ((threadIdx.x & 31) == 0)
        asm volatile("{\n.reg .pred p;\nL_%=:\nmbarrier.try_wait.parity.shared::cta.b64 p, [%0], 0, 100000;\n@!p bra L_%=;\n}" ::"r"(bar) : "memory");
    __syncwarp();
}
__device__ __forceinline__ void mbar_watch(uint32_t bar, uint32_t parity) {
    asm volatile("{\n.reg .pred p;\n.reg .u32 n;\nmov.u32 n, 0;\n"
                 "L_%=:\nmbarrier.try_wait.parity.shared::cta.b64 p, [%0], %1;\n@p bra D_%=;\n"
                 "add.u32 n, n, 1;\nsetp.lt.u32 p, n, %2;\n@p bra L_%=;\ntrap;\nD_%=:\n}"
                 ::"r"(bar), "r"(parity), "n"(SPIN_LIMIT) : "memory");
}
__device__ __forceinline__ void step_watch(uint32_t a, uint32_t step) {
    asm volatile("{\n.reg .pred p;\n.reg .u32 n, v;\nmov.u32 n, 0;\n"
                 "L_%=:\nld.volatile.shared.u32 v, [%0];\nsetp.ge.u32 p, v, %1;\n@p bra D_%=;\nnanosleep.u32 400;\n"
                 "add.u32 n, n, 1;\nsetp.lt.u32 p, n, %2;\n@p bra L_%=;\ntrap;\nD_%=:\n}"
                 ::"r"(a), "r"(step), "n"(SPIN_LIMIT) : "memory");
}
__device__ __forceinline__ void mbar_arrive_if(uint32_t bar, bool on) {
    asm volatile("{\n.reg .pred p;\nsetp.ne.s32 p, %1, 0;\n@p mbarrier.arrive.shared::cta.b64 _, [%0];\n}" ::"r"(bar), "r"((int)on) : "memory");
}
__device__ __forceinline__ void tma2d(uint32_t dst, const CUtensorMap* m, int c0, int c1, uint32_t bar) {
    asm volatile("{\n.reg .pred p;\nelect.sync _|p, 0xffffffff;\n"
                 "@p cp.async.bulk.tensor.2d.shared::cluster.global.mbarrier::complete_tx::bytes [%0], [%1, {%3, %4}], [%2];\n}"
                 ::"r"(dst), "l"(m), "r"(bar), "r"(c0), "r"(c1) : "memory");
}
__device__ __forceinline__ void tma3d_prefetch(const CUtensorMap* m, int row, int cb) {
    asm volatile("{\n.reg .pred p;\nelect.sync _|p, 0xffffffff;\n@p cp.async.bulk.prefetch.tensor.3d.L2.global [%0, {%1, %2, %3}];\n}"
                 ::"l"(m), "r"(0), "r"(row), "r"(cb) : "memory");
}
__device__ __forceinline__ void l2_prefetch(const void* p, uint32_t bytes) {
    asm volatile("{\n.reg .pred p;\nelect.sync _|p, 0xffffffff;\n@p cp.async.bulk.prefetch.L2.global [%0], %1;\n}" ::"l"(p), "r"(bytes) : "memory");
}
__device__ __forceinline__ void bulk_store(void* dst, uint32_t src, uint32_t bytes) {
    asm volatile("{\n.reg .pred p;\nelect.sync _|p, 0xffffffff;\n@p cp.async.bulk.global.shared::cta.bulk_group [%0], [%1], %2;\n}"
                 ::"l"(dst), "r"(src), "r"(bytes) : "memory");
}
__device__ __forceinline__ void flag_wait(const uint32_t* f, uint32_t target) {
    asm volatile("{\n.reg .pred p;\n.reg .u32 v;\n"
                 "L_%=:\nld.acquire.gpu.global.u32 v, [%0];\nsub.u32 v, v, %1;\nsetp.lt.s32 p, v, 0;\n@p nanosleep.u32 100;\n@p bra L_%=;\n}"
                 ::"l"(f), "r"(target) : "memory");
}
__device__ __forceinline__ uint4 ld_poll(const uint4* p) {
    uint4 v;
    asm volatile("{\n.reg .b128 t;\nld.relaxed.gpu.global.b128 t, [%4];\nmov.b128 {%0, %1, %2, %3}, t;\n}"
                 : "=r"(v.x), "=r"(v.y), "=r"(v.z), "=r"(v.w) : "l"(p) : "memory");
    return v;
}
__device__ __forceinline__ void st_pub(uint4* p, uint4 v, bool on) {
    asm volatile("{\n.reg .pred p;\n.reg .b128 t;\nsetp.ne.s32 p, %5, 0;\nmov.b128 t, {%1, %2, %3, %4};\n@p st.relaxed.gpu.global.b128 [%0], t;\n}"
                 ::"l"(p), "r"(v.x), "r"(v.y), "r"(v.z), "r"(v.w), "r"((int)on) : "memory");
}
__device__ __forceinline__ void st_pub(uint32_t* p, uint32_t v, bool on) {
    asm volatile("{\n.reg .pred p;\nsetp.ne.s32 p, %2, 0;\n@p st.relaxed.gpu.global.u32 [%0], %1;\n}" ::"l"(p), "r"(v), "r"((int)on) : "memory");
}
__device__ __forceinline__ void flag_add(uint32_t* p) {
    asm volatile("red.release.gpu.global.add.u32 [%0], 1;" ::"l"(p) : "memory");
}
__device__ __forceinline__ uint32_t lds32(uint32_t a) {
    uint32_t v;
    asm volatile("ld.shared.u32 %0, [%1];" : "=r"(v) : "r"(a) : "memory");
    return v;
}
__device__ __forceinline__ uint4 lds128(uint32_t a) {
    uint4 v;
    asm volatile("ld.shared.v4.u32 {%0, %1, %2, %3}, [%4];" : "=r"(v.x), "=r"(v.y), "=r"(v.z), "=r"(v.w) : "r"(a) : "memory");
    return v;
}
__device__ __forceinline__ void sched_fence(uint32_t& v, uint32_t z) {
    uint32_t ck;
    asm volatile("mov.u32 %0, %%clock;" : "=r"(ck)::"memory");
    v ^= ck & z;
}
__device__ __forceinline__ void fence_async_global() { asm volatile("fence.proxy.async.global;" ::: "memory"); }
__device__ __forceinline__ void fence_async_smem() { asm volatile("fence.proxy.async.shared::cta;" ::: "memory"); }
__device__ __forceinline__ void bar_sync(int id, int n) { asm volatile("bar.sync %0, %1;" ::"r"(id), "r"(n) : "memory"); }
__device__ __forceinline__ void bar_arrive(int id, int n) { asm volatile("bar.arrive %0, %1;" ::"r"(id), "r"(n) : "memory"); }
__device__ __forceinline__ void wg_fence() { asm volatile("wgmma.fence.sync.aligned;" ::: "memory"); }
__device__ __forceinline__ void wg_commit() { asm volatile("wgmma.commit_group.sync.aligned;" ::: "memory"); }
template <int N> __device__ __forceinline__ void wg_wait() { asm volatile("wgmma.wait_group.sync.aligned %0;" ::"n"(N) : "memory"); }
template <int N> __device__ __forceinline__ void reg_fence(float (&d)[N]) {
#pragma unroll
    for (int i = 0; i < N; i++) asm volatile("" : "+f"(d[i])::"memory");
}
template <int N> __device__ __forceinline__ void reg_fence(uint32_t (&d)[N]) {
#pragma unroll
    for (int i = 0; i < N; i++) asm volatile("" : "+r"(d[i])::"memory");
}
__device__ __forceinline__ uint32_t desc_k(uint32_t a) { return ((a & 0x3ffff) >> 4) | (1u << 16); }
__device__ __forceinline__ uint32_t desc_mn(uint32_t a) { return ((a & 0x3ffff) >> 4) | (1024u << 16); }

template <int TB>
__device__ __forceinline__ void wgmma_ss128(float (&d)[64], uint32_t da, uint32_t db, int acc, uint32_t ha = 0x40000040u, uint32_t hb = 0x40000040u) {
    asm volatile("{\n.reg .pred p;\n.reg .b64 a, b;\nsetp.ne.b32 p, %66, 0;\nmov.b64 a, {%64, %68};\nmov.b64 b, {%65, %69};\n"
        "wgmma.mma_async.sync.aligned.m64n128k16.f32.bf16.bf16 {%0, %1, %2, %3, %4, %5, %6, %7, %8, %9, %10, %11, %12, %13, %14, %15, %16, %17, %18, %19, %20, %21, %22, %23, %24, %25, %26, %27, %28, %29, %30, %31, %32, %33, %34, %35, %36, %37, %38, %39, %40, %41, %42, %43, %44, %45, %46, %47, %48, %49, %50, %51, %52, %53, %54, %55, %56, %57, %58, %59, %60, %61, %62, %63}, a, b, p, 1, 1, 0, %67;\n}"
        : "+f"(d[0]), "+f"(d[1]), "+f"(d[2]), "+f"(d[3]), "+f"(d[4]), "+f"(d[5]), "+f"(d[6]), "+f"(d[7]), "+f"(d[8]), "+f"(d[9]), "+f"(d[10]), "+f"(d[11]), "+f"(d[12]), "+f"(d[13]), "+f"(d[14]), "+f"(d[15]), "+f"(d[16]), "+f"(d[17]), "+f"(d[18]), "+f"(d[19]), "+f"(d[20]), "+f"(d[21]), "+f"(d[22]), "+f"(d[23]), "+f"(d[24]), "+f"(d[25]), "+f"(d[26]), "+f"(d[27]), "+f"(d[28]), "+f"(d[29]), "+f"(d[30]), "+f"(d[31]), "+f"(d[32]), "+f"(d[33]), "+f"(d[34]), "+f"(d[35]), "+f"(d[36]), "+f"(d[37]), "+f"(d[38]), "+f"(d[39]), "+f"(d[40]), "+f"(d[41]), "+f"(d[42]), "+f"(d[43]), "+f"(d[44]), "+f"(d[45]), "+f"(d[46]), "+f"(d[47]), "+f"(d[48]), "+f"(d[49]), "+f"(d[50]), "+f"(d[51]), "+f"(d[52]), "+f"(d[53]), "+f"(d[54]), "+f"(d[55]), "+f"(d[56]), "+f"(d[57]), "+f"(d[58]), "+f"(d[59]), "+f"(d[60]), "+f"(d[61]), "+f"(d[62]), "+f"(d[63])
        : "r"(da), "r"(db), "r"(acc), "n"(TB), "r"(ha), "r"(hb));
}
template <int TB>
__device__ __forceinline__ void wgmma_ss128_init(float (&d)[64], uint32_t da, uint32_t db, uint32_t ha = 0x40000040u, uint32_t hb = 0x40000040u) {
    asm volatile("{\n.reg .pred p;\n.reg .b64 a, b;\nsetp.ne.b32 p, 0, 0;\nmov.b64 a, {%64, %67};\nmov.b64 b, {%65, %68};\n"
        "wgmma.mma_async.sync.aligned.m64n128k16.f32.bf16.bf16 {%0, %1, %2, %3, %4, %5, %6, %7, %8, %9, %10, %11, %12, %13, %14, %15, %16, %17, %18, %19, %20, %21, %22, %23, %24, %25, %26, %27, %28, %29, %30, %31, %32, %33, %34, %35, %36, %37, %38, %39, %40, %41, %42, %43, %44, %45, %46, %47, %48, %49, %50, %51, %52, %53, %54, %55, %56, %57, %58, %59, %60, %61, %62, %63}, a, b, p, 1, 1, 0, %66;\n}"
        : "=f"(d[0]), "=f"(d[1]), "=f"(d[2]), "=f"(d[3]), "=f"(d[4]), "=f"(d[5]), "=f"(d[6]), "=f"(d[7]), "=f"(d[8]), "=f"(d[9]), "=f"(d[10]), "=f"(d[11]), "=f"(d[12]), "=f"(d[13]), "=f"(d[14]), "=f"(d[15]), "=f"(d[16]), "=f"(d[17]), "=f"(d[18]), "=f"(d[19]), "=f"(d[20]), "=f"(d[21]), "=f"(d[22]), "=f"(d[23]), "=f"(d[24]), "=f"(d[25]), "=f"(d[26]), "=f"(d[27]), "=f"(d[28]), "=f"(d[29]), "=f"(d[30]), "=f"(d[31]), "=f"(d[32]), "=f"(d[33]), "=f"(d[34]), "=f"(d[35]), "=f"(d[36]), "=f"(d[37]), "=f"(d[38]), "=f"(d[39]), "=f"(d[40]), "=f"(d[41]), "=f"(d[42]), "=f"(d[43]), "=f"(d[44]), "=f"(d[45]), "=f"(d[46]), "=f"(d[47]), "=f"(d[48]), "=f"(d[49]), "=f"(d[50]), "=f"(d[51]), "=f"(d[52]), "=f"(d[53]), "=f"(d[54]), "=f"(d[55]), "=f"(d[56]), "=f"(d[57]), "=f"(d[58]), "=f"(d[59]), "=f"(d[60]), "=f"(d[61]), "=f"(d[62]), "=f"(d[63])
        : "r"(da), "r"(db), "n"(TB), "r"(ha), "r"(hb));
}
template <int TB>
__device__ __forceinline__ void wgmma_ss64(float (&d)[32], uint32_t da, uint32_t db, int acc, uint32_t ha = 0x40000040u, uint32_t hb = 0x40000040u) {
    asm volatile("{\n.reg .pred p;\n.reg .b64 a, b;\nsetp.ne.b32 p, %34, 0;\nmov.b64 a, {%32, %36};\nmov.b64 b, {%33, %37};\n"
        "wgmma.mma_async.sync.aligned.m64n64k16.f32.bf16.bf16 {%0, %1, %2, %3, %4, %5, %6, %7, %8, %9, %10, %11, %12, %13, %14, %15, %16, %17, %18, %19, %20, %21, %22, %23, %24, %25, %26, %27, %28, %29, %30, %31}, a, b, p, 1, 1, 0, %35;\n}"
        : "+f"(d[0]), "+f"(d[1]), "+f"(d[2]), "+f"(d[3]), "+f"(d[4]), "+f"(d[5]), "+f"(d[6]), "+f"(d[7]), "+f"(d[8]), "+f"(d[9]), "+f"(d[10]), "+f"(d[11]), "+f"(d[12]), "+f"(d[13]), "+f"(d[14]), "+f"(d[15]), "+f"(d[16]), "+f"(d[17]), "+f"(d[18]), "+f"(d[19]), "+f"(d[20]), "+f"(d[21]), "+f"(d[22]), "+f"(d[23]), "+f"(d[24]), "+f"(d[25]), "+f"(d[26]), "+f"(d[27]), "+f"(d[28]), "+f"(d[29]), "+f"(d[30]), "+f"(d[31])
        : "r"(da), "r"(db), "r"(acc), "n"(TB), "r"(ha), "r"(hb));
}
template <int TB>
__device__ __forceinline__ void wgmma_ss64_init(float (&d)[32], uint32_t da, uint32_t db, uint32_t ha = 0x40000040u, uint32_t hb = 0x40000040u) {
    asm volatile("{\n.reg .pred p;\n.reg .b64 a, b;\nsetp.ne.b32 p, 0, 0;\nmov.b64 a, {%32, %35};\nmov.b64 b, {%33, %36};\n"
        "wgmma.mma_async.sync.aligned.m64n64k16.f32.bf16.bf16 {%0, %1, %2, %3, %4, %5, %6, %7, %8, %9, %10, %11, %12, %13, %14, %15, %16, %17, %18, %19, %20, %21, %22, %23, %24, %25, %26, %27, %28, %29, %30, %31}, a, b, p, 1, 1, 0, %34;\n}"
        : "=f"(d[0]), "=f"(d[1]), "=f"(d[2]), "=f"(d[3]), "=f"(d[4]), "=f"(d[5]), "=f"(d[6]), "=f"(d[7]), "=f"(d[8]), "=f"(d[9]), "=f"(d[10]), "=f"(d[11]), "=f"(d[12]), "=f"(d[13]), "=f"(d[14]), "=f"(d[15]), "=f"(d[16]), "=f"(d[17]), "=f"(d[18]), "=f"(d[19]), "=f"(d[20]), "=f"(d[21]), "=f"(d[22]), "=f"(d[23]), "=f"(d[24]), "=f"(d[25]), "=f"(d[26]), "=f"(d[27]), "=f"(d[28]), "=f"(d[29]), "=f"(d[30]), "=f"(d[31])
        : "r"(da), "r"(db), "n"(TB), "r"(ha), "r"(hb));
}
__device__ __forceinline__ void wgmma_rs128(float (&d)[64], uint32_t a0, uint32_t a1, uint32_t a2, uint32_t a3, uint32_t db, int acc, uint32_t hb = 0x40000040u) {
    asm volatile("{\n.reg .pred p;\n.reg .b64 b;\nsetp.ne.b32 p, %69, 0;\nmov.b64 b, {%68, %70};\n"
        "wgmma.mma_async.sync.aligned.m64n128k16.f32.bf16.bf16 {%0, %1, %2, %3, %4, %5, %6, %7, %8, %9, %10, %11, %12, %13, %14, %15, %16, %17, %18, %19, %20, %21, %22, %23, %24, %25, %26, %27, %28, %29, %30, %31, %32, %33, %34, %35, %36, %37, %38, %39, %40, %41, %42, %43, %44, %45, %46, %47, %48, %49, %50, %51, %52, %53, %54, %55, %56, %57, %58, %59, %60, %61, %62, %63}, {%64, %65, %66, %67}, b, p, 1, 1, 1;\n}"
        : "+f"(d[0]), "+f"(d[1]), "+f"(d[2]), "+f"(d[3]), "+f"(d[4]), "+f"(d[5]), "+f"(d[6]), "+f"(d[7]), "+f"(d[8]), "+f"(d[9]), "+f"(d[10]), "+f"(d[11]), "+f"(d[12]), "+f"(d[13]), "+f"(d[14]), "+f"(d[15]), "+f"(d[16]), "+f"(d[17]), "+f"(d[18]), "+f"(d[19]), "+f"(d[20]), "+f"(d[21]), "+f"(d[22]), "+f"(d[23]), "+f"(d[24]), "+f"(d[25]), "+f"(d[26]), "+f"(d[27]), "+f"(d[28]), "+f"(d[29]), "+f"(d[30]), "+f"(d[31]), "+f"(d[32]), "+f"(d[33]), "+f"(d[34]), "+f"(d[35]), "+f"(d[36]), "+f"(d[37]), "+f"(d[38]), "+f"(d[39]), "+f"(d[40]), "+f"(d[41]), "+f"(d[42]), "+f"(d[43]), "+f"(d[44]), "+f"(d[45]), "+f"(d[46]), "+f"(d[47]), "+f"(d[48]), "+f"(d[49]), "+f"(d[50]), "+f"(d[51]), "+f"(d[52]), "+f"(d[53]), "+f"(d[54]), "+f"(d[55]), "+f"(d[56]), "+f"(d[57]), "+f"(d[58]), "+f"(d[59]), "+f"(d[60]), "+f"(d[61]), "+f"(d[62]), "+f"(d[63])
        : "r"(a0), "r"(a1), "r"(a2), "r"(a3), "r"(db), "r"(acc), "r"(hb));
}

__device__ __forceinline__ uint32_t pack2(float lo, float hi) {
    uint32_t r;
    asm("cvt.rn.bf16x2.f32 %0, %1, %2;" : "=r"(r) : "f"(hi), "f"(lo));
    return r;
}
__device__ __forceinline__ float bf_lo(uint32_t v) { return __uint_as_float(v << 16); }
__device__ __forceinline__ float bf_hi(uint32_t v) { return __uint_as_float(v & 0xffff0000u); }
__device__ __forceinline__ float rbf(float v) { return bf_lo(pack2(v, v)); }
__device__ __forceinline__ uint32_t badd(uint32_t a, uint32_t b) {
    uint32_t r;
    asm("add.rn.bf16x2 %0, %1, %2;" : "=r"(r) : "r"(a), "r"(b));
    return r;
}
__device__ __forceinline__ uint32_t bsub(uint32_t a, uint32_t b) {
    uint32_t r;
    asm("sub.rn.bf16x2 %0, %1, %2;" : "=r"(r) : "r"(a), "r"(b));
    return r;
}
__device__ __forceinline__ uint32_t bmul(uint32_t a, uint32_t b) {
    uint32_t r;
    asm("mul.rn.bf16x2 %0, %1, %2;" : "=r"(r) : "r"(a), "r"(b));
    return r;
}
__device__ __forceinline__ uint32_t ln_apply(uint32_t x, uint32_t mb, float rs, uint32_t scale, uint32_t shift) {
    const uint32_t d = bsub(x, mb);
    return badd(bmul(pack2(bf_lo(d) * rs, bf_hi(d) * rs), scale), shift);
}
__device__ __forceinline__ float ex2(float v) {
    float r;
    asm("ex2.approx.ftz.f32 %0, %1;" : "=f"(r) : "f"(v));
    return r;
}
__device__ __forceinline__ float rcp(float v) {
    float r;
    asm("rcp.approx.ftz.f32 %0, %1;" : "=f"(r) : "f"(v));
    return r;
}
__device__ __forceinline__ float sqrt_fast(float v) {
    float r;
    asm("sqrt.approx.ftz.f32 %0, %1;" : "=f"(r) : "f"(v));
    return r;
}
__device__ __forceinline__ float ln_rstd(float var) { return rcp(rbf(sqrt_fast(rbf(rbf(var) + 1e-5f)))); }
__device__ __forceinline__ float sigmoid(float v) { return rcp(1.f + ex2(-1.4426950408889634f * v)); }
__device__ __forceinline__ float quad_sum(float v) {
    v += __shfl_xor_sync(0xffffffffu, v, 1);
    return v + __shfl_xor_sync(0xffffffffu, v, 2);
}

constexpr uint32_t HI_128 = 0x40000040u, HI_IMG = 0x80000080u, HI_Q = 0x80000040u;
template <int M, int RH>
__device__ __forceinline__ uint4 img_pack(const float (&d)[64], float s) {
    uint4 v;
    v.x = pack2(d[16 * M + 2 * RH] * s, d[16 * M + 2 * RH + 1] * s);
    v.y = pack2(d[16 * M + 4 + 2 * RH] * s, d[16 * M + 5 + 2 * RH] * s);
    v.z = pack2(d[16 * M + 8 + 2 * RH] * s, d[16 * M + 9 + 2 * RH] * s);
    v.w = pack2(d[16 * M + 12 + 2 * RH] * s, d[16 * M + 13 + 2 * RH] * s);
    return v;
}
template <int M>
__device__ __forceinline__ void img_store_global(uint8_t* img, uint32_t toff, const float (&d)[64], float s0, float s1) {
    uint4* p = reinterpret_cast<uint4*>(img + toff) + M * 32;
    p[0] = img_pack<M, 0>(d, s0);
    p[128] = img_pack<M, 1>(d, s1);
}
__device__ __forceinline__ void sts128(uint32_t a, uint4 v) {
    asm volatile("st.shared.v4.b32 [%0], {%1, %2, %3, %4};" ::"r"(a), "r"(v.x), "r"(v.y), "r"(v.z), "r"(v.w) : "memory");
}
constexpr float SM_C = 0.08838834764831845f * 1.4426950408889634f;
__device__ __forceinline__ float pack2f(float lo, float hi) {
    float r;
    asm("{\n.reg .b32 t;\ncvt.rn.bf16x2.f32 t, %1, %2;\nmov.b32 %0, t;\n}" : "=f"(r) : "f"(hi), "f"(lo));
    return r;
}
template <int M, bool SCALE, bool PARK>
__device__ __forceinline__ void pack_group(float (&d)[64], float (&v)[8], float s0, float s1) {
#pragma unroll
    for (int i = 0; i < 8; i++) {
        const int k = 16 * M + 4 * (i & 3) + 2 * (i >> 2);
        v[i] = SCALE ? pack2f(d[k] * (i < 4 ? s0 : s1), d[k + 1] * (i < 4 ? s0 : s1)) : pack2f(d[k], d[k + 1]);
        if (PARK && M > 0) d[16 * (M > 0 ? M - 1 : 0) + i] = v[i];
    }
}
__device__ __forceinline__ uint32_t q_off(uint32_t toff) { return (((toff >> 1) & ~2047u) ^ 8192) + (toff & 511); }
template <int M, bool PARK>
__device__ __forceinline__ void ctx_store_part(float4* p, float (&d)[64], float i0, float i1) {
    float v[8];
    pack_group<M, true, PARK>(d, v, i0, i1);
    p[M * 32] = make_float4(v[0], v[1], v[2], v[3]);
    p[M * 32 + 128] = make_float4(v[4], v[5], v[6], v[7]);
}
template <bool PARK>
__device__ __forceinline__ void ctx_store(uint8_t* img, uint32_t toff, float (&o)[64], float l0, float l1) {
    const float i0 = rcp(quad_sum(l0)), i1 = rcp(quad_sum(l1));
    float4* p = reinterpret_cast<float4*>(img + toff);
    ctx_store_part<0, PARK>(p, o, i0, i1); ctx_store_part<1, PARK>(p, o, i0, i1); ctx_store_part<2, PARK>(p, o, i0, i1); ctx_store_part<3, PARK>(p, o, i0, i1);
}

template <int M>
__device__ __forceinline__ void tile_store_part(float4* p, uint32_t a, float (&d)[64], float i0, float i1, int ctx) {
    float v[8];
    pack_group<M, true, true>(d, v, i0, i1);
#pragma unroll
    for (int h = 0; h < 2; h++)
        asm volatile("{\n.reg .pred p;\nsetp.ne.s32 p, %6, 0;\n@p st.global.v4.f32 [%0], {%2, %3, %4, %5};\n@!p st.shared.v4.f32 [%1], {%2, %3, %4, %5};\n}"
                     ::"l"(p + M * 32 + h * 128), "r"(a + (M >> 1) * 16384 + (M & 1) * 512 + h * 1024),
                     "f"(v[4 * h]), "f"(v[4 * h + 1]), "f"(v[4 * h + 2]), "f"(v[4 * h + 3]), "r"(ctx) : "memory");
}
__device__ __forceinline__ void tile_store(uint8_t* img, uint32_t a, uint32_t toff, float (&d)[64], float i0, float i1, int ctx) {
    float4* p = reinterpret_cast<float4*>(img + toff);
    a += q_off(toff);
    tile_store_part<0>(p, a, d, i0, i1, ctx); tile_store_part<1>(p, a, d, i0, i1, ctx);
    tile_store_part<2>(p, a, d, i0, i1, ctx); tile_store_part<3>(p, a, d, i0, i1, ctx);
}

__device__ __forceinline__ void slot_wait(uint32_t bars, uint32_t& ph, uint32_t slot) {
    mbar_wait(bars + 8 * slot, (ph >> slot) & 1);
    ph ^= 1u << slot;
}
__device__ __forceinline__ void release_if(uint32_t eb, uint32_t slot, bool on) {
    asm volatile("{\n.reg .pred p;\nsetp.ne.s32 p, %1, 0;\n@p mbarrier.arrive.shared::cluster.b64 _, [%0];\n}" ::"r"(eb + 8 * slot), "r"((int)on) : "memory");
}
__device__ __forceinline__ void slot_acquire(uint32_t sb, uint32_t& ph, uint32_t slot) {
    slot_wait(sb + BAR_EMPTY, ph, slot);
    asm volatile("{\n.reg .pred p;\nelect.sync _|p, 0xffffffff;\n@p mbarrier.arrive.expect_tx.shared::cta.b64 _, [%0], 32768;\n}"
                 ::"r"(sb + BAR_FULL + 8 * slot) : "memory");
}
__device__ __forceinline__ void load_bulk(uint32_t sb, uint32_t slot, uint32_t off, const void* src, uint32_t bytes, bool both, bool first) {
    if (both)
        asm volatile("{\n.reg .pred p;\nelect.sync _|p, 0xffffffff;\n"
                     "@p cp.async.bulk.shared::cluster.global.mbarrier::complete_tx::bytes.multicast::cluster.L2::cache_hint [%0], [%1], %5, [%2], %4, %3;\n}"
                     ::"r"(sb + slot * SLOT + off), "l"(src), "r"(sb + BAR_FULL + 8 * slot), "l"(first ? L2_FIRST : L2_NORMAL), "h"((uint16_t)3),
                     "r"(bytes) : "memory");
    else
        asm volatile("{\n.reg .pred p;\nelect.sync _|p, 0xffffffff;\n"
                     "@p cp.async.bulk.shared::cluster.global.mbarrier::complete_tx::bytes.L2::cache_hint [%0], [%1], %4, [%2], %3;\n}"
                     ::"r"(sb + slot * SLOT + off), "l"(src), "r"(sb + BAR_FULL + 8 * slot), "l"(first ? L2_FIRST : L2_NORMAL), "r"(bytes) : "memory");
}
__device__ __forceinline__ void load_tile(uint32_t sb, uint32_t slot, uint32_t off, const CUtensorMap* m, int row, int cb, bool both, bool first) {
    if (both)
        asm volatile("{\n.reg .pred p;\nelect.sync _|p, 0xffffffff;\n"
                     "@p cp.async.bulk.tensor.3d.shared::cluster.global.mbarrier::complete_tx::bytes.multicast::cluster.L2::cache_hint [%0], [%1, {%3, %4, %5}], [%2], %7, %6;\n}"
                     ::"r"(sb + slot * SLOT + off), "l"(m), "r"(sb + BAR_FULL + 8 * slot), "r"(0), "r"(row), "r"(cb),
                     "l"(first ? L2_FIRST : L2_NORMAL), "h"((uint16_t)3) : "memory");
    else
        asm volatile("{\n.reg .pred p;\nelect.sync _|p, 0xffffffff;\n"
                     "@p cp.async.bulk.tensor.3d.shared::cluster.global.mbarrier::complete_tx::bytes.L2::cache_hint [%0], [%1, {%3, %4, %5}], [%2], %6;\n}"
                     ::"r"(sb + slot * SLOT + off), "l"(m), "r"(sb + BAR_FULL + 8 * slot), "r"(0), "r"(row), "r"(cb),
                     "l"(first ? L2_FIRST : L2_NORMAL) : "memory");
}
__device__ __forceinline__ uint32_t ring_next(uint32_t r) { return r == 4 ? 0 : r + 1; }
__device__ __forceinline__ uint32_t w_table(int hp) { return hp ? 0x3104u : 0x4210u; }
__device__ __forceinline__ uint32_t a_table(int hp) { return hp ? 0x625u : 0x635u; }
__device__ __forceinline__ uint32_t a_next(uint32_t& t) {
    const uint32_t s = t & 15;
    t = (t >> 4) | (s << 8);
    return s;
}
constexpr uint32_t O_TABLE = 0x1604235u;
__device__ __forceinline__ uint32_t o_next(uint32_t& t) {
    const uint32_t s = t & 15;
    t = (t >> 4) | (s << 24);
    return s;
}
__device__ __forceinline__ int o_head(int i, int kh) { return i < 16 ? 4 * (i & 7) + 2 * (kh ^ 1) + (i >> 3) : 29 + 2 * kh; }

template <bool INIT>
__device__ __forceinline__ void gemm_issue(float (&d)[64], uint32_t a, uint32_t b, int acc, bool img) {
    const uint32_t ha = img ? HI_IMG : HI_128, o2 = img ? 32 : 4, o4 = img ? 64 : 1024;
    wg_fence();
#pragma unroll
    for (int k = 0; k < 8; k++) {
        if (INIT && k == 0) wgmma_ss128_init<1>(d, a, b, ha);
        else wgmma_ss128<1>(d, a + (k >> 2) * o4 + ((k >> 1) & 1) * o2 + (k & 1) * 2, b + k * 128, k ? 1 : acc, ha);
    }
    wg_commit();
}

template <bool ODD>
__device__ __forceinline__ bool proj_tile(float (&acc)[64], float (&prev)[64], int t, int q0, uint32_t sb, int wg, uint32_t eb, bool rel, uint32_t& fph,
                                          uint32_t wtab, uint32_t& atab, uint8_t* prev_img, uint32_t toff, float s0, float s1, bool first,
                                          const bf16* x, int xrow, uint32_t (&v)[32]) {
    const uint32_t a0 = desc_k(sb + (wg ^ (ODD && t == 5)) * 8192), b0 = desc_mn(sb);
    const int lane = threadIdx.x & 31;
    constexpr int U = ODD ? UNR : 1;
#pragma unroll U
    for (int q = ODD ? 0 : q0; q < 4; q++) {
        const uint32_t ws = (wtab >> (4 * q)) & 15, as = a_next(atab);
        if (!ODD && t != 2) slot_wait(sb + BAR_FULL, fph, ws);
        slot_wait(sb + BAR_FULL, fph, as);
        if (ODD && q == 2 && t == 5) {
#pragma unroll
            for (int i = 0; i < 8; i++) sts128(sb + 5 * SLOT + q_off(toff) + (i >> 2) * 16384 + (i & 2) * 256 + (i & 1) * 1024, make_uint4(v[4 * i], v[4 * i + 1], v[4 * i + 2], v[4 * i + 3]));
        }
        bar_sync(1 + wg, 256);
        gemm_issue<false>(acc, a0 + as * (SLOT / 16), b0 + ws * (SLOT / 16), q, false);
        bar_arrive(2 - wg, 256);
        wg_wait<1>();
        reg_fence(prev);
        if (ODD && t == 5) {
            if (q == 0) {
#pragma unroll
                for (int i = 0; i < 32; i++) {
                    const int k = 16 * (i >> 3) + 4 * (i & 3) + ((i >> 1) & 2);
                    v[i] = pack2(prev[k], prev[k + 1]);
                }
            }
            if (q == 2) {
                fence_async_smem();
                slot_wait(sb + BAR_FULL, fph, wtab & 15);
                wg_wait<0>();
                release_if(eb, as, rel);
                release_if(eb, ws, rel);
                reg_fence(acc);
                return true;
            }
        } else {
            if (first) {
                const uint4* xp = reinterpret_cast<const uint4*>(x) + xrow * 64;
                if (!ODD) {
                    if (q == XQ && lane < 16) asm volatile("prefetch.global.L1 [%0];" ::"l"(xp + lane * 8) : "memory");
                    if (q == 3) {
#pragma unroll
                        for (int i = 0; i < 4; i++) {
                            const uint4 u = __ldg(xp + lane + 32 * i);
                            v[4 * i] = u.x; v[4 * i + 1] = u.y; v[4 * i + 2] = u.z; v[4 * i + 3] = u.w;
                        }
                        v[16] = __ldg(&xp[0].x) << 16;
                        v[17] = __ldg(&xp[64].x) << 16;
                        float st[4] = {0.f, 0.f, 0.f, 0.f};
#pragma unroll
                        for (int k = 0; k < 16; k++) {
                            const float d0 = bf_lo(v[k]) - __uint_as_float(v[16 + (k >> 3)]), d1 = bf_hi(v[k]) - __uint_as_float(v[16 + (k >> 3)]);
                            st[k >> 3] += d0 + d1;
                            st[2 + (k >> 3)] = fmaf(d0, d0, fmaf(d1, d1, st[2 + (k >> 3)]));
                        }
#pragma unroll
                        for (int i = 0; i < 4; i++) v[20 + i] = __float_as_uint(st[i]);
                    }
                } else if (q == 0) {
#pragma unroll
                    for (int i = 0; i < 20; i++)
                        v[20 + (i & 3)] = __float_as_uint(__uint_as_float(v[20 + (i & 3)]) + __uint_as_float(__shfl_xor_sync(0xffffffffu, v[20 + (i & 3)], 1 << (i >> 2))));
                } else if (q == 1) {
#pragma unroll
                    for (int i = 0; i < 2; i++) {
                        const float d = __uint_as_float(v[20 + i]) * (1.f / 512.f);
                        const float rs = ln_rstd(fmaxf(fmaf(-d, d, __uint_as_float(v[22 + i]) * (1.f / 512.f)), 0.f));
                        const uint32_t mb = pack2(__uint_as_float(v[16 + i]) + d, __uint_as_float(v[16 + i]) + d);
#pragma unroll
                        for (int k = 8 * i; k < 8 * i + 8; k++) {
                            const uint32_t y = bsub(v[k], mb);
                            v[k] = pack2(bf_lo(y) * rs, bf_hi(y) * rs);
                        }
                    }
                } else {
                    mbar_wait(sb + BAR_FLAG + 8 * 8, 0);
                    const uint4 a = lds128(sb + SM_TAB + q * 512 + lane * 16), c = lds128(sb + SM_TAB - 1024 + q * 512 + lane * 16);
                    uint8_t* p = g_h + ((xrow >> 7) * 8 + (q & 1) * 4 + (lane >> 3)) * 16384 + (xrow & 127) * 128;
#pragma unroll
                    for (int i = 0; i < 2; i++) {
                        *reinterpret_cast<uint4*>(p + i * 128 + (((lane ^ xrow ^ i) & 7) << 4)) =
                            make_uint4(badd(bmul(v[8 * i], a.x), c.x), badd(bmul(v[8 * i + 1], a.y), c.y),
                                       badd(bmul(v[8 * i + 2], a.z), c.z), badd(bmul(v[8 * i + 3], a.w), c.w));
#pragma unroll
                        for (int k = 0; k < 4; k++) v[8 * i + k] = v[8 * i + 4 + k];
                    }
                    __syncwarp();
                    mbar_arrive_if(sb + BAR_DONE, lane == 0 && q == 3);
                }
            }
            if (ODD || !first) {
                if (q == 0) img_store_global<0>(prev_img, toff, prev, s0, s1);
                if (q == 1) img_store_global<1>(prev_img, toff, prev, s0, s1);
                if (q == 2) img_store_global<2>(prev_img, toff, prev, s0, s1);
                if (q == 3) img_store_global<3>(prev_img, toff, prev, s0, s1);
            }
        }
        wg_wait<0>();
        release_if(eb, as, rel && !(ODD && (q & 1) && t == 5));
        if (ODD) release_if(eb, ws, rel && t != 1);
    }
    reg_fence(acc);
    return false;
}

__device__ __forceinline__ void qk_issue(float (&s)[64], uint32_t q, uint32_t k) {
    wg_fence();
    wgmma_ss128_init<0>(s, q, k, HI_Q, HI_IMG);
#pragma unroll
    for (int i = 1; i < 8; i++) wgmma_ss128<0>(s, q + (i >> 2) * 1024 + (i & 2) * 16 + (i & 1) * 2, k + (i >> 1) * 32 + (i & 1) * 2, 1, HI_Q, HI_IMG);
    wg_commit();
}
__device__ __forceinline__ void qk_issue(float (&s)[32], uint32_t q, uint32_t k) {
    wg_fence();
    wgmma_ss64_init<0>(s, q, k, HI_Q, HI_IMG);
#pragma unroll
    for (int i = 1; i < 8; i++) wgmma_ss64<0>(s, q + (i >> 2) * 1024 + (i & 2) * 16 + (i & 1) * 2, k + (i >> 1) * 32 + (i & 1) * 2, 1, HI_Q, HI_IMG);
    wg_commit();
}
__device__ __forceinline__ void pv_issue(float (&o)[64], const uint32_t (&p)[32], uint32_t v, int acc, bool half) {
    if (half) {
        asm volatile("// half" ::: "memory");
        wg_fence();
#pragma unroll
        for (int i = 0; i < 4; i++) wgmma_rs128(o, p[4 * i], p[4 * i + 1], p[4 * i + 2], p[4 * i + 3], v + i * 256, i ? 1 : acc, HI_IMG);
        wg_commit();
        asm volatile("// half" ::: "memory");
    } else {
        wg_fence();
#pragma unroll
        for (int i = 0; i < 8; i++) wgmma_rs128(o, p[4 * i], p[4 * i + 1], p[4 * i + 2], p[4 * i + 3], v + i * 256, i ? 1 : acc, HI_IMG);
        wg_commit();
    }
}
__device__ __forceinline__ void tri_mask(float (&s)[64], float x) {
#pragma unroll
    for (int k = 0; k < 16; k++) {
        float b;
        asm("sub.sat.f32 %0, %1, %2;" : "=f"(b) : "f"((float)(8 * (k >> 1) + (k & 1))), "f"(x));
        const int i = 32 + 4 * (k >> 1) + (k & 1);
        asm("fma.rn.f32 %0, %1, 0fFF61B1E6, %0;" : "+f"(s[i]) : "f"(b));
        if (k < 14) asm("fma.rn.f32 %0, %1, 0fFF61B1E6, %0;" : "+f"(s[i + 6]) : "f"(b));
    }
}
__device__ __forceinline__ void tri_mask_copy(float (&s)[64], const float (&h)[32], float x) {
#pragma unroll
    for (int i = 0; i < 32; i++) {
        asm("{\n.reg .pred p;\nsetp.lt.f32 p, %2, %3;\nselp.f32 %0, 0fFF800000, %1, p;\n}"
            : "=f"(s[i]) : "f"(h[i]), "f"(x), "f"((float)(8 * (i >> 2) - 4 * (i & 2) + (i & 1))));
        s[32 + i] = __uint_as_float(0xff800000u);
    }
}
constexpr float SM_HI = 1152921504606846976.f, SM_LO = 1.f / 1152921504606846976.f;
__device__ __forceinline__ bool softmax_unsafe(float t0, float t1, bool first) {
    bool bad = __any_sync(0xffffffffu, fmaxf(t0, t1) > SM_HI);
    if (first) {
        uint32_t a = __ballot_sync(0xffffffffu, t0 >= SM_LO), b = __ballot_sync(0xffffffffu, t1 >= SM_LO);
        a |= a >> 1;
        b |= b >> 1;
        bad |= ((a | (a >> 2)) & (b | (b >> 2)) & 0x11111111u) != 0x11111111u;
    }
    return bad;
}
__device__ __forceinline__ void softmax_shift(float (&s)[64], float d0, float d1) {
#pragma unroll
    for (int i = 0; i < 64; i++) s[i] -= (i & 2) ? d1 : d0;
}
__device__ __forceinline__ void softmax_remax(float (&s)[64], float (&m)[2], bool first, float& a0, float& a1) {
    float m0 = fmaxf(s[0], s[1]), m1 = fmaxf(s[2], s[3]);
#pragma unroll
    for (int k = 1; k < 16; k++) {
        m0 = fmaxf(m0, fmaxf(s[4 * k], s[4 * k + 1]));
        m1 = fmaxf(m1, fmaxf(s[4 * k + 2], s[4 * k + 3]));
    }
    m0 = fmaxf(m0, __shfl_xor_sync(0xffffffffu, m0, 1));
    m1 = fmaxf(m1, __shfl_xor_sync(0xffffffffu, m1, 1));
    m0 = fmaxf(m0, __shfl_xor_sync(0xffffffffu, m0, 2));
    m1 = fmaxf(m1, __shfl_xor_sync(0xffffffffu, m1, 2));
    if (!first) {
        m0 = fmaxf(m0, 0.f);
        m1 = fmaxf(m1, 0.f);
    }
    a0 = first ? 1.f : ex2(-m0);
    a1 = first ? 1.f : ex2(-m1);
    m[0] += m0;
    m[1] += m1;
    softmax_shift(s, m0, m1);
}
template <int J0, int J1>
__device__ __forceinline__ void softmax_exp(const float (&s)[64], uint32_t (&p)[32], float (&t)[4]) {
#pragma unroll
    for (int k = J0; k < J1; k++) {
        const float e0 = ex2(s[4 * k]), e1 = ex2(s[4 * k + 1]), e2 = ex2(s[4 * k + 2]), e3 = ex2(s[4 * k + 3]);
        if (k == 0) { t[0] = e0; t[1] = e1; t[2] = e2; t[3] = e3; }
        else { t[0] += e0; t[1] += e1; t[2] += e2; t[3] += e3; }
        p[2 * k] = pack2(e0, e1);
        p[2 * k + 1] = pack2(e2, e3);
    }
}
__device__ __forceinline__ void fma8(float (&acc)[8], float a, uint4 w) {
    acc[0] = fmaf(a, bf_lo(w.x), acc[0]); acc[1] = fmaf(a, bf_hi(w.x), acc[1]);
    acc[2] = fmaf(a, bf_lo(w.y), acc[2]); acc[3] = fmaf(a, bf_hi(w.y), acc[3]);
    acc[4] = fmaf(a, bf_lo(w.z), acc[4]); acc[5] = fmaf(a, bf_hi(w.z), acc[5]);
    acc[6] = fmaf(a, bf_lo(w.w), acc[6]); acc[7] = fmaf(a, bf_hi(w.w), acc[7]);
}
__device__ __forceinline__ void mma16816(float (&d)[4], const uint32_t* a, uint32_t b0, uint32_t b1) {
    asm("mma.sync.aligned.m16n8k16.row.col.f32.bf16.bf16.f32 {%0, %1, %2, %3}, {%4, %5, %6, %7}, {%8, %9}, {%0, %1, %2, %3};"
        : "+f"(d[0]), "+f"(d[1]), "+f"(d[2]), "+f"(d[3]) : "r"(a[0]), "r"(a[1]), "r"(a[2]), "r"(a[3]), "r"(b0), "r"(b1));
}
__device__ __forceinline__ uint32_t best_key(const uint32_t* keys, int lane, uint32_t ep) {
    uint32_t best;
#pragma unroll 1
    for (;;) {
        const uint4 k = ld_poll(reinterpret_cast<const uint4*>(keys) + lane);
        best = max(max(k.x, k.y), max(k.z, k.w));
        if (__all_sync(0xffffffffu, (((k.x ^ ep) | (k.y ^ ep) | (k.z ^ ep) | (k.w ^ ep)) & 31) == 0)) break;
        if (KSLEEP) __nanosleep(KSLEEP);
    }
    return __reduce_max_sync(0xffffffffu, best);
}

__global__ void __cluster_dims__(2, 1, 1) __launch_bounds__(384, 1)
fused_kernel(const __grid_constant__ CUtensorMap tm_ckv, const __grid_constant__ CUtensorMap tm_wq,
             const __grid_constant__ CUtensorMap tm_wuk, const __grid_constant__ CUtensorMap tm_wuv,
             const __grid_constant__ CUtensorMap tm_wo, const __grid_constant__ CUtensorMap tm_wg,
             const __grid_constant__ CUtensorMap tm_wu,
             const __grid_constant__ CUtensorMap tm_wm, const __grid_constant__ CUtensorMap tm_x, const Params P) {
    extern __shared__ __align__(1024) uint8_t smem[];
    const uint32_t sb = (uint32_t)__cvta_generic_to_shared(smem);
    const int tid = threadIdx.x, lane = tid & 31, warp = __shfl_sync(0xffffffffu, tid >> 5, 0), wg = warp >> 2;
    const uint32_t sm = blockIdx.x < 8 ? blockIdx.x + 124 : blockIdx.x - 8, smq = ((sm - 64) * 147) >> 11;
    const int rb = sm < 64 ? (sm & 14) * 8 + (sm >> 4) * 2 + (sm & 1)
                 : sm < 120 ? ((sm - 64 - smq * 14) & 14) * 8 + 24 + smq * 2 + (sm & 1) : sm < 124 ? sm + 8 : sm - 116;
    const int grp = rb >> 3, j = rb & 7, cq = j & 3, kh = grp & 1, ort = (grp & 14) + (j >> 2);
    if (warp == 0) TS(0);

    if (lane == 0) {
        if (warp == 8) {
            asm volatile("prefetch.tensormap [%0];" ::"l"(rb >= NCTA ? &tm_wm : (j & 1) ? &tm_wuv : &tm_wuk) : "memory");
            asm volatile("prefetch.tensormap [%0];" ::"l"(&tm_ckv) : "memory");
            *reinterpret_cast<uint2*>(smem + SM_EP + 16) = make_uint2(0, 0);
        }
        const u64 cnt = (warp < 5 ? (rb < NCTA ? 0x844444441111111ull : 0x888888881111111ull) : warp < 10 ? 0x111111188888888ull : 0x118121ull) >> (12 * (warp % 5));
#pragma unroll
        for (int i = 0; i < 3; i++) mbar_init(sb + SM_BAR + 24 * warp + 8 * i, ((uint32_t)cnt >> (4 * i)) & 15);
        fence_async_smem();
        asm volatile("fence.mbarrier_init.release.cluster;" ::: "memory");
    }
    __syncthreads();
    asm volatile("barrier.cluster.arrive.relaxed.aligned;\nbarrier.cluster.wait.aligned;" ::: "memory");

    if (rb >= NCTA) {
        float* sc = reinterpret_cast<float*>(smem + 6 * SLOT);
        float* red = sc + 512;
        uint32_t ph = 0x7f, sl = 0;
        if (warp == 8) {
#pragma unroll 1
            for (int i = 0; i < 24; i++) {
                slot_acquire(sb, ph, sl);
                tma2d(sb + sl * SLOT, &tm_wm, (i >> 3) * 1024 + (rb - NCTA) * 256, (i & 7) * 64, sb + BAR_FULL + 8 * sl);
                if (++sl == 6) sl = 0;
            }
#pragma unroll 1
            for (int i = 0; i <= NFFN / NSPARE; i++) {
                const int b = (rb - NCTA) * (NFFN / NSPARE) + i;
                if (i < NFFN / NSPARE) {
                    asm volatile("cp.async.bulk.wait_group.read 0;" ::: "memory");
                    uint32_t done = 0x7f;
                    slot_acquire(sb, done, i & 1);
#pragma unroll 1
                    for (int k = 0; k < 4; k++) tma2d(sb + (i & 1) * SLOT + k * 8192, k < 2 ? &tm_wg : &tm_wu, b * 16, (k & 1) * 256, sb + BAR_FULL + 8 * (i & 1));
                }
                if (i) {
                    mbar_wait(sb + BAR_FULL + 8 * (~i & 1), ((i - 1) >> 1) & 1);
                    bulk_store(g_wf + (b - 1) * SLOT, sb + (~i & 1) * SLOT, SLOT);
                    asm volatile("cp.async.bulk.commit_group;" ::: "memory");
                }
            }
            asm volatile("cp.async.bulk.wait_group 0;" ::: "memory");
            fence_async_global();
            TS(4);
        } else if (warp < 8) {
            const uint32_t c2 = __ldg(reinterpret_cast<const uint32_t*>(P.c) + tid), ep = __ldcg(&g_sync.epoch[0]) + 1;
            sc[2 * tid] = rbf(bf_lo(c2) * sigmoid(bf_lo(c2)));
            sc[2 * tid + 1] = rbf(bf_hi(c2) * sigmoid(bf_hi(c2)));
            ph = 0;
#pragma unroll 1
            for (int ps = 0; ps < 3; ps++) {
                bar_sync(1, 256);
                float acc[8] = {0.f, 0.f, 0.f, 0.f, 0.f, 0.f, 0.f, 0.f};
#pragma unroll 1
                for (int bt = 0; bt < 8; bt++) {
                    slot_wait(sb + BAR_FULL, ph, sl);
#pragma unroll 4
                    for (int i = 0; i < 8; i++)
                        fma8(acc, sc[bt * 64 + warp * 8 + i], *reinterpret_cast<const uint4*>(smem + sl * SLOT + (warp * 8 + i) * 512 + lane * 16));
                    __syncwarp();
                    mbar_arrive_if(sb + BAR_EMPTY + 8 * sl, lane == 0);
                    if (++sl == 6) sl = 0;
                }
                *reinterpret_cast<float4*>(red + warp * 256 + lane * 8) = make_float4(acc[0], acc[1], acc[2], acc[3]);
                *reinterpret_cast<float4*>(red + warp * 256 + lane * 8 + 4) = make_float4(acc[4], acc[5], acc[6], acc[7]);
                bar_sync(1, 256);
                float v = 0.f;
#pragma unroll
                for (int i = 0; i < 8; i++) v += red[i * 256 + tid];
                if (ps == 0) st_pub(g_mod1 + (rb - NCTA) * 256 + tid, (pack2(0.f, v) & 0xffff0000u) | (ep & 0xffffu), true);
                else g_mod[ps * 1024 + (rb - NCTA) * 256 + tid] = __float2bfloat16_rn(v);
                if (warp == 0) TS(1 + ps);
            }
        }
        __syncthreads();
        if (tid < 2) flag_add(&g_sync.cnt[7 * 8]);
        return;
    }

    if (wg == 2) {
        asm volatile("setmaxnreg.dec.sync.aligned.u32 40;");
        const CUtensorMap* tw = (j & 1) ? &tm_wuv : &tm_wuk;
        if (warp == 8) {
            const uint32_t rank = j & 1, half = rank * 16384;
            uint32_t eph = 0x7f, r = 0;
#pragma unroll 1
            for (int hp = 0; hp < 2; hp++) {
                uint32_t wtab = w_table(hp), atab = a_table(hp);
                const int hc = 4 * grp + 2 * hp;
#pragma unroll 1
                for (int u = 0; u < 16; u++) {
                    if (u < 4) {
                        const uint32_t ws = (wtab >> (4 * u)) & 15;
                        slot_acquire(sb, eph, ws);
                        load_tile(sb, ws, 0, tw, u * 128, hc, false, HINT & 1);
                        PT();
                    }
                    if (hp == 1 && (u & 7) == 4) mbar_wait(sb + BAR_FLAG + 24 + (u & 8), 0);
                    const uint32_t as = a_next(atab);
                    slot_acquire(sb, eph, as);
                    load_tile(sb, as, half, &tm_ckv, ((u & 12) + (j >> 1)) * 128, (u & 3) * 2 + rank, true, (HINT & 8) && hp);
                    PT();
                    if (hp == 1 && (u | 2) == 3 && lane == 0)
                        asm volatile("red.relaxed.gpu.global.add.u32 [%0], 1;" ::"l"(&g_sync.cnt[(grp * 8 + 3 + (u >> 1)) * 8]) : "memory");
                }
                const uint8_t* src = g_h + (15 - j) * 4 * SLOT;
#pragma unroll 1
                for (int u = 0; u < 8; u++) {
                    if ((u & 3) == 0) {
                        mbar_wait(sb + BAR_FLAG + (2 + 8 * hp) * u, 0);
                        fence_async_global();
                    }
                    if (u < 4) {
                        const uint32_t ws = (wtab >> (4 * u)) & 15;
                        slot_acquire(sb, eph, ws);
                        load_tile(sb, ws, half, &tm_wq, u * 128, hc + rank, true, HINT & 1);
                        PT();
                    }
                    const uint32_t as = a_next(atab);
                    slot_acquire(sb, eph, as);
                    load_bulk(sb, as, 0, src, SLOT, false, (HINT & 8) && hp);
                    PT();
                    src += u == 3 ? (8 * j - 63) * SLOT : SLOT;
                }
                const int step = hp ? -2 * SLOT : 2 * SLOT;
                src = g_KV + (size_t)(grp * 32 + 30 * hp) * SLOT + half - step;
#pragma unroll 1
                for (int n = 0; n <= 17; n++) {
                    if (n == 8) {
                        mbar_wait(sb + BAR_FLAG + 16 + 32 * hp, 0);
                        fence_async_global();
                    }
                    const uint8_t* v = src + SLOT;
                    src += n < 16 - j ? step : n == 16 - j ? (2 * j - 15) * step : -step;
                    if (n < 17) {
                        slot_acquire(sb, eph, r);
                        if (n != 15 - (j & 6)) load_bulk(sb, r, half, src, SLOT / 2, true, (HINT & 4) && (hp || !(HINT & 32)));
                        else load_bulk(sb, r, 0, src - half, SLOT, false, (HINT & 4) && (hp || !(HINT & 32)));
                        PT();
                        r = ring_next(r);
                    }
                    if (n) {
                        slot_acquire(sb, eph, r);
                        if (n != 16 - (j & 6)) load_bulk(sb, r, half, v, SLOT / 2, true, (HINT & 4) && (hp || !(HINT & 32)));
                        else load_bulk(sb, r, 0, v - half, SLOT, false, (HINT & 4) && (hp || !(HINT & 32)));
                        PT();
                        r = ring_next(r);
                    }
                    asm volatile("st.volatile.shared.u32 [%0], %1;" ::"r"(sb + SM_EP + 16), "r"(18 * hp + n + 1) : "memory");
                }
            }
            uint32_t otab = O_TABLE, ready = 0;
#pragma unroll 1
            for (int i = 0; i < 17; i++) {
                const bool dyn = i >= 8 && i < 15;
                const uint32_t want = dyn ? 15u << (4 * (i - 8)) : 1u << max(i + 14, 28);
                if (!(ready & want)) {
                    do {
                        asm volatile("ld.acquire.cta.shared.u32 %0, [%1];" : "=r"(ready) : "r"(sb + SM_EP + 20) : "memory");
                        ready = __shfl_sync(0xffffffffu, ready, 0);
                    } while (!(ready & want));
                    fence_async_global();
                }
                const int head = o_head(dyn ? (ready >> (4 * (i - 8))) & 15 : i, kh);
                const uint32_t as = o_next(otab), ws = o_next(otab), off = i < 15 ? half : kh * 16384;
                slot_acquire(sb, eph, as);
                load_bulk(sb, as, off, g_ctx + (size_t)(ort * 32 + head) * SLOT + off, SLOT / 2, i < 15, HINT & 16);
                if (i == 15) load_tile(sb, as, off ^ 16384, &tm_x, ort * 128 + kh * 64, cq * 2, false, false);
                if (i == 16) load_bulk(sb, as, off ^ 16384, P.wdown + min(rb, NFFN - 1) * 8192, SLOT / 2, false, false);
                PT();
                slot_acquire(sb, eph, ws);
                load_tile(sb, ws, 0, &tm_wo, head * 128, cq * 2, false, HINT & 2);
                PT();
                if (i == 0) o_next(otab);
            }
            if (rb < NFFN) {
                slot_acquire(sb, eph, 5);
                load_bulk(sb, 5, 0, g_wf + rb * SLOT, SLOT, false, false);
            }
        } else if (warp == 9) {
            l2_prefetch(P.ckv + rb * 2048, 4096);
            mbar_watch(sb + BAR_FULL, 0);
            l2_prefetch(P.ckv + 512 * 512 + rb * 2048, 4096);
            mbar_watch(sb + BAR_FULL + 8 * 4, 0);
            l2_prefetch(P.ckv + 1024 * 512 + rb * 4096, 8192);
            TS(40);
#pragma unroll 1
            for (int i = 0; i < 15; i++) {
                step_watch(sb + SM_EP + 16, i == 0 ? 0 : i < 5 ? PFA + i : 13 + PFB + i);
                if (i == 12) mbar_watch(sb + BAR_FLAG + 8 * 7, 0);
                const int rf = min(rb, NFFN - 1);
                const uint8_t* p = i == 3 ? reinterpret_cast<const uint8_t*>(P.ckv) + rb * 16384
                                 : i == 4 ? g_h + rb * 16384
                                 : i < 9 ? g_ctx + (size_t)(ort * 32 + o_head(cq + 2 * ((i - 5) & 2), kh)) * SLOT + (i & 1) * 16384
                                 : i < 11 ? reinterpret_cast<const uint8_t*>(P.wo) + (grp * 16 + (~i & 1) * 8 + j) * 16384
                                 : i == 11 ? reinterpret_cast<const uint8_t*>(P.x) + rb * 16384
                                 : i == 12 ? reinterpret_cast<const uint8_t*>(P.wdown) + rf * 16384 : g_wf + rf * SLOT + (i & 1) * 16384;
                if (i < 3) tma3d_prefetch(i == 1 ? tw : &tm_wq, (j >> 1) * 128, grp * 4 + (i == 1 ? 2 : i + (j & 1)));
                else l2_prefetch(p, 16384);
            }
            const uint32_t v = lds32(sb + SM_EP) - 1;
            sts128(sb + SM_RED + lane * 16, make_uint4(v, v, v, v));
            fence_async_smem();
            __syncwarp();
#pragma unroll 1
            for (int i = 0; i < OB / 32; i++) bulk_store(g_out + rb * OB + i * 32, sb + SM_RED, 512);
            asm volatile("cp.async.bulk.commit_group;\ncp.async.bulk.wait_group 0;" ::: "memory");
            fence_async_global();
            __syncwarp();
            mbar_arrive_if(sb + BAR_PF, lane == 0);
            if (lane == 0) mbar_watch(sb + BAR_END, 0);
        } else {
            const uint32_t ep = __ldcg(&g_sync.epoch[0]) + 1;
            asm volatile("st.shared.u32 [%0], %1;" ::"r"(sb + SM_EP), "r"(ep) : "memory");
            mbar_wait(sb + BAR_FULL + 8 * 4, 0);
            {
                uint4 v[4];
                for (;;) {
                    uint32_t bad = 0;
#pragma unroll
                    for (int k = 0; k < 4; k++) v[k] = ld_poll(reinterpret_cast<const uint4*>(g_mod1) + (warp & 1) * 128 + k * 32 + lane);
#pragma unroll
                    for (int k = 0; k < 4; k++) bad |= (v[k].x ^ ep) | (v[k].y ^ ep) | (v[k].z ^ ep) | (v[k].w ^ ep);
                    if (__all_sync(0xffffffffu, (bad & 0xffff) == 0)) break;
                    __nanosleep(100);
                }
                const uint32_t one = (warp & 1) ? ONE2 : 0x80008000u;
#pragma unroll
                for (int k = 0; k < 4; k++)
                    *reinterpret_cast<uint2*>(smem + SM_TAB + (warp & 1) * 1024 + k * 256 + lane * 8) =
                        make_uint2(badd(__byte_perm(v[k].x, v[k].y, 0x7632), one), badd(__byte_perm(v[k].z, v[k].w, 0x7632), one));
            }
            __syncwarp();
            mbar_arrive_if(sb + BAR_FLAG + 8 * 8, lane == 0);
            if (warp == 10) {
#pragma unroll 1
                for (int i = 0; i < 9; i++) {
                    mbar_sleep(sb + BAR_DONE + 8 * i);
                    if (lane == 0) flag_add(i && ((i - 1) & 2) ? &g_sync.ctxcnt[((i & 1) ? 15 - j : j) * 32 + 2 * grp + (i > 4)] : &g_sync.cnt[(grp * 8 + i) * 8]);
                    if (i == 0) TS(43);
                }
            } else {
                TS(42);
#pragma unroll 1
                for (int i = 0; i < 8; i++) {
                    mbar_sleep(sb + BAR_DONE + 8 * (i == 7 ? 6 : i == 4 ? 3 : i));
                    if (lane < 2) flag_wait(&g_sync.cnt[((i == 0 ? (lane ? j : 15 - j) : i == 7 ? 0 : grp) * 8 + i) * 8], 8 * ep);
                    __syncwarp();
                    mbar_arrive_if(sb + BAR_FLAG + 8 * i, lane == 0 && i < 7);
                    TS(48 + i);
                }
                const uint32_t *mp = reinterpret_cast<const uint32_t*>(g_mod) + lane, *wp = reinterpret_cast<const uint32_t*>(P.wr) + lane;
                float ra = 0.f, rs = 0.f;
#pragma unroll 1
                for (int k = 0; k < 256; k += 32) {
                    const uint32_t ga = __ldcg(mp + 512 + k), sh = __ldcg(mp + 768 + k), c1 = badd(__ldcg(mp + 1024 + k), ONE2);
                    const uint32_t gb = __ldcg(mp + 1280 + k), ww = __ldg(wp + k);
                    const float a0 = bf_lo(c1) * bf_lo(ww), a1 = bf_hi(c1) * bf_hi(ww);
                    ra += a0 + a1;
                    rs = fmaf(bf_lo(sh), bf_lo(ww), fmaf(bf_hi(sh), bf_hi(ww), rs));
                    if (k >> 6 == cq) {
                        sts128(sb + SM_TAB + ((k & 32) + lane) * 16, make_uint4(ga << 16, ga & 0xffff0000u, __float_as_uint(a0), __float_as_uint(a1)));
                        sts128(sb + SM_TAB + 1024 + ((k & 32) + lane) * 16, make_uint4(c1, sh, gb, 0));
                    }
                }
#pragma unroll 1
                for (int o = 16; o > 0; o >>= 1) {
                    ra += __shfl_xor_sync(0xffffffffu, ra, o);
                    rs += __shfl_xor_sync(0xffffffffu, rs, o);
                }
                *reinterpret_cast<float2*>(smem + SM_EP + 8) = make_float2(ra, rs);
                __syncwarp();
                mbar_arrive_if(sb + BAR_FLAG + 8 * 7, lane == 0);
                const uint32_t* f = &g_sync.ctxcnt[ort * 32 + o_head(min(lane, 16), kh)];
                uint32_t ready = -(j & 1), list = 0, sh = 0, qa;
                asm("mapa.shared::cluster.u32 %0, %1, %2;" : "=r"(qa) : "r"(sb + SM_EP + 20), "r"(lane & 1));
                while (ready != ~0u) {
                    uint32_t v;
                    asm volatile("ld.acquire.gpu.global.u32 %0, [%1];" : "=r"(v) : "l"(f) : "memory");
                    const uint32_t now = __ballot_sync(0xffffffffu, (int)(v - ep) >= 0);
#pragma unroll 1
                    for (uint32_t fresh = now & ~ready & 0x7f00; fresh; fresh &= fresh - 1, sh += 4) list |= (__ffs(fresh) - 1) << sh;
                    list |= (((now & 0xff) + 1) >> 8 << 28) | ((now & 0x18000) << 14);
                    if (now != ready && lane < 2) asm volatile("st.relaxed.cluster.shared::cluster.u32 [%0], %1;" ::"r"(qa), "r"(list) : "memory");
                    if ((now & 0xff) == 0xff) mbar_sleep(sb + BAR_DONE + 8 * 7);
                    ready = now;
                    __nanosleep(POLL_NS);
                }
                TS(45);
            }
        }
    } else {
        asm volatile("setmaxnreg.inc.sync.aligned.u32 232;");
        const bool elected = (tid & 127) == 0, rel = (tid & 95) == 0;
        uint32_t eb;
        asm("mapa.shared::cluster.u32 %0, %1, %2;" : "=r"(eb) : "r"(sb + BAR_EMPTY), "r"(warp & 1));
        const int g = lane >> 2, c4 = lane & 3;
        const uint32_t toff = warp * 4096 + g * 64 + ((c4 ^ (g >> 1)) << 4);
        uint32_t fph = 0, r = 0;
        if (wg == 1) bar_arrive(1, 256);
        const uint32_t kd = desc_k(sb), wd = desc_mn(sb), vd = ((sb & 0x3ffff) >> 4) | (32u << 16);
        const int nL = 16 - j, hn = nL - 1 + wg;
        float s[64], o[64], li[2] = {0.f, 0.f};
        uint8_t* cimg = g_ctx;
        uint32_t p[32] = {};
#pragma unroll 1
        for (int hp = 0; hp < 2; hp++) {
            float m[2] = {0.f, 0.f}, l[2] = {0.f, 0.f}, t[4] = {0.f, 0.f, 0.f, 0.f};
            bool shifted = false, bad = false, plain = false;
            uint32_t qa = desc_k(sb + 5 * SLOT + (wg ^ 1) * 8192);
            uint8_t* limg = g_ctx + (size_t)((15 - j) * 32 + 2 * grp + hp) * SLOT;
            {
                const int step = hp ? -8 * SLOT : 8 * SLOT;
                uint8_t* img = g_KV + (size_t)(grp * 32 + (hp ? j ^ 30 : j)) * SLOT - step;
                const float sc = (j & 1) ? 1.f : SM_C;
                const uint32_t wtab = w_table(hp);
                uint32_t atab = hp ? 0x562u : a_table(0);
#pragma unroll 1
                for (int u = 0;; u += 2) {
                    proj_tile<false>(s, o, u, u ? 0 : hp, sb, wg, eb, rel, fph, wtab, atab, u ? img : cimg, toff, u ? sc : li[0], u ? sc : li[1], (hp | u) == 0, P.x, rb * 16 + warp * 2, p);
                    __syncwarp();
                    mbar_arrive_if(sb + BAR_DONE + 4 * u + 32 * hp, lane == 0 && (hp | u) != 0);
                    if (elected) TS(1 + 10 * hp + u + 20 * wg);
                    if (proj_tile<true>(o, s, u + 1, 0, sb, wg, eb, rel, fph, wtab, atab, img + step, toff, sc, sc, (hp | u) == 0, P.x, rb * 16 + warp * 2, p)) break;
                    if (elected) TS(2 + 10 * hp + u + 20 * wg);
                    img += 2 * step;
                }
            }
            if (elected) TS(6 + 10 * hp + 20 * wg);
            int n = -1;
#pragma unroll 1
            for (;;) {
                while (bad || plain) {
                    if (bad) {
                        float a0, a1;
                        softmax_remax(s, m, n == 0 || n == nL, a0, a1);
                        shifted = true;
                        l[0] *= a0;
                        l[1] *= a1;
#pragma unroll
                        for (int i = 0; i < 64; i++) o[i] *= (i & 2) ? a1 : a0;
                    }
                    softmax_exp<0, 16>(s, p, t);
                    t[0] += t[1];
                    t[2] += t[3];
                    bad = !bad && softmax_unsafe(t[0], t[2], false);
                    plain = false;
                }
#pragma unroll 1
                do {
                    l[0] += t[0];
                    l[1] += t[2];
                    if (++n > 16) break;
                    const uint32_t ks = r;
                    uint32_t vs = ring_next(r);
                    r = ring_next(vs);
                    bar_sync(1 + wg, 256);
                    const float x = (float)((warp & 3) * 16 + g - 2 * c4);
                    if (n == hn) {
                        float sh[32];
                        qk_issue(sh, qa, kd + ks * (SLOT / 16));
                        slot_wait(sb + BAR_FULL, fph, vs);
                        pv_issue(o, p, vd + vs * (SLOT / 16), 1, false);
                        bar_arrive(2 - wg, 256);
                        wg_wait<1>();
                        reg_fence(sh);
                        tri_mask_copy(s, sh, x);
                        release_if(eb, ks, rel);
                        release_if(eb, 5 + wg, rel && (!wg || n == 16));
                        if (!wg) {
                            qa += SLOT / 16;
                            fence_async_smem();
                            if (shifted) softmax_shift(s, m[0], m[1]);
                        }
                        float e[4 * EARLY];
#pragma unroll
                        for (int i = 0; i < 4 * EARLY; i++) {
                            e[i] = ex2(s[i]);
                            t[i & 3] = i < 4 ? e[i] : t[i & 3] + e[i];
                        }
                        reg_fence(e);
                        slot_wait(sb + BAR_FULL, fph, r);
                        wg_wait<0>();
                        reg_fence(o);
                        reg_fence(e);
                        release_if(eb, vs, rel);
#pragma unroll
                        for (int i = 0; i < 2 * EARLY; i++) p[i] = pack2(e[2 * i], e[2 * i + 1]);
                        softmax_exp<EARLY, 8>(s, p, t);
                        if (wg) {
                            ctx_store<true>(limg, toff, o, l[0], l[1]);
                            __syncwarp();
                            mbar_arrive_if(sb + BAR_DONE + 24 + 32 * hp, lane == 0);
                            l[0] = l[1] = m[0] = m[1] = 0.f;
                            shifted = false;
                        }
                        t[0] += t[1];
                        t[2] += t[3];
                        bad = softmax_unsafe(t[0], t[2], wg);
                        continue;
                    }
                    if (n == 0 || n == nL) {
                        qk_issue(s, qa, kd + ks * (SLOT / 16));
                        if (n == 0) {
                            r = vs;
                            vs = 4 - hp;
                            slot_wait(sb + BAR_FULL, fph, 6);
                            gemm_issue<false>(o, qa + SLOT / 16, wd + vs * (SLOT / 16), 1, false);
                        } else {
                            slot_wait(sb + BAR_FULL, fph, vs);
                            pv_issue(o, p, vd + vs * (SLOT / 16), 1, true);
                        }
                        bar_arrive(2 - wg, 256);
                        const float i0 = n ? rcp(quad_sum(l[0])) : 1.f, i1 = n ? rcp(quad_sum(l[1])) : 1.f;
                        wg_wait<1>();
                        reg_fence(s);
                        release_if(eb, ks, rel);
                        release_if(eb, 6, rel && n == 16);
                        tri_mask(s, n ? x : 64.f);
                        float e[4 * EARLY];
#pragma unroll
                        for (int i = 0; i < 4 * EARLY; i++) {
                            e[i] = ex2(s[i]);
                            t[i & 3] = i < 4 ? e[i] : t[i & 3] + e[i];
                        }
                        reg_fence(e);
                        reg_fence(s);
                        reg_fence(t);
                        slot_wait(sb + BAR_FULL, fph, r);
                        if (SF & 1) sched_fence(fph, P.zero);
                        wg_wait<0>();
                        reg_fence(o);
                        reg_fence(e);
                        release_if(eb, vs, rel);
#pragma unroll
                        for (int i = 0; i < 2 * EARLY; i++) p[i] = pack2(e[2 * i], e[2 * i + 1]);
                        softmax_exp<EARLY, MSPLIT>(s, p, t);
                        tile_store(limg, sb + 6 * SLOT, toff, o, i0, i1, n);
                        reg_fence(t);
                        if (SF & 2) sched_fence(fph, P.zero);
                        reg_fence(s);
                        softmax_exp<MSPLIT, 16>(s, p, t);
                        __syncwarp();
                        mbar_arrive_if(sb + BAR_DONE + 24 + 32 * hp, lane == 0 && n);
                        l[0] = l[1] = m[0] = m[1] = 0.f;
                        shifted = false;
                        t[0] += t[1];
                        t[2] += t[3];
                        bad = __any_sync(0xffffffffu, fmaxf(t[0], t[2]) > SM_HI || fminf(t[0], t[2]) < SM_LO);
                        continue;
                    }
                    qk_issue(s, qa, kd + ks * (SLOT / 16));
                    slot_wait(sb + BAR_FULL, fph, vs);
                    pv_issue(o, p, vd + vs * (SLOT / 16), n != 1 && n != nL + 1, n == hn + 1);
                    bar_arrive(2 - wg, 256);
                    wg_wait<1>();
                    reg_fence(s);
                    release_if(eb, ks, rel);
                    release_if(eb, 6, rel && n == 16);
                    if (n == nL - 1) {
                        tri_mask(s, x);
                        release_if(eb, 5, rel);
                        qa += SLOT / 16;
                        fence_async_smem();
                    }
                    if (shifted) {
                        slot_wait(sb + BAR_FULL, fph, r);
                        wg_wait<0>();
                        reg_fence(o);
                        release_if(eb, vs, rel);
                        softmax_shift(s, m[0], m[1]);
                        plain = true;
                        break;
                    }
                    float e[4 * EARLY];
#pragma unroll
                    for (int i = 0; i < 4 * EARLY; i++) {
                        e[i] = ex2(s[i]);
                        t[i & 3] = i < 4 ? e[i] : t[i & 3] + e[i];
                    }
                    reg_fence(e);
                    slot_wait(sb + BAR_FULL, fph, r);
                    wg_wait<0>();
                    reg_fence(o);
                    reg_fence(e);
                    release_if(eb, vs, rel);
#pragma unroll
                    for (int i = 0; i < 2 * EARLY; i++) p[i] = pack2(e[2 * i], e[2 * i + 1]);
                    softmax_exp<EARLY, 16>(s, p, t);
                    t[0] += t[1];
                    t[2] += t[3];
                    bad = softmax_unsafe(t[0], t[2], false);
                } while (!bad);
                if (!bad && !plain) break;
            }
            const uint32_t vs = r, ga = desc_k(sb + (hp ? 2 * (wg ^ kh ^ 1) : wg) * 8192);
            r = ring_next(r);
            slot_wait(sb + BAR_FULL, fph, 5);
            slot_wait(sb + BAR_FULL, fph, r);
            bar_sync(1 + wg, 256);
            gemm_issue<true>(s, ga + 5 * (SLOT / 16), wd + r * (SLOT / 16), 0, hp);
            pv_issue(o, p, vd + vs * (SLOT / 16), j, hn == 16);
            bar_arrive(2 - wg, 256);
            li[0] = rcp(quad_sum(l[0]));
            li[1] = rcp(quad_sum(l[1]));
            cimg = limg + (ptrdiff_t)(2 * j - 15) * 32 * SLOT + (wg ? -16384 : 16384);
            wg_wait<1>();
            release_if(eb, 5, rel);
            release_if(eb, r, rel && hp);
            wg_wait<0>();
            release_if(eb, vs, rel);
            reg_fence(o);
            img_store_global<0>(cimg, toff, o, li[0], li[1]);
            if (elected) TS(8 + 10 * hp + 20 * wg);
        }
        uint32_t otab = 0x2351604u;
        const uint32_t oa = desc_k(sb + (wg ^ kh ^ 1) * 16384);
        const int t7 = tid & 127, w4 = warp & 3, row = ort * 128 + kh * 64 + w4 * 16 + g;
#pragma unroll 1
        for (int i = 1; i < 15 - wg; i++) {
            const uint32_t as = o_next(otab), ws = o_next(otab);
            slot_wait(sb + BAR_FULL, fph, as);
            slot_wait(sb + BAR_FULL, fph, ws);
            bar_sync(1 + wg, 256);
            gemm_issue<false>(s, oa + as * (SLOT / 16), wd + ws * (SLOT / 16), 1, true);
            bar_arrive(2 - wg, 256);
            wg_wait<1>();
            reg_fence(o);
            if (i == 1) img_store_global<1>(cimg, toff, o, li[0], li[1]);
            if (i == 2) {
                img_store_global<2>(cimg, toff, o, li[0], li[1]);
                img_store_global<3>(cimg, toff, o, li[0], li[1]);
                __syncwarp();
                mbar_arrive_if(sb + BAR_DONE + 64, lane == 0);
            }
            wg_wait<0>();
            release_if(eb, as, rel);
            release_if(eb, ws, rel);
        }
        mbar_wait(sb + BAR_PF, 0);
        const uint32_t ep = lds32(sb + SM_EP);
        uint32_t eb2 = sb + BAR_END;
        if (wg == 0) {
            reg_fence(s);
            if (elected) TS(9);
            TT(1);
#pragma unroll
            for (int v = 0; v < 8; v++)
                st_pub(g_out + rb * OB + v * 128 + t7, make_uint4((pack2(s[8 * v], s[8 * v + 1]) & ~1u) | (ep & 1), pack2(s[8 * v + 2], s[8 * v + 3]),
                                                                      pack2(s[8 * v + 4], s[8 * v + 5]), pack2(s[8 * v + 6], s[8 * v + 7])), true);
            constexpr uint32_t s1 = 5, s2 = 6;
            bar_sync(4, 256);
            uint32_t wf[64];
            float wn[64];
            if (rb < NFFN) {
                slot_wait(sb + BAR_FULL, fph, s1);
                const uint32_t a = sb + s1 * SLOT + (w4 * 128 + (lane >> 4) * 8 + (lane & 7)) * 32 + ((lane >> 3) & 1) * 16;
#pragma unroll
                for (int i = 0; i < 16; i++)
                    asm volatile("ldmatrix.sync.aligned.m8n8.x4.trans.shared.b16 {%0, %1, %2, %3}, [%4];"
                                 : "=r"(wf[4 * i]), "=r"(wf[4 * i + 1]), "=r"(wf[4 * i + 2]), "=r"(wf[4 * i + 3])
                                 : "r"(a + (i >> 3) * 16384 + (i & 7) * 512) : "memory");
                slot_wait(sb + BAR_FULL, fph, s2);
#pragma unroll
                for (int i = 0; i < 16; i++) {
                    const uint2 w = *reinterpret_cast<const uint2*>(smem + s2 * SLOT + (kh ^ 1) * 16384 + i * 1024 + t7 * 8);
                    wn[4 * i] = bf_lo(w.x); wn[4 * i + 1] = bf_hi(w.x); wn[4 * i + 2] = bf_lo(w.y); wn[4 * i + 3] = bf_hi(w.y);
                }
                reg_fence(wn);
            }
            const uint32_t gbf = __ldcg(reinterpret_cast<const uint32_t*>(g_mod) + 1280 + rb * 2 + (tid & 1));
            if (elected) TS(10);
            TT(2);
            uint32_t best;
            if (KALL) best = best_key(g_key + cq * 128, lane, ep);
            if (warp == 0) {
                if (KGATE) bar_sync(5, 160);
                const uint32_t k = KALL ? best : best_key(g_key + cq * 128, lane, ep);
                if (lane == 0) asm volatile("st.shared.u32 [%0], %1;" ::"r"(sb + SM_EP + 4), "r"(k) : "memory");
                mbar_arrive_if(sb + BAR_BEST, lane == 0);
            }
            if (!KALL) {
                mbar_wait(sb + BAR_BEST, 0);
                best = lds32(sb + SM_EP + 4);
            }
            const int sel = (~best >> 5) & 2047;
            if (elected) TS(19);
            TT(3);
            const uint4* cp = g_cand + (sel >> 4) * 192;
            float* sred = reinterpret_cast<float*>(smem + SM_RED);
            const int pq = (2 * rb + (tid & 1)) & 63, pv = (pq >> 2) / 3;
            const uint4* fp = cp + (rb >> 5) * 24 + pv * 4 + (pq & 3);
            uint4 fh = {}, fx = {};
            if (rb < NFFN) {
                uint4 cv[6];
                for (;;) {
                    uint32_t bad = 0;
#pragma unroll
                    for (int v = 0; v < 6; v++) cv[v] = ld_poll(cp + w4 * 24 + v * 4 + c4);
#pragma unroll
                    for (int v = 0; v < 6; v++) bad |= cv[v].w ^ ep;
                    if (__all_sync(0xffffffffu, bad == 0)) break;
                    if (CSLEEP) __nanosleep(CSLEEP);
                }
                if (elected) TS(20);
            TT(4);
                float d[4][4] = {};
#pragma unroll
                for (int k = 0; k < 8; k++) {
                    const uint32_t b0 = (&cv[(2 * k) / 3].x)[(2 * k) % 3], b1 = (&cv[(2 * k + 1) / 3].x)[(2 * k + 1) % 3];
                    mma16816(d[k & 1], wf + 4 * k, b0, b1);
                    mma16816(d[2 + (k & 1)], wf + 32 + 4 * k, b0, b1);
                }
                const float u = (c4 & 2) ? ((c4 & 1) ? d[2][2] + d[3][2] : d[2][0] + d[3][0]) : ((c4 & 1) ? d[0][2] + d[1][2] : d[0][0] + d[1][0]);
                sred[w4 * 32 + c4 * 8 + g] = u;
                bar_sync(3, 128);
                const float v = rbf((sred[lane] + sred[32 + lane]) + (sred[64 + lane] + sred[96 + lane]));
                const float act = rbf(rbf(v * sigmoid(v)) * __shfl_down_sync(0xffffffffu, v, 16));
                float y[4] = {0.f, 0.f, 0.f, 0.f};
#pragma unroll
                for (int k = 0; k < 16; k++) {
                    const float a = __shfl_sync(0xffffffffu, act, k);
#pragma unroll
                    for (int i = 0; i < 4; i++) y[i] = fmaf(a, wn[4 * k + i], y[i]);
                }
                st_pub(g_out + rb * OB + OB_Y + t7, make_uint4((__float_as_uint(y[0]) & ~15u) | (ep & 15), __float_as_uint(y[1]), __float_as_uint(y[2]), __float_as_uint(y[3])), true);
            }
            if (OUTLATE == 2) bar_arrive(6, 256);
            if (rb == 0 && tid == 0) g_sync.epoch[0] = ep;
            if (elected) TS(60);
            TT(5);
            uint4 yv;
            if (warp == 0) { fh = ld_poll(fp); fx = ld_poll(fp + 96); }
            if (YPRE) __nanosleep(YPRE);
            for (;;) {
                yv = ld_poll(g_out + min(t7, NFFN - 1) * OB + OB_Y + rb);
                if (__all_sync(0xffffffffu, ((yv.x ^ ep) & 15) == 0)) break;
                if (YSLEEP) __nanosleep(YSLEEP);
            }
            if (elected) TS(61);
            TT(6);
            float y[4] = {0.f, 0.f, 0.f, 0.f};
            if (t7 < NFFN) { y[0] = __uint_as_float(yv.x); y[1] = __uint_as_float(yv.y); y[2] = __uint_as_float(yv.z); y[3] = __uint_as_float(yv.w); }
            const float z0 = ((lane & 16) ? y[2] : y[0]) + __shfl_xor_sync(0xffffffffu, (lane & 16) ? y[0] : y[2], 16);
            const float z1 = ((lane & 16) ? y[3] : y[1]) + __shfl_xor_sync(0xffffffffu, (lane & 16) ? y[1] : y[3], 16);
            float z = ((lane & 8) ? z1 : z0) + __shfl_xor_sync(0xffffffffu, (lane & 8) ? z0 : z1, 8);
            z += __shfl_xor_sync(0xffffffffu, z, 4);
            z = quad_sum(z);
            if ((lane & 7) == 0) sred[128 + (lane >> 3) * 4 + w4] = z;
            bar_sync(3, 128);
            if (tid < 2) {
                while (fh.w != ep || fx.w != ep) { fh = ld_poll(fp); fx = ld_poll(fp + 96); }
                const float4 y0 = *reinterpret_cast<const float4*>(sred + 128 + tid * 8), y1 = *reinterpret_cast<const float4*>(sred + 132 + tid * 8);
                const int cm = (pq >> 2) - 3 * pv;
                const uint32_t h2 = cm == 0 ? fh.x : cm == 1 ? fh.y : fh.z, x2 = cm == 0 ? fx.x : cm == 1 ? fx.y : fx.z;
                const float sg = sigmoid(bf_hi((best & 0x80000000u) ? (best ^ 0x80000000u) : ~best));
                reinterpret_cast<uint32_t*>(P.out)[sel * 256 + rb * 2 + tid] =
                    badd(x2, bmul(gbf, badd(h2, bmul(pack2((y0.x + y0.y) + (y0.z + y0.w), (y1.x + y1.y) + (y1.z + y1.w)), pack2(sg, sg)))));
            }
            if (elected) TS(62);
            TT(7);
        } else {
            const float4* tf = reinterpret_cast<const float4*>(smem + SM_TAB) + c4;
            const uint32_t xa = sb + 4 * SLOT + (kh ^ 1) * 16384 + (w4 * 16 + (lane & 15)) * 128;
            uint32_t x2[32];
            bar_sync(2, 256);
#pragma unroll 1
            for (int i = 14; i < 17; i++) {
                const uint32_t as = o_next(otab), ws = o_next(otab);
                slot_wait(sb + BAR_FULL, fph, as);
                slot_wait(sb + BAR_FULL, fph, ws);
                gemm_issue<false>(s, oa + as * (SLOT / 16), wd + ws * (SLOT / 16), 1, true);
                wg_wait<1>();
            }
            if (elected) TS(29);
            TT(1);
            {
#pragma unroll
                for (int k = 0; k < 8; k++)
                    asm volatile("ldmatrix.sync.aligned.m8n8.x4.shared.b16 {%0, %1, %2, %3}, [%4];"
                                 : "=r"(x2[4 * k]), "=r"(x2[4 * k + 1]), "=r"(x2[4 * k + 2]), "=r"(x2[4 * k + 3])
                                 : "r"(xa + (k >> 2) * 8192 + (((2 * (k & 3) + (lane >> 4)) ^ (lane & 7)) << 4)) : "memory");
            }
            wg_wait<0>();
            reg_fence(s);
            bar_arrive(4, 256);
            if (elected) TS(39);
            TT(2);
            const uint4* pr = g_out + (rb ^ 8) * OB + t7;
            uint4 pa[8];
#pragma unroll
            for (int v = 0; v < 8; v++) pa[v] = ld_poll(pr + v * 128);
            float4 tc[16];
#pragma unroll
            for (int k = 0; k < 16; k++) {
                tc[k] = tf[k * 4];
#pragma unroll
                for (int i = 4 * k; i < 4 * k + 4; i++) s[i] = fmaf((i & 1) ? tc[k].y : tc[k].x, s[i], (i & 1) ? bf_hi(x2[i >> 1]) : bf_lo(x2[i >> 1]));
            }
            reg_fence(s);
            for (;;) {
                uint32_t bad = 0;
#pragma unroll
                for (int v = 0; v < 8; v++) bad |= pa[v].x ^ ep;
                if (__all_sync(0xffffffffu, (bad & 1) == 0)) break;
                if (PSLEEP) __nanosleep(PSLEEP);
#pragma unroll
                for (int v = 0; v < 8; v++) pa[v] = ld_poll(pr + v * 128);
            }
            if (elected) TS(30);
            TT(3);
            float st[6] = {0.f, 0.f, 0.f, 0.f, 0.f, 0.f};
#pragma unroll
            for (int i = 0; i < 64; i++) {
                const int rh = (i >> 1) & 1;
                const uint32_t w = (&pa[i >> 3].x)[(i >> 1) & 3];
                const float v = fmaf((i & 1) ? tc[i >> 2].y : tc[i >> 2].x, (i & 1) ? bf_hi(w) : bf_lo(w), s[i]);
                s[i] = v;
                st[rh] += v;
                st[2 + rh] = fmaf(v, v, st[2 + rh]);
                st[4 + rh] = fmaf(v, (i & 1) ? tc[i >> 2].w : tc[i >> 2].z, st[4 + rh]);
            }
#pragma unroll
            for (int i = 0; i < 6; i++) st[i] = quad_sum(st[i]);
            st_pub(g_out + rb * OB + OB_STAT + (w4 * 8 + g) * 2 + (c4 & 1),
                   make_uint4(__float_as_uint((c4 & 1) ? st[1] : st[0]), __float_as_uint((c4 & 1) ? st[3] : st[2]),
                              __float_as_uint((c4 & 1) ? st[5] : st[4]), ep), c4 < 2);
            if (TF & 1) sched_fence(eb2, P.zero);
            if (elected) TS(56);
            TT(4);
            uint32_t cb[16], sh[16], gb[16];
#pragma unroll
            for (int i = 0; i < 16; i++) {
                const float4 c = tf[64 + i * 4];
                cb[i] = __float_as_uint(c.x); sh[i] = __float_as_uint(c.y); gb[i] = __float_as_uint(c.z);
            }
            const float ra = __uint_as_float(lds32(sb + SM_EP + 8)), rb0 = __uint_as_float(lds32(sb + SM_EP + 12));
#pragma unroll
            for (int i = 0; i < 32; i++) x2[i] = pack2(s[2 * i], s[2 * i + 1]);
            reg_fence(x2);
            uint4 r0, r1;
            if (SPRE) __nanosleep(SPRE);
            for (;;) {
                r0 = ld_poll(g_out + ((rb & ~3) + c4) * OB + OB_STAT + (w4 * 8 + g) * 2);
                r1 = ld_poll(g_out + ((rb & ~3) + c4) * OB + OB_STAT + (w4 * 8 + g) * 2 + 1);
                if (__all_sync(0xffffffffu, r0.w == ep && r1.w == ep)) break;
                if (SSLEEP) __nanosleep(SSLEEP);
            }
            if (elected) TS(57);
            TT(5);
            const float m0 = quad_sum(__uint_as_float(r0.x)) * (1.f / 512.f), m1 = quad_sum(__uint_as_float(r1.x)) * (1.f / 512.f);
            const float rs0 = ln_rstd(fmaxf(fmaf(-m0, m0, quad_sum(__uint_as_float(r0.y)) * (1.f / 512.f)), 0.f));
            const float rs1 = ln_rstd(fmaxf(fmaf(-m1, m1, quad_sum(__uint_as_float(r1.y)) * (1.f / 512.f)), 0.f));
            const uint32_t mb0 = pack2(m0, m0), mb1 = pack2(m1, m1);
            const uint32_t lg = pack2(fmaf(rs0, fmaf(-bf_lo(mb0), ra, quad_sum(__uint_as_float(r0.z))), rb0),
                                      fmaf(rs1, fmaf(-bf_lo(mb1), ra, quad_sum(__uint_as_float(r1.z))), rb0));
            const uint32_t u0 = lg << 16, u1 = lg & 0xffff0000u;
            const uint32_t k0 = ((u0 ^ (((int)u0 >> 31) | 0x80000000u)) & 0xffff0000u) | ((2047 - row) << 5) | (ep & 31);
            const uint32_t k1 = ((u1 ^ (((int)u1 >> 31) | 0x80000000u)) & 0xffff0000u) | ((2039 - row) << 5) | (ep & 31);
            const uint32_t kb = __reduce_max_sync(0xffffffffu, max(k0, k1));
            st_pub(g_key + cq * 128 + (row >> 4), kb, lane == 0);
            if (KGATE) bar_arrive(5, 160);
            if (TF & 2) sched_fence(eb2, P.zero);
            {
                uint32_t cx[18], ch[18];
#pragma unroll
                for (int i = 0; i < 16; i++) {
                    cx[i] = kb == k1 ? x2[2 * i + 1] : x2[2 * i];
                    ch[i] = ln_apply(cx[i], kb == k1 ? mb1 : mb0, kb == k1 ? rs1 : rs0, cb[i], sh[i]);
                }
                cx[16] = cx[17] = ch[16] = ch[17] = 0;
                uint4* cp = g_cand + (row >> 4) * 192 + cq * 24 + c4;
#pragma unroll
                for (int v = 0; v < 6; v++) st_pub(cp + v * 4, make_uint4(ch[3 * v], ch[3 * v + 1], ch[3 * v + 2], ep), kb == k0 || kb == k1);
                if (TF & 4) sched_fence(eb2, P.zero);
#pragma unroll
                for (int v = 0; v < 6; v++) st_pub(cp + 96 + v * 4, make_uint4(cx[3 * v], cx[3 * v + 1], cx[3 * v + 2], ep), kb == k0 || kb == k1);
            }
            if (elected) TS(58);
            TT(6);
            uint2 ov[16];
#pragma unroll
            for (int i = 0; i < 16; i++) {
                const int rh = i & 1, jj = i & 14;
                const uint32_t v0 = badd(x2[2 * jj + rh], bmul(gb[jj], ln_apply(x2[2 * jj + rh], rh ? mb1 : mb0, rh ? rs1 : rs0, cb[jj], sh[jj])));
                const uint32_t v1 = badd(x2[2 * jj + 2 + rh], bmul(gb[jj + 1], ln_apply(x2[2 * jj + 2 + rh], rh ? mb1 : mb0, rh ? rs1 : rs0, cb[jj + 1], sh[jj + 1])));
                const uint32_t rv = __shfl_xor_sync(0xffffffffu, (c4 & 1) ? v0 : v1, 1);
                ov[i] = (c4 & 1) ? make_uint2(rv, v1) : make_uint2(v0, rv);
            }
            uint2* op = reinterpret_cast<uint2*>(P.out) + row * 128 + cq * 32 + (c4 & 1) * 2 + (c4 >> 1);
            if (OUTLATE == 0) {
#pragma unroll
                for (int i = 0; i < 16; i++)
                    if (kb != ((i & 1) ? k1 : k0)) op[(i & 1) * 1024 + (i & 14) * 2] = ov[i];
            }
            if (OUTLATE == 2) bar_sync(6, 256);
            mbar_wait(sb + BAR_BEST, 0);
            const uint32_t best = lds32(sb + SM_EP + 4);
#pragma unroll
            for (int i = 0; i < 16; i++)
                if (OUTLATE ? best != ((i & 1) ? k1 : k0) : best != kb && kb == ((i & 1) ? k1 : k0)) op[(i & 1) * 1024 + (i & 14) * 2] = ov[i];
            if (elected) TS(59);
            TT(7);
        }
        mbar_arrive_if(eb2, lane == 0);
    }
}

typedef CUresult (*EncodeFn)(CUtensorMap*, CUtensorMapDataType, cuuint32_t, void*, const cuuint64_t*, const cuuint64_t*,
                             const cuuint32_t*, const cuuint32_t*, CUtensorMapInterleave, CUtensorMapSwizzle,
                             CUtensorMapL2promotion, CUtensorMapFloatOOBfill);

void make_2d(EncodeFn fn, CUtensorMap* m, const void* p, uint64_t cols, uint64_t rows, uint32_t bc, uint32_t br) {
    cuuint64_t dims[2] = {cols, rows}, strides[1] = {cols * 2};
    cuuint32_t box[2] = {bc, br}, es[2] = {1, 1};
    fn(m, CU_TENSOR_MAP_DATA_TYPE_BFLOAT16, 2, const_cast<void*>(p), dims, strides, box, es, CU_TENSOR_MAP_INTERLEAVE_NONE,
       CU_TENSOR_MAP_SWIZZLE_NONE, CU_TENSOR_MAP_L2_PROMOTION_L2_128B, CU_TENSOR_MAP_FLOAT_OOB_FILL_NONE);
}
void make_3d(EncodeFn fn, CUtensorMap* m, const void* p, uint64_t cols, uint64_t rows, uint32_t br = 128, uint32_t nb = 2) {
    cuuint64_t dims[3] = {64, rows, cols / 64}, strides[2] = {cols * 2, 128};
    cuuint32_t box[3] = {64, br, nb}, es[3] = {1, 1, 1};
    fn(m, CU_TENSOR_MAP_DATA_TYPE_BFLOAT16, 3, const_cast<void*>(p), dims, strides, box, es, CU_TENSOR_MAP_INTERLEAVE_NONE,
       CU_TENSOR_MAP_SWIZZLE_128B, CU_TENSOR_MAP_L2_PROMOTION_L2_256B, CU_TENSOR_MAP_FLOAT_OOB_FILL_NONE);
}

}

extern "C" void kernel_launch(void* const* d_in, const int* in_sizes, int n_in, void* d_out, int out_size) {
    static EncodeFn fn = nullptr;
    if (!fn) {
        void* f = nullptr;
        cudaDriverEntryPointQueryResult st;
        cudaGetDriverEntryPoint("cuTensorMapEncodeTiled", &f, cudaEnableDefault, &st);
        fn = (EncodeFn)f;
        cudaFuncSetAttribute(fused_kernel, cudaFuncAttributeMaxDynamicSharedMemorySize, SMEM_BYTES);
    }
    CUtensorMap ckv, wq, wuk, wuv, wo, wg, wu, wm, xm;
    make_3d(fn, &ckv, d_in[1], 512, 2048, 128, 1);
    make_3d(fn, &xm, d_in[0], 512, 2048, 64);
    make_3d(fn, &wq, d_in[2], 4096, 512, 128, 1);
    make_3d(fn, &wuk, d_in[3], 4096, 512);
    make_3d(fn, &wuv, d_in[4], 4096, 512);
    make_3d(fn, &wo, d_in[5], 512, 4096);
    make_2d(fn, &wg, d_in[8], 1792, 512, 16, 256);
    make_2d(fn, &wu, d_in[9], 1792, 512, 16, 256);
    make_2d(fn, &wm, d_in[12], 3072, 512, 256, 64);
    Params p;
    p.x = (const bf16*)d_in[0];
    p.ckv = (const bf16*)d_in[1];
    p.wo = (const bf16*)d_in[5];
    p.wr = (const bf16*)d_in[7];
    p.wdown = (const bf16*)d_in[10];
    p.c = (const bf16*)d_in[11];
    p.out = (bf16*)d_out;
    p.zero = 0;
    fused_kernel<<<NCTA + NSPARE, 384, SMEM_BYTES>>>(ckv, wq, wuk, wuv, wo, wg, wu, wm, xm, p);
}
```

```cpp
#include <cuda.h>
#include <cuda_bf16.h>
#include <cuda_runtime.h>
#include <stdint.h>
#include <stdio.h>

namespace {

typedef __nv_bfloat16 bf16;
typedef unsigned long long u64;

constexpr int NCTA = 128, NSPARE = 4;
constexpr int SLOT = 32768;
constexpr int SM_BAR = 7 * SLOT;
constexpr int BAR_FULL = SM_BAR;
constexpr int BAR_EMPTY = BAR_FULL + 8 * 7;
constexpr int BAR_DONE = BAR_EMPTY + 8 * 7;
constexpr int BAR_FLAG = BAR_DONE + 8 * 9;
constexpr int BAR_PF = BAR_FLAG + 8 * 9;
constexpr int BAR_END = BAR_PF + 8;
constexpr int BAR_BEST = BAR_END + 8;
constexpr int SM_EP = BAR_END + 24;
constexpr int SM_RED = SM_BAR + 384;
constexpr int SM_TAB = SM_BAR + 1024;
constexpr int SMEM_BYTES = SM_BAR + 3072;
constexpr int NFFN = 112;
#define HINT 479
constexpr u64 L2_NORMAL = 0x1000000000000000ull, L2_FIRST = 0x12F0000000000000ull;
#define PFA 8
#define PFB 6
#define UNR 1
#define POLL_NS 50
#define MSPLIT 13
#define SF 3
#define XQ 0
#define TF 7
#define OUTLATE 0
#define KSLEEP 150
#define YSLEEP 50
#define YPRE 150
#define SSLEEP 50
#define SPRE 0
#define PSLEEP 100
#define CSLEEP 0
#define SPEC 24
#define EARLY 7
constexpr uint32_t SPIN_LIMIT = 1u << 22;
constexpr uint32_t ONE2 = 0x3f803f80u;

struct Sync {
    uint32_t cnt[16 * 8 * 8];
    uint32_t ctxcnt[16 * 32];
    uint32_t epoch[32];
};

__device__ __align__(1024) uint8_t g_KV[16 * 16 * 2 * SLOT];
__device__ __align__(1024) uint8_t g_ctx[16 * 32 * SLOT];
__device__ __align__(1024) uint8_t g_h[16 * 4 * SLOT];
constexpr int OB = 1216, OB_STAT = 1024, OB_Y = 1088;
__device__ __align__(1024) uint4 g_out[128 * OB];
__device__ __align__(1024) bf16 g_mod[3072];
__device__ __align__(1024) uint32_t g_mod1[1024];
__device__ __align__(1024) uint4 g_cand[128 * 192];
__device__ __align__(1024) uint32_t g_key[4 * 128];
__device__ __align__(1024) uint8_t g_wf[NFFN * SLOT];
__device__ __align__(1024) Sync g_sync;
#define TS(i)

#define TT(i)
#define PT()

struct Params {
    const bf16 *x, *ckv, *wo, *wr, *wdown, *c;
    bf16* out;
    int zero;
};

__device__ __forceinline__ void mbar_init(uint32_t bar, uint32_t cnt) {
    asm volatile("mbarrier.init.shared::cta.b64 [%0], %1;" ::"r"(bar), "r"(cnt) : "memory");
}
__device__ __forceinline__ void mbar_wait(uint32_t bar, uint32_t parity) {
    asm volatile("{\n.reg .pred p;\nL_%=:\nmbarrier.try_wait.parity.shared::cta.b64 p, [%0], %1;\n@!p bra L_%=;\n}" ::"r"(bar), "r"(parity) : "memory");
}
__device__ __forceinline__ void mbar_sleep(uint32_t bar) {
    if ((threadIdx.x & 31) == 0)
        asm volatile("{\n.reg .pred p;\nL_%=:\nmbarrier.try_wait.parity.shared::cta.b64 p, [%0], 0, 100000;\n@!p bra L_%=;\n}" ::"r"(bar) : "memory");
    __syncwarp();
}
__device__ __forceinline__ void mbar_watch(uint32_t bar, uint32_t parity) {
    asm volatile("{\n.reg .pred p;\n.reg .u32 n;\nmov.u32 n, 0;\n"
                 "L_%=:\nmbarrier.try_wait.parity.shared::cta.b64 p, [%0], %1;\n@p bra D_%=;\n"
                 "add.u32 n, n, 1;\nsetp.lt.u32 p, n, %2;\n@p bra L_%=;\ntrap;\nD_%=:\n}"
                 ::"r"(bar), "r"(parity), "n"(SPIN_LIMIT) : "memory");
}
__device__ __forceinline__ void step_watch(uint32_t a, uint32_t step) {
    asm volatile("{\n.reg .pred p;\n.reg .u32 n, v;\nmov.u32 n, 0;\n"
                 "L_%=:\nld.volatile.shared.u32 v, [%0];\nsetp.ge.u32 p, v, %1;\n@p bra D_%=;\nnanosleep.u32 400;\n"
                 "add.u32 n, n, 1;\nsetp.lt.u32 p, n, %2;\n@p bra L_%=;\ntrap;\nD_%=:\n}"
                 ::"r"(a), "r"(step), "n"(SPIN_LIMIT) : "memory");
}
__device__ __forceinline__ void mbar_arrive_if(uint32_t bar, bool on) {
    asm volatile("{\n.reg .pred p;\nsetp.ne.s32 p, %1, 0;\n@p mbarrier.arrive.shared::cta.b64 _, [%0];\n}" ::"r"(bar), "r"((int)on) : "memory");
}
__device__ __forceinline__ void tma2d(uint32_t dst, const CUtensorMap* m, int c0, int c1, uint32_t bar, bool first) {
    asm volatile("{\n.reg .pred p;\nelect.sync _|p, 0xffffffff;\n"
                 "@p cp.async.bulk.tensor.2d.shared::cluster.global.mbarrier::complete_tx::bytes.L2::cache_hint [%0], [%1, {%3, %4}], [%2], %5;\n}"
                 ::"r"(dst), "l"(m), "r"(bar), "r"(c0), "r"(c1), "l"(first ? L2_FIRST : L2_NORMAL) : "memory");
}
__device__ __forceinline__ void tma3d_prefetch(const CUtensorMap* m, int row, int cb) {
    asm volatile("{\n.reg .pred p;\nelect.sync _|p, 0xffffffff;\n@p cp.async.bulk.prefetch.tensor.3d.L2.global [%0, {%1, %2, %3}];\n}"
                 ::"l"(m), "r"(0), "r"(row), "r"(cb) : "memory");
}
__device__ __forceinline__ void l2_prefetch(const void* p, uint32_t bytes) {
    asm volatile("{\n.reg .pred p;\nelect.sync _|p, 0xffffffff;\n@p cp.async.bulk.prefetch.L2.global [%0], %1;\n}" ::"l"(p), "r"(bytes) : "memory");
}
__device__ __forceinline__ void bulk_store(void* dst, uint32_t src, uint32_t bytes, bool first) {
    asm volatile("{\n.reg .pred p;\nelect.sync _|p, 0xffffffff;\n@p cp.async.bulk.global.shared::cta.bulk_group.L2::cache_hint [%0], [%1], %2, %3;\n}"
                 ::"l"(dst), "r"(src), "r"(bytes), "l"(first ? L2_FIRST : L2_NORMAL) : "memory");
}
__device__ __forceinline__ void flag_wait(const uint32_t* f, uint32_t target) {
    asm volatile("{\n.reg .pred p;\n.reg .u32 v;\n"
                 "L_%=:\nld.acquire.gpu.global.u32 v, [%0];\nsub.u32 v, v, %1;\nsetp.lt.s32 p, v, 0;\n@p nanosleep.u32 100;\n@p bra L_%=;\n}"
                 ::"l"(f), "r"(target) : "memory");
}
__device__ __forceinline__ uint4 ld_poll(const uint4* p) {
    uint4 v;
    asm volatile("{\n.reg .b128 t;\nld.relaxed.gpu.global.b128 t, [%4];\nmov.b128 {%0, %1, %2, %3}, t;\n}"
                 : "=r"(v.x), "=r"(v.y), "=r"(v.z), "=r"(v.w) : "l"(p) : "memory");
    return v;
}
__device__ __forceinline__ void st_pub(uint4* p, uint4 v, bool on) {
    asm volatile("{\n.reg .pred p;\n.reg .b128 t;\nsetp.ne.s32 p, %5, 0;\nmov.b128 t, {%1, %2, %3, %4};\n@p st.relaxed.gpu.global.b128 [%0], t;\n}"
                 ::"l"(p), "r"(v.x), "r"(v.y), "r"(v.z), "r"(v.w), "r"((int)on) : "memory");
}
__device__ __forceinline__ void st_pub(uint32_t* p, uint32_t v, bool on) {
    asm volatile("{\n.reg .pred p;\nsetp.ne.s32 p, %2, 0;\n@p st.relaxed.gpu.global.u32 [%0], %1;\n}" ::"l"(p), "r"(v), "r"((int)on) : "memory");
}
__device__ __forceinline__ void flag_add(uint32_t* p) {
    asm volatile("red.release.gpu.global.add.u32 [%0], 1;" ::"l"(p) : "memory");
}
__device__ __forceinline__ uint32_t lds32(uint32_t a) {
    uint32_t v;
    asm volatile("ld.shared.u32 %0, [%1];" : "=r"(v) : "r"(a) : "memory");
    return v;
}
__device__ __forceinline__ uint4 lds128(uint32_t a) {
    uint4 v;
    asm volatile("ld.shared.v4.u32 {%0, %1, %2, %3}, [%4];" : "=r"(v.x), "=r"(v.y), "=r"(v.z), "=r"(v.w) : "r"(a) : "memory");
    return v;
}
__device__ __forceinline__ void sched_fence(uint32_t& v, uint32_t z) {
    uint32_t ck;
    asm volatile("mov.u32 %0, %%clock;" : "=r"(ck)::"memory");
    v ^= ck & z;
}
__device__ __forceinline__ void fence_async_global() { asm volatile("fence.proxy.async.global;" ::: "memory"); }
__device__ __forceinline__ void fence_async_smem() { asm volatile("fence.proxy.async.shared::cta;" ::: "memory"); }
__device__ __forceinline__ void bar_sync(int id, int n) { asm volatile("bar.sync %0, %1;" ::"r"(id), "r"(n) : "memory"); }
__device__ __forceinline__ void bar_arrive(int id, int n) { asm volatile("bar.arrive %0, %1;" ::"r"(id), "r"(n) : "memory"); }
__device__ __forceinline__ void wg_fence() { asm volatile("wgmma.fence.sync.aligned;" ::: "memory"); }
__device__ __forceinline__ void wg_commit() { asm volatile("wgmma.commit_group.sync.aligned;" ::: "memory"); }
template <int N> __device__ __forceinline__ void wg_wait() { asm volatile("wgmma.wait_group.sync.aligned %0;" ::"n"(N) : "memory"); }
template <int N> __device__ __forceinline__ void reg_fence(float (&d)[N]) {
#pragma unroll
    for (int i = 0; i < N; i++) asm volatile("" : "+f"(d[i])::"memory");
}
template <int N> __device__ __forceinline__ void reg_fence(uint32_t (&d)[N]) {
#pragma unroll
    for (int i = 0; i < N; i++) asm volatile("" : "+r"(d[i])::"memory");
}
__device__ __forceinline__ uint32_t desc_k(uint32_t a) { return ((a & 0x3ffff) >> 4) | (1u << 16); }
__device__ __forceinline__ uint32_t desc_mn(uint32_t a) { return ((a & 0x3ffff) >> 4) | (1024u << 16); }

template <int TB>
__device__ __forceinline__ void wgmma_ss128(float (&d)[64], uint32_t da, uint32_t db, int acc, uint32_t ha = 0x40000040u, uint32_t hb = 0x40000040u) {
    asm volatile("{\n.reg .pred p;\n.reg .b64 a, b;\nsetp.ne.b32 p, %66, 0;\nmov.b64 a, {%64, %68};\nmov.b64 b, {%65, %69};\n"
        "wgmma.mma_async.sync.aligned.m64n128k16.f32.bf16.bf16 {%0, %1, %2, %3, %4, %5, %6, %7, %8, %9, %10, %11, %12, %13, %14, %15, %16, %17, %18, %19, %20, %21, %22, %23, %24, %25, %26, %27, %28, %29, %30, %31, %32, %33, %34, %35, %36, %37, %38, %39, %40, %41, %42, %43, %44, %45, %46, %47, %48, %49, %50, %51, %52, %53, %54, %55, %56, %57, %58, %59, %60, %61, %62, %63}, a, b, p, 1, 1, 0, %67;\n}"
        : "+f"(d[0]), "+f"(d[1]), "+f"(d[2]), "+f"(d[3]), "+f"(d[4]), "+f"(d[5]), "+f"(d[6]), "+f"(d[7]), "+f"(d[8]), "+f"(d[9]), "+f"(d[10]), "+f"(d[11]), "+f"(d[12]), "+f"(d[13]), "+f"(d[14]), "+f"(d[15]), "+f"(d[16]), "+f"(d[17]), "+f"(d[18]), "+f"(d[19]), "+f"(d[20]), "+f"(d[21]), "+f"(d[22]), "+f"(d[23]), "+f"(d[24]), "+f"(d[25]), "+f"(d[26]), "+f"(d[27]), "+f"(d[28]), "+f"(d[29]), "+f"(d[30]), "+f"(d[31]), "+f"(d[32]), "+f"(d[33]), "+f"(d[34]), "+f"(d[35]), "+f"(d[36]), "+f"(d[37]), "+f"(d[38]), "+f"(d[39]), "+f"(d[40]), "+f"(d[41]), "+f"(d[42]), "+f"(d[43]), "+f"(d[44]), "+f"(d[45]), "+f"(d[46]), "+f"(d[47]), "+f"(d[48]), "+f"(d[49]), "+f"(d[50]), "+f"(d[51]), "+f"(d[52]), "+f"(d[53]), "+f"(d[54]), "+f"(d[55]), "+f"(d[56]), "+f"(d[57]), "+f"(d[58]), "+f"(d[59]), "+f"(d[60]), "+f"(d[61]), "+f"(d[62]), "+f"(d[63])
        : "r"(da), "r"(db), "r"(acc), "n"(TB), "r"(ha), "r"(hb));
}
template <int TB>
__device__ __forceinline__ void wgmma_ss128_init(float (&d)[64], uint32_t da, uint32_t db, uint32_t ha = 0x40000040u, uint32_t hb = 0x40000040u) {
    asm volatile("{\n.reg .pred p;\n.reg .b64 a, b;\nsetp.ne.b32 p, 0, 0;\nmov.b64 a, {%64, %67};\nmov.b64 b, {%65, %68};\n"
        "wgmma.mma_async.sync.aligned.m64n128k16.f32.bf16.bf16 {%0, %1, %2, %3, %4, %5, %6, %7, %8, %9, %10, %11, %12, %13, %14, %15, %16, %17, %18, %19, %20, %21, %22, %23, %24, %25, %26, %27, %28, %29, %30, %31, %32, %33, %34, %35, %36, %37, %38, %39, %40, %41, %42, %43, %44, %45, %46, %47, %48, %49, %50, %51, %52, %53, %54, %55, %56, %57, %58, %59, %60, %61, %62, %63}, a, b, p, 1, 1, 0, %66;\n}"
        : "=f"(d[0]), "=f"(d[1]), "=f"(d[2]), "=f"(d[3]), "=f"(d[4]), "=f"(d[5]), "=f"(d[6]), "=f"(d[7]), "=f"(d[8]), "=f"(d[9]), "=f"(d[10]), "=f"(d[11]), "=f"(d[12]), "=f"(d[13]), "=f"(d[14]), "=f"(d[15]), "=f"(d[16]), "=f"(d[17]), "=f"(d[18]), "=f"(d[19]), "=f"(d[20]), "=f"(d[21]), "=f"(d[22]), "=f"(d[23]), "=f"(d[24]), "=f"(d[25]), "=f"(d[26]), "=f"(d[27]), "=f"(d[28]), "=f"(d[29]), "=f"(d[30]), "=f"(d[31]), "=f"(d[32]), "=f"(d[33]), "=f"(d[34]), "=f"(d[35]), "=f"(d[36]), "=f"(d[37]), "=f"(d[38]), "=f"(d[39]), "=f"(d[40]), "=f"(d[41]), "=f"(d[42]), "=f"(d[43]), "=f"(d[44]), "=f"(d[45]), "=f"(d[46]), "=f"(d[47]), "=f"(d[48]), "=f"(d[49]), "=f"(d[50]), "=f"(d[51]), "=f"(d[52]), "=f"(d[53]), "=f"(d[54]), "=f"(d[55]), "=f"(d[56]), "=f"(d[57]), "=f"(d[58]), "=f"(d[59]), "=f"(d[60]), "=f"(d[61]), "=f"(d[62]), "=f"(d[63])
        : "r"(da), "r"(db), "n"(TB), "r"(ha), "r"(hb));
}
template <int TB>
__device__ __forceinline__ void wgmma_ss64(float (&d)[32], uint32_t da, uint32_t db, int acc, uint32_t ha = 0x40000040u, uint32_t hb = 0x40000040u) {
    asm volatile("{\n.reg .pred p;\n.reg .b64 a, b;\nsetp.ne.b32 p, %34, 0;\nmov.b64 a, {%32, %36};\nmov.b64 b, {%33, %37};\n"
        "wgmma.mma_async.sync.aligned.m64n64k16.f32.bf16.bf16 {%0, %1, %2, %3, %4, %5, %6, %7, %8, %9, %10, %11, %12, %13, %14, %15, %16, %17, %18, %19, %20, %21, %22, %23, %24, %25, %26, %27, %28, %29, %30, %31}, a, b, p, 1, 1, 0, %35;\n}"
        : "+f"(d[0]), "+f"(d[1]), "+f"(d[2]), "+f"(d[3]), "+f"(d[4]), "+f"(d[5]), "+f"(d[6]), "+f"(d[7]), "+f"(d[8]), "+f"(d[9]), "+f"(d[10]), "+f"(d[11]), "+f"(d[12]), "+f"(d[13]), "+f"(d[14]), "+f"(d[15]), "+f"(d[16]), "+f"(d[17]), "+f"(d[18]), "+f"(d[19]), "+f"(d[20]), "+f"(d[21]), "+f"(d[22]), "+f"(d[23]), "+f"(d[24]), "+f"(d[25]), "+f"(d[26]), "+f"(d[27]), "+f"(d[28]), "+f"(d[29]), "+f"(d[30]), "+f"(d[31])
        : "r"(da), "r"(db), "r"(acc), "n"(TB), "r"(ha), "r"(hb));
}
template <int TB>
__device__ __forceinline__ void wgmma_ss64_init(float (&d)[32], uint32_t da, uint32_t db, uint32_t ha = 0x40000040u, uint32_t hb = 0x40000040u) {
    asm volatile("{\n.reg .pred p;\n.reg .b64 a, b;\nsetp.ne.b32 p, 0, 0;\nmov.b64 a, {%32, %35};\nmov.b64 b, {%33, %36};\n"
        "wgmma.mma_async.sync.aligned.m64n64k16.f32.bf16.bf16 {%0, %1, %2, %3, %4, %5, %6, %7, %8, %9, %10, %11, %12, %13, %14, %15, %16, %17, %18, %19, %20, %21, %22, %23, %24, %25, %26, %27, %28, %29, %30, %31}, a, b, p, 1, 1, 0, %34;\n}"
        : "=f"(d[0]), "=f"(d[1]), "=f"(d[2]), "=f"(d[3]), "=f"(d[4]), "=f"(d[5]), "=f"(d[6]), "=f"(d[7]), "=f"(d[8]), "=f"(d[9]), "=f"(d[10]), "=f"(d[11]), "=f"(d[12]), "=f"(d[13]), "=f"(d[14]), "=f"(d[15]), "=f"(d[16]), "=f"(d[17]), "=f"(d[18]), "=f"(d[19]), "=f"(d[20]), "=f"(d[21]), "=f"(d[22]), "=f"(d[23]), "=f"(d[24]), "=f"(d[25]), "=f"(d[26]), "=f"(d[27]), "=f"(d[28]), "=f"(d[29]), "=f"(d[30]), "=f"(d[31])
        : "r"(da), "r"(db), "n"(TB), "r"(ha), "r"(hb));
}
__device__ __forceinline__ void wgmma_rs128(float (&d)[64], uint32_t a0, uint32_t a1, uint32_t a2, uint32_t a3, uint32_t db, int acc, uint32_t hb = 0x40000040u) {
    asm volatile("{\n.reg .pred p;\n.reg .b64 b;\nsetp.ne.b32 p, %69, 0;\nmov.b64 b, {%68, %70};\n"
        "wgmma.mma_async.sync.aligned.m64n128k16.f32.bf16.bf16 {%0, %1, %2, %3, %4, %5, %6, %7, %8, %9, %10, %11, %12, %13, %14, %15, %16, %17, %18, %19, %20, %21, %22, %23, %24, %25, %26, %27, %28, %29, %30, %31, %32, %33, %34, %35, %36, %37, %38, %39, %40, %41, %42, %43, %44, %45, %46, %47, %48, %49, %50, %51, %52, %53, %54, %55, %56, %57, %58, %59, %60, %61, %62, %63}, {%64, %65, %66, %67}, b, p, 1, 1, 1;\n}"
        : "+f"(d[0]), "+f"(d[1]), "+f"(d[2]), "+f"(d[3]), "+f"(d[4]), "+f"(d[5]), "+f"(d[6]), "+f"(d[7]), "+f"(d[8]), "+f"(d[9]), "+f"(d[10]), "+f"(d[11]), "+f"(d[12]), "+f"(d[13]), "+f"(d[14]), "+f"(d[15]), "+f"(d[16]), "+f"(d[17]), "+f"(d[18]), "+f"(d[19]), "+f"(d[20]), "+f"(d[21]), "+f"(d[22]), "+f"(d[23]), "+f"(d[24]), "+f"(d[25]), "+f"(d[26]), "+f"(d[27]), "+f"(d[28]), "+f"(d[29]), "+f"(d[30]), "+f"(d[31]), "+f"(d[32]), "+f"(d[33]), "+f"(d[34]), "+f"(d[35]), "+f"(d[36]), "+f"(d[37]), "+f"(d[38]), "+f"(d[39]), "+f"(d[40]), "+f"(d[41]), "+f"(d[42]), "+f"(d[43]), "+f"(d[44]), "+f"(d[45]), "+f"(d[46]), "+f"(d[47]), "+f"(d[48]), "+f"(d[49]), "+f"(d[50]), "+f"(d[51]), "+f"(d[52]), "+f"(d[53]), "+f"(d[54]), "+f"(d[55]), "+f"(d[56]), "+f"(d[57]), "+f"(d[58]), "+f"(d[59]), "+f"(d[60]), "+f"(d[61]), "+f"(d[62]), "+f"(d[63])
        : "r"(a0), "r"(a1), "r"(a2), "r"(a3), "r"(db), "r"(acc), "r"(hb));
}

__device__ __forceinline__ uint32_t pack2(float lo, float hi) {
    uint32_t r;
    asm("cvt.rn.bf16x2.f32 %0, %1, %2;" : "=r"(r) : "f"(hi), "f"(lo));
    return r;
}
__device__ __forceinline__ float bf_lo(uint32_t v) { return __uint_as_float(v << 16); }
__device__ __forceinline__ float bf_hi(uint32_t v) { return __uint_as_float(v & 0xffff0000u); }
__device__ __forceinline__ float rbf(float v) { return bf_lo(pack2(v, v)); }
__device__ __forceinline__ uint32_t badd(uint32_t a, uint32_t b) {
    uint32_t r;
    asm("add.rn.bf16x2 %0, %1, %2;" : "=r"(r) : "r"(a), "r"(b));
    return r;
}
__device__ __forceinline__ uint32_t bsub(uint32_t a, uint32_t b) {
    uint32_t r;
    asm("sub.rn.bf16x2 %0, %1, %2;" : "=r"(r) : "r"(a), "r"(b));
    return r;
}
__device__ __forceinline__ uint32_t bmul(uint32_t a, uint32_t b) {
    uint32_t r;
    asm("mul.rn.bf16x2 %0, %1, %2;" : "=r"(r) : "r"(a), "r"(b));
    return r;
}
__device__ __forceinline__ uint32_t ln_apply(uint32_t x, uint32_t mb, float rs, uint32_t scale, uint32_t shift) {
    const uint32_t d = bsub(x, mb);
    return badd(bmul(pack2(bf_lo(d) * rs, bf_hi(d) * rs), scale), shift);
}
__device__ __forceinline__ float ex2(float v) {
    float r;
    asm("ex2.approx.ftz.f32 %0, %1;" : "=f"(r) : "f"(v));
    return r;
}
__device__ __forceinline__ float rcp(float v) {
    float r;
    asm("rcp.approx.ftz.f32 %0, %1;" : "=f"(r) : "f"(v));
    return r;
}
__device__ __forceinline__ float sqrt_fast(float v) {
    float r;
    asm("sqrt.approx.ftz.f32 %0, %1;" : "=f"(r) : "f"(v));
    return r;
}
__device__ __forceinline__ float ln_rstd(float var) { return rcp(rbf(sqrt_fast(rbf(rbf(var) + 1e-5f)))); }
__device__ __forceinline__ float sigmoid(float v) { return rcp(1.f + ex2(-1.4426950408889634f * v)); }
__device__ __forceinline__ float quad_sum(float v) {
    v += __shfl_xor_sync(0xffffffffu, v, 1);
    return v + __shfl_xor_sync(0xffffffffu, v, 2);
}

constexpr uint32_t HI_128 = 0x40000040u, HI_IMG = 0x80000080u, HI_Q = 0x80000040u;
template <int M, int RH>
__device__ __forceinline__ uint4 img_pack(const float (&d)[64], float s) {
    uint4 v;
    v.x = pack2(d[16 * M + 2 * RH] * s, d[16 * M + 2 * RH + 1] * s);
    v.y = pack2(d[16 * M + 4 + 2 * RH] * s, d[16 * M + 5 + 2 * RH] * s);
    v.z = pack2(d[16 * M + 8 + 2 * RH] * s, d[16 * M + 9 + 2 * RH] * s);
    v.w = pack2(d[16 * M + 12 + 2 * RH] * s, d[16 * M + 13 + 2 * RH] * s);
    return v;
}
template <int M>
__device__ __forceinline__ void img_store_global(uint8_t* img, uint32_t toff, const float (&d)[64], float s0, float s1) {
    uint4* p = reinterpret_cast<uint4*>(img + toff) + M * 32;
    p[0] = img_pack<M, 0>(d, s0);
    p[128] = img_pack<M, 1>(d, s1);
}
__device__ __forceinline__ void sts128(uint32_t a, uint4 v) {
    asm volatile("st.shared.v4.b32 [%0], {%1, %2, %3, %4};" ::"r"(a), "r"(v.x), "r"(v.y), "r"(v.z), "r"(v.w) : "memory");
}
constexpr float SM_C = 0.08838834764831845f * 1.4426950408889634f;
__device__ __forceinline__ float pack2f(float lo, float hi) {
    float r;
    asm("{\n.reg .b32 t;\ncvt.rn.bf16x2.f32 t, %1, %2;\nmov.b32 %0, t;\n}" : "=f"(r) : "f"(hi), "f"(lo));
    return r;
}
template <int M, bool SCALE, bool PARK>
__device__ __forceinline__ void pack_group(float (&d)[64], float (&v)[8], float s0, float s1) {
#pragma unroll
    for (int i = 0; i < 8; i++) {
        const int k = 16 * M + 4 * (i & 3) + 2 * (i >> 2);
        v[i] = SCALE ? pack2f(d[k] * (i < 4 ? s0 : s1), d[k + 1] * (i < 4 ? s0 : s1)) : pack2f(d[k], d[k + 1]);
        if (PARK && M > 0) d[16 * (M > 0 ? M - 1 : 0) + i] = v[i];
    }
}
__device__ __forceinline__ uint32_t q_off(uint32_t toff) { return (((toff >> 1) & ~2047u) ^ 8192) + (toff & 511); }
template <int M, bool PARK>
__device__ __forceinline__ void ctx_store_part(float4* p, float (&d)[64], float i0, float i1) {
    float v[8];
    pack_group<M, true, PARK>(d, v, i0, i1);
    p[M * 32] = make_float4(v[0], v[1], v[2], v[3]);
    p[M * 32 + 128] = make_float4(v[4], v[5], v[6], v[7]);
}
template <bool PARK>
__device__ __forceinline__ void ctx_store(uint8_t* img, uint32_t toff, float (&o)[64], float l0, float l1) {
    const float i0 = rcp(quad_sum(l0)), i1 = rcp(quad_sum(l1));
    float4* p = reinterpret_cast<float4*>(img + toff);
    ctx_store_part<0, PARK>(p, o, i0, i1); ctx_store_part<1, PARK>(p, o, i0, i1); ctx_store_part<2, PARK>(p, o, i0, i1); ctx_store_part<3, PARK>(p, o, i0, i1);
}

template <int M>
__device__ __forceinline__ void tile_store_part(float4* p, uint32_t a, float (&d)[64], float i0, float i1, int ctx) {
    float v[8];
    pack_group<M, true, true>(d, v, i0, i1);
#pragma unroll
    for (int h = 0; h < 2; h++)
        asm volatile("{\n.reg .pred p;\nsetp.ne.s32 p, %6, 0;\n@p st.global.v4.f32 [%0], {%2, %3, %4, %5};\n@!p st.shared.v4.f32 [%1], {%2, %3, %4, %5};\n}"
                     ::"l"(p + M * 32 + h * 128), "r"(a + (M >> 1) * 16384 + (M & 1) * 512 + h * 1024),
                     "f"(v[4 * h]), "f"(v[4 * h + 1]), "f"(v[4 * h + 2]), "f"(v[4 * h + 3]), "r"(ctx) : "memory");
}
__device__ __forceinline__ void tile_store(uint8_t* img, uint32_t a, uint32_t toff, float (&d)[64], float i0, float i1, int ctx) {
    float4* p = reinterpret_cast<float4*>(img + toff);
    a += q_off(toff);
    tile_store_part<0>(p, a, d, i0, i1, ctx); tile_store_part<1>(p, a, d, i0, i1, ctx);
    tile_store_part<2>(p, a, d, i0, i1, ctx); tile_store_part<3>(p, a, d, i0, i1, ctx);
}

__device__ __forceinline__ void slot_wait(uint32_t bars, uint32_t& ph, uint32_t slot) {
    mbar_wait(bars + 8 * slot, (ph >> slot) & 1);
    ph ^= 1u << slot;
}
__device__ __forceinline__ void release_if(uint32_t eb, uint32_t slot, bool on) {
    asm volatile("{\n.reg .pred p;\nsetp.ne.s32 p, %1, 0;\n@p mbarrier.arrive.shared::cluster.b64 _, [%0];\n}" ::"r"(eb + 8 * slot), "r"((int)on) : "memory");
}
__device__ __forceinline__ void slot_acquire(uint32_t sb, uint32_t& ph, uint32_t slot) {
    slot_wait(sb + BAR_EMPTY, ph, slot);
    asm volatile("{\n.reg .pred p;\nelect.sync _|p, 0xffffffff;\n@p mbarrier.arrive.expect_tx.shared::cta.b64 _, [%0], 32768;\n}"
                 ::"r"(sb + BAR_FULL + 8 * slot) : "memory");
}
__device__ __forceinline__ void load_bulk(uint32_t sb, uint32_t slot, uint32_t off, const void* src, uint32_t bytes, bool both, bool first) {
    if (both)
        asm volatile("{\n.reg .pred p;\nelect.sync _|p, 0xffffffff;\n"
                     "@p cp.async.bulk.shared::cluster.global.mbarrier::complete_tx::bytes.multicast::cluster.L2::cache_hint [%0], [%1], %5, [%2], %4, %3;\n}"
                     ::"r"(sb + slot * SLOT + off), "l"(src), "r"(sb + BAR_FULL + 8 * slot), "l"(first ? L2_FIRST : L2_NORMAL), "h"((uint16_t)3),
                     "r"(bytes) : "memory");
    else
        asm volatile("{\n.reg .pred p;\nelect.sync _|p, 0xffffffff;\n"
                     "@p cp.async.bulk.shared::cluster.global.mbarrier::complete_tx::bytes.L2::cache_hint [%0], [%1], %4, [%2], %3;\n}"
                     ::"r"(sb + slot * SLOT + off), "l"(src), "r"(sb + BAR_FULL + 8 * slot), "l"(first ? L2_FIRST : L2_NORMAL), "r"(bytes) : "memory");
}
__device__ __forceinline__ void load_tile(uint32_t sb, uint32_t slot, uint32_t off, const CUtensorMap* m, int row, int cb, bool both, bool first) {
    if (both)
        asm volatile("{\n.reg .pred p;\nelect.sync _|p, 0xffffffff;\n"
                     "@p cp.async.bulk.tensor.3d.shared::cluster.global.mbarrier::complete_tx::bytes.multicast::cluster.L2::cache_hint [%0], [%1, {%3, %4, %5}], [%2], %7, %6;\n}"
                     ::"r"(sb + slot * SLOT + off), "l"(m), "r"(sb + BAR_FULL + 8 * slot), "r"(0), "r"(row), "r"(cb),
                     "l"(first ? L2_FIRST : L2_NORMAL), "h"((uint16_t)3) : "memory");
    else
        asm volatile("{\n.reg .pred p;\nelect.sync _|p, 0xffffffff;\n"
                     "@p cp.async.bulk.tensor.3d.shared::cluster.global.mbarrier::complete_tx::bytes.L2::cache_hint [%0], [%1, {%3, %4, %5}], [%2], %6;\n}"
                     ::"r"(sb + slot * SLOT + off), "l"(m), "r"(sb + BAR_FULL + 8 * slot), "r"(0), "r"(row), "r"(cb),
                     "l"(first ? L2_FIRST : L2_NORMAL) : "memory");
}
__device__ __forceinline__ uint32_t ring_next(uint32_t r) { return r == 4 ? 0 : r + 1; }
__device__ __forceinline__ uint32_t w_table(int hp) { return hp ? 0x3104u : 0x4210u; }
__device__ __forceinline__ uint32_t a_table(int hp) { return hp ? 0x625u : 0x635u; }
__device__ __forceinline__ uint32_t a_next(uint32_t& t) {
    const uint32_t s = t & 15;
    t = (t >> 4) | (s << 8);
    return s;
}
constexpr uint32_t O_TABLE = 0x1604235u;
__device__ __forceinline__ uint32_t o_next(uint32_t& t) {
    const uint32_t s = t & 15;
    t = (t >> 4) | (s << 24);
    return s;
}
__device__ __forceinline__ int o_head(int i, int kh) { return i < 16 ? 4 * (i & 7) + 2 * (kh ^ 1) + (i >> 3) : 29 + 2 * kh; }

template <bool INIT>
__device__ __forceinline__ void gemm_issue(float (&d)[64], uint32_t a, uint32_t b, int acc, bool img) {
    const uint32_t ha = img ? HI_IMG : HI_128, o2 = img ? 32 : 4, o4 = img ? 64 : 1024;
    wg_fence();
#pragma unroll
    for (int k = 0; k < 8; k++) {
        if (INIT && k == 0) wgmma_ss128_init<1>(d, a, b, ha);
        else wgmma_ss128<1>(d, a + (k >> 2) * o4 + ((k >> 1) & 1) * o2 + (k & 1) * 2, b + k * 128, k ? 1 : acc, ha);
    }
    wg_commit();
}

template <bool ODD>
__device__ __forceinline__ bool proj_tile(float (&acc)[64], float (&prev)[64], int t, int q0, uint32_t sb, int wg, uint32_t eb, bool rel, uint32_t& fph,
                                          uint32_t wtab, uint32_t& atab, uint8_t* prev_img, uint32_t toff, float s0, float s1, bool first,
                                          const bf16* x, int xrow, uint32_t (&v)[32]) {
    const uint32_t a0 = desc_k(sb + (wg ^ (ODD && t == 5)) * 8192), b0 = desc_mn(sb);
    const int lane = threadIdx.x & 31;
    constexpr int U = ODD ? UNR : 1;
#pragma unroll U
    for (int q = ODD ? 0 : q0; q < 4; q++) {
        const uint32_t ws = (wtab >> (4 * q)) & 15, as = a_next(atab);
        if (!ODD && t != 2) slot_wait(sb + BAR_FULL, fph, ws);
        slot_wait(sb + BAR_FULL, fph, as);
        if (ODD && q == 2 && t == 5) {
#pragma unroll
            for (int i = 0; i < 8; i++) sts128(sb + 5 * SLOT + q_off(toff) + (i >> 2) * 16384 + (i & 2) * 256 + (i & 1) * 1024, make_uint4(v[4 * i], v[4 * i + 1], v[4 * i + 2], v[4 * i + 3]));
        }
        bar_sync(1 + wg, 256);
        gemm_issue<false>(acc, a0 + as * (SLOT / 16), b0 + ws * (SLOT / 16), q, false);
        bar_arrive(2 - wg, 256);
        wg_wait<1>();
        reg_fence(prev);
        if (ODD && t == 5) {
            if (q == 0) {
#pragma unroll
                for (int i = 0; i < 32; i++) {
                    const int k = 16 * (i >> 3) + 4 * (i & 3) + ((i >> 1) & 2);
                    v[i] = pack2(prev[k], prev[k + 1]);
                }
            }
            if (q == 2) {
                fence_async_smem();
                slot_wait(sb + BAR_FULL, fph, wtab & 15);
                wg_wait<0>();
                release_if(eb, as, rel);
                release_if(eb, ws, rel);
                reg_fence(acc);
                return true;
            }
        } else {
            if (first) {
                const uint4* xp = reinterpret_cast<const uint4*>(x) + xrow * 64;
                if (!ODD) {
                    if (q == XQ && lane < 16) asm volatile("prefetch.global.L1 [%0];" ::"l"(xp + lane * 8) : "memory");
                    if (q == 3) {
#pragma unroll
                        for (int i = 0; i < 4; i++) {
                            const uint4 u = __ldg(xp + lane + 32 * i);
                            v[4 * i] = u.x; v[4 * i + 1] = u.y; v[4 * i + 2] = u.z; v[4 * i + 3] = u.w;
                        }
                        v[16] = __ldg(&xp[0].x) << 16;
                        v[17] = __ldg(&xp[64].x) << 16;
                        float st[4] = {0.f, 0.f, 0.f, 0.f};
#pragma unroll
                        for (int k = 0; k < 16; k++) {
                            const float d0 = bf_lo(v[k]) - __uint_as_float(v[16 + (k >> 3)]), d1 = bf_hi(v[k]) - __uint_as_float(v[16 + (k >> 3)]);
                            st[k >> 3] += d0 + d1;
                            st[2 + (k >> 3)] = fmaf(d0, d0, fmaf(d1, d1, st[2 + (k >> 3)]));
                        }
#pragma unroll
                        for (int i = 0; i < 4; i++) v[20 + i] = __float_as_uint(st[i]);
                    }
                } else if (q == 0) {
#pragma unroll
                    for (int i = 0; i < 20; i++)
                        v[20 + (i & 3)] = __float_as_uint(__uint_as_float(v[20 + (i & 3)]) + __uint_as_float(__shfl_xor_sync(0xffffffffu, v[20 + (i & 3)], 1 << (i >> 2))));
                } else if (q == 1) {
#pragma unroll
                    for (int i = 0; i < 2; i++) {
                        const float d = __uint_as_float(v[20 + i]) * (1.f / 512.f);
                        const float rs = ln_rstd(fmaxf(fmaf(-d, d, __uint_as_float(v[22 + i]) * (1.f / 512.f)), 0.f));
                        const uint32_t mb = pack2(__uint_as_float(v[16 + i]) + d, __uint_as_float(v[16 + i]) + d);
#pragma unroll
                        for (int k = 8 * i; k < 8 * i + 8; k++) {
                            const uint32_t y = bsub(v[k], mb);
                            v[k] = pack2(bf_lo(y) * rs, bf_hi(y) * rs);
                        }
                    }
                } else {
                    mbar_wait(sb + BAR_FLAG + 8 * 8, 0);
                    const uint4 a = lds128(sb + SM_TAB + q * 512 + lane * 16), c = lds128(sb + SM_TAB - 1024 + q * 512 + lane * 16);
                    uint8_t* p = g_h + ((xrow >> 7) * 8 + (q & 1) * 4 + (lane >> 3)) * 16384 + (xrow & 127) * 128;
#pragma unroll
                    for (int i = 0; i < 2; i++) {
                        *reinterpret_cast<uint4*>(p + i * 128 + (((lane ^ xrow ^ i) & 7) << 4)) =
                            make_uint4(badd(bmul(v[8 * i], a.x), c.x), badd(bmul(v[8 * i + 1], a.y), c.y),
                                       badd(bmul(v[8 * i + 2], a.z), c.z), badd(bmul(v[8 * i + 3], a.w), c.w));
#pragma unroll
                        for (int k = 0; k < 4; k++) v[8 * i + k] = v[8 * i + 4 + k];
                    }
                    __syncwarp();
                    mbar_arrive_if(sb + BAR_DONE, lane == 0 && q == 3);
                }
            }
            if (ODD || !first) {
                if (q == 0) img_store_global<0>(prev_img, toff, prev, s0, s1);
                if (q == 1) img_store_global<1>(prev_img, toff, prev, s0, s1);
                if (q == 2) img_store_global<2>(prev_img, toff, prev, s0, s1);
                if (q == 3) img_store_global<3>(prev_img, toff, prev, s0, s1);
            }
        }
        wg_wait<0>();
        release_if(eb, as, rel && !(ODD && (q & 1) && t == 5));
        if (ODD) release_if(eb, ws, rel && t != 1);
    }
    reg_fence(acc);
    return false;
}

__device__ __forceinline__ void qk_issue(float (&s)[64], uint32_t q, uint32_t k) {
    wg_fence();
    wgmma_ss128_init<0>(s, q, k, HI_Q, HI_IMG);
#pragma unroll
    for (int i = 1; i < 8; i++) wgmma_ss128<0>(s, q + (i >> 2) * 1024 + (i & 2) * 16 + (i & 1) * 2, k + (i >> 1) * 32 + (i & 1) * 2, 1, HI_Q, HI_IMG);
    wg_commit();
}
__device__ __forceinline__ void qk_issue(float (&s)[32], uint32_t q, uint32_t k) {
    wg_fence();
    wgmma_ss64_init<0>(s, q, k, HI_Q, HI_IMG);
#pragma unroll
    for (int i = 1; i < 8; i++) wgmma_ss64<0>(s, q + (i >> 2) * 1024 + (i & 2) * 16 + (i & 1) * 2, k + (i >> 1) * 32 + (i & 1) * 2, 1, HI_Q, HI_IMG);
    wg_commit();
}
__device__ __forceinline__ void pv_issue(float (&o)[64], const uint32_t (&p)[32], uint32_t v, int acc, bool half) {
    if (half) {
        asm volatile("// half" ::: "memory");
        wg_fence();
#pragma unroll
        for (int i = 0; i < 4; i++) wgmma_rs128(o, p[4 * i], p[4 * i + 1], p[4 * i + 2], p[4 * i + 3], v + i * 256, i ? 1 : acc, HI_IMG);
        wg_commit();
        asm volatile("// half" ::: "memory");
    } else {
        wg_fence();
#pragma unroll
        for (int i = 0; i < 8; i++) wgmma_rs128(o, p[4 * i], p[4 * i + 1], p[4 * i + 2], p[4 * i + 3], v + i * 256, i ? 1 : acc, HI_IMG);
        wg_commit();
    }
}
__device__ __forceinline__ void tri_mask(float (&s)[64], float x) {
#pragma unroll
    for (int k = 0; k < 16; k++) {
        float b;
        asm("sub.sat.f32 %0, %1, %2;" : "=f"(b) : "f"((float)(8 * (k >> 1) + (k & 1))), "f"(x));
        const int i = 32 + 4 * (k >> 1) + (k & 1);
        asm("fma.rn.f32 %0, %1, 0fFF61B1E6, %0;" : "+f"(s[i]) : "f"(b));
        if (k < 14) asm("fma.rn.f32 %0, %1, 0fFF61B1E6, %0;" : "+f"(s[i + 6]) : "f"(b));
    }
}
__device__ __forceinline__ void tri_mask_copy(float (&s)[64], const float (&h)[32], float x) {
#pragma unroll
    for (int i = 0; i < 32; i++) {
        asm("{\n.reg .pred p;\nsetp.lt.f32 p, %2, %3;\nselp.f32 %0, 0fFF800000, %1, p;\n}"
            : "=f"(s[i]) : "f"(h[i]), "f"(x), "f"((float)(8 * (i >> 2) - 4 * (i & 2) + (i & 1))));
        s[32 + i] = __uint_as_float(0xff800000u);
    }
}
constexpr float SM_HI = 1152921504606846976.f, SM_LO = 1.f / 1152921504606846976.f;
__device__ __forceinline__ bool softmax_unsafe(float t0, float t1, bool first) {
    bool bad = __any_sync(0xffffffffu, fmaxf(t0, t1) > SM_HI);
    if (first) {
        uint32_t a = __ballot_sync(0xffffffffu, t0 >= SM_LO), b = __ballot_sync(0xffffffffu, t1 >= SM_LO);
        a |= a >> 1;
        b |= b >> 1;
        bad |= ((a | (a >> 2)) & (b | (b >> 2)) & 0x11111111u) != 0x11111111u;
    }
    return bad;
}
__device__ __forceinline__ void softmax_shift(float (&s)[64], float d0, float d1) {
#pragma unroll
    for (int i = 0; i < 64; i++) s[i] -= (i & 2) ? d1 : d0;
}
__device__ __forceinline__ void softmax_remax(float (&s)[64], float (&m)[2], bool first, float& a0, float& a1) {
    float m0 = fmaxf(s[0], s[1]), m1 = fmaxf(s[2], s[3]);
#pragma unroll
    for (int k = 1; k < 16; k++) {
        m0 = fmaxf(m0, fmaxf(s[4 * k], s[4 * k + 1]));
        m1 = fmaxf(m1, fmaxf(s[4 * k + 2], s[4 * k + 3]));
    }
    m0 = fmaxf(m0, __shfl_xor_sync(0xffffffffu, m0, 1));
    m1 = fmaxf(m1, __shfl_xor_sync(0xffffffffu, m1, 1));
    m0 = fmaxf(m0, __shfl_xor_sync(0xffffffffu, m0, 2));
    m1 = fmaxf(m1, __shfl_xor_sync(0xffffffffu, m1, 2));
    if (!first) {
        m0 = fmaxf(m0, 0.f);
        m1 = fmaxf(m1, 0.f);
    }
    a0 = first ? 1.f : ex2(-m0);
    a1 = first ? 1.f : ex2(-m1);
    m[0] += m0;
    m[1] += m1;
    softmax_shift(s, m0, m1);
}
template <int J0, int J1>
__device__ __forceinline__ void softmax_exp(const float (&s)[64], uint32_t (&p)[32], float (&t)[4]) {
#pragma unroll
    for (int k = J0; k < J1; k++) {
        const float e0 = ex2(s[4 * k]), e1 = ex2(s[4 * k + 1]), e2 = ex2(s[4 * k + 2]), e3 = ex2(s[4 * k + 3]);
        if (k == 0) { t[0] = e0; t[1] = e1; t[2] = e2; t[3] = e3; }
        else { t[0] += e0; t[1] += e1; t[2] += e2; t[3] += e3; }
        p[2 * k] = pack2(e0, e1);
        p[2 * k + 1] = pack2(e2, e3);
    }
}
__device__ __forceinline__ void fma8(float (&acc)[8], float a, uint4 w) {
    acc[0] = fmaf(a, bf_lo(w.x), acc[0]); acc[1] = fmaf(a, bf_hi(w.x), acc[1]);
    acc[2] = fmaf(a, bf_lo(w.y), acc[2]); acc[3] = fmaf(a, bf_hi(w.y), acc[3]);
    acc[4] = fmaf(a, bf_lo(w.z), acc[4]); acc[5] = fmaf(a, bf_hi(w.z), acc[5]);
    acc[6] = fmaf(a, bf_lo(w.w), acc[6]); acc[7] = fmaf(a, bf_hi(w.w), acc[7]);
}
__device__ __forceinline__ void mma16816(float (&d)[4], const uint32_t* a, uint32_t b0, uint32_t b1) {
    asm("mma.sync.aligned.m16n8k16.row.col.f32.bf16.bf16.f32 {%0, %1, %2, %3}, {%4, %5, %6, %7}, {%8, %9}, {%0, %1, %2, %3};"
        : "+f"(d[0]), "+f"(d[1]), "+f"(d[2]), "+f"(d[3]) : "r"(a[0]), "r"(a[1]), "r"(a[2]), "r"(a[3]), "r"(b0), "r"(b1));
}
__device__ __forceinline__ uint2 best_key(const uint32_t* keys, int lane, uint32_t ep, uint32_t cur, int enough) {
#pragma unroll 1
    for (;;) {
        const uint4 k = ld_poll(reinterpret_cast<const uint4*>(keys) + lane);
        const bool ok = (((k.x ^ ep) | (k.y ^ ep) | (k.z ^ ep) | (k.w ^ ep)) & 31) == 0;
        const uint32_t best = __reduce_max_sync(0xffffffffu, ok ? max(max(k.x, k.y), max(k.z, k.w)) : 0u);
        const int n = __popc(__ballot_sync(0xffffffffu, ok));
        if (n == 32 || (n >= enough && best != cur)) return make_uint2(best, n == 32);
        __nanosleep(KSLEEP);
    }
}

__global__ void __cluster_dims__(2, 1, 1) __launch_bounds__(384, 1)
fused_kernel(const __grid_constant__ CUtensorMap tm_ckv, const __grid_constant__ CUtensorMap tm_wq,
             const __grid_constant__ CUtensorMap tm_wuk, const __grid_constant__ CUtensorMap tm_wuv,
             const __grid_constant__ CUtensorMap tm_wo, const __grid_constant__ CUtensorMap tm_wg,
             const __grid_constant__ CUtensorMap tm_wu,
             const __grid_constant__ CUtensorMap tm_wm, const __grid_constant__ CUtensorMap tm_x, const Params P) {
    extern __shared__ __align__(1024) uint8_t smem[];
    const uint32_t sb = (uint32_t)__cvta_generic_to_shared(smem);
    const int tid = threadIdx.x, lane = tid & 31, warp = __shfl_sync(0xffffffffu, tid >> 5, 0), wg = warp >> 2;
    const uint32_t sm = blockIdx.x < 8 ? blockIdx.x + 124 : blockIdx.x - 8, smq = ((sm - 64) * 147) >> 11;
    const int rb = sm < 64 ? (sm & 14) * 8 + (sm >> 4) * 2 + (sm & 1)
                 : sm < 120 ? ((sm - 64 - smq * 14) & 14) * 8 + 24 + smq * 2 + (sm & 1) : sm < 124 ? sm + 8 : sm - 116;
    const int grp = rb >> 3, j = rb & 7, cq = j & 3, kh = grp & 1, ort = (grp & 14) + (j >> 2);
    if (warp == 0) TS(0);

    if (lane == 0) {
        if (warp == 8) {
            asm volatile("prefetch.tensormap [%0];" ::"l"(rb >= NCTA ? &tm_wm : (j & 1) ? &tm_wuv : &tm_wuk) : "memory");
            asm volatile("prefetch.tensormap [%0];" ::"l"(&tm_ckv) : "memory");
            *reinterpret_cast<uint2*>(smem + SM_EP + 16) = make_uint2(0, 0);
        }
        const u64 cnt = (warp < 5 ? (rb < NCTA ? 0x844444441111111ull : 0x888888881111111ull) : warp < 10 ? 0x111111188888888ull : 0x118121ull) >> (12 * (warp % 5));
#pragma unroll
        for (int i = 0; i < 3; i++) mbar_init(sb + SM_BAR + 24 * warp + 8 * i, ((uint32_t)cnt >> (4 * i)) & 15);
        fence_async_smem();
        asm volatile("fence.mbarrier_init.release.cluster;" ::: "memory");
    }
    __syncthreads();
    asm volatile("barrier.cluster.arrive.relaxed.aligned;\nbarrier.cluster.wait.aligned;" ::: "memory");

    if (rb >= NCTA) {
        float* sc = reinterpret_cast<float*>(smem + 6 * SLOT);
        float* red = sc + 512;
        uint32_t ph = 0x7f, sl = 0;
        if (warp == 8) {
#pragma unroll 1
            for (int i = 0; i < 24; i++) {
                slot_acquire(sb, ph, sl);
                tma2d(sb + sl * SLOT, &tm_wm, (i >> 3) * 1024 + (rb - NCTA) * 256, (i & 7) * 64, sb + BAR_FULL + 8 * sl, HINT & 64);
                if (++sl == 6) sl = 0;
            }
#pragma unroll 1
            for (int i = 0; i <= NFFN / NSPARE; i++) {
                const int b = (rb - NCTA) * (NFFN / NSPARE) + i;
                if (i < NFFN / NSPARE) {
                    asm volatile("cp.async.bulk.wait_group.read 0;" ::: "memory");
                    uint32_t done = 0x7f;
                    slot_acquire(sb, done, i & 1);
#pragma unroll 1
                    for (int k = 0; k < 4; k++) tma2d(sb + (i & 1) * SLOT + k * 8192, k < 2 ? &tm_wg : &tm_wu, b * 16, (k & 1) * 256, sb + BAR_FULL + 8 * (i & 1), (HINT & 128) && (i & 3) == 3);
                }
                if (i) {
                    mbar_wait(sb + BAR_FULL + 8 * (~i & 1), ((i - 1) >> 1) & 1);
                    bulk_store(g_wf + (b - 1) * SLOT, sb + (~i & 1) * SLOT, SLOT, HINT & 256);
                    asm volatile("cp.async.bulk.commit_group;" ::: "memory");
                }
            }
            asm volatile("cp.async.bulk.wait_group 0;" ::: "memory");
            fence_async_global();
            TS(4);
        } else if (warp < 8) {
            const uint32_t c2 = __ldg(reinterpret_cast<const uint32_t*>(P.c) + tid), ep = __ldcg(&g_sync.epoch[0]) + 1;
            sc[2 * tid] = rbf(bf_lo(c2) * sigmoid(bf_lo(c2)));
            sc[2 * tid + 1] = rbf(bf_hi(c2) * sigmoid(bf_hi(c2)));
            ph = 0;
#pragma unroll 1
            for (int ps = 0; ps < 3; ps++) {
                bar_sync(1, 256);
                float acc[8] = {0.f, 0.f, 0.f, 0.f, 0.f, 0.f, 0.f, 0.f};
#pragma unroll 1
                for (int bt = 0; bt < 8; bt++) {
                    slot_wait(sb + BAR_FULL, ph, sl);
#pragma unroll 4
                    for (int i = 0; i < 8; i++)
                        fma8(acc, sc[bt * 64 + warp * 8 + i], *reinterpret_cast<const uint4*>(smem + sl * SLOT + (warp * 8 + i) * 512 + lane * 16));
                    __syncwarp();
                    mbar_arrive_if(sb + BAR_EMPTY + 8 * sl, lane == 0);
                    if (++sl == 6) sl = 0;
                }
                *reinterpret_cast<float4*>(red + warp * 256 + lane * 8) = make_float4(acc[0], acc[1], acc[2], acc[3]);
                *reinterpret_cast<float4*>(red + warp * 256 + lane * 8 + 4) = make_float4(acc[4], acc[5], acc[6], acc[7]);
                bar_sync(1, 256);
                float v = 0.f;
#pragma unroll
                for (int i = 0; i < 8; i++) v += red[i * 256 + tid];
                if (ps == 0) st_pub(g_mod1 + (rb - NCTA) * 256 + tid, (pack2(0.f, v) & 0xffff0000u) | (ep & 0xffffu), true);
                else g_mod[ps * 1024 + (rb - NCTA) * 256 + tid] = __float2bfloat16_rn(v);
                if (warp == 0) TS(1 + ps);
            }
        }
        __syncthreads();
        if (tid < 2) flag_add(&g_sync.cnt[7 * 8]);
        return;
    }

    if (wg == 2) {
        asm volatile("setmaxnreg.dec.sync.aligned.u32 40;");
        const CUtensorMap* tw = (j & 1) ? &tm_wuv : &tm_wuk;
        if (warp == 8) {
            const uint32_t rank = j & 1, half = rank * 16384;
            uint32_t eph = 0x7f, r = 0;
#pragma unroll 1
            for (int hp = 0; hp < 2; hp++) {
                uint32_t wtab = w_table(hp), atab = a_table(hp);
                const int hc = 4 * grp + 2 * hp;
#pragma unroll 1
                for (int u = 0; u < 16; u++) {
                    if (u < 4) {
                        const uint32_t ws = (wtab >> (4 * u)) & 15;
                        slot_acquire(sb, eph, ws);
                        load_tile(sb, ws, 0, tw, u * 128, hc, false, HINT & 1);
                        PT();
                    }
                    if (hp == 1 && (u & 7) == 4) mbar_wait(sb + BAR_FLAG + 24 + (u & 8), 0);
                    const uint32_t as = a_next(atab);
                    slot_acquire(sb, eph, as);
                    load_tile(sb, as, half, &tm_ckv, ((u & 12) + (j >> 1)) * 128, (u & 3) * 2 + rank, true, (HINT & 8) && hp);
                    PT();
                    if (hp == 1 && (u | 2) == 3 && lane == 0)
                        asm volatile("red.relaxed.gpu.global.add.u32 [%0], 1;" ::"l"(&g_sync.cnt[(grp * 8 + 3 + (u >> 1)) * 8]) : "memory");
                }
                const uint8_t* src = g_h + (15 - j) * 4 * SLOT;
#pragma unroll 1
                for (int u = 0; u < 8; u++) {
                    if ((u & 3) == 0) {
                        mbar_wait(sb + BAR_FLAG + (2 + 8 * hp) * u, 0);
                        fence_async_global();
                    }
                    if (u < 4) {
                        const uint32_t ws = (wtab >> (4 * u)) & 15;
                        slot_acquire(sb, eph, ws);
                        load_tile(sb, ws, half, &tm_wq, u * 128, hc + rank, true, HINT & 1);
                        PT();
                    }
                    const uint32_t as = a_next(atab);
                    slot_acquire(sb, eph, as);
                    load_bulk(sb, as, 0, src, SLOT, false, (HINT & 8) && hp);
                    PT();
                    src += u == 3 ? (8 * j - 63) * SLOT : SLOT;
                }
                const int step = hp ? -2 * SLOT : 2 * SLOT;
                src = g_KV + (size_t)(grp * 32 + 30 * hp) * SLOT + half - step;
#pragma unroll 1
                for (int n = 0; n <= 17; n++) {
                    if (n == 8) {
                        mbar_wait(sb + BAR_FLAG + 16 + 32 * hp, 0);
                        fence_async_global();
                    }
                    const uint8_t* v = src + SLOT;
                    src += n < 16 - j ? step : n == 16 - j ? (2 * j - 15) * step : -step;
                    if (n < 17) {
                        slot_acquire(sb, eph, r);
                        if (n != 15 - (j & 6)) load_bulk(sb, r, half, src, SLOT / 2, true, (HINT & 4) && (hp || !(HINT & 32)));
                        else load_bulk(sb, r, 0, src - half, SLOT, false, (HINT & 4) && (hp || !(HINT & 32)));
                        PT();
                        r = ring_next(r);
                    }
                    if (n) {
                        slot_acquire(sb, eph, r);
                        if (n != 16 - (j & 6)) load_bulk(sb, r, half, v, SLOT / 2, true, (HINT & 4) && (hp || !(HINT & 32)));
                        else load_bulk(sb, r, 0, v - half, SLOT, false, (HINT & 4) && (hp || !(HINT & 32)));
                        PT();
                        r = ring_next(r);
                    }
                    asm volatile("st.volatile.shared.u32 [%0], %1;" ::"r"(sb + SM_EP + 16), "r"(18 * hp + n + 1) : "memory");
                }
            }
            uint32_t otab = O_TABLE, ready = 0;
#pragma unroll 1
            for (int i = 0; i < 17; i++) {
                const bool dyn = i >= 8 && i < 15;
                const uint32_t want = dyn ? 15u << (4 * (i - 8)) : 1u << max(i + 14, 28);
                if (!(ready & want)) {
                    do {
                        asm volatile("ld.acquire.cta.shared.u32 %0, [%1];" : "=r"(ready) : "r"(sb + SM_EP + 20) : "memory");
                        ready = __shfl_sync(0xffffffffu, ready, 0);
                    } while (!(ready & want));
                    fence_async_global();
                }
                const int head = o_head(dyn ? (ready >> (4 * (i - 8))) & 15 : i, kh);
                const uint32_t as = o_next(otab), ws = o_next(otab), off = i < 15 ? half : kh * 16384;
                slot_acquire(sb, eph, as);
                load_bulk(sb, as, off, g_ctx + (size_t)(ort * 32 + head) * SLOT + off, SLOT / 2, i < 15, HINT & 16);
                if (i == 15) load_tile(sb, as, off ^ 16384, &tm_x, ort * 128 + kh * 64, cq * 2, false, false);
                if (i == 16) load_bulk(sb, as, off ^ 16384, P.wdown + min(rb, NFFN - 1) * 8192, SLOT / 2, false, false);
                PT();
                slot_acquire(sb, eph, ws);
                load_tile(sb, ws, 0, &tm_wo, head * 128, cq * 2, false, HINT & 2);
                PT();
                if (i == 0) o_next(otab);
            }
            if (rb < NFFN) {
                slot_acquire(sb, eph, 5);
                load_bulk(sb, 5, 0, g_wf + rb * SLOT, SLOT, false, false);
            }
        } else if (warp == 9) {
            l2_prefetch(P.ckv + rb * 2048, 4096);
            mbar_watch(sb + BAR_FULL, 0);
            l2_prefetch(P.ckv + 512 * 512 + rb * 2048, 4096);
            mbar_watch(sb + BAR_FULL + 8 * 4, 0);
            l2_prefetch(P.ckv + 1024 * 512 + rb * 4096, 8192);
            TS(40);
#pragma unroll 1
            for (int i = 0; i < 15; i++) {
                step_watch(sb + SM_EP + 16, i == 0 ? 0 : i < 5 ? PFA + i : 13 + PFB + i);
                if (i == 12) mbar_watch(sb + BAR_FLAG + 8 * 7, 0);
                const int rf = min(rb, NFFN - 1);
                const uint8_t* p = i == 3 ? reinterpret_cast<const uint8_t*>(P.ckv) + rb * 16384
                                 : i == 4 ? g_h + rb * 16384
                                 : i < 9 ? g_ctx + (size_t)(ort * 32 + o_head(cq + 2 * ((i - 5) & 2), kh)) * SLOT + (i & 1) * 16384
                                 : i < 11 ? reinterpret_cast<const uint8_t*>(P.wo) + (grp * 16 + (~i & 1) * 8 + j) * 16384
                                 : i == 11 ? reinterpret_cast<const uint8_t*>(P.x) + rb * 16384
                                 : i == 12 ? reinterpret_cast<const uint8_t*>(P.wdown) + rf * 16384 : g_wf + rf * SLOT + (i & 1) * 16384;
                if (i < 3) tma3d_prefetch(i == 1 ? tw : &tm_wq, (j >> 1) * 128, grp * 4 + (i == 1 ? 2 : i + (j & 1)));
                else l2_prefetch(p, 16384);
            }
            const uint32_t v = lds32(sb + SM_EP) - 1;
            sts128(sb + SM_RED + lane * 16, make_uint4(v, v, v, v));
            fence_async_smem();
            __syncwarp();
#pragma unroll 1
            for (int i = 0; i < OB / 32; i++) bulk_store(g_out + rb * OB + i * 32, sb + SM_RED, 512, false);
            asm volatile("cp.async.bulk.commit_group;\ncp.async.bulk.wait_group 0;" ::: "memory");
            fence_async_global();
            __syncwarp();
            mbar_arrive_if(sb + BAR_PF, lane == 0);
            if (lane == 0) mbar_watch(sb + BAR_END, 0);
        } else {
            const uint32_t ep = __ldcg(&g_sync.epoch[0]) + 1;
            asm volatile("st.shared.u32 [%0], %1;" ::"r"(sb + SM_EP), "r"(ep) : "memory");
            mbar_wait(sb + BAR_FULL + 8 * 4, 0);
            {
                uint4 v[4];
                for (;;) {
                    uint32_t bad = 0;
#pragma unroll
                    for (int k = 0; k < 4; k++) v[k] = ld_poll(reinterpret_cast<const uint4*>(g_mod1) + (warp & 1) * 128 + k * 32 + lane);
#pragma unroll
                    for (int k = 0; k < 4; k++) bad |= (v[k].x ^ ep) | (v[k].y ^ ep) | (v[k].z ^ ep) | (v[k].w ^ ep);
                    if (__all_sync(0xffffffffu, (bad & 0xffff) == 0)) break;
                    __nanosleep(100);
                }
                const uint32_t one = (warp & 1) ? ONE2 : 0x80008000u;
#pragma unroll
                for (int k = 0; k < 4; k++)
                    *reinterpret_cast<uint2*>(smem + SM_TAB + (warp & 1) * 1024 + k * 256 + lane * 8) =
                        make_uint2(badd(__byte_perm(v[k].x, v[k].y, 0x7632), one), badd(__byte_perm(v[k].z, v[k].w, 0x7632), one));
            }
            __syncwarp();
            mbar_arrive_if(sb + BAR_FLAG + 8 * 8, lane == 0);
            if (warp == 10) {
#pragma unroll 1
                for (int i = 0; i < 9; i++) {
                    mbar_sleep(sb + BAR_DONE + 8 * i);
                    if (lane == 0) flag_add(i && ((i - 1) & 2) ? &g_sync.ctxcnt[((i & 1) ? 15 - j : j) * 32 + 2 * grp + (i > 4)] : &g_sync.cnt[(grp * 8 + i) * 8]);
                    if (i == 0) TS(43);
                }
            } else {
                TS(42);
#pragma unroll 1
                for (int i = 0; i < 8; i++) {
                    mbar_sleep(sb + BAR_DONE + 8 * (i == 7 ? 6 : i == 4 ? 3 : i));
                    if (lane < 2) flag_wait(&g_sync.cnt[((i == 0 ? (lane ? j : 15 - j) : i == 7 ? 0 : grp) * 8 + i) * 8], 8 * ep);
                    __syncwarp();
                    mbar_arrive_if(sb + BAR_FLAG + 8 * i, lane == 0 && i < 7);
                    TS(48 + i);
                }
                const uint32_t *mp = reinterpret_cast<const uint32_t*>(g_mod) + lane, *wp = reinterpret_cast<const uint32_t*>(P.wr) + lane;
                float ra = 0.f, rs = 0.f;
#pragma unroll 1
                for (int k = 0; k < 256; k += 32) {
                    const uint32_t ga = __ldcg(mp + 512 + k), sh = __ldcg(mp + 768 + k), c1 = badd(__ldcg(mp + 1024 + k), ONE2);
                    const uint32_t gb = __ldcg(mp + 1280 + k), ww = __ldg(wp + k);
                    const float a0 = bf_lo(c1) * bf_lo(ww), a1 = bf_hi(c1) * bf_hi(ww);
                    ra += a0 + a1;
                    rs = fmaf(bf_lo(sh), bf_lo(ww), fmaf(bf_hi(sh), bf_hi(ww), rs));
                    if (k >> 6 == cq) {
                        sts128(sb + SM_TAB + ((k & 32) + lane) * 16, make_uint4(ga << 16, ga & 0xffff0000u, __float_as_uint(a0), __float_as_uint(a1)));
                        sts128(sb + SM_TAB + 1024 + ((k & 32) + lane) * 16, make_uint4(c1, sh, gb, 0));
                    }
                }
#pragma unroll 1
                for (int o = 16; o > 0; o >>= 1) {
                    ra += __shfl_xor_sync(0xffffffffu, ra, o);
                    rs += __shfl_xor_sync(0xffffffffu, rs, o);
                }
                *reinterpret_cast<float2*>(smem + SM_EP + 8) = make_float2(ra, rs);
                __syncwarp();
                mbar_arrive_if(sb + BAR_FLAG + 8 * 7, lane == 0);
                const uint32_t* f = &g_sync.ctxcnt[ort * 32 + o_head(min(lane, 16), kh)];
                uint32_t ready = -(j & 1), list = 0, sh = 0, qa;
                asm("mapa.shared::cluster.u32 %0, %1, %2;" : "=r"(qa) : "r"(sb + SM_EP + 20), "r"(lane & 1));
                while (ready != ~0u) {
                    uint32_t v;
                    asm volatile("ld.acquire.gpu.global.u32 %0, [%1];" : "=r"(v) : "l"(f) : "memory");
                    const uint32_t now = __ballot_sync(0xffffffffu, (int)(v - ep) >= 0);
#pragma unroll 1
                    for (uint32_t fresh = now & ~ready & 0x7f00; fresh; fresh &= fresh - 1, sh += 4) list |= (__ffs(fresh) - 1) << sh;
                    list |= (((now & 0xff) + 1) >> 8 << 28) | ((now & 0x18000) << 14);
                    if (now != ready && lane < 2) asm volatile("st.relaxed.cluster.shared::cluster.u32 [%0], %1;" ::"r"(qa), "r"(list) : "memory");
                    if ((now & 0xff) == 0xff) mbar_sleep(sb + BAR_DONE + 8 * 7);
                    ready = now;
                    __nanosleep(POLL_NS);
                }
                TS(45);
            }
        }
    } else {
        asm volatile("setmaxnreg.inc.sync.aligned.u32 232;");
        const bool elected = (tid & 127) == 0, rel = (tid & 95) == 0;
        uint32_t eb;
        asm("mapa.shared::cluster.u32 %0, %1, %2;" : "=r"(eb) : "r"(sb + BAR_EMPTY), "r"(warp & 1));
        const int g = lane >> 2, c4 = lane & 3;
        const uint32_t toff = warp * 4096 + g * 64 + ((c4 ^ (g >> 1)) << 4);
        uint32_t fph = 0, r = 0;
        if (wg == 1) bar_arrive(1, 256);
        const uint32_t kd = desc_k(sb), wd = desc_mn(sb), vd = ((sb & 0x3ffff) >> 4) | (32u << 16);
        const int nL = 16 - j, hn = nL - 1 + wg;
        float s[64], o[64], li[2] = {0.f, 0.f};
        uint8_t* cimg = g_ctx;
        uint32_t p[32] = {};
#pragma unroll 1
        for (int hp = 0; hp < 2; hp++) {
            float m[2] = {0.f, 0.f}, l[2] = {0.f, 0.f}, t[4] = {0.f, 0.f, 0.f, 0.f};
            bool shifted = false, bad = false, plain = false;
            uint32_t qa = desc_k(sb + 5 * SLOT + (wg ^ 1) * 8192);
            uint8_t* limg = g_ctx + (size_t)((15 - j) * 32 + 2 * grp + hp) * SLOT;
            {
                const int step = hp ? -8 * SLOT : 8 * SLOT;
                uint8_t* img = g_KV + (size_t)(grp * 32 + (hp ? j ^ 30 : j)) * SLOT - step;
                const float sc = (j & 1) ? 1.f : SM_C;
                const uint32_t wtab = w_table(hp);
                uint32_t atab = hp ? 0x562u : a_table(0);
#pragma unroll 1
                for (int u = 0;; u += 2) {
                    proj_tile<false>(s, o, u, u ? 0 : hp, sb, wg, eb, rel, fph, wtab, atab, u ? img : cimg, toff, u ? sc : li[0], u ? sc : li[1], (hp | u) == 0, P.x, rb * 16 + warp * 2, p);
                    __syncwarp();
                    mbar_arrive_if(sb + BAR_DONE + 4 * u + 32 * hp, lane == 0 && (hp | u) != 0);
                    if (elected) TS(1 + 10 * hp + u + 20 * wg);
                    if (proj_tile<true>(o, s, u + 1, 0, sb, wg, eb, rel, fph, wtab, atab, img + step, toff, sc, sc, (hp | u) == 0, P.x, rb * 16 + warp * 2, p)) break;
                    if (elected) TS(2 + 10 * hp + u + 20 * wg);
                    img += 2 * step;
                }
            }
            if (elected) TS(6 + 10 * hp + 20 * wg);
            int n = -1;
#pragma unroll 1
            for (;;) {
                while (bad || plain) {
                    if (bad) {
                        float a0, a1;
                        softmax_remax(s, m, n == 0 || n == nL, a0, a1);
                        shifted = true;
                        l[0] *= a0;
                        l[1] *= a1;
#pragma unroll
                        for (int i = 0; i < 64; i++) o[i] *= (i & 2) ? a1 : a0;
                    }
                    softmax_exp<0, 16>(s, p, t);
                    t[0] += t[1];
                    t[2] += t[3];
                    bad = !bad && softmax_unsafe(t[0], t[2], false);
                    plain = false;
                }
#pragma unroll 1
                do {
                    l[0] += t[0];
                    l[1] += t[2];
                    if (++n > 16) break;
                    const uint32_t ks = r;
                    uint32_t vs = ring_next(r);
                    r = ring_next(vs);
                    bar_sync(1 + wg, 256);
                    const float x = (float)((warp & 3) * 16 + g - 2 * c4);
                    if (n == hn) {
                        float sh[32];
                        qk_issue(sh, qa, kd + ks * (SLOT / 16));
                        slot_wait(sb + BAR_FULL, fph, vs);
                        pv_issue(o, p, vd + vs * (SLOT / 16), 1, false);
                        bar_arrive(2 - wg, 256);
                        wg_wait<1>();
                        reg_fence(sh);
                        tri_mask_copy(s, sh, x);
                        release_if(eb, ks, rel);
                        release_if(eb, 5 + wg, rel && (!wg || n == 16));
                        if (!wg) {
                            qa += SLOT / 16;
                            fence_async_smem();
                            if (shifted) softmax_shift(s, m[0], m[1]);
                        }
                        float e[4 * EARLY];
#pragma unroll
                        for (int i = 0; i < 4 * EARLY; i++) {
                            e[i] = ex2(s[i]);
                            t[i & 3] = i < 4 ? e[i] : t[i & 3] + e[i];
                        }
                        reg_fence(e);
                        slot_wait(sb + BAR_FULL, fph, r);
                        wg_wait<0>();
                        reg_fence(o);
                        reg_fence(e);
                        release_if(eb, vs, rel);
#pragma unroll
                        for (int i = 0; i < 2 * EARLY; i++) p[i] = pack2(e[2 * i], e[2 * i + 1]);
                        softmax_exp<EARLY, 8>(s, p, t);
                        if (wg) {
                            ctx_store<true>(limg, toff, o, l[0], l[1]);
                            __syncwarp();
                            mbar_arrive_if(sb + BAR_DONE + 24 + 32 * hp, lane == 0);
                            l[0] = l[1] = m[0] = m[1] = 0.f;
                            shifted = false;
                        }
                        t[0] += t[1];
                        t[2] += t[3];
                        bad = softmax_unsafe(t[0], t[2], wg);
                        continue;
                    }
                    if (n == 0 || n == nL) {
                        qk_issue(s, qa, kd + ks * (SLOT / 16));
                        if (n == 0) {
                            r = vs;
                            vs = 4 - hp;
                            slot_wait(sb + BAR_FULL, fph, 6);
                            gemm_issue<false>(o, qa + SLOT / 16, wd + vs * (SLOT / 16), 1, false);
                        } else {
                            slot_wait(sb + BAR_FULL, fph, vs);
                            pv_issue(o, p, vd + vs * (SLOT / 16), 1, true);
                        }
                        bar_arrive(2 - wg, 256);
                        const float i0 = n ? rcp(quad_sum(l[0])) : 1.f, i1 = n ? rcp(quad_sum(l[1])) : 1.f;
                        wg_wait<1>();
                        reg_fence(s);
                        release_if(eb, ks, rel);
                        release_if(eb, 6, rel && n == 16);
                        tri_mask(s, n ? x : 64.f);
                        float e[4 * EARLY];
#pragma unroll
                        for (int i = 0; i < 4 * EARLY; i++) {
                            e[i] = ex2(s[i]);
                            t[i & 3] = i < 4 ? e[i] : t[i & 3] + e[i];
                        }
                        reg_fence(e);
                        reg_fence(s);
                        reg_fence(t);
                        slot_wait(sb + BAR_FULL, fph, r);
                        if (SF & 1) sched_fence(fph, P.zero);
                        wg_wait<0>();
                        reg_fence(o);
                        reg_fence(e);
                        release_if(eb, vs, rel);
#pragma unroll
                        for (int i = 0; i < 2 * EARLY; i++) p[i] = pack2(e[2 * i], e[2 * i + 1]);
                        softmax_exp<EARLY, MSPLIT>(s, p, t);
                        tile_store(limg, sb + 6 * SLOT, toff, o, i0, i1, n);
                        reg_fence(t);
                        if (SF & 2) sched_fence(fph, P.zero);
                        reg_fence(s);
                        softmax_exp<MSPLIT, 16>(s, p, t);
                        __syncwarp();
                        mbar_arrive_if(sb + BAR_DONE + 24 + 32 * hp, lane == 0 && n);
                        l[0] = l[1] = m[0] = m[1] = 0.f;
                        shifted = false;
                        t[0] += t[1];
                        t[2] += t[3];
                        bad = __any_sync(0xffffffffu, fmaxf(t[0], t[2]) > SM_HI || fminf(t[0], t[2]) < SM_LO);
                        continue;
                    }
                    qk_issue(s, qa, kd + ks * (SLOT / 16));
                    slot_wait(sb + BAR_FULL, fph, vs);
                    pv_issue(o, p, vd + vs * (SLOT / 16), n != 1 && n != nL + 1, n == hn + 1);
                    bar_arrive(2 - wg, 256);
                    wg_wait<1>();
                    reg_fence(s);
                    release_if(eb, ks, rel);
                    release_if(eb, 6, rel && n == 16);
                    if (n == nL - 1) {
                        tri_mask(s, x);
                        release_if(eb, 5, rel);
                        qa += SLOT / 16;
                        fence_async_smem();
                    }
                    if (shifted) {
                        slot_wait(sb + BAR_FULL, fph, r);
                        wg_wait<0>();
                        reg_fence(o);
                        release_if(eb, vs, rel);
                        softmax_shift(s, m[0], m[1]);
                        plain = true;
                        break;
                    }
                    float e[4 * EARLY];
#pragma unroll
                    for (int i = 0; i < 4 * EARLY; i++) {
                        e[i] = ex2(s[i]);
                        t[i & 3] = i < 4 ? e[i] : t[i & 3] + e[i];
                    }
                    reg_fence(e);
                    slot_wait(sb + BAR_FULL, fph, r);
                    wg_wait<0>();
                    reg_fence(o);
                    reg_fence(e);
                    release_if(eb, vs, rel);
#pragma unroll
                    for (int i = 0; i < 2 * EARLY; i++) p[i] = pack2(e[2 * i], e[2 * i + 1]);
                    softmax_exp<EARLY, 16>(s, p, t);
                    t[0] += t[1];
                    t[2] += t[3];
                    bad = softmax_unsafe(t[0], t[2], false);
                } while (!bad);
                if (!bad && !plain) break;
            }
            const uint32_t vs = r, ga = desc_k(sb + (hp ? 2 * (wg ^ kh ^ 1) : wg) * 8192);
            r = ring_next(r);
            slot_wait(sb + BAR_FULL, fph, 5);
            slot_wait(sb + BAR_FULL, fph, r);
            bar_sync(1 + wg, 256);
            gemm_issue<true>(s, ga + 5 * (SLOT / 16), wd + r * (SLOT / 16), 0, hp);
            pv_issue(o, p, vd + vs * (SLOT / 16), j, hn == 16);
            bar_arrive(2 - wg, 256);
            li[0] = rcp(quad_sum(l[0]));
            li[1] = rcp(quad_sum(l[1]));
            cimg = limg + (ptrdiff_t)(2 * j - 15) * 32 * SLOT + (wg ? -16384 : 16384);
            wg_wait<1>();
            release_if(eb, 5, rel);
            release_if(eb, r, rel && hp);
            wg_wait<0>();
            release_if(eb, vs, rel);
            reg_fence(o);
            img_store_global<0>(cimg, toff, o, li[0], li[1]);
            if (elected) TS(8 + 10 * hp + 20 * wg);
        }
        uint32_t otab = 0x2351604u;
        const uint32_t oa = desc_k(sb + (wg ^ kh ^ 1) * 16384);
        const int t7 = tid & 127, w4 = warp & 3, row = ort * 128 + kh * 64 + w4 * 16 + g;
#pragma unroll 1
        for (int i = 1; i < 15 - wg; i++) {
            const uint32_t as = o_next(otab), ws = o_next(otab);
            slot_wait(sb + BAR_FULL, fph, as);
            slot_wait(sb + BAR_FULL, fph, ws);
            bar_sync(1 + wg, 256);
            gemm_issue<false>(s, oa + as * (SLOT / 16), wd + ws * (SLOT / 16), 1, true);
            bar_arrive(2 - wg, 256);
            wg_wait<1>();
            reg_fence(o);
            if (i == 1) img_store_global<1>(cimg, toff, o, li[0], li[1]);
            if (i == 2) {
                img_store_global<2>(cimg, toff, o, li[0], li[1]);
                img_store_global<3>(cimg, toff, o, li[0], li[1]);
                __syncwarp();
                mbar_arrive_if(sb + BAR_DONE + 64, lane == 0);
            }
            wg_wait<0>();
            release_if(eb, as, rel);
            release_if(eb, ws, rel);
        }
        mbar_wait(sb + BAR_PF, 0);
        const uint32_t ep = lds32(sb + SM_EP);
        uint32_t eb2 = sb + BAR_END;
        if (wg == 0) {
            reg_fence(s);
            if (elected) TS(9);
            TT(1);
#pragma unroll
            for (int v = 0; v < 8; v++)
                st_pub(g_out + rb * OB + v * 128 + t7, make_uint4((pack2(s[8 * v], s[8 * v + 1]) & ~1u) | (ep & 1), pack2(s[8 * v + 2], s[8 * v + 3]),
                                                                      pack2(s[8 * v + 4], s[8 * v + 5]), pack2(s[8 * v + 6], s[8 * v + 7])), true);
            constexpr uint32_t s1 = 5, s2 = 6;
            bar_sync(4, 256);
            uint32_t wf[64];
            float wn[64];
            if (rb < NFFN) {
                slot_wait(sb + BAR_FULL, fph, s1);
                const uint32_t a = sb + s1 * SLOT + (w4 * 128 + (lane >> 4) * 8 + (lane & 7)) * 32 + ((lane >> 3) & 1) * 16;
#pragma unroll
                for (int i = 0; i < 16; i++)
                    asm volatile("ldmatrix.sync.aligned.m8n8.x4.trans.shared.b16 {%0, %1, %2, %3}, [%4];"
                                 : "=r"(wf[4 * i]), "=r"(wf[4 * i + 1]), "=r"(wf[4 * i + 2]), "=r"(wf[4 * i + 3])
                                 : "r"(a + (i >> 3) * 16384 + (i & 7) * 512) : "memory");
                slot_wait(sb + BAR_FULL, fph, s2);
#pragma unroll
                for (int i = 0; i < 16; i++) {
                    const uint2 w = *reinterpret_cast<const uint2*>(smem + s2 * SLOT + (kh ^ 1) * 16384 + i * 1024 + t7 * 8);
                    wn[4 * i] = bf_lo(w.x); wn[4 * i + 1] = bf_hi(w.x); wn[4 * i + 2] = bf_lo(w.y); wn[4 * i + 3] = bf_hi(w.y);
                }
                reg_fence(wn);
            }
            const uint32_t gbf = __ldcg(reinterpret_cast<const uint32_t*>(g_mod) + 1280 + rb * 2 + (tid & 1));
            if (elected) TS(10);
            TT(2);
            float* sred = reinterpret_cast<float*>(smem + SM_RED);
            uint32_t best = ep ^ 1, all;
            bool fresh;
            do {
                if (warp == 0) {
                    const uint2 k = best_key(g_key + cq * 128, lane, ep, best, rb < NFFN ? SPEC : 32);
                    *reinterpret_cast<uint2*>(smem + SM_EP + 24) = k;
                    mbar_arrive_if(sb + BAR_BEST, lane == 0 && k.y);
                }
                bar_sync(3, 128);
                const uint2 k = *reinterpret_cast<const uint2*>(smem + SM_EP + 24);
                fresh = k.x != best;
                best = k.x;
                all = k.y;
                TT(3);
                if (!fresh || rb >= NFFN) break;
                const uint4* cp = g_cand + ((~best >> 9) & 127) * 192;
                uint4 cv[6];
                for (;;) {
                    uint32_t bad = 0;
#pragma unroll
                    for (int v = 0; v < 6; v++) cv[v] = ld_poll(cp + w4 * 24 + v * 4 + c4);
#pragma unroll
                    for (int v = 0; v < 6; v++) bad |= cv[v].w ^ ep;
                    if (__all_sync(0xffffffffu, bad == 0)) break;
                    if (CSLEEP) __nanosleep(CSLEEP);
                }
            TT(4);
                float d[4][4] = {};
#pragma unroll
                for (int k = 0; k < 8; k++) {
                    const uint32_t b0 = (&cv[(2 * k) / 3].x)[(2 * k) % 3], b1 = (&cv[(2 * k + 1) / 3].x)[(2 * k + 1) % 3];
                    mma16816(d[k & 1], wf + 4 * k, b0, b1);
                    mma16816(d[2 + (k & 1)], wf + 32 + 4 * k, b0, b1);
                }
                const float u = (c4 & 2) ? ((c4 & 1) ? d[2][2] + d[3][2] : d[2][0] + d[3][0]) : ((c4 & 1) ? d[0][2] + d[1][2] : d[0][0] + d[1][0]);
                sred[w4 * 32 + c4 * 8 + g] = u;
                bar_sync(3, 128);
                const float v = rbf((sred[lane] + sred[32 + lane]) + (sred[64 + lane] + sred[96 + lane]));
                const float act = rbf(rbf(v * sigmoid(v)) * __shfl_down_sync(0xffffffffu, v, 16));
                float y[4] = {0.f, 0.f, 0.f, 0.f};
#pragma unroll
                for (int k = 0; k < 16; k++) {
                    const float a = __shfl_sync(0xffffffffu, act, k);
#pragma unroll
                    for (int i = 0; i < 4; i++) y[i] = fmaf(a, wn[4 * k + i], y[i]);
                }
                st_pub(g_out + rb * OB + OB_Y + t7, make_uint4((__float_as_uint(y[0]) & ~15u) | (ep & 15), (__float_as_uint(y[1]) & ~127u) | ((best >> 9) & 127),
                                                               __float_as_uint(y[2]), __float_as_uint(y[3])), true);
            } while (!all);
            const int sel = (~best >> 5) & 2047;
            const int pq = (2 * rb + (tid & 1)) & 63, pv = (pq >> 2) / 3;
            const uint4* fp = g_cand + (sel >> 4) * 192 + (rb >> 5) * 24 + pv * 4 + (pq & 3);
            uint4 fh = {}, fx = {};
            if (rb == 0 && tid == 0) g_sync.epoch[0] = ep;
            if (elected) TS(60);
            TT(5);
            uint4 yv;
            if (warp == 0) { fh = ld_poll(fp); fx = ld_poll(fp + 96); }
            if (fresh && rb < NFFN) __nanosleep(YPRE);
            for (;;) {
                yv = ld_poll(g_out + min(t7, NFFN - 1) * OB + OB_Y + rb);
                if (__all_sync(0xffffffffu, (((yv.x ^ ep) & 15) | ((yv.y ^ (best >> 9)) & 127)) == 0)) break;
                if (YSLEEP) __nanosleep(YSLEEP);
            }
            if (elected) TS(61);
            TT(6);
            float y[4] = {0.f, 0.f, 0.f, 0.f};
            if (t7 < NFFN) { y[0] = __uint_as_float(yv.x); y[1] = __uint_as_float(yv.y); y[2] = __uint_as_float(yv.z); y[3] = __uint_as_float(yv.w); }
            const float z0 = ((lane & 16) ? y[2] : y[0]) + __shfl_xor_sync(0xffffffffu, (lane & 16) ? y[0] : y[2], 16);
            const float z1 = ((lane & 16) ? y[3] : y[1]) + __shfl_xor_sync(0xffffffffu, (lane & 16) ? y[1] : y[3], 16);
            float z = ((lane & 8) ? z1 : z0) + __shfl_xor_sync(0xffffffffu, (lane & 8) ? z0 : z1, 8);
            z += __shfl_xor_sync(0xffffffffu, z, 4);
            z = quad_sum(z);
            if ((lane & 7) == 0) sred[128 + (lane >> 3) * 4 + w4] = z;
            bar_sync(3, 128);
            if (tid < 2) {
                while (fh.w != ep || fx.w != ep) { fh = ld_poll(fp); fx = ld_poll(fp + 96); }
                const float4 y0 = *reinterpret_cast<const float4*>(sred + 128 + tid * 8), y1 = *reinterpret_cast<const float4*>(sred + 132 + tid * 8);
                const int cm = (pq >> 2) - 3 * pv;
                const uint32_t h2 = cm == 0 ? fh.x : cm == 1 ? fh.y : fh.z, x2 = cm == 0 ? fx.x : cm == 1 ? fx.y : fx.z;
                const float sg = sigmoid(bf_hi((best & 0x80000000u) ? (best ^ 0x80000000u) : ~best));
                reinterpret_cast<uint32_t*>(P.out)[sel * 256 + rb * 2 + tid] =
                    badd(x2, bmul(gbf, badd(h2, bmul(pack2((y0.x + y0.y) + (y0.z + y0.w), (y1.x + y1.y) + (y1.z + y1.w)), pack2(sg, sg)))));
            }
            if (elected) TS(62);
            TT(7);
        } else {
            const float4* tf = reinterpret_cast<const float4*>(smem + SM_TAB) + c4;
            const uint32_t xa = sb + 4 * SLOT + (kh ^ 1) * 16384 + (w4 * 16 + (lane & 15)) * 128;
            uint32_t x2[32];
            bar_sync(2, 256);
#pragma unroll 1
            for (int i = 14; i < 17; i++) {
                const uint32_t as = o_next(otab), ws = o_next(otab);
                slot_wait(sb + BAR_FULL, fph, as);
                slot_wait(sb + BAR_FULL, fph, ws);
                gemm_issue<false>(s, oa + as * (SLOT / 16), wd + ws * (SLOT / 16), 1, true);
                wg_wait<1>();
            }
            if (elected) TS(29);
            TT(1);
            {
#pragma unroll
                for (int k = 0; k < 8; k++)
                    asm volatile("ldmatrix.sync.aligned.m8n8.x4.shared.b16 {%0, %1, %2, %3}, [%4];"
                                 : "=r"(x2[4 * k]), "=r"(x2[4 * k + 1]), "=r"(x2[4 * k + 2]), "=r"(x2[4 * k + 3])
                                 : "r"(xa + (k >> 2) * 8192 + (((2 * (k & 3) + (lane >> 4)) ^ (lane & 7)) << 4)) : "memory");
            }
            wg_wait<0>();
            reg_fence(s);
            bar_arrive(4, 256);
            if (elected) TS(39);
            TT(2);
            const uint4* pr = g_out + (rb ^ 8) * OB + t7;
            uint4 pa[8];
#pragma unroll
            for (int v = 0; v < 8; v++) pa[v] = ld_poll(pr + v * 128);
            float4 tc[16];
#pragma unroll
            for (int k = 0; k < 16; k++) {
                tc[k] = tf[k * 4];
#pragma unroll
                for (int i = 4 * k; i < 4 * k + 4; i++) s[i] = fmaf((i & 1) ? tc[k].y : tc[k].x, s[i], (i & 1) ? bf_hi(x2[i >> 1]) : bf_lo(x2[i >> 1]));
            }
            reg_fence(s);
            for (;;) {
                uint32_t bad = 0;
#pragma unroll
                for (int v = 0; v < 8; v++) bad |= pa[v].x ^ ep;
                if (__all_sync(0xffffffffu, (bad & 1) == 0)) break;
                if (PSLEEP) __nanosleep(PSLEEP);
#pragma unroll
                for (int v = 0; v < 8; v++) pa[v] = ld_poll(pr + v * 128);
            }
            if (elected) TS(30);
            TT(3);
            float st[6] = {0.f, 0.f, 0.f, 0.f, 0.f, 0.f};
#pragma unroll
            for (int i = 0; i < 64; i++) {
                const int rh = (i >> 1) & 1;
                const uint32_t w = (&pa[i >> 3].x)[(i >> 1) & 3];
                const float v = fmaf((i & 1) ? tc[i >> 2].y : tc[i >> 2].x, (i & 1) ? bf_hi(w) : bf_lo(w), s[i]);
                s[i] = v;
                st[rh] += v;
                st[2 + rh] = fmaf(v, v, st[2 + rh]);
                st[4 + rh] = fmaf(v, (i & 1) ? tc[i >> 2].w : tc[i >> 2].z, st[4 + rh]);
            }
#pragma unroll
            for (int i = 0; i < 6; i++) st[i] = quad_sum(st[i]);
            st_pub(g_out + rb * OB + OB_STAT + (w4 * 8 + g) * 2 + (c4 & 1),
                   make_uint4(__float_as_uint((c4 & 1) ? st[1] : st[0]), __float_as_uint((c4 & 1) ? st[3] : st[2]),
                              __float_as_uint((c4 & 1) ? st[5] : st[4]), ep), c4 < 2);
            if (TF & 1) sched_fence(eb2, P.zero);
            if (elected) TS(56);
            TT(4);
            uint32_t cb[16], sh[16], gb[16];
#pragma unroll
            for (int i = 0; i < 16; i++) {
                const float4 c = tf[64 + i * 4];
                cb[i] = __float_as_uint(c.x); sh[i] = __float_as_uint(c.y); gb[i] = __float_as_uint(c.z);
            }
            const float ra = __uint_as_float(lds32(sb + SM_EP + 8)), rb0 = __uint_as_float(lds32(sb + SM_EP + 12));
#pragma unroll
            for (int i = 0; i < 32; i++) x2[i] = pack2(s[2 * i], s[2 * i + 1]);
            reg_fence(x2);
            uint4 r0, r1;
            if (SPRE) __nanosleep(SPRE);
            for (;;) {
                r0 = ld_poll(g_out + ((rb & ~3) + c4) * OB + OB_STAT + (w4 * 8 + g) * 2);
                r1 = ld_poll(g_out + ((rb & ~3) + c4) * OB + OB_STAT + (w4 * 8 + g) * 2 + 1);
                if (__all_sync(0xffffffffu, r0.w == ep && r1.w == ep)) break;
                if (SSLEEP) __nanosleep(SSLEEP);
            }
            if (elected) TS(57);
            TT(5);
            const float m0 = quad_sum(__uint_as_float(r0.x)) * (1.f / 512.f), m1 = quad_sum(__uint_as_float(r1.x)) * (1.f / 512.f);
            const float rs0 = ln_rstd(fmaxf(fmaf(-m0, m0, quad_sum(__uint_as_float(r0.y)) * (1.f / 512.f)), 0.f));
            const float rs1 = ln_rstd(fmaxf(fmaf(-m1, m1, quad_sum(__uint_as_float(r1.y)) * (1.f / 512.f)), 0.f));
            const uint32_t mb0 = pack2(m0, m0), mb1 = pack2(m1, m1);
            const uint32_t lg = pack2(fmaf(rs0, fmaf(-bf_lo(mb0), ra, quad_sum(__uint_as_float(r0.z))), rb0),
                                      fmaf(rs1, fmaf(-bf_lo(mb1), ra, quad_sum(__uint_as_float(r1.z))), rb0));
            const uint32_t u0 = lg << 16, u1 = lg & 0xffff0000u;
            const uint32_t k0 = ((u0 ^ (((int)u0 >> 31) | 0x80000000u)) & 0xffff0000u) | ((2047 - row) << 5) | (ep & 31);
            const uint32_t k1 = ((u1 ^ (((int)u1 >> 31) | 0x80000000u)) & 0xffff0000u) | ((2039 - row) << 5) | (ep & 31);
            const uint32_t kb = __reduce_max_sync(0xffffffffu, max(k0, k1));
            st_pub(g_key + cq * 128 + (row >> 4), kb, lane == 0);
            if (TF & 2) sched_fence(eb2, P.zero);
            {
                uint32_t cx[18], ch[18];
#pragma unroll
                for (int i = 0; i < 16; i++) {
                    cx[i] = kb == k1 ? x2[2 * i + 1] : x2[2 * i];
                    ch[i] = ln_apply(cx[i], kb == k1 ? mb1 : mb0, kb == k1 ? rs1 : rs0, cb[i], sh[i]);
                }
                cx[16] = cx[17] = ch[16] = ch[17] = 0;
                uint4* cp = g_cand + (row >> 4) * 192 + cq * 24 + c4;
#pragma unroll
                for (int v = 0; v < 6; v++) st_pub(cp + v * 4, make_uint4(ch[3 * v], ch[3 * v + 1], ch[3 * v + 2], ep), kb == k0 || kb == k1);
                if (TF & 4) sched_fence(eb2, P.zero);
#pragma unroll
                for (int v = 0; v < 6; v++) st_pub(cp + 96 + v * 4, make_uint4(cx[3 * v], cx[3 * v + 1], cx[3 * v + 2], ep), kb == k0 || kb == k1);
            }
            if (elected) TS(58);
            TT(6);
            uint2 ov[16];
#pragma unroll
            for (int i = 0; i < 16; i++) {
                const int rh = i & 1, jj = i & 14;
                const uint32_t v0 = badd(x2[2 * jj + rh], bmul(gb[jj], ln_apply(x2[2 * jj + rh], rh ? mb1 : mb0, rh ? rs1 : rs0, cb[jj], sh[jj])));
                const uint32_t v1 = badd(x2[2 * jj + 2 + rh], bmul(gb[jj + 1], ln_apply(x2[2 * jj + 2 + rh], rh ? mb1 : mb0, rh ? rs1 : rs0, cb[jj + 1], sh[jj + 1])));
                const uint32_t rv = __shfl_xor_sync(0xffffffffu, (c4 & 1) ? v0 : v1, 1);
                ov[i] = (c4 & 1) ? make_uint2(rv, v1) : make_uint2(v0, rv);
            }
            uint2* op = reinterpret_cast<uint2*>(P.out) + row * 128 + cq * 32 + (c4 & 1) * 2 + (c4 >> 1);
            if (OUTLATE == 0) {
#pragma unroll
                for (int i = 0; i < 16; i++)
                    if (kb != ((i & 1) ? k1 : k0)) op[(i & 1) * 1024 + (i & 14) * 2] = ov[i];
            }
            mbar_wait(sb + BAR_BEST, 0);
            const uint32_t best = lds32(sb + SM_EP + 24);
#pragma unroll
            for (int i = 0; i < 16; i++)
                if (OUTLATE ? best != ((i & 1) ? k1 : k0) : best != kb && kb == ((i & 1) ? k1 : k0)) op[(i & 1) * 1024 + (i & 14) * 2] = ov[i];
            if (elected) TS(59);
            TT(7);
        }
        mbar_arrive_if(eb2, lane == 0);
    }
}

typedef CUresult (*EncodeFn)(CUtensorMap*, CUtensorMapDataType, cuuint32_t, void*, const cuuint64_t*, const cuuint64_t*,
                             const cuuint32_t*, const cuuint32_t*, CUtensorMapInterleave, CUtensorMapSwizzle,
                             CUtensorMapL2promotion, CUtensorMapFloatOOBfill);

void make_2d(EncodeFn fn, CUtensorMap* m, const void* p, uint64_t cols, uint64_t rows, uint32_t bc, uint32_t br) {
    cuuint64_t dims[2] = {cols, rows}, strides[1] = {cols * 2};
    cuuint32_t box[2] = {bc, br}, es[2] = {1, 1};
    fn(m, CU_TENSOR_MAP_DATA_TYPE_BFLOAT16, 2, const_cast<void*>(p), dims, strides, box, es, CU_TENSOR_MAP_INTERLEAVE_NONE,
       CU_TENSOR_MAP_SWIZZLE_NONE, CU_TENSOR_MAP_L2_PROMOTION_L2_128B, CU_TENSOR_MAP_FLOAT_OOB_FILL_NONE);
}
void make_3d(EncodeFn fn, CUtensorMap* m, const void* p, uint64_t cols, uint64_t rows, uint32_t br = 128, uint32_t nb = 2) {
    cuuint64_t dims[3] = {64, rows, cols / 64}, strides[2] = {cols * 2, 128};
    cuuint32_t box[3] = {64, br, nb}, es[3] = {1, 1, 1};
    fn(m, CU_TENSOR_MAP_DATA_TYPE_BFLOAT16, 3, const_cast<void*>(p), dims, strides, box, es, CU_TENSOR_MAP_INTERLEAVE_NONE,
       CU_TENSOR_MAP_SWIZZLE_128B, CU_TENSOR_MAP_L2_PROMOTION_L2_256B, CU_TENSOR_MAP_FLOAT_OOB_FILL_NONE);
}

}

extern "C" void kernel_launch(void* const* d_in, const int* in_sizes, int n_in, void* d_out, int out_size) {
    static EncodeFn fn = nullptr;
    if (!fn) {
        void* f = nullptr;
        cudaDriverEntryPointQueryResult st;
        cudaGetDriverEntryPoint("cuTensorMapEncodeTiled", &f, cudaEnableDefault, &st);
        fn = (EncodeFn)f;
        cudaFuncSetAttribute(fused_kernel, cudaFuncAttributeMaxDynamicSharedMemorySize, SMEM_BYTES);
    }
    CUtensorMap ckv, wq, wuk, wuv, wo, wg, wu, wm, xm;
    make_3d(fn, &ckv, d_in[1], 512, 2048, 128, 1);
    make_3d(fn, &xm, d_in[0], 512, 2048, 64);
    make_3d(fn, &wq, d_in[2], 4096, 512, 128, 1);
    make_3d(fn, &wuk, d_in[3], 4096, 512);
    make_3d(fn, &wuv, d_in[4], 4096, 512);
    make_3d(fn, &wo, d_in[5], 512, 4096);
    make_2d(fn, &wg, d_in[8], 1792, 512, 16, 256);
    make_2d(fn, &wu, d_in[9], 1792, 512, 16, 256);
    make_2d(fn, &wm, d_in[12], 3072, 512, 256, 64);
    Params p;
    p.x = (const bf16*)d_in[0];
    p.ckv = (const bf16*)d_in[1];
    p.wo = (const bf16*)d_in[5];
    p.wr = (const bf16*)d_in[7];
    p.wdown = (const bf16*)d_in[10];
    p.c = (const bf16*)d_in[11];
    p.out = (bf16*)d_out;
    p.zero = 0;
    fused_kernel<<<NCTA + NSPARE, 384, SMEM_BYTES>>>(ckv, wq, wuk, wuv, wo, wg, wu, wm, xm, p);
}
```

```cpp
#include <cuda.h>
#include <cuda_bf16.h>
#include <cuda_runtime.h>
#include <stdint.h>
#include <stdio.h>

namespace {

typedef __nv_bfloat16 bf16;
typedef unsigned long long u64;

constexpr int NCTA = 128, NSPARE = 4;
constexpr int SLOT = 32768;
constexpr int SM_BAR = 7 * SLOT;
constexpr int BAR_FULL = SM_BAR;
constexpr int BAR_EMPTY = BAR_FULL + 8 * 7;
constexpr int BAR_DONE = BAR_EMPTY + 8 * 7;
constexpr int BAR_FLAG = BAR_DONE + 8 * 9;
constexpr int BAR_PF = BAR_FLAG + 8 * 9;
constexpr int BAR_END = BAR_PF + 8;
constexpr int BAR_BEST = BAR_END + 8;
constexpr int SM_EP = BAR_END + 24;
constexpr int SM_RED = SM_BAR + 384;
constexpr int SM_TAB = SM_BAR + 1024;
constexpr int SMEM_BYTES = SM_BAR + 3072;
constexpr int NFFN = 112;
#define HINT 479
constexpr u64 L2_NORMAL = 0x1000000000000000ull, L2_FIRST = 0x12F0000000000000ull;
#define PFA 8
#define PFB 6
#define UNR 1
#define POLL_NS 50
#define MSPLIT 13
#define SF 3
#define XQ 0
#define TF 1
#define KSLEEP 150
#define YSLEEP 50
#define YPRE 150
#define SSLEEP 50
#define SPRE 0
#define PSLEEP 100
#define CSLEEP 0
#define SPEC 24
#define EARLY 7
constexpr uint32_t SPIN_LIMIT = 1u << 22;
constexpr uint32_t ONE2 = 0x3f803f80u;

struct Sync {
    uint32_t cnt[16 * 8 * 8];
    uint32_t ctxcnt[16 * 32];
    uint32_t epoch[32];
};

__device__ __align__(1024) uint8_t g_KV[16 * 16 * 2 * SLOT];
__device__ __align__(1024) uint8_t g_ctx[16 * 32 * SLOT];
__device__ __align__(1024) uint8_t g_h[16 * 4 * SLOT];
constexpr int OB = 1216, OB_STAT = 1024, OB_Y = 1088;
__device__ __align__(1024) uint4 g_out[128 * OB];
__device__ __align__(1024) bf16 g_mod[3072];
__device__ __align__(1024) uint32_t g_mod1[1024];
__device__ __align__(1024) uint4 g_cand[128 * 192];
__device__ __align__(1024) uint32_t g_key[4 * 128];
__device__ __align__(1024) uint8_t g_wf[NFFN * SLOT];
__device__ __align__(1024) Sync g_sync;
#define TS(i)

#define TT(i)
#define PT()

struct Params {
    const bf16 *x, *ckv, *wo, *wr, *wdown, *c;
    bf16* out;
    int zero;
};

__device__ __forceinline__ void mbar_init(uint32_t bar, uint32_t cnt) {
    asm volatile("mbarrier.init.shared::cta.b64 [%0], %1;" ::"r"(bar), "r"(cnt) : "memory");
}
__device__ __forceinline__ void mbar_wait(uint32_t bar, uint32_t parity) {
    asm volatile("{\n.reg .pred p;\nL_%=:\nmbarrier.try_wait.parity.shared::cta.b64 p, [%0], %1;\n@!p bra L_%=;\n}" ::"r"(bar), "r"(parity) : "memory");
}
__device__ __forceinline__ void mbar_sleep(uint32_t bar) {
    if ((threadIdx.x & 31) == 0)
        asm volatile("{\n.reg .pred p;\nL_%=:\nmbarrier.try_wait.parity.shared::cta.b64 p, [%0], 0, 100000;\n@!p bra L_%=;\n}" ::"r"(bar) : "memory");
    __syncwarp();
}
__device__ __forceinline__ void mbar_watch(uint32_t bar, uint32_t parity) {
    asm volatile("{\n.reg .pred p;\n.reg .u32 n;\nmov.u32 n, 0;\n"
                 "L_%=:\nmbarrier.try_wait.parity.shared::cta.b64 p, [%0], %1;\n@p bra D_%=;\n"
                 "add.u32 n, n, 1;\nsetp.lt.u32 p, n, %2;\n@p bra L_%=;\ntrap;\nD_%=:\n}"
                 ::"r"(bar), "r"(parity), "n"(SPIN_LIMIT) : "memory");
}
__device__ __forceinline__ void step_watch(uint32_t a, uint32_t step) {
    asm volatile("{\n.reg .pred p;\n.reg .u32 n, v;\nmov.u32 n, 0;\n"
                 "L_%=:\nld.volatile.shared.u32 v, [%0];\nsetp.ge.u32 p, v, %1;\n@p bra D_%=;\nnanosleep.u32 400;\n"
                 "add.u32 n, n, 1;\nsetp.lt.u32 p, n, %2;\n@p bra L_%=;\ntrap;\nD_%=:\n}"
                 ::"r"(a), "r"(step), "n"(SPIN_LIMIT) : "memory");
}
__device__ __forceinline__ void mbar_arrive_if(uint32_t bar, bool on) {
    asm volatile("{\n.reg .pred p;\nsetp.ne.s32 p, %1, 0;\n@p mbarrier.arrive.shared::cta.b64 _, [%0];\n}" ::"r"(bar), "r"((int)on) : "memory");
}
__device__ __forceinline__ void tma2d(uint32_t dst, const CUtensorMap* m, int c0, int c1, uint32_t bar, bool first) {
    asm volatile("{\n.reg .pred p;\nelect.sync _|p, 0xffffffff;\n"
                 "@p cp.async.bulk.tensor.2d.shared::cluster.global.mbarrier::complete_tx::bytes.L2::cache_hint [%0], [%1, {%3, %4}], [%2], %5;\n}"
                 ::"r"(dst), "l"(m), "r"(bar), "r"(c0), "r"(c1), "l"(first ? L2_FIRST : L2_NORMAL) : "memory");
}
__device__ __forceinline__ void tma3d_prefetch(const CUtensorMap* m, int row, int cb) {
    asm volatile("{\n.reg .pred p;\nelect.sync _|p, 0xffffffff;\n@p cp.async.bulk.prefetch.tensor.3d.L2.global [%0, {%1, %2, %3}];\n}"
                 ::"l"(m), "r"(0), "r"(row), "r"(cb) : "memory");
}
__device__ __forceinline__ void l2_prefetch(const void* p, uint32_t bytes) {
    asm volatile("{\n.reg .pred p;\nelect.sync _|p, 0xffffffff;\n@p cp.async.bulk.prefetch.L2.global [%0], %1;\n}" ::"l"(p), "r"(bytes) : "memory");
}
__device__ __forceinline__ void bulk_store(void* dst, uint32_t src, uint32_t bytes, bool first) {
    asm volatile("{\n.reg .pred p;\nelect.sync _|p, 0xffffffff;\n@p cp.async.bulk.global.shared::cta.bulk_group.L2::cache_hint [%0], [%1], %2, %3;\n}"
                 ::"l"(dst), "r"(src), "r"(bytes), "l"(first ? L2_FIRST : L2_NORMAL) : "memory");
}
__device__ __forceinline__ void flag_wait(const uint32_t* f, uint32_t target) {
    asm volatile("{\n.reg .pred p;\n.reg .u32 v;\n"
                 "L_%=:\nld.acquire.gpu.global.u32 v, [%0];\nsub.u32 v, v, %1;\nsetp.lt.s32 p, v, 0;\n@p nanosleep.u32 100;\n@p bra L_%=;\n}"
                 ::"l"(f), "r"(target) : "memory");
}
__device__ __forceinline__ uint4 ld_poll(const uint4* p) {
    uint4 v;
    asm volatile("{\n.reg .b128 t;\nld.relaxed.gpu.global.b128 t, [%4];\nmov.b128 {%0, %1, %2, %3}, t;\n}"
                 : "=r"(v.x), "=r"(v.y), "=r"(v.z), "=r"(v.w) : "l"(p) : "memory");
    return v;
}
__device__ __forceinline__ void st_pub(uint4* p, uint4 v, bool on) {
    asm volatile("{\n.reg .pred p;\n.reg .b128 t;\nsetp.ne.s32 p, %5, 0;\nmov.b128 t, {%1, %2, %3, %4};\n@p st.relaxed.gpu.global.b128 [%0], t;\n}"
                 ::"l"(p), "r"(v.x), "r"(v.y), "r"(v.z), "r"(v.w), "r"((int)on) : "memory");
}
__device__ __forceinline__ void st_pub(uint32_t* p, uint32_t v, bool on) {
    asm volatile("{\n.reg .pred p;\nsetp.ne.s32 p, %2, 0;\n@p st.relaxed.gpu.global.u32 [%0], %1;\n}" ::"l"(p), "r"(v), "r"((int)on) : "memory");
}
__device__ __forceinline__ void flag_add(uint32_t* p) {
    asm volatile("red.release.gpu.global.add.u32 [%0], 1;" ::"l"(p) : "memory");
}
__device__ __forceinline__ uint32_t lds32(uint32_t a) {
    uint32_t v;
    asm volatile("ld.shared.u32 %0, [%1];" : "=r"(v) : "r"(a) : "memory");
    return v;
}
__device__ __forceinline__ uint4 lds128(uint32_t a) {
    uint4 v;
    asm volatile("ld.shared.v4.u32 {%0, %1, %2, %3}, [%4];" : "=r"(v.x), "=r"(v.y), "=r"(v.z), "=r"(v.w) : "r"(a) : "memory");
    return v;
}
__device__ __forceinline__ void sched_fence(uint32_t& v, uint32_t z) {
    uint32_t ck;
    asm volatile("mov.u32 %0, %%clock;" : "=r"(ck)::"memory");
    v ^= ck & z;
}
__device__ __forceinline__ void fence_async_global() { asm volatile("fence.proxy.async.global;" ::: "memory"); }
__device__ __forceinline__ void fence_async_smem() { asm volatile("fence.proxy.async.shared::cta;" ::: "memory"); }
__device__ __forceinline__ void bar_sync(int id, int n) { asm volatile("bar.sync %0, %1;" ::"r"(id), "r"(n) : "memory"); }
__device__ __forceinline__ void bar_arrive(int id, int n) { asm volatile("bar.arrive %0, %1;" ::"r"(id), "r"(n) : "memory"); }
__device__ __forceinline__ void wg_fence() { asm volatile("wgmma.fence.sync.aligned;" ::: "memory"); }
__device__ __forceinline__ void wg_commit() { asm volatile("wgmma.commit_group.sync.aligned;" ::: "memory"); }
template <int N> __device__ __forceinline__ void wg_wait() { asm volatile("wgmma.wait_group.sync.aligned %0;" ::"n"(N) : "memory"); }
template <int N> __device__ __forceinline__ void reg_fence(float (&d)[N]) {
#pragma unroll
    for (int i = 0; i < N; i++) asm volatile("" : "+f"(d[i])::"memory");
}
template <int N> __device__ __forceinline__ void reg_fence(uint32_t (&d)[N]) {
#pragma unroll
    for (int i = 0; i < N; i++) asm volatile("" : "+r"(d[i])::"memory");
}
__device__ __forceinline__ uint32_t desc_k(uint32_t a) { return ((a & 0x3ffff) >> 4) | (1u << 16); }
__device__ __forceinline__ uint32_t desc_mn(uint32_t a) { return ((a & 0x3ffff) >> 4) | (1024u << 16); }

template <int TB>
__device__ __forceinline__ void wgmma_ss128(float (&d)[64], uint32_t da, uint32_t db, int acc, uint32_t ha = 0x40000040u, uint32_t hb = 0x40000040u) {
    asm volatile("{\n.reg .pred p;\n.reg .b64 a, b;\nsetp.ne.b32 p, %66, 0;\nmov.b64 a, {%64, %68};\nmov.b64 b, {%65, %69};\n"
        "wgmma.mma_async.sync.aligned.m64n128k16.f32.bf16.bf16 {%0, %1, %2, %3, %4, %5, %6, %7, %8, %9, %10, %11, %12, %13, %14, %15, %16, %17, %18, %19, %20, %21, %22, %23, %24, %25, %26, %27, %28, %29, %30, %31, %32, %33, %34, %35, %36, %37, %38, %39, %40, %41, %42, %43, %44, %45, %46, %47, %48, %49, %50, %51, %52, %53, %54, %55, %56, %57, %58, %59, %60, %61, %62, %63}, a, b, p, 1, 1, 0, %67;\n}"
        : "+f"(d[0]), "+f"(d[1]), "+f"(d[2]), "+f"(d[3]), "+f"(d[4]), "+f"(d[5]), "+f"(d[6]), "+f"(d[7]), "+f"(d[8]), "+f"(d[9]), "+f"(d[10]), "+f"(d[11]), "+f"(d[12]), "+f"(d[13]), "+f"(d[14]), "+f"(d[15]), "+f"(d[16]), "+f"(d[17]), "+f"(d[18]), "+f"(d[19]), "+f"(d[20]), "+f"(d[21]), "+f"(d[22]), "+f"(d[23]), "+f"(d[24]), "+f"(d[25]), "+f"(d[26]), "+f"(d[27]), "+f"(d[28]), "+f"(d[29]), "+f"(d[30]), "+f"(d[31]), "+f"(d[32]), "+f"(d[33]), "+f"(d[34]), "+f"(d[35]), "+f"(d[36]), "+f"(d[37]), "+f"(d[38]), "+f"(d[39]), "+f"(d[40]), "+f"(d[41]), "+f"(d[42]), "+f"(d[43]), "+f"(d[44]), "+f"(d[45]), "+f"(d[46]), "+f"(d[47]), "+f"(d[48]), "+f"(d[49]), "+f"(d[50]), "+f"(d[51]), "+f"(d[52]), "+f"(d[53]), "+f"(d[54]), "+f"(d[55]), "+f"(d[56]), "+f"(d[57]), "+f"(d[58]), "+f"(d[59]), "+f"(d[60]), "+f"(d[61]), "+f"(d[62]), "+f"(d[63])
        : "r"(da), "r"(db), "r"(acc), "n"(TB), "r"(ha), "r"(hb));
}
template <int TB>
__device__ __forceinline__ void wgmma_ss128_init(float (&d)[64], uint32_t da, uint32_t db, uint32_t ha = 0x40000040u, uint32_t hb = 0x40000040u) {
    asm volatile("{\n.reg .pred p;\n.reg .b64 a, b;\nsetp.ne.b32 p, 0, 0;\nmov.b64 a, {%64, %67};\nmov.b64 b, {%65, %68};\n"
        "wgmma.mma_async.sync.aligned.m64n128k16.f32.bf16.bf16 {%0, %1, %2, %3, %4, %5, %6, %7, %8, %9, %10, %11, %12, %13, %14, %15, %16, %17, %18, %19, %20, %21, %22, %23, %24, %25, %26, %27, %28, %29, %30, %31, %32, %33, %34, %35, %36, %37, %38, %39, %40, %41, %42, %43, %44, %45, %46, %47, %48, %49, %50, %51, %52, %53, %54, %55, %56, %57, %58, %59, %60, %61, %62, %63}, a, b, p, 1, 1, 0, %66;\n}"
        : "=f"(d[0]), "=f"(d[1]), "=f"(d[2]), "=f"(d[3]), "=f"(d[4]), "=f"(d[5]), "=f"(d[6]), "=f"(d[7]), "=f"(d[8]), "=f"(d[9]), "=f"(d[10]), "=f"(d[11]), "=f"(d[12]), "=f"(d[13]), "=f"(d[14]), "=f"(d[15]), "=f"(d[16]), "=f"(d[17]), "=f"(d[18]), "=f"(d[19]), "=f"(d[20]), "=f"(d[21]), "=f"(d[22]), "=f"(d[23]), "=f"(d[24]), "=f"(d[25]), "=f"(d[26]), "=f"(d[27]), "=f"(d[28]), "=f"(d[29]), "=f"(d[30]), "=f"(d[31]), "=f"(d[32]), "=f"(d[33]), "=f"(d[34]), "=f"(d[35]), "=f"(d[36]), "=f"(d[37]), "=f"(d[38]), "=f"(d[39]), "=f"(d[40]), "=f"(d[41]), "=f"(d[42]), "=f"(d[43]), "=f"(d[44]), "=f"(d[45]), "=f"(d[46]), "=f"(d[47]), "=f"(d[48]), "=f"(d[49]), "=f"(d[50]), "=f"(d[51]), "=f"(d[52]), "=f"(d[53]), "=f"(d[54]), "=f"(d[55]), "=f"(d[56]), "=f"(d[57]), "=f"(d[58]), "=f"(d[59]), "=f"(d[60]), "=f"(d[61]), "=f"(d[62]), "=f"(d[63])
        : "r"(da), "r"(db), "n"(TB), "r"(ha), "r"(hb));
}
template <int TB>
__device__ __forceinline__ void wgmma_ss64(float (&d)[32], uint32_t da, uint32_t db, int acc, uint32_t ha = 0x40000040u, uint32_t hb = 0x40000040u) {
    asm volatile("{\n.reg .pred p;\n.reg .b64 a, b;\nsetp.ne.b32 p, %34, 0;\nmov.b64 a, {%32, %36};\nmov.b64 b, {%33, %37};\n"
        "wgmma.mma_async.sync.aligned.m64n64k16.f32.bf16.bf16 {%0, %1, %2, %3, %4, %5, %6, %7, %8, %9, %10, %11, %12, %13, %14, %15, %16, %17, %18, %19, %20, %21, %22, %23, %24, %25, %26, %27, %28, %29, %30, %31}, a, b, p, 1, 1, 0, %35;\n}"
        : "+f"(d[0]), "+f"(d[1]), "+f"(d[2]), "+f"(d[3]), "+f"(d[4]), "+f"(d[5]), "+f"(d[6]), "+f"(d[7]), "+f"(d[8]), "+f"(d[9]), "+f"(d[10]), "+f"(d[11]), "+f"(d[12]), "+f"(d[13]), "+f"(d[14]), "+f"(d[15]), "+f"(d[16]), "+f"(d[17]), "+f"(d[18]), "+f"(d[19]), "+f"(d[20]), "+f"(d[21]), "+f"(d[22]), "+f"(d[23]), "+f"(d[24]), "+f"(d[25]), "+f"(d[26]), "+f"(d[27]), "+f"(d[28]), "+f"(d[29]), "+f"(d[30]), "+f"(d[31])
        : "r"(da), "r"(db), "r"(acc), "n"(TB), "r"(ha), "r"(hb));
}
template <int TB>
__device__ __forceinline__ void wgmma_ss64_init(float (&d)[32], uint32_t da, uint32_t db, uint32_t ha = 0x40000040u, uint32_t hb = 0x40000040u) {
    asm volatile("{\n.reg .pred p;\n.reg .b64 a, b;\nsetp.ne.b32 p, 0, 0;\nmov.b64 a, {%32, %35};\nmov.b64 b, {%33, %36};\n"
        "wgmma.mma_async.sync.aligned.m64n64k16.f32.bf16.bf16 {%0, %1, %2, %3, %4, %5, %6, %7, %8, %9, %10, %11, %12, %13, %14, %15, %16, %17, %18, %19, %20, %21, %22, %23, %24, %25, %26, %27, %28, %29, %30, %31}, a, b, p, 1, 1, 0, %34;\n}"
        : "=f"(d[0]), "=f"(d[1]), "=f"(d[2]), "=f"(d[3]), "=f"(d[4]), "=f"(d[5]), "=f"(d[6]), "=f"(d[7]), "=f"(d[8]), "=f"(d[9]), "=f"(d[10]), "=f"(d[11]), "=f"(d[12]), "=f"(d[13]), "=f"(d[14]), "=f"(d[15]), "=f"(d[16]), "=f"(d[17]), "=f"(d[18]), "=f"(d[19]), "=f"(d[20]), "=f"(d[21]), "=f"(d[22]), "=f"(d[23]), "=f"(d[24]), "=f"(d[25]), "=f"(d[26]), "=f"(d[27]), "=f"(d[28]), "=f"(d[29]), "=f"(d[30]), "=f"(d[31])
        : "r"(da), "r"(db), "n"(TB), "r"(ha), "r"(hb));
}
__device__ __forceinline__ void wgmma_rs128(float (&d)[64], uint32_t a0, uint32_t a1, uint32_t a2, uint32_t a3, uint32_t db, int acc, uint32_t hb = 0x40000040u) {
    asm volatile("{\n.reg .pred p;\n.reg .b64 b;\nsetp.ne.b32 p, %69, 0;\nmov.b64 b, {%68, %70};\n"
        "wgmma.mma_async.sync.aligned.m64n128k16.f32.bf16.bf16 {%0, %1, %2, %3, %4, %5, %6, %7, %8, %9, %10, %11, %12, %13, %14, %15, %16, %17, %18, %19, %20, %21, %22, %23, %24, %25, %26, %27, %28, %29, %30, %31, %32, %33, %34, %35, %36, %37, %38, %39, %40, %41, %42, %43, %44, %45, %46, %47, %48, %49, %50, %51, %52, %53, %54, %55, %56, %57, %58, %59, %60, %61, %62, %63}, {%64, %65, %66, %67}, b, p, 1, 1, 1;\n}"
        : "+f"(d[0]), "+f"(d[1]), "+f"(d[2]), "+f"(d[3]), "+f"(d[4]), "+f"(d[5]), "+f"(d[6]), "+f"(d[7]), "+f"(d[8]), "+f"(d[9]), "+f"(d[10]), "+f"(d[11]), "+f"(d[12]), "+f"(d[13]), "+f"(d[14]), "+f"(d[15]), "+f"(d[16]), "+f"(d[17]), "+f"(d[18]), "+f"(d[19]), "+f"(d[20]), "+f"(d[21]), "+f"(d[22]), "+f"(d[23]), "+f"(d[24]), "+f"(d[25]), "+f"(d[26]), "+f"(d[27]), "+f"(d[28]), "+f"(d[29]), "+f"(d[30]), "+f"(d[31]), "+f"(d[32]), "+f"(d[33]), "+f"(d[34]), "+f"(d[35]), "+f"(d[36]), "+f"(d[37]), "+f"(d[38]), "+f"(d[39]), "+f"(d[40]), "+f"(d[41]), "+f"(d[42]), "+f"(d[43]), "+f"(d[44]), "+f"(d[45]), "+f"(d[46]), "+f"(d[47]), "+f"(d[48]), "+f"(d[49]), "+f"(d[50]), "+f"(d[51]), "+f"(d[52]), "+f"(d[53]), "+f"(d[54]), "+f"(d[55]), "+f"(d[56]), "+f"(d[57]), "+f"(d[58]), "+f"(d[59]), "+f"(d[60]), "+f"(d[61]), "+f"(d[62]), "+f"(d[63])
        : "r"(a0), "r"(a1), "r"(a2), "r"(a3), "r"(db), "r"(acc), "r"(hb));
}

__device__ __forceinline__ uint32_t pack2(float lo, float hi) {
    uint32_t r;
    asm("cvt.rn.bf16x2.f32 %0, %1, %2;" : "=r"(r) : "f"(hi), "f"(lo));
    return r;
}
__device__ __forceinline__ float bf_lo(uint32_t v) { return __uint_as_float(v << 16); }
__device__ __forceinline__ float bf_hi(uint32_t v) { return __uint_as_float(v & 0xffff0000u); }
__device__ __forceinline__ float rbf(float v) { return bf_lo(pack2(v, v)); }
__device__ __forceinline__ uint32_t badd(uint32_t a, uint32_t b) {
    uint32_t r;
    asm("add.rn.bf16x2 %0, %1, %2;" : "=r"(r) : "r"(a), "r"(b));
    return r;
}
__device__ __forceinline__ uint32_t bsub(uint32_t a, uint32_t b) {
    uint32_t r;
    asm("sub.rn.bf16x2 %0, %1, %2;" : "=r"(r) : "r"(a), "r"(b));
    return r;
}
__device__ __forceinline__ uint32_t bmul(uint32_t a, uint32_t b) {
    uint32_t r;
    asm("mul.rn.bf16x2 %0, %1, %2;" : "=r"(r) : "r"(a), "r"(b));
    return r;
}
__device__ __forceinline__ uint32_t ln_apply(uint32_t x, uint32_t mb, float rs, uint32_t scale, uint32_t shift) {
    const uint32_t d = bsub(x, mb);
    return badd(bmul(pack2(bf_lo(d) * rs, bf_hi(d) * rs), scale), shift);
}
__device__ __forceinline__ float ex2(float v) {
    float r;
    asm("ex2.approx.ftz.f32 %0, %1;" : "=f"(r) : "f"(v));
    return r;
}
__device__ __forceinline__ float rcp(float v) {
    float r;
    asm("rcp.approx.ftz.f32 %0, %1;" : "=f"(r) : "f"(v));
    return r;
}
__device__ __forceinline__ float sqrt_fast(float v) {
    float r;
    asm("sqrt.approx.ftz.f32 %0, %1;" : "=f"(r) : "f"(v));
    return r;
}
__device__ __forceinline__ float ln_rstd(float var) { return rcp(rbf(sqrt_fast(rbf(rbf(var) + 1e-5f)))); }
__device__ __forceinline__ float sigmoid(float v) { return rcp(1.f + ex2(-1.4426950408889634f * v)); }
__device__ __forceinline__ float quad_sum(float v) {
    v += __shfl_xor_sync(0xffffffffu, v, 1);
    return v + __shfl_xor_sync(0xffffffffu, v, 2);
}

constexpr uint32_t HI_128 = 0x40000040u, HI_IMG = 0x80000080u, HI_Q = 0x80000040u;
template <int M, int RH>
__device__ __forceinline__ uint4 img_pack(const float (&d)[64], float s) {
    uint4 v;
    v.x = pack2(d[16 * M + 2 * RH] * s, d[16 * M + 2 * RH + 1] * s);
    v.y = pack2(d[16 * M + 4 + 2 * RH] * s, d[16 * M + 5 + 2 * RH] * s);
    v.z = pack2(d[16 * M + 8 + 2 * RH] * s, d[16 * M + 9 + 2 * RH] * s);
    v.w = pack2(d[16 * M + 12 + 2 * RH] * s, d[16 * M + 13 + 2 * RH] * s);
    return v;
}
template <int M>
__device__ __forceinline__ void img_store_global(uint8_t* img, uint32_t toff, const float (&d)[64], float s0, float s1) {
    uint4* p = reinterpret_cast<uint4*>(img + toff) + M * 32;
    p[0] = img_pack<M, 0>(d, s0);
    p[128] = img_pack<M, 1>(d, s1);
}
__device__ __forceinline__ void sts128(uint32_t a, uint4 v) {
    asm volatile("st.shared.v4.b32 [%0], {%1, %2, %3, %4};" ::"r"(a), "r"(v.x), "r"(v.y), "r"(v.z), "r"(v.w) : "memory");
}
constexpr float SM_C = 0.08838834764831845f * 1.4426950408889634f;
__device__ __forceinline__ float pack2f(float lo, float hi) {
    float r;
    asm("{\n.reg .b32 t;\ncvt.rn.bf16x2.f32 t, %1, %2;\nmov.b32 %0, t;\n}" : "=f"(r) : "f"(hi), "f"(lo));
    return r;
}
template <int M, bool SCALE, bool PARK>
__device__ __forceinline__ void pack_group(float (&d)[64], float (&v)[8], float s0, float s1) {
#pragma unroll
    for (int i = 0; i < 8; i++) {
        const int k = 16 * M + 4 * (i & 3) + 2 * (i >> 2);
        v[i] = SCALE ? pack2f(d[k] * (i < 4 ? s0 : s1), d[k + 1] * (i < 4 ? s0 : s1)) : pack2f(d[k], d[k + 1]);
        if (PARK && M > 0) d[16 * (M > 0 ? M - 1 : 0) + i] = v[i];
    }
}
__device__ __forceinline__ uint32_t q_off(uint32_t toff) { return (((toff >> 1) & ~2047u) ^ 8192) + (toff & 511); }
template <int M, bool PARK>
__device__ __forceinline__ void ctx_store_part(float4* p, float (&d)[64], float i0, float i1) {
    float v[8];
    pack_group<M, true, PARK>(d, v, i0, i1);
    p[M * 32] = make_float4(v[0], v[1], v[2], v[3]);
    p[M * 32 + 128] = make_float4(v[4], v[5], v[6], v[7]);
}
template <bool PARK>
__device__ __forceinline__ void ctx_store(uint8_t* img, uint32_t toff, float (&o)[64], float l0, float l1) {
    const float i0 = rcp(quad_sum(l0)), i1 = rcp(quad_sum(l1));
    float4* p = reinterpret_cast<float4*>(img + toff);
    ctx_store_part<0, PARK>(p, o, i0, i1); ctx_store_part<1, PARK>(p, o, i0, i1); ctx_store_part<2, PARK>(p, o, i0, i1); ctx_store_part<3, PARK>(p, o, i0, i1);
}

template <int M>
__device__ __forceinline__ void tile_store_part(float4* p, uint32_t a, float (&d)[64], float i0, float i1, int ctx) {
    float v[8];
    pack_group<M, true, true>(d, v, i0, i1);
#pragma unroll
    for (int h = 0; h < 2; h++)
        asm volatile("{\n.reg .pred p;\nsetp.ne.s32 p, %6, 0;\n@p st.global.v4.f32 [%0], {%2, %3, %4, %5};\n@!p st.shared.v4.f32 [%1], {%2, %3, %4, %5};\n}"
                     ::"l"(p + M * 32 + h * 128), "r"(a + (M >> 1) * 16384 + (M & 1) * 512 + h * 1024),
                     "f"(v[4 * h]), "f"(v[4 * h + 1]), "f"(v[4 * h + 2]), "f"(v[4 * h + 3]), "r"(ctx) : "memory");
}
__device__ __forceinline__ void tile_store(uint8_t* img, uint32_t a, uint32_t toff, float (&d)[64], float i0, float i1, int ctx) {
    float4* p = reinterpret_cast<float4*>(img + toff);
    a += q_off(toff);
    tile_store_part<0>(p, a, d, i0, i1, ctx); tile_store_part<1>(p, a, d, i0, i1, ctx);
    tile_store_part<2>(p, a, d, i0, i1, ctx); tile_store_part<3>(p, a, d, i0, i1, ctx);
}

__device__ __forceinline__ void slot_wait(uint32_t bars, uint32_t& ph, uint32_t slot) {
    mbar_wait(bars + 8 * slot, (ph >> slot) & 1);
    ph ^= 1u << slot;
}
__device__ __forceinline__ void release_if(uint32_t eb, uint32_t slot, bool on) {
    asm volatile("{\n.reg .pred p;\nsetp.ne.s32 p, %1, 0;\n@p mbarrier.arrive.shared::cluster.b64 _, [%0];\n}" ::"r"(eb + 8 * slot), "r"((int)on) : "memory");
}
__device__ __forceinline__ void slot_acquire(uint32_t sb, uint32_t& ph, uint32_t slot) {
    slot_wait(sb + BAR_EMPTY, ph, slot);
    asm volatile("{\n.reg .pred p;\nelect.sync _|p, 0xffffffff;\n@p mbarrier.arrive.expect_tx.shared::cta.b64 _, [%0], 32768;\n}"
                 ::"r"(sb + BAR_FULL + 8 * slot) : "memory");
}
__device__ __forceinline__ void load_bulk(uint32_t sb, uint32_t slot, uint32_t off, const void* src, uint32_t bytes, bool both, bool first) {
    if (both)
        asm volatile("{\n.reg .pred p;\nelect.sync _|p, 0xffffffff;\n"
                     "@p cp.async.bulk.shared::cluster.global.mbarrier::complete_tx::bytes.multicast::cluster.L2::cache_hint [%0], [%1], %5, [%2], %4, %3;\n}"
                     ::"r"(sb + slot * SLOT + off), "l"(src), "r"(sb + BAR_FULL + 8 * slot), "l"(first ? L2_FIRST : L2_NORMAL), "h"((uint16_t)3),
                     "r"(bytes) : "memory");
    else
        asm volatile("{\n.reg .pred p;\nelect.sync _|p, 0xffffffff;\n"
                     "@p cp.async.bulk.shared::cluster.global.mbarrier::complete_tx::bytes.L2::cache_hint [%0], [%1], %4, [%2], %3;\n}"
                     ::"r"(sb + slot * SLOT + off), "l"(src), "r"(sb + BAR_FULL + 8 * slot), "l"(first ? L2_FIRST : L2_NORMAL), "r"(bytes) : "memory");
}
__device__ __forceinline__ void load_tile(uint32_t sb, uint32_t slot, uint32_t off, const CUtensorMap* m, int row, int cb, bool both, bool first) {
    if (both)
        asm volatile("{\n.reg .pred p;\nelect.sync _|p, 0xffffffff;\n"
                     "@p cp.async.bulk.tensor.3d.shared::cluster.global.mbarrier::complete_tx::bytes.multicast::cluster.L2::cache_hint [%0], [%1, {%3, %4, %5}], [%2], %7, %6;\n}"
                     ::"r"(sb + slot * SLOT + off), "l"(m), "r"(sb + BAR_FULL + 8 * slot), "r"(0), "r"(row), "r"(cb),
                     "l"(first ? L2_FIRST : L2_NORMAL), "h"((uint16_t)3) : "memory");
    else
        asm volatile("{\n.reg .pred p;\nelect.sync _|p, 0xffffffff;\n"
                     "@p cp.async.bulk.tensor.3d.shared::cluster.global.mbarrier::complete_tx::bytes.L2::cache_hint [%0], [%1, {%3, %4, %5}], [%2], %6;\n}"
                     ::"r"(sb + slot * SLOT + off), "l"(m), "r"(sb + BAR_FULL + 8 * slot), "r"(0), "r"(row), "r"(cb),
                     "l"(first ? L2_FIRST : L2_NORMAL) : "memory");
}
__device__ __forceinline__ uint32_t ring_next(uint32_t r) { return r == 4 ? 0 : r + 1; }
__device__ __forceinline__ uint32_t w_table(int hp) { return hp ? 0x3104u : 0x4210u; }
__device__ __forceinline__ uint32_t a_table(int hp) { return hp ? 0x625u : 0x635u; }
__device__ __forceinline__ uint32_t a_next(uint32_t& t) {
    const uint32_t s = t & 15;
    t = (t >> 4) | (s << 8);
    return s;
}
constexpr uint32_t O_TABLE = 0x1604235u;
__device__ __forceinline__ uint32_t o_next(uint32_t& t) {
    const uint32_t s = t & 15;
    t = (t >> 4) | (s << 24);
    return s;
}
__device__ __forceinline__ int o_head(int i, int kh) { return i < 16 ? 4 * (i & 7) + 2 * (kh ^ 1) + (i >> 3) : 29 + 2 * kh; }

template <bool INIT>
__device__ __forceinline__ void gemm_issue(float (&d)[64], uint32_t a, uint32_t b, int acc, bool img) {
    const uint32_t ha = img ? HI_IMG : HI_128, o2 = img ? 32 : 4, o4 = img ? 64 : 1024;
    wg_fence();
#pragma unroll
    for (int k = 0; k < 8; k++) {
        if (INIT && k == 0) wgmma_ss128_init<1>(d, a, b, ha);
        else wgmma_ss128<1>(d, a + (k >> 2) * o4 + ((k >> 1) & 1) * o2 + (k & 1) * 2, b + k * 128, k ? 1 : acc, ha);
    }
    wg_commit();
}

template <bool ODD>
__device__ __forceinline__ bool proj_tile(float (&acc)[64], float (&prev)[64], int t, int q0, uint32_t sb, int wg, uint32_t eb, bool rel, uint32_t& fph,
                                          uint32_t wtab, uint32_t& atab, uint8_t* prev_img, uint32_t toff, float s0, float s1, bool first,
                                          const bf16* x, int xrow, uint32_t (&v)[32]) {
    const uint32_t a0 = desc_k(sb + (wg ^ (ODD && t == 5)) * 8192), b0 = desc_mn(sb);
    const int lane = threadIdx.x & 31;
    constexpr int U = ODD ? UNR : 1;
#pragma unroll U
    for (int q = ODD ? 0 : q0; q < 4; q++) {
        const uint32_t ws = (wtab >> (4 * q)) & 15, as = a_next(atab);
        if (!ODD && t != 2) slot_wait(sb + BAR_FULL, fph, ws);
        slot_wait(sb + BAR_FULL, fph, as);
        if (ODD && q == 2 && t == 5) {
#pragma unroll
            for (int i = 0; i < 8; i++) sts128(sb + 5 * SLOT + q_off(toff) + (i >> 2) * 16384 + (i & 2) * 256 + (i & 1) * 1024, make_uint4(v[4 * i], v[4 * i + 1], v[4 * i + 2], v[4 * i + 3]));
        }
        bar_sync(1 + wg, 256);
        gemm_issue<false>(acc, a0 + as * (SLOT / 16), b0 + ws * (SLOT / 16), q, false);
        bar_arrive(2 - wg, 256);
        wg_wait<1>();
        reg_fence(prev);
        if (ODD && t == 5) {
            if (q == 0) {
#pragma unroll
                for (int i = 0; i < 32; i++) {
                    const int k = 16 * (i >> 3) + 4 * (i & 3) + ((i >> 1) & 2);
                    v[i] = pack2(prev[k], prev[k + 1]);
                }
            }
            if (q == 2) {
                fence_async_smem();
                slot_wait(sb + BAR_FULL, fph, wtab & 15);
                wg_wait<0>();
                release_if(eb, as, rel);
                release_if(eb, ws, rel);
                reg_fence(acc);
                return true;
            }
        } else {
            if (first) {
                const uint4* xp = reinterpret_cast<const uint4*>(x) + xrow * 64;
                if (!ODD) {
                    if (q == XQ && lane < 16) asm volatile("prefetch.global.L1 [%0];" ::"l"(xp + lane * 8) : "memory");
                    if (q == 3) {
#pragma unroll
                        for (int i = 0; i < 4; i++) {
                            const uint4 u = __ldg(xp + lane + 32 * i);
                            v[4 * i] = u.x; v[4 * i + 1] = u.y; v[4 * i + 2] = u.z; v[4 * i + 3] = u.w;
                        }
                        v[16] = __ldg(&xp[0].x) << 16;
                        v[17] = __ldg(&xp[64].x) << 16;
                        float st[4] = {0.f, 0.f, 0.f, 0.f};
#pragma unroll
                        for (int k = 0; k < 16; k++) {
                            const float d0 = bf_lo(v[k]) - __uint_as_float(v[16 + (k >> 3)]), d1 = bf_hi(v[k]) - __uint_as_float(v[16 + (k >> 3)]);
                            st[k >> 3] += d0 + d1;
                            st[2 + (k >> 3)] = fmaf(d0, d0, fmaf(d1, d1, st[2 + (k >> 3)]));
                        }
#pragma unroll
                        for (int i = 0; i < 4; i++) v[20 + i] = __float_as_uint(st[i]);
                    }
                } else if (q == 0) {
#pragma unroll
                    for (int i = 0; i < 20; i++)
                        v[20 + (i & 3)] = __float_as_uint(__uint_as_float(v[20 + (i & 3)]) + __uint_as_float(__shfl_xor_sync(0xffffffffu, v[20 + (i & 3)], 1 << (i >> 2))));
                } else if (q == 1) {
#pragma unroll
                    for (int i = 0; i < 2; i++) {
                        const float d = __uint_as_float(v[20 + i]) * (1.f / 512.f);
                        const float rs = ln_rstd(fmaxf(fmaf(-d, d, __uint_as_float(v[22 + i]) * (1.f / 512.f)), 0.f));
                        const uint32_t mb = pack2(__uint_as_float(v[16 + i]) + d, __uint_as_float(v[16 + i]) + d);
#pragma unroll
                        for (int k = 8 * i; k < 8 * i + 8; k++) {
                            const uint32_t y = bsub(v[k], mb);
                            v[k] = pack2(bf_lo(y) * rs, bf_hi(y) * rs);
                        }
                    }
                } else {
                    mbar_wait(sb + BAR_FLAG + 8 * 8, 0);
                    const uint4 a = lds128(sb + SM_TAB + q * 512 + lane * 16), c = lds128(sb + SM_TAB - 1024 + q * 512 + lane * 16);
                    uint8_t* p = g_h + ((xrow >> 7) * 8 + (q & 1) * 4 + (lane >> 3)) * 16384 + (xrow & 127) * 128;
#pragma unroll
                    for (int i = 0; i < 2; i++) {
                        *reinterpret_cast<uint4*>(p + i * 128 + (((lane ^ xrow ^ i) & 7) << 4)) =
                            make_uint4(badd(bmul(v[8 * i], a.x), c.x), badd(bmul(v[8 * i + 1], a.y), c.y),
                                       badd(bmul(v[8 * i + 2], a.z), c.z), badd(bmul(v[8 * i + 3], a.w), c.w));
#pragma unroll
                        for (int k = 0; k < 4; k++) v[8 * i + k] = v[8 * i + 4 + k];
                    }
                    __syncwarp();
                    mbar_arrive_if(sb + BAR_DONE, lane == 0 && q == 3);
                }
            }
            if (ODD || !first) {
                if (q == 0) img_store_global<0>(prev_img, toff, prev, s0, s1);
                if (q == 1) img_store_global<1>(prev_img, toff, prev, s0, s1);
                if (q == 2) img_store_global<2>(prev_img, toff, prev, s0, s1);
                if (q == 3) img_store_global<3>(prev_img, toff, prev, s0, s1);
            }
        }
        wg_wait<0>();
        release_if(eb, as, rel && !(ODD && (q & 1) && t == 5));
        if (ODD) release_if(eb, ws, rel && t != 1);
    }
    reg_fence(acc);
    return false;
}

__device__ __forceinline__ void qk_issue(float (&s)[64], uint32_t q, uint32_t k) {
    wg_fence();
    wgmma_ss128_init<0>(s, q, k, HI_Q, HI_IMG);
#pragma unroll
    for (int i = 1; i < 8; i++) wgmma_ss128<0>(s, q + (i >> 2) * 1024 + (i & 2) * 16 + (i & 1) * 2, k + (i >> 1) * 32 + (i & 1) * 2, 1, HI_Q, HI_IMG);
    wg_commit();
}
__device__ __forceinline__ void qk_issue(float (&s)[32], uint32_t q, uint32_t k) {
    wg_fence();
    wgmma_ss64_init<0>(s, q, k, HI_Q, HI_IMG);
#pragma unroll
    for (int i = 1; i < 8; i++) wgmma_ss64<0>(s, q + (i >> 2) * 1024 + (i & 2) * 16 + (i & 1) * 2, k + (i >> 1) * 32 + (i & 1) * 2, 1, HI_Q, HI_IMG);
    wg_commit();
}
__device__ __forceinline__ void pv_issue(float (&o)[64], const uint32_t (&p)[32], uint32_t v, int acc, bool half) {
    if (half) {
        asm volatile("// half" ::: "memory");
        wg_fence();
#pragma unroll
        for (int i = 0; i < 4; i++) wgmma_rs128(o, p[4 * i], p[4 * i + 1], p[4 * i + 2], p[4 * i + 3], v + i * 256, i ? 1 : acc, HI_IMG);
        wg_commit();
        asm volatile("// half" ::: "memory");
    } else {
        wg_fence();
#pragma unroll
        for (int i = 0; i < 8; i++) wgmma_rs128(o, p[4 * i], p[4 * i + 1], p[4 * i + 2], p[4 * i + 3], v + i * 256, i ? 1 : acc, HI_IMG);
        wg_commit();
    }
}
__device__ __forceinline__ void tri_mask(float (&s)[64], float x) {
#pragma unroll
    for (int k = 0; k < 16; k++) {
        float b;
        asm("sub.sat.f32 %0, %1, %2;" : "=f"(b) : "f"((float)(8 * (k >> 1) + (k & 1))), "f"(x));
        const int i = 32 + 4 * (k >> 1) + (k & 1);
        asm("fma.rn.f32 %0, %1, 0fFF61B1E6, %0;" : "+f"(s[i]) : "f"(b));
        if (k < 14) asm("fma.rn.f32 %0, %1, 0fFF61B1E6, %0;" : "+f"(s[i + 6]) : "f"(b));
    }
}
__device__ __forceinline__ void tri_mask_copy(float (&s)[64], const float (&h)[32], float x) {
#pragma unroll
    for (int i = 0; i < 32; i++) {
        asm("{\n.reg .pred p;\nsetp.lt.f32 p, %2, %3;\nselp.f32 %0, 0fFF800000, %1, p;\n}"
            : "=f"(s[i]) : "f"(h[i]), "f"(x), "f"((float)(8 * (i >> 2) - 4 * (i & 2) + (i & 1))));
        s[32 + i] = __uint_as_float(0xff800000u);
    }
}
constexpr float SM_HI = 1152921504606846976.f, SM_LO = 1.f / 1152921504606846976.f;
__device__ __forceinline__ bool softmax_unsafe(float t0, float t1, bool first) {
    bool bad = __any_sync(0xffffffffu, fmaxf(t0, t1) > SM_HI);
    if (first) {
        uint32_t a = __ballot_sync(0xffffffffu, t0 >= SM_LO), b = __ballot_sync(0xffffffffu, t1 >= SM_LO);
        a |= a >> 1;
        b |= b >> 1;
        bad |= ((a | (a >> 2)) & (b | (b >> 2)) & 0x11111111u) != 0x11111111u;
    }
    return bad;
}
__device__ __forceinline__ void softmax_shift(float (&s)[64], float d0, float d1) {
#pragma unroll
    for (int i = 0; i < 64; i++) s[i] -= (i & 2) ? d1 : d0;
}
__device__ __forceinline__ void softmax_remax(float (&s)[64], float (&m)[2], bool first, float& a0, float& a1) {
    float m0 = fmaxf(s[0], s[1]), m1 = fmaxf(s[2], s[3]);
#pragma unroll
    for (int k = 1; k < 16; k++) {
        m0 = fmaxf(m0, fmaxf(s[4 * k], s[4 * k + 1]));
        m1 = fmaxf(m1, fmaxf(s[4 * k + 2], s[4 * k + 3]));
    }
    m0 = fmaxf(m0, __shfl_xor_sync(0xffffffffu, m0, 1));
    m1 = fmaxf(m1, __shfl_xor_sync(0xffffffffu, m1, 1));
    m0 = fmaxf(m0, __shfl_xor_sync(0xffffffffu, m0, 2));
    m1 = fmaxf(m1, __shfl_xor_sync(0xffffffffu, m1, 2));
    if (!first) {
        m0 = fmaxf(m0, 0.f);
        m1 = fmaxf(m1, 0.f);
    }
    a0 = first ? 1.f : ex2(-m0);
    a1 = first ? 1.f : ex2(-m1);
    m[0] += m0;
    m[1] += m1;
    softmax_shift(s, m0, m1);
}
template <int J0, int J1>
__device__ __forceinline__ void softmax_exp(const float (&s)[64], uint32_t (&p)[32], float (&t)[4]) {
#pragma unroll
    for (int k = J0; k < J1; k++) {
        const float e0 = ex2(s[4 * k]), e1 = ex2(s[4 * k + 1]), e2 = ex2(s[4 * k + 2]), e3 = ex2(s[4 * k + 3]);
        if (k == 0) { t[0] = e0; t[1] = e1; t[2] = e2; t[3] = e3; }
        else { t[0] += e0; t[1] += e1; t[2] += e2; t[3] += e3; }
        p[2 * k] = pack2(e0, e1);
        p[2 * k + 1] = pack2(e2, e3);
    }
}
__device__ __forceinline__ void fma8(float (&acc)[8], float a, uint4 w) {
    acc[0] = fmaf(a, bf_lo(w.x), acc[0]); acc[1] = fmaf(a, bf_hi(w.x), acc[1]);
    acc[2] = fmaf(a, bf_lo(w.y), acc[2]); acc[3] = fmaf(a, bf_hi(w.y), acc[3]);
    acc[4] = fmaf(a, bf_lo(w.z), acc[4]); acc[5] = fmaf(a, bf_hi(w.z), acc[5]);
    acc[6] = fmaf(a, bf_lo(w.w), acc[6]); acc[7] = fmaf(a, bf_hi(w.w), acc[7]);
}
__device__ __forceinline__ void mma16816(float (&d)[4], const uint32_t* a, uint32_t b0, uint32_t b1) {
    asm("mma.sync.aligned.m16n8k16.row.col.f32.bf16.bf16.f32 {%0, %1, %2, %3}, {%4, %5, %6, %7}, {%8, %9}, {%0, %1, %2, %3};"
        : "+f"(d[0]), "+f"(d[1]), "+f"(d[2]), "+f"(d[3]) : "r"(a[0]), "r"(a[1]), "r"(a[2]), "r"(a[3]), "r"(b0), "r"(b1));
}
__device__ __forceinline__ uint2 best_key(const uint32_t* keys, int lane, uint32_t ep, uint32_t cur, int enough) {
#pragma unroll 1
    for (;;) {
        const uint4 k = ld_poll(reinterpret_cast<const uint4*>(keys) + lane);
        const bool ok = (((k.x ^ ep) | (k.y ^ ep) | (k.z ^ ep) | (k.w ^ ep)) & 31) == 0;
        const uint32_t best = __reduce_max_sync(0xffffffffu, ok ? max(max(k.x, k.y), max(k.z, k.w)) : 0u);
        const int n = __popc(__ballot_sync(0xffffffffu, ok));
        if (n == 32 || (n >= enough && best != cur)) return make_uint2(best, n == 32);
        __nanosleep(KSLEEP);
    }
}

__global__ void __cluster_dims__(2, 1, 1) __launch_bounds__(384, 1)
fused_kernel(const __grid_constant__ CUtensorMap tm_ckv, const __grid_constant__ CUtensorMap tm_wq,
             const __grid_constant__ CUtensorMap tm_wuk, const __grid_constant__ CUtensorMap tm_wuv,
             const __grid_constant__ CUtensorMap tm_wo, const __grid_constant__ CUtensorMap tm_wg,
             const __grid_constant__ CUtensorMap tm_wu,
             const __grid_constant__ CUtensorMap tm_wm, const __grid_constant__ CUtensorMap tm_x, const Params P) {
    extern __shared__ __align__(1024) uint8_t smem[];
    const uint32_t sb = (uint32_t)__cvta_generic_to_shared(smem);
    const int tid = threadIdx.x, lane = tid & 31, warp = __shfl_sync(0xffffffffu, tid >> 5, 0), wg = warp >> 2;
    const uint32_t sm = blockIdx.x < 8 ? blockIdx.x + 124 : blockIdx.x - 8, smq = ((sm - 64) * 147) >> 11;
    const int rb = sm < 64 ? (sm & 14) * 8 + (sm >> 4) * 2 + (sm & 1)
                 : sm < 120 ? ((sm - 64 - smq * 14) & 14) * 8 + 24 + smq * 2 + (sm & 1) : sm < 124 ? sm + 8 : sm - 116;
    const int grp = rb >> 3, j = rb & 7, cq = j & 3, kh = grp & 1, ort = (grp & 14) + (j >> 2);
    if (warp == 0) TS(0);

    if (lane == 0) {
        if (warp == 8) {
            asm volatile("prefetch.tensormap [%0];" ::"l"(rb >= NCTA ? &tm_wm : (j & 1) ? &tm_wuv : &tm_wuk) : "memory");
            asm volatile("prefetch.tensormap [%0];" ::"l"(&tm_ckv) : "memory");
            *reinterpret_cast<uint2*>(smem + SM_EP + 16) = make_uint2(0, 0);
        }
        const u64 cnt = (warp < 5 ? (rb < NCTA ? 0x844444441111111ull : 0x888888881111111ull) : warp < 10 ? 0x111111188888888ull : 0x118121ull) >> (12 * (warp % 5));
#pragma unroll
        for (int i = 0; i < 3; i++) mbar_init(sb + SM_BAR + 24 * warp + 8 * i, ((uint32_t)cnt >> (4 * i)) & 15);
        fence_async_smem();
        asm volatile("fence.mbarrier_init.release.cluster;" ::: "memory");
    }
    __syncthreads();
    asm volatile("barrier.cluster.arrive.relaxed.aligned;\nbarrier.cluster.wait.aligned;" ::: "memory");

    if (rb >= NCTA) {
        float* sc = reinterpret_cast<float*>(smem + 6 * SLOT);
        float* red = sc + 512;
        uint32_t ph = 0x7f, sl = 0;
        if (warp == 8) {
#pragma unroll 1
            for (int i = 0; i < 24; i++) {
                slot_acquire(sb, ph, sl);
                tma2d(sb + sl * SLOT, &tm_wm, (i >> 3) * 1024 + (rb - NCTA) * 256, (i & 7) * 64, sb + BAR_FULL + 8 * sl, HINT & 64);
                if (++sl == 6) sl = 0;
            }
#pragma unroll 1
            for (int i = 0; i <= NFFN / NSPARE; i++) {
                const int b = (rb - NCTA) * (NFFN / NSPARE) + i;
                if (i < NFFN / NSPARE) {
                    asm volatile("cp.async.bulk.wait_group.read 0;" ::: "memory");
                    uint32_t done = 0x7f;
                    slot_acquire(sb, done, i & 1);
#pragma unroll 1
                    for (int k = 0; k < 4; k++) tma2d(sb + (i & 1) * SLOT + k * 8192, k < 2 ? &tm_wg : &tm_wu, b * 16, (k & 1) * 256, sb + BAR_FULL + 8 * (i & 1), (HINT & 128) && (i & 3) == 3);
                }
                if (i) {
                    mbar_wait(sb + BAR_FULL + 8 * (~i & 1), ((i - 1) >> 1) & 1);
                    bulk_store(g_wf + (b - 1) * SLOT, sb + (~i & 1) * SLOT, SLOT, HINT & 256);
                    asm volatile("cp.async.bulk.commit_group;" ::: "memory");
                }
            }
            asm volatile("cp.async.bulk.wait_group 0;" ::: "memory");
            fence_async_global();
            TS(4);
        } else if (warp < 8) {
            const uint32_t c2 = __ldg(reinterpret_cast<const uint32_t*>(P.c) + tid), ep = __ldcg(&g_sync.epoch[0]) + 1;
            sc[2 * tid] = rbf(bf_lo(c2) * sigmoid(bf_lo(c2)));
            sc[2 * tid + 1] = rbf(bf_hi(c2) * sigmoid(bf_hi(c2)));
            ph = 0;
#pragma unroll 1
            for (int ps = 0; ps < 3; ps++) {
                bar_sync(1, 256);
                float acc[8] = {0.f, 0.f, 0.f, 0.f, 0.f, 0.f, 0.f, 0.f};
#pragma unroll 1
                for (int bt = 0; bt < 8; bt++) {
                    slot_wait(sb + BAR_FULL, ph, sl);
#pragma unroll 4
                    for (int i = 0; i < 8; i++)
                        fma8(acc, sc[bt * 64 + warp * 8 + i], *reinterpret_cast<const uint4*>(smem + sl * SLOT + (warp * 8 + i) * 512 + lane * 16));
                    __syncwarp();
                    mbar_arrive_if(sb + BAR_EMPTY + 8 * sl, lane == 0);
                    if (++sl == 6) sl = 0;
                }
                *reinterpret_cast<float4*>(red + warp * 256 + lane * 8) = make_float4(acc[0], acc[1], acc[2], acc[3]);
                *reinterpret_cast<float4*>(red + warp * 256 + lane * 8 + 4) = make_float4(acc[4], acc[5], acc[6], acc[7]);
                bar_sync(1, 256);
                float v = 0.f;
#pragma unroll
                for (int i = 0; i < 8; i++) v += red[i * 256 + tid];
                if (ps == 0) st_pub(g_mod1 + (rb - NCTA) * 256 + tid, (pack2(0.f, v) & 0xffff0000u) | (ep & 0xffffu), true);
                else g_mod[ps * 1024 + (rb - NCTA) * 256 + tid] = __float2bfloat16_rn(v);
                if (warp == 0) TS(1 + ps);
            }
        }
        __syncthreads();
        if (tid < 2) flag_add(&g_sync.cnt[7 * 8]);
        return;
    }

    if (wg == 2) {
        asm volatile("setmaxnreg.dec.sync.aligned.u32 40;");
        const CUtensorMap* tw = (j & 1) ? &tm_wuv : &tm_wuk;
        if (warp == 8) {
            const uint32_t rank = j & 1, half = rank * 16384;
            uint32_t eph = 0x7f, r = 0;
#pragma unroll 1
            for (int hp = 0; hp < 2; hp++) {
                uint32_t wtab = w_table(hp), atab = a_table(hp);
                const int hc = 4 * grp + 2 * hp;
#pragma unroll 1
                for (int u = 0; u < 16; u++) {
                    if (u < 4) {
                        const uint32_t ws = (wtab >> (4 * u)) & 15;
                        slot_acquire(sb, eph, ws);
                        load_tile(sb, ws, 0, tw, u * 128, hc, false, HINT & 1);
                        PT();
                    }
                    if (hp == 1 && (u & 7) == 4) mbar_wait(sb + BAR_FLAG + 24 + (u & 8), 0);
                    const uint32_t as = a_next(atab);
                    slot_acquire(sb, eph, as);
                    load_tile(sb, as, half, &tm_ckv, ((u & 12) + (j >> 1)) * 128, (u & 3) * 2 + rank, true, (HINT & 8) && hp);
                    PT();
                    if (hp == 1 && (u | 2) == 3 && lane == 0)
                        asm volatile("red.relaxed.gpu.global.add.u32 [%0], 1;" ::"l"(&g_sync.cnt[(grp * 8 + 3 + (u >> 1)) * 8]) : "memory");
                }
                const uint8_t* src = g_h + (15 - j) * 4 * SLOT;
#pragma unroll 1
                for (int u = 0; u < 8; u++) {
                    if ((u & 3) == 0) {
                        mbar_wait(sb + BAR_FLAG + (2 + 8 * hp) * u, 0);
                        fence_async_global();
                    }
                    if (u < 4) {
                        const uint32_t ws = (wtab >> (4 * u)) & 15;
                        slot_acquire(sb, eph, ws);
                        load_tile(sb, ws, half, &tm_wq, u * 128, hc + rank, true, HINT & 1);
                        PT();
                    }
                    const uint32_t as = a_next(atab);
                    slot_acquire(sb, eph, as);
                    load_bulk(sb, as, 0, src, SLOT, false, (HINT & 8) && hp);
                    PT();
                    src += u == 3 ? (8 * j - 63) * SLOT : SLOT;
                }
                const int step = hp ? -2 * SLOT : 2 * SLOT;
                src = g_KV + (size_t)(grp * 32 + 30 * hp) * SLOT + half - step;
#pragma unroll 1
                for (int n = 0; n <= 17; n++) {
                    if (n == 8) {
                        mbar_wait(sb + BAR_FLAG + 16 + 32 * hp, 0);
                        fence_async_global();
                    }
                    const uint8_t* v = src + SLOT;
                    src += n < 16 - j ? step : n == 16 - j ? (2 * j - 15) * step : -step;
                    if (n < 17) {
                        slot_acquire(sb, eph, r);
                        if (n != 15 - (j & 6)) load_bulk(sb, r, half, src, SLOT / 2, true, (HINT & 4) && (hp || !(HINT & 32)));
                        else load_bulk(sb, r, 0, src - half, SLOT, false, (HINT & 4) && (hp || !(HINT & 32)));
                        PT();
                        r = ring_next(r);
                    }
                    if (n) {
                        slot_acquire(sb, eph, r);
                        if (n != 16 - (j & 6)) load_bulk(sb, r, half, v, SLOT / 2, true, (HINT & 4) && (hp || !(HINT & 32)));
                        else load_bulk(sb, r, 0, v - half, SLOT, false, (HINT & 4) && (hp || !(HINT & 32)));
                        PT();
                        r = ring_next(r);
                    }
                    asm volatile("st.volatile.shared.u32 [%0], %1;" ::"r"(sb + SM_EP + 16), "r"(18 * hp + n + 1) : "memory");
                }
            }
            uint32_t otab = O_TABLE, ready = 0;
#pragma unroll 1
            for (int i = 0; i < 17; i++) {
                const bool dyn = i >= 8 && i < 15;
                const uint32_t want = dyn ? 15u << (4 * (i - 8)) : 1u << max(i + 14, 28);
                if (!(ready & want)) {
                    do {
                        asm volatile("ld.acquire.cta.shared.u32 %0, [%1];" : "=r"(ready) : "r"(sb + SM_EP + 20) : "memory");
                        ready = __shfl_sync(0xffffffffu, ready, 0);
                    } while (!(ready & want));
                    fence_async_global();
                }
                const int head = o_head(dyn ? (ready >> (4 * (i - 8))) & 15 : i, kh);
                const uint32_t as = o_next(otab), ws = o_next(otab), off = i < 15 ? half : kh * 16384;
                slot_acquire(sb, eph, as);
                load_bulk(sb, as, off, g_ctx + (size_t)(ort * 32 + head) * SLOT + off, SLOT / 2, i < 15, HINT & 16);
                if (i == 15) load_tile(sb, as, off ^ 16384, &tm_x, ort * 128 + kh * 64, cq * 2, false, false);
                if (i == 16) load_bulk(sb, as, off ^ 16384, P.wdown + min(rb, NFFN - 1) * 8192, SLOT / 2, false, false);
                PT();
                slot_acquire(sb, eph, ws);
                load_tile(sb, ws, 0, &tm_wo, head * 128, cq * 2, false, HINT & 2);
                PT();
                if (i == 0) o_next(otab);
            }
            if (rb < NFFN) {
                slot_acquire(sb, eph, 5);
                load_bulk(sb, 5, 0, g_wf + rb * SLOT, SLOT, false, false);
            }
        } else if (warp == 9) {
            l2_prefetch(P.ckv + rb * 2048, 4096);
            mbar_watch(sb + BAR_FULL, 0);
            l2_prefetch(P.ckv + 512 * 512 + rb * 2048, 4096);
            mbar_watch(sb + BAR_FULL + 8 * 4, 0);
            l2_prefetch(P.ckv + 1024 * 512 + rb * 4096, 8192);
            TS(40);
#pragma unroll 1
            for (int i = 0; i < 15; i++) {
                step_watch(sb + SM_EP + 16, i == 0 ? 0 : i < 5 ? PFA + i : 13 + PFB + i);
                if (i == 12) mbar_watch(sb + BAR_FLAG + 8 * 7, 0);
                const int rf = min(rb, NFFN - 1);
                const uint8_t* p = i == 3 ? reinterpret_cast<const uint8_t*>(P.ckv) + rb * 16384
                                 : i == 4 ? g_h + rb * 16384
                                 : i < 9 ? g_ctx + (size_t)(ort * 32 + o_head(cq + 2 * ((i - 5) & 2), kh)) * SLOT + (i & 1) * 16384
                                 : i < 11 ? reinterpret_cast<const uint8_t*>(P.wo) + (grp * 16 + (~i & 1) * 8 + j) * 16384
                                 : i == 11 ? reinterpret_cast<const uint8_t*>(P.x) + rb * 16384
                                 : i == 12 ? reinterpret_cast<const uint8_t*>(P.wdown) + rf * 16384 : g_wf + rf * SLOT + (i & 1) * 16384;
                if (i < 3) tma3d_prefetch(i == 1 ? tw : &tm_wq, (j >> 1) * 128, grp * 4 + (i == 1 ? 2 : i + (j & 1)));
                else l2_prefetch(p, 16384);
            }
            const uint32_t v = lds32(sb + SM_EP) - 1;
            sts128(sb + SM_RED + lane * 16, make_uint4(v, v, v, v));
            fence_async_smem();
            __syncwarp();
#pragma unroll 1
            for (int i = 0; i < OB / 32; i++) bulk_store(g_out + rb * OB + i * 32, sb + SM_RED, 512, false);
            asm volatile("cp.async.bulk.commit_group;\ncp.async.bulk.wait_group 0;" ::: "memory");
            fence_async_global();
            __syncwarp();
            mbar_arrive_if(sb + BAR_PF, lane == 0);
            if (lane == 0) mbar_watch(sb + BAR_END, 0);
        } else {
            const uint32_t ep = __ldcg(&g_sync.epoch[0]) + 1;
            asm volatile("st.shared.u32 [%0], %1;" ::"r"(sb + SM_EP), "r"(ep) : "memory");
            mbar_wait(sb + BAR_FULL + 8 * 4, 0);
            {
                uint4 v[4];
                for (;;) {
                    uint32_t bad = 0;
#pragma unroll
                    for (int k = 0; k < 4; k++) v[k] = ld_poll(reinterpret_cast<const uint4*>(g_mod1) + (warp & 1) * 128 + k * 32 + lane);
#pragma unroll
                    for (int k = 0; k < 4; k++) bad |= (v[k].x ^ ep) | (v[k].y ^ ep) | (v[k].z ^ ep) | (v[k].w ^ ep);
                    if (__all_sync(0xffffffffu, (bad & 0xffff) == 0)) break;
                    __nanosleep(100);
                }
                const uint32_t one = (warp & 1) ? ONE2 : 0x80008000u;
#pragma unroll
                for (int k = 0; k < 4; k++)
                    *reinterpret_cast<uint2*>(smem + SM_TAB + (warp & 1) * 1024 + k * 256 + lane * 8) =
                        make_uint2(badd(__byte_perm(v[k].x, v[k].y, 0x7632), one), badd(__byte_perm(v[k].z, v[k].w, 0x7632), one));
            }
            __syncwarp();
            mbar_arrive_if(sb + BAR_FLAG + 8 * 8, lane == 0);
            if (warp == 10) {
#pragma unroll 1
                for (int i = 0; i < 9; i++) {
                    mbar_sleep(sb + BAR_DONE + 8 * i);
                    if (lane == 0) flag_add(i && ((i - 1) & 2) ? &g_sync.ctxcnt[((i & 1) ? 15 - j : j) * 32 + 2 * grp + (i > 4)] : &g_sync.cnt[(grp * 8 + i) * 8]);
                    if (i == 0) TS(43);
                }
            } else {
                TS(42);
#pragma unroll 1
                for (int i = 0; i < 8; i++) {
                    mbar_sleep(sb + BAR_DONE + 8 * (i == 7 ? 6 : i == 4 ? 3 : i));
                    if (lane < 2) flag_wait(&g_sync.cnt[((i == 0 ? (lane ? j : 15 - j) : i == 7 ? 0 : grp) * 8 + i) * 8], 8 * ep);
                    __syncwarp();
                    mbar_arrive_if(sb + BAR_FLAG + 8 * i, lane == 0 && i < 7);
                    TS(48 + i);
                }
                const uint32_t *mp = reinterpret_cast<const uint32_t*>(g_mod) + lane, *wp = reinterpret_cast<const uint32_t*>(P.wr) + lane;
                float ra = 0.f, rs = 0.f;
#pragma unroll 1
                for (int k = 0; k < 256; k += 32) {
                    const uint32_t ga = __ldcg(mp + 512 + k), sh = __ldcg(mp + 768 + k), c1 = badd(__ldcg(mp + 1024 + k), ONE2);
                    const uint32_t gb = __ldcg(mp + 1280 + k), ww = __ldg(wp + k);
                    const float a0 = bf_lo(c1) * bf_lo(ww), a1 = bf_hi(c1) * bf_hi(ww);
                    ra += a0 + a1;
                    rs = fmaf(bf_lo(sh), bf_lo(ww), fmaf(bf_hi(sh), bf_hi(ww), rs));
                    if (k >> 6 == cq) {
                        sts128(sb + SM_TAB + ((k & 32) + lane) * 16, make_uint4(ga << 16, ga & 0xffff0000u, __float_as_uint(a0), __float_as_uint(a1)));
                        sts128(sb + SM_TAB + 1024 + ((k & 32) + lane) * 16, make_uint4(c1, sh, gb, 0));
                    }
                }
#pragma unroll 1
                for (int o = 16; o > 0; o >>= 1) {
                    ra += __shfl_xor_sync(0xffffffffu, ra, o);
                    rs += __shfl_xor_sync(0xffffffffu, rs, o);
                }
                *reinterpret_cast<float2*>(smem + SM_EP + 8) = make_float2(ra, rs);
                __syncwarp();
                mbar_arrive_if(sb + BAR_FLAG + 8 * 7, lane == 0);
                const uint32_t* f = &g_sync.ctxcnt[ort * 32 + o_head(min(lane, 16), kh)];
                uint32_t ready = -(j & 1), list = 0, sh = 0, qa;
                asm("mapa.shared::cluster.u32 %0, %1, %2;" : "=r"(qa) : "r"(sb + SM_EP + 20), "r"(lane & 1));
                while (ready != ~0u) {
                    uint32_t v;
                    asm volatile("ld.acquire.gpu.global.u32 %0, [%1];" : "=r"(v) : "l"(f) : "memory");
                    const uint32_t now = __ballot_sync(0xffffffffu, (int)(v - ep) >= 0);
#pragma unroll 1
                    for (uint32_t fresh = now & ~ready & 0x7f00; fresh; fresh &= fresh - 1, sh += 4) list |= (__ffs(fresh) - 1) << sh;
                    list |= (((now & 0xff) + 1) >> 8 << 28) | ((now & 0x18000) << 14);
                    if (now != ready && lane < 2) asm volatile("st.relaxed.cluster.shared::cluster.u32 [%0], %1;" ::"r"(qa), "r"(list) : "memory");
                    if ((now & 0xff) == 0xff) mbar_sleep(sb + BAR_DONE + 8 * 7);
                    ready = now;
                    __nanosleep(POLL_NS);
                }
                TS(45);
            }
        }
    } else {
        asm volatile("setmaxnreg.inc.sync.aligned.u32 232;");
        const bool elected = (tid & 127) == 0, rel = (tid & 95) == 0;
        uint32_t eb;
        asm("mapa.shared::cluster.u32 %0, %1, %2;" : "=r"(eb) : "r"(sb + BAR_EMPTY), "r"(warp & 1));
        const int g = lane >> 2, c4 = lane & 3;
        const uint32_t toff = warp * 4096 + g * 64 + ((c4 ^ (g >> 1)) << 4);
        uint32_t fph = 0, r = 0;
        if (wg == 1) bar_arrive(1, 256);
        const uint32_t kd = desc_k(sb), wd = desc_mn(sb), vd = ((sb & 0x3ffff) >> 4) | (32u << 16);
        const int nL = 16 - j, hn = nL - 1 + wg;
        float s[64], o[64], li[2] = {0.f, 0.f};
        uint8_t* cimg = g_ctx;
        uint32_t p[32] = {};
#pragma unroll 1
        for (int hp = 0; hp < 2; hp++) {
            float m[2] = {0.f, 0.f}, l[2] = {0.f, 0.f}, t[4] = {0.f, 0.f, 0.f, 0.f};
            bool shifted = false, bad = false, plain = false;
            uint32_t qa = desc_k(sb + 5 * SLOT + (wg ^ 1) * 8192);
            uint8_t* limg = g_ctx + (size_t)((15 - j) * 32 + 2 * grp + hp) * SLOT;
            {
                const int step = hp ? -8 * SLOT : 8 * SLOT;
                uint8_t* img = g_KV + (size_t)(grp * 32 + (hp ? j ^ 30 : j)) * SLOT - step;
                const float sc = (j & 1) ? 1.f : SM_C;
                const uint32_t wtab = w_table(hp);
                uint32_t atab = hp ? 0x562u : a_table(0);
#pragma unroll 1
                for (int u = 0;; u += 2) {
                    proj_tile<false>(s, o, u, u ? 0 : hp, sb, wg, eb, rel, fph, wtab, atab, u ? img : cimg, toff, u ? sc : li[0], u ? sc : li[1], (hp | u) == 0, P.x, rb * 16 + warp * 2, p);
                    __syncwarp();
                    mbar_arrive_if(sb + BAR_DONE + 4 * u + 32 * hp, lane == 0 && (hp | u) != 0);
                    if (elected) TS(1 + 10 * hp + u + 20 * wg);
                    if (proj_tile<true>(o, s, u + 1, 0, sb, wg, eb, rel, fph, wtab, atab, img + step, toff, sc, sc, (hp | u) == 0, P.x, rb * 16 + warp * 2, p)) break;
                    if (elected) TS(2 + 10 * hp + u + 20 * wg);
                    img += 2 * step;
                }
            }
            if (elected) TS(6 + 10 * hp + 20 * wg);
            int n = -1;
#pragma unroll 1
            for (;;) {
                while (bad || plain) {
                    if (bad) {
                        float a0, a1;
                        softmax_remax(s, m, n == 0 || n == nL, a0, a1);
                        shifted = true;
                        l[0] *= a0;
                        l[1] *= a1;
#pragma unroll
                        for (int i = 0; i < 64; i++) o[i] *= (i & 2) ? a1 : a0;
                    }
                    softmax_exp<0, 16>(s, p, t);
                    t[0] += t[1];
                    t[2] += t[3];
                    bad = !bad && softmax_unsafe(t[0], t[2], false);
                    plain = false;
                }
#pragma unroll 1
                do {
                    l[0] += t[0];
                    l[1] += t[2];
                    if (++n > 16) break;
                    const uint32_t ks = r;
                    uint32_t vs = ring_next(r);
                    r = ring_next(vs);
                    bar_sync(1 + wg, 256);
                    const float x = (float)((warp & 3) * 16 + g - 2 * c4);
                    if (n == hn) {
                        float sh[32];
                        qk_issue(sh, qa, kd + ks * (SLOT / 16));
                        slot_wait(sb + BAR_FULL, fph, vs);
                        pv_issue(o, p, vd + vs * (SLOT / 16), 1, false);
                        bar_arrive(2 - wg, 256);
                        wg_wait<1>();
                        reg_fence(sh);
                        tri_mask_copy(s, sh, x);
                        release_if(eb, ks, rel);
                        release_if(eb, 5 + wg, rel && (!wg || n == 16));
                        if (!wg) {
                            qa += SLOT / 16;
                            fence_async_smem();
                            if (shifted) softmax_shift(s, m[0], m[1]);
                        }
                        float e[4 * EARLY];
#pragma unroll
                        for (int i = 0; i < 4 * EARLY; i++) {
                            e[i] = ex2(s[i]);
                            t[i & 3] = i < 4 ? e[i] : t[i & 3] + e[i];
                        }
                        reg_fence(e);
                        slot_wait(sb + BAR_FULL, fph, r);
                        wg_wait<0>();
                        reg_fence(o);
                        reg_fence(e);
                        release_if(eb, vs, rel);
#pragma unroll
                        for (int i = 0; i < 2 * EARLY; i++) p[i] = pack2(e[2 * i], e[2 * i + 1]);
                        softmax_exp<EARLY, 8>(s, p, t);
                        if (wg) {
                            ctx_store<true>(limg, toff, o, l[0], l[1]);
                            __syncwarp();
                            mbar_arrive_if(sb + BAR_DONE + 24 + 32 * hp, lane == 0);
                            l[0] = l[1] = m[0] = m[1] = 0.f;
                            shifted = false;
                        }
                        t[0] += t[1];
                        t[2] += t[3];
                        bad = softmax_unsafe(t[0], t[2], wg);
                        continue;
                    }
                    if (n == 0 || n == nL) {
                        qk_issue(s, qa, kd + ks * (SLOT / 16));
                        if (n == 0) {
                            r = vs;
                            vs = 4 - hp;
                            slot_wait(sb + BAR_FULL, fph, 6);
                            gemm_issue<false>(o, qa + SLOT / 16, wd + vs * (SLOT / 16), 1, false);
                        } else {
                            slot_wait(sb + BAR_FULL, fph, vs);
                            pv_issue(o, p, vd + vs * (SLOT / 16), 1, true);
                        }
                        bar_arrive(2 - wg, 256);
                        const float i0 = n ? rcp(quad_sum(l[0])) : 1.f, i1 = n ? rcp(quad_sum(l[1])) : 1.f;
                        wg_wait<1>();
                        reg_fence(s);
                        release_if(eb, ks, rel);
                        release_if(eb, 6, rel && n == 16);
                        tri_mask(s, n ? x : 64.f);
                        float e[4 * EARLY];
#pragma unroll
                        for (int i = 0; i < 4 * EARLY; i++) {
                            e[i] = ex2(s[i]);
                            t[i & 3] = i < 4 ? e[i] : t[i & 3] + e[i];
                        }
                        reg_fence(e);
                        reg_fence(s);
                        reg_fence(t);
                        slot_wait(sb + BAR_FULL, fph, r);
                        if (SF & 1) sched_fence(fph, P.zero);
                        wg_wait<0>();
                        reg_fence(o);
                        reg_fence(e);
                        release_if(eb, vs, rel);
#pragma unroll
                        for (int i = 0; i < 2 * EARLY; i++) p[i] = pack2(e[2 * i], e[2 * i + 1]);
                        softmax_exp<EARLY, MSPLIT>(s, p, t);
                        tile_store(limg, sb + 6 * SLOT, toff, o, i0, i1, n);
                        reg_fence(t);
                        if (SF & 2) sched_fence(fph, P.zero);
                        reg_fence(s);
                        softmax_exp<MSPLIT, 16>(s, p, t);
                        __syncwarp();
                        mbar_arrive_if(sb + BAR_DONE + 24 + 32 * hp, lane == 0 && n);
                        l[0] = l[1] = m[0] = m[1] = 0.f;
                        shifted = false;
                        t[0] += t[1];
                        t[2] += t[3];
                        bad = __any_sync(0xffffffffu, fmaxf(t[0], t[2]) > SM_HI || fminf(t[0], t[2]) < SM_LO);
                        continue;
                    }
                    qk_issue(s, qa, kd + ks * (SLOT / 16));
                    slot_wait(sb + BAR_FULL, fph, vs);
                    pv_issue(o, p, vd + vs * (SLOT / 16), n != 1 && n != nL + 1, n == hn + 1);
                    bar_arrive(2 - wg, 256);
                    wg_wait<1>();
                    reg_fence(s);
                    release_if(eb, ks, rel);
                    release_if(eb, 6, rel && n == 16);
                    if (n == nL - 1) {
                        tri_mask(s, x);
                        release_if(eb, 5, rel);
                        qa += SLOT / 16;
                        fence_async_smem();
                    }
                    if (shifted) {
                        slot_wait(sb + BAR_FULL, fph, r);
                        wg_wait<0>();
                        reg_fence(o);
                        release_if(eb, vs, rel);
                        softmax_shift(s, m[0], m[1]);
                        plain = true;
                        break;
                    }
                    float e[4 * EARLY];
#pragma unroll
                    for (int i = 0; i < 4 * EARLY; i++) {
                        e[i] = ex2(s[i]);
                        t[i & 3] = i < 4 ? e[i] : t[i & 3] + e[i];
                    }
                    reg_fence(e);
                    slot_wait(sb + BAR_FULL, fph, r);
                    wg_wait<0>();
                    reg_fence(o);
                    reg_fence(e);
                    release_if(eb, vs, rel);
#pragma unroll
                    for (int i = 0; i < 2 * EARLY; i++) p[i] = pack2(e[2 * i], e[2 * i + 1]);
                    softmax_exp<EARLY, 16>(s, p, t);
                    t[0] += t[1];
                    t[2] += t[3];
                    bad = softmax_unsafe(t[0], t[2], false);
                } while (!bad);
                if (!bad && !plain) break;
            }
            const uint32_t vs = r, ga = desc_k(sb + (hp ? 2 * (wg ^ kh ^ 1) : wg) * 8192);
            r = ring_next(r);
            slot_wait(sb + BAR_FULL, fph, 5);
            slot_wait(sb + BAR_FULL, fph, r);
            bar_sync(1 + wg, 256);
            gemm_issue<true>(s, ga + 5 * (SLOT / 16), wd + r * (SLOT / 16), 0, hp);
            pv_issue(o, p, vd + vs * (SLOT / 16), j, hn == 16);
            bar_arrive(2 - wg, 256);
            li[0] = rcp(quad_sum(l[0]));
            li[1] = rcp(quad_sum(l[1]));
            cimg = limg + (ptrdiff_t)(2 * j - 15) * 32 * SLOT + (wg ? -16384 : 16384);
            wg_wait<1>();
            release_if(eb, 5, rel);
            release_if(eb, r, rel && hp);
            wg_wait<0>();
            release_if(eb, vs, rel);
            reg_fence(o);
            img_store_global<0>(cimg, toff, o, li[0], li[1]);
            if (elected) TS(8 + 10 * hp + 20 * wg);
        }
        uint32_t otab = 0x2351604u;
        const uint32_t oa = desc_k(sb + (wg ^ kh ^ 1) * 16384);
        const int t7 = tid & 127, w4 = warp & 3, row = ort * 128 + kh * 64 + w4 * 16 + g;
#pragma unroll 1
        for (int i = 1; i < 15 - wg; i++) {
            const uint32_t as = o_next(otab), ws = o_next(otab);
            slot_wait(sb + BAR_FULL, fph, as);
            slot_wait(sb + BAR_FULL, fph, ws);
            bar_sync(1 + wg, 256);
            gemm_issue<false>(s, oa + as * (SLOT / 16), wd + ws * (SLOT / 16), 1, true);
            bar_arrive(2 - wg, 256);
            wg_wait<1>();
            reg_fence(o);
            if (i == 1) img_store_global<1>(cimg, toff, o, li[0], li[1]);
            if (i == 2) {
                img_store_global<2>(cimg, toff, o, li[0], li[1]);
                img_store_global<3>(cimg, toff, o, li[0], li[1]);
                __syncwarp();
                mbar_arrive_if(sb + BAR_DONE + 64, lane == 0);
            }
            wg_wait<0>();
            release_if(eb, as, rel);
            release_if(eb, ws, rel);
        }
        mbar_wait(sb + BAR_PF, 0);
        const uint32_t ep = lds32(sb + SM_EP);
        uint32_t eb2 = sb + BAR_END;
        if (wg == 0) {
            reg_fence(s);
            if (elected) TS(9);
            TT(1);
#pragma unroll
            for (int v = 0; v < 8; v++)
                st_pub(g_out + rb * OB + v * 128 + t7, make_uint4((pack2(s[8 * v], s[8 * v + 1]) & ~1u) | (ep & 1), pack2(s[8 * v + 2], s[8 * v + 3]),
                                                                      pack2(s[8 * v + 4], s[8 * v + 5]), pack2(s[8 * v + 6], s[8 * v + 7])), true);
            constexpr uint32_t s1 = 5, s2 = 6;
            bar_sync(4, 256);
            uint32_t wf[64];
            float wn[64];
            if (rb < NFFN) {
                slot_wait(sb + BAR_FULL, fph, s1);
                const uint32_t a = sb + s1 * SLOT + (w4 * 128 + (lane >> 4) * 8 + (lane & 7)) * 32 + ((lane >> 3) & 1) * 16;
#pragma unroll
                for (int i = 0; i < 16; i++)
                    asm volatile("ldmatrix.sync.aligned.m8n8.x4.trans.shared.b16 {%0, %1, %2, %3}, [%4];"
                                 : "=r"(wf[4 * i]), "=r"(wf[4 * i + 1]), "=r"(wf[4 * i + 2]), "=r"(wf[4 * i + 3])
                                 : "r"(a + (i >> 3) * 16384 + (i & 7) * 512) : "memory");
                slot_wait(sb + BAR_FULL, fph, s2);
#pragma unroll
                for (int i = 0; i < 16; i++) {
                    const uint2 w = *reinterpret_cast<const uint2*>(smem + s2 * SLOT + (kh ^ 1) * 16384 + i * 1024 + t7 * 8);
                    wn[4 * i] = bf_lo(w.x); wn[4 * i + 1] = bf_hi(w.x); wn[4 * i + 2] = bf_lo(w.y); wn[4 * i + 3] = bf_hi(w.y);
                }
                reg_fence(wn);
            }
            const uint32_t gbf = __ldcg(reinterpret_cast<const uint32_t*>(g_mod) + 1280 + rb * 2 + (tid & 1));
            if (elected) TS(10);
            TT(2);
            float* sred = reinterpret_cast<float*>(smem + SM_RED);
            uint32_t best = ep ^ 1, all;
            bool fresh;
            do {
                if (warp == 0) {
                    const uint2 k = best_key(g_key + cq * 128, lane, ep, best, rb < NFFN ? SPEC : 32);
                    *reinterpret_cast<uint2*>(smem + SM_EP + 24) = k;
                    mbar_arrive_if(sb + BAR_BEST, lane == 0 && k.y);
                }
                bar_sync(3, 128);
                const uint2 k = *reinterpret_cast<const uint2*>(smem + SM_EP + 24);
                fresh = k.x != best;
                best = k.x;
                all = k.y;
                TT(3);
                if (!fresh || rb >= NFFN) break;
                const uint4* cp = g_cand + ((~best >> 9) & 127) * 192;
                uint4 cv[6];
                for (;;) {
                    uint32_t bad = 0;
#pragma unroll
                    for (int v = 0; v < 6; v++) cv[v] = ld_poll(cp + w4 * 24 + v * 4 + c4);
#pragma unroll
                    for (int v = 0; v < 6; v++) bad |= cv[v].w ^ ep;
                    if (__all_sync(0xffffffffu, bad == 0)) break;
                    if (CSLEEP) __nanosleep(CSLEEP);
                }
            TT(4);
                float d[4][4] = {};
#pragma unroll
                for (int k = 0; k < 8; k++) {
                    const uint32_t b0 = (&cv[(2 * k) / 3].x)[(2 * k) % 3], b1 = (&cv[(2 * k + 1) / 3].x)[(2 * k + 1) % 3];
                    mma16816(d[k & 1], wf + 4 * k, b0, b1);
                    mma16816(d[2 + (k & 1)], wf + 32 + 4 * k, b0, b1);
                }
                const float u = (c4 & 2) ? ((c4 & 1) ? d[2][2] + d[3][2] : d[2][0] + d[3][0]) : ((c4 & 1) ? d[0][2] + d[1][2] : d[0][0] + d[1][0]);
                sred[w4 * 32 + c4 * 8 + g] = u;
                bar_sync(3, 128);
                const float v = rbf((sred[lane] + sred[32 + lane]) + (sred[64 + lane] + sred[96 + lane]));
                const float act = rbf(rbf(v * sigmoid(v)) * __shfl_down_sync(0xffffffffu, v, 16));
                float y[4] = {0.f, 0.f, 0.f, 0.f};
#pragma unroll
                for (int k = 0; k < 16; k++) {
                    const float a = __shfl_sync(0xffffffffu, act, k);
#pragma unroll
                    for (int i = 0; i < 4; i++) y[i] = fmaf(a, wn[4 * k + i], y[i]);
                }
                st_pub(g_out + rb * OB + OB_Y + t7, make_uint4((__float_as_uint(y[0]) & ~15u) | (ep & 15), (__float_as_uint(y[1]) & ~127u) | ((best >> 9) & 127),
                                                               __float_as_uint(y[2]), __float_as_uint(y[3])), true);
            } while (!all);
            const int sel = (~best >> 5) & 2047;
            const int pq = (2 * rb + (tid & 1)) & 63, pv = (pq >> 2) / 3;
            const uint4* fp = g_cand + (sel >> 4) * 192 + (rb >> 5) * 24 + pv * 4 + (pq & 3);
            uint4 fh = {}, fx = {};
            if (rb == 0 && tid == 0) g_sync.epoch[0] = ep;
            if (elected) TS(60);
            TT(5);
            uint4 yv;
            if (warp == 0) { fh = ld_poll(fp); fx = ld_poll(fp + 96); }
            if (fresh && rb < NFFN) __nanosleep(YPRE);
            for (;;) {
                yv = ld_poll(g_out + min(t7, NFFN - 1) * OB + OB_Y + rb);
                if (__all_sync(0xffffffffu, (((yv.x ^ ep) & 15) | ((yv.y ^ (best >> 9)) & 127)) == 0)) break;
                if (YSLEEP) __nanosleep(YSLEEP);
            }
            if (elected) TS(61);
            TT(6);
            float y[4] = {0.f, 0.f, 0.f, 0.f};
            if (t7 < NFFN) { y[0] = __uint_as_float(yv.x); y[1] = __uint_as_float(yv.y); y[2] = __uint_as_float(yv.z); y[3] = __uint_as_float(yv.w); }
            const float z0 = ((lane & 16) ? y[2] : y[0]) + __shfl_xor_sync(0xffffffffu, (lane & 16) ? y[0] : y[2], 16);
            const float z1 = ((lane & 16) ? y[3] : y[1]) + __shfl_xor_sync(0xffffffffu, (lane & 16) ? y[1] : y[3], 16);
            float z = ((lane & 8) ? z1 : z0) + __shfl_xor_sync(0xffffffffu, (lane & 8) ? z0 : z1, 8);
            z += __shfl_xor_sync(0xffffffffu, z, 4);
            z = quad_sum(z);
            if ((lane & 7) == 0) sred[128 + (lane >> 3) * 4 + w4] = z;
            bar_sync(3, 128);
            if (tid < 2) {
                while (fh.w != ep || fx.w != ep) { fh = ld_poll(fp); fx = ld_poll(fp + 96); }
                const float4 y0 = *reinterpret_cast<const float4*>(sred + 128 + tid * 8), y1 = *reinterpret_cast<const float4*>(sred + 132 + tid * 8);
                const int cm = (pq >> 2) - 3 * pv;
                const uint32_t h2 = cm == 0 ? fh.x : cm == 1 ? fh.y : fh.z, x2 = cm == 0 ? fx.x : cm == 1 ? fx.y : fx.z;
                const float sg = sigmoid(bf_hi((best & 0x80000000u) ? (best ^ 0x80000000u) : ~best));
                reinterpret_cast<uint32_t*>(P.out)[sel * 256 + rb * 2 + tid] =
                    badd(x2, bmul(gbf, badd(h2, bmul(pack2((y0.x + y0.y) + (y0.z + y0.w), (y1.x + y1.y) + (y1.z + y1.w)), pack2(sg, sg)))));
            }
            if (elected) TS(62);
            TT(7);
        } else {
            const float4* tf = reinterpret_cast<const float4*>(smem + SM_TAB) + c4;
            const uint32_t xa = sb + 4 * SLOT + (kh ^ 1) * 16384 + (w4 * 16 + (lane & 15)) * 128;
            uint32_t x2[32];
            bar_sync(2, 256);
#pragma unroll 1
            for (int i = 14; i < 17; i++) {
                const uint32_t as = o_next(otab), ws = o_next(otab);
                slot_wait(sb + BAR_FULL, fph, as);
                slot_wait(sb + BAR_FULL, fph, ws);
                gemm_issue<false>(s, oa + as * (SLOT / 16), wd + ws * (SLOT / 16), 1, true);
                wg_wait<1>();
            }
            if (elected) TS(29);
            TT(1);
            {
#pragma unroll
                for (int k = 0; k < 8; k++)
                    asm volatile("ldmatrix.sync.aligned.m8n8.x4.shared.b16 {%0, %1, %2, %3}, [%4];"
                                 : "=r"(x2[4 * k]), "=r"(x2[4 * k + 1]), "=r"(x2[4 * k + 2]), "=r"(x2[4 * k + 3])
                                 : "r"(xa + (k >> 2) * 8192 + (((2 * (k & 3) + (lane >> 4)) ^ (lane & 7)) << 4)) : "memory");
            }
            wg_wait<0>();
            reg_fence(s);
            bar_arrive(4, 256);
            if (elected) TS(39);
            TT(2);
            const uint4* pr = g_out + (rb ^ 8) * OB + t7;
            uint4 pa[8];
#pragma unroll
            for (int v = 0; v < 8; v++) pa[v] = ld_poll(pr + v * 128);
            float4 tc[16];
#pragma unroll
            for (int k = 0; k < 16; k++) {
                tc[k] = tf[k * 4];
#pragma unroll
                for (int i = 4 * k; i < 4 * k + 4; i++) s[i] = fmaf((i & 1) ? tc[k].y : tc[k].x, s[i], (i & 1) ? bf_hi(x2[i >> 1]) : bf_lo(x2[i >> 1]));
            }
            reg_fence(s);
            for (;;) {
                uint32_t bad = 0;
#pragma unroll
                for (int v = 0; v < 8; v++) bad |= pa[v].x ^ ep;
                if (__all_sync(0xffffffffu, (bad & 1) == 0)) break;
                if (PSLEEP) __nanosleep(PSLEEP);
#pragma unroll
                for (int v = 0; v < 8; v++) pa[v] = ld_poll(pr + v * 128);
            }
            if (elected) TS(30);
            TT(3);
            float st[6] = {0.f, 0.f, 0.f, 0.f, 0.f, 0.f};
#pragma unroll
            for (int i = 0; i < 64; i++) {
                const int rh = (i >> 1) & 1;
                const uint32_t w = (&pa[i >> 3].x)[(i >> 1) & 3];
                const float v = fmaf((i & 1) ? tc[i >> 2].y : tc[i >> 2].x, (i & 1) ? bf_hi(w) : bf_lo(w), s[i]);
                s[i] = v;
                st[rh] += v;
                st[2 + rh] = fmaf(v, v, st[2 + rh]);
                st[4 + rh] = fmaf(v, (i & 1) ? tc[i >> 2].w : tc[i >> 2].z, st[4 + rh]);
            }
#pragma unroll
            for (int i = 0; i < 6; i++) st[i] = quad_sum(st[i]);
            st_pub(g_out + rb * OB + OB_STAT + (w4 * 8 + g) * 2 + (c4 & 1),
                   make_uint4(__float_as_uint((c4 & 1) ? st[1] : st[0]), __float_as_uint((c4 & 1) ? st[3] : st[2]),
                              __float_as_uint((c4 & 1) ? st[5] : st[4]), ep), c4 < 2);
            if (TF & 1) sched_fence(eb2, P.zero);
            if (elected) TS(56);
            TT(4);
            uint32_t cb[16], sh[16], gb[16];
#pragma unroll
            for (int i = 0; i < 16; i++) {
                const float4 c = tf[64 + i * 4];
                cb[i] = __float_as_uint(c.x); sh[i] = __float_as_uint(c.y); gb[i] = __float_as_uint(c.z);
            }
            const float ra = __uint_as_float(lds32(sb + SM_EP + 8)), rb0 = __uint_as_float(lds32(sb + SM_EP + 12));
#pragma unroll
            for (int i = 0; i < 32; i++) x2[i] = pack2(s[2 * i], s[2 * i + 1]);
            reg_fence(x2);
            uint4 r0, r1;
            if (SPRE) __nanosleep(SPRE);
            for (;;) {
                r0 = ld_poll(g_out + ((rb & ~3) + c4) * OB + OB_STAT + (w4 * 8 + g) * 2);
                r1 = ld_poll(g_out + ((rb & ~3) + c4) * OB + OB_STAT + (w4 * 8 + g) * 2 + 1);
                if (__all_sync(0xffffffffu, r0.w == ep && r1.w == ep)) break;
                if (SSLEEP) __nanosleep(SSLEEP);
            }
            if (elected) TS(57);
            TT(5);
            const float m0 = quad_sum(__uint_as_float(r0.x)) * (1.f / 512.f), m1 = quad_sum(__uint_as_float(r1.x)) * (1.f / 512.f);
            const float rs0 = ln_rstd(fmaxf(fmaf(-m0, m0, quad_sum(__uint_as_float(r0.y)) * (1.f / 512.f)), 0.f));
            const float rs1 = ln_rstd(fmaxf(fmaf(-m1, m1, quad_sum(__uint_as_float(r1.y)) * (1.f / 512.f)), 0.f));
            const uint32_t mb0 = pack2(m0, m0), mb1 = pack2(m1, m1);
            const uint32_t lg = pack2(fmaf(rs0, fmaf(-bf_lo(mb0), ra, quad_sum(__uint_as_float(r0.z))), rb0),
                                      fmaf(rs1, fmaf(-bf_lo(mb1), ra, quad_sum(__uint_as_float(r1.z))), rb0));
            const uint32_t u0 = lg << 16, u1 = lg & 0xffff0000u;
            const uint32_t k0 = ((u0 ^ (((int)u0 >> 31) | 0x80000000u)) & 0xffff0000u) | ((2047 - row) << 5) | (ep & 31);
            const uint32_t k1 = ((u1 ^ (((int)u1 >> 31) | 0x80000000u)) & 0xffff0000u) | ((2039 - row) << 5) | (ep & 31);
            const uint32_t kb = __reduce_max_sync(0xffffffffu, max(k0, k1));
            st_pub(g_key + cq * 128 + (row >> 4), kb, lane == 0);
            const bool cand = kb == k0 || kb == k1;
            uint4* cp = g_cand + (row >> 4) * 192 + cq * 24 + c4;
#pragma unroll 1
            for (int it = 0; it < 3; it++) {
                bool put = it == 1 || !cand;
                if (it == 2) {
                    mbar_wait(sb + BAR_BEST, 0);
                    put = cand && lds32(sb + SM_EP + 24) != kb;
                }
                const bool hi = (kb == k1) != (it == 1);
                uint32_t cx[18], ch[18];
#pragma unroll
                for (int i = 0; i < 16; i++) {
                    cx[i] = hi ? x2[2 * i + 1] : x2[2 * i];
                    ch[i] = ln_apply(cx[i], hi ? mb1 : mb0, hi ? rs1 : rs0, cb[i], sh[i]);
                }
                cx[16] = cx[17] = ch[16] = ch[17] = 0;
#pragma unroll
                for (int v = 0; v < 6; v++) st_pub(cp + v * 4, make_uint4(ch[3 * v], ch[3 * v + 1], ch[3 * v + 2], ep), cand && it == 0);
                if (TF & 4) sched_fence(eb2, P.zero);
#pragma unroll
                for (int v = 0; v < 6; v++) st_pub(cp + 96 + v * 4, make_uint4(cx[3 * v], cx[3 * v + 1], cx[3 * v + 2], ep), cand && it == 0);
                if (it == 0) TT(6);
                uint2* op = reinterpret_cast<uint2*>(P.out) + (row + 8 * hi) * 128 + cq * 32 + (c4 & 1) * 2 + (c4 >> 1);
#pragma unroll
                for (int i = 0; i < 16; i += 2) {
                    const uint32_t v0 = badd(cx[i], bmul(gb[i], ch[i])), v1 = badd(cx[i + 1], bmul(gb[i + 1], ch[i + 1]));
                    const uint32_t rv = __shfl_xor_sync(0xffffffffu, (c4 & 1) ? v0 : v1, 1);
                    if (put) op[i * 2] = (c4 & 1) ? make_uint2(rv, v1) : make_uint2(v0, rv);
                }
            }
            if (elected) TS(59);
            TT(7);
        }
        mbar_arrive_if(eb2, lane == 0);
    }
}

typedef CUresult (*EncodeFn)(CUtensorMap*, CUtensorMapDataType, cuuint32_t, void*, const cuuint64_t*, const cuuint64_t*,
                             const cuuint32_t*, const cuuint32_t*, CUtensorMapInterleave, CUtensorMapSwizzle,
                             CUtensorMapL2promotion, CUtensorMapFloatOOBfill);

void make_2d(EncodeFn fn, CUtensorMap* m, const void* p, uint64_t cols, uint64_t rows, uint32_t bc, uint32_t br) {
    cuuint64_t dims[2] = {cols, rows}, strides[1] = {cols * 2};
    cuuint32_t box[2] = {bc, br}, es[2] = {1, 1};
    fn(m, CU_TENSOR_MAP_DATA_TYPE_BFLOAT16, 2, const_cast<void*>(p), dims, strides, box, es, CU_TENSOR_MAP_INTERLEAVE_NONE,
       CU_TENSOR_MAP_SWIZZLE_NONE, CU_TENSOR_MAP_L2_PROMOTION_L2_128B, CU_TENSOR_MAP_FLOAT_OOB_FILL_NONE);
}
void make_3d(EncodeFn fn, CUtensorMap* m, const void* p, uint64_t cols, uint64_t rows, uint32_t br = 128, uint32_t nb = 2) {
    cuuint64_t dims[3] = {64, rows, cols / 64}, strides[2] = {cols * 2, 128};
    cuuint32_t box[3] = {64, br, nb}, es[3] = {1, 1, 1};
    fn(m, CU_TENSOR_MAP_DATA_TYPE_BFLOAT16, 3, const_cast<void*>(p), dims, strides, box, es, CU_TENSOR_MAP_INTERLEAVE_NONE,
       CU_TENSOR_MAP_SWIZZLE_128B, CU_TENSOR_MAP_L2_PROMOTION_L2_256B, CU_TENSOR_MAP_FLOAT_OOB_FILL_NONE);
}

}

extern "C" void kernel_launch(void* const* d_in, const int* in_sizes, int n_in, void* d_out, int out_size) {
    static EncodeFn fn = nullptr;
    if (!fn) {
        void* f = nullptr;
        cudaDriverEntryPointQueryResult st;
        cudaGetDriverEntryPoint("cuTensorMapEncodeTiled", &f, cudaEnableDefault, &st);
        fn = (EncodeFn)f;
        cudaFuncSetAttribute(fused_kernel, cudaFuncAttributeMaxDynamicSharedMemorySize, SMEM_BYTES);
    }
    CUtensorMap ckv, wq, wuk, wuv, wo, wg, wu, wm, xm;
    make_3d(fn, &ckv, d_in[1], 512, 2048, 128, 1);
    make_3d(fn, &xm, d_in[0], 512, 2048, 64);
    make_3d(fn, &wq, d_in[2], 4096, 512, 128, 1);
    make_3d(fn, &wuk, d_in[3], 4096, 512);
    make_3d(fn, &wuv, d_in[4], 4096, 512);
    make_3d(fn, &wo, d_in[5], 512, 4096);
    make_2d(fn, &wg, d_in[8], 1792, 512, 16, 256);
    make_2d(fn, &wu, d_in[9], 1792, 512, 16, 256);
    make_2d(fn, &wm, d_in[12], 3072, 512, 256, 64);
    Params p;
    p.x = (const bf16*)d_in[0];
    p.ckv = (const bf16*)d_in[1];
    p.wo = (const bf16*)d_in[5];
    p.wr = (const bf16*)d_in[7];
    p.wdown = (const bf16*)d_in[10];
    p.c = (const bf16*)d_in[11];
    p.out = (bf16*)d_out;
    p.zero = 0;
    fused_kernel<<<NCTA + NSPARE, 384, SMEM_BYTES>>>(ckv, wq, wuk, wuv, wo, wg, wu, wm, xm, p);
}
```

```cpp
#include <cuda.h>
#include <cuda_bf16.h>
#include <cuda_runtime.h>
#include <stdint.h>
#include <stdio.h>

namespace {

typedef __nv_bfloat16 bf16;
typedef unsigned long long u64;

constexpr int NCTA = 128, NSPARE = 4;
constexpr int SLOT = 32768;
constexpr int SM_BAR = 7 * SLOT;
constexpr int BAR_FULL = SM_BAR;
constexpr int BAR_EMPTY = BAR_FULL + 8 * 7;
constexpr int BAR_DONE = BAR_EMPTY + 8 * 7;
constexpr int BAR_FLAG = BAR_DONE + 8 * 9;
constexpr int BAR_PF = BAR_FLAG + 8 * 9;
constexpr int BAR_END = BAR_PF + 8;
constexpr int BAR_BEST = BAR_END + 8;
constexpr int SM_EP = BAR_END + 24;
constexpr int SM_RED = SM_BAR + 384;
constexpr int SM_TAB = SM_BAR + 1024;
constexpr int SMEM_BYTES = SM_BAR + 3072;
constexpr int NFFN = 112;
#define HINT 479
constexpr u64 L2_NORMAL = 0x1000000000000000ull, L2_FIRST = 0x12F0000000000000ull;
#define PFA 8
#define PFB 6
#define UNR 1
#define POLL_NS 50
#define MSPLIT 13
#define SF 3
#define NSH 1
#define XPF 2
#define TF 1
#define KSLEEP 150
#define YSLEEP 50
#define YPRE 150
#define SSLEEP 50
#define SPRE 0
#define PSLEEP 100
#define CSLEEP 0
#define SPEC 24
#define EARLY 7
constexpr uint32_t SPIN_LIMIT = 1u << 22;
constexpr uint32_t ONE2 = 0x3f803f80u;

struct Sync {
    uint32_t cnt[16 * 8 * 8];
    uint32_t ctxcnt[16 * 32];
    uint32_t epoch[32];
};

__device__ __align__(1024) uint8_t g_KV[16 * 16 * 2 * SLOT];
__device__ __align__(1024) uint8_t g_ctx[16 * 32 * SLOT];
__device__ __align__(1024) uint8_t g_h[16 * 4 * SLOT];
constexpr int OB = 1216, OB_STAT = 1024, OB_Y = 1088;
__device__ __align__(1024) uint4 g_out[128 * OB];
__device__ __align__(1024) bf16 g_mod[3072];
__device__ __align__(1024) uint32_t g_mod1[1024];
__device__ __align__(1024) uint4 g_cand[128 * 192];
__device__ __align__(1024) uint32_t g_key[4 * 128];
__device__ __align__(1024) uint8_t g_wf[NFFN * SLOT];
__device__ __align__(1024) Sync g_sync;
#define TS(i)

#define TT(i)
#define PT()

struct Params {
    const bf16 *x, *ckv, *wo, *wr, *wdown, *c;
    bf16* out;
    int zero;
};

__device__ __forceinline__ void mbar_init(uint32_t bar, uint32_t cnt) {
    asm volatile("mbarrier.init.shared::cta.b64 [%0], %1;" ::"r"(bar), "r"(cnt) : "memory");
}
__device__ __forceinline__ void mbar_wait(uint32_t bar, uint32_t parity) {
    asm volatile("{\n.reg .pred p;\nL_%=:\nmbarrier.try_wait.parity.shared::cta.b64 p, [%0], %1;\n@!p bra L_%=;\n}" ::"r"(bar), "r"(parity) : "memory");
}
__device__ __forceinline__ void mbar_sleep(uint32_t bar) {
    if ((threadIdx.x & 31) == 0)
        asm volatile("{\n.reg .pred p;\nL_%=:\nmbarrier.try_wait.parity.shared::cta.b64 p, [%0], 0, 100000;\n@!p bra L_%=;\n}" ::"r"(bar) : "memory");
    __syncwarp();
}
__device__ __forceinline__ void mbar_watch(uint32_t bar, uint32_t parity) {
    asm volatile("{\n.reg .pred p;\n.reg .u32 n;\nmov.u32 n, 0;\n"
                 "L_%=:\nmbarrier.try_wait.parity.shared::cta.b64 p, [%0], %1;\n@p bra D_%=;\n"
                 "add.u32 n, n, 1;\nsetp.lt.u32 p, n, %2;\n@p bra L_%=;\ntrap;\nD_%=:\n}"
                 ::"r"(bar), "r"(parity), "n"(SPIN_LIMIT) : "memory");
}
__device__ __forceinline__ void step_watch(uint32_t a, uint32_t step) {
    asm volatile("{\n.reg .pred p;\n.reg .u32 n, v;\nmov.u32 n, 0;\n"
                 "L_%=:\nld.volatile.shared.u32 v, [%0];\nsetp.ge.u32 p, v, %1;\n@p bra D_%=;\nnanosleep.u32 400;\n"
                 "add.u32 n, n, 1;\nsetp.lt.u32 p, n, %2;\n@p bra L_%=;\ntrap;\nD_%=:\n}"
                 ::"r"(a), "r"(step), "n"(SPIN_LIMIT) : "memory");
}
__device__ __forceinline__ void mbar_arrive_if(uint32_t bar, bool on) {
    asm volatile("{\n.reg .pred p;\nsetp.ne.s32 p, %1, 0;\n@p mbarrier.arrive.shared::cta.b64 _, [%0];\n}" ::"r"(bar), "r"((int)on) : "memory");
}
__device__ __forceinline__ void tma2d(uint32_t dst, const CUtensorMap* m, int c0, int c1, uint32_t bar, bool first) {
    asm volatile("{\n.reg .pred p;\nelect.sync _|p, 0xffffffff;\n"
                 "@p cp.async.bulk.tensor.2d.shared::cluster.global.mbarrier::complete_tx::bytes.L2::cache_hint [%0], [%1, {%3, %4}], [%2], %5;\n}"
                 ::"r"(dst), "l"(m), "r"(bar), "r"(c0), "r"(c1), "l"(first ? L2_FIRST : L2_NORMAL) : "memory");
}
__device__ __forceinline__ void tma3d_prefetch(const CUtensorMap* m, int row, int cb) {
    asm volatile("{\n.reg .pred p;\nelect.sync _|p, 0xffffffff;\n@p cp.async.bulk.prefetch.tensor.3d.L2.global [%0, {%1, %2, %3}];\n}"
                 ::"l"(m), "r"(0), "r"(row), "r"(cb) : "memory");
}
__device__ __forceinline__ void l2_prefetch(const void* p, uint32_t bytes) {
    asm volatile("{\n.reg .pred p;\nelect.sync _|p, 0xffffffff;\n@p cp.async.bulk.prefetch.L2.global [%0], %1;\n}" ::"l"(p), "r"(bytes) : "memory");
}
__device__ __forceinline__ void bulk_store(void* dst, uint32_t src, uint32_t bytes, bool first) {
    asm volatile("{\n.reg .pred p;\nelect.sync _|p, 0xffffffff;\n@p cp.async.bulk.global.shared::cta.bulk_group.L2::cache_hint [%0], [%1], %2, %3;\n}"
                 ::"l"(dst), "r"(src), "r"(bytes), "l"(first ? L2_FIRST : L2_NORMAL) : "memory");
}
__device__ __forceinline__ void flag_wait(const uint32_t* f, uint32_t target) {
    asm volatile("{\n.reg .pred p;\n.reg .u32 v;\n"
                 "L_%=:\nld.acquire.gpu.global.u32 v, [%0];\nsub.u32 v, v, %1;\nsetp.lt.s32 p, v, 0;\n@p nanosleep.u32 100;\n@p bra L_%=;\n}"
                 ::"l"(f), "r"(target) : "memory");
}
__device__ __forceinline__ uint4 ld_poll(const uint4* p) {
    uint4 v;
    asm volatile("{\n.reg .b128 t;\nld.relaxed.gpu.global.b128 t, [%4];\nmov.b128 {%0, %1, %2, %3}, t;\n}"
                 : "=r"(v.x), "=r"(v.y), "=r"(v.z), "=r"(v.w) : "l"(p) : "memory");
    return v;
}
__device__ __forceinline__ void st_pub(uint4* p, uint4 v, bool on) {
    asm volatile("{\n.reg .pred p;\n.reg .b128 t;\nsetp.ne.s32 p, %5, 0;\nmov.b128 t, {%1, %2, %3, %4};\n@p st.relaxed.gpu.global.b128 [%0], t;\n}"
                 ::"l"(p), "r"(v.x), "r"(v.y), "r"(v.z), "r"(v.w), "r"((int)on) : "memory");
}
__device__ __forceinline__ void st_pub(uint32_t* p, uint32_t v, bool on) {
    asm volatile("{\n.reg .pred p;\nsetp.ne.s32 p, %2, 0;\n@p st.relaxed.gpu.global.u32 [%0], %1;\n}" ::"l"(p), "r"(v), "r"((int)on) : "memory");
}
__device__ __forceinline__ void flag_add(uint32_t* p) {
    asm volatile("red.release.gpu.global.add.u32 [%0], 1;" ::"l"(p) : "memory");
}
__device__ __forceinline__ uint32_t lds32(uint32_t a) {
    uint32_t v;
    asm volatile("ld.shared.u32 %0, [%1];" : "=r"(v) : "r"(a) : "memory");
    return v;
}
__device__ __forceinline__ uint4 lds128(uint32_t a) {
    uint4 v;
    asm volatile("ld.shared.v4.u32 {%0, %1, %2, %3}, [%4];" : "=r"(v.x), "=r"(v.y), "=r"(v.z), "=r"(v.w) : "r"(a) : "memory");
    return v;
}
__device__ __forceinline__ void sched_fence(uint32_t& v, uint32_t z) {
    uint32_t ck;
    asm volatile("mov.u32 %0, %%clock;" : "=r"(ck)::"memory");
    v ^= ck & z;
}
__device__ __forceinline__ void fence_async_global() { asm volatile("fence.proxy.async.global;" ::: "memory"); }
__device__ __forceinline__ void fence_async_smem() { asm volatile("fence.proxy.async.shared::cta;" ::: "memory"); }
__device__ __forceinline__ void bar_sync(int id, int n) { asm volatile("bar.sync %0, %1;" ::"r"(id), "r"(n) : "memory"); }
__device__ __forceinline__ void bar_arrive(int id, int n) { asm volatile("bar.arrive %0, %1;" ::"r"(id), "r"(n) : "memory"); }
__device__ __forceinline__ void wg_fence() { asm volatile("wgmma.fence.sync.aligned;" ::: "memory"); }
__device__ __forceinline__ void wg_commit() { asm volatile("wgmma.commit_group.sync.aligned;" ::: "memory"); }
template <int N> __device__ __forceinline__ void wg_wait() { asm volatile("wgmma.wait_group.sync.aligned %0;" ::"n"(N) : "memory"); }
template <int N> __device__ __forceinline__ void reg_fence(float (&d)[N]) {
#pragma unroll
    for (int i = 0; i < N; i++) asm volatile("" : "+f"(d[i])::"memory");
}
template <int N> __device__ __forceinline__ void reg_fence(uint32_t (&d)[N]) {
#pragma unroll
    for (int i = 0; i < N; i++) asm volatile("" : "+r"(d[i])::"memory");
}
__device__ __forceinline__ uint32_t desc_k(uint32_t a) { return ((a & 0x3ffff) >> 4) | (1u << 16); }
__device__ __forceinline__ uint32_t desc_mn(uint32_t a) { return ((a & 0x3ffff) >> 4) | (1024u << 16); }

template <int TB>
__device__ __forceinline__ void wgmma_ss128(float (&d)[64], uint32_t da, uint32_t db, int acc, uint32_t ha = 0x40000040u, uint32_t hb = 0x40000040u) {
    asm volatile("{\n.reg .pred p;\n.reg .b64 a, b;\nsetp.ne.b32 p, %66, 0;\nmov.b64 a, {%64, %68};\nmov.b64 b, {%65, %69};\n"
        "wgmma.mma_async.sync.aligned.m64n128k16.f32.bf16.bf16 {%0, %1, %2, %3, %4, %5, %6, %7, %8, %9, %10, %11, %12, %13, %14, %15, %16, %17, %18, %19, %20, %21, %22, %23, %24, %25, %26, %27, %28, %29, %30, %31, %32, %33, %34, %35, %36, %37, %38, %39, %40, %41, %42, %43, %44, %45, %46, %47, %48, %49, %50, %51, %52, %53, %54, %55, %56, %57, %58, %59, %60, %61, %62, %63}, a, b, p, 1, 1, 0, %67;\n}"
        : "+f"(d[0]), "+f"(d[1]), "+f"(d[2]), "+f"(d[3]), "+f"(d[4]), "+f"(d[5]), "+f"(d[6]), "+f"(d[7]), "+f"(d[8]), "+f"(d[9]), "+f"(d[10]), "+f"(d[11]), "+f"(d[12]), "+f"(d[13]), "+f"(d[14]), "+f"(d[15]), "+f"(d[16]), "+f"(d[17]), "+f"(d[18]), "+f"(d[19]), "+f"(d[20]), "+f"(d[21]), "+f"(d[22]), "+f"(d[23]), "+f"(d[24]), "+f"(d[25]), "+f"(d[26]), "+f"(d[27]), "+f"(d[28]), "+f"(d[29]), "+f"(d[30]), "+f"(d[31]), "+f"(d[32]), "+f"(d[33]), "+f"(d[34]), "+f"(d[35]), "+f"(d[36]), "+f"(d[37]), "+f"(d[38]), "+f"(d[39]), "+f"(d[40]), "+f"(d[41]), "+f"(d[42]), "+f"(d[43]), "+f"(d[44]), "+f"(d[45]), "+f"(d[46]), "+f"(d[47]), "+f"(d[48]), "+f"(d[49]), "+f"(d[50]), "+f"(d[51]), "+f"(d[52]), "+f"(d[53]), "+f"(d[54]), "+f"(d[55]), "+f"(d[56]), "+f"(d[57]), "+f"(d[58]), "+f"(d[59]), "+f"(d[60]), "+f"(d[61]), "+f"(d[62]), "+f"(d[63])
        : "r"(da), "r"(db), "r"(acc), "n"(TB), "r"(ha), "r"(hb));
}
template <int TB>
__device__ __forceinline__ void wgmma_ss128_init(float (&d)[64], uint32_t da, uint32_t db, uint32_t ha = 0x40000040u, uint32_t hb = 0x40000040u) {
    asm volatile("{\n.reg .pred p;\n.reg .b64 a, b;\nsetp.ne.b32 p, 0, 0;\nmov.b64 a, {%64, %67};\nmov.b64 b, {%65, %68};\n"
        "wgmma.mma_async.sync.aligned.m64n128k16.f32.bf16.bf16 {%0, %1, %2, %3, %4, %5, %6, %7, %8, %9, %10, %11, %12, %13, %14, %15, %16, %17, %18, %19, %20, %21, %22, %23, %24, %25, %26, %27, %28, %29, %30, %31, %32, %33, %34, %35, %36, %37, %38, %39, %40, %41, %42, %43, %44, %45, %46, %47, %48, %49, %50, %51, %52, %53, %54, %55, %56, %57, %58, %59, %60, %61, %62, %63}, a, b, p, 1, 1, 0, %66;\n}"
        : "=f"(d[0]), "=f"(d[1]), "=f"(d[2]), "=f"(d[3]), "=f"(d[4]), "=f"(d[5]), "=f"(d[6]), "=f"(d[7]), "=f"(d[8]), "=f"(d[9]), "=f"(d[10]), "=f"(d[11]), "=f"(d[12]), "=f"(d[13]), "=f"(d[14]), "=f"(d[15]), "=f"(d[16]), "=f"(d[17]), "=f"(d[18]), "=f"(d[19]), "=f"(d[20]), "=f"(d[21]), "=f"(d[22]), "=f"(d[23]), "=f"(d[24]), "=f"(d[25]), "=f"(d[26]), "=f"(d[27]), "=f"(d[28]), "=f"(d[29]), "=f"(d[30]), "=f"(d[31]), "=f"(d[32]), "=f"(d[33]), "=f"(d[34]), "=f"(d[35]), "=f"(d[36]), "=f"(d[37]), "=f"(d[38]), "=f"(d[39]), "=f"(d[40]), "=f"(d[41]), "=f"(d[42]), "=f"(d[43]), "=f"(d[44]), "=f"(d[45]), "=f"(d[46]), "=f"(d[47]), "=f"(d[48]), "=f"(d[49]), "=f"(d[50]), "=f"(d[51]), "=f"(d[52]), "=f"(d[53]), "=f"(d[54]), "=f"(d[55]), "=f"(d[56]), "=f"(d[57]), "=f"(d[58]), "=f"(d[59]), "=f"(d[60]), "=f"(d[61]), "=f"(d[62]), "=f"(d[63])
        : "r"(da), "r"(db), "n"(TB), "r"(ha), "r"(hb));
}
template <int TB>
__device__ __forceinline__ void wgmma_ss64(float (&d)[32], uint32_t da, uint32_t db, int acc, uint32_t ha = 0x40000040u, uint32_t hb = 0x40000040u) {
    asm volatile("{\n.reg .pred p;\n.reg .b64 a, b;\nsetp.ne.b32 p, %34, 0;\nmov.b64 a, {%32, %36};\nmov.b64 b, {%33, %37};\n"
        "wgmma.mma_async.sync.aligned.m64n64k16.f32.bf16.bf16 {%0, %1, %2, %3, %4, %5, %6, %7, %8, %9, %10, %11, %12, %13, %14, %15, %16, %17, %18, %19, %20, %21, %22, %23, %24, %25, %26, %27, %28, %29, %30, %31}, a, b, p, 1, 1, 0, %35;\n}"
        : "+f"(d[0]), "+f"(d[1]), "+f"(d[2]), "+f"(d[3]), "+f"(d[4]), "+f"(d[5]), "+f"(d[6]), "+f"(d[7]), "+f"(d[8]), "+f"(d[9]), "+f"(d[10]), "+f"(d[11]), "+f"(d[12]), "+f"(d[13]), "+f"(d[14]), "+f"(d[15]), "+f"(d[16]), "+f"(d[17]), "+f"(d[18]), "+f"(d[19]), "+f"(d[20]), "+f"(d[21]), "+f"(d[22]), "+f"(d[23]), "+f"(d[24]), "+f"(d[25]), "+f"(d[26]), "+f"(d[27]), "+f"(d[28]), "+f"(d[29]), "+f"(d[30]), "+f"(d[31])
        : "r"(da), "r"(db), "r"(acc), "n"(TB), "r"(ha), "r"(hb));
}
template <int TB>
__device__ __forceinline__ void wgmma_ss64_init(float (&d)[32], uint32_t da, uint32_t db, uint32_t ha = 0x40000040u, uint32_t hb = 0x40000040u) {
    asm volatile("{\n.reg .pred p;\n.reg .b64 a, b;\nsetp.ne.b32 p, 0, 0;\nmov.b64 a, {%32, %35};\nmov.b64 b, {%33, %36};\n"
        "wgmma.mma_async.sync.aligned.m64n64k16.f32.bf16.bf16 {%0, %1, %2, %3, %4, %5, %6, %7, %8, %9, %10, %11, %12, %13, %14, %15, %16, %17, %18, %19, %20, %21, %22, %23, %24, %25, %26, %27, %28, %29, %30, %31}, a, b, p, 1, 1, 0, %34;\n}"
        : "=f"(d[0]), "=f"(d[1]), "=f"(d[2]), "=f"(d[3]), "=f"(d[4]), "=f"(d[5]), "=f"(d[6]), "=f"(d[7]), "=f"(d[8]), "=f"(d[9]), "=f"(d[10]), "=f"(d[11]), "=f"(d[12]), "=f"(d[13]), "=f"(d[14]), "=f"(d[15]), "=f"(d[16]), "=f"(d[17]), "=f"(d[18]), "=f"(d[19]), "=f"(d[20]), "=f"(d[21]), "=f"(d[22]), "=f"(d[23]), "=f"(d[24]), "=f"(d[25]), "=f"(d[26]), "=f"(d[27]), "=f"(d[28]), "=f"(d[29]), "=f"(d[30]), "=f"(d[31])
        : "r"(da), "r"(db), "n"(TB), "r"(ha), "r"(hb));
}
__device__ __forceinline__ void wgmma_rs128(float (&d)[64], uint32_t a0, uint32_t a1, uint32_t a2, uint32_t a3, uint32_t db, int acc, uint32_t hb = 0x40000040u) {
    asm volatile("{\n.reg .pred p;\n.reg .b64 b;\nsetp.ne.b32 p, %69, 0;\nmov.b64 b, {%68, %70};\n"
        "wgmma.mma_async.sync.aligned.m64n128k16.f32.bf16.bf16 {%0, %1, %2, %3, %4, %5, %6, %7, %8, %9, %10, %11, %12, %13, %14, %15, %16, %17, %18, %19, %20, %21, %22, %23, %24, %25, %26, %27, %28, %29, %30, %31, %32, %33, %34, %35, %36, %37, %38, %39, %40, %41, %42, %43, %44, %45, %46, %47, %48, %49, %50, %51, %52, %53, %54, %55, %56, %57, %58, %59, %60, %61, %62, %63}, {%64, %65, %66, %67}, b, p, 1, 1, 1;\n}"
        : "+f"(d[0]), "+f"(d[1]), "+f"(d[2]), "+f"(d[3]), "+f"(d[4]), "+f"(d[5]), "+f"(d[6]), "+f"(d[7]), "+f"(d[8]), "+f"(d[9]), "+f"(d[10]), "+f"(d[11]), "+f"(d[12]), "+f"(d[13]), "+f"(d[14]), "+f"(d[15]), "+f"(d[16]), "+f"(d[17]), "+f"(d[18]), "+f"(d[19]), "+f"(d[20]), "+f"(d[21]), "+f"(d[22]), "+f"(d[23]), "+f"(d[24]), "+f"(d[25]), "+f"(d[26]), "+f"(d[27]), "+f"(d[28]), "+f"(d[29]), "+f"(d[30]), "+f"(d[31]), "+f"(d[32]), "+f"(d[33]), "+f"(d[34]), "+f"(d[35]), "+f"(d[36]), "+f"(d[37]), "+f"(d[38]), "+f"(d[39]), "+f"(d[40]), "+f"(d[41]), "+f"(d[42]), "+f"(d[43]), "+f"(d[44]), "+f"(d[45]), "+f"(d[46]), "+f"(d[47]), "+f"(d[48]), "+f"(d[49]), "+f"(d[50]), "+f"(d[51]), "+f"(d[52]), "+f"(d[53]), "+f"(d[54]), "+f"(d[55]), "+f"(d[56]), "+f"(d[57]), "+f"(d[58]), "+f"(d[59]), "+f"(d[60]), "+f"(d[61]), "+f"(d[62]), "+f"(d[63])
        : "r"(a0), "r"(a1), "r"(a2), "r"(a3), "r"(db), "r"(acc), "r"(hb));
}

__device__ __forceinline__ uint32_t pack2(float lo, float hi) {
    uint32_t r;
    asm("cvt.rn.bf16x2.f32 %0, %1, %2;" : "=r"(r) : "f"(hi), "f"(lo));
    return r;
}
__device__ __forceinline__ float bf_lo(uint32_t v) { return __uint_as_float(v << 16); }
__device__ __forceinline__ float bf_hi(uint32_t v) { return __uint_as_float(v & 0xffff0000u); }
__device__ __forceinline__ float rbf(float v) { return bf_lo(pack2(v, v)); }
__device__ __forceinline__ uint32_t badd(uint32_t a, uint32_t b) {
    uint32_t r;
    asm("add.rn.bf16x2 %0, %1, %2;" : "=r"(r) : "r"(a), "r"(b));
    return r;
}
__device__ __forceinline__ uint32_t bsub(uint32_t a, uint32_t b) {
    uint32_t r;
    asm("sub.rn.bf16x2 %0, %1, %2;" : "=r"(r) : "r"(a), "r"(b));
    return r;
}
__device__ __forceinline__ uint32_t bmul(uint32_t a, uint32_t b) {
    uint32_t r;
    asm("mul.rn.bf16x2 %0, %1, %2;" : "=r"(r) : "r"(a), "r"(b));
    return r;
}
__device__ __forceinline__ uint32_t ln_apply(uint32_t x, uint32_t mb, float rs, uint32_t scale, uint32_t shift) {
    const uint32_t d = bsub(x, mb);
    return badd(bmul(pack2(bf_lo(d) * rs, bf_hi(d) * rs), scale), shift);
}
__device__ __forceinline__ float ex2(float v) {
    float r;
    asm("ex2.approx.ftz.f32 %0, %1;" : "=f"(r) : "f"(v));
    return r;
}
__device__ __forceinline__ float rcp(float v) {
    float r;
    asm("rcp.approx.ftz.f32 %0, %1;" : "=f"(r) : "f"(v));
    return r;
}
__device__ __forceinline__ float sqrt_fast(float v) {
    float r;
    asm("sqrt.approx.ftz.f32 %0, %1;" : "=f"(r) : "f"(v));
    return r;
}
__device__ __forceinline__ float ln_rstd(float var) { return rcp(rbf(sqrt_fast(rbf(rbf(var) + 1e-5f)))); }
__device__ __forceinline__ float sigmoid(float v) { return rcp(1.f + ex2(-1.4426950408889634f * v)); }
__device__ __forceinline__ float quad_sum(float v) {
    v += __shfl_xor_sync(0xffffffffu, v, 1);
    return v + __shfl_xor_sync(0xffffffffu, v, 2);
}

constexpr uint32_t HI_128 = 0x40000040u, HI_IMG = 0x80000080u, HI_Q = 0x80000040u;
template <int M, int RH>
__device__ __forceinline__ uint4 img_pack(const float (&d)[64], float s) {
    uint4 v;
    v.x = pack2(d[16 * M + 2 * RH] * s, d[16 * M + 2 * RH + 1] * s);
    v.y = pack2(d[16 * M + 4 + 2 * RH] * s, d[16 * M + 5 + 2 * RH] * s);
    v.z = pack2(d[16 * M + 8 + 2 * RH] * s, d[16 * M + 9 + 2 * RH] * s);
    v.w = pack2(d[16 * M + 12 + 2 * RH] * s, d[16 * M + 13 + 2 * RH] * s);
    return v;
}
template <int M>
__device__ __forceinline__ void img_store_global(uint8_t* img, uint32_t toff, const float (&d)[64], float s0, float s1) {
    uint4* p = reinterpret_cast<uint4*>(img + toff) + M * 32;
    p[0] = img_pack<M, 0>(d, s0);
    p[128] = img_pack<M, 1>(d, s1);
}
__device__ __forceinline__ void sts128(uint32_t a, uint4 v) {
    asm volatile("st.shared.v4.b32 [%0], {%1, %2, %3, %4};" ::"r"(a), "r"(v.x), "r"(v.y), "r"(v.z), "r"(v.w) : "memory");
}
constexpr float SM_C = 0.08838834764831845f * 1.4426950408889634f;
__device__ __forceinline__ float pack2f(float lo, float hi) {
    float r;
    asm("{\n.reg .b32 t;\ncvt.rn.bf16x2.f32 t, %1, %2;\nmov.b32 %0, t;\n}" : "=f"(r) : "f"(hi), "f"(lo));
    return r;
}
template <int M, bool SCALE, bool PARK>
__device__ __forceinline__ void pack_group(float (&d)[64], float (&v)[8], float s0, float s1) {
#pragma unroll
    for (int i = 0; i < 8; i++) {
        const int k = 16 * M + 4 * (i & 3) + 2 * (i >> 2);
        v[i] = SCALE ? pack2f(d[k] * (i < 4 ? s0 : s1), d[k + 1] * (i < 4 ? s0 : s1)) : pack2f(d[k], d[k + 1]);
        if (PARK && M > 0) d[16 * (M > 0 ? M - 1 : 0) + i] = v[i];
    }
}
__device__ __forceinline__ uint32_t q_off(uint32_t toff) { return (((toff >> 1) & ~2047u) ^ 8192) + (toff & 511); }
template <int M, bool PARK>
__device__ __forceinline__ void ctx_store_part(float4* p, float (&d)[64], float i0, float i1) {
    float v[8];
    pack_group<M, true, PARK>(d, v, i0, i1);
    p[M * 32] = make_float4(v[0], v[1], v[2], v[3]);
    p[M * 32 + 128] = make_float4(v[4], v[5], v[6], v[7]);
}
template <bool PARK>
__device__ __forceinline__ void ctx_store(uint8_t* img, uint32_t toff, float (&o)[64], float l0, float l1) {
    const float i0 = rcp(quad_sum(l0)), i1 = rcp(quad_sum(l1));
    float4* p = reinterpret_cast<float4*>(img + toff);
    ctx_store_part<0, PARK>(p, o, i0, i1); ctx_store_part<1, PARK>(p, o, i0, i1); ctx_store_part<2, PARK>(p, o, i0, i1); ctx_store_part<3, PARK>(p, o, i0, i1);
}

template <int M>
__device__ __forceinline__ void tile_store_part(float4* p, uint32_t a, float (&d)[64], float i0, float i1, int ctx) {
    float v[8];
    pack_group<M, true, true>(d, v, i0, i1);
#pragma unroll
    for (int h = 0; h < 2; h++)
        asm volatile("{\n.reg .pred p;\nsetp.ne.s32 p, %6, 0;\n@p st.global.v4.f32 [%0], {%2, %3, %4, %5};\n@!p st.shared.v4.f32 [%1], {%2, %3, %4, %5};\n}"
                     ::"l"(p + M * 32 + h * 128), "r"(a + (M >> 1) * 16384 + (M & 1) * 512 + h * 1024),
                     "f"(v[4 * h]), "f"(v[4 * h + 1]), "f"(v[4 * h + 2]), "f"(v[4 * h + 3]), "r"(ctx) : "memory");
}
__device__ __forceinline__ void tile_store(uint8_t* img, uint32_t a, uint32_t toff, float (&d)[64], float i0, float i1, int ctx) {
    float4* p = reinterpret_cast<float4*>(img + toff);
    a += q_off(toff);
    tile_store_part<0>(p, a, d, i0, i1, ctx); tile_store_part<1>(p, a, d, i0, i1, ctx);
    tile_store_part<2>(p, a, d, i0, i1, ctx); tile_store_part<3>(p, a, d, i0, i1, ctx);
}

__device__ __forceinline__ void slot_wait(uint32_t bars, uint32_t& ph, uint32_t slot) {
    mbar_wait(bars + 8 * slot, (ph >> slot) & 1);
    ph ^= 1u << slot;
}
__device__ __forceinline__ void release_if(uint32_t eb, uint32_t slot, bool on) {
    asm volatile("{\n.reg .pred p;\nsetp.ne.s32 p, %1, 0;\n@p mbarrier.arrive.shared::cluster.b64 _, [%0];\n}" ::"r"(eb + 8 * slot), "r"((int)on) : "memory");
}
__device__ __forceinline__ void slot_acquire(uint32_t sb, uint32_t& ph, uint32_t slot) {
    slot_wait(sb + BAR_EMPTY, ph, slot);
    asm volatile("{\n.reg .pred p;\nelect.sync _|p, 0xffffffff;\n@p mbarrier.arrive.expect_tx.shared::cta.b64 _, [%0], 32768;\n}"
                 ::"r"(sb + BAR_FULL + 8 * slot) : "memory");
}
__device__ __forceinline__ void load_bulk(uint32_t sb, uint32_t slot, uint32_t off, const void* src, uint32_t bytes, bool both, bool first) {
    if (both)
        asm volatile("{\n.reg .pred p;\nelect.sync _|p, 0xffffffff;\n"
                     "@p cp.async.bulk.shared::cluster.global.mbarrier::complete_tx::bytes.multicast::cluster.L2::cache_hint [%0], [%1], %5, [%2], %4, %3;\n}"
                     ::"r"(sb + slot * SLOT + off), "l"(src), "r"(sb + BAR_FULL + 8 * slot), "l"(first ? L2_FIRST : L2_NORMAL), "h"((uint16_t)3),
                     "r"(bytes) : "memory");
    else
        asm volatile("{\n.reg .pred p;\nelect.sync _|p, 0xffffffff;\n"
                     "@p cp.async.bulk.shared::cluster.global.mbarrier::complete_tx::bytes.L2::cache_hint [%0], [%1], %4, [%2], %3;\n}"
                     ::"r"(sb + slot * SLOT + off), "l"(src), "r"(sb + BAR_FULL + 8 * slot), "l"(first ? L2_FIRST : L2_NORMAL), "r"(bytes) : "memory");
}
__device__ __forceinline__ void load_tile(uint32_t sb, uint32_t slot, uint32_t off, const CUtensorMap* m, int row, int cb, bool both, bool first) {
    if (both)
        asm volatile("{\n.reg .pred p;\nelect.sync _|p, 0xffffffff;\n"
                     "@p cp.async.bulk.tensor.3d.shared::cluster.global.mbarrier::complete_tx::bytes.multicast::cluster.L2::cache_hint [%0], [%1, {%3, %4, %5}], [%2], %7, %6;\n}"
                     ::"r"(sb + slot * SLOT + off), "l"(m), "r"(sb + BAR_FULL + 8 * slot), "r"(0), "r"(row), "r"(cb),
                     "l"(first ? L2_FIRST : L2_NORMAL), "h"((uint16_t)3) : "memory");
    else
        asm volatile("{\n.reg .pred p;\nelect.sync _|p, 0xffffffff;\n"
                     "@p cp.async.bulk.tensor.3d.shared::cluster.global.mbarrier::complete_tx::bytes.L2::cache_hint [%0], [%1, {%3, %4, %5}], [%2], %6;\n}"
                     ::"r"(sb + slot * SLOT + off), "l"(m), "r"(sb + BAR_FULL + 8 * slot), "r"(0), "r"(row), "r"(cb),
                     "l"(first ? L2_FIRST : L2_NORMAL) : "memory");
}
__device__ __forceinline__ uint32_t ring_next(uint32_t r) { return r == 4 ? 0 : r + 1; }
__device__ __forceinline__ uint32_t w_table(int hp) { return hp ? 0x3104u : 0x4210u; }
__device__ __forceinline__ uint32_t a_table(int hp) { return hp ? 0x625u : 0x635u; }
__device__ __forceinline__ uint32_t a_next(uint32_t& t) {
    const uint32_t s = t & 15;
    t = (t >> 4) | (s << 8);
    return s;
}
constexpr uint32_t O_TABLE = 0x1604235u;
__device__ __forceinline__ uint32_t o_next(uint32_t& t) {
    const uint32_t s = t & 15;
    t = (t >> 4) | (s << 24);
    return s;
}
__device__ __forceinline__ int o_head(int i, int kh) { return i < 16 ? 4 * (i & 7) + 2 * (kh ^ 1) + (i >> 3) : 29 + 2 * kh; }

template <bool INIT>
__device__ __forceinline__ void gemm_issue(float (&d)[64], uint32_t a, uint32_t b, int acc, bool img) {
    const uint32_t ha = img ? HI_IMG : HI_128, o2 = img ? 32 : 4, o4 = img ? 64 : 1024;
    wg_fence();
#pragma unroll
    for (int k = 0; k < 8; k++) {
        if (INIT && k == 0) wgmma_ss128_init<1>(d, a, b, ha);
        else wgmma_ss128<1>(d, a + (k >> 2) * o4 + ((k >> 1) & 1) * o2 + (k & 1) * 2, b + k * 128, k ? 1 : acc, ha);
    }
    wg_commit();
}

template <bool ODD>
__device__ __forceinline__ bool proj_tile(float (&acc)[64], float (&prev)[64], int t, int q0, uint32_t sb, int wg, uint32_t eb, bool rel, uint32_t& fph,
                                          uint32_t wtab, uint32_t& atab, uint8_t* prev_img, uint32_t toff, float s0, float s1,
                                          uint32_t (&v)[32]) {
    const uint32_t a0 = desc_k(sb + (wg ^ (ODD && t == 5)) * 8192), b0 = desc_mn(sb);
    constexpr int U = ODD ? UNR : 1;
#pragma unroll U
    for (int q = ODD ? 0 : q0; q < 4; q++) {
        const uint32_t ws = (wtab >> (4 * q)) & 15, as = a_next(atab);
        if (!ODD && t != 2) slot_wait(sb + BAR_FULL, fph, ws);
        slot_wait(sb + BAR_FULL, fph, as);
        if (ODD && q == 2 && t == 5) {
#pragma unroll
            for (int i = 0; i < 8; i++) sts128(sb + 5 * SLOT + q_off(toff) + (i >> 2) * 16384 + (i & 2) * 256 + (i & 1) * 1024, make_uint4(v[4 * i], v[4 * i + 1], v[4 * i + 2], v[4 * i + 3]));
        }
        bar_sync(1 + wg, 256);
        gemm_issue<false>(acc, a0 + as * (SLOT / 16), b0 + ws * (SLOT / 16), q, false);
        bar_arrive(2 - wg, 256);
        wg_wait<1>();
        reg_fence(prev);
        if (ODD && t == 5) {
            if (q == 0) {
#pragma unroll
                for (int i = 0; i < 32; i++) {
                    const int k = 16 * (i >> 3) + 4 * (i & 3) + ((i >> 1) & 2);
                    v[i] = pack2(prev[k], prev[k + 1]);
                }
            }
            if (q == 2) {
                fence_async_smem();
                slot_wait(sb + BAR_FULL, fph, wtab & 15);
                wg_wait<0>();
                release_if(eb, as, rel);
                release_if(eb, ws, rel);
                reg_fence(acc);
                return true;
            }
        } else {
            if (q == 0) img_store_global<0>(prev_img, toff, prev, s0, s1);
            if (q == 1) img_store_global<1>(prev_img, toff, prev, s0, s1);
            if (q == 2) img_store_global<2>(prev_img, toff, prev, s0, s1);
            if (q == 3) img_store_global<3>(prev_img, toff, prev, s0, s1);
        }
        wg_wait<0>();
        release_if(eb, as, rel && !(ODD && (q & 1) && t == 5));
        if (ODD) release_if(eb, ws, rel && t != 1);
    }
    reg_fence(acc);
    return false;
}

__device__ __forceinline__ void qk_issue(float (&s)[64], uint32_t q, uint32_t k) {
    wg_fence();
    wgmma_ss128_init<0>(s, q, k, HI_Q, HI_IMG);
#pragma unroll
    for (int i = 1; i < 8; i++) wgmma_ss128<0>(s, q + (i >> 2) * 1024 + (i & 2) * 16 + (i & 1) * 2, k + (i >> 1) * 32 + (i & 1) * 2, 1, HI_Q, HI_IMG);
    wg_commit();
}
__device__ __forceinline__ void qk_issue(float (&s)[32], uint32_t q, uint32_t k) {
    wg_fence();
    wgmma_ss64_init<0>(s, q, k, HI_Q, HI_IMG);
#pragma unroll
    for (int i = 1; i < 8; i++) wgmma_ss64<0>(s, q + (i >> 2) * 1024 + (i & 2) * 16 + (i & 1) * 2, k + (i >> 1) * 32 + (i & 1) * 2, 1, HI_Q, HI_IMG);
    wg_commit();
}
__device__ __forceinline__ void pv_issue(float (&o)[64], const uint32_t (&p)[32], uint32_t v, int acc, bool half) {
    if (half) {
        asm volatile("// half" ::: "memory");
        wg_fence();
#pragma unroll
        for (int i = 0; i < 4; i++) wgmma_rs128(o, p[4 * i], p[4 * i + 1], p[4 * i + 2], p[4 * i + 3], v + i * 256, i ? 1 : acc, HI_IMG);
        wg_commit();
        asm volatile("// half" ::: "memory");
    } else {
        wg_fence();
#pragma unroll
        for (int i = 0; i < 8; i++) wgmma_rs128(o, p[4 * i], p[4 * i + 1], p[4 * i + 2], p[4 * i + 3], v + i * 256, i ? 1 : acc, HI_IMG);
        wg_commit();
    }
}
__device__ __forceinline__ void tri_mask(float (&s)[64], float x) {
#pragma unroll
    for (int k = 0; k < 16; k++) {
        float b;
        asm("sub.sat.f32 %0, %1, %2;" : "=f"(b) : "f"((float)(8 * (k >> 1) + (k & 1))), "f"(x));
        const int i = 32 + 4 * (k >> 1) + (k & 1);
        asm("fma.rn.f32 %0, %1, 0fFF61B1E6, %0;" : "+f"(s[i]) : "f"(b));
        if (k < 14) asm("fma.rn.f32 %0, %1, 0fFF61B1E6, %0;" : "+f"(s[i + 6]) : "f"(b));
    }
}
__device__ __forceinline__ void tri_mask_copy(float (&s)[64], const float (&h)[32], float x) {
#pragma unroll
    for (int i = 0; i < 32; i++) {
        asm("{\n.reg .pred p;\nsetp.lt.f32 p, %2, %3;\nselp.f32 %0, 0fFF800000, %1, p;\n}"
            : "=f"(s[i]) : "f"(h[i]), "f"(x), "f"((float)(8 * (i >> 2) - 4 * (i & 2) + (i & 1))));
        s[32 + i] = __uint_as_float(0xff800000u);
    }
}
constexpr float SM_HI = 1152921504606846976.f, SM_LO = 1.f / 1152921504606846976.f;
__device__ __forceinline__ bool softmax_unsafe(float t0, float t1, bool first) {
    bool bad = __any_sync(0xffffffffu, fmaxf(t0, t1) > SM_HI);
    if (first) {
        uint32_t a = __ballot_sync(0xffffffffu, t0 >= SM_LO), b = __ballot_sync(0xffffffffu, t1 >= SM_LO);
        a |= a >> 1;
        b |= b >> 1;
        bad |= ((a | (a >> 2)) & (b | (b >> 2)) & 0x11111111u) != 0x11111111u;
    }
    return bad;
}
__device__ __forceinline__ void softmax_shift(float (&s)[64], float d0, float d1) {
#pragma unroll
    for (int i = 0; i < 64; i++) s[i] -= (i & 2) ? d1 : d0;
}
__device__ __forceinline__ void softmax_remax(float (&s)[64], float (&m)[2], bool first, float& a0, float& a1) {
    float m0 = fmaxf(s[0], s[1]), m1 = fmaxf(s[2], s[3]);
#pragma unroll
    for (int k = 1; k < 16; k++) {
        m0 = fmaxf(m0, fmaxf(s[4 * k], s[4 * k + 1]));
        m1 = fmaxf(m1, fmaxf(s[4 * k + 2], s[4 * k + 3]));
    }
    m0 = fmaxf(m0, __shfl_xor_sync(0xffffffffu, m0, 1));
    m1 = fmaxf(m1, __shfl_xor_sync(0xffffffffu, m1, 1));
    m0 = fmaxf(m0, __shfl_xor_sync(0xffffffffu, m0, 2));
    m1 = fmaxf(m1, __shfl_xor_sync(0xffffffffu, m1, 2));
    if (!first) {
        m0 = fmaxf(m0, 0.f);
        m1 = fmaxf(m1, 0.f);
    }
    a0 = first ? 1.f : ex2(-m0);
    a1 = first ? 1.f : ex2(-m1);
    m[0] += m0;
    m[1] += m1;
    softmax_shift(s, m0, m1);
}
template <int J0, int J1>
__device__ __forceinline__ void softmax_exp(const float (&s)[64], uint32_t (&p)[32], float (&t)[4]) {
#pragma unroll
    for (int k = J0; k < J1; k++) {
        const float e0 = ex2(s[4 * k]), e1 = ex2(s[4 * k + 1]), e2 = ex2(s[4 * k + 2]), e3 = ex2(s[4 * k + 3]);
        if (k == 0) { t[0] = e0; t[1] = e1; t[2] = e2; t[3] = e3; }
        else { t[0] += e0; t[1] += e1; t[2] += e2; t[3] += e3; }
        p[2 * k] = pack2(e0, e1);
        p[2 * k + 1] = pack2(e2, e3);
    }
}
__device__ __forceinline__ void fma8(float (&acc)[8], float a, uint4 w) {
    acc[0] = fmaf(a, bf_lo(w.x), acc[0]); acc[1] = fmaf(a, bf_hi(w.x), acc[1]);
    acc[2] = fmaf(a, bf_lo(w.y), acc[2]); acc[3] = fmaf(a, bf_hi(w.y), acc[3]);
    acc[4] = fmaf(a, bf_lo(w.z), acc[4]); acc[5] = fmaf(a, bf_hi(w.z), acc[5]);
    acc[6] = fmaf(a, bf_lo(w.w), acc[6]); acc[7] = fmaf(a, bf_hi(w.w), acc[7]);
}
__device__ __forceinline__ void mma16816(float (&d)[4], const uint32_t* a, uint32_t b0, uint32_t b1) {
    asm("mma.sync.aligned.m16n8k16.row.col.f32.bf16.bf16.f32 {%0, %1, %2, %3}, {%4, %5, %6, %7}, {%8, %9}, {%0, %1, %2, %3};"
        : "+f"(d[0]), "+f"(d[1]), "+f"(d[2]), "+f"(d[3]) : "r"(a[0]), "r"(a[1]), "r"(a[2]), "r"(a[3]), "r"(b0), "r"(b1));
}
__device__ __forceinline__ uint2 best_key(const uint32_t* keys, int lane, uint32_t ep, uint32_t cur, int enough) {
#pragma unroll 1
    for (;;) {
        const uint4 k = ld_poll(reinterpret_cast<const uint4*>(keys) + lane);
        const bool ok = (((k.x ^ ep) | (k.y ^ ep) | (k.z ^ ep) | (k.w ^ ep)) & 31) == 0;
        const uint32_t best = __reduce_max_sync(0xffffffffu, ok ? max(max(k.x, k.y), max(k.z, k.w)) : 0u);
        const int n = __popc(__ballot_sync(0xffffffffu, ok));
        if (n == 32 || (n >= enough && best != cur)) return make_uint2(best, n == 32);
        __nanosleep(KSLEEP);
    }
}

__global__ void __cluster_dims__(2, 1, 1) __launch_bounds__(384, 1)
fused_kernel(const __grid_constant__ CUtensorMap tm_ckv, const __grid_constant__ CUtensorMap tm_wq,
             const __grid_constant__ CUtensorMap tm_wuk, const __grid_constant__ CUtensorMap tm_wuv,
             const __grid_constant__ CUtensorMap tm_wo, const __grid_constant__ CUtensorMap tm_wg,
             const __grid_constant__ CUtensorMap tm_wu,
             const __grid_constant__ CUtensorMap tm_wm, const __grid_constant__ CUtensorMap tm_x, const Params P) {
    extern __shared__ __align__(1024) uint8_t smem[];
    const uint32_t sb = (uint32_t)__cvta_generic_to_shared(smem);
    const int tid = threadIdx.x, lane = tid & 31, warp = __shfl_sync(0xffffffffu, tid >> 5, 0), wg = warp >> 2;
    const uint32_t sm = blockIdx.x < 8 ? blockIdx.x + 124 : blockIdx.x - 8, smq = ((sm - 64) * 147) >> 11;
    const int rb = sm < 64 ? (sm & 14) * 8 + (sm >> 4) * 2 + (sm & 1)
                 : sm < 120 ? ((sm - 64 - smq * 14) & 14) * 8 + 24 + smq * 2 + (sm & 1) : sm < 124 ? sm + 8 : sm - 116;
    const int grp = rb >> 3, j = rb & 7, cq = j & 3, kh = grp & 1, ort = (grp & 14) + (j >> 2);
    if (warp == 0) TS(0);

    if (lane == 0) {
        if (warp == 8) {
            asm volatile("prefetch.tensormap [%0];" ::"l"(rb >= NCTA ? &tm_wm : (j & 1) ? &tm_wuv : &tm_wuk) : "memory");
            asm volatile("prefetch.tensormap [%0];" ::"l"(&tm_ckv) : "memory");
            *reinterpret_cast<uint2*>(smem + SM_EP + 16) = make_uint2(0, 0);
        }
        const u64 cnt = (warp < 5 ? (rb < NCTA ? 0x844444441111111ull : 0x888888881111111ull) : warp < 10 ? 0x111111188888888ull : 0x118121ull) >> (12 * (warp % 5));
#pragma unroll
        for (int i = 0; i < 3; i++) mbar_init(sb + SM_BAR + 24 * warp + 8 * i, ((uint32_t)cnt >> (4 * i)) & 15);
        fence_async_smem();
        asm volatile("fence.mbarrier_init.release.cluster;" ::: "memory");
    }
    __syncthreads();
    asm volatile("barrier.cluster.arrive.relaxed.aligned;\nbarrier.cluster.wait.aligned;" ::: "memory");

    if (rb >= NCTA) {
        float* sc = reinterpret_cast<float*>(smem + 6 * SLOT);
        float* red = sc + 512;
        uint32_t ph = 0x7f, sl = 0;
        if (warp == 8) {
#pragma unroll 1
            for (int i = 0; i < 24; i++) {
                slot_acquire(sb, ph, sl);
                tma2d(sb + sl * SLOT, &tm_wm, (i >> 3) * 1024 + (rb - NCTA) * 256, (i & 7) * 64, sb + BAR_FULL + 8 * sl, HINT & 64);
                if (++sl == 6) sl = 0;
            }
#pragma unroll 1
            for (int i = 0; i <= NFFN / NSPARE; i++) {
                const int b = (rb - NCTA) * (NFFN / NSPARE) + i;
                if (i < NFFN / NSPARE) {
                    asm volatile("cp.async.bulk.wait_group.read 0;" ::: "memory");
                    uint32_t done = 0x7f;
                    slot_acquire(sb, done, i & 1);
#pragma unroll 1
                    for (int k = 0; k < 4; k++) tma2d(sb + (i & 1) * SLOT + k * 8192, k < 2 ? &tm_wg : &tm_wu, b * 16, (k & 1) * 256, sb + BAR_FULL + 8 * (i & 1), (HINT & 128) && (i & 3) == 3);
                }
                if (i) {
                    mbar_wait(sb + BAR_FULL + 8 * (~i & 1), ((i - 1) >> 1) & 1);
                    bulk_store(g_wf + (b - 1) * SLOT, sb + (~i & 1) * SLOT, SLOT, HINT & 256);
                    asm volatile("cp.async.bulk.commit_group;" ::: "memory");
                }
            }
            asm volatile("cp.async.bulk.wait_group 0;" ::: "memory");
            fence_async_global();
            TS(4);
        } else if (warp < 8) {
            const uint32_t c2 = __ldg(reinterpret_cast<const uint32_t*>(P.c) + tid), ep = __ldcg(&g_sync.epoch[0]) + 1;
            sc[2 * tid] = rbf(bf_lo(c2) * sigmoid(bf_lo(c2)));
            sc[2 * tid + 1] = rbf(bf_hi(c2) * sigmoid(bf_hi(c2)));
            ph = 0;
#pragma unroll 1
            for (int ps = 0; ps < 3; ps++) {
                bar_sync(1, 256);
                float acc[8] = {0.f, 0.f, 0.f, 0.f, 0.f, 0.f, 0.f, 0.f};
#pragma unroll 1
                for (int bt = 0; bt < 8; bt++) {
                    slot_wait(sb + BAR_FULL, ph, sl);
#pragma unroll 4
                    for (int i = 0; i < 8; i++)
                        fma8(acc, sc[bt * 64 + warp * 8 + i], *reinterpret_cast<const uint4*>(smem + sl * SLOT + (warp * 8 + i) * 512 + lane * 16));
                    __syncwarp();
                    mbar_arrive_if(sb + BAR_EMPTY + 8 * sl, lane == 0);
                    if (++sl == 6) sl = 0;
                }
                *reinterpret_cast<float4*>(red + warp * 256 + lane * 8) = make_float4(acc[0], acc[1], acc[2], acc[3]);
                *reinterpret_cast<float4*>(red + warp * 256 + lane * 8 + 4) = make_float4(acc[4], acc[5], acc[6], acc[7]);
                bar_sync(1, 256);
                float v = 0.f;
#pragma unroll
                for (int i = 0; i < 8; i++) v += red[i * 256 + tid];
                if (ps == 0) st_pub(g_mod1 + (rb - NCTA) * 256 + tid, (pack2(0.f, v) & 0xffff0000u) | (ep & 0xffffu), true);
                else g_mod[ps * 1024 + (rb - NCTA) * 256 + tid] = __float2bfloat16_rn(v);
                if (warp == 0) TS(1 + ps);
            }
        }
        __syncthreads();
        if (tid < 2) flag_add(&g_sync.cnt[7 * 8]);
        return;
    }

    if (wg == 2) {
        asm volatile("setmaxnreg.dec.sync.aligned.u32 40;");
        const CUtensorMap* tw = (j & 1) ? &tm_wuv : &tm_wuk;
        if (warp == 8) {
            const uint32_t rank = j & 1, half = rank * 16384;
            uint32_t eph = 0x7f, r = 0;
#pragma unroll 1
            for (int hp = 0; hp < 2; hp++) {
                uint32_t wtab = w_table(hp), atab = a_table(hp);
                const int hc = 4 * grp + 2 * hp;
#pragma unroll 1
                for (int u = 0; u < 16; u++) {
                    if (u < 4) {
                        const uint32_t ws = (wtab >> (4 * u)) & 15;
                        slot_acquire(sb, eph, ws);
                        load_tile(sb, ws, 0, tw, u * 128, hc, false, HINT & 1);
                        PT();
                    }
                    if (hp == 1 && (u & 7) == 4) mbar_wait(sb + BAR_FLAG + 24 + (u & 8), 0);
                    const uint32_t as = a_next(atab);
                    slot_acquire(sb, eph, as);
                    load_tile(sb, as, half, &tm_ckv, ((u & 12) + (j >> 1)) * 128, (u & 3) * 2 + rank, true, (HINT & 8) && hp);
                    PT();
                    if (hp == 1 && (u | 2) == 3 && lane == 0)
                        asm volatile("red.relaxed.gpu.global.add.u32 [%0], 1;" ::"l"(&g_sync.cnt[(grp * 8 + 3 + (u >> 1)) * 8]) : "memory");
                }
                const uint8_t* src = g_h + (15 - j) * 4 * SLOT;
#pragma unroll 1
                for (int u = 0; u < 8; u++) {
                    if ((u & 3) == 0) {
                        mbar_wait(sb + BAR_FLAG + (2 + 8 * hp) * u, 0);
                        fence_async_global();
                    }
                    if (u < 4) {
                        const uint32_t ws = (wtab >> (4 * u)) & 15;
                        slot_acquire(sb, eph, ws);
                        load_tile(sb, ws, half, &tm_wq, u * 128, hc + rank, true, HINT & 1);
                        PT();
                    }
                    const uint32_t as = a_next(atab);
                    slot_acquire(sb, eph, as);
                    load_bulk(sb, as, 0, src, SLOT, false, (HINT & 8) && hp);
                    PT();
                    src += u == 3 ? (8 * j - 63) * SLOT : SLOT;
                }
                const int step = hp ? -2 * SLOT : 2 * SLOT;
                src = g_KV + (size_t)(grp * 32 + 30 * hp) * SLOT + half - step;
#pragma unroll 1
                for (int n = 0; n <= 17; n++) {
                    if (n == 8) {
                        mbar_wait(sb + BAR_FLAG + 16 + 32 * hp, 0);
                        fence_async_global();
                    }
                    const uint8_t* v = src + SLOT;
                    src += n < 16 - j ? step : n == 16 - j ? (2 * j - 15) * step : -step;
                    if (n < 17) {
                        slot_acquire(sb, eph, r);
                        if (n != 15 - (j & 6)) load_bulk(sb, r, half, src, SLOT / 2, true, (HINT & 4) && (hp || !(HINT & 32)));
                        else load_bulk(sb, r, 0, src - half, SLOT, false, (HINT & 4) && (hp || !(HINT & 32)));
                        PT();
                        r = ring_next(r);
                    }
                    if (n) {
                        slot_acquire(sb, eph, r);
                        if (n != 16 - (j & 6)) load_bulk(sb, r, half, v, SLOT / 2, true, (HINT & 4) && (hp || !(HINT & 32)));
                        else load_bulk(sb, r, 0, v - half, SLOT, false, (HINT & 4) && (hp || !(HINT & 32)));
                        PT();
                        r = ring_next(r);
                    }
                    asm volatile("st.volatile.shared.u32 [%0], %1;" ::"r"(sb + SM_EP + 16), "r"(18 * hp + n + 1) : "memory");
                }
            }
            uint32_t otab = O_TABLE, ready = 0;
#pragma unroll 1
            for (int i = 0; i < 17; i++) {
                const bool dyn = i >= 8 && i < 15;
                const uint32_t want = dyn ? 15u << (4 * (i - 8)) : 1u << max(i + 14, 28);
                if (!(ready & want)) {
                    do {
                        asm volatile("ld.acquire.cta.shared.u32 %0, [%1];" : "=r"(ready) : "r"(sb + SM_EP + 20) : "memory");
                        ready = __shfl_sync(0xffffffffu, ready, 0);
                    } while (!(ready & want));
                    fence_async_global();
                }
                const int head = o_head(dyn ? (ready >> (4 * (i - 8))) & 15 : i, kh);
                const uint32_t as = o_next(otab), ws = o_next(otab), off = i < 15 ? half : kh * 16384;
                slot_acquire(sb, eph, as);
                load_bulk(sb, as, off, g_ctx + (size_t)(ort * 32 + head) * SLOT + off, SLOT / 2, i < 15, HINT & 16);
                if (i == 15) load_tile(sb, as, off ^ 16384, &tm_x, ort * 128 + kh * 64, cq * 2, false, false);
                if (i == 16) load_bulk(sb, as, off ^ 16384, P.wdown + min(rb, NFFN - 1) * 8192, SLOT / 2, false, false);
                PT();
                slot_acquire(sb, eph, ws);
                load_tile(sb, ws, 0, &tm_wo, head * 128, cq * 2, false, HINT & 2);
                PT();
                if (i == 0) o_next(otab);
            }
            if (rb < NFFN) {
                slot_acquire(sb, eph, 5);
                load_bulk(sb, 5, 0, g_wf + rb * SLOT, SLOT, false, false);
            }
        } else if (warp == 9) {
            l2_prefetch(P.ckv + rb * 2048, 4096);
            mbar_watch(sb + BAR_FULL, 0);
            l2_prefetch(P.ckv + 512 * 512 + rb * 2048, 4096);
            mbar_watch(sb + BAR_FULL + 8 * XPF, 0);
            l2_prefetch(P.x + rb * 8192, 16384);
            mbar_watch(sb + BAR_FULL + 8 * 4, 0);
            l2_prefetch(P.ckv + 1024 * 512 + rb * 4096, 8192);
            TS(40);
#pragma unroll 1
            for (int i = 0; i < 15; i++) {
                step_watch(sb + SM_EP + 16, i == 0 ? 0 : i < 5 ? PFA + i : 13 + PFB + i);
                if (i == 12) mbar_watch(sb + BAR_FLAG + 8 * 7, 0);
                const int rf = min(rb, NFFN - 1);
                const uint8_t* p = i == 3 ? reinterpret_cast<const uint8_t*>(P.ckv) + rb * 16384
                                 : i == 4 ? g_h + rb * 16384
                                 : i < 9 ? g_ctx + (size_t)(ort * 32 + o_head(cq + 2 * ((i - 5) & 2), kh)) * SLOT + (i & 1) * 16384
                                 : i < 11 ? reinterpret_cast<const uint8_t*>(P.wo) + (grp * 16 + (~i & 1) * 8 + j) * 16384
                                 : i == 11 ? reinterpret_cast<const uint8_t*>(P.x) + rb * 16384
                                 : i == 12 ? reinterpret_cast<const uint8_t*>(P.wdown) + rf * 16384 : g_wf + rf * SLOT + (i & 1) * 16384;
                if (i < 3) tma3d_prefetch(i == 1 ? tw : &tm_wq, (j >> 1) * 128, grp * 4 + (i == 1 ? 2 : i + (j & 1)));
                else l2_prefetch(p, 16384);
            }
            const uint32_t v = lds32(sb + SM_EP) - 1;
            sts128(sb + SM_RED + lane * 16, make_uint4(v, v, v, v));
            fence_async_smem();
            __syncwarp();
#pragma unroll 1
            for (int i = 0; i < OB / 32; i++) bulk_store(g_out + rb * OB + i * 32, sb + SM_RED, 512, false);
            asm volatile("cp.async.bulk.commit_group;\ncp.async.bulk.wait_group 0;" ::: "memory");
            fence_async_global();
            __syncwarp();
            mbar_arrive_if(sb + BAR_PF, lane == 0);
            if (lane == 0) mbar_watch(sb + BAR_END, 0);
        } else {
            const uint32_t ep = __ldcg(&g_sync.epoch[0]) + 1;
            asm volatile("st.shared.u32 [%0], %1;" ::"r"(sb + SM_EP), "r"(ep) : "memory");
            mbar_wait(sb + BAR_FULL + 8 * 4, 0);
            {
                uint4 v[4];
                for (;;) {
                    uint32_t bad = 0;
#pragma unroll
                    for (int k = 0; k < 4; k++) v[k] = ld_poll(reinterpret_cast<const uint4*>(g_mod1) + (warp & 1) * 128 + k * 32 + lane);
#pragma unroll
                    for (int k = 0; k < 4; k++) bad |= (v[k].x ^ ep) | (v[k].y ^ ep) | (v[k].z ^ ep) | (v[k].w ^ ep);
                    if (__all_sync(0xffffffffu, (bad & 0xffff) == 0)) break;
                    __nanosleep(100);
                }
                const uint32_t one = (warp & 1) ? ONE2 : 0x80008000u;
#pragma unroll
                for (int k = 0; k < 4; k++)
                    *reinterpret_cast<uint2*>(smem + SM_TAB + (warp & 1) * 1024 + k * 256 + lane * 8) =
                        make_uint2(badd(__byte_perm(v[k].x, v[k].y, 0x7632), one), badd(__byte_perm(v[k].z, v[k].w, 0x7632), one));
            }
            __syncwarp();
            mbar_arrive_if(sb + BAR_FLAG + 8 * 8, lane == 0);
            if (warp == 10) {
#pragma unroll 1
                for (int i = 0; i < 9; i++) {
                    mbar_sleep(sb + BAR_DONE + 8 * i);
                    if (lane == 0) flag_add(i && ((i - 1) & 2) ? &g_sync.ctxcnt[((i & 1) ? 15 - j : j) * 32 + 2 * grp + (i > 4)] : &g_sync.cnt[(grp * 8 + i) * 8]);
                    if (i == 0) TS(43);
                }
            } else {
                TS(42);
#pragma unroll 1
                for (int i = 0; i < 8; i++) {
                    mbar_sleep(sb + BAR_DONE + 8 * (i == 7 ? 6 : i == 4 ? 3 : i));
                    if (lane < 2) flag_wait(&g_sync.cnt[((i == 0 ? (lane ? j : 15 - j) : i == 7 ? 0 : grp) * 8 + i) * 8], 8 * ep);
                    __syncwarp();
                    mbar_arrive_if(sb + BAR_FLAG + 8 * i, lane == 0 && i < 7);
                    TS(48 + i);
                }
                const uint32_t *mp = reinterpret_cast<const uint32_t*>(g_mod) + lane, *wp = reinterpret_cast<const uint32_t*>(P.wr) + lane;
                float ra = 0.f, rs = 0.f;
#pragma unroll 1
                for (int k = 0; k < 256; k += 32) {
                    const uint32_t ga = __ldcg(mp + 512 + k), sh = __ldcg(mp + 768 + k), c1 = badd(__ldcg(mp + 1024 + k), ONE2);
                    const uint32_t gb = __ldcg(mp + 1280 + k), ww = __ldg(wp + k);
                    const float a0 = bf_lo(c1) * bf_lo(ww), a1 = bf_hi(c1) * bf_hi(ww);
                    ra += a0 + a1;
                    rs = fmaf(bf_lo(sh), bf_lo(ww), fmaf(bf_hi(sh), bf_hi(ww), rs));
                    if (k >> 6 == cq) {
                        sts128(sb + SM_TAB + ((k & 32) + lane) * 16, make_uint4(ga << 16, ga & 0xffff0000u, __float_as_uint(a0), __float_as_uint(a1)));
                        sts128(sb + SM_TAB + 1024 + ((k & 32) + lane) * 16, make_uint4(c1, sh, gb, 0));
                    }
                }
#pragma unroll 1
                for (int o = 16; o > 0; o >>= 1) {
                    ra += __shfl_xor_sync(0xffffffffu, ra, o);
                    rs += __shfl_xor_sync(0xffffffffu, rs, o);
                }
                *reinterpret_cast<float2*>(smem + SM_EP + 8) = make_float2(ra, rs);
                __syncwarp();
                mbar_arrive_if(sb + BAR_FLAG + 8 * 7, lane == 0);
                const uint32_t* f = &g_sync.ctxcnt[ort * 32 + o_head(min(lane, 16), kh)];
                uint32_t ready = -(j & 1), list = 0, sh = 0, qa;
                asm("mapa.shared::cluster.u32 %0, %1, %2;" : "=r"(qa) : "r"(sb + SM_EP + 20), "r"(lane & 1));
                while (ready != ~0u) {
                    uint32_t v;
                    asm volatile("ld.acquire.gpu.global.u32 %0, [%1];" : "=r"(v) : "l"(f) : "memory");
                    const uint32_t now = __ballot_sync(0xffffffffu, (int)(v - ep) >= 0);
#pragma unroll 1
                    for (uint32_t fresh = now & ~ready & 0x7f00; fresh; fresh &= fresh - 1, sh += 4) list |= (__ffs(fresh) - 1) << sh;
                    list |= (((now & 0xff) + 1) >> 8 << 28) | ((now & 0x18000) << 14);
                    if (now != ready && lane < 2) asm volatile("st.relaxed.cluster.shared::cluster.u32 [%0], %1;" ::"r"(qa), "r"(list) : "memory");
                    if ((now & 0xff) == 0xff) mbar_sleep(sb + BAR_DONE + 8 * 7);
                    ready = now;
                    __nanosleep(POLL_NS);
                }
                TS(45);
            }
        }
    } else {
        asm volatile("setmaxnreg.inc.sync.aligned.u32 232;");
        const bool elected = (tid & 127) == 0, rel = (tid & 95) == 0;
        uint32_t eb;
        asm("mapa.shared::cluster.u32 %0, %1, %2;" : "=r"(eb) : "r"(sb + BAR_EMPTY), "r"(warp & 1));
        const int g = lane >> 2, c4 = lane & 3;
        const uint32_t toff = warp * 4096 + g * 64 + ((c4 ^ (g >> 1)) << 4);
        uint32_t fph = 0x3f, r = 0;
        if (wg == 1) bar_arrive(1, 256);
        const uint32_t kd = desc_k(sb), wd = desc_mn(sb), vd = ((sb & 0x3ffff) >> 4) | (32u << 16);
        const int nL = 16 - j, hn = nL - 1 + wg;
        float s[64], o[64], li[2] = {0.f, 0.f};
        uint8_t* cimg = g_ctx;
        const float sc = (j & 1) ? 1.f : SM_C;
#pragma unroll 1
        for (int q = 0; q < 3; q++) {
            const uint32_t as = (0x635u >> (4 * q)) & 15;
            mbar_wait(sb + BAR_FULL + 8 * q, 0);
            mbar_wait(sb + BAR_FULL + 8 * as, 0);
            bar_sync(1 + wg, 256);
            gemm_issue<false>(s, kd + wg * 512 + as * (SLOT / 16), wd + q * (SLOT / 16), q, false);
            bar_arrive(2 - wg, 256);
            wg_wait<0>();
            release_if(eb, as, rel);
        }
        {
            const int xrow = rb * 16 + warp * 2;
            const uint4* xp = reinterpret_cast<const uint4*>(P.x) + xrow * 64;
            uint8_t* img = g_KV + (size_t)(grp * 32 + j) * SLOT;
            uint32_t x[16], x0[2];
            float st[4] = {0.f, 0.f, 0.f, 0.f};
            mbar_wait(sb + BAR_FULL + 8 * 4, 0);
#pragma unroll
            for (int q = 3; q < 8; q++) {
                const uint32_t ws = (0x4210u >> (4 * (q & 3))) & 15, as = (0x635u >> (4 * (q % 3))) & 15;
                mbar_wait(sb + BAR_FULL + 8 * as, (q / 3) & 1);
                bar_sync(1 + wg, 256);
                if (q == 3) gemm_issue<false>(s, kd + wg * 512 + as * (SLOT / 16), wd + ws * (SLOT / 16), 1, false);
                else if (q == 4) gemm_issue<true>(o, kd + wg * 512 + as * (SLOT / 16), wd + ws * (SLOT / 16), 0, false);
                else gemm_issue<false>(o, kd + wg * 512 + as * (SLOT / 16), wd + ws * (SLOT / 16), 1, false);
                bar_arrive(2 - wg, 256);
                sched_fence(fph, P.zero);
                if (q > 3) reg_fence(s);
                if (q == 3) {
#pragma unroll
                    for (int i = 0; i < 4; i++)
                        asm volatile("ld.global.nc.v4.u32 {%0, %1, %2, %3}, [%4];" : "=r"(x[4 * i]), "=r"(x[4 * i + 1]), "=r"(x[4 * i + 2]), "=r"(x[4 * i + 3])
                                     : "l"(xp + lane + 32 * i) : "memory");
#pragma unroll
                    for (int i = 0; i < 2; i++) asm volatile("ld.global.nc.u32 %0, [%1];" : "=r"(x0[i]) : "l"(xp + 64 * i) : "memory");
                }
                if (q == 4) {
                    img_store_global<0>(img, toff, s, sc, sc);
#pragma unroll
                    for (int k = 0; k < 16; k++) {
                        const float d0 = bf_lo(x[k]) - bf_lo(x0[k >> 3]), d1 = bf_hi(x[k]) - bf_lo(x0[k >> 3]);
                        st[k >> 3] += d0 + d1;
                        st[2 + (k >> 3)] = fmaf(d0, d0, fmaf(d1, d1, st[2 + (k >> 3)]));
                    }
#pragma unroll
                    for (int i = 0; i < 4 * NSH; i++) st[i & 3] += __shfl_xor_sync(0xffffffffu, st[i & 3], 1 << (i >> 2));
                    reg_fence(st);
                }
                if (q == 5) {
#pragma unroll
                    for (int i = 4 * NSH; i < 20; i++) st[i & 3] += __shfl_xor_sync(0xffffffffu, st[i & 3], 1 << (i >> 2));
                    img_store_global<1>(img, toff, s, sc, sc);
#pragma unroll
                    for (int i = 0; i < 2; i++) {
                        const float d = st[i] * (1.f / 512.f);
                        st[2 + i] = ln_rstd(fmaxf(fmaf(-d, d, st[2 + i] * (1.f / 512.f)), 0.f));
                        x0[i] = pack2(bf_lo(x0[i]) + d, bf_lo(x0[i]) + d);
                    }
                    reg_fence(st);
                    reg_fence(x0);
                }
                if (q > 5) {
                    if (q == 6) mbar_wait(sb + BAR_FLAG + 8 * 8, 0);
                    const uint4 a = lds128(sb + SM_TAB + 1024 + (q & 1) * 512 + lane * 16), c = lds128(sb + SM_TAB + (q & 1) * 512 + lane * 16);
                    uint8_t* hp = g_h + (grp * 8 + (q & 1) * 4 + (lane >> 3)) * 16384 + (xrow & 127) * 128;
#pragma unroll
                    for (int i = 0; i < 2; i++) {
                        const uint32_t* y = x + 8 * i + 4 * (q & 1);
                        *reinterpret_cast<uint4*>(hp + i * 128 + (((lane ^ xrow ^ i) & 7) << 4)) =
                            make_uint4(ln_apply(y[0], x0[i], st[2 + i], a.x, c.x), ln_apply(y[1], x0[i], st[2 + i], a.y, c.y),
                                       ln_apply(y[2], x0[i], st[2 + i], a.z, c.z), ln_apply(y[3], x0[i], st[2 + i], a.w, c.w));
                    }
                    if (q == 7) {
                        __syncwarp();
                        mbar_arrive_if(sb + BAR_DONE, lane == 0);
                    }
                    if (q == 6) img_store_global<2>(img, toff, s, sc, sc);
                    else img_store_global<3>(img, toff, s, sc, sc);
                }
                sched_fence(fph, P.zero);
                wg_wait<0>();
                release_if(eb, as, rel);
            }
            reg_fence(o);
        }
        uint32_t p[32] = {};
#pragma unroll 1
        for (int hp = 0; hp < 2; hp++) {
            float m[2] = {0.f, 0.f}, l[2] = {0.f, 0.f}, t[4] = {0.f, 0.f, 0.f, 0.f};
            bool shifted = false, bad = false, plain = false;
            uint32_t qa = desc_k(sb + 5 * SLOT + (wg ^ 1) * 8192);
            uint8_t* limg = g_ctx + (size_t)((15 - j) * 32 + 2 * grp + hp) * SLOT;
            {
                const int step = hp ? -8 * SLOT : 8 * SLOT;
                uint8_t* img = g_KV + (size_t)(grp * 32 + (hp ? j ^ 30 : j) + 8) * SLOT;
                const uint32_t wtab = w_table(hp);
                uint32_t atab = hp ? 0x562u : 0x356u;
#pragma unroll 1
                for (int u = 2 - 2 * hp;; u += 2) {
                    proj_tile<false>(s, o, u, !u, sb, wg, eb, rel, fph, wtab, atab, u ? img : cimg, toff, u ? sc : li[0], u ? sc : li[1], p);
                    __syncwarp();
                    mbar_arrive_if(sb + BAR_DONE + 4 * u + 32 * hp, lane == 0);
                    if (elected) TS(1 + 10 * hp + u + 20 * wg);
                    if (proj_tile<true>(o, s, u + 1, 0, sb, wg, eb, rel, fph, wtab, atab, img + step, toff, sc, sc, p)) break;
                    if (elected) TS(2 + 10 * hp + u + 20 * wg);
                    img += 2 * step;
                }
            }
            if (elected) TS(6 + 10 * hp + 20 * wg);
            int n = -1;
#pragma unroll 1
            for (;;) {
                while (bad || plain) {
                    if (bad) {
                        float a0, a1;
                        softmax_remax(s, m, n == 0 || n == nL, a0, a1);
                        shifted = true;
                        l[0] *= a0;
                        l[1] *= a1;
#pragma unroll
                        for (int i = 0; i < 64; i++) o[i] *= (i & 2) ? a1 : a0;
                    }
                    softmax_exp<0, 16>(s, p, t);
                    t[0] += t[1];
                    t[2] += t[3];
                    bad = !bad && softmax_unsafe(t[0], t[2], false);
                    plain = false;
                }
#pragma unroll 1
                do {
                    l[0] += t[0];
                    l[1] += t[2];
                    if (++n > 16) break;
                    const uint32_t ks = r;
                    uint32_t vs = ring_next(r);
                    r = ring_next(vs);
                    bar_sync(1 + wg, 256);
                    const float x = (float)((warp & 3) * 16 + g - 2 * c4);
                    if (n == hn) {
                        float sh[32];
                        qk_issue(sh, qa, kd + ks * (SLOT / 16));
                        slot_wait(sb + BAR_FULL, fph, vs);
                        pv_issue(o, p, vd + vs * (SLOT / 16), 1, false);
                        bar_arrive(2 - wg, 256);
                        wg_wait<1>();
                        reg_fence(sh);
                        tri_mask_copy(s, sh, x);
                        release_if(eb, ks, rel);
                        release_if(eb, 5 + wg, rel && (!wg || n == 16));
                        if (!wg) {
                            qa += SLOT / 16;
                            fence_async_smem();
                            if (shifted) softmax_shift(s, m[0], m[1]);
                        }
                        float e[4 * EARLY];
#pragma unroll
                        for (int i = 0; i < 4 * EARLY; i++) {
                            e[i] = ex2(s[i]);
                            t[i & 3] = i < 4 ? e[i] : t[i & 3] + e[i];
                        }
                        reg_fence(e);
                        slot_wait(sb + BAR_FULL, fph, r);
                        wg_wait<0>();
                        reg_fence(o);
                        reg_fence(e);
                        release_if(eb, vs, rel);
#pragma unroll
                        for (int i = 0; i < 2 * EARLY; i++) p[i] = pack2(e[2 * i], e[2 * i + 1]);
                        softmax_exp<EARLY, 8>(s, p, t);
                        if (wg) {
                            ctx_store<true>(limg, toff, o, l[0], l[1]);
                            __syncwarp();
                            mbar_arrive_if(sb + BAR_DONE + 24 + 32 * hp, lane == 0);
                            l[0] = l[1] = m[0] = m[1] = 0.f;
                            shifted = false;
                        }
                        t[0] += t[1];
                        t[2] += t[3];
                        bad = softmax_unsafe(t[0], t[2], wg);
                        continue;
                    }
                    if (n == 0 || n == nL) {
                        qk_issue(s, qa, kd + ks * (SLOT / 16));
                        if (n == 0) {
                            r = vs;
                            vs = 4 - hp;
                            slot_wait(sb + BAR_FULL, fph, 6);
                            gemm_issue<false>(o, qa + SLOT / 16, wd + vs * (SLOT / 16), 1, false);
                        } else {
                            slot_wait(sb + BAR_FULL, fph, vs);
                            pv_issue(o, p, vd + vs * (SLOT / 16), 1, true);
                        }
                        bar_arrive(2 - wg, 256);
                        const float i0 = n ? rcp(quad_sum(l[0])) : 1.f, i1 = n ? rcp(quad_sum(l[1])) : 1.f;
                        wg_wait<1>();
                        reg_fence(s);
                        release_if(eb, ks, rel);
                        release_if(eb, 6, rel && n == 16);
                        tri_mask(s, n ? x : 64.f);
                        float e[4 * EARLY];
#pragma unroll
                        for (int i = 0; i < 4 * EARLY; i++) {
                            e[i] = ex2(s[i]);
                            t[i & 3] = i < 4 ? e[i] : t[i & 3] + e[i];
                        }
                        reg_fence(e);
                        reg_fence(s);
                        reg_fence(t);
                        slot_wait(sb + BAR_FULL, fph, r);
                        if (SF & 1) sched_fence(fph, P.zero);
                        wg_wait<0>();
                        reg_fence(o);
                        reg_fence(e);
                        release_if(eb, vs, rel);
#pragma unroll
                        for (int i = 0; i < 2 * EARLY; i++) p[i] = pack2(e[2 * i], e[2 * i + 1]);
                        softmax_exp<EARLY, MSPLIT>(s, p, t);
                        tile_store(limg, sb + 6 * SLOT, toff, o, i0, i1, n);
                        reg_fence(t);
                        if (SF & 2) sched_fence(fph, P.zero);
                        reg_fence(s);
                        softmax_exp<MSPLIT, 16>(s, p, t);
                        __syncwarp();
                        mbar_arrive_if(sb + BAR_DONE + 24 + 32 * hp, lane == 0 && n);
                        l[0] = l[1] = m[0] = m[1] = 0.f;
                        shifted = false;
                        t[0] += t[1];
                        t[2] += t[3];
                        bad = __any_sync(0xffffffffu, fmaxf(t[0], t[2]) > SM_HI || fminf(t[0], t[2]) < SM_LO);
                        continue;
                    }
                    qk_issue(s, qa, kd + ks * (SLOT / 16));
                    slot_wait(sb + BAR_FULL, fph, vs);
                    pv_issue(o, p, vd + vs * (SLOT / 16), n != 1 && n != nL + 1, n == hn + 1);
                    bar_arrive(2 - wg, 256);
                    wg_wait<1>();
                    reg_fence(s);
                    release_if(eb, ks, rel);
                    release_if(eb, 6, rel && n == 16);
                    if (n == nL - 1) {
                        tri_mask(s, x);
                        release_if(eb, 5, rel);
                        qa += SLOT / 16;
                        fence_async_smem();
                    }
                    if (shifted) {
                        slot_wait(sb + BAR_FULL, fph, r);
                        wg_wait<0>();
                        reg_fence(o);
                        release_if(eb, vs, rel);
                        softmax_shift(s, m[0], m[1]);
                        plain = true;
                        break;
                    }
                    float e[4 * EARLY];
#pragma unroll
                    for (int i = 0; i < 4 * EARLY; i++) {
                        e[i] = ex2(s[i]);
                        t[i & 3] = i < 4 ? e[i] : t[i & 3] + e[i];
                    }
                    reg_fence(e);
                    slot_wait(sb + BAR_FULL, fph, r);
                    wg_wait<0>();
                    reg_fence(o);
                    reg_fence(e);
                    release_if(eb, vs, rel);
#pragma unroll
                    for (int i = 0; i < 2 * EARLY; i++) p[i] = pack2(e[2 * i], e[2 * i + 1]);
                    softmax_exp<EARLY, 16>(s, p, t);
                    t[0] += t[1];
                    t[2] += t[3];
                    bad = softmax_unsafe(t[0], t[2], false);
                } while (!bad);
                if (!bad && !plain) break;
            }
            const uint32_t vs = r, ga = desc_k(sb + (hp ? 2 * (wg ^ kh ^ 1) : wg) * 8192);
            r = ring_next(r);
            slot_wait(sb + BAR_FULL, fph, 5);
            slot_wait(sb + BAR_FULL, fph, r);
            bar_sync(1 + wg, 256);
            gemm_issue<true>(s, ga + 5 * (SLOT / 16), wd + r * (SLOT / 16), 0, hp);
            pv_issue(o, p, vd + vs * (SLOT / 16), j, hn == 16);
            bar_arrive(2 - wg, 256);
            li[0] = rcp(quad_sum(l[0]));
            li[1] = rcp(quad_sum(l[1]));
            cimg = limg + (ptrdiff_t)(2 * j - 15) * 32 * SLOT + (wg ? -16384 : 16384);
            wg_wait<1>();
            release_if(eb, 5, rel);
            release_if(eb, r, rel && hp);
            wg_wait<0>();
            release_if(eb, vs, rel);
            reg_fence(o);
            img_store_global<0>(cimg, toff, o, li[0], li[1]);
            if (elected) TS(8 + 10 * hp + 20 * wg);
        }
        uint32_t otab = 0x2351604u;
        const uint32_t oa = desc_k(sb + (wg ^ kh ^ 1) * 16384);
        const int t7 = tid & 127, w4 = warp & 3, row = ort * 128 + kh * 64 + w4 * 16 + g;
#pragma unroll 1
        for (int i = 1; i < 15 - wg; i++) {
            const uint32_t as = o_next(otab), ws = o_next(otab);
            slot_wait(sb + BAR_FULL, fph, as);
            slot_wait(sb + BAR_FULL, fph, ws);
            bar_sync(1 + wg, 256);
            gemm_issue<false>(s, oa + as * (SLOT / 16), wd + ws * (SLOT / 16), 1, true);
            bar_arrive(2 - wg, 256);
            wg_wait<1>();
            reg_fence(o);
            if (i == 1) img_store_global<1>(cimg, toff, o, li[0], li[1]);
            if (i == 2) {
                img_store_global<2>(cimg, toff, o, li[0], li[1]);
                img_store_global<3>(cimg, toff, o, li[0], li[1]);
                __syncwarp();
                mbar_arrive_if(sb + BAR_DONE + 64, lane == 0);
            }
            wg_wait<0>();
            release_if(eb, as, rel);
            release_if(eb, ws, rel);
        }
        mbar_wait(sb + BAR_PF, 0);
        const uint32_t ep = lds32(sb + SM_EP);
        uint32_t eb2 = sb + BAR_END;
        if (wg == 0) {
            reg_fence(s);
            if (elected) TS(9);
            TT(1);
#pragma unroll
            for (int v = 0; v < 8; v++)
                st_pub(g_out + rb * OB + v * 128 + t7, make_uint4((pack2(s[8 * v], s[8 * v + 1]) & ~1u) | (ep & 1), pack2(s[8 * v + 2], s[8 * v + 3]),
                                                                      pack2(s[8 * v + 4], s[8 * v + 5]), pack2(s[8 * v + 6], s[8 * v + 7])), true);
            constexpr uint32_t s1 = 5, s2 = 6;
            bar_sync(4, 256);
            uint32_t wf[64];
            float wn[64];
            if (rb < NFFN) {
                slot_wait(sb + BAR_FULL, fph, s1);
                const uint32_t a = sb + s1 * SLOT + (w4 * 128 + (lane >> 4) * 8 + (lane & 7)) * 32 + ((lane >> 3) & 1) * 16;
#pragma unroll
                for (int i = 0; i < 16; i++)
                    asm volatile("ldmatrix.sync.aligned.m8n8.x4.trans.shared.b16 {%0, %1, %2, %3}, [%4];"
                                 : "=r"(wf[4 * i]), "=r"(wf[4 * i + 1]), "=r"(wf[4 * i + 2]), "=r"(wf[4 * i + 3])
                                 : "r"(a + (i >> 3) * 16384 + (i & 7) * 512) : "memory");
                slot_wait(sb + BAR_FULL, fph, s2);
#pragma unroll
                for (int i = 0; i < 16; i++) {
                    const uint2 w = *reinterpret_cast<const uint2*>(smem + s2 * SLOT + (kh ^ 1) * 16384 + i * 1024 + t7 * 8);
                    wn[4 * i] = bf_lo(w.x); wn[4 * i + 1] = bf_hi(w.x); wn[4 * i + 2] = bf_lo(w.y); wn[4 * i + 3] = bf_hi(w.y);
                }
                reg_fence(wn);
            }
            const uint32_t gbf = __ldcg(reinterpret_cast<const uint32_t*>(g_mod) + 1280 + rb * 2 + (tid & 1));
            if (elected) TS(10);
            TT(2);
            float* sred = reinterpret_cast<float*>(smem + SM_RED);
            uint32_t best = ep ^ 1, all;
            bool fresh;
            do {
                if (warp == 0) {
                    const uint2 k = best_key(g_key + cq * 128, lane, ep, best, rb < NFFN ? SPEC : 32);
                    *reinterpret_cast<uint2*>(smem + SM_EP + 24) = k;
                    mbar_arrive_if(sb + BAR_BEST, lane == 0 && k.y);
                }
                bar_sync(3, 128);
                const uint2 k = *reinterpret_cast<const uint2*>(smem + SM_EP + 24);
                fresh = k.x != best;
                best = k.x;
                all = k.y;
                TT(3);
                if (!fresh || rb >= NFFN) break;
                const uint4* cp = g_cand + ((~best >> 9) & 127) * 192;
                uint4 cv[6];
                for (;;) {
                    uint32_t bad = 0;
#pragma unroll
                    for (int v = 0; v < 6; v++) cv[v] = ld_poll(cp + w4 * 24 + v * 4 + c4);
#pragma unroll
                    for (int v = 0; v < 6; v++) bad |= cv[v].w ^ ep;
                    if (__all_sync(0xffffffffu, bad == 0)) break;
                    if (CSLEEP) __nanosleep(CSLEEP);
                }
            TT(4);
                float d[4][4] = {};
#pragma unroll
                for (int k = 0; k < 8; k++) {
                    const uint32_t b0 = (&cv[(2 * k) / 3].x)[(2 * k) % 3], b1 = (&cv[(2 * k + 1) / 3].x)[(2 * k + 1) % 3];
                    mma16816(d[k & 1], wf + 4 * k, b0, b1);
                    mma16816(d[2 + (k & 1)], wf + 32 + 4 * k, b0, b1);
                }
                const float u = (c4 & 2) ? ((c4 & 1) ? d[2][2] + d[3][2] : d[2][0] + d[3][0]) : ((c4 & 1) ? d[0][2] + d[1][2] : d[0][0] + d[1][0]);
                sred[w4 * 32 + c4 * 8 + g] = u;
                bar_sync(3, 128);
                const float v = rbf((sred[lane] + sred[32 + lane]) + (sred[64 + lane] + sred[96 + lane]));
                const float act = rbf(rbf(v * sigmoid(v)) * __shfl_down_sync(0xffffffffu, v, 16));
                float y[4] = {0.f, 0.f, 0.f, 0.f};
#pragma unroll
                for (int k = 0; k < 16; k++) {
                    const float a = __shfl_sync(0xffffffffu, act, k);
#pragma unroll
                    for (int i = 0; i < 4; i++) y[i] = fmaf(a, wn[4 * k + i], y[i]);
                }
                st_pub(g_out + rb * OB + OB_Y + t7, make_uint4((__float_as_uint(y[0]) & ~15u) | (ep & 15), (__float_as_uint(y[1]) & ~127u) | ((best >> 9) & 127),
                                                               __float_as_uint(y[2]), __float_as_uint(y[3])), true);
            } while (!all);
            const int sel = (~best >> 5) & 2047;
            const int pq = (2 * rb + (tid & 1)) & 63, pv = (pq >> 2) / 3;
            const uint4* fp = g_cand + (sel >> 4) * 192 + (rb >> 5) * 24 + pv * 4 + (pq & 3);
            uint4 fh = {}, fx = {};
            if (rb == 0 && tid == 0) g_sync.epoch[0] = ep;
            if (elected) TS(60);
            TT(5);
            uint4 yv;
            if (warp == 0) { fh = ld_poll(fp); fx = ld_poll(fp + 96); }
            if (fresh && rb < NFFN) __nanosleep(YPRE);
            for (;;) {
                yv = ld_poll(g_out + min(t7, NFFN - 1) * OB + OB_Y + rb);
                if (__all_sync(0xffffffffu, (((yv.x ^ ep) & 15) | ((yv.y ^ (best >> 9)) & 127)) == 0)) break;
                if (YSLEEP) __nanosleep(YSLEEP);
            }
            if (elected) TS(61);
            TT(6);
            float y[4] = {0.f, 0.f, 0.f, 0.f};
            if (t7 < NFFN) { y[0] = __uint_as_float(yv.x); y[1] = __uint_as_float(yv.y); y[2] = __uint_as_float(yv.z); y[3] = __uint_as_float(yv.w); }
            const float z0 = ((lane & 16) ? y[2] : y[0]) + __shfl_xor_sync(0xffffffffu, (lane & 16) ? y[0] : y[2], 16);
            const float z1 = ((lane & 16) ? y[3] : y[1]) + __shfl_xor_sync(0xffffffffu, (lane & 16) ? y[1] : y[3], 16);
            float z = ((lane & 8) ? z1 : z0) + __shfl_xor_sync(0xffffffffu, (lane & 8) ? z0 : z1, 8);
            z += __shfl_xor_sync(0xffffffffu, z, 4);
            z = quad_sum(z);
            if ((lane & 7) == 0) sred[128 + (lane >> 3) * 4 + w4] = z;
            bar_sync(3, 128);
            if (tid < 2) {
                while (fh.w != ep || fx.w != ep) { fh = ld_poll(fp); fx = ld_poll(fp + 96); }
                const float4 y0 = *reinterpret_cast<const float4*>(sred + 128 + tid * 8), y1 = *reinterpret_cast<const float4*>(sred + 132 + tid * 8);
                const int cm = (pq >> 2) - 3 * pv;
                const uint32_t h2 = cm == 0 ? fh.x : cm == 1 ? fh.y : fh.z, x2 = cm == 0 ? fx.x : cm == 1 ? fx.y : fx.z;
                const float sg = sigmoid(bf_hi((best & 0x80000000u) ? (best ^ 0x80000000u) : ~best));
                reinterpret_cast<uint32_t*>(P.out)[sel * 256 + rb * 2 + tid] =
                    badd(x2, bmul(gbf, badd(h2, bmul(pack2((y0.x + y0.y) + (y0.z + y0.w), (y1.x + y1.y) + (y1.z + y1.w)), pack2(sg, sg)))));
            }
            if (elected) TS(62);
            TT(7);
        } else {
            const float4* tf = reinterpret_cast<const float4*>(smem + SM_TAB) + c4;
            const uint32_t xa = sb + 4 * SLOT + (kh ^ 1) * 16384 + (w4 * 16 + (lane & 15)) * 128;
            uint32_t x2[32];
            bar_sync(2, 256);
#pragma unroll 1
            for (int i = 14; i < 17; i++) {
                const uint32_t as = o_next(otab), ws = o_next(otab);
                slot_wait(sb + BAR_FULL, fph, as);
                slot_wait(sb + BAR_FULL, fph, ws);
                gemm_issue<false>(s, oa + as * (SLOT / 16), wd + ws * (SLOT / 16), 1, true);
                wg_wait<1>();
            }
            if (elected) TS(29);
            TT(1);
            {
#pragma unroll
                for (int k = 0; k < 8; k++)
                    asm volatile("ldmatrix.sync.aligned.m8n8.x4.shared.b16 {%0, %1, %2, %3}, [%4];"
                                 : "=r"(x2[4 * k]), "=r"(x2[4 * k + 1]), "=r"(x2[4 * k + 2]), "=r"(x2[4 * k + 3])
                                 : "r"(xa + (k >> 2) * 8192 + (((2 * (k & 3) + (lane >> 4)) ^ (lane & 7)) << 4)) : "memory");
            }
            wg_wait<0>();
            reg_fence(s);
            bar_arrive(4, 256);
            if (elected) TS(39);
            TT(2);
            const uint4* pr = g_out + (rb ^ 8) * OB + t7;
            uint4 pa[8];
#pragma unroll
            for (int v = 0; v < 8; v++) pa[v] = ld_poll(pr + v * 128);
            float4 tc[16];
#pragma unroll
            for (int k = 0; k < 16; k++) {
                tc[k] = tf[k * 4];
#pragma unroll
                for (int i = 4 * k; i < 4 * k + 4; i++) s[i] = fmaf((i & 1) ? tc[k].y : tc[k].x, s[i], (i & 1) ? bf_hi(x2[i >> 1]) : bf_lo(x2[i >> 1]));
            }
            reg_fence(s);
            for (;;) {
                uint32_t bad = 0;
#pragma unroll
                for (int v = 0; v < 8; v++) bad |= pa[v].x ^ ep;
                if (__all_sync(0xffffffffu, (bad & 1) == 0)) break;
                if (PSLEEP) __nanosleep(PSLEEP);
#pragma unroll
                for (int v = 0; v < 8; v++) pa[v] = ld_poll(pr + v * 128);
            }
            if (elected) TS(30);
            TT(3);
            float st[6] = {0.f, 0.f, 0.f, 0.f, 0.f, 0.f};
#pragma unroll
            for (int i = 0; i < 64; i++) {
                const int rh = (i >> 1) & 1;
                const uint32_t w = (&pa[i >> 3].x)[(i >> 1) & 3];
                const float v = fmaf((i & 1) ? tc[i >> 2].y : tc[i >> 2].x, (i & 1) ? bf_hi(w) : bf_lo(w), s[i]);
                s[i] = v;
                st[rh] += v;
                st[2 + rh] = fmaf(v, v, st[2 + rh]);
                st[4 + rh] = fmaf(v, (i & 1) ? tc[i >> 2].w : tc[i >> 2].z, st[4 + rh]);
            }
#pragma unroll
            for (int i = 0; i < 6; i++) st[i] = quad_sum(st[i]);
            st_pub(g_out + rb * OB + OB_STAT + (w4 * 8 + g) * 2 + (c4 & 1),
                   make_uint4(__float_as_uint((c4 & 1) ? st[1] : st[0]), __float_as_uint((c4 & 1) ? st[3] : st[2]),
                              __float_as_uint((c4 & 1) ? st[5] : st[4]), ep), c4 < 2);
            if (TF & 1) sched_fence(eb2, P.zero);
            if (elected) TS(56);
            TT(4);
            uint32_t cb[16], sh[16], gb[16];
#pragma unroll
            for (int i = 0; i < 16; i++) {
                const float4 c = tf[64 + i * 4];
                cb[i] = __float_as_uint(c.x); sh[i] = __float_as_uint(c.y); gb[i] = __float_as_uint(c.z);
            }
            const float ra = __uint_as_float(lds32(sb + SM_EP + 8)), rb0 = __uint_as_float(lds32(sb + SM_EP + 12));
#pragma unroll
            for (int i = 0; i < 32; i++) x2[i] = pack2(s[2 * i], s[2 * i + 1]);
            reg_fence(x2);
            uint4 r0, r1;
            if (SPRE) __nanosleep(SPRE);
            for (;;) {
                r0 = ld_poll(g_out + ((rb & ~3) + c4) * OB + OB_STAT + (w4 * 8 + g) * 2);
                r1 = ld_poll(g_out + ((rb & ~3) + c4) * OB + OB_STAT + (w4 * 8 + g) * 2 + 1);
                if (__all_sync(0xffffffffu, r0.w == ep && r1.w == ep)) break;
                if (SSLEEP) __nanosleep(SSLEEP);
            }
            if (elected) TS(57);
            TT(5);
            const float m0 = quad_sum(__uint_as_float(r0.x)) * (1.f / 512.f), m1 = quad_sum(__uint_as_float(r1.x)) * (1.f / 512.f);
            const float rs0 = ln_rstd(fmaxf(fmaf(-m0, m0, quad_sum(__uint_as_float(r0.y)) * (1.f / 512.f)), 0.f));
            const float rs1 = ln_rstd(fmaxf(fmaf(-m1, m1, quad_sum(__uint_as_float(r1.y)) * (1.f / 512.f)), 0.f));
            const uint32_t mb0 = pack2(m0, m0), mb1 = pack2(m1, m1);
            const uint32_t lg = pack2(fmaf(rs0, fmaf(-bf_lo(mb0), ra, quad_sum(__uint_as_float(r0.z))), rb0),
                                      fmaf(rs1, fmaf(-bf_lo(mb1), ra, quad_sum(__uint_as_float(r1.z))), rb0));
            const uint32_t u0 = lg << 16, u1 = lg & 0xffff0000u;
            const uint32_t k0 = ((u0 ^ (((int)u0 >> 31) | 0x80000000u)) & 0xffff0000u) | ((2047 - row) << 5) | (ep & 31);
            const uint32_t k1 = ((u1 ^ (((int)u1 >> 31) | 0x80000000u)) & 0xffff0000u) | ((2039 - row) << 5) | (ep & 31);
            const uint32_t kb = __reduce_max_sync(0xffffffffu, max(k0, k1));
            st_pub(g_key + cq * 128 + (row >> 4), kb, lane == 0);
            const bool cand = kb == k0 || kb == k1;
            uint4* cp = g_cand + (row >> 4) * 192 + cq * 24 + c4;
#pragma unroll 1
            for (int it = 0; it < 3; it++) {
                bool put = it == 1 || !cand;
                if (it == 2) {
                    mbar_wait(sb + BAR_BEST, 0);
                    put = cand && lds32(sb + SM_EP + 24) != kb;
                }
                const bool hi = (kb == k1) != (it == 1);
                uint32_t cx[18], ch[18];
#pragma unroll
                for (int i = 0; i < 16; i++) {
                    cx[i] = hi ? x2[2 * i + 1] : x2[2 * i];
                    ch[i] = ln_apply(cx[i], hi ? mb1 : mb0, hi ? rs1 : rs0, cb[i], sh[i]);
                }
                cx[16] = cx[17] = ch[16] = ch[17] = 0;
#pragma unroll
                for (int v = 0; v < 6; v++) st_pub(cp + v * 4, make_uint4(ch[3 * v], ch[3 * v + 1], ch[3 * v + 2], ep), cand && it == 0);
                if (TF & 4) sched_fence(eb2, P.zero);
#pragma unroll
                for (int v = 0; v < 6; v++) st_pub(cp + 96 + v * 4, make_uint4(cx[3 * v], cx[3 * v + 1], cx[3 * v + 2], ep), cand && it == 0);
                if (it == 0) TT(6);
                uint2* op = reinterpret_cast<uint2*>(P.out) + (row + 8 * hi) * 128 + cq * 32 + (c4 & 1) * 2 + (c4 >> 1);
#pragma unroll
                for (int i = 0; i < 16; i += 2) {
                    const uint32_t v0 = badd(cx[i], bmul(gb[i], ch[i])), v1 = badd(cx[i + 1], bmul(gb[i + 1], ch[i + 1]));
                    const uint32_t rv = __shfl_xor_sync(0xffffffffu, (c4 & 1) ? v0 : v1, 1);
                    if (put) op[i * 2] = (c4 & 1) ? make_uint2(rv, v1) : make_uint2(v0, rv);
                }
            }
            if (elected) TS(59);
            TT(7);
        }
        mbar_arrive_if(eb2, lane == 0);
    }
}

typedef CUresult (*EncodeFn)(CUtensorMap*, CUtensorMapDataType, cuuint32_t, void*, const cuuint64_t*, const cuuint64_t*,
                             const cuuint32_t*, const cuuint32_t*, CUtensorMapInterleave, CUtensorMapSwizzle,
                             CUtensorMapL2promotion, CUtensorMapFloatOOBfill);

void make_2d(EncodeFn fn, CUtensorMap* m, const void* p, uint64_t cols, uint64_t rows, uint32_t bc, uint32_t br) {
    cuuint64_t dims[2] = {cols, rows}, strides[1] = {cols * 2};
    cuuint32_t box[2] = {bc, br}, es[2] = {1, 1};
    fn(m, CU_TENSOR_MAP_DATA_TYPE_BFLOAT16, 2, const_cast<void*>(p), dims, strides, box, es, CU_TENSOR_MAP_INTERLEAVE_NONE,
       CU_TENSOR_MAP_SWIZZLE_NONE, CU_TENSOR_MAP_L2_PROMOTION_L2_128B, CU_TENSOR_MAP_FLOAT_OOB_FILL_NONE);
}
void make_3d(EncodeFn fn, CUtensorMap* m, const void* p, uint64_t cols, uint64_t rows, uint32_t br = 128, uint32_t nb = 2) {
    cuuint64_t dims[3] = {64, rows, cols / 64}, strides[2] = {cols * 2, 128};
    cuuint32_t box[3] = {64, br, nb}, es[3] = {1, 1, 1};
    fn(m, CU_TENSOR_MAP_DATA_TYPE_BFLOAT16, 3, const_cast<void*>(p), dims, strides, box, es, CU_TENSOR_MAP_INTERLEAVE_NONE,
       CU_TENSOR_MAP_SWIZZLE_128B, CU_TENSOR_MAP_L2_PROMOTION_L2_256B, CU_TENSOR_MAP_FLOAT_OOB_FILL_NONE);
}

}

extern "C" void kernel_launch(void* const* d_in, const int* in_sizes, int n_in, void* d_out, int out_size) {
    static EncodeFn fn = nullptr;
    if (!fn) {
        void* f = nullptr;
        cudaDriverEntryPointQueryResult st;
        cudaGetDriverEntryPoint("cuTensorMapEncodeTiled", &f, cudaEnableDefault, &st);
        fn = (EncodeFn)f;
        cudaFuncSetAttribute(fused_kernel, cudaFuncAttributeMaxDynamicSharedMemorySize, SMEM_BYTES);
    }
    CUtensorMap ckv, wq, wuk, wuv, wo, wg, wu, wm, xm;
    make_3d(fn, &ckv, d_in[1], 512, 2048, 128, 1);
    make_3d(fn, &xm, d_in[0], 512, 2048, 64);
    make_3d(fn, &wq, d_in[2], 4096, 512, 128, 1);
    make_3d(fn, &wuk, d_in[3], 4096, 512);
    make_3d(fn, &wuv, d_in[4], 4096, 512);
    make_3d(fn, &wo, d_in[5], 512, 4096);
    make_2d(fn, &wg, d_in[8], 1792, 512, 16, 256);
    make_2d(fn, &wu, d_in[9], 1792, 512, 16, 256);
    make_2d(fn, &wm, d_in[12], 3072, 512, 256, 64);
    Params p;
    p.x = (const bf16*)d_in[0];
    p.ckv = (const bf16*)d_in[1];
    p.wo = (const bf16*)d_in[5];
    p.wr = (const bf16*)d_in[7];
    p.wdown = (const bf16*)d_in[10];
    p.c = (const bf16*)d_in[11];
    p.out = (bf16*)d_out;
    p.zero = 0;
    fused_kernel<<<NCTA + NSPARE, 384, SMEM_BYTES>>>(ckv, wq, wuk, wuv, wo, wg, wu, wm, xm, p);
}
```

```cpp
#include <cuda.h>
#include <cuda_bf16.h>
#include <cuda_runtime.h>
#include <stdint.h>
#include <stdio.h>

namespace {

typedef __nv_bfloat16 bf16;
typedef unsigned long long u64;

constexpr int NCTA = 128, NSPARE = 4;
constexpr int SLOT = 32768;
constexpr int SM_BAR = 7 * SLOT;
constexpr int BAR_FULL = SM_BAR;
constexpr int BAR_EMPTY = BAR_FULL + 8 * 7;
constexpr int BAR_DONE = BAR_EMPTY + 8 * 7;
constexpr int BAR_FLAG = BAR_DONE + 8 * 9;
constexpr int BAR_PF = BAR_FLAG + 8 * 9;
constexpr int BAR_END = BAR_PF + 8;
constexpr int BAR_BEST = BAR_END + 8;
constexpr int SM_EP = BAR_END + 24;
constexpr int SM_RED = SM_BAR + 384;
constexpr int SM_TAB = SM_BAR + 1024;
constexpr int SMEM_BYTES = SM_BAR + 3072;
constexpr int NFFN = 112;
#define HINT 479
constexpr u64 L2_NORMAL = 0x1000000000000000ull, L2_FIRST = 0x12F0000000000000ull;
#define PFA 8
#define PFB 6
#define UNR 1
#define POLL_NS 50
#define MSPLIT 13
#define SF 3
#define NSH 1
#define XPF 2
#define TF 1
#define KSLEEP 150
#define YSLEEP 50
#define YPRE 150
#define SSLEEP 50
#define SPRE 0
#define PSLEEP 100
#define CSLEEP 0
#define SPEC 24
#define EARLY 7
constexpr uint32_t SPIN_LIMIT = 1u << 22;
constexpr uint32_t ONE2 = 0x3f803f80u;

struct Sync {
    uint32_t cnt[16 * 8 * 8];
    uint32_t ctxcnt[16 * 32];
    uint32_t epoch[32];
};

__device__ __align__(1024) uint8_t g_KV[16 * 16 * 2 * SLOT];
__device__ __align__(1024) uint8_t g_ctx[16 * 32 * SLOT];
__device__ __align__(1024) uint8_t g_h[16 * 4 * SLOT];
constexpr int OB = 1216, OB_STAT = 1024, OB_Y = 1088;
__device__ __align__(1024) uint4 g_out[128 * OB];
__device__ __align__(1024) bf16 g_mod[3072];
__device__ __align__(1024) uint32_t g_mod1[1024];
__device__ __align__(1024) uint4 g_cand[128 * 192];
__device__ __align__(1024) uint32_t g_key[4 * 128];
__device__ __align__(1024) uint8_t g_wf[NFFN * SLOT];
__device__ __align__(1024) Sync g_sync;
#define TS(i)

#define TT(i)
#define PT()

struct Params {
    const bf16 *x, *ckv, *wo, *wr, *wdown, *c;
    bf16* out;
    int zero;
};

__device__ __forceinline__ void mbar_init(uint32_t bar, uint32_t cnt) {
    asm volatile("mbarrier.init.shared::cta.b64 [%0], %1;" ::"r"(bar), "r"(cnt) : "memory");
}
__device__ __forceinline__ void mbar_wait(uint32_t bar, uint32_t parity) {
    asm volatile("{\n.reg .pred p;\nL_%=:\nmbarrier.try_wait.parity.shared::cta.b64 p, [%0], %1;\n@!p bra L_%=;\n}" ::"r"(bar), "r"(parity) : "memory");
}
__device__ __forceinline__ void mbar_sleep(uint32_t bar) {
    if ((threadIdx.x & 31) == 0)
        asm volatile("{\n.reg .pred p;\nL_%=:\nmbarrier.try_wait.parity.shared::cta.b64 p, [%0], 0, 100000;\n@!p bra L_%=;\n}" ::"r"(bar) : "memory");
    __syncwarp();
}
__device__ __forceinline__ void mbar_watch(uint32_t bar, uint32_t parity) {
    asm volatile("{\n.reg .pred p;\n.reg .u32 n;\nmov.u32 n, 0;\n"
                 "L_%=:\nmbarrier.try_wait.parity.shared::cta.b64 p, [%0], %1;\n@p bra D_%=;\n"
                 "add.u32 n, n, 1;\nsetp.lt.u32 p, n, %2;\n@p bra L_%=;\ntrap;\nD_%=:\n}"
                 ::"r"(bar), "r"(parity), "n"(SPIN_LIMIT) : "memory");
}
__device__ __forceinline__ void step_watch(uint32_t a, uint32_t step) {
    asm volatile("{\n.reg .pred p;\n.reg .u32 n, v;\nmov.u32 n, 0;\n"
                 "L_%=:\nld.volatile.shared.u32 v, [%0];\nsetp.ge.u32 p, v, %1;\n@p bra D_%=;\nnanosleep.u32 400;\n"
                 "add.u32 n, n, 1;\nsetp.lt.u32 p, n, %2;\n@p bra L_%=;\ntrap;\nD_%=:\n}"
                 ::"r"(a), "r"(step), "n"(SPIN_LIMIT) : "memory");
}
__device__ __forceinline__ void mbar_arrive_if(uint32_t bar, bool on) {
    asm volatile("{\n.reg .pred p;\nsetp.ne.s32 p, %1, 0;\n@p mbarrier.arrive.shared::cta.b64 _, [%0];\n}" ::"r"(bar), "r"((int)on) : "memory");
}
__device__ __forceinline__ void tma2d(uint32_t dst, const CUtensorMap* m, int c0, int c1, uint32_t bar, bool first) {
    asm volatile("{\n.reg .pred p;\nelect.sync _|p, 0xffffffff;\n"
                 "@p cp.async.bulk.tensor.2d.shared::cluster.global.mbarrier::complete_tx::bytes.L2::cache_hint [%0], [%1, {%3, %4}], [%2], %5;\n}"
                 ::"r"(dst), "l"(m), "r"(bar), "r"(c0), "r"(c1), "l"(first ? L2_FIRST : L2_NORMAL) : "memory");
}
__device__ __forceinline__ void tma3d_prefetch(const CUtensorMap* m, int row, int cb) {
    asm volatile("{\n.reg .pred p;\nelect.sync _|p, 0xffffffff;\n@p cp.async.bulk.prefetch.tensor.3d.L2.global [%0, {%1, %2, %3}];\n}"
                 ::"l"(m), "r"(0), "r"(row), "r"(cb) : "memory");
}
__device__ __forceinline__ void l2_prefetch(const void* p, uint32_t bytes) {
    asm volatile("{\n.reg .pred p;\nelect.sync _|p, 0xffffffff;\n@p cp.async.bulk.prefetch.L2.global [%0], %1;\n}" ::"l"(p), "r"(bytes) : "memory");
}
__device__ __forceinline__ void bulk_store(void* dst, uint32_t src, uint32_t bytes, bool first) {
    asm volatile("{\n.reg .pred p;\nelect.sync _|p, 0xffffffff;\n@p cp.async.bulk.global.shared::cta.bulk_group.L2::cache_hint [%0], [%1], %2, %3;\n}"
                 ::"l"(dst), "r"(src), "r"(bytes), "l"(first ? L2_FIRST : L2_NORMAL) : "memory");
}
__device__ __forceinline__ void flag_wait(const uint32_t* f, uint32_t target) {
    asm volatile("{\n.reg .pred p;\n.reg .u32 v;\n"
                 "L_%=:\nld.acquire.gpu.global.u32 v, [%0];\nsub.u32 v, v, %1;\nsetp.lt.s32 p, v, 0;\n@p nanosleep.u32 100;\n@p bra L_%=;\n}"
                 ::"l"(f), "r"(target) : "memory");
}
__device__ __forceinline__ uint4 ld_poll(const uint4* p) {
    uint4 v;
    asm volatile("{\n.reg .b128 t;\nld.relaxed.gpu.global.b128 t, [%4];\nmov.b128 {%0, %1, %2, %3}, t;\n}"
                 : "=r"(v.x), "=r"(v.y), "=r"(v.z), "=r"(v.w) : "l"(p) : "memory");
    return v;
}
__device__ __forceinline__ void st_pub(uint4* p, uint4 v, bool on) {
    asm volatile("{\n.reg .pred p;\n.reg .b128 t;\nsetp.ne.s32 p, %5, 0;\nmov.b128 t, {%1, %2, %3, %4};\n@p st.relaxed.gpu.global.b128 [%0], t;\n}"
                 ::"l"(p), "r"(v.x), "r"(v.y), "r"(v.z), "r"(v.w), "r"((int)on) : "memory");
}
__device__ __forceinline__ void st_pub(uint32_t* p, uint32_t v, bool on) {
    asm volatile("{\n.reg .pred p;\nsetp.ne.s32 p, %2, 0;\n@p st.relaxed.gpu.global.u32 [%0], %1;\n}" ::"l"(p), "r"(v), "r"((int)on) : "memory");
}
__device__ __forceinline__ void flag_add(uint32_t* p) {
    asm volatile("red.release.gpu.global.add.u32 [%0], 1;" ::"l"(p) : "memory");
}
__device__ __forceinline__ uint32_t lds32(uint32_t a) {
    uint32_t v;
    asm volatile("ld.shared.u32 %0, [%1];" : "=r"(v) : "r"(a) : "memory");
    return v;
}
__device__ __forceinline__ uint4 lds128(uint32_t a) {
    uint4 v;
    asm volatile("ld.shared.v4.u32 {%0, %1, %2, %3}, [%4];" : "=r"(v.x), "=r"(v.y), "=r"(v.z), "=r"(v.w) : "r"(a) : "memory");
    return v;
}
__device__ __forceinline__ void sched_fence(uint32_t& v, uint32_t z) {
    uint32_t ck;
    asm volatile("mov.u32 %0, %%clock;" : "=r"(ck)::"memory");
    v ^= ck & z;
}
__device__ __forceinline__ void fence_async_global() { asm volatile("fence.proxy.async.global;" ::: "memory"); }
__device__ __forceinline__ void fence_async_smem() { asm volatile("fence.proxy.async.shared::cta;" ::: "memory"); }
__device__ __forceinline__ void bar_sync(int id, int n) { asm volatile("bar.sync %0, %1;" ::"r"(id), "r"(n) : "memory"); }
__device__ __forceinline__ void bar_arrive(int id, int n) { asm volatile("bar.arrive %0, %1;" ::"r"(id), "r"(n) : "memory"); }
__device__ __forceinline__ void wg_fence() { asm volatile("wgmma.fence.sync.aligned;" ::: "memory"); }
__device__ __forceinline__ void wg_commit() { asm volatile("wgmma.commit_group.sync.aligned;" ::: "memory"); }
template <int N> __device__ __forceinline__ void wg_wait() { asm volatile("wgmma.wait_group.sync.aligned %0;" ::"n"(N) : "memory"); }
template <int N> __device__ __forceinline__ void reg_fence(float (&d)[N]) {
#pragma unroll
    for (int i = 0; i < N; i++) asm volatile("" : "+f"(d[i])::"memory");
}
template <int N> __device__ __forceinline__ void reg_fence(uint32_t (&d)[N]) {
#pragma unroll
    for (int i = 0; i < N; i++) asm volatile("" : "+r"(d[i])::"memory");
}
__device__ __forceinline__ uint32_t desc_k(uint32_t a) { return ((a & 0x3ffff) >> 4) | (1u << 16); }
__device__ __forceinline__ uint32_t desc_mn(uint32_t a) { return ((a & 0x3ffff) >> 4) | (1024u << 16); }

template <int TB>
__device__ __forceinline__ void wgmma_ss128(float (&d)[64], uint32_t da, uint32_t db, int acc, uint32_t ha = 0x40000040u, uint32_t hb = 0x40000040u) {
    asm volatile("{\n.reg .pred p;\n.reg .b64 a, b;\nsetp.ne.b32 p, %66, 0;\nmov.b64 a, {%64, %68};\nmov.b64 b, {%65, %69};\n"
        "wgmma.mma_async.sync.aligned.m64n128k16.f32.bf16.bf16 {%0, %1, %2, %3, %4, %5, %6, %7, %8, %9, %10, %11, %12, %13, %14, %15, %16, %17, %18, %19, %20, %21, %22, %23, %24, %25, %26, %27, %28, %29, %30, %31, %32, %33, %34, %35, %36, %37, %38, %39, %40, %41, %42, %43, %44, %45, %46, %47, %48, %49, %50, %51, %52, %53, %54, %55, %56, %57, %58, %59, %60, %61, %62, %63}, a, b, p, 1, 1, 0, %67;\n}"
        : "+f"(d[0]), "+f"(d[1]), "+f"(d[2]), "+f"(d[3]), "+f"(d[4]), "+f"(d[5]), "+f"(d[6]), "+f"(d[7]), "+f"(d[8]), "+f"(d[9]), "+f"(d[10]), "+f"(d[11]), "+f"(d[12]), "+f"(d[13]), "+f"(d[14]), "+f"(d[15]), "+f"(d[16]), "+f"(d[17]), "+f"(d[18]), "+f"(d[19]), "+f"(d[20]), "+f"(d[21]), "+f"(d[22]), "+f"(d[23]), "+f"(d[24]), "+f"(d[25]), "+f"(d[26]), "+f"(d[27]), "+f"(d[28]), "+f"(d[29]), "+f"(d[30]), "+f"(d[31]), "+f"(d[32]), "+f"(d[33]), "+f"(d[34]), "+f"(d[35]), "+f"(d[36]), "+f"(d[37]), "+f"(d[38]), "+f"(d[39]), "+f"(d[40]), "+f"(d[41]), "+f"(d[42]), "+f"(d[43]), "+f"(d[44]), "+f"(d[45]), "+f"(d[46]), "+f"(d[47]), "+f"(d[48]), "+f"(d[49]), "+f"(d[50]), "+f"(d[51]), "+f"(d[52]), "+f"(d[53]), "+f"(d[54]), "+f"(d[55]), "+f"(d[56]), "+f"(d[57]), "+f"(d[58]), "+f"(d[59]), "+f"(d[60]), "+f"(d[61]), "+f"(d[62]), "+f"(d[63])
        : "r"(da), "r"(db), "r"(acc), "n"(TB), "r"(ha), "r"(hb));
}
template <int TB>
__device__ __forceinline__ void wgmma_ss128_init(float (&d)[64], uint32_t da, uint32_t db, uint32_t ha = 0x40000040u, uint32_t hb = 0x40000040u) {
    asm volatile("{\n.reg .pred p;\n.reg .b64 a, b;\nsetp.ne.b32 p, 0, 0;\nmov.b64 a, {%64, %67};\nmov.b64 b, {%65, %68};\n"
        "wgmma.mma_async.sync.aligned.m64n128k16.f32.bf16.bf16 {%0, %1, %2, %3, %4, %5, %6, %7, %8, %9, %10, %11, %12, %13, %14, %15, %16, %17, %18, %19, %20, %21, %22, %23, %24, %25, %26, %27, %28, %29, %30, %31, %32, %33, %34, %35, %36, %37, %38, %39, %40, %41, %42, %43, %44, %45, %46, %47, %48, %49, %50, %51, %52, %53, %54, %55, %56, %57, %58, %59, %60, %61, %62, %63}, a, b, p, 1, 1, 0, %66;\n}"
        : "=f"(d[0]), "=f"(d[1]), "=f"(d[2]), "=f"(d[3]), "=f"(d[4]), "=f"(d[5]), "=f"(d[6]), "=f"(d[7]), "=f"(d[8]), "=f"(d[9]), "=f"(d[10]), "=f"(d[11]), "=f"(d[12]), "=f"(d[13]), "=f"(d[14]), "=f"(d[15]), "=f"(d[16]), "=f"(d[17]), "=f"(d[18]), "=f"(d[19]), "=f"(d[20]), "=f"(d[21]), "=f"(d[22]), "=f"(d[23]), "=f"(d[24]), "=f"(d[25]), "=f"(d[26]), "=f"(d[27]), "=f"(d[28]), "=f"(d[29]), "=f"(d[30]), "=f"(d[31]), "=f"(d[32]), "=f"(d[33]), "=f"(d[34]), "=f"(d[35]), "=f"(d[36]), "=f"(d[37]), "=f"(d[38]), "=f"(d[39]), "=f"(d[40]), "=f"(d[41]), "=f"(d[42]), "=f"(d[43]), "=f"(d[44]), "=f"(d[45]), "=f"(d[46]), "=f"(d[47]), "=f"(d[48]), "=f"(d[49]), "=f"(d[50]), "=f"(d[51]), "=f"(d[52]), "=f"(d[53]), "=f"(d[54]), "=f"(d[55]), "=f"(d[56]), "=f"(d[57]), "=f"(d[58]), "=f"(d[59]), "=f"(d[60]), "=f"(d[61]), "=f"(d[62]), "=f"(d[63])
        : "r"(da), "r"(db), "n"(TB), "r"(ha), "r"(hb));
}
template <int TB>
__device__ __forceinline__ void wgmma_ss64(float (&d)[32], uint32_t da, uint32_t db, int acc, uint32_t ha = 0x40000040u, uint32_t hb = 0x40000040u) {
    asm volatile("{\n.reg .pred p;\n.reg .b64 a, b;\nsetp.ne.b32 p, %34, 0;\nmov.b64 a, {%32, %36};\nmov.b64 b, {%33, %37};\n"
        "wgmma.mma_async.sync.aligned.m64n64k16.f32.bf16.bf16 {%0, %1, %2, %3, %4, %5, %6, %7, %8, %9, %10, %11, %12, %13, %14, %15, %16, %17, %18, %19, %20, %21, %22, %23, %24, %25, %26, %27, %28, %29, %30, %31}, a, b, p, 1, 1, 0, %35;\n}"
        : "+f"(d[0]), "+f"(d[1]), "+f"(d[2]), "+f"(d[3]), "+f"(d[4]), "+f"(d[5]), "+f"(d[6]), "+f"(d[7]), "+f"(d[8]), "+f"(d[9]), "+f"(d[10]), "+f"(d[11]), "+f"(d[12]), "+f"(d[13]), "+f"(d[14]), "+f"(d[15]), "+f"(d[16]), "+f"(d[17]), "+f"(d[18]), "+f"(d[19]), "+f"(d[20]), "+f"(d[21]), "+f"(d[22]), "+f"(d[23]), "+f"(d[24]), "+f"(d[25]), "+f"(d[26]), "+f"(d[27]), "+f"(d[28]), "+f"(d[29]), "+f"(d[30]), "+f"(d[31])
        : "r"(da), "r"(db), "r"(acc), "n"(TB), "r"(ha), "r"(hb));
}
template <int TB>
__device__ __forceinline__ void wgmma_ss64_init(float (&d)[32], uint32_t da, uint32_t db, uint32_t ha = 0x40000040u, uint32_t hb = 0x40000040u) {
    asm volatile("{\n.reg .pred p;\n.reg .b64 a, b;\nsetp.ne.b32 p, 0, 0;\nmov.b64 a, {%32, %35};\nmov.b64 b, {%33, %36};\n"
        "wgmma.mma_async.sync.aligned.m64n64k16.f32.bf16.bf16 {%0, %1, %2, %3, %4, %5, %6, %7, %8, %9, %10, %11, %12, %13, %14, %15, %16, %17, %18, %19, %20, %21, %22, %23, %24, %25, %26, %27, %28, %29, %30, %31}, a, b, p, 1, 1, 0, %34;\n}"
        : "=f"(d[0]), "=f"(d[1]), "=f"(d[2]), "=f"(d[3]), "=f"(d[4]), "=f"(d[5]), "=f"(d[6]), "=f"(d[7]), "=f"(d[8]), "=f"(d[9]), "=f"(d[10]), "=f"(d[11]), "=f"(d[12]), "=f"(d[13]), "=f"(d[14]), "=f"(d[15]), "=f"(d[16]), "=f"(d[17]), "=f"(d[18]), "=f"(d[19]), "=f"(d[20]), "=f"(d[21]), "=f"(d[22]), "=f"(d[23]), "=f"(d[24]), "=f"(d[25]), "=f"(d[26]), "=f"(d[27]), "=f"(d[28]), "=f"(d[29]), "=f"(d[30]), "=f"(d[31])
        : "r"(da), "r"(db), "n"(TB), "r"(ha), "r"(hb));
}
__device__ __forceinline__ void wgmma_rs128(float (&d)[64], uint32_t a0, uint32_t a1, uint32_t a2, uint32_t a3, uint32_t db, int acc, uint32_t hb = 0x40000040u) {
    asm volatile("{\n.reg .pred p;\n.reg .b64 b;\nsetp.ne.b32 p, %69, 0;\nmov.b64 b, {%68, %70};\n"
        "wgmma.mma_async.sync.aligned.m64n128k16.f32.bf16.bf16 {%0, %1, %2, %3, %4, %5, %6, %7, %8, %9, %10, %11, %12, %13, %14, %15, %16, %17, %18, %19, %20, %21, %22, %23, %24, %25, %26, %27, %28, %29, %30, %31, %32, %33, %34, %35, %36, %37, %38, %39, %40, %41, %42, %43, %44, %45, %46, %47, %48, %49, %50, %51, %52, %53, %54, %55, %56, %57, %58, %59, %60, %61, %62, %63}, {%64, %65, %66, %67}, b, p, 1, 1, 1;\n}"
        : "+f"(d[0]), "+f"(d[1]), "+f"(d[2]), "+f"(d[3]), "+f"(d[4]), "+f"(d[5]), "+f"(d[6]), "+f"(d[7]), "+f"(d[8]), "+f"(d[9]), "+f"(d[10]), "+f"(d[11]), "+f"(d[12]), "+f"(d[13]), "+f"(d[14]), "+f"(d[15]), "+f"(d[16]), "+f"(d[17]), "+f"(d[18]), "+f"(d[19]), "+f"(d[20]), "+f"(d[21]), "+f"(d[22]), "+f"(d[23]), "+f"(d[24]), "+f"(d[25]), "+f"(d[26]), "+f"(d[27]), "+f"(d[28]), "+f"(d[29]), "+f"(d[30]), "+f"(d[31]), "+f"(d[32]), "+f"(d[33]), "+f"(d[34]), "+f"(d[35]), "+f"(d[36]), "+f"(d[37]), "+f"(d[38]), "+f"(d[39]), "+f"(d[40]), "+f"(d[41]), "+f"(d[42]), "+f"(d[43]), "+f"(d[44]), "+f"(d[45]), "+f"(d[46]), "+f"(d[47]), "+f"(d[48]), "+f"(d[49]), "+f"(d[50]), "+f"(d[51]), "+f"(d[52]), "+f"(d[53]), "+f"(d[54]), "+f"(d[55]), "+f"(d[56]), "+f"(d[57]), "+f"(d[58]), "+f"(d[59]), "+f"(d[60]), "+f"(d[61]), "+f"(d[62]), "+f"(d[63])
        : "r"(a0), "r"(a1), "r"(a2), "r"(a3), "r"(db), "r"(acc), "r"(hb));
}

__device__ __forceinline__ uint32_t pack2(float lo, float hi) {
    uint32_t r;
    asm("cvt.rn.bf16x2.f32 %0, %1, %2;" : "=r"(r) : "f"(hi), "f"(lo));
    return r;
}
__device__ __forceinline__ float bf_lo(uint32_t v) { return __uint_as_float(v << 16); }
__device__ __forceinline__ float bf_hi(uint32_t v) { return __uint_as_float(v & 0xffff0000u); }
__device__ __forceinline__ float rbf(float v) { return bf_lo(pack2(v, v)); }
__device__ __forceinline__ uint32_t badd(uint32_t a, uint32_t b) {
    uint32_t r;
    asm("add.rn.bf16x2 %0, %1, %2;" : "=r"(r) : "r"(a), "r"(b));
    return r;
}
__device__ __forceinline__ uint32_t bsub(uint32_t a, uint32_t b) {
    uint32_t r;
    asm("sub.rn.bf16x2 %0, %1, %2;" : "=r"(r) : "r"(a), "r"(b));
    return r;
}
__device__ __forceinline__ uint32_t bmul(uint32_t a, uint32_t b) {
    uint32_t r;
    asm("mul.rn.bf16x2 %0, %1, %2;" : "=r"(r) : "r"(a), "r"(b));
    return r;
}
__device__ __forceinline__ uint32_t ln_apply(uint32_t x, uint32_t mb, float rs, uint32_t scale, uint32_t shift) {
    const uint32_t d = bsub(x, mb);
    return badd(bmul(pack2(bf_lo(d) * rs, bf_hi(d) * rs), scale), shift);
}
__device__ __forceinline__ float ex2(float v) {
    float r;
    asm("ex2.approx.ftz.f32 %0, %1;" : "=f"(r) : "f"(v));
    return r;
}
__device__ __forceinline__ float rcp(float v) {
    float r;
    asm("rcp.approx.ftz.f32 %0, %1;" : "=f"(r) : "f"(v));
    return r;
}
__device__ __forceinline__ float sqrt_fast(float v) {
    float r;
    asm("sqrt.approx.ftz.f32 %0, %1;" : "=f"(r) : "f"(v));
    return r;
}
__device__ __forceinline__ float ln_rstd(float var) { return rcp(rbf(sqrt_fast(rbf(rbf(var) + 1e-5f)))); }
__device__ __forceinline__ float sigmoid(float v) { return rcp(1.f + ex2(-1.4426950408889634f * v)); }
__device__ __forceinline__ float quad_sum(float v) {
    v += __shfl_xor_sync(0xffffffffu, v, 1);
    return v + __shfl_xor_sync(0xffffffffu, v, 2);
}

constexpr uint32_t HI_128 = 0x40000040u, HI_IMG = 0x80000080u, HI_Q = 0x80000040u;
template <int M, int RH>
__device__ __forceinline__ uint4 img_pack(const float (&d)[64], float s) {
    uint4 v;
    v.x = pack2(d[16 * M + 2 * RH] * s, d[16 * M + 2 * RH + 1] * s);
    v.y = pack2(d[16 * M + 4 + 2 * RH] * s, d[16 * M + 5 + 2 * RH] * s);
    v.z = pack2(d[16 * M + 8 + 2 * RH] * s, d[16 * M + 9 + 2 * RH] * s);
    v.w = pack2(d[16 * M + 12 + 2 * RH] * s, d[16 * M + 13 + 2 * RH] * s);
    return v;
}
template <int M>
__device__ __forceinline__ void img_store_global(uint8_t* img, uint32_t toff, const float (&d)[64], float s0, float s1) {
    uint4* p = reinterpret_cast<uint4*>(img + toff) + M * 32;
    p[0] = img_pack<M, 0>(d, s0);
    p[128] = img_pack<M, 1>(d, s1);
}
__device__ __forceinline__ void sts128(uint32_t a, uint4 v) {
    asm volatile("st.shared.v4.b32 [%0], {%1, %2, %3, %4};" ::"r"(a), "r"(v.x), "r"(v.y), "r"(v.z), "r"(v.w) : "memory");
}
constexpr float SM_C = 0.08838834764831845f * 1.4426950408889634f;
__device__ __forceinline__ float pack2f(float lo, float hi) {
    float r;
    asm("{\n.reg .b32 t;\ncvt.rn.bf16x2.f32 t, %1, %2;\nmov.b32 %0, t;\n}" : "=f"(r) : "f"(hi), "f"(lo));
    return r;
}
template <int M, bool SCALE, bool PARK>
__device__ __forceinline__ void pack_group(float (&d)[64], float (&v)[8], float s0, float s1) {
#pragma unroll
    for (int i = 0; i < 8; i++) {
        const int k = 16 * M + 4 * (i & 3) + 2 * (i >> 2);
        v[i] = SCALE ? pack2f(d[k] * (i < 4 ? s0 : s1), d[k + 1] * (i < 4 ? s0 : s1)) : pack2f(d[k], d[k + 1]);
        if (PARK && M > 0) d[16 * (M > 0 ? M - 1 : 0) + i] = v[i];
    }
}
__device__ __forceinline__ uint32_t q_off(uint32_t toff) { return (((toff >> 1) & ~2047u) ^ 8192) + (toff & 511); }
template <int M, bool PARK>
__device__ __forceinline__ void ctx_store_part(float4* p, float (&d)[64], float i0, float i1) {
    float v[8];
    pack_group<M, true, PARK>(d, v, i0, i1);
    p[M * 32] = make_float4(v[0], v[1], v[2], v[3]);
    p[M * 32 + 128] = make_float4(v[4], v[5], v[6], v[7]);
}
template <bool PARK>
__device__ __forceinline__ void ctx_store(uint8_t* img, uint32_t toff, float (&o)[64], float l0, float l1) {
    const float i0 = rcp(quad_sum(l0)), i1 = rcp(quad_sum(l1));
    float4* p = reinterpret_cast<float4*>(img + toff);
    ctx_store_part<0, PARK>(p, o, i0, i1); ctx_store_part<1, PARK>(p, o, i0, i1); ctx_store_part<2, PARK>(p, o, i0, i1); ctx_store_part<3, PARK>(p, o, i0, i1);
}

template <int M>
__device__ __forceinline__ void tile_store_part(float4* p, uint32_t a, float (&d)[64], float i0, float i1, int ctx) {
    float v[8];
    pack_group<M, true, true>(d, v, i0, i1);
#pragma unroll
    for (int h = 0; h < 2; h++)
        asm volatile("{\n.reg .pred p;\nsetp.ne.s32 p, %6, 0;\n@p st.global.v4.f32 [%0], {%2, %3, %4, %5};\n@!p st.shared.v4.f32 [%1], {%2, %3, %4, %5};\n}"
                     ::"l"(p + M * 32 + h * 128), "r"(a + (M >> 1) * 16384 + (M & 1) * 512 + h * 1024),
                     "f"(v[4 * h]), "f"(v[4 * h + 1]), "f"(v[4 * h + 2]), "f"(v[4 * h + 3]), "r"(ctx) : "memory");
}
__device__ __forceinline__ void tile_store(uint8_t* img, uint32_t a, uint32_t toff, float (&d)[64], float i0, float i1, int ctx) {
    float4* p = reinterpret_cast<float4*>(img + toff);
    a += q_off(toff);
    tile_store_part<0>(p, a, d, i0, i1, ctx); tile_store_part<1>(p, a, d, i0, i1, ctx);
    tile_store_part<2>(p, a, d, i0, i1, ctx); tile_store_part<3>(p, a, d, i0, i1, ctx);
}

__device__ __forceinline__ void slot_wait(uint32_t bars, uint32_t& ph, uint32_t slot) {
    mbar_wait(bars + 8 * slot, (ph >> slot) & 1);
    ph ^= 1u << slot;
}
__device__ __forceinline__ void release_if(uint32_t eb, uint32_t slot, bool on) {
    asm volatile("{\n.reg .pred p;\nsetp.ne.s32 p, %1, 0;\n@p mbarrier.arrive.shared::cluster.b64 _, [%0];\n}" ::"r"(eb + 8 * slot), "r"((int)on) : "memory");
}
__device__ __forceinline__ void slot_acquire(uint32_t sb, uint32_t& ph, uint32_t slot) {
    slot_wait(sb + BAR_EMPTY, ph, slot);
    asm volatile("{\n.reg .pred p;\nelect.sync _|p, 0xffffffff;\n@p mbarrier.arrive.expect_tx.shared::cta.b64 _, [%0], 32768;\n}"
                 ::"r"(sb + BAR_FULL + 8 * slot) : "memory");
}
__device__ __forceinline__ void load_bulk(uint32_t sb, uint32_t slot, uint32_t off, const void* src, uint32_t bytes, bool both, bool first) {
    if (both)
        asm volatile("{\n.reg .pred p;\nelect.sync _|p, 0xffffffff;\n"
                     "@p cp.async.bulk.shared::cluster.global.mbarrier::complete_tx::bytes.multicast::cluster.L2::cache_hint [%0], [%1], %5, [%2], %4, %3;\n}"
                     ::"r"(sb + slot * SLOT + off), "l"(src), "r"(sb + BAR_FULL + 8 * slot), "l"(first ? L2_FIRST : L2_NORMAL), "h"((uint16_t)3),
                     "r"(bytes) : "memory");
    else
        asm volatile("{\n.reg .pred p;\nelect.sync _|p, 0xffffffff;\n"
                     "@p cp.async.bulk.shared::cluster.global.mbarrier::complete_tx::bytes.L2::cache_hint [%0], [%1], %4, [%2], %3;\n}"
                     ::"r"(sb + slot * SLOT + off), "l"(src), "r"(sb + BAR_FULL + 8 * slot), "l"(first ? L2_FIRST : L2_NORMAL), "r"(bytes) : "memory");
}
__device__ __forceinline__ void load_tile(uint32_t sb, uint32_t slot, uint32_t off, const CUtensorMap* m, int row, int cb, bool both, bool first) {
    if (both)
        asm volatile("{\n.reg .pred p;\nelect.sync _|p, 0xffffffff;\n"
                     "@p cp.async.bulk.tensor.3d.shared::cluster.global.mbarrier::complete_tx::bytes.multicast::cluster.L2::cache_hint [%0], [%1, {%3, %4, %5}], [%2], %7, %6;\n}"
                     ::"r"(sb + slot * SLOT + off), "l"(m), "r"(sb + BAR_FULL + 8 * slot), "r"(0), "r"(row), "r"(cb),
                     "l"(first ? L2_FIRST : L2_NORMAL), "h"((uint16_t)3) : "memory");
    else
        asm volatile("{\n.reg .pred p;\nelect.sync _|p, 0xffffffff;\n"
                     "@p cp.async.bulk.tensor.3d.shared::cluster.global.mbarrier::complete_tx::bytes.L2::cache_hint [%0], [%1, {%3, %4, %5}], [%2], %6;\n}"
                     ::"r"(sb + slot * SLOT + off), "l"(m), "r"(sb + BAR_FULL + 8 * slot), "r"(0), "r"(row), "r"(cb),
                     "l"(first ? L2_FIRST : L2_NORMAL) : "memory");
}
__device__ __forceinline__ uint32_t ring_next(uint32_t r) { return r == 4 ? 0 : r + 1; }
__device__ __forceinline__ uint32_t w_table(int hp) { return hp ? 0x3104u : 0x4210u; }
__device__ __forceinline__ uint32_t a_table(int hp) { return hp ? 0x625u : 0x635u; }
__device__ __forceinline__ uint32_t a_next(uint32_t& t) {
    const uint32_t s = t & 15;
    t = (t >> 4) | (s << 8);
    return s;
}
constexpr uint32_t O_TABLE = 0x1604235u;
__device__ __forceinline__ uint32_t o_next(uint32_t& t) {
    const uint32_t s = t & 15;
    t = (t >> 4) | (s << 24);
    return s;
}
__device__ __forceinline__ int o_head(int i, int kh) { return i < 16 ? 4 * (i & 7) + 2 * (kh ^ 1) + (i >> 3) : 29 + 2 * kh; }

template <bool INIT>
__device__ __forceinline__ void gemm_issue(float (&d)[64], uint32_t a, uint32_t b, int acc, bool img) {
    const uint32_t ha = img ? HI_IMG : HI_128, o2 = img ? 32 : 4, o4 = img ? 64 : 1024;
    wg_fence();
#pragma unroll
    for (int k = 0; k < 8; k++) {
        if (INIT && k == 0) wgmma_ss128_init<1>(d, a, b, ha);
        else wgmma_ss128<1>(d, a + (k >> 2) * o4 + ((k >> 1) & 1) * o2 + (k & 1) * 2, b + k * 128, k ? 1 : acc, ha);
    }
    wg_commit();
}

template <bool ODD>
__device__ __forceinline__ bool proj_tile(float (&acc)[64], float (&prev)[64], int t, int q0, uint32_t sb, int wg, uint32_t eb, bool rel, uint32_t& fph,
                                          uint32_t wtab, uint32_t& atab, uint8_t* prev_img, uint32_t toff, float s0, float s1,
                                          uint32_t (&v)[32]) {
    const uint32_t a0 = desc_k(sb + (wg ^ (ODD && t == 5)) * 8192), b0 = desc_mn(sb);
    constexpr int U = ODD ? UNR : 1;
#pragma unroll U
    for (int q = ODD ? 0 : q0; q < 4; q++) {
        const uint32_t ws = (wtab >> (4 * q)) & 15, as = a_next(atab);
        if (!ODD && t != 2) slot_wait(sb + BAR_FULL, fph, ws);
        slot_wait(sb + BAR_FULL, fph, as);
        if (ODD && q == 2 && t == 5) {
#pragma unroll
            for (int i = 0; i < 8; i++) sts128(sb + 5 * SLOT + q_off(toff) + (i >> 2) * 16384 + (i & 2) * 256 + (i & 1) * 1024, make_uint4(v[4 * i], v[4 * i + 1], v[4 * i + 2], v[4 * i + 3]));
        }
        bar_sync(1 + wg, 256);
        gemm_issue<false>(acc, a0 + as * (SLOT / 16), b0 + ws * (SLOT / 16), q, false);
        bar_arrive(2 - wg, 256);
        wg_wait<1>();
        reg_fence(prev);
        if (ODD && t == 5) {
            if (q == 0) {
#pragma unroll
                for (int i = 0; i < 32; i++) {
                    const int k = 16 * (i >> 3) + 4 * (i & 3) + ((i >> 1) & 2);
                    v[i] = pack2(prev[k], prev[k + 1]);
                }
            }
            if (q == 2) {
                fence_async_smem();
                slot_wait(sb + BAR_FULL, fph, wtab & 15);
                wg_wait<0>();
                release_if(eb, as, rel);
                release_if(eb, ws, rel);
                reg_fence(acc);
                return true;
            }
        } else {
            if (q == 0) img_store_global<0>(prev_img, toff, prev, s0, s1);
            if (q == 1) img_store_global<1>(prev_img, toff, prev, s0, s1);
            if (q == 2) img_store_global<2>(prev_img, toff, prev, s0, s1);
            if (q == 3) img_store_global<3>(prev_img, toff, prev, s0, s1);
        }
        wg_wait<0>();
        release_if(eb, as, rel && !(ODD && (q & 1) && t == 5));
        if (ODD) release_if(eb, ws, rel && t != 1);
    }
    reg_fence(acc);
    return false;
}

__device__ __forceinline__ void qk_issue(float (&s)[64], uint32_t q, uint32_t k) {
    wg_fence();
    wgmma_ss128_init<0>(s, q, k, HI_Q, HI_IMG);
#pragma unroll
    for (int i = 1; i < 8; i++) wgmma_ss128<0>(s, q + (i >> 2) * 1024 + (i & 2) * 16 + (i & 1) * 2, k + (i >> 1) * 32 + (i & 1) * 2, 1, HI_Q, HI_IMG);
    wg_commit();
}
__device__ __forceinline__ void qk_issue(float (&s)[32], uint32_t q, uint32_t k) {
    wg_fence();
    wgmma_ss64_init<0>(s, q, k, HI_Q, HI_IMG);
#pragma unroll
    for (int i = 1; i < 8; i++) wgmma_ss64<0>(s, q + (i >> 2) * 1024 + (i & 2) * 16 + (i & 1) * 2, k + (i >> 1) * 32 + (i & 1) * 2, 1, HI_Q, HI_IMG);
    wg_commit();
}
__device__ __forceinline__ void pv_issue(float (&o)[64], const uint32_t (&p)[32], uint32_t v, int acc, bool half) {
    if (half) {
        asm volatile("// half" ::: "memory");
        wg_fence();
#pragma unroll
        for (int i = 0; i < 4; i++) wgmma_rs128(o, p[4 * i], p[4 * i + 1], p[4 * i + 2], p[4 * i + 3], v + i * 256, i ? 1 : acc, HI_IMG);
        wg_commit();
        asm volatile("// half" ::: "memory");
    } else {
        wg_fence();
#pragma unroll
        for (int i = 0; i < 8; i++) wgmma_rs128(o, p[4 * i], p[4 * i + 1], p[4 * i + 2], p[4 * i + 3], v + i * 256, i ? 1 : acc, HI_IMG);
        wg_commit();
    }
}
__device__ __forceinline__ void tri_mask(float (&s)[64], float x) {
#pragma unroll
    for (int k = 0; k < 16; k++) {
        float b;
        asm("sub.sat.f32 %0, %1, %2;" : "=f"(b) : "f"((float)(8 * (k >> 1) + (k & 1))), "f"(x));
        const int i = 32 + 4 * (k >> 1) + (k & 1);
        asm("fma.rn.f32 %0, %1, 0fFF61B1E6, %0;" : "+f"(s[i]) : "f"(b));
        if (k < 14) asm("fma.rn.f32 %0, %1, 0fFF61B1E6, %0;" : "+f"(s[i + 6]) : "f"(b));
    }
}
__device__ __forceinline__ void tri_mask_copy(float (&s)[64], const float (&h)[32], float x) {
#pragma unroll
    for (int i = 0; i < 32; i++) {
        asm("{\n.reg .pred p;\nsetp.lt.f32 p, %2, %3;\nselp.f32 %0, 0fFF800000, %1, p;\n}"
            : "=f"(s[i]) : "f"(h[i]), "f"(x), "f"((float)(8 * (i >> 2) - 4 * (i & 2) + (i & 1))));
        s[32 + i] = __uint_as_float(0xff800000u);
    }
}
constexpr float SM_HI = 1152921504606846976.f, SM_LO = 1.f / 1152921504606846976.f;
__device__ __forceinline__ bool softmax_unsafe(float t0, float t1, bool first) {
    bool bad = __any_sync(0xffffffffu, fmaxf(t0, t1) > SM_HI);
    if (first) {
        uint32_t a = __ballot_sync(0xffffffffu, t0 >= SM_LO), b = __ballot_sync(0xffffffffu, t1 >= SM_LO);
        a |= a >> 1;
        b |= b >> 1;
        bad |= ((a | (a >> 2)) & (b | (b >> 2)) & 0x11111111u) != 0x11111111u;
    }
    return bad;
}
__device__ __forceinline__ void softmax_shift(float (&s)[64], float d0, float d1) {
#pragma unroll
    for (int i = 0; i < 64; i++) s[i] -= (i & 2) ? d1 : d0;
}
__device__ __forceinline__ void softmax_remax(float (&s)[64], float (&m)[2], bool first, float& a0, float& a1) {
    float m0 = fmaxf(s[0], s[1]), m1 = fmaxf(s[2], s[3]);
#pragma unroll
    for (int k = 1; k < 16; k++) {
        m0 = fmaxf(m0, fmaxf(s[4 * k], s[4 * k + 1]));
        m1 = fmaxf(m1, fmaxf(s[4 * k + 2], s[4 * k + 3]));
    }
    m0 = fmaxf(m0, __shfl_xor_sync(0xffffffffu, m0, 1));
    m1 = fmaxf(m1, __shfl_xor_sync(0xffffffffu, m1, 1));
    m0 = fmaxf(m0, __shfl_xor_sync(0xffffffffu, m0, 2));
    m1 = fmaxf(m1, __shfl_xor_sync(0xffffffffu, m1, 2));
    if (!first) {
        m0 = fmaxf(m0, 0.f);
        m1 = fmaxf(m1, 0.f);
    }
    a0 = first ? 1.f : ex2(-m0);
    a1 = first ? 1.f : ex2(-m1);
    m[0] += m0;
    m[1] += m1;
    softmax_shift(s, m0, m1);
}
template <int J0, int J1>
__device__ __forceinline__ void softmax_exp(const float (&s)[64], uint32_t (&p)[32], float (&t)[4]) {
#pragma unroll
    for (int k = J0; k < J1; k++) {
        const float e0 = ex2(s[4 * k]), e1 = ex2(s[4 * k + 1]), e2 = ex2(s[4 * k + 2]), e3 = ex2(s[4 * k + 3]);
        if (k == 0) { t[0] = e0; t[1] = e1; t[2] = e2; t[3] = e3; }
        else { t[0] += e0; t[1] += e1; t[2] += e2; t[3] += e3; }
        p[2 * k] = pack2(e0, e1);
        p[2 * k + 1] = pack2(e2, e3);
    }
}
__device__ __forceinline__ void fma8(float (&acc)[8], float a, uint4 w) {
    acc[0] = fmaf(a, bf_lo(w.x), acc[0]); acc[1] = fmaf(a, bf_hi(w.x), acc[1]);
    acc[2] = fmaf(a, bf_lo(w.y), acc[2]); acc[3] = fmaf(a, bf_hi(w.y), acc[3]);
    acc[4] = fmaf(a, bf_lo(w.z), acc[4]); acc[5] = fmaf(a, bf_hi(w.z), acc[5]);
    acc[6] = fmaf(a, bf_lo(w.w), acc[6]); acc[7] = fmaf(a, bf_hi(w.w), acc[7]);
}
__device__ __forceinline__ void mma16816(float (&d)[4], const uint32_t* a, uint32_t b0, uint32_t b1) {
    asm("mma.sync.aligned.m16n8k16.row.col.f32.bf16.bf16.f32 {%0, %1, %2, %3}, {%4, %5, %6, %7}, {%8, %9}, {%0, %1, %2, %3};"
        : "+f"(d[0]), "+f"(d[1]), "+f"(d[2]), "+f"(d[3]) : "r"(a[0]), "r"(a[1]), "r"(a[2]), "r"(a[3]), "r"(b0), "r"(b1));
}
__device__ __forceinline__ uint2 best_key(const uint32_t* keys, int lane, uint32_t ep, uint32_t cur, int enough) {
#pragma unroll 1
    for (;;) {
        const uint4 k = ld_poll(reinterpret_cast<const uint4*>(keys) + lane);
        const bool ok = (((k.x ^ ep) | (k.y ^ ep) | (k.z ^ ep) | (k.w ^ ep)) & 31) == 0;
        const uint32_t best = __reduce_max_sync(0xffffffffu, ok ? max(max(k.x, k.y), max(k.z, k.w)) : 0u);
        const int n = __popc(__ballot_sync(0xffffffffu, ok));
        if (n == 32 || (n >= enough && best != cur)) return make_uint2(best, n == 32);
        __nanosleep(KSLEEP);
    }
}

__global__ void __cluster_dims__(2, 1, 1) __launch_bounds__(384, 1)
fused_kernel(const __grid_constant__ CUtensorMap tm_ckv, const __grid_constant__ CUtensorMap tm_wq,
             const __grid_constant__ CUtensorMap tm_wuk, const __grid_constant__ CUtensorMap tm_wuv,
             const __grid_constant__ CUtensorMap tm_wo, const __grid_constant__ CUtensorMap tm_wg,
             const __grid_constant__ CUtensorMap tm_wu,
             const __grid_constant__ CUtensorMap tm_wm, const __grid_constant__ CUtensorMap tm_x, const Params P) {
    extern __shared__ __align__(1024) uint8_t smem[];
    const uint32_t sb = (uint32_t)__cvta_generic_to_shared(smem);
    const int tid = threadIdx.x, lane = tid & 31, warp = __shfl_sync(0xffffffffu, tid >> 5, 0), wg = warp >> 2;
    const uint32_t sm = blockIdx.x < 8 ? blockIdx.x + 124 : blockIdx.x - 8, smq = ((sm - 64) * 147) >> 11;
    const int rb = sm < 64 ? (sm & 14) * 8 + (sm >> 4) * 2 + (sm & 1)
                 : sm < 120 ? ((sm - 64 - smq * 14) & 14) * 8 + 24 + smq * 2 + (sm & 1) : sm < 124 ? sm + 8 : sm - 116;
    const int grp = rb >> 3, j = rb & 7, cq = j & 3, kh = grp & 1, ort = (grp & 14) + (j >> 2);
    if (warp == 0) TS(0);

    if (lane == 0) {
        if (warp == 8) {
            asm volatile("prefetch.tensormap [%0];" ::"l"(rb >= NCTA ? &tm_wm : (j & 1) ? &tm_wuv : &tm_wuk) : "memory");
            asm volatile("prefetch.tensormap [%0];" ::"l"(&tm_ckv) : "memory");
            *reinterpret_cast<uint2*>(smem + SM_EP + 16) = make_uint2(0, 0);
        }
        const u64 cnt = (warp < 5 ? (rb < NCTA ? 0x844444441111111ull : 0x888888881111111ull) : warp < 10 ? 0x111111188888888ull : 0x118121ull) >> (12 * (warp % 5));
#pragma unroll
        for (int i = 0; i < 3; i++) mbar_init(sb + SM_BAR + 24 * warp + 8 * i, ((uint32_t)cnt >> (4 * i)) & 15);
        fence_async_smem();
        asm volatile("fence.mbarrier_init.release.cluster;" ::: "memory");
    }
    __syncthreads();
    asm volatile("barrier.cluster.arrive.relaxed.aligned;\nbarrier.cluster.wait.aligned;" ::: "memory");

    if (rb >= NCTA) {
        float* sc = reinterpret_cast<float*>(smem + 6 * SLOT);
        float* red = sc + 512;
        uint32_t ph = 0x7f, sl = 0;
        if (warp == 8) {
#pragma unroll 1
            for (int i = 0; i < 24; i++) {
                slot_acquire(sb, ph, sl);
                tma2d(sb + sl * SLOT, &tm_wm, (i >> 3) * 1024 + (rb - NCTA) * 256, (i & 7) * 64, sb + BAR_FULL + 8 * sl, HINT & 64);
                if (++sl == 6) sl = 0;
            }
#pragma unroll 1
            for (int i = 0; i <= NFFN / NSPARE; i++) {
                const int b = (rb - NCTA) * (NFFN / NSPARE) + i;
                if (i < NFFN / NSPARE) {
                    asm volatile("cp.async.bulk.wait_group.read 0;" ::: "memory");
                    uint32_t done = 0x7f;
                    slot_acquire(sb, done, i & 1);
#pragma unroll 1
                    for (int k = 0; k < 4; k++) tma2d(sb + (i & 1) * SLOT + k * 8192, k < 2 ? &tm_wg : &tm_wu, b * 16, (k & 1) * 256, sb + BAR_FULL + 8 * (i & 1), (HINT & 128) && (i & 3) == 3);
                }
                if (i) {
                    mbar_wait(sb + BAR_FULL + 8 * (~i & 1), ((i - 1) >> 1) & 1);
                    bulk_store(g_wf + (b - 1) * SLOT, sb + (~i & 1) * SLOT, SLOT, HINT & 256);
                    asm volatile("cp.async.bulk.commit_group;" ::: "memory");
                }
            }
            asm volatile("cp.async.bulk.wait_group 0;" ::: "memory");
            fence_async_global();
            TS(4);
        } else if (warp < 8) {
            const uint32_t c2 = __ldg(reinterpret_cast<const uint32_t*>(P.c) + tid), ep = __ldcg(&g_sync.epoch[0]) + 1;
            sc[2 * tid] = rbf(bf_lo(c2) * sigmoid(bf_lo(c2)));
            sc[2 * tid + 1] = rbf(bf_hi(c2) * sigmoid(bf_hi(c2)));
            ph = 0;
#pragma unroll 1
            for (int ps = 0; ps < 3; ps++) {
                bar_sync(1, 256);
                float acc[8] = {0.f, 0.f, 0.f, 0.f, 0.f, 0.f, 0.f, 0.f};
#pragma unroll 1
                for (int bt = 0; bt < 8; bt++) {
                    slot_wait(sb + BAR_FULL, ph, sl);
#pragma unroll 4
                    for (int i = 0; i < 8; i++)
                        fma8(acc, sc[bt * 64 + warp * 8 + i], *reinterpret_cast<const uint4*>(smem + sl * SLOT + (warp * 8 + i) * 512 + lane * 16));
                    __syncwarp();
                    mbar_arrive_if(sb + BAR_EMPTY + 8 * sl, lane == 0);
                    if (++sl == 6) sl = 0;
                }
                *reinterpret_cast<float4*>(red + warp * 256 + lane * 8) = make_float4(acc[0], acc[1], acc[2], acc[3]);
                *reinterpret_cast<float4*>(red + warp * 256 + lane * 8 + 4) = make_float4(acc[4], acc[5], acc[6], acc[7]);
                bar_sync(1, 256);
                float v = 0.f;
#pragma unroll
                for (int i = 0; i < 8; i++) v += red[i * 256 + tid];
                if (ps == 0) st_pub(g_mod1 + (rb - NCTA) * 256 + tid, (pack2(0.f, v) & 0xffff0000u) | (ep & 0xffffu), true);
                else g_mod[ps * 1024 + (rb - NCTA) * 256 + tid] = __float2bfloat16_rn(v);
                if (warp == 0) TS(1 + ps);
            }
        }
        __syncthreads();
        if (tid < 2) flag_add(&g_sync.cnt[7 * 8]);
        return;
    }

    if (wg == 2) {
        asm volatile("setmaxnreg.dec.sync.aligned.u32 40;");
        const CUtensorMap* tw = (j & 1) ? &tm_wuv : &tm_wuk;
        if (warp == 8) {
            const uint32_t rank = j & 1, half = rank * 16384;
            uint32_t eph = 0x7f, r = 0;
#pragma unroll 1
            for (int hp = 0; hp < 2; hp++) {
                uint32_t wtab = w_table(hp), atab = a_table(hp);
                const int hc = 4 * grp + 2 * hp;
#pragma unroll 1
                for (int u = 0; u < 16; u++) {
                    if (u < 4) {
                        const uint32_t ws = (wtab >> (4 * u)) & 15;
                        slot_acquire(sb, eph, ws);
                        load_tile(sb, ws, 0, tw, u * 128, hc, false, HINT & 1);
                        PT();
                    }
                    if (hp == 1 && (u & 7) == 4) mbar_wait(sb + BAR_FLAG + 24 + (u & 8), 0);
                    const uint32_t as = a_next(atab);
                    slot_acquire(sb, eph, as);
                    load_tile(sb, as, half, &tm_ckv, ((u & 12) + (j >> 1)) * 128, (u & 3) * 2 + rank, true, (HINT & 8) && hp);
                    PT();
                    if (hp == 1 && (u | 2) == 3 && lane == 0)
                        asm volatile("red.relaxed.gpu.global.add.u32 [%0], 1;" ::"l"(&g_sync.cnt[(grp * 8 + 3 + (u >> 1)) * 8]) : "memory");
                }
                const uint8_t* src = g_h + (15 - j) * 4 * SLOT;
#pragma unroll 1
                for (int u = 0; u < 8; u++) {
                    if ((u & 3) == 0) {
                        mbar_wait(sb + BAR_FLAG + (2 + 8 * hp) * u, 0);
                        fence_async_global();
                    }
                    if (u < 4) {
                        const uint32_t ws = (wtab >> (4 * u)) & 15;
                        slot_acquire(sb, eph, ws);
                        load_tile(sb, ws, half, &tm_wq, u * 128, hc + rank, true, HINT & 1);
                        PT();
                    }
                    const uint32_t as = a_next(atab);
                    slot_acquire(sb, eph, as);
                    load_bulk(sb, as, 0, src, SLOT, false, (HINT & 8) && hp);
                    PT();
                    src += u == 3 ? (8 * j - 63) * SLOT : SLOT;
                }
                const int step = hp ? -2 * SLOT : 2 * SLOT;
                src = g_KV + (size_t)(grp * 32 + 30 * hp) * SLOT + half - step;
#pragma unroll 1
                for (int n = 0; n <= 17; n++) {
                    if (n == 8) {
                        mbar_wait(sb + BAR_FLAG + 16 + 32 * hp, 0);
                        fence_async_global();
                    }
                    const uint8_t* v = src + SLOT;
                    src += n < 16 - j ? step : n == 16 - j ? (2 * j - 15) * step : -step;
                    if (n < 17) {
                        slot_acquire(sb, eph, r);
                        if (n != 15 - (j & 6)) load_bulk(sb, r, half, src, SLOT / 2, true, (HINT & 4) && (hp || !(HINT & 32)));
                        else load_bulk(sb, r, 0, src - half, SLOT, false, (HINT & 4) && (hp || !(HINT & 32)));
                        PT();
                        r = ring_next(r);
                    }
                    if (n) {
                        slot_acquire(sb, eph, r);
                        if (n != 16 - (j & 6)) load_bulk(sb, r, half, v, SLOT / 2, true, (HINT & 4) && (hp || !(HINT & 32)));
                        else load_bulk(sb, r, 0, v - half, SLOT, false, (HINT & 4) && (hp || !(HINT & 32)));
                        PT();
                        r = ring_next(r);
                    }
                    asm volatile("st.volatile.shared.u32 [%0], %1;" ::"r"(sb + SM_EP + 16), "r"(18 * hp + n + 1) : "memory");
                }
            }
            uint32_t otab = O_TABLE, ready = 0;
#pragma unroll 1
            for (int i = 0; i < 17; i++) {
                const bool dyn = i >= 8 && i < 15;
                const uint32_t want = dyn ? 15u << (4 * (i - 8)) : 1u << max(i + 14, 28);
                if (!(ready & want)) {
                    do {
                        asm volatile("ld.acquire.cta.shared.u32 %0, [%1];" : "=r"(ready) : "r"(sb + SM_EP + 20) : "memory");
                        ready = __shfl_sync(0xffffffffu, ready, 0);
                    } while (!(ready & want));
                    fence_async_global();
                }
                const int head = o_head(dyn ? (ready >> (4 * (i - 8))) & 15 : i, kh);
                const uint32_t as = o_next(otab), ws = o_next(otab), off = i < 15 ? half : kh * 16384;
                slot_acquire(sb, eph, as);
                load_bulk(sb, as, off, g_ctx + (size_t)(ort * 32 + head) * SLOT + off, SLOT / 2, i < 15, HINT & 16);
                if (i == 15) load_tile(sb, as, off ^ 16384, &tm_x, ort * 128 + kh * 64, cq * 2, false, false);
                if (i == 16) load_bulk(sb, as, off ^ 16384, P.wdown + min(rb, NFFN - 1) * 8192, SLOT / 2, false, false);
                PT();
                slot_acquire(sb, eph, ws);
                load_tile(sb, ws, 0, &tm_wo, head * 128, cq * 2, false, HINT & 2);
                PT();
                if (i == 0) o_next(otab);
            }
            if (rb < NFFN) {
                slot_acquire(sb, eph, 5);
                load_bulk(sb, 5, 0, g_wf + rb * SLOT, SLOT, false, false);
            }
        } else if (warp == 9) {
            l2_prefetch(P.ckv + rb * 2048, 4096);
            mbar_watch(sb + BAR_FULL, 0);
            l2_prefetch(P.ckv + 512 * 512 + rb * 2048, 4096);
            mbar_watch(sb + BAR_FULL + 8 * XPF, 0);
            l2_prefetch(P.x + rb * 8192, 16384);
            mbar_watch(sb + BAR_FULL + 8 * 4, 0);
            l2_prefetch(P.ckv + 1024 * 512 + rb * 4096, 8192);
            TS(40);
#pragma unroll 1
            for (int i = 0; i < 15; i++) {
                step_watch(sb + SM_EP + 16, i == 0 ? 0 : i < 5 ? PFA + i : 13 + PFB + i);
                if (i == 12) mbar_watch(sb + BAR_FLAG + 8 * 7, 0);
                const int rf = min(rb, NFFN - 1);
                const uint8_t* p = i == 3 ? reinterpret_cast<const uint8_t*>(P.ckv) + rb * 16384
                                 : i == 4 ? g_h + rb * 16384
                                 : i < 9 ? g_ctx + (size_t)(ort * 32 + o_head(cq + 2 * ((i - 5) & 2), kh)) * SLOT + (i & 1) * 16384
                                 : i < 11 ? reinterpret_cast<const uint8_t*>(P.wo) + (grp * 16 + (~i & 1) * 8 + j) * 16384
                                 : i == 11 ? reinterpret_cast<const uint8_t*>(P.x) + rb * 16384
                                 : i == 12 ? reinterpret_cast<const uint8_t*>(P.wdown) + rf * 16384 : g_wf + rf * SLOT + (i & 1) * 16384;
                if (i < 3) tma3d_prefetch(i == 1 ? tw : &tm_wq, (j >> 1) * 128, grp * 4 + (i == 1 ? 2 : i + (j & 1)));
                else l2_prefetch(p, 16384);
            }
            const uint32_t v = lds32(sb + SM_EP) - 1;
            sts128(sb + SM_RED + lane * 16, make_uint4(v, v, v, v));
            fence_async_smem();
            __syncwarp();
#pragma unroll 1
            for (int i = 0; i < OB / 32; i++) bulk_store(g_out + rb * OB + i * 32, sb + SM_RED, 512, false);
            asm volatile("cp.async.bulk.commit_group;\ncp.async.bulk.wait_group 0;" ::: "memory");
            fence_async_global();
            __syncwarp();
            mbar_arrive_if(sb + BAR_PF, lane == 0);
            if (lane == 0) mbar_watch(sb + BAR_END, 0);
        } else {
            const uint32_t ep = __ldcg(&g_sync.epoch[0]) + 1;
            asm volatile("st.shared.u32 [%0], %1;" ::"r"(sb + SM_EP), "r"(ep) : "memory");
            mbar_wait(sb + BAR_FULL + 8 * 4, 0);
            {
                uint4 v[4];
                for (;;) {
                    uint32_t bad = 0;
#pragma unroll
                    for (int k = 0; k < 4; k++) v[k] = ld_poll(reinterpret_cast<const uint4*>(g_mod1) + (warp & 1) * 128 + k * 32 + lane);
#pragma unroll
                    for (int k = 0; k < 4; k++) bad |= (v[k].x ^ ep) | (v[k].y ^ ep) | (v[k].z ^ ep) | (v[k].w ^ ep);
                    if (__all_sync(0xffffffffu, (bad & 0xffff) == 0)) break;
                    __nanosleep(100);
                }
                const uint32_t one = (warp & 1) ? ONE2 : 0x80008000u;
#pragma unroll
                for (int k = 0; k < 4; k++)
                    *reinterpret_cast<uint2*>(smem + SM_TAB + (warp & 1) * 1024 + k * 256 + lane * 8) =
                        make_uint2(badd(__byte_perm(v[k].x, v[k].y, 0x7632), one), badd(__byte_perm(v[k].z, v[k].w, 0x7632), one));
            }
            __syncwarp();
            mbar_arrive_if(sb + BAR_FLAG + 8 * 8, lane == 0);
            if (warp == 10) {
#pragma unroll 1
                for (int i = 0; i < 9; i++) {
                    mbar_sleep(sb + BAR_DONE + 8 * i);
                    if (lane == 0) flag_add(i && ((i - 1) & 2) ? &g_sync.ctxcnt[((i & 1) ? 15 - j : j) * 32 + 2 * grp + (i > 4)] : &g_sync.cnt[(grp * 8 + i) * 8]);
                    if (i == 0) TS(43);
                }
            } else {
                TS(42);
#pragma unroll 1
                for (int i = 0; i < 8; i++) {
                    mbar_sleep(sb + BAR_DONE + 8 * (i == 7 ? 6 : i == 4 ? 3 : i));
                    if (lane < 2) flag_wait(&g_sync.cnt[((i == 0 ? (lane ? j : 15 - j) : i == 7 ? 0 : grp) * 8 + i) * 8], 8 * ep);
                    __syncwarp();
                    mbar_arrive_if(sb + BAR_FLAG + 8 * i, lane == 0 && i < 7);
                    TS(48 + i);
                }
                const uint32_t *mp = reinterpret_cast<const uint32_t*>(g_mod) + lane, *wp = reinterpret_cast<const uint32_t*>(P.wr) + lane;
                float ra = 0.f, rs = 0.f;
#pragma unroll 1
                for (int k = 0; k < 256; k += 32) {
                    const uint32_t ga = __ldcg(mp + 512 + k), sh = __ldcg(mp + 768 + k), c1 = badd(__ldcg(mp + 1024 + k), ONE2);
                    const uint32_t gb = __ldcg(mp + 1280 + k), ww = __ldg(wp + k);
                    const uint32_t a = bmul(c1, ww);
                    ra += bf_lo(a) + bf_hi(a);
                    rs = fmaf(bf_lo(sh), bf_lo(ww), fmaf(bf_hi(sh), bf_hi(ww), rs));
                    if (k >> 6 == cq) {
                        sts128(sb + SM_TAB + ((k & 32) + lane) * 16, make_uint4(ga << 16, ga & 0xffff0000u, a, 0));
                        sts128(sb + SM_TAB + 1024 + ((k & 32) + lane) * 16, make_uint4(c1, sh, gb, 0));
                    }
                }
#pragma unroll 1
                for (int o = 16; o > 0; o >>= 1) {
                    ra += __shfl_xor_sync(0xffffffffu, ra, o);
                    rs += __shfl_xor_sync(0xffffffffu, rs, o);
                }
                *reinterpret_cast<float2*>(smem + SM_EP + 8) = make_float2(ra, rs);
                __syncwarp();
                mbar_arrive_if(sb + BAR_FLAG + 8 * 7, lane == 0);
                const uint32_t* f = &g_sync.ctxcnt[ort * 32 + o_head(min(lane, 16), kh)];
                uint32_t ready = -(j & 1), list = 0, sh = 0, qa;
                asm("mapa.shared::cluster.u32 %0, %1, %2;" : "=r"(qa) : "r"(sb + SM_EP + 20), "r"(lane & 1));
                while (ready != ~0u) {
                    uint32_t v;
                    asm volatile("ld.acquire.gpu.global.u32 %0, [%1];" : "=r"(v) : "l"(f) : "memory");
                    const uint32_t now = __ballot_sync(0xffffffffu, (int)(v - ep) >= 0);
#pragma unroll 1
                    for (uint32_t fresh = now & ~ready & 0x7f00; fresh; fresh &= fresh - 1, sh += 4) list |= (__ffs(fresh) - 1) << sh;
                    list |= (((now & 0xff) + 1) >> 8 << 28) | ((now & 0x18000) << 14);
                    if (now != ready && lane < 2) asm volatile("st.relaxed.cluster.shared::cluster.u32 [%0], %1;" ::"r"(qa), "r"(list) : "memory");
                    if ((now & 0xff) == 0xff) mbar_sleep(sb + BAR_DONE + 8 * 7);
                    ready = now;
                    __nanosleep(POLL_NS);
                }
                TS(45);
            }
        }
    } else {
        asm volatile("setmaxnreg.inc.sync.aligned.u32 232;");
        const bool elected = (tid & 127) == 0, rel = (tid & 95) == 0;
        uint32_t eb;
        asm("mapa.shared::cluster.u32 %0, %1, %2;" : "=r"(eb) : "r"(sb + BAR_EMPTY), "r"(warp & 1));
        const int g = lane >> 2, c4 = lane & 3;
        const uint32_t toff = warp * 4096 + g * 64 + ((c4 ^ (g >> 1)) << 4);
        uint32_t fph = 0x3f, r = 0;
        if (wg == 1) bar_arrive(1, 256);
        const uint32_t kd = desc_k(sb), wd = desc_mn(sb), vd = ((sb & 0x3ffff) >> 4) | (32u << 16);
        const int nL = 16 - j, hn = nL - 1 + wg;
        float s[64], o[64], li[2] = {0.f, 0.f};
        uint8_t* cimg = g_ctx;
        const float sc = (j & 1) ? 1.f : SM_C;
#pragma unroll 1
        for (int q = 0; q < 3; q++) {
            const uint32_t as = (0x635u >> (4 * q)) & 15;
            mbar_wait(sb + BAR_FULL + 8 * q, 0);
            mbar_wait(sb + BAR_FULL + 8 * as, 0);
            bar_sync(1 + wg, 256);
            gemm_issue<false>(s, kd + wg * 512 + as * (SLOT / 16), wd + q * (SLOT / 16), q, false);
            bar_arrive(2 - wg, 256);
            wg_wait<0>();
            release_if(eb, as, rel);
        }
        {
            const int xrow = rb * 16 + warp * 2;
            const uint4* xp = reinterpret_cast<const uint4*>(P.x) + xrow * 64;
            uint8_t* img = g_KV + (size_t)(grp * 32 + j) * SLOT;
            uint32_t x[16], x0[2];
            float st[4] = {0.f, 0.f, 0.f, 0.f};
            mbar_wait(sb + BAR_FULL + 8 * 4, 0);
#pragma unroll
            for (int q = 3; q < 8; q++) {
                const uint32_t ws = (0x4210u >> (4 * (q & 3))) & 15, as = (0x635u >> (4 * (q % 3))) & 15;
                mbar_wait(sb + BAR_FULL + 8 * as, (q / 3) & 1);
                bar_sync(1 + wg, 256);
                if (q == 3) gemm_issue<false>(s, kd + wg * 512 + as * (SLOT / 16), wd + ws * (SLOT / 16), 1, false);
                else if (q == 4) gemm_issue<true>(o, kd + wg * 512 + as * (SLOT / 16), wd + ws * (SLOT / 16), 0, false);
                else gemm_issue<false>(o, kd + wg * 512 + as * (SLOT / 16), wd + ws * (SLOT / 16), 1, false);
                bar_arrive(2 - wg, 256);
                sched_fence(fph, P.zero);
                if (q > 3) reg_fence(s);
                if (q == 3) {
#pragma unroll
                    for (int i = 0; i < 4; i++)
                        asm volatile("ld.global.nc.v4.u32 {%0, %1, %2, %3}, [%4];" : "=r"(x[4 * i]), "=r"(x[4 * i + 1]), "=r"(x[4 * i + 2]), "=r"(x[4 * i + 3])
                                     : "l"(xp + lane + 32 * i) : "memory");
#pragma unroll
                    for (int i = 0; i < 2; i++) asm volatile("ld.global.nc.u32 %0, [%1];" : "=r"(x0[i]) : "l"(xp + 64 * i) : "memory");
                }
                if (q == 4) {
                    img_store_global<0>(img, toff, s, sc, sc);
#pragma unroll
                    for (int k = 0; k < 16; k++) {
                        const float d0 = bf_lo(x[k]) - bf_lo(x0[k >> 3]), d1 = bf_hi(x[k]) - bf_lo(x0[k >> 3]);
                        st[k >> 3] += d0 + d1;
                        st[2 + (k >> 3)] = fmaf(d0, d0, fmaf(d1, d1, st[2 + (k >> 3)]));
                    }
#pragma unroll
                    for (int i = 0; i < 4 * NSH; i++) st[i & 3] += __shfl_xor_sync(0xffffffffu, st[i & 3], 1 << (i >> 2));
                    reg_fence(st);
                }
                if (q == 5) {
#pragma unroll
                    for (int i = 4 * NSH; i < 20; i++) st[i & 3] += __shfl_xor_sync(0xffffffffu, st[i & 3], 1 << (i >> 2));
                    img_store_global<1>(img, toff, s, sc, sc);
#pragma unroll
                    for (int i = 0; i < 2; i++) {
                        const float d = st[i] * (1.f / 512.f);
                        st[2 + i] = ln_rstd(fmaxf(fmaf(-d, d, st[2 + i] * (1.f / 512.f)), 0.f));
                        x0[i] = pack2(bf_lo(x0[i]) + d, bf_lo(x0[i]) + d);
                    }
                    reg_fence(st);
                    reg_fence(x0);
                }
                if (q > 5) {
                    if (q == 6) mbar_wait(sb + BAR_FLAG + 8 * 8, 0);
                    const uint4 a = lds128(sb + SM_TAB + 1024 + (q & 1) * 512 + lane * 16), c = lds128(sb + SM_TAB + (q & 1) * 512 + lane * 16);
                    uint8_t* hp = g_h + (grp * 8 + (q & 1) * 4 + (lane >> 3)) * 16384 + (xrow & 127) * 128;
#pragma unroll
                    for (int i = 0; i < 2; i++) {
                        const uint32_t* y = x + 8 * i + 4 * (q & 1);
                        *reinterpret_cast<uint4*>(hp + i * 128 + (((lane ^ xrow ^ i) & 7) << 4)) =
                            make_uint4(ln_apply(y[0], x0[i], st[2 + i], a.x, c.x), ln_apply(y[1], x0[i], st[2 + i], a.y, c.y),
                                       ln_apply(y[2], x0[i], st[2 + i], a.z, c.z), ln_apply(y[3], x0[i], st[2 + i], a.w, c.w));
                    }
                    if (q == 7) {
                        __syncwarp();
                        mbar_arrive_if(sb + BAR_DONE, lane == 0);
                    }
                    if (q == 6) img_store_global<2>(img, toff, s, sc, sc);
                    else img_store_global<3>(img, toff, s, sc, sc);
                }
                sched_fence(fph, P.zero);
                wg_wait<0>();
                release_if(eb, as, rel);
            }
            reg_fence(o);
        }
        uint32_t p[32] = {};
#pragma unroll 1
        for (int hp = 0; hp < 2; hp++) {
            float m[2] = {0.f, 0.f}, l[2] = {0.f, 0.f}, t[4] = {0.f, 0.f, 0.f, 0.f};
            bool shifted = false, bad = false, plain = false;
            uint32_t qa = desc_k(sb + 5 * SLOT + (wg ^ 1) * 8192);
            uint8_t* limg = g_ctx + (size_t)((15 - j) * 32 + 2 * grp + hp) * SLOT;
            {
                const int step = hp ? -8 * SLOT : 8 * SLOT;
                uint8_t* img = g_KV + (size_t)(grp * 32 + (hp ? j ^ 30 : j) + 8) * SLOT;
                const uint32_t wtab = w_table(hp);
                uint32_t atab = hp ? 0x562u : 0x356u;
#pragma unroll 1
                for (int u = 2 - 2 * hp;; u += 2) {
                    proj_tile<false>(s, o, u, !u, sb, wg, eb, rel, fph, wtab, atab, u ? img : cimg, toff, u ? sc : li[0], u ? sc : li[1], p);
                    __syncwarp();
                    mbar_arrive_if(sb + BAR_DONE + 4 * u + 32 * hp, lane == 0);
                    if (elected) TS(1 + 10 * hp + u + 20 * wg);
                    if (proj_tile<true>(o, s, u + 1, 0, sb, wg, eb, rel, fph, wtab, atab, img + step, toff, sc, sc, p)) break;
                    if (elected) TS(2 + 10 * hp + u + 20 * wg);
                    img += 2 * step;
                }
            }
            if (elected) TS(6 + 10 * hp + 20 * wg);
            int n = -1;
#pragma unroll 1
            for (;;) {
                while (bad || plain) {
                    if (bad) {
                        float a0, a1;
                        softmax_remax(s, m, n == 0 || n == nL, a0, a1);
                        shifted = true;
                        l[0] *= a0;
                        l[1] *= a1;
#pragma unroll
                        for (int i = 0; i < 64; i++) o[i] *= (i & 2) ? a1 : a0;
                    }
                    softmax_exp<0, 16>(s, p, t);
                    t[0] += t[1];
                    t[2] += t[3];
                    bad = !bad && softmax_unsafe(t[0], t[2], false);
                    plain = false;
                }
#pragma unroll 1
                do {
                    l[0] += t[0];
                    l[1] += t[2];
                    if (++n > 16) break;
                    const uint32_t ks = r;
                    uint32_t vs = ring_next(r);
                    r = ring_next(vs);
                    bar_sync(1 + wg, 256);
                    const float x = (float)((warp & 3) * 16 + g - 2 * c4);
                    if (n == hn) {
                        float sh[32];
                        qk_issue(sh, qa, kd + ks * (SLOT / 16));
                        slot_wait(sb + BAR_FULL, fph, vs);
                        pv_issue(o, p, vd + vs * (SLOT / 16), 1, false);
                        bar_arrive(2 - wg, 256);
                        wg_wait<1>();
                        reg_fence(sh);
                        tri_mask_copy(s, sh, x);
                        release_if(eb, ks, rel);
                        release_if(eb, 5 + wg, rel && (!wg || n == 16));
                        if (!wg) {
                            qa += SLOT / 16;
                            fence_async_smem();
                            if (shifted) softmax_shift(s, m[0], m[1]);
                        }
                        float e[4 * EARLY];
#pragma unroll
                        for (int i = 0; i < 4 * EARLY; i++) {
                            e[i] = ex2(s[i]);
                            t[i & 3] = i < 4 ? e[i] : t[i & 3] + e[i];
                        }
                        reg_fence(e);
                        slot_wait(sb + BAR_FULL, fph, r);
                        wg_wait<0>();
                        reg_fence(o);
                        reg_fence(e);
                        release_if(eb, vs, rel);
#pragma unroll
                        for (int i = 0; i < 2 * EARLY; i++) p[i] = pack2(e[2 * i], e[2 * i + 1]);
                        softmax_exp<EARLY, 8>(s, p, t);
                        if (wg) {
                            ctx_store<true>(limg, toff, o, l[0], l[1]);
                            __syncwarp();
                            mbar_arrive_if(sb + BAR_DONE + 24 + 32 * hp, lane == 0);
                            l[0] = l[1] = m[0] = m[1] = 0.f;
                            shifted = false;
                        }
                        t[0] += t[1];
                        t[2] += t[3];
                        bad = softmax_unsafe(t[0], t[2], wg);
                        continue;
                    }
                    if (n == 0 || n == nL) {
                        qk_issue(s, qa, kd + ks * (SLOT / 16));
                        if (n == 0) {
                            r = vs;
                            vs = 4 - hp;
                            slot_wait(sb + BAR_FULL, fph, 6);
                            gemm_issue<false>(o, qa + SLOT / 16, wd + vs * (SLOT / 16), 1, false);
                        } else {
                            slot_wait(sb + BAR_FULL, fph, vs);
                            pv_issue(o, p, vd + vs * (SLOT / 16), 1, true);
                        }
                        bar_arrive(2 - wg, 256);
                        const float i0 = n ? rcp(quad_sum(l[0])) : 1.f, i1 = n ? rcp(quad_sum(l[1])) : 1.f;
                        wg_wait<1>();
                        reg_fence(s);
                        release_if(eb, ks, rel);
                        release_if(eb, 6, rel && n == 16);
                        tri_mask(s, n ? x : 64.f);
                        float e[4 * EARLY];
#pragma unroll
                        for (int i = 0; i < 4 * EARLY; i++) {
                            e[i] = ex2(s[i]);
                            t[i & 3] = i < 4 ? e[i] : t[i & 3] + e[i];
                        }
                        reg_fence(e);
                        reg_fence(s);
                        reg_fence(t);
                        slot_wait(sb + BAR_FULL, fph, r);
                        if (SF & 1) sched_fence(fph, P.zero);
                        wg_wait<0>();
                        reg_fence(o);
                        reg_fence(e);
                        release_if(eb, vs, rel);
#pragma unroll
                        for (int i = 0; i < 2 * EARLY; i++) p[i] = pack2(e[2 * i], e[2 * i + 1]);
                        softmax_exp<EARLY, MSPLIT>(s, p, t);
                        tile_store(limg, sb + 6 * SLOT, toff, o, i0, i1, n);
                        reg_fence(t);
                        if (SF & 2) sched_fence(fph, P.zero);
                        reg_fence(s);
                        softmax_exp<MSPLIT, 16>(s, p, t);
                        __syncwarp();
                        mbar_arrive_if(sb + BAR_DONE + 24 + 32 * hp, lane == 0 && n);
                        l[0] = l[1] = m[0] = m[1] = 0.f;
                        shifted = false;
                        t[0] += t[1];
                        t[2] += t[3];
                        bad = __any_sync(0xffffffffu, fmaxf(t[0], t[2]) > SM_HI || fminf(t[0], t[2]) < SM_LO);
                        continue;
                    }
                    qk_issue(s, qa, kd + ks * (SLOT / 16));
                    slot_wait(sb + BAR_FULL, fph, vs);
                    pv_issue(o, p, vd + vs * (SLOT / 16), n != 1 && n != nL + 1, n == hn + 1);
                    bar_arrive(2 - wg, 256);
                    wg_wait<1>();
                    reg_fence(s);
                    release_if(eb, ks, rel);
                    release_if(eb, 6, rel && n == 16);
                    if (n == nL - 1) {
                        tri_mask(s, x);
                        release_if(eb, 5, rel);
                        qa += SLOT / 16;
                        fence_async_smem();
                    }
                    if (shifted) {
                        slot_wait(sb + BAR_FULL, fph, r);
                        wg_wait<0>();
                        reg_fence(o);
                        release_if(eb, vs, rel);
                        softmax_shift(s, m[0], m[1]);
                        plain = true;
                        break;
                    }
                    float e[4 * EARLY];
#pragma unroll
                    for (int i = 0; i < 4 * EARLY; i++) {
                        e[i] = ex2(s[i]);
                        t[i & 3] = i < 4 ? e[i] : t[i & 3] + e[i];
                    }
                    reg_fence(e);
                    slot_wait(sb + BAR_FULL, fph, r);
                    wg_wait<0>();
                    reg_fence(o);
                    reg_fence(e);
                    release_if(eb, vs, rel);
#pragma unroll
                    for (int i = 0; i < 2 * EARLY; i++) p[i] = pack2(e[2 * i], e[2 * i + 1]);
                    softmax_exp<EARLY, 16>(s, p, t);
                    t[0] += t[1];
                    t[2] += t[3];
                    bad = softmax_unsafe(t[0], t[2], false);
                } while (!bad);
                if (!bad && !plain) break;
            }
            const uint32_t vs = r, ga = desc_k(sb + (hp ? 2 * (wg ^ kh ^ 1) : wg) * 8192);
            r = ring_next(r);
            slot_wait(sb + BAR_FULL, fph, 5);
            slot_wait(sb + BAR_FULL, fph, r);
            bar_sync(1 + wg, 256);
            gemm_issue<true>(s, ga + 5 * (SLOT / 16), wd + r * (SLOT / 16), 0, hp);
            pv_issue(o, p, vd + vs * (SLOT / 16), j, hn == 16);
            bar_arrive(2 - wg, 256);
            li[0] = rcp(quad_sum(l[0]));
            li[1] = rcp(quad_sum(l[1]));
            cimg = limg + (ptrdiff_t)(2 * j - 15) * 32 * SLOT + (wg ? -16384 : 16384);
            wg_wait<1>();
            release_if(eb, 5, rel);
            release_if(eb, r, rel && hp);
            wg_wait<0>();
            release_if(eb, vs, rel);
            reg_fence(o);
            img_store_global<0>(cimg, toff, o, li[0], li[1]);
            if (elected) TS(8 + 10 * hp + 20 * wg);
        }
        uint32_t otab = 0x2351604u;
        const uint32_t oa = desc_k(sb + (wg ^ kh ^ 1) * 16384);
        const int t7 = tid & 127, w4 = warp & 3, row = ort * 128 + kh * 64 + w4 * 16 + g;
#pragma unroll 1
        for (int i = 1; i < 15 - wg; i++) {
            const uint32_t as = o_next(otab), ws = o_next(otab);
            slot_wait(sb + BAR_FULL, fph, as);
            slot_wait(sb + BAR_FULL, fph, ws);
            bar_sync(1 + wg, 256);
            gemm_issue<false>(s, oa + as * (SLOT / 16), wd + ws * (SLOT / 16), 1, true);
            bar_arrive(2 - wg, 256);
            wg_wait<1>();
            reg_fence(o);
            if (i == 1) img_store_global<1>(cimg, toff, o, li[0], li[1]);
            if (i == 2) {
                img_store_global<2>(cimg, toff, o, li[0], li[1]);
                img_store_global<3>(cimg, toff, o, li[0], li[1]);
                __syncwarp();
                mbar_arrive_if(sb + BAR_DONE + 64, lane == 0);
            }
            wg_wait<0>();
            release_if(eb, as, rel);
            release_if(eb, ws, rel);
        }
        mbar_wait(sb + BAR_PF, 0);
        const uint32_t ep = lds32(sb + SM_EP);
        uint32_t eb2 = sb + BAR_END;
        if (wg == 0) {
            reg_fence(s);
            if (elected) TS(9);
            TT(1);
#pragma unroll
            for (int v = 0; v < 8; v++)
                st_pub(g_out + rb * OB + v * 128 + t7, make_uint4((pack2(s[8 * v], s[8 * v + 1]) & ~1u) | (ep & 1), pack2(s[8 * v + 2], s[8 * v + 3]),
                                                                      pack2(s[8 * v + 4], s[8 * v + 5]), pack2(s[8 * v + 6], s[8 * v + 7])), true);
            constexpr uint32_t s1 = 5, s2 = 6;
            bar_sync(4, 256);
            uint32_t wf[64];
            float wn[64];
            if (rb < NFFN) {
                slot_wait(sb + BAR_FULL, fph, s1);
                const uint32_t a = sb + s1 * SLOT + (w4 * 128 + (lane >> 4) * 8 + (lane & 7)) * 32 + ((lane >> 3) & 1) * 16;
#pragma unroll
                for (int i = 0; i < 16; i++)
                    asm volatile("ldmatrix.sync.aligned.m8n8.x4.trans.shared.b16 {%0, %1, %2, %3}, [%4];"
                                 : "=r"(wf[4 * i]), "=r"(wf[4 * i + 1]), "=r"(wf[4 * i + 2]), "=r"(wf[4 * i + 3])
                                 : "r"(a + (i >> 3) * 16384 + (i & 7) * 512) : "memory");
                slot_wait(sb + BAR_FULL, fph, s2);
#pragma unroll
                for (int i = 0; i < 16; i++) {
                    const uint2 w = *reinterpret_cast<const uint2*>(smem + s2 * SLOT + (kh ^ 1) * 16384 + i * 1024 + t7 * 8);
                    wn[4 * i] = bf_lo(w.x); wn[4 * i + 1] = bf_hi(w.x); wn[4 * i + 2] = bf_lo(w.y); wn[4 * i + 3] = bf_hi(w.y);
                }
                reg_fence(wn);
            }
            const uint32_t gbf = __ldcg(reinterpret_cast<const uint32_t*>(g_mod) + 1280 + rb * 2 + (tid & 1));
            if (elected) TS(10);
            TT(2);
            float* sred = reinterpret_cast<float*>(smem + SM_RED);
            uint32_t best = ep ^ 1, all;
            bool fresh;
            do {
                if (warp == 0) {
                    const uint2 k = best_key(g_key + cq * 128, lane, ep, best, rb < NFFN ? SPEC : 32);
                    *reinterpret_cast<uint2*>(smem + SM_EP + 24) = k;
                    mbar_arrive_if(sb + BAR_BEST, lane == 0 && k.y);
                }
                bar_sync(3, 128);
                const uint2 k = *reinterpret_cast<const uint2*>(smem + SM_EP + 24);
                fresh = k.x != best;
                best = k.x;
                all = k.y;
                TT(3);
                if (!fresh || rb >= NFFN) break;
                const uint4* cp = g_cand + ((~best >> 9) & 127) * 192;
                uint4 cv[6];
                for (;;) {
                    uint32_t bad = 0;
#pragma unroll
                    for (int v = 0; v < 6; v++) cv[v] = ld_poll(cp + w4 * 24 + v * 4 + c4);
#pragma unroll
                    for (int v = 0; v < 6; v++) bad |= cv[v].w ^ ep;
                    if (__all_sync(0xffffffffu, bad == 0)) break;
                    if (CSLEEP) __nanosleep(CSLEEP);
                }
            TT(4);
                float d[4][4] = {};
#pragma unroll
                for (int k = 0; k < 8; k++) {
                    const uint32_t b0 = (&cv[(2 * k) / 3].x)[(2 * k) % 3], b1 = (&cv[(2 * k + 1) / 3].x)[(2 * k + 1) % 3];
                    mma16816(d[k & 1], wf + 4 * k, b0, b1);
                    mma16816(d[2 + (k & 1)], wf + 32 + 4 * k, b0, b1);
                }
                const float u = (c4 & 2) ? ((c4 & 1) ? d[2][2] + d[3][2] : d[2][0] + d[3][0]) : ((c4 & 1) ? d[0][2] + d[1][2] : d[0][0] + d[1][0]);
                sred[w4 * 32 + c4 * 8 + g] = u;
                bar_sync(3, 128);
                const float v = rbf((sred[lane] + sred[32 + lane]) + (sred[64 + lane] + sred[96 + lane]));
                const float act = rbf(rbf(v * sigmoid(v)) * __shfl_down_sync(0xffffffffu, v, 16));
                float y[4] = {0.f, 0.f, 0.f, 0.f};
#pragma unroll
                for (int k = 0; k < 16; k++) {
                    const float a = __shfl_sync(0xffffffffu, act, k);
#pragma unroll
                    for (int i = 0; i < 4; i++) y[i] = fmaf(a, wn[4 * k + i], y[i]);
                }
                st_pub(g_out + rb * OB + OB_Y + t7, make_uint4((__float_as_uint(y[0]) & ~15u) | (ep & 15), (__float_as_uint(y[1]) & ~127u) | ((best >> 9) & 127),
                                                               __float_as_uint(y[2]), __float_as_uint(y[3])), true);
            } while (!all);
            const int sel = (~best >> 5) & 2047;
            const int pq = (2 * rb + (tid & 1)) & 63, pv = (pq >> 2) / 3;
            const uint4* fp = g_cand + (sel >> 4) * 192 + (rb >> 5) * 24 + pv * 4 + (pq & 3);
            uint4 fh = {}, fx = {};
            if (rb == 0 && tid == 0) g_sync.epoch[0] = ep;
            if (elected) TS(60);
            TT(5);
            uint4 yv;
            if (warp == 0) { fh = ld_poll(fp); fx = ld_poll(fp + 96); }
            if (fresh && rb < NFFN) __nanosleep(YPRE);
            for (;;) {
                yv = ld_poll(g_out + min(t7, NFFN - 1) * OB + OB_Y + rb);
                if (__all_sync(0xffffffffu, (((yv.x ^ ep) & 15) | ((yv.y ^ (best >> 9)) & 127)) == 0)) break;
                if (YSLEEP) __nanosleep(YSLEEP);
            }
            if (elected) TS(61);
            TT(6);
            float y[4] = {0.f, 0.f, 0.f, 0.f};
            if (t7 < NFFN) { y[0] = __uint_as_float(yv.x); y[1] = __uint_as_float(yv.y); y[2] = __uint_as_float(yv.z); y[3] = __uint_as_float(yv.w); }
            const float z0 = ((lane & 16) ? y[2] : y[0]) + __shfl_xor_sync(0xffffffffu, (lane & 16) ? y[0] : y[2], 16);
            const float z1 = ((lane & 16) ? y[3] : y[1]) + __shfl_xor_sync(0xffffffffu, (lane & 16) ? y[1] : y[3], 16);
            float z = ((lane & 8) ? z1 : z0) + __shfl_xor_sync(0xffffffffu, (lane & 8) ? z0 : z1, 8);
            z += __shfl_xor_sync(0xffffffffu, z, 4);
            z = quad_sum(z);
            if ((lane & 7) == 0) sred[128 + (lane >> 3) * 4 + w4] = z;
            bar_sync(3, 128);
            if (tid < 2) {
                while (fh.w != ep || fx.w != ep) { fh = ld_poll(fp); fx = ld_poll(fp + 96); }
                const float4 y0 = *reinterpret_cast<const float4*>(sred + 128 + tid * 8), y1 = *reinterpret_cast<const float4*>(sred + 132 + tid * 8);
                const int cm = (pq >> 2) - 3 * pv;
                const uint32_t h2 = cm == 0 ? fh.x : cm == 1 ? fh.y : fh.z, x2 = cm == 0 ? fx.x : cm == 1 ? fx.y : fx.z;
                const float sg = sigmoid(bf_hi((best & 0x80000000u) ? (best ^ 0x80000000u) : ~best));
                reinterpret_cast<uint32_t*>(P.out)[sel * 256 + rb * 2 + tid] =
                    badd(x2, bmul(gbf, badd(h2, bmul(pack2((y0.x + y0.y) + (y0.z + y0.w), (y1.x + y1.y) + (y1.z + y1.w)), pack2(sg, sg)))));
            }
            if (elected) TS(62);
            TT(7);
        } else {
            const float4* tf = reinterpret_cast<const float4*>(smem + SM_TAB) + c4;
            const uint32_t xa = sb + 4 * SLOT + (kh ^ 1) * 16384 + (w4 * 16 + (lane & 15)) * 128;
            uint32_t x2[32];
            bar_sync(2, 256);
#pragma unroll 1
            for (int i = 14; i < 17; i++) {
                const uint32_t as = o_next(otab), ws = o_next(otab);
                slot_wait(sb + BAR_FULL, fph, as);
                slot_wait(sb + BAR_FULL, fph, ws);
                gemm_issue<false>(s, oa + as * (SLOT / 16), wd + ws * (SLOT / 16), 1, true);
                wg_wait<1>();
            }
            if (elected) TS(29);
            TT(1);
            {
#pragma unroll
                for (int k = 0; k < 8; k++)
                    asm volatile("ldmatrix.sync.aligned.m8n8.x4.shared.b16 {%0, %1, %2, %3}, [%4];"
                                 : "=r"(x2[4 * k]), "=r"(x2[4 * k + 1]), "=r"(x2[4 * k + 2]), "=r"(x2[4 * k + 3])
                                 : "r"(xa + (k >> 2) * 8192 + (((2 * (k & 3) + (lane >> 4)) ^ (lane & 7)) << 4)) : "memory");
            }
            wg_wait<0>();
            reg_fence(s);
            bar_arrive(4, 256);
            if (elected) TS(39);
            TT(2);
            const uint4* pr = g_out + (rb ^ 8) * OB + t7;
            uint4 pa[8];
#pragma unroll
            for (int v = 0; v < 8; v++) pa[v] = ld_poll(pr + v * 128);
            float4 tc[16];
#pragma unroll
            for (int k = 0; k < 16; k++) {
                tc[k] = tf[k * 4];
                if (!(g & 1)) tc[k].z = __uint_as_float(ONE2);
#pragma unroll
                for (int i = 4 * k; i < 4 * k + 4; i++) s[i] = fmaf((i & 1) ? tc[k].y : tc[k].x, s[i], (i & 1) ? bf_hi(x2[i >> 1]) : bf_lo(x2[i >> 1]));
            }
            reg_fence(s);
            for (;;) {
                uint32_t bad = 0;
#pragma unroll
                for (int v = 0; v < 8; v++) bad |= pa[v].x ^ ep;
                if (__all_sync(0xffffffffu, (bad & 1) == 0)) break;
                if (PSLEEP) __nanosleep(PSLEEP);
#pragma unroll
                for (int v = 0; v < 8; v++) pa[v] = ld_poll(pr + v * 128);
            }
            if (elected) TS(30);
            TT(3);
            float sd[4] = {}, q0[4] = {}, q1[4] = {};
#pragma unroll
            for (int k = 0; k < 8; k++) {
#pragma unroll
                for (int i = 4 * k; i < 4 * k + 4; i++) {
                    const uint32_t w = (&pa[k].x)[i & 3];
                    x2[i] = pack2(fmaf(tc[i >> 1].x, bf_lo(w), s[2 * i]), fmaf(tc[i >> 1].y, bf_hi(w), s[2 * i + 1]));
                }
                mma16816(sd, x2 + 4 * k, __float_as_uint(tc[2 * k].z), __float_as_uint(tc[2 * k + 1].z));
                mma16816(q0, x2 + 4 * k, x2[4 * k], x2[4 * k + 2]);
                mma16816(q1, x2 + 4 * k, x2[4 * k + 1], x2[4 * k + 3]);
            }
            uint4* sp = g_out + rb * OB + OB_STAT + (w4 * 8 + g) * 2;
            st_pub(sp, make_uint4(__float_as_uint(sd[0]), __float_as_uint((g & 1) ? q0[1] : q0[0]), __float_as_uint(sd[1]), ep), c4 == g >> 1);
            st_pub(sp + 1, make_uint4(__float_as_uint(sd[2]), __float_as_uint((g & 1) ? q1[3] : q1[2]), __float_as_uint(sd[3]), ep), c4 == g >> 1);
            if (TF & 1) sched_fence(eb2, P.zero);
            if (elected) TS(56);
            TT(4);
            uint32_t cb[16], sh[16], gb[16];
#pragma unroll
            for (int i = 0; i < 16; i++) {
                const float4 c = tf[64 + i * 4];
                cb[i] = __float_as_uint(c.x); sh[i] = __float_as_uint(c.y); gb[i] = __float_as_uint(c.z);
            }
            const float ra = __uint_as_float(lds32(sb + SM_EP + 8)), rb0 = __uint_as_float(lds32(sb + SM_EP + 12));
            uint4 r0, r1;
            if (SPRE) __nanosleep(SPRE);
            for (;;) {
                r0 = ld_poll(g_out + ((rb & ~3) + c4) * OB + OB_STAT + (w4 * 8 + g) * 2);
                r1 = ld_poll(g_out + ((rb & ~3) + c4) * OB + OB_STAT + (w4 * 8 + g) * 2 + 1);
                if (__all_sync(0xffffffffu, r0.w == ep && r1.w == ep)) break;
                if (SSLEEP) __nanosleep(SSLEEP);
            }
            if (elected) TS(57);
            TT(5);
            const float m0 = quad_sum(__uint_as_float(r0.x)) * (1.f / 512.f), m1 = quad_sum(__uint_as_float(r1.x)) * (1.f / 512.f);
            const float rs0 = ln_rstd(fmaxf(fmaf(-m0, m0, quad_sum(__uint_as_float(r0.y)) * (1.f / 512.f)), 0.f));
            const float rs1 = ln_rstd(fmaxf(fmaf(-m1, m1, quad_sum(__uint_as_float(r1.y)) * (1.f / 512.f)), 0.f));
            const uint32_t mb0 = pack2(m0, m0), mb1 = pack2(m1, m1);
            const uint32_t lg = pack2(fmaf(rs0, fmaf(-bf_lo(mb0), ra, quad_sum(__uint_as_float(r0.z))), rb0),
                                      fmaf(rs1, fmaf(-bf_lo(mb1), ra, quad_sum(__uint_as_float(r1.z))), rb0));
            const uint32_t u0 = lg << 16, u1 = lg & 0xffff0000u;
            const uint32_t k0 = ((u0 ^ (((int)u0 >> 31) | 0x80000000u)) & 0xffff0000u) | ((2047 - row) << 5) | (ep & 31);
            const uint32_t k1 = ((u1 ^ (((int)u1 >> 31) | 0x80000000u)) & 0xffff0000u) | ((2039 - row) << 5) | (ep & 31);
            const uint32_t kb = __reduce_max_sync(0xffffffffu, max(k0, k1));
            st_pub(g_key + cq * 128 + (row >> 4), kb, lane == 0);
            const bool cand = kb == k0 || kb == k1;
            uint4* cp = g_cand + (row >> 4) * 192 + cq * 24 + c4;
#pragma unroll 1
            for (int it = 0; it < 3; it++) {
                bool put = it == 1 || !cand;
                if (it == 2) {
                    mbar_wait(sb + BAR_BEST, 0);
                    put = cand && lds32(sb + SM_EP + 24) != kb;
                }
                const bool hi = (kb == k1) != (it == 1);
                uint32_t cx[18], ch[18];
#pragma unroll
                for (int i = 0; i < 16; i++) {
                    cx[i] = hi ? x2[2 * i + 1] : x2[2 * i];
                    ch[i] = ln_apply(cx[i], hi ? mb1 : mb0, hi ? rs1 : rs0, cb[i], sh[i]);
                }
                cx[16] = cx[17] = ch[16] = ch[17] = 0;
#pragma unroll
                for (int v = 0; v < 6; v++) st_pub(cp + v * 4, make_uint4(ch[3 * v], ch[3 * v + 1], ch[3 * v + 2], ep), cand && it == 0);
                if (TF & 4) sched_fence(eb2, P.zero);
#pragma unroll
                for (int v = 0; v < 6; v++) st_pub(cp + 96 + v * 4, make_uint4(cx[3 * v], cx[3 * v + 1], cx[3 * v + 2], ep), cand && it == 0);
                if (it == 0) TT(6);
                uint2* op = reinterpret_cast<uint2*>(P.out) + (row + 8 * hi) * 128 + cq * 32 + (c4 & 1) * 2 + (c4 >> 1);
#pragma unroll
                for (int i = 0; i < 16; i += 2) {
                    const uint32_t v0 = badd(cx[i], bmul(gb[i], ch[i])), v1 = badd(cx[i + 1], bmul(gb[i + 1], ch[i + 1]));
                    const uint32_t rv = __shfl_xor_sync(0xffffffffu, (c4 & 1) ? v0 : v1, 1);
                    if (put) op[i * 2] = (c4 & 1) ? make_uint2(rv, v1) : make_uint2(v0, rv);
                }
            }
            if (elected) TS(59);
            TT(7);
        }
        mbar_arrive_if(eb2, lane == 0);
    }
}

typedef CUresult (*EncodeFn)(CUtensorMap*, CUtensorMapDataType, cuuint32_t, void*, const cuuint64_t*, const cuuint64_t*,
                             const cuuint32_t*, const cuuint32_t*, CUtensorMapInterleave, CUtensorMapSwizzle,
                             CUtensorMapL2promotion, CUtensorMapFloatOOBfill);

void make_2d(EncodeFn fn, CUtensorMap* m, const void* p, uint64_t cols, uint64_t rows, uint32_t bc, uint32_t br) {
    cuuint64_t dims[2] = {cols, rows}, strides[1] = {cols * 2};
    cuuint32_t box[2] = {bc, br}, es[2] = {1, 1};
    fn(m, CU_TENSOR_MAP_DATA_TYPE_BFLOAT16, 2, const_cast<void*>(p), dims, strides, box, es, CU_TENSOR_MAP_INTERLEAVE_NONE,
       CU_TENSOR_MAP_SWIZZLE_NONE, CU_TENSOR_MAP_L2_PROMOTION_L2_128B, CU_TENSOR_MAP_FLOAT_OOB_FILL_NONE);
}
void make_3d(EncodeFn fn, CUtensorMap* m, const void* p, uint64_t cols, uint64_t rows, uint32_t br = 128, uint32_t nb = 2) {
    cuuint64_t dims[3] = {64, rows, cols / 64}, strides[2] = {cols * 2, 128};
    cuuint32_t box[3] = {64, br, nb}, es[3] = {1, 1, 1};
    fn(m, CU_TENSOR_MAP_DATA_TYPE_BFLOAT16, 3, const_cast<void*>(p), dims, strides, box, es, CU_TENSOR_MAP_INTERLEAVE_NONE,
       CU_TENSOR_MAP_SWIZZLE_128B, CU_TENSOR_MAP_L2_PROMOTION_L2_256B, CU_TENSOR_MAP_FLOAT_OOB_FILL_NONE);
}

}

extern "C" void kernel_launch(void* const* d_in, const int* in_sizes, int n_in, void* d_out, int out_size) {
    static EncodeFn fn = nullptr;
    if (!fn) {
        void* f = nullptr;
        cudaDriverEntryPointQueryResult st;
        cudaGetDriverEntryPoint("cuTensorMapEncodeTiled", &f, cudaEnableDefault, &st);
        fn = (EncodeFn)f;
        cudaFuncSetAttribute(fused_kernel, cudaFuncAttributeMaxDynamicSharedMemorySize, SMEM_BYTES);
    }
    CUtensorMap ckv, wq, wuk, wuv, wo, wg, wu, wm, xm;
    make_3d(fn, &ckv, d_in[1], 512, 2048, 128, 1);
    make_3d(fn, &xm, d_in[0], 512, 2048, 64);
    make_3d(fn, &wq, d_in[2], 4096, 512, 128, 1);
    make_3d(fn, &wuk, d_in[3], 4096, 512);
    make_3d(fn, &wuv, d_in[4], 4096, 512);
    make_3d(fn, &wo, d_in[5], 512, 4096);
    make_2d(fn, &wg, d_in[8], 1792, 512, 16, 256);
    make_2d(fn, &wu, d_in[9], 1792, 512, 16, 256);
    make_2d(fn, &wm, d_in[12], 3072, 512, 256, 64);
    Params p;
    p.x = (const bf16*)d_in[0];
    p.ckv = (const bf16*)d_in[1];
    p.wo = (const bf16*)d_in[5];
    p.wr = (const bf16*)d_in[7];
    p.wdown = (const bf16*)d_in[10];
    p.c = (const bf16*)d_in[11];
    p.out = (bf16*)d_out;
    p.zero = 0;
    fused_kernel<<<NCTA + NSPARE, 384, SMEM_BYTES>>>(ckv, wq, wuk, wuv, wo, wg, wu, wm, xm, p);
}
```

```cpp
#include <cuda.h>
#include <cuda_bf16.h>
#include <cuda_runtime.h>
#include <stdint.h>
#include <stdio.h>

namespace {

typedef __nv_bfloat16 bf16;
typedef unsigned long long u64;

constexpr int NCTA = 128, NSPARE = 4;
constexpr int SLOT = 32768;
constexpr int SM_BAR = 7 * SLOT;
constexpr int BAR_FULL = SM_BAR;
constexpr int BAR_EMPTY = BAR_FULL + 8 * 7;
constexpr int BAR_DONE = BAR_EMPTY + 8 * 7;
constexpr int BAR_FLAG = BAR_DONE + 8 * 9;
constexpr int BAR_PF = BAR_FLAG + 8 * 9;
constexpr int BAR_END = BAR_PF + 8;
constexpr int BAR_BEST = BAR_END + 8;
constexpr int SM_EP = BAR_END + 24;
constexpr int SM_RED = SM_BAR + 384;
constexpr int SM_TAB = SM_BAR + 1024;
constexpr int SMEM_BYTES = SM_BAR + 3072;
constexpr int NFFN = 112;
#define HINT 479
constexpr u64 L2_NORMAL = 0x1000000000000000ull, L2_FIRST = 0x12F0000000000000ull;
#define PFA 8
#define PFB 6
#define UNR 1
#define POLL_NS 50
#define MSPLIT 13
#define SF 3
#define NSH 1
#define XPF 2
#define TF 1
#define KSLEEP 150
#define YSLEEP 50
#define YPRE 150
#define SSLEEP 50
#define SPRE 0
#define PSLEEP 100
#define CSLEEP 0
#define SPEC 24
#define OMAP 2
#define KVG 7
#define EARLY 7
constexpr uint32_t SPIN_LIMIT = 1u << 22;
constexpr uint32_t ONE2 = 0x3f803f80u;

struct Sync {
    uint32_t cnt[16 * 8 * 8];
    uint32_t ctxcnt[16 * 32];
    uint32_t epoch[32];
};

__device__ __align__(1024) uint8_t g_KV[16 * 16 * 2 * SLOT];
__device__ __align__(1024) uint8_t g_ctx[16 * 32 * SLOT];
__device__ __align__(1024) uint8_t g_h[16 * 4 * SLOT];
constexpr int OB = 1216, OB_STAT = 1024, OB_Y = 1088;
__device__ __align__(1024) uint4 g_out[128 * OB];
__device__ __align__(1024) bf16 g_mod[3072];
__device__ __align__(1024) uint32_t g_mod1[1024];
__device__ __align__(1024) uint4 g_cand[128 * 192];
__device__ __align__(1024) uint32_t g_key[4 * 128];
__device__ __align__(1024) uint8_t g_wf[NFFN * SLOT];
__device__ __align__(1024) Sync g_sync;
#define TS(i)

#define TT(i)
#define PT()

struct Params {
    const bf16 *x, *ckv, *wo, *wr, *wdown, *c;
    bf16* out;
    int zero;
};

__device__ __forceinline__ void mbar_init(uint32_t bar, uint32_t cnt) {
    asm volatile("mbarrier.init.shared::cta.b64 [%0], %1;" ::"r"(bar), "r"(cnt) : "memory");
}
__device__ __forceinline__ void mbar_wait(uint32_t bar, uint32_t parity) {
    asm volatile("{\n.reg .pred p;\nL_%=:\nmbarrier.try_wait.parity.shared::cta.b64 p, [%0], %1;\n@!p bra L_%=;\n}" ::"r"(bar), "r"(parity) : "memory");
}
__device__ __forceinline__ void mbar_sleep(uint32_t bar) {
    if ((threadIdx.x & 31) == 0)
        asm volatile("{\n.reg .pred p;\nL_%=:\nmbarrier.try_wait.parity.shared::cta.b64 p, [%0], 0, 100000;\n@!p bra L_%=;\n}" ::"r"(bar) : "memory");
    __syncwarp();
}
__device__ __forceinline__ void mbar_watch(uint32_t bar, uint32_t parity) {
    asm volatile("{\n.reg .pred p;\n.reg .u32 n;\nmov.u32 n, 0;\n"
                 "L_%=:\nmbarrier.try_wait.parity.shared::cta.b64 p, [%0], %1;\n@p bra D_%=;\n"
                 "add.u32 n, n, 1;\nsetp.lt.u32 p, n, %2;\n@p bra L_%=;\ntrap;\nD_%=:\n}"
                 ::"r"(bar), "r"(parity), "n"(SPIN_LIMIT) : "memory");
}
__device__ __forceinline__ void step_watch(uint32_t a, uint32_t step) {
    asm volatile("{\n.reg .pred p;\n.reg .u32 n, v;\nmov.u32 n, 0;\n"
                 "L_%=:\nld.volatile.shared.u32 v, [%0];\nsetp.ge.u32 p, v, %1;\n@p bra D_%=;\nnanosleep.u32 400;\n"
                 "add.u32 n, n, 1;\nsetp.lt.u32 p, n, %2;\n@p bra L_%=;\ntrap;\nD_%=:\n}"
                 ::"r"(a), "r"(step), "n"(SPIN_LIMIT) : "memory");
}
__device__ __forceinline__ void mbar_arrive_if(uint32_t bar, bool on) {
    asm volatile("{\n.reg .pred p;\nsetp.ne.s32 p, %1, 0;\n@p mbarrier.arrive.shared::cta.b64 _, [%0];\n}" ::"r"(bar), "r"((int)on) : "memory");
}
__device__ __forceinline__ void tma2d(uint32_t dst, const CUtensorMap* m, int c0, int c1, uint32_t bar, bool first) {
    asm volatile("{\n.reg .pred p;\nelect.sync _|p, 0xffffffff;\n"
                 "@p cp.async.bulk.tensor.2d.shared::cluster.global.mbarrier::complete_tx::bytes.L2::cache_hint [%0], [%1, {%3, %4}], [%2], %5;\n}"
                 ::"r"(dst), "l"(m), "r"(bar), "r"(c0), "r"(c1), "l"(first ? L2_FIRST : L2_NORMAL) : "memory");
}
__device__ __forceinline__ void tma3d_prefetch(const CUtensorMap* m, int row, int cb) {
    asm volatile("{\n.reg .pred p;\nelect.sync _|p, 0xffffffff;\n@p cp.async.bulk.prefetch.tensor.3d.L2.global [%0, {%1, %2, %3}];\n}"
                 ::"l"(m), "r"(0), "r"(row), "r"(cb) : "memory");
}
__device__ __forceinline__ void l2_prefetch(const void* p, uint32_t bytes) {
    asm volatile("{\n.reg .pred p;\nelect.sync _|p, 0xffffffff;\n@p cp.async.bulk.prefetch.L2.global [%0], %1;\n}" ::"l"(p), "r"(bytes) : "memory");
}
__device__ __forceinline__ void bulk_store(void* dst, uint32_t src, uint32_t bytes, bool first) {
    asm volatile("{\n.reg .pred p;\nelect.sync _|p, 0xffffffff;\n@p cp.async.bulk.global.shared::cta.bulk_group.L2::cache_hint [%0], [%1], %2, %3;\n}"
                 ::"l"(dst), "r"(src), "r"(bytes), "l"(first ? L2_FIRST : L2_NORMAL) : "memory");
}
__device__ __forceinline__ void flag_wait(const uint32_t* f, uint32_t target) {
    asm volatile("{\n.reg .pred p;\n.reg .u32 v;\n"
                 "L_%=:\nld.acquire.gpu.global.u32 v, [%0];\nsub.u32 v, v, %1;\nsetp.lt.s32 p, v, 0;\n@p nanosleep.u32 100;\n@p bra L_%=;\n}"
                 ::"l"(f), "r"(target) : "memory");
}
__device__ __forceinline__ uint4 ld_poll(const uint4* p) {
    uint4 v;
    asm volatile("{\n.reg .b128 t;\nld.relaxed.gpu.global.b128 t, [%4];\nmov.b128 {%0, %1, %2, %3}, t;\n}"
                 : "=r"(v.x), "=r"(v.y), "=r"(v.z), "=r"(v.w) : "l"(p) : "memory");
    return v;
}
__device__ __forceinline__ void st_pub(uint4* p, uint4 v, bool on) {
    asm volatile("{\n.reg .pred p;\n.reg .b128 t;\nsetp.ne.s32 p, %5, 0;\nmov.b128 t, {%1, %2, %3, %4};\n@p st.relaxed.gpu.global.b128 [%0], t;\n}"
                 ::"l"(p), "r"(v.x), "r"(v.y), "r"(v.z), "r"(v.w), "r"((int)on) : "memory");
}
__device__ __forceinline__ void st_pub(uint32_t* p, uint32_t v, bool on) {
    asm volatile("{\n.reg .pred p;\nsetp.ne.s32 p, %2, 0;\n@p st.relaxed.gpu.global.u32 [%0], %1;\n}" ::"l"(p), "r"(v), "r"((int)on) : "memory");
}
__device__ __forceinline__ void flag_add(uint32_t* p) {
    asm volatile("red.release.gpu.global.add.u32 [%0], 1;" ::"l"(p) : "memory");
}
__device__ __forceinline__ uint32_t lds32(uint32_t a) {
    uint32_t v;
    asm volatile("ld.shared.u32 %0, [%1];" : "=r"(v) : "r"(a) : "memory");
    return v;
}
__device__ __forceinline__ uint4 lds128(uint32_t a) {
    uint4 v;
    asm volatile("ld.shared.v4.u32 {%0, %1, %2, %3}, [%4];" : "=r"(v.x), "=r"(v.y), "=r"(v.z), "=r"(v.w) : "r"(a) : "memory");
    return v;
}
__device__ __forceinline__ void sched_fence(uint32_t& v, uint32_t z) {
    uint32_t ck;
    asm volatile("mov.u32 %0, %%clock;" : "=r"(ck)::"memory");
    v ^= ck & z;
}
__device__ __forceinline__ void fence_async_global() { asm volatile("fence.proxy.async.global;" ::: "memory"); }
__device__ __forceinline__ void fence_async_smem() { asm volatile("fence.proxy.async.shared::cta;" ::: "memory"); }
__device__ __forceinline__ void bar_sync(int id, int n) { asm volatile("bar.sync %0, %1;" ::"r"(id), "r"(n) : "memory"); }
__device__ __forceinline__ void bar_arrive(int id, int n) { asm volatile("bar.arrive %0, %1;" ::"r"(id), "r"(n) : "memory"); }
__device__ __forceinline__ void wg_fence() { asm volatile("wgmma.fence.sync.aligned;" ::: "memory"); }
__device__ __forceinline__ void wg_commit() { asm volatile("wgmma.commit_group.sync.aligned;" ::: "memory"); }
template <int N> __device__ __forceinline__ void wg_wait() { asm volatile("wgmma.wait_group.sync.aligned %0;" ::"n"(N) : "memory"); }
template <int N> __device__ __forceinline__ void reg_fence(float (&d)[N]) {
#pragma unroll
    for (int i = 0; i < N; i++) asm volatile("" : "+f"(d[i])::"memory");
}
template <int N> __device__ __forceinline__ void reg_fence(uint32_t (&d)[N]) {
#pragma unroll
    for (int i = 0; i < N; i++) asm volatile("" : "+r"(d[i])::"memory");
}
__device__ __forceinline__ uint32_t desc_k(uint32_t a) { return ((a & 0x3ffff) >> 4) | (1u << 16); }
__device__ __forceinline__ uint32_t desc_mn(uint32_t a) { return ((a & 0x3ffff) >> 4) | (1024u << 16); }

template <int TB>
__device__ __forceinline__ void wgmma_ss128(float (&d)[64], uint32_t da, uint32_t db, int acc, uint32_t ha = 0x40000040u, uint32_t hb = 0x40000040u) {
    asm volatile("{\n.reg .pred p;\n.reg .b64 a, b;\nsetp.ne.b32 p, %66, 0;\nmov.b64 a, {%64, %68};\nmov.b64 b, {%65, %69};\n"
        "wgmma.mma_async.sync.aligned.m64n128k16.f32.bf16.bf16 {%0, %1, %2, %3, %4, %5, %6, %7, %8, %9, %10, %11, %12, %13, %14, %15, %16, %17, %18, %19, %20, %21, %22, %23, %24, %25, %26, %27, %28, %29, %30, %31, %32, %33, %34, %35, %36, %37, %38, %39, %40, %41, %42, %43, %44, %45, %46, %47, %48, %49, %50, %51, %52, %53, %54, %55, %56, %57, %58, %59, %60, %61, %62, %63}, a, b, p, 1, 1, 0, %67;\n}"
        : "+f"(d[0]), "+f"(d[1]), "+f"(d[2]), "+f"(d[3]), "+f"(d[4]), "+f"(d[5]), "+f"(d[6]), "+f"(d[7]), "+f"(d[8]), "+f"(d[9]), "+f"(d[10]), "+f"(d[11]), "+f"(d[12]), "+f"(d[13]), "+f"(d[14]), "+f"(d[15]), "+f"(d[16]), "+f"(d[17]), "+f"(d[18]), "+f"(d[19]), "+f"(d[20]), "+f"(d[21]), "+f"(d[22]), "+f"(d[23]), "+f"(d[24]), "+f"(d[25]), "+f"(d[26]), "+f"(d[27]), "+f"(d[28]), "+f"(d[29]), "+f"(d[30]), "+f"(d[31]), "+f"(d[32]), "+f"(d[33]), "+f"(d[34]), "+f"(d[35]), "+f"(d[36]), "+f"(d[37]), "+f"(d[38]), "+f"(d[39]), "+f"(d[40]), "+f"(d[41]), "+f"(d[42]), "+f"(d[43]), "+f"(d[44]), "+f"(d[45]), "+f"(d[46]), "+f"(d[47]), "+f"(d[48]), "+f"(d[49]), "+f"(d[50]), "+f"(d[51]), "+f"(d[52]), "+f"(d[53]), "+f"(d[54]), "+f"(d[55]), "+f"(d[56]), "+f"(d[57]), "+f"(d[58]), "+f"(d[59]), "+f"(d[60]), "+f"(d[61]), "+f"(d[62]), "+f"(d[63])
        : "r"(da), "r"(db), "r"(acc), "n"(TB), "r"(ha), "r"(hb));
}
template <int TB>
__device__ __forceinline__ void wgmma_ss128_init(float (&d)[64], uint32_t da, uint32_t db, uint32_t ha = 0x40000040u, uint32_t hb = 0x40000040u) {
    asm volatile("{\n.reg .pred p;\n.reg .b64 a, b;\nsetp.ne.b32 p, 0, 0;\nmov.b64 a, {%64, %67};\nmov.b64 b, {%65, %68};\n"
        "wgmma.mma_async.sync.aligned.m64n128k16.f32.bf16.bf16 {%0, %1, %2, %3, %4, %5, %6, %7, %8, %9, %10, %11, %12, %13, %14, %15, %16, %17, %18, %19, %20, %21, %22, %23, %24, %25, %26, %27, %28, %29, %30, %31, %32, %33, %34, %35, %36, %37, %38, %39, %40, %41, %42, %43, %44, %45, %46, %47, %48, %49, %50, %51, %52, %53, %54, %55, %56, %57, %58, %59, %60, %61, %62, %63}, a, b, p, 1, 1, 0, %66;\n}"
        : "=f"(d[0]), "=f"(d[1]), "=f"(d[2]), "=f"(d[3]), "=f"(d[4]), "=f"(d[5]), "=f"(d[6]), "=f"(d[7]), "=f"(d[8]), "=f"(d[9]), "=f"(d[10]), "=f"(d[11]), "=f"(d[12]), "=f"(d[13]), "=f"(d[14]), "=f"(d[15]), "=f"(d[16]), "=f"(d[17]), "=f"(d[18]), "=f"(d[19]), "=f"(d[20]), "=f"(d[21]), "=f"(d[22]), "=f"(d[23]), "=f"(d[24]), "=f"(d[25]), "=f"(d[26]), "=f"(d[27]), "=f"(d[28]), "=f"(d[29]), "=f"(d[30]), "=f"(d[31]), "=f"(d[32]), "=f"(d[33]), "=f"(d[34]), "=f"(d[35]), "=f"(d[36]), "=f"(d[37]), "=f"(d[38]), "=f"(d[39]), "=f"(d[40]), "=f"(d[41]), "=f"(d[42]), "=f"(d[43]), "=f"(d[44]), "=f"(d[45]), "=f"(d[46]), "=f"(d[47]), "=f"(d[48]), "=f"(d[49]), "=f"(d[50]), "=f"(d[51]), "=f"(d[52]), "=f"(d[53]), "=f"(d[54]), "=f"(d[55]), "=f"(d[56]), "=f"(d[57]), "=f"(d[58]), "=f"(d[59]), "=f"(d[60]), "=f"(d[61]), "=f"(d[62]), "=f"(d[63])
        : "r"(da), "r"(db), "n"(TB), "r"(ha), "r"(hb));
}
template <int TB>
__device__ __forceinline__ void wgmma_ss64(float (&d)[32], uint32_t da, uint32_t db, int acc, uint32_t ha = 0x40000040u, uint32_t hb = 0x40000040u) {
    asm volatile("{\n.reg .pred p;\n.reg .b64 a, b;\nsetp.ne.b32 p, %34, 0;\nmov.b64 a, {%32, %36};\nmov.b64 b, {%33, %37};\n"
        "wgmma.mma_async.sync.aligned.m64n64k16.f32.bf16.bf16 {%0, %1, %2, %3, %4, %5, %6, %7, %8, %9, %10, %11, %12, %13, %14, %15, %16, %17, %18, %19, %20, %21, %22, %23, %24, %25, %26, %27, %28, %29, %30, %31}, a, b, p, 1, 1, 0, %35;\n}"
        : "+f"(d[0]), "+f"(d[1]), "+f"(d[2]), "+f"(d[3]), "+f"(d[4]), "+f"(d[5]), "+f"(d[6]), "+f"(d[7]), "+f"(d[8]), "+f"(d[9]), "+f"(d[10]), "+f"(d[11]), "+f"(d[12]), "+f"(d[13]), "+f"(d[14]), "+f"(d[15]), "+f"(d[16]), "+f"(d[17]), "+f"(d[18]), "+f"(d[19]), "+f"(d[20]), "+f"(d[21]), "+f"(d[22]), "+f"(d[23]), "+f"(d[24]), "+f"(d[25]), "+f"(d[26]), "+f"(d[27]), "+f"(d[28]), "+f"(d[29]), "+f"(d[30]), "+f"(d[31])
        : "r"(da), "r"(db), "r"(acc), "n"(TB), "r"(ha), "r"(hb));
}
template <int TB>
__device__ __forceinline__ void wgmma_ss64_init(float (&d)[32], uint32_t da, uint32_t db, uint32_t ha = 0x40000040u, uint32_t hb = 0x40000040u) {
    asm volatile("{\n.reg .pred p;\n.reg .b64 a, b;\nsetp.ne.b32 p, 0, 0;\nmov.b64 a, {%32, %35};\nmov.b64 b, {%33, %36};\n"
        "wgmma.mma_async.sync.aligned.m64n64k16.f32.bf16.bf16 {%0, %1, %2, %3, %4, %5, %6, %7, %8, %9, %10, %11, %12, %13, %14, %15, %16, %17, %18, %19, %20, %21, %22, %23, %24, %25, %26, %27, %28, %29, %30, %31}, a, b, p, 1, 1, 0, %34;\n}"
        : "=f"(d[0]), "=f"(d[1]), "=f"(d[2]), "=f"(d[3]), "=f"(d[4]), "=f"(d[5]), "=f"(d[6]), "=f"(d[7]), "=f"(d[8]), "=f"(d[9]), "=f"(d[10]), "=f"(d[11]), "=f"(d[12]), "=f"(d[13]), "=f"(d[14]), "=f"(d[15]), "=f"(d[16]), "=f"(d[17]), "=f"(d[18]), "=f"(d[19]), "=f"(d[20]), "=f"(d[21]), "=f"(d[22]), "=f"(d[23]), "=f"(d[24]), "=f"(d[25]), "=f"(d[26]), "=f"(d[27]), "=f"(d[28]), "=f"(d[29]), "=f"(d[30]), "=f"(d[31])
        : "r"(da), "r"(db), "n"(TB), "r"(ha), "r"(hb));
}
__device__ __forceinline__ void wgmma_rs128(float (&d)[64], uint32_t a0, uint32_t a1, uint32_t a2, uint32_t a3, uint32_t db, int acc, uint32_t hb = 0x40000040u) {
    asm volatile("{\n.reg .pred p;\n.reg .b64 b;\nsetp.ne.b32 p, %69, 0;\nmov.b64 b, {%68, %70};\n"
        "wgmma.mma_async.sync.aligned.m64n128k16.f32.bf16.bf16 {%0, %1, %2, %3, %4, %5, %6, %7, %8, %9, %10, %11, %12, %13, %14, %15, %16, %17, %18, %19, %20, %21, %22, %23, %24, %25, %26, %27, %28, %29, %30, %31, %32, %33, %34, %35, %36, %37, %38, %39, %40, %41, %42, %43, %44, %45, %46, %47, %48, %49, %50, %51, %52, %53, %54, %55, %56, %57, %58, %59, %60, %61, %62, %63}, {%64, %65, %66, %67}, b, p, 1, 1, 1;\n}"
        : "+f"(d[0]), "+f"(d[1]), "+f"(d[2]), "+f"(d[3]), "+f"(d[4]), "+f"(d[5]), "+f"(d[6]), "+f"(d[7]), "+f"(d[8]), "+f"(d[9]), "+f"(d[10]), "+f"(d[11]), "+f"(d[12]), "+f"(d[13]), "+f"(d[14]), "+f"(d[15]), "+f"(d[16]), "+f"(d[17]), "+f"(d[18]), "+f"(d[19]), "+f"(d[20]), "+f"(d[21]), "+f"(d[22]), "+f"(d[23]), "+f"(d[24]), "+f"(d[25]), "+f"(d[26]), "+f"(d[27]), "+f"(d[28]), "+f"(d[29]), "+f"(d[30]), "+f"(d[31]), "+f"(d[32]), "+f"(d[33]), "+f"(d[34]), "+f"(d[35]), "+f"(d[36]), "+f"(d[37]), "+f"(d[38]), "+f"(d[39]), "+f"(d[40]), "+f"(d[41]), "+f"(d[42]), "+f"(d[43]), "+f"(d[44]), "+f"(d[45]), "+f"(d[46]), "+f"(d[47]), "+f"(d[48]), "+f"(d[49]), "+f"(d[50]), "+f"(d[51]), "+f"(d[52]), "+f"(d[53]), "+f"(d[54]), "+f"(d[55]), "+f"(d[56]), "+f"(d[57]), "+f"(d[58]), "+f"(d[59]), "+f"(d[60]), "+f"(d[61]), "+f"(d[62]), "+f"(d[63])
        : "r"(a0), "r"(a1), "r"(a2), "r"(a3), "r"(db), "r"(acc), "r"(hb));
}

__device__ __forceinline__ uint32_t pack2(float lo, float hi) {
    uint32_t r;
    asm("cvt.rn.bf16x2.f32 %0, %1, %2;" : "=r"(r) : "f"(hi), "f"(lo));
    return r;
}
__device__ __forceinline__ float bf_lo(uint32_t v) { return __uint_as_float(v << 16); }
__device__ __forceinline__ float bf_hi(uint32_t v) { return __uint_as_float(v & 0xffff0000u); }
__device__ __forceinline__ float rbf(float v) { return bf_lo(pack2(v, v)); }
__device__ __forceinline__ uint32_t badd(uint32_t a, uint32_t b) {
    uint32_t r;
    asm("add.rn.bf16x2 %0, %1, %2;" : "=r"(r) : "r"(a), "r"(b));
    return r;
}
__device__ __forceinline__ uint32_t bsub(uint32_t a, uint32_t b) {
    uint32_t r;
    asm("sub.rn.bf16x2 %0, %1, %2;" : "=r"(r) : "r"(a), "r"(b));
    return r;
}
__device__ __forceinline__ uint32_t bmul(uint32_t a, uint32_t b) {
    uint32_t r;
    asm("mul.rn.bf16x2 %0, %1, %2;" : "=r"(r) : "r"(a), "r"(b));
    return r;
}
__device__ __forceinline__ uint32_t ln_apply(uint32_t x, uint32_t mb, float rs, uint32_t scale, uint32_t shift) {
    const uint32_t d = bsub(x, mb);
    return badd(bmul(pack2(bf_lo(d) * rs, bf_hi(d) * rs), scale), shift);
}
__device__ __forceinline__ float ex2(float v) {
    float r;
    asm("ex2.approx.ftz.f32 %0, %1;" : "=f"(r) : "f"(v));
    return r;
}
__device__ __forceinline__ float rcp(float v) {
    float r;
    asm("rcp.approx.ftz.f32 %0, %1;" : "=f"(r) : "f"(v));
    return r;
}
__device__ __forceinline__ float sqrt_fast(float v) {
    float r;
    asm("sqrt.approx.ftz.f32 %0, %1;" : "=f"(r) : "f"(v));
    return r;
}
__device__ __forceinline__ float ln_rstd(float var) { return rcp(rbf(sqrt_fast(rbf(rbf(var) + 1e-5f)))); }
__device__ __forceinline__ float sigmoid(float v) { return rcp(1.f + ex2(-1.4426950408889634f * v)); }
__device__ __forceinline__ float quad_sum(float v) {
    v += __shfl_xor_sync(0xffffffffu, v, 1);
    return v + __shfl_xor_sync(0xffffffffu, v, 2);
}

constexpr uint32_t HI_128 = 0x40000040u, HI_IMG = 0x80000080u, HI_Q = 0x80000040u;
template <int M, int RH>
__device__ __forceinline__ uint4 img_pack(const float (&d)[64], float s) {
    uint4 v;
    v.x = pack2(d[16 * M + 2 * RH] * s, d[16 * M + 2 * RH + 1] * s);
    v.y = pack2(d[16 * M + 4 + 2 * RH] * s, d[16 * M + 5 + 2 * RH] * s);
    v.z = pack2(d[16 * M + 8 + 2 * RH] * s, d[16 * M + 9 + 2 * RH] * s);
    v.w = pack2(d[16 * M + 12 + 2 * RH] * s, d[16 * M + 13 + 2 * RH] * s);
    return v;
}
template <int M>
__device__ __forceinline__ void img_store_global(uint8_t* img, uint32_t toff, const float (&d)[64], float s0, float s1) {
    uint4* p = reinterpret_cast<uint4*>(img + toff) + M * 32;
    p[0] = img_pack<M, 0>(d, s0);
    p[128] = img_pack<M, 1>(d, s1);
}
__device__ __forceinline__ void sts128(uint32_t a, uint4 v) {
    asm volatile("st.shared.v4.b32 [%0], {%1, %2, %3, %4};" ::"r"(a), "r"(v.x), "r"(v.y), "r"(v.z), "r"(v.w) : "memory");
}
constexpr float SM_C = 0.08838834764831845f * 1.4426950408889634f;
__device__ __forceinline__ float pack2f(float lo, float hi) {
    float r;
    asm("{\n.reg .b32 t;\ncvt.rn.bf16x2.f32 t, %1, %2;\nmov.b32 %0, t;\n}" : "=f"(r) : "f"(hi), "f"(lo));
    return r;
}
template <int M, bool SCALE, bool PARK>
__device__ __forceinline__ void pack_group(float (&d)[64], float (&v)[8], float s0, float s1) {
#pragma unroll
    for (int i = 0; i < 8; i++) {
        const int k = 16 * M + 4 * (i & 3) + 2 * (i >> 2);
        v[i] = SCALE ? pack2f(d[k] * (i < 4 ? s0 : s1), d[k + 1] * (i < 4 ? s0 : s1)) : pack2f(d[k], d[k + 1]);
        if (PARK && M > 0) d[16 * (M > 0 ? M - 1 : 0) + i] = v[i];
    }
}
__device__ __forceinline__ uint32_t q_off(uint32_t toff) { return (((toff >> 1) & ~2047u) ^ 8192) + (toff & 511); }
template <int M, bool PARK>
__device__ __forceinline__ void ctx_store_part(float4* p, float (&d)[64], float i0, float i1) {
    float v[8];
    pack_group<M, true, PARK>(d, v, i0, i1);
    p[M * 32] = make_float4(v[0], v[1], v[2], v[3]);
    p[M * 32 + 128] = make_float4(v[4], v[5], v[6], v[7]);
}
template <bool PARK>
__device__ __forceinline__ void ctx_store(uint8_t* img, uint32_t toff, float (&o)[64], float l0, float l1) {
    const float i0 = rcp(quad_sum(l0)), i1 = rcp(quad_sum(l1));
    float4* p = reinterpret_cast<float4*>(img + toff);
    ctx_store_part<0, PARK>(p, o, i0, i1); ctx_store_part<1, PARK>(p, o, i0, i1); ctx_store_part<2, PARK>(p, o, i0, i1); ctx_store_part<3, PARK>(p, o, i0, i1);
}

template <int M>
__device__ __forceinline__ void tile_store_part(float4* p, uint32_t a, float (&d)[64], float i0, float i1, int ctx) {
    float v[8];
    pack_group<M, true, true>(d, v, i0, i1);
#pragma unroll
    for (int h = 0; h < 2; h++)
        asm volatile("{\n.reg .pred p;\nsetp.ne.s32 p, %6, 0;\n@p st.global.v4.f32 [%0], {%2, %3, %4, %5};\n@!p st.shared.v4.f32 [%1], {%2, %3, %4, %5};\n}"
                     ::"l"(p + M * 32 + h * 128), "r"(a + (M >> 1) * 16384 + (M & 1) * 512 + h * 1024),
                     "f"(v[4 * h]), "f"(v[4 * h + 1]), "f"(v[4 * h + 2]), "f"(v[4 * h + 3]), "r"(ctx) : "memory");
}
__device__ __forceinline__ void tile_store(uint8_t* img, uint32_t a, uint32_t toff, float (&d)[64], float i0, float i1, int ctx) {
    float4* p = reinterpret_cast<float4*>(img + toff);
    a += q_off(toff);
    tile_store_part<0>(p, a, d, i0, i1, ctx); tile_store_part<1>(p, a, d, i0, i1, ctx);
    tile_store_part<2>(p, a, d, i0, i1, ctx); tile_store_part<3>(p, a, d, i0, i1, ctx);
}

__device__ __forceinline__ void slot_wait(uint32_t bars, uint32_t& ph, uint32_t slot) {
    mbar_wait(bars + 8 * slot, (ph >> slot) & 1);
    ph ^= 1u << slot;
}
__device__ __forceinline__ void release_if(uint32_t eb, uint32_t slot, bool on) {
    asm volatile("{\n.reg .pred p;\nsetp.ne.s32 p, %1, 0;\n@p mbarrier.arrive.shared::cluster.b64 _, [%0];\n}" ::"r"(eb + 8 * slot), "r"((int)on) : "memory");
}
__device__ __forceinline__ void slot_acquire(uint32_t sb, uint32_t& ph, uint32_t slot) {
    slot_wait(sb + BAR_EMPTY, ph, slot);
    asm volatile("{\n.reg .pred p;\nelect.sync _|p, 0xffffffff;\n@p mbarrier.arrive.expect_tx.shared::cta.b64 _, [%0], 32768;\n}"
                 ::"r"(sb + BAR_FULL + 8 * slot) : "memory");
}
__device__ __forceinline__ void load_bulk(uint32_t sb, uint32_t slot, uint32_t off, const void* src, uint32_t bytes, bool both, bool first) {
    if (both)
        asm volatile("{\n.reg .pred p;\nelect.sync _|p, 0xffffffff;\n"
                     "@p cp.async.bulk.shared::cluster.global.mbarrier::complete_tx::bytes.multicast::cluster.L2::cache_hint [%0], [%1], %5, [%2], %4, %3;\n}"
                     ::"r"(sb + slot * SLOT + off), "l"(src), "r"(sb + BAR_FULL + 8 * slot), "l"(first ? L2_FIRST : L2_NORMAL), "h"((uint16_t)3),
                     "r"(bytes) : "memory");
    else
        asm volatile("{\n.reg .pred p;\nelect.sync _|p, 0xffffffff;\n"
                     "@p cp.async.bulk.shared::cluster.global.mbarrier::complete_tx::bytes.L2::cache_hint [%0], [%1], %4, [%2], %3;\n}"
                     ::"r"(sb + slot * SLOT + off), "l"(src), "r"(sb + BAR_FULL + 8 * slot), "l"(first ? L2_FIRST : L2_NORMAL), "r"(bytes) : "memory");
}
__device__ __forceinline__ void load_tile(uint32_t sb, uint32_t slot, uint32_t off, const CUtensorMap* m, int row, int cb, bool both, bool first) {
    if (both)
        asm volatile("{\n.reg .pred p;\nelect.sync _|p, 0xffffffff;\n"
                     "@p cp.async.bulk.tensor.3d.shared::cluster.global.mbarrier::complete_tx::bytes.multicast::cluster.L2::cache_hint [%0], [%1, {%3, %4, %5}], [%2], %7, %6;\n}"
                     ::"r"(sb + slot * SLOT + off), "l"(m), "r"(sb + BAR_FULL + 8 * slot), "r"(0), "r"(row), "r"(cb),
                     "l"(first ? L2_FIRST : L2_NORMAL), "h"((uint16_t)3) : "memory");
    else
        asm volatile("{\n.reg .pred p;\nelect.sync _|p, 0xffffffff;\n"
                     "@p cp.async.bulk.tensor.3d.shared::cluster.global.mbarrier::complete_tx::bytes.L2::cache_hint [%0], [%1, {%3, %4, %5}], [%2], %6;\n}"
                     ::"r"(sb + slot * SLOT + off), "l"(m), "r"(sb + BAR_FULL + 8 * slot), "r"(0), "r"(row), "r"(cb),
                     "l"(first ? L2_FIRST : L2_NORMAL) : "memory");
}
__device__ __forceinline__ uint32_t ring_next(uint32_t r) { return r == 4 ? 0 : r + 1; }
__device__ __forceinline__ uint32_t w_table(int hp) { return hp ? 0x3104u : 0x4210u; }
__device__ __forceinline__ uint32_t a_table(int hp) { return hp ? 0x625u : 0x635u; }
__device__ __forceinline__ uint32_t a_next(uint32_t& t) {
    const uint32_t s = t & 15;
    t = (t >> 4) | (s << 8);
    return s;
}
constexpr uint32_t O_TABLE = 0x1604235u;
__device__ __forceinline__ uint32_t o_next(uint32_t& t) {
    const uint32_t s = t & 15;
    t = (t >> 4) | (s << 24);
    return s;
}
__device__ __forceinline__ int o_head(int i, int kh) { return i < 16 ? 4 * (i & 7) + 2 * (kh ^ 1) + (i >> 3) : 29 + 2 * kh; }

template <bool INIT>
__device__ __forceinline__ void gemm_issue(float (&d)[64], uint32_t a, uint32_t b, int acc, bool img) {
    const uint32_t ha = img ? HI_IMG : HI_128, o2 = img ? 32 : 4, o4 = img ? 64 : 1024;
    wg_fence();
#pragma unroll
    for (int k = 0; k < 8; k++) {
        if (INIT && k == 0) wgmma_ss128_init<1>(d, a, b, ha);
        else wgmma_ss128<1>(d, a + (k >> 2) * o4 + ((k >> 1) & 1) * o2 + (k & 1) * 2, b + k * 128, k ? 1 : acc, ha);
    }
    wg_commit();
}

template <bool ODD>
__device__ __forceinline__ bool proj_tile(float (&acc)[64], float (&prev)[64], int t, int q0, uint32_t sb, int wg, uint32_t eb, bool rel, uint32_t& fph,
                                          uint32_t wtab, uint32_t& atab, uint8_t* prev_img, uint32_t toff, float s0, float s1,
                                          uint32_t (&v)[32]) {
    const uint32_t a0 = desc_k(sb + (wg ^ (ODD && t == 5)) * 8192), b0 = desc_mn(sb);
    constexpr int U = ODD ? UNR : 1;
#pragma unroll U
    for (int q = ODD ? 0 : q0; q < 4; q++) {
        const uint32_t ws = (wtab >> (4 * q)) & 15, as = a_next(atab);
        if (!ODD && t != 2) slot_wait(sb + BAR_FULL, fph, ws);
        slot_wait(sb + BAR_FULL, fph, as);
        if (ODD && q == 2 && t == 5) {
#pragma unroll
            for (int i = 0; i < 8; i++) sts128(sb + 5 * SLOT + q_off(toff) + (i >> 2) * 16384 + (i & 2) * 256 + (i & 1) * 1024, make_uint4(v[4 * i], v[4 * i + 1], v[4 * i + 2], v[4 * i + 3]));
        }
        bar_sync(1 + wg, 256);
        gemm_issue<false>(acc, a0 + as * (SLOT / 16), b0 + ws * (SLOT / 16), q, false);
        bar_arrive(2 - wg, 256);
        wg_wait<1>();
        reg_fence(prev);
        if (ODD && t == 5) {
            if (q == 0) {
#pragma unroll
                for (int i = 0; i < 32; i++) {
                    const int k = 16 * (i >> 3) + 4 * (i & 3) + ((i >> 1) & 2);
                    v[i] = pack2(prev[k], prev[k + 1]);
                }
            }
            if (q == 2) {
                fence_async_smem();
                slot_wait(sb + BAR_FULL, fph, wtab & 15);
                wg_wait<0>();
                release_if(eb, as, rel);
                release_if(eb, ws, rel);
                reg_fence(acc);
                return true;
            }
        } else {
            if (q == 0) img_store_global<0>(prev_img, toff, prev, s0, s1);
            if (q == 1) img_store_global<1>(prev_img, toff, prev, s0, s1);
            if (q == 2) img_store_global<2>(prev_img, toff, prev, s0, s1);
            if (q == 3) img_store_global<3>(prev_img, toff, prev, s0, s1);
        }
        wg_wait<0>();
        release_if(eb, as, rel && !(ODD && (q & 1) && t == 5));
        if (ODD) release_if(eb, ws, rel && t != 1);
    }
    reg_fence(acc);
    return false;
}

__device__ __forceinline__ void qk_issue(float (&s)[64], uint32_t q, uint32_t k) {
    wg_fence();
    wgmma_ss128_init<0>(s, q, k, HI_Q, HI_IMG);
#pragma unroll
    for (int i = 1; i < 8; i++) wgmma_ss128<0>(s, q + (i >> 2) * 1024 + (i & 2) * 16 + (i & 1) * 2, k + (i >> 1) * 32 + (i & 1) * 2, 1, HI_Q, HI_IMG);
    wg_commit();
}
__device__ __forceinline__ void qk_issue(float (&s)[32], uint32_t q, uint32_t k) {
    wg_fence();
    wgmma_ss64_init<0>(s, q, k, HI_Q, HI_IMG);
#pragma unroll
    for (int i = 1; i < 8; i++) wgmma_ss64<0>(s, q + (i >> 2) * 1024 + (i & 2) * 16 + (i & 1) * 2, k + (i >> 1) * 32 + (i & 1) * 2, 1, HI_Q, HI_IMG);
    wg_commit();
}
__device__ __forceinline__ void pv_issue(float (&o)[64], const uint32_t (&p)[32], uint32_t v, int acc, bool half) {
    if (half) {
        asm volatile("// half" ::: "memory");
        wg_fence();
#pragma unroll
        for (int i = 0; i < 4; i++) wgmma_rs128(o, p[4 * i], p[4 * i + 1], p[4 * i + 2], p[4 * i + 3], v + i * 256, i ? 1 : acc, HI_IMG);
        wg_commit();
        asm volatile("// half" ::: "memory");
    } else {
        wg_fence();
#pragma unroll
        for (int i = 0; i < 8; i++) wgmma_rs128(o, p[4 * i], p[4 * i + 1], p[4 * i + 2], p[4 * i + 3], v + i * 256, i ? 1 : acc, HI_IMG);
        wg_commit();
    }
}
__device__ __forceinline__ void tri_mask(float (&s)[64], float x) {
#pragma unroll
    for (int k = 0; k < 16; k++) {
        float b;
        asm("sub.sat.f32 %0, %1, %2;" : "=f"(b) : "f"((float)(8 * (k >> 1) + (k & 1))), "f"(x));
        const int i = 32 + 4 * (k >> 1) + (k & 1);
        asm("fma.rn.f32 %0, %1, 0fFF61B1E6, %0;" : "+f"(s[i]) : "f"(b));
        if (k < 14) asm("fma.rn.f32 %0, %1, 0fFF61B1E6, %0;" : "+f"(s[i + 6]) : "f"(b));
    }
}
__device__ __forceinline__ void tri_mask_copy(float (&s)[64], const float (&h)[32], float x) {
#pragma unroll
    for (int i = 0; i < 32; i++) {
        asm("{\n.reg .pred p;\nsetp.lt.f32 p, %2, %3;\nselp.f32 %0, 0fFF800000, %1, p;\n}"
            : "=f"(s[i]) : "f"(h[i]), "f"(x), "f"((float)(8 * (i >> 2) - 4 * (i & 2) + (i & 1))));
        s[32 + i] = __uint_as_float(0xff800000u);
    }
}
constexpr float SM_HI = 1152921504606846976.f, SM_LO = 1.f / 1152921504606846976.f;
__device__ __forceinline__ bool softmax_unsafe(float t0, float t1, bool first) {
    bool bad = __any_sync(0xffffffffu, fmaxf(t0, t1) > SM_HI);
    if (first) {
        uint32_t a = __ballot_sync(0xffffffffu, t0 >= SM_LO), b = __ballot_sync(0xffffffffu, t1 >= SM_LO);
        a |= a >> 1;
        b |= b >> 1;
        bad |= ((a | (a >> 2)) & (b | (b >> 2)) & 0x11111111u) != 0x11111111u;
    }
    return bad;
}
__device__ __forceinline__ void softmax_shift(float (&s)[64], float d0, float d1) {
#pragma unroll
    for (int i = 0; i < 64; i++) s[i] -= (i & 2) ? d1 : d0;
}
__device__ __forceinline__ void softmax_remax(float (&s)[64], float (&m)[2], bool first, float& a0, float& a1) {
    float m0 = fmaxf(s[0], s[1]), m1 = fmaxf(s[2], s[3]);
#pragma unroll
    for (int k = 1; k < 16; k++) {
        m0 = fmaxf(m0, fmaxf(s[4 * k], s[4 * k + 1]));
        m1 = fmaxf(m1, fmaxf(s[4 * k + 2], s[4 * k + 3]));
    }
    m0 = fmaxf(m0, __shfl_xor_sync(0xffffffffu, m0, 1));
    m1 = fmaxf(m1, __shfl_xor_sync(0xffffffffu, m1, 1));
    m0 = fmaxf(m0, __shfl_xor_sync(0xffffffffu, m0, 2));
    m1 = fmaxf(m1, __shfl_xor_sync(0xffffffffu, m1, 2));
    if (!first) {
        m0 = fmaxf(m0, 0.f);
        m1 = fmaxf(m1, 0.f);
    }
    a0 = first ? 1.f : ex2(-m0);
    a1 = first ? 1.f : ex2(-m1);
    m[0] += m0;
    m[1] += m1;
    softmax_shift(s, m0, m1);
}
template <int J0, int J1>
__device__ __forceinline__ void softmax_exp(const float (&s)[64], uint32_t (&p)[32], float (&t)[4]) {
#pragma unroll
    for (int k = J0; k < J1; k++) {
        const float e0 = ex2(s[4 * k]), e1 = ex2(s[4 * k + 1]), e2 = ex2(s[4 * k + 2]), e3 = ex2(s[4 * k + 3]);
        if (k == 0) { t[0] = e0; t[1] = e1; t[2] = e2; t[3] = e3; }
        else { t[0] += e0; t[1] += e1; t[2] += e2; t[3] += e3; }
        p[2 * k] = pack2(e0, e1);
        p[2 * k + 1] = pack2(e2, e3);
    }
}
__device__ __forceinline__ void fma8(float (&acc)[8], float a, uint4 w) {
    acc[0] = fmaf(a, bf_lo(w.x), acc[0]); acc[1] = fmaf(a, bf_hi(w.x), acc[1]);
    acc[2] = fmaf(a, bf_lo(w.y), acc[2]); acc[3] = fmaf(a, bf_hi(w.y), acc[3]);
    acc[4] = fmaf(a, bf_lo(w.z), acc[4]); acc[5] = fmaf(a, bf_hi(w.z), acc[5]);
    acc[6] = fmaf(a, bf_lo(w.w), acc[6]); acc[7] = fmaf(a, bf_hi(w.w), acc[7]);
}
__device__ __forceinline__ void mma16816(float (&d)[4], const uint32_t* a, uint32_t b0, uint32_t b1) {
    asm("mma.sync.aligned.m16n8k16.row.col.f32.bf16.bf16.f32 {%0, %1, %2, %3}, {%4, %5, %6, %7}, {%8, %9}, {%0, %1, %2, %3};"
        : "+f"(d[0]), "+f"(d[1]), "+f"(d[2]), "+f"(d[3]) : "r"(a[0]), "r"(a[1]), "r"(a[2]), "r"(a[3]), "r"(b0), "r"(b1));
}
__device__ __forceinline__ uint2 best_key(const uint32_t* keys, int lane, uint32_t ep, uint32_t cur, int enough) {
#pragma unroll 1
    for (;;) {
        const uint4 k = ld_poll(reinterpret_cast<const uint4*>(keys) + lane);
        const bool ok = (((k.x ^ ep) | (k.y ^ ep) | (k.z ^ ep) | (k.w ^ ep)) & 31) == 0;
        const uint32_t best = __reduce_max_sync(0xffffffffu, ok ? max(max(k.x, k.y), max(k.z, k.w)) : 0u);
        const int n = __popc(__ballot_sync(0xffffffffu, ok));
        if (n == 32 || (n >= enough && best != cur)) return make_uint2(best, n == 32);
        __nanosleep(KSLEEP);
    }
}

__global__ void __cluster_dims__(2, 1, 1) __launch_bounds__(384, 1)
fused_kernel(const __grid_constant__ CUtensorMap tm_ckv, const __grid_constant__ CUtensorMap tm_wq,
             const __grid_constant__ CUtensorMap tm_wuk, const __grid_constant__ CUtensorMap tm_wuv,
             const __grid_constant__ CUtensorMap tm_wo, const __grid_constant__ CUtensorMap tm_wg,
             const __grid_constant__ CUtensorMap tm_wu,
             const __grid_constant__ CUtensorMap tm_wm, const __grid_constant__ CUtensorMap tm_x, const Params P) {
    extern __shared__ __align__(1024) uint8_t smem[];
    const uint32_t sb = (uint32_t)__cvta_generic_to_shared(smem);
    const int tid = threadIdx.x, lane = tid & 31, warp = __shfl_sync(0xffffffffu, tid >> 5, 0), wg = warp >> 2;
    const uint32_t sm = blockIdx.x < 8 ? blockIdx.x + 124 : blockIdx.x - 8, smq = ((sm - 64) * 147) >> 11;
    const int rb = sm < 64 ? (sm & 14) * 8 + (sm >> 4) * 2 + (sm & 1)
                 : sm < 120 ? ((sm - 64 - smq * 14) & 14) * 8 + 24 + smq * 2 + (sm & 1) : sm < 124 ? sm + 8 : sm - 116;
    const int grp = rb >> 3, j = rb & 7, kh = (grp >> (OMAP - 1)) & 1;
    const int cq = (j & 1) + ((grp >> (OMAP - 1)) & 2), ort = (OMAP == 1 ? grp & 12 : (grp & 8) + (grp & 1) * 4) + (j >> 1);
    if (warp == 0) TS(0);

    if (lane == 0) {
        if (warp == 8) {
            asm volatile("prefetch.tensormap [%0];" ::"l"(rb >= NCTA ? &tm_wm : (j & 1) ? &tm_wuv : &tm_wuk) : "memory");
            asm volatile("prefetch.tensormap [%0];" ::"l"(&tm_ckv) : "memory");
            *reinterpret_cast<uint2*>(smem + SM_EP + 16) = make_uint2(0, 0);
        }
        const u64 cnt = (warp < 5 ? (rb < NCTA ? 0x844444441111111ull : 0x888888881111111ull) : warp < 10 ? 0x111111188888888ull : 0x118121ull) >> (12 * (warp % 5));
#pragma unroll
        for (int i = 0; i < 3; i++) mbar_init(sb + SM_BAR + 24 * warp + 8 * i, ((uint32_t)cnt >> (4 * i)) & 15);
        fence_async_smem();
        asm volatile("fence.mbarrier_init.release.cluster;" ::: "memory");
    }
    __syncthreads();
    asm volatile("barrier.cluster.arrive.relaxed.aligned;\nbarrier.cluster.wait.aligned;" ::: "memory");

    if (rb >= NCTA) {
        float* sc = reinterpret_cast<float*>(smem + 6 * SLOT);
        float* red = sc + 512;
        uint32_t ph = 0x7f, sl = 0;
        if (warp == 8) {
#pragma unroll 1
            for (int i = 0; i < 24; i++) {
                slot_acquire(sb, ph, sl);
                tma2d(sb + sl * SLOT, &tm_wm, (i >> 3) * 1024 + (rb - NCTA) * 256, (i & 7) * 64, sb + BAR_FULL + 8 * sl, HINT & 64);
                if (++sl == 6) sl = 0;
            }
#pragma unroll 1
            for (int i = 0; i <= NFFN / NSPARE; i++) {
                const int b = (rb - NCTA) * (NFFN / NSPARE) + i;
                if (i < NFFN / NSPARE) {
                    asm volatile("cp.async.bulk.wait_group.read 0;" ::: "memory");
                    uint32_t done = 0x7f;
                    slot_acquire(sb, done, i & 1);
#pragma unroll 1
                    for (int k = 0; k < 4; k++) tma2d(sb + (i & 1) * SLOT + k * 8192, k < 2 ? &tm_wg : &tm_wu, b * 16, (k & 1) * 256, sb + BAR_FULL + 8 * (i & 1), (HINT & 128) && (i & 3) == 3);
                }
                if (i) {
                    mbar_wait(sb + BAR_FULL + 8 * (~i & 1), ((i - 1) >> 1) & 1);
                    bulk_store(g_wf + (b - 1) * SLOT, sb + (~i & 1) * SLOT, SLOT, HINT & 256);
                    asm volatile("cp.async.bulk.commit_group;" ::: "memory");
                }
            }
            asm volatile("cp.async.bulk.wait_group 0;" ::: "memory");
            fence_async_global();
            TS(4);
        } else if (warp < 8) {
            const uint32_t c2 = __ldg(reinterpret_cast<const uint32_t*>(P.c) + tid), ep = __ldcg(&g_sync.epoch[0]) + 1;
            sc[2 * tid] = rbf(bf_lo(c2) * sigmoid(bf_lo(c2)));
            sc[2 * tid + 1] = rbf(bf_hi(c2) * sigmoid(bf_hi(c2)));
            ph = 0;
#pragma unroll 1
            for (int ps = 0; ps < 3; ps++) {
                bar_sync(1, 256);
                float acc[8] = {0.f, 0.f, 0.f, 0.f, 0.f, 0.f, 0.f, 0.f};
#pragma unroll 1
                for (int bt = 0; bt < 8; bt++) {
                    slot_wait(sb + BAR_FULL, ph, sl);
#pragma unroll 4
                    for (int i = 0; i < 8; i++)
                        fma8(acc, sc[bt * 64 + warp * 8 + i], *reinterpret_cast<const uint4*>(smem + sl * SLOT + (warp * 8 + i) * 512 + lane * 16));
                    __syncwarp();
                    mbar_arrive_if(sb + BAR_EMPTY + 8 * sl, lane == 0);
                    if (++sl == 6) sl = 0;
                }
                *reinterpret_cast<float4*>(red + warp * 256 + lane * 8) = make_float4(acc[0], acc[1], acc[2], acc[3]);
                *reinterpret_cast<float4*>(red + warp * 256 + lane * 8 + 4) = make_float4(acc[4], acc[5], acc[6], acc[7]);
                bar_sync(1, 256);
                float v = 0.f;
#pragma unroll
                for (int i = 0; i < 8; i++) v += red[i * 256 + tid];
                if (ps == 0) st_pub(g_mod1 + (rb - NCTA) * 256 + tid, (pack2(0.f, v) & 0xffff0000u) | (ep & 0xffffu), true);
                else g_mod[ps * 1024 + (rb - NCTA) * 256 + tid] = __float2bfloat16_rn(v);
                if (warp == 0) TS(1 + ps);
            }
        }
        __syncthreads();
        if (tid < 2) flag_add(&g_sync.cnt[7 * 8]);
        return;
    }

    if (wg == 2) {
        asm volatile("setmaxnreg.dec.sync.aligned.u32 40;");
        const CUtensorMap* tw = (j & 1) ? &tm_wuv : &tm_wuk;
        if (warp == 8) {
            const uint32_t rank = j & 1, half = rank * 16384;
            uint32_t eph = 0x7f, r = 0;
#pragma unroll 1
            for (int hp = 0; hp < 2; hp++) {
                uint32_t wtab = w_table(hp), atab = a_table(hp);
                const int hc = 4 * grp + 2 * hp;
#pragma unroll 1
                for (int u = 0; u < 16; u++) {
                    if (u < 4) {
                        const uint32_t ws = (wtab >> (4 * u)) & 15;
                        slot_acquire(sb, eph, ws);
                        load_tile(sb, ws, 0, tw, u * 128, hc, false, HINT & 1);
                        PT();
                    }
                    if (hp == 1 && (u & 7) == 4) mbar_wait(sb + BAR_FLAG + 24 + (u & 8), 0);
                    const uint32_t as = a_next(atab);
                    slot_acquire(sb, eph, as);
                    load_tile(sb, as, half, &tm_ckv, ((u & 12) + (j >> 1)) * 128, (u & 3) * 2 + rank, true, (HINT & 8) && hp);
                    PT();
                    if (hp == 1 && (u | 2) == 3 && lane == 0)
                        asm volatile("red.relaxed.gpu.global.add.u32 [%0], 1;" ::"l"(&g_sync.cnt[(grp * 8 + 3 + (u >> 1)) * 8]) : "memory");
                }
                const uint8_t* src = g_h + (15 - j) * 4 * SLOT;
#pragma unroll 1
                for (int u = 0; u < 8; u++) {
                    if (u == 0 || u == KVG) {
                        mbar_wait(sb + BAR_FLAG + (u ? 8 + 32 * hp : 0), 0);
                        fence_async_global();
                    }
                    if (u < 4) {
                        const uint32_t ws = (wtab >> (4 * u)) & 15;
                        slot_acquire(sb, eph, ws);
                        load_tile(sb, ws, half, &tm_wq, u * 128, hc + rank, true, HINT & 1);
                        PT();
                    }
                    const uint32_t as = a_next(atab);
                    slot_acquire(sb, eph, as);
                    load_bulk(sb, as, 0, src, SLOT, false, (HINT & 8) && hp);
                    PT();
                    src += u == 3 ? (8 * j - 63) * SLOT : SLOT;
                }
                const int step = hp ? -2 * SLOT : 2 * SLOT;
                src = g_KV + (size_t)(grp * 32 + 30 * hp) * SLOT + half - step;
#pragma unroll 1
                for (int n = 0; n <= 17; n++) {
                    if (n == 8) {
                        mbar_wait(sb + BAR_FLAG + 16 + 32 * hp, 0);
                        fence_async_global();
                    }
                    const uint8_t* v = src + SLOT;
                    src += n < 16 - j ? step : n == 16 - j ? (2 * j - 15) * step : -step;
                    if (n < 17) {
                        slot_acquire(sb, eph, r);
                        if (n != 15 - (j & 6)) load_bulk(sb, r, half, src, SLOT / 2, true, (HINT & 4) && (hp || !(HINT & 32)));
                        else load_bulk(sb, r, 0, src - half, SLOT, false, (HINT & 4) && (hp || !(HINT & 32)));
                        PT();
                        r = ring_next(r);
                    }
                    if (n) {
                        slot_acquire(sb, eph, r);
                        if (n != 16 - (j & 6)) load_bulk(sb, r, half, v, SLOT / 2, true, (HINT & 4) && (hp || !(HINT & 32)));
                        else load_bulk(sb, r, 0, v - half, SLOT, false, (HINT & 4) && (hp || !(HINT & 32)));
                        PT();
                        r = ring_next(r);
                    }
                    asm volatile("st.volatile.shared.u32 [%0], %1;" ::"r"(sb + SM_EP + 16), "r"(18 * hp + n + 1) : "memory");
                }
            }
            uint32_t otab = O_TABLE, ready = 0;
#pragma unroll 1
            for (int i = 0; i < 17; i++) {
                const bool dyn = i >= 8 && i < 15;
                const uint32_t want = dyn ? 15u << (4 * (i - 8)) : 1u << max(i + 14, 28);
                if (!(ready & want)) {
                    do {
                        asm volatile("ld.acquire.cta.shared.u32 %0, [%1];" : "=r"(ready) : "r"(sb + SM_EP + 20) : "memory");
                        ready = __shfl_sync(0xffffffffu, ready, 0);
                    } while (!(ready & want));
                    fence_async_global();
                }
                const int head = o_head(dyn ? (ready >> (4 * (i - 8))) & 15 : i, kh);
                const uint32_t as = o_next(otab), ws = o_next(otab), off = i < 15 ? half : kh * 16384;
                slot_acquire(sb, eph, as);
                load_bulk(sb, as, off, g_ctx + (size_t)(ort * 32 + head) * SLOT + off, SLOT / 2, i < 15, HINT & 16);
                if (i == 15) load_tile(sb, as, off ^ 16384, &tm_x, ort * 128 + kh * 64, cq * 2, false, false);
                if (i == 16) load_bulk(sb, as, off ^ 16384, P.wdown + min(rb, NFFN - 1) * 8192, SLOT / 2, false, false);
                PT();
                slot_acquire(sb, eph, ws);
                load_tile(sb, ws, 0, &tm_wo, head * 128, cq * 2, false, HINT & 2);
                PT();
                if (i == 0) o_next(otab);
            }
            if (rb < NFFN) {
                slot_acquire(sb, eph, 5);
                load_bulk(sb, 5, 0, g_wf + rb * SLOT, SLOT, false, false);
            }
        } else if (warp == 9) {
            l2_prefetch(P.ckv + rb * 2048, 4096);
            mbar_watch(sb + BAR_FULL, 0);
            l2_prefetch(P.ckv + 512 * 512 + rb * 2048, 4096);
            mbar_watch(sb + BAR_FULL + 8 * XPF, 0);
            l2_prefetch(P.x + rb * 8192, 16384);
            mbar_watch(sb + BAR_FULL + 8 * 4, 0);
            l2_prefetch(P.ckv + 1024 * 512 + rb * 4096, 8192);
            TS(40);
#pragma unroll 1
            for (int i = 0; i < 15; i++) {
                step_watch(sb + SM_EP + 16, i == 0 ? 0 : i < 5 ? PFA + i : 13 + PFB + i);
                if (i == 12) mbar_watch(sb + BAR_FLAG + 8 * 7, 0);
                const int rf = min(rb, NFFN - 1);
                const uint8_t* p = i == 3 ? reinterpret_cast<const uint8_t*>(P.ckv) + rb * 16384
                                 : i == 4 ? g_h + rb * 16384
                                 : i < 9 ? g_ctx + (size_t)(ort * 32 + o_head(cq + 2 * ((i - 5) & 2), kh)) * SLOT + (i & 1) * 16384
                                 : i < 11 ? reinterpret_cast<const uint8_t*>(P.wo) + (grp * 16 + (~i & 1) * 8 + j) * 16384
                                 : i == 11 ? reinterpret_cast<const uint8_t*>(P.x) + rb * 16384
                                 : i == 12 ? reinterpret_cast<const uint8_t*>(P.wdown) + rf * 16384 : g_wf + rf * SLOT + (i & 1) * 16384;
                if (i < 3) tma3d_prefetch(i == 1 ? tw : &tm_wq, (j >> 1) * 128, grp * 4 + (i == 1 ? 2 : i + (j & 1)));
                else l2_prefetch(p, 16384);
            }
            const uint32_t v = lds32(sb + SM_EP) - 1;
            sts128(sb + SM_RED + lane * 16, make_uint4(v, v, v, v));
            fence_async_smem();
            __syncwarp();
#pragma unroll 1
            for (int i = 0; i < OB / 32; i++) bulk_store(g_out + rb * OB + i * 32, sb + SM_RED, 512, false);
            asm volatile("cp.async.bulk.commit_group;\ncp.async.bulk.wait_group 0;" ::: "memory");
            fence_async_global();
            __syncwarp();
            mbar_arrive_if(sb + BAR_PF, lane == 0);
            if (lane == 0) mbar_watch(sb + BAR_END, 0);
        } else {
            const uint32_t ep = __ldcg(&g_sync.epoch[0]) + 1;
            asm volatile("st.shared.u32 [%0], %1;" ::"r"(sb + SM_EP), "r"(ep) : "memory");
            mbar_wait(sb + BAR_FULL + 8 * 4, 0);
            {
                uint4 v[4];
                for (;;) {
                    uint32_t bad = 0;
#pragma unroll
                    for (int k = 0; k < 4; k++) v[k] = ld_poll(reinterpret_cast<const uint4*>(g_mod1) + (warp & 1) * 128 + k * 32 + lane);
#pragma unroll
                    for (int k = 0; k < 4; k++) bad |= (v[k].x ^ ep) | (v[k].y ^ ep) | (v[k].z ^ ep) | (v[k].w ^ ep);
                    if (__all_sync(0xffffffffu, (bad & 0xffff) == 0)) break;
                    __nanosleep(100);
                }
                const uint32_t one = (warp & 1) ? ONE2 : 0x80008000u;
#pragma unroll
                for (int k = 0; k < 4; k++)
                    *reinterpret_cast<uint2*>(smem + SM_TAB + (warp & 1) * 1024 + k * 256 + lane * 8) =
                        make_uint2(badd(__byte_perm(v[k].x, v[k].y, 0x7632), one), badd(__byte_perm(v[k].z, v[k].w, 0x7632), one));
            }
            __syncwarp();
            mbar_arrive_if(sb + BAR_FLAG + 8 * 8, lane == 0);
            if (warp == 10) {
#pragma unroll 1
                for (int i = 0; i < 9; i++) {
                    mbar_sleep(sb + BAR_DONE + 8 * i);
                    if (lane == 0) flag_add(i && ((i - 1) & 2) ? &g_sync.ctxcnt[((i & 1) ? 15 - j : j) * 32 + 2 * grp + (i > 4)] : &g_sync.cnt[(grp * 8 + i) * 8]);
                    if (i == 0) TS(43);
                }
            } else {
                TS(42);
#pragma unroll 1
                for (int i = 0; i < 8; i++) {
                    mbar_sleep(sb + BAR_DONE + 8 * (i == 7 ? 6 : i == 4 ? 3 : i));
                    if (lane < 2) flag_wait(&g_sync.cnt[((i == 0 ? (lane ? j : 15 - j) : i == 7 ? 0 : grp) * 8 + i) * 8], 8 * ep);
                    __syncwarp();
                    mbar_arrive_if(sb + BAR_FLAG + 8 * i, lane == 0 && i < 7);
                    TS(48 + i);
                }
                const uint32_t *mp = reinterpret_cast<const uint32_t*>(g_mod) + lane, *wp = reinterpret_cast<const uint32_t*>(P.wr) + lane;
                float ra = 0.f, rs = 0.f;
#pragma unroll 1
                for (int k = 0; k < 256; k += 32) {
                    const uint32_t ga = __ldcg(mp + 512 + k), sh = __ldcg(mp + 768 + k), c1 = badd(__ldcg(mp + 1024 + k), ONE2);
                    const uint32_t gb = __ldcg(mp + 1280 + k), ww = __ldg(wp + k);
                    const uint32_t a = bmul(c1, ww);
                    ra += bf_lo(a) + bf_hi(a);
                    rs = fmaf(bf_lo(sh), bf_lo(ww), fmaf(bf_hi(sh), bf_hi(ww), rs));
                    if (k >> 6 == cq) {
                        sts128(sb + SM_TAB + ((k & 32) + lane) * 16, make_uint4(ga << 16, ga & 0xffff0000u, a, 0));
                        sts128(sb + SM_TAB + 1024 + ((k & 32) + lane) * 16, make_uint4(c1, sh, gb, 0));
                    }
                }
#pragma unroll 1
                for (int o = 16; o > 0; o >>= 1) {
                    ra += __shfl_xor_sync(0xffffffffu, ra, o);
                    rs += __shfl_xor_sync(0xffffffffu, rs, o);
                }
                *reinterpret_cast<float2*>(smem + SM_EP + 8) = make_float2(ra, rs);
                __syncwarp();
                mbar_arrive_if(sb + BAR_FLAG + 8 * 7, lane == 0);
                const uint32_t* f = &g_sync.ctxcnt[ort * 32 + o_head(min(lane, 16), kh)];
                uint32_t ready = -(j & 1), list = 0, sh = 0, qa;
                asm("mapa.shared::cluster.u32 %0, %1, %2;" : "=r"(qa) : "r"(sb + SM_EP + 20), "r"(lane & 1));
                while (ready != ~0u) {
                    uint32_t v;
                    asm volatile("ld.acquire.gpu.global.u32 %0, [%1];" : "=r"(v) : "l"(f) : "memory");
                    const uint32_t now = __ballot_sync(0xffffffffu, (int)(v - ep) >= 0);
#pragma unroll 1
                    for (uint32_t fresh = now & ~ready & 0x7f00; fresh; fresh &= fresh - 1, sh += 4) list |= (__ffs(fresh) - 1) << sh;
                    list |= (((now & 0xff) + 1) >> 8 << 28) | ((now & 0x18000) << 14);
                    if (now != ready && lane < 2) asm volatile("st.relaxed.cluster.shared::cluster.u32 [%0], %1;" ::"r"(qa), "r"(list) : "memory");
                    if ((now & 0xff) == 0xff) mbar_sleep(sb + BAR_DONE + 8 * 7);
                    ready = now;
                    __nanosleep(POLL_NS);
                }
                TS(45);
            }
        }
    } else {
        asm volatile("setmaxnreg.inc.sync.aligned.u32 232;");
        const bool elected = (tid & 127) == 0, rel = (tid & 95) == 0;
        uint32_t eb;
        asm("mapa.shared::cluster.u32 %0, %1, %2;" : "=r"(eb) : "r"(sb + BAR_EMPTY), "r"(warp & 1));
        const int g = lane >> 2, c4 = lane & 3;
        const uint32_t toff = warp * 4096 + g * 64 + ((c4 ^ (g >> 1)) << 4);
        uint32_t fph = 0x3f, r = 0;
        if (wg == 1) bar_arrive(1, 256);
        const uint32_t kd = desc_k(sb), wd = desc_mn(sb), vd = ((sb & 0x3ffff) >> 4) | (32u << 16);
        const int nL = 16 - j, hn = nL - 1 + wg;
        float s[64], o[64], li[2] = {0.f, 0.f};
        uint8_t* cimg = g_ctx;
        const float sc = (j & 1) ? 1.f : SM_C;
#pragma unroll 1
        for (int q = 0; q < 3; q++) {
            const uint32_t as = (0x635u >> (4 * q)) & 15;
            mbar_wait(sb + BAR_FULL + 8 * q, 0);
            mbar_wait(sb + BAR_FULL + 8 * as, 0);
            bar_sync(1 + wg, 256);
            gemm_issue<false>(s, kd + wg * 512 + as * (SLOT / 16), wd + q * (SLOT / 16), q, false);
            bar_arrive(2 - wg, 256);
            wg_wait<0>();
            release_if(eb, as, rel);
        }
        {
            const int xrow = rb * 16 + warp * 2;
            const uint4* xp = reinterpret_cast<const uint4*>(P.x) + xrow * 64;
            uint8_t* img = g_KV + (size_t)(grp * 32 + j) * SLOT;
            uint32_t x[16], x0[2];
            float st[4] = {0.f, 0.f, 0.f, 0.f};
            mbar_wait(sb + BAR_FULL + 8 * 4, 0);
#pragma unroll
            for (int q = 3; q < 8; q++) {
                const uint32_t ws = (0x4210u >> (4 * (q & 3))) & 15, as = (0x635u >> (4 * (q % 3))) & 15;
                mbar_wait(sb + BAR_FULL + 8 * as, (q / 3) & 1);
                bar_sync(1 + wg, 256);
                if (q == 3) gemm_issue<false>(s, kd + wg * 512 + as * (SLOT / 16), wd + ws * (SLOT / 16), 1, false);
                else if (q == 4) gemm_issue<true>(o, kd + wg * 512 + as * (SLOT / 16), wd + ws * (SLOT / 16), 0, false);
                else gemm_issue<false>(o, kd + wg * 512 + as * (SLOT / 16), wd + ws * (SLOT / 16), 1, false);
                bar_arrive(2 - wg, 256);
                sched_fence(fph, P.zero);
                if (q > 3) reg_fence(s);
                if (q == 3) {
#pragma unroll
                    for (int i = 0; i < 4; i++)
                        asm volatile("ld.global.nc.v4.u32 {%0, %1, %2, %3}, [%4];" : "=r"(x[4 * i]), "=r"(x[4 * i + 1]), "=r"(x[4 * i + 2]), "=r"(x[4 * i + 3])
                                     : "l"(xp + lane + 32 * i) : "memory");
#pragma unroll
                    for (int i = 0; i < 2; i++) asm volatile("ld.global.nc.u32 %0, [%1];" : "=r"(x0[i]) : "l"(xp + 64 * i) : "memory");
                }
                if (q == 4) {
                    img_store_global<0>(img, toff, s, sc, sc);
#pragma unroll
                    for (int k = 0; k < 16; k++) {
                        const float d0 = bf_lo(x[k]) - bf_lo(x0[k >> 3]), d1 = bf_hi(x[k]) - bf_lo(x0[k >> 3]);
                        st[k >> 3] += d0 + d1;
                        st[2 + (k >> 3)] = fmaf(d0, d0, fmaf(d1, d1, st[2 + (k >> 3)]));
                    }
#pragma unroll
                    for (int i = 0; i < 4 * NSH; i++) st[i & 3] += __shfl_xor_sync(0xffffffffu, st[i & 3], 1 << (i >> 2));
                    reg_fence(st);
                }
                if (q == 5) {
#pragma unroll
                    for (int i = 4 * NSH; i < 20; i++) st[i & 3] += __shfl_xor_sync(0xffffffffu, st[i & 3], 1 << (i >> 2));
                    img_store_global<1>(img, toff, s, sc, sc);
#pragma unroll
                    for (int i = 0; i < 2; i++) {
                        const float d = st[i] * (1.f / 512.f);
                        st[2 + i] = ln_rstd(fmaxf(fmaf(-d, d, st[2 + i] * (1.f / 512.f)), 0.f));
                        x0[i] = pack2(bf_lo(x0[i]) + d, bf_lo(x0[i]) + d);
                    }
                    reg_fence(st);
                    reg_fence(x0);
                }
                if (q > 5) {
                    if (q == 6) mbar_wait(sb + BAR_FLAG + 8 * 8, 0);
                    const uint4 a = lds128(sb + SM_TAB + 1024 + (q & 1) * 512 + lane * 16), c = lds128(sb + SM_TAB + (q & 1) * 512 + lane * 16);
                    uint8_t* hp = g_h + (grp * 8 + (q & 1) * 4 + (lane >> 3)) * 16384 + (xrow & 127) * 128;
#pragma unroll
                    for (int i = 0; i < 2; i++) {
                        const uint32_t* y = x + 8 * i + 4 * (q & 1);
                        *reinterpret_cast<uint4*>(hp + i * 128 + (((lane ^ xrow ^ i) & 7) << 4)) =
                            make_uint4(ln_apply(y[0], x0[i], st[2 + i], a.x, c.x), ln_apply(y[1], x0[i], st[2 + i], a.y, c.y),
                                       ln_apply(y[2], x0[i], st[2 + i], a.z, c.z), ln_apply(y[3], x0[i], st[2 + i], a.w, c.w));
                    }
                    if (q == 7) {
                        __syncwarp();
                        mbar_arrive_if(sb + BAR_DONE, lane == 0);
                    }
                    if (q == 6) img_store_global<2>(img, toff, s, sc, sc);
                    else img_store_global<3>(img, toff, s, sc, sc);
                }
                sched_fence(fph, P.zero);
                wg_wait<0>();
                release_if(eb, as, rel);
            }
            reg_fence(o);
        }
        uint32_t p[32] = {};
#pragma unroll 1
        for (int hp = 0; hp < 2; hp++) {
            float m[2] = {0.f, 0.f}, l[2] = {0.f, 0.f}, t[4] = {0.f, 0.f, 0.f, 0.f};
            bool shifted = false, bad = false, plain = false;
            uint32_t qa = desc_k(sb + 5 * SLOT + (wg ^ 1) * 8192);
            uint8_t* limg = g_ctx + (size_t)((15 - j) * 32 + 2 * grp + hp) * SLOT;
            {
                const int step = hp ? -8 * SLOT : 8 * SLOT;
                uint8_t* img = g_KV + (size_t)(grp * 32 + (hp ? j ^ 30 : j) + 8) * SLOT;
                const uint32_t wtab = w_table(hp);
                uint32_t atab = hp ? 0x562u : 0x356u;
#pragma unroll 1
                for (int u = 2 - 2 * hp;; u += 2) {
                    proj_tile<false>(s, o, u, !u, sb, wg, eb, rel, fph, wtab, atab, u ? img : cimg, toff, u ? sc : li[0], u ? sc : li[1], p);
                    __syncwarp();
                    mbar_arrive_if(sb + BAR_DONE + 4 * u + 32 * hp, lane == 0);
                    if (elected) TS(1 + 10 * hp + u + 20 * wg);
                    if (proj_tile<true>(o, s, u + 1, 0, sb, wg, eb, rel, fph, wtab, atab, img + step, toff, sc, sc, p)) break;
                    if (elected) TS(2 + 10 * hp + u + 20 * wg);
                    img += 2 * step;
                }
            }
            if (elected) TS(6 + 10 * hp + 20 * wg);
            int n = -1;
#pragma unroll 1
            for (;;) {
                while (bad || plain) {
                    if (bad) {
                        float a0, a1;
                        softmax_remax(s, m, n == 0 || n == nL, a0, a1);
                        shifted = true;
                        l[0] *= a0;
                        l[1] *= a1;
#pragma unroll
                        for (int i = 0; i < 64; i++) o[i] *= (i & 2) ? a1 : a0;
                    }
                    softmax_exp<0, 16>(s, p, t);
                    t[0] += t[1];
                    t[2] += t[3];
                    bad = !bad && softmax_unsafe(t[0], t[2], false);
                    plain = false;
                }
#pragma unroll 1
                do {
                    l[0] += t[0];
                    l[1] += t[2];
                    if (++n > 16) break;
                    const uint32_t ks = r;
                    uint32_t vs = ring_next(r);
                    r = ring_next(vs);
                    bar_sync(1 + wg, 256);
                    const float x = (float)((warp & 3) * 16 + g - 2 * c4);
                    if (n == hn) {
                        float sh[32];
                        qk_issue(sh, qa, kd + ks * (SLOT / 16));
                        slot_wait(sb + BAR_FULL, fph, vs);
                        pv_issue(o, p, vd + vs * (SLOT / 16), 1, false);
                        bar_arrive(2 - wg, 256);
                        wg_wait<1>();
                        reg_fence(sh);
                        tri_mask_copy(s, sh, x);
                        release_if(eb, ks, rel);
                        release_if(eb, 5 + wg, rel && (!wg || n == 16));
                        if (!wg) {
                            qa += SLOT / 16;
                            fence_async_smem();
                            if (shifted) softmax_shift(s, m[0], m[1]);
                        }
                        float e[4 * EARLY];
#pragma unroll
                        for (int i = 0; i < 4 * EARLY; i++) {
                            e[i] = ex2(s[i]);
                            t[i & 3] = i < 4 ? e[i] : t[i & 3] + e[i];
                        }
                        reg_fence(e);
                        slot_wait(sb + BAR_FULL, fph, r);
                        wg_wait<0>();
                        reg_fence(o);
                        reg_fence(e);
                        release_if(eb, vs, rel);
#pragma unroll
                        for (int i = 0; i < 2 * EARLY; i++) p[i] = pack2(e[2 * i], e[2 * i + 1]);
                        softmax_exp<EARLY, 8>(s, p, t);
                        if (wg) {
                            ctx_store<true>(limg, toff, o, l[0], l[1]);
                            __syncwarp();
                            mbar_arrive_if(sb + BAR_DONE + 24 + 32 * hp, lane == 0);
                            l[0] = l[1] = m[0] = m[1] = 0.f;
                            shifted = false;
                        }
                        t[0] += t[1];
                        t[2] += t[3];
                        bad = softmax_unsafe(t[0], t[2], wg);
                        continue;
                    }
                    if (n == 0 || n == nL) {
                        qk_issue(s, qa, kd + ks * (SLOT / 16));
                        if (n == 0) {
                            r = vs;
                            vs = 4 - hp;
                            slot_wait(sb + BAR_FULL, fph, 6);
                            gemm_issue<false>(o, qa + SLOT / 16, wd + vs * (SLOT / 16), 1, false);
                        } else {
                            slot_wait(sb + BAR_FULL, fph, vs);
                            pv_issue(o, p, vd + vs * (SLOT / 16), 1, true);
                        }
                        bar_arrive(2 - wg, 256);
                        const float i0 = n ? rcp(quad_sum(l[0])) : 1.f, i1 = n ? rcp(quad_sum(l[1])) : 1.f;
                        wg_wait<1>();
                        reg_fence(s);
                        release_if(eb, ks, rel);
                        release_if(eb, 6, rel && n == 16);
                        tri_mask(s, n ? x : 64.f);
                        float e[4 * EARLY];
#pragma unroll
                        for (int i = 0; i < 4 * EARLY; i++) {
                            e[i] = ex2(s[i]);
                            t[i & 3] = i < 4 ? e[i] : t[i & 3] + e[i];
                        }
                        reg_fence(e);
                        reg_fence(s);
                        reg_fence(t);
                        slot_wait(sb + BAR_FULL, fph, r);
                        if (SF & 1) sched_fence(fph, P.zero);
                        wg_wait<0>();
                        reg_fence(o);
                        reg_fence(e);
                        release_if(eb, vs, rel);
#pragma unroll
                        for (int i = 0; i < 2 * EARLY; i++) p[i] = pack2(e[2 * i], e[2 * i + 1]);
                        softmax_exp<EARLY, MSPLIT>(s, p, t);
                        tile_store(limg, sb + 6 * SLOT, toff, o, i0, i1, n);
                        reg_fence(t);
                        if (SF & 2) sched_fence(fph, P.zero);
                        reg_fence(s);
                        softmax_exp<MSPLIT, 16>(s, p, t);
                        __syncwarp();
                        mbar_arrive_if(sb + BAR_DONE + 24 + 32 * hp, lane == 0 && n);
                        l[0] = l[1] = m[0] = m[1] = 0.f;
                        shifted = false;
                        t[0] += t[1];
                        t[2] += t[3];
                        bad = __any_sync(0xffffffffu, fmaxf(t[0], t[2]) > SM_HI || fminf(t[0], t[2]) < SM_LO);
                        continue;
                    }
                    qk_issue(s, qa, kd + ks * (SLOT / 16));
                    slot_wait(sb + BAR_FULL, fph, vs);
                    pv_issue(o, p, vd + vs * (SLOT / 16), n != 1 && n != nL + 1, n == hn + 1);
                    bar_arrive(2 - wg, 256);
                    wg_wait<1>();
                    reg_fence(s);
                    release_if(eb, ks, rel);
                    release_if(eb, 6, rel && n == 16);
                    if (n == nL - 1) {
                        tri_mask(s, x);
                        release_if(eb, 5, rel);
                        qa += SLOT / 16;
                        fence_async_smem();
                    }
                    if (shifted) {
                        slot_wait(sb + BAR_FULL, fph, r);
                        wg_wait<0>();
                        reg_fence(o);
                        release_if(eb, vs, rel);
                        softmax_shift(s, m[0], m[1]);
                        plain = true;
                        break;
                    }
                    float e[4 * EARLY];
#pragma unroll
                    for (int i = 0; i < 4 * EARLY; i++) {
                        e[i] = ex2(s[i]);
                        t[i & 3] = i < 4 ? e[i] : t[i & 3] + e[i];
                    }
                    reg_fence(e);
                    slot_wait(sb + BAR_FULL, fph, r);
                    wg_wait<0>();
                    reg_fence(o);
                    reg_fence(e);
                    release_if(eb, vs, rel);
#pragma unroll
                    for (int i = 0; i < 2 * EARLY; i++) p[i] = pack2(e[2 * i], e[2 * i + 1]);
                    softmax_exp<EARLY, 16>(s, p, t);
                    t[0] += t[1];
                    t[2] += t[3];
                    bad = softmax_unsafe(t[0], t[2], false);
                } while (!bad);
                if (!bad && !plain) break;
            }
            const uint32_t vs = r, ga = desc_k(sb + (hp ? 2 * (wg ^ kh ^ 1) : wg) * 8192);
            r = ring_next(r);
            slot_wait(sb + BAR_FULL, fph, 5);
            slot_wait(sb + BAR_FULL, fph, r);
            bar_sync(1 + wg, 256);
            gemm_issue<true>(s, ga + 5 * (SLOT / 16), wd + r * (SLOT / 16), 0, hp);
            pv_issue(o, p, vd + vs * (SLOT / 16), j, hn == 16);
            bar_arrive(2 - wg, 256);
            li[0] = rcp(quad_sum(l[0]));
            li[1] = rcp(quad_sum(l[1]));
            cimg = limg + (ptrdiff_t)(2 * j - 15) * 32 * SLOT + (wg ? -16384 : 16384);
            wg_wait<1>();
            release_if(eb, 5, rel);
            release_if(eb, r, rel && hp);
            wg_wait<0>();
            release_if(eb, vs, rel);
            reg_fence(o);
            img_store_global<0>(cimg, toff, o, li[0], li[1]);
            if (elected) TS(8 + 10 * hp + 20 * wg);
        }
        uint32_t otab = 0x2351604u;
        const uint32_t oa = desc_k(sb + (wg ^ kh ^ 1) * 16384);
        const int t7 = tid & 127, w4 = warp & 3, row = ort * 128 + kh * 64 + w4 * 16 + g;
#pragma unroll 1
        for (int i = 1; i < 15 - wg; i++) {
            const uint32_t as = o_next(otab), ws = o_next(otab);
            slot_wait(sb + BAR_FULL, fph, as);
            slot_wait(sb + BAR_FULL, fph, ws);
            bar_sync(1 + wg, 256);
            gemm_issue<false>(s, oa + as * (SLOT / 16), wd + ws * (SLOT / 16), 1, true);
            bar_arrive(2 - wg, 256);
            wg_wait<1>();
            reg_fence(o);
            if (i == 1) img_store_global<1>(cimg, toff, o, li[0], li[1]);
            if (i == 2) {
                img_store_global<2>(cimg, toff, o, li[0], li[1]);
                img_store_global<3>(cimg, toff, o, li[0], li[1]);
                __syncwarp();
                mbar_arrive_if(sb + BAR_DONE + 64, lane == 0);
            }
            wg_wait<0>();
            release_if(eb, as, rel);
            release_if(eb, ws, rel);
        }
        mbar_wait(sb + BAR_PF, 0);
        const uint32_t ep = lds32(sb + SM_EP);
        uint32_t eb2 = sb + BAR_END;
        if (wg == 0) {
            reg_fence(s);
            if (elected) TS(9);
            TT(1);
#pragma unroll
            for (int v = 0; v < 8; v++)
                st_pub(g_out + rb * OB + v * 128 + t7, make_uint4((pack2(s[8 * v], s[8 * v + 1]) & ~1u) | (ep & 1), pack2(s[8 * v + 2], s[8 * v + 3]),
                                                                      pack2(s[8 * v + 4], s[8 * v + 5]), pack2(s[8 * v + 6], s[8 * v + 7])), true);
            constexpr uint32_t s1 = 5, s2 = 6;
            bar_sync(4, 256);
            uint32_t wf[64];
            float wn[64];
            if (rb < NFFN) {
                slot_wait(sb + BAR_FULL, fph, s1);
                const uint32_t a = sb + s1 * SLOT + (w4 * 128 + (lane >> 4) * 8 + (lane & 7)) * 32 + ((lane >> 3) & 1) * 16;
#pragma unroll
                for (int i = 0; i < 16; i++)
                    asm volatile("ldmatrix.sync.aligned.m8n8.x4.trans.shared.b16 {%0, %1, %2, %3}, [%4];"
                                 : "=r"(wf[4 * i]), "=r"(wf[4 * i + 1]), "=r"(wf[4 * i + 2]), "=r"(wf[4 * i + 3])
                                 : "r"(a + (i >> 3) * 16384 + (i & 7) * 512) : "memory");
                slot_wait(sb + BAR_FULL, fph, s2);
#pragma unroll
                for (int i = 0; i < 16; i++) {
                    const uint2 w = *reinterpret_cast<const uint2*>(smem + s2 * SLOT + (kh ^ 1) * 16384 + i * 1024 + t7 * 8);
                    wn[4 * i] = bf_lo(w.x); wn[4 * i + 1] = bf_hi(w.x); wn[4 * i + 2] = bf_lo(w.y); wn[4 * i + 3] = bf_hi(w.y);
                }
                reg_fence(wn);
            }
            const uint32_t gbf = __ldcg(reinterpret_cast<const uint32_t*>(g_mod) + 1280 + rb * 2 + (tid & 1));
            if (elected) TS(10);
            TT(2);
            float* sred = reinterpret_cast<float*>(smem + SM_RED);
            uint32_t best = ep ^ 1, all;
            bool fresh;
            do {
                if (warp == 0) {
                    const uint2 k = best_key(g_key + cq * 128, lane, ep, best, rb < NFFN ? SPEC : 32);
                    *reinterpret_cast<uint2*>(smem + SM_EP + 24) = k;
                    mbar_arrive_if(sb + BAR_BEST, lane == 0 && k.y);
                }
                bar_sync(3, 128);
                const uint2 k = *reinterpret_cast<const uint2*>(smem + SM_EP + 24);
                fresh = k.x != best;
                best = k.x;
                all = k.y;
                TT(3);
                if (!fresh || rb >= NFFN) break;
                const uint4* cp = g_cand + ((~best >> 9) & 127) * 192;
                uint4 cv[6];
                for (;;) {
                    uint32_t bad = 0;
#pragma unroll
                    for (int v = 0; v < 6; v++) cv[v] = ld_poll(cp + w4 * 24 + v * 4 + c4);
#pragma unroll
                    for (int v = 0; v < 6; v++) bad |= cv[v].w ^ ep;
                    if (__all_sync(0xffffffffu, bad == 0)) break;
                    if (CSLEEP) __nanosleep(CSLEEP);
                }
            TT(4);
                float d[4][4] = {};
#pragma unroll
                for (int k = 0; k < 8; k++) {
                    const uint32_t b0 = (&cv[(2 * k) / 3].x)[(2 * k) % 3], b1 = (&cv[(2 * k + 1) / 3].x)[(2 * k + 1) % 3];
                    mma16816(d[k & 1], wf + 4 * k, b0, b1);
                    mma16816(d[2 + (k & 1)], wf + 32 + 4 * k, b0, b1);
                }
                const float u = (c4 & 2) ? ((c4 & 1) ? d[2][2] + d[3][2] : d[2][0] + d[3][0]) : ((c4 & 1) ? d[0][2] + d[1][2] : d[0][0] + d[1][0]);
                sred[w4 * 32 + c4 * 8 + g] = u;
                bar_sync(3, 128);
                const float v = rbf((sred[lane] + sred[32 + lane]) + (sred[64 + lane] + sred[96 + lane]));
                const float act = rbf(rbf(v * sigmoid(v)) * __shfl_down_sync(0xffffffffu, v, 16));
                float y[4] = {0.f, 0.f, 0.f, 0.f};
#pragma unroll
                for (int k = 0; k < 16; k++) {
                    const float a = __shfl_sync(0xffffffffu, act, k);
#pragma unroll
                    for (int i = 0; i < 4; i++) y[i] = fmaf(a, wn[4 * k + i], y[i]);
                }
                st_pub(g_out + rb * OB + OB_Y + t7, make_uint4((__float_as_uint(y[0]) & ~15u) | (ep & 15), (__float_as_uint(y[1]) & ~127u) | ((best >> 9) & 127),
                                                               __float_as_uint(y[2]), __float_as_uint(y[3])), true);
            } while (!all);
            const int sel = (~best >> 5) & 2047;
            const int pq = (2 * rb + (tid & 1)) & 63, pv = (pq >> 2) / 3;
            const uint4* fp = g_cand + (sel >> 4) * 192 + (rb >> 5) * 24 + pv * 4 + (pq & 3);
            uint4 fh = {}, fx = {};
            if (rb == 0 && tid == 0) g_sync.epoch[0] = ep;
            if (elected) TS(60);
            TT(5);
            uint4 yv;
            if (warp == 0) { fh = ld_poll(fp); fx = ld_poll(fp + 96); }
            if (fresh && rb < NFFN) __nanosleep(YPRE);
            for (;;) {
                yv = ld_poll(g_out + min(t7, NFFN - 1) * OB + OB_Y + rb);
                if (__all_sync(0xffffffffu, (((yv.x ^ ep) & 15) | ((yv.y ^ (best >> 9)) & 127)) == 0)) break;
                if (YSLEEP) __nanosleep(YSLEEP);
            }
            if (elected) TS(61);
            TT(6);
            float y[4] = {0.f, 0.f, 0.f, 0.f};
            if (t7 < NFFN) { y[0] = __uint_as_float(yv.x); y[1] = __uint_as_float(yv.y); y[2] = __uint_as_float(yv.z); y[3] = __uint_as_float(yv.w); }
            const float z0 = ((lane & 16) ? y[2] : y[0]) + __shfl_xor_sync(0xffffffffu, (lane & 16) ? y[0] : y[2], 16);
            const float z1 = ((lane & 16) ? y[3] : y[1]) + __shfl_xor_sync(0xffffffffu, (lane & 16) ? y[1] : y[3], 16);
            float z = ((lane & 8) ? z1 : z0) + __shfl_xor_sync(0xffffffffu, (lane & 8) ? z0 : z1, 8);
            z += __shfl_xor_sync(0xffffffffu, z, 4);
            z = quad_sum(z);
            if ((lane & 7) == 0) sred[128 + (lane >> 3) * 4 + w4] = z;
            bar_sync(3, 128);
            if (tid < 2) {
                while (fh.w != ep || fx.w != ep) { fh = ld_poll(fp); fx = ld_poll(fp + 96); }
                const float4 y0 = *reinterpret_cast<const float4*>(sred + 128 + tid * 8), y1 = *reinterpret_cast<const float4*>(sred + 132 + tid * 8);
                const int cm = (pq >> 2) - 3 * pv;
                const uint32_t h2 = cm == 0 ? fh.x : cm == 1 ? fh.y : fh.z, x2 = cm == 0 ? fx.x : cm == 1 ? fx.y : fx.z;
                const float sg = sigmoid(bf_hi((best & 0x80000000u) ? (best ^ 0x80000000u) : ~best));
                reinterpret_cast<uint32_t*>(P.out)[sel * 256 + rb * 2 + tid] =
                    badd(x2, bmul(gbf, badd(h2, bmul(pack2((y0.x + y0.y) + (y0.z + y0.w), (y1.x + y1.y) + (y1.z + y1.w)), pack2(sg, sg)))));
            }
            if (elected) TS(62);
            TT(7);
        } else {
            const float4* tf = reinterpret_cast<const float4*>(smem + SM_TAB) + c4;
            const uint32_t xa = sb + 4 * SLOT + (kh ^ 1) * 16384 + (w4 * 16 + (lane & 15)) * 128;
            uint32_t x2[32];
            bar_sync(2, 256);
#pragma unroll 1
            for (int i = 14; i < 17; i++) {
                const uint32_t as = o_next(otab), ws = o_next(otab);
                slot_wait(sb + BAR_FULL, fph, as);
                slot_wait(sb + BAR_FULL, fph, ws);
                gemm_issue<false>(s, oa + as * (SLOT / 16), wd + ws * (SLOT / 16), 1, true);
                wg_wait<1>();
            }
            if (elected) TS(29);
            TT(1);
            {
#pragma unroll
                for (int k = 0; k < 8; k++)
                    asm volatile("ldmatrix.sync.aligned.m8n8.x4.shared.b16 {%0, %1, %2, %3}, [%4];"
                                 : "=r"(x2[4 * k]), "=r"(x2[4 * k + 1]), "=r"(x2[4 * k + 2]), "=r"(x2[4 * k + 3])
                                 : "r"(xa + (k >> 2) * 8192 + (((2 * (k & 3) + (lane >> 4)) ^ (lane & 7)) << 4)) : "memory");
            }
            wg_wait<0>();
            reg_fence(s);
            bar_arrive(4, 256);
            if (elected) TS(39);
            TT(2);
            const uint4* pr = g_out + (rb ^ (8 * OMAP)) * OB + t7;
            uint4 pa[8];
#pragma unroll
            for (int v = 0; v < 8; v++) pa[v] = ld_poll(pr + v * 128);
            float4 tc[16];
#pragma unroll
            for (int k = 0; k < 16; k++) {
                tc[k] = tf[k * 4];
                if (!(g & 1)) tc[k].z = __uint_as_float(ONE2);
#pragma unroll
                for (int i = 4 * k; i < 4 * k + 4; i++) s[i] = fmaf((i & 1) ? tc[k].y : tc[k].x, s[i], (i & 1) ? bf_hi(x2[i >> 1]) : bf_lo(x2[i >> 1]));
            }
            reg_fence(s);
            for (;;) {
                uint32_t bad = 0;
#pragma unroll
                for (int v = 0; v < 8; v++) bad |= pa[v].x ^ ep;
                if (__all_sync(0xffffffffu, (bad & 1) == 0)) break;
                if (PSLEEP) __nanosleep(PSLEEP);
#pragma unroll
                for (int v = 0; v < 8; v++) pa[v] = ld_poll(pr + v * 128);
            }
            if (elected) TS(30);
            TT(3);
            float sd[4] = {}, q0[4] = {}, q1[4] = {};
#pragma unroll
            for (int k = 0; k < 8; k++) {
#pragma unroll
                for (int i = 4 * k; i < 4 * k + 4; i++) {
                    const uint32_t w = (&pa[k].x)[i & 3];
                    x2[i] = pack2(fmaf(tc[i >> 1].x, bf_lo(w), s[2 * i]), fmaf(tc[i >> 1].y, bf_hi(w), s[2 * i + 1]));
                }
                mma16816(sd, x2 + 4 * k, __float_as_uint(tc[2 * k].z), __float_as_uint(tc[2 * k + 1].z));
                mma16816(q0, x2 + 4 * k, x2[4 * k], x2[4 * k + 2]);
                mma16816(q1, x2 + 4 * k, x2[4 * k + 1], x2[4 * k + 3]);
            }
            uint4* sp = g_out + rb * OB + OB_STAT + (w4 * 8 + g) * 2;
            st_pub(sp, make_uint4(__float_as_uint(sd[0]), __float_as_uint((g & 1) ? q0[1] : q0[0]), __float_as_uint(sd[1]), ep), c4 == g >> 1);
            st_pub(sp + 1, make_uint4(__float_as_uint(sd[2]), __float_as_uint((g & 1) ? q1[3] : q1[2]), __float_as_uint(sd[3]), ep), c4 == g >> 1);
            if (TF & 1) sched_fence(eb2, P.zero);
            if (elected) TS(56);
            TT(4);
            uint32_t cb[16], sh[16], gb[16];
#pragma unroll
            for (int i = 0; i < 16; i++) {
                const float4 c = tf[64 + i * 4];
                cb[i] = __float_as_uint(c.x); sh[i] = __float_as_uint(c.y); gb[i] = __float_as_uint(c.z);
            }
            const float ra = __uint_as_float(lds32(sb + SM_EP + 8)), rb0 = __uint_as_float(lds32(sb + SM_EP + 12));
            uint4 r0, r1;
            if (SPRE) __nanosleep(SPRE);
            for (;;) {
                r0 = ld_poll(g_out + ((rb & ~(16 * OMAP + 1)) + (c4 & 1) + (c4 & 2) * 8 * OMAP) * OB + OB_STAT + (w4 * 8 + g) * 2);
                r1 = ld_poll(g_out + ((rb & ~(16 * OMAP + 1)) + (c4 & 1) + (c4 & 2) * 8 * OMAP) * OB + OB_STAT + (w4 * 8 + g) * 2 + 1);
                if (__all_sync(0xffffffffu, r0.w == ep && r1.w == ep)) break;
                if (SSLEEP) __nanosleep(SSLEEP);
            }
            if (elected) TS(57);
            TT(5);
            const float m0 = quad_sum(__uint_as_float(r0.x)) * (1.f / 512.f), m1 = quad_sum(__uint_as_float(r1.x)) * (1.f / 512.f);
            const float rs0 = ln_rstd(fmaxf(fmaf(-m0, m0, quad_sum(__uint_as_float(r0.y)) * (1.f / 512.f)), 0.f));
            const float rs1 = ln_rstd(fmaxf(fmaf(-m1, m1, quad_sum(__uint_as_float(r1.y)) * (1.f / 512.f)), 0.f));
            const uint32_t mb0 = pack2(m0, m0), mb1 = pack2(m1, m1);
            const uint32_t lg = pack2(fmaf(rs0, fmaf(-bf_lo(mb0), ra, quad_sum(__uint_as_float(r0.z))), rb0),
                                      fmaf(rs1, fmaf(-bf_lo(mb1), ra, quad_sum(__uint_as_float(r1.z))), rb0));
            const uint32_t u0 = lg << 16, u1 = lg & 0xffff0000u;
            const uint32_t k0 = ((u0 ^ (((int)u0 >> 31) | 0x80000000u)) & 0xffff0000u) | ((2047 - row) << 5) | (ep & 31);
            const uint32_t k1 = ((u1 ^ (((int)u1 >> 31) | 0x80000000u)) & 0xffff0000u) | ((2039 - row) << 5) | (ep & 31);
            const uint32_t kb = __reduce_max_sync(0xffffffffu, max(k0, k1));
            st_pub(g_key + cq * 128 + (row >> 4), kb, lane == 0);
            const bool cand = kb == k0 || kb == k1;
            uint4* cp = g_cand + (row >> 4) * 192 + cq * 24 + c4;
#pragma unroll 1
            for (int it = 0; it < 3; it++) {
                bool put = it == 1 || !cand;
                if (it == 2) {
                    mbar_wait(sb + BAR_BEST, 0);
                    put = cand && lds32(sb + SM_EP + 24) != kb;
                }
                const bool hi = (kb == k1) != (it == 1);
                uint32_t cx[18], ch[18];
#pragma unroll
                for (int i = 0; i < 16; i++) {
                    cx[i] = hi ? x2[2 * i + 1] : x2[2 * i];
                    ch[i] = ln_apply(cx[i], hi ? mb1 : mb0, hi ? rs1 : rs0, cb[i], sh[i]);
                }
                cx[16] = cx[17] = ch[16] = ch[17] = 0;
#pragma unroll
                for (int v = 0; v < 6; v++) st_pub(cp + v * 4, make_uint4(ch[3 * v], ch[3 * v + 1], ch[3 * v + 2], ep), cand && it == 0);
                if (TF & 4) sched_fence(eb2, P.zero);
#pragma unroll
                for (int v = 0; v < 6; v++) st_pub(cp + 96 + v * 4, make_uint4(cx[3 * v], cx[3 * v + 1], cx[3 * v + 2], ep), cand && it == 0);
                if (it == 0) TT(6);
                uint2* op = reinterpret_cast<uint2*>(P.out) + (row + 8 * hi) * 128 + cq * 32 + (c4 & 1) * 2 + (c4 >> 1);
#pragma unroll
                for (int i = 0; i < 16; i += 2) {
                    const uint32_t v0 = badd(cx[i], bmul(gb[i], ch[i])), v1 = badd(cx[i + 1], bmul(gb[i + 1], ch[i + 1]));
                    const uint32_t rv = __shfl_xor_sync(0xffffffffu, (c4 & 1) ? v0 : v1, 1);
                    if (put) op[i * 2] = (c4 & 1) ? make_uint2(rv, v1) : make_uint2(v0, rv);
                }
            }
            if (elected) TS(59);
            TT(7);
        }
        mbar_arrive_if(eb2, lane == 0);
    }
}

typedef CUresult (*EncodeFn)(CUtensorMap*, CUtensorMapDataType, cuuint32_t, void*, const cuuint64_t*, const cuuint64_t*,
                             const cuuint32_t*, const cuuint32_t*, CUtensorMapInterleave, CUtensorMapSwizzle,
                             CUtensorMapL2promotion, CUtensorMapFloatOOBfill);

void make_2d(EncodeFn fn, CUtensorMap* m, const void* p, uint64_t cols, uint64_t rows, uint32_t bc, uint32_t br) {
    cuuint64_t dims[2] = {cols, rows}, strides[1] = {cols * 2};
    cuuint32_t box[2] = {bc, br}, es[2] = {1, 1};
    fn(m, CU_TENSOR_MAP_DATA_TYPE_BFLOAT16, 2, const_cast<void*>(p), dims, strides, box, es, CU_TENSOR_MAP_INTERLEAVE_NONE,
       CU_TENSOR_MAP_SWIZZLE_NONE, CU_TENSOR_MAP_L2_PROMOTION_L2_128B, CU_TENSOR_MAP_FLOAT_OOB_FILL_NONE);
}
void make_3d(EncodeFn fn, CUtensorMap* m, const void* p, uint64_t cols, uint64_t rows, uint32_t br = 128, uint32_t nb = 2) {
    cuuint64_t dims[3] = {64, rows, cols / 64}, strides[2] = {cols * 2, 128};
    cuuint32_t box[3] = {64, br, nb}, es[3] = {1, 1, 1};
    fn(m, CU_TENSOR_MAP_DATA_TYPE_BFLOAT16, 3, const_cast<void*>(p), dims, strides, box, es, CU_TENSOR_MAP_INTERLEAVE_NONE,
       CU_TENSOR_MAP_SWIZZLE_128B, CU_TENSOR_MAP_L2_PROMOTION_L2_256B, CU_TENSOR_MAP_FLOAT_OOB_FILL_NONE);
}

}

extern "C" void kernel_launch(void* const* d_in, const int* in_sizes, int n_in, void* d_out, int out_size) {
    static EncodeFn fn = nullptr;
    if (!fn) {
        void* f = nullptr;
        cudaDriverEntryPointQueryResult st;
        cudaGetDriverEntryPoint("cuTensorMapEncodeTiled", &f, cudaEnableDefault, &st);
        fn = (EncodeFn)f;
        cudaFuncSetAttribute(fused_kernel, cudaFuncAttributeMaxDynamicSharedMemorySize, SMEM_BYTES);
    }
    CUtensorMap ckv, wq, wuk, wuv, wo, wg, wu, wm, xm;
    make_3d(fn, &ckv, d_in[1], 512, 2048, 128, 1);
    make_3d(fn, &xm, d_in[0], 512, 2048, 64);
    make_3d(fn, &wq, d_in[2], 4096, 512, 128, 1);
    make_3d(fn, &wuk, d_in[3], 4096, 512);
    make_3d(fn, &wuv, d_in[4], 4096, 512);
    make_3d(fn, &wo, d_in[5], 512, 4096);
    make_2d(fn, &wg, d_in[8], 1792, 512, 16, 256);
    make_2d(fn, &wu, d_in[9], 1792, 512, 16, 256);
    make_2d(fn, &wm, d_in[12], 3072, 512, 256, 64);
    Params p;
    p.x = (const bf16*)d_in[0];
    p.ckv = (const bf16*)d_in[1];
    p.wo = (const bf16*)d_in[5];
    p.wr = (const bf16*)d_in[7];
    p.wdown = (const bf16*)d_in[10];
    p.c = (const bf16*)d_in[11];
    p.out = (bf16*)d_out;
    p.zero = 0;
    fused_kernel<<<NCTA + NSPARE, 384, SMEM_BYTES>>>(ckv, wq, wuk, wuv, wo, wg, wu, wm, xm, p);
}
```

```cpp
#include <cuda.h>
#include <cuda_bf16.h>
#include <cuda_runtime.h>
#include <stdint.h>
#include <stdio.h>

namespace {

typedef __nv_bfloat16 bf16;
typedef unsigned long long u64;

constexpr int NCTA = 128, NSPARE = 4;
constexpr int SLOT = 32768;
constexpr int SM_BAR = 7 * SLOT;
constexpr int BAR_FULL = SM_BAR;
constexpr int BAR_EMPTY = BAR_FULL + 8 * 7;
constexpr int BAR_DONE = BAR_EMPTY + 8 * 7;
constexpr int BAR_FLAG = BAR_DONE + 8 * 9;
constexpr int BAR_PF = BAR_FLAG + 8 * 9;
constexpr int BAR_END = BAR_PF + 8;
constexpr int BAR_BEST = BAR_END + 8;
constexpr int SM_EP = BAR_END + 24;
constexpr int SM_RED = SM_BAR + 384;
constexpr int SM_TAB = SM_BAR + 1024;
constexpr int SMEM_BYTES = SM_BAR + 3072;
constexpr int NFFN = 112;
#define HINT 479
constexpr u64 L2_NORMAL = 0x1000000000000000ull, L2_FIRST = 0x12F0000000000000ull;
#define PFA 8
#define PFB 6
#define UNR 1
#define POLL_NS 50
#define MSPLIT 13
#define SF 3
#define NSH 1
#define XPF 2
#define TF 1
#define KSLEEP 150
#define YSLEEP 50
#define YPRE 150
#define SSLEEP 50
#define SPRE 0
#define PSLEEP 100
#define CSLEEP 0
#define SPEC 24
#define OMAP 2
#define KVG 7
#define EARLY 7
constexpr uint32_t SPIN_LIMIT = 1u << 22;
constexpr uint32_t ONE2 = 0x3f803f80u;

struct Sync {
    uint32_t cnt[16 * 8 * 8];
    uint32_t ctxcnt[16 * 32];
    uint32_t epoch[32];
};

__device__ __align__(1024) uint8_t g_KV[16 * 16 * 2 * SLOT];
__device__ __align__(1024) uint8_t g_ctx[16 * 32 * SLOT];
__device__ __align__(1024) uint8_t g_h[16 * 4 * SLOT];
constexpr int OB = 1216, OB_STAT = 1024, OB_Y = 1088;
__device__ __align__(1024) uint4 g_out[128 * OB];
__device__ __align__(1024) bf16 g_mod[3072];
__device__ __align__(1024) uint32_t g_mod1[1024];
__device__ __align__(1024) uint4 g_cand[128 * 192];
__device__ __align__(1024) uint32_t g_key[4 * 128];
__device__ __align__(1024) uint8_t g_wf[NFFN * SLOT];
__device__ __align__(1024) Sync g_sync;
#define TS(i)

#define TT(i)
#define PT()

struct Params {
    const bf16 *x, *ckv, *wo, *wr, *wdown, *c;
    bf16* out;
    int zero;
};

__device__ __forceinline__ void mbar_init(uint32_t bar, uint32_t cnt) {
    asm volatile("mbarrier.init.shared::cta.b64 [%0], %1;" ::"r"(bar), "r"(cnt) : "memory");
}
__device__ __forceinline__ void mbar_wait(uint32_t bar, uint32_t parity) {
    asm volatile("{\n.reg .pred p;\nL_%=:\nmbarrier.try_wait.parity.shared::cta.b64 p, [%0], %1;\n@!p bra L_%=;\n}" ::"r"(bar), "r"(parity) : "memory");
}
__device__ __forceinline__ void mbar_sleep(uint32_t bar) {
    if ((threadIdx.x & 31) == 0)
        asm volatile("{\n.reg .pred p;\nL_%=:\nmbarrier.try_wait.parity.shared::cta.b64 p, [%0], 0, 100000;\n@!p bra L_%=;\n}" ::"r"(bar) : "memory");
    __syncwarp();
}
__device__ __forceinline__ void mbar_watch(uint32_t bar, uint32_t parity) {
    asm volatile("{\n.reg .pred p;\n.reg .u32 n;\nmov.u32 n, 0;\n"
                 "L_%=:\nmbarrier.try_wait.parity.shared::cta.b64 p, [%0], %1;\n@p bra D_%=;\n"
                 "add.u32 n, n, 1;\nsetp.lt.u32 p, n, %2;\n@p bra L_%=;\ntrap;\nD_%=:\n}"
                 ::"r"(bar), "r"(parity), "n"(SPIN_LIMIT) : "memory");
}
__device__ __forceinline__ void step_watch(uint32_t a, uint32_t step) {
    asm volatile("{\n.reg .pred p;\n.reg .u32 n, v;\nmov.u32 n, 0;\n"
                 "L_%=:\nld.volatile.shared.u32 v, [%0];\nsetp.ge.u32 p, v, %1;\n@p bra D_%=;\nnanosleep.u32 400;\n"
                 "add.u32 n, n, 1;\nsetp.lt.u32 p, n, %2;\n@p bra L_%=;\ntrap;\nD_%=:\n}"
                 ::"r"(a), "r"(step), "n"(SPIN_LIMIT) : "memory");
}
__device__ __forceinline__ void mbar_arrive_if(uint32_t bar, bool on) {
    asm volatile("{\n.reg .pred p;\nsetp.ne.s32 p, %1, 0;\n@p mbarrier.arrive.shared::cta.b64 _, [%0];\n}" ::"r"(bar), "r"((int)on) : "memory");
}
__device__ __forceinline__ void tma2d(uint32_t dst, const CUtensorMap* m, int c0, int c1, uint32_t bar, bool first) {
    asm volatile("{\n.reg .pred p;\nelect.sync _|p, 0xffffffff;\n"
                 "@p cp.async.bulk.tensor.2d.shared::cluster.global.mbarrier::complete_tx::bytes.L2::cache_hint [%0], [%1, {%3, %4}], [%2], %5;\n}"
                 ::"r"(dst), "l"(m), "r"(bar), "r"(c0), "r"(c1), "l"(first ? L2_FIRST : L2_NORMAL) : "memory");
}
__device__ __forceinline__ void tma3d_prefetch(const CUtensorMap* m, int row, int cb) {
    asm volatile("{\n.reg .pred p;\nelect.sync _|p, 0xffffffff;\n@p cp.async.bulk.prefetch.tensor.3d.L2.global [%0, {%1, %2, %3}];\n}"
                 ::"l"(m), "r"(0), "r"(row), "r"(cb) : "memory");
}
__device__ __forceinline__ void l2_prefetch(const void* p, uint32_t bytes) {
    asm volatile("{\n.reg .pred p;\nelect.sync _|p, 0xffffffff;\n@p cp.async.bulk.prefetch.L2.global [%0], %1;\n}" ::"l"(p), "r"(bytes) : "memory");
}
__device__ __forceinline__ void bulk_store(void* dst, uint32_t src, uint32_t bytes, bool first) {
    asm volatile("{\n.reg .pred p;\nelect.sync _|p, 0xffffffff;\n@p cp.async.bulk.global.shared::cta.bulk_group.L2::cache_hint [%0], [%1], %2, %3;\n}"
                 ::"l"(dst), "r"(src), "r"(bytes), "l"(first ? L2_FIRST : L2_NORMAL) : "memory");
}
__device__ __forceinline__ void flag_wait(const uint32_t* f, uint32_t target) {
    asm volatile("{\n.reg .pred p;\n.reg .u32 v;\n"
                 "L_%=:\nld.acquire.gpu.global.u32 v, [%0];\nsub.u32 v, v, %1;\nsetp.lt.s32 p, v, 0;\n@p nanosleep.u32 100;\n@p bra L_%=;\n}"
                 ::"l"(f), "r"(target) : "memory");
}
__device__ __forceinline__ uint4 ld_poll(const uint4* p) {
    uint4 v;
    asm volatile("{\n.reg .b128 t;\nld.relaxed.gpu.global.b128 t, [%4];\nmov.b128 {%0, %1, %2, %3}, t;\n}"
                 : "=r"(v.x), "=r"(v.y), "=r"(v.z), "=r"(v.w) : "l"(p) : "memory");
    return v;
}
__device__ __forceinline__ void st_pub(uint4* p, uint4 v, bool on) {
    asm volatile("{\n.reg .pred p;\n.reg .b128 t;\nsetp.ne.s32 p, %5, 0;\nmov.b128 t, {%1, %2, %3, %4};\n@p st.relaxed.gpu.global.b128 [%0], t;\n}"
                 ::"l"(p), "r"(v.x), "r"(v.y), "r"(v.z), "r"(v.w), "r"((int)on) : "memory");
}
__device__ __forceinline__ void st_pub(uint32_t* p, uint32_t v, bool on) {
    asm volatile("{\n.reg .pred p;\nsetp.ne.s32 p, %2, 0;\n@p st.relaxed.gpu.global.u32 [%0], %1;\n}" ::"l"(p), "r"(v), "r"((int)on) : "memory");
}
__device__ __forceinline__ void flag_add(uint32_t* p) {
    asm volatile("red.release.gpu.global.add.u32 [%0], 1;" ::"l"(p) : "memory");
}
__device__ __forceinline__ uint32_t lds32(uint32_t a) {
    uint32_t v;
    asm volatile("ld.shared.u32 %0, [%1];" : "=r"(v) : "r"(a) : "memory");
    return v;
}
__device__ __forceinline__ uint4 lds128(uint32_t a) {
    uint4 v;
    asm volatile("ld.shared.v4.u32 {%0, %1, %2, %3}, [%4];" : "=r"(v.x), "=r"(v.y), "=r"(v.z), "=r"(v.w) : "r"(a) : "memory");
    return v;
}
__device__ __forceinline__ void sched_fence(uint32_t& v, uint32_t z) {
    uint32_t ck;
    asm volatile("mov.u32 %0, %%clock;" : "=r"(ck)::"memory");
    v ^= ck & z;
}
__device__ __forceinline__ void fence_async_global() { asm volatile("fence.proxy.async.global;" ::: "memory"); }
__device__ __forceinline__ void fence_async_smem() { asm volatile("fence.proxy.async.shared::cta;" ::: "memory"); }
__device__ __forceinline__ void bar_sync(int id, int n) { asm volatile("bar.sync %0, %1;" ::"r"(id), "r"(n) : "memory"); }
__device__ __forceinline__ void bar_arrive(int id, int n) { asm volatile("bar.arrive %0, %1;" ::"r"(id), "r"(n) : "memory"); }
__device__ __forceinline__ void wg_fence() { asm volatile("wgmma.fence.sync.aligned;" ::: "memory"); }
__device__ __forceinline__ void wg_commit() { asm volatile("wgmma.commit_group.sync.aligned;" ::: "memory"); }
template <int N> __device__ __forceinline__ void wg_wait() { asm volatile("wgmma.wait_group.sync.aligned %0;" ::"n"(N) : "memory"); }
template <int N> __device__ __forceinline__ void reg_fence(float (&d)[N]) {
#pragma unroll
    for (int i = 0; i < N; i++) asm volatile("" : "+f"(d[i])::"memory");
}
template <int N> __device__ __forceinline__ void reg_fence(uint32_t (&d)[N]) {
#pragma unroll
    for (int i = 0; i < N; i++) asm volatile("" : "+r"(d[i])::"memory");
}
__device__ __forceinline__ uint32_t desc_k(uint32_t a) { return ((a & 0x3ffff) >> 4) | (1u << 16); }
__device__ __forceinline__ uint32_t desc_mn(uint32_t a) { return ((a & 0x3ffff) >> 4) | (1024u << 16); }

template <int TB>
__device__ __forceinline__ void wgmma_ss128(float (&d)[64], uint32_t da, uint32_t db, int acc, uint32_t ha = 0x40000040u, uint32_t hb = 0x40000040u) {
    asm volatile("{\n.reg .pred p;\n.reg .b64 a, b;\nsetp.ne.b32 p, %66, 0;\nmov.b64 a, {%64, %68};\nmov.b64 b, {%65, %69};\n"
        "wgmma.mma_async.sync.aligned.m64n128k16.f32.bf16.bf16 {%0, %1, %2, %3, %4, %5, %6, %7, %8, %9, %10, %11, %12, %13, %14, %15, %16, %17, %18, %19, %20, %21, %22, %23, %24, %25, %26, %27, %28, %29, %30, %31, %32, %33, %34, %35, %36, %37, %38, %39, %40, %41, %42, %43, %44, %45, %46, %47, %48, %49, %50, %51, %52, %53, %54, %55, %56, %57, %58, %59, %60, %61, %62, %63}, a, b, p, 1, 1, 0, %67;\n}"
        : "+f"(d[0]), "+f"(d[1]), "+f"(d[2]), "+f"(d[3]), "+f"(d[4]), "+f"(d[5]), "+f"(d[6]), "+f"(d[7]), "+f"(d[8]), "+f"(d[9]), "+f"(d[10]), "+f"(d[11]), "+f"(d[12]), "+f"(d[13]), "+f"(d[14]), "+f"(d[15]), "+f"(d[16]), "+f"(d[17]), "+f"(d[18]), "+f"(d[19]), "+f"(d[20]), "+f"(d[21]), "+f"(d[22]), "+f"(d[23]), "+f"(d[24]), "+f"(d[25]), "+f"(d[26]), "+f"(d[27]), "+f"(d[28]), "+f"(d[29]), "+f"(d[30]), "+f"(d[31]), "+f"(d[32]), "+f"(d[33]), "+f"(d[34]), "+f"(d[35]), "+f"(d[36]), "+f"(d[37]), "+f"(d[38]), "+f"(d[39]), "+f"(d[40]), "+f"(d[41]), "+f"(d[42]), "+f"(d[43]), "+f"(d[44]), "+f"(d[45]), "+f"(d[46]), "+f"(d[47]), "+f"(d[48]), "+f"(d[49]), "+f"(d[50]), "+f"(d[51]), "+f"(d[52]), "+f"(d[53]), "+f"(d[54]), "+f"(d[55]), "+f"(d[56]), "+f"(d[57]), "+f"(d[58]), "+f"(d[59]), "+f"(d[60]), "+f"(d[61]), "+f"(d[62]), "+f"(d[63])
        : "r"(da), "r"(db), "r"(acc), "n"(TB), "r"(ha), "r"(hb));
}
template <int TB>
__device__ __forceinline__ void wgmma_ss128_init(float (&d)[64], uint32_t da, uint32_t db, uint32_t ha = 0x40000040u, uint32_t hb = 0x40000040u) {
    asm volatile("{\n.reg .pred p;\n.reg .b64 a, b;\nsetp.ne.b32 p, 0, 0;\nmov.b64 a, {%64, %67};\nmov.b64 b, {%65, %68};\n"
        "wgmma.mma_async.sync.aligned.m64n128k16.f32.bf16.bf16 {%0, %1, %2, %3, %4, %5, %6, %7, %8, %9, %10, %11, %12, %13, %14, %15, %16, %17, %18, %19, %20, %21, %22, %23, %24, %25, %26, %27, %28, %29, %30, %31, %32, %33, %34, %35, %36, %37, %38, %39, %40, %41, %42, %43, %44, %45, %46, %47, %48, %49, %50, %51, %52, %53, %54, %55, %56, %57, %58, %59, %60, %61, %62, %63}, a, b, p, 1, 1, 0, %66;\n}"
        : "=f"(d[0]), "=f"(d[1]), "=f"(d[2]), "=f"(d[3]), "=f"(d[4]), "=f"(d[5]), "=f"(d[6]), "=f"(d[7]), "=f"(d[8]), "=f"(d[9]), "=f"(d[10]), "=f"(d[11]), "=f"(d[12]), "=f"(d[13]), "=f"(d[14]), "=f"(d[15]), "=f"(d[16]), "=f"(d[17]), "=f"(d[18]), "=f"(d[19]), "=f"(d[20]), "=f"(d[21]), "=f"(d[22]), "=f"(d[23]), "=f"(d[24]), "=f"(d[25]), "=f"(d[26]), "=f"(d[27]), "=f"(d[28]), "=f"(d[29]), "=f"(d[30]), "=f"(d[31]), "=f"(d[32]), "=f"(d[33]), "=f"(d[34]), "=f"(d[35]), "=f"(d[36]), "=f"(d[37]), "=f"(d[38]), "=f"(d[39]), "=f"(d[40]), "=f"(d[41]), "=f"(d[42]), "=f"(d[43]), "=f"(d[44]), "=f"(d[45]), "=f"(d[46]), "=f"(d[47]), "=f"(d[48]), "=f"(d[49]), "=f"(d[50]), "=f"(d[51]), "=f"(d[52]), "=f"(d[53]), "=f"(d[54]), "=f"(d[55]), "=f"(d[56]), "=f"(d[57]), "=f"(d[58]), "=f"(d[59]), "=f"(d[60]), "=f"(d[61]), "=f"(d[62]), "=f"(d[63])
        : "r"(da), "r"(db), "n"(TB), "r"(ha), "r"(hb));
}
template <int TB>
__device__ __forceinline__ void wgmma_ss64(float (&d)[32], uint32_t da, uint32_t db, int acc, uint32_t ha = 0x40000040u, uint32_t hb = 0x40000040u) {
    asm volatile("{\n.reg .pred p;\n.reg .b64 a, b;\nsetp.ne.b32 p, %34, 0;\nmov.b64 a, {%32, %36};\nmov.b64 b, {%33, %37};\n"
        "wgmma.mma_async.sync.aligned.m64n64k16.f32.bf16.bf16 {%0, %1, %2, %3, %4, %5, %6, %7, %8, %9, %10, %11, %12, %13, %14, %15, %16, %17, %18, %19, %20, %21, %22, %23, %24, %25, %26, %27, %28, %29, %30, %31}, a, b, p, 1, 1, 0, %35;\n}"
        : "+f"(d[0]), "+f"(d[1]), "+f"(d[2]), "+f"(d[3]), "+f"(d[4]), "+f"(d[5]), "+f"(d[6]), "+f"(d[7]), "+f"(d[8]), "+f"(d[9]), "+f"(d[10]), "+f"(d[11]), "+f"(d[12]), "+f"(d[13]), "+f"(d[14]), "+f"(d[15]), "+f"(d[16]), "+f"(d[17]), "+f"(d[18]), "+f"(d[19]), "+f"(d[20]), "+f"(d[21]), "+f"(d[22]), "+f"(d[23]), "+f"(d[24]), "+f"(d[25]), "+f"(d[26]), "+f"(d[27]), "+f"(d[28]), "+f"(d[29]), "+f"(d[30]), "+f"(d[31])
        : "r"(da), "r"(db), "r"(acc), "n"(TB), "r"(ha), "r"(hb));
}
template <int TB>
__device__ __forceinline__ void wgmma_ss64_init(float (&d)[32], uint32_t da, uint32_t db, uint32_t ha = 0x40000040u, uint32_t hb = 0x40000040u) {
    asm volatile("{\n.reg .pred p;\n.reg .b64 a, b;\nsetp.ne.b32 p, 0, 0;\nmov.b64 a, {%32, %35};\nmov.b64 b, {%33, %36};\n"
        "wgmma.mma_async.sync.aligned.m64n64k16.f32.bf16.bf16 {%0, %1, %2, %3, %4, %5, %6, %7, %8, %9, %10, %11, %12, %13, %14, %15, %16, %17, %18, %19, %20, %21, %22, %23, %24, %25, %26, %27, %28, %29, %30, %31}, a, b, p, 1, 1, 0, %34;\n}"
        : "=f"(d[0]), "=f"(d[1]), "=f"(d[2]), "=f"(d[3]), "=f"(d[4]), "=f"(d[5]), "=f"(d[6]), "=f"(d[7]), "=f"(d[8]), "=f"(d[9]), "=f"(d[10]), "=f"(d[11]), "=f"(d[12]), "=f"(d[13]), "=f"(d[14]), "=f"(d[15]), "=f"(d[16]), "=f"(d[17]), "=f"(d[18]), "=f"(d[19]), "=f"(d[20]), "=f"(d[21]), "=f"(d[22]), "=f"(d[23]), "=f"(d[24]), "=f"(d[25]), "=f"(d[26]), "=f"(d[27]), "=f"(d[28]), "=f"(d[29]), "=f"(d[30]), "=f"(d[31])
        : "r"(da), "r"(db), "n"(TB), "r"(ha), "r"(hb));
}
__device__ __forceinline__ void wgmma_rs128(float (&d)[64], uint32_t a0, uint32_t a1, uint32_t a2, uint32_t a3, uint32_t db, int acc, uint32_t hb = 0x40000040u) {
    asm volatile("{\n.reg .pred p;\n.reg .b64 b;\nsetp.ne.b32 p, %69, 0;\nmov.b64 b, {%68, %70};\n"
        "wgmma.mma_async.sync.aligned.m64n128k16.f32.bf16.bf16 {%0, %1, %2, %3, %4, %5, %6, %7, %8, %9, %10, %11, %12, %13, %14, %15, %16, %17, %18, %19, %20, %21, %22, %23, %24, %25, %26, %27, %28, %29, %30, %31, %32, %33, %34, %35, %36, %37, %38, %39, %40, %41, %42, %43, %44, %45, %46, %47, %48, %49, %50, %51, %52, %53, %54, %55, %56, %57, %58, %59, %60, %61, %62, %63}, {%64, %65, %66, %67}, b, p, 1, 1, 1;\n}"
        : "+f"(d[0]), "+f"(d[1]), "+f"(d[2]), "+f"(d[3]), "+f"(d[4]), "+f"(d[5]), "+f"(d[6]), "+f"(d[7]), "+f"(d[8]), "+f"(d[9]), "+f"(d[10]), "+f"(d[11]), "+f"(d[12]), "+f"(d[13]), "+f"(d[14]), "+f"(d[15]), "+f"(d[16]), "+f"(d[17]), "+f"(d[18]), "+f"(d[19]), "+f"(d[20]), "+f"(d[21]), "+f"(d[22]), "+f"(d[23]), "+f"(d[24]), "+f"(d[25]), "+f"(d[26]), "+f"(d[27]), "+f"(d[28]), "+f"(d[29]), "+f"(d[30]), "+f"(d[31]), "+f"(d[32]), "+f"(d[33]), "+f"(d[34]), "+f"(d[35]), "+f"(d[36]), "+f"(d[37]), "+f"(d[38]), "+f"(d[39]), "+f"(d[40]), "+f"(d[41]), "+f"(d[42]), "+f"(d[43]), "+f"(d[44]), "+f"(d[45]), "+f"(d[46]), "+f"(d[47]), "+f"(d[48]), "+f"(d[49]), "+f"(d[50]), "+f"(d[51]), "+f"(d[52]), "+f"(d[53]), "+f"(d[54]), "+f"(d[55]), "+f"(d[56]), "+f"(d[57]), "+f"(d[58]), "+f"(d[59]), "+f"(d[60]), "+f"(d[61]), "+f"(d[62]), "+f"(d[63])
        : "r"(a0), "r"(a1), "r"(a2), "r"(a3), "r"(db), "r"(acc), "r"(hb));
}

__device__ __forceinline__ uint32_t pack2(float lo, float hi) {
    uint32_t r;
    asm("cvt.rn.bf16x2.f32 %0, %1, %2;" : "=r"(r) : "f"(hi), "f"(lo));
    return r;
}
__device__ __forceinline__ float bf_lo(uint32_t v) { return __uint_as_float(v << 16); }
__device__ __forceinline__ float bf_hi(uint32_t v) { return __uint_as_float(v & 0xffff0000u); }
__device__ __forceinline__ float rbf(float v) { return bf_lo(pack2(v, v)); }
__device__ __forceinline__ uint32_t badd(uint32_t a, uint32_t b) {
    uint32_t r;
    asm("add.rn.bf16x2 %0, %1, %2;" : "=r"(r) : "r"(a), "r"(b));
    return r;
}
__device__ __forceinline__ uint32_t bsub(uint32_t a, uint32_t b) {
    uint32_t r;
    asm("sub.rn.bf16x2 %0, %1, %2;" : "=r"(r) : "r"(a), "r"(b));
    return r;
}
__device__ __forceinline__ uint32_t bmul(uint32_t a, uint32_t b) {
    uint32_t r;
    asm("mul.rn.bf16x2 %0, %1, %2;" : "=r"(r) : "r"(a), "r"(b));
    return r;
}
__device__ __forceinline__ uint32_t ln_apply(uint32_t x, uint32_t mb, float rs, uint32_t scale, uint32_t shift) {
    const uint32_t d = bsub(x, mb);
    return badd(bmul(pack2(bf_lo(d) * rs, bf_hi(d) * rs), scale), shift);
}
__device__ __forceinline__ float ex2(float v) {
    float r;
    asm("ex2.approx.ftz.f32 %0, %1;" : "=f"(r) : "f"(v));
    return r;
}
__device__ __forceinline__ float rcp(float v) {
    float r;
    asm("rcp.approx.ftz.f32 %0, %1;" : "=f"(r) : "f"(v));
    return r;
}
__device__ __forceinline__ float sqrt_fast(float v) {
    float r;
    asm("sqrt.approx.ftz.f32 %0, %1;" : "=f"(r) : "f"(v));
    return r;
}
__device__ __forceinline__ float ln_rstd(float var) { return rcp(rbf(sqrt_fast(rbf(rbf(var) + 1e-5f)))); }
__device__ __forceinline__ float sigmoid(float v) { return rcp(1.f + ex2(-1.4426950408889634f * v)); }
__device__ __forceinline__ float quad_sum(float v) {
    v += __shfl_xor_sync(0xffffffffu, v, 1);
    return v + __shfl_xor_sync(0xffffffffu, v, 2);
}

constexpr uint32_t HI_128 = 0x40000040u, HI_IMG = 0x80000080u, HI_Q = 0x80000040u;
template <int M, int RH>
__device__ __forceinline__ uint4 img_pack(const float (&d)[64], float s) {
    uint4 v;
    v.x = pack2(d[16 * M + 2 * RH] * s, d[16 * M + 2 * RH + 1] * s);
    v.y = pack2(d[16 * M + 4 + 2 * RH] * s, d[16 * M + 5 + 2 * RH] * s);
    v.z = pack2(d[16 * M + 8 + 2 * RH] * s, d[16 * M + 9 + 2 * RH] * s);
    v.w = pack2(d[16 * M + 12 + 2 * RH] * s, d[16 * M + 13 + 2 * RH] * s);
    return v;
}
template <int M>
__device__ __forceinline__ void img_store_global(uint8_t* img, uint32_t toff, const float (&d)[64], float s0, float s1) {
    uint4* p = reinterpret_cast<uint4*>(img + toff) + M * 32;
    p[0] = img_pack<M, 0>(d, s0);
    p[128] = img_pack<M, 1>(d, s1);
}
__device__ __forceinline__ void sts128(uint32_t a, uint4 v) {
    asm volatile("st.shared.v4.b32 [%0], {%1, %2, %3, %4};" ::"r"(a), "r"(v.x), "r"(v.y), "r"(v.z), "r"(v.w) : "memory");
}
constexpr float SM_C = 0.08838834764831845f * 1.4426950408889634f;
__device__ __forceinline__ float pack2f(float lo, float hi) {
    float r;
    asm("{\n.reg .b32 t;\ncvt.rn.bf16x2.f32 t, %1, %2;\nmov.b32 %0, t;\n}" : "=f"(r) : "f"(hi), "f"(lo));
    return r;
}
template <int M, bool SCALE, bool PARK>
__device__ __forceinline__ void pack_group(float (&d)[64], float (&v)[8], float s0, float s1) {
#pragma unroll
    for (int i = 0; i < 8; i++) {
        const int k = 16 * M + 4 * (i & 3) + 2 * (i >> 2);
        v[i] = SCALE ? pack2f(d[k] * (i < 4 ? s0 : s1), d[k + 1] * (i < 4 ? s0 : s1)) : pack2f(d[k], d[k + 1]);
        if (PARK && M > 0) d[16 * (M > 0 ? M - 1 : 0) + i] = v[i];
    }
}
__device__ __forceinline__ uint32_t q_off(uint32_t toff) { return (((toff >> 1) & ~2047u) ^ 8192) + (toff & 511); }
template <int M, bool PARK>
__device__ __forceinline__ void ctx_store_part(float4* p, float (&d)[64], float i0, float i1) {
    float v[8];
    pack_group<M, true, PARK>(d, v, i0, i1);
    p[M * 32] = make_float4(v[0], v[1], v[2], v[3]);
    p[M * 32 + 128] = make_float4(v[4], v[5], v[6], v[7]);
}
template <bool PARK>
__device__ __forceinline__ void ctx_store(uint8_t* img, uint32_t toff, float (&o)[64], float l0, float l1) {
    const float i0 = rcp(quad_sum(l0)), i1 = rcp(quad_sum(l1));
    float4* p = reinterpret_cast<float4*>(img + toff);
    ctx_store_part<0, PARK>(p, o, i0, i1); ctx_store_part<1, PARK>(p, o, i0, i1); ctx_store_part<2, PARK>(p, o, i0, i1); ctx_store_part<3, PARK>(p, o, i0, i1);
}

template <int M>
__device__ __forceinline__ void tile_store_part(float4* p, uint32_t a, float (&d)[64], float i0, float i1, int ctx) {
    float v[8];
    pack_group<M, true, true>(d, v, i0, i1);
#pragma unroll
    for (int h = 0; h < 2; h++)
        asm volatile("{\n.reg .pred p;\nsetp.ne.s32 p, %6, 0;\n@p st.global.v4.f32 [%0], {%2, %3, %4, %5};\n@!p st.shared.v4.f32 [%1], {%2, %3, %4, %5};\n}"
                     ::"l"(p + M * 32 + h * 128), "r"(a + (M >> 1) * 16384 + (M & 1) * 512 + h * 1024),
                     "f"(v[4 * h]), "f"(v[4 * h + 1]), "f"(v[4 * h + 2]), "f"(v[4 * h + 3]), "r"(ctx) : "memory");
}
__device__ __forceinline__ void tile_store(uint8_t* img, uint32_t a, uint32_t toff, float (&d)[64], float i0, float i1, int ctx) {
    float4* p = reinterpret_cast<float4*>(img + toff);
    a += q_off(toff);
    tile_store_part<0>(p, a, d, i0, i1, ctx); tile_store_part<1>(p, a, d, i0, i1, ctx);
    tile_store_part<2>(p, a, d, i0, i1, ctx); tile_store_part<3>(p, a, d, i0, i1, ctx);
}

__device__ __forceinline__ void slot_wait(uint32_t bars, uint32_t& ph, uint32_t slot) {
    mbar_wait(bars + 8 * slot, (ph >> slot) & 1);
    ph ^= 1u << slot;
}
__device__ __forceinline__ void release_if(uint32_t eb, uint32_t slot, bool on) {
    asm volatile("{\n.reg .pred p;\nsetp.ne.s32 p, %1, 0;\n@p mbarrier.arrive.shared::cluster.b64 _, [%0];\n}" ::"r"(eb + 8 * slot), "r"((int)on) : "memory");
}
__device__ __forceinline__ void slot_acquire(uint32_t sb, uint32_t& ph, uint32_t slot) {
    slot_wait(sb + BAR_EMPTY, ph, slot);
    asm volatile("{\n.reg .pred p;\nelect.sync _|p, 0xffffffff;\n@p mbarrier.arrive.expect_tx.shared::cta.b64 _, [%0], 32768;\n}"
                 ::"r"(sb + BAR_FULL + 8 * slot) : "memory");
}
__device__ __forceinline__ void load_bulk(uint32_t sb, uint32_t slot, uint32_t off, const void* src, uint32_t bytes, bool both, bool first) {
    if (both)
        asm volatile("{\n.reg .pred p;\nelect.sync _|p, 0xffffffff;\n"
                     "@p cp.async.bulk.shared::cluster.global.mbarrier::complete_tx::bytes.multicast::cluster.L2::cache_hint [%0], [%1], %5, [%2], %4, %3;\n}"
                     ::"r"(sb + slot * SLOT + off), "l"(src), "r"(sb + BAR_FULL + 8 * slot), "l"(first ? L2_FIRST : L2_NORMAL), "h"((uint16_t)3),
                     "r"(bytes) : "memory");
    else
        asm volatile("{\n.reg .pred p;\nelect.sync _|p, 0xffffffff;\n"
                     "@p cp.async.bulk.shared::cluster.global.mbarrier::complete_tx::bytes.L2::cache_hint [%0], [%1], %4, [%2], %3;\n}"
                     ::"r"(sb + slot * SLOT + off), "l"(src), "r"(sb + BAR_FULL + 8 * slot), "l"(first ? L2_FIRST : L2_NORMAL), "r"(bytes) : "memory");
}
__device__ __forceinline__ void load_tile(uint32_t sb, uint32_t slot, uint32_t off, const CUtensorMap* m, int row, int cb, bool both, bool first) {
    if (both)
        asm volatile("{\n.reg .pred p;\nelect.sync _|p, 0xffffffff;\n"
                     "@p cp.async.bulk.tensor.3d.shared::cluster.global.mbarrier::complete_tx::bytes.multicast::cluster.L2::cache_hint [%0], [%1, {%3, %4, %5}], [%2], %7, %6;\n}"
                     ::"r"(sb + slot * SLOT + off), "l"(m), "r"(sb + BAR_FULL + 8 * slot), "r"(0), "r"(row), "r"(cb),
                     "l"(first ? L2_FIRST : L2_NORMAL), "h"((uint16_t)3) : "memory");
    else
        asm volatile("{\n.reg .pred p;\nelect.sync _|p, 0xffffffff;\n"
                     "@p cp.async.bulk.tensor.3d.shared::cluster.global.mbarrier::complete_tx::bytes.L2::cache_hint [%0], [%1, {%3, %4, %5}], [%2], %6;\n}"
                     ::"r"(sb + slot * SLOT + off), "l"(m), "r"(sb + BAR_FULL + 8 * slot), "r"(0), "r"(row), "r"(cb),
                     "l"(first ? L2_FIRST : L2_NORMAL) : "memory");
}
__device__ __forceinline__ uint32_t ring_next(uint32_t r) { return r == 4 ? 0 : r + 1; }
__device__ __forceinline__ uint32_t w_table(int hp) { return hp ? 0x3104u : 0x4210u; }
__device__ __forceinline__ uint32_t a_table(int hp) { return hp ? 0x625u : 0x635u; }
__device__ __forceinline__ uint32_t a_next(uint32_t& t) {
    const uint32_t s = t & 15;
    t = (t >> 4) | (s << 8);
    return s;
}
constexpr uint32_t O_TABLE = 0x1604235u;
__device__ __forceinline__ uint32_t o_next(uint32_t& t) {
    const uint32_t s = t & 15;
    t = (t >> 4) | (s << 24);
    return s;
}
__device__ __forceinline__ int o_head(int i, int kh) { return i < 16 ? 4 * (i & 7) + 2 * (kh ^ 1) + (i >> 3) : 29 + 2 * kh; }

template <bool INIT>
__device__ __forceinline__ void gemm_issue(float (&d)[64], uint32_t a, uint32_t b, int acc, bool img) {
    const uint32_t ha = img ? HI_IMG : HI_128, o2 = img ? 32 : 4, o4 = img ? 64 : 1024;
    wg_fence();
#pragma unroll
    for (int k = 0; k < 8; k++) {
        if (INIT && k == 0) wgmma_ss128_init<1>(d, a, b, ha);
        else wgmma_ss128<1>(d, a + (k >> 2) * o4 + ((k >> 1) & 1) * o2 + (k & 1) * 2, b + k * 128, k ? 1 : acc, ha);
    }
    wg_commit();
}

template <bool ODD>
__device__ __forceinline__ bool proj_tile(float (&acc)[64], float (&prev)[64], int t, int q0, uint32_t sb, int wg, uint32_t eb, bool rel, uint32_t& fph,
                                          uint32_t wtab, uint32_t& atab, uint8_t* prev_img, uint32_t toff, float s0, float s1,
                                          uint32_t (&v)[32]) {
    const uint32_t a0 = desc_k(sb + (wg ^ (ODD && t == 5)) * 8192), b0 = desc_mn(sb);
    constexpr int U = ODD ? UNR : 1;
#pragma unroll U
    for (int q = ODD ? 0 : q0; q < 4; q++) {
        const uint32_t ws = (wtab >> (4 * q)) & 15, as = a_next(atab);
        if (!ODD && t != 2) slot_wait(sb + BAR_FULL, fph, ws);
        slot_wait(sb + BAR_FULL, fph, as);
        if (ODD && q == 2 && t == 5) {
#pragma unroll
            for (int i = 0; i < 8; i++) sts128(sb + 5 * SLOT + q_off(toff) + (i >> 2) * 16384 + (i & 2) * 256 + (i & 1) * 1024, make_uint4(v[4 * i], v[4 * i + 1], v[4 * i + 2], v[4 * i + 3]));
        }
        bar_sync(1 + wg, 256);
        gemm_issue<false>(acc, a0 + as * (SLOT / 16), b0 + ws * (SLOT / 16), q, false);
        bar_arrive(2 - wg, 256);
        wg_wait<1>();
        reg_fence(prev);
        if (ODD && t == 5) {
            if (q == 0) {
#pragma unroll
                for (int i = 0; i < 32; i++) {
                    const int k = 16 * (i >> 3) + 4 * (i & 3) + ((i >> 1) & 2);
                    v[i] = pack2(prev[k], prev[k + 1]);
                }
            }
            if (q == 2) {
                fence_async_smem();
                slot_wait(sb + BAR_FULL, fph, wtab & 15);
                wg_wait<0>();
                release_if(eb, as, rel);
                release_if(eb, ws, rel);
                reg_fence(acc);
                return true;
            }
        } else {
            if (q == 0) img_store_global<0>(prev_img, toff, prev, s0, s1);
            if (q == 1) img_store_global<1>(prev_img, toff, prev, s0, s1);
            if (q == 2) img_store_global<2>(prev_img, toff, prev, s0, s1);
            if (q == 3) img_store_global<3>(prev_img, toff, prev, s0, s1);
        }
        wg_wait<0>();
        release_if(eb, as, rel && !(ODD && (q & 1) && t == 5));
        if (ODD) release_if(eb, ws, rel && t != 1);
    }
    reg_fence(acc);
    return false;
}

__device__ __forceinline__ void qk_issue(float (&s)[64], uint32_t q, uint32_t k) {
    wg_fence();
    wgmma_ss128_init<0>(s, q, k, HI_Q, HI_IMG);
#pragma unroll
    for (int i = 1; i < 8; i++) wgmma_ss128<0>(s, q + (i >> 2) * 1024 + (i & 2) * 16 + (i & 1) * 2, k + (i >> 1) * 32 + (i & 1) * 2, 1, HI_Q, HI_IMG);
    wg_commit();
}
__device__ __forceinline__ void qk_issue(float (&s)[32], uint32_t q, uint32_t k) {
    wg_fence();
    wgmma_ss64_init<0>(s, q, k, HI_Q, HI_IMG);
#pragma unroll
    for (int i = 1; i < 8; i++) wgmma_ss64<0>(s, q + (i >> 2) * 1024 + (i & 2) * 16 + (i & 1) * 2, k + (i >> 1) * 32 + (i & 1) * 2, 1, HI_Q, HI_IMG);
    wg_commit();
}
__device__ __forceinline__ void pv_issue(float (&o)[64], const uint32_t (&p)[32], uint32_t v, int acc, bool half) {
    if (half) {
        asm volatile("// half" ::: "memory");
        wg_fence();
#pragma unroll
        for (int i = 0; i < 4; i++) wgmma_rs128(o, p[4 * i], p[4 * i + 1], p[4 * i + 2], p[4 * i + 3], v + i * 256, i ? 1 : acc, HI_IMG);
        wg_commit();
        asm volatile("// half" ::: "memory");
    } else {
        wg_fence();
#pragma unroll
        for (int i = 0; i < 8; i++) wgmma_rs128(o, p[4 * i], p[4 * i + 1], p[4 * i + 2], p[4 * i + 3], v + i * 256, i ? 1 : acc, HI_IMG);
        wg_commit();
    }
}
__device__ __forceinline__ void tri_mask(float (&s)[64], float x) {
#pragma unroll
    for (int k = 0; k < 16; k++) {
        float b;
        asm("sub.sat.f32 %0, %1, %2;" : "=f"(b) : "f"((float)(8 * (k >> 1) + (k & 1))), "f"(x));
        const int i = 32 + 4 * (k >> 1) + (k & 1);
        asm("fma.rn.f32 %0, %1, 0fFF61B1E6, %0;" : "+f"(s[i]) : "f"(b));
        if (k < 14) asm("fma.rn.f32 %0, %1, 0fFF61B1E6, %0;" : "+f"(s[i + 6]) : "f"(b));
    }
}
__device__ __forceinline__ void tri_mask_copy(float (&s)[64], const float (&h)[32], float x) {
#pragma unroll
    for (int i = 0; i < 32; i++) {
        asm("{\n.reg .pred p;\nsetp.lt.f32 p, %2, %3;\nselp.f32 %0, 0fFF800000, %1, p;\n}"
            : "=f"(s[i]) : "f"(h[i]), "f"(x), "f"((float)(8 * (i >> 2) - 4 * (i & 2) + (i & 1))));
        s[32 + i] = __uint_as_float(0xff800000u);
    }
}
constexpr float SM_HI = 1152921504606846976.f, SM_LO = 1.f / 1152921504606846976.f;
__device__ __forceinline__ bool softmax_unsafe(float t0, float t1, bool first) {
    bool bad = __any_sync(0xffffffffu, fmaxf(t0, t1) > SM_HI);
    if (first) {
        uint32_t a = __ballot_sync(0xffffffffu, t0 >= SM_LO), b = __ballot_sync(0xffffffffu, t1 >= SM_LO);
        a |= a >> 1;
        b |= b >> 1;
        bad |= ((a | (a >> 2)) & (b | (b >> 2)) & 0x11111111u) != 0x11111111u;
    }
    return bad;
}
__device__ __forceinline__ void softmax_shift(float (&s)[64], float d0, float d1) {
#pragma unroll
    for (int i = 0; i < 64; i++) s[i] -= (i & 2) ? d1 : d0;
}
__device__ __forceinline__ void softmax_remax(float (&s)[64], float (&m)[2], bool first, float& a0, float& a1) {
    float m0 = fmaxf(s[0], s[1]), m1 = fmaxf(s[2], s[3]);
#pragma unroll
    for (int k = 1; k < 16; k++) {
        m0 = fmaxf(m0, fmaxf(s[4 * k], s[4 * k + 1]));
        m1 = fmaxf(m1, fmaxf(s[4 * k + 2], s[4 * k + 3]));
    }
    m0 = fmaxf(m0, __shfl_xor_sync(0xffffffffu, m0, 1));
    m1 = fmaxf(m1, __shfl_xor_sync(0xffffffffu, m1, 1));
    m0 = fmaxf(m0, __shfl_xor_sync(0xffffffffu, m0, 2));
    m1 = fmaxf(m1, __shfl_xor_sync(0xffffffffu, m1, 2));
    if (!first) {
        m0 = fmaxf(m0, 0.f);
        m1 = fmaxf(m1, 0.f);
    }
    a0 = first ? 1.f : ex2(-m0);
    a1 = first ? 1.f : ex2(-m1);
    m[0] += m0;
    m[1] += m1;
    softmax_shift(s, m0, m1);
}
template <int J0, int J1>
__device__ __forceinline__ void softmax_exp(const float (&s)[64], uint32_t (&p)[32], float (&t)[4]) {
#pragma unroll
    for (int k = J0; k < J1; k++) {
        const float e0 = ex2(s[4 * k]), e1 = ex2(s[4 * k + 1]), e2 = ex2(s[4 * k + 2]), e3 = ex2(s[4 * k + 3]);
        if (k == 0) { t[0] = e0; t[1] = e1; t[2] = e2; t[3] = e3; }
        else { t[0] += e0; t[1] += e1; t[2] += e2; t[3] += e3; }
        p[2 * k] = pack2(e0, e1);
        p[2 * k + 1] = pack2(e2, e3);
    }
}
__device__ __forceinline__ void fma8(float (&acc)[8], float a, uint4 w) {
    acc[0] = fmaf(a, bf_lo(w.x), acc[0]); acc[1] = fmaf(a, bf_hi(w.x), acc[1]);
    acc[2] = fmaf(a, bf_lo(w.y), acc[2]); acc[3] = fmaf(a, bf_hi(w.y), acc[3]);
    acc[4] = fmaf(a, bf_lo(w.z), acc[4]); acc[5] = fmaf(a, bf_hi(w.z), acc[5]);
    acc[6] = fmaf(a, bf_lo(w.w), acc[6]); acc[7] = fmaf(a, bf_hi(w.w), acc[7]);
}
__device__ __forceinline__ void mma16816(float (&d)[4], const uint32_t* a, uint32_t b0, uint32_t b1) {
    asm("mma.sync.aligned.m16n8k16.row.col.f32.bf16.bf16.f32 {%0, %1, %2, %3}, {%4, %5, %6, %7}, {%8, %9}, {%0, %1, %2, %3};"
        : "+f"(d[0]), "+f"(d[1]), "+f"(d[2]), "+f"(d[3]) : "r"(a[0]), "r"(a[1]), "r"(a[2]), "r"(a[3]), "r"(b0), "r"(b1));
}
__device__ __forceinline__ uint2 best_key(const uint32_t* keys, int lane, uint32_t ep, uint32_t cur, int enough) {
#pragma unroll 1
    for (;;) {
        const uint4 k = ld_poll(reinterpret_cast<const uint4*>(keys) + lane);
        const bool ok = (((k.x ^ ep) | (k.y ^ ep) | (k.z ^ ep) | (k.w ^ ep)) & 31) == 0;
        const uint32_t best = __reduce_max_sync(0xffffffffu, ok ? max(max(k.x, k.y), max(k.z, k.w)) : 0u);
        const int n = __popc(__ballot_sync(0xffffffffu, ok));
        if (n == 32 || (n >= enough && best != cur)) return make_uint2(best, n == 32);
        __nanosleep(KSLEEP);
    }
}

__global__ void __cluster_dims__(2, 1, 1) __launch_bounds__(384, 1)
fused_kernel(const __grid_constant__ CUtensorMap tm_ckv, const __grid_constant__ CUtensorMap tm_wq,
             const __grid_constant__ CUtensorMap tm_wuk, const __grid_constant__ CUtensorMap tm_wuv,
             const __grid_constant__ CUtensorMap tm_wo, const __grid_constant__ CUtensorMap tm_wg,
             const __grid_constant__ CUtensorMap tm_wu,
             const __grid_constant__ CUtensorMap tm_wm, const __grid_constant__ CUtensorMap tm_x, const Params P) {
    extern __shared__ __align__(1024) uint8_t smem[];
    const uint32_t sb = (uint32_t)__cvta_generic_to_shared(smem);
    const int tid = threadIdx.x, lane = tid & 31, warp = __shfl_sync(0xffffffffu, tid >> 5, 0), wg = warp >> 2;
    const uint32_t sm = blockIdx.x < 8 ? blockIdx.x + 124 : blockIdx.x - 8, smq = ((sm - 64) * 147) >> 11;
    const int rb = sm < 64 ? (sm & 14) * 8 + (sm >> 4) * 2 + (sm & 1)
                 : sm < 120 ? ((sm - 64 - smq * 14) & 14) * 8 + 24 + smq * 2 + (sm & 1) : sm < 124 ? sm + 8 : sm - 116;
    const int grp = rb >> 3, j = rb & 7, kh = (grp >> (OMAP - 1)) & 1;
    const int cq = (j & 1) + ((grp >> (OMAP - 1)) & 2), ort = (OMAP == 1 ? grp & 12 : (grp & 8) + (grp & 1) * 4) + (j >> 1);
    if (warp == 0) TS(0);

    if (lane == 0) {
        if (warp == 8) {
            asm volatile("prefetch.tensormap [%0];" ::"l"(rb >= NCTA ? &tm_wm : (j & 1) ? &tm_wuv : &tm_wuk) : "memory");
            asm volatile("prefetch.tensormap [%0];" ::"l"(&tm_ckv) : "memory");
            *reinterpret_cast<uint2*>(smem + SM_EP + 16) = make_uint2(0, 0);
        }
        const u64 cnt = (warp < 5 ? (rb < NCTA ? 0x844444441111111ull : 0x888888881111111ull) : warp < 10 ? 0x111111188888888ull : 0x118121ull) >> (12 * (warp % 5));
#pragma unroll
        for (int i = 0; i < 3; i++) mbar_init(sb + SM_BAR + 24 * warp + 8 * i, ((uint32_t)cnt >> (4 * i)) & 15);
        fence_async_smem();
        asm volatile("fence.mbarrier_init.release.cluster;" ::: "memory");
    }
    __syncthreads();
    asm volatile("barrier.cluster.arrive.relaxed.aligned;\nbarrier.cluster.wait.aligned;" ::: "memory");

    if (rb >= NCTA) {
        float* sc = reinterpret_cast<float*>(smem + 6 * SLOT);
        float* red = sc + 512;
        uint32_t ph = 0x7f, sl = 0;
        if (warp == 8) {
#pragma unroll 1
            for (int i = 0; i < 24; i++) {
                slot_acquire(sb, ph, sl);
                tma2d(sb + sl * SLOT, &tm_wm, (i >> 3) * 1024 + (rb - NCTA) * 256, (i & 7) * 64, sb + BAR_FULL + 8 * sl, HINT & 64);
                if (++sl == 6) sl = 0;
            }
#pragma unroll 1
            for (int i = 0; i <= NFFN / NSPARE; i++) {
                const int b = (rb - NCTA) * (NFFN / NSPARE) + i;
                if (i < NFFN / NSPARE) {
                    asm volatile("cp.async.bulk.wait_group.read 0;" ::: "memory");
                    uint32_t done = 0x7f;
                    slot_acquire(sb, done, i & 1);
#pragma unroll 1
                    for (int k = 0; k < 4; k++) tma2d(sb + (i & 1) * SLOT + k * 8192, k < 2 ? &tm_wg : &tm_wu, b * 16, (k & 1) * 256, sb + BAR_FULL + 8 * (i & 1), (HINT & 128) && (i & 3) == 3);
                }
                if (i) {
                    mbar_wait(sb + BAR_FULL + 8 * (~i & 1), ((i - 1) >> 1) & 1);
                    bulk_store(g_wf + (b - 1) * SLOT, sb + (~i & 1) * SLOT, SLOT, HINT & 256);
                    asm volatile("cp.async.bulk.commit_group;" ::: "memory");
                }
            }
            asm volatile("cp.async.bulk.wait_group 0;" ::: "memory");
            fence_async_global();
            TS(4);
        } else if (warp < 8) {
            const uint32_t c2 = __ldg(reinterpret_cast<const uint32_t*>(P.c) + tid), ep = __ldcg(&g_sync.epoch[0]) + 1;
            sc[2 * tid] = rbf(bf_lo(c2) * sigmoid(bf_lo(c2)));
            sc[2 * tid + 1] = rbf(bf_hi(c2) * sigmoid(bf_hi(c2)));
            ph = 0;
#pragma unroll 1
            for (int ps = 0; ps < 3; ps++) {
                bar_sync(1, 256);
                float acc[8] = {0.f, 0.f, 0.f, 0.f, 0.f, 0.f, 0.f, 0.f};
#pragma unroll 1
                for (int bt = 0; bt < 8; bt++) {
                    slot_wait(sb + BAR_FULL, ph, sl);
#pragma unroll 4
                    for (int i = 0; i < 8; i++)
                        fma8(acc, sc[bt * 64 + warp * 8 + i], *reinterpret_cast<const uint4*>(smem + sl * SLOT + (warp * 8 + i) * 512 + lane * 16));
                    __syncwarp();
                    mbar_arrive_if(sb + BAR_EMPTY + 8 * sl, lane == 0);
                    if (++sl == 6) sl = 0;
                }
                *reinterpret_cast<float4*>(red + warp * 256 + lane * 8) = make_float4(acc[0], acc[1], acc[2], acc[3]);
                *reinterpret_cast<float4*>(red + warp * 256 + lane * 8 + 4) = make_float4(acc[4], acc[5], acc[6], acc[7]);
                bar_sync(1, 256);
                float v = 0.f;
#pragma unroll
                for (int i = 0; i < 8; i++) v += red[i * 256 + tid];
                if (ps == 0) st_pub(g_mod1 + (rb - NCTA) * 256 + tid, (pack2(0.f, v) & 0xffff0000u) | (ep & 0xffffu), true);
                else g_mod[ps * 1024 + (rb - NCTA) * 256 + tid] = __float2bfloat16_rn(v);
                if (warp == 0) TS(1 + ps);
            }
        }
        __syncthreads();
        if (tid < 2) flag_add(&g_sync.cnt[7 * 8]);
        return;
    }

    if (wg == 2) {
        asm volatile("setmaxnreg.dec.sync.aligned.u32 40;");
        const CUtensorMap* tw = (j & 1) ? &tm_wuv : &tm_wuk;
        if (warp == 8) {
            const uint32_t rank = j & 1, half = rank * 16384;
            uint32_t eph = 0x7f, r = 0;
#pragma unroll 1
            for (int hp = 0; hp < 2; hp++) {
                uint32_t wtab = w_table(hp), atab = a_table(hp);
                const int hc = 4 * grp + 2 * hp;
#pragma unroll 1
                for (int u = 0; u < 16; u++) {
                    if (u < 4) {
                        const uint32_t ws = (wtab >> (4 * u)) & 15;
                        slot_acquire(sb, eph, ws);
                        load_tile(sb, ws, 0, tw, u * 128, hc, false, HINT & 1);
                        PT();
                    }
                    if (hp == 1 && (u & 7) == 4) mbar_wait(sb + BAR_FLAG + 24 + (u & 8), 0);
                    const uint32_t as = a_next(atab);
                    slot_acquire(sb, eph, as);
                    load_tile(sb, as, half, &tm_ckv, ((u & 12) + (j >> 1)) * 128, (u & 3) * 2 + rank, true, (HINT & 8) && hp);
                    PT();
                    if (hp == 1 && (u | 2) == 3 && lane == 0)
                        asm volatile("red.relaxed.gpu.global.add.u32 [%0], 1;" ::"l"(&g_sync.cnt[(grp * 8 + 3 + (u >> 1)) * 8]) : "memory");
                }
                const uint8_t* src = g_h + (15 - j) * 4 * SLOT;
#pragma unroll 1
                for (int u = 0; u < 8; u++) {
                    if (u == 0 || u == KVG) {
                        mbar_wait(sb + BAR_FLAG + (u ? 8 + 32 * hp : 0), 0);
                        fence_async_global();
                    }
                    if (u < 4) {
                        const uint32_t ws = (wtab >> (4 * u)) & 15;
                        slot_acquire(sb, eph, ws);
                        load_tile(sb, ws, 0, &tm_wq, u * 128, hc, false, HINT & 1);
                        PT();
                    }
                    const uint32_t as = a_next(atab);
                    slot_acquire(sb, eph, as);
                    load_bulk(sb, as, 0, src, SLOT, false, (HINT & 8) && hp);
                    PT();
                    src += u == 3 ? (8 * j - 63) * SLOT : SLOT;
                }
                const int step = hp ? -2 * SLOT : 2 * SLOT;
                src = g_KV + (size_t)(grp * 32 + 30 * hp) * SLOT + half - step;
#pragma unroll 1
                for (int n = 0; n <= 17; n++) {
                    if (n == 8) {
                        mbar_wait(sb + BAR_FLAG + 16 + 32 * hp, 0);
                        fence_async_global();
                    }
                    const uint8_t* v = src + SLOT;
                    src += n < 16 - j ? step : n == 16 - j ? (2 * j - 15) * step : -step;
                    if (n < 17) {
                        slot_acquire(sb, eph, r);
                        if (n != 15 - (j & 6)) load_bulk(sb, r, half, src, SLOT / 2, true, HINT & 4);
                        else load_bulk(sb, r, 0, src - half, SLOT, false, HINT & 4);
                        PT();
                        r = ring_next(r);
                    }
                    if (n) {
                        slot_acquire(sb, eph, r);
                        if (n != 16 - (j & 6)) load_bulk(sb, r, half, v, SLOT / 2, true, HINT & 4);
                        else load_bulk(sb, r, 0, v - half, SLOT, false, HINT & 4);
                        PT();
                        r = ring_next(r);
                    }
                    asm volatile("st.volatile.shared.u32 [%0], %1;" ::"r"(sb + SM_EP + 16), "r"(18 * hp + n + 1) : "memory");
                }
            }
            uint32_t otab = O_TABLE, ready = 0;
#pragma unroll 1
            for (int i = 0; i < 17; i++) {
                const bool dyn = i >= 8 && i < 15;
                const uint32_t want = dyn ? 15u << (4 * (i - 8)) : 1u << max(i + 14, 28);
                if (!(ready & want)) {
                    do {
                        asm volatile("ld.acquire.cta.shared.u32 %0, [%1];" : "=r"(ready) : "r"(sb + SM_EP + 20) : "memory");
                        ready = __shfl_sync(0xffffffffu, ready, 0);
                    } while (!(ready & want));
                    fence_async_global();
                }
                const int head = o_head(dyn ? (ready >> (4 * (i - 8))) & 15 : i, kh);
                const uint32_t as = o_next(otab), ws = o_next(otab), off = i < 15 ? half : kh * 16384;
                slot_acquire(sb, eph, as);
                load_bulk(sb, as, off, g_ctx + (size_t)(ort * 32 + head) * SLOT + off, SLOT / 2, i < 15, HINT & 16);
                if (i == 15) load_tile(sb, as, off ^ 16384, &tm_x, ort * 128 + kh * 64, cq * 2, false, false);
                if (i == 16) load_bulk(sb, as, off ^ 16384, P.wdown + min(rb, NFFN - 1) * 8192, SLOT / 2, false, false);
                PT();
                slot_acquire(sb, eph, ws);
                load_tile(sb, ws, 0, &tm_wo, head * 128, cq * 2, false, HINT & 2);
                PT();
                if (i == 0) o_next(otab);
            }
            if (rb < NFFN) {
                slot_acquire(sb, eph, 5);
                load_bulk(sb, 5, 0, g_wf + rb * SLOT, SLOT, false, false);
            }
        } else if (warp == 9) {
            l2_prefetch(P.ckv + rb * 2048, 4096);
            mbar_watch(sb + BAR_FULL, 0);
            l2_prefetch(P.ckv + 512 * 512 + rb * 2048, 4096);
            mbar_watch(sb + BAR_FULL + 8 * XPF, 0);
            l2_prefetch(P.x + rb * 8192, 16384);
            mbar_watch(sb + BAR_FULL + 8 * 4, 0);
            l2_prefetch(P.ckv + 1024 * 512 + rb * 4096, 8192);
            TS(40);
#pragma unroll 1
            for (int i = 0; i < 15; i++) {
                step_watch(sb + SM_EP + 16, i == 0 ? 0 : i < 5 ? PFA + i : 13 + PFB + i);
                if (i == 12) mbar_watch(sb + BAR_FLAG + 8 * 7, 0);
                const int rf = min(rb, NFFN - 1);
                const uint8_t* p = i == 3 ? reinterpret_cast<const uint8_t*>(P.ckv) + rb * 16384
                                 : i == 4 ? g_h + rb * 16384
                                 : i < 9 ? g_ctx + (size_t)(ort * 32 + o_head(cq + 2 * ((i - 5) & 2), kh)) * SLOT + (i & 1) * 16384
                                 : i < 11 ? reinterpret_cast<const uint8_t*>(P.wo) + (grp * 16 + (~i & 1) * 8 + j) * 16384
                                 : i == 11 ? reinterpret_cast<const uint8_t*>(P.x) + rb * 16384
                                 : i == 12 ? reinterpret_cast<const uint8_t*>(P.wdown) + rf * 16384 : g_wf + rf * SLOT + (i & 1) * 16384;
                if (i >= 3) l2_prefetch(p, 16384);
                else if ((i | j) & 1) tma3d_prefetch(i == 1 ? tw : &tm_wq, (j >> 1) * 128, grp * 4 + (i ? 2 : 0));
            }
            const uint32_t v = lds32(sb + SM_EP) - 1;
            sts128(sb + SM_RED + lane * 16, make_uint4(v, v, v, v));
            fence_async_smem();
            __syncwarp();
#pragma unroll 1
            for (int i = 0; i < OB / 32; i++) bulk_store(g_out + rb * OB + i * 32, sb + SM_RED, 512, false);
            asm volatile("cp.async.bulk.commit_group;\ncp.async.bulk.wait_group 0;" ::: "memory");
            fence_async_global();
            __syncwarp();
            mbar_arrive_if(sb + BAR_PF, lane == 0);
            if (lane == 0) mbar_watch(sb + BAR_END, 0);
        } else {
            const uint32_t ep = __ldcg(&g_sync.epoch[0]) + 1;
            asm volatile("st.shared.u32 [%0], %1;" ::"r"(sb + SM_EP), "r"(ep) : "memory");
            mbar_wait(sb + BAR_FULL + 8 * 4, 0);
            {
                uint4 v[4];
                for (;;) {
                    uint32_t bad = 0;
#pragma unroll
                    for (int k = 0; k < 4; k++) v[k] = ld_poll(reinterpret_cast<const uint4*>(g_mod1) + (warp & 1) * 128 + k * 32 + lane);
#pragma unroll
                    for (int k = 0; k < 4; k++) bad |= (v[k].x ^ ep) | (v[k].y ^ ep) | (v[k].z ^ ep) | (v[k].w ^ ep);
                    if (__all_sync(0xffffffffu, (bad & 0xffff) == 0)) break;
                    __nanosleep(100);
                }
                const uint32_t one = (warp & 1) ? ONE2 : 0x80008000u;
#pragma unroll
                for (int k = 0; k < 4; k++)
                    *reinterpret_cast<uint2*>(smem + SM_TAB + (warp & 1) * 1024 + k * 256 + lane * 8) =
                        make_uint2(badd(__byte_perm(v[k].x, v[k].y, 0x7632), one), badd(__byte_perm(v[k].z, v[k].w, 0x7632), one));
            }
            __syncwarp();
            mbar_arrive_if(sb + BAR_FLAG + 8 * 8, lane == 0);
            if (warp == 10) {
#pragma unroll 1
                for (int i = 0; i < 9; i++) {
                    mbar_sleep(sb + BAR_DONE + 8 * i);
                    if (lane == 0) flag_add(i && ((i - 1) & 2) ? &g_sync.ctxcnt[((i & 1) ? 15 - j : j) * 32 + 2 * grp + (i > 4)] : &g_sync.cnt[(grp * 8 + i) * 8]);
                    if (i == 0) TS(43);
                }
            } else {
                TS(42);
#pragma unroll 1
                for (int i = 0; i < 8; i++) {
                    mbar_sleep(sb + BAR_DONE + 8 * (i == 7 ? 6 : i == 4 ? 3 : i));
                    if (lane < 2) flag_wait(&g_sync.cnt[((i == 0 ? (lane ? j : 15 - j) : i == 7 ? 0 : grp) * 8 + i) * 8], 8 * ep);
                    __syncwarp();
                    mbar_arrive_if(sb + BAR_FLAG + 8 * i, lane == 0 && i < 7);
                    TS(48 + i);
                }
                const uint32_t *mp = reinterpret_cast<const uint32_t*>(g_mod) + lane, *wp = reinterpret_cast<const uint32_t*>(P.wr) + lane;
                float ra = 0.f, rs = 0.f;
#pragma unroll 1
                for (int k = 0; k < 256; k += 32) {
                    const uint32_t ga = __ldcg(mp + 512 + k), sh = __ldcg(mp + 768 + k), c1 = badd(__ldcg(mp + 1024 + k), ONE2);
                    const uint32_t gb = __ldcg(mp + 1280 + k), ww = __ldg(wp + k);
                    const uint32_t a = bmul(c1, ww);
                    ra += bf_lo(a) + bf_hi(a);
                    rs = fmaf(bf_lo(sh), bf_lo(ww), fmaf(bf_hi(sh), bf_hi(ww), rs));
                    if (k >> 6 == cq) {
                        sts128(sb + SM_TAB + ((k & 32) + lane) * 16, make_uint4(ga << 16, ga & 0xffff0000u, a, 0));
                        sts128(sb + SM_TAB + 1024 + ((k & 32) + lane) * 16, make_uint4(c1, sh, gb, 0));
                    }
                }
#pragma unroll 1
                for (int o = 16; o > 0; o >>= 1) {
                    ra += __shfl_xor_sync(0xffffffffu, ra, o);
                    rs += __shfl_xor_sync(0xffffffffu, rs, o);
                }
                *reinterpret_cast<float2*>(smem + SM_EP + 8) = make_float2(ra, rs);
                __syncwarp();
                mbar_arrive_if(sb + BAR_FLAG + 8 * 7, lane == 0);
                const uint32_t* f = &g_sync.ctxcnt[ort * 32 + o_head(min(lane, 16), kh)];
                uint32_t ready = -(j & 1), list = 0, sh = 0, qa;
                asm("mapa.shared::cluster.u32 %0, %1, %2;" : "=r"(qa) : "r"(sb + SM_EP + 20), "r"(lane & 1));
                while (ready != ~0u) {
                    uint32_t v;
                    asm volatile("ld.acquire.gpu.global.u32 %0, [%1];" : "=r"(v) : "l"(f) : "memory");
                    const uint32_t now = __ballot_sync(0xffffffffu, (int)(v - ep) >= 0);
#pragma unroll 1
                    for (uint32_t fresh = now & ~ready & 0x7f00; fresh; fresh &= fresh - 1, sh += 4) list |= (__ffs(fresh) - 1) << sh;
                    list |= (((now & 0xff) + 1) >> 8 << 28) | ((now & 0x18000) << 14);
                    if (now != ready && lane < 2) asm volatile("st.relaxed.cluster.shared::cluster.u32 [%0], %1;" ::"r"(qa), "r"(list) : "memory");
                    if ((now & 0xff) == 0xff) mbar_sleep(sb + BAR_DONE + 8 * 7);
                    ready = now;
                    __nanosleep(POLL_NS);
                }
                TS(45);
            }
        }
    } else {
        asm volatile("setmaxnreg.inc.sync.aligned.u32 232;");
        const bool elected = (tid & 127) == 0, rel = (tid & 95) == 0;
        uint32_t eb;
        asm("mapa.shared::cluster.u32 %0, %1, %2;" : "=r"(eb) : "r"(sb + BAR_EMPTY), "r"(warp & 1));
        const int g = lane >> 2, c4 = lane & 3;
        const uint32_t toff = warp * 4096 + g * 64 + ((c4 ^ (g >> 1)) << 4);
        uint32_t fph = 0x3f, r = 0;
        if (wg == 1) bar_arrive(1, 256);
        const uint32_t kd = desc_k(sb), wd = desc_mn(sb), vd = ((sb & 0x3ffff) >> 4) | (32u << 16);
        const int nL = 16 - j, hn = nL - 1 + wg;
        float s[64], o[64], li[2] = {0.f, 0.f};
        uint8_t* cimg = g_ctx;
        const float sc = (j & 1) ? 1.f : SM_C;
#pragma unroll 1
        for (int q = 0; q < 3; q++) {
            const uint32_t as = (0x635u >> (4 * q)) & 15;
            mbar_wait(sb + BAR_FULL + 8 * q, 0);
            mbar_wait(sb + BAR_FULL + 8 * as, 0);
            bar_sync(1 + wg, 256);
            gemm_issue<false>(s, kd + wg * 512 + as * (SLOT / 16), wd + q * (SLOT / 16), q, false);
            bar_arrive(2 - wg, 256);
            wg_wait<0>();
            release_if(eb, as, rel);
        }
        {
            const int xrow = rb * 16 + warp * 2;
            const uint4* xp = reinterpret_cast<const uint4*>(P.x) + xrow * 64;
            uint8_t* img = g_KV + (size_t)(grp * 32 + j) * SLOT;
            uint32_t x[16], x0[2];
            float st[4] = {0.f, 0.f, 0.f, 0.f};
            mbar_wait(sb + BAR_FULL + 8 * 4, 0);
#pragma unroll
            for (int q = 3; q < 8; q++) {
                const uint32_t ws = (0x4210u >> (4 * (q & 3))) & 15, as = (0x635u >> (4 * (q % 3))) & 15;
                mbar_wait(sb + BAR_FULL + 8 * as, (q / 3) & 1);
                bar_sync(1 + wg, 256);
                if (q == 3) gemm_issue<false>(s, kd + wg * 512 + as * (SLOT / 16), wd + ws * (SLOT / 16), 1, false);
                else if (q == 4) gemm_issue<true>(o, kd + wg * 512 + as * (SLOT / 16), wd + ws * (SLOT / 16), 0, false);
                else gemm_issue<false>(o, kd + wg * 512 + as * (SLOT / 16), wd + ws * (SLOT / 16), 1, false);
                bar_arrive(2 - wg, 256);
                sched_fence(fph, P.zero);
                if (q > 3) reg_fence(s);
                if (q == 3) {
#pragma unroll
                    for (int i = 0; i < 4; i++)
                        asm volatile("ld.global.nc.v4.u32 {%0, %1, %2, %3}, [%4];" : "=r"(x[4 * i]), "=r"(x[4 * i + 1]), "=r"(x[4 * i + 2]), "=r"(x[4 * i + 3])
                                     : "l"(xp + lane + 32 * i) : "memory");
#pragma unroll
                    for (int i = 0; i < 2; i++) asm volatile("ld.global.nc.u32 %0, [%1];" : "=r"(x0[i]) : "l"(xp + 64 * i) : "memory");
                }
                if (q == 4) {
                    img_store_global<0>(img, toff, s, sc, sc);
#pragma unroll
                    for (int k = 0; k < 16; k++) {
                        const float d0 = bf_lo(x[k]) - bf_lo(x0[k >> 3]), d1 = bf_hi(x[k]) - bf_lo(x0[k >> 3]);
                        st[k >> 3] += d0 + d1;
                        st[2 + (k >> 3)] = fmaf(d0, d0, fmaf(d1, d1, st[2 + (k >> 3)]));
                    }
#pragma unroll
                    for (int i = 0; i < 4 * NSH; i++) st[i & 3] += __shfl_xor_sync(0xffffffffu, st[i & 3], 1 << (i >> 2));
                    reg_fence(st);
                }
                if (q == 5) {
#pragma unroll
                    for (int i = 4 * NSH; i < 20; i++) st[i & 3] += __shfl_xor_sync(0xffffffffu, st[i & 3], 1 << (i >> 2));
                    img_store_global<1>(img, toff, s, sc, sc);
#pragma unroll
                    for (int i = 0; i < 2; i++) {
                        const float d = st[i] * (1.f / 512.f);
                        st[2 + i] = ln_rstd(fmaxf(fmaf(-d, d, st[2 + i] * (1.f / 512.f)), 0.f));
                        x0[i] = pack2(bf_lo(x0[i]) + d, bf_lo(x0[i]) + d);
                    }
                    reg_fence(st);
                    reg_fence(x0);
                }
                if (q > 5) {
                    if (q == 6) mbar_wait(sb + BAR_FLAG + 8 * 8, 0);
                    const uint4 a = lds128(sb + SM_TAB + 1024 + (q & 1) * 512 + lane * 16), c = lds128(sb + SM_TAB + (q & 1) * 512 + lane * 16);
                    uint8_t* hp = g_h + (grp * 8 + (q & 1) * 4 + (lane >> 3)) * 16384 + (xrow & 127) * 128;
#pragma unroll
                    for (int i = 0; i < 2; i++) {
                        const uint32_t* y = x + 8 * i + 4 * (q & 1);
                        *reinterpret_cast<uint4*>(hp + i * 128 + (((lane ^ xrow ^ i) & 7) << 4)) =
                            make_uint4(ln_apply(y[0], x0[i], st[2 + i], a.x, c.x), ln_apply(y[1], x0[i], st[2 + i], a.y, c.y),
                                       ln_apply(y[2], x0[i], st[2 + i], a.z, c.z), ln_apply(y[3], x0[i], st[2 + i], a.w, c.w));
                    }
                    if (q == 7) {
                        __syncwarp();
                        mbar_arrive_if(sb + BAR_DONE, lane == 0);
                    }
                    if (q == 6) img_store_global<2>(img, toff, s, sc, sc);
                    else img_store_global<3>(img, toff, s, sc, sc);
                }
                sched_fence(fph, P.zero);
                wg_wait<0>();
                release_if(eb, as, rel);
            }
            reg_fence(o);
        }
        uint32_t p[32] = {};
#pragma unroll 1
        for (int hp = 0; hp < 2; hp++) {
            float m[2] = {0.f, 0.f}, l[2] = {0.f, 0.f}, t[4] = {0.f, 0.f, 0.f, 0.f};
            bool shifted = false, bad = false, plain = false;
            uint32_t qa = desc_k(sb + 5 * SLOT + (wg ^ 1) * 8192);
            uint8_t* limg = g_ctx + (size_t)((15 - j) * 32 + 2 * grp + hp) * SLOT;
            {
                const int step = hp ? -8 * SLOT : 8 * SLOT;
                uint8_t* img = g_KV + (size_t)(grp * 32 + (hp ? j ^ 30 : j) + 8) * SLOT;
                const uint32_t wtab = w_table(hp);
                uint32_t atab = hp ? 0x562u : 0x356u;
#pragma unroll 1
                for (int u = 2 - 2 * hp;; u += 2) {
                    proj_tile<false>(s, o, u, !u, sb, wg, eb, rel, fph, wtab, atab, u ? img : cimg, toff, u ? sc : li[0], u ? sc : li[1], p);
                    __syncwarp();
                    mbar_arrive_if(sb + BAR_DONE + 4 * u + 32 * hp, lane == 0);
                    if (elected) TS(1 + 10 * hp + u + 20 * wg);
                    if (proj_tile<true>(o, s, u + 1, 0, sb, wg, eb, rel, fph, wtab, atab, img + step, toff, sc, sc, p)) break;
                    if (elected) TS(2 + 10 * hp + u + 20 * wg);
                    img += 2 * step;
                }
            }
            if (elected) TS(6 + 10 * hp + 20 * wg);
            int n = -1;
#pragma unroll 1
            for (;;) {
                while (bad || plain) {
                    if (bad) {
                        float a0, a1;
                        softmax_remax(s, m, n == 0 || n == nL, a0, a1);
                        shifted = true;
                        l[0] *= a0;
                        l[1] *= a1;
#pragma unroll
                        for (int i = 0; i < 64; i++) o[i] *= (i & 2) ? a1 : a0;
                    }
                    softmax_exp<0, 16>(s, p, t);
                    t[0] += t[1];
                    t[2] += t[3];
                    bad = !bad && softmax_unsafe(t[0], t[2], false);
                    plain = false;
                }
#pragma unroll 1
                do {
                    l[0] += t[0];
                    l[1] += t[2];
                    if (++n > 16) break;
                    const uint32_t ks = r;
                    uint32_t vs = ring_next(r);
                    r = ring_next(vs);
                    bar_sync(1 + wg, 256);
                    const float x = (float)((warp & 3) * 16 + g - 2 * c4);
                    if (n == hn) {
                        float sh[32];
                        qk_issue(sh, qa, kd + ks * (SLOT / 16));
                        slot_wait(sb + BAR_FULL, fph, vs);
                        pv_issue(o, p, vd + vs * (SLOT / 16), 1, false);
                        bar_arrive(2 - wg, 256);
                        wg_wait<1>();
                        reg_fence(sh);
                        tri_mask_copy(s, sh, x);
                        release_if(eb, ks, rel);
                        release_if(eb, 5 + wg, rel && (!wg || n == 16));
                        if (!wg) {
                            qa += SLOT / 16;
                            fence_async_smem();
                            if (shifted) softmax_shift(s, m[0], m[1]);
                        }
                        float e[4 * EARLY];
#pragma unroll
                        for (int i = 0; i < 4 * EARLY; i++) {
                            e[i] = ex2(s[i]);
                            t[i & 3] = i < 4 ? e[i] : t[i & 3] + e[i];
                        }
                        reg_fence(e);
                        slot_wait(sb + BAR_FULL, fph, r);
                        wg_wait<0>();
                        reg_fence(o);
                        reg_fence(e);
                        release_if(eb, vs, rel);
#pragma unroll
                        for (int i = 0; i < 2 * EARLY; i++) p[i] = pack2(e[2 * i], e[2 * i + 1]);
                        softmax_exp<EARLY, 8>(s, p, t);
                        if (wg) {
                            ctx_store<true>(limg, toff, o, l[0], l[1]);
                            __syncwarp();
                            mbar_arrive_if(sb + BAR_DONE + 24 + 32 * hp, lane == 0);
                            l[0] = l[1] = m[0] = m[1] = 0.f;
                            shifted = false;
                        }
                        t[0] += t[1];
                        t[2] += t[3];
                        bad = softmax_unsafe(t[0], t[2], wg);
                        continue;
                    }
                    if (n == 0 || n == nL) {
                        qk_issue(s, qa, kd + ks * (SLOT / 16));
                        if (n == 0) {
                            r = vs;
                            vs = 4 - hp;
                            slot_wait(sb + BAR_FULL, fph, 6);
                            gemm_issue<false>(o, qa + SLOT / 16, wd + vs * (SLOT / 16), 1, false);
                        } else {
                            slot_wait(sb + BAR_FULL, fph, vs);
                            pv_issue(o, p, vd + vs * (SLOT / 16), 1, true);
                        }
                        bar_arrive(2 - wg, 256);
                        const float i0 = n ? rcp(quad_sum(l[0])) : 1.f, i1 = n ? rcp(quad_sum(l[1])) : 1.f;
                        wg_wait<1>();
                        reg_fence(s);
                        release_if(eb, ks, rel);
                        release_if(eb, 6, rel && n == 16);
                        tri_mask(s, n ? x : 64.f);
                        float e[4 * EARLY];
#pragma unroll
                        for (int i = 0; i < 4 * EARLY; i++) {
                            e[i] = ex2(s[i]);
                            t[i & 3] = i < 4 ? e[i] : t[i & 3] + e[i];
                        }
                        reg_fence(e);
                        reg_fence(s);
                        reg_fence(t);
                        slot_wait(sb + BAR_FULL, fph, r);
                        if (SF & 1) sched_fence(fph, P.zero);
                        wg_wait<0>();
                        reg_fence(o);
                        reg_fence(e);
                        release_if(eb, vs, rel);
#pragma unroll
                        for (int i = 0; i < 2 * EARLY; i++) p[i] = pack2(e[2 * i], e[2 * i + 1]);
                        softmax_exp<EARLY, MSPLIT>(s, p, t);
                        tile_store(limg, sb + 6 * SLOT, toff, o, i0, i1, n);
                        reg_fence(t);
                        if (SF & 2) sched_fence(fph, P.zero);
                        reg_fence(s);
                        softmax_exp<MSPLIT, 16>(s, p, t);
                        __syncwarp();
                        mbar_arrive_if(sb + BAR_DONE + 24 + 32 * hp, lane == 0 && n);
                        l[0] = l[1] = m[0] = m[1] = 0.f;
                        shifted = false;
                        t[0] += t[1];
                        t[2] += t[3];
                        bad = __any_sync(0xffffffffu, fmaxf(t[0], t[2]) > SM_HI || fminf(t[0], t[2]) < SM_LO);
                        continue;
                    }
                    qk_issue(s, qa, kd + ks * (SLOT / 16));
                    slot_wait(sb + BAR_FULL, fph, vs);
                    pv_issue(o, p, vd + vs * (SLOT / 16), n != 1 && n != nL + 1, n == hn + 1);
                    bar_arrive(2 - wg, 256);
                    wg_wait<1>();
                    reg_fence(s);
                    release_if(eb, ks, rel);
                    release_if(eb, 6, rel && n == 16);
                    if (n == nL - 1) {
                        tri_mask(s, x);
                        release_if(eb, 5, rel);
                        qa += SLOT / 16;
                        fence_async_smem();
                    }
                    if (shifted) {
                        slot_wait(sb + BAR_FULL, fph, r);
                        wg_wait<0>();
                        reg_fence(o);
                        release_if(eb, vs, rel);
                        softmax_shift(s, m[0], m[1]);
                        plain = true;
                        break;
                    }
                    float e[4 * EARLY];
#pragma unroll
                    for (int i = 0; i < 4 * EARLY; i++) {
                        e[i] = ex2(s[i]);
                        t[i & 3] = i < 4 ? e[i] : t[i & 3] + e[i];
                    }
                    reg_fence(e);
                    slot_wait(sb + BAR_FULL, fph, r);
                    wg_wait<0>();
                    reg_fence(o);
                    reg_fence(e);
                    release_if(eb, vs, rel);
#pragma unroll
                    for (int i = 0; i < 2 * EARLY; i++) p[i] = pack2(e[2 * i], e[2 * i + 1]);
                    softmax_exp<EARLY, 16>(s, p, t);
                    t[0] += t[1];
                    t[2] += t[3];
                    bad = softmax_unsafe(t[0], t[2], false);
                } while (!bad);
                if (!bad && !plain) break;
            }
            const uint32_t vs = r, ga = desc_k(sb + (hp ? 2 * (wg ^ kh ^ 1) : wg) * 8192);
            r = ring_next(r);
            slot_wait(sb + BAR_FULL, fph, 5);
            slot_wait(sb + BAR_FULL, fph, r);
            bar_sync(1 + wg, 256);
            gemm_issue<true>(s, ga + 5 * (SLOT / 16), wd + r * (SLOT / 16), 0, hp);
            pv_issue(o, p, vd + vs * (SLOT / 16), j, hn == 16);
            bar_arrive(2 - wg, 256);
            li[0] = rcp(quad_sum(l[0]));
            li[1] = rcp(quad_sum(l[1]));
            cimg = limg + (ptrdiff_t)(2 * j - 15) * 32 * SLOT + (wg ? -16384 : 16384);
            wg_wait<1>();
            release_if(eb, 5, rel);
            release_if(eb, r, rel && hp);
            wg_wait<0>();
            release_if(eb, vs, rel);
            reg_fence(o);
            img_store_global<0>(cimg, toff, o, li[0], li[1]);
            if (elected) TS(8 + 10 * hp + 20 * wg);
        }
        uint32_t otab = 0x2351604u;
        const uint32_t oa = desc_k(sb + (wg ^ kh ^ 1) * 16384);
        const int t7 = tid & 127, w4 = warp & 3, row = ort * 128 + kh * 64 + w4 * 16 + g;
#pragma unroll 1
        for (int i = 1; i < 15 - wg; i++) {
            const uint32_t as = o_next(otab), ws = o_next(otab);
            slot_wait(sb + BAR_FULL, fph, as);
            slot_wait(sb + BAR_FULL, fph, ws);
            bar_sync(1 + wg, 256);
            gemm_issue<false>(s, oa + as * (SLOT / 16), wd + ws * (SLOT / 16), 1, true);
            bar_arrive(2 - wg, 256);
            wg_wait<1>();
            reg_fence(o);
            if (i == 1) img_store_global<1>(cimg, toff, o, li[0], li[1]);
            if (i == 2) {
                img_store_global<2>(cimg, toff, o, li[0], li[1]);
                img_store_global<3>(cimg, toff, o, li[0], li[1]);
                __syncwarp();
                mbar_arrive_if(sb + BAR_DONE + 64, lane == 0);
            }
            wg_wait<0>();
            release_if(eb, as, rel);
            release_if(eb, ws, rel);
        }
        mbar_wait(sb + BAR_PF, 0);
        const uint32_t ep = lds32(sb + SM_EP);
        uint32_t eb2 = sb + BAR_END;
        if (wg == 0) {
            reg_fence(s);
            if (elected) TS(9);
            TT(1);
#pragma unroll
            for (int v = 0; v < 8; v++)
                st_pub(g_out + rb * OB + v * 128 + t7, make_uint4((pack2(s[8 * v], s[8 * v + 1]) & ~1u) | (ep & 1), pack2(s[8 * v + 2], s[8 * v + 3]),
                                                                      pack2(s[8 * v + 4], s[8 * v + 5]), pack2(s[8 * v + 6], s[8 * v + 7])), true);
            constexpr uint32_t s1 = 5, s2 = 6;
            bar_sync(4, 256);
            uint32_t wf[64];
            float wn[64];
            if (rb < NFFN) {
                slot_wait(sb + BAR_FULL, fph, s1);
                const uint32_t a = sb + s1 * SLOT + (w4 * 128 + (lane >> 4) * 8 + (lane & 7)) * 32 + ((lane >> 3) & 1) * 16;
#pragma unroll
                for (int i = 0; i < 16; i++)
                    asm volatile("ldmatrix.sync.aligned.m8n8.x4.trans.shared.b16 {%0, %1, %2, %3}, [%4];"
                                 : "=r"(wf[4 * i]), "=r"(wf[4 * i + 1]), "=r"(wf[4 * i + 2]), "=r"(wf[4 * i + 3])
                                 : "r"(a + (i >> 3) * 16384 + (i & 7) * 512) : "memory");
                slot_wait(sb + BAR_FULL, fph, s2);
#pragma unroll
                for (int i = 0; i < 16; i++) {
                    const uint2 w = *reinterpret_cast<const uint2*>(smem + s2 * SLOT + (kh ^ 1) * 16384 + i * 1024 + t7 * 8);
                    wn[4 * i] = bf_lo(w.x); wn[4 * i + 1] = bf_hi(w.x); wn[4 * i + 2] = bf_lo(w.y); wn[4 * i + 3] = bf_hi(w.y);
                }
                reg_fence(wn);
            }
            const uint32_t gbf = __ldcg(reinterpret_cast<const uint32_t*>(g_mod) + 1280 + rb * 2 + (tid & 1));
            if (elected) TS(10);
            TT(2);
            float* sred = reinterpret_cast<float*>(smem + SM_RED);
            uint32_t best = ep ^ 1, all;
            bool fresh;
            do {
                if (warp == 0) {
                    const uint2 k = best_key(g_key + cq * 128, lane, ep, best, rb < NFFN ? SPEC : 32);
                    *reinterpret_cast<uint2*>(smem + SM_EP + 24) = k;
                    mbar_arrive_if(sb + BAR_BEST, lane == 0 && k.y);
                }
                bar_sync(3, 128);
                const uint2 k = *reinterpret_cast<const uint2*>(smem + SM_EP + 24);
                fresh = k.x != best;
                best = k.x;
                all = k.y;
                TT(3);
                if (!fresh || rb >= NFFN) break;
                const uint4* cp = g_cand + ((~best >> 9) & 127) * 192;
                uint4 cv[6];
                for (;;) {
                    uint32_t bad = 0;
#pragma unroll
                    for (int v = 0; v < 6; v++) cv[v] = ld_poll(cp + w4 * 24 + v * 4 + c4);
#pragma unroll
                    for (int v = 0; v < 6; v++) bad |= cv[v].w ^ ep;
                    if (__all_sync(0xffffffffu, bad == 0)) break;
                    if (CSLEEP) __nanosleep(CSLEEP);
                }
            TT(4);
                float d[4][4] = {};
#pragma unroll
                for (int k = 0; k < 8; k++) {
                    const uint32_t b0 = (&cv[(2 * k) / 3].x)[(2 * k) % 3], b1 = (&cv[(2 * k + 1) / 3].x)[(2 * k + 1) % 3];
                    mma16816(d[k & 1], wf + 4 * k, b0, b1);
                    mma16816(d[2 + (k & 1)], wf + 32 + 4 * k, b0, b1);
                }
                const float u = (c4 & 2) ? ((c4 & 1) ? d[2][2] + d[3][2] : d[2][0] + d[3][0]) : ((c4 & 1) ? d[0][2] + d[1][2] : d[0][0] + d[1][0]);
                sred[w4 * 32 + c4 * 8 + g] = u;
                bar_sync(3, 128);
                const float v = rbf((sred[lane] + sred[32 + lane]) + (sred[64 + lane] + sred[96 + lane]));
                const float act = rbf(rbf(v * sigmoid(v)) * __shfl_down_sync(0xffffffffu, v, 16));
                float y[4] = {0.f, 0.f, 0.f, 0.f};
#pragma unroll
                for (int k = 0; k < 16; k++) {
                    const float a = __shfl_sync(0xffffffffu, act, k);
#pragma unroll
                    for (int i = 0; i < 4; i++) y[i] = fmaf(a, wn[4 * k + i], y[i]);
                }
                st_pub(g_out + rb * OB + OB_Y + t7, make_uint4((__float_as_uint(y[0]) & ~15u) | (ep & 15), (__float_as_uint(y[1]) & ~127u) | ((best >> 9) & 127),
                                                               __float_as_uint(y[2]), __float_as_uint(y[3])), true);
            } while (!all);
            const int sel = (~best >> 5) & 2047;
            const int pq = (2 * rb + (tid & 1)) & 63, pv = (pq >> 2) / 3;
            const uint4* fp = g_cand + (sel >> 4) * 192 + (rb >> 5) * 24 + pv * 4 + (pq & 3);
            uint4 fh = {}, fx = {};
            if (rb == 0 && tid == 0) g_sync.epoch[0] = ep;
            if (elected) TS(60);
            TT(5);
            uint4 yv;
            if (warp == 0) { fh = ld_poll(fp); fx = ld_poll(fp + 96); }
            if (fresh && rb < NFFN) __nanosleep(YPRE);
            for (;;) {
                yv = ld_poll(g_out + min(t7, NFFN - 1) * OB + OB_Y + rb);
                if (__all_sync(0xffffffffu, (((yv.x ^ ep) & 15) | ((yv.y ^ (best >> 9)) & 127)) == 0)) break;
                if (YSLEEP) __nanosleep(YSLEEP);
            }
            if (elected) TS(61);
            TT(6);
            float y[4] = {0.f, 0.f, 0.f, 0.f};
            if (t7 < NFFN) { y[0] = __uint_as_float(yv.x); y[1] = __uint_as_float(yv.y); y[2] = __uint_as_float(yv.z); y[3] = __uint_as_float(yv.w); }
            const float z0 = ((lane & 16) ? y[2] : y[0]) + __shfl_xor_sync(0xffffffffu, (lane & 16) ? y[0] : y[2], 16);
            const float z1 = ((lane & 16) ? y[3] : y[1]) + __shfl_xor_sync(0xffffffffu, (lane & 16) ? y[1] : y[3], 16);
            float z = ((lane & 8) ? z1 : z0) + __shfl_xor_sync(0xffffffffu, (lane & 8) ? z0 : z1, 8);
            z += __shfl_xor_sync(0xffffffffu, z, 4);
            z = quad_sum(z);
            if ((lane & 7) == 0) sred[128 + (lane >> 3) * 4 + w4] = z;
            bar_sync(3, 128);
            if (tid < 2) {
                while (fh.w != ep || fx.w != ep) { fh = ld_poll(fp); fx = ld_poll(fp + 96); }
                const float4 y0 = *reinterpret_cast<const float4*>(sred + 128 + tid * 8), y1 = *reinterpret_cast<const float4*>(sred + 132 + tid * 8);
                const int cm = (pq >> 2) - 3 * pv;
                const uint32_t h2 = cm == 0 ? fh.x : cm == 1 ? fh.y : fh.z, x2 = cm == 0 ? fx.x : cm == 1 ? fx.y : fx.z;
                const float sg = sigmoid(bf_hi((best & 0x80000000u) ? (best ^ 0x80000000u) : ~best));
                reinterpret_cast<uint32_t*>(P.out)[sel * 256 + rb * 2 + tid] =
                    badd(x2, bmul(gbf, badd(h2, bmul(pack2((y0.x + y0.y) + (y0.z + y0.w), (y1.x + y1.y) + (y1.z + y1.w)), pack2(sg, sg)))));
            }
            if (elected) TS(62);
            TT(7);
        } else {
            const float4* tf = reinterpret_cast<const float4*>(smem + SM_TAB) + c4;
            const uint32_t xa = sb + 4 * SLOT + (kh ^ 1) * 16384 + (w4 * 16 + (lane & 15)) * 128;
            uint32_t x2[32];
            bar_sync(2, 256);
#pragma unroll 1
            for (int i = 14; i < 17; i++) {
                const uint32_t as = o_next(otab), ws = o_next(otab);
                slot_wait(sb + BAR_FULL, fph, as);
                slot_wait(sb + BAR_FULL, fph, ws);
                gemm_issue<false>(s, oa + as * (SLOT / 16), wd + ws * (SLOT / 16), 1, true);
                wg_wait<1>();
            }
            if (elected) TS(29);
            TT(1);
            {
#pragma unroll
                for (int k = 0; k < 8; k++)
                    asm volatile("ldmatrix.sync.aligned.m8n8.x4.shared.b16 {%0, %1, %2, %3}, [%4];"
                                 : "=r"(x2[4 * k]), "=r"(x2[4 * k + 1]), "=r"(x2[4 * k + 2]), "=r"(x2[4 * k + 3])
                                 : "r"(xa + (k >> 2) * 8192 + (((2 * (k & 3) + (lane >> 4)) ^ (lane & 7)) << 4)) : "memory");
            }
            wg_wait<0>();
            reg_fence(s);
            bar_arrive(4, 256);
            if (elected) TS(39);
            TT(2);
            const uint4* pr = g_out + (rb ^ (8 * OMAP)) * OB + t7;
            uint4 pa[8];
#pragma unroll
            for (int v = 0; v < 8; v++) pa[v] = ld_poll(pr + v * 128);
            float4 tc[16];
#pragma unroll
            for (int k = 0; k < 16; k++) {
                tc[k] = tf[k * 4];
                if (!(g & 1)) tc[k].z = __uint_as_float(ONE2);
#pragma unroll
                for (int i = 4 * k; i < 4 * k + 4; i++) s[i] = fmaf((i & 1) ? tc[k].y : tc[k].x, s[i], (i & 1) ? bf_hi(x2[i >> 1]) : bf_lo(x2[i >> 1]));
            }
            reg_fence(s);
            for (;;) {
                uint32_t bad = 0;
#pragma unroll
                for (int v = 0; v < 8; v++) bad |= pa[v].x ^ ep;
                if (__all_sync(0xffffffffu, (bad & 1) == 0)) break;
                if (PSLEEP) __nanosleep(PSLEEP);
#pragma unroll
                for (int v = 0; v < 8; v++) pa[v] = ld_poll(pr + v * 128);
            }
            if (elected) TS(30);
            TT(3);
            float sd[4] = {}, q0[4] = {}, q1[4] = {};
#pragma unroll
            for (int k = 0; k < 8; k++) {
#pragma unroll
                for (int i = 4 * k; i < 4 * k + 4; i++) {
                    const uint32_t w = (&pa[k].x)[i & 3];
                    x2[i] = pack2(fmaf(tc[i >> 1].x, bf_lo(w), s[2 * i]), fmaf(tc[i >> 1].y, bf_hi(w), s[2 * i + 1]));
                }
                mma16816(sd, x2 + 4 * k, __float_as_uint(tc[2 * k].z), __float_as_uint(tc[2 * k + 1].z));
                mma16816(q0, x2 + 4 * k, x2[4 * k], x2[4 * k + 2]);
                mma16816(q1, x2 + 4 * k, x2[4 * k + 1], x2[4 * k + 3]);
            }
            uint4* sp = g_out + rb * OB + OB_STAT + (w4 * 8 + g) * 2;
            st_pub(sp, make_uint4(__float_as_uint(sd[0]), __float_as_uint((g & 1) ? q0[1] : q0[0]), __float_as_uint(sd[1]), ep), c4 == g >> 1);
            st_pub(sp + 1, make_uint4(__float_as_uint(sd[2]), __float_as_uint((g & 1) ? q1[3] : q1[2]), __float_as_uint(sd[3]), ep), c4 == g >> 1);
            if (TF & 1) sched_fence(eb2, P.zero);
            if (elected) TS(56);
            TT(4);
            uint32_t cb[16], sh[16], gb[16];
#pragma unroll
            for (int i = 0; i < 16; i++) {
                const float4 c = tf[64 + i * 4];
                cb[i] = __float_as_uint(c.x); sh[i] = __float_as_uint(c.y); gb[i] = __float_as_uint(c.z);
            }
            const float ra = __uint_as_float(lds32(sb + SM_EP + 8)), rb0 = __uint_as_float(lds32(sb + SM_EP + 12));
            uint4 r0, r1;
            if (SPRE) __nanosleep(SPRE);
            for (;;) {
                r0 = ld_poll(g_out + ((rb & ~(16 * OMAP + 1)) + (c4 & 1) + (c4 & 2) * 8 * OMAP) * OB + OB_STAT + (w4 * 8 + g) * 2);
                r1 = ld_poll(g_out + ((rb & ~(16 * OMAP + 1)) + (c4 & 1) + (c4 & 2) * 8 * OMAP) * OB + OB_STAT + (w4 * 8 + g) * 2 + 1);
                if (__all_sync(0xffffffffu, r0.w == ep && r1.w == ep)) break;
                if (SSLEEP) __nanosleep(SSLEEP);
            }
            if (elected) TS(57);
            TT(5);
            const float m0 = quad_sum(__uint_as_float(r0.x)) * (1.f / 512.f), m1 = quad_sum(__uint_as_float(r1.x)) * (1.f / 512.f);
            const float rs0 = ln_rstd(fmaxf(fmaf(-m0, m0, quad_sum(__uint_as_float(r0.y)) * (1.f / 512.f)), 0.f));
            const float rs1 = ln_rstd(fmaxf(fmaf(-m1, m1, quad_sum(__uint_as_float(r1.y)) * (1.f / 512.f)), 0.f));
            const uint32_t mb0 = pack2(m0, m0), mb1 = pack2(m1, m1);
            const uint32_t lg = pack2(fmaf(rs0, fmaf(-bf_lo(mb0), ra, quad_sum(__uint_as_float(r0.z))), rb0),
                                      fmaf(rs1, fmaf(-bf_lo(mb1), ra, quad_sum(__uint_as_float(r1.z))), rb0));
            const uint32_t u0 = lg << 16, u1 = lg & 0xffff0000u;
            const uint32_t k0 = ((u0 ^ (((int)u0 >> 31) | 0x80000000u)) & 0xffff0000u) | ((2047 - row) << 5) | (ep & 31);
            const uint32_t k1 = ((u1 ^ (((int)u1 >> 31) | 0x80000000u)) & 0xffff0000u) | ((2039 - row) << 5) | (ep & 31);
            const uint32_t kb = __reduce_max_sync(0xffffffffu, max(k0, k1));
            st_pub(g_key + cq * 128 + (row >> 4), kb, lane == 0);
            const bool cand = kb == k0 || kb == k1;
            uint4* cp = g_cand + (row >> 4) * 192 + cq * 24 + c4;
#pragma unroll 1
            for (int it = 0; it < 3; it++) {
                bool put = it == 1 || !cand;
                if (it == 2) {
                    mbar_wait(sb + BAR_BEST, 0);
                    put = cand && lds32(sb + SM_EP + 24) != kb;
                }
                const bool hi = (kb == k1) != (it == 1);
                uint32_t cx[18], ch[18];
#pragma unroll
                for (int i = 0; i < 16; i++) {
                    cx[i] = hi ? x2[2 * i + 1] : x2[2 * i];
                    ch[i] = ln_apply(cx[i], hi ? mb1 : mb0, hi ? rs1 : rs0, cb[i], sh[i]);
                }
                cx[16] = cx[17] = ch[16] = ch[17] = 0;
#pragma unroll
                for (int v = 0; v < 6; v++) st_pub(cp + v * 4, make_uint4(ch[3 * v], ch[3 * v + 1], ch[3 * v + 2], ep), cand && it == 0);
                if (TF & 4) sched_fence(eb2, P.zero);
#pragma unroll
                for (int v = 0; v < 6; v++) st_pub(cp + 96 + v * 4, make_uint4(cx[3 * v], cx[3 * v + 1], cx[3 * v + 2], ep), cand && it == 0);
                if (it == 0) TT(6);
                uint2* op = reinterpret_cast<uint2*>(P.out) + (row + 8 * hi) * 128 + cq * 32 + (c4 & 1) * 2 + (c4 >> 1);
#pragma unroll
                for (int i = 0; i < 16; i += 2) {
                    const uint32_t v0 = badd(cx[i], bmul(gb[i], ch[i])), v1 = badd(cx[i + 1], bmul(gb[i + 1], ch[i + 1]));
                    const uint32_t rv = __shfl_xor_sync(0xffffffffu, (c4 & 1) ? v0 : v1, 1);
                    if (put) op[i * 2] = (c4 & 1) ? make_uint2(rv, v1) : make_uint2(v0, rv);
                }
            }
            if (elected) TS(59);
            TT(7);
        }
        mbar_arrive_if(eb2, lane == 0);
    }
}

typedef CUresult (*EncodeFn)(CUtensorMap*, CUtensorMapDataType, cuuint32_t, void*, const cuuint64_t*, const cuuint64_t*,
                             const cuuint32_t*, const cuuint32_t*, CUtensorMapInterleave, CUtensorMapSwizzle,
                             CUtensorMapL2promotion, CUtensorMapFloatOOBfill);

void make_2d(EncodeFn fn, CUtensorMap* m, const void* p, uint64_t cols, uint64_t rows, uint32_t bc, uint32_t br) {
    cuuint64_t dims[2] = {cols, rows}, strides[1] = {cols * 2};
    cuuint32_t box[2] = {bc, br}, es[2] = {1, 1};
    fn(m, CU_TENSOR_MAP_DATA_TYPE_BFLOAT16, 2, const_cast<void*>(p), dims, strides, box, es, CU_TENSOR_MAP_INTERLEAVE_NONE,
       CU_TENSOR_MAP_SWIZZLE_NONE, CU_TENSOR_MAP_L2_PROMOTION_L2_128B, CU_TENSOR_MAP_FLOAT_OOB_FILL_NONE);
}
void make_3d(EncodeFn fn, CUtensorMap* m, const void* p, uint64_t cols, uint64_t rows, uint32_t br = 128, uint32_t nb = 2) {
    cuuint64_t dims[3] = {64, rows, cols / 64}, strides[2] = {cols * 2, 128};
    cuuint32_t box[3] = {64, br, nb}, es[3] = {1, 1, 1};
    fn(m, CU_TENSOR_MAP_DATA_TYPE_BFLOAT16, 3, const_cast<void*>(p), dims, strides, box, es, CU_TENSOR_MAP_INTERLEAVE_NONE,
       CU_TENSOR_MAP_SWIZZLE_128B, CU_TENSOR_MAP_L2_PROMOTION_L2_256B, CU_TENSOR_MAP_FLOAT_OOB_FILL_NONE);
}

}

extern "C" void kernel_launch(void* const* d_in, const int* in_sizes, int n_in, void* d_out, int out_size) {
    static EncodeFn fn = nullptr;
    if (!fn) {
        void* f = nullptr;
        cudaDriverEntryPointQueryResult st;
        cudaGetDriverEntryPoint("cuTensorMapEncodeTiled", &f, cudaEnableDefault, &st);
        fn = (EncodeFn)f;
        cudaFuncSetAttribute(fused_kernel, cudaFuncAttributeMaxDynamicSharedMemorySize, SMEM_BYTES);
    }
    CUtensorMap ckv, wq, wuk, wuv, wo, wg, wu, wm, xm;
    make_3d(fn, &ckv, d_in[1], 512, 2048, 128, 1);
    make_3d(fn, &xm, d_in[0], 512, 2048, 64);
    make_3d(fn, &wq, d_in[2], 4096, 512);
    make_3d(fn, &wuk, d_in[3], 4096, 512);
    make_3d(fn, &wuv, d_in[4], 4096, 512);
    make_3d(fn, &wo, d_in[5], 512, 4096);
    make_2d(fn, &wg, d_in[8], 1792, 512, 16, 256);
    make_2d(fn, &wu, d_in[9], 1792, 512, 16, 256);
    make_2d(fn, &wm, d_in[12], 3072, 512, 256, 64);
    Params p;
    p.x = (const bf16*)d_in[0];
    p.ckv = (const bf16*)d_in[1];
    p.wo = (const bf16*)d_in[5];
    p.wr = (const bf16*)d_in[7];
    p.wdown = (const bf16*)d_in[10];
    p.c = (const bf16*)d_in[11];
    p.out = (bf16*)d_out;
    p.zero = 0;
    fused_kernel<<<NCTA + NSPARE, 384, SMEM_BYTES>>>(ckv, wq, wuk, wuv, wo, wg, wu, wm, xm, p);
}
```

```cpp
#include <cuda.h>
#include <cuda_bf16.h>
#include <cuda_runtime.h>
#include <stdint.h>
#include <stdio.h>

namespace {

typedef __nv_bfloat16 bf16;
typedef unsigned long long u64;

constexpr int NCTA = 128, NSPARE = 4;
constexpr int SLOT = 32768;
constexpr int SM_BAR = 7 * SLOT;
constexpr int BAR_FULL = SM_BAR;
constexpr int BAR_EMPTY = BAR_FULL + 8 * 7;
constexpr int BAR_DONE = BAR_EMPTY + 8 * 7;
constexpr int BAR_FLAG = BAR_DONE + 8 * 9;
constexpr int BAR_PF = BAR_FLAG + 8 * 9;
constexpr int BAR_END = BAR_PF + 8;
constexpr int BAR_BEST = BAR_END + 8;
constexpr int SM_EP = BAR_END + 24;
constexpr int SM_RED = SM_BAR + 384;
constexpr int SM_TAB = SM_BAR + 1024;
constexpr int SMEM_BYTES = SM_BAR + 3072;
constexpr int NFFN = 112;
#define HINT 479
constexpr u64 L2_NORMAL = 0x1000000000000000ull, L2_FIRST = 0x12F0000000000000ull;
#define PFA 8
#define PFB 6
#define UNR 1
#define POLL_NS 50
#define MSPLIT 13
#define SF 3
#define NSH 1
#define XPF 2
#define TF 1
#define KSLEEP 200
#define YSLEEP 50
#define YPRE 150
#define SSLEEP 50
#define SPRE 0
#define PSLEEP 100
#define CSLEEP 0
#define SPEC 28
#define OMAP 2
#define KVG 7
#define PEARLY 0
#define ELATE 0
#define EARLY 7
constexpr uint32_t SPIN_LIMIT = 1u << 22;
constexpr uint32_t ONE2 = 0x3f803f80u;

struct Sync {
    uint32_t cnt[16 * 8 * 8];
    uint32_t ctxcnt[16 * 32];
    uint32_t epoch[32];
};

__device__ __align__(1024) uint8_t g_KV[16 * 16 * 2 * SLOT];
__device__ __align__(1024) uint8_t g_ctx[16 * 32 * SLOT];
__device__ __align__(1024) uint8_t g_h[16 * 4 * SLOT];
constexpr int OB = 1216, OB_STAT = 1024, OB_Y = 1088;
__device__ __align__(1024) uint4 g_out[128 * OB];
__device__ __align__(1024) bf16 g_mod[3072];
__device__ __align__(1024) uint32_t g_mod1[1024];
__device__ __align__(1024) uint4 g_cand[128 * 192];
__device__ __align__(1024) uint32_t g_key[4 * 128];
__device__ __align__(1024) uint8_t g_wf[NFFN * SLOT];
__device__ __align__(1024) Sync g_sync;
#define TS(i)

#define TT(i)
#define PT()

struct Params {
    const bf16 *x, *ckv, *wo, *wr, *wdown, *c;
    bf16* out;
    int zero;
};

__device__ __forceinline__ void mbar_init(uint32_t bar, uint32_t cnt) {
    asm volatile("mbarrier.init.shared::cta.b64 [%0], %1;" ::"r"(bar), "r"(cnt) : "memory");
}
__device__ __forceinline__ void mbar_wait(uint32_t bar, uint32_t parity) {
    asm volatile("{\n.reg .pred p;\nL_%=:\nmbarrier.try_wait.parity.shared::cta.b64 p, [%0], %1;\n@!p bra L_%=;\n}" ::"r"(bar), "r"(parity) : "memory");
}
__device__ __forceinline__ void mbar_sleep(uint32_t bar) {
    if ((threadIdx.x & 31) == 0)
        asm volatile("{\n.reg .pred p;\nL_%=:\nmbarrier.try_wait.parity.shared::cta.b64 p, [%0], 0, 100000;\n@!p bra L_%=;\n}" ::"r"(bar) : "memory");
    __syncwarp();
}
__device__ __forceinline__ void mbar_watch(uint32_t bar, uint32_t parity) {
    asm volatile("{\n.reg .pred p;\n.reg .u32 n;\nmov.u32 n, 0;\n"
                 "L_%=:\nmbarrier.try_wait.parity.shared::cta.b64 p, [%0], %1;\n@p bra D_%=;\n"
                 "add.u32 n, n, 1;\nsetp.lt.u32 p, n, %2;\n@p bra L_%=;\ntrap;\nD_%=:\n}"
                 ::"r"(bar), "r"(parity), "n"(SPIN_LIMIT) : "memory");
}
__device__ __forceinline__ void step_watch(uint32_t a, uint32_t step) {
    asm volatile("{\n.reg .pred p;\n.reg .u32 n, v;\nmov.u32 n, 0;\n"
                 "L_%=:\nld.volatile.shared.u32 v, [%0];\nsetp.ge.u32 p, v, %1;\n@p bra D_%=;\nnanosleep.u32 400;\n"
                 "add.u32 n, n, 1;\nsetp.lt.u32 p, n, %2;\n@p bra L_%=;\ntrap;\nD_%=:\n}"
                 ::"r"(a), "r"(step), "n"(SPIN_LIMIT) : "memory");
}
__device__ __forceinline__ void mbar_arrive_if(uint32_t bar, bool on) {
    asm volatile("{\n.reg .pred p;\nsetp.ne.s32 p, %1, 0;\n@p mbarrier.arrive.shared::cta.b64 _, [%0];\n}" ::"r"(bar), "r"((int)on) : "memory");
}
__device__ __forceinline__ void tma2d(uint32_t dst, const CUtensorMap* m, int c0, int c1, uint32_t bar, bool first) {
    asm volatile("{\n.reg .pred p;\nelect.sync _|p, 0xffffffff;\n"
                 "@p cp.async.bulk.tensor.2d.shared::cluster.global.mbarrier::complete_tx::bytes.L2::cache_hint [%0], [%1, {%3, %4}], [%2], %5;\n}"
                 ::"r"(dst), "l"(m), "r"(bar), "r"(c0), "r"(c1), "l"(first ? L2_FIRST : L2_NORMAL) : "memory");
}
__device__ __forceinline__ void tma3d_prefetch(const CUtensorMap* m, int row, int cb) {
    asm volatile("{\n.reg .pred p;\nelect.sync _|p, 0xffffffff;\n@p cp.async.bulk.prefetch.tensor.3d.L2.global [%0, {%1, %2, %3}];\n}"
                 ::"l"(m), "r"(0), "r"(row), "r"(cb) : "memory");
}
__device__ __forceinline__ void l2_prefetch(const void* p, uint32_t bytes) {
    asm volatile("{\n.reg .pred p;\nelect.sync _|p, 0xffffffff;\n@p cp.async.bulk.prefetch.L2.global [%0], %1;\n}" ::"l"(p), "r"(bytes) : "memory");
}
__device__ __forceinline__ void bulk_store(void* dst, uint32_t src, uint32_t bytes, bool first) {
    asm volatile("{\n.reg .pred p;\nelect.sync _|p, 0xffffffff;\n@p cp.async.bulk.global.shared::cta.bulk_group.L2::cache_hint [%0], [%1], %2, %3;\n}"
                 ::"l"(dst), "r"(src), "r"(bytes), "l"(first ? L2_FIRST : L2_NORMAL) : "memory");
}
__device__ __forceinline__ void flag_wait(const uint32_t* f, uint32_t target) {
    asm volatile("{\n.reg .pred p;\n.reg .u32 v;\n"
                 "L_%=:\nld.acquire.gpu.global.u32 v, [%0];\nsub.u32 v, v, %1;\nsetp.lt.s32 p, v, 0;\n@p nanosleep.u32 100;\n@p bra L_%=;\n}"
                 ::"l"(f), "r"(target) : "memory");
}
__device__ __forceinline__ uint4 ld_poll(const uint4* p) {
    uint4 v;
    asm volatile("{\n.reg .b128 t;\nld.relaxed.gpu.global.b128 t, [%4];\nmov.b128 {%0, %1, %2, %3}, t;\n}"
                 : "=r"(v.x), "=r"(v.y), "=r"(v.z), "=r"(v.w) : "l"(p) : "memory");
    return v;
}
__device__ __forceinline__ void st_pub(uint4* p, uint4 v, bool on) {
    asm volatile("{\n.reg .pred p;\n.reg .b128 t;\nsetp.ne.s32 p, %5, 0;\nmov.b128 t, {%1, %2, %3, %4};\n@p st.relaxed.gpu.global.b128 [%0], t;\n}"
                 ::"l"(p), "r"(v.x), "r"(v.y), "r"(v.z), "r"(v.w), "r"((int)on) : "memory");
}
__device__ __forceinline__ void st_pub(uint32_t* p, uint32_t v, bool on) {
    asm volatile("{\n.reg .pred p;\nsetp.ne.s32 p, %2, 0;\n@p st.relaxed.gpu.global.u32 [%0], %1;\n}" ::"l"(p), "r"(v), "r"((int)on) : "memory");
}
__device__ __forceinline__ void flag_add(uint32_t* p) {
    asm volatile("red.release.gpu.global.add.u32 [%0], 1;" ::"l"(p) : "memory");
}
__device__ __forceinline__ uint32_t lds32(uint32_t a) {
    uint32_t v;
    asm volatile("ld.shared.u32 %0, [%1];" : "=r"(v) : "r"(a) : "memory");
    return v;
}
__device__ __forceinline__ uint4 lds128(uint32_t a) {
    uint4 v;
    asm volatile("ld.shared.v4.u32 {%0, %1, %2, %3}, [%4];" : "=r"(v.x), "=r"(v.y), "=r"(v.z), "=r"(v.w) : "r"(a) : "memory");
    return v;
}
__device__ __forceinline__ void sched_fence(uint32_t& v, uint32_t z) {
    uint32_t ck;
    asm volatile("mov.u32 %0, %%clock;" : "=r"(ck)::"memory");
    v ^= ck & z;
}
__device__ __forceinline__ void fence_async_global() { asm volatile("fence.proxy.async.global;" ::: "memory"); }
__device__ __forceinline__ void fence_async_smem() { asm volatile("fence.proxy.async.shared::cta;" ::: "memory"); }
__device__ __forceinline__ void bar_sync(int id, int n) { asm volatile("bar.sync %0, %1;" ::"r"(id), "r"(n) : "memory"); }
__device__ __forceinline__ void bar_arrive(int id, int n) { asm volatile("bar.arrive %0, %1;" ::"r"(id), "r"(n) : "memory"); }
__device__ __forceinline__ void wg_fence() { asm volatile("wgmma.fence.sync.aligned;" ::: "memory"); }
__device__ __forceinline__ void wg_commit() { asm volatile("wgmma.commit_group.sync.aligned;" ::: "memory"); }
template <int N> __device__ __forceinline__ void wg_wait() { asm volatile("wgmma.wait_group.sync.aligned %0;" ::"n"(N) : "memory"); }
template <int N> __device__ __forceinline__ void reg_fence(float (&d)[N]) {
#pragma unroll
    for (int i = 0; i < N; i++) asm volatile("" : "+f"(d[i])::"memory");
}
template <int N> __device__ __forceinline__ void reg_fence(uint32_t (&d)[N]) {
#pragma unroll
    for (int i = 0; i < N; i++) asm volatile("" : "+r"(d[i])::"memory");
}
__device__ __forceinline__ uint32_t desc_k(uint32_t a) { return ((a & 0x3ffff) >> 4) | (1u << 16); }
__device__ __forceinline__ uint32_t desc_mn(uint32_t a) { return ((a & 0x3ffff) >> 4) | (1024u << 16); }

template <int TB>
__device__ __forceinline__ void wgmma_ss128(float (&d)[64], uint32_t da, uint32_t db, int acc, uint32_t ha = 0x40000040u, uint32_t hb = 0x40000040u) {
    asm volatile("{\n.reg .pred p;\n.reg .b64 a, b;\nsetp.ne.b32 p, %66, 0;\nmov.b64 a, {%64, %68};\nmov.b64 b, {%65, %69};\n"
        "wgmma.mma_async.sync.aligned.m64n128k16.f32.bf16.bf16 {%0, %1, %2, %3, %4, %5, %6, %7, %8, %9, %10, %11, %12, %13, %14, %15, %16, %17, %18, %19, %20, %21, %22, %23, %24, %25, %26, %27, %28, %29, %30, %31, %32, %33, %34, %35, %36, %37, %38, %39, %40, %41, %42, %43, %44, %45, %46, %47, %48, %49, %50, %51, %52, %53, %54, %55, %56, %57, %58, %59, %60, %61, %62, %63}, a, b, p, 1, 1, 0, %67;\n}"
        : "+f"(d[0]), "+f"(d[1]), "+f"(d[2]), "+f"(d[3]), "+f"(d[4]), "+f"(d[5]), "+f"(d[6]), "+f"(d[7]), "+f"(d[8]), "+f"(d[9]), "+f"(d[10]), "+f"(d[11]), "+f"(d[12]), "+f"(d[13]), "+f"(d[14]), "+f"(d[15]), "+f"(d[16]), "+f"(d[17]), "+f"(d[18]), "+f"(d[19]), "+f"(d[20]), "+f"(d[21]), "+f"(d[22]), "+f"(d[23]), "+f"(d[24]), "+f"(d[25]), "+f"(d[26]), "+f"(d[27]), "+f"(d[28]), "+f"(d[29]), "+f"(d[30]), "+f"(d[31]), "+f"(d[32]), "+f"(d[33]), "+f"(d[34]), "+f"(d[35]), "+f"(d[36]), "+f"(d[37]), "+f"(d[38]), "+f"(d[39]), "+f"(d[40]), "+f"(d[41]), "+f"(d[42]), "+f"(d[43]), "+f"(d[44]), "+f"(d[45]), "+f"(d[46]), "+f"(d[47]), "+f"(d[48]), "+f"(d[49]), "+f"(d[50]), "+f"(d[51]), "+f"(d[52]), "+f"(d[53]), "+f"(d[54]), "+f"(d[55]), "+f"(d[56]), "+f"(d[57]), "+f"(d[58]), "+f"(d[59]), "+f"(d[60]), "+f"(d[61]), "+f"(d[62]), "+f"(d[63])
        : "r"(da), "r"(db), "r"(acc), "n"(TB), "r"(ha), "r"(hb));
}
template <int TB>
__device__ __forceinline__ void wgmma_ss128_init(float (&d)[64], uint32_t da, uint32_t db, uint32_t ha = 0x40000040u, uint32_t hb = 0x40000040u) {
    asm volatile("{\n.reg .pred p;\n.reg .b64 a, b;\nsetp.ne.b32 p, 0, 0;\nmov.b64 a, {%64, %67};\nmov.b64 b, {%65, %68};\n"
        "wgmma.mma_async.sync.aligned.m64n128k16.f32.bf16.bf16 {%0, %1, %2, %3, %4, %5, %6, %7, %8, %9, %10, %11, %12, %13, %14, %15, %16, %17, %18, %19, %20, %21, %22, %23, %24, %25, %26, %27, %28, %29, %30, %31, %32, %33, %34, %35, %36, %37, %38, %39, %40, %41, %42, %43, %44, %45, %46, %47, %48, %49, %50, %51, %52, %53, %54, %55, %56, %57, %58, %59, %60, %61, %62, %63}, a, b, p, 1, 1, 0, %66;\n}"
        : "=f"(d[0]), "=f"(d[1]), "=f"(d[2]), "=f"(d[3]), "=f"(d[4]), "=f"(d[5]), "=f"(d[6]), "=f"(d[7]), "=f"(d[8]), "=f"(d[9]), "=f"(d[10]), "=f"(d[11]), "=f"(d[12]), "=f"(d[13]), "=f"(d[14]), "=f"(d[15]), "=f"(d[16]), "=f"(d[17]), "=f"(d[18]), "=f"(d[19]), "=f"(d[20]), "=f"(d[21]), "=f"(d[22]), "=f"(d[23]), "=f"(d[24]), "=f"(d[25]), "=f"(d[26]), "=f"(d[27]), "=f"(d[28]), "=f"(d[29]), "=f"(d[30]), "=f"(d[31]), "=f"(d[32]), "=f"(d[33]), "=f"(d[34]), "=f"(d[35]), "=f"(d[36]), "=f"(d[37]), "=f"(d[38]), "=f"(d[39]), "=f"(d[40]), "=f"(d[41]), "=f"(d[42]), "=f"(d[43]), "=f"(d[44]), "=f"(d[45]), "=f"(d[46]), "=f"(d[47]), "=f"(d[48]), "=f"(d[49]), "=f"(d[50]), "=f"(d[51]), "=f"(d[52]), "=f"(d[53]), "=f"(d[54]), "=f"(d[55]), "=f"(d[56]), "=f"(d[57]), "=f"(d[58]), "=f"(d[59]), "=f"(d[60]), "=f"(d[61]), "=f"(d[62]), "=f"(d[63])
        : "r"(da), "r"(db), "n"(TB), "r"(ha), "r"(hb));
}
template <int TB>
__device__ __forceinline__ void wgmma_ss64(float (&d)[32], uint32_t da, uint32_t db, int acc, uint32_t ha = 0x40000040u, uint32_t hb = 0x40000040u) {
    asm volatile("{\n.reg .pred p;\n.reg .b64 a, b;\nsetp.ne.b32 p, %34, 0;\nmov.b64 a, {%32, %36};\nmov.b64 b, {%33, %37};\n"
        "wgmma.mma_async.sync.aligned.m64n64k16.f32.bf16.bf16 {%0, %1, %2, %3, %4, %5, %6, %7, %8, %9, %10, %11, %12, %13, %14, %15, %16, %17, %18, %19, %20, %21, %22, %23, %24, %25, %26, %27, %28, %29, %30, %31}, a, b, p, 1, 1, 0, %35;\n}"
        : "+f"(d[0]), "+f"(d[1]), "+f"(d[2]), "+f"(d[3]), "+f"(d[4]), "+f"(d[5]), "+f"(d[6]), "+f"(d[7]), "+f"(d[8]), "+f"(d[9]), "+f"(d[10]), "+f"(d[11]), "+f"(d[12]), "+f"(d[13]), "+f"(d[14]), "+f"(d[15]), "+f"(d[16]), "+f"(d[17]), "+f"(d[18]), "+f"(d[19]), "+f"(d[20]), "+f"(d[21]), "+f"(d[22]), "+f"(d[23]), "+f"(d[24]), "+f"(d[25]), "+f"(d[26]), "+f"(d[27]), "+f"(d[28]), "+f"(d[29]), "+f"(d[30]), "+f"(d[31])
        : "r"(da), "r"(db), "r"(acc), "n"(TB), "r"(ha), "r"(hb));
}
template <int TB>
__device__ __forceinline__ void wgmma_ss64_init(float (&d)[32], uint32_t da, uint32_t db, uint32_t ha = 0x40000040u, uint32_t hb = 0x40000040u) {
    asm volatile("{\n.reg .pred p;\n.reg .b64 a, b;\nsetp.ne.b32 p, 0, 0;\nmov.b64 a, {%32, %35};\nmov.b64 b, {%33, %36};\n"
        "wgmma.mma_async.sync.aligned.m64n64k16.f32.bf16.bf16 {%0, %1, %2, %3, %4, %5, %6, %7, %8, %9, %10, %11, %12, %13, %14, %15, %16, %17, %18, %19, %20, %21, %22, %23, %24, %25, %26, %27, %28, %29, %30, %31}, a, b, p, 1, 1, 0, %34;\n}"
        : "=f"(d[0]), "=f"(d[1]), "=f"(d[2]), "=f"(d[3]), "=f"(d[4]), "=f"(d[5]), "=f"(d[6]), "=f"(d[7]), "=f"(d[8]), "=f"(d[9]), "=f"(d[10]), "=f"(d[11]), "=f"(d[12]), "=f"(d[13]), "=f"(d[14]), "=f"(d[15]), "=f"(d[16]), "=f"(d[17]), "=f"(d[18]), "=f"(d[19]), "=f"(d[20]), "=f"(d[21]), "=f"(d[22]), "=f"(d[23]), "=f"(d[24]), "=f"(d[25]), "=f"(d[26]), "=f"(d[27]), "=f"(d[28]), "=f"(d[29]), "=f"(d[30]), "=f"(d[31])
        : "r"(da), "r"(db), "n"(TB), "r"(ha), "r"(hb));
}
__device__ __forceinline__ void wgmma_rs128(float (&d)[64], uint32_t a0, uint32_t a1, uint32_t a2, uint32_t a3, uint32_t db, int acc, uint32_t hb = 0x40000040u) {
    asm volatile("{\n.reg .pred p;\n.reg .b64 b;\nsetp.ne.b32 p, %69, 0;\nmov.b64 b, {%68, %70};\n"
        "wgmma.mma_async.sync.aligned.m64n128k16.f32.bf16.bf16 {%0, %1, %2, %3, %4, %5, %6, %7, %8, %9, %10, %11, %12, %13, %14, %15, %16, %17, %18, %19, %20, %21, %22, %23, %24, %25, %26, %27, %28, %29, %30, %31, %32, %33, %34, %35, %36, %37, %38, %39, %40, %41, %42, %43, %44, %45, %46, %47, %48, %49, %50, %51, %52, %53, %54, %55, %56, %57, %58, %59, %60, %61, %62, %63}, {%64, %65, %66, %67}, b, p, 1, 1, 1;\n}"
        : "+f"(d[0]), "+f"(d[1]), "+f"(d[2]), "+f"(d[3]), "+f"(d[4]), "+f"(d[5]), "+f"(d[6]), "+f"(d[7]), "+f"(d[8]), "+f"(d[9]), "+f"(d[10]), "+f"(d[11]), "+f"(d[12]), "+f"(d[13]), "+f"(d[14]), "+f"(d[15]), "+f"(d[16]), "+f"(d[17]), "+f"(d[18]), "+f"(d[19]), "+f"(d[20]), "+f"(d[21]), "+f"(d[22]), "+f"(d[23]), "+f"(d[24]), "+f"(d[25]), "+f"(d[26]), "+f"(d[27]), "+f"(d[28]), "+f"(d[29]), "+f"(d[30]), "+f"(d[31]), "+f"(d[32]), "+f"(d[33]), "+f"(d[34]), "+f"(d[35]), "+f"(d[36]), "+f"(d[37]), "+f"(d[38]), "+f"(d[39]), "+f"(d[40]), "+f"(d[41]), "+f"(d[42]), "+f"(d[43]), "+f"(d[44]), "+f"(d[45]), "+f"(d[46]), "+f"(d[47]), "+f"(d[48]), "+f"(d[49]), "+f"(d[50]), "+f"(d[51]), "+f"(d[52]), "+f"(d[53]), "+f"(d[54]), "+f"(d[55]), "+f"(d[56]), "+f"(d[57]), "+f"(d[58]), "+f"(d[59]), "+f"(d[60]), "+f"(d[61]), "+f"(d[62]), "+f"(d[63])
        : "r"(a0), "r"(a1), "r"(a2), "r"(a3), "r"(db), "r"(acc), "r"(hb));
}

__device__ __forceinline__ uint32_t pack2(float lo, float hi) {
    uint32_t r;
    asm("cvt.rn.bf16x2.f32 %0, %1, %2;" : "=r"(r) : "f"(hi), "f"(lo));
    return r;
}
__device__ __forceinline__ float bf_lo(uint32_t v) { return __uint_as_float(v << 16); }
__device__ __forceinline__ float bf_hi(uint32_t v) { return __uint_as_float(v & 0xffff0000u); }
__device__ __forceinline__ float rbf(float v) { return bf_lo(pack2(v, v)); }
__device__ __forceinline__ uint32_t badd(uint32_t a, uint32_t b) {
    uint32_t r;
    asm("add.rn.bf16x2 %0, %1, %2;" : "=r"(r) : "r"(a), "r"(b));
    return r;
}
__device__ __forceinline__ uint32_t bsub(uint32_t a, uint32_t b) {
    uint32_t r;
    asm("sub.rn.bf16x2 %0, %1, %2;" : "=r"(r) : "r"(a), "r"(b));
    return r;
}
__device__ __forceinline__ uint32_t bmul(uint32_t a, uint32_t b) {
    uint32_t r;
    asm("mul.rn.bf16x2 %0, %1, %2;" : "=r"(r) : "r"(a), "r"(b));
    return r;
}
__device__ __forceinline__ uint32_t ln_apply(uint32_t x, uint32_t mb, float rs, uint32_t scale, uint32_t shift) {
    const uint32_t d = bsub(x, mb);
    return badd(bmul(pack2(bf_lo(d) * rs, bf_hi(d) * rs), scale), shift);
}
__device__ __forceinline__ float ex2(float v) {
    float r;
    asm("ex2.approx.ftz.f32 %0, %1;" : "=f"(r) : "f"(v));
    return r;
}
__device__ __forceinline__ float rcp(float v) {
    float r;
    asm("rcp.approx.ftz.f32 %0, %1;" : "=f"(r) : "f"(v));
    return r;
}
__device__ __forceinline__ float sqrt_fast(float v) {
    float r;
    asm("sqrt.approx.ftz.f32 %0, %1;" : "=f"(r) : "f"(v));
    return r;
}
__device__ __forceinline__ float ln_rstd(float var) { return rcp(rbf(sqrt_fast(rbf(rbf(var) + 1e-5f)))); }
__device__ __forceinline__ float sigmoid(float v) { return rcp(1.f + ex2(-1.4426950408889634f * v)); }
__device__ __forceinline__ float quad_sum(float v) {
    v += __shfl_xor_sync(0xffffffffu, v, 1);
    return v + __shfl_xor_sync(0xffffffffu, v, 2);
}

constexpr uint32_t HI_128 = 0x40000040u, HI_IMG = 0x80000080u, HI_Q = 0x80000040u;
template <int M, int RH>
__device__ __forceinline__ uint4 img_pack(const float (&d)[64], float s) {
    uint4 v;
    v.x = pack2(d[16 * M + 2 * RH] * s, d[16 * M + 2 * RH + 1] * s);
    v.y = pack2(d[16 * M + 4 + 2 * RH] * s, d[16 * M + 5 + 2 * RH] * s);
    v.z = pack2(d[16 * M + 8 + 2 * RH] * s, d[16 * M + 9 + 2 * RH] * s);
    v.w = pack2(d[16 * M + 12 + 2 * RH] * s, d[16 * M + 13 + 2 * RH] * s);
    return v;
}
template <int M>
__device__ __forceinline__ void img_store_global(uint8_t* img, uint32_t toff, const float (&d)[64], float s0, float s1) {
    uint4* p = reinterpret_cast<uint4*>(img + toff) + M * 32;
    p[0] = img_pack<M, 0>(d, s0);
    p[128] = img_pack<M, 1>(d, s1);
}
__device__ __forceinline__ void sts128(uint32_t a, uint4 v) {
    asm volatile("st.shared.v4.b32 [%0], {%1, %2, %3, %4};" ::"r"(a), "r"(v.x), "r"(v.y), "r"(v.z), "r"(v.w) : "memory");
}
constexpr float SM_C = 0.08838834764831845f * 1.4426950408889634f;
__device__ __forceinline__ float pack2f(float lo, float hi) {
    float r;
    asm("{\n.reg .b32 t;\ncvt.rn.bf16x2.f32 t, %1, %2;\nmov.b32 %0, t;\n}" : "=f"(r) : "f"(hi), "f"(lo));
    return r;
}
template <int M, bool SCALE, bool PARK>
__device__ __forceinline__ void pack_group(float (&d)[64], float (&v)[8], float s0, float s1) {
#pragma unroll
    for (int i = 0; i < 8; i++) {
        const int k = 16 * M + 4 * (i & 3) + 2 * (i >> 2);
        v[i] = SCALE ? pack2f(d[k] * (i < 4 ? s0 : s1), d[k + 1] * (i < 4 ? s0 : s1)) : pack2f(d[k], d[k + 1]);
        if (PARK && M > 0) d[16 * (M > 0 ? M - 1 : 0) + i] = v[i];
    }
}
__device__ __forceinline__ uint32_t q_off(uint32_t toff) { return (((toff >> 1) & ~2047u) ^ 8192) + (toff & 511); }
template <int M, bool PARK>
__device__ __forceinline__ void ctx_store_part(float4* p, float (&d)[64], float i0, float i1) {
    float v[8];
    pack_group<M, true, PARK>(d, v, i0, i1);
    p[M * 32] = make_float4(v[0], v[1], v[2], v[3]);
    p[M * 32 + 128] = make_float4(v[4], v[5], v[6], v[7]);
}
template <bool PARK>
__device__ __forceinline__ void ctx_store(uint8_t* img, uint32_t toff, float (&o)[64], float l0, float l1) {
    const float i0 = rcp(quad_sum(l0)), i1 = rcp(quad_sum(l1));
    float4* p = reinterpret_cast<float4*>(img + toff);
    ctx_store_part<0, PARK>(p, o, i0, i1); ctx_store_part<1, PARK>(p, o, i0, i1); ctx_store_part<2, PARK>(p, o, i0, i1); ctx_store_part<3, PARK>(p, o, i0, i1);
}

template <int M>
__device__ __forceinline__ void tile_store_part(float4* p, uint32_t a, float (&d)[64], float i0, float i1, int ctx) {
    float v[8];
    pack_group<M, true, true>(d, v, i0, i1);
#pragma unroll
    for (int h = 0; h < 2; h++)
        asm volatile("{\n.reg .pred p;\nsetp.ne.s32 p, %6, 0;\n@p st.global.v4.f32 [%0], {%2, %3, %4, %5};\n@!p st.shared.v4.f32 [%1], {%2, %3, %4, %5};\n}"
                     ::"l"(p + M * 32 + h * 128), "r"(a + (M >> 1) * 16384 + (M & 1) * 512 + h * 1024),
                     "f"(v[4 * h]), "f"(v[4 * h + 1]), "f"(v[4 * h + 2]), "f"(v[4 * h + 3]), "r"(ctx) : "memory");
}
__device__ __forceinline__ void tile_store(uint8_t* img, uint32_t a, uint32_t toff, float (&d)[64], float i0, float i1, int ctx) {
    float4* p = reinterpret_cast<float4*>(img + toff);
    a += q_off(toff);
    tile_store_part<0>(p, a, d, i0, i1, ctx); tile_store_part<1>(p, a, d, i0, i1, ctx);
    tile_store_part<2>(p, a, d, i0, i1, ctx); tile_store_part<3>(p, a, d, i0, i1, ctx);
}

__device__ __forceinline__ void slot_wait(uint32_t bars, uint32_t& ph, uint32_t slot) {
    mbar_wait(bars + 8 * slot, (ph >> slot) & 1);
    ph ^= 1u << slot;
}
__device__ __forceinline__ void release_if(uint32_t eb, uint32_t slot, bool on) {
    asm volatile("{\n.reg .pred p;\nsetp.ne.s32 p, %1, 0;\n@p mbarrier.arrive.shared::cluster.b64 _, [%0];\n}" ::"r"(eb + 8 * slot), "r"((int)on) : "memory");
}
__device__ __forceinline__ void slot_acquire(uint32_t sb, uint32_t& ph, uint32_t slot) {
    slot_wait(sb + BAR_EMPTY, ph, slot);
    asm volatile("{\n.reg .pred p;\nelect.sync _|p, 0xffffffff;\n@p mbarrier.arrive.expect_tx.shared::cta.b64 _, [%0], 32768;\n}"
                 ::"r"(sb + BAR_FULL + 8 * slot) : "memory");
}
__device__ __forceinline__ void load_bulk(uint32_t sb, uint32_t slot, uint32_t off, const void* src, uint32_t bytes, bool both, bool first) {
    if (both)
        asm volatile("{\n.reg .pred p;\nelect.sync _|p, 0xffffffff;\n"
                     "@p cp.async.bulk.shared::cluster.global.mbarrier::complete_tx::bytes.multicast::cluster.L2::cache_hint [%0], [%1], %5, [%2], %4, %3;\n}"
                     ::"r"(sb + slot * SLOT + off), "l"(src), "r"(sb + BAR_FULL + 8 * slot), "l"(first ? L2_FIRST : L2_NORMAL), "h"((uint16_t)3),
                     "r"(bytes) : "memory");
    else
        asm volatile("{\n.reg .pred p;\nelect.sync _|p, 0xffffffff;\n"
                     "@p cp.async.bulk.shared::cluster.global.mbarrier::complete_tx::bytes.L2::cache_hint [%0], [%1], %4, [%2], %3;\n}"
                     ::"r"(sb + slot * SLOT + off), "l"(src), "r"(sb + BAR_FULL + 8 * slot), "l"(first ? L2_FIRST : L2_NORMAL), "r"(bytes) : "memory");
}
__device__ __forceinline__ void load_tile(uint32_t sb, uint32_t slot, uint32_t off, const CUtensorMap* m, int row, int cb, bool both, bool first) {
    if (both)
        asm volatile("{\n.reg .pred p;\nelect.sync _|p, 0xffffffff;\n"
                     "@p cp.async.bulk.tensor.3d.shared::cluster.global.mbarrier::complete_tx::bytes.multicast::cluster.L2::cache_hint [%0], [%1, {%3, %4, %5}], [%2], %7, %6;\n}"
                     ::"r"(sb + slot * SLOT + off), "l"(m), "r"(sb + BAR_FULL + 8 * slot), "r"(0), "r"(row), "r"(cb),
                     "l"(first ? L2_FIRST : L2_NORMAL), "h"((uint16_t)3) : "memory");
    else
        asm volatile("{\n.reg .pred p;\nelect.sync _|p, 0xffffffff;\n"
                     "@p cp.async.bulk.tensor.3d.shared::cluster.global.mbarrier::complete_tx::bytes.L2::cache_hint [%0], [%1, {%3, %4, %5}], [%2], %6;\n}"
                     ::"r"(sb + slot * SLOT + off), "l"(m), "r"(sb + BAR_FULL + 8 * slot), "r"(0), "r"(row), "r"(cb),
                     "l"(first ? L2_FIRST : L2_NORMAL) : "memory");
}
__device__ __forceinline__ uint32_t ring_next(uint32_t r) { return r == 4 ? 0 : r + 1; }
__device__ __forceinline__ uint32_t w_table(int hp) { return hp ? 0x3104u : 0x4210u; }
__device__ __forceinline__ uint32_t a_table(int hp) { return hp ? 0x625u : 0x635u; }
__device__ __forceinline__ uint32_t a_next(uint32_t& t) {
    const uint32_t s = t & 15;
    t = (t >> 4) | (s << 8);
    return s;
}
constexpr uint32_t O_TABLE = 0x1604235u;
__device__ __forceinline__ uint32_t o_next(uint32_t& t) {
    const uint32_t s = t & 15;
    t = (t >> 4) | (s << 24);
    return s;
}
__device__ __forceinline__ int o_head(int i, int kh) { return i < 16 ? 4 * (i & 7) + 2 * (kh ^ 1) + (i >> 3) : 29 + 2 * kh; }

template <bool INIT>
__device__ __forceinline__ void gemm_issue(float (&d)[64], uint32_t a, uint32_t b, int acc, bool img) {
    const uint32_t ha = img ? HI_IMG : HI_128, o2 = img ? 32 : 4, o4 = img ? 64 : 1024;
    wg_fence();
#pragma unroll
    for (int k = 0; k < 8; k++) {
        if (INIT && k == 0) wgmma_ss128_init<1>(d, a, b, ha);
        else wgmma_ss128<1>(d, a + (k >> 2) * o4 + ((k >> 1) & 1) * o2 + (k & 1) * 2, b + k * 128, k ? 1 : acc, ha);
    }
    wg_commit();
}

template <bool ODD>
__device__ __forceinline__ bool proj_tile(float (&acc)[64], float (&prev)[64], int t, int q0, uint32_t sb, int wg, uint32_t eb, bool rel, uint32_t& fph,
                                          uint32_t wtab, uint32_t& atab, uint8_t* prev_img, uint32_t toff, float s0, float s1,
                                          uint32_t (&v)[32]) {
    const uint32_t a0 = desc_k(sb + (wg ^ (ODD && t == 5)) * 8192), b0 = desc_mn(sb);
    constexpr int U = ODD ? UNR : 1;
#pragma unroll U
    for (int q = ODD ? 0 : q0; q < 4; q++) {
        const uint32_t ws = (wtab >> (4 * q)) & 15, as = a_next(atab);
        if (!ODD && t != 2) slot_wait(sb + BAR_FULL, fph, ws);
        slot_wait(sb + BAR_FULL, fph, as);
        if (ODD && q == 2 && t == 5) {
#pragma unroll
            for (int i = 0; i < 8; i++) sts128(sb + 5 * SLOT + q_off(toff) + (i >> 2) * 16384 + (i & 2) * 256 + (i & 1) * 1024, make_uint4(v[4 * i], v[4 * i + 1], v[4 * i + 2], v[4 * i + 3]));
        }
        bar_sync(1 + wg, 256);
        gemm_issue<false>(acc, a0 + as * (SLOT / 16), b0 + ws * (SLOT / 16), q, false);
        bar_arrive(2 - wg, 256);
        wg_wait<1>();
        reg_fence(prev);
        if (ODD && t == 5) {
            if (q == 0) {
#pragma unroll
                for (int i = 0; i < 32; i++) {
                    const int k = 16 * (i >> 3) + 4 * (i & 3) + ((i >> 1) & 2);
                    v[i] = pack2(prev[k], prev[k + 1]);
                }
            }
            if (q == 2) {
                fence_async_smem();
                slot_wait(sb + BAR_FULL, fph, wtab & 15);
                wg_wait<0>();
                release_if(eb, as, rel);
                release_if(eb, ws, rel);
                reg_fence(acc);
                return true;
            }
        } else {
            if (q == 0) img_store_global<0>(prev_img, toff, prev, s0, s1);
            if (q == 1) img_store_global<1>(prev_img, toff, prev, s0, s1);
            if (q == 2) img_store_global<2>(prev_img, toff, prev, s0, s1);
            if (q == 3) img_store_global<3>(prev_img, toff, prev, s0, s1);
        }
        wg_wait<0>();
        release_if(eb, as, rel && !(ODD && (q & 1) && t == 5));
        if (ODD) release_if(eb, ws, rel && t != 1);
    }
    reg_fence(acc);
    return false;
}

__device__ __forceinline__ void qk_issue(float (&s)[64], uint32_t q, uint32_t k) {
    wg_fence();
    wgmma_ss128_init<0>(s, q, k, HI_Q, HI_IMG);
#pragma unroll
    for (int i = 1; i < 8; i++) wgmma_ss128<0>(s, q + (i >> 2) * 1024 + (i & 2) * 16 + (i & 1) * 2, k + (i >> 1) * 32 + (i & 1) * 2, 1, HI_Q, HI_IMG);
    wg_commit();
}
__device__ __forceinline__ void qk_issue(float (&s)[32], uint32_t q, uint32_t k) {
    wg_fence();
    wgmma_ss64_init<0>(s, q, k, HI_Q, HI_IMG);
#pragma unroll
    for (int i = 1; i < 8; i++) wgmma_ss64<0>(s, q + (i >> 2) * 1024 + (i & 2) * 16 + (i & 1) * 2, k + (i >> 1) * 32 + (i & 1) * 2, 1, HI_Q, HI_IMG);
    wg_commit();
}
__device__ __forceinline__ void pv_issue(float (&o)[64], const uint32_t (&p)[32], uint32_t v, int acc, bool half) {
    if (half) {
        asm volatile("// half" ::: "memory");
        wg_fence();
#pragma unroll
        for (int i = 0; i < 4; i++) wgmma_rs128(o, p[4 * i], p[4 * i + 1], p[4 * i + 2], p[4 * i + 3], v + i * 256, i ? 1 : acc, HI_IMG);
        wg_commit();
        asm volatile("// half" ::: "memory");
    } else {
        wg_fence();
#pragma unroll
        for (int i = 0; i < 8; i++) wgmma_rs128(o, p[4 * i], p[4 * i + 1], p[4 * i + 2], p[4 * i + 3], v + i * 256, i ? 1 : acc, HI_IMG);
        wg_commit();
    }
}
__device__ __forceinline__ void tri_mask(float (&s)[64], float x) {
#pragma unroll
    for (int k = 0; k < 16; k++) {
        float b;
        asm("sub.sat.f32 %0, %1, %2;" : "=f"(b) : "f"((float)(8 * (k >> 1) + (k & 1))), "f"(x));
        const int i = 32 + 4 * (k >> 1) + (k & 1);
        asm("fma.rn.f32 %0, %1, 0fFF61B1E6, %0;" : "+f"(s[i]) : "f"(b));
        if (k < 14) asm("fma.rn.f32 %0, %1, 0fFF61B1E6, %0;" : "+f"(s[i + 6]) : "f"(b));
    }
}
__device__ __forceinline__ void tri_mask_copy(float (&s)[64], const float (&h)[32], float x) {
#pragma unroll
    for (int i = 0; i < 32; i++) {
        asm("{\n.reg .pred p;\nsetp.lt.f32 p, %2, %3;\nselp.f32 %0, 0fFF800000, %1, p;\n}"
            : "=f"(s[i]) : "f"(h[i]), "f"(x), "f"((float)(8 * (i >> 2) - 4 * (i & 2) + (i & 1))));
        s[32 + i] = __uint_as_float(0xff800000u);
    }
}
constexpr float SM_HI = 1152921504606846976.f, SM_LO = 1.f / 1152921504606846976.f;
__device__ __forceinline__ bool softmax_unsafe(float t0, float t1, bool first) {
    bool bad = __any_sync(0xffffffffu, fmaxf(t0, t1) > SM_HI);
    if (first) {
        uint32_t a = __ballot_sync(0xffffffffu, t0 >= SM_LO), b = __ballot_sync(0xffffffffu, t1 >= SM_LO);
        a |= a >> 1;
        b |= b >> 1;
        bad |= ((a | (a >> 2)) & (b | (b >> 2)) & 0x11111111u) != 0x11111111u;
    }
    return bad;
}
__device__ __forceinline__ void softmax_shift(float (&s)[64], float d0, float d1) {
#pragma unroll
    for (int i = 0; i < 64; i++) s[i] -= (i & 2) ? d1 : d0;
}
__device__ __forceinline__ void softmax_remax(float (&s)[64], float (&m)[2], bool first, float& a0, float& a1) {
    float m0 = fmaxf(s[0], s[1]), m1 = fmaxf(s[2], s[3]);
#pragma unroll
    for (int k = 1; k < 16; k++) {
        m0 = fmaxf(m0, fmaxf(s[4 * k], s[4 * k + 1]));
        m1 = fmaxf(m1, fmaxf(s[4 * k + 2], s[4 * k + 3]));
    }
    m0 = fmaxf(m0, __shfl_xor_sync(0xffffffffu, m0, 1));
    m1 = fmaxf(m1, __shfl_xor_sync(0xffffffffu, m1, 1));
    m0 = fmaxf(m0, __shfl_xor_sync(0xffffffffu, m0, 2));
    m1 = fmaxf(m1, __shfl_xor_sync(0xffffffffu, m1, 2));
    if (!first) {
        m0 = fmaxf(m0, 0.f);
        m1 = fmaxf(m1, 0.f);
    }
    a0 = first ? 1.f : ex2(-m0);
    a1 = first ? 1.f : ex2(-m1);
    m[0] += m0;
    m[1] += m1;
    softmax_shift(s, m0, m1);
}
template <int J0, int J1>
__device__ __forceinline__ void softmax_exp(const float (&s)[64], uint32_t (&p)[32], float (&t)[4]) {
#pragma unroll
    for (int k = J0; k < J1; k++) {
        const float e0 = ex2(s[4 * k]), e1 = ex2(s[4 * k + 1]), e2 = ex2(s[4 * k + 2]), e3 = ex2(s[4 * k + 3]);
        if (k == 0) { t[0] = e0; t[1] = e1; t[2] = e2; t[3] = e3; }
        else { t[0] += e0; t[1] += e1; t[2] += e2; t[3] += e3; }
        p[2 * k] = pack2(e0, e1);
        p[2 * k + 1] = pack2(e2, e3);
    }
}
__device__ __forceinline__ void fma8(float (&acc)[8], float a, uint4 w) {
    acc[0] = fmaf(a, bf_lo(w.x), acc[0]); acc[1] = fmaf(a, bf_hi(w.x), acc[1]);
    acc[2] = fmaf(a, bf_lo(w.y), acc[2]); acc[3] = fmaf(a, bf_hi(w.y), acc[3]);
    acc[4] = fmaf(a, bf_lo(w.z), acc[4]); acc[5] = fmaf(a, bf_hi(w.z), acc[5]);
    acc[6] = fmaf(a, bf_lo(w.w), acc[6]); acc[7] = fmaf(a, bf_hi(w.w), acc[7]);
}
__device__ __forceinline__ void mma16816(float (&d)[4], const uint32_t* a, uint32_t b0, uint32_t b1) {
    asm("mma.sync.aligned.m16n8k16.row.col.f32.bf16.bf16.f32 {%0, %1, %2, %3}, {%4, %5, %6, %7}, {%8, %9}, {%0, %1, %2, %3};"
        : "+f"(d[0]), "+f"(d[1]), "+f"(d[2]), "+f"(d[3]) : "r"(a[0]), "r"(a[1]), "r"(a[2]), "r"(a[3]), "r"(b0), "r"(b1));
}
__device__ __forceinline__ uint2 best_key(const uint32_t* keys, int lane, uint32_t ep, uint32_t cur, int enough) {
#pragma unroll 1
    for (;;) {
        const uint4 k = ld_poll(reinterpret_cast<const uint4*>(keys) + lane);
        const bool ok = (((k.x ^ ep) | (k.y ^ ep) | (k.z ^ ep) | (k.w ^ ep)) & 31) == 0;
        const uint32_t best = __reduce_max_sync(0xffffffffu, ok ? max(max(k.x, k.y), max(k.z, k.w)) : 0u);
        const int n = __popc(__ballot_sync(0xffffffffu, ok));
        if (n == 32 || (n >= enough && best != cur)) return make_uint2(best, n == 32);
        __nanosleep(KSLEEP);
    }
}

__global__ void __cluster_dims__(2, 1, 1) __launch_bounds__(384, 1)
fused_kernel(const __grid_constant__ CUtensorMap tm_ckv, const __grid_constant__ CUtensorMap tm_wq,
             const __grid_constant__ CUtensorMap tm_wuk, const __grid_constant__ CUtensorMap tm_wuv,
             const __grid_constant__ CUtensorMap tm_wo, const __grid_constant__ CUtensorMap tm_wg,
             const __grid_constant__ CUtensorMap tm_wu,
             const __grid_constant__ CUtensorMap tm_wm, const __grid_constant__ CUtensorMap tm_x, const Params P) {
    extern __shared__ __align__(1024) uint8_t smem[];
    const uint32_t sb = (uint32_t)__cvta_generic_to_shared(smem);
    const int tid = threadIdx.x, lane = tid & 31, warp = __shfl_sync(0xffffffffu, tid >> 5, 0), wg = warp >> 2;
    const uint32_t sm = blockIdx.x < 8 ? blockIdx.x + 124 : blockIdx.x - 8, smq = ((sm - 64) * 147) >> 11;
    const int rb = sm < 64 ? (sm & 14) * 8 + (sm >> 4) * 2 + (sm & 1)
                 : sm < 120 ? ((sm - 64 - smq * 14) & 14) * 8 + 24 + smq * 2 + (sm & 1) : sm < 124 ? sm + 8 : sm - 116;
    const int grp = rb >> 3, j = rb & 7, kh = (grp >> (OMAP - 1)) & 1;
    const int cq = (j & 1) + ((grp >> (OMAP - 1)) & 2), ort = (OMAP == 1 ? grp & 12 : (grp & 8) + (grp & 1) * 4) + (j >> 1);
    if (warp == 0) TS(0);

    if (lane == 0) {
        if (warp == 8) {
            asm volatile("prefetch.tensormap [%0];" ::"l"(rb >= NCTA ? &tm_wm : (j & 1) ? &tm_wuv : &tm_wuk) : "memory");
            asm volatile("prefetch.tensormap [%0];" ::"l"(&tm_ckv) : "memory");
            *reinterpret_cast<uint2*>(smem + SM_EP + 16) = make_uint2(0, 0);
        }
        const u64 cnt = (warp < 5 ? (rb < NCTA ? 0x844444441111111ull : 0x888888881111111ull) : warp < 10 ? 0x111111188888888ull : 0x118121ull) >> (12 * (warp % 5));
#pragma unroll
        for (int i = 0; i < 3; i++) mbar_init(sb + SM_BAR + 24 * warp + 8 * i, ((uint32_t)cnt >> (4 * i)) & 15);
        fence_async_smem();
        asm volatile("fence.mbarrier_init.release.cluster;" ::: "memory");
    }
    __syncthreads();
    asm volatile("barrier.cluster.arrive.relaxed.aligned;\nbarrier.cluster.wait.aligned;" ::: "memory");

    if (rb >= NCTA) {
        float* sc = reinterpret_cast<float*>(smem + 6 * SLOT);
        float* red = sc + 512;
        uint32_t ph = 0x7f, sl = 0;
        if (warp == 8) {
#pragma unroll 1
            for (int i = 0; i < 24; i++) {
                slot_acquire(sb, ph, sl);
                tma2d(sb + sl * SLOT, &tm_wm, (i >> 3) * 1024 + (rb - NCTA) * 256, (i & 7) * 64, sb + BAR_FULL + 8 * sl, HINT & 64);
                if (++sl == 6) sl = 0;
            }
#pragma unroll 1
            for (int i = 0; i <= NFFN / NSPARE; i++) {
                const int b = (rb - NCTA) * (NFFN / NSPARE) + i;
                if (i < NFFN / NSPARE) {
                    asm volatile("cp.async.bulk.wait_group.read 0;" ::: "memory");
                    uint32_t done = 0x7f;
                    slot_acquire(sb, done, i & 1);
#pragma unroll 1
                    for (int k = 0; k < 4; k++) tma2d(sb + (i & 1) * SLOT + k * 8192, k < 2 ? &tm_wg : &tm_wu, b * 16, (k & 1) * 256, sb + BAR_FULL + 8 * (i & 1), (HINT & 128) && (i & 3) == 3);
                }
                if (i) {
                    mbar_wait(sb + BAR_FULL + 8 * (~i & 1), ((i - 1) >> 1) & 1);
                    bulk_store(g_wf + (b - 1) * SLOT, sb + (~i & 1) * SLOT, SLOT, HINT & 256);
                    asm volatile("cp.async.bulk.commit_group;" ::: "memory");
                }
            }
            asm volatile("cp.async.bulk.wait_group 0;" ::: "memory");
            fence_async_global();
            TS(4);
        } else if (warp < 8) {
            const uint32_t c2 = __ldg(reinterpret_cast<const uint32_t*>(P.c) + tid), ep = __ldcg(&g_sync.epoch[0]) + 1;
            sc[2 * tid] = rbf(bf_lo(c2) * sigmoid(bf_lo(c2)));
            sc[2 * tid + 1] = rbf(bf_hi(c2) * sigmoid(bf_hi(c2)));
            ph = 0;
#pragma unroll 1
            for (int ps = 0; ps < 3; ps++) {
                bar_sync(1, 256);
                float acc[8] = {0.f, 0.f, 0.f, 0.f, 0.f, 0.f, 0.f, 0.f};
#pragma unroll 1
                for (int bt = 0; bt < 8; bt++) {
                    slot_wait(sb + BAR_FULL, ph, sl);
#pragma unroll 4
                    for (int i = 0; i < 8; i++)
                        fma8(acc, sc[bt * 64 + warp * 8 + i], *reinterpret_cast<const uint4*>(smem + sl * SLOT + (warp * 8 + i) * 512 + lane * 16));
                    __syncwarp();
                    mbar_arrive_if(sb + BAR_EMPTY + 8 * sl, lane == 0);
                    if (++sl == 6) sl = 0;
                }
                *reinterpret_cast<float4*>(red + warp * 256 + lane * 8) = make_float4(acc[0], acc[1], acc[2], acc[3]);
                *reinterpret_cast<float4*>(red + warp * 256 + lane * 8 + 4) = make_float4(acc[4], acc[5], acc[6], acc[7]);
                bar_sync(1, 256);
                float v = 0.f;
#pragma unroll
                for (int i = 0; i < 8; i++) v += red[i * 256 + tid];
                if (ps == 0) st_pub(g_mod1 + (rb - NCTA) * 256 + tid, (pack2(0.f, v) & 0xffff0000u) | (ep & 0xffffu), true);
                else g_mod[ps * 1024 + (rb - NCTA) * 256 + tid] = __float2bfloat16_rn(v);
                if (warp == 0) TS(1 + ps);
            }
        }
        __syncthreads();
        if (tid < 2) flag_add(&g_sync.cnt[7 * 8]);
        return;
    }

    if (wg == 2) {
        asm volatile("setmaxnreg.dec.sync.aligned.u32 40;");
        const CUtensorMap* tw = (j & 1) ? &tm_wuv : &tm_wuk;
        if (warp == 8) {
            const uint32_t rank = j & 1, half = rank * 16384;
            uint32_t eph = 0x7f, r = 0;
#pragma unroll 1
            for (int hp = 0; hp < 2; hp++) {
                uint32_t wtab = w_table(hp), atab = a_table(hp);
                const int hc = 4 * grp + 2 * hp;
#pragma unroll 1
                for (int u = 0; u < 16; u++) {
                    if (u < 4) {
                        const uint32_t ws = (wtab >> (4 * u)) & 15;
                        slot_acquire(sb, eph, ws);
                        load_tile(sb, ws, 0, tw, u * 128, hc, false, HINT & 1);
                        PT();
                    }
                    if (hp == 1 && (u & 7) == 4) mbar_wait(sb + BAR_FLAG + 24 + (u & 8), 0);
                    const uint32_t as = a_next(atab);
                    slot_acquire(sb, eph, as);
                    load_tile(sb, as, half, &tm_ckv, ((u & 12) + (j >> 1)) * 128, (u & 3) * 2 + rank, true, (HINT & 8) && hp);
                    PT();
                    if (hp == 1 && (u | 2) == 3 && lane == 0)
                        asm volatile("red.relaxed.gpu.global.add.u32 [%0], 1;" ::"l"(&g_sync.cnt[(grp * 8 + 3 + (u >> 1)) * 8]) : "memory");
                }
                const uint8_t* src = g_h + (15 - j) * 4 * SLOT;
#pragma unroll 1
                for (int u = 0; u < 8; u++) {
                    if (u == 0 || u == KVG) {
                        mbar_wait(sb + BAR_FLAG + (u ? 8 + 32 * hp : 0), 0);
                        fence_async_global();
                    }
                    if (u < 4) {
                        const uint32_t ws = (wtab >> (4 * u)) & 15;
                        slot_acquire(sb, eph, ws);
                        load_tile(sb, ws, 0, &tm_wq, u * 128, hc, false, HINT & 1);
                        PT();
                    }
                    const uint32_t as = a_next(atab);
                    slot_acquire(sb, eph, as);
                    load_bulk(sb, as, 0, src, SLOT, false, (HINT & 8) && hp);
                    PT();
                    src += u == 3 ? (8 * j - 63) * SLOT : SLOT;
                }
                const int step = hp ? -2 * SLOT : 2 * SLOT;
                src = g_KV + (size_t)(grp * 32 + 30 * hp) * SLOT + half - step;
#pragma unroll 1
                for (int n = 0; n <= 17; n++) {
                    if (n == 8) {
                        mbar_wait(sb + BAR_FLAG + 16 + 32 * hp, 0);
                        fence_async_global();
                    }
                    const uint8_t* v = src + SLOT;
                    src += n < 16 - j ? step : n == 16 - j ? (2 * j - 15) * step : -step;
                    if (n < 17) {
                        slot_acquire(sb, eph, r);
                        if (n != 15 - (j & 6)) load_bulk(sb, r, half, src, SLOT / 2, true, HINT & 4);
                        else load_bulk(sb, r, 0, src - half, SLOT, false, HINT & 4);
                        PT();
                        r = ring_next(r);
                    }
                    if (n) {
                        slot_acquire(sb, eph, r);
                        if (n != 16 - (j & 6)) load_bulk(sb, r, half, v, SLOT / 2, true, HINT & 4);
                        else load_bulk(sb, r, 0, v - half, SLOT, false, HINT & 4);
                        PT();
                        r = ring_next(r);
                    }
                    asm volatile("st.volatile.shared.u32 [%0], %1;" ::"r"(sb + SM_EP + 16), "r"(18 * hp + n + 1) : "memory");
                }
            }
            uint32_t otab = O_TABLE, ready = 0;
#pragma unroll 1
            for (int i = 0; i < 17; i++) {
                const bool dyn = i >= 8 && i < 15;
                const uint32_t want = dyn ? 15u << (4 * (i - 8)) : 1u << max(i + 14, 28);
                if (!(ready & want)) {
                    do {
                        asm volatile("ld.acquire.cta.shared.u32 %0, [%1];" : "=r"(ready) : "r"(sb + SM_EP + 20) : "memory");
                        ready = __shfl_sync(0xffffffffu, ready, 0);
                    } while (!(ready & want));
                    fence_async_global();
                }
                const int head = o_head(dyn ? (ready >> (4 * (i - 8))) & 15 : i, kh);
                const uint32_t as = o_next(otab), ws = o_next(otab), off = i < 15 ? half : kh * 16384;
                slot_acquire(sb, eph, as);
                load_bulk(sb, as, off, g_ctx + (size_t)(ort * 32 + head) * SLOT + off, SLOT / 2, i < 15, HINT & 16);
                if (i == 15) load_tile(sb, as, off ^ 16384, &tm_x, ort * 128 + kh * 64, cq * 2, false, false);
                if (i == 16) load_bulk(sb, as, off ^ 16384, P.wdown + min(rb, NFFN - 1) * 8192, SLOT / 2, false, false);
                PT();
                slot_acquire(sb, eph, ws);
                load_tile(sb, ws, 0, &tm_wo, head * 128, cq * 2, false, HINT & 2);
                PT();
                if (i == 0) o_next(otab);
            }
            if (rb < NFFN) {
                slot_acquire(sb, eph, 5);
                load_bulk(sb, 5, 0, g_wf + rb * SLOT, SLOT, false, false);
            }
        } else if (warp == 9) {
            l2_prefetch(P.ckv + rb * 2048, 4096);
            mbar_watch(sb + BAR_FULL, 0);
            l2_prefetch(P.ckv + 512 * 512 + rb * 2048, 4096);
            mbar_watch(sb + BAR_FULL + 8 * XPF, 0);
            l2_prefetch(P.x + rb * 8192, 16384);
            mbar_watch(sb + BAR_FULL + 8 * 4, 0);
            l2_prefetch(P.ckv + 1024 * 512 + rb * 4096, 8192);
            TS(40);
#pragma unroll 1
            for (int i = 0; i < 15; i++) {
                step_watch(sb + SM_EP + 16, i == 0 ? 0 : i < 5 ? PFA + i : 13 + PFB + i);
                if (i == 12) mbar_watch(sb + BAR_FLAG + 8 * 7, 0);
                const int rf = min(rb, NFFN - 1);
                const uint8_t* p = i == 3 ? reinterpret_cast<const uint8_t*>(P.ckv) + rb * 16384
                                 : i == 4 ? g_h + rb * 16384
                                 : i < 9 ? g_ctx + (size_t)(ort * 32 + o_head(cq + 2 * ((i - 5) & 2), kh)) * SLOT + (i & 1) * 16384
                                 : i < 11 ? reinterpret_cast<const uint8_t*>(P.wo) + (grp * 16 + (~i & 1) * 8 + j) * 16384
                                 : i == 11 ? reinterpret_cast<const uint8_t*>(P.x) + rb * 16384
                                 : i == 12 ? reinterpret_cast<const uint8_t*>(P.wdown) + rf * 16384 : g_wf + rf * SLOT + (i & 1) * 16384;
                if (i >= 3) l2_prefetch(p, 16384);
                else if ((i | j) & 1) tma3d_prefetch(i == 1 ? tw : &tm_wq, (j >> 1) * 128, grp * 4 + (i ? 2 : 0));
            }
            const uint32_t v = lds32(sb + SM_EP) - 1;
            sts128(sb + SM_RED + lane * 16, make_uint4(v, v, v, v));
            fence_async_smem();
            __syncwarp();
#pragma unroll 1
            for (int i = 0; i < OB / 32; i++) bulk_store(g_out + rb * OB + i * 32, sb + SM_RED, 512, false);
            asm volatile("cp.async.bulk.commit_group;\ncp.async.bulk.wait_group 0;" ::: "memory");
            fence_async_global();
            __syncwarp();
            mbar_arrive_if(sb + BAR_PF, lane == 0);
            if (lane == 0) mbar_watch(sb + BAR_END, 0);
        } else {
            const uint32_t ep = __ldcg(&g_sync.epoch[0]) + 1;
            asm volatile("st.shared.u32 [%0], %1;" ::"r"(sb + SM_EP), "r"(ep) : "memory");
            mbar_wait(sb + BAR_FULL + 8 * 4, 0);
            {
                uint4 v[4];
                for (;;) {
                    uint32_t bad = 0;
#pragma unroll
                    for (int k = 0; k < 4; k++) v[k] = ld_poll(reinterpret_cast<const uint4*>(g_mod1) + (warp & 1) * 128 + k * 32 + lane);
#pragma unroll
                    for (int k = 0; k < 4; k++) bad |= (v[k].x ^ ep) | (v[k].y ^ ep) | (v[k].z ^ ep) | (v[k].w ^ ep);
                    if (__all_sync(0xffffffffu, (bad & 0xffff) == 0)) break;
                    __nanosleep(100);
                }
                const uint32_t one = (warp & 1) ? ONE2 : 0x80008000u;
#pragma unroll
                for (int k = 0; k < 4; k++)
                    *reinterpret_cast<uint2*>(smem + SM_TAB + (warp & 1) * 1024 + k * 256 + lane * 8) =
                        make_uint2(badd(__byte_perm(v[k].x, v[k].y, 0x7632), one), badd(__byte_perm(v[k].z, v[k].w, 0x7632), one));
            }
            __syncwarp();
            mbar_arrive_if(sb + BAR_FLAG + 8 * 8, lane == 0);
            if (warp == 10) {
#pragma unroll 1
                for (int i = 0; i < 9; i++) {
                    mbar_sleep(sb + BAR_DONE + 8 * i);
                    if (lane == 0) flag_add(i && ((i - 1) & 2) ? &g_sync.ctxcnt[((i & 1) ? 15 - j : j) * 32 + 2 * grp + (i > 4)] : &g_sync.cnt[(grp * 8 + i) * 8]);
                    if (i == 0) TS(43);
                }
            } else {
                TS(42);
#pragma unroll 1
                for (int i = 0; i < 8; i++) {
                    mbar_sleep(sb + BAR_DONE + 8 * (i == 7 ? 6 : i == 4 ? 3 : i));
                    if (lane < 2) flag_wait(&g_sync.cnt[((i == 0 ? (lane ? j : 15 - j) : i == 7 ? 0 : grp) * 8 + i) * 8], 8 * ep);
                    __syncwarp();
                    mbar_arrive_if(sb + BAR_FLAG + 8 * i, lane == 0 && i < 7);
                    TS(48 + i);
                }
                const uint32_t *mp = reinterpret_cast<const uint32_t*>(g_mod) + lane, *wp = reinterpret_cast<const uint32_t*>(P.wr) + lane;
                float ra = 0.f, rs = 0.f;
#pragma unroll 1
                for (int k = 0; k < 256; k += 32) {
                    const uint32_t ga = __ldcg(mp + 512 + k), sh = __ldcg(mp + 768 + k), c1 = badd(__ldcg(mp + 1024 + k), ONE2);
                    const uint32_t gb = __ldcg(mp + 1280 + k), ww = __ldg(wp + k);
                    const uint32_t a = bmul(c1, ww);
                    ra += bf_lo(a) + bf_hi(a);
                    rs = fmaf(bf_lo(sh), bf_lo(ww), fmaf(bf_hi(sh), bf_hi(ww), rs));
                    if (k >> 6 == cq) {
                        sts128(sb + SM_TAB + ((k & 32) + lane) * 16, make_uint4(ga << 16, ga & 0xffff0000u, a, 0));
                        sts128(sb + SM_TAB + 1024 + ((k & 32) + lane) * 16, make_uint4(c1, sh, gb, 0));
                    }
                }
#pragma unroll 1
                for (int o = 16; o > 0; o >>= 1) {
                    ra += __shfl_xor_sync(0xffffffffu, ra, o);
                    rs += __shfl_xor_sync(0xffffffffu, rs, o);
                }
                *reinterpret_cast<float2*>(smem + SM_EP + 8) = make_float2(ra, rs);
                __syncwarp();
                mbar_arrive_if(sb + BAR_FLAG + 8 * 7, lane == 0);
                const uint32_t* f = &g_sync.ctxcnt[ort * 32 + o_head(min(lane, 16), kh)];
                uint32_t ready = -(j & 1), list = 0, sh = 0, qa;
                asm("mapa.shared::cluster.u32 %0, %1, %2;" : "=r"(qa) : "r"(sb + SM_EP + 20), "r"(lane & 1));
                while (ready != ~0u) {
                    uint32_t v;
                    asm volatile("ld.acquire.gpu.global.u32 %0, [%1];" : "=r"(v) : "l"(f) : "memory");
                    const uint32_t now = __ballot_sync(0xffffffffu, (int)(v - ep) >= 0);
#pragma unroll 1
                    for (uint32_t fresh = now & ~ready & 0x7f00; fresh; fresh &= fresh - 1, sh += 4) list |= (__ffs(fresh) - 1) << sh;
                    list |= (((now & 0xff) + 1) >> 8 << 28) | ((now & 0x18000) << 14);
                    if (now != ready && lane < 2) asm volatile("st.relaxed.cluster.shared::cluster.u32 [%0], %1;" ::"r"(qa), "r"(list) : "memory");
                    if ((now & 0xff) == 0xff) mbar_sleep(sb + BAR_DONE + 8 * 7);
                    ready = now;
                    __nanosleep(POLL_NS);
                }
                TS(45);
            }
        }
    } else {
        asm volatile("setmaxnreg.inc.sync.aligned.u32 232;");
        const bool elected = (tid & 127) == 0, rel = (tid & 95) == 0;
        uint32_t eb;
        asm("mapa.shared::cluster.u32 %0, %1, %2;" : "=r"(eb) : "r"(sb + BAR_EMPTY), "r"(warp & 1));
        const int g = lane >> 2, c4 = lane & 3;
        const uint32_t toff = warp * 4096 + g * 64 + ((c4 ^ (g >> 1)) << 4);
        uint32_t fph = 0x3f, r = 0;
        if (wg == 1) bar_arrive(1, 256);
        const uint32_t kd = desc_k(sb), wd = desc_mn(sb), vd = ((sb & 0x3ffff) >> 4) | (32u << 16);
        const int nL = 16 - j, hn = nL - 1 + wg;
        float s[64], o[64], li[2] = {0.f, 0.f};
        uint8_t* cimg = g_ctx;
        const float sc = (j & 1) ? 1.f : SM_C;
#pragma unroll 1
        for (int q = 0; q < 3; q++) {
            const uint32_t as = (0x635u >> (4 * q)) & 15;
            mbar_wait(sb + BAR_FULL + 8 * q, 0);
            mbar_wait(sb + BAR_FULL + 8 * as, 0);
            bar_sync(1 + wg, 256);
            gemm_issue<false>(s, kd + wg * 512 + as * (SLOT / 16), wd + q * (SLOT / 16), q, false);
            bar_arrive(2 - wg, 256);
            wg_wait<0>();
            release_if(eb, as, rel);
        }
        {
            const int xrow = rb * 16 + warp * 2;
            const uint4* xp = reinterpret_cast<const uint4*>(P.x) + xrow * 64;
            uint8_t* img = g_KV + (size_t)(grp * 32 + j) * SLOT;
            uint32_t x[16], x0[2];
            float st[4] = {0.f, 0.f, 0.f, 0.f};
            mbar_wait(sb + BAR_FULL + 8 * 4, 0);
#pragma unroll
            for (int q = 3; q < 8; q++) {
                const uint32_t ws = (0x4210u >> (4 * (q & 3))) & 15, as = (0x635u >> (4 * (q % 3))) & 15;
                mbar_wait(sb + BAR_FULL + 8 * as, (q / 3) & 1);
                bar_sync(1 + wg, 256);
                if (q == 3) gemm_issue<false>(s, kd + wg * 512 + as * (SLOT / 16), wd + ws * (SLOT / 16), 1, false);
                else if (q == 4) gemm_issue<true>(o, kd + wg * 512 + as * (SLOT / 16), wd + ws * (SLOT / 16), 0, false);
                else gemm_issue<false>(o, kd + wg * 512 + as * (SLOT / 16), wd + ws * (SLOT / 16), 1, false);
                bar_arrive(2 - wg, 256);
                sched_fence(fph, P.zero);
                if (q > 3) reg_fence(s);
                if (q == 3) {
#pragma unroll
                    for (int i = 0; i < 4; i++)
                        asm volatile("ld.global.nc.v4.u32 {%0, %1, %2, %3}, [%4];" : "=r"(x[4 * i]), "=r"(x[4 * i + 1]), "=r"(x[4 * i + 2]), "=r"(x[4 * i + 3])
                                     : "l"(xp + lane + 32 * i) : "memory");
#pragma unroll
                    for (int i = 0; i < 2; i++) asm volatile("ld.global.nc.u32 %0, [%1];" : "=r"(x0[i]) : "l"(xp + 64 * i) : "memory");
                }
                if (q == 4) {
                    img_store_global<0>(img, toff, s, sc, sc);
#pragma unroll
                    for (int k = 0; k < 16; k++) {
                        const float d0 = bf_lo(x[k]) - bf_lo(x0[k >> 3]), d1 = bf_hi(x[k]) - bf_lo(x0[k >> 3]);
                        st[k >> 3] += d0 + d1;
                        st[2 + (k >> 3)] = fmaf(d0, d0, fmaf(d1, d1, st[2 + (k >> 3)]));
                    }
#pragma unroll
                    for (int i = 0; i < 4 * NSH; i++) st[i & 3] += __shfl_xor_sync(0xffffffffu, st[i & 3], 1 << (i >> 2));
                    reg_fence(st);
                }
                if (q == 5) {
#pragma unroll
                    for (int i = 4 * NSH; i < 20; i++) st[i & 3] += __shfl_xor_sync(0xffffffffu, st[i & 3], 1 << (i >> 2));
                    img_store_global<1>(img, toff, s, sc, sc);
#pragma unroll
                    for (int i = 0; i < 2; i++) {
                        const float d = st[i] * (1.f / 512.f);
                        st[2 + i] = ln_rstd(fmaxf(fmaf(-d, d, st[2 + i] * (1.f / 512.f)), 0.f));
                        x0[i] = pack2(bf_lo(x0[i]) + d, bf_lo(x0[i]) + d);
                    }
                    reg_fence(st);
                    reg_fence(x0);
                }
                if (q > 5) {
                    if (q == 6) mbar_wait(sb + BAR_FLAG + 8 * 8, 0);
                    const uint4 a = lds128(sb + SM_TAB + 1024 + (q & 1) * 512 + lane * 16), c = lds128(sb + SM_TAB + (q & 1) * 512 + lane * 16);
                    uint8_t* hp = g_h + (grp * 8 + (q & 1) * 4 + (lane >> 3)) * 16384 + (xrow & 127) * 128;
#pragma unroll
                    for (int i = 0; i < 2; i++) {
                        const uint32_t* y = x + 8 * i + 4 * (q & 1);
                        *reinterpret_cast<uint4*>(hp + i * 128 + (((lane ^ xrow ^ i) & 7) << 4)) =
                            make_uint4(ln_apply(y[0], x0[i], st[2 + i], a.x, c.x), ln_apply(y[1], x0[i], st[2 + i], a.y, c.y),
                                       ln_apply(y[2], x0[i], st[2 + i], a.z, c.z), ln_apply(y[3], x0[i], st[2 + i], a.w, c.w));
                    }
                    if (q == 7) {
                        __syncwarp();
                        mbar_arrive_if(sb + BAR_DONE, lane == 0);
                    }
                    if (q == 6) img_store_global<2>(img, toff, s, sc, sc);
                    else img_store_global<3>(img, toff, s, sc, sc);
                }
                sched_fence(fph, P.zero);
                wg_wait<0>();
                release_if(eb, as, rel);
            }
            reg_fence(o);
        }
        uint32_t p[32] = {};
#pragma unroll 1
        for (int hp = 0; hp < 2; hp++) {
            float m[2] = {0.f, 0.f}, l[2] = {0.f, 0.f}, t[4] = {0.f, 0.f, 0.f, 0.f};
            bool shifted = false, bad = false, plain = false;
            uint32_t qa = desc_k(sb + 5 * SLOT + (wg ^ 1) * 8192);
            uint8_t* limg = g_ctx + (size_t)((15 - j) * 32 + 2 * grp + hp) * SLOT;
            {
                const int step = hp ? -8 * SLOT : 8 * SLOT;
                uint8_t* img = g_KV + (size_t)(grp * 32 + (hp ? j ^ 30 : j) + 8) * SLOT;
                const uint32_t wtab = w_table(hp);
                uint32_t atab = hp ? 0x562u : 0x356u;
#pragma unroll 1
                for (int u = 2 - 2 * hp;; u += 2) {
                    proj_tile<false>(s, o, u, !u, sb, wg, eb, rel, fph, wtab, atab, u ? img : cimg, toff, u ? sc : li[0], u ? sc : li[1], p);
                    __syncwarp();
                    mbar_arrive_if(sb + BAR_DONE + 4 * u + 32 * hp, lane == 0);
                    if (elected) TS(1 + 10 * hp + u + 20 * wg);
                    if (proj_tile<true>(o, s, u + 1, 0, sb, wg, eb, rel, fph, wtab, atab, img + step, toff, sc, sc, p)) break;
                    if (elected) TS(2 + 10 * hp + u + 20 * wg);
                    img += 2 * step;
                }
            }
            if (elected) TS(6 + 10 * hp + 20 * wg);
            int n = -1;
#pragma unroll 1
            for (;;) {
                while (bad || plain) {
                    if (bad) {
                        float a0, a1;
                        softmax_remax(s, m, n == 0 || n == nL, a0, a1);
                        shifted = true;
                        l[0] *= a0;
                        l[1] *= a1;
#pragma unroll
                        for (int i = 0; i < 64; i++) o[i] *= (i & 2) ? a1 : a0;
                    }
                    softmax_exp<0, 16>(s, p, t);
                    t[0] += t[1];
                    t[2] += t[3];
                    bad = !bad && softmax_unsafe(t[0], t[2], false);
                    plain = false;
                }
#pragma unroll 1
                do {
                    l[0] += t[0];
                    l[1] += t[2];
                    if (++n > 16) break;
                    const uint32_t ks = r;
                    uint32_t vs = ring_next(r);
                    r = ring_next(vs);
                    bar_sync(1 + wg, 256);
                    const float x = (float)((warp & 3) * 16 + g - 2 * c4);
                    if (n == hn) {
                        float sh[32];
                        qk_issue(sh, qa, kd + ks * (SLOT / 16));
                        slot_wait(sb + BAR_FULL, fph, vs);
                        pv_issue(o, p, vd + vs * (SLOT / 16), 1, false);
                        bar_arrive(2 - wg, 256);
                        wg_wait<1>();
                        reg_fence(sh);
                        tri_mask_copy(s, sh, x);
                        release_if(eb, ks, rel);
                        release_if(eb, 5 + wg, rel && (!wg || n == 16));
                        if (!wg) {
                            qa += SLOT / 16;
                            fence_async_smem();
                            if (shifted) softmax_shift(s, m[0], m[1]);
                        }
                        float e[4 * EARLY];
#pragma unroll
                        for (int i = 0; i < 4 * EARLY; i++) {
                            e[i] = ex2(s[i]);
                            t[i & 3] = i < 4 ? e[i] : t[i & 3] + e[i];
                        }
                        reg_fence(e);
                        slot_wait(sb + BAR_FULL, fph, r);
                        wg_wait<0>();
                        reg_fence(o);
                        reg_fence(e);
                        release_if(eb, vs, rel);
#pragma unroll
                        for (int i = 0; i < 2 * EARLY; i++) p[i] = pack2(e[2 * i], e[2 * i + 1]);
                        softmax_exp<EARLY, 8>(s, p, t);
                        if (wg) {
                            ctx_store<true>(limg, toff, o, l[0], l[1]);
                            __syncwarp();
                            mbar_arrive_if(sb + BAR_DONE + 24 + 32 * hp, lane == 0);
                            l[0] = l[1] = m[0] = m[1] = 0.f;
                            shifted = false;
                        }
                        t[0] += t[1];
                        t[2] += t[3];
                        bad = softmax_unsafe(t[0], t[2], wg);
                        continue;
                    }
                    if (n == 0 || n == nL) {
                        qk_issue(s, qa, kd + ks * (SLOT / 16));
                        if (n == 0) {
                            r = vs;
                            vs = 4 - hp;
                            slot_wait(sb + BAR_FULL, fph, 6);
                            gemm_issue<false>(o, qa + SLOT / 16, wd + vs * (SLOT / 16), 1, false);
                        } else {
                            slot_wait(sb + BAR_FULL, fph, vs);
                            pv_issue(o, p, vd + vs * (SLOT / 16), 1, true);
                        }
                        bar_arrive(2 - wg, 256);
                        const float i0 = n ? rcp(quad_sum(l[0])) : 1.f, i1 = n ? rcp(quad_sum(l[1])) : 1.f;
                        wg_wait<1>();
                        reg_fence(s);
                        release_if(eb, ks, rel);
                        release_if(eb, 6, rel && n == 16);
                        tri_mask(s, n ? x : 64.f);
                        float e[4 * EARLY];
#pragma unroll
                        for (int i = 0; i < 4 * EARLY; i++) {
                            e[i] = ex2(s[i]);
                            t[i & 3] = i < 4 ? e[i] : t[i & 3] + e[i];
                        }
                        reg_fence(e);
                        reg_fence(s);
                        reg_fence(t);
                        slot_wait(sb + BAR_FULL, fph, r);
                        if (SF & 1) sched_fence(fph, P.zero);
                        wg_wait<0>();
                        reg_fence(o);
                        reg_fence(e);
                        release_if(eb, vs, rel);
#pragma unroll
                        for (int i = 0; i < 2 * EARLY; i++) p[i] = pack2(e[2 * i], e[2 * i + 1]);
                        softmax_exp<EARLY, MSPLIT>(s, p, t);
                        tile_store(limg, sb + 6 * SLOT, toff, o, i0, i1, n);
                        reg_fence(t);
                        if (SF & 2) sched_fence(fph, P.zero);
                        reg_fence(s);
                        softmax_exp<MSPLIT, 16>(s, p, t);
                        __syncwarp();
                        mbar_arrive_if(sb + BAR_DONE + 24 + 32 * hp, lane == 0 && n);
                        l[0] = l[1] = m[0] = m[1] = 0.f;
                        shifted = false;
                        t[0] += t[1];
                        t[2] += t[3];
                        bad = __any_sync(0xffffffffu, fmaxf(t[0], t[2]) > SM_HI || fminf(t[0], t[2]) < SM_LO);
                        continue;
                    }
                    qk_issue(s, qa, kd + ks * (SLOT / 16));
                    slot_wait(sb + BAR_FULL, fph, vs);
                    pv_issue(o, p, vd + vs * (SLOT / 16), n != 1 && n != nL + 1, n == hn + 1);
                    bar_arrive(2 - wg, 256);
                    wg_wait<1>();
                    reg_fence(s);
                    release_if(eb, ks, rel);
                    release_if(eb, 6, rel && n == 16);
                    if (n == nL - 1) {
                        tri_mask(s, x);
                        release_if(eb, 5, rel);
                        qa += SLOT / 16;
                        fence_async_smem();
                    }
                    if (shifted) {
                        slot_wait(sb + BAR_FULL, fph, r);
                        wg_wait<0>();
                        reg_fence(o);
                        release_if(eb, vs, rel);
                        softmax_shift(s, m[0], m[1]);
                        plain = true;
                        break;
                    }
                    float e[4 * EARLY];
#pragma unroll
                    for (int i = 0; i < 4 * EARLY; i++) {
                        e[i] = ex2(s[i]);
                        t[i & 3] = i < 4 ? e[i] : t[i & 3] + e[i];
                    }
                    reg_fence(e);
                    slot_wait(sb + BAR_FULL, fph, r);
                    wg_wait<0>();
                    reg_fence(o);
                    reg_fence(e);
                    release_if(eb, vs, rel);
#pragma unroll
                    for (int i = 0; i < 2 * EARLY; i++) p[i] = pack2(e[2 * i], e[2 * i + 1]);
                    softmax_exp<EARLY, 16>(s, p, t);
                    t[0] += t[1];
                    t[2] += t[3];
                    bad = softmax_unsafe(t[0], t[2], false);
                } while (!bad);
                if (!bad && !plain) break;
            }
            const uint32_t vs = r, ga = desc_k(sb + (hp ? 2 * (wg ^ kh ^ 1) : wg) * 8192);
            r = ring_next(r);
            slot_wait(sb + BAR_FULL, fph, 5);
            slot_wait(sb + BAR_FULL, fph, r);
            bar_sync(1 + wg, 256);
            gemm_issue<true>(s, ga + 5 * (SLOT / 16), wd + r * (SLOT / 16), 0, hp);
            pv_issue(o, p, vd + vs * (SLOT / 16), j, hn == 16);
            bar_arrive(2 - wg, 256);
            li[0] = rcp(quad_sum(l[0]));
            li[1] = rcp(quad_sum(l[1]));
            cimg = limg + (ptrdiff_t)(2 * j - 15) * 32 * SLOT + (wg ? -16384 : 16384);
            wg_wait<1>();
            release_if(eb, 5, rel);
            release_if(eb, r, rel && hp);
            wg_wait<0>();
            release_if(eb, vs, rel);
            reg_fence(o);
            img_store_global<0>(cimg, toff, o, li[0], li[1]);
            if (elected) TS(8 + 10 * hp + 20 * wg);
        }
        uint32_t otab = 0x2351604u;
        const uint32_t oa = desc_k(sb + (wg ^ kh ^ 1) * 16384);
        const int t7 = tid & 127, w4 = warp & 3, row = ort * 128 + kh * 64 + w4 * 16 + g;
#pragma unroll 1
        for (int i = 1; i < 15 - wg; i++) {
            const uint32_t as = o_next(otab), ws = o_next(otab);
            slot_wait(sb + BAR_FULL, fph, as);
            slot_wait(sb + BAR_FULL, fph, ws);
            bar_sync(1 + wg, 256);
            gemm_issue<false>(s, oa + as * (SLOT / 16), wd + ws * (SLOT / 16), 1, true);
            bar_arrive(2 - wg, 256);
            wg_wait<1>();
            reg_fence(o);
            if (i == 1) img_store_global<1>(cimg, toff, o, li[0], li[1]);
            if (i == 2) {
                img_store_global<2>(cimg, toff, o, li[0], li[1]);
                img_store_global<3>(cimg, toff, o, li[0], li[1]);
                __syncwarp();
                mbar_arrive_if(sb + BAR_DONE + 64, lane == 0);
            }
            wg_wait<0>();
            release_if(eb, as, rel);
            release_if(eb, ws, rel);
        }
        mbar_wait(sb + BAR_PF, 0);
        const uint32_t ep = lds32(sb + SM_EP);
        uint32_t eb2 = sb + BAR_END;
        if (wg == 0) {
            reg_fence(s);
            if (elected) TS(9);
            TT(1);
#pragma unroll
            for (int v = 0; v < 8; v++)
                st_pub(g_out + rb * OB + v * 128 + t7, make_uint4((pack2(s[8 * v], s[8 * v + 1]) & ~1u) | (ep & 1), pack2(s[8 * v + 2], s[8 * v + 3]),
                                                                      pack2(s[8 * v + 4], s[8 * v + 5]), pack2(s[8 * v + 6], s[8 * v + 7])), true);
            constexpr uint32_t s1 = 5, s2 = 6;
            if (ELATE >= 0) bar_sync(4, 256);
            uint32_t wf[64];
            float wn[64];
            if (rb < NFFN) {
                slot_wait(sb + BAR_FULL, fph, s1);
                const uint32_t a = sb + s1 * SLOT + (w4 * 128 + (lane >> 4) * 8 + (lane & 7)) * 32 + (((lane >> 3) ^ (lane >> 2)) & 1) * 16;
#pragma unroll
                for (int i = 0; i < 16; i++)
                    asm volatile("ldmatrix.sync.aligned.m8n8.x4.trans.shared.b16 {%0, %1, %2, %3}, [%4];"
                                 : "=r"(wf[4 * i]), "=r"(wf[4 * i + 1]), "=r"(wf[4 * i + 2]), "=r"(wf[4 * i + 3])
                                 : "r"(a + (i >> 3) * 16384 + (i & 7) * 512) : "memory");
                slot_wait(sb + BAR_FULL, fph, s2);
#pragma unroll
                for (int i = 0; i < 16; i++) {
                    const uint2 w = *reinterpret_cast<const uint2*>(smem + s2 * SLOT + (kh ^ 1) * 16384 + i * 1024 + t7 * 8);
                    wn[4 * i] = bf_lo(w.x); wn[4 * i + 1] = bf_hi(w.x); wn[4 * i + 2] = bf_lo(w.y); wn[4 * i + 3] = bf_hi(w.y);
                }
                reg_fence(wn);
            }
            const uint32_t gbf = __ldcg(reinterpret_cast<const uint32_t*>(g_mod) + 1280 + rb * 2 + (tid & 1));
            if (elected) TS(10);
            TT(2);
            float* sred = reinterpret_cast<float*>(smem + SM_RED);
            uint32_t best = ep ^ 1, all;
            bool fresh;
            do {
                if (warp == 0) {
                    const uint2 k = best_key(g_key + cq * 128, lane, ep, best, rb < NFFN ? SPEC : 32);
                    *reinterpret_cast<uint2*>(smem + SM_EP + 24) = k;
                    mbar_arrive_if(sb + BAR_BEST, lane == 0 && k.y);
                }
                bar_sync(3, 128);
                const uint2 k = *reinterpret_cast<const uint2*>(smem + SM_EP + 24);
                fresh = k.x != best;
                best = k.x;
                all = k.y;
                TT(3);
                if (!fresh || rb >= NFFN) break;
                const uint4* cp = g_cand + ((~best >> 9) & 127) * 192;
                uint4 cv[6];
                for (;;) {
                    uint32_t bad = 0;
#pragma unroll
                    for (int v = 0; v < 6; v++) cv[v] = ld_poll(cp + w4 * 24 + v * 4 + c4);
#pragma unroll
                    for (int v = 0; v < 6; v++) bad |= cv[v].w ^ ep;
                    if (__all_sync(0xffffffffu, bad == 0)) break;
                    if (CSLEEP) __nanosleep(CSLEEP);
                }
            TT(4);
                float d[4][4] = {};
#pragma unroll
                for (int k = 0; k < 8; k++) {
                    const uint32_t b0 = (&cv[(2 * k) / 3].x)[(2 * k) % 3], b1 = (&cv[(2 * k + 1) / 3].x)[(2 * k + 1) % 3];
                    mma16816(d[k & 1], wf + 4 * k, b0, b1);
                    mma16816(d[2 + (k & 1)], wf + 32 + 4 * k, b0, b1);
                }
                const float u = (c4 & 2) ? ((c4 & 1) ? d[2][2] + d[3][2] : d[2][0] + d[3][0]) : ((c4 & 1) ? d[0][2] + d[1][2] : d[0][0] + d[1][0]);
                sred[w4 * 32 + c4 * 8 + g] = u;
                bar_sync(3, 128);
                const float v = rbf((sred[lane] + sred[32 + lane]) + (sred[64 + lane] + sred[96 + lane]));
                const float act = rbf(rbf(v * sigmoid(v)) * __shfl_down_sync(0xffffffffu, v, 16));
                float y[4] = {0.f, 0.f, 0.f, 0.f};
#pragma unroll
                for (int k = 0; k < 16; k++) {
                    const float a = __shfl_sync(0xffffffffu, act, k);
#pragma unroll
                    for (int i = 0; i < 4; i++) y[i] = fmaf(a, wn[4 * k + i], y[i]);
                }
                st_pub(g_out + rb * OB + OB_Y + t7, make_uint4((__float_as_uint(y[0]) & ~15u) | (ep & 15), (__float_as_uint(y[1]) & ~127u) | ((best >> 9) & 127),
                                                               __float_as_uint(y[2]), __float_as_uint(y[3])), true);
            } while (!all);
            const int sel = (~best >> 5) & 2047;
            const int pq = (2 * rb + (tid & 1)) & 63, pv = (pq >> 2) / 3;
            const uint4* fp = g_cand + (sel >> 4) * 192 + (rb >> 5) * 24 + pv * 4 + (pq & 3);
            uint4 fh = {}, fx = {};
            if (rb == 0 && tid == 0) g_sync.epoch[0] = ep;
            if (elected) TS(60);
            TT(5);
            uint4 yv;
            if (warp == 0) { fh = ld_poll(fp); fx = ld_poll(fp + 96); }
            if (fresh && rb < NFFN) __nanosleep(YPRE);
            for (;;) {
                yv = ld_poll(g_out + min(t7, NFFN - 1) * OB + OB_Y + rb);
                if (__all_sync(0xffffffffu, (((yv.x ^ ep) & 15) | ((yv.y ^ (best >> 9)) & 127)) == 0)) break;
                if (YSLEEP) __nanosleep(YSLEEP);
            }
            if (elected) TS(61);
            TT(6);
            float y[4] = {0.f, 0.f, 0.f, 0.f};
            if (t7 < NFFN) { y[0] = __uint_as_float(yv.x); y[1] = __uint_as_float(yv.y); y[2] = __uint_as_float(yv.z); y[3] = __uint_as_float(yv.w); }
            const float z0 = ((lane & 16) ? y[2] : y[0]) + __shfl_xor_sync(0xffffffffu, (lane & 16) ? y[0] : y[2], 16);
            const float z1 = ((lane & 16) ? y[3] : y[1]) + __shfl_xor_sync(0xffffffffu, (lane & 16) ? y[1] : y[3], 16);
            float z = ((lane & 8) ? z1 : z0) + __shfl_xor_sync(0xffffffffu, (lane & 8) ? z0 : z1, 8);
            z += __shfl_xor_sync(0xffffffffu, z, 4);
            z = quad_sum(z);
            if ((lane & 7) == 0) sred[128 + (lane >> 3) * 4 + w4] = z;
            bar_sync(3, 128);
            if (tid < 2) {
                while (fh.w != ep || fx.w != ep) { fh = ld_poll(fp); fx = ld_poll(fp + 96); }
                const float4 y0 = *reinterpret_cast<const float4*>(sred + 128 + tid * 8), y1 = *reinterpret_cast<const float4*>(sred + 132 + tid * 8);
                const int cm = (pq >> 2) - 3 * pv;
                const uint32_t h2 = cm == 0 ? fh.x : cm == 1 ? fh.y : fh.z, x2 = cm == 0 ? fx.x : cm == 1 ? fx.y : fx.z;
                const float sg = sigmoid(bf_hi((best & 0x80000000u) ? (best ^ 0x80000000u) : ~best));
                reinterpret_cast<uint32_t*>(P.out)[sel * 256 + rb * 2 + tid] =
                    badd(x2, bmul(gbf, badd(h2, bmul(pack2((y0.x + y0.y) + (y0.z + y0.w), (y1.x + y1.y) + (y1.z + y1.w)), pack2(sg, sg)))));
            }
            if (elected) TS(62);
            TT(7);
        } else {
            const float4* tf = reinterpret_cast<const float4*>(smem + SM_TAB) + c4;
            const uint32_t xa = sb + 4 * SLOT + (kh ^ 1) * 16384 + (w4 * 16 + (lane & 15)) * 128;
            uint32_t x2[32];
            bar_sync(2, 256);
#pragma unroll 1
            for (int i = 14; i < 17; i++) {
                const uint32_t as = o_next(otab), ws = o_next(otab);
                slot_wait(sb + BAR_FULL, fph, as);
                slot_wait(sb + BAR_FULL, fph, ws);
                gemm_issue<false>(s, oa + as * (SLOT / 16), wd + ws * (SLOT / 16), 1, true);
                wg_wait<1>();
            }
            const uint4* pr = g_out + (rb ^ (8 * OMAP)) * OB + t7;
            uint4 pa[8];
            if (PEARLY) {
#pragma unroll
                for (int v = 0; v < 8; v++) pa[v] = ld_poll(pr + v * 128);
            }
            if (elected) TS(29);
            TT(1);
            {
#pragma unroll
                for (int k = 0; k < 8; k++)
                    asm volatile("ldmatrix.sync.aligned.m8n8.x4.shared.b16 {%0, %1, %2, %3}, [%4];"
                                 : "=r"(x2[4 * k]), "=r"(x2[4 * k + 1]), "=r"(x2[4 * k + 2]), "=r"(x2[4 * k + 3])
                                 : "r"(xa + (k >> 2) * 8192 + (((2 * (k & 3) + (lane >> 4)) ^ (lane & 7)) << 4)) : "memory");
            }
            wg_wait<0>();
            reg_fence(s);
            if (!ELATE) bar_arrive(4, 256);
            if (elected) TS(39);
            TT(2);
            if (!PEARLY) {
#pragma unroll
                for (int v = 0; v < 8; v++) pa[v] = ld_poll(pr + v * 128);
            }
            float4 tc[16];
#pragma unroll
            for (int k = 0; k < 16; k++) {
                tc[k] = tf[k * 4];
                if (!(g & 1)) tc[k].z = __uint_as_float(ONE2);
#pragma unroll
                for (int i = 4 * k; i < 4 * k + 4; i++) s[i] = fmaf((i & 1) ? tc[k].y : tc[k].x, s[i], (i & 1) ? bf_hi(x2[i >> 1]) : bf_lo(x2[i >> 1]));
            }
            reg_fence(s);
            for (;;) {
                uint32_t bad = 0;
#pragma unroll
                for (int v = 0; v < 8; v++) bad |= pa[v].x ^ ep;
                if (__all_sync(0xffffffffu, (bad & 1) == 0)) break;
                if (PSLEEP) __nanosleep(PSLEEP);
#pragma unroll
                for (int v = 0; v < 8; v++) pa[v] = ld_poll(pr + v * 128);
            }
            if (ELATE == 1) bar_arrive(4, 256);
            if (elected) TS(30);
            TT(3);
            float sd[4] = {}, q0[4] = {}, q1[4] = {};
#pragma unroll
            for (int k = 0; k < 8; k++) {
#pragma unroll
                for (int i = 4 * k; i < 4 * k + 4; i++) {
                    const uint32_t w = (&pa[k].x)[i & 3];
                    x2[i] = pack2(fmaf(tc[i >> 1].x, bf_lo(w), s[2 * i]), fmaf(tc[i >> 1].y, bf_hi(w), s[2 * i + 1]));
                }
                mma16816(sd, x2 + 4 * k, __float_as_uint(tc[2 * k].z), __float_as_uint(tc[2 * k + 1].z));
                mma16816(q0, x2 + 4 * k, x2[4 * k], x2[4 * k + 2]);
                mma16816(q1, x2 + 4 * k, x2[4 * k + 1], x2[4 * k + 3]);
            }
            uint4* sp = g_out + rb * OB + OB_STAT + (w4 * 8 + g) * 2;
            st_pub(sp, make_uint4(__float_as_uint(sd[0]), __float_as_uint((g & 1) ? q0[1] : q0[0]), __float_as_uint(sd[1]), ep), c4 == g >> 1);
            st_pub(sp + 1, make_uint4(__float_as_uint(sd[2]), __float_as_uint((g & 1) ? q1[3] : q1[2]), __float_as_uint(sd[3]), ep), c4 == g >> 1);
            if (ELATE == 2) bar_arrive(4, 256);
            if (TF & 1) sched_fence(eb2, P.zero);
            if (elected) TS(56);
            TT(4);
            uint32_t cb[16], sh[16], gb[16];
#pragma unroll
            for (int i = 0; i < 16; i++) {
                const float4 c = tf[64 + i * 4];
                cb[i] = __float_as_uint(c.x); sh[i] = __float_as_uint(c.y); gb[i] = __float_as_uint(c.z);
            }
            const float ra = __uint_as_float(lds32(sb + SM_EP + 8)), rb0 = __uint_as_float(lds32(sb + SM_EP + 12));
            uint4 r0, r1;
            if (SPRE) __nanosleep(SPRE);
            for (;;) {
                r0 = ld_poll(g_out + ((rb & ~(16 * OMAP + 1)) + (c4 & 1) + (c4 & 2) * 8 * OMAP) * OB + OB_STAT + (w4 * 8 + g) * 2);
                r1 = ld_poll(g_out + ((rb & ~(16 * OMAP + 1)) + (c4 & 1) + (c4 & 2) * 8 * OMAP) * OB + OB_STAT + (w4 * 8 + g) * 2 + 1);
                if (__all_sync(0xffffffffu, r0.w == ep && r1.w == ep)) break;
                if (SSLEEP) __nanosleep(SSLEEP);
            }
            if (elected) TS(57);
            TT(5);
            const float m0 = quad_sum(__uint_as_float(r0.x)) * (1.f / 512.f), m1 = quad_sum(__uint_as_float(r1.x)) * (1.f / 512.f);
            const float rs0 = ln_rstd(fmaxf(fmaf(-m0, m0, quad_sum(__uint_as_float(r0.y)) * (1.f / 512.f)), 0.f));
            const float rs1 = ln_rstd(fmaxf(fmaf(-m1, m1, quad_sum(__uint_as_float(r1.y)) * (1.f / 512.f)), 0.f));
            const uint32_t mb0 = pack2(m0, m0), mb1 = pack2(m1, m1);
            const uint32_t lg = pack2(fmaf(rs0, fmaf(-bf_lo(mb0), ra, quad_sum(__uint_as_float(r0.z))), rb0),
                                      fmaf(rs1, fmaf(-bf_lo(mb1), ra, quad_sum(__uint_as_float(r1.z))), rb0));
            const uint32_t u0 = lg << 16, u1 = lg & 0xffff0000u;
            const uint32_t k0 = ((u0 ^ (((int)u0 >> 31) | 0x80000000u)) & 0xffff0000u) | ((2047 - row) << 5) | (ep & 31);
            const uint32_t k1 = ((u1 ^ (((int)u1 >> 31) | 0x80000000u)) & 0xffff0000u) | ((2039 - row) << 5) | (ep & 31);
            const uint32_t kb = __reduce_max_sync(0xffffffffu, max(k0, k1));
            st_pub(g_key + cq * 128 + (row >> 4), kb, lane == 0);
            const bool cand = kb == k0 || kb == k1;
            uint4* cp = g_cand + (row >> 4) * 192 + cq * 24 + c4;
#pragma unroll 1
            for (int it = 0; it < 3; it++) {
                bool put = it == 1 || !cand;
                if (it == 2) {
                    mbar_wait(sb + BAR_BEST, 0);
                    put = cand && lds32(sb + SM_EP + 24) != kb;
                }
                const bool hi = (kb == k1) != (it == 1);
                uint32_t cx[18], ch[18];
#pragma unroll
                for (int i = 0; i < 16; i++) {
                    cx[i] = hi ? x2[2 * i + 1] : x2[2 * i];
                    ch[i] = ln_apply(cx[i], hi ? mb1 : mb0, hi ? rs1 : rs0, cb[i], sh[i]);
                }
                cx[16] = cx[17] = ch[16] = ch[17] = 0;
#pragma unroll
                for (int v = 0; v < 6; v++) st_pub(cp + v * 4, make_uint4(ch[3 * v], ch[3 * v + 1], ch[3 * v + 2], ep), cand && it == 0);
                if (TF & 4) sched_fence(eb2, P.zero);
#pragma unroll
                for (int v = 0; v < 6; v++) st_pub(cp + 96 + v * 4, make_uint4(cx[3 * v], cx[3 * v + 1], cx[3 * v + 2], ep), cand && it == 0);
                if (it == 0) TT(6);
                uint2* op = reinterpret_cast<uint2*>(P.out) + (row + 8 * hi) * 128 + cq * 32 + (c4 & 1) * 2 + (c4 >> 1);
#pragma unroll
                for (int i = 0; i < 16; i += 2) {
                    const uint32_t v0 = badd(cx[i], bmul(gb[i], ch[i])), v1 = badd(cx[i + 1], bmul(gb[i + 1], ch[i + 1]));
                    const uint32_t rv = __shfl_xor_sync(0xffffffffu, (c4 & 1) ? v0 : v1, 1);
                    if (put) op[i * 2] = (c4 & 1) ? make_uint2(rv, v1) : make_uint2(v0, rv);
                }
            }
            if (elected) TS(59);
            TT(7);
        }
        mbar_arrive_if(eb2, lane == 0);
    }
}

typedef CUresult (*EncodeFn)(CUtensorMap*, CUtensorMapDataType, cuuint32_t, void*, const cuuint64_t*, const cuuint64_t*,
                             const cuuint32_t*, const cuuint32_t*, CUtensorMapInterleave, CUtensorMapSwizzle,
                             CUtensorMapL2promotion, CUtensorMapFloatOOBfill);

void make_2d(EncodeFn fn, CUtensorMap* m, const void* p, uint64_t cols, uint64_t rows, uint32_t bc, uint32_t br, CUtensorMapSwizzle sw) {
    cuuint64_t dims[2] = {cols, rows}, strides[1] = {cols * 2};
    cuuint32_t box[2] = {bc, br}, es[2] = {1, 1};
    fn(m, CU_TENSOR_MAP_DATA_TYPE_BFLOAT16, 2, const_cast<void*>(p), dims, strides, box, es, CU_TENSOR_MAP_INTERLEAVE_NONE,
       sw, CU_TENSOR_MAP_L2_PROMOTION_L2_128B, CU_TENSOR_MAP_FLOAT_OOB_FILL_NONE);
}
void make_3d(EncodeFn fn, CUtensorMap* m, const void* p, uint64_t cols, uint64_t rows, uint32_t br = 128, uint32_t nb = 2) {
    cuuint64_t dims[3] = {64, rows, cols / 64}, strides[2] = {cols * 2, 128};
    cuuint32_t box[3] = {64, br, nb}, es[3] = {1, 1, 1};
    fn(m, CU_TENSOR_MAP_DATA_TYPE_BFLOAT16, 3, const_cast<void*>(p), dims, strides, box, es, CU_TENSOR_MAP_INTERLEAVE_NONE,
       CU_TENSOR_MAP_SWIZZLE_128B, CU_TENSOR_MAP_L2_PROMOTION_L2_256B, CU_TENSOR_MAP_FLOAT_OOB_FILL_NONE);
}

}

extern "C" void kernel_launch(void* const* d_in, const int* in_sizes, int n_in, void* d_out, int out_size) {
    static EncodeFn fn = nullptr;
    if (!fn) {
        void* f = nullptr;
        cudaDriverEntryPointQueryResult st;
        cudaGetDriverEntryPoint("cuTensorMapEncodeTiled", &f, cudaEnableDefault, &st);
        fn = (EncodeFn)f;
        cudaFuncSetAttribute(fused_kernel, cudaFuncAttributeMaxDynamicSharedMemorySize, SMEM_BYTES);
    }
    CUtensorMap ckv, wq, wuk, wuv, wo, wg, wu, wm, xm;
    make_3d(fn, &ckv, d_in[1], 512, 2048, 128, 1);
    make_3d(fn, &xm, d_in[0], 512, 2048, 64);
    make_3d(fn, &wq, d_in[2], 4096, 512);
    make_3d(fn, &wuk, d_in[3], 4096, 512);
    make_3d(fn, &wuv, d_in[4], 4096, 512);
    make_3d(fn, &wo, d_in[5], 512, 4096);
    make_2d(fn, &wg, d_in[8], 1792, 512, 16, 256, CU_TENSOR_MAP_SWIZZLE_32B);
    make_2d(fn, &wu, d_in[9], 1792, 512, 16, 256, CU_TENSOR_MAP_SWIZZLE_32B);
    make_2d(fn, &wm, d_in[12], 3072, 512, 256, 64, CU_TENSOR_MAP_SWIZZLE_NONE);
    Params p;
    p.x = (const bf16*)d_in[0];
    p.ckv = (const bf16*)d_in[1];
    p.wo = (const bf16*)d_in[5];
    p.wr = (const bf16*)d_in[7];
    p.wdown = (const bf16*)d_in[10];
    p.c = (const bf16*)d_in[11];
    p.out = (bf16*)d_out;
    p.zero = 0;
    fused_kernel<<<NCTA + NSPARE, 384, SMEM_BYTES>>>(ckv, wq, wuk, wuv, wo, wg, wu, wm, xm, p);
}
```

```cpp
#include <cuda.h>
#include <cuda_bf16.h>
#include <cuda_runtime.h>
#include <stdint.h>
#include <stdio.h>

namespace {

typedef __nv_bfloat16 bf16;
typedef unsigned long long u64;

constexpr int NCTA = 128, NSPARE = 4;
constexpr int SLOT = 32768;
constexpr int SM_BAR = 7 * SLOT;
constexpr int BAR_FULL = SM_BAR;
constexpr int BAR_EMPTY = BAR_FULL + 8 * 7;
constexpr int BAR_DONE = BAR_EMPTY + 8 * 7;
constexpr int BAR_FLAG = BAR_DONE + 8 * 9;
constexpr int BAR_PF = BAR_FLAG + 8 * 9;
constexpr int BAR_END = BAR_PF + 8;
constexpr int BAR_BEST = BAR_END + 8;
constexpr int SM_EP = BAR_END + 40;
constexpr int SM_RED = SM_BAR + 384;
constexpr int SM_TAB = SM_BAR + 1024;
constexpr int SMEM_BYTES = SM_BAR + 3072;
constexpr int NFFN = 112;
#define HINT 479
constexpr u64 L2_NORMAL = 0x1000000000000000ull, L2_FIRST = 0x12F0000000000000ull;
#define PFA 8
#define PFB 6
#define UNR 1
#define POLL_NS 50
#define MSPLIT 13
#define SF 3
#define NSH 1
#define XPF 2
#define TF 1
#define KSLEEP 200
#define YSLEEP 50
#define YPRE 150
#define SSLEEP 50
#define SPRE 0
#define PSLEEP 100
#define CSLEEP 0
#define SPEC 28
#define OMAP 2
#define KVG 7
#define PEARLY 0
#define ELATE 0
#define EARLY 7
constexpr uint32_t SPIN_LIMIT = 1u << 22;
constexpr uint32_t ONE2 = 0x3f803f80u;

struct Sync {
    uint32_t cnt[16 * 8 * 8];
    uint32_t ctxcnt[16 * 32];
    uint32_t epoch[32];
};

__device__ __align__(1024) uint8_t g_KV[16 * 16 * 2 * SLOT];
__device__ __align__(1024) uint8_t g_ctx[16 * 32 * SLOT];
__device__ __align__(1024) uint8_t g_h[16 * 4 * SLOT];
constexpr int OB = 1216, OB_STAT = 1024, OB_Y = 1088;
__device__ __align__(1024) uint4 g_out[128 * OB];
__device__ __align__(1024) bf16 g_mod[3072];
__device__ __align__(1024) uint32_t g_mod1[1024];
__device__ __align__(1024) uint4 g_cand[128 * 192];
__device__ __align__(1024) uint32_t g_key[4 * 128];
__device__ __align__(1024) uint8_t g_wf[NFFN * SLOT];
__device__ __align__(1024) Sync g_sync;
#define TS(i)

#define TT(i)
#define PT()

struct Params {
    const bf16 *x, *ckv, *wo, *wr, *wdown, *c;
    bf16* out;
    int zero;
};

__device__ __forceinline__ void mbar_init(uint32_t bar, uint32_t cnt) {
    asm volatile("mbarrier.init.shared::cta.b64 [%0], %1;" ::"r"(bar), "r"(cnt) : "memory");
}
__device__ __forceinline__ void mbar_wait(uint32_t bar, uint32_t parity) {
    asm volatile("{\n.reg .pred p;\nL_%=:\nmbarrier.try_wait.parity.shared::cta.b64 p, [%0], %1;\n@!p bra L_%=;\n}" ::"r"(bar), "r"(parity) : "memory");
}
__device__ __forceinline__ void mbar_sleep(uint32_t bar) {
    if ((threadIdx.x & 31) == 0)
        asm volatile("{\n.reg .pred p;\nL_%=:\nmbarrier.try_wait.parity.shared::cta.b64 p, [%0], 0, 100000;\n@!p bra L_%=;\n}" ::"r"(bar) : "memory");
    __syncwarp();
}
__device__ __forceinline__ void mbar_watch(uint32_t bar, uint32_t parity) {
    asm volatile("{\n.reg .pred p;\n.reg .u32 n;\nmov.u32 n, 0;\n"
                 "L_%=:\nmbarrier.try_wait.parity.shared::cta.b64 p, [%0], %1;\n@p bra D_%=;\n"
                 "add.u32 n, n, 1;\nsetp.lt.u32 p, n, %2;\n@p bra L_%=;\ntrap;\nD_%=:\n}"
                 ::"r"(bar), "r"(parity), "n"(SPIN_LIMIT) : "memory");
}
__device__ __forceinline__ void step_watch(uint32_t a, uint32_t step) {
    asm volatile("{\n.reg .pred p;\n.reg .u32 n, v;\nmov.u32 n, 0;\n"
                 "L_%=:\nld.volatile.shared.u32 v, [%0];\nsetp.ge.u32 p, v, %1;\n@p bra D_%=;\nnanosleep.u32 400;\n"
                 "add.u32 n, n, 1;\nsetp.lt.u32 p, n, %2;\n@p bra L_%=;\ntrap;\nD_%=:\n}"
                 ::"r"(a), "r"(step), "n"(SPIN_LIMIT) : "memory");
}
__device__ __forceinline__ void mbar_arrive_if(uint32_t bar, bool on) {
    asm volatile("{\n.reg .pred p;\nsetp.ne.s32 p, %1, 0;\n@p mbarrier.arrive.shared::cta.b64 _, [%0];\n}" ::"r"(bar), "r"((int)on) : "memory");
}
__device__ __forceinline__ void tma2d(uint32_t dst, const CUtensorMap* m, int c0, int c1, uint32_t bar, bool first) {
    asm volatile("{\n.reg .pred p;\nelect.sync _|p, 0xffffffff;\n"
                 "@p cp.async.bulk.tensor.2d.shared::cluster.global.mbarrier::complete_tx::bytes.L2::cache_hint [%0], [%1, {%3, %4}], [%2], %5;\n}"
                 ::"r"(dst), "l"(m), "r"(bar), "r"(c0), "r"(c1), "l"(first ? L2_FIRST : L2_NORMAL) : "memory");
}
__device__ __forceinline__ void tma3d_prefetch(const CUtensorMap* m, int row, int cb) {
    asm volatile("{\n.reg .pred p;\nelect.sync _|p, 0xffffffff;\n@p cp.async.bulk.prefetch.tensor.3d.L2.global [%0, {%1, %2, %3}];\n}"
                 ::"l"(m), "r"(0), "r"(row), "r"(cb) : "memory");
}
__device__ __forceinline__ void l2_prefetch(const void* p, uint32_t bytes) {
    asm volatile("{\n.reg .pred p;\nelect.sync _|p, 0xffffffff;\n@p cp.async.bulk.prefetch.L2.global [%0], %1;\n}" ::"l"(p), "r"(bytes) : "memory");
}
__device__ __forceinline__ void bulk_store(void* dst, uint32_t src, uint32_t bytes, bool first) {
    asm volatile("{\n.reg .pred p;\nelect.sync _|p, 0xffffffff;\n@p cp.async.bulk.global.shared::cta.bulk_group.L2::cache_hint [%0], [%1], %2, %3;\n}"
                 ::"l"(dst), "r"(src), "r"(bytes), "l"(first ? L2_FIRST : L2_NORMAL) : "memory");
}
__device__ __forceinline__ void flag_wait(const uint32_t* f, uint32_t target) {
    asm volatile("{\n.reg .pred p;\n.reg .u32 v;\n"
                 "L_%=:\nld.acquire.gpu.global.u32 v, [%0];\nsub.u32 v, v, %1;\nsetp.lt.s32 p, v, 0;\n@p nanosleep.u32 100;\n@p bra L_%=;\n}"
                 ::"l"(f), "r"(target) : "memory");
}
__device__ __forceinline__ uint4 ld_poll(const uint4* p) {
    uint4 v;
    asm volatile("{\n.reg .b128 t;\nld.relaxed.gpu.global.b128 t, [%4];\nmov.b128 {%0, %1, %2, %3}, t;\n}"
                 : "=r"(v.x), "=r"(v.y), "=r"(v.z), "=r"(v.w) : "l"(p) : "memory");
    return v;
}
__device__ __forceinline__ void st_pub(uint4* p, uint4 v, bool on) {
    asm volatile("{\n.reg .pred p;\n.reg .b128 t;\nsetp.ne.s32 p, %5, 0;\nmov.b128 t, {%1, %2, %3, %4};\n@p st.relaxed.gpu.global.b128 [%0], t;\n}"
                 ::"l"(p), "r"(v.x), "r"(v.y), "r"(v.z), "r"(v.w), "r"((int)on) : "memory");
}
__device__ __forceinline__ void st_pub(uint32_t* p, uint32_t v, bool on) {
    asm volatile("{\n.reg .pred p;\nsetp.ne.s32 p, %2, 0;\n@p st.relaxed.gpu.global.u32 [%0], %1;\n}" ::"l"(p), "r"(v), "r"((int)on) : "memory");
}
__device__ __forceinline__ void flag_add(uint32_t* p) {
    asm volatile("red.release.gpu.global.add.u32 [%0], 1;" ::"l"(p) : "memory");
}
__device__ __forceinline__ uint32_t lds32(uint32_t a) {
    uint32_t v;
    asm volatile("ld.shared.u32 %0, [%1];" : "=r"(v) : "r"(a) : "memory");
    return v;
}
__device__ __forceinline__ uint4 lds128(uint32_t a) {
    uint4 v;
    asm volatile("ld.shared.v4.u32 {%0, %1, %2, %3}, [%4];" : "=r"(v.x), "=r"(v.y), "=r"(v.z), "=r"(v.w) : "r"(a) : "memory");
    return v;
}
__device__ __forceinline__ void sched_fence(uint32_t& v, uint32_t z) {
    uint32_t ck;
    asm volatile("mov.u32 %0, %%clock;" : "=r"(ck)::"memory");
    v ^= ck & z;
}
__device__ __forceinline__ void fence_async_global() { asm volatile("fence.proxy.async.global;" ::: "memory"); }
__device__ __forceinline__ void fence_async_smem() { asm volatile("fence.proxy.async.shared::cta;" ::: "memory"); }
__device__ __forceinline__ void bar_sync(int id, int n) { asm volatile("bar.sync %0, %1;" ::"r"(id), "r"(n) : "memory"); }
__device__ __forceinline__ void bar_arrive(int id, int n) { asm volatile("bar.arrive %0, %1;" ::"r"(id), "r"(n) : "memory"); }
__device__ __forceinline__ void wg_fence() { asm volatile("wgmma.fence.sync.aligned;" ::: "memory"); }
__device__ __forceinline__ void wg_commit() { asm volatile("wgmma.commit_group.sync.aligned;" ::: "memory"); }
template <int N> __device__ __forceinline__ void wg_wait() { asm volatile("wgmma.wait_group.sync.aligned %0;" ::"n"(N) : "memory"); }
template <int N> __device__ __forceinline__ void reg_fence(float (&d)[N]) {
#pragma unroll
    for (int i = 0; i < N; i++) asm volatile("" : "+f"(d[i])::"memory");
}
template <int N> __device__ __forceinline__ void reg_fence(uint32_t (&d)[N]) {
#pragma unroll
    for (int i = 0; i < N; i++) asm volatile("" : "+r"(d[i])::"memory");
}
__device__ __forceinline__ uint32_t desc_k(uint32_t a) { return ((a & 0x3ffff) >> 4) | (1u << 16); }
__device__ __forceinline__ uint32_t desc_mn(uint32_t a) { return ((a & 0x3ffff) >> 4) | (1024u << 16); }

template <int TB>
__device__ __forceinline__ void wgmma_ss128(float (&d)[64], uint32_t da, uint32_t db, int acc, uint32_t ha = 0x40000040u, uint32_t hb = 0x40000040u) {
    asm volatile("{\n.reg .pred p;\n.reg .b64 a, b;\nsetp.ne.b32 p, %66, 0;\nmov.b64 a, {%64, %68};\nmov.b64 b, {%65, %69};\n"
        "wgmma.mma_async.sync.aligned.m64n128k16.f32.bf16.bf16 {%0, %1, %2, %3, %4, %5, %6, %7, %8, %9, %10, %11, %12, %13, %14, %15, %16, %17, %18, %19, %20, %21, %22, %23, %24, %25, %26, %27, %28, %29, %30, %31, %32, %33, %34, %35, %36, %37, %38, %39, %40, %41, %42, %43, %44, %45, %46, %47, %48, %49, %50, %51, %52, %53, %54, %55, %56, %57, %58, %59, %60, %61, %62, %63}, a, b, p, 1, 1, 0, %67;\n}"
        : "+f"(d[0]), "+f"(d[1]), "+f"(d[2]), "+f"(d[3]), "+f"(d[4]), "+f"(d[5]), "+f"(d[6]), "+f"(d[7]), "+f"(d[8]), "+f"(d[9]), "+f"(d[10]), "+f"(d[11]), "+f"(d[12]), "+f"(d[13]), "+f"(d[14]), "+f"(d[15]), "+f"(d[16]), "+f"(d[17]), "+f"(d[18]), "+f"(d[19]), "+f"(d[20]), "+f"(d[21]), "+f"(d[22]), "+f"(d[23]), "+f"(d[24]), "+f"(d[25]), "+f"(d[26]), "+f"(d[27]), "+f"(d[28]), "+f"(d[29]), "+f"(d[30]), "+f"(d[31]), "+f"(d[32]), "+f"(d[33]), "+f"(d[34]), "+f"(d[35]), "+f"(d[36]), "+f"(d[37]), "+f"(d[38]), "+f"(d[39]), "+f"(d[40]), "+f"(d[41]), "+f"(d[42]), "+f"(d[43]), "+f"(d[44]), "+f"(d[45]), "+f"(d[46]), "+f"(d[47]), "+f"(d[48]), "+f"(d[49]), "+f"(d[50]), "+f"(d[51]), "+f"(d[52]), "+f"(d[53]), "+f"(d[54]), "+f"(d[55]), "+f"(d[56]), "+f"(d[57]), "+f"(d[58]), "+f"(d[59]), "+f"(d[60]), "+f"(d[61]), "+f"(d[62]), "+f"(d[63])
        : "r"(da), "r"(db), "r"(acc), "n"(TB), "r"(ha), "r"(hb));
}
template <int TB>
__device__ __forceinline__ void wgmma_ss128_init(float (&d)[64], uint32_t da, uint32_t db, uint32_t ha = 0x40000040u, uint32_t hb = 0x40000040u) {
    asm volatile("{\n.reg .pred p;\n.reg .b64 a, b;\nsetp.ne.b32 p, 0, 0;\nmov.b64 a, {%64, %67};\nmov.b64 b, {%65, %68};\n"
        "wgmma.mma_async.sync.aligned.m64n128k16.f32.bf16.bf16 {%0, %1, %2, %3, %4, %5, %6, %7, %8, %9, %10, %11, %12, %13, %14, %15, %16, %17, %18, %19, %20, %21, %22, %23, %24, %25, %26, %27, %28, %29, %30, %31, %32, %33, %34, %35, %36, %37, %38, %39, %40, %41, %42, %43, %44, %45, %46, %47, %48, %49, %50, %51, %52, %53, %54, %55, %56, %57, %58, %59, %60, %61, %62, %63}, a, b, p, 1, 1, 0, %66;\n}"
        : "=f"(d[0]), "=f"(d[1]), "=f"(d[2]), "=f"(d[3]), "=f"(d[4]), "=f"(d[5]), "=f"(d[6]), "=f"(d[7]), "=f"(d[8]), "=f"(d[9]), "=f"(d[10]), "=f"(d[11]), "=f"(d[12]), "=f"(d[13]), "=f"(d[14]), "=f"(d[15]), "=f"(d[16]), "=f"(d[17]), "=f"(d[18]), "=f"(d[19]), "=f"(d[20]), "=f"(d[21]), "=f"(d[22]), "=f"(d[23]), "=f"(d[24]), "=f"(d[25]), "=f"(d[26]), "=f"(d[27]), "=f"(d[28]), "=f"(d[29]), "=f"(d[30]), "=f"(d[31]), "=f"(d[32]), "=f"(d[33]), "=f"(d[34]), "=f"(d[35]), "=f"(d[36]), "=f"(d[37]), "=f"(d[38]), "=f"(d[39]), "=f"(d[40]), "=f"(d[41]), "=f"(d[42]), "=f"(d[43]), "=f"(d[44]), "=f"(d[45]), "=f"(d[46]), "=f"(d[47]), "=f"(d[48]), "=f"(d[49]), "=f"(d[50]), "=f"(d[51]), "=f"(d[52]), "=f"(d[53]), "=f"(d[54]), "=f"(d[55]), "=f"(d[56]), "=f"(d[57]), "=f"(d[58]), "=f"(d[59]), "=f"(d[60]), "=f"(d[61]), "=f"(d[62]), "=f"(d[63])
        : "r"(da), "r"(db), "n"(TB), "r"(ha), "r"(hb));
}
template <int TB>
__device__ __forceinline__ void wgmma_ss64(float (&d)[32], uint32_t da, uint32_t db, int acc, uint32_t ha = 0x40000040u, uint32_t hb = 0x40000040u) {
    asm volatile("{\n.reg .pred p;\n.reg .b64 a, b;\nsetp.ne.b32 p, %34, 0;\nmov.b64 a, {%32, %36};\nmov.b64 b, {%33, %37};\n"
        "wgmma.mma_async.sync.aligned.m64n64k16.f32.bf16.bf16 {%0, %1, %2, %3, %4, %5, %6, %7, %8, %9, %10, %11, %12, %13, %14, %15, %16, %17, %18, %19, %20, %21, %22, %23, %24, %25, %26, %27, %28, %29, %30, %31}, a, b, p, 1, 1, 0, %35;\n}"
        : "+f"(d[0]), "+f"(d[1]), "+f"(d[2]), "+f"(d[3]), "+f"(d[4]), "+f"(d[5]), "+f"(d[6]), "+f"(d[7]), "+f"(d[8]), "+f"(d[9]), "+f"(d[10]), "+f"(d[11]), "+f"(d[12]), "+f"(d[13]), "+f"(d[14]), "+f"(d[15]), "+f"(d[16]), "+f"(d[17]), "+f"(d[18]), "+f"(d[19]), "+f"(d[20]), "+f"(d[21]), "+f"(d[22]), "+f"(d[23]), "+f"(d[24]), "+f"(d[25]), "+f"(d[26]), "+f"(d[27]), "+f"(d[28]), "+f"(d[29]), "+f"(d[30]), "+f"(d[31])
        : "r"(da), "r"(db), "r"(acc), "n"(TB), "r"(ha), "r"(hb));
}
template <int TB>
__device__ __forceinline__ void wgmma_ss64_init(float (&d)[32], uint32_t da, uint32_t db, uint32_t ha = 0x40000040u, uint32_t hb = 0x40000040u) {
    asm volatile("{\n.reg .pred p;\n.reg .b64 a, b;\nsetp.ne.b32 p, 0, 0;\nmov.b64 a, {%32, %35};\nmov.b64 b, {%33, %36};\n"
        "wgmma.mma_async.sync.aligned.m64n64k16.f32.bf16.bf16 {%0, %1, %2, %3, %4, %5, %6, %7, %8, %9, %10, %11, %12, %13, %14, %15, %16, %17, %18, %19, %20, %21, %22, %23, %24, %25, %26, %27, %28, %29, %30, %31}, a, b, p, 1, 1, 0, %34;\n}"
        : "=f"(d[0]), "=f"(d[1]), "=f"(d[2]), "=f"(d[3]), "=f"(d[4]), "=f"(d[5]), "=f"(d[6]), "=f"(d[7]), "=f"(d[8]), "=f"(d[9]), "=f"(d[10]), "=f"(d[11]), "=f"(d[12]), "=f"(d[13]), "=f"(d[14]), "=f"(d[15]), "=f"(d[16]), "=f"(d[17]), "=f"(d[18]), "=f"(d[19]), "=f"(d[20]), "=f"(d[21]), "=f"(d[22]), "=f"(d[23]), "=f"(d[24]), "=f"(d[25]), "=f"(d[26]), "=f"(d[27]), "=f"(d[28]), "=f"(d[29]), "=f"(d[30]), "=f"(d[31])
        : "r"(da), "r"(db), "n"(TB), "r"(ha), "r"(hb));
}
__device__ __forceinline__ void wgmma_rs128(float (&d)[64], uint32_t a0, uint32_t a1, uint32_t a2, uint32_t a3, uint32_t db, int acc, uint32_t hb = 0x40000040u) {
    asm volatile("{\n.reg .pred p;\n.reg .b64 b;\nsetp.ne.b32 p, %69, 0;\nmov.b64 b, {%68, %70};\n"
        "wgmma.mma_async.sync.aligned.m64n128k16.f32.bf16.bf16 {%0, %1, %2, %3, %4, %5, %6, %7, %8, %9, %10, %11, %12, %13, %14, %15, %16, %17, %18, %19, %20, %21, %22, %23, %24, %25, %26, %27, %28, %29, %30, %31, %32, %33, %34, %35, %36, %37, %38, %39, %40, %41, %42, %43, %44, %45, %46, %47, %48, %49, %50, %51, %52, %53, %54, %55, %56, %57, %58, %59, %60, %61, %62, %63}, {%64, %65, %66, %67}, b, p, 1, 1, 1;\n}"
        : "+f"(d[0]), "+f"(d[1]), "+f"(d[2]), "+f"(d[3]), "+f"(d[4]), "+f"(d[5]), "+f"(d[6]), "+f"(d[7]), "+f"(d[8]), "+f"(d[9]), "+f"(d[10]), "+f"(d[11]), "+f"(d[12]), "+f"(d[13]), "+f"(d[14]), "+f"(d[15]), "+f"(d[16]), "+f"(d[17]), "+f"(d[18]), "+f"(d[19]), "+f"(d[20]), "+f"(d[21]), "+f"(d[22]), "+f"(d[23]), "+f"(d[24]), "+f"(d[25]), "+f"(d[26]), "+f"(d[27]), "+f"(d[28]), "+f"(d[29]), "+f"(d[30]), "+f"(d[31]), "+f"(d[32]), "+f"(d[33]), "+f"(d[34]), "+f"(d[35]), "+f"(d[36]), "+f"(d[37]), "+f"(d[38]), "+f"(d[39]), "+f"(d[40]), "+f"(d[41]), "+f"(d[42]), "+f"(d[43]), "+f"(d[44]), "+f"(d[45]), "+f"(d[46]), "+f"(d[47]), "+f"(d[48]), "+f"(d[49]), "+f"(d[50]), "+f"(d[51]), "+f"(d[52]), "+f"(d[53]), "+f"(d[54]), "+f"(d[55]), "+f"(d[56]), "+f"(d[57]), "+f"(d[58]), "+f"(d[59]), "+f"(d[60]), "+f"(d[61]), "+f"(d[62]), "+f"(d[63])
        : "r"(a0), "r"(a1), "r"(a2), "r"(a3), "r"(db), "r"(acc), "r"(hb));
}

__device__ __forceinline__ uint32_t pack2(float lo, float hi) {
    uint32_t r;
    asm("cvt.rn.bf16x2.f32 %0, %1, %2;" : "=r"(r) : "f"(hi), "f"(lo));
    return r;
}
__device__ __forceinline__ float bf_lo(uint32_t v) { return __uint_as_float(v << 16); }
__device__ __forceinline__ float bf_hi(uint32_t v) { return __uint_as_float(v & 0xffff0000u); }
__device__ __forceinline__ float rbf(float v) { return bf_lo(pack2(v, v)); }
__device__ __forceinline__ uint32_t badd(uint32_t a, uint32_t b) {
    uint32_t r;
    asm("add.rn.bf16x2 %0, %1, %2;" : "=r"(r) : "r"(a), "r"(b));
    return r;
}
__device__ __forceinline__ uint32_t bsub(uint32_t a, uint32_t b) {
    uint32_t r;
    asm("sub.rn.bf16x2 %0, %1, %2;" : "=r"(r) : "r"(a), "r"(b));
    return r;
}
__device__ __forceinline__ uint32_t bmul(uint32_t a, uint32_t b) {
    uint32_t r;
    asm("mul.rn.bf16x2 %0, %1, %2;" : "=r"(r) : "r"(a), "r"(b));
    return r;
}
__device__ __forceinline__ uint32_t ln_apply(uint32_t x, uint32_t mb, float rs, uint32_t scale, uint32_t shift) {
    const uint32_t d = bsub(x, mb);
    return badd(bmul(pack2(bf_lo(d) * rs, bf_hi(d) * rs), scale), shift);
}
__device__ __forceinline__ float ex2(float v) {
    float r;
    asm("ex2.approx.ftz.f32 %0, %1;" : "=f"(r) : "f"(v));
    return r;
}
__device__ __forceinline__ float rcp(float v) {
    float r;
    asm("rcp.approx.ftz.f32 %0, %1;" : "=f"(r) : "f"(v));
    return r;
}
__device__ __forceinline__ float sqrt_fast(float v) {
    float r;
    asm("sqrt.approx.ftz.f32 %0, %1;" : "=f"(r) : "f"(v));
    return r;
}
__device__ __forceinline__ float ln_rstd(float var) { return rcp(rbf(sqrt_fast(rbf(rbf(var) + 1e-5f)))); }
__device__ __forceinline__ float sigmoid(float v) { return rcp(1.f + ex2(-1.4426950408889634f * v)); }
__device__ __forceinline__ float quad_sum(float v) {
    v += __shfl_xor_sync(0xffffffffu, v, 1);
    return v + __shfl_xor_sync(0xffffffffu, v, 2);
}

constexpr uint32_t HI_128 = 0x40000040u, HI_IMG = 0x80000080u, HI_Q = 0x80000040u;
template <int M, int RH>
__device__ __forceinline__ uint4 img_pack(const float (&d)[64], float s) {
    uint4 v;
    v.x = pack2(d[16 * M + 2 * RH] * s, d[16 * M + 2 * RH + 1] * s);
    v.y = pack2(d[16 * M + 4 + 2 * RH] * s, d[16 * M + 5 + 2 * RH] * s);
    v.z = pack2(d[16 * M + 8 + 2 * RH] * s, d[16 * M + 9 + 2 * RH] * s);
    v.w = pack2(d[16 * M + 12 + 2 * RH] * s, d[16 * M + 13 + 2 * RH] * s);
    return v;
}
template <int M>
__device__ __forceinline__ void img_store_global(uint8_t* img, uint32_t toff, const float (&d)[64], float s0, float s1) {
    uint4* p = reinterpret_cast<uint4*>(img + toff) + M * 32;
    p[0] = img_pack<M, 0>(d, s0);
    p[128] = img_pack<M, 1>(d, s1);
}
__device__ __forceinline__ void sts128(uint32_t a, uint4 v) {
    asm volatile("st.shared.v4.b32 [%0], {%1, %2, %3, %4};" ::"r"(a), "r"(v.x), "r"(v.y), "r"(v.z), "r"(v.w) : "memory");
}
constexpr float SM_C = 0.08838834764831845f * 1.4426950408889634f;
__device__ __forceinline__ float pack2f(float lo, float hi) {
    float r;
    asm("{\n.reg .b32 t;\ncvt.rn.bf16x2.f32 t, %1, %2;\nmov.b32 %0, t;\n}" : "=f"(r) : "f"(hi), "f"(lo));
    return r;
}
template <int M, bool SCALE, bool PARK>
__device__ __forceinline__ void pack_group(float (&d)[64], float (&v)[8], float s0, float s1) {
#pragma unroll
    for (int i = 0; i < 8; i++) {
        const int k = 16 * M + 4 * (i & 3) + 2 * (i >> 2);
        v[i] = SCALE ? pack2f(d[k] * (i < 4 ? s0 : s1), d[k + 1] * (i < 4 ? s0 : s1)) : pack2f(d[k], d[k + 1]);
        if (PARK && M > 0) d[16 * (M > 0 ? M - 1 : 0) + i] = v[i];
    }
}
__device__ __forceinline__ uint32_t q_off(uint32_t toff) { return (((toff >> 1) & ~2047u) ^ 8192) + (toff & 511); }
template <int M, bool PARK>
__device__ __forceinline__ void ctx_store_part(float4* p, float (&d)[64], float i0, float i1) {
    float v[8];
    pack_group<M, true, PARK>(d, v, i0, i1);
    p[M * 32] = make_float4(v[0], v[1], v[2], v[3]);
    p[M * 32 + 128] = make_float4(v[4], v[5], v[6], v[7]);
}
template <bool PARK>
__device__ __forceinline__ void ctx_store(uint8_t* img, uint32_t toff, float (&o)[64], float l0, float l1) {
    const float i0 = rcp(quad_sum(l0)), i1 = rcp(quad_sum(l1));
    float4* p = reinterpret_cast<float4*>(img + toff);
    ctx_store_part<0, PARK>(p, o, i0, i1); ctx_store_part<1, PARK>(p, o, i0, i1); ctx_store_part<2, PARK>(p, o, i0, i1); ctx_store_part<3, PARK>(p, o, i0, i1);
}

template <int M>
__device__ __forceinline__ void tile_store_part(float4* p, uint32_t a, float (&d)[64], float i0, float i1, int ctx) {
    float v[8];
    pack_group<M, true, true>(d, v, i0, i1);
#pragma unroll
    for (int h = 0; h < 2; h++)
        asm volatile("{\n.reg .pred p;\nsetp.ne.s32 p, %6, 0;\n@p st.global.v4.f32 [%0], {%2, %3, %4, %5};\n@!p st.shared.v4.f32 [%1], {%2, %3, %4, %5};\n}"
                     ::"l"(p + M * 32 + h * 128), "r"(a + (M >> 1) * 16384 + (M & 1) * 512 + h * 1024),
                     "f"(v[4 * h]), "f"(v[4 * h + 1]), "f"(v[4 * h + 2]), "f"(v[4 * h + 3]), "r"(ctx) : "memory");
}
__device__ __forceinline__ void tile_store(uint8_t* img, uint32_t a, uint32_t toff, float (&d)[64], float i0, float i1, int ctx) {
    float4* p = reinterpret_cast<float4*>(img + toff);
    a += q_off(toff);
    tile_store_part<0>(p, a, d, i0, i1, ctx); tile_store_part<1>(p, a, d, i0, i1, ctx);
    tile_store_part<2>(p, a, d, i0, i1, ctx); tile_store_part<3>(p, a, d, i0, i1, ctx);
}

__device__ __forceinline__ void slot_wait(uint32_t bars, uint32_t& ph, uint32_t slot) {
    mbar_wait(bars + 8 * slot, (ph >> slot) & 1);
    ph ^= 1u << slot;
}
__device__ __forceinline__ void release_if(uint32_t eb, uint32_t slot, bool on) {
    asm volatile("{\n.reg .pred p;\nsetp.ne.s32 p, %1, 0;\n@p mbarrier.arrive.shared::cluster.b64 _, [%0];\n}" ::"r"(eb + 8 * slot), "r"((int)on) : "memory");
}
__device__ __forceinline__ void slot_expect(uint32_t sb, uint32_t slot) {
    asm volatile("{\n.reg .pred p;\nelect.sync _|p, 0xffffffff;\n@p mbarrier.arrive.expect_tx.shared::cta.b64 _, [%0], 32768;\n}"
                 ::"r"(sb + BAR_FULL + 8 * slot) : "memory");
}
__device__ __forceinline__ void slot_acquire(uint32_t sb, uint32_t& ph, uint32_t slot) {
    slot_wait(sb + BAR_EMPTY, ph, slot);
    slot_expect(sb, slot);
}
__device__ __forceinline__ void load_bulk(uint32_t sb, uint32_t slot, uint32_t off, const void* src, uint32_t bytes, bool both, bool first) {
    if (both)
        asm volatile("{\n.reg .pred p;\nelect.sync _|p, 0xffffffff;\n"
                     "@p cp.async.bulk.shared::cluster.global.mbarrier::complete_tx::bytes.multicast::cluster.L2::cache_hint [%0], [%1], %5, [%2], %4, %3;\n}"
                     ::"r"(sb + slot * SLOT + off), "l"(src), "r"(sb + BAR_FULL + 8 * slot), "l"(first ? L2_FIRST : L2_NORMAL), "h"((uint16_t)3),
                     "r"(bytes) : "memory");
    else
        asm volatile("{\n.reg .pred p;\nelect.sync _|p, 0xffffffff;\n"
                     "@p cp.async.bulk.shared::cluster.global.mbarrier::complete_tx::bytes.L2::cache_hint [%0], [%1], %4, [%2], %3;\n}"
                     ::"r"(sb + slot * SLOT + off), "l"(src), "r"(sb + BAR_FULL + 8 * slot), "l"(first ? L2_FIRST : L2_NORMAL), "r"(bytes) : "memory");
}
__device__ __forceinline__ void load_tile(uint32_t sb, uint32_t slot, uint32_t off, const CUtensorMap* m, int row, int cb, bool both, bool first) {
    if (both)
        asm volatile("{\n.reg .pred p;\nelect.sync _|p, 0xffffffff;\n"
                     "@p cp.async.bulk.tensor.3d.shared::cluster.global.mbarrier::complete_tx::bytes.multicast::cluster.L2::cache_hint [%0], [%1, {%3, %4, %5}], [%2], %7, %6;\n}"
                     ::"r"(sb + slot * SLOT + off), "l"(m), "r"(sb + BAR_FULL + 8 * slot), "r"(0), "r"(row), "r"(cb),
                     "l"(first ? L2_FIRST : L2_NORMAL), "h"((uint16_t)3) : "memory");
    else
        asm volatile("{\n.reg .pred p;\nelect.sync _|p, 0xffffffff;\n"
                     "@p cp.async.bulk.tensor.3d.shared::cluster.global.mbarrier::complete_tx::bytes.L2::cache_hint [%0], [%1, {%3, %4, %5}], [%2], %6;\n}"
                     ::"r"(sb + slot * SLOT + off), "l"(m), "r"(sb + BAR_FULL + 8 * slot), "r"(0), "r"(row), "r"(cb),
                     "l"(first ? L2_FIRST : L2_NORMAL) : "memory");
}
__device__ __forceinline__ uint32_t ring_next(uint32_t r) { return r == 4 ? 0 : r + 1; }
__device__ __forceinline__ uint32_t w_table(int hp) { return hp ? 0x3104u : 0x4210u; }
__device__ __forceinline__ uint32_t a_table(int hp) { return hp ? 0x625u : 0x635u; }
__device__ __forceinline__ uint32_t a_next(uint32_t& t) {
    const uint32_t s = t & 15;
    t = (t >> 4) | (s << 8);
    return s;
}
constexpr uint32_t O_TABLE = 0x1604235u;
__device__ __forceinline__ uint32_t o_next(uint32_t& t) {
    const uint32_t s = t & 15;
    t = (t >> 4) | (s << 24);
    return s;
}
__device__ __forceinline__ int o_head(int i, int kh) { return i < 16 ? 4 * (i & 7) + 2 * (kh ^ 1) + (i >> 3) : 29 + 2 * kh; }

template <bool INIT>
__device__ __forceinline__ void gemm_issue(float (&d)[64], uint32_t a, uint32_t b, int acc, bool img) {
    const uint32_t ha = img ? HI_IMG : HI_128, o2 = img ? 32 : 4, o4 = img ? 64 : 1024;
    wg_fence();
#pragma unroll
    for (int k = 0; k < 8; k++) {
        if (INIT && k == 0) wgmma_ss128_init<1>(d, a, b, ha);
        else wgmma_ss128<1>(d, a + (k >> 2) * o4 + ((k >> 1) & 1) * o2 + (k & 1) * 2, b + k * 128, k ? 1 : acc, ha);
    }
    wg_commit();
}

template <bool ODD>
__device__ __forceinline__ bool proj_tile(float (&acc)[64], float (&prev)[64], int t, int q0, uint32_t sb, int wg, uint32_t eb, bool rel, uint32_t& fph,
                                          uint32_t wtab, uint32_t& atab, uint8_t* prev_img, uint32_t toff, float s0, float s1,
                                          uint32_t (&v)[32]) {
    const uint32_t a0 = desc_k(sb + (wg ^ (ODD && t == 5)) * 8192), b0 = desc_mn(sb);
    constexpr int U = ODD ? UNR : 1;
#pragma unroll U
    for (int q = ODD ? 0 : q0; q < 4; q++) {
        const uint32_t ws = (wtab >> (4 * q)) & 15, as = a_next(atab);
        if (!ODD && t != 2) slot_wait(sb + BAR_FULL, fph, ws);
        slot_wait(sb + BAR_FULL, fph, as);
        if (ODD && q == 2 && t == 5) {
#pragma unroll
            for (int i = 0; i < 8; i++) sts128(sb + 5 * SLOT + q_off(toff) + (i >> 2) * 16384 + (i & 2) * 256 + (i & 1) * 1024, make_uint4(v[4 * i], v[4 * i + 1], v[4 * i + 2], v[4 * i + 3]));
        }
        bar_sync(1 + wg, 256);
        gemm_issue<false>(acc, a0 + as * (SLOT / 16), b0 + ws * (SLOT / 16), q, false);
        bar_arrive(2 - wg, 256);
        wg_wait<1>();
        reg_fence(prev);
        if (ODD && t == 5) {
            if (q == 0) {
#pragma unroll
                for (int i = 0; i < 32; i++) {
                    const int k = 16 * (i >> 3) + 4 * (i & 3) + ((i >> 1) & 2);
                    v[i] = pack2(prev[k], prev[k + 1]);
                }
            }
            if (q == 2) {
                fence_async_smem();
                slot_wait(sb + BAR_FULL, fph, wtab & 15);
                wg_wait<0>();
                release_if(eb, as, rel);
                release_if(eb, ws, rel);
                reg_fence(acc);
                return true;
            }
        } else {
            if (q == 0) img_store_global<0>(prev_img, toff, prev, s0, s1);
            if (q == 1) img_store_global<1>(prev_img, toff, prev, s0, s1);
            if (q == 2) img_store_global<2>(prev_img, toff, prev, s0, s1);
            if (q == 3) img_store_global<3>(prev_img, toff, prev, s0, s1);
        }
        wg_wait<0>();
        release_if(eb, as, rel && !(ODD && (q & 1) && t == 5));
        if (ODD) release_if(eb, ws, rel && t != 1);
    }
    reg_fence(acc);
    return false;
}

__device__ __forceinline__ void qk_issue(float (&s)[64], uint32_t q, uint32_t k) {
    wg_fence();
    wgmma_ss128_init<0>(s, q, k, HI_Q, HI_IMG);
#pragma unroll
    for (int i = 1; i < 8; i++) wgmma_ss128<0>(s, q + (i >> 2) * 1024 + (i & 2) * 16 + (i & 1) * 2, k + (i >> 1) * 32 + (i & 1) * 2, 1, HI_Q, HI_IMG);
    wg_commit();
}
__device__ __forceinline__ void qk_issue(float (&s)[32], uint32_t q, uint32_t k) {
    wg_fence();
    wgmma_ss64_init<0>(s, q, k, HI_Q, HI_IMG);
#pragma unroll
    for (int i = 1; i < 8; i++) wgmma_ss64<0>(s, q + (i >> 2) * 1024 + (i & 2) * 16 + (i & 1) * 2, k + (i >> 1) * 32 + (i & 1) * 2, 1, HI_Q, HI_IMG);
    wg_commit();
}
__device__ __forceinline__ void pv_issue(float (&o)[64], const uint32_t (&p)[32], uint32_t v, int acc, bool half) {
    if (half) {
        asm volatile("// half" ::: "memory");
        wg_fence();
#pragma unroll
        for (int i = 0; i < 4; i++) wgmma_rs128(o, p[4 * i], p[4 * i + 1], p[4 * i + 2], p[4 * i + 3], v + i * 256, i ? 1 : acc, HI_IMG);
        wg_commit();
        asm volatile("// half" ::: "memory");
    } else {
        wg_fence();
#pragma unroll
        for (int i = 0; i < 8; i++) wgmma_rs128(o, p[4 * i], p[4 * i + 1], p[4 * i + 2], p[4 * i + 3], v + i * 256, i ? 1 : acc, HI_IMG);
        wg_commit();
    }
}
__device__ __forceinline__ void tri_mask(float (&s)[64], float x) {
#pragma unroll
    for (int k = 0; k < 16; k++) {
        float b;
        asm("sub.sat.f32 %0, %1, %2;" : "=f"(b) : "f"((float)(8 * (k >> 1) + (k & 1))), "f"(x));
        const int i = 32 + 4 * (k >> 1) + (k & 1);
        asm("fma.rn.f32 %0, %1, 0fFF61B1E6, %0;" : "+f"(s[i]) : "f"(b));
        if (k < 14) asm("fma.rn.f32 %0, %1, 0fFF61B1E6, %0;" : "+f"(s[i + 6]) : "f"(b));
    }
}
__device__ __forceinline__ void tri_mask_copy(float (&s)[64], const float (&h)[32], float x) {
#pragma unroll
    for (int i = 0; i < 32; i++) {
        asm("{\n.reg .pred p;\nsetp.lt.f32 p, %2, %3;\nselp.f32 %0, 0fFF800000, %1, p;\n}"
            : "=f"(s[i]) : "f"(h[i]), "f"(x), "f"((float)(8 * (i >> 2) - 4 * (i & 2) + (i & 1))));
        s[32 + i] = __uint_as_float(0xff800000u);
    }
}
constexpr float SM_HI = 1152921504606846976.f, SM_LO = 1.f / 1152921504606846976.f;
__device__ __forceinline__ bool softmax_unsafe(float t0, float t1, bool first) {
    bool bad = __any_sync(0xffffffffu, fmaxf(t0, t1) > SM_HI);
    if (first) {
        uint32_t a = __ballot_sync(0xffffffffu, t0 >= SM_LO), b = __ballot_sync(0xffffffffu, t1 >= SM_LO);
        a |= a >> 1;
        b |= b >> 1;
        bad |= ((a | (a >> 2)) & (b | (b >> 2)) & 0x11111111u) != 0x11111111u;
    }
    return bad;
}
__device__ __forceinline__ void softmax_shift(float (&s)[64], float d0, float d1) {
#pragma unroll
    for (int i = 0; i < 64; i++) s[i] -= (i & 2) ? d1 : d0;
}
__device__ __forceinline__ void softmax_remax(float (&s)[64], float (&m)[2], bool first, float& a0, float& a1) {
    float m0 = fmaxf(s[0], s[1]), m1 = fmaxf(s[2], s[3]);
#pragma unroll
    for (int k = 1; k < 16; k++) {
        m0 = fmaxf(m0, fmaxf(s[4 * k], s[4 * k + 1]));
        m1 = fmaxf(m1, fmaxf(s[4 * k + 2], s[4 * k + 3]));
    }
    m0 = fmaxf(m0, __shfl_xor_sync(0xffffffffu, m0, 1));
    m1 = fmaxf(m1, __shfl_xor_sync(0xffffffffu, m1, 1));
    m0 = fmaxf(m0, __shfl_xor_sync(0xffffffffu, m0, 2));
    m1 = fmaxf(m1, __shfl_xor_sync(0xffffffffu, m1, 2));
    if (!first) {
        m0 = fmaxf(m0, 0.f);
        m1 = fmaxf(m1, 0.f);
    }
    a0 = first ? 1.f : ex2(-m0);
    a1 = first ? 1.f : ex2(-m1);
    m[0] += m0;
    m[1] += m1;
    softmax_shift(s, m0, m1);
}
template <int J0, int J1>
__device__ __forceinline__ void softmax_exp(const float (&s)[64], uint32_t (&p)[32], float (&t)[4]) {
#pragma unroll
    for (int k = J0; k < J1; k++) {
        const float e0 = ex2(s[4 * k]), e1 = ex2(s[4 * k + 1]), e2 = ex2(s[4 * k + 2]), e3 = ex2(s[4 * k + 3]);
        if (k == 0) { t[0] = e0; t[1] = e1; t[2] = e2; t[3] = e3; }
        else { t[0] += e0; t[1] += e1; t[2] += e2; t[3] += e3; }
        p[2 * k] = pack2(e0, e1);
        p[2 * k + 1] = pack2(e2, e3);
    }
}
__device__ __forceinline__ void fma8(float (&acc)[8], float a, uint4 w) {
    acc[0] = fmaf(a, bf_lo(w.x), acc[0]); acc[1] = fmaf(a, bf_hi(w.x), acc[1]);
    acc[2] = fmaf(a, bf_lo(w.y), acc[2]); acc[3] = fmaf(a, bf_hi(w.y), acc[3]);
    acc[4] = fmaf(a, bf_lo(w.z), acc[4]); acc[5] = fmaf(a, bf_hi(w.z), acc[5]);
    acc[6] = fmaf(a, bf_lo(w.w), acc[6]); acc[7] = fmaf(a, bf_hi(w.w), acc[7]);
}
__device__ __forceinline__ void mma16816(float (&d)[4], const uint32_t* a, uint32_t b0, uint32_t b1) {
    asm("mma.sync.aligned.m16n8k16.row.col.f32.bf16.bf16.f32 {%0, %1, %2, %3}, {%4, %5, %6, %7}, {%8, %9}, {%0, %1, %2, %3};"
        : "+f"(d[0]), "+f"(d[1]), "+f"(d[2]), "+f"(d[3]) : "r"(a[0]), "r"(a[1]), "r"(a[2]), "r"(a[3]), "r"(b0), "r"(b1));
}
__device__ __forceinline__ uint2 best_key(const uint32_t* keys, int lane, uint32_t ep, uint32_t cur, int enough) {
#pragma unroll 1
    for (;;) {
        const uint4 k = ld_poll(reinterpret_cast<const uint4*>(keys) + lane);
        const bool ok = (((k.x ^ ep) | (k.y ^ ep) | (k.z ^ ep) | (k.w ^ ep)) & 31) == 0;
        const uint32_t best = __reduce_max_sync(0xffffffffu, ok ? max(max(k.x, k.y), max(k.z, k.w)) : 0u);
        const int n = __popc(__ballot_sync(0xffffffffu, ok));
        if (n == 32 || (n >= enough && best != cur)) return make_uint2(best, n == 32);
        __nanosleep(KSLEEP);
    }
}

__global__ void __cluster_dims__(2, 1, 1) __launch_bounds__(384, 1)
fused_kernel(const __grid_constant__ CUtensorMap tm_ckv, const __grid_constant__ CUtensorMap tm_wq,
             const __grid_constant__ CUtensorMap tm_wuk, const __grid_constant__ CUtensorMap tm_wuv,
             const __grid_constant__ CUtensorMap tm_wo, const __grid_constant__ CUtensorMap tm_wg,
             const __grid_constant__ CUtensorMap tm_wu,
             const __grid_constant__ CUtensorMap tm_wm, const __grid_constant__ CUtensorMap tm_x, const Params P) {
    extern __shared__ __align__(1024) uint8_t smem[];
    const uint32_t sb = (uint32_t)__cvta_generic_to_shared(smem);
    const int tid = threadIdx.x, lane = tid & 31, warp = __shfl_sync(0xffffffffu, tid >> 5, 0), wg = warp >> 2;
    const uint32_t sm = blockIdx.x < 8 ? blockIdx.x + 124 : blockIdx.x - 8, smq = ((sm - 64) * 147) >> 11;
    const int rb = sm < 64 ? (sm & 14) * 8 + (sm >> 4) * 2 + (sm & 1)
                 : sm < 120 ? ((sm - 64 - smq * 14) & 14) * 8 + 24 + smq * 2 + (sm & 1) : sm < 124 ? sm + 8 : sm - 116;
    const int grp = rb >> 3, j = rb & 7, kh = (grp >> (OMAP - 1)) & 1;
    const int cq = (j & 1) + ((grp >> (OMAP - 1)) & 2), ort = (OMAP == 1 ? grp & 12 : (grp & 8) + (grp & 1) * 4) + (j >> 1);
    if (warp == 0) TS(0);

    const CUtensorMap* tw = (j & 1) ? &tm_wuv : &tm_wuk;
    if (warp == 8) {
        if (lane == 0) {
#pragma unroll
            for (int i = 0; i < 7; i++) mbar_init(sb + BAR_FULL + 8 * i, 1);
            fence_async_smem();
        }
        __syncwarp();
        if (rb < NCTA) {
#pragma unroll 1
            for (int u = 0; u < 4; u++) {
                const uint32_t ws = u + (u == 3), as = (0x635u >> (4 * u)) & 15;
                slot_expect(sb, ws);
                load_tile(sb, ws, 0, tw, u * 128, 4 * grp, false, HINT & 1);
                if (u == 3) break;
                slot_expect(sb, as);
                load_tile(sb, as, 0, &tm_ckv, (j >> 1) * 128, u * 2, false, false);
                load_tile(sb, as, 16384, &tm_ckv, (j >> 1) * 128, u * 2 + 1, false, false);
            }
        }
    } else if (lane == 0 && warp < 11) {
        const int w = warp - (warp > 8);
        if (w == 9) *reinterpret_cast<uint2*>(smem + SM_EP + 16) = make_uint2(0, 0);
        const u64 cnt = (w < 5 ? (rb < NCTA ? 0x888888884444444ull : 0x888888888888888ull) : 0x111812111111118ull) >> (12 * (w % 5));
#pragma unroll
        for (int i = 0; i < 3; i++) mbar_init(sb + BAR_EMPTY + 24 * w + 8 * i, ((uint32_t)cnt >> (4 * i)) & 15);
    }
    asm volatile("fence.mbarrier_init.release.cluster;" ::: "memory");
    __syncthreads();
    asm volatile("barrier.cluster.arrive.relaxed.aligned;\nbarrier.cluster.wait.aligned;" ::: "memory");

    if (rb >= NCTA) {
        float* sc = reinterpret_cast<float*>(smem + 6 * SLOT);
        float* red = sc + 512;
        uint32_t ph = 0x7f, sl = 0;
        if (warp == 8) {
#pragma unroll 1
            for (int i = 0; i < 24; i++) {
                slot_acquire(sb, ph, sl);
                tma2d(sb + sl * SLOT, &tm_wm, (i >> 3) * 1024 + (rb - NCTA) * 256, (i & 7) * 64, sb + BAR_FULL + 8 * sl, HINT & 64);
                if (++sl == 6) sl = 0;
            }
#pragma unroll 1
            for (int i = 0; i <= NFFN / NSPARE; i++) {
                const int b = (rb - NCTA) * (NFFN / NSPARE) + i;
                if (i < NFFN / NSPARE) {
                    asm volatile("cp.async.bulk.wait_group.read 0;" ::: "memory");
                    uint32_t done = 0x7f;
                    slot_acquire(sb, done, i & 1);
#pragma unroll 1
                    for (int k = 0; k < 4; k++) tma2d(sb + (i & 1) * SLOT + k * 8192, k < 2 ? &tm_wg : &tm_wu, b * 16, (k & 1) * 256, sb + BAR_FULL + 8 * (i & 1), (HINT & 128) && (i & 3) == 3);
                }
                if (i) {
                    mbar_wait(sb + BAR_FULL + 8 * (~i & 1), ((i - 1) >> 1) & 1);
                    bulk_store(g_wf + (b - 1) * SLOT, sb + (~i & 1) * SLOT, SLOT, HINT & 256);
                    asm volatile("cp.async.bulk.commit_group;" ::: "memory");
                }
            }
            asm volatile("cp.async.bulk.wait_group 0;" ::: "memory");
            fence_async_global();
            TS(4);
        } else if (warp < 8) {
            const uint32_t c2 = __ldg(reinterpret_cast<const uint32_t*>(P.c) + tid), ep = __ldcg(&g_sync.epoch[0]) + 1;
            sc[2 * tid] = rbf(bf_lo(c2) * sigmoid(bf_lo(c2)));
            sc[2 * tid + 1] = rbf(bf_hi(c2) * sigmoid(bf_hi(c2)));
            ph = 0;
#pragma unroll 1
            for (int ps = 0; ps < 3; ps++) {
                bar_sync(1, 256);
                float acc[8] = {0.f, 0.f, 0.f, 0.f, 0.f, 0.f, 0.f, 0.f};
#pragma unroll 1
                for (int bt = 0; bt < 8; bt++) {
                    slot_wait(sb + BAR_FULL, ph, sl);
#pragma unroll 4
                    for (int i = 0; i < 8; i++)
                        fma8(acc, sc[bt * 64 + warp * 8 + i], *reinterpret_cast<const uint4*>(smem + sl * SLOT + (warp * 8 + i) * 512 + lane * 16));
                    __syncwarp();
                    mbar_arrive_if(sb + BAR_EMPTY + 8 * sl, lane == 0);
                    if (++sl == 6) sl = 0;
                }
                *reinterpret_cast<float4*>(red + warp * 256 + lane * 8) = make_float4(acc[0], acc[1], acc[2], acc[3]);
                *reinterpret_cast<float4*>(red + warp * 256 + lane * 8 + 4) = make_float4(acc[4], acc[5], acc[6], acc[7]);
                bar_sync(1, 256);
                float v = 0.f;
#pragma unroll
                for (int i = 0; i < 8; i++) v += red[i * 256 + tid];
                if (ps == 0) st_pub(g_mod1 + (rb - NCTA) * 256 + tid, (pack2(0.f, v) & 0xffff0000u) | (ep & 0xffffu), true);
                else g_mod[ps * 1024 + (rb - NCTA) * 256 + tid] = __float2bfloat16_rn(v);
                if (warp == 0) TS(1 + ps);
            }
        }
        __syncthreads();
        if (tid < 2) flag_add(&g_sync.cnt[7 * 8]);
        return;
    }

    if (wg == 2) {
        asm volatile("setmaxnreg.dec.sync.aligned.u32 40;");
        if (warp == 8) {
            const uint32_t rank = j & 1, half = rank * 16384;
            uint32_t eph = 0, r = 0;
#pragma unroll 1
            for (int hp = 0; hp < 2; hp++) {
                uint32_t wtab = w_table(hp), atab = a_table(hp);
                const int hc = 4 * grp + 2 * hp;
#pragma unroll 1
                for (int u = 3 - 3 * hp; u < 16; u++) {
                    if (hp && u < 4) {
                        const uint32_t ws = (wtab >> (4 * u)) & 15;
                        slot_acquire(sb, eph, ws);
                        load_tile(sb, ws, 0, tw, u * 128, hc, false, HINT & 1);
                        PT();
                    }
                    if (hp == 1 && (u & 7) == 4) mbar_wait(sb + BAR_FLAG + 24 + (u & 8), 0);
                    const uint32_t as = a_next(atab);
                    slot_acquire(sb, eph, as);
                    load_tile(sb, as, half, &tm_ckv, ((u & 12) + (j >> 1)) * 128, (u & 3) * 2 + rank, true, (HINT & 8) && hp);
                    PT();
                    if (hp == 1 && (u | 2) == 3 && lane == 0)
                        asm volatile("red.relaxed.gpu.global.add.u32 [%0], 1;" ::"l"(&g_sync.cnt[(grp * 8 + 3 + (u >> 1)) * 8]) : "memory");
                }
                const uint8_t* src = g_h + (15 - j) * 4 * SLOT;
#pragma unroll 1
                for (int u = 0; u < 8; u++) {
                    if (u == 0 || u == KVG) {
                        mbar_wait(sb + BAR_FLAG + (u ? 8 + 32 * hp : 0), 0);
                        fence_async_global();
                    }
                    if (u < 4) {
                        const uint32_t ws = (wtab >> (4 * u)) & 15;
                        slot_acquire(sb, eph, ws);
                        load_tile(sb, ws, 0, &tm_wq, u * 128, hc, false, HINT & 1);
                        PT();
                    }
                    const uint32_t as = a_next(atab);
                    slot_acquire(sb, eph, as);
                    load_bulk(sb, as, 0, src, SLOT, false, (HINT & 8) && hp);
                    PT();
                    src += u == 3 ? (8 * j - 63) * SLOT : SLOT;
                }
                const int step = hp ? -2 * SLOT : 2 * SLOT;
                src = g_KV + (size_t)(grp * 32 + 30 * hp) * SLOT + half - step;
#pragma unroll 1
                for (int n = 0; n <= 17; n++) {
                    if (n == 8) {
                        mbar_wait(sb + BAR_FLAG + 16 + 32 * hp, 0);
                        fence_async_global();
                    }
                    const uint8_t* v = src + SLOT;
                    src += n < 16 - j ? step : n == 16 - j ? (2 * j - 15) * step : -step;
                    if (n < 17) {
                        slot_acquire(sb, eph, r);
                        if (n != 15 - (j & 6)) load_bulk(sb, r, half, src, SLOT / 2, true, HINT & 4);
                        else load_bulk(sb, r, 0, src - half, SLOT, false, HINT & 4);
                        PT();
                        r = ring_next(r);
                    }
                    if (n) {
                        slot_acquire(sb, eph, r);
                        if (n != 16 - (j & 6)) load_bulk(sb, r, half, v, SLOT / 2, true, HINT & 4);
                        else load_bulk(sb, r, 0, v - half, SLOT, false, HINT & 4);
                        PT();
                        r = ring_next(r);
                    }
                    asm volatile("st.volatile.shared.u32 [%0], %1;" ::"r"(sb + SM_EP + 16), "r"(18 * hp + n + 1) : "memory");
                }
            }
            uint32_t otab = O_TABLE, ready = 0;
#pragma unroll 1
            for (int i = 0; i < 17; i++) {
                const bool dyn = i >= 8 && i < 15;
                const uint32_t want = dyn ? 15u << (4 * (i - 8)) : 1u << max(i + 14, 28);
                if (!(ready & want)) {
                    do {
                        asm volatile("ld.acquire.cta.shared.u32 %0, [%1];" : "=r"(ready) : "r"(sb + SM_EP + 20) : "memory");
                        ready = __shfl_sync(0xffffffffu, ready, 0);
                    } while (!(ready & want));
                    fence_async_global();
                }
                const int head = o_head(dyn ? (ready >> (4 * (i - 8))) & 15 : i, kh);
                const uint32_t as = o_next(otab), ws = o_next(otab), off = i < 15 ? half : kh * 16384;
                slot_acquire(sb, eph, as);
                load_bulk(sb, as, off, g_ctx + (size_t)(ort * 32 + head) * SLOT + off, SLOT / 2, i < 15, HINT & 16);
                if (i == 15) load_tile(sb, as, off ^ 16384, &tm_x, ort * 128 + kh * 64, cq * 2, false, false);
                if (i == 16) load_bulk(sb, as, off ^ 16384, P.wdown + min(rb, NFFN - 1) * 8192, SLOT / 2, false, false);
                PT();
                slot_acquire(sb, eph, ws);
                load_tile(sb, ws, 0, &tm_wo, head * 128, cq * 2, false, HINT & 2);
                PT();
                if (i == 0) o_next(otab);
            }
            if (rb < NFFN) {
                slot_acquire(sb, eph, 5);
                load_bulk(sb, 5, 0, g_wf + rb * SLOT, SLOT, false, false);
            }
        } else if (warp == 9) {
            l2_prefetch(P.ckv + rb * 2048, 4096);
            mbar_watch(sb + BAR_FULL, 0);
            l2_prefetch(P.ckv + 512 * 512 + rb * 2048, 4096);
            mbar_watch(sb + BAR_FULL + 8 * XPF, 0);
            l2_prefetch(P.x + rb * 8192, 16384);
            mbar_watch(sb + BAR_FULL + 8 * 4, 0);
            l2_prefetch(P.ckv + 1024 * 512 + rb * 4096, 8192);
            TS(40);
#pragma unroll 1
            for (int i = 0; i < 15; i++) {
                step_watch(sb + SM_EP + 16, i == 0 ? 0 : i < 5 ? PFA + i : 13 + PFB + i);
                if (i == 12) mbar_watch(sb + BAR_FLAG + 8 * 7, 0);
                const int rf = min(rb, NFFN - 1);
                const uint8_t* p = i == 3 ? reinterpret_cast<const uint8_t*>(P.ckv) + rb * 16384
                                 : i == 4 ? g_h + rb * 16384
                                 : i < 9 ? g_ctx + (size_t)(ort * 32 + o_head(cq + 2 * ((i - 5) & 2), kh)) * SLOT + (i & 1) * 16384
                                 : i < 11 ? reinterpret_cast<const uint8_t*>(P.wo) + (grp * 16 + (~i & 1) * 8 + j) * 16384
                                 : i == 11 ? reinterpret_cast<const uint8_t*>(P.x) + rb * 16384
                                 : i == 12 ? reinterpret_cast<const uint8_t*>(P.wdown) + rf * 16384 : g_wf + rf * SLOT + (i & 1) * 16384;
                if (i >= 3) l2_prefetch(p, 16384);
                else if ((i | j) & 1) tma3d_prefetch(i == 1 ? tw : &tm_wq, (j >> 1) * 128, grp * 4 + (i ? 2 : 0));
            }
            const uint32_t v = lds32(sb + SM_EP) - 1;
            sts128(sb + SM_RED + lane * 16, make_uint4(v, v, v, v));
            fence_async_smem();
            __syncwarp();
#pragma unroll 1
            for (int i = 0; i < OB / 32; i++) bulk_store(g_out + rb * OB + i * 32, sb + SM_RED, 512, false);
            asm volatile("cp.async.bulk.commit_group;\ncp.async.bulk.wait_group 0;" ::: "memory");
            fence_async_global();
            __syncwarp();
            mbar_arrive_if(sb + BAR_PF, lane == 0);
            if (lane == 0) mbar_watch(sb + BAR_END, 0);
        } else {
            const uint32_t ep = __ldcg(&g_sync.epoch[0]) + 1;
            asm volatile("st.shared.u32 [%0], %1;" ::"r"(sb + SM_EP), "r"(ep) : "memory");
            mbar_wait(sb + BAR_FULL + 8 * 4, 0);
            {
                uint4 v[4];
                for (;;) {
                    uint32_t bad = 0;
#pragma unroll
                    for (int k = 0; k < 4; k++) v[k] = ld_poll(reinterpret_cast<const uint4*>(g_mod1) + (warp & 1) * 128 + k * 32 + lane);
#pragma unroll
                    for (int k = 0; k < 4; k++) bad |= (v[k].x ^ ep) | (v[k].y ^ ep) | (v[k].z ^ ep) | (v[k].w ^ ep);
                    if (__all_sync(0xffffffffu, (bad & 0xffff) == 0)) break;
                    __nanosleep(100);
                }
                const uint32_t one = (warp & 1) ? ONE2 : 0x80008000u;
#pragma unroll
                for (int k = 0; k < 4; k++)
                    *reinterpret_cast<uint2*>(smem + SM_TAB + (warp & 1) * 1024 + k * 256 + lane * 8) =
                        make_uint2(badd(__byte_perm(v[k].x, v[k].y, 0x7632), one), badd(__byte_perm(v[k].z, v[k].w, 0x7632), one));
            }
            __syncwarp();
            mbar_arrive_if(sb + BAR_FLAG + 8 * 8, lane == 0);
            if (warp == 10) {
#pragma unroll 1
                for (int i = 0; i < 9; i++) {
                    mbar_sleep(sb + BAR_DONE + 8 * i);
                    if (lane == 0) flag_add(i && ((i - 1) & 2) ? &g_sync.ctxcnt[((i & 1) ? 15 - j : j) * 32 + 2 * grp + (i > 4)] : &g_sync.cnt[(grp * 8 + i) * 8]);
                    if (i == 0) TS(43);
                }
            } else {
                TS(42);
#pragma unroll 1
                for (int i = 0; i < 8; i++) {
                    mbar_sleep(sb + BAR_DONE + 8 * (i == 7 ? 6 : i == 4 ? 3 : i));
                    if (lane < 2) flag_wait(&g_sync.cnt[((i == 0 ? (lane ? j : 15 - j) : i == 7 ? 0 : grp) * 8 + i) * 8], 8 * ep);
                    __syncwarp();
                    mbar_arrive_if(sb + BAR_FLAG + 8 * i, lane == 0 && i < 7);
                    TS(48 + i);
                }
                const uint32_t *mp = reinterpret_cast<const uint32_t*>(g_mod) + lane, *wp = reinterpret_cast<const uint32_t*>(P.wr) + lane;
                float ra = 0.f, rs = 0.f;
#pragma unroll 1
                for (int k = 0; k < 256; k += 32) {
                    const uint32_t ga = __ldcg(mp + 512 + k), sh = __ldcg(mp + 768 + k), c1 = badd(__ldcg(mp + 1024 + k), ONE2);
                    const uint32_t gb = __ldcg(mp + 1280 + k), ww = __ldg(wp + k);
                    const uint32_t a = bmul(c1, ww);
                    ra += bf_lo(a) + bf_hi(a);
                    rs = fmaf(bf_lo(sh), bf_lo(ww), fmaf(bf_hi(sh), bf_hi(ww), rs));
                    if (k >> 6 == cq) {
                        sts128(sb + SM_TAB + ((k & 32) + lane) * 16, make_uint4(ga << 16, ga & 0xffff0000u, a, 0));
                        sts128(sb + SM_TAB + 1024 + ((k & 32) + lane) * 16, make_uint4(c1, sh, gb, 0));
                    }
                }
#pragma unroll 1
                for (int o = 16; o > 0; o >>= 1) {
                    ra += __shfl_xor_sync(0xffffffffu, ra, o);
                    rs += __shfl_xor_sync(0xffffffffu, rs, o);
                }
                *reinterpret_cast<float2*>(smem + SM_EP + 8) = make_float2(ra, rs);
                __syncwarp();
                mbar_arrive_if(sb + BAR_FLAG + 8 * 7, lane == 0);
                const uint32_t* f = &g_sync.ctxcnt[ort * 32 + o_head(min(lane, 16), kh)];
                uint32_t ready = -(j & 1), list = 0, sh = 0, qa;
                asm("mapa.shared::cluster.u32 %0, %1, %2;" : "=r"(qa) : "r"(sb + SM_EP + 20), "r"(lane & 1));
                while (ready != ~0u) {
                    uint32_t v;
                    asm volatile("ld.acquire.gpu.global.u32 %0, [%1];" : "=r"(v) : "l"(f) : "memory");
                    const uint32_t now = __ballot_sync(0xffffffffu, (int)(v - ep) >= 0);
#pragma unroll 1
                    for (uint32_t fresh = now & ~ready & 0x7f00; fresh; fresh &= fresh - 1, sh += 4) list |= (__ffs(fresh) - 1) << sh;
                    list |= (((now & 0xff) + 1) >> 8 << 28) | ((now & 0x18000) << 14);
                    if (now != ready && lane < 2) asm volatile("st.relaxed.cluster.shared::cluster.u32 [%0], %1;" ::"r"(qa), "r"(list) : "memory");
                    if ((now & 0xff) == 0xff) mbar_sleep(sb + BAR_DONE + 8 * 7);
                    ready = now;
                    __nanosleep(POLL_NS);
                }
                TS(45);
            }
        }
    } else {
        asm volatile("setmaxnreg.inc.sync.aligned.u32 232;");
        const bool elected = (tid & 127) == 0, rel = (tid & 95) == 0;
        uint32_t eb;
        asm("mapa.shared::cluster.u32 %0, %1, %2;" : "=r"(eb) : "r"(sb + BAR_EMPTY), "r"(warp & 1));
        const int g = lane >> 2, c4 = lane & 3;
        const uint32_t toff = warp * 4096 + g * 64 + ((c4 ^ (g >> 1)) << 4);
        uint32_t fph = 0x3f, r = 0;
        if (wg == 1) bar_arrive(1, 256);
        const uint32_t kd = desc_k(sb), wd = desc_mn(sb), vd = ((sb & 0x3ffff) >> 4) | (32u << 16);
        const int nL = 16 - j, hn = nL - 1 + wg;
        float s[64], o[64], li[2] = {0.f, 0.f};
        uint8_t* cimg = g_ctx;
        const float sc = (j & 1) ? 1.f : SM_C;
#pragma unroll 1
        for (int q = 0; q < 3; q++) {
            const uint32_t as = (0x635u >> (4 * q)) & 15;
            mbar_wait(sb + BAR_FULL + 8 * q, 0);
            mbar_wait(sb + BAR_FULL + 8 * as, 0);
            bar_sync(1 + wg, 256);
            gemm_issue<false>(s, kd + wg * 512 + as * (SLOT / 16), wd + q * (SLOT / 16), q, false);
            bar_arrive(2 - wg, 256);
            wg_wait<0>();
            release_if(eb, as, rel);
        }
        {
            const int xrow = rb * 16 + warp * 2;
            const uint4* xp = reinterpret_cast<const uint4*>(P.x) + xrow * 64;
            uint8_t* img = g_KV + (size_t)(grp * 32 + j) * SLOT;
            uint32_t x[16], x0[2];
            float st[4] = {0.f, 0.f, 0.f, 0.f};
            mbar_wait(sb + BAR_FULL + 8 * 4, 0);
#pragma unroll
            for (int q = 3; q < 8; q++) {
                const uint32_t ws = (0x4210u >> (4 * (q & 3))) & 15, as = (0x635u >> (4 * (q % 3))) & 15;
                mbar_wait(sb + BAR_FULL + 8 * as, (q / 3) & 1);
                bar_sync(1 + wg, 256);
                if (q == 3) gemm_issue<false>(s, kd + wg * 512 + as * (SLOT / 16), wd + ws * (SLOT / 16), 1, false);
                else if (q == 4) gemm_issue<true>(o, kd + wg * 512 + as * (SLOT / 16), wd + ws * (SLOT / 16), 0, false);
                else gemm_issue<false>(o, kd + wg * 512 + as * (SLOT / 16), wd + ws * (SLOT / 16), 1, false);
                bar_arrive(2 - wg, 256);
                sched_fence(fph, P.zero);
                if (q > 3) reg_fence(s);
                if (q == 3) {
#pragma unroll
                    for (int i = 0; i < 4; i++)
                        asm volatile("ld.global.nc.v4.u32 {%0, %1, %2, %3}, [%4];" : "=r"(x[4 * i]), "=r"(x[4 * i + 1]), "=r"(x[4 * i + 2]), "=r"(x[4 * i + 3])
                                     : "l"(xp + lane + 32 * i) : "memory");
#pragma unroll
                    for (int i = 0; i < 2; i++) asm volatile("ld.global.nc.u32 %0, [%1];" : "=r"(x0[i]) : "l"(xp + 64 * i) : "memory");
                }
                if (q == 4) {
                    img_store_global<0>(img, toff, s, sc, sc);
#pragma unroll
                    for (int k = 0; k < 16; k++) {
                        const float d0 = bf_lo(x[k]) - bf_lo(x0[k >> 3]), d1 = bf_hi(x[k]) - bf_lo(x0[k >> 3]);
                        st[k >> 3] += d0 + d1;
                        st[2 + (k >> 3)] = fmaf(d0, d0, fmaf(d1, d1, st[2 + (k >> 3)]));
                    }
#pragma unroll
                    for (int i = 0; i < 4 * NSH; i++) st[i & 3] += __shfl_xor_sync(0xffffffffu, st[i & 3], 1 << (i >> 2));
                    reg_fence(st);
                }
                if (q == 5) {
#pragma unroll
                    for (int i = 4 * NSH; i < 20; i++) st[i & 3] += __shfl_xor_sync(0xffffffffu, st[i & 3], 1 << (i >> 2));
                    img_store_global<1>(img, toff, s, sc, sc);
#pragma unroll
                    for (int i = 0; i < 2; i++) {
                        const float d = st[i] * (1.f / 512.f);
                        st[2 + i] = ln_rstd(fmaxf(fmaf(-d, d, st[2 + i] * (1.f / 512.f)), 0.f));
                        x0[i] = pack2(bf_lo(x0[i]) + d, bf_lo(x0[i]) + d);
                    }
                    reg_fence(st);
                    reg_fence(x0);
                }
                if (q > 5) {
                    if (q == 6) mbar_wait(sb + BAR_FLAG + 8 * 8, 0);
                    const uint4 a = lds128(sb + SM_TAB + 1024 + (q & 1) * 512 + lane * 16), c = lds128(sb + SM_TAB + (q & 1) * 512 + lane * 16);
                    uint8_t* hp = g_h + (grp * 8 + (q & 1) * 4 + (lane >> 3)) * 16384 + (xrow & 127) * 128;
#pragma unroll
                    for (int i = 0; i < 2; i++) {
                        const uint32_t* y = x + 8 * i + 4 * (q & 1);
                        *reinterpret_cast<uint4*>(hp + i * 128 + (((lane ^ xrow ^ i) & 7) << 4)) =
                            make_uint4(ln_apply(y[0], x0[i], st[2 + i], a.x, c.x), ln_apply(y[1], x0[i], st[2 + i], a.y, c.y),
                                       ln_apply(y[2], x0[i], st[2 + i], a.z, c.z), ln_apply(y[3], x0[i], st[2 + i], a.w, c.w));
                    }
                    if (q == 7) {
                        __syncwarp();
                        mbar_arrive_if(sb + BAR_DONE, lane == 0);
                    }
                    if (q == 6) img_store_global<2>(img, toff, s, sc, sc);
                    else img_store_global<3>(img, toff, s, sc, sc);
                }
                sched_fence(fph, P.zero);
                wg_wait<0>();
                release_if(eb, as, rel);
            }
            reg_fence(o);
        }
        uint32_t p[32] = {};
#pragma unroll 1
        for (int hp = 0; hp < 2; hp++) {
            float m[2] = {0.f, 0.f}, l[2] = {0.f, 0.f}, t[4] = {0.f, 0.f, 0.f, 0.f};
            bool shifted = false, bad = false, plain = false;
            uint32_t qa = desc_k(sb + 5 * SLOT + (wg ^ 1) * 8192);
            uint8_t* limg = g_ctx + (size_t)((15 - j) * 32 + 2 * grp + hp) * SLOT;
            {
                const int step = hp ? -8 * SLOT : 8 * SLOT;
                uint8_t* img = g_KV + (size_t)(grp * 32 + (hp ? j ^ 30 : j) + 8) * SLOT;
                const uint32_t wtab = w_table(hp);
                uint32_t atab = hp ? 0x562u : 0x356u;
#pragma unroll 1
                for (int u = 2 - 2 * hp;; u += 2) {
                    proj_tile<false>(s, o, u, !u, sb, wg, eb, rel, fph, wtab, atab, u ? img : cimg, toff, u ? sc : li[0], u ? sc : li[1], p);
                    __syncwarp();
                    mbar_arrive_if(sb + BAR_DONE + 4 * u + 32 * hp, lane == 0);
                    if (elected) TS(1 + 10 * hp + u + 20 * wg);
                    if (proj_tile<true>(o, s, u + 1, 0, sb, wg, eb, rel, fph, wtab, atab, img + step, toff, sc, sc, p)) break;
                    if (elected) TS(2 + 10 * hp + u + 20 * wg);
                    img += 2 * step;
                }
            }
            if (elected) TS(6 + 10 * hp + 20 * wg);
            int n = -1;
#pragma unroll 1
            for (;;) {
                while (bad || plain) {
                    if (bad) {
                        float a0, a1;
                        softmax_remax(s, m, n == 0 || n == nL, a0, a1);
                        shifted = true;
                        l[0] *= a0;
                        l[1] *= a1;
#pragma unroll
                        for (int i = 0; i < 64; i++) o[i] *= (i & 2) ? a1 : a0;
                    }
                    softmax_exp<0, 16>(s, p, t);
                    t[0] += t[1];
                    t[2] += t[3];
                    bad = !bad && softmax_unsafe(t[0], t[2], false);
                    plain = false;
                }
#pragma unroll 1
                do {
                    l[0] += t[0];
                    l[1] += t[2];
                    if (++n > 16) break;
                    const uint32_t ks = r;
                    uint32_t vs = ring_next(r);
                    r = ring_next(vs);
                    bar_sync(1 + wg, 256);
                    const float x = (float)((warp & 3) * 16 + g - 2 * c4);
                    if (n == hn) {
                        float sh[32];
                        qk_issue(sh, qa, kd + ks * (SLOT / 16));
                        slot_wait(sb + BAR_FULL, fph, vs);
                        pv_issue(o, p, vd + vs * (SLOT / 16), 1, false);
                        bar_arrive(2 - wg, 256);
                        wg_wait<1>();
                        reg_fence(sh);
                        tri_mask_copy(s, sh, x);
                        release_if(eb, ks, rel);
                        release_if(eb, 5 + wg, rel && (!wg || n == 16));
                        if (!wg) {
                            qa += SLOT / 16;
                            fence_async_smem();
                            if (shifted) softmax_shift(s, m[0], m[1]);
                        }
                        float e[4 * EARLY];
#pragma unroll
                        for (int i = 0; i < 4 * EARLY; i++) {
                            e[i] = ex2(s[i]);
                            t[i & 3] = i < 4 ? e[i] : t[i & 3] + e[i];
                        }
                        reg_fence(e);
                        slot_wait(sb + BAR_FULL, fph, r);
                        wg_wait<0>();
                        reg_fence(o);
                        reg_fence(e);
                        release_if(eb, vs, rel);
#pragma unroll
                        for (int i = 0; i < 2 * EARLY; i++) p[i] = pack2(e[2 * i], e[2 * i + 1]);
                        softmax_exp<EARLY, 8>(s, p, t);
                        if (wg) {
                            ctx_store<true>(limg, toff, o, l[0], l[1]);
                            __syncwarp();
                            mbar_arrive_if(sb + BAR_DONE + 24 + 32 * hp, lane == 0);
                            l[0] = l[1] = m[0] = m[1] = 0.f;
                            shifted = false;
                        }
                        t[0] += t[1];
                        t[2] += t[3];
                        bad = softmax_unsafe(t[0], t[2], wg);
                        continue;
                    }
                    if (n == 0 || n == nL) {
                        qk_issue(s, qa, kd + ks * (SLOT / 16));
                        if (n == 0) {
                            r = vs;
                            vs = 4 - hp;
                            slot_wait(sb + BAR_FULL, fph, 6);
                            gemm_issue<false>(o, qa + SLOT / 16, wd + vs * (SLOT / 16), 1, false);
                        } else {
                            slot_wait(sb + BAR_FULL, fph, vs);
                            pv_issue(o, p, vd + vs * (SLOT / 16), 1, true);
                        }
                        bar_arrive(2 - wg, 256);
                        const float i0 = n ? rcp(quad_sum(l[0])) : 1.f, i1 = n ? rcp(quad_sum(l[1])) : 1.f;
                        wg_wait<1>();
                        reg_fence(s);
                        release_if(eb, ks, rel);
                        release_if(eb, 6, rel && n == 16);
                        tri_mask(s, n ? x : 64.f);
                        float e[4 * EARLY];
#pragma unroll
                        for (int i = 0; i < 4 * EARLY; i++) {
                            e[i] = ex2(s[i]);
                            t[i & 3] = i < 4 ? e[i] : t[i & 3] + e[i];
                        }
                        reg_fence(e);
                        reg_fence(s);
                        reg_fence(t);
                        slot_wait(sb + BAR_FULL, fph, r);
                        if (SF & 1) sched_fence(fph, P.zero);
                        wg_wait<0>();
                        reg_fence(o);
                        reg_fence(e);
                        release_if(eb, vs, rel);
#pragma unroll
                        for (int i = 0; i < 2 * EARLY; i++) p[i] = pack2(e[2 * i], e[2 * i + 1]);
                        softmax_exp<EARLY, MSPLIT>(s, p, t);
                        tile_store(limg, sb + 6 * SLOT, toff, o, i0, i1, n);
                        reg_fence(t);
                        if (SF & 2) sched_fence(fph, P.zero);
                        reg_fence(s);
                        softmax_exp<MSPLIT, 16>(s, p, t);
                        __syncwarp();
                        mbar_arrive_if(sb + BAR_DONE + 24 + 32 * hp, lane == 0 && n);
                        l[0] = l[1] = m[0] = m[1] = 0.f;
                        shifted = false;
                        t[0] += t[1];
                        t[2] += t[3];
                        bad = __any_sync(0xffffffffu, fmaxf(t[0], t[2]) > SM_HI || fminf(t[0], t[2]) < SM_LO);
                        continue;
                    }
                    qk_issue(s, qa, kd + ks * (SLOT / 16));
                    slot_wait(sb + BAR_FULL, fph, vs);
                    pv_issue(o, p, vd + vs * (SLOT / 16), n != 1 && n != nL + 1, n == hn + 1);
                    bar_arrive(2 - wg, 256);
                    wg_wait<1>();
                    reg_fence(s);
                    release_if(eb, ks, rel);
                    release_if(eb, 6, rel && n == 16);
                    if (n == nL - 1) {
                        tri_mask(s, x);
                        release_if(eb, 5, rel);
                        qa += SLOT / 16;
                        fence_async_smem();
                    }
                    if (shifted) {
                        slot_wait(sb + BAR_FULL, fph, r);
                        wg_wait<0>();
                        reg_fence(o);
                        release_if(eb, vs, rel);
                        softmax_shift(s, m[0], m[1]);
                        plain = true;
                        break;
                    }
                    float e[4 * EARLY];
#pragma unroll
                    for (int i = 0; i < 4 * EARLY; i++) {
                        e[i] = ex2(s[i]);
                        t[i & 3] = i < 4 ? e[i] : t[i & 3] + e[i];
                    }
                    reg_fence(e);
                    slot_wait(sb + BAR_FULL, fph, r);
                    wg_wait<0>();
                    reg_fence(o);
                    reg_fence(e);
                    release_if(eb, vs, rel);
#pragma unroll
                    for (int i = 0; i < 2 * EARLY; i++) p[i] = pack2(e[2 * i], e[2 * i + 1]);
                    softmax_exp<EARLY, 16>(s, p, t);
                    t[0] += t[1];
                    t[2] += t[3];
                    bad = softmax_unsafe(t[0], t[2], false);
                } while (!bad);
                if (!bad && !plain) break;
            }
            const uint32_t vs = r, ga = desc_k(sb + (hp ? 2 * (wg ^ kh ^ 1) : wg) * 8192);
            r = ring_next(r);
            slot_wait(sb + BAR_FULL, fph, 5);
            slot_wait(sb + BAR_FULL, fph, r);
            bar_sync(1 + wg, 256);
            gemm_issue<true>(s, ga + 5 * (SLOT / 16), wd + r * (SLOT / 16), 0, hp);
            pv_issue(o, p, vd + vs * (SLOT / 16), j, hn == 16);
            bar_arrive(2 - wg, 256);
            li[0] = rcp(quad_sum(l[0]));
            li[1] = rcp(quad_sum(l[1]));
            cimg = limg + (ptrdiff_t)(2 * j - 15) * 32 * SLOT + (wg ? -16384 : 16384);
            wg_wait<1>();
            release_if(eb, 5, rel);
            release_if(eb, r, rel && hp);
            wg_wait<0>();
            release_if(eb, vs, rel);
            reg_fence(o);
            img_store_global<0>(cimg, toff, o, li[0], li[1]);
            if (elected) TS(8 + 10 * hp + 20 * wg);
        }
        uint32_t otab = 0x2351604u;
        const uint32_t oa = desc_k(sb + (wg ^ kh ^ 1) * 16384);
        const int t7 = tid & 127, w4 = warp & 3, row = ort * 128 + kh * 64 + w4 * 16 + g;
#pragma unroll 1
        for (int i = 1; i < 15 - wg; i++) {
            const uint32_t as = o_next(otab), ws = o_next(otab);
            slot_wait(sb + BAR_FULL, fph, as);
            slot_wait(sb + BAR_FULL, fph, ws);
            bar_sync(1 + wg, 256);
            gemm_issue<false>(s, oa + as * (SLOT / 16), wd + ws * (SLOT / 16), 1, true);
            bar_arrive(2 - wg, 256);
            wg_wait<1>();
            reg_fence(o);
            if (i == 1) img_store_global<1>(cimg, toff, o, li[0], li[1]);
            if (i == 2) {
                img_store_global<2>(cimg, toff, o, li[0], li[1]);
                img_store_global<3>(cimg, toff, o, li[0], li[1]);
                __syncwarp();
                mbar_arrive_if(sb + BAR_DONE + 64, lane == 0);
            }
            wg_wait<0>();
            release_if(eb, as, rel);
            release_if(eb, ws, rel);
        }
        mbar_wait(sb + BAR_PF, 0);
        const uint32_t ep = lds32(sb + SM_EP);
        uint32_t eb2 = sb + BAR_END;
        if (wg == 0) {
            reg_fence(s);
            if (elected) TS(9);
            TT(1);
#pragma unroll
            for (int v = 0; v < 8; v++)
                st_pub(g_out + rb * OB + v * 128 + t7, make_uint4((pack2(s[8 * v], s[8 * v + 1]) & ~1u) | (ep & 1), pack2(s[8 * v + 2], s[8 * v + 3]),
                                                                      pack2(s[8 * v + 4], s[8 * v + 5]), pack2(s[8 * v + 6], s[8 * v + 7])), true);
            constexpr uint32_t s1 = 5, s2 = 6;
            if (ELATE >= 0) bar_sync(4, 256);
            uint32_t wf[64];
            float wn[64];
            if (rb < NFFN) {
                slot_wait(sb + BAR_FULL, fph, s1);
                const uint32_t a = sb + s1 * SLOT + (w4 * 128 + (lane >> 4) * 8 + (lane & 7)) * 32 + (((lane >> 3) ^ (lane >> 2)) & 1) * 16;
#pragma unroll
                for (int i = 0; i < 16; i++)
                    asm volatile("ldmatrix.sync.aligned.m8n8.x4.trans.shared.b16 {%0, %1, %2, %3}, [%4];"
                                 : "=r"(wf[4 * i]), "=r"(wf[4 * i + 1]), "=r"(wf[4 * i + 2]), "=r"(wf[4 * i + 3])
                                 : "r"(a + (i >> 3) * 16384 + (i & 7) * 512) : "memory");
                slot_wait(sb + BAR_FULL, fph, s2);
#pragma unroll
                for (int i = 0; i < 16; i++) {
                    const uint2 w = *reinterpret_cast<const uint2*>(smem + s2 * SLOT + (kh ^ 1) * 16384 + i * 1024 + t7 * 8);
                    wn[4 * i] = bf_lo(w.x); wn[4 * i + 1] = bf_hi(w.x); wn[4 * i + 2] = bf_lo(w.y); wn[4 * i + 3] = bf_hi(w.y);
                }
                reg_fence(wn);
            }
            const uint32_t gbf = __ldcg(reinterpret_cast<const uint32_t*>(g_mod) + 1280 + rb * 2 + (tid & 1));
            if (elected) TS(10);
            TT(2);
            float* sred = reinterpret_cast<float*>(smem + SM_RED);
            uint32_t best = ep ^ 1, all;
            bool fresh;
            do {
                if (warp == 0) {
                    const uint2 k = best_key(g_key + cq * 128, lane, ep, best, rb < NFFN ? SPEC : 32);
                    *reinterpret_cast<uint2*>(smem + SM_EP + 24) = k;
                    mbar_arrive_if(sb + BAR_BEST, lane == 0 && k.y);
                }
                bar_sync(3, 128);
                const uint2 k = *reinterpret_cast<const uint2*>(smem + SM_EP + 24);
                fresh = k.x != best;
                best = k.x;
                all = k.y;
                TT(3);
                if (!fresh || rb >= NFFN) break;
                const uint4* cp = g_cand + ((~best >> 9) & 127) * 192;
                uint4 cv[6];
                for (;;) {
                    uint32_t bad = 0;
#pragma unroll
                    for (int v = 0; v < 6; v++) cv[v] = ld_poll(cp + w4 * 24 + v * 4 + c4);
#pragma unroll
                    for (int v = 0; v < 6; v++) bad |= cv[v].w ^ ep;
                    if (__all_sync(0xffffffffu, bad == 0)) break;
                    if (CSLEEP) __nanosleep(CSLEEP);
                }
            TT(4);
                float d[4][4] = {};
#pragma unroll
                for (int k = 0; k < 8; k++) {
                    const uint32_t b0 = (&cv[(2 * k) / 3].x)[(2 * k) % 3], b1 = (&cv[(2 * k + 1) / 3].x)[(2 * k + 1) % 3];
                    mma16816(d[k & 1], wf + 4 * k, b0, b1);
                    mma16816(d[2 + (k & 1)], wf + 32 + 4 * k, b0, b1);
                }
                const float u = (c4 & 2) ? ((c4 & 1) ? d[2][2] + d[3][2] : d[2][0] + d[3][0]) : ((c4 & 1) ? d[0][2] + d[1][2] : d[0][0] + d[1][0]);
                sred[w4 * 32 + c4 * 8 + g] = u;
                bar_sync(3, 128);
                const float v = rbf((sred[lane] + sred[32 + lane]) + (sred[64 + lane] + sred[96 + lane]));
                const float act = rbf(rbf(v * sigmoid(v)) * __shfl_down_sync(0xffffffffu, v, 16));
                float y[4] = {0.f, 0.f, 0.f, 0.f};
#pragma unroll
                for (int k = 0; k < 16; k++) {
                    const float a = __shfl_sync(0xffffffffu, act, k);
#pragma unroll
                    for (int i = 0; i < 4; i++) y[i] = fmaf(a, wn[4 * k + i], y[i]);
                }
                st_pub(g_out + rb * OB + OB_Y + t7, make_uint4((__float_as_uint(y[0]) & ~15u) | (ep & 15), (__float_as_uint(y[1]) & ~127u) | ((best >> 9) & 127),
                                                               __float_as_uint(y[2]), __float_as_uint(y[3])), true);
            } while (!all);
            const int sel = (~best >> 5) & 2047;
            const int pq = (2 * rb + (tid & 1)) & 63, pv = (pq >> 2) / 3;
            const uint4* fp = g_cand + (sel >> 4) * 192 + (rb >> 5) * 24 + pv * 4 + (pq & 3);
            uint4 fh = {}, fx = {};
            if (rb == 0 && tid == 0) g_sync.epoch[0] = ep;
            if (elected) TS(60);
            TT(5);
            uint4 yv;
            if (warp == 0) { fh = ld_poll(fp); fx = ld_poll(fp + 96); }
            if (fresh && rb < NFFN) __nanosleep(YPRE);
            for (;;) {
                yv = ld_poll(g_out + min(t7, NFFN - 1) * OB + OB_Y + rb);
                if (__all_sync(0xffffffffu, (((yv.x ^ ep) & 15) | ((yv.y ^ (best >> 9)) & 127)) == 0)) break;
                if (YSLEEP) __nanosleep(YSLEEP);
            }
            if (elected) TS(61);
            TT(6);
            float y[4] = {0.f, 0.f, 0.f, 0.f};
            if (t7 < NFFN) { y[0] = __uint_as_float(yv.x); y[1] = __uint_as_float(yv.y); y[2] = __uint_as_float(yv.z); y[3] = __uint_as_float(yv.w); }
            const float z0 = ((lane & 16) ? y[2] : y[0]) + __shfl_xor_sync(0xffffffffu, (lane & 16) ? y[0] : y[2], 16);
            const float z1 = ((lane & 16) ? y[3] : y[1]) + __shfl_xor_sync(0xffffffffu, (lane & 16) ? y[1] : y[3], 16);
            float z = ((lane & 8) ? z1 : z0) + __shfl_xor_sync(0xffffffffu, (lane & 8) ? z0 : z1, 8);
            z += __shfl_xor_sync(0xffffffffu, z, 4);
            z = quad_sum(z);
            if ((lane & 7) == 0) sred[128 + (lane >> 3) * 4 + w4] = z;
            bar_sync(3, 128);
            if (tid < 2) {
                while (fh.w != ep || fx.w != ep) { fh = ld_poll(fp); fx = ld_poll(fp + 96); }
                const float4 y0 = *reinterpret_cast<const float4*>(sred + 128 + tid * 8), y1 = *reinterpret_cast<const float4*>(sred + 132 + tid * 8);
                const int cm = (pq >> 2) - 3 * pv;
                const uint32_t h2 = cm == 0 ? fh.x : cm == 1 ? fh.y : fh.z, x2 = cm == 0 ? fx.x : cm == 1 ? fx.y : fx.z;
                const float sg = sigmoid(bf_hi((best & 0x80000000u) ? (best ^ 0x80000000u) : ~best));
                reinterpret_cast<uint32_t*>(P.out)[sel * 256 + rb * 2 + tid] =
                    badd(x2, bmul(gbf, badd(h2, bmul(pack2((y0.x + y0.y) + (y0.z + y0.w), (y1.x + y1.y) + (y1.z + y1.w)), pack2(sg, sg)))));
            }
            if (elected) TS(62);
            TT(7);
        } else {
            const float4* tf = reinterpret_cast<const float4*>(smem + SM_TAB) + c4;
            const uint32_t xa = sb + 4 * SLOT + (kh ^ 1) * 16384 + (w4 * 16 + (lane & 15)) * 128;
            uint32_t x2[32];
            bar_sync(2, 256);
#pragma unroll 1
            for (int i = 14; i < 17; i++) {
                const uint32_t as = o_next(otab), ws = o_next(otab);
                slot_wait(sb + BAR_FULL, fph, as);
                slot_wait(sb + BAR_FULL, fph, ws);
                gemm_issue<false>(s, oa + as * (SLOT / 16), wd + ws * (SLOT / 16), 1, true);
                wg_wait<1>();
            }
            const uint4* pr = g_out + (rb ^ (8 * OMAP)) * OB + t7;
            uint4 pa[8];
            if (PEARLY) {
#pragma unroll
                for (int v = 0; v < 8; v++) pa[v] = ld_poll(pr + v * 128);
            }
            if (elected) TS(29);
            TT(1);
            {
#pragma unroll
                for (int k = 0; k < 8; k++)
                    asm volatile("ldmatrix.sync.aligned.m8n8.x4.shared.b16 {%0, %1, %2, %3}, [%4];"
                                 : "=r"(x2[4 * k]), "=r"(x2[4 * k + 1]), "=r"(x2[4 * k + 2]), "=r"(x2[4 * k + 3])
                                 : "r"(xa + (k >> 2) * 8192 + (((2 * (k & 3) + (lane >> 4)) ^ (lane & 7)) << 4)) : "memory");
            }
            wg_wait<0>();
            reg_fence(s);
            if (!ELATE) bar_arrive(4, 256);
            if (elected) TS(39);
            TT(2);
            if (!PEARLY) {
#pragma unroll
                for (int v = 0; v < 8; v++) pa[v] = ld_poll(pr + v * 128);
            }
            float4 tc[16];
#pragma unroll
            for (int k = 0; k < 16; k++) {
                tc[k] = tf[k * 4];
                if (!(g & 1)) tc[k].z = __uint_as_float(ONE2);
#pragma unroll
                for (int i = 4 * k; i < 4 * k + 4; i++) s[i] = fmaf((i & 1) ? tc[k].y : tc[k].x, s[i], (i & 1) ? bf_hi(x2[i >> 1]) : bf_lo(x2[i >> 1]));
            }
            reg_fence(s);
            for (;;) {
                uint32_t bad = 0;
#pragma unroll
                for (int v = 0; v < 8; v++) bad |= pa[v].x ^ ep;
                if (__all_sync(0xffffffffu, (bad & 1) == 0)) break;
                if (PSLEEP) __nanosleep(PSLEEP);
#pragma unroll
                for (int v = 0; v < 8; v++) pa[v] = ld_poll(pr + v * 128);
            }
            if (ELATE == 1) bar_arrive(4, 256);
            if (elected) TS(30);
            TT(3);
            float sd[4] = {}, q0[4] = {}, q1[4] = {};
#pragma unroll
            for (int k = 0; k < 8; k++) {
#pragma unroll
                for (int i = 4 * k; i < 4 * k + 4; i++) {
                    const uint32_t w = (&pa[k].x)[i & 3];
                    x2[i] = pack2(fmaf(tc[i >> 1].x, bf_lo(w), s[2 * i]), fmaf(tc[i >> 1].y, bf_hi(w), s[2 * i + 1]));
                }
                mma16816(sd, x2 + 4 * k, __float_as_uint(tc[2 * k].z), __float_as_uint(tc[2 * k + 1].z));
                mma16816(q0, x2 + 4 * k, x2[4 * k], x2[4 * k + 2]);
                mma16816(q1, x2 + 4 * k, x2[4 * k + 1], x2[4 * k + 3]);
            }
            uint4* sp = g_out + rb * OB + OB_STAT + (w4 * 8 + g) * 2;
            st_pub(sp, make_uint4(__float_as_uint(sd[0]), __float_as_uint((g & 1) ? q0[1] : q0[0]), __float_as_uint(sd[1]), ep), c4 == g >> 1);
            st_pub(sp + 1, make_uint4(__float_as_uint(sd[2]), __float_as_uint((g & 1) ? q1[3] : q1[2]), __float_as_uint(sd[3]), ep), c4 == g >> 1);
            if (ELATE == 2) bar_arrive(4, 256);
            if (TF & 1) sched_fence(eb2, P.zero);
            if (elected) TS(56);
            TT(4);
            uint32_t cb[16], sh[16], gb[16];
#pragma unroll
            for (int i = 0; i < 16; i++) {
                const float4 c = tf[64 + i * 4];
                cb[i] = __float_as_uint(c.x); sh[i] = __float_as_uint(c.y); gb[i] = __float_as_uint(c.z);
            }
            const float ra = __uint_as_float(lds32(sb + SM_EP + 8)), rb0 = __uint_as_float(lds32(sb + SM_EP + 12));
            uint4 r0, r1;
            if (SPRE) __nanosleep(SPRE);
            for (;;) {
                r0 = ld_poll(g_out + ((rb & ~(16 * OMAP + 1)) + (c4 & 1) + (c4 & 2) * 8 * OMAP) * OB + OB_STAT + (w4 * 8 + g) * 2);
                r1 = ld_poll(g_out + ((rb & ~(16 * OMAP + 1)) + (c4 & 1) + (c4 & 2) * 8 * OMAP) * OB + OB_STAT + (w4 * 8 + g) * 2 + 1);
                if (__all_sync(0xffffffffu, r0.w == ep && r1.w == ep)) break;
                if (SSLEEP) __nanosleep(SSLEEP);
            }
            if (elected) TS(57);
            TT(5);
            const float m0 = quad_sum(__uint_as_float(r0.x)) * (1.f / 512.f), m1 = quad_sum(__uint_as_float(r1.x)) * (1.f / 512.f);
            const float rs0 = ln_rstd(fmaxf(fmaf(-m0, m0, quad_sum(__uint_as_float(r0.y)) * (1.f / 512.f)), 0.f));
            const float rs1 = ln_rstd(fmaxf(fmaf(-m1, m1, quad_sum(__uint_as_float(r1.y)) * (1.f / 512.f)), 0.f));
            const uint32_t mb0 = pack2(m0, m0), mb1 = pack2(m1, m1);
            const uint32_t lg = pack2(fmaf(rs0, fmaf(-bf_lo(mb0), ra, quad_sum(__uint_as_float(r0.z))), rb0),
                                      fmaf(rs1, fmaf(-bf_lo(mb1), ra, quad_sum(__uint_as_float(r1.z))), rb0));
            const uint32_t u0 = lg << 16, u1 = lg & 0xffff0000u;
            const uint32_t k0 = ((u0 ^ (((int)u0 >> 31) | 0x80000000u)) & 0xffff0000u) | ((2047 - row) << 5) | (ep & 31);
            const uint32_t k1 = ((u1 ^ (((int)u1 >> 31) | 0x80000000u)) & 0xffff0000u) | ((2039 - row) << 5) | (ep & 31);
            const uint32_t kb = __reduce_max_sync(0xffffffffu, max(k0, k1));
            st_pub(g_key + cq * 128 + (row >> 4), kb, lane == 0);
            const bool cand = kb == k0 || kb == k1;
            uint4* cp = g_cand + (row >> 4) * 192 + cq * 24 + c4;
#pragma unroll 1
            for (int it = 0; it < 3; it++) {
                bool put = it == 1 || !cand;
                if (it == 2) {
                    mbar_wait(sb + BAR_BEST, 0);
                    put = cand && lds32(sb + SM_EP + 24) != kb;
                }
                const bool hi = (kb == k1) != (it == 1);
                uint32_t cx[18], ch[18];
#pragma unroll
                for (int i = 0; i < 16; i++) {
                    cx[i] = hi ? x2[2 * i + 1] : x2[2 * i];
                    ch[i] = ln_apply(cx[i], hi ? mb1 : mb0, hi ? rs1 : rs0, cb[i], sh[i]);
                }
                cx[16] = cx[17] = ch[16] = ch[17] = 0;
#pragma unroll
                for (int v = 0; v < 6; v++) st_pub(cp + v * 4, make_uint4(ch[3 * v], ch[3 * v + 1], ch[3 * v + 2], ep), cand && it == 0);
                if (TF & 4) sched_fence(eb2, P.zero);
#pragma unroll
                for (int v = 0; v < 6; v++) st_pub(cp + 96 + v * 4, make_uint4(cx[3 * v], cx[3 * v + 1], cx[3 * v + 2], ep), cand && it == 0);
                if (it == 0) TT(6);
                uint2* op = reinterpret_cast<uint2*>(P.out) + (row + 8 * hi) * 128 + cq * 32 + (c4 & 1) * 2 + (c4 >> 1);
#pragma unroll
                for (int i = 0; i < 16; i += 2) {
                    const uint32_t v0 = badd(cx[i], bmul(gb[i], ch[i])), v1 = badd(cx[i + 1], bmul(gb[i + 1], ch[i + 1]));
                    const uint32_t rv = __shfl_xor_sync(0xffffffffu, (c4 & 1) ? v0 : v1, 1);
                    if (put) op[i * 2] = (c4 & 1) ? make_uint2(rv, v1) : make_uint2(v0, rv);
                }
            }
            if (elected) TS(59);
            TT(7);
        }
        mbar_arrive_if(eb2, lane == 0);
    }
}

typedef CUresult (*EncodeFn)(CUtensorMap*, CUtensorMapDataType, cuuint32_t, void*, const cuuint64_t*, const cuuint64_t*,
                             const cuuint32_t*, const cuuint32_t*, CUtensorMapInterleave, CUtensorMapSwizzle,
                             CUtensorMapL2promotion, CUtensorMapFloatOOBfill);

void make_2d(EncodeFn fn, CUtensorMap* m, const void* p, uint64_t cols, uint64_t rows, uint32_t bc, uint32_t br, CUtensorMapSwizzle sw) {
    cuuint64_t dims[2] = {cols, rows}, strides[1] = {cols * 2};
    cuuint32_t box[2] = {bc, br}, es[2] = {1, 1};
    fn(m, CU_TENSOR_MAP_DATA_TYPE_BFLOAT16, 2, const_cast<void*>(p), dims, strides, box, es, CU_TENSOR_MAP_INTERLEAVE_NONE,
       sw, CU_TENSOR_MAP_L2_PROMOTION_L2_128B, CU_TENSOR_MAP_FLOAT_OOB_FILL_NONE);
}
void make_3d(EncodeFn fn, CUtensorMap* m, const void* p, uint64_t cols, uint64_t rows, uint32_t br = 128, uint32_t nb = 2) {
    cuuint64_t dims[3] = {64, rows, cols / 64}, strides[2] = {cols * 2, 128};
    cuuint32_t box[3] = {64, br, nb}, es[3] = {1, 1, 1};
    fn(m, CU_TENSOR_MAP_DATA_TYPE_BFLOAT16, 3, const_cast<void*>(p), dims, strides, box, es, CU_TENSOR_MAP_INTERLEAVE_NONE,
       CU_TENSOR_MAP_SWIZZLE_128B, CU_TENSOR_MAP_L2_PROMOTION_L2_256B, CU_TENSOR_MAP_FLOAT_OOB_FILL_NONE);
}

}

extern "C" void kernel_launch(void* const* d_in, const int* in_sizes, int n_in, void* d_out, int out_size) {
    static EncodeFn fn = nullptr;
    if (!fn) {
        void* f = nullptr;
        cudaDriverEntryPointQueryResult st;
        cudaGetDriverEntryPoint("cuTensorMapEncodeTiled", &f, cudaEnableDefault, &st);
        fn = (EncodeFn)f;
        cudaFuncSetAttribute(fused_kernel, cudaFuncAttributeMaxDynamicSharedMemorySize, SMEM_BYTES);
    }
    CUtensorMap ckv, wq, wuk, wuv, wo, wg, wu, wm, xm;
    make_3d(fn, &ckv, d_in[1], 512, 2048, 128, 1);
    make_3d(fn, &xm, d_in[0], 512, 2048, 64);
    make_3d(fn, &wq, d_in[2], 4096, 512);
    make_3d(fn, &wuk, d_in[3], 4096, 512);
    make_3d(fn, &wuv, d_in[4], 4096, 512);
    make_3d(fn, &wo, d_in[5], 512, 4096);
    make_2d(fn, &wg, d_in[8], 1792, 512, 16, 256, CU_TENSOR_MAP_SWIZZLE_32B);
    make_2d(fn, &wu, d_in[9], 1792, 512, 16, 256, CU_TENSOR_MAP_SWIZZLE_32B);
    make_2d(fn, &wm, d_in[12], 3072, 512, 256, 64, CU_TENSOR_MAP_SWIZZLE_NONE);
    Params p;
    p.x = (const bf16*)d_in[0];
    p.ckv = (const bf16*)d_in[1];
    p.wo = (const bf16*)d_in[5];
    p.wr = (const bf16*)d_in[7];
    p.wdown = (const bf16*)d_in[10];
    p.c = (const bf16*)d_in[11];
    p.out = (bf16*)d_out;
    p.zero = 0;
    fused_kernel<<<NCTA + NSPARE, 384, SMEM_BYTES>>>(ckv, wq, wuk, wuv, wo, wg, wu, wm, xm, p);
}
```

```cpp
#include <cuda.h>
#include <cuda_bf16.h>
#include <cuda_runtime.h>
#include <stdint.h>
#include <stdio.h>

namespace {

typedef __nv_bfloat16 bf16;
typedef unsigned long long u64;

constexpr int NCTA = 128, NSPARE = 4;
constexpr int SLOT = 32768;
constexpr int SM_BAR = 7 * SLOT;
constexpr int BAR_FULL = SM_BAR;
constexpr int BAR_EMPTY = BAR_FULL + 8 * 7;
constexpr int BAR_DONE = BAR_EMPTY + 8 * 7;
constexpr int BAR_FLAG = BAR_DONE + 8 * 9;
constexpr int BAR_PF = BAR_FLAG + 8 * 9;
constexpr int BAR_END = BAR_PF + 8;
constexpr int BAR_BEST = BAR_END + 8;
constexpr int SM_EP = BAR_END + 40;
constexpr int SM_RED = SM_BAR + 384;
constexpr int SM_TAB = SM_BAR + 1024;
constexpr int SMEM_BYTES = SM_BAR + 3072;
constexpr int NFFN = 112;
#define HINT 479
constexpr u64 L2_NORMAL = 0x1000000000000000ull, L2_FIRST = 0x12F0000000000000ull;
#define PFA 8
#define PFB 6
#define UNR 1
#define POLL_NS 50
#define MSPLIT 13
#define SF 3
#define NSH 1
#define XPF 1
#define TF 1
#define KSLEEP 200
#define YSLEEP 50
#define YPRE 150
#define SSLEEP 50
#define SPRE 0
#define PSLEEP 100
#define CSLEEP 0
#define SPEC 28
#define OMAP 2
#define KVG 7
#define PEARLY 0
#define ELATE 0
#define MPRE 0
#define EARLY 7
constexpr uint32_t SPIN_LIMIT = 1u << 22;
constexpr uint32_t ONE2 = 0x3f803f80u;

struct Sync {
    uint32_t cnt[16 * 8 * 8];
    uint32_t ctxcnt[16 * 32];
    uint32_t epoch[32];
};

__device__ __align__(1024) uint8_t g_KV[16 * 16 * 2 * SLOT];
__device__ __align__(1024) uint8_t g_ctx[16 * 32 * SLOT];
__device__ __align__(1024) uint8_t g_h[16 * 4 * SLOT];
constexpr int OB = 1216, OB_STAT = 1024, OB_Y = 1088;
__device__ __align__(1024) uint4 g_out[128 * OB];
__device__ __align__(1024) bf16 g_mod[3072];
__device__ __align__(1024) uint32_t g_mod1[1024];
__device__ __align__(1024) uint4 g_cand[128 * 192];
__device__ __align__(1024) uint32_t g_key[4 * 128];
__device__ __align__(1024) uint8_t g_wf[NFFN * SLOT];
__device__ __align__(1024) Sync g_sync;
#define TS(i)

#define TT(i)
#define PT()

struct Params {
    const bf16 *x, *ckv, *wo, *wr, *wdown, *c;
    bf16* out;
    int zero;
};

__device__ __forceinline__ void mbar_init(uint32_t bar, uint32_t cnt) {
    asm volatile("mbarrier.init.shared::cta.b64 [%0], %1;" ::"r"(bar), "r"(cnt) : "memory");
}
__device__ __forceinline__ void mbar_wait(uint32_t bar, uint32_t parity) {
    asm volatile("{\n.reg .pred p;\nL_%=:\nmbarrier.try_wait.parity.shared::cta.b64 p, [%0], %1;\n@!p bra L_%=;\n}" ::"r"(bar), "r"(parity) : "memory");
}
__device__ __forceinline__ void mbar_sleep(uint32_t bar) {
    if ((threadIdx.x & 31) == 0)
        asm volatile("{\n.reg .pred p;\nL_%=:\nmbarrier.try_wait.parity.shared::cta.b64 p, [%0], 0, 100000;\n@!p bra L_%=;\n}" ::"r"(bar) : "memory");
    __syncwarp();
}
__device__ __forceinline__ void mbar_watch(uint32_t bar, uint32_t parity) {
    asm volatile("{\n.reg .pred p;\n.reg .u32 n;\nmov.u32 n, 0;\n"
                 "L_%=:\nmbarrier.try_wait.parity.shared::cta.b64 p, [%0], %1;\n@p bra D_%=;\n"
                 "add.u32 n, n, 1;\nsetp.lt.u32 p, n, %2;\n@p bra L_%=;\ntrap;\nD_%=:\n}"
                 ::"r"(bar), "r"(parity), "n"(SPIN_LIMIT) : "memory");
}
__device__ __forceinline__ void step_watch(uint32_t a, uint32_t step) {
    asm volatile("{\n.reg .pred p;\n.reg .u32 n, v;\nmov.u32 n, 0;\n"
                 "L_%=:\nld.volatile.shared.u32 v, [%0];\nsetp.ge.u32 p, v, %1;\n@p bra D_%=;\nnanosleep.u32 400;\n"
                 "add.u32 n, n, 1;\nsetp.lt.u32 p, n, %2;\n@p bra L_%=;\ntrap;\nD_%=:\n}"
                 ::"r"(a), "r"(step), "n"(SPIN_LIMIT) : "memory");
}
__device__ __forceinline__ void mbar_arrive_if(uint32_t bar, bool on) {
    asm volatile("{\n.reg .pred p;\nsetp.ne.s32 p, %1, 0;\n@p mbarrier.arrive.shared::cta.b64 _, [%0];\n}" ::"r"(bar), "r"((int)on) : "memory");
}
__device__ __forceinline__ void tma2d(uint32_t dst, const CUtensorMap* m, int c0, int c1, uint32_t bar, bool first) {
    asm volatile("{\n.reg .pred p;\nelect.sync _|p, 0xffffffff;\n"
                 "@p cp.async.bulk.tensor.2d.shared::cluster.global.mbarrier::complete_tx::bytes.L2::cache_hint [%0], [%1, {%3, %4}], [%2], %5;\n}"
                 ::"r"(dst), "l"(m), "r"(bar), "r"(c0), "r"(c1), "l"(first ? L2_FIRST : L2_NORMAL) : "memory");
}
__device__ __forceinline__ void tma3d_prefetch(const CUtensorMap* m, int row, int cb) {
    asm volatile("{\n.reg .pred p;\nelect.sync _|p, 0xffffffff;\n@p cp.async.bulk.prefetch.tensor.3d.L2.global [%0, {%1, %2, %3}];\n}"
                 ::"l"(m), "r"(0), "r"(row), "r"(cb) : "memory");
}
__device__ __forceinline__ void l2_prefetch(const void* p, uint32_t bytes) {
    asm volatile("{\n.reg .pred p;\nelect.sync _|p, 0xffffffff;\n@p cp.async.bulk.prefetch.L2.global [%0], %1;\n}" ::"l"(p), "r"(bytes) : "memory");
}
__device__ __forceinline__ void bulk_store(void* dst, uint32_t src, uint32_t bytes, bool first) {
    asm volatile("{\n.reg .pred p;\nelect.sync _|p, 0xffffffff;\n@p cp.async.bulk.global.shared::cta.bulk_group.L2::cache_hint [%0], [%1], %2, %3;\n}"
                 ::"l"(dst), "r"(src), "r"(bytes), "l"(first ? L2_FIRST : L2_NORMAL) : "memory");
}
__device__ __forceinline__ void flag_wait(const uint32_t* f, uint32_t target) {
    asm volatile("{\n.reg .pred p;\n.reg .u32 v;\n"
                 "L_%=:\nld.acquire.gpu.global.u32 v, [%0];\nsub.u32 v, v, %1;\nsetp.lt.s32 p, v, 0;\n@p nanosleep.u32 100;\n@p bra L_%=;\n}"
                 ::"l"(f), "r"(target) : "memory");
}
__device__ __forceinline__ uint4 ld_poll(const uint4* p) {
    uint4 v;
    asm volatile("{\n.reg .b128 t;\nld.relaxed.gpu.global.b128 t, [%4];\nmov.b128 {%0, %1, %2, %3}, t;\n}"
                 : "=r"(v.x), "=r"(v.y), "=r"(v.z), "=r"(v.w) : "l"(p) : "memory");
    return v;
}
__device__ __forceinline__ void st_pub(uint4* p, uint4 v, bool on) {
    asm volatile("{\n.reg .pred p;\n.reg .b128 t;\nsetp.ne.s32 p, %5, 0;\nmov.b128 t, {%1, %2, %3, %4};\n@p st.relaxed.gpu.global.b128 [%0], t;\n}"
                 ::"l"(p), "r"(v.x), "r"(v.y), "r"(v.z), "r"(v.w), "r"((int)on) : "memory");
}
__device__ __forceinline__ void st_pub(uint32_t* p, uint32_t v, bool on) {
    asm volatile("{\n.reg .pred p;\nsetp.ne.s32 p, %2, 0;\n@p st.relaxed.gpu.global.u32 [%0], %1;\n}" ::"l"(p), "r"(v), "r"((int)on) : "memory");
}
__device__ __forceinline__ void flag_add(uint32_t* p) {
    asm volatile("red.release.gpu.global.add.u32 [%0], 1;" ::"l"(p) : "memory");
}
__device__ __forceinline__ uint32_t lds32(uint32_t a) {
    uint32_t v;
    asm volatile("ld.shared.u32 %0, [%1];" : "=r"(v) : "r"(a) : "memory");
    return v;
}
__device__ __forceinline__ uint4 lds128(uint32_t a) {
    uint4 v;
    asm volatile("ld.shared.v4.u32 {%0, %1, %2, %3}, [%4];" : "=r"(v.x), "=r"(v.y), "=r"(v.z), "=r"(v.w) : "r"(a) : "memory");
    return v;
}
__device__ __forceinline__ void sched_fence(uint32_t& v, uint32_t z) {
    uint32_t ck;
    asm volatile("mov.u32 %0, %%clock;" : "=r"(ck)::"memory");
    v ^= ck & z;
}
__device__ __forceinline__ void fence_async_global() { asm volatile("fence.proxy.async.global;" ::: "memory"); }
__device__ __forceinline__ void fence_async_smem() { asm volatile("fence.proxy.async.shared::cta;" ::: "memory"); }
__device__ __forceinline__ void bar_sync(int id, int n) { asm volatile("bar.sync %0, %1;" ::"r"(id), "r"(n) : "memory"); }
__device__ __forceinline__ void bar_arrive(int id, int n) { asm volatile("bar.arrive %0, %1;" ::"r"(id), "r"(n) : "memory"); }
__device__ __forceinline__ void wg_fence() { asm volatile("wgmma.fence.sync.aligned;" ::: "memory"); }
__device__ __forceinline__ void wg_commit() { asm volatile("wgmma.commit_group.sync.aligned;" ::: "memory"); }
template <int N> __device__ __forceinline__ void wg_wait() { asm volatile("wgmma.wait_group.sync.aligned %0;" ::"n"(N) : "memory"); }
template <int N> __device__ __forceinline__ void reg_fence(float (&d)[N]) {
#pragma unroll
    for (int i = 0; i < N; i++) asm volatile("" : "+f"(d[i])::"memory");
}
template <int N> __device__ __forceinline__ void reg_fence(uint32_t (&d)[N]) {
#pragma unroll
    for (int i = 0; i < N; i++) asm volatile("" : "+r"(d[i])::"memory");
}
__device__ __forceinline__ uint32_t desc_k(uint32_t a) { return ((a & 0x3ffff) >> 4) | (1u << 16); }
__device__ __forceinline__ uint32_t desc_mn(uint32_t a) { return ((a & 0x3ffff) >> 4) | (1024u << 16); }

template <int TB>
__device__ __forceinline__ void wgmma_ss128(float (&d)[64], uint32_t da, uint32_t db, int acc, uint32_t ha = 0x40000040u, uint32_t hb = 0x40000040u) {
    asm volatile("{\n.reg .pred p;\n.reg .b64 a, b;\nsetp.ne.b32 p, %66, 0;\nmov.b64 a, {%64, %68};\nmov.b64 b, {%65, %69};\n"
        "wgmma.mma_async.sync.aligned.m64n128k16.f32.bf16.bf16 {%0, %1, %2, %3, %4, %5, %6, %7, %8, %9, %10, %11, %12, %13, %14, %15, %16, %17, %18, %19, %20, %21, %22, %23, %24, %25, %26, %27, %28, %29, %30, %31, %32, %33, %34, %35, %36, %37, %38, %39, %40, %41, %42, %43, %44, %45, %46, %47, %48, %49, %50, %51, %52, %53, %54, %55, %56, %57, %58, %59, %60, %61, %62, %63}, a, b, p, 1, 1, 0, %67;\n}"
        : "+f"(d[0]), "+f"(d[1]), "+f"(d[2]), "+f"(d[3]), "+f"(d[4]), "+f"(d[5]), "+f"(d[6]), "+f"(d[7]), "+f"(d[8]), "+f"(d[9]), "+f"(d[10]), "+f"(d[11]), "+f"(d[12]), "+f"(d[13]), "+f"(d[14]), "+f"(d[15]), "+f"(d[16]), "+f"(d[17]), "+f"(d[18]), "+f"(d[19]), "+f"(d[20]), "+f"(d[21]), "+f"(d[22]), "+f"(d[23]), "+f"(d[24]), "+f"(d[25]), "+f"(d[26]), "+f"(d[27]), "+f"(d[28]), "+f"(d[29]), "+f"(d[30]), "+f"(d[31]), "+f"(d[32]), "+f"(d[33]), "+f"(d[34]), "+f"(d[35]), "+f"(d[36]), "+f"(d[37]), "+f"(d[38]), "+f"(d[39]), "+f"(d[40]), "+f"(d[41]), "+f"(d[42]), "+f"(d[43]), "+f"(d[44]), "+f"(d[45]), "+f"(d[46]), "+f"(d[47]), "+f"(d[48]), "+f"(d[49]), "+f"(d[50]), "+f"(d[51]), "+f"(d[52]), "+f"(d[53]), "+f"(d[54]), "+f"(d[55]), "+f"(d[56]), "+f"(d[57]), "+f"(d[58]), "+f"(d[59]), "+f"(d[60]), "+f"(d[61]), "+f"(d[62]), "+f"(d[63])
        : "r"(da), "r"(db), "r"(acc), "n"(TB), "r"(ha), "r"(hb));
}
template <int TB>
__device__ __forceinline__ void wgmma_ss128_init(float (&d)[64], uint32_t da, uint32_t db, uint32_t ha = 0x40000040u, uint32_t hb = 0x40000040u) {
    asm volatile("{\n.reg .pred p;\n.reg .b64 a, b;\nsetp.ne.b32 p, 0, 0;\nmov.b64 a, {%64, %67};\nmov.b64 b, {%65, %68};\n"
        "wgmma.mma_async.sync.aligned.m64n128k16.f32.bf16.bf16 {%0, %1, %2, %3, %4, %5, %6, %7, %8, %9, %10, %11, %12, %13, %14, %15, %16, %17, %18, %19, %20, %21, %22, %23, %24, %25, %26, %27, %28, %29, %30, %31, %32, %33, %34, %35, %36, %37, %38, %39, %40, %41, %42, %43, %44, %45, %46, %47, %48, %49, %50, %51, %52, %53, %54, %55, %56, %57, %58, %59, %60, %61, %62, %63}, a, b, p, 1, 1, 0, %66;\n}"
        : "=f"(d[0]), "=f"(d[1]), "=f"(d[2]), "=f"(d[3]), "=f"(d[4]), "=f"(d[5]), "=f"(d[6]), "=f"(d[7]), "=f"(d[8]), "=f"(d[9]), "=f"(d[10]), "=f"(d[11]), "=f"(d[12]), "=f"(d[13]), "=f"(d[14]), "=f"(d[15]), "=f"(d[16]), "=f"(d[17]), "=f"(d[18]), "=f"(d[19]), "=f"(d[20]), "=f"(d[21]), "=f"(d[22]), "=f"(d[23]), "=f"(d[24]), "=f"(d[25]), "=f"(d[26]), "=f"(d[27]), "=f"(d[28]), "=f"(d[29]), "=f"(d[30]), "=f"(d[31]), "=f"(d[32]), "=f"(d[33]), "=f"(d[34]), "=f"(d[35]), "=f"(d[36]), "=f"(d[37]), "=f"(d[38]), "=f"(d[39]), "=f"(d[40]), "=f"(d[41]), "=f"(d[42]), "=f"(d[43]), "=f"(d[44]), "=f"(d[45]), "=f"(d[46]), "=f"(d[47]), "=f"(d[48]), "=f"(d[49]), "=f"(d[50]), "=f"(d[51]), "=f"(d[52]), "=f"(d[53]), "=f"(d[54]), "=f"(d[55]), "=f"(d[56]), "=f"(d[57]), "=f"(d[58]), "=f"(d[59]), "=f"(d[60]), "=f"(d[61]), "=f"(d[62]), "=f"(d[63])
        : "r"(da), "r"(db), "n"(TB), "r"(ha), "r"(hb));
}
template <int TB>
__device__ __forceinline__ void wgmma_ss64(float (&d)[32], uint32_t da, uint32_t db, int acc, uint32_t ha = 0x40000040u, uint32_t hb = 0x40000040u) {
    asm volatile("{\n.reg .pred p;\n.reg .b64 a, b;\nsetp.ne.b32 p, %34, 0;\nmov.b64 a, {%32, %36};\nmov.b64 b, {%33, %37};\n"
        "wgmma.mma_async.sync.aligned.m64n64k16.f32.bf16.bf16 {%0, %1, %2, %3, %4, %5, %6, %7, %8, %9, %10, %11, %12, %13, %14, %15, %16, %17, %18, %19, %20, %21, %22, %23, %24, %25, %26, %27, %28, %29, %30, %31}, a, b, p, 1, 1, 0, %35;\n}"
        : "+f"(d[0]), "+f"(d[1]), "+f"(d[2]), "+f"(d[3]), "+f"(d[4]), "+f"(d[5]), "+f"(d[6]), "+f"(d[7]), "+f"(d[8]), "+f"(d[9]), "+f"(d[10]), "+f"(d[11]), "+f"(d[12]), "+f"(d[13]), "+f"(d[14]), "+f"(d[15]), "+f"(d[16]), "+f"(d[17]), "+f"(d[18]), "+f"(d[19]), "+f"(d[20]), "+f"(d[21]), "+f"(d[22]), "+f"(d[23]), "+f"(d[24]), "+f"(d[25]), "+f"(d[26]), "+f"(d[27]), "+f"(d[28]), "+f"(d[29]), "+f"(d[30]), "+f"(d[31])
        : "r"(da), "r"(db), "r"(acc), "n"(TB), "r"(ha), "r"(hb));
}
template <int TB>
__device__ __forceinline__ void wgmma_ss64_init(float (&d)[32], uint32_t da, uint32_t db, uint32_t ha = 0x40000040u, uint32_t hb = 0x40000040u) {
    asm volatile("{\n.reg .pred p;\n.reg .b64 a, b;\nsetp.ne.b32 p, 0, 0;\nmov.b64 a, {%32, %35};\nmov.b64 b, {%33, %36};\n"
        "wgmma.mma_async.sync.aligned.m64n64k16.f32.bf16.bf16 {%0, %1, %2, %3, %4, %5, %6, %7, %8, %9, %10, %11, %12, %13, %14, %15, %16, %17, %18, %19, %20, %21, %22, %23, %24, %25, %26, %27, %28, %29, %30, %31}, a, b, p, 1, 1, 0, %34;\n}"
        : "=f"(d[0]), "=f"(d[1]), "=f"(d[2]), "=f"(d[3]), "=f"(d[4]), "=f"(d[5]), "=f"(d[6]), "=f"(d[7]), "=f"(d[8]), "=f"(d[9]), "=f"(d[10]), "=f"(d[11]), "=f"(d[12]), "=f"(d[13]), "=f"(d[14]), "=f"(d[15]), "=f"(d[16]), "=f"(d[17]), "=f"(d[18]), "=f"(d[19]), "=f"(d[20]), "=f"(d[21]), "=f"(d[22]), "=f"(d[23]), "=f"(d[24]), "=f"(d[25]), "=f"(d[26]), "=f"(d[27]), "=f"(d[28]), "=f"(d[29]), "=f"(d[30]), "=f"(d[31])
        : "r"(da), "r"(db), "n"(TB), "r"(ha), "r"(hb));
}
__device__ __forceinline__ void wgmma_rs128(float (&d)[64], uint32_t a0, uint32_t a1, uint32_t a2, uint32_t a3, uint32_t db, int acc, uint32_t hb = 0x40000040u) {
    asm volatile("{\n.reg .pred p;\n.reg .b64 b;\nsetp.ne.b32 p, %69, 0;\nmov.b64 b, {%68, %70};\n"
        "wgmma.mma_async.sync.aligned.m64n128k16.f32.bf16.bf16 {%0, %1, %2, %3, %4, %5, %6, %7, %8, %9, %10, %11, %12, %13, %14, %15, %16, %17, %18, %19, %20, %21, %22, %23, %24, %25, %26, %27, %28, %29, %30, %31, %32, %33, %34, %35, %36, %37, %38, %39, %40, %41, %42, %43, %44, %45, %46, %47, %48, %49, %50, %51, %52, %53, %54, %55, %56, %57, %58, %59, %60, %61, %62, %63}, {%64, %65, %66, %67}, b, p, 1, 1, 1;\n}"
        : "+f"(d[0]), "+f"(d[1]), "+f"(d[2]), "+f"(d[3]), "+f"(d[4]), "+f"(d[5]), "+f"(d[6]), "+f"(d[7]), "+f"(d[8]), "+f"(d[9]), "+f"(d[10]), "+f"(d[11]), "+f"(d[12]), "+f"(d[13]), "+f"(d[14]), "+f"(d[15]), "+f"(d[16]), "+f"(d[17]), "+f"(d[18]), "+f"(d[19]), "+f"(d[20]), "+f"(d[21]), "+f"(d[22]), "+f"(d[23]), "+f"(d[24]), "+f"(d[25]), "+f"(d[26]), "+f"(d[27]), "+f"(d[28]), "+f"(d[29]), "+f"(d[30]), "+f"(d[31]), "+f"(d[32]), "+f"(d[33]), "+f"(d[34]), "+f"(d[35]), "+f"(d[36]), "+f"(d[37]), "+f"(d[38]), "+f"(d[39]), "+f"(d[40]), "+f"(d[41]), "+f"(d[42]), "+f"(d[43]), "+f"(d[44]), "+f"(d[45]), "+f"(d[46]), "+f"(d[47]), "+f"(d[48]), "+f"(d[49]), "+f"(d[50]), "+f"(d[51]), "+f"(d[52]), "+f"(d[53]), "+f"(d[54]), "+f"(d[55]), "+f"(d[56]), "+f"(d[57]), "+f"(d[58]), "+f"(d[59]), "+f"(d[60]), "+f"(d[61]), "+f"(d[62]), "+f"(d[63])
        : "r"(a0), "r"(a1), "r"(a2), "r"(a3), "r"(db), "r"(acc), "r"(hb));
}

__device__ __forceinline__ uint32_t pack2(float lo, float hi) {
    uint32_t r;
    asm("cvt.rn.bf16x2.f32 %0, %1, %2;" : "=r"(r) : "f"(hi), "f"(lo));
    return r;
}
__device__ __forceinline__ float bf_lo(uint32_t v) { return __uint_as_float(v << 16); }
__device__ __forceinline__ float bf_hi(uint32_t v) { return __uint_as_float(v & 0xffff0000u); }
__device__ __forceinline__ float rbf(float v) { return bf_lo(pack2(v, v)); }
__device__ __forceinline__ uint32_t badd(uint32_t a, uint32_t b) {
    uint32_t r;
    asm("add.rn.bf16x2 %0, %1, %2;" : "=r"(r) : "r"(a), "r"(b));
    return r;
}
__device__ __forceinline__ uint32_t bsub(uint32_t a, uint32_t b) {
    uint32_t r;
    asm("sub.rn.bf16x2 %0, %1, %2;" : "=r"(r) : "r"(a), "r"(b));
    return r;
}
__device__ __forceinline__ uint32_t bmul(uint32_t a, uint32_t b) {
    uint32_t r;
    asm("mul.rn.bf16x2 %0, %1, %2;" : "=r"(r) : "r"(a), "r"(b));
    return r;
}
__device__ __forceinline__ uint32_t ln_apply(uint32_t x, uint32_t mb, float rs, uint32_t scale, uint32_t shift) {
    const uint32_t d = bsub(x, mb);
    return badd(bmul(pack2(bf_lo(d) * rs, bf_hi(d) * rs), scale), shift);
}
__device__ __forceinline__ float ex2(float v) {
    float r;
    asm("ex2.approx.ftz.f32 %0, %1;" : "=f"(r) : "f"(v));
    return r;
}
__device__ __forceinline__ float rcp(float v) {
    float r;
    asm("rcp.approx.ftz.f32 %0, %1;" : "=f"(r) : "f"(v));
    return r;
}
__device__ __forceinline__ float sqrt_fast(float v) {
    float r;
    asm("sqrt.approx.ftz.f32 %0, %1;" : "=f"(r) : "f"(v));
    return r;
}
__device__ __forceinline__ float ln_rstd(float var) { return rcp(rbf(sqrt_fast(rbf(rbf(var) + 1e-5f)))); }
__device__ __forceinline__ float sigmoid(float v) { return rcp(1.f + ex2(-1.4426950408889634f * v)); }
__device__ __forceinline__ float quad_sum(float v) {
    v += __shfl_xor_sync(0xffffffffu, v, 1);
    return v + __shfl_xor_sync(0xffffffffu, v, 2);
}

constexpr uint32_t HI_128 = 0x40000040u, HI_IMG = 0x80000080u, HI_Q = 0x80000040u;
template <int M, int RH>
__device__ __forceinline__ uint4 img_pack(const float (&d)[64], float s) {
    uint4 v;
    v.x = pack2(d[16 * M + 2 * RH] * s, d[16 * M + 2 * RH + 1] * s);
    v.y = pack2(d[16 * M + 4 + 2 * RH] * s, d[16 * M + 5 + 2 * RH] * s);
    v.z = pack2(d[16 * M + 8 + 2 * RH] * s, d[16 * M + 9 + 2 * RH] * s);
    v.w = pack2(d[16 * M + 12 + 2 * RH] * s, d[16 * M + 13 + 2 * RH] * s);
    return v;
}
template <int M>
__device__ __forceinline__ void img_store_global(uint8_t* img, uint32_t toff, const float (&d)[64], float s0, float s1) {
    uint4* p = reinterpret_cast<uint4*>(img + toff) + M * 32;
    p[0] = img_pack<M, 0>(d, s0);
    p[128] = img_pack<M, 1>(d, s1);
}
__device__ __forceinline__ void sts128(uint32_t a, uint4 v) {
    asm volatile("st.shared.v4.b32 [%0], {%1, %2, %3, %4};" ::"r"(a), "r"(v.x), "r"(v.y), "r"(v.z), "r"(v.w) : "memory");
}
constexpr float SM_C = 0.08838834764831845f * 1.4426950408889634f;
__device__ __forceinline__ float pack2f(float lo, float hi) {
    float r;
    asm("{\n.reg .b32 t;\ncvt.rn.bf16x2.f32 t, %1, %2;\nmov.b32 %0, t;\n}" : "=f"(r) : "f"(hi), "f"(lo));
    return r;
}
template <int M, bool SCALE, bool PARK>
__device__ __forceinline__ void pack_group(float (&d)[64], float (&v)[8], float s0, float s1) {
#pragma unroll
    for (int i = 0; i < 8; i++) {
        const int k = 16 * M + 4 * (i & 3) + 2 * (i >> 2);
        v[i] = SCALE ? pack2f(d[k] * (i < 4 ? s0 : s1), d[k + 1] * (i < 4 ? s0 : s1)) : pack2f(d[k], d[k + 1]);
        if (PARK && M > 0) d[16 * (M > 0 ? M - 1 : 0) + i] = v[i];
    }
}
__device__ __forceinline__ uint32_t q_off(uint32_t toff) { return (((toff >> 1) & ~2047u) ^ 8192) + (toff & 511); }
template <int M, bool PARK>
__device__ __forceinline__ void ctx_store_part(float4* p, float (&d)[64], float i0, float i1) {
    float v[8];
    pack_group<M, true, PARK>(d, v, i0, i1);
    p[M * 32] = make_float4(v[0], v[1], v[2], v[3]);
    p[M * 32 + 128] = make_float4(v[4], v[5], v[6], v[7]);
}
template <bool PARK>
__device__ __forceinline__ void ctx_store(uint8_t* img, uint32_t toff, float (&o)[64], float l0, float l1) {
    const float i0 = rcp(quad_sum(l0)), i1 = rcp(quad_sum(l1));
    float4* p = reinterpret_cast<float4*>(img + toff);
    ctx_store_part<0, PARK>(p, o, i0, i1); ctx_store_part<1, PARK>(p, o, i0, i1); ctx_store_part<2, PARK>(p, o, i0, i1); ctx_store_part<3, PARK>(p, o, i0, i1);
}

template <int M>
__device__ __forceinline__ void tile_store_part(float4* p, uint32_t a, float (&d)[64], float i0, float i1, int ctx) {
    float v[8];
    pack_group<M, true, true>(d, v, i0, i1);
#pragma unroll
    for (int h = 0; h < 2; h++)
        asm volatile("{\n.reg .pred p;\nsetp.ne.s32 p, %6, 0;\n@p st.global.v4.f32 [%0], {%2, %3, %4, %5};\n@!p st.shared.v4.f32 [%1], {%2, %3, %4, %5};\n}"
                     ::"l"(p + M * 32 + h * 128), "r"(a + (M >> 1) * 16384 + (M & 1) * 512 + h * 1024),
                     "f"(v[4 * h]), "f"(v[4 * h + 1]), "f"(v[4 * h + 2]), "f"(v[4 * h + 3]), "r"(ctx) : "memory");
}
__device__ __forceinline__ void tile_store(uint8_t* img, uint32_t a, uint32_t toff, float (&d)[64], float i0, float i1, int ctx) {
    float4* p = reinterpret_cast<float4*>(img + toff);
    a += q_off(toff);
    tile_store_part<0>(p, a, d, i0, i1, ctx); tile_store_part<1>(p, a, d, i0, i1, ctx);
    tile_store_part<2>(p, a, d, i0, i1, ctx); tile_store_part<3>(p, a, d, i0, i1, ctx);
}

__device__ __forceinline__ void slot_wait(uint32_t bars, uint32_t& ph, uint32_t slot) {
    mbar_wait(bars + 8 * slot, (ph >> slot) & 1);
    ph ^= 1u << slot;
}
__device__ __forceinline__ void release_if(uint32_t eb, uint32_t slot, bool on) {
    asm volatile("{\n.reg .pred p;\nsetp.ne.s32 p, %1, 0;\n@p mbarrier.arrive.shared::cluster.b64 _, [%0];\n}" ::"r"(eb + 8 * slot), "r"((int)on) : "memory");
}
__device__ __forceinline__ void slot_expect(uint32_t sb, uint32_t slot) {
    asm volatile("{\n.reg .pred p;\nelect.sync _|p, 0xffffffff;\n@p mbarrier.arrive.expect_tx.shared::cta.b64 _, [%0], 32768;\n}"
                 ::"r"(sb + BAR_FULL + 8 * slot) : "memory");
}
__device__ __forceinline__ void slot_acquire(uint32_t sb, uint32_t& ph, uint32_t slot) {
    slot_wait(sb + BAR_EMPTY, ph, slot);
    slot_expect(sb, slot);
}
__device__ __forceinline__ void load_bulk(uint32_t sb, uint32_t slot, uint32_t off, const void* src, uint32_t bytes, bool both, bool first) {
    if (both)
        asm volatile("{\n.reg .pred p;\nelect.sync _|p, 0xffffffff;\n"
                     "@p cp.async.bulk.shared::cluster.global.mbarrier::complete_tx::bytes.multicast::cluster.L2::cache_hint [%0], [%1], %5, [%2], %4, %3;\n}"
                     ::"r"(sb + slot * SLOT + off), "l"(src), "r"(sb + BAR_FULL + 8 * slot), "l"(first ? L2_FIRST : L2_NORMAL), "h"((uint16_t)3),
                     "r"(bytes) : "memory");
    else
        asm volatile("{\n.reg .pred p;\nelect.sync _|p, 0xffffffff;\n"
                     "@p cp.async.bulk.shared::cluster.global.mbarrier::complete_tx::bytes.L2::cache_hint [%0], [%1], %4, [%2], %3;\n}"
                     ::"r"(sb + slot * SLOT + off), "l"(src), "r"(sb + BAR_FULL + 8 * slot), "l"(first ? L2_FIRST : L2_NORMAL), "r"(bytes) : "memory");
}
__device__ __forceinline__ void load_tile(uint32_t sb, uint32_t slot, uint32_t off, const CUtensorMap* m, int row, int cb, bool both, bool first) {
    if (both)
        asm volatile("{\n.reg .pred p;\nelect.sync _|p, 0xffffffff;\n"
                     "@p cp.async.bulk.tensor.3d.shared::cluster.global.mbarrier::complete_tx::bytes.multicast::cluster.L2::cache_hint [%0], [%1, {%3, %4, %5}], [%2], %7, %6;\n}"
                     ::"r"(sb + slot * SLOT + off), "l"(m), "r"(sb + BAR_FULL + 8 * slot), "r"(0), "r"(row), "r"(cb),
                     "l"(first ? L2_FIRST : L2_NORMAL), "h"((uint16_t)3) : "memory");
    else
        asm volatile("{\n.reg .pred p;\nelect.sync _|p, 0xffffffff;\n"
                     "@p cp.async.bulk.tensor.3d.shared::cluster.global.mbarrier::complete_tx::bytes.L2::cache_hint [%0], [%1, {%3, %4, %5}], [%2], %6;\n}"
                     ::"r"(sb + slot * SLOT + off), "l"(m), "r"(sb + BAR_FULL + 8 * slot), "r"(0), "r"(row), "r"(cb),
                     "l"(first ? L2_FIRST : L2_NORMAL) : "memory");
}
__device__ __forceinline__ uint32_t ring_next(uint32_t r) { return r == 4 ? 0 : r + 1; }
__device__ __forceinline__ uint32_t w_table(int hp) { return hp ? 0x3104u : 0x4210u; }
__device__ __forceinline__ uint32_t a_table(int hp) { return hp ? 0x625u : 0x635u; }
__device__ __forceinline__ uint32_t a_next(uint32_t& t) {
    const uint32_t s = t & 15;
    t = (t >> 4) | (s << 8);
    return s;
}
constexpr uint32_t O_TABLE = 0x1604235u;
__device__ __forceinline__ uint32_t o_next(uint32_t& t) {
    const uint32_t s = t & 15;
    t = (t >> 4) | (s << 24);
    return s;
}
__device__ __forceinline__ int o_head(int i, int kh) { return i < 16 ? 4 * (i & 7) + 2 * (kh ^ 1) + (i >> 3) : 29 + 2 * kh; }

template <bool INIT>
__device__ __forceinline__ void gemm_issue(float (&d)[64], uint32_t a, uint32_t b, int acc, bool img) {
    const uint32_t ha = img ? HI_IMG : HI_128, o2 = img ? 32 : 4, o4 = img ? 64 : 1024;
    wg_fence();
#pragma unroll
    for (int k = 0; k < 8; k++) {
        if (INIT && k == 0) wgmma_ss128_init<1>(d, a, b, ha);
        else wgmma_ss128<1>(d, a + (k >> 2) * o4 + ((k >> 1) & 1) * o2 + (k & 1) * 2, b + k * 128, k ? 1 : acc, ha);
    }
    wg_commit();
}

template <bool ODD>
__device__ __forceinline__ bool proj_tile(float (&acc)[64], float (&prev)[64], int t, int q0, uint32_t sb, int wg, uint32_t eb, bool rel, uint32_t& fph,
                                          uint32_t wtab, uint32_t& atab, uint8_t* prev_img, uint32_t toff, float s0, float s1,
                                          uint32_t (&v)[32]) {
    const uint32_t a0 = desc_k(sb + (wg ^ (ODD && t == 5)) * 8192), b0 = desc_mn(sb);
    constexpr int U = ODD ? UNR : 1;
#pragma unroll U
    for (int q = ODD ? 0 : q0; q < 4; q++) {
        const uint32_t ws = (wtab >> (4 * q)) & 15, as = a_next(atab);
        if (!ODD && t != 2) slot_wait(sb + BAR_FULL, fph, ws);
        slot_wait(sb + BAR_FULL, fph, as);
        if (ODD && q == 2 && t == 5) {
#pragma unroll
            for (int i = 0; i < 8; i++) sts128(sb + 5 * SLOT + q_off(toff) + (i >> 2) * 16384 + (i & 2) * 256 + (i & 1) * 1024, make_uint4(v[4 * i], v[4 * i + 1], v[4 * i + 2], v[4 * i + 3]));
        }
        bar_sync(1 + wg, 256);
        gemm_issue<false>(acc, a0 + as * (SLOT / 16), b0 + ws * (SLOT / 16), q, false);
        bar_arrive(2 - wg, 256);
        wg_wait<1>();
        reg_fence(prev);
        if (ODD && t == 5) {
            if (q == 0) {
#pragma unroll
                for (int i = 0; i < 32; i++) {
                    const int k = 16 * (i >> 3) + 4 * (i & 3) + ((i >> 1) & 2);
                    v[i] = pack2(prev[k], prev[k + 1]);
                }
            }
            if (q == 2) {
                fence_async_smem();
                slot_wait(sb + BAR_FULL, fph, wtab & 15);
                wg_wait<0>();
                release_if(eb, as, rel);
                release_if(eb, ws, rel);
                reg_fence(acc);
                return true;
            }
        } else {
            if (q == 0) img_store_global<0>(prev_img, toff, prev, s0, s1);
            if (q == 1) img_store_global<1>(prev_img, toff, prev, s0, s1);
            if (q == 2) img_store_global<2>(prev_img, toff, prev, s0, s1);
            if (q == 3) img_store_global<3>(prev_img, toff, prev, s0, s1);
        }
        wg_wait<0>();
        release_if(eb, as, rel && !(ODD && (q & 1) && t == 5));
        if (ODD) release_if(eb, ws, rel && t != 1);
    }
    reg_fence(acc);
    return false;
}

__device__ __forceinline__ void qk_issue(float (&s)[64], uint32_t q, uint32_t k) {
    wg_fence();
    wgmma_ss128_init<0>(s, q, k, HI_Q, HI_IMG);
#pragma unroll
    for (int i = 1; i < 8; i++) wgmma_ss128<0>(s, q + (i >> 2) * 1024 + (i & 2) * 16 + (i & 1) * 2, k + (i >> 1) * 32 + (i & 1) * 2, 1, HI_Q, HI_IMG);
    wg_commit();
}
__device__ __forceinline__ void qk_issue(float (&s)[32], uint32_t q, uint32_t k) {
    wg_fence();
    wgmma_ss64_init<0>(s, q, k, HI_Q, HI_IMG);
#pragma unroll
    for (int i = 1; i < 8; i++) wgmma_ss64<0>(s, q + (i >> 2) * 1024 + (i & 2) * 16 + (i & 1) * 2, k + (i >> 1) * 32 + (i & 1) * 2, 1, HI_Q, HI_IMG);
    wg_commit();
}
__device__ __forceinline__ void pv_issue(float (&o)[64], const uint32_t (&p)[32], uint32_t v, int acc, bool half) {
    if (half) {
        asm volatile("// half" ::: "memory");
        wg_fence();
#pragma unroll
        for (int i = 0; i < 4; i++) wgmma_rs128(o, p[4 * i], p[4 * i + 1], p[4 * i + 2], p[4 * i + 3], v + i * 256, i ? 1 : acc, HI_IMG);
        wg_commit();
        asm volatile("// half" ::: "memory");
    } else {
        wg_fence();
#pragma unroll
        for (int i = 0; i < 8; i++) wgmma_rs128(o, p[4 * i], p[4 * i + 1], p[4 * i + 2], p[4 * i + 3], v + i * 256, i ? 1 : acc, HI_IMG);
        wg_commit();
    }
}
__device__ __forceinline__ void tri_mask(float (&s)[64], float x) {
#pragma unroll
    for (int k = 0; k < 16; k++) {
        float b;
        asm("sub.sat.f32 %0, %1, %2;" : "=f"(b) : "f"((float)(8 * (k >> 1) + (k & 1))), "f"(x));
        const int i = 32 + 4 * (k >> 1) + (k & 1);
        asm("fma.rn.f32 %0, %1, 0fFF61B1E6, %0;" : "+f"(s[i]) : "f"(b));
        if (k < 14) asm("fma.rn.f32 %0, %1, 0fFF61B1E6, %0;" : "+f"(s[i + 6]) : "f"(b));
    }
}
__device__ __forceinline__ void tri_mask_copy(float (&s)[64], const float (&h)[32], float x) {
#pragma unroll
    for (int i = 0; i < 32; i++) {
        asm("{\n.reg .pred p;\nsetp.lt.f32 p, %2, %3;\nselp.f32 %0, 0fFF800000, %1, p;\n}"
            : "=f"(s[i]) : "f"(h[i]), "f"(x), "f"((float)(8 * (i >> 2) - 4 * (i & 2) + (i & 1))));
        s[32 + i] = __uint_as_float(0xff800000u);
    }
}
constexpr float SM_HI = 1152921504606846976.f, SM_LO = 1.f / 1152921504606846976.f;
__device__ __forceinline__ bool softmax_unsafe(float t0, float t1, bool first) {
    bool bad = __any_sync(0xffffffffu, fmaxf(t0, t1) > SM_HI);
    if (first) {
        uint32_t a = __ballot_sync(0xffffffffu, t0 >= SM_LO), b = __ballot_sync(0xffffffffu, t1 >= SM_LO);
        a |= a >> 1;
        b |= b >> 1;
        bad |= ((a | (a >> 2)) & (b | (b >> 2)) & 0x11111111u) != 0x11111111u;
    }
    return bad;
}
__device__ __forceinline__ void softmax_shift(float (&s)[64], float d0, float d1) {
#pragma unroll
    for (int i = 0; i < 64; i++) s[i] -= (i & 2) ? d1 : d0;
}
__device__ __forceinline__ void softmax_remax(float (&s)[64], float (&m)[2], bool first, float& a0, float& a1) {
    float m0 = fmaxf(s[0], s[1]), m1 = fmaxf(s[2], s[3]);
#pragma unroll
    for (int k = 1; k < 16; k++) {
        m0 = fmaxf(m0, fmaxf(s[4 * k], s[4 * k + 1]));
        m1 = fmaxf(m1, fmaxf(s[4 * k + 2], s[4 * k + 3]));
    }
    m0 = fmaxf(m0, __shfl_xor_sync(0xffffffffu, m0, 1));
    m1 = fmaxf(m1, __shfl_xor_sync(0xffffffffu, m1, 1));
    m0 = fmaxf(m0, __shfl_xor_sync(0xffffffffu, m0, 2));
    m1 = fmaxf(m1, __shfl_xor_sync(0xffffffffu, m1, 2));
    if (!first) {
        m0 = fmaxf(m0, 0.f);
        m1 = fmaxf(m1, 0.f);
    }
    a0 = first ? 1.f : ex2(-m0);
    a1 = first ? 1.f : ex2(-m1);
    m[0] += m0;
    m[1] += m1;
    softmax_shift(s, m0, m1);
}
template <int J0, int J1>
__device__ __forceinline__ void softmax_exp(const float (&s)[64], uint32_t (&p)[32], float (&t)[4]) {
#pragma unroll
    for (int k = J0; k < J1; k++) {
        const float e0 = ex2(s[4 * k]), e1 = ex2(s[4 * k + 1]), e2 = ex2(s[4 * k + 2]), e3 = ex2(s[4 * k + 3]);
        if (k == 0) { t[0] = e0; t[1] = e1; t[2] = e2; t[3] = e3; }
        else { t[0] += e0; t[1] += e1; t[2] += e2; t[3] += e3; }
        p[2 * k] = pack2(e0, e1);
        p[2 * k + 1] = pack2(e2, e3);
    }
}
__device__ __forceinline__ void mma16816(float (&d)[4], const uint32_t* a, uint32_t b0, uint32_t b1) {
    asm("mma.sync.aligned.m16n8k16.row.col.f32.bf16.bf16.f32 {%0, %1, %2, %3}, {%4, %5, %6, %7}, {%8, %9}, {%0, %1, %2, %3};"
        : "+f"(d[0]), "+f"(d[1]), "+f"(d[2]), "+f"(d[3]) : "r"(a[0]), "r"(a[1]), "r"(a[2]), "r"(a[3]), "r"(b0), "r"(b1));
}
__device__ __forceinline__ uint2 best_key(const uint32_t* keys, int lane, uint32_t ep, uint32_t cur, int enough) {
#pragma unroll 1
    for (;;) {
        const uint4 k = ld_poll(reinterpret_cast<const uint4*>(keys) + lane);
        const bool ok = (((k.x ^ ep) | (k.y ^ ep) | (k.z ^ ep) | (k.w ^ ep)) & 31) == 0;
        const uint32_t best = __reduce_max_sync(0xffffffffu, ok ? max(max(k.x, k.y), max(k.z, k.w)) : 0u);
        const int n = __popc(__ballot_sync(0xffffffffu, ok));
        if (n == 32 || (n >= enough && best != cur)) return make_uint2(best, n == 32);
        __nanosleep(KSLEEP);
    }
}

__global__ void __cluster_dims__(2, 1, 1) __launch_bounds__(384, 1)
fused_kernel(const __grid_constant__ CUtensorMap tm_ckv, const __grid_constant__ CUtensorMap tm_wq,
             const __grid_constant__ CUtensorMap tm_wuk, const __grid_constant__ CUtensorMap tm_wuv,
             const __grid_constant__ CUtensorMap tm_wo, const __grid_constant__ CUtensorMap tm_wg,
             const __grid_constant__ CUtensorMap tm_wu,
             const __grid_constant__ CUtensorMap tm_wm, const __grid_constant__ CUtensorMap tm_x, const Params P) {
    extern __shared__ __align__(1024) uint8_t smem[];
    const uint32_t sb = (uint32_t)__cvta_generic_to_shared(smem);
    const int tid = threadIdx.x, lane = tid & 31, warp = __shfl_sync(0xffffffffu, tid >> 5, 0), wg = warp >> 2;
    const uint32_t sm = blockIdx.x < 8 ? blockIdx.x + 124 : blockIdx.x - 8, smq = ((sm - 64) * 147) >> 11;
    const int rb = sm < 64 ? (sm & 14) * 8 + (sm >> 4) * 2 + (sm & 1)
                 : sm < 120 ? ((sm - 64 - smq * 14) & 14) * 8 + 24 + smq * 2 + (sm & 1) : sm < 124 ? sm + 8 : sm - 116;
    const int grp = rb >> 3, j = rb & 7, kh = (grp >> (OMAP - 1)) & 1;
    const int cq = (j & 1) + ((grp >> (OMAP - 1)) & 2), ort = (OMAP == 1 ? grp & 12 : (grp & 8) + (grp & 1) * 4) + (j >> 1);
    if (warp == 0) TS(0);

    const CUtensorMap* tw = (j & 1) ? &tm_wuv : &tm_wuk;
    if (lane == 0) {
        if (warp == 8) {
#pragma unroll
            for (int i = 0; i < 7; i++) mbar_init(sb + BAR_FULL + 8 * i, 1);
            fence_async_smem();
        } else if (warp < 11) {
            const int w = warp - (warp > 8);
            const u64 cnt = (w < 5 ? (rb < NCTA ? 0x888888884444444ull : 0x888888888888888ull) : 0x111812111111118ull) >> (12 * (w % 5));
#pragma unroll
            for (int i = 0; i < 3; i++) mbar_init(sb + BAR_EMPTY + 24 * w + 8 * i, ((uint32_t)cnt >> (4 * i)) & 15);
        }
        asm volatile("fence.mbarrier_init.release.cluster;" ::: "memory");
    }
    __syncwarp();
    asm volatile("barrier.cluster.arrive.relaxed.aligned;" ::: "memory");
    if (warp == 8) {
        if (rb < NCTA) {
#pragma unroll 1
            for (int u = 0; u < 4; u++) {
                const uint32_t ws = u + (u == 3), as = (0x635u >> (4 * u)) & 15;
                slot_expect(sb, ws);
                load_tile(sb, ws, 0, tw, u * 128, 4 * grp, false, HINT & 1);
                if (u == 3) break;
                slot_expect(sb, as);
                load_tile(sb, as, 0, &tm_ckv, (j >> 1) * 128, u * 2, false, false);
                load_tile(sb, as, 16384, &tm_ckv, (j >> 1) * 128, u * 2 + 1, false, false);
            }
        } else {
#pragma unroll 1
            for (int i = 0; i < 6; i++) {
                slot_expect(sb, i);
                load_tile(sb, i, 0, &tm_wm, i * 64, (rb - NCTA) * 4, false, HINT & 64);
                if (i > 3) tma3d_prefetch(&tm_wm, i * 64 + 128, (rb - NCTA) * 4);
            }
        }
    }
    asm volatile("barrier.cluster.wait.aligned;" ::: "memory");

    if (rb >= NCTA) {
        uint32_t ph = 0, sl = 0;
        if (warp == 8) {
#pragma unroll 1
            for (int i = 6; i < 24; i++) {
                slot_acquire(sb, ph, sl);
                load_tile(sb, sl, 0, &tm_wm, (i & 7) * 64, (i >> 3) * 16 + (rb - NCTA) * 4, false, HINT & 64);
                if (++sl == 6) sl = 0;
            }
#pragma unroll 1
            for (int i = 0; i <= NFFN / NSPARE; i++) {
                const int b = (rb - NCTA) * (NFFN / NSPARE) + i;
                if (i < NFFN / NSPARE) {
                    asm volatile("cp.async.bulk.wait_group.read 0;" ::: "memory");
                    uint32_t done = 0x7f;
                    slot_acquire(sb, done, i & 1);
#pragma unroll 1
                    for (int k = 0; k < 4; k++) tma2d(sb + (i & 1) * SLOT + k * 8192, k < 2 ? &tm_wg : &tm_wu, b * 16, (k & 1) * 256, sb + BAR_FULL + 8 * (i & 1), (HINT & 128) && (i & 3) == 3);
                }
                if (i) {
                    mbar_wait(sb + BAR_FULL + 8 * (~i & 1), ((i - 1) >> 1) & 1);
                    bulk_store(g_wf + (b - 1) * SLOT, sb + (~i & 1) * SLOT, SLOT, HINT & 256);
                    asm volatile("cp.async.bulk.commit_group;" ::: "memory");
                }
            }
            asm volatile("cp.async.bulk.wait_group 0;" ::: "memory");
            fence_async_global();
            TS(4);
        } else if (warp < 8) {
            const uint32_t c2 = __ldg(reinterpret_cast<const uint32_t*>(P.c) + tid), ep = __ldcg(&g_sync.epoch[0]) + 1;
            uint32_t* sc = reinterpret_cast<uint32_t*>(smem + 6 * SLOT);
            sc[tid] = pack2(bf_lo(c2) * sigmoid(bf_lo(c2)), bf_hi(c2) * sigmoid(bf_hi(c2)));
            bar_sync(1, 256);
            const uint32_t a = sb + (warp >> 1) * 8192 + ((lane >> 4) * 8 + (lane & 7)) * 128, ch = (warp & 1) * 4 + ((lane >> 3) & 1);
#pragma unroll 1
            for (int ps = 0; ps < 3; ps++) {
                float d[2][4] = {};
#pragma unroll 1
                for (int bt = 0; bt < 8; bt++) {
                    slot_wait(sb + BAR_FULL, ph, sl);
#pragma unroll
                    for (int i = 0; i < 8; i++) {
                        uint32_t w[4];
                        asm volatile("ldmatrix.sync.aligned.m8n8.x4.trans.shared.b16 {%0, %1, %2, %3}, [%4];" : "=r"(w[0]), "=r"(w[1]), "=r"(w[2]), "=r"(w[3])
                                     : "r"(a + sl * SLOT + (i >> 1) * 2048 + (((ch + 2 * (i & 1)) ^ (lane & 7)) << 4)) : "memory");
                        mma16816(d[i & 1], w, sc[bt * 32 + (i >> 1) * 8 + (lane & 3)], sc[bt * 32 + (i >> 1) * 8 + 4 + (lane & 3)]);
                    }
                    __syncwarp();
                    mbar_arrive_if(sb + BAR_EMPTY + 8 * sl, lane == 0);
                    if (++sl == 6) sl = 0;
                }
                const float v = (lane & 2) ? ((lane & 1) ? d[1][2] : d[1][0]) : ((lane & 1) ? d[0][2] : d[0][0]);
                const int col = (rb - NCTA) * 256 + warp * 32 + (lane & 3) * 8 + (lane >> 2);
                if (ps == 0) st_pub(g_mod1 + col, (pack2(0.f, v) & 0xffff0000u) | (ep & 0xffffu), true);
                else g_mod[ps * 1024 + col] = __float2bfloat16_rn(v);
                if (warp == 0) TS(1 + ps);
            }
        }
        __syncthreads();
        if (tid < 2) flag_add(&g_sync.cnt[7 * 8]);
        return;
    }

    if (wg == 2) {
        asm volatile("setmaxnreg.dec.sync.aligned.u32 40;");
        if (warp == 8) {
            const uint32_t rank = j & 1, half = rank * 16384;
            uint32_t eph = 0, r = 0;
            *reinterpret_cast<volatile uint32_t*>(smem + SM_EP + 20) = 0;
#pragma unroll 1
            for (int hp = 0; hp < 2; hp++) {
                uint32_t wtab = w_table(hp), atab = a_table(hp);
                const int hc = 4 * grp + 2 * hp;
#pragma unroll 1
                for (int u = 3 - 3 * hp; u < 16; u++) {
                    if (hp && u < 4) {
                        const uint32_t ws = (wtab >> (4 * u)) & 15;
                        slot_acquire(sb, eph, ws);
                        load_tile(sb, ws, 0, tw, u * 128, hc, false, HINT & 1);
                        PT();
                    }
                    if (hp == 1 && (u & 7) == 4) mbar_wait(sb + BAR_FLAG + 24 + (u & 8), 0);
                    const uint32_t as = a_next(atab);
                    slot_acquire(sb, eph, as);
                    load_tile(sb, as, half, &tm_ckv, ((u & 12) + (j >> 1)) * 128, (u & 3) * 2 + rank, true, (HINT & 8) && hp);
                    PT();
                    if (hp == 1 && (u | 2) == 3 && lane == 0)
                        asm volatile("red.relaxed.gpu.global.add.u32 [%0], 1;" ::"l"(&g_sync.cnt[(grp * 8 + 3 + (u >> 1)) * 8]) : "memory");
                }
                const uint8_t* src = g_h + (15 - j) * 4 * SLOT;
#pragma unroll 1
                for (int u = 0; u < 8; u++) {
                    if (u == 0 || u == KVG) {
                        mbar_wait(sb + BAR_FLAG + (u ? 8 + 32 * hp : 0), 0);
                        fence_async_global();
                    }
                    if (u < 4) {
                        const uint32_t ws = (wtab >> (4 * u)) & 15;
                        slot_acquire(sb, eph, ws);
                        load_tile(sb, ws, 0, &tm_wq, u * 128, hc, false, HINT & 1);
                        PT();
                    }
                    const uint32_t as = a_next(atab);
                    slot_acquire(sb, eph, as);
                    load_bulk(sb, as, 0, src, SLOT, false, (HINT & 8) && hp);
                    PT();
                    src += u == 3 ? (8 * j - 63) * SLOT : SLOT;
                }
                const int step = hp ? -2 * SLOT : 2 * SLOT;
                src = g_KV + (size_t)(grp * 32 + 30 * hp) * SLOT + half - step;
#pragma unroll 1
                for (int n = 0; n <= 17; n++) {
                    if (n == 8) {
                        mbar_wait(sb + BAR_FLAG + 16 + 32 * hp, 0);
                        fence_async_global();
                    }
                    const uint8_t* v = src + SLOT;
                    src += n < 16 - j ? step : n == 16 - j ? (2 * j - 15) * step : -step;
                    if (n < 17) {
                        slot_acquire(sb, eph, r);
                        if (n != 15 - (j & 6)) load_bulk(sb, r, half, src, SLOT / 2, true, HINT & 4);
                        else load_bulk(sb, r, 0, src - half, SLOT, false, HINT & 4);
                        PT();
                        r = ring_next(r);
                    }
                    if (n) {
                        slot_acquire(sb, eph, r);
                        if (n != 16 - (j & 6)) load_bulk(sb, r, half, v, SLOT / 2, true, HINT & 4);
                        else load_bulk(sb, r, 0, v - half, SLOT, false, HINT & 4);
                        PT();
                        r = ring_next(r);
                    }
                    asm volatile("st.volatile.shared.u32 [%0], %1;" ::"r"(sb + SM_EP + 16), "r"(18 * hp + n + 1) : "memory");
                }
            }
            uint32_t otab = O_TABLE, ready = 0;
#pragma unroll 1
            for (int i = 0; i < 17; i++) {
                const bool dyn = i >= 8 && i < 15;
                const uint32_t want = dyn ? 15u << (4 * (i - 8)) : 1u << max(i + 14, 28);
                if (!(ready & want)) {
                    do {
                        asm volatile("ld.acquire.cta.shared.u32 %0, [%1];" : "=r"(ready) : "r"(sb + SM_EP + 20) : "memory");
                        ready = __shfl_sync(0xffffffffu, ready, 0);
                    } while (!(ready & want));
                    fence_async_global();
                }
                const int head = o_head(dyn ? (ready >> (4 * (i - 8))) & 15 : i, kh);
                const uint32_t as = o_next(otab), ws = o_next(otab), off = i < 15 ? half : kh * 16384;
                slot_acquire(sb, eph, as);
                load_bulk(sb, as, off, g_ctx + (size_t)(ort * 32 + head) * SLOT + off, SLOT / 2, i < 15, HINT & 16);
                if (i == 15) load_tile(sb, as, off ^ 16384, &tm_x, ort * 128 + kh * 64, cq * 2, false, false);
                if (i == 16) load_bulk(sb, as, off ^ 16384, P.wdown + min(rb, NFFN - 1) * 8192, SLOT / 2, false, false);
                PT();
                slot_acquire(sb, eph, ws);
                load_tile(sb, ws, 0, &tm_wo, head * 128, cq * 2, false, HINT & 2);
                PT();
                if (i == 0) o_next(otab);
            }
            if (rb < NFFN) {
                slot_acquire(sb, eph, 5);
                load_bulk(sb, 5, 0, g_wf + rb * SLOT, SLOT, false, false);
            }
        } else if (warp == 9) {
            *reinterpret_cast<volatile uint32_t*>(smem + SM_EP + 16) = 0;
            l2_prefetch(P.ckv + rb * 2048, 4096);
            mbar_watch(sb + BAR_FULL, 0);
            l2_prefetch(P.ckv + 512 * 512 + rb * 2048, 4096);
            mbar_watch(sb + BAR_FULL + 8 * XPF, 0);
            l2_prefetch(P.x + rb * 8192, 16384);
            mbar_watch(sb + BAR_FULL + 8 * 4, 0);
            l2_prefetch(P.ckv + 1024 * 512 + rb * 4096, 8192);
            TS(40);
#pragma unroll 1
            for (int i = 0; i < 15; i++) {
                step_watch(sb + SM_EP + 16, i == 0 ? 0 : i < 5 ? PFA + i : 13 + PFB + i);
                if (i == 12) mbar_watch(sb + BAR_FLAG + 8 * 7, 0);
                const int rf = min(rb, NFFN - 1);
                const uint8_t* p = i == 3 ? reinterpret_cast<const uint8_t*>(P.ckv) + rb * 16384
                                 : i == 4 ? g_h + rb * 16384
                                 : i < 9 ? g_ctx + (size_t)(ort * 32 + o_head(cq + 2 * ((i - 5) & 2), kh)) * SLOT + (i & 1) * 16384
                                 : i < 11 ? reinterpret_cast<const uint8_t*>(P.wo) + (grp * 16 + (~i & 1) * 8 + j) * 16384
                                 : i == 11 ? reinterpret_cast<const uint8_t*>(P.x) + rb * 16384
                                 : i == 12 ? reinterpret_cast<const uint8_t*>(P.wdown) + rf * 16384 : g_wf + rf * SLOT + (i & 1) * 16384;
                if (i >= 3) l2_prefetch(p, 16384);
                else if ((i | j) & 1) tma3d_prefetch(i == 1 ? tw : &tm_wq, (j >> 1) * 128, grp * 4 + (i ? 2 : 0));
            }
            const uint32_t v = lds32(sb + SM_EP) - 1;
            sts128(sb + SM_RED + lane * 16, make_uint4(v, v, v, v));
            fence_async_smem();
            __syncwarp();
#pragma unroll 1
            for (int i = 0; i < OB / 32; i++) bulk_store(g_out + rb * OB + i * 32, sb + SM_RED, 512, false);
            asm volatile("cp.async.bulk.commit_group;\ncp.async.bulk.wait_group 0;" ::: "memory");
            fence_async_global();
            __syncwarp();
            mbar_arrive_if(sb + BAR_PF, lane == 0);
            if (lane == 0) mbar_watch(sb + BAR_END, 0);
        } else {
            const uint32_t ep = __ldcg(&g_sync.epoch[0]) + 1;
            asm volatile("st.shared.u32 [%0], %1;" ::"r"(sb + SM_EP), "r"(ep) : "memory");
            mbar_wait(sb + BAR_FULL + 8 * 4, 0);
            __nanosleep(MPRE);
            {
                uint4 v[4];
                for (;;) {
                    uint32_t bad = 0;
#pragma unroll
                    for (int k = 0; k < 4; k++) v[k] = ld_poll(reinterpret_cast<const uint4*>(g_mod1) + (warp & 1) * 128 + k * 32 + lane);
#pragma unroll
                    for (int k = 0; k < 4; k++) bad |= (v[k].x ^ ep) | (v[k].y ^ ep) | (v[k].z ^ ep) | (v[k].w ^ ep);
                    if (__all_sync(0xffffffffu, (bad & 0xffff) == 0)) break;
                    __nanosleep(100);
                }
                const uint32_t one = (warp & 1) ? ONE2 : 0x80008000u;
#pragma unroll
                for (int k = 0; k < 4; k++)
                    *reinterpret_cast<uint2*>(smem + SM_TAB + (warp & 1) * 1024 + k * 256 + lane * 8) =
                        make_uint2(badd(__byte_perm(v[k].x, v[k].y, 0x7632), one), badd(__byte_perm(v[k].z, v[k].w, 0x7632), one));
            }
            __syncwarp();
            mbar_arrive_if(sb + BAR_FLAG + 8 * 8, lane == 0);
            if (warp == 10) {
#pragma unroll 1
                for (int i = 0; i < 9; i++) {
                    mbar_sleep(sb + BAR_DONE + 8 * i);
                    if (lane == 0) flag_add(i && ((i - 1) & 2) ? &g_sync.ctxcnt[((i & 1) ? 15 - j : j) * 32 + 2 * grp + (i > 4)] : &g_sync.cnt[(grp * 8 + i) * 8]);
                    if (i == 0) TS(43);
                }
            } else {
                TS(42);
#pragma unroll 1
                for (int i = 0; i < 8; i++) {
                    mbar_sleep(sb + BAR_DONE + 8 * (i == 7 ? 6 : i == 4 ? 3 : i));
                    if (lane < 2) flag_wait(&g_sync.cnt[((i == 0 ? (lane ? j : 15 - j) : i == 7 ? 0 : grp) * 8 + i) * 8], 8 * ep);
                    __syncwarp();
                    mbar_arrive_if(sb + BAR_FLAG + 8 * i, lane == 0 && i < 7);
                    TS(48 + i);
                }
                const uint32_t *mp = reinterpret_cast<const uint32_t*>(g_mod) + lane, *wp = reinterpret_cast<const uint32_t*>(P.wr) + lane;
                float ra = 0.f, rs = 0.f;
#pragma unroll 1
                for (int k = 0; k < 256; k += 32) {
                    const uint32_t ga = __ldcg(mp + 512 + k), sh = __ldcg(mp + 768 + k), c1 = badd(__ldcg(mp + 1024 + k), ONE2);
                    const uint32_t gb = __ldcg(mp + 1280 + k), ww = __ldg(wp + k);
                    const uint32_t a = bmul(c1, ww);
                    ra += bf_lo(a) + bf_hi(a);
                    rs = fmaf(bf_lo(sh), bf_lo(ww), fmaf(bf_hi(sh), bf_hi(ww), rs));
                    if (k >> 6 == cq) {
                        sts128(sb + SM_TAB + ((k & 32) + lane) * 16, make_uint4(ga << 16, ga & 0xffff0000u, a, 0));
                        sts128(sb + SM_TAB + 1024 + ((k & 32) + lane) * 16, make_uint4(c1, sh, gb, 0));
                    }
                }
#pragma unroll 1
                for (int o = 16; o > 0; o >>= 1) {
                    ra += __shfl_xor_sync(0xffffffffu, ra, o);
                    rs += __shfl_xor_sync(0xffffffffu, rs, o);
                }
                *reinterpret_cast<float2*>(smem + SM_EP + 8) = make_float2(ra, rs);
                __syncwarp();
                mbar_arrive_if(sb + BAR_FLAG + 8 * 7, lane == 0);
                const uint32_t* f = &g_sync.ctxcnt[ort * 32 + o_head(min(lane, 16), kh)];
                uint32_t ready = -(j & 1), list = 0, sh = 0, qa;
                asm("mapa.shared::cluster.u32 %0, %1, %2;" : "=r"(qa) : "r"(sb + SM_EP + 20), "r"(lane & 1));
                while (ready != ~0u) {
                    uint32_t v;
                    asm volatile("ld.acquire.gpu.global.u32 %0, [%1];" : "=r"(v) : "l"(f) : "memory");
                    const uint32_t now = __ballot_sync(0xffffffffu, (int)(v - ep) >= 0);
#pragma unroll 1
                    for (uint32_t fresh = now & ~ready & 0x7f00; fresh; fresh &= fresh - 1, sh += 4) list |= (__ffs(fresh) - 1) << sh;
                    list |= (((now & 0xff) + 1) >> 8 << 28) | ((now & 0x18000) << 14);
                    if (now != ready && lane < 2) asm volatile("st.relaxed.cluster.shared::cluster.u32 [%0], %1;" ::"r"(qa), "r"(list) : "memory");
                    if ((now & 0xff) == 0xff) mbar_sleep(sb + BAR_DONE + 8 * 7);
                    ready = now;
                    __nanosleep(POLL_NS);
                }
                TS(45);
            }
        }
    } else {
        asm volatile("setmaxnreg.inc.sync.aligned.u32 232;");
        const bool elected = (tid & 127) == 0, rel = (tid & 95) == 0;
        uint32_t eb;
        asm("mapa.shared::cluster.u32 %0, %1, %2;" : "=r"(eb) : "r"(sb + BAR_EMPTY), "r"(warp & 1));
        const int g = lane >> 2, c4 = lane & 3;
        const uint32_t toff = warp * 4096 + g * 64 + ((c4 ^ (g >> 1)) << 4);
        uint32_t fph = 0x3f, r = 0;
        if (wg == 1) bar_arrive(1, 256);
        const uint32_t kd = desc_k(sb), wd = desc_mn(sb), vd = ((sb & 0x3ffff) >> 4) | (32u << 16);
        const int nL = 16 - j, hn = nL - 1 + wg;
        float s[64], o[64], li[2] = {0.f, 0.f};
        uint8_t* cimg = g_ctx;
        const float sc = (j & 1) ? 1.f : SM_C;
#pragma unroll 1
        for (int q = 0; q < 3; q++) {
            const uint32_t as = (0x635u >> (4 * q)) & 15;
            mbar_wait(sb + BAR_FULL + 8 * q, 0);
            mbar_wait(sb + BAR_FULL + 8 * as, 0);
            bar_sync(1 + wg, 256);
            gemm_issue<false>(s, kd + wg * 512 + as * (SLOT / 16), wd + q * (SLOT / 16), q, false);
            bar_arrive(2 - wg, 256);
            wg_wait<0>();
            release_if(eb, as, rel);
        }
        {
            const int xrow = rb * 16 + warp * 2;
            const uint4* xp = reinterpret_cast<const uint4*>(P.x) + xrow * 64;
            uint8_t* img = g_KV + (size_t)(grp * 32 + j) * SLOT;
            uint32_t x[16], x0[2];
            float st[4] = {0.f, 0.f, 0.f, 0.f};
            mbar_wait(sb + BAR_FULL + 8 * 4, 0);
#pragma unroll
            for (int q = 3; q < 8; q++) {
                const uint32_t ws = (0x4210u >> (4 * (q & 3))) & 15, as = (0x635u >> (4 * (q % 3))) & 15;
                mbar_wait(sb + BAR_FULL + 8 * as, (q / 3) & 1);
                bar_sync(1 + wg, 256);
                if (q == 3) gemm_issue<false>(s, kd + wg * 512 + as * (SLOT / 16), wd + ws * (SLOT / 16), 1, false);
                else if (q == 4) gemm_issue<true>(o, kd + wg * 512 + as * (SLOT / 16), wd + ws * (SLOT / 16), 0, false);
                else gemm_issue<false>(o, kd + wg * 512 + as * (SLOT / 16), wd + ws * (SLOT / 16), 1, false);
                bar_arrive(2 - wg, 256);
                sched_fence(fph, P.zero);
                if (q > 3) reg_fence(s);
                if (q == 3) {
#pragma unroll
                    for (int i = 0; i < 4; i++)
                        asm volatile("ld.global.nc.v4.u32 {%0, %1, %2, %3}, [%4];" : "=r"(x[4 * i]), "=r"(x[4 * i + 1]), "=r"(x[4 * i + 2]), "=r"(x[4 * i + 3])
                                     : "l"(xp + lane + 32 * i) : "memory");
#pragma unroll
                    for (int i = 0; i < 2; i++) asm volatile("ld.global.nc.u32 %0, [%1];" : "=r"(x0[i]) : "l"(xp + 64 * i) : "memory");
                }
                if (q == 4) {
                    img_store_global<0>(img, toff, s, sc, sc);
#pragma unroll
                    for (int k = 0; k < 16; k++) {
                        const float d0 = bf_lo(x[k]) - bf_lo(x0[k >> 3]), d1 = bf_hi(x[k]) - bf_lo(x0[k >> 3]);
                        st[k >> 3] += d0 + d1;
                        st[2 + (k >> 3)] = fmaf(d0, d0, fmaf(d1, d1, st[2 + (k >> 3)]));
                    }
#pragma unroll
                    for (int i = 0; i < 4 * NSH; i++) st[i & 3] += __shfl_xor_sync(0xffffffffu, st[i & 3], 1 << (i >> 2));
                    reg_fence(st);
                }
                if (q == 5) {
#pragma unroll
                    for (int i = 4 * NSH; i < 20; i++) st[i & 3] += __shfl_xor_sync(0xffffffffu, st[i & 3], 1 << (i >> 2));
                    img_store_global<1>(img, toff, s, sc, sc);
#pragma unroll
                    for (int i = 0; i < 2; i++) {
                        const float d = st[i] * (1.f / 512.f);
                        st[2 + i] = ln_rstd(fmaxf(fmaf(-d, d, st[2 + i] * (1.f / 512.f)), 0.f));
                        x0[i] = pack2(bf_lo(x0[i]) + d, bf_lo(x0[i]) + d);
                    }
                    reg_fence(st);
                    reg_fence(x0);
                }
                if (q > 5) {
                    if (q == 6) mbar_wait(sb + BAR_FLAG + 8 * 8, 0);
                    const uint4 a = lds128(sb + SM_TAB + 1024 + (q & 1) * 512 + lane * 16), c = lds128(sb + SM_TAB + (q & 1) * 512 + lane * 16);
                    uint8_t* hp = g_h + (grp * 8 + (q & 1) * 4 + (lane >> 3)) * 16384 + (xrow & 127) * 128;
#pragma unroll
                    for (int i = 0; i < 2; i++) {
                        const uint32_t* y = x + 8 * i + 4 * (q & 1);
                        *reinterpret_cast<uint4*>(hp + i * 128 + (((lane ^ xrow ^ i) & 7) << 4)) =
                            make_uint4(ln_apply(y[0], x0[i], st[2 + i], a.x, c.x), ln_apply(y[1], x0[i], st[2 + i], a.y, c.y),
                                       ln_apply(y[2], x0[i], st[2 + i], a.z, c.z), ln_apply(y[3], x0[i], st[2 + i], a.w, c.w));
                    }
                    if (q == 7) {
                        __syncwarp();
                        mbar_arrive_if(sb + BAR_DONE, lane == 0);
                    }
                    if (q == 6) img_store_global<2>(img, toff, s, sc, sc);
                    else img_store_global<3>(img, toff, s, sc, sc);
                }
                sched_fence(fph, P.zero);
                wg_wait<0>();
                release_if(eb, as, rel);
            }
            reg_fence(o);
        }
        uint32_t p[32] = {};
#pragma unroll 1
        for (int hp = 0; hp < 2; hp++) {
            float m[2] = {0.f, 0.f}, l[2] = {0.f, 0.f}, t[4] = {0.f, 0.f, 0.f, 0.f};
            bool shifted = false, bad = false, plain = false;
            uint32_t qa = desc_k(sb + 5 * SLOT + (wg ^ 1) * 8192);
            uint8_t* limg = g_ctx + (size_t)((15 - j) * 32 + 2 * grp + hp) * SLOT;
            {
                const int step = hp ? -8 * SLOT : 8 * SLOT;
                uint8_t* img = g_KV + (size_t)(grp * 32 + (hp ? j ^ 30 : j) + 8) * SLOT;
                const uint32_t wtab = w_table(hp);
                uint32_t atab = hp ? 0x562u : 0x356u;
#pragma unroll 1
                for (int u = 2 - 2 * hp;; u += 2) {
                    proj_tile<false>(s, o, u, !u, sb, wg, eb, rel, fph, wtab, atab, u ? img : cimg, toff, u ? sc : li[0], u ? sc : li[1], p);
                    __syncwarp();
                    mbar_arrive_if(sb + BAR_DONE + 4 * u + 32 * hp, lane == 0);
                    if (elected) TS(1 + 10 * hp + u + 20 * wg);
                    if (proj_tile<true>(o, s, u + 1, 0, sb, wg, eb, rel, fph, wtab, atab, img + step, toff, sc, sc, p)) break;
                    if (elected) TS(2 + 10 * hp + u + 20 * wg);
                    img += 2 * step;
                }
            }
            if (elected) TS(6 + 10 * hp + 20 * wg);
            int n = -1;
#pragma unroll 1
            for (;;) {
                while (bad || plain) {
                    if (bad) {
                        float a0, a1;
                        softmax_remax(s, m, n == 0 || n == nL, a0, a1);
                        shifted = true;
                        l[0] *= a0;
                        l[1] *= a1;
#pragma unroll
                        for (int i = 0; i < 64; i++) o[i] *= (i & 2) ? a1 : a0;
                    }
                    softmax_exp<0, 16>(s, p, t);
                    t[0] += t[1];
                    t[2] += t[3];
                    bad = !bad && softmax_unsafe(t[0], t[2], false);
                    plain = false;
                }
#pragma unroll 1
                do {
                    l[0] += t[0];
                    l[1] += t[2];
                    if (++n > 16) break;
                    const uint32_t ks = r;
                    uint32_t vs = ring_next(r);
                    r = ring_next(vs);
                    bar_sync(1 + wg, 256);
                    const float x = (float)((warp & 3) * 16 + g - 2 * c4);
                    if (n == hn) {
                        float sh[32];
                        qk_issue(sh, qa, kd + ks * (SLOT / 16));
                        slot_wait(sb + BAR_FULL, fph, vs);
                        pv_issue(o, p, vd + vs * (SLOT / 16), 1, false);
                        bar_arrive(2 - wg, 256);
                        wg_wait<1>();
                        reg_fence(sh);
                        tri_mask_copy(s, sh, x);
                        release_if(eb, ks, rel);
                        release_if(eb, 5 + wg, rel && (!wg || n == 16));
                        if (!wg) {
                            qa += SLOT / 16;
                            fence_async_smem();
                            if (shifted) softmax_shift(s, m[0], m[1]);
                        }
                        float e[4 * EARLY];
#pragma unroll
                        for (int i = 0; i < 4 * EARLY; i++) {
                            e[i] = ex2(s[i]);
                            t[i & 3] = i < 4 ? e[i] : t[i & 3] + e[i];
                        }
                        reg_fence(e);
                        slot_wait(sb + BAR_FULL, fph, r);
                        wg_wait<0>();
                        reg_fence(o);
                        reg_fence(e);
                        release_if(eb, vs, rel);
#pragma unroll
                        for (int i = 0; i < 2 * EARLY; i++) p[i] = pack2(e[2 * i], e[2 * i + 1]);
                        softmax_exp<EARLY, 8>(s, p, t);
                        if (wg) {
                            ctx_store<true>(limg, toff, o, l[0], l[1]);
                            __syncwarp();
                            mbar_arrive_if(sb + BAR_DONE + 24 + 32 * hp, lane == 0);
                            l[0] = l[1] = m[0] = m[1] = 0.f;
                            shifted = false;
                        }
                        t[0] += t[1];
                        t[2] += t[3];
                        bad = softmax_unsafe(t[0], t[2], wg);
                        continue;
                    }
                    if (n == 0 || n == nL) {
                        qk_issue(s, qa, kd + ks * (SLOT / 16));
                        if (n == 0) {
                            r = vs;
                            vs = 4 - hp;
                            slot_wait(sb + BAR_FULL, fph, 6);
                            gemm_issue<false>(o, qa + SLOT / 16, wd + vs * (SLOT / 16), 1, false);
                        } else {
                            slot_wait(sb + BAR_FULL, fph, vs);
                            pv_issue(o, p, vd + vs * (SLOT / 16), 1, true);
                        }
                        bar_arrive(2 - wg, 256);
                        const float i0 = n ? rcp(quad_sum(l[0])) : 1.f, i1 = n ? rcp(quad_sum(l[1])) : 1.f;
                        wg_wait<1>();
                        reg_fence(s);
                        release_if(eb, ks, rel);
                        release_if(eb, 6, rel && n == 16);
                        tri_mask(s, n ? x : 64.f);
                        float e[4 * EARLY];
#pragma unroll
                        for (int i = 0; i < 4 * EARLY; i++) {
                            e[i] = ex2(s[i]);
                            t[i & 3] = i < 4 ? e[i] : t[i & 3] + e[i];
                        }
                        reg_fence(e);
                        reg_fence(s);
                        reg_fence(t);
                        slot_wait(sb + BAR_FULL, fph, r);
                        if (SF & 1) sched_fence(fph, P.zero);
                        wg_wait<0>();
                        reg_fence(o);
                        reg_fence(e);
                        release_if(eb, vs, rel);
#pragma unroll
                        for (int i = 0; i < 2 * EARLY; i++) p[i] = pack2(e[2 * i], e[2 * i + 1]);
                        softmax_exp<EARLY, MSPLIT>(s, p, t);
                        tile_store(limg, sb + 6 * SLOT, toff, o, i0, i1, n);
                        reg_fence(t);
                        if (SF & 2) sched_fence(fph, P.zero);
                        reg_fence(s);
                        softmax_exp<MSPLIT, 16>(s, p, t);
                        __syncwarp();
                        mbar_arrive_if(sb + BAR_DONE + 24 + 32 * hp, lane == 0 && n);
                        l[0] = l[1] = m[0] = m[1] = 0.f;
                        shifted = false;
                        t[0] += t[1];
                        t[2] += t[3];
                        bad = __any_sync(0xffffffffu, fmaxf(t[0], t[2]) > SM_HI || fminf(t[0], t[2]) < SM_LO);
                        continue;
                    }
                    qk_issue(s, qa, kd + ks * (SLOT / 16));
                    slot_wait(sb + BAR_FULL, fph, vs);
                    pv_issue(o, p, vd + vs * (SLOT / 16), n != 1 && n != nL + 1, n == hn + 1);
                    bar_arrive(2 - wg, 256);
                    wg_wait<1>();
                    reg_fence(s);
                    release_if(eb, ks, rel);
                    release_if(eb, 6, rel && n == 16);
                    if (n == nL - 1) {
                        tri_mask(s, x);
                        release_if(eb, 5, rel);
                        qa += SLOT / 16;
                        fence_async_smem();
                    }
                    if (shifted) {
                        slot_wait(sb + BAR_FULL, fph, r);
                        wg_wait<0>();
                        reg_fence(o);
                        release_if(eb, vs, rel);
                        softmax_shift(s, m[0], m[1]);
                        plain = true;
                        break;
                    }
                    float e[4 * EARLY];
#pragma unroll
                    for (int i = 0; i < 4 * EARLY; i++) {
                        e[i] = ex2(s[i]);
                        t[i & 3] = i < 4 ? e[i] : t[i & 3] + e[i];
                    }
                    reg_fence(e);
                    slot_wait(sb + BAR_FULL, fph, r);
                    wg_wait<0>();
                    reg_fence(o);
                    reg_fence(e);
                    release_if(eb, vs, rel);
#pragma unroll
                    for (int i = 0; i < 2 * EARLY; i++) p[i] = pack2(e[2 * i], e[2 * i + 1]);
                    softmax_exp<EARLY, 16>(s, p, t);
                    t[0] += t[1];
                    t[2] += t[3];
                    bad = softmax_unsafe(t[0], t[2], false);
                } while (!bad);
                if (!bad && !plain) break;
            }
            const uint32_t vs = r, ga = desc_k(sb + (hp ? 2 * (wg ^ kh ^ 1) : wg) * 8192);
            r = ring_next(r);
            slot_wait(sb + BAR_FULL, fph, 5);
            slot_wait(sb + BAR_FULL, fph, r);
            bar_sync(1 + wg, 256);
            gemm_issue<true>(s, ga + 5 * (SLOT / 16), wd + r * (SLOT / 16), 0, hp);
            pv_issue(o, p, vd + vs * (SLOT / 16), j, hn == 16);
            bar_arrive(2 - wg, 256);
            li[0] = rcp(quad_sum(l[0]));
            li[1] = rcp(quad_sum(l[1]));
            cimg = limg + (ptrdiff_t)(2 * j - 15) * 32 * SLOT + (wg ? -16384 : 16384);
            wg_wait<1>();
            release_if(eb, 5, rel);
            release_if(eb, r, rel && hp);
            wg_wait<0>();
            release_if(eb, vs, rel);
            reg_fence(o);
            img_store_global<0>(cimg, toff, o, li[0], li[1]);
            if (elected) TS(8 + 10 * hp + 20 * wg);
        }
        uint32_t otab = 0x2351604u;
        const uint32_t oa = desc_k(sb + (wg ^ kh ^ 1) * 16384);
        const int t7 = tid & 127, w4 = warp & 3, row = ort * 128 + kh * 64 + w4 * 16 + g;
#pragma unroll 1
        for (int i = 1; i < 15 - wg; i++) {
            const uint32_t as = o_next(otab), ws = o_next(otab);
            slot_wait(sb + BAR_FULL, fph, as);
            slot_wait(sb + BAR_FULL, fph, ws);
            bar_sync(1 + wg, 256);
            gemm_issue<false>(s, oa + as * (SLOT / 16), wd + ws * (SLOT / 16), 1, true);
            bar_arrive(2 - wg, 256);
            wg_wait<1>();
            reg_fence(o);
            if (i == 1) img_store_global<1>(cimg, toff, o, li[0], li[1]);
            if (i == 2) {
                img_store_global<2>(cimg, toff, o, li[0], li[1]);
                img_store_global<3>(cimg, toff, o, li[0], li[1]);
                __syncwarp();
                mbar_arrive_if(sb + BAR_DONE + 64, lane == 0);
            }
            wg_wait<0>();
            release_if(eb, as, rel);
            release_if(eb, ws, rel);
        }
        mbar_wait(sb + BAR_PF, 0);
        const uint32_t ep = lds32(sb + SM_EP);
        uint32_t eb2 = sb + BAR_END;
        if (wg == 0) {
            reg_fence(s);
            if (elected) TS(9);
            TT(1);
#pragma unroll
            for (int v = 0; v < 8; v++)
                st_pub(g_out + rb * OB + v * 128 + t7, make_uint4((pack2(s[8 * v], s[8 * v + 1]) & ~1u) | (ep & 1), pack2(s[8 * v + 2], s[8 * v + 3]),
                                                                      pack2(s[8 * v + 4], s[8 * v + 5]), pack2(s[8 * v + 6], s[8 * v + 7])), true);
            constexpr uint32_t s1 = 5, s2 = 6;
            if (ELATE >= 0) bar_sync(4, 256);
            uint32_t wf[64];
            float wn[64];
            if (rb < NFFN) {
                slot_wait(sb + BAR_FULL, fph, s1);
                const uint32_t a = sb + s1 * SLOT + (w4 * 128 + (lane >> 4) * 8 + (lane & 7)) * 32 + (((lane >> 3) ^ (lane >> 2)) & 1) * 16;
#pragma unroll
                for (int i = 0; i < 16; i++)
                    asm volatile("ldmatrix.sync.aligned.m8n8.x4.trans.shared.b16 {%0, %1, %2, %3}, [%4];"
                                 : "=r"(wf[4 * i]), "=r"(wf[4 * i + 1]), "=r"(wf[4 * i + 2]), "=r"(wf[4 * i + 3])
                                 : "r"(a + (i >> 3) * 16384 + (i & 7) * 512) : "memory");
                slot_wait(sb + BAR_FULL, fph, s2);
#pragma unroll
                for (int i = 0; i < 16; i++) {
                    const uint2 w = *reinterpret_cast<const uint2*>(smem + s2 * SLOT + (kh ^ 1) * 16384 + i * 1024 + t7 * 8);
                    wn[4 * i] = bf_lo(w.x); wn[4 * i + 1] = bf_hi(w.x); wn[4 * i + 2] = bf_lo(w.y); wn[4 * i + 3] = bf_hi(w.y);
                }
                reg_fence(wn);
            }
            const uint32_t gbf = __ldcg(reinterpret_cast<const uint32_t*>(g_mod) + 1280 + rb * 2 + (tid & 1));
            if (elected) TS(10);
            TT(2);
            float* sred = reinterpret_cast<float*>(smem + SM_RED);
            uint32_t best = ep ^ 1, all;
            bool fresh;
            do {
                if (warp == 0) {
                    const uint2 k = best_key(g_key + cq * 128, lane, ep, best, rb < NFFN ? SPEC : 32);
                    *reinterpret_cast<uint2*>(smem + SM_EP + 24) = k;
                    mbar_arrive_if(sb + BAR_BEST, lane == 0 && k.y);
                }
                bar_sync(3, 128);
                const uint2 k = *reinterpret_cast<const uint2*>(smem + SM_EP + 24);
                fresh = k.x != best;
                best = k.x;
                all = k.y;
                TT(3);
                if (!fresh || rb >= NFFN) break;
                const uint4* cp = g_cand + ((~best >> 9) & 127) * 192;
                uint4 cv[6];
                for (;;) {
                    uint32_t bad = 0;
#pragma unroll
                    for (int v = 0; v < 6; v++) cv[v] = ld_poll(cp + w4 * 24 + v * 4 + c4);
#pragma unroll
                    for (int v = 0; v < 6; v++) bad |= cv[v].w ^ ep;
                    if (__all_sync(0xffffffffu, bad == 0)) break;
                    if (CSLEEP) __nanosleep(CSLEEP);
                }
            TT(4);
                float d[4][4] = {};
#pragma unroll
                for (int k = 0; k < 8; k++) {
                    const uint32_t b0 = (&cv[(2 * k) / 3].x)[(2 * k) % 3], b1 = (&cv[(2 * k + 1) / 3].x)[(2 * k + 1) % 3];
                    mma16816(d[k & 1], wf + 4 * k, b0, b1);
                    mma16816(d[2 + (k & 1)], wf + 32 + 4 * k, b0, b1);
                }
                const float u = (c4 & 2) ? ((c4 & 1) ? d[2][2] + d[3][2] : d[2][0] + d[3][0]) : ((c4 & 1) ? d[0][2] + d[1][2] : d[0][0] + d[1][0]);
                sred[w4 * 32 + c4 * 8 + g] = u;
                bar_sync(3, 128);
                const float v = rbf((sred[lane] + sred[32 + lane]) + (sred[64 + lane] + sred[96 + lane]));
                const float act = rbf(rbf(v * sigmoid(v)) * __shfl_down_sync(0xffffffffu, v, 16));
                float y[4] = {0.f, 0.f, 0.f, 0.f};
#pragma unroll
                for (int k = 0; k < 16; k++) {
                    const float a = __shfl_sync(0xffffffffu, act, k);
#pragma unroll
                    for (int i = 0; i < 4; i++) y[i] = fmaf(a, wn[4 * k + i], y[i]);
                }
                st_pub(g_out + rb * OB + OB_Y + t7, make_uint4((__float_as_uint(y[0]) & ~15u) | (ep & 15), (__float_as_uint(y[1]) & ~127u) | ((best >> 9) & 127),
                                                               __float_as_uint(y[2]), __float_as_uint(y[3])), true);
            } while (!all);
            const int sel = (~best >> 5) & 2047;
            const int pq = (2 * rb + (tid & 1)) & 63, pv = (pq >> 2) / 3;
            const uint4* fp = g_cand + (sel >> 4) * 192 + (rb >> 5) * 24 + pv * 4 + (pq & 3);
            uint4 fh = {}, fx = {};
            if (rb == 0 && tid == 0) g_sync.epoch[0] = ep;
            if (elected) TS(60);
            TT(5);
            uint4 yv;
            if (warp == 0) { fh = ld_poll(fp); fx = ld_poll(fp + 96); }
            if (fresh && rb < NFFN) __nanosleep(YPRE);
            for (;;) {
                yv = ld_poll(g_out + min(t7, NFFN - 1) * OB + OB_Y + rb);
                if (__all_sync(0xffffffffu, (((yv.x ^ ep) & 15) | ((yv.y ^ (best >> 9)) & 127)) == 0)) break;
                if (YSLEEP) __nanosleep(YSLEEP);
            }
            if (elected) TS(61);
            TT(6);
            float y[4] = {0.f, 0.f, 0.f, 0.f};
            if (t7 < NFFN) { y[0] = __uint_as_float(yv.x); y[1] = __uint_as_float(yv.y); y[2] = __uint_as_float(yv.z); y[3] = __uint_as_float(yv.w); }
            const float z0 = ((lane & 16) ? y[2] : y[0]) + __shfl_xor_sync(0xffffffffu, (lane & 16) ? y[0] : y[2], 16);
            const float z1 = ((lane & 16) ? y[3] : y[1]) + __shfl_xor_sync(0xffffffffu, (lane & 16) ? y[1] : y[3], 16);
            float z = ((lane & 8) ? z1 : z0) + __shfl_xor_sync(0xffffffffu, (lane & 8) ? z0 : z1, 8);
            z += __shfl_xor_sync(0xffffffffu, z, 4);
            z = quad_sum(z);
            if ((lane & 7) == 0) sred[128 + (lane >> 3) * 4 + w4] = z;
            bar_sync(3, 128);
            if (tid < 2) {
                while (fh.w != ep || fx.w != ep) { fh = ld_poll(fp); fx = ld_poll(fp + 96); }
                const float4 y0 = *reinterpret_cast<const float4*>(sred + 128 + tid * 8), y1 = *reinterpret_cast<const float4*>(sred + 132 + tid * 8);
                const int cm = (pq >> 2) - 3 * pv;
                const uint32_t h2 = cm == 0 ? fh.x : cm == 1 ? fh.y : fh.z, x2 = cm == 0 ? fx.x : cm == 1 ? fx.y : fx.z;
                const float sg = sigmoid(bf_hi((best & 0x80000000u) ? (best ^ 0x80000000u) : ~best));
                reinterpret_cast<uint32_t*>(P.out)[sel * 256 + rb * 2 + tid] =
                    badd(x2, bmul(gbf, badd(h2, bmul(pack2((y0.x + y0.y) + (y0.z + y0.w), (y1.x + y1.y) + (y1.z + y1.w)), pack2(sg, sg)))));
            }
            if (elected) TS(62);
            TT(7);
        } else {
            const float4* tf = reinterpret_cast<const float4*>(smem + SM_TAB) + c4;
            const uint32_t xa = sb + 4 * SLOT + (kh ^ 1) * 16384 + (w4 * 16 + (lane & 15)) * 128;
            uint32_t x2[32];
            bar_sync(2, 256);
#pragma unroll 1
            for (int i = 14; i < 17; i++) {
                const uint32_t as = o_next(otab), ws = o_next(otab);
                slot_wait(sb + BAR_FULL, fph, as);
                slot_wait(sb + BAR_FULL, fph, ws);
                gemm_issue<false>(s, oa + as * (SLOT / 16), wd + ws * (SLOT / 16), 1, true);
                wg_wait<1>();
            }
            const uint4* pr = g_out + (rb ^ (8 * OMAP)) * OB + t7;
            uint4 pa[8];
            if (PEARLY) {
#pragma unroll
                for (int v = 0; v < 8; v++) pa[v] = ld_poll(pr + v * 128);
            }
            if (elected) TS(29);
            TT(1);
            {
#pragma unroll
                for (int k = 0; k < 8; k++)
                    asm volatile("ldmatrix.sync.aligned.m8n8.x4.shared.b16 {%0, %1, %2, %3}, [%4];"
                                 : "=r"(x2[4 * k]), "=r"(x2[4 * k + 1]), "=r"(x2[4 * k + 2]), "=r"(x2[4 * k + 3])
                                 : "r"(xa + (k >> 2) * 8192 + (((2 * (k & 3) + (lane >> 4)) ^ (lane & 7)) << 4)) : "memory");
            }
            wg_wait<0>();
            reg_fence(s);
            if (!ELATE) bar_arrive(4, 256);
            if (elected) TS(39);
            TT(2);
            if (!PEARLY) {
#pragma unroll
                for (int v = 0; v < 8; v++) pa[v] = ld_poll(pr + v * 128);
            }
            float4 tc[16];
#pragma unroll
            for (int k = 0; k < 16; k++) {
                tc[k] = tf[k * 4];
                if (!(g & 1)) tc[k].z = __uint_as_float(ONE2);
#pragma unroll
                for (int i = 4 * k; i < 4 * k + 4; i++) s[i] = fmaf((i & 1) ? tc[k].y : tc[k].x, s[i], (i & 1) ? bf_hi(x2[i >> 1]) : bf_lo(x2[i >> 1]));
            }
            reg_fence(s);
            for (;;) {
                uint32_t bad = 0;
#pragma unroll
                for (int v = 0; v < 8; v++) bad |= pa[v].x ^ ep;
                if (__all_sync(0xffffffffu, (bad & 1) == 0)) break;
                if (PSLEEP) __nanosleep(PSLEEP);
#pragma unroll
                for (int v = 0; v < 8; v++) pa[v] = ld_poll(pr + v * 128);
            }
            if (ELATE == 1) bar_arrive(4, 256);
            if (elected) TS(30);
            TT(3);
            float sd[4] = {}, q0[4] = {}, q1[4] = {};
#pragma unroll
            for (int k = 0; k < 8; k++) {
#pragma unroll
                for (int i = 4 * k; i < 4 * k + 4; i++) {
                    const uint32_t w = (&pa[k].x)[i & 3];
                    x2[i] = pack2(fmaf(tc[i >> 1].x, bf_lo(w), s[2 * i]), fmaf(tc[i >> 1].y, bf_hi(w), s[2 * i + 1]));
                }
                mma16816(sd, x2 + 4 * k, __float_as_uint(tc[2 * k].z), __float_as_uint(tc[2 * k + 1].z));
                mma16816(q0, x2 + 4 * k, x2[4 * k], x2[4 * k + 2]);
                mma16816(q1, x2 + 4 * k, x2[4 * k + 1], x2[4 * k + 3]);
            }
            uint4* sp = g_out + rb * OB + OB_STAT + (w4 * 8 + g) * 2;
            st_pub(sp, make_uint4(__float_as_uint(sd[0]), __float_as_uint((g & 1) ? q0[1] : q0[0]), __float_as_uint(sd[1]), ep), c4 == g >> 1);
            st_pub(sp + 1, make_uint4(__float_as_uint(sd[2]), __float_as_uint((g & 1) ? q1[3] : q1[2]), __float_as_uint(sd[3]), ep), c4 == g >> 1);
            if (ELATE == 2) bar_arrive(4, 256);
            if (TF & 1) sched_fence(eb2, P.zero);
            if (elected) TS(56);
            TT(4);
            uint32_t cb[16], sh[16], gb[16];
#pragma unroll
            for (int i = 0; i < 16; i++) {
                const float4 c = tf[64 + i * 4];
                cb[i] = __float_as_uint(c.x); sh[i] = __float_as_uint(c.y); gb[i] = __float_as_uint(c.z);
            }
            const float ra = __uint_as_float(lds32(sb + SM_EP + 8)), rb0 = __uint_as_float(lds32(sb + SM_EP + 12));
            uint4 r0, r1;
            if (SPRE) __nanosleep(SPRE);
            for (;;) {
                r0 = ld_poll(g_out + ((rb & ~(16 * OMAP + 1)) + (c4 & 1) + (c4 & 2) * 8 * OMAP) * OB + OB_STAT + (w4 * 8 + g) * 2);
                r1 = ld_poll(g_out + ((rb & ~(16 * OMAP + 1)) + (c4 & 1) + (c4 & 2) * 8 * OMAP) * OB + OB_STAT + (w4 * 8 + g) * 2 + 1);
                if (__all_sync(0xffffffffu, r0.w == ep && r1.w == ep)) break;
                if (SSLEEP) __nanosleep(SSLEEP);
            }
            if (elected) TS(57);
            TT(5);
            const float m0 = quad_sum(__uint_as_float(r0.x)) * (1.f / 512.f), m1 = quad_sum(__uint_as_float(r1.x)) * (1.f / 512.f);
            const float rs0 = ln_rstd(fmaxf(fmaf(-m0, m0, quad_sum(__uint_as_float(r0.y)) * (1.f / 512.f)), 0.f));
            const float rs1 = ln_rstd(fmaxf(fmaf(-m1, m1, quad_sum(__uint_as_float(r1.y)) * (1.f / 512.f)), 0.f));
            const uint32_t mb0 = pack2(m0, m0), mb1 = pack2(m1, m1);
            const uint32_t lg = pack2(fmaf(rs0, fmaf(-bf_lo(mb0), ra, quad_sum(__uint_as_float(r0.z))), rb0),
                                      fmaf(rs1, fmaf(-bf_lo(mb1), ra, quad_sum(__uint_as_float(r1.z))), rb0));
            const uint32_t u0 = lg << 16, u1 = lg & 0xffff0000u;
            const uint32_t k0 = ((u0 ^ (((int)u0 >> 31) | 0x80000000u)) & 0xffff0000u) | ((2047 - row) << 5) | (ep & 31);
            const uint32_t k1 = ((u1 ^ (((int)u1 >> 31) | 0x80000000u)) & 0xffff0000u) | ((2039 - row) << 5) | (ep & 31);
            const uint32_t kb = __reduce_max_sync(0xffffffffu, max(k0, k1));
            st_pub(g_key + cq * 128 + (row >> 4), kb, lane == 0);
            const bool cand = kb == k0 || kb == k1;
            uint4* cp = g_cand + (row >> 4) * 192 + cq * 24 + c4;
#pragma unroll 1
            for (int it = 0; it < 3; it++) {
                bool put = it == 1 || !cand;
                if (it == 2) {
                    mbar_wait(sb + BAR_BEST, 0);
                    put = cand && lds32(sb + SM_EP + 24) != kb;
                }
                const bool hi = (kb == k1) != (it == 1);
                uint32_t cx[18], ch[18];
#pragma unroll
                for (int i = 0; i < 16; i++) {
                    cx[i] = hi ? x2[2 * i + 1] : x2[2 * i];
                    ch[i] = ln_apply(cx[i], hi ? mb1 : mb0, hi ? rs1 : rs0, cb[i], sh[i]);
                }
                cx[16] = cx[17] = ch[16] = ch[17] = 0;
#pragma unroll
                for (int v = 0; v < 6; v++) st_pub(cp + v * 4, make_uint4(ch[3 * v], ch[3 * v + 1], ch[3 * v + 2], ep), cand && it == 0);
                if (TF & 4) sched_fence(eb2, P.zero);
#pragma unroll
                for (int v = 0; v < 6; v++) st_pub(cp + 96 + v * 4, make_uint4(cx[3 * v], cx[3 * v + 1], cx[3 * v + 2], ep), cand && it == 0);
                if (it == 0) TT(6);
                uint2* op = reinterpret_cast<uint2*>(P.out) + (row + 8 * hi) * 128 + cq * 32 + (c4 & 1) * 2 + (c4 >> 1);
#pragma unroll
                for (int i = 0; i < 16; i += 2) {
                    const uint32_t v0 = badd(cx[i], bmul(gb[i], ch[i])), v1 = badd(cx[i + 1], bmul(gb[i + 1], ch[i + 1]));
                    const uint32_t rv = __shfl_xor_sync(0xffffffffu, (c4 & 1) ? v0 : v1, 1);
                    if (put) op[i * 2] = (c4 & 1) ? make_uint2(rv, v1) : make_uint2(v0, rv);
                }
            }
            if (elected) TS(59);
            TT(7);
        }
        mbar_arrive_if(eb2, lane == 0);
    }
}

typedef CUresult (*EncodeFn)(CUtensorMap*, CUtensorMapDataType, cuuint32_t, void*, const cuuint64_t*, const cuuint64_t*,
                             const cuuint32_t*, const cuuint32_t*, CUtensorMapInterleave, CUtensorMapSwizzle,
                             CUtensorMapL2promotion, CUtensorMapFloatOOBfill);

void make_2d(EncodeFn fn, CUtensorMap* m, const void* p, uint64_t cols, uint64_t rows, uint32_t bc, uint32_t br, CUtensorMapSwizzle sw) {
    cuuint64_t dims[2] = {cols, rows}, strides[1] = {cols * 2};
    cuuint32_t box[2] = {bc, br}, es[2] = {1, 1};
    fn(m, CU_TENSOR_MAP_DATA_TYPE_BFLOAT16, 2, const_cast<void*>(p), dims, strides, box, es, CU_TENSOR_MAP_INTERLEAVE_NONE,
       sw, CU_TENSOR_MAP_L2_PROMOTION_L2_128B, CU_TENSOR_MAP_FLOAT_OOB_FILL_NONE);
}
void make_3d(EncodeFn fn, CUtensorMap* m, const void* p, uint64_t cols, uint64_t rows, uint32_t br = 128, uint32_t nb = 2) {
    cuuint64_t dims[3] = {64, rows, cols / 64}, strides[2] = {cols * 2, 128};
    cuuint32_t box[3] = {64, br, nb}, es[3] = {1, 1, 1};
    fn(m, CU_TENSOR_MAP_DATA_TYPE_BFLOAT16, 3, const_cast<void*>(p), dims, strides, box, es, CU_TENSOR_MAP_INTERLEAVE_NONE,
       CU_TENSOR_MAP_SWIZZLE_128B, CU_TENSOR_MAP_L2_PROMOTION_L2_256B, CU_TENSOR_MAP_FLOAT_OOB_FILL_NONE);
}

}

extern "C" void kernel_launch(void* const* d_in, const int* in_sizes, int n_in, void* d_out, int out_size) {
    static EncodeFn fn = nullptr;
    if (!fn) {
        void* f = nullptr;
        cudaDriverEntryPointQueryResult st;
        cudaGetDriverEntryPoint("cuTensorMapEncodeTiled", &f, cudaEnableDefault, &st);
        fn = (EncodeFn)f;
        cudaFuncSetAttribute(fused_kernel, cudaFuncAttributeMaxDynamicSharedMemorySize, SMEM_BYTES);
    }
    CUtensorMap ckv, wq, wuk, wuv, wo, wg, wu, wm, xm;
    make_3d(fn, &ckv, d_in[1], 512, 2048, 128, 1);
    make_3d(fn, &xm, d_in[0], 512, 2048, 64);
    make_3d(fn, &wq, d_in[2], 4096, 512);
    make_3d(fn, &wuk, d_in[3], 4096, 512);
    make_3d(fn, &wuv, d_in[4], 4096, 512);
    make_3d(fn, &wo, d_in[5], 512, 4096);
    make_2d(fn, &wg, d_in[8], 1792, 512, 16, 256, CU_TENSOR_MAP_SWIZZLE_32B);
    make_2d(fn, &wu, d_in[9], 1792, 512, 16, 256, CU_TENSOR_MAP_SWIZZLE_32B);
    make_3d(fn, &wm, d_in[12], 3072, 512, 64, 4);
    Params p;
    p.x = (const bf16*)d_in[0];
    p.ckv = (const bf16*)d_in[1];
    p.wo = (const bf16*)d_in[5];
    p.wr = (const bf16*)d_in[7];
    p.wdown = (const bf16*)d_in[10];
    p.c = (const bf16*)d_in[11];
    p.out = (bf16*)d_out;
    p.zero = 0;
    fused_kernel<<<NCTA + NSPARE, 384, SMEM_BYTES>>>(ckv, wq, wuk, wuv, wo, wg, wu, wm, xm, p);
}
```

```cpp
#include <cuda.h>
#include <cuda_bf16.h>
#include <cuda_runtime.h>
#include <stdint.h>
#include <stdio.h>

namespace {

typedef __nv_bfloat16 bf16;
typedef unsigned long long u64;

constexpr int NCTA = 128, NSPARE = 4;
constexpr int SLOT = 32768;
constexpr int SM_BAR = 7 * SLOT;
constexpr int BAR_FULL = SM_BAR;
constexpr int BAR_EMPTY = BAR_FULL + 8 * 7;
constexpr int BAR_DONE = BAR_EMPTY + 8 * 7;
constexpr int BAR_FLAG = BAR_DONE + 8 * 9;
constexpr int BAR_PF = BAR_FLAG + 8 * 9;
constexpr int BAR_END = BAR_PF + 8;
constexpr int BAR_BEST = BAR_END + 8;
constexpr int SM_EP = BAR_END + 40;
constexpr int SM_RED = SM_BAR + 384;
constexpr int SM_TAB = SM_BAR + 1024;
constexpr int SMEM_BYTES = SM_BAR + 3072;
constexpr int NFFN = 112;
#define HINT 479
constexpr u64 L2_NORMAL = 0x1000000000000000ull, L2_FIRST = 0x12F0000000000000ull;
#define PFA 8
#define PFB 6
#define UNR 1
#define POLL_NS 50
#define MSPLIT 13
#define SF 3
#define NSH 1
#define XPF 1
#define TF 3
#define KSLEEP 200
#define YSLEEP 50
#define YPRE 150
#define SSLEEP 50
#define SPRE 0
#define PSLEEP 100
#define CSLEEP 0
#define SPEC 28
#define OMAP 2
#define KVG 7
#define PEARLY 0
#define ELATE 0
#define EARLY 7
constexpr uint32_t SPIN_LIMIT = 1u << 22;
constexpr uint32_t ONE2 = 0x3f803f80u;

struct Sync {
    uint32_t cnt[16 * 8 * 8];
    uint32_t ctxcnt[16 * 32];
    uint32_t epoch[32];
};

__device__ __align__(1024) uint8_t g_KV[16 * 16 * 2 * SLOT];
__device__ __align__(1024) uint8_t g_ctx[16 * 32 * SLOT];
__device__ __align__(1024) uint8_t g_h[16 * 4 * SLOT];
constexpr int OB = 1216, OB_STAT = 1024, OB_Y = 1088;
__device__ __align__(1024) uint4 g_out[128 * OB];
__device__ __align__(1024) bf16 g_mod[3072];
__device__ __align__(1024) uint32_t g_mod1[1024];
__device__ __align__(1024) uint4 g_cand[128 * 192];
__device__ __align__(1024) uint32_t g_key[4 * 128];
__device__ __align__(1024) uint8_t g_wf[NFFN * SLOT];
__device__ __align__(1024) Sync g_sync;
#define TS(i)

#define TT(i)
#define PT()

struct Params {
    const bf16 *x, *ckv, *wo, *wr, *wdown, *c;
    bf16* out;
    int zero;
};

__device__ __forceinline__ void mbar_init(uint32_t bar, uint32_t cnt) {
    asm volatile("mbarrier.init.shared::cta.b64 [%0], %1;" ::"r"(bar), "r"(cnt) : "memory");
}
__device__ __forceinline__ void mbar_wait(uint32_t bar, uint32_t parity) {
    asm volatile("{\n.reg .pred p;\nL_%=:\nmbarrier.try_wait.parity.shared::cta.b64 p, [%0], %1;\n@!p bra L_%=;\n}" ::"r"(bar), "r"(parity) : "memory");
}
__device__ __forceinline__ void mbar_sleep(uint32_t bar) {
    if ((threadIdx.x & 31) == 0)
        asm volatile("{\n.reg .pred p;\nL_%=:\nmbarrier.try_wait.parity.shared::cta.b64 p, [%0], 0, 100000;\n@!p bra L_%=;\n}" ::"r"(bar) : "memory");
    __syncwarp();
}
__device__ __forceinline__ void mbar_watch(uint32_t bar, uint32_t parity) {
    asm volatile("{\n.reg .pred p;\n.reg .u32 n;\nmov.u32 n, 0;\n"
                 "L_%=:\nmbarrier.try_wait.parity.shared::cta.b64 p, [%0], %1;\n@p bra D_%=;\n"
                 "add.u32 n, n, 1;\nsetp.lt.u32 p, n, %2;\n@p bra L_%=;\ntrap;\nD_%=:\n}"
                 ::"r"(bar), "r"(parity), "n"(SPIN_LIMIT) : "memory");
}
__device__ __forceinline__ void step_watch(uint32_t a, uint32_t step) {
    asm volatile("{\n.reg .pred p;\n.reg .u32 n, v;\nmov.u32 n, 0;\n"
                 "L_%=:\nld.volatile.shared.u32 v, [%0];\nsetp.ge.u32 p, v, %1;\n@p bra D_%=;\nnanosleep.u32 400;\n"
                 "add.u32 n, n, 1;\nsetp.lt.u32 p, n, %2;\n@p bra L_%=;\ntrap;\nD_%=:\n}"
                 ::"r"(a), "r"(step), "n"(SPIN_LIMIT) : "memory");
}
__device__ __forceinline__ void mbar_arrive_if(uint32_t bar, bool on) {
    asm volatile("{\n.reg .pred p;\nsetp.ne.s32 p, %1, 0;\n@p mbarrier.arrive.shared::cta.b64 _, [%0];\n}" ::"r"(bar), "r"((int)on) : "memory");
}
__device__ __forceinline__ void tma2d(uint32_t dst, const CUtensorMap* m, int c0, int c1, uint32_t bar, bool first) {
    asm volatile("{\n.reg .pred p;\nelect.sync _|p, 0xffffffff;\n"
                 "@p cp.async.bulk.tensor.2d.shared::cluster.global.mbarrier::complete_tx::bytes.L2::cache_hint [%0], [%1, {%3, %4}], [%2], %5;\n}"
                 ::"r"(dst), "l"(m), "r"(bar), "r"(c0), "r"(c1), "l"(first ? L2_FIRST : L2_NORMAL) : "memory");
}
__device__ __forceinline__ void tma3d_prefetch(const CUtensorMap* m, int row, int cb) {
    asm volatile("{\n.reg .pred p;\nelect.sync _|p, 0xffffffff;\n@p cp.async.bulk.prefetch.tensor.3d.L2.global [%0, {%1, %2, %3}];\n}"
                 ::"l"(m), "r"(0), "r"(row), "r"(cb) : "memory");
}
__device__ __forceinline__ void l2_prefetch(const void* p, uint32_t bytes) {
    asm volatile("{\n.reg .pred p;\nelect.sync _|p, 0xffffffff;\n@p cp.async.bulk.prefetch.L2.global [%0], %1;\n}" ::"l"(p), "r"(bytes) : "memory");
}
__device__ __forceinline__ void bulk_store(void* dst, uint32_t src, uint32_t bytes, bool first) {
    asm volatile("{\n.reg .pred p;\nelect.sync _|p, 0xffffffff;\n@p cp.async.bulk.global.shared::cta.bulk_group.L2::cache_hint [%0], [%1], %2, %3;\n}"
                 ::"l"(dst), "r"(src), "r"(bytes), "l"(first ? L2_FIRST : L2_NORMAL) : "memory");
}
__device__ __forceinline__ void flag_wait(const uint32_t* f, uint32_t target) {
    asm volatile("{\n.reg .pred p;\n.reg .u32 v;\n"
                 "L_%=:\nld.acquire.gpu.global.u32 v, [%0];\nsub.u32 v, v, %1;\nsetp.lt.s32 p, v, 0;\n@p nanosleep.u32 100;\n@p bra L_%=;\n}"
                 ::"l"(f), "r"(target) : "memory");
}
__device__ __forceinline__ uint4 ld_poll(const uint4* p) {
    uint4 v;
    asm volatile("{\n.reg .b128 t;\nld.relaxed.gpu.global.b128 t, [%4];\nmov.b128 {%0, %1, %2, %3}, t;\n}"
                 : "=r"(v.x), "=r"(v.y), "=r"(v.z), "=r"(v.w) : "l"(p) : "memory");
    return v;
}
__device__ __forceinline__ void st_pub(uint4* p, uint4 v, bool on) {
    asm volatile("{\n.reg .pred p;\n.reg .b128 t;\nsetp.ne.s32 p, %5, 0;\nmov.b128 t, {%1, %2, %3, %4};\n@p st.relaxed.gpu.global.b128 [%0], t;\n}"
                 ::"l"(p), "r"(v.x), "r"(v.y), "r"(v.z), "r"(v.w), "r"((int)on) : "memory");
}
__device__ __forceinline__ void st_pub(uint32_t* p, uint32_t v, bool on) {
    asm volatile("{\n.reg .pred p;\nsetp.ne.s32 p, %2, 0;\n@p st.relaxed.gpu.global.u32 [%0], %1;\n}" ::"l"(p), "r"(v), "r"((int)on) : "memory");
}
__device__ __forceinline__ void flag_add(uint32_t* p) {
    asm volatile("red.release.gpu.global.add.u32 [%0], 1;" ::"l"(p) : "memory");
}
__device__ __forceinline__ uint32_t lds32(uint32_t a) {
    uint32_t v;
    asm volatile("ld.shared.u32 %0, [%1];" : "=r"(v) : "r"(a) : "memory");
    return v;
}
__device__ __forceinline__ uint4 lds128(uint32_t a) {
    uint4 v;
    asm volatile("ld.shared.v4.u32 {%0, %1, %2, %3}, [%4];" : "=r"(v.x), "=r"(v.y), "=r"(v.z), "=r"(v.w) : "r"(a) : "memory");
    return v;
}
__device__ __forceinline__ void sched_fence(uint32_t& v, uint32_t z) {
    uint32_t ck;
    asm volatile("mov.u32 %0, %%clock;" : "=r"(ck)::"memory");
    v ^= ck & z;
}
__device__ __forceinline__ void fence_async_global() { asm volatile("fence.proxy.async.global;" ::: "memory"); }
__device__ __forceinline__ void fence_async_smem() { asm volatile("fence.proxy.async.shared::cta;" ::: "memory"); }
__device__ __forceinline__ void bar_sync(int id, int n) { asm volatile("bar.sync %0, %1;" ::"r"(id), "r"(n) : "memory"); }
__device__ __forceinline__ void bar_arrive(int id, int n) { asm volatile("bar.arrive %0, %1;" ::"r"(id), "r"(n) : "memory"); }
__device__ __forceinline__ void wg_fence() { asm volatile("wgmma.fence.sync.aligned;" ::: "memory"); }
__device__ __forceinline__ void wg_commit() { asm volatile("wgmma.commit_group.sync.aligned;" ::: "memory"); }
template <int N> __device__ __forceinline__ void wg_wait() { asm volatile("wgmma.wait_group.sync.aligned %0;" ::"n"(N) : "memory"); }
template <int N> __device__ __forceinline__ void reg_fence(float (&d)[N]) {
#pragma unroll
    for (int i = 0; i < N; i++) asm volatile("" : "+f"(d[i])::"memory");
}
template <int N> __device__ __forceinline__ void reg_fence(uint32_t (&d)[N]) {
#pragma unroll
    for (int i = 0; i < N; i++) asm volatile("" : "+r"(d[i])::"memory");
}
__device__ __forceinline__ uint32_t desc_k(uint32_t a) { return ((a & 0x3ffff) >> 4) | (1u << 16); }
__device__ __forceinline__ uint32_t desc_mn(uint32_t a) { return ((a & 0x3ffff) >> 4) | (1024u << 16); }

__device__ __forceinline__ uint64_t desc64(uint32_t lo, uint32_t hi) {
    uint64_t d;
    asm("mov.b64 %0, {%1, %2};" : "=l"(d) : "r"(lo), "r"(hi));
    return d;
}
__device__ __forceinline__ void desc_add(uint64_t& d, uint32_t x) { asm("add.u64 %0, %0, %1;" : "+l"(d) : "l"((uint64_t)x)); }

template <int TB>
__device__ __forceinline__ void wgmma_ss128(float (&d)[64], uint64_t da, uint64_t db, int acc) {
    asm volatile("{\n.reg .pred p;\nsetp.ne.b32 p, %66, 0;\n"
        "wgmma.mma_async.sync.aligned.m64n128k16.f32.bf16.bf16 {%0, %1, %2, %3, %4, %5, %6, %7, %8, %9, %10, %11, %12, %13, %14, %15, %16, %17, %18, %19, %20, %21, %22, %23, %24, %25, %26, %27, %28, %29, %30, %31, %32, %33, %34, %35, %36, %37, %38, %39, %40, %41, %42, %43, %44, %45, %46, %47, %48, %49, %50, %51, %52, %53, %54, %55, %56, %57, %58, %59, %60, %61, %62, %63}, %64, %65, p, 1, 1, 0, %67;\n}"
        : "+f"(d[0]), "+f"(d[1]), "+f"(d[2]), "+f"(d[3]), "+f"(d[4]), "+f"(d[5]), "+f"(d[6]), "+f"(d[7]), "+f"(d[8]), "+f"(d[9]), "+f"(d[10]), "+f"(d[11]), "+f"(d[12]), "+f"(d[13]), "+f"(d[14]), "+f"(d[15]), "+f"(d[16]), "+f"(d[17]), "+f"(d[18]), "+f"(d[19]), "+f"(d[20]), "+f"(d[21]), "+f"(d[22]), "+f"(d[23]), "+f"(d[24]), "+f"(d[25]), "+f"(d[26]), "+f"(d[27]), "+f"(d[28]), "+f"(d[29]), "+f"(d[30]), "+f"(d[31]), "+f"(d[32]), "+f"(d[33]), "+f"(d[34]), "+f"(d[35]), "+f"(d[36]), "+f"(d[37]), "+f"(d[38]), "+f"(d[39]), "+f"(d[40]), "+f"(d[41]), "+f"(d[42]), "+f"(d[43]), "+f"(d[44]), "+f"(d[45]), "+f"(d[46]), "+f"(d[47]), "+f"(d[48]), "+f"(d[49]), "+f"(d[50]), "+f"(d[51]), "+f"(d[52]), "+f"(d[53]), "+f"(d[54]), "+f"(d[55]), "+f"(d[56]), "+f"(d[57]), "+f"(d[58]), "+f"(d[59]), "+f"(d[60]), "+f"(d[61]), "+f"(d[62]), "+f"(d[63])
        : "l"(da), "l"(db), "r"(acc), "n"(TB));
}
template <int TB>
__device__ __forceinline__ void wgmma_ss128_init(float (&d)[64], uint64_t da, uint64_t db) {
    asm volatile("{\n.reg .pred p;\nsetp.ne.b32 p, 0, 0;\n"
        "wgmma.mma_async.sync.aligned.m64n128k16.f32.bf16.bf16 {%0, %1, %2, %3, %4, %5, %6, %7, %8, %9, %10, %11, %12, %13, %14, %15, %16, %17, %18, %19, %20, %21, %22, %23, %24, %25, %26, %27, %28, %29, %30, %31, %32, %33, %34, %35, %36, %37, %38, %39, %40, %41, %42, %43, %44, %45, %46, %47, %48, %49, %50, %51, %52, %53, %54, %55, %56, %57, %58, %59, %60, %61, %62, %63}, %64, %65, p, 1, 1, 0, %66;\n}"
        : "=f"(d[0]), "=f"(d[1]), "=f"(d[2]), "=f"(d[3]), "=f"(d[4]), "=f"(d[5]), "=f"(d[6]), "=f"(d[7]), "=f"(d[8]), "=f"(d[9]), "=f"(d[10]), "=f"(d[11]), "=f"(d[12]), "=f"(d[13]), "=f"(d[14]), "=f"(d[15]), "=f"(d[16]), "=f"(d[17]), "=f"(d[18]), "=f"(d[19]), "=f"(d[20]), "=f"(d[21]), "=f"(d[22]), "=f"(d[23]), "=f"(d[24]), "=f"(d[25]), "=f"(d[26]), "=f"(d[27]), "=f"(d[28]), "=f"(d[29]), "=f"(d[30]), "=f"(d[31]), "=f"(d[32]), "=f"(d[33]), "=f"(d[34]), "=f"(d[35]), "=f"(d[36]), "=f"(d[37]), "=f"(d[38]), "=f"(d[39]), "=f"(d[40]), "=f"(d[41]), "=f"(d[42]), "=f"(d[43]), "=f"(d[44]), "=f"(d[45]), "=f"(d[46]), "=f"(d[47]), "=f"(d[48]), "=f"(d[49]), "=f"(d[50]), "=f"(d[51]), "=f"(d[52]), "=f"(d[53]), "=f"(d[54]), "=f"(d[55]), "=f"(d[56]), "=f"(d[57]), "=f"(d[58]), "=f"(d[59]), "=f"(d[60]), "=f"(d[61]), "=f"(d[62]), "=f"(d[63])
        : "l"(da), "l"(db), "n"(TB));
}
template <int TB>
__device__ __forceinline__ void wgmma_ss64(float (&d)[32], uint64_t da, uint64_t db, int acc) {
    asm volatile("{\n.reg .pred p;\nsetp.ne.b32 p, %34, 0;\n"
        "wgmma.mma_async.sync.aligned.m64n64k16.f32.bf16.bf16 {%0, %1, %2, %3, %4, %5, %6, %7, %8, %9, %10, %11, %12, %13, %14, %15, %16, %17, %18, %19, %20, %21, %22, %23, %24, %25, %26, %27, %28, %29, %30, %31}, %32, %33, p, 1, 1, 0, %35;\n}"
        : "+f"(d[0]), "+f"(d[1]), "+f"(d[2]), "+f"(d[3]), "+f"(d[4]), "+f"(d[5]), "+f"(d[6]), "+f"(d[7]), "+f"(d[8]), "+f"(d[9]), "+f"(d[10]), "+f"(d[11]), "+f"(d[12]), "+f"(d[13]), "+f"(d[14]), "+f"(d[15]), "+f"(d[16]), "+f"(d[17]), "+f"(d[18]), "+f"(d[19]), "+f"(d[20]), "+f"(d[21]), "+f"(d[22]), "+f"(d[23]), "+f"(d[24]), "+f"(d[25]), "+f"(d[26]), "+f"(d[27]), "+f"(d[28]), "+f"(d[29]), "+f"(d[30]), "+f"(d[31])
        : "l"(da), "l"(db), "r"(acc), "n"(TB));
}
template <int TB>
__device__ __forceinline__ void wgmma_ss64_init(float (&d)[32], uint64_t da, uint64_t db) {
    asm volatile("{\n.reg .pred p;\nsetp.ne.b32 p, 0, 0;\n"
        "wgmma.mma_async.sync.aligned.m64n64k16.f32.bf16.bf16 {%0, %1, %2, %3, %4, %5, %6, %7, %8, %9, %10, %11, %12, %13, %14, %15, %16, %17, %18, %19, %20, %21, %22, %23, %24, %25, %26, %27, %28, %29, %30, %31}, %32, %33, p, 1, 1, 0, %34;\n}"
        : "=f"(d[0]), "=f"(d[1]), "=f"(d[2]), "=f"(d[3]), "=f"(d[4]), "=f"(d[5]), "=f"(d[6]), "=f"(d[7]), "=f"(d[8]), "=f"(d[9]), "=f"(d[10]), "=f"(d[11]), "=f"(d[12]), "=f"(d[13]), "=f"(d[14]), "=f"(d[15]), "=f"(d[16]), "=f"(d[17]), "=f"(d[18]), "=f"(d[19]), "=f"(d[20]), "=f"(d[21]), "=f"(d[22]), "=f"(d[23]), "=f"(d[24]), "=f"(d[25]), "=f"(d[26]), "=f"(d[27]), "=f"(d[28]), "=f"(d[29]), "=f"(d[30]), "=f"(d[31])
        : "l"(da), "l"(db), "n"(TB));
}
__device__ __forceinline__ void wgmma_rs128(float (&d)[64], uint32_t a0, uint32_t a1, uint32_t a2, uint32_t a3, uint64_t db, int acc) {
    asm volatile("{\n.reg .pred p;\nsetp.ne.b32 p, %69, 0;\n"
        "wgmma.mma_async.sync.aligned.m64n128k16.f32.bf16.bf16 {%0, %1, %2, %3, %4, %5, %6, %7, %8, %9, %10, %11, %12, %13, %14, %15, %16, %17, %18, %19, %20, %21, %22, %23, %24, %25, %26, %27, %28, %29, %30, %31, %32, %33, %34, %35, %36, %37, %38, %39, %40, %41, %42, %43, %44, %45, %46, %47, %48, %49, %50, %51, %52, %53, %54, %55, %56, %57, %58, %59, %60, %61, %62, %63}, {%64, %65, %66, %67}, %68, p, 1, 1, 1;\n}"
        : "+f"(d[0]), "+f"(d[1]), "+f"(d[2]), "+f"(d[3]), "+f"(d[4]), "+f"(d[5]), "+f"(d[6]), "+f"(d[7]), "+f"(d[8]), "+f"(d[9]), "+f"(d[10]), "+f"(d[11]), "+f"(d[12]), "+f"(d[13]), "+f"(d[14]), "+f"(d[15]), "+f"(d[16]), "+f"(d[17]), "+f"(d[18]), "+f"(d[19]), "+f"(d[20]), "+f"(d[21]), "+f"(d[22]), "+f"(d[23]), "+f"(d[24]), "+f"(d[25]), "+f"(d[26]), "+f"(d[27]), "+f"(d[28]), "+f"(d[29]), "+f"(d[30]), "+f"(d[31]), "+f"(d[32]), "+f"(d[33]), "+f"(d[34]), "+f"(d[35]), "+f"(d[36]), "+f"(d[37]), "+f"(d[38]), "+f"(d[39]), "+f"(d[40]), "+f"(d[41]), "+f"(d[42]), "+f"(d[43]), "+f"(d[44]), "+f"(d[45]), "+f"(d[46]), "+f"(d[47]), "+f"(d[48]), "+f"(d[49]), "+f"(d[50]), "+f"(d[51]), "+f"(d[52]), "+f"(d[53]), "+f"(d[54]), "+f"(d[55]), "+f"(d[56]), "+f"(d[57]), "+f"(d[58]), "+f"(d[59]), "+f"(d[60]), "+f"(d[61]), "+f"(d[62]), "+f"(d[63])
        : "r"(a0), "r"(a1), "r"(a2), "r"(a3), "l"(db), "r"(acc));
}

__device__ __forceinline__ uint32_t pack2(float lo, float hi) {
    uint32_t r;
    asm("cvt.rn.bf16x2.f32 %0, %1, %2;" : "=r"(r) : "f"(hi), "f"(lo));
    return r;
}
__device__ __forceinline__ float bf_lo(uint32_t v) { return __uint_as_float(v << 16); }
__device__ __forceinline__ float bf_hi(uint32_t v) { return __uint_as_float(v & 0xffff0000u); }
__device__ __forceinline__ float rbf(float v) { return bf_lo(pack2(v, v)); }
__device__ __forceinline__ uint32_t badd(uint32_t a, uint32_t b) {
    uint32_t r;
    asm("add.rn.bf16x2 %0, %1, %2;" : "=r"(r) : "r"(a), "r"(b));
    return r;
}
__device__ __forceinline__ uint32_t bsub(uint32_t a, uint32_t b) {
    uint32_t r;
    asm("sub.rn.bf16x2 %0, %1, %2;" : "=r"(r) : "r"(a), "r"(b));
    return r;
}
__device__ __forceinline__ uint32_t bmul(uint32_t a, uint32_t b) {
    uint32_t r;
    asm("mul.rn.bf16x2 %0, %1, %2;" : "=r"(r) : "r"(a), "r"(b));
    return r;
}
__device__ __forceinline__ uint32_t ln_apply(uint32_t x, uint32_t mb, float rs, uint32_t scale, uint32_t shift) {
    const uint32_t d = bsub(x, mb);
    return badd(bmul(pack2(bf_lo(d) * rs, bf_hi(d) * rs), scale), shift);
}
__device__ __forceinline__ float ex2(float v) {
    float r;
    asm("ex2.approx.ftz.f32 %0, %1;" : "=f"(r) : "f"(v));
    return r;
}
__device__ __forceinline__ float rcp(float v) {
    float r;
    asm("rcp.approx.ftz.f32 %0, %1;" : "=f"(r) : "f"(v));
    return r;
}
__device__ __forceinline__ float sqrt_fast(float v) {
    float r;
    asm("sqrt.approx.ftz.f32 %0, %1;" : "=f"(r) : "f"(v));
    return r;
}
__device__ __forceinline__ float ln_rstd(float var) { return rcp(rbf(sqrt_fast(rbf(rbf(var) + 1e-5f)))); }
__device__ __forceinline__ float sigmoid(float v) { return rcp(1.f + ex2(-1.4426950408889634f * v)); }
__device__ __forceinline__ float quad_sum(float v) {
    v += __shfl_xor_sync(0xffffffffu, v, 1);
    return v + __shfl_xor_sync(0xffffffffu, v, 2);
}

constexpr uint32_t HI_128 = 0x40000040u, HI_IMG = 0x80000080u, HI_Q = 0x80000040u;
template <int M, int RH>
__device__ __forceinline__ uint4 img_pack(const float (&d)[64], float s) {
    uint4 v;
    v.x = pack2(d[16 * M + 2 * RH] * s, d[16 * M + 2 * RH + 1] * s);
    v.y = pack2(d[16 * M + 4 + 2 * RH] * s, d[16 * M + 5 + 2 * RH] * s);
    v.z = pack2(d[16 * M + 8 + 2 * RH] * s, d[16 * M + 9 + 2 * RH] * s);
    v.w = pack2(d[16 * M + 12 + 2 * RH] * s, d[16 * M + 13 + 2 * RH] * s);
    return v;
}
template <int M>
__device__ __forceinline__ void img_store_global(uint8_t* img, uint32_t toff, const float (&d)[64], float s0, float s1) {
    uint4* p = reinterpret_cast<uint4*>(img + toff) + M * 32;
    p[0] = img_pack<M, 0>(d, s0);
    p[128] = img_pack<M, 1>(d, s1);
}
__device__ __forceinline__ void sts128(uint32_t a, uint4 v) {
    asm volatile("st.shared.v4.b32 [%0], {%1, %2, %3, %4};" ::"r"(a), "r"(v.x), "r"(v.y), "r"(v.z), "r"(v.w) : "memory");
}
constexpr float SM_C = 0.08838834764831845f * 1.4426950408889634f;
__device__ __forceinline__ float pack2f(float lo, float hi) {
    float r;
    asm("{\n.reg .b32 t;\ncvt.rn.bf16x2.f32 t, %1, %2;\nmov.b32 %0, t;\n}" : "=f"(r) : "f"(hi), "f"(lo));
    return r;
}
template <int M, bool SCALE, bool PARK>
__device__ __forceinline__ void pack_group(float (&d)[64], float (&v)[8], float s0, float s1) {
#pragma unroll
    for (int i = 0; i < 8; i++) {
        const int k = 16 * M + 4 * (i & 3) + 2 * (i >> 2);
        v[i] = SCALE ? pack2f(d[k] * (i < 4 ? s0 : s1), d[k + 1] * (i < 4 ? s0 : s1)) : pack2f(d[k], d[k + 1]);
        if (PARK && M > 0) d[16 * (M > 0 ? M - 1 : 0) + i] = v[i];
    }
}
__device__ __forceinline__ uint32_t q_off(uint32_t toff) { return (((toff >> 1) & ~2047u) ^ 8192) + (toff & 511); }
template <int M, bool PARK>
__device__ __forceinline__ void ctx_store_part(float4* p, float (&d)[64], float i0, float i1) {
    float v[8];
    pack_group<M, true, PARK>(d, v, i0, i1);
    p[M * 32] = make_float4(v[0], v[1], v[2], v[3]);
    p[M * 32 + 128] = make_float4(v[4], v[5], v[6], v[7]);
}
template <bool PARK>
__device__ __forceinline__ void ctx_store(uint8_t* img, uint32_t toff, float (&o)[64], float l0, float l1) {
    const float i0 = rcp(quad_sum(l0)), i1 = rcp(quad_sum(l1));
    float4* p = reinterpret_cast<float4*>(img + toff);
    ctx_store_part<0, PARK>(p, o, i0, i1); ctx_store_part<1, PARK>(p, o, i0, i1); ctx_store_part<2, PARK>(p, o, i0, i1); ctx_store_part<3, PARK>(p, o, i0, i1);
}

template <int M>
__device__ __forceinline__ void tile_store_part(float4* p, uint32_t a, float (&d)[64], float i0, float i1, int ctx) {
    float v[8];
    pack_group<M, true, true>(d, v, i0, i1);
#pragma unroll
    for (int h = 0; h < 2; h++)
        asm volatile("{\n.reg .pred p;\nsetp.ne.s32 p, %6, 0;\n@p st.global.v4.f32 [%0], {%2, %3, %4, %5};\n@!p st.shared.v4.f32 [%1], {%2, %3, %4, %5};\n}"
                     ::"l"(p + M * 32 + h * 128), "r"(a + (M >> 1) * 16384 + (M & 1) * 512 + h * 1024),
                     "f"(v[4 * h]), "f"(v[4 * h + 1]), "f"(v[4 * h + 2]), "f"(v[4 * h + 3]), "r"(ctx) : "memory");
}
__device__ __forceinline__ void tile_store(uint8_t* img, uint32_t a, uint32_t toff, float (&d)[64], float i0, float i1, int ctx) {
    float4* p = reinterpret_cast<float4*>(img + toff);
    a += q_off(toff);
    tile_store_part<0>(p, a, d, i0, i1, ctx); tile_store_part<1>(p, a, d, i0, i1, ctx);
    tile_store_part<2>(p, a, d, i0, i1, ctx); tile_store_part<3>(p, a, d, i0, i1, ctx);
}

__device__ __forceinline__ void slot_wait(uint32_t bars, uint32_t& ph, uint32_t slot) {
    mbar_wait(bars + 8 * slot, (ph >> slot) & 1);
    ph ^= 1u << slot;
}
__device__ __forceinline__ void release_if(uint32_t eb, uint32_t slot, bool on) {
    asm volatile("{\n.reg .pred p;\nsetp.ne.s32 p, %1, 0;\n@p mbarrier.arrive.shared::cluster.b64 _, [%0];\n}" ::"r"(eb + 8 * slot), "r"((int)on) : "memory");
}
__device__ __forceinline__ void slot_expect(uint32_t sb, uint32_t slot) {
    asm volatile("{\n.reg .pred p;\nelect.sync _|p, 0xffffffff;\n@p mbarrier.arrive.expect_tx.shared::cta.b64 _, [%0], 32768;\n}"
                 ::"r"(sb + BAR_FULL + 8 * slot) : "memory");
}
__device__ __forceinline__ void slot_acquire(uint32_t sb, uint32_t& ph, uint32_t slot) {
    slot_wait(sb + BAR_EMPTY, ph, slot);
    slot_expect(sb, slot);
}
__device__ __forceinline__ void load_bulk(uint32_t sb, uint32_t slot, uint32_t off, const void* src, uint32_t bytes, bool both, bool first) {
    if (both)
        asm volatile("{\n.reg .pred p;\nelect.sync _|p, 0xffffffff;\n"
                     "@p cp.async.bulk.shared::cluster.global.mbarrier::complete_tx::bytes.multicast::cluster.L2::cache_hint [%0], [%1], %5, [%2], %4, %3;\n}"
                     ::"r"(sb + slot * SLOT + off), "l"(src), "r"(sb + BAR_FULL + 8 * slot), "l"(first ? L2_FIRST : L2_NORMAL), "h"((uint16_t)3),
                     "r"(bytes) : "memory");
    else
        asm volatile("{\n.reg .pred p;\nelect.sync _|p, 0xffffffff;\n"
                     "@p cp.async.bulk.shared::cluster.global.mbarrier::complete_tx::bytes.L2::cache_hint [%0], [%1], %4, [%2], %3;\n}"
                     ::"r"(sb + slot * SLOT + off), "l"(src), "r"(sb + BAR_FULL + 8 * slot), "l"(first ? L2_FIRST : L2_NORMAL), "r"(bytes) : "memory");
}
__device__ __forceinline__ void load_tile(uint32_t sb, uint32_t slot, uint32_t off, const CUtensorMap* m, int row, int cb, bool both, bool first) {
    if (both)
        asm volatile("{\n.reg .pred p;\nelect.sync _|p, 0xffffffff;\n"
                     "@p cp.async.bulk.tensor.3d.shared::cluster.global.mbarrier::complete_tx::bytes.multicast::cluster.L2::cache_hint [%0], [%1, {%3, %4, %5}], [%2], %7, %6;\n}"
                     ::"r"(sb + slot * SLOT + off), "l"(m), "r"(sb + BAR_FULL + 8 * slot), "r"(0), "r"(row), "r"(cb),
                     "l"(first ? L2_FIRST : L2_NORMAL), "h"((uint16_t)3) : "memory");
    else
        asm volatile("{\n.reg .pred p;\nelect.sync _|p, 0xffffffff;\n"
                     "@p cp.async.bulk.tensor.3d.shared::cluster.global.mbarrier::complete_tx::bytes.L2::cache_hint [%0], [%1, {%3, %4, %5}], [%2], %6;\n}"
                     ::"r"(sb + slot * SLOT + off), "l"(m), "r"(sb + BAR_FULL + 8 * slot), "r"(0), "r"(row), "r"(cb),
                     "l"(first ? L2_FIRST : L2_NORMAL) : "memory");
}
__device__ __forceinline__ uint32_t ring_next(uint32_t r) { return r == 4 ? 0 : r + 1; }
__device__ __forceinline__ uint32_t w_table(int hp) { return hp ? 0x3104u : 0x4210u; }
__device__ __forceinline__ uint32_t a_table(int hp) { return hp ? 0x625u : 0x635u; }
__device__ __forceinline__ uint32_t a_next(uint32_t& t) {
    const uint32_t s = t & 15;
    t = (t >> 4) | (s << 8);
    return s;
}
constexpr uint32_t O_TABLE = 0x1604235u;
__device__ __forceinline__ uint32_t o_next(uint32_t& t) {
    const uint32_t s = t & 15;
    t = (t >> 4) | (s << 24);
    return s;
}
__device__ __forceinline__ int o_head(int i, int kh) { return i < 16 ? 4 * (i & 7) + 2 * (kh ^ 1) + (i >> 3) : 29 + 2 * kh; }

template <bool INIT>
__device__ __forceinline__ void gemm_issue(float (&d)[64], uint32_t a, uint32_t b, int acc, bool img) {
    uint64_t da = desc64(a, img ? HI_IMG : HI_128), db = desc64(b, HI_128);
    wg_fence();
#pragma unroll
    for (int k = 0; k < 8; k++) {
        if (INIT && k == 0) wgmma_ss128_init<1>(d, da, db);
        else wgmma_ss128<1>(d, da, db, k ? 1 : acc);
        desc_add(da, !(k & 1) ? 2 : img ? 30 : k == 3 ? 1018 : 2);
        desc_add(db, 128);
    }
    wg_commit();
}

template <bool ODD>
__device__ __forceinline__ bool proj_tile(float (&acc)[64], float (&prev)[64], int t, int q0, uint32_t sb, int wg, uint32_t eb, bool rel, uint32_t& fph,
                                          uint32_t wtab, uint32_t& atab, uint8_t* prev_img, uint32_t toff, float s0, float s1,
                                          uint32_t (&v)[32]) {
    const uint32_t a0 = desc_k(sb + (wg ^ (ODD && t == 5)) * 8192), b0 = desc_mn(sb);
    constexpr int U = ODD ? UNR : 1;
#pragma unroll U
    for (int q = ODD ? 0 : q0; q < 4; q++) {
        const uint32_t ws = (wtab >> (4 * q)) & 15, as = a_next(atab);
        if (!ODD && t != 2) slot_wait(sb + BAR_FULL, fph, ws);
        slot_wait(sb + BAR_FULL, fph, as);
        if (ODD && q == 2 && t == 5) {
#pragma unroll
            for (int i = 0; i < 8; i++) sts128(sb + 5 * SLOT + q_off(toff) + (i >> 2) * 16384 + (i & 2) * 256 + (i & 1) * 1024, make_uint4(v[4 * i], v[4 * i + 1], v[4 * i + 2], v[4 * i + 3]));
        }
        bar_sync(1 + wg, 256);
        gemm_issue<false>(acc, a0 + as * (SLOT / 16), b0 + ws * (SLOT / 16), q, false);
        bar_arrive(2 - wg, 256);
        wg_wait<1>();
        reg_fence(prev);
        if (ODD && t == 5) {
            if (q == 0) {
#pragma unroll
                for (int i = 0; i < 32; i++) {
                    const int k = 16 * (i >> 3) + 4 * (i & 3) + ((i >> 1) & 2);
                    v[i] = pack2(prev[k], prev[k + 1]);
                }
            }
            if (q == 2) {
                fence_async_smem();
                slot_wait(sb + BAR_FULL, fph, wtab & 15);
                wg_wait<0>();
                release_if(eb, as, rel);
                release_if(eb, ws, rel);
                reg_fence(acc);
                return true;
            }
        } else {
            if (q == 0) img_store_global<0>(prev_img, toff, prev, s0, s1);
            if (q == 1) img_store_global<1>(prev_img, toff, prev, s0, s1);
            if (q == 2) img_store_global<2>(prev_img, toff, prev, s0, s1);
            if (q == 3) img_store_global<3>(prev_img, toff, prev, s0, s1);
        }
        wg_wait<0>();
        release_if(eb, as, rel && !(ODD && (q & 1) && t == 5));
        if (ODD) release_if(eb, ws, rel && t != 1);
    }
    reg_fence(acc);
    return false;
}

__device__ __forceinline__ void qk_issue(float (&s)[64], uint32_t q, uint32_t k) {
    wg_fence();
    uint64_t da = desc64(q, HI_Q), db = desc64(k, HI_IMG);
    wgmma_ss128_init<0>(s, da, db);
#pragma unroll
    for (int i = 1; i < 8; i++) {
        desc_add(da, (i & 1) ? 2 : i == 4 ? 990 : 30);
        desc_add(db, (i & 1) ? 2 : 30);
        wgmma_ss128<0>(s, da, db, 1);
    }
    wg_commit();
}
__device__ __forceinline__ void qk_issue(float (&s)[32], uint32_t q, uint32_t k) {
    wg_fence();
    uint64_t da = desc64(q, HI_Q), db = desc64(k, HI_IMG);
    wgmma_ss64_init<0>(s, da, db);
#pragma unroll
    for (int i = 1; i < 8; i++) {
        desc_add(da, (i & 1) ? 2 : i == 4 ? 990 : 30);
        desc_add(db, (i & 1) ? 2 : 30);
        wgmma_ss64<0>(s, da, db, 1);
    }
    wg_commit();
}
__device__ __forceinline__ void pv_issue(float (&o)[64], const uint32_t (&p)[32], uint32_t v, int acc, bool half) {
    uint64_t db = desc64(v, HI_IMG);
    if (half) {
        asm volatile("// half" ::: "memory");
        wg_fence();
#pragma unroll
        for (int i = 0; i < 4; i++) {
            wgmma_rs128(o, p[4 * i], p[4 * i + 1], p[4 * i + 2], p[4 * i + 3], db, i ? 1 : acc);
            desc_add(db, 256);
        }
        wg_commit();
        asm volatile("// half" ::: "memory");
    } else {
        wg_fence();
#pragma unroll
        for (int i = 0; i < 8; i++) {
            wgmma_rs128(o, p[4 * i], p[4 * i + 1], p[4 * i + 2], p[4 * i + 3], db, i ? 1 : acc);
            desc_add(db, 256);
        }
        wg_commit();
    }
}
__device__ __forceinline__ void tri_mask(float (&s)[64], float x) {
#pragma unroll
    for (int k = 0; k < 16; k++) {
        float b;
        asm("sub.sat.f32 %0, %1, %2;" : "=f"(b) : "f"((float)(8 * (k >> 1) + (k & 1))), "f"(x));
        const int i = 32 + 4 * (k >> 1) + (k & 1);
        asm("fma.rn.f32 %0, %1, 0fFF61B1E6, %0;" : "+f"(s[i]) : "f"(b));
        if (k < 14) asm("fma.rn.f32 %0, %1, 0fFF61B1E6, %0;" : "+f"(s[i + 6]) : "f"(b));
    }
}
__device__ __forceinline__ void tri_mask_copy(float (&s)[64], const float (&h)[32], float x) {
#pragma unroll
    for (int i = 0; i < 32; i++) {
        asm("{\n.reg .pred p;\nsetp.lt.f32 p, %2, %3;\nselp.f32 %0, 0fFF800000, %1, p;\n}"
            : "=f"(s[i]) : "f"(h[i]), "f"(x), "f"((float)(8 * (i >> 2) - 4 * (i & 2) + (i & 1))));
        s[32 + i] = __uint_as_float(0xff800000u);
    }
}
constexpr float SM_HI = 1152921504606846976.f, SM_LO = 1.f / 1152921504606846976.f;
__device__ __forceinline__ bool softmax_unsafe(float t0, float t1, bool first) {
    bool bad = __any_sync(0xffffffffu, fmaxf(t0, t1) > SM_HI);
    if (first) {
        uint32_t a = __ballot_sync(0xffffffffu, t0 >= SM_LO), b = __ballot_sync(0xffffffffu, t1 >= SM_LO);
        a |= a >> 1;
        b |= b >> 1;
        bad |= ((a | (a >> 2)) & (b | (b >> 2)) & 0x11111111u) != 0x11111111u;
    }
    return bad;
}
__device__ __forceinline__ void softmax_remax(const float (&s)[64], float (&m)[2], bool first, float& m0, float& m1, float& a0, float& a1) {
    m0 = fmaxf(s[0], s[1]), m1 = fmaxf(s[2], s[3]);
#pragma unroll
    for (int k = 1; k < 16; k++) {
        m0 = fmaxf(m0, fmaxf(s[4 * k], s[4 * k + 1]));
        m1 = fmaxf(m1, fmaxf(s[4 * k + 2], s[4 * k + 3]));
    }
    m0 = fmaxf(m0, __shfl_xor_sync(0xffffffffu, m0, 1));
    m1 = fmaxf(m1, __shfl_xor_sync(0xffffffffu, m1, 1));
    m0 = fmaxf(m0, __shfl_xor_sync(0xffffffffu, m0, 2));
    m1 = fmaxf(m1, __shfl_xor_sync(0xffffffffu, m1, 2));
    if (!first) {
        m0 = fmaxf(m0, 0.f);
        m1 = fmaxf(m1, 0.f);
    }
    a0 = first ? 1.f : ex2(-m0);
    a1 = first ? 1.f : ex2(-m1);
    m[0] += m0;
    m[1] += m1;
}
template <int J0, int J1>
__device__ __forceinline__ void softmax_exp(const float (&s)[64], uint32_t (&p)[32], float (&t)[4]) {
#pragma unroll
    for (int k = J0; k < J1; k++) {
        const float e0 = ex2(s[4 * k]), e1 = ex2(s[4 * k + 1]), e2 = ex2(s[4 * k + 2]), e3 = ex2(s[4 * k + 3]);
        if (k == 0) { t[0] = e0; t[1] = e1; t[2] = e2; t[3] = e3; }
        else { t[0] += e0; t[1] += e1; t[2] += e2; t[3] += e3; }
        p[2 * k] = pack2(e0, e1);
        p[2 * k + 1] = pack2(e2, e3);
    }
}
__device__ __forceinline__ void mma16816(float (&d)[4], const uint32_t* a, uint32_t b0, uint32_t b1) {
    asm("mma.sync.aligned.m16n8k16.row.col.f32.bf16.bf16.f32 {%0, %1, %2, %3}, {%4, %5, %6, %7}, {%8, %9}, {%0, %1, %2, %3};"
        : "+f"(d[0]), "+f"(d[1]), "+f"(d[2]), "+f"(d[3]) : "r"(a[0]), "r"(a[1]), "r"(a[2]), "r"(a[3]), "r"(b0), "r"(b1));
}
__device__ __forceinline__ uint2 best_key(const uint32_t* keys, int lane, uint32_t ep, uint32_t cur, int enough) {
#pragma unroll 1
    for (;;) {
        const uint4 k = ld_poll(reinterpret_cast<const uint4*>(keys) + lane);
        const bool ok = (((k.x ^ ep) | (k.y ^ ep) | (k.z ^ ep) | (k.w ^ ep)) & 31) == 0;
        const uint32_t best = __reduce_max_sync(0xffffffffu, ok ? max(max(k.x, k.y), max(k.z, k.w)) : 0u);
        const int n = __popc(__ballot_sync(0xffffffffu, ok));
        if (n == 32 || (n >= enough && best != cur)) return make_uint2(best, n == 32);
        __nanosleep(KSLEEP);
    }
}

__global__ void __cluster_dims__(2, 1, 1) __launch_bounds__(384, 1)
fused_kernel(const __grid_constant__ CUtensorMap tm_ckv, const __grid_constant__ CUtensorMap tm_wq,
             const __grid_constant__ CUtensorMap tm_wuk, const __grid_constant__ CUtensorMap tm_wuv,
             const __grid_constant__ CUtensorMap tm_wo, const __grid_constant__ CUtensorMap tm_wg,
             const __grid_constant__ CUtensorMap tm_wu,
             const __grid_constant__ CUtensorMap tm_wm, const __grid_constant__ CUtensorMap tm_x, const Params P) {
    extern __shared__ __align__(1024) uint8_t smem[];
    const uint32_t sb = (uint32_t)__cvta_generic_to_shared(smem);
    const int tid = threadIdx.x, lane = tid & 31, warp = __shfl_sync(0xffffffffu, tid >> 5, 0), wg = warp >> 2;
    const uint32_t sm = blockIdx.x < 8 ? blockIdx.x + 124 : blockIdx.x - 8, smq = ((sm - 64) * 147) >> 11;
    const int rb = sm < 64 ? (sm & 14) * 8 + (sm >> 4) * 2 + (sm & 1)
                 : sm < 120 ? ((sm - 64 - smq * 14) & 14) * 8 + 24 + smq * 2 + (sm & 1) : sm < 124 ? sm + 8 : sm - 116;
    const int grp = rb >> 3, j = rb & 7, kh = (grp >> (OMAP - 1)) & 1;
    const int cq = (j & 1) + ((grp >> (OMAP - 1)) & 2), ort = (OMAP == 1 ? grp & 12 : (grp & 8) + (grp & 1) * 4) + (j >> 1);
    if (warp == 0) TS(0);

    const CUtensorMap* tw = (j & 1) ? &tm_wuv : &tm_wuk;
    if (lane == 0) {
        if (warp == 8) {
#pragma unroll
            for (int i = 0; i < 7; i++) mbar_init(sb + BAR_FULL + 8 * i, 1);
            fence_async_smem();
        } else if (warp < 11) {
            const int w = warp - (warp > 8);
            const u64 cnt = (w < 5 ? (rb < NCTA ? 0x888888884444444ull : 0x888888888888888ull) : 0x111812111111118ull) >> (12 * (w % 5));
#pragma unroll
            for (int i = 0; i < 3; i++) mbar_init(sb + BAR_EMPTY + 24 * w + 8 * i, ((uint32_t)cnt >> (4 * i)) & 15);
        }
        asm volatile("fence.mbarrier_init.release.cluster;" ::: "memory");
    }
    __syncwarp();
    asm volatile("barrier.cluster.arrive.relaxed.aligned;" ::: "memory");
    if (warp == 8) {
        if (rb < NCTA) {
#pragma unroll 1
            for (int u = 0; u < 4; u++) {
                const uint32_t ws = u + (u == 3), as = (0x635u >> (4 * u)) & 15;
                slot_expect(sb, ws);
                load_tile(sb, ws, 0, tw, u * 128, 4 * grp, false, HINT & 1);
                if (u == 3) break;
                slot_expect(sb, as);
                load_tile(sb, as, 0, &tm_ckv, (j >> 1) * 128, u * 2, false, false);
                load_tile(sb, as, 16384, &tm_ckv, (j >> 1) * 128, u * 2 + 1, false, false);
            }
        } else {
#pragma unroll 1
            for (int i = 0; i < 6; i++) {
                slot_expect(sb, i);
                load_tile(sb, i, 0, &tm_wm, i * 64, (rb - NCTA) * 4, false, HINT & 64);
                if (i > 3) tma3d_prefetch(&tm_wm, i * 64 + 128, (rb - NCTA) * 4);
            }
        }
    }
    asm volatile("barrier.cluster.wait.aligned;" ::: "memory");

    if (rb >= NCTA) {
        uint32_t ph = 0, sl = 0;
        if (warp == 8) {
#pragma unroll 1
            for (int i = 6; i < 24; i++) {
                slot_acquire(sb, ph, sl);
                load_tile(sb, sl, 0, &tm_wm, (i & 7) * 64, (i >> 3) * 16 + (rb - NCTA) * 4, false, HINT & 64);
                if (++sl == 6) sl = 0;
            }
#pragma unroll 1
            for (int i = 0; i <= NFFN / NSPARE; i++) {
                const int b = (rb - NCTA) * (NFFN / NSPARE) + i;
                if (i < NFFN / NSPARE) {
                    asm volatile("cp.async.bulk.wait_group.read 0;" ::: "memory");
                    uint32_t done = 0x7f;
                    slot_acquire(sb, done, i & 1);
#pragma unroll 1
                    for (int k = 0; k < 4; k++) tma2d(sb + (i & 1) * SLOT + k * 8192, k < 2 ? &tm_wg : &tm_wu, b * 16, (k & 1) * 256, sb + BAR_FULL + 8 * (i & 1), (HINT & 128) && (i & 3) == 3);
                }
                if (i) {
                    mbar_wait(sb + BAR_FULL + 8 * (~i & 1), ((i - 1) >> 1) & 1);
                    bulk_store(g_wf + (b - 1) * SLOT, sb + (~i & 1) * SLOT, SLOT, HINT & 256);
                    asm volatile("cp.async.bulk.commit_group;" ::: "memory");
                }
            }
            asm volatile("cp.async.bulk.wait_group 0;" ::: "memory");
            fence_async_global();
            TS(4);
        } else if (warp < 8) {
            const uint32_t c2 = __ldg(reinterpret_cast<const uint32_t*>(P.c) + tid), ep = __ldcg(&g_sync.epoch[0]) + 1;
            uint32_t* sc = reinterpret_cast<uint32_t*>(smem + 6 * SLOT);
            sc[tid] = pack2(bf_lo(c2) * sigmoid(bf_lo(c2)), bf_hi(c2) * sigmoid(bf_hi(c2)));
            bar_sync(1, 256);
            const uint32_t a = sb + (warp >> 1) * 8192 + ((lane >> 4) * 8 + (lane & 7)) * 128, ch = (warp & 1) * 4 + ((lane >> 3) & 1);
#pragma unroll 1
            for (int ps = 0; ps < 3; ps++) {
                float d[2][4] = {};
#pragma unroll 1
                for (int bt = 0; bt < 8; bt++) {
                    slot_wait(sb + BAR_FULL, ph, sl);
#pragma unroll
                    for (int i = 0; i < 8; i++) {
                        uint32_t w[4];
                        asm volatile("ldmatrix.sync.aligned.m8n8.x4.trans.shared.b16 {%0, %1, %2, %3}, [%4];" : "=r"(w[0]), "=r"(w[1]), "=r"(w[2]), "=r"(w[3])
                                     : "r"(a + sl * SLOT + (i >> 1) * 2048 + (((ch + 2 * (i & 1)) ^ (lane & 7)) << 4)) : "memory");
                        mma16816(d[i & 1], w, sc[bt * 32 + (i >> 1) * 8 + (lane & 3)], sc[bt * 32 + (i >> 1) * 8 + 4 + (lane & 3)]);
                    }
                    __syncwarp();
                    mbar_arrive_if(sb + BAR_EMPTY + 8 * sl, lane == 0);
                    if (++sl == 6) sl = 0;
                }
                const float v = (lane & 2) ? ((lane & 1) ? d[1][2] : d[1][0]) : ((lane & 1) ? d[0][2] : d[0][0]);
                const int col = (rb - NCTA) * 256 + warp * 32 + (lane & 3) * 8 + (lane >> 2);
                if (ps == 0) st_pub(g_mod1 + col, (pack2(0.f, v) & 0xffff0000u) | (ep & 0xffffu), true);
                else g_mod[ps * 1024 + col] = __float2bfloat16_rn(v);
                if (warp == 0) TS(1 + ps);
            }
        }
        __syncthreads();
        if (tid < 2) flag_add(&g_sync.cnt[7 * 8]);
        return;
    }

    if (wg == 2) {
        asm volatile("setmaxnreg.dec.sync.aligned.u32 40;");
        if (warp == 8) {
            const uint32_t rank = j & 1, half = rank * 16384;
            uint32_t eph = 0, r = 0;
            *reinterpret_cast<volatile uint32_t*>(smem + SM_EP + 20) = 0;
#pragma unroll 1
            for (int hp = 0; hp < 2; hp++) {
                uint32_t wtab = w_table(hp), atab = a_table(hp);
                const int hc = 4 * grp + 2 * hp;
#pragma unroll 1
                for (int u = 3 - 3 * hp; u < 16; u++) {
                    if (hp && u < 4) {
                        const uint32_t ws = (wtab >> (4 * u)) & 15;
                        slot_acquire(sb, eph, ws);
                        load_tile(sb, ws, 0, tw, u * 128, hc, false, HINT & 1);
                        PT();
                    }
                    if (hp == 1 && (u & 7) == 4) mbar_wait(sb + BAR_FLAG + 24 + (u & 8), 0);
                    const uint32_t as = a_next(atab);
                    slot_acquire(sb, eph, as);
                    load_tile(sb, as, half, &tm_ckv, ((u & 12) + (j >> 1)) * 128, (u & 3) * 2 + rank, true, (HINT & 8) && hp);
                    PT();
                    if (hp == 1 && (u | 2) == 3 && lane == 0)
                        asm volatile("red.relaxed.gpu.global.add.u32 [%0], 1;" ::"l"(&g_sync.cnt[(grp * 8 + 3 + (u >> 1)) * 8]) : "memory");
                }
                const uint8_t* src = g_h + (15 - j) * 4 * SLOT;
#pragma unroll 1
                for (int u = 0; u < 8; u++) {
                    if (u == 0 || u == KVG) {
                        mbar_wait(sb + BAR_FLAG + (u ? 8 + 32 * hp : 0), 0);
                        fence_async_global();
                    }
                    if (u < 4) {
                        const uint32_t ws = (wtab >> (4 * u)) & 15;
                        slot_acquire(sb, eph, ws);
                        load_tile(sb, ws, 0, &tm_wq, u * 128, hc, false, HINT & 1);
                        PT();
                    }
                    const uint32_t as = a_next(atab);
                    slot_acquire(sb, eph, as);
                    load_bulk(sb, as, 0, src, SLOT, false, (HINT & 8) && hp);
                    PT();
                    src += u == 3 ? (8 * j - 63) * SLOT : SLOT;
                }
                const int step = hp ? -2 * SLOT : 2 * SLOT;
                src = g_KV + (size_t)(grp * 32 + 30 * hp) * SLOT + half - step;
#pragma unroll 1
                for (int n = 0; n <= 17; n++) {
                    if (n == 8) {
                        mbar_wait(sb + BAR_FLAG + 16 + 32 * hp, 0);
                        fence_async_global();
                    }
                    const uint8_t* v = src + SLOT;
                    src += n < 16 - j ? step : n == 16 - j ? (2 * j - 15) * step : -step;
                    if (n < 17) {
                        slot_acquire(sb, eph, r);
                        if (n != 15 - (j & 6)) load_bulk(sb, r, half, src, SLOT / 2, true, HINT & 4);
                        else load_bulk(sb, r, 0, src - half, SLOT, false, HINT & 4);
                        PT();
                        r = ring_next(r);
                    }
                    if (n) {
                        slot_acquire(sb, eph, r);
                        if (n != 16 - (j & 6)) load_bulk(sb, r, half, v, SLOT / 2, true, HINT & 4);
                        else load_bulk(sb, r, 0, v - half, SLOT, false, HINT & 4);
                        PT();
                        r = ring_next(r);
                    }
                    asm volatile("st.volatile.shared.u32 [%0], %1;" ::"r"(sb + SM_EP + 16), "r"(18 * hp + n + 1) : "memory");
                }
            }
            uint32_t otab = O_TABLE, ready = 0;
#pragma unroll 1
            for (int i = 0; i < 17; i++) {
                const bool dyn = i >= 8 && i < 15;
                const uint32_t want = dyn ? 15u << (4 * (i - 8)) : 1u << max(i + 14, 28);
                if (!(ready & want)) {
                    do {
                        asm volatile("ld.acquire.cta.shared.u32 %0, [%1];" : "=r"(ready) : "r"(sb + SM_EP + 20) : "memory");
                        ready = __shfl_sync(0xffffffffu, ready, 0);
                    } while (!(ready & want));
                    fence_async_global();
                }
                const int head = o_head(dyn ? (ready >> (4 * (i - 8))) & 15 : i, kh);
                const uint32_t as = o_next(otab), ws = o_next(otab), off = i < 15 ? half : kh * 16384;
                slot_acquire(sb, eph, as);
                load_bulk(sb, as, off, g_ctx + (size_t)(ort * 32 + head) * SLOT + off, SLOT / 2, i < 15, HINT & 16);
                if (i == 15) load_tile(sb, as, off ^ 16384, &tm_x, ort * 128 + kh * 64, cq * 2, false, false);
                if (i == 16) load_bulk(sb, as, off ^ 16384, P.wdown + min(rb, NFFN - 1) * 8192, SLOT / 2, false, false);
                PT();
                slot_acquire(sb, eph, ws);
                load_tile(sb, ws, 0, &tm_wo, head * 128, cq * 2, false, HINT & 2);
                PT();
                if (i == 0) o_next(otab);
            }
            if (rb < NFFN) {
                slot_acquire(sb, eph, 5);
                load_bulk(sb, 5, 0, g_wf + rb * SLOT, SLOT, false, false);
            }
        } else if (warp == 9) {
            *reinterpret_cast<volatile uint32_t*>(smem + SM_EP + 16) = 0;
            l2_prefetch(P.ckv + rb * 2048, 4096);
            mbar_watch(sb + BAR_FULL, 0);
            l2_prefetch(P.ckv + 512 * 512 + rb * 2048, 4096);
            mbar_watch(sb + BAR_FULL + 8 * XPF, 0);
            l2_prefetch(P.x + rb * 8192, 16384);
            mbar_watch(sb + BAR_FULL + 8 * 4, 0);
            l2_prefetch(P.ckv + 1024 * 512 + rb * 4096, 8192);
            TS(40);
#pragma unroll 1
            for (int i = 0; i < 15; i++) {
                step_watch(sb + SM_EP + 16, i == 0 ? 0 : i < 5 ? PFA + i : 13 + PFB + i);
                if (i == 12) mbar_watch(sb + BAR_FLAG + 8 * 7, 0);
                const int rf = min(rb, NFFN - 1);
                const uint8_t* p = i == 3 ? reinterpret_cast<const uint8_t*>(P.ckv) + rb * 16384
                                 : i == 4 ? g_h + rb * 16384
                                 : i < 9 ? g_ctx + (size_t)(ort * 32 + o_head(cq + 2 * ((i - 5) & 2), kh)) * SLOT + (i & 1) * 16384
                                 : i < 11 ? reinterpret_cast<const uint8_t*>(P.wo) + (grp * 16 + (~i & 1) * 8 + j) * 16384
                                 : i == 11 ? reinterpret_cast<const uint8_t*>(P.x) + rb * 16384
                                 : i == 12 ? reinterpret_cast<const uint8_t*>(P.wdown) + rf * 16384 : g_wf + rf * SLOT + (i & 1) * 16384;
                if (i >= 3) l2_prefetch(p, 16384);
                else if ((i | j) & 1) tma3d_prefetch(i == 1 ? tw : &tm_wq, (j >> 1) * 128, grp * 4 + (i ? 2 : 0));
            }
            const uint32_t v = lds32(sb + SM_EP) - 1;
            sts128(sb + SM_RED + lane * 16, make_uint4(v, v, v, v));
            fence_async_smem();
            __syncwarp();
#pragma unroll 1
            for (int i = 0; i < OB / 32; i++) bulk_store(g_out + rb * OB + i * 32, sb + SM_RED, 512, false);
            asm volatile("cp.async.bulk.commit_group;\ncp.async.bulk.wait_group 0;" ::: "memory");
            fence_async_global();
            __syncwarp();
            mbar_arrive_if(sb + BAR_PF, lane == 0);
            if (lane == 0) mbar_watch(sb + BAR_END, 0);
        } else {
            const uint32_t ep = __ldcg(&g_sync.epoch[0]) + 1;
            asm volatile("st.shared.u32 [%0], %1;" ::"r"(sb + SM_EP), "r"(ep) : "memory");
            mbar_wait(sb + BAR_FULL + 8 * 4, 0);
            {
                uint4 v[4];
                for (;;) {
                    uint32_t bad = 0;
#pragma unroll
                    for (int k = 0; k < 4; k++) v[k] = ld_poll(reinterpret_cast<const uint4*>(g_mod1) + (warp & 1) * 128 + k * 32 + lane);
#pragma unroll
                    for (int k = 0; k < 4; k++) bad |= (v[k].x ^ ep) | (v[k].y ^ ep) | (v[k].z ^ ep) | (v[k].w ^ ep);
                    if (__all_sync(0xffffffffu, (bad & 0xffff) == 0)) break;
                    __nanosleep(100);
                }
                const uint32_t one = (warp & 1) ? ONE2 : 0x80008000u;
#pragma unroll
                for (int k = 0; k < 4; k++)
                    *reinterpret_cast<uint2*>(smem + SM_TAB + (warp & 1) * 1024 + k * 256 + lane * 8) =
                        make_uint2(badd(__byte_perm(v[k].x, v[k].y, 0x7632), one), badd(__byte_perm(v[k].z, v[k].w, 0x7632), one));
            }
            __syncwarp();
            mbar_arrive_if(sb + BAR_FLAG + 8 * 8, lane == 0);
            if (warp == 10) {
#pragma unroll 1
                for (int i = 0; i < 9; i++) {
                    mbar_sleep(sb + BAR_DONE + 8 * i);
                    if (lane == 0) flag_add(i && ((i - 1) & 2) ? &g_sync.ctxcnt[((i & 1) ? 15 - j : j) * 32 + 2 * grp + (i > 4)] : &g_sync.cnt[(grp * 8 + i) * 8]);
                    if (i == 0) TS(43);
                }
            } else {
                TS(42);
#pragma unroll 1
                for (int i = 0; i < 8; i++) {
                    mbar_sleep(sb + BAR_DONE + 8 * (i == 7 ? 6 : i == 4 ? 3 : i));
                    if (lane < 2) flag_wait(&g_sync.cnt[((i == 0 ? (lane ? j : 15 - j) : i == 7 ? 0 : grp) * 8 + i) * 8], 8 * ep);
                    __syncwarp();
                    mbar_arrive_if(sb + BAR_FLAG + 8 * i, lane == 0 && i < 7);
                    TS(48 + i);
                }
                const uint32_t *mp = reinterpret_cast<const uint32_t*>(g_mod) + lane, *wp = reinterpret_cast<const uint32_t*>(P.wr) + lane;
                float ra = 0.f, rs = 0.f;
#pragma unroll 1
                for (int k = 0; k < 256; k += 32) {
                    const uint32_t ga = __ldcg(mp + 512 + k), sh = __ldcg(mp + 768 + k), c1 = badd(__ldcg(mp + 1024 + k), ONE2);
                    const uint32_t gb = __ldcg(mp + 1280 + k), ww = __ldg(wp + k);
                    const uint32_t a = bmul(c1, ww);
                    ra += bf_lo(a) + bf_hi(a);
                    rs = fmaf(bf_lo(sh), bf_lo(ww), fmaf(bf_hi(sh), bf_hi(ww), rs));
                    if (k >> 6 == cq) {
                        sts128(sb + SM_TAB + ((k & 32) + lane) * 16, make_uint4(ga << 16, ga & 0xffff0000u, a, 0));
                        sts128(sb + SM_TAB + 1024 + ((k & 32) + lane) * 16, make_uint4(c1, sh, gb, 0));
                    }
                }
#pragma unroll 1
                for (int o = 16; o > 0; o >>= 1) {
                    ra += __shfl_xor_sync(0xffffffffu, ra, o);
                    rs += __shfl_xor_sync(0xffffffffu, rs, o);
                }
                *reinterpret_cast<float2*>(smem + SM_EP + 8) = make_float2(ra, rs);
                __syncwarp();
                mbar_arrive_if(sb + BAR_FLAG + 8 * 7, lane == 0);
                const uint32_t* f = &g_sync.ctxcnt[ort * 32 + o_head(min(lane, 16), kh)];
                uint32_t ready = -(j & 1), list = 0, sh = 0, qa;
                asm("mapa.shared::cluster.u32 %0, %1, %2;" : "=r"(qa) : "r"(sb + SM_EP + 20), "r"(lane & 1));
                while (ready != ~0u) {
                    uint32_t v;
                    asm volatile("ld.acquire.gpu.global.u32 %0, [%1];" : "=r"(v) : "l"(f) : "memory");
                    const uint32_t now = __ballot_sync(0xffffffffu, (int)(v - ep) >= 0);
#pragma unroll 1
                    for (uint32_t fresh = now & ~ready & 0x7f00; fresh; fresh &= fresh - 1, sh += 4) list |= (__ffs(fresh) - 1) << sh;
                    list |= (((now & 0xff) + 1) >> 8 << 28) | ((now & 0x18000) << 14);
                    if (now != ready && lane < 2) asm volatile("st.relaxed.cluster.shared::cluster.u32 [%0], %1;" ::"r"(qa), "r"(list) : "memory");
                    if ((now & 0xff) == 0xff) mbar_sleep(sb + BAR_DONE + 8 * 7);
                    ready = now;
                    __nanosleep(POLL_NS);
                }
                TS(45);
            }
        }
    } else {
        const bool elected = (tid & 127) == 0, rel = (tid & 95) == 0;
        uint32_t eb;
        asm("mapa.shared::cluster.u32 %0, %1, %2;" : "=r"(eb) : "r"(sb + BAR_EMPTY), "r"(warp & 1));
        const int g = lane >> 2, c4 = lane & 3;
        const uint32_t toff = warp * 4096 + g * 64 + ((c4 ^ (g >> 1)) << 4);
        uint32_t fph = 0x3f, r = 0;
        if (wg == 1) bar_arrive(1, 256);
        const uint32_t kd = desc_k(sb), wd = desc_mn(sb), vd = ((sb & 0x3ffff) >> 4) | (32u << 16);
        const int nL = 16 - j, hn = nL - 1 + wg;
        float s[64], o[64], li[2] = {0.f, 0.f};
        uint8_t* cimg = g_ctx;
        const float sc = (j & 1) ? 1.f : SM_C;
#pragma unroll 1
        for (int q = 0; q < 3; q++) {
            const uint32_t as = (0x635u >> (4 * q)) & 15;
            mbar_wait(sb + BAR_FULL + 8 * q, 0);
            mbar_wait(sb + BAR_FULL + 8 * as, 0);
            bar_sync(1 + wg, 256);
            gemm_issue<false>(s, kd + wg * 512 + as * (SLOT / 16), wd + q * (SLOT / 16), q, false);
            bar_arrive(2 - wg, 256);
            wg_wait<0>();
            release_if(eb, as, rel);
        }
        reg_fence(s);
        asm volatile("setmaxnreg.inc.sync.aligned.u32 232;");
        {
            const int xrow = rb * 16 + warp * 2;
            const uint4* xp = reinterpret_cast<const uint4*>(P.x) + xrow * 64;
            uint8_t* img = g_KV + (size_t)(grp * 32 + j) * SLOT;
            uint32_t x[16], x0[2];
            float st[4] = {0.f, 0.f, 0.f, 0.f};
            mbar_wait(sb + BAR_FULL + 8 * 4, 0);
#pragma unroll
            for (int q = 3; q < 8; q++) {
                const uint32_t ws = (0x4210u >> (4 * (q & 3))) & 15, as = (0x635u >> (4 * (q % 3))) & 15;
                mbar_wait(sb + BAR_FULL + 8 * as, (q / 3) & 1);
                bar_sync(1 + wg, 256);
                if (q == 3) gemm_issue<false>(s, kd + wg * 512 + as * (SLOT / 16), wd + ws * (SLOT / 16), 1, false);
                else if (q == 4) gemm_issue<true>(o, kd + wg * 512 + as * (SLOT / 16), wd + ws * (SLOT / 16), 0, false);
                else gemm_issue<false>(o, kd + wg * 512 + as * (SLOT / 16), wd + ws * (SLOT / 16), 1, false);
                bar_arrive(2 - wg, 256);
                sched_fence(fph, P.zero);
                if (q > 3) reg_fence(s);
                if (q == 3) {
#pragma unroll
                    for (int i = 0; i < 4; i++)
                        asm volatile("ld.global.nc.v4.u32 {%0, %1, %2, %3}, [%4];" : "=r"(x[4 * i]), "=r"(x[4 * i + 1]), "=r"(x[4 * i + 2]), "=r"(x[4 * i + 3])
                                     : "l"(xp + lane + 32 * i) : "memory");
#pragma unroll
                    for (int i = 0; i < 2; i++) asm volatile("ld.global.nc.u32 %0, [%1];" : "=r"(x0[i]) : "l"(xp + 64 * i) : "memory");
                }
                if (q == 4) {
                    img_store_global<0>(img, toff, s, sc, sc);
#pragma unroll
                    for (int k = 0; k < 16; k++) {
                        const float d0 = bf_lo(x[k]) - bf_lo(x0[k >> 3]), d1 = bf_hi(x[k]) - bf_lo(x0[k >> 3]);
                        st[k >> 3] += d0 + d1;
                        st[2 + (k >> 3)] = fmaf(d0, d0, fmaf(d1, d1, st[2 + (k >> 3)]));
                    }
#pragma unroll
                    for (int i = 0; i < 4 * NSH; i++) st[i & 3] += __shfl_xor_sync(0xffffffffu, st[i & 3], 1 << (i >> 2));
                    reg_fence(st);
                }
                if (q == 5) {
#pragma unroll
                    for (int i = 4 * NSH; i < 20; i++) st[i & 3] += __shfl_xor_sync(0xffffffffu, st[i & 3], 1 << (i >> 2));
                    img_store_global<1>(img, toff, s, sc, sc);
#pragma unroll
                    for (int i = 0; i < 2; i++) {
                        const float d = st[i] * (1.f / 512.f);
                        st[2 + i] = ln_rstd(fmaxf(fmaf(-d, d, st[2 + i] * (1.f / 512.f)), 0.f));
                        x0[i] = pack2(bf_lo(x0[i]) + d, bf_lo(x0[i]) + d);
                    }
                    reg_fence(st);
                    reg_fence(x0);
                }
                if (q > 5) {
                    if (q == 6) mbar_wait(sb + BAR_FLAG + 8 * 8, 0);
                    const uint4 a = lds128(sb + SM_TAB + 1024 + (q & 1) * 512 + lane * 16), c = lds128(sb + SM_TAB + (q & 1) * 512 + lane * 16);
                    uint8_t* hp = g_h + (grp * 8 + (q & 1) * 4 + (lane >> 3)) * 16384 + (xrow & 127) * 128;
#pragma unroll
                    for (int i = 0; i < 2; i++) {
                        const uint32_t* y = x + 8 * i + 4 * (q & 1);
                        *reinterpret_cast<uint4*>(hp + i * 128 + (((lane ^ xrow ^ i) & 7) << 4)) =
                            make_uint4(ln_apply(y[0], x0[i], st[2 + i], a.x, c.x), ln_apply(y[1], x0[i], st[2 + i], a.y, c.y),
                                       ln_apply(y[2], x0[i], st[2 + i], a.z, c.z), ln_apply(y[3], x0[i], st[2 + i], a.w, c.w));
                    }
                    if (q == 7) {
                        __syncwarp();
                        mbar_arrive_if(sb + BAR_DONE, lane == 0);
                    }
                    if (q == 6) img_store_global<2>(img, toff, s, sc, sc);
                    else img_store_global<3>(img, toff, s, sc, sc);
                }
                sched_fence(fph, P.zero);
                wg_wait<0>();
                release_if(eb, as, rel);
            }
            reg_fence(o);
        }
        uint32_t p[32] = {};
#pragma unroll 1
        for (int hp = 0; hp < 2; hp++) {
            float m[2] = {0.f, 0.f}, l[2] = {0.f, 0.f}, t[4] = {0.f, 0.f, 0.f, 0.f};
            bool shifted = false, bad = false, plain = false;
            uint32_t qa = desc_k(sb + 5 * SLOT + (wg ^ 1) * 8192);
            uint8_t* limg = g_ctx + (size_t)((15 - j) * 32 + 2 * grp + hp) * SLOT;
            {
                const int step = hp ? -8 * SLOT : 8 * SLOT;
                uint8_t* img = g_KV + (size_t)(grp * 32 + (hp ? j ^ 30 : j) + 8) * SLOT;
                const uint32_t wtab = w_table(hp);
                uint32_t atab = hp ? 0x562u : 0x356u;
#pragma unroll 1
                for (int u = 2 - 2 * hp;; u += 2) {
                    proj_tile<false>(s, o, u, !u, sb, wg, eb, rel, fph, wtab, atab, u ? img : cimg, toff, u ? sc : li[0], u ? sc : li[1], p);
                    __syncwarp();
                    mbar_arrive_if(sb + BAR_DONE + 4 * u + 32 * hp, lane == 0);
                    if (elected) TS(1 + 10 * hp + u + 20 * wg);
                    if (proj_tile<true>(o, s, u + 1, 0, sb, wg, eb, rel, fph, wtab, atab, img + step, toff, sc, sc, p)) break;
                    if (elected) TS(2 + 10 * hp + u + 20 * wg);
                    img += 2 * step;
                }
            }
            if (elected) TS(6 + 10 * hp + 20 * wg);
            int n = -1;
#pragma unroll 1
            for (;;) {
                while (bad || plain) {
                    float d0 = m[0], d1 = m[1];
                    if (bad) {
                        float a0, a1;
                        softmax_remax(s, m, n == 0 || n == nL, d0, d1, a0, a1);
                        shifted = true;
                        l[0] *= a0;
                        l[1] *= a1;
#pragma unroll
                        for (int i = 0; i < 64; i++) o[i] *= (i & 2) ? a1 : a0;
                    }
#pragma unroll
                    for (int i = 0; i < 64; i++) s[i] -= (i & 2) ? d1 : d0;
                    softmax_exp<0, 16>(s, p, t);
                    t[0] += t[1];
                    t[2] += t[3];
                    bad = !bad && softmax_unsafe(t[0], t[2], false);
                    plain = false;
                }
#pragma unroll 1
                do {
                    l[0] += t[0];
                    l[1] += t[2];
                    if (++n > 16) break;
                    const uint32_t ks = r;
                    uint32_t vs = ring_next(r);
                    r = ring_next(vs);
                    bar_sync(1 + wg, 256);
                    const float x = (float)((warp & 3) * 16 + g - 2 * c4);
                    if (n == hn) {
                        float sh[32];
                        qk_issue(sh, qa, kd + ks * (SLOT / 16));
                        slot_wait(sb + BAR_FULL, fph, vs);
                        pv_issue(o, p, vd + vs * (SLOT / 16), 1, false);
                        bar_arrive(2 - wg, 256);
                        wg_wait<1>();
                        reg_fence(sh);
                        tri_mask_copy(s, sh, x);
                        release_if(eb, ks, rel);
                        release_if(eb, 5 + wg, rel && (!wg || n == 16));
                        if (!wg) {
                            qa += SLOT / 16;
                            fence_async_smem();
                        }
                        float e[4 * EARLY];
#pragma unroll
                        for (int i = 0; i < 4 * EARLY; i++) {
                            e[i] = ex2(s[i]);
                            t[i & 3] = i < 4 ? e[i] : t[i & 3] + e[i];
                        }
                        reg_fence(e);
                        slot_wait(sb + BAR_FULL, fph, r);
                        wg_wait<0>();
                        reg_fence(o);
                        reg_fence(e);
                        release_if(eb, vs, rel);
#pragma unroll
                        for (int i = 0; i < 2 * EARLY; i++) p[i] = pack2(e[2 * i], e[2 * i + 1]);
                        softmax_exp<EARLY, 8>(s, p, t);
                        if (wg) {
                            ctx_store<true>(limg, toff, o, l[0], l[1]);
                            __syncwarp();
                            mbar_arrive_if(sb + BAR_DONE + 24 + 32 * hp, lane == 0);
                            l[0] = l[1] = m[0] = m[1] = 0.f;
                            shifted = false;
                        }
                        t[0] += t[1];
                        t[2] += t[3];
                        plain = shifted;
                        if (plain) break;
                        bad = softmax_unsafe(t[0], t[2], wg);
                        continue;
                    }
                    if (n == 0 || n == nL) {
                        qk_issue(s, qa, kd + ks * (SLOT / 16));
                        if (n == 0) {
                            r = vs;
                            vs = 4 - hp;
                            slot_wait(sb + BAR_FULL, fph, 6);
                            gemm_issue<false>(o, qa + SLOT / 16, wd + vs * (SLOT / 16), 1, false);
                        } else {
                            slot_wait(sb + BAR_FULL, fph, vs);
                            pv_issue(o, p, vd + vs * (SLOT / 16), 1, true);
                        }
                        bar_arrive(2 - wg, 256);
                        const float i0 = n ? rcp(quad_sum(l[0])) : 1.f, i1 = n ? rcp(quad_sum(l[1])) : 1.f;
                        wg_wait<1>();
                        reg_fence(s);
                        release_if(eb, ks, rel);
                        release_if(eb, 6, rel && n == 16);
                        tri_mask(s, n ? x : 64.f);
                        float e[4 * EARLY];
#pragma unroll
                        for (int i = 0; i < 4 * EARLY; i++) {
                            e[i] = ex2(s[i]);
                            t[i & 3] = i < 4 ? e[i] : t[i & 3] + e[i];
                        }
                        reg_fence(e);
                        reg_fence(s);
                        reg_fence(t);
                        slot_wait(sb + BAR_FULL, fph, r);
                        if (SF & 1) sched_fence(fph, P.zero);
                        wg_wait<0>();
                        reg_fence(o);
                        reg_fence(e);
                        release_if(eb, vs, rel);
#pragma unroll
                        for (int i = 0; i < 2 * EARLY; i++) p[i] = pack2(e[2 * i], e[2 * i + 1]);
                        softmax_exp<EARLY, MSPLIT>(s, p, t);
                        tile_store(limg, sb + 6 * SLOT, toff, o, i0, i1, n);
                        reg_fence(t);
                        if (SF & 2) sched_fence(fph, P.zero);
                        reg_fence(s);
                        softmax_exp<MSPLIT, 16>(s, p, t);
                        __syncwarp();
                        mbar_arrive_if(sb + BAR_DONE + 24 + 32 * hp, lane == 0 && n);
                        l[0] = l[1] = m[0] = m[1] = 0.f;
                        shifted = false;
                        t[0] += t[1];
                        t[2] += t[3];
                        bad = __any_sync(0xffffffffu, fmaxf(t[0], t[2]) > SM_HI || fminf(t[0], t[2]) < SM_LO);
                        continue;
                    }
                    qk_issue(s, qa, kd + ks * (SLOT / 16));
                    slot_wait(sb + BAR_FULL, fph, vs);
                    pv_issue(o, p, vd + vs * (SLOT / 16), n != 1 && n != nL + 1, n == hn + 1);
                    bar_arrive(2 - wg, 256);
                    wg_wait<1>();
                    reg_fence(s);
                    release_if(eb, ks, rel);
                    release_if(eb, 6, rel && n == 16);
                    if (n == nL - 1) {
                        tri_mask(s, x);
                        release_if(eb, 5, rel);
                        qa += SLOT / 16;
                        fence_async_smem();
                    }
                    if (shifted) {
                        slot_wait(sb + BAR_FULL, fph, r);
                        wg_wait<0>();
                        reg_fence(o);
                        release_if(eb, vs, rel);
                        plain = true;
                        break;
                    }
                    float e[4 * EARLY];
#pragma unroll
                    for (int i = 0; i < 4 * EARLY; i++) {
                        e[i] = ex2(s[i]);
                        t[i & 3] = i < 4 ? e[i] : t[i & 3] + e[i];
                    }
                    reg_fence(e);
                    slot_wait(sb + BAR_FULL, fph, r);
                    wg_wait<0>();
                    reg_fence(o);
                    reg_fence(e);
                    release_if(eb, vs, rel);
#pragma unroll
                    for (int i = 0; i < 2 * EARLY; i++) p[i] = pack2(e[2 * i], e[2 * i + 1]);
                    softmax_exp<EARLY, 16>(s, p, t);
                    t[0] += t[1];
                    t[2] += t[3];
                    bad = softmax_unsafe(t[0], t[2], false);
                } while (!bad);
                if (!bad && !plain) break;
            }
            const uint32_t vs = r, ga = desc_k(sb + (hp ? 2 * (wg ^ kh ^ 1) : wg) * 8192);
            r = ring_next(r);
            slot_wait(sb + BAR_FULL, fph, 5);
            slot_wait(sb + BAR_FULL, fph, r);
            bar_sync(1 + wg, 256);
            gemm_issue<true>(s, ga + 5 * (SLOT / 16), wd + r * (SLOT / 16), 0, hp);
            pv_issue(o, p, vd + vs * (SLOT / 16), j, hn == 16);
            bar_arrive(2 - wg, 256);
            li[0] = rcp(quad_sum(l[0]));
            li[1] = rcp(quad_sum(l[1]));
            cimg = limg + (ptrdiff_t)(2 * j - 15) * 32 * SLOT + (wg ? -16384 : 16384);
            wg_wait<1>();
            release_if(eb, 5, rel);
            release_if(eb, r, rel && hp);
            wg_wait<0>();
            release_if(eb, vs, rel);
            reg_fence(o);
            img_store_global<0>(cimg, toff, o, li[0], li[1]);
            if (elected) TS(8 + 10 * hp + 20 * wg);
        }
        uint32_t otab = 0x2351604u;
        const uint32_t oa = desc_k(sb + (wg ^ kh ^ 1) * 16384);
        const int t7 = tid & 127, w4 = warp & 3, row = ort * 128 + kh * 64 + w4 * 16 + g;
#pragma unroll 1
        for (int i = 1; i < 15 - wg; i++) {
            const uint32_t as = o_next(otab), ws = o_next(otab);
            slot_wait(sb + BAR_FULL, fph, as);
            slot_wait(sb + BAR_FULL, fph, ws);
            bar_sync(1 + wg, 256);
            gemm_issue<false>(s, oa + as * (SLOT / 16), wd + ws * (SLOT / 16), 1, true);
            bar_arrive(2 - wg, 256);
            wg_wait<1>();
            reg_fence(o);
            if (i == 1) img_store_global<1>(cimg, toff, o, li[0], li[1]);
            if (i == 2) {
                img_store_global<2>(cimg, toff, o, li[0], li[1]);
                img_store_global<3>(cimg, toff, o, li[0], li[1]);
                __syncwarp();
                mbar_arrive_if(sb + BAR_DONE + 64, lane == 0);
            }
            wg_wait<0>();
            release_if(eb, as, rel);
            release_if(eb, ws, rel);
        }
        mbar_wait(sb + BAR_PF, 0);
        const uint32_t ep = lds32(sb + SM_EP);
        uint32_t eb2 = sb + BAR_END;
        if (wg == 0) {
            reg_fence(s);
            if (elected) TS(9);
            TT(1);
#pragma unroll
            for (int v = 0; v < 8; v++)
                st_pub(g_out + rb * OB + v * 128 + t7, make_uint4((pack2(s[8 * v], s[8 * v + 1]) & ~1u) | (ep & 1), pack2(s[8 * v + 2], s[8 * v + 3]),
                                                                      pack2(s[8 * v + 4], s[8 * v + 5]), pack2(s[8 * v + 6], s[8 * v + 7])), true);
            constexpr uint32_t s1 = 5, s2 = 6;
            if (ELATE >= 0) bar_sync(4, 256);
            uint32_t wf[64];
            float wn[64];
            if (rb < NFFN) {
                slot_wait(sb + BAR_FULL, fph, s1);
                const uint32_t a = sb + s1 * SLOT + (w4 * 128 + (lane >> 4) * 8 + (lane & 7)) * 32 + (((lane >> 3) ^ (lane >> 2)) & 1) * 16;
#pragma unroll
                for (int i = 0; i < 16; i++)
                    asm volatile("ldmatrix.sync.aligned.m8n8.x4.trans.shared.b16 {%0, %1, %2, %3}, [%4];"
                                 : "=r"(wf[4 * i]), "=r"(wf[4 * i + 1]), "=r"(wf[4 * i + 2]), "=r"(wf[4 * i + 3])
                                 : "r"(a + (i >> 3) * 16384 + (i & 7) * 512) : "memory");
                slot_wait(sb + BAR_FULL, fph, s2);
#pragma unroll
                for (int i = 0; i < 16; i++) {
                    const uint2 w = *reinterpret_cast<const uint2*>(smem + s2 * SLOT + (kh ^ 1) * 16384 + i * 1024 + t7 * 8);
                    wn[4 * i] = bf_lo(w.x); wn[4 * i + 1] = bf_hi(w.x); wn[4 * i + 2] = bf_lo(w.y); wn[4 * i + 3] = bf_hi(w.y);
                }
                reg_fence(wn);
            }
            const uint32_t gbf = __ldcg(reinterpret_cast<const uint32_t*>(g_mod) + 1280 + rb * 2 + (tid & 1));
            if (elected) TS(10);
            TT(2);
            float* sred = reinterpret_cast<float*>(smem + SM_RED);
            uint32_t best = ep ^ 1, all;
            bool fresh;
            do {
                if (warp == 0) {
                    const uint2 k = best_key(g_key + cq * 128, lane, ep, best, rb < NFFN ? SPEC : 32);
                    *reinterpret_cast<uint2*>(smem + SM_EP + 24) = k;
                    mbar_arrive_if(sb + BAR_BEST, lane == 0 && k.y);
                }
                bar_sync(3, 128);
                const uint2 k = *reinterpret_cast<const uint2*>(smem + SM_EP + 24);
                fresh = k.x != best;
                best = k.x;
                all = k.y;
                TT(3);
                if (!fresh || rb >= NFFN) break;
                const uint4* cp = g_cand + ((~best >> 9) & 127) * 192;
                uint4 cv[6];
                for (;;) {
                    uint32_t bad = 0;
#pragma unroll
                    for (int v = 0; v < 6; v++) cv[v] = ld_poll(cp + w4 * 24 + v * 4 + c4);
#pragma unroll
                    for (int v = 0; v < 6; v++) bad |= cv[v].w ^ ep;
                    if (__all_sync(0xffffffffu, bad == 0)) break;
                    if (CSLEEP) __nanosleep(CSLEEP);
                }
            TT(4);
                float d[4][4] = {};
#pragma unroll
                for (int k = 0; k < 8; k++) {
                    const uint32_t b0 = (&cv[(2 * k) / 3].x)[(2 * k) % 3], b1 = (&cv[(2 * k + 1) / 3].x)[(2 * k + 1) % 3];
                    mma16816(d[k & 1], wf + 4 * k, b0, b1);
                    mma16816(d[2 + (k & 1)], wf + 32 + 4 * k, b0, b1);
                }
                const float u = (c4 & 2) ? ((c4 & 1) ? d[2][2] + d[3][2] : d[2][0] + d[3][0]) : ((c4 & 1) ? d[0][2] + d[1][2] : d[0][0] + d[1][0]);
                sred[w4 * 32 + c4 * 8 + g] = u;
                bar_sync(3, 128);
                const float v = rbf((sred[lane] + sred[32 + lane]) + (sred[64 + lane] + sred[96 + lane]));
                const float act = rbf(rbf(v * sigmoid(v)) * __shfl_down_sync(0xffffffffu, v, 16));
                float y[4] = {0.f, 0.f, 0.f, 0.f};
#pragma unroll
                for (int k = 0; k < 16; k++) {
                    const float a = __shfl_sync(0xffffffffu, act, k);
#pragma unroll
                    for (int i = 0; i < 4; i++) y[i] = fmaf(a, wn[4 * k + i], y[i]);
                }
                st_pub(g_out + rb * OB + OB_Y + t7, make_uint4((__float_as_uint(y[0]) & ~15u) | (ep & 15), (__float_as_uint(y[1]) & ~127u) | ((best >> 9) & 127),
                                                               __float_as_uint(y[2]), __float_as_uint(y[3])), true);
            } while (!all);
            const int sel = (~best >> 5) & 2047;
            const int pq = (2 * rb + (tid & 1)) & 63, pv = (pq >> 2) / 3;
            const uint4* fp = g_cand + (sel >> 4) * 192 + (rb >> 5) * 24 + pv * 4 + (pq & 3);
            uint4 fh = {}, fx = {};
            if (rb == 0 && tid == 0) g_sync.epoch[0] = ep;
            if (elected) TS(60);
            TT(5);
            uint4 yv;
            if (warp == 0) { fh = ld_poll(fp); fx = ld_poll(fp + 96); }
            if (fresh && rb < NFFN) __nanosleep(YPRE);
            for (;;) {
                yv = ld_poll(g_out + min(t7, NFFN - 1) * OB + OB_Y + rb);
                if (__all_sync(0xffffffffu, (((yv.x ^ ep) & 15) | ((yv.y ^ (best >> 9)) & 127)) == 0)) break;
                if (YSLEEP) __nanosleep(YSLEEP);
            }
            if (elected) TS(61);
            TT(6);
            float y[4] = {0.f, 0.f, 0.f, 0.f};
            if (t7 < NFFN) { y[0] = __uint_as_float(yv.x); y[1] = __uint_as_float(yv.y); y[2] = __uint_as_float(yv.z); y[3] = __uint_as_float(yv.w); }
            const float z0 = ((lane & 16) ? y[2] : y[0]) + __shfl_xor_sync(0xffffffffu, (lane & 16) ? y[0] : y[2], 16);
            const float z1 = ((lane & 16) ? y[3] : y[1]) + __shfl_xor_sync(0xffffffffu, (lane & 16) ? y[1] : y[3], 16);
            float z = ((lane & 8) ? z1 : z0) + __shfl_xor_sync(0xffffffffu, (lane & 8) ? z0 : z1, 8);
            z += __shfl_xor_sync(0xffffffffu, z, 4);
            z = quad_sum(z);
            if ((lane & 7) == 0) sred[128 + (lane >> 3) * 4 + w4] = z;
            bar_sync(3, 128);
            if (tid < 2) {
                while (fh.w != ep || fx.w != ep) { fh = ld_poll(fp); fx = ld_poll(fp + 96); }
                const float4 y0 = *reinterpret_cast<const float4*>(sred + 128 + tid * 8), y1 = *reinterpret_cast<const float4*>(sred + 132 + tid * 8);
                const int cm = (pq >> 2) - 3 * pv;
                const uint32_t h2 = cm == 0 ? fh.x : cm == 1 ? fh.y : fh.z, x2 = cm == 0 ? fx.x : cm == 1 ? fx.y : fx.z;
                const float sg = sigmoid(bf_hi((best & 0x80000000u) ? (best ^ 0x80000000u) : ~best));
                reinterpret_cast<uint32_t*>(P.out)[sel * 256 + rb * 2 + tid] =
                    badd(x2, bmul(gbf, badd(h2, bmul(pack2((y0.x + y0.y) + (y0.z + y0.w), (y1.x + y1.y) + (y1.z + y1.w)), pack2(sg, sg)))));
            }
            if (elected) TS(62);
            TT(7);
        } else {
            const float4* tf = reinterpret_cast<const float4*>(smem + SM_TAB) + c4;
            const uint32_t xa = sb + 4 * SLOT + (kh ^ 1) * 16384 + (w4 * 16 + (lane & 15)) * 128;
            uint32_t x2[32];
            bar_sync(2, 256);
#pragma unroll 1
            for (int i = 14; i < 17; i++) {
                const uint32_t as = o_next(otab), ws = o_next(otab);
                slot_wait(sb + BAR_FULL, fph, as);
                slot_wait(sb + BAR_FULL, fph, ws);
                gemm_issue<false>(s, oa + as * (SLOT / 16), wd + ws * (SLOT / 16), 1, true);
                wg_wait<1>();
            }
            const uint4* pr = g_out + (rb ^ (8 * OMAP)) * OB + t7;
            uint4 pa[8];
            if (PEARLY) {
#pragma unroll
                for (int v = 0; v < 8; v++) pa[v] = ld_poll(pr + v * 128);
            }
            if (elected) TS(29);
            TT(1);
            {
#pragma unroll
                for (int k = 0; k < 8; k++)
                    asm volatile("ldmatrix.sync.aligned.m8n8.x4.shared.b16 {%0, %1, %2, %3}, [%4];"
                                 : "=r"(x2[4 * k]), "=r"(x2[4 * k + 1]), "=r"(x2[4 * k + 2]), "=r"(x2[4 * k + 3])
                                 : "r"(xa + (k >> 2) * 8192 + (((2 * (k & 3) + (lane >> 4)) ^ (lane & 7)) << 4)) : "memory");
            }
            wg_wait<0>();
            reg_fence(s);
            if (!ELATE) bar_arrive(4, 256);
            if (elected) TS(39);
            TT(2);
            if (!PEARLY) {
#pragma unroll
                for (int v = 0; v < 8; v++) pa[v] = ld_poll(pr + v * 128);
            }
            float4 tc[16];
#pragma unroll
            for (int k = 0; k < 16; k++) {
                tc[k] = tf[k * 4];
                if (!(g & 1)) tc[k].z = __uint_as_float(ONE2);
#pragma unroll
                for (int i = 4 * k; i < 4 * k + 4; i++) s[i] = fmaf((i & 1) ? tc[k].y : tc[k].x, s[i], (i & 1) ? bf_hi(x2[i >> 1]) : bf_lo(x2[i >> 1]));
            }
            reg_fence(s);
            if (TF & 2) sched_fence(eb2, P.zero);
            for (;;) {
                uint32_t bad = 0;
#pragma unroll
                for (int v = 0; v < 8; v++) asm("lop3.b32 %0, %0, %1, %2, 0xf6;" : "+r"(bad) : "r"(pa[v].x), "r"(ep));
                if (__all_sync(0xffffffffu, (bad & 1) == 0)) break;
                if (PSLEEP) __nanosleep(PSLEEP);
#pragma unroll
                for (int v = 0; v < 8; v++) pa[v] = ld_poll(pr + v * 128);
            }
            if (ELATE == 1) bar_arrive(4, 256);
            if (elected) TS(30);
            TT(3);
            float sd[4] = {}, q0[4] = {}, q1[4] = {};
#pragma unroll
            for (int k = 0; k < 8; k++) {
#pragma unroll
                for (int i = 4 * k; i < 4 * k + 4; i++) {
                    const uint32_t w = (&pa[k].x)[i & 3];
                    x2[i] = pack2(fmaf(tc[i >> 1].x, bf_lo(w), s[2 * i]), fmaf(tc[i >> 1].y, bf_hi(w), s[2 * i + 1]));
                }
                mma16816(sd, x2 + 4 * k, __float_as_uint(tc[2 * k].z), __float_as_uint(tc[2 * k + 1].z));
                mma16816(q0, x2 + 4 * k, x2[4 * k], x2[4 * k + 2]);
                mma16816(q1, x2 + 4 * k, x2[4 * k + 1], x2[4 * k + 3]);
            }
            uint4* sp = g_out + rb * OB + OB_STAT + (w4 * 8 + g) * 2;
            st_pub(sp, make_uint4(__float_as_uint(sd[0]), __float_as_uint((g & 1) ? q0[1] : q0[0]), __float_as_uint(sd[1]), ep), c4 == g >> 1);
            st_pub(sp + 1, make_uint4(__float_as_uint(sd[2]), __float_as_uint((g & 1) ? q1[3] : q1[2]), __float_as_uint(sd[3]), ep), c4 == g >> 1);
            if (ELATE == 2) bar_arrive(4, 256);
            if (TF & 1) sched_fence(eb2, P.zero);
            if (elected) TS(56);
            TT(4);
            uint32_t cb[16], sh[16], gb[16];
#pragma unroll
            for (int i = 0; i < 16; i++) {
                const float4 c = tf[64 + i * 4];
                cb[i] = __float_as_uint(c.x); sh[i] = __float_as_uint(c.y); gb[i] = __float_as_uint(c.z);
            }
            const float ra = __uint_as_float(lds32(sb + SM_EP + 8)), rb0 = __uint_as_float(lds32(sb + SM_EP + 12));
            uint4 r0, r1;
            if (SPRE) __nanosleep(SPRE);
            for (;;) {
                r0 = ld_poll(g_out + ((rb & ~(16 * OMAP + 1)) + (c4 & 1) + (c4 & 2) * 8 * OMAP) * OB + OB_STAT + (w4 * 8 + g) * 2);
                r1 = ld_poll(g_out + ((rb & ~(16 * OMAP + 1)) + (c4 & 1) + (c4 & 2) * 8 * OMAP) * OB + OB_STAT + (w4 * 8 + g) * 2 + 1);
                if (__all_sync(0xffffffffu, r0.w == ep && r1.w == ep)) break;
                if (SSLEEP) __nanosleep(SSLEEP);
            }
            if (elected) TS(57);
            TT(5);
            const float m0 = quad_sum(__uint_as_float(r0.x)) * (1.f / 512.f), m1 = quad_sum(__uint_as_float(r1.x)) * (1.f / 512.f);
            const float rs0 = ln_rstd(fmaxf(fmaf(-m0, m0, quad_sum(__uint_as_float(r0.y)) * (1.f / 512.f)), 0.f));
            const float rs1 = ln_rstd(fmaxf(fmaf(-m1, m1, quad_sum(__uint_as_float(r1.y)) * (1.f / 512.f)), 0.f));
            const uint32_t mb0 = pack2(m0, m0), mb1 = pack2(m1, m1);
            const uint32_t lg = pack2(fmaf(rs0, fmaf(-bf_lo(mb0), ra, quad_sum(__uint_as_float(r0.z))), rb0),
                                      fmaf(rs1, fmaf(-bf_lo(mb1), ra, quad_sum(__uint_as_float(r1.z))), rb0));
            const uint32_t u0 = lg << 16, u1 = lg & 0xffff0000u;
            const uint32_t k0 = ((u0 ^ (((int)u0 >> 31) | 0x80000000u)) & 0xffff0000u) | ((2047 - row) << 5) | (ep & 31);
            const uint32_t k1 = ((u1 ^ (((int)u1 >> 31) | 0x80000000u)) & 0xffff0000u) | ((2039 - row) << 5) | (ep & 31);
            const uint32_t kb = __reduce_max_sync(0xffffffffu, max(k0, k1));
            st_pub(g_key + cq * 128 + (row >> 4), kb, lane == 0);
            const bool cand = kb == k0 || kb == k1;
            uint4* cp = g_cand + (row >> 4) * 192 + cq * 24 + c4;
#pragma unroll 1
            for (int it = 0; it < 3; it++) {
                bool put = it == 1 || !cand;
                if (it == 2) {
                    mbar_wait(sb + BAR_BEST, 0);
                    put = cand && lds32(sb + SM_EP + 24) != kb;
                }
                const bool hi = (kb == k1) != (it == 1);
                uint32_t cx[18], ch[18];
#pragma unroll
                for (int i = 0; i < 16; i++) {
                    cx[i] = hi ? x2[2 * i + 1] : x2[2 * i];
                    ch[i] = ln_apply(cx[i], hi ? mb1 : mb0, hi ? rs1 : rs0, cb[i], sh[i]);
                }
                cx[16] = cx[17] = ch[16] = ch[17] = 0;
#pragma unroll
                for (int v = 0; v < 6; v++) st_pub(cp + v * 4, make_uint4(ch[3 * v], ch[3 * v + 1], ch[3 * v + 2], ep), cand && it == 0);
#pragma unroll
                for (int v = 0; v < 6; v++) st_pub(cp + 96 + v * 4, make_uint4(cx[3 * v], cx[3 * v + 1], cx[3 * v + 2], ep), cand && it == 0);
                if (it == 0) TT(6);
                uint2* op = reinterpret_cast<uint2*>(P.out) + (row + 8 * hi) * 128 + cq * 32 + (c4 & 1) * 2 + (c4 >> 1);
#pragma unroll
                for (int i = 0; i < 16; i += 2) {
                    const uint32_t v0 = badd(cx[i], bmul(gb[i], ch[i])), v1 = badd(cx[i + 1], bmul(gb[i + 1], ch[i + 1]));
                    const uint32_t rv = __shfl_xor_sync(0xffffffffu, (c4 & 1) ? v0 : v1, 1);
                    if (put) op[i * 2] = (c4 & 1) ? make_uint2(rv, v1) : make_uint2(v0, rv);
                }
            }
            if (elected) TS(59);
            TT(7);
        }
        mbar_arrive_if(eb2, lane == 0);
    }
}

typedef CUresult (*EncodeFn)(CUtensorMap*, CUtensorMapDataType, cuuint32_t, void*, const cuuint64_t*, const cuuint64_t*,
                             const cuuint32_t*, const cuuint32_t*, CUtensorMapInterleave, CUtensorMapSwizzle,
                             CUtensorMapL2promotion, CUtensorMapFloatOOBfill);

void make_2d(EncodeFn fn, CUtensorMap* m, const void* p, uint64_t cols, uint64_t rows, uint32_t bc, uint32_t br, CUtensorMapSwizzle sw) {
    cuuint64_t dims[2] = {cols, rows}, strides[1] = {cols * 2};
    cuuint32_t box[2] = {bc, br}, es[2] = {1, 1};
    fn(m, CU_TENSOR_MAP_DATA_TYPE_BFLOAT16, 2, const_cast<void*>(p), dims, strides, box, es, CU_TENSOR_MAP_INTERLEAVE_NONE,
       sw, CU_TENSOR_MAP_L2_PROMOTION_L2_128B, CU_TENSOR_MAP_FLOAT_OOB_FILL_NONE);
}
void make_3d(EncodeFn fn, CUtensorMap* m, const void* p, uint64_t cols, uint64_t rows, uint32_t br = 128, uint32_t nb = 2) {
    cuuint64_t dims[3] = {64, rows, cols / 64}, strides[2] = {cols * 2, 128};
    cuuint32_t box[3] = {64, br, nb}, es[3] = {1, 1, 1};
    fn(m, CU_TENSOR_MAP_DATA_TYPE_BFLOAT16, 3, const_cast<void*>(p), dims, strides, box, es, CU_TENSOR_MAP_INTERLEAVE_NONE,
       CU_TENSOR_MAP_SWIZZLE_128B, CU_TENSOR_MAP_L2_PROMOTION_L2_256B, CU_TENSOR_MAP_FLOAT_OOB_FILL_NONE);
}

}

extern "C" void kernel_launch(void* const* d_in, const int* in_sizes, int n_in, void* d_out, int out_size) {
    static EncodeFn fn = nullptr;
    if (!fn) {
        void* f = nullptr;
        cudaDriverEntryPointQueryResult st;
        cudaGetDriverEntryPoint("cuTensorMapEncodeTiled", &f, cudaEnableDefault, &st);
        fn = (EncodeFn)f;
        cudaFuncSetAttribute(fused_kernel, cudaFuncAttributeMaxDynamicSharedMemorySize, SMEM_BYTES);
    }
    CUtensorMap ckv, wq, wuk, wuv, wo, wg, wu, wm, xm;
    make_3d(fn, &ckv, d_in[1], 512, 2048, 128, 1);
    make_3d(fn, &xm, d_in[0], 512, 2048, 64);
    make_3d(fn, &wq, d_in[2], 4096, 512);
    make_3d(fn, &wuk, d_in[3], 4096, 512);
    make_3d(fn, &wuv, d_in[4], 4096, 512);
    make_3d(fn, &wo, d_in[5], 512, 4096);
    make_2d(fn, &wg, d_in[8], 1792, 512, 16, 256, CU_TENSOR_MAP_SWIZZLE_32B);
    make_2d(fn, &wu, d_in[9], 1792, 512, 16, 256, CU_TENSOR_MAP_SWIZZLE_32B);
    make_3d(fn, &wm, d_in[12], 3072, 512, 64, 4);
    Params p;
    p.x = (const bf16*)d_in[0];
    p.ckv = (const bf16*)d_in[1];
    p.wo = (const bf16*)d_in[5];
    p.wr = (const bf16*)d_in[7];
    p.wdown = (const bf16*)d_in[10];
    p.c = (const bf16*)d_in[11];
    p.out = (bf16*)d_out;
    p.zero = 0;
    fused_kernel<<<NCTA + NSPARE, 384, SMEM_BYTES>>>(ckv, wq, wuk, wuv, wo, wg, wu, wm, xm, p);
}
```

```cpp
#include <cuda.h>
#include <cuda_bf16.h>
#include <cuda_runtime.h>
#include <stdint.h>
#include <stdio.h>

namespace {

typedef __nv_bfloat16 bf16;
typedef unsigned long long u64;

constexpr int NCTA = 128, NSPARE = 4;
constexpr int SLOT = 32768;
constexpr int SM_BAR = 7 * SLOT;
constexpr int BAR_FULL = SM_BAR;
constexpr int BAR_EMPTY = BAR_FULL + 8 * 7;
constexpr int BAR_DONE = BAR_EMPTY + 8 * 7;
constexpr int BAR_FLAG = BAR_DONE + 8 * 9;
constexpr int BAR_PF = BAR_FLAG + 8 * 9;
constexpr int BAR_END = BAR_PF + 8;
constexpr int BAR_BEST = BAR_END + 8;
constexpr int SM_EP = BAR_END + 40;
constexpr int SM_RED = SM_BAR + 384;
constexpr int SM_TAB = SM_BAR + 1024;
constexpr int SMEM_BYTES = SM_BAR + 3072;
constexpr int NFFN = 112;
#define HINT 479
constexpr u64 L2_NORMAL = 0x1000000000000000ull, L2_FIRST = 0x12F0000000000000ull;
#define PFA 8
#define PFB 6
#define UNR 1
#define POLL_NS 50
#define MSPLIT 13
#define SF 1
#define NSH 1
#define XPF 1
#define TF 3
#define KSLEEP 200
#define YSLEEP 50
#define YPRE 150
#define SSLEEP 50
#define SPRE 0
#define PSLEEP 100
#define CSLEEP 0
#define SPEC 28
#define OMAP 2
#define KVG 7
#define PEARLY 0
#define ELATE 0
#define EARLY2 4
#define EARLY 7
constexpr uint32_t SPIN_LIMIT = 1u << 22;
constexpr uint32_t ONE2 = 0x3f803f80u;

struct Sync {
    uint32_t cnt[16 * 8 * 8];
    uint32_t ctxcnt[16 * 32];
    uint32_t epoch[32];
};

__device__ __align__(1024) uint8_t g_img[2 * 512 * SLOT];
#define g_KV g_img
#define g_ctx (g_img + 512 * SLOT)
__device__ __align__(1024) uint8_t g_h[16 * 4 * SLOT];
constexpr int OB = 1216, OB_STAT = 1024, OB_Y = 1088;
__device__ __align__(1024) uint4 g_out[128 * OB];
__device__ __align__(1024) bf16 g_mod[3072];
__device__ __align__(1024) uint32_t g_mod1[1024];
__device__ __align__(1024) uint4 g_cand[128 * 192];
__device__ __align__(1024) uint32_t g_key[4 * 128];
__device__ __align__(1024) uint8_t g_wf[NFFN * SLOT];
__device__ __align__(1024) Sync g_sync;
#define TS(i)

#define TT(i)
#define PT()

struct Params {
    const bf16 *x, *ckv, *wo, *wr, *wdown, *c;
    bf16* out;
    int zero;
};

__device__ __forceinline__ void mbar_init(uint32_t bar, uint32_t cnt) {
    asm volatile("mbarrier.init.shared::cta.b64 [%0], %1;" ::"r"(bar), "r"(cnt) : "memory");
}
__device__ __forceinline__ void mbar_wait(uint32_t bar, uint32_t parity) {
    asm volatile("{\n.reg .pred p;\nL_%=:\nmbarrier.try_wait.parity.shared::cta.b64 p, [%0], %1;\n@!p bra L_%=;\n}" ::"r"(bar), "r"(parity) : "memory");
}
__device__ __forceinline__ void mbar_sleep(uint32_t bar) {
    if ((threadIdx.x & 31) == 0)
        asm volatile("{\n.reg .pred p;\nL_%=:\nmbarrier.try_wait.parity.shared::cta.b64 p, [%0], 0, 100000;\n@!p bra L_%=;\n}" ::"r"(bar) : "memory");
    __syncwarp();
}
__device__ __forceinline__ void mbar_watch(uint32_t bar, uint32_t parity) {
    asm volatile("{\n.reg .pred p;\n.reg .u32 n;\nmov.u32 n, 0;\n"
                 "L_%=:\nmbarrier.try_wait.parity.shared::cta.b64 p, [%0], %1;\n@p bra D_%=;\n"
                 "add.u32 n, n, 1;\nsetp.lt.u32 p, n, %2;\n@p bra L_%=;\ntrap;\nD_%=:\n}"
                 ::"r"(bar), "r"(parity), "n"(SPIN_LIMIT) : "memory");
}
__device__ __forceinline__ void step_watch(uint32_t a, uint32_t step) {
    asm volatile("{\n.reg .pred p;\n.reg .u32 n, v;\nmov.u32 n, 0;\n"
                 "L_%=:\nld.volatile.shared.u32 v, [%0];\nsetp.ge.u32 p, v, %1;\n@p bra D_%=;\nnanosleep.u32 400;\n"
                 "add.u32 n, n, 1;\nsetp.lt.u32 p, n, %2;\n@p bra L_%=;\ntrap;\nD_%=:\n}"
                 ::"r"(a), "r"(step), "n"(SPIN_LIMIT) : "memory");
}
__device__ __forceinline__ void mbar_arrive_if(uint32_t bar, bool on) {
    asm volatile("{\n.reg .pred p;\nsetp.ne.s32 p, %1, 0;\n@p mbarrier.arrive.shared::cta.b64 _, [%0];\n}" ::"r"(bar), "r"((int)on) : "memory");
}
__device__ __forceinline__ void tma2d(uint32_t dst, const CUtensorMap* m, int c0, int c1, uint32_t bar, bool first) {
    asm volatile("{\n.reg .pred p;\nelect.sync _|p, 0xffffffff;\n"
                 "@p cp.async.bulk.tensor.2d.shared::cluster.global.mbarrier::complete_tx::bytes.L2::cache_hint [%0], [%1, {%3, %4}], [%2], %5;\n}"
                 ::"r"(dst), "l"(m), "r"(bar), "r"(c0), "r"(c1), "l"(first ? L2_FIRST : L2_NORMAL) : "memory");
}
__device__ __forceinline__ void tma3d_prefetch(const CUtensorMap* m, int row, int cb) {
    asm volatile("{\n.reg .pred p;\nelect.sync _|p, 0xffffffff;\n@p cp.async.bulk.prefetch.tensor.3d.L2.global [%0, {%1, %2, %3}];\n}"
                 ::"l"(m), "r"(0), "r"(row), "r"(cb) : "memory");
}
__device__ __forceinline__ void l2_prefetch(const void* p, uint32_t bytes) {
    asm volatile("{\n.reg .pred p;\nelect.sync _|p, 0xffffffff;\n@p cp.async.bulk.prefetch.L2.global [%0], %1;\n}" ::"l"(p), "r"(bytes) : "memory");
}
__device__ __forceinline__ void bulk_store(void* dst, uint32_t src, uint32_t bytes, bool first) {
    asm volatile("{\n.reg .pred p;\nelect.sync _|p, 0xffffffff;\n@p cp.async.bulk.global.shared::cta.bulk_group.L2::cache_hint [%0], [%1], %2, %3;\n}"
                 ::"l"(dst), "r"(src), "r"(bytes), "l"(first ? L2_FIRST : L2_NORMAL) : "memory");
}
__device__ __forceinline__ void flag_wait(const uint32_t* f, uint32_t target) {
    asm volatile("{\n.reg .pred p;\n.reg .u32 v;\n"
                 "L_%=:\nld.acquire.gpu.global.u32 v, [%0];\nsub.u32 v, v, %1;\nsetp.lt.s32 p, v, 0;\n@p nanosleep.u32 100;\n@p bra L_%=;\n}"
                 ::"l"(f), "r"(target) : "memory");
}
__device__ __forceinline__ uint4 ld_poll(const uint4* p) {
    uint4 v;
    asm volatile("{\n.reg .b128 t;\nld.relaxed.gpu.global.b128 t, [%4];\nmov.b128 {%0, %1, %2, %3}, t;\n}"
                 : "=r"(v.x), "=r"(v.y), "=r"(v.z), "=r"(v.w) : "l"(p) : "memory");
    return v;
}
__device__ __forceinline__ void st_pub(uint4* p, uint4 v, bool on) {
    asm volatile("{\n.reg .pred p;\n.reg .b128 t;\nsetp.ne.s32 p, %5, 0;\nmov.b128 t, {%1, %2, %3, %4};\n@p st.relaxed.gpu.global.b128 [%0], t;\n}"
                 ::"l"(p), "r"(v.x), "r"(v.y), "r"(v.z), "r"(v.w), "r"((int)on) : "memory");
}
__device__ __forceinline__ void st_pub(uint32_t* p, uint32_t v, bool on) {
    asm volatile("{\n.reg .pred p;\nsetp.ne.s32 p, %2, 0;\n@p st.relaxed.gpu.global.u32 [%0], %1;\n}" ::"l"(p), "r"(v), "r"((int)on) : "memory");
}
__device__ __forceinline__ void flag_add(uint32_t* p) {
    asm volatile("red.release.gpu.global.add.u32 [%0], 1;" ::"l"(p) : "memory");
}
__device__ __forceinline__ uint32_t lds32(uint32_t a) {
    uint32_t v;
    asm volatile("ld.shared.u32 %0, [%1];" : "=r"(v) : "r"(a) : "memory");
    return v;
}
__device__ __forceinline__ uint4 lds128(uint32_t a) {
    uint4 v;
    asm volatile("ld.shared.v4.u32 {%0, %1, %2, %3}, [%4];" : "=r"(v.x), "=r"(v.y), "=r"(v.z), "=r"(v.w) : "r"(a) : "memory");
    return v;
}
__device__ __forceinline__ void sched_fence(uint32_t& v, uint32_t z) {
    uint32_t ck;
    asm volatile("mov.u32 %0, %%clock;" : "=r"(ck)::"memory");
    v ^= ck & z;
}
__device__ __forceinline__ void fence_async_global() { asm volatile("fence.proxy.async.global;" ::: "memory"); }
__device__ __forceinline__ void fence_async_smem() { asm volatile("fence.proxy.async.shared::cta;" ::: "memory"); }
__device__ __forceinline__ void bar_sync(int id, int n) { asm volatile("bar.sync %0, %1;" ::"r"(id), "r"(n) : "memory"); }
__device__ __forceinline__ void bar_arrive(int id, int n) { asm volatile("bar.arrive %0, %1;" ::"r"(id), "r"(n) : "memory"); }
__device__ __forceinline__ void wg_fence() { asm volatile("wgmma.fence.sync.aligned;" ::: "memory"); }
__device__ __forceinline__ void wg_commit() { asm volatile("wgmma.commit_group.sync.aligned;" ::: "memory"); }
template <int N> __device__ __forceinline__ void wg_wait() { asm volatile("wgmma.wait_group.sync.aligned %0;" ::"n"(N) : "memory"); }
template <int N> __device__ __forceinline__ void reg_fence(float (&d)[N]) {
#pragma unroll
    for (int i = 0; i < N; i++) asm volatile("" : "+f"(d[i])::"memory");
}
template <int N> __device__ __forceinline__ void reg_fence(uint32_t (&d)[N]) {
#pragma unroll
    for (int i = 0; i < N; i++) asm volatile("" : "+r"(d[i])::"memory");
}
__device__ __forceinline__ uint32_t desc_k(uint32_t a) { return ((a & 0x3ffff) >> 4) | (1u << 16); }
__device__ __forceinline__ uint32_t desc_mn(uint32_t a) { return ((a & 0x3ffff) >> 4) | (1024u << 16); }

__device__ __forceinline__ uint64_t desc64(uint32_t lo, uint32_t hi) {
    uint64_t d;
    asm("mov.b64 %0, {%1, %2};" : "=l"(d) : "r"(lo), "r"(hi));
    return d;
}
__device__ __forceinline__ void desc_add(uint64_t& d, uint32_t x) { asm("add.u64 %0, %0, %1;" : "+l"(d) : "l"((uint64_t)x)); }

template <int TB>
__device__ __forceinline__ void wgmma_ss128(float (&d)[64], uint64_t da, uint64_t db, int acc) {
    asm volatile("{\n.reg .pred p;\nsetp.ne.b32 p, %66, 0;\n"
        "wgmma.mma_async.sync.aligned.m64n128k16.f32.bf16.bf16 {%0, %1, %2, %3, %4, %5, %6, %7, %8, %9, %10, %11, %12, %13, %14, %15, %16, %17, %18, %19, %20, %21, %22, %23, %24, %25, %26, %27, %28, %29, %30, %31, %32, %33, %34, %35, %36, %37, %38, %39, %40, %41, %42, %43, %44, %45, %46, %47, %48, %49, %50, %51, %52, %53, %54, %55, %56, %57, %58, %59, %60, %61, %62, %63}, %64, %65, p, 1, 1, 0, %67;\n}"
        : "+f"(d[0]), "+f"(d[1]), "+f"(d[2]), "+f"(d[3]), "+f"(d[4]), "+f"(d[5]), "+f"(d[6]), "+f"(d[7]), "+f"(d[8]), "+f"(d[9]), "+f"(d[10]), "+f"(d[11]), "+f"(d[12]), "+f"(d[13]), "+f"(d[14]), "+f"(d[15]), "+f"(d[16]), "+f"(d[17]), "+f"(d[18]), "+f"(d[19]), "+f"(d[20]), "+f"(d[21]), "+f"(d[22]), "+f"(d[23]), "+f"(d[24]), "+f"(d[25]), "+f"(d[26]), "+f"(d[27]), "+f"(d[28]), "+f"(d[29]), "+f"(d[30]), "+f"(d[31]), "+f"(d[32]), "+f"(d[33]), "+f"(d[34]), "+f"(d[35]), "+f"(d[36]), "+f"(d[37]), "+f"(d[38]), "+f"(d[39]), "+f"(d[40]), "+f"(d[41]), "+f"(d[42]), "+f"(d[43]), "+f"(d[44]), "+f"(d[45]), "+f"(d[46]), "+f"(d[47]), "+f"(d[48]), "+f"(d[49]), "+f"(d[50]), "+f"(d[51]), "+f"(d[52]), "+f"(d[53]), "+f"(d[54]), "+f"(d[55]), "+f"(d[56]), "+f"(d[57]), "+f"(d[58]), "+f"(d[59]), "+f"(d[60]), "+f"(d[61]), "+f"(d[62]), "+f"(d[63])
        : "l"(da), "l"(db), "r"(acc), "n"(TB));
}
template <int TB>
__device__ __forceinline__ void wgmma_ss128_init(float (&d)[64], uint64_t da, uint64_t db) {
    asm volatile("{\n.reg .pred p;\nsetp.ne.b32 p, 0, 0;\n"
        "wgmma.mma_async.sync.aligned.m64n128k16.f32.bf16.bf16 {%0, %1, %2, %3, %4, %5, %6, %7, %8, %9, %10, %11, %12, %13, %14, %15, %16, %17, %18, %19, %20, %21, %22, %23, %24, %25, %26, %27, %28, %29, %30, %31, %32, %33, %34, %35, %36, %37, %38, %39, %40, %41, %42, %43, %44, %45, %46, %47, %48, %49, %50, %51, %52, %53, %54, %55, %56, %57, %58, %59, %60, %61, %62, %63}, %64, %65, p, 1, 1, 0, %66;\n}"
        : "=f"(d[0]), "=f"(d[1]), "=f"(d[2]), "=f"(d[3]), "=f"(d[4]), "=f"(d[5]), "=f"(d[6]), "=f"(d[7]), "=f"(d[8]), "=f"(d[9]), "=f"(d[10]), "=f"(d[11]), "=f"(d[12]), "=f"(d[13]), "=f"(d[14]), "=f"(d[15]), "=f"(d[16]), "=f"(d[17]), "=f"(d[18]), "=f"(d[19]), "=f"(d[20]), "=f"(d[21]), "=f"(d[22]), "=f"(d[23]), "=f"(d[24]), "=f"(d[25]), "=f"(d[26]), "=f"(d[27]), "=f"(d[28]), "=f"(d[29]), "=f"(d[30]), "=f"(d[31]), "=f"(d[32]), "=f"(d[33]), "=f"(d[34]), "=f"(d[35]), "=f"(d[36]), "=f"(d[37]), "=f"(d[38]), "=f"(d[39]), "=f"(d[40]), "=f"(d[41]), "=f"(d[42]), "=f"(d[43]), "=f"(d[44]), "=f"(d[45]), "=f"(d[46]), "=f"(d[47]), "=f"(d[48]), "=f"(d[49]), "=f"(d[50]), "=f"(d[51]), "=f"(d[52]), "=f"(d[53]), "=f"(d[54]), "=f"(d[55]), "=f"(d[56]), "=f"(d[57]), "=f"(d[58]), "=f"(d[59]), "=f"(d[60]), "=f"(d[61]), "=f"(d[62]), "=f"(d[63])
        : "l"(da), "l"(db), "n"(TB));
}
template <int TB>
__device__ __forceinline__ void wgmma_ss64(float (&d)[32], uint64_t da, uint64_t db, int acc) {
    asm volatile("{\n.reg .pred p;\nsetp.ne.b32 p, %34, 0;\n"
        "wgmma.mma_async.sync.aligned.m64n64k16.f32.bf16.bf16 {%0, %1, %2, %3, %4, %5, %6, %7, %8, %9, %10, %11, %12, %13, %14, %15, %16, %17, %18, %19, %20, %21, %22, %23, %24, %25, %26, %27, %28, %29, %30, %31}, %32, %33, p, 1, 1, 0, %35;\n}"
        : "+f"(d[0]), "+f"(d[1]), "+f"(d[2]), "+f"(d[3]), "+f"(d[4]), "+f"(d[5]), "+f"(d[6]), "+f"(d[7]), "+f"(d[8]), "+f"(d[9]), "+f"(d[10]), "+f"(d[11]), "+f"(d[12]), "+f"(d[13]), "+f"(d[14]), "+f"(d[15]), "+f"(d[16]), "+f"(d[17]), "+f"(d[18]), "+f"(d[19]), "+f"(d[20]), "+f"(d[21]), "+f"(d[22]), "+f"(d[23]), "+f"(d[24]), "+f"(d[25]), "+f"(d[26]), "+f"(d[27]), "+f"(d[28]), "+f"(d[29]), "+f"(d[30]), "+f"(d[31])
        : "l"(da), "l"(db), "r"(acc), "n"(TB));
}
template <int TB>
__device__ __forceinline__ void wgmma_ss64_init(float (&d)[32], uint64_t da, uint64_t db) {
    asm volatile("{\n.reg .pred p;\nsetp.ne.b32 p, 0, 0;\n"
        "wgmma.mma_async.sync.aligned.m64n64k16.f32.bf16.bf16 {%0, %1, %2, %3, %4, %5, %6, %7, %8, %9, %10, %11, %12, %13, %14, %15, %16, %17, %18, %19, %20, %21, %22, %23, %24, %25, %26, %27, %28, %29, %30, %31}, %32, %33, p, 1, 1, 0, %34;\n}"
        : "=f"(d[0]), "=f"(d[1]), "=f"(d[2]), "=f"(d[3]), "=f"(d[4]), "=f"(d[5]), "=f"(d[6]), "=f"(d[7]), "=f"(d[8]), "=f"(d[9]), "=f"(d[10]), "=f"(d[11]), "=f"(d[12]), "=f"(d[13]), "=f"(d[14]), "=f"(d[15]), "=f"(d[16]), "=f"(d[17]), "=f"(d[18]), "=f"(d[19]), "=f"(d[20]), "=f"(d[21]), "=f"(d[22]), "=f"(d[23]), "=f"(d[24]), "=f"(d[25]), "=f"(d[26]), "=f"(d[27]), "=f"(d[28]), "=f"(d[29]), "=f"(d[30]), "=f"(d[31])
        : "l"(da), "l"(db), "n"(TB));
}
__device__ __forceinline__ void wgmma_rs128(float (&d)[64], uint32_t a0, uint32_t a1, uint32_t a2, uint32_t a3, uint64_t db, int acc) {
    asm volatile("{\n.reg .pred p;\nsetp.ne.b32 p, %69, 0;\n"
        "wgmma.mma_async.sync.aligned.m64n128k16.f32.bf16.bf16 {%0, %1, %2, %3, %4, %5, %6, %7, %8, %9, %10, %11, %12, %13, %14, %15, %16, %17, %18, %19, %20, %21, %22, %23, %24, %25, %26, %27, %28, %29, %30, %31, %32, %33, %34, %35, %36, %37, %38, %39, %40, %41, %42, %43, %44, %45, %46, %47, %48, %49, %50, %51, %52, %53, %54, %55, %56, %57, %58, %59, %60, %61, %62, %63}, {%64, %65, %66, %67}, %68, p, 1, 1, 1;\n}"
        : "+f"(d[0]), "+f"(d[1]), "+f"(d[2]), "+f"(d[3]), "+f"(d[4]), "+f"(d[5]), "+f"(d[6]), "+f"(d[7]), "+f"(d[8]), "+f"(d[9]), "+f"(d[10]), "+f"(d[11]), "+f"(d[12]), "+f"(d[13]), "+f"(d[14]), "+f"(d[15]), "+f"(d[16]), "+f"(d[17]), "+f"(d[18]), "+f"(d[19]), "+f"(d[20]), "+f"(d[21]), "+f"(d[22]), "+f"(d[23]), "+f"(d[24]), "+f"(d[25]), "+f"(d[26]), "+f"(d[27]), "+f"(d[28]), "+f"(d[29]), "+f"(d[30]), "+f"(d[31]), "+f"(d[32]), "+f"(d[33]), "+f"(d[34]), "+f"(d[35]), "+f"(d[36]), "+f"(d[37]), "+f"(d[38]), "+f"(d[39]), "+f"(d[40]), "+f"(d[41]), "+f"(d[42]), "+f"(d[43]), "+f"(d[44]), "+f"(d[45]), "+f"(d[46]), "+f"(d[47]), "+f"(d[48]), "+f"(d[49]), "+f"(d[50]), "+f"(d[51]), "+f"(d[52]), "+f"(d[53]), "+f"(d[54]), "+f"(d[55]), "+f"(d[56]), "+f"(d[57]), "+f"(d[58]), "+f"(d[59]), "+f"(d[60]), "+f"(d[61]), "+f"(d[62]), "+f"(d[63])
        : "r"(a0), "r"(a1), "r"(a2), "r"(a3), "l"(db), "r"(acc));
}

__device__ __forceinline__ uint32_t pack2(float lo, float hi) {
    uint32_t r;
    asm("cvt.rn.bf16x2.f32 %0, %1, %2;" : "=r"(r) : "f"(hi), "f"(lo));
    return r;
}
__device__ __forceinline__ float bf_lo(uint32_t v) { return __uint_as_float(v << 16); }
__device__ __forceinline__ float bf_hi(uint32_t v) { return __uint_as_float(v & 0xffff0000u); }
__device__ __forceinline__ float rbf(float v) { return bf_lo(pack2(v, v)); }
__device__ __forceinline__ uint32_t badd(uint32_t a, uint32_t b) {
    uint32_t r;
    asm("add.rn.bf16x2 %0, %1, %2;" : "=r"(r) : "r"(a), "r"(b));
    return r;
}
__device__ __forceinline__ uint32_t bsub(uint32_t a, uint32_t b) {
    uint32_t r;
    asm("sub.rn.bf16x2 %0, %1, %2;" : "=r"(r) : "r"(a), "r"(b));
    return r;
}
__device__ __forceinline__ uint32_t bmul(uint32_t a, uint32_t b) {
    uint32_t r;
    asm("mul.rn.bf16x2 %0, %1, %2;" : "=r"(r) : "r"(a), "r"(b));
    return r;
}
__device__ __forceinline__ uint32_t ln_apply(uint32_t x, uint32_t mb, float rs, uint32_t scale, uint32_t shift) {
    const uint32_t d = bsub(x, mb);
    return badd(bmul(pack2(bf_lo(d) * rs, bf_hi(d) * rs), scale), shift);
}
__device__ __forceinline__ float ex2(float v) {
    float r;
    asm("ex2.approx.ftz.f32 %0, %1;" : "=f"(r) : "f"(v));
    return r;
}
__device__ __forceinline__ float rcp(float v) {
    float r;
    asm("rcp.approx.ftz.f32 %0, %1;" : "=f"(r) : "f"(v));
    return r;
}
__device__ __forceinline__ float sqrt_fast(float v) {
    float r;
    asm("sqrt.approx.ftz.f32 %0, %1;" : "=f"(r) : "f"(v));
    return r;
}
__device__ __forceinline__ float ln_rstd(float var) { return rcp(rbf(sqrt_fast(rbf(rbf(var) + 1e-5f)))); }
__device__ __forceinline__ float sigmoid(float v) { return rcp(1.f + ex2(-1.4426950408889634f * v)); }
__device__ __forceinline__ float quad_sum(float v) {
    v += __shfl_xor_sync(0xffffffffu, v, 1);
    return v + __shfl_xor_sync(0xffffffffu, v, 2);
}

constexpr uint32_t HI_128 = 0x40000040u, HI_IMG = 0x80000080u, HI_Q = 0x80000040u;
template <int M, int RH>
__device__ __forceinline__ uint4 img_pack(const float (&d)[64], float s) {
    uint4 v;
    v.x = pack2(d[16 * M + 2 * RH] * s, d[16 * M + 2 * RH + 1] * s);
    v.y = pack2(d[16 * M + 4 + 2 * RH] * s, d[16 * M + 5 + 2 * RH] * s);
    v.z = pack2(d[16 * M + 8 + 2 * RH] * s, d[16 * M + 9 + 2 * RH] * s);
    v.w = pack2(d[16 * M + 12 + 2 * RH] * s, d[16 * M + 13 + 2 * RH] * s);
    return v;
}
template <int M>
__device__ __forceinline__ void img_store_global(uint32_t img, uint32_t toff, const float (&d)[64], float s0, float s1) {
    uint4* p = reinterpret_cast<uint4*>(g_img + (img + toff)) + M * 32;
    p[0] = img_pack<M, 0>(d, s0);
    p[128] = img_pack<M, 1>(d, s1);
}
__device__ __forceinline__ void sts128(uint32_t a, uint4 v) {
    asm volatile("st.shared.v4.b32 [%0], {%1, %2, %3, %4};" ::"r"(a), "r"(v.x), "r"(v.y), "r"(v.z), "r"(v.w) : "memory");
}
constexpr float SM_C = 0.08838834764831845f * 1.4426950408889634f;
__device__ __forceinline__ float pack2f(float lo, float hi) {
    float r;
    asm("{\n.reg .b32 t;\ncvt.rn.bf16x2.f32 t, %1, %2;\nmov.b32 %0, t;\n}" : "=f"(r) : "f"(hi), "f"(lo));
    return r;
}
template <int M, bool SCALE, bool PARK>
__device__ __forceinline__ void pack_group(float (&d)[64], float (&v)[8], float s0, float s1) {
#pragma unroll
    for (int i = 0; i < 8; i++) {
        const int k = 16 * M + 4 * (i & 3) + 2 * (i >> 2);
        v[i] = SCALE ? pack2f(d[k] * (i < 4 ? s0 : s1), d[k + 1] * (i < 4 ? s0 : s1)) : pack2f(d[k], d[k + 1]);
        if (PARK && M > 0) d[16 * (M > 0 ? M - 1 : 0) + i] = v[i];
    }
}
__device__ __forceinline__ uint32_t q_off(uint32_t toff) {
    asm volatile("" : "+r"(toff));
    return (((toff >> 1) & ~2047u) ^ 8192) + (toff & 511);
}
template <int M>
__device__ __forceinline__ void ctx_store_part(float4* p, float (&d)[64], float i0, float i1) {
    float v[8];
    pack_group<M, true, true>(d, v, i0, i1);
    p[M * 32] = make_float4(v[0], v[1], v[2], v[3]);
    p[M * 32 + 128] = make_float4(v[4], v[5], v[6], v[7]);
}
__device__ __forceinline__ void ctx_store(uint32_t img, uint32_t toff, float (&o)[64], float i0, float i1) {
    asm volatile("" : "+r"(toff));
    float4* p = reinterpret_cast<float4*>(g_img + (img + toff));
    ctx_store_part<0>(p, o, i0, i1); ctx_store_part<1>(p, o, i0, i1); ctx_store_part<2>(p, o, i0, i1); ctx_store_part<3>(p, o, i0, i1);
}

__device__ __forceinline__ void slot_wait(uint32_t bars, uint32_t& ph, uint32_t slot) {
    mbar_wait(bars + 8 * slot, (ph >> slot) & 1);
    ph ^= 1u << slot;
}
__device__ __forceinline__ void release_if(uint32_t eb, uint32_t slot, bool on) {
    asm volatile("{\n.reg .pred p;\nsetp.ne.s32 p, %1, 0;\n@p mbarrier.arrive.shared::cluster.b64 _, [%0];\n}" ::"r"(eb + 8 * slot), "r"((int)on) : "memory");
}
__device__ __forceinline__ void slot_expect(uint32_t sb, uint32_t slot) {
    asm volatile("{\n.reg .pred p;\nelect.sync _|p, 0xffffffff;\n@p mbarrier.arrive.expect_tx.shared::cta.b64 _, [%0], 32768;\n}"
                 ::"r"(sb + BAR_FULL + 8 * slot) : "memory");
}
__device__ __forceinline__ void slot_acquire(uint32_t sb, uint32_t& ph, uint32_t slot) {
    slot_wait(sb + BAR_EMPTY, ph, slot);
    slot_expect(sb, slot);
}
__device__ __forceinline__ void load_bulk(uint32_t sb, uint32_t slot, uint32_t off, const void* src, uint32_t bytes, bool both, bool first) {
    if (both)
        asm volatile("{\n.reg .pred p;\nelect.sync _|p, 0xffffffff;\n"
                     "@p cp.async.bulk.shared::cluster.global.mbarrier::complete_tx::bytes.multicast::cluster.L2::cache_hint [%0], [%1], %5, [%2], %4, %3;\n}"
                     ::"r"(sb + slot * SLOT + off), "l"(src), "r"(sb + BAR_FULL + 8 * slot), "l"(first ? L2_FIRST : L2_NORMAL), "h"((uint16_t)3),
                     "r"(bytes) : "memory");
    else
        asm volatile("{\n.reg .pred p;\nelect.sync _|p, 0xffffffff;\n"
                     "@p cp.async.bulk.shared::cluster.global.mbarrier::complete_tx::bytes.L2::cache_hint [%0], [%1], %4, [%2], %3;\n}"
                     ::"r"(sb + slot * SLOT + off), "l"(src), "r"(sb + BAR_FULL + 8 * slot), "l"(first ? L2_FIRST : L2_NORMAL), "r"(bytes) : "memory");
}
__device__ __forceinline__ void load_tile(uint32_t sb, uint32_t slot, uint32_t off, const CUtensorMap* m, int row, int cb, bool both, bool first) {
    if (both)
        asm volatile("{\n.reg .pred p;\nelect.sync _|p, 0xffffffff;\n"
                     "@p cp.async.bulk.tensor.3d.shared::cluster.global.mbarrier::complete_tx::bytes.multicast::cluster.L2::cache_hint [%0], [%1, {%3, %4, %5}], [%2], %7, %6;\n}"
                     ::"r"(sb + slot * SLOT + off), "l"(m), "r"(sb + BAR_FULL + 8 * slot), "r"(0), "r"(row), "r"(cb),
                     "l"(first ? L2_FIRST : L2_NORMAL), "h"((uint16_t)3) : "memory");
    else
        asm volatile("{\n.reg .pred p;\nelect.sync _|p, 0xffffffff;\n"
                     "@p cp.async.bulk.tensor.3d.shared::cluster.global.mbarrier::complete_tx::bytes.L2::cache_hint [%0], [%1, {%3, %4, %5}], [%2], %6;\n}"
                     ::"r"(sb + slot * SLOT + off), "l"(m), "r"(sb + BAR_FULL + 8 * slot), "r"(0), "r"(row), "r"(cb),
                     "l"(first ? L2_FIRST : L2_NORMAL) : "memory");
}
__device__ __forceinline__ uint32_t ring_next(uint32_t r) { return r == 4 ? 0 : r + 1; }
__device__ __forceinline__ uint32_t w_table(int hp) { return hp ? 0x3104u : 0x4210u; }
__device__ __forceinline__ uint32_t a_table(int hp) { return hp ? 0x625u : 0x635u; }
__device__ __forceinline__ uint32_t a_next(uint32_t& t) {
    const uint32_t s = t & 15;
    t = (t >> 4) | (s << 8);
    return s;
}
constexpr uint32_t O_TABLE = 0x1604235u;
__device__ __forceinline__ uint32_t o_next(uint32_t& t) {
    const uint32_t s = t & 15;
    t = (t >> 4) | (s << 24);
    return s;
}
__device__ __forceinline__ int o_head(int i, int kh) { return i < 16 ? 4 * (i & 7) + 2 * (kh ^ 1) + (i >> 3) : 29 + 2 * kh; }

template <bool INIT>
__device__ __forceinline__ void gemm_issue(float (&d)[64], uint32_t a, uint32_t b, int acc, bool img) {
    uint64_t da = desc64(a, img ? HI_IMG : HI_128), db = desc64(b, HI_128);
    wg_fence();
#pragma unroll
    for (int k = 0; k < 8; k++) {
        if (INIT && k == 0) wgmma_ss128_init<1>(d, da, db);
        else wgmma_ss128<1>(d, da, db, k ? 1 : acc);
        desc_add(da, !(k & 1) ? 2 : img ? 30 : k == 3 ? 1018 : 2);
        desc_add(db, 128);
    }
    wg_commit();
}

template <bool ODD>
__device__ __forceinline__ bool proj_tile(float (&acc)[64], float (&prev)[64], int t, int q0, uint32_t sb, int wg, uint32_t eb, bool rel, uint32_t& fph,
                                          uint32_t wtab, uint32_t& atab, uint32_t prev_img, uint32_t toff, float s0, float s1,
                                          uint32_t (&v)[32]) {
    const uint32_t a0 = desc_k(sb + (wg ^ (ODD && t == 5)) * 8192), b0 = desc_mn(sb);
    constexpr int U = ODD ? UNR : 1;
#pragma unroll U
    for (int q = ODD ? 0 : q0; q < 4; q++) {
        const uint32_t ws = (wtab >> (4 * q)) & 15, as = a_next(atab);
        if (!ODD && t != 2) slot_wait(sb + BAR_FULL, fph, ws);
        slot_wait(sb + BAR_FULL, fph, as);
        if (ODD && q == 2 && t == 5) {
            const uint32_t a = sb + 5 * SLOT + q_off(toff);
#pragma unroll
            for (int i = 0; i < 8; i++) sts128(a + (i >> 2) * 16384 + (i & 2) * 256 + (i & 1) * 1024, make_uint4(v[4 * i], v[4 * i + 1], v[4 * i + 2], v[4 * i + 3]));
        }
        bar_sync(1 + wg, 256);
        gemm_issue<false>(acc, a0 + as * (SLOT / 16), b0 + ws * (SLOT / 16), q, false);
        bar_arrive(2 - wg, 256);
        wg_wait<1>();
        reg_fence(prev);
        if (ODD && t == 5) {
            if (q == 0) {
#pragma unroll
                for (int i = 0; i < 32; i++) {
                    const int k = 16 * (i >> 3) + 4 * (i & 3) + ((i >> 1) & 2);
                    v[i] = pack2(prev[k], prev[k + 1]);
                }
            }
            if (q == 2) {
                fence_async_smem();
                slot_wait(sb + BAR_FULL, fph, wtab & 15);
                wg_wait<0>();
                release_if(eb, as, rel);
                release_if(eb, ws, rel);
                reg_fence(acc);
                return true;
            }
        } else {
            if (q == 0) img_store_global<0>(prev_img, toff, prev, s0, s1);
            if (q == 1) img_store_global<1>(prev_img, toff, prev, s0, s1);
            if (q == 2) img_store_global<2>(prev_img, toff, prev, s0, s1);
            if (q == 3) img_store_global<3>(prev_img, toff, prev, s0, s1);
        }
        wg_wait<0>();
        release_if(eb, as, rel && !(ODD && (q & 1) && t == 5));
        if (ODD) release_if(eb, ws, rel && t != 1);
    }
    reg_fence(acc);
    return false;
}

__device__ __forceinline__ void qk_issue(float (&s)[64], uint32_t q, uint32_t k) {
    wg_fence();
    uint64_t da = desc64(q, HI_Q), db = desc64(k, HI_IMG);
    wgmma_ss128_init<0>(s, da, db);
#pragma unroll
    for (int i = 1; i < 8; i++) {
        desc_add(da, (i & 1) ? 2 : i == 4 ? 990 : 30);
        desc_add(db, (i & 1) ? 2 : 30);
        wgmma_ss128<0>(s, da, db, 1);
    }
    wg_commit();
}
__device__ __forceinline__ void qk_issue(float (&s)[32], uint32_t q, uint32_t k) {
    wg_fence();
    uint64_t da = desc64(q, HI_Q), db = desc64(k, HI_IMG);
    wgmma_ss64_init<0>(s, da, db);
#pragma unroll
    for (int i = 1; i < 8; i++) {
        desc_add(da, (i & 1) ? 2 : i == 4 ? 990 : 30);
        desc_add(db, (i & 1) ? 2 : 30);
        wgmma_ss64<0>(s, da, db, 1);
    }
    wg_commit();
}
__device__ __forceinline__ void pv_issue(float (&o)[64], const uint32_t (&p)[32], uint32_t v, int acc, bool half) {
    uint64_t db = desc64(v, HI_IMG);
    if (half) {
        asm volatile("// half" ::: "memory");
        wg_fence();
#pragma unroll
        for (int i = 0; i < 4; i++) {
            wgmma_rs128(o, p[4 * i], p[4 * i + 1], p[4 * i + 2], p[4 * i + 3], db, i ? 1 : acc);
            desc_add(db, 256);
        }
        wg_commit();
        asm volatile("// half" ::: "memory");
    } else {
        wg_fence();
#pragma unroll
        for (int i = 0; i < 8; i++) {
            wgmma_rs128(o, p[4 * i], p[4 * i + 1], p[4 * i + 2], p[4 * i + 3], db, i ? 1 : acc);
            desc_add(db, 256);
        }
        wg_commit();
    }
}
__device__ __forceinline__ void tri_mask(float (&s)[64], float x) {
#pragma unroll
    for (int k = 0; k < 16; k++) {
        float b;
        asm("sub.sat.f32 %0, %1, %2;" : "=f"(b) : "f"((float)(8 * (k >> 1) + (k & 1))), "f"(x));
        const int i = 32 + 4 * (k >> 1) + (k & 1);
        asm("fma.rn.f32 %0, %1, 0fFF61B1E6, %0;" : "+f"(s[i]) : "f"(b));
        if (k < 14) asm("fma.rn.f32 %0, %1, 0fFF61B1E6, %0;" : "+f"(s[i + 6]) : "f"(b));
    }
}
__device__ __forceinline__ void tri_mask_copy(float (&s)[64], const float (&h)[32], float x) {
#pragma unroll
    for (int i = 0; i < 32; i++) {
            asm("{\n.reg .pred p;\nsetp.lt.f32 p, %2, %3;\nselp.f32 %0, 0fFF800000, %1, p;\n}"
                : "=f"(s[i]) : "f"(h[i]), "f"(x), "f"((float)(8 * (i >> 2) - 4 * (i & 2) + (i & 1))));
        s[32 + i] = __uint_as_float(0xff800000u);
    }
}
constexpr float SM_HI = 1152921504606846976.f, SM_LO = 1.f / 1152921504606846976.f;
__device__ __forceinline__ bool softmax_unsafe(float t0, float t1, bool first) {
    bool bad = __any_sync(0xffffffffu, fmaxf(t0, t1) > SM_HI);
    if (first) {
        uint32_t a = __ballot_sync(0xffffffffu, t0 >= SM_LO), b = __ballot_sync(0xffffffffu, t1 >= SM_LO);
        a |= a >> 1;
        b |= b >> 1;
        bad |= ((a | (a >> 2)) & (b | (b >> 2)) & 0x11111111u) != 0x11111111u;
    }
    return bad;
}
__device__ __forceinline__ void softmax_remax(const float (&s)[64], float (&m)[2], bool first, float& m0, float& m1, float& a0, float& a1) {
    m0 = fmaxf(s[0], s[1]), m1 = fmaxf(s[2], s[3]);
#pragma unroll
    for (int k = 1; k < 16; k++) {
        m0 = fmaxf(m0, fmaxf(s[4 * k], s[4 * k + 1]));
        m1 = fmaxf(m1, fmaxf(s[4 * k + 2], s[4 * k + 3]));
    }
    m0 = fmaxf(m0, __shfl_xor_sync(0xffffffffu, m0, 1));
    m1 = fmaxf(m1, __shfl_xor_sync(0xffffffffu, m1, 1));
    m0 = fmaxf(m0, __shfl_xor_sync(0xffffffffu, m0, 2));
    m1 = fmaxf(m1, __shfl_xor_sync(0xffffffffu, m1, 2));
    if (!first) {
        m0 = fmaxf(m0, 0.f);
        m1 = fmaxf(m1, 0.f);
    }
    a0 = first ? 1.f : ex2(-m0);
    a1 = first ? 1.f : ex2(-m1);
    m[0] += m0;
    m[1] += m1;
}
template <int J0, int J1>
__device__ __forceinline__ void softmax_exp(const float (&s)[64], uint32_t (&p)[32], float (&t)[4]) {
#pragma unroll
    for (int k = J0; k < J1; k++) {
        const float e0 = ex2(s[4 * k]), e1 = ex2(s[4 * k + 1]), e2 = ex2(s[4 * k + 2]), e3 = ex2(s[4 * k + 3]);
        if (k == 0) { t[0] = e0; t[1] = e1; t[2] = e2; t[3] = e3; }
        else { t[0] += e0; t[1] += e1; t[2] += e2; t[3] += e3; }
        p[2 * k] = pack2(e0, e1);
        p[2 * k + 1] = pack2(e2, e3);
    }
}
__device__ __forceinline__ void mma16816(float (&d)[4], const uint32_t* a, uint32_t b0, uint32_t b1) {
    asm("mma.sync.aligned.m16n8k16.row.col.f32.bf16.bf16.f32 {%0, %1, %2, %3}, {%4, %5, %6, %7}, {%8, %9}, {%0, %1, %2, %3};"
        : "+f"(d[0]), "+f"(d[1]), "+f"(d[2]), "+f"(d[3]) : "r"(a[0]), "r"(a[1]), "r"(a[2]), "r"(a[3]), "r"(b0), "r"(b1));
}
__device__ __forceinline__ uint2 best_key(const uint32_t* keys, int lane, uint32_t ep, uint32_t cur, int enough) {
#pragma unroll 1
    for (;;) {
        const uint4 k = ld_poll(reinterpret_cast<const uint4*>(keys) + lane);
        const bool ok = (((k.x ^ ep) | (k.y ^ ep) | (k.z ^ ep) | (k.w ^ ep)) & 31) == 0;
        const uint32_t best = __reduce_max_sync(0xffffffffu, ok ? max(max(k.x, k.y), max(k.z, k.w)) : 0u);
        const int n = __popc(__ballot_sync(0xffffffffu, ok));
        if (n == 32 || (n >= enough && best != cur)) return make_uint2(best, n == 32);
        __nanosleep(KSLEEP);
    }
}

__global__ void __cluster_dims__(2, 1, 1) __launch_bounds__(384, 1)
fused_kernel(const __grid_constant__ CUtensorMap tm_ckv, const __grid_constant__ CUtensorMap tm_wq,
             const __grid_constant__ CUtensorMap tm_wuk, const __grid_constant__ CUtensorMap tm_wuv,
             const __grid_constant__ CUtensorMap tm_wo, const __grid_constant__ CUtensorMap tm_wg,
             const __grid_constant__ CUtensorMap tm_wu,
             const __grid_constant__ CUtensorMap tm_wm, const __grid_constant__ CUtensorMap tm_x, const Params P) {
    extern __shared__ __align__(1024) uint8_t smem[];
    const uint32_t sb = (uint32_t)__cvta_generic_to_shared(smem);
    const int tid = threadIdx.x, lane = tid & 31, warp = __shfl_sync(0xffffffffu, tid >> 5, 0), wg = warp >> 2;
    const uint32_t sm = blockIdx.x < 8 ? blockIdx.x + 124 : blockIdx.x - 8, smq = ((sm - 64) * 147) >> 11;
    const int rb = sm < 64 ? (sm & 14) * 8 + (sm >> 4) * 2 + (sm & 1)
                 : sm < 120 ? ((sm - 64 - smq * 14) & 14) * 8 + 24 + smq * 2 + (sm & 1) : sm < 124 ? sm + 8 : sm - 116;
    const int grp = rb >> 3, j = rb & 7, kh = (grp >> (OMAP - 1)) & 1;
    const int cq = (j & 1) + ((grp >> (OMAP - 1)) & 2), ort = (OMAP == 1 ? grp & 12 : (grp & 8) + (grp & 1) * 4) + (j >> 1);
    if (warp == 0) TS(0);

    const CUtensorMap* tw = (j & 1) ? &tm_wuv : &tm_wuk;
    if (lane == 0) {
        if (warp == 8) {
#pragma unroll
            for (int i = 0; i < 7; i++) mbar_init(sb + BAR_FULL + 8 * i, 1);
            fence_async_smem();
        } else if (warp < 11) {
            const int w = warp - (warp > 8);
            const u64 cnt = (w < 5 ? (rb < NCTA ? 0x888888884444444ull : 0x888888888888888ull) : 0x111812111111118ull) >> (12 * (w % 5));
#pragma unroll
            for (int i = 0; i < 3; i++) mbar_init(sb + BAR_EMPTY + 24 * w + 8 * i, ((uint32_t)cnt >> (4 * i)) & 15);
        }
        asm volatile("fence.mbarrier_init.release.cluster;" ::: "memory");
    }
    __syncwarp();
    asm volatile("barrier.cluster.arrive.relaxed.aligned;" ::: "memory");
    if (warp == 8) {
        if (rb < NCTA) {
#pragma unroll 1
            for (int u = 0; u < 4; u++) {
                const uint32_t ws = u + (u == 3), as = (0x635u >> (4 * u)) & 15;
                slot_expect(sb, ws);
                load_tile(sb, ws, 0, tw, u * 128, 4 * grp, false, HINT & 1);
                if (u == 3) break;
                slot_expect(sb, as);
                load_tile(sb, as, 0, &tm_ckv, (j >> 1) * 128, u * 2, false, false);
                load_tile(sb, as, 16384, &tm_ckv, (j >> 1) * 128, u * 2 + 1, false, false);
            }
        } else {
#pragma unroll 1
            for (int i = 0; i < 6; i++) {
                slot_expect(sb, i);
                load_tile(sb, i, 0, &tm_wm, i * 64, (rb - NCTA) * 4, false, HINT & 64);
                if (i > 3) tma3d_prefetch(&tm_wm, i * 64 + 128, (rb - NCTA) * 4);
            }
        }
    }
    asm volatile("barrier.cluster.wait.aligned;" ::: "memory");

    if (rb >= NCTA) {
        uint32_t ph = 0, sl = 0;
        if (warp == 8) {
#pragma unroll 1
            for (int i = 6; i < 24; i++) {
                slot_acquire(sb, ph, sl);
                load_tile(sb, sl, 0, &tm_wm, (i & 7) * 64, (i >> 3) * 16 + (rb - NCTA) * 4, false, HINT & 64);
                if (++sl == 6) sl = 0;
            }
#pragma unroll 1
            for (int i = 0; i <= NFFN / NSPARE; i++) {
                const int b = (rb - NCTA) * (NFFN / NSPARE) + i;
                if (i < NFFN / NSPARE) {
                    asm volatile("cp.async.bulk.wait_group.read 0;" ::: "memory");
                    uint32_t done = 0x7f;
                    slot_acquire(sb, done, i & 1);
#pragma unroll 1
                    for (int k = 0; k < 4; k++) tma2d(sb + (i & 1) * SLOT + k * 8192, k < 2 ? &tm_wg : &tm_wu, b * 16, (k & 1) * 256, sb + BAR_FULL + 8 * (i & 1), (HINT & 128) && (i & 3) == 3);
                }
                if (i) {
                    mbar_wait(sb + BAR_FULL + 8 * (~i & 1), ((i - 1) >> 1) & 1);
                    bulk_store(g_wf + (b - 1) * SLOT, sb + (~i & 1) * SLOT, SLOT, HINT & 256);
                    asm volatile("cp.async.bulk.commit_group;" ::: "memory");
                }
            }
            asm volatile("cp.async.bulk.wait_group 0;" ::: "memory");
            fence_async_global();
            TS(4);
        } else if (warp < 8) {
            const uint32_t c2 = __ldg(reinterpret_cast<const uint32_t*>(P.c) + tid), ep = __ldcg(&g_sync.epoch[0]) + 1;
            uint32_t* sc = reinterpret_cast<uint32_t*>(smem + 6 * SLOT);
            sc[tid] = pack2(bf_lo(c2) * sigmoid(bf_lo(c2)), bf_hi(c2) * sigmoid(bf_hi(c2)));
            bar_sync(1, 256);
            const uint32_t a = sb + (warp >> 1) * 8192 + ((lane >> 4) * 8 + (lane & 7)) * 128, ch = (warp & 1) * 4 + ((lane >> 3) & 1);
#pragma unroll 1
            for (int ps = 0; ps < 3; ps++) {
                float d[2][4] = {};
#pragma unroll 1
                for (int bt = 0; bt < 8; bt++) {
                    slot_wait(sb + BAR_FULL, ph, sl);
#pragma unroll
                    for (int i = 0; i < 8; i++) {
                        uint32_t w[4];
                        asm volatile("ldmatrix.sync.aligned.m8n8.x4.trans.shared.b16 {%0, %1, %2, %3}, [%4];" : "=r"(w[0]), "=r"(w[1]), "=r"(w[2]), "=r"(w[3])
                                     : "r"(a + sl * SLOT + (i >> 1) * 2048 + (((ch + 2 * (i & 1)) ^ (lane & 7)) << 4)) : "memory");
                        mma16816(d[i & 1], w, sc[bt * 32 + (i >> 1) * 8 + (lane & 3)], sc[bt * 32 + (i >> 1) * 8 + 4 + (lane & 3)]);
                    }
                    __syncwarp();
                    mbar_arrive_if(sb + BAR_EMPTY + 8 * sl, lane == 0);
                    if (++sl == 6) sl = 0;
                }
                const float v = (lane & 2) ? ((lane & 1) ? d[1][2] : d[1][0]) : ((lane & 1) ? d[0][2] : d[0][0]);
                const int col = (rb - NCTA) * 256 + warp * 32 + (lane & 3) * 8 + (lane >> 2);
                if (ps == 0) st_pub(g_mod1 + col, (pack2(0.f, v) & 0xffff0000u) | (ep & 0xffffu), true);
                else g_mod[ps * 1024 + col] = __float2bfloat16_rn(v);
                if (warp == 0) TS(1 + ps);
            }
        }
        __syncthreads();
        if (tid < 2) flag_add(&g_sync.cnt[7 * 8]);
        return;
    }

    if (wg == 2) {
        asm volatile("setmaxnreg.dec.sync.aligned.u32 40;");
        if (warp == 8) {
            const uint32_t rank = j & 1, half = rank * 16384;
            uint32_t eph = 0, r = 0;
            *reinterpret_cast<volatile uint32_t*>(smem + SM_EP + 20) = 0;
#pragma unroll 1
            for (int hp = 0; hp < 2; hp++) {
                uint32_t wtab = w_table(hp), atab = a_table(hp);
                const int hc = 4 * grp + 2 * hp;
#pragma unroll 1
                for (int u = 3 - 3 * hp; u < 16; u++) {
                    if (hp && u < 4) {
                        const uint32_t ws = (wtab >> (4 * u)) & 15;
                        slot_acquire(sb, eph, ws);
                        load_tile(sb, ws, 0, tw, u * 128, hc, false, HINT & 1);
                        PT();
                    }
                    if (hp == 1 && (u & 7) == 4) mbar_wait(sb + BAR_FLAG + 24 + (u & 8), 0);
                    const uint32_t as = a_next(atab);
                    slot_acquire(sb, eph, as);
                    load_tile(sb, as, half, &tm_ckv, ((u & 12) + (j >> 1)) * 128, (u & 3) * 2 + rank, true, (HINT & 8) && hp);
                    PT();
                    if (hp == 1 && (u | 2) == 3 && lane == 0)
                        asm volatile("red.relaxed.gpu.global.add.u32 [%0], 1;" ::"l"(&g_sync.cnt[(grp * 8 + 3 + (u >> 1)) * 8]) : "memory");
                }
                const uint8_t* src = g_h + (15 - j) * 4 * SLOT;
#pragma unroll 1
                for (int u = 0; u < 8; u++) {
                    if (u == 0 || u == KVG) {
                        mbar_wait(sb + BAR_FLAG + (u ? 8 + 32 * hp : 0), 0);
                        fence_async_global();
                    }
                    if (u < 4) {
                        const uint32_t ws = (wtab >> (4 * u)) & 15;
                        slot_acquire(sb, eph, ws);
                        load_tile(sb, ws, 0, &tm_wq, u * 128, hc, false, HINT & 1);
                        PT();
                    }
                    const uint32_t as = a_next(atab);
                    slot_acquire(sb, eph, as);
                    load_bulk(sb, as, 0, src, SLOT, false, (HINT & 8) && hp);
                    PT();
                    src += u == 3 ? (8 * j - 63) * SLOT : SLOT;
                }
                const int step = hp ? -2 * SLOT : 2 * SLOT;
                src = g_KV + (size_t)(grp * 32 + 30 * hp) * SLOT + half - step;
#pragma unroll 1
                for (int n = 0; n <= 17; n++) {
                    if (n == 8) {
                        mbar_wait(sb + BAR_FLAG + 16 + 32 * hp, 0);
                        fence_async_global();
                    }
                    const uint8_t* v = src + SLOT;
                    src += n < 16 - j ? step : n == 16 - j ? (2 * j - 15) * step : -step;
                    if (n < 17) {
                        slot_acquire(sb, eph, r);
                        if (n != 15 - (j & 6)) load_bulk(sb, r, half, src, SLOT / 2, true, HINT & 4);
                        else load_bulk(sb, r, 0, src - half, SLOT, false, HINT & 4);
                        PT();
                        r = ring_next(r);
                    }
                    if (n) {
                        slot_acquire(sb, eph, r);
                        if (n != 16 - (j & 6)) load_bulk(sb, r, half, v, SLOT / 2, true, HINT & 4);
                        else load_bulk(sb, r, 0, v - half, SLOT, false, HINT & 4);
                        PT();
                        r = ring_next(r);
                    }
                    asm volatile("st.volatile.shared.u32 [%0], %1;" ::"r"(sb + SM_EP + 16), "r"(18 * hp + n + 1) : "memory");
                }
            }
            uint32_t otab = O_TABLE, ready = 0;
#pragma unroll 1
            for (int i = 0; i < 17; i++) {
                const bool dyn = i >= 8 && i < 15;
                const uint32_t want = dyn ? 15u << (4 * (i - 8)) : 1u << max(i + 14, 28);
                if (!(ready & want)) {
                    do {
                        asm volatile("ld.acquire.cta.shared.u32 %0, [%1];" : "=r"(ready) : "r"(sb + SM_EP + 20) : "memory");
                        ready = __shfl_sync(0xffffffffu, ready, 0);
                    } while (!(ready & want));
                    fence_async_global();
                }
                const int head = o_head(dyn ? (ready >> (4 * (i - 8))) & 15 : i, kh);
                const uint32_t as = o_next(otab), ws = o_next(otab), off = i < 15 ? half : kh * 16384;
                slot_acquire(sb, eph, as);
                load_bulk(sb, as, off, g_ctx + (size_t)(ort * 32 + head) * SLOT + off, SLOT / 2, i < 15, HINT & 16);
                if (i == 15) load_tile(sb, as, off ^ 16384, &tm_x, ort * 128 + kh * 64, cq * 2, false, false);
                if (i == 16) load_bulk(sb, as, off ^ 16384, P.wdown + min(rb, NFFN - 1) * 8192, SLOT / 2, false, false);
                PT();
                slot_acquire(sb, eph, ws);
                load_tile(sb, ws, 0, &tm_wo, head * 128, cq * 2, false, HINT & 2);
                PT();
                if (i == 0) o_next(otab);
            }
            if (rb < NFFN) {
                slot_acquire(sb, eph, 5);
                load_bulk(sb, 5, 0, g_wf + rb * SLOT, SLOT, false, false);
            }
        } else if (warp == 9) {
            *reinterpret_cast<volatile uint32_t*>(smem + SM_EP + 16) = 0;
            l2_prefetch(P.ckv + rb * 2048, 4096);
            mbar_watch(sb + BAR_FULL, 0);
            l2_prefetch(P.ckv + 512 * 512 + rb * 2048, 4096);
            mbar_watch(sb + BAR_FULL + 8 * XPF, 0);
            l2_prefetch(P.x + rb * 8192, 16384);
            mbar_watch(sb + BAR_FULL + 8 * 4, 0);
            l2_prefetch(P.ckv + 1024 * 512 + rb * 4096, 8192);
            TS(40);
#pragma unroll 1
            for (int i = 0; i < 15; i++) {
                step_watch(sb + SM_EP + 16, i == 0 ? 0 : i < 5 ? PFA + i : 13 + PFB + i);
                if (i == 12) mbar_watch(sb + BAR_FLAG + 8 * 7, 0);
                const int rf = min(rb, NFFN - 1);
                const uint8_t* p = i == 3 ? reinterpret_cast<const uint8_t*>(P.ckv) + rb * 16384
                                 : i == 4 ? g_h + rb * 16384
                                 : i < 9 ? g_ctx + (size_t)(ort * 32 + o_head(cq + 2 * ((i - 5) & 2), kh)) * SLOT + (i & 1) * 16384
                                 : i < 11 ? reinterpret_cast<const uint8_t*>(P.wo) + (grp * 16 + (~i & 1) * 8 + j) * 16384
                                 : i == 11 ? reinterpret_cast<const uint8_t*>(P.x) + rb * 16384
                                 : i == 12 ? reinterpret_cast<const uint8_t*>(P.wdown) + rf * 16384 : g_wf + rf * SLOT + (i & 1) * 16384;
                if (i >= 3) l2_prefetch(p, 16384);
                else if ((i | j) & 1) tma3d_prefetch(i == 1 ? tw : &tm_wq, (j >> 1) * 128, grp * 4 + (i ? 2 : 0));
            }
            const uint32_t v = lds32(sb + SM_EP) - 1;
            sts128(sb + SM_RED + lane * 16, make_uint4(v, v, v, v));
            fence_async_smem();
            __syncwarp();
#pragma unroll 1
            for (int i = 0; i < OB / 32; i++) bulk_store(g_out + rb * OB + i * 32, sb + SM_RED, 512, false);
            asm volatile("cp.async.bulk.commit_group;\ncp.async.bulk.wait_group 0;" ::: "memory");
            fence_async_global();
            __syncwarp();
            mbar_arrive_if(sb + BAR_PF, lane == 0);
            if (lane == 0) mbar_watch(sb + BAR_END, 0);
        } else {
            const uint32_t ep = __ldcg(&g_sync.epoch[0]) + 1;
            asm volatile("st.shared.u32 [%0], %1;" ::"r"(sb + SM_EP), "r"(ep) : "memory");
            mbar_wait(sb + BAR_FULL + 8 * 4, 0);
            {
                uint4 v[4];
                for (;;) {
                    uint32_t bad = 0;
#pragma unroll
                    for (int k = 0; k < 4; k++) v[k] = ld_poll(reinterpret_cast<const uint4*>(g_mod1) + (warp & 1) * 128 + k * 32 + lane);
#pragma unroll
                    for (int k = 0; k < 4; k++) bad |= (v[k].x ^ ep) | (v[k].y ^ ep) | (v[k].z ^ ep) | (v[k].w ^ ep);
                    if (__all_sync(0xffffffffu, (bad & 0xffff) == 0)) break;
                    __nanosleep(100);
                }
                const uint32_t one = (warp & 1) ? ONE2 : 0x80008000u;
#pragma unroll
                for (int k = 0; k < 4; k++)
                    *reinterpret_cast<uint2*>(smem + SM_TAB + (warp & 1) * 1024 + k * 256 + lane * 8) =
                        make_uint2(badd(__byte_perm(v[k].x, v[k].y, 0x7632), one), badd(__byte_perm(v[k].z, v[k].w, 0x7632), one));
            }
            __syncwarp();
            mbar_arrive_if(sb + BAR_FLAG + 8 * 8, lane == 0);
            if (warp == 10) {
#pragma unroll 1
                for (int i = 0; i < 9; i++) {
                    mbar_sleep(sb + BAR_DONE + 8 * i);
                    if (lane == 0) flag_add(i && ((i - 1) & 2) ? &g_sync.ctxcnt[((i & 1) ? 15 - j : j) * 32 + 2 * grp + (i > 4)] : &g_sync.cnt[(grp * 8 + i) * 8]);
                    if (i == 0) TS(43);
                }
            } else {
                TS(42);
#pragma unroll 1
                for (int i = 0; i < 8; i++) {
                    mbar_sleep(sb + BAR_DONE + 8 * (i == 7 ? 6 : i == 4 ? 3 : i));
                    if (lane < 2) flag_wait(&g_sync.cnt[((i == 0 ? (lane ? j : 15 - j) : i == 7 ? 0 : grp) * 8 + i) * 8], 8 * ep);
                    __syncwarp();
                    mbar_arrive_if(sb + BAR_FLAG + 8 * i, lane == 0 && i < 7);
                    TS(48 + i);
                }
                const uint32_t *mp = reinterpret_cast<const uint32_t*>(g_mod) + lane, *wp = reinterpret_cast<const uint32_t*>(P.wr) + lane;
                float ra = 0.f, rs = 0.f;
#pragma unroll 1
                for (int k = 0; k < 256; k += 32) {
                    const uint32_t ga = __ldcg(mp + 512 + k), sh = __ldcg(mp + 768 + k), c1 = badd(__ldcg(mp + 1024 + k), ONE2);
                    const uint32_t gb = __ldcg(mp + 1280 + k), ww = __ldg(wp + k);
                    const uint32_t a = bmul(c1, ww);
                    ra += bf_lo(a) + bf_hi(a);
                    rs = fmaf(bf_lo(sh), bf_lo(ww), fmaf(bf_hi(sh), bf_hi(ww), rs));
                    if (k >> 6 == cq) {
                        sts128(sb + SM_TAB + ((k & 32) + lane) * 16, make_uint4(ga << 16, ga & 0xffff0000u, a, 0));
                        sts128(sb + SM_TAB + 1024 + ((k & 32) + lane) * 16, make_uint4(c1, sh, gb, 0));
                    }
                }
#pragma unroll 1
                for (int o = 16; o > 0; o >>= 1) {
                    ra += __shfl_xor_sync(0xffffffffu, ra, o);
                    rs += __shfl_xor_sync(0xffffffffu, rs, o);
                }
                *reinterpret_cast<float2*>(smem + SM_EP + 8) = make_float2(ra, rs);
                __syncwarp();
                mbar_arrive_if(sb + BAR_FLAG + 8 * 7, lane == 0);
                const uint32_t* f = &g_sync.ctxcnt[ort * 32 + o_head(min(lane, 16), kh)];
                uint32_t ready = -(j & 1), list = 0, sh = 0, qa;
                asm("mapa.shared::cluster.u32 %0, %1, %2;" : "=r"(qa) : "r"(sb + SM_EP + 20), "r"(lane & 1));
                while (ready != ~0u) {
                    uint32_t v;
                    asm volatile("ld.acquire.gpu.global.u32 %0, [%1];" : "=r"(v) : "l"(f) : "memory");
                    const uint32_t now = __ballot_sync(0xffffffffu, (int)(v - ep) >= 0);
#pragma unroll 1
                    for (uint32_t fresh = now & ~ready & 0x7f00; fresh; fresh &= fresh - 1, sh += 4) list |= (__ffs(fresh) - 1) << sh;
                    list |= (((now & 0xff) + 1) >> 8 << 28) | ((now & 0x18000) << 14);
                    if (now != ready && lane < 2) asm volatile("st.relaxed.cluster.shared::cluster.u32 [%0], %1;" ::"r"(qa), "r"(list) : "memory");
                    if ((now & 0xff) == 0xff) mbar_sleep(sb + BAR_DONE + 8 * 7);
                    ready = now;
                    __nanosleep(POLL_NS);
                }
                TS(45);
            }
        }
    } else {
        const bool elected = (tid & 127) == 0, rel = (tid & 95) == 0;
        uint32_t eb;
        asm("mapa.shared::cluster.u32 %0, %1, %2;" : "=r"(eb) : "r"(sb + BAR_EMPTY), "r"(warp & 1));
        const int g = lane >> 2, c4 = lane & 3;
        uint32_t toff = warp * 4096 + g * 64 + ((c4 ^ (g >> 1)) << 4);
        uint32_t fph = 0x3f, r = 0;
        if (wg == 1) bar_arrive(1, 256);
        const uint32_t kd = desc_k(sb), wd = desc_mn(sb), vd = ((sb & 0x3ffff) >> 4) | (32u << 16);
        const int nL = 16 - j, hn = nL - 1 + wg;
        float s[64], o[64], li[2] = {0.f, 0.f};
        uint32_t cimg = 0;
        const float sc = (j & 1) ? 1.f : SM_C;
#pragma unroll 1
        for (int q = 0; q < 3; q++) {
            const uint32_t as = (0x635u >> (4 * q)) & 15;
            mbar_wait(sb + BAR_FULL + 8 * q, 0);
            mbar_wait(sb + BAR_FULL + 8 * as, 0);
            bar_sync(1 + wg, 256);
            gemm_issue<false>(s, kd + wg * 512 + as * (SLOT / 16), wd + q * (SLOT / 16), q, false);
            bar_arrive(2 - wg, 256);
            wg_wait<0>();
            release_if(eb, as, rel);
        }
        reg_fence(s);
        asm volatile("setmaxnreg.inc.sync.aligned.u32 232;");
        {
            const int xrow = rb * 16 + warp * 2;
            const uint4* xp = reinterpret_cast<const uint4*>(P.x) + xrow * 64;
            const uint32_t img = (grp * 32 + j) * SLOT;
            uint32_t x[16], x0[2];
            float st[4] = {0.f, 0.f, 0.f, 0.f};
            mbar_wait(sb + BAR_FULL + 8 * 4, 0);
#pragma unroll
            for (int q = 3; q < 8; q++) {
                const uint32_t ws = (0x4210u >> (4 * (q & 3))) & 15, as = (0x635u >> (4 * (q % 3))) & 15;
                mbar_wait(sb + BAR_FULL + 8 * as, (q / 3) & 1);
                bar_sync(1 + wg, 256);
                if (q == 3) gemm_issue<false>(s, kd + wg * 512 + as * (SLOT / 16), wd + ws * (SLOT / 16), 1, false);
                else if (q == 4) gemm_issue<true>(o, kd + wg * 512 + as * (SLOT / 16), wd + ws * (SLOT / 16), 0, false);
                else gemm_issue<false>(o, kd + wg * 512 + as * (SLOT / 16), wd + ws * (SLOT / 16), 1, false);
                bar_arrive(2 - wg, 256);
                sched_fence(fph, P.zero);
                if (q > 3) reg_fence(s);
                if (q == 3) {
#pragma unroll
                    for (int i = 0; i < 4; i++)
                        asm volatile("ld.global.nc.v4.u32 {%0, %1, %2, %3}, [%4];" : "=r"(x[4 * i]), "=r"(x[4 * i + 1]), "=r"(x[4 * i + 2]), "=r"(x[4 * i + 3])
                                     : "l"(xp + lane + 32 * i) : "memory");
#pragma unroll
                    for (int i = 0; i < 2; i++) asm volatile("ld.global.nc.u32 %0, [%1];" : "=r"(x0[i]) : "l"(xp + 64 * i) : "memory");
                }
                if (q == 4) {
                    img_store_global<0>(img, toff, s, sc, sc);
#pragma unroll
                    for (int k = 0; k < 16; k++) {
                        const float d0 = bf_lo(x[k]) - bf_lo(x0[k >> 3]), d1 = bf_hi(x[k]) - bf_lo(x0[k >> 3]);
                        st[k >> 3] += d0 + d1;
                        st[2 + (k >> 3)] = fmaf(d0, d0, fmaf(d1, d1, st[2 + (k >> 3)]));
                    }
#pragma unroll
                    for (int i = 0; i < 4 * NSH; i++) st[i & 3] += __shfl_xor_sync(0xffffffffu, st[i & 3], 1 << (i >> 2));
                    reg_fence(st);
                }
                if (q == 5) {
#pragma unroll
                    for (int i = 4 * NSH; i < 20; i++) st[i & 3] += __shfl_xor_sync(0xffffffffu, st[i & 3], 1 << (i >> 2));
                    img_store_global<1>(img, toff, s, sc, sc);
#pragma unroll
                    for (int i = 0; i < 2; i++) {
                        const float d = st[i] * (1.f / 512.f);
                        st[2 + i] = ln_rstd(fmaxf(fmaf(-d, d, st[2 + i] * (1.f / 512.f)), 0.f));
                        x0[i] = pack2(bf_lo(x0[i]) + d, bf_lo(x0[i]) + d);
                    }
                    reg_fence(st);
                    reg_fence(x0);
                }
                if (q > 5) {
                    if (q == 6) mbar_wait(sb + BAR_FLAG + 8 * 8, 0);
                    const uint4 a = lds128(sb + SM_TAB + 1024 + (q & 1) * 512 + lane * 16), c = lds128(sb + SM_TAB + (q & 1) * 512 + lane * 16);
                    uint8_t* hp = g_h + (grp * 8 + (q & 1) * 4 + (lane >> 3)) * 16384 + (xrow & 127) * 128;
#pragma unroll
                    for (int i = 0; i < 2; i++) {
                        const uint32_t* y = x + 8 * i + 4 * (q & 1);
                        *reinterpret_cast<uint4*>(hp + i * 128 + (((lane ^ xrow ^ i) & 7) << 4)) =
                            make_uint4(ln_apply(y[0], x0[i], st[2 + i], a.x, c.x), ln_apply(y[1], x0[i], st[2 + i], a.y, c.y),
                                       ln_apply(y[2], x0[i], st[2 + i], a.z, c.z), ln_apply(y[3], x0[i], st[2 + i], a.w, c.w));
                    }
                    if (q == 7) {
                        __syncwarp();
                        mbar_arrive_if(sb + BAR_DONE, lane == 0);
                    }
                    if (q == 6) img_store_global<2>(img, toff, s, sc, sc);
                    else img_store_global<3>(img, toff, s, sc, sc);
                }
                sched_fence(fph, P.zero);
                wg_wait<0>();
                release_if(eb, as, rel);
            }
            reg_fence(o);
        }
        uint32_t p[32] = {};
#pragma unroll 1
        for (int hp = 0; hp < 2; hp++) {
            float m[2] = {0.f, 0.f}, l[2] = {0.f, 0.f}, t[4] = {0.f, 0.f, 0.f, 0.f};
            bool shifted = false, bad = false, plain = false;
            uint32_t qa = desc_k(sb + 5 * SLOT + (wg ^ 1) * 8192);
            const uint32_t limg = (512 + (15 - j) * 32 + 2 * grp + hp) * SLOT;
            {
                const int step = hp ? -8 * SLOT : 8 * SLOT;
                uint32_t img = (grp * 32 + (hp ? j ^ 30 : j) + 8) * SLOT;
                const uint32_t wtab = w_table(hp);
                uint32_t atab = hp ? 0x562u : 0x356u;
#pragma unroll 1
                for (int u = 2 - 2 * hp;; u += 2) {
                    proj_tile<false>(s, o, u, !u, sb, wg, eb, rel, fph, wtab, atab, u ? img : cimg, toff, u ? sc : li[0], u ? sc : li[1], p);
                    __syncwarp();
                    mbar_arrive_if(sb + BAR_DONE + 4 * u + 32 * hp, lane == 0);
                    if (elected) TS(1 + 10 * hp + u + 20 * wg);
                    if (proj_tile<true>(o, s, u + 1, 0, sb, wg, eb, rel, fph, wtab, atab, img + step, toff, sc, sc, p)) break;
                    if (elected) TS(2 + 10 * hp + u + 20 * wg);
                    img += 2 * step;
                }
            }
            asm volatile("" : "+r"(toff));
            if (elected) TS(6 + 10 * hp + 20 * wg);
            int n = -1;
#pragma unroll 1
            for (;;) {
                while (bad || plain) {
                    float d0 = m[0], d1 = m[1];
                    if (bad) {
                        float a0, a1;
                        softmax_remax(s, m, n == 0 || n == nL, d0, d1, a0, a1);
                        shifted = true;
                        l[0] *= a0;
                        l[1] *= a1;
#pragma unroll
                        for (int i = 0; i < 64; i++) o[i] *= (i & 2) ? a1 : a0;
                    }
#pragma unroll
                    for (int i = 0; i < 64; i++) s[i] -= (i & 2) ? d1 : d0;
                    softmax_exp<0, 16>(s, p, t);
                    t[0] += t[1];
                    t[2] += t[3];
                    bad = !bad && softmax_unsafe(t[0], t[2], false);
                    plain = false;
                }
#pragma unroll 1
                do {
                    l[0] += t[0];
                    l[1] += t[2];
                    if (++n > 16) break;
                    const uint32_t ks = r;
                    uint32_t vs = ring_next(r);
                    r = ring_next(vs);
                    bar_sync(1 + wg, 256);
                    const float x = (float)((warp & 3) * 16 + g - 2 * c4);
                    if (n == hn) {
                        float sh[32];
                        qk_issue(sh, qa, kd + ks * (SLOT / 16));
                        slot_wait(sb + BAR_FULL, fph, vs);
                        pv_issue(o, p, vd + vs * (SLOT / 16), 1, false);
                        bar_arrive(2 - wg, 256);
                        wg_wait<1>();
                        reg_fence(sh);
                        tri_mask_copy(s, sh, x);
                        release_if(eb, ks, rel);
                        release_if(eb, 5 + wg, rel && (!wg || n == 16));
                        if (!wg) qa += SLOT / 16;
                        float e[4 * EARLY];
#pragma unroll
                        for (int i = 0; i < 4 * EARLY; i++) {
                            e[i] = ex2(s[i]);
                            t[i & 3] = i < 4 ? e[i] : t[i & 3] + e[i];
                        }
                        reg_fence(e);
                        slot_wait(sb + BAR_FULL, fph, r);
                        wg_wait<0>();
                        reg_fence(o);
                        reg_fence(e);
                        release_if(eb, vs, rel);
#pragma unroll
                        for (int i = 0; i < 2 * EARLY; i++) p[i] = pack2(e[2 * i], e[2 * i + 1]);
                        softmax_exp<EARLY, 8>(s, p, t);
                        if (wg) {
                            ctx_store(limg, toff, o, rcp(quad_sum(l[0])), rcp(quad_sum(l[1])));
                            __syncwarp();
                            mbar_arrive_if(sb + BAR_DONE + 24 + 32 * hp, lane == 0);
                            l[0] = l[1] = m[0] = m[1] = 0.f;
                            shifted = false;
                        }
                        t[0] += t[1];
                        t[2] += t[3];
                        plain = shifted;
                        if (plain) break;
                        bad = softmax_unsafe(t[0], t[2], wg);
                        continue;
                    }
                    if (n == nL) {
                        qk_issue(s, qa, kd + ks * (SLOT / 16));
                        slot_wait(sb + BAR_FULL, fph, vs);
                        pv_issue(o, p, vd + vs * (SLOT / 16), 1, true);
                        bar_arrive(2 - wg, 256);
                        const float i0 = rcp(quad_sum(l[0])), i1 = rcp(quad_sum(l[1]));
                        wg_wait<1>();
                        reg_fence(s);
                        release_if(eb, ks, rel);
                        release_if(eb, 6, rel && n == 16);
                        tri_mask(s, x);
                        float e[4 * EARLY2];
#pragma unroll
                        for (int i = 0; i < 4 * EARLY2; i++) {
                            e[i] = ex2(s[i]);
                            t[i & 3] = i < 4 ? e[i] : t[i & 3] + e[i];
                        }
                        reg_fence(e);
                        reg_fence(s);
                        reg_fence(t);
                        slot_wait(sb + BAR_FULL, fph, r);
                        if (SF & 1) sched_fence(fph, P.zero);
                        wg_wait<0>();
                        reg_fence(o);
                        reg_fence(e);
                        release_if(eb, vs, rel);
#pragma unroll
                        for (int i = 0; i < 2 * EARLY2; i++) p[i] = pack2(e[2 * i], e[2 * i + 1]);
                        softmax_exp<EARLY2, MSPLIT>(s, p, t);
                        ctx_store(limg, toff, o, i0, i1);
                        reg_fence(t);
                        if (SF & 2) sched_fence(fph, P.zero);
                        reg_fence(s);
                        softmax_exp<MSPLIT, 16>(s, p, t);
                        __syncwarp();
                        mbar_arrive_if(sb + BAR_DONE + 24 + 32 * hp, lane == 0);
                        l[0] = l[1] = m[0] = m[1] = 0.f;
                        shifted = false;
                        t[0] += t[1];
                        t[2] += t[3];
                        bad = __any_sync(0xffffffffu, fmaxf(t[0], t[2]) > SM_HI || fminf(t[0], t[2]) < SM_LO);
                        continue;
                    }
                    qk_issue(s, qa, kd + ks * (SLOT / 16));
                    if (n == 0) {
                        r = vs;
                        vs = 4 - hp;
                        slot_wait(sb + BAR_FULL, fph, 6);
                        gemm_issue<false>(o, qa + SLOT / 16, wd + vs * (SLOT / 16), 1, false);
                    } else {
                        slot_wait(sb + BAR_FULL, fph, vs);
                        if (n == 1) {
                            wg_wait<1>();
                            reg_fence(o);
                            const uint32_t a = sb + 6 * SLOT + q_off(toff);
#pragma unroll
                            for (int i = 0; i < 8; i++) {
                                const int k = 16 * (i >> 1) + 2 * (i & 1);
                                sts128(a + (i >> 2) * 16384 + (i & 2) * 256 + (i & 1) * 1024,
                                       make_uint4(pack2(o[k], o[k + 1]), pack2(o[k + 4], o[k + 5]), pack2(o[k + 8], o[k + 9]), pack2(o[k + 12], o[k + 13])));
                            }
                        }
                        pv_issue(o, p, vd + vs * (SLOT / 16), n != 1 && n != nL + 1, n == hn + 1);
                    }
                    bar_arrive(2 - wg, 256);
                    wg_wait<1>();
                    reg_fence(s);
                    release_if(eb, ks, rel);
                    release_if(eb, 6, rel && n == 16);
                    if (n == nL - 1) {
                        tri_mask(s, x);
                        release_if(eb, 5, rel);
                        qa += SLOT / 16;
                    }
                    if (n == 2) fence_async_smem();
                    if (shifted) {
                        slot_wait(sb + BAR_FULL, fph, r);
                        wg_wait<0>();
                        reg_fence(o);
                        release_if(eb, vs, rel);
                        plain = true;
                        break;
                    }
                    float e[4 * EARLY];
#pragma unroll
                    for (int i = 0; i < 4 * EARLY; i++) {
                        e[i] = ex2(s[i]);
                        t[i & 3] = i < 4 ? e[i] : t[i & 3] + e[i];
                    }
                    reg_fence(e);
                    slot_wait(sb + BAR_FULL, fph, r);
                    wg_wait<0>();
                    reg_fence(o);
                    reg_fence(e);
                    release_if(eb, vs, rel);
#pragma unroll
                    for (int i = 0; i < 2 * EARLY; i++) p[i] = pack2(e[2 * i], e[2 * i + 1]);
                    softmax_exp<EARLY, 16>(s, p, t);
                    t[0] += t[1];
                    t[2] += t[3];
                    bad = __any_sync(0xffffffffu, fmaxf(t[0], t[2]) > SM_HI || (n == 0 && fminf(t[0], t[2]) < SM_LO));
                } while (!bad);
                if (!bad && !plain) break;
            }
            asm volatile("" : "+r"(toff));
            const uint32_t vs = r, ga = desc_k(sb + (hp ? 2 * (wg ^ kh ^ 1) : wg) * 8192);
            r = ring_next(r);
            slot_wait(sb + BAR_FULL, fph, 5);
            slot_wait(sb + BAR_FULL, fph, r);
            bar_sync(1 + wg, 256);
            gemm_issue<true>(s, ga + 5 * (SLOT / 16), wd + r * (SLOT / 16), 0, hp);
            pv_issue(o, p, vd + vs * (SLOT / 16), j, hn == 16);
            bar_arrive(2 - wg, 256);
            li[0] = rcp(quad_sum(l[0]));
            li[1] = rcp(quad_sum(l[1]));
            cimg = limg + (2 * j - 15) * 32 * SLOT + (wg ? -16384 : 16384);
            wg_wait<1>();
            release_if(eb, 5, rel);
            release_if(eb, r, rel && hp);
            wg_wait<0>();
            release_if(eb, vs, rel);
            reg_fence(o);
            img_store_global<0>(cimg, toff, o, li[0], li[1]);
            if (elected) TS(8 + 10 * hp + 20 * wg);
        }
        uint32_t otab = 0x2351604u;
        const uint32_t oa = desc_k(sb + (wg ^ kh ^ 1) * 16384);
        const int t7 = tid & 127, w4 = warp & 3, row = ort * 128 + kh * 64 + w4 * 16 + g;
#pragma unroll 1
        for (int i = 1; i < 15 - wg; i++) {
            const uint32_t as = o_next(otab), ws = o_next(otab);
            slot_wait(sb + BAR_FULL, fph, as);
            slot_wait(sb + BAR_FULL, fph, ws);
            bar_sync(1 + wg, 256);
            gemm_issue<false>(s, oa + as * (SLOT / 16), wd + ws * (SLOT / 16), 1, true);
            bar_arrive(2 - wg, 256);
            wg_wait<1>();
            reg_fence(o);
            if (i == 1) img_store_global<1>(cimg, toff, o, li[0], li[1]);
            if (i == 2) {
                img_store_global<2>(cimg, toff, o, li[0], li[1]);
                img_store_global<3>(cimg, toff, o, li[0], li[1]);
                __syncwarp();
                mbar_arrive_if(sb + BAR_DONE + 64, lane == 0);
            }
            wg_wait<0>();
            release_if(eb, as, rel);
            release_if(eb, ws, rel);
        }
        mbar_wait(sb + BAR_PF, 0);
        const uint32_t ep = lds32(sb + SM_EP);
        uint32_t eb2 = sb + BAR_END;
        if (wg == 0) {
            reg_fence(s);
            if (elected) TS(9);
            TT(1);
#pragma unroll
            for (int v = 0; v < 8; v++)
                st_pub(g_out + rb * OB + v * 128 + t7, make_uint4((pack2(s[8 * v], s[8 * v + 1]) & ~1u) | (ep & 1), pack2(s[8 * v + 2], s[8 * v + 3]),
                                                                      pack2(s[8 * v + 4], s[8 * v + 5]), pack2(s[8 * v + 6], s[8 * v + 7])), true);
            constexpr uint32_t s1 = 5, s2 = 6;
            if (ELATE >= 0) bar_sync(4, 256);
            uint32_t wf[64];
            float wn[64];
            if (rb < NFFN) {
                slot_wait(sb + BAR_FULL, fph, s1);
                const uint32_t a = sb + s1 * SLOT + (w4 * 128 + (lane >> 4) * 8 + (lane & 7)) * 32 + (((lane >> 3) ^ (lane >> 2)) & 1) * 16;
#pragma unroll
                for (int i = 0; i < 16; i++)
                    asm volatile("ldmatrix.sync.aligned.m8n8.x4.trans.shared.b16 {%0, %1, %2, %3}, [%4];"
                                 : "=r"(wf[4 * i]), "=r"(wf[4 * i + 1]), "=r"(wf[4 * i + 2]), "=r"(wf[4 * i + 3])
                                 : "r"(a + (i >> 3) * 16384 + (i & 7) * 512) : "memory");
                slot_wait(sb + BAR_FULL, fph, s2);
#pragma unroll
                for (int i = 0; i < 16; i++) {
                    const uint2 w = *reinterpret_cast<const uint2*>(smem + s2 * SLOT + (kh ^ 1) * 16384 + i * 1024 + t7 * 8);
                    wn[4 * i] = bf_lo(w.x); wn[4 * i + 1] = bf_hi(w.x); wn[4 * i + 2] = bf_lo(w.y); wn[4 * i + 3] = bf_hi(w.y);
                }
                reg_fence(wn);
            }
            const uint32_t gbf = __ldcg(reinterpret_cast<const uint32_t*>(g_mod) + 1280 + rb * 2 + (tid & 1));
            if (elected) TS(10);
            TT(2);
            float* sred = reinterpret_cast<float*>(smem + SM_RED);
            uint32_t best = ep ^ 1, all;
            bool fresh;
            do {
                if (warp == 0) {
                    const uint2 k = best_key(g_key + cq * 128, lane, ep, best, rb < NFFN ? SPEC : 32);
                    *reinterpret_cast<uint2*>(smem + SM_EP + 24) = k;
                    mbar_arrive_if(sb + BAR_BEST, lane == 0 && k.y);
                }
                bar_sync(3, 128);
                const uint2 k = *reinterpret_cast<const uint2*>(smem + SM_EP + 24);
                fresh = k.x != best;
                best = k.x;
                all = k.y;
                TT(3);
                if (!fresh || rb >= NFFN) break;
                const uint4* cp = g_cand + ((~best >> 9) & 127) * 192;
                uint4 cv[6];
                for (;;) {
                    uint32_t bad = 0;
#pragma unroll
                    for (int v = 0; v < 6; v++) cv[v] = ld_poll(cp + w4 * 24 + v * 4 + c4);
#pragma unroll
                    for (int v = 0; v < 6; v++) bad |= cv[v].w ^ ep;
                    if (__all_sync(0xffffffffu, bad == 0)) break;
                    if (CSLEEP) __nanosleep(CSLEEP);
                }
            TT(4);
                float d[4][4] = {};
#pragma unroll
                for (int k = 0; k < 8; k++) {
                    const uint32_t b0 = (&cv[(2 * k) / 3].x)[(2 * k) % 3], b1 = (&cv[(2 * k + 1) / 3].x)[(2 * k + 1) % 3];
                    mma16816(d[k & 1], wf + 4 * k, b0, b1);
                    mma16816(d[2 + (k & 1)], wf + 32 + 4 * k, b0, b1);
                }
                const float u = (c4 & 2) ? ((c4 & 1) ? d[2][2] + d[3][2] : d[2][0] + d[3][0]) : ((c4 & 1) ? d[0][2] + d[1][2] : d[0][0] + d[1][0]);
                sred[w4 * 32 + c4 * 8 + g] = u;
                bar_sync(3, 128);
                const float v = rbf((sred[lane] + sred[32 + lane]) + (sred[64 + lane] + sred[96 + lane]));
                const float act = rbf(rbf(v * sigmoid(v)) * __shfl_down_sync(0xffffffffu, v, 16));
                float y[4] = {0.f, 0.f, 0.f, 0.f};
#pragma unroll
                for (int k = 0; k < 16; k++) {
                    const float a = __shfl_sync(0xffffffffu, act, k);
#pragma unroll
                    for (int i = 0; i < 4; i++) y[i] = fmaf(a, wn[4 * k + i], y[i]);
                }
                st_pub(g_out + rb * OB + OB_Y + t7, make_uint4((__float_as_uint(y[0]) & ~15u) | (ep & 15), (__float_as_uint(y[1]) & ~127u) | ((best >> 9) & 127),
                                                               __float_as_uint(y[2]), __float_as_uint(y[3])), true);
            } while (!all);
            const int sel = (~best >> 5) & 2047;
            const int pq = (2 * rb + (tid & 1)) & 63, pv = (pq >> 2) / 3;
            const uint4* fp = g_cand + (sel >> 4) * 192 + (rb >> 5) * 24 + pv * 4 + (pq & 3);
            uint4 fh = {}, fx = {};
            if (rb == 0 && tid == 0) g_sync.epoch[0] = ep;
            if (elected) TS(60);
            TT(5);
            uint4 yv;
            if (warp == 0) { fh = ld_poll(fp); fx = ld_poll(fp + 96); }
            if (fresh && rb < NFFN) __nanosleep(YPRE);
            for (;;) {
                yv = ld_poll(g_out + min(t7, NFFN - 1) * OB + OB_Y + rb);
                if (__all_sync(0xffffffffu, (((yv.x ^ ep) & 15) | ((yv.y ^ (best >> 9)) & 127)) == 0)) break;
                if (YSLEEP) __nanosleep(YSLEEP);
            }
            if (elected) TS(61);
            TT(6);
            float y[4] = {0.f, 0.f, 0.f, 0.f};
            if (t7 < NFFN) { y[0] = __uint_as_float(yv.x); y[1] = __uint_as_float(yv.y); y[2] = __uint_as_float(yv.z); y[3] = __uint_as_float(yv.w); }
            const float z0 = ((lane & 16) ? y[2] : y[0]) + __shfl_xor_sync(0xffffffffu, (lane & 16) ? y[0] : y[2], 16);
            const float z1 = ((lane & 16) ? y[3] : y[1]) + __shfl_xor_sync(0xffffffffu, (lane & 16) ? y[1] : y[3], 16);
            float z = ((lane & 8) ? z1 : z0) + __shfl_xor_sync(0xffffffffu, (lane & 8) ? z0 : z1, 8);
            z += __shfl_xor_sync(0xffffffffu, z, 4);
            z = quad_sum(z);
            if ((lane & 7) == 0) sred[128 + (lane >> 3) * 4 + w4] = z;
            bar_sync(3, 128);
            if (tid < 2) {
                while (fh.w != ep || fx.w != ep) { fh = ld_poll(fp); fx = ld_poll(fp + 96); }
                const float4 y0 = *reinterpret_cast<const float4*>(sred + 128 + tid * 8), y1 = *reinterpret_cast<const float4*>(sred + 132 + tid * 8);
                const int cm = (pq >> 2) - 3 * pv;
                const uint32_t h2 = cm == 0 ? fh.x : cm == 1 ? fh.y : fh.z, x2 = cm == 0 ? fx.x : cm == 1 ? fx.y : fx.z;
                const float sg = sigmoid(bf_hi((best & 0x80000000u) ? (best ^ 0x80000000u) : ~best));
                reinterpret_cast<uint32_t*>(P.out)[sel * 256 + rb * 2 + tid] =
                    badd(x2, bmul(gbf, badd(h2, bmul(pack2((y0.x + y0.y) + (y0.z + y0.w), (y1.x + y1.y) + (y1.z + y1.w)), pack2(sg, sg)))));
            }
            if (elected) TS(62);
            TT(7);
        } else {
            const float4* tf = reinterpret_cast<const float4*>(smem + SM_TAB) + c4;
            const uint32_t xa = sb + 4 * SLOT + (kh ^ 1) * 16384 + (w4 * 16 + (lane & 15)) * 128;
            uint32_t x2[32];
            bar_sync(2, 256);
#pragma unroll 1
            for (int i = 14; i < 17; i++) {
                const uint32_t as = o_next(otab), ws = o_next(otab);
                slot_wait(sb + BAR_FULL, fph, as);
                slot_wait(sb + BAR_FULL, fph, ws);
                gemm_issue<false>(s, oa + as * (SLOT / 16), wd + ws * (SLOT / 16), 1, true);
                wg_wait<1>();
            }
            const uint4* pr = g_out + (rb ^ (8 * OMAP)) * OB + t7;
            uint4 pa[8];
            if (PEARLY) {
#pragma unroll
                for (int v = 0; v < 8; v++) pa[v] = ld_poll(pr + v * 128);
            }
            if (elected) TS(29);
            TT(1);
            {
#pragma unroll
                for (int k = 0; k < 8; k++)
                    asm volatile("ldmatrix.sync.aligned.m8n8.x4.shared.b16 {%0, %1, %2, %3}, [%4];"
                                 : "=r"(x2[4 * k]), "=r"(x2[4 * k + 1]), "=r"(x2[4 * k + 2]), "=r"(x2[4 * k + 3])
                                 : "r"(xa + (k >> 2) * 8192 + (((2 * (k & 3) + (lane >> 4)) ^ (lane & 7)) << 4)) : "memory");
            }
            wg_wait<0>();
            reg_fence(s);
            if (!ELATE) bar_arrive(4, 256);
            if (elected) TS(39);
            TT(2);
            if (!PEARLY) {
#pragma unroll
                for (int v = 0; v < 8; v++) pa[v] = ld_poll(pr + v * 128);
            }
            float4 tc[16];
#pragma unroll
            for (int k = 0; k < 16; k++) {
                tc[k] = tf[k * 4];
                if (!(g & 1)) tc[k].z = __uint_as_float(ONE2);
#pragma unroll
                for (int i = 4 * k; i < 4 * k + 4; i++) s[i] = fmaf((i & 1) ? tc[k].y : tc[k].x, s[i], (i & 1) ? bf_hi(x2[i >> 1]) : bf_lo(x2[i >> 1]));
            }
            reg_fence(s);
            if (TF & 2) sched_fence(eb2, P.zero);
            for (;;) {
                uint32_t bad = 0;
#pragma unroll
                for (int v = 0; v < 8; v++) asm("lop3.b32 %0, %0, %1, %2, 0xf6;" : "+r"(bad) : "r"(pa[v].x), "r"(ep));
                if (__all_sync(0xffffffffu, (bad & 1) == 0)) break;
                if (PSLEEP) __nanosleep(PSLEEP);
#pragma unroll
                for (int v = 0; v < 8; v++) pa[v] = ld_poll(pr + v * 128);
            }
            if (ELATE == 1) bar_arrive(4, 256);
            if (elected) TS(30);
            TT(3);
            float sd[4] = {}, q0[4] = {}, q1[4] = {};
#pragma unroll
            for (int k = 0; k < 8; k++) {
#pragma unroll
                for (int i = 4 * k; i < 4 * k + 4; i++) {
                    const uint32_t w = (&pa[k].x)[i & 3];
                    x2[i] = pack2(fmaf(tc[i >> 1].x, bf_lo(w), s[2 * i]), fmaf(tc[i >> 1].y, bf_hi(w), s[2 * i + 1]));
                }
                mma16816(sd, x2 + 4 * k, __float_as_uint(tc[2 * k].z), __float_as_uint(tc[2 * k + 1].z));
                mma16816(q0, x2 + 4 * k, x2[4 * k], x2[4 * k + 2]);
                mma16816(q1, x2 + 4 * k, x2[4 * k + 1], x2[4 * k + 3]);
            }
            uint4* sp = g_out + rb * OB + OB_STAT + (w4 * 8 + g) * 2;
            st_pub(sp, make_uint4(__float_as_uint(sd[0]), __float_as_uint((g & 1) ? q0[1] : q0[0]), __float_as_uint(sd[1]), ep), c4 == g >> 1);
            st_pub(sp + 1, make_uint4(__float_as_uint(sd[2]), __float_as_uint((g & 1) ? q1[3] : q1[2]), __float_as_uint(sd[3]), ep), c4 == g >> 1);
            if (ELATE == 2) bar_arrive(4, 256);
            if (TF & 1) sched_fence(eb2, P.zero);
            if (elected) TS(56);
            TT(4);
            uint32_t cb[16], sh[16], gb[16];
#pragma unroll
            for (int i = 0; i < 16; i++) {
                const float4 c = tf[64 + i * 4];
                cb[i] = __float_as_uint(c.x); sh[i] = __float_as_uint(c.y); gb[i] = __float_as_uint(c.z);
            }
            const float ra = __uint_as_float(lds32(sb + SM_EP + 8)), rb0 = __uint_as_float(lds32(sb + SM_EP + 12));
            uint4 r0, r1;
            if (SPRE) __nanosleep(SPRE);
            for (;;) {
                r0 = ld_poll(g_out + ((rb & ~(16 * OMAP + 1)) + (c4 & 1) + (c4 & 2) * 8 * OMAP) * OB + OB_STAT + (w4 * 8 + g) * 2);
                r1 = ld_poll(g_out + ((rb & ~(16 * OMAP + 1)) + (c4 & 1) + (c4 & 2) * 8 * OMAP) * OB + OB_STAT + (w4 * 8 + g) * 2 + 1);
                if (__all_sync(0xffffffffu, r0.w == ep && r1.w == ep)) break;
                if (SSLEEP) __nanosleep(SSLEEP);
            }
            if (elected) TS(57);
            TT(5);
            const float m0 = quad_sum(__uint_as_float(r0.x)) * (1.f / 512.f), m1 = quad_sum(__uint_as_float(r1.x)) * (1.f / 512.f);
            const float rs0 = ln_rstd(fmaxf(fmaf(-m0, m0, quad_sum(__uint_as_float(r0.y)) * (1.f / 512.f)), 0.f));
            const float rs1 = ln_rstd(fmaxf(fmaf(-m1, m1, quad_sum(__uint_as_float(r1.y)) * (1.f / 512.f)), 0.f));
            const uint32_t mb0 = pack2(m0, m0), mb1 = pack2(m1, m1);
            const uint32_t lg = pack2(fmaf(rs0, fmaf(-bf_lo(mb0), ra, quad_sum(__uint_as_float(r0.z))), rb0),
                                      fmaf(rs1, fmaf(-bf_lo(mb1), ra, quad_sum(__uint_as_float(r1.z))), rb0));
            const uint32_t u0 = lg << 16, u1 = lg & 0xffff0000u;
            const uint32_t k0 = ((u0 ^ (((int)u0 >> 31) | 0x80000000u)) & 0xffff0000u) | ((2047 - row) << 5) | (ep & 31);
            const uint32_t k1 = ((u1 ^ (((int)u1 >> 31) | 0x80000000u)) & 0xffff0000u) | ((2039 - row) << 5) | (ep & 31);
            const uint32_t kb = __reduce_max_sync(0xffffffffu, max(k0, k1));
            st_pub(g_key + cq * 128 + (row >> 4), kb, lane == 0);
            const bool cand = kb == k0 || kb == k1;
            uint4* cp = g_cand + (row >> 4) * 192 + cq * 24 + c4;
#pragma unroll 1
            for (int it = 0; it < 3; it++) {
                bool put = it == 1 || !cand;
                if (it == 2) {
                    mbar_wait(sb + BAR_BEST, 0);
                    put = cand && lds32(sb + SM_EP + 24) != kb;
                }
                const bool hi = (kb == k1) != (it == 1);
                uint32_t cx[18], ch[18];
#pragma unroll
                for (int i = 0; i < 16; i++) {
                    cx[i] = hi ? x2[2 * i + 1] : x2[2 * i];
                    ch[i] = ln_apply(cx[i], hi ? mb1 : mb0, hi ? rs1 : rs0, cb[i], sh[i]);
                }
                cx[16] = cx[17] = ch[16] = ch[17] = 0;
#pragma unroll
                for (int v = 0; v < 6; v++) st_pub(cp + v * 4, make_uint4(ch[3 * v], ch[3 * v + 1], ch[3 * v + 2], ep), cand && it == 0);
#pragma unroll
                for (int v = 0; v < 6; v++) st_pub(cp + 96 + v * 4, make_uint4(cx[3 * v], cx[3 * v + 1], cx[3 * v + 2], ep), cand && it == 0);
                if (it == 0) TT(6);
                uint2* op = reinterpret_cast<uint2*>(P.out) + (row + 8 * hi) * 128 + cq * 32 + (c4 & 1) * 2 + (c4 >> 1);
#pragma unroll
                for (int i = 0; i < 16; i += 2) {
                    const uint32_t v0 = badd(cx[i], bmul(gb[i], ch[i])), v1 = badd(cx[i + 1], bmul(gb[i + 1], ch[i + 1]));
                    const uint32_t rv = __shfl_xor_sync(0xffffffffu, (c4 & 1) ? v0 : v1, 1);
                    if (put) op[i * 2] = (c4 & 1) ? make_uint2(rv, v1) : make_uint2(v0, rv);
                }
            }
            if (elected) TS(59);
            TT(7);
        }
        mbar_arrive_if(eb2, lane == 0);
    }
}

typedef CUresult (*EncodeFn)(CUtensorMap*, CUtensorMapDataType, cuuint32_t, void*, const cuuint64_t*, const cuuint64_t*,
                             const cuuint32_t*, const cuuint32_t*, CUtensorMapInterleave, CUtensorMapSwizzle,
                             CUtensorMapL2promotion, CUtensorMapFloatOOBfill);

void make_2d(EncodeFn fn, CUtensorMap* m, const void* p, uint64_t cols, uint64_t rows, uint32_t bc, uint32_t br, CUtensorMapSwizzle sw) {
    cuuint64_t dims[2] = {cols, rows}, strides[1] = {cols * 2};
    cuuint32_t box[2] = {bc, br}, es[2] = {1, 1};
    fn(m, CU_TENSOR_MAP_DATA_TYPE_BFLOAT16, 2, const_cast<void*>(p), dims, strides, box, es, CU_TENSOR_MAP_INTERLEAVE_NONE,
       sw, CU_TENSOR_MAP_L2_PROMOTION_L2_128B, CU_TENSOR_MAP_FLOAT_OOB_FILL_NONE);
}
void make_3d(EncodeFn fn, CUtensorMap* m, const void* p, uint64_t cols, uint64_t rows, uint32_t br = 128, uint32_t nb = 2) {
    cuuint64_t dims[3] = {64, rows, cols / 64}, strides[2] = {cols * 2, 128};
    cuuint32_t box[3] = {64, br, nb}, es[3] = {1, 1, 1};
    fn(m, CU_TENSOR_MAP_DATA_TYPE_BFLOAT16, 3, const_cast<void*>(p), dims, strides, box, es, CU_TENSOR_MAP_INTERLEAVE_NONE,
       CU_TENSOR_MAP_SWIZZLE_128B, CU_TENSOR_MAP_L2_PROMOTION_L2_256B, CU_TENSOR_MAP_FLOAT_OOB_FILL_NONE);
}

}

extern "C" void kernel_launch(void* const* d_in, const int* in_sizes, int n_in, void* d_out, int out_size) {
    static EncodeFn fn = nullptr;
    if (!fn) {
        void* f = nullptr;
        cudaDriverEntryPointQueryResult st;
        cudaGetDriverEntryPoint("cuTensorMapEncodeTiled", &f, cudaEnableDefault, &st);
        fn = (EncodeFn)f;
        cudaFuncSetAttribute(fused_kernel, cudaFuncAttributeMaxDynamicSharedMemorySize, SMEM_BYTES);
    }
    CUtensorMap ckv, wq, wuk, wuv, wo, wg, wu, wm, xm;
    make_3d(fn, &ckv, d_in[1], 512, 2048, 128, 1);
    make_3d(fn, &xm, d_in[0], 512, 2048, 64);
    make_3d(fn, &wq, d_in[2], 4096, 512);
    make_3d(fn, &wuk, d_in[3], 4096, 512);
    make_3d(fn, &wuv, d_in[4], 4096, 512);
    make_3d(fn, &wo, d_in[5], 512, 4096);
    make_2d(fn, &wg, d_in[8], 1792, 512, 16, 256, CU_TENSOR_MAP_SWIZZLE_32B);
    make_2d(fn, &wu, d_in[9], 1792, 512, 16, 256, CU_TENSOR_MAP_SWIZZLE_32B);
    make_3d(fn, &wm, d_in[12], 3072, 512, 64, 4);
    Params p;
    p.x = (const bf16*)d_in[0];
    p.ckv = (const bf16*)d_in[1];
    p.wo = (const bf16*)d_in[5];
    p.wr = (const bf16*)d_in[7];
    p.wdown = (const bf16*)d_in[10];
    p.c = (const bf16*)d_in[11];
    p.out = (bf16*)d_out;
    p.zero = 0;
    fused_kernel<<<NCTA + NSPARE, 384, SMEM_BYTES>>>(ckv, wq, wuk, wuv, wo, wg, wu, wm, xm, p);
}
```

```cpp
#include <cuda.h>
#include <cuda_bf16.h>
#include <cuda_runtime.h>
#include <stdint.h>
#include <stdio.h>

namespace {

typedef __nv_bfloat16 bf16;
typedef unsigned long long u64;

constexpr int NCTA = 128, NSPARE = 4;
constexpr int SLOT = 32768;
constexpr int SM_BAR = 7 * SLOT;
constexpr int BAR_FULL = SM_BAR;
constexpr int BAR_EMPTY = BAR_FULL + 8 * 7;
constexpr int BAR_DONE = BAR_EMPTY + 8 * 7;
constexpr int BAR_FLAG = BAR_DONE + 8 * 9;
constexpr int BAR_PF = BAR_FLAG + 8 * 9;
constexpr int BAR_END = BAR_PF + 8;
constexpr int BAR_BEST = BAR_END + 8;
constexpr int SM_EP = BAR_END + 40;
constexpr int SM_RED = SM_BAR + 384;
constexpr int SM_TAB = SM_BAR + 1024;
constexpr int SMEM_BYTES = SM_BAR + 3072;
constexpr int NFFN = 112;
#define HINT 479
constexpr u64 L2_NORMAL = 0x1000000000000000ull, L2_FIRST = 0x12F0000000000000ull;
#define PFA 8
#define PFB 6
#define POLL_NS 50
#define MSPLIT 13
#define SF 1
#define NSH 1
#define XPF 1
#define TF 3
#define KSLEEP 200
#define YSLEEP 50
#define YPRE 150
#define SSLEEP 50
#define SPRE 0
#define PSLEEP 100
#define CSLEEP 0
#define SPEC 28
#define OMAP 2
#define KVG 7
#define PEARLY 0
#define ELATE 0
#define EARLY2 4
#define EARLY 7
constexpr uint32_t SPIN_LIMIT = 1u << 22;
constexpr uint32_t ONE2 = 0x3f803f80u;

struct Sync {
    uint32_t cnt[16 * 8 * 8];
    uint32_t ctxcnt[16 * 32];
    uint32_t epoch[32];
};

__device__ __align__(1024) uint8_t g_img[2 * 512 * SLOT];
#define g_KV g_img
#define g_ctx (g_img + 512 * SLOT)
__device__ __align__(1024) uint8_t g_h[16 * 4 * SLOT];
constexpr int OB = 1216, OB_STAT = 1024, OB_Y = 1088;
__device__ __align__(1024) uint4 g_out[128 * OB];
__device__ __align__(1024) bf16 g_mod[3072];
__device__ __align__(1024) uint32_t g_mod1[1024];
__device__ __align__(1024) uint4 g_cand[128 * 192];
__device__ __align__(1024) uint32_t g_key[4 * 128];
__device__ __align__(1024) uint8_t g_wf[NFFN * SLOT];
__device__ __align__(1024) Sync g_sync;
#define TS(i)

#define TT(i)
#define PT()

struct Params {
    const bf16 *x, *ckv, *wo, *wr, *wdown, *c;
    bf16* out;
    int zero;
};

__device__ __forceinline__ void mbar_init(uint32_t bar, uint32_t cnt) {
    asm volatile("mbarrier.init.shared::cta.b64 [%0], %1;" ::"r"(bar), "r"(cnt) : "memory");
}
__device__ __forceinline__ void mbar_wait(uint32_t bar, uint32_t parity) {
    asm volatile("{\n.reg .pred p;\nL_%=:\nmbarrier.try_wait.parity.shared::cta.b64 p, [%0], %1;\n@!p bra L_%=;\n}" ::"r"(bar), "r"(parity) : "memory");
}
__device__ __forceinline__ void mbar_sleep(uint32_t bar) {
    if ((threadIdx.x & 31) == 0)
        asm volatile("{\n.reg .pred p;\nL_%=:\nmbarrier.try_wait.parity.shared::cta.b64 p, [%0], 0, 100000;\n@!p bra L_%=;\n}" ::"r"(bar) : "memory");
    __syncwarp();
}
__device__ __forceinline__ void mbar_watch(uint32_t bar, uint32_t parity) {
    asm volatile("{\n.reg .pred p;\n.reg .u32 n;\nmov.u32 n, 0;\n"
                 "L_%=:\nmbarrier.try_wait.parity.shared::cta.b64 p, [%0], %1;\n@p bra D_%=;\n"
                 "add.u32 n, n, 1;\nsetp.lt.u32 p, n, %2;\n@p bra L_%=;\ntrap;\nD_%=:\n}"
                 ::"r"(bar), "r"(parity), "n"(SPIN_LIMIT) : "memory");
}
__device__ __forceinline__ void step_watch(uint32_t a, uint32_t step) {
    asm volatile("{\n.reg .pred p;\n.reg .u32 n, v;\nmov.u32 n, 0;\n"
                 "L_%=:\nld.volatile.shared.u32 v, [%0];\nsetp.ge.u32 p, v, %1;\n@p bra D_%=;\nnanosleep.u32 400;\n"
                 "add.u32 n, n, 1;\nsetp.lt.u32 p, n, %2;\n@p bra L_%=;\ntrap;\nD_%=:\n}"
                 ::"r"(a), "r"(step), "n"(SPIN_LIMIT) : "memory");
}
__device__ __forceinline__ void mbar_arrive_if(uint32_t bar, bool on) {
    asm volatile("{\n.reg .pred p;\nsetp.ne.s32 p, %1, 0;\n@p mbarrier.arrive.shared::cta.b64 _, [%0];\n}" ::"r"(bar), "r"((int)on) : "memory");
}
__device__ __forceinline__ void tma2d(uint32_t dst, const CUtensorMap* m, int c0, int c1, uint32_t bar, bool first) {
    asm volatile("{\n.reg .pred p;\nelect.sync _|p, 0xffffffff;\n"
                 "@p cp.async.bulk.tensor.2d.shared::cluster.global.mbarrier::complete_tx::bytes.L2::cache_hint [%0], [%1, {%3, %4}], [%2], %5;\n}"
                 ::"r"(dst), "l"(m), "r"(bar), "r"(c0), "r"(c1), "l"(first ? L2_FIRST : L2_NORMAL) : "memory");
}
__device__ __forceinline__ void tma3d_prefetch(const CUtensorMap* m, int row, int cb) {
    asm volatile("{\n.reg .pred p;\nelect.sync _|p, 0xffffffff;\n@p cp.async.bulk.prefetch.tensor.3d.L2.global [%0, {%1, %2, %3}];\n}"
                 ::"l"(m), "r"(0), "r"(row), "r"(cb) : "memory");
}
__device__ __forceinline__ void l2_prefetch(const void* p, uint32_t bytes) {
    asm volatile("{\n.reg .pred p;\nelect.sync _|p, 0xffffffff;\n@p cp.async.bulk.prefetch.L2.global [%0], %1;\n}" ::"l"(p), "r"(bytes) : "memory");
}
__device__ __forceinline__ void bulk_store(void* dst, uint32_t src, uint32_t bytes, bool first) {
    asm volatile("{\n.reg .pred p;\nelect.sync _|p, 0xffffffff;\n@p cp.async.bulk.global.shared::cta.bulk_group.L2::cache_hint [%0], [%1], %2, %3;\n}"
                 ::"l"(dst), "r"(src), "r"(bytes), "l"(first ? L2_FIRST : L2_NORMAL) : "memory");
}
__device__ __forceinline__ void flag_wait(const uint32_t* f, uint32_t target) {
    asm volatile("{\n.reg .pred p;\n.reg .u32 v;\n"
                 "L_%=:\nld.acquire.gpu.global.u32 v, [%0];\nsub.u32 v, v, %1;\nsetp.lt.s32 p, v, 0;\n@p nanosleep.u32 100;\n@p bra L_%=;\n}"
                 ::"l"(f), "r"(target) : "memory");
}
__device__ __forceinline__ uint4 ld_poll(const uint4* p) {
    uint4 v;
    asm volatile("{\n.reg .b128 t;\nld.relaxed.gpu.global.b128 t, [%4];\nmov.b128 {%0, %1, %2, %3}, t;\n}"
                 : "=r"(v.x), "=r"(v.y), "=r"(v.z), "=r"(v.w) : "l"(p) : "memory");
    return v;
}
__device__ __forceinline__ void st_pub(uint4* p, uint4 v, bool on) {
    asm volatile("{\n.reg .pred p;\n.reg .b128 t;\nsetp.ne.s32 p, %5, 0;\nmov.b128 t, {%1, %2, %3, %4};\n@p st.relaxed.gpu.global.b128 [%0], t;\n}"
                 ::"l"(p), "r"(v.x), "r"(v.y), "r"(v.z), "r"(v.w), "r"((int)on) : "memory");
}
__device__ __forceinline__ void st_pub(uint32_t* p, uint32_t v, bool on) {
    asm volatile("{\n.reg .pred p;\nsetp.ne.s32 p, %2, 0;\n@p st.relaxed.gpu.global.u32 [%0], %1;\n}" ::"l"(p), "r"(v), "r"((int)on) : "memory");
}
__device__ __forceinline__ void flag_add(uint32_t* p) {
    asm volatile("red.release.gpu.global.add.u32 [%0], 1;" ::"l"(p) : "memory");
}
__device__ __forceinline__ uint32_t lds32(uint32_t a) {
    uint32_t v;
    asm volatile("ld.shared.u32 %0, [%1];" : "=r"(v) : "r"(a) : "memory");
    return v;
}
__device__ __forceinline__ uint4 lds128(uint32_t a) {
    uint4 v;
    asm volatile("ld.shared.v4.u32 {%0, %1, %2, %3}, [%4];" : "=r"(v.x), "=r"(v.y), "=r"(v.z), "=r"(v.w) : "r"(a) : "memory");
    return v;
}
__device__ __forceinline__ void sched_fence(uint32_t& v, uint32_t z) {
    uint32_t ck;
    asm volatile("mov.u32 %0, %%clock;" : "=r"(ck)::"memory");
    v ^= ck & z;
}
__device__ __forceinline__ void fence_async_global() { asm volatile("fence.proxy.async.global;" ::: "memory"); }
__device__ __forceinline__ void fence_async_smem() { asm volatile("fence.proxy.async.shared::cta;" ::: "memory"); }
__device__ __forceinline__ void bar_sync(int id, int n) { asm volatile("bar.sync %0, %1;" ::"r"(id), "r"(n) : "memory"); }
__device__ __forceinline__ void bar_arrive(int id, int n) { asm volatile("bar.arrive %0, %1;" ::"r"(id), "r"(n) : "memory"); }
__device__ __forceinline__ void wg_fence() { asm volatile("wgmma.fence.sync.aligned;" ::: "memory"); }
__device__ __forceinline__ void wg_commit() { asm volatile("wgmma.commit_group.sync.aligned;" ::: "memory"); }
template <int N> __device__ __forceinline__ void wg_wait() { asm volatile("wgmma.wait_group.sync.aligned %0;" ::"n"(N) : "memory"); }
template <int N> __device__ __forceinline__ void reg_fence(float (&d)[N]) {
#pragma unroll
    for (int i = 0; i < N; i++) asm volatile("" : "+f"(d[i])::"memory");
}
template <int N> __device__ __forceinline__ void reg_fence(uint32_t (&d)[N]) {
#pragma unroll
    for (int i = 0; i < N; i++) asm volatile("" : "+r"(d[i])::"memory");
}
__device__ __forceinline__ uint32_t desc_k(uint32_t a) { return ((a & 0x3ffff) >> 4) | (1u << 16); }
__device__ __forceinline__ uint32_t desc_mn(uint32_t a) { return ((a & 0x3ffff) >> 4) | (1024u << 16); }

__device__ __forceinline__ uint64_t desc64(uint32_t lo, uint32_t hi) {
    uint64_t d;
    asm("mov.b64 %0, {%1, %2};" : "=l"(d) : "r"(lo), "r"(hi));
    return d;
}
__device__ __forceinline__ void desc_add(uint64_t& d, uint32_t x) { asm("add.u64 %0, %0, %1;" : "+l"(d) : "l"((uint64_t)x)); }

template <int TB>
__device__ __forceinline__ void wgmma_ss128(float (&d)[64], uint64_t da, uint64_t db, int acc) {
    asm volatile("{\n.reg .pred p;\nsetp.ne.b32 p, %66, 0;\n"
        "wgmma.mma_async.sync.aligned.m64n128k16.f32.bf16.bf16 {%0, %1, %2, %3, %4, %5, %6, %7, %8, %9, %10, %11, %12, %13, %14, %15, %16, %17, %18, %19, %20, %21, %22, %23, %24, %25, %26, %27, %28, %29, %30, %31, %32, %33, %34, %35, %36, %37, %38, %39, %40, %41, %42, %43, %44, %45, %46, %47, %48, %49, %50, %51, %52, %53, %54, %55, %56, %57, %58, %59, %60, %61, %62, %63}, %64, %65, p, 1, 1, 0, %67;\n}"
        : "+f"(d[0]), "+f"(d[1]), "+f"(d[2]), "+f"(d[3]), "+f"(d[4]), "+f"(d[5]), "+f"(d[6]), "+f"(d[7]), "+f"(d[8]), "+f"(d[9]), "+f"(d[10]), "+f"(d[11]), "+f"(d[12]), "+f"(d[13]), "+f"(d[14]), "+f"(d[15]), "+f"(d[16]), "+f"(d[17]), "+f"(d[18]), "+f"(d[19]), "+f"(d[20]), "+f"(d[21]), "+f"(d[22]), "+f"(d[23]), "+f"(d[24]), "+f"(d[25]), "+f"(d[26]), "+f"(d[27]), "+f"(d[28]), "+f"(d[29]), "+f"(d[30]), "+f"(d[31]), "+f"(d[32]), "+f"(d[33]), "+f"(d[34]), "+f"(d[35]), "+f"(d[36]), "+f"(d[37]), "+f"(d[38]), "+f"(d[39]), "+f"(d[40]), "+f"(d[41]), "+f"(d[42]), "+f"(d[43]), "+f"(d[44]), "+f"(d[45]), "+f"(d[46]), "+f"(d[47]), "+f"(d[48]), "+f"(d[49]), "+f"(d[50]), "+f"(d[51]), "+f"(d[52]), "+f"(d[53]), "+f"(d[54]), "+f"(d[55]), "+f"(d[56]), "+f"(d[57]), "+f"(d[58]), "+f"(d[59]), "+f"(d[60]), "+f"(d[61]), "+f"(d[62]), "+f"(d[63])
        : "l"(da), "l"(db), "r"(acc), "n"(TB));
}
template <int TB>
__device__ __forceinline__ void wgmma_ss128_init(float (&d)[64], uint64_t da, uint64_t db) {
    asm volatile("{\n.reg .pred p;\nsetp.ne.b32 p, 0, 0;\n"
        "wgmma.mma_async.sync.aligned.m64n128k16.f32.bf16.bf16 {%0, %1, %2, %3, %4, %5, %6, %7, %8, %9, %10, %11, %12, %13, %14, %15, %16, %17, %18, %19, %20, %21, %22, %23, %24, %25, %26, %27, %28, %29, %30, %31, %32, %33, %34, %35, %36, %37, %38, %39, %40, %41, %42, %43, %44, %45, %46, %47, %48, %49, %50, %51, %52, %53, %54, %55, %56, %57, %58, %59, %60, %61, %62, %63}, %64, %65, p, 1, 1, 0, %66;\n}"
        : "=f"(d[0]), "=f"(d[1]), "=f"(d[2]), "=f"(d[3]), "=f"(d[4]), "=f"(d[5]), "=f"(d[6]), "=f"(d[7]), "=f"(d[8]), "=f"(d[9]), "=f"(d[10]), "=f"(d[11]), "=f"(d[12]), "=f"(d[13]), "=f"(d[14]), "=f"(d[15]), "=f"(d[16]), "=f"(d[17]), "=f"(d[18]), "=f"(d[19]), "=f"(d[20]), "=f"(d[21]), "=f"(d[22]), "=f"(d[23]), "=f"(d[24]), "=f"(d[25]), "=f"(d[26]), "=f"(d[27]), "=f"(d[28]), "=f"(d[29]), "=f"(d[30]), "=f"(d[31]), "=f"(d[32]), "=f"(d[33]), "=f"(d[34]), "=f"(d[35]), "=f"(d[36]), "=f"(d[37]), "=f"(d[38]), "=f"(d[39]), "=f"(d[40]), "=f"(d[41]), "=f"(d[42]), "=f"(d[43]), "=f"(d[44]), "=f"(d[45]), "=f"(d[46]), "=f"(d[47]), "=f"(d[48]), "=f"(d[49]), "=f"(d[50]), "=f"(d[51]), "=f"(d[52]), "=f"(d[53]), "=f"(d[54]), "=f"(d[55]), "=f"(d[56]), "=f"(d[57]), "=f"(d[58]), "=f"(d[59]), "=f"(d[60]), "=f"(d[61]), "=f"(d[62]), "=f"(d[63])
        : "l"(da), "l"(db), "n"(TB));
}
template <int TB>
__device__ __forceinline__ void wgmma_ss64(float (&d)[32], uint64_t da, uint64_t db, int acc) {
    asm volatile("{\n.reg .pred p;\nsetp.ne.b32 p, %34, 0;\n"
        "wgmma.mma_async.sync.aligned.m64n64k16.f32.bf16.bf16 {%0, %1, %2, %3, %4, %5, %6, %7, %8, %9, %10, %11, %12, %13, %14, %15, %16, %17, %18, %19, %20, %21, %22, %23, %24, %25, %26, %27, %28, %29, %30, %31}, %32, %33, p, 1, 1, 0, %35;\n}"
        : "+f"(d[0]), "+f"(d[1]), "+f"(d[2]), "+f"(d[3]), "+f"(d[4]), "+f"(d[5]), "+f"(d[6]), "+f"(d[7]), "+f"(d[8]), "+f"(d[9]), "+f"(d[10]), "+f"(d[11]), "+f"(d[12]), "+f"(d[13]), "+f"(d[14]), "+f"(d[15]), "+f"(d[16]), "+f"(d[17]), "+f"(d[18]), "+f"(d[19]), "+f"(d[20]), "+f"(d[21]), "+f"(d[22]), "+f"(d[23]), "+f"(d[24]), "+f"(d[25]), "+f"(d[26]), "+f"(d[27]), "+f"(d[28]), "+f"(d[29]), "+f"(d[30]), "+f"(d[31])
        : "l"(da), "l"(db), "r"(acc), "n"(TB));
}
template <int TB>
__device__ __forceinline__ void wgmma_ss64_init(float (&d)[32], uint64_t da, uint64_t db) {
    asm volatile("{\n.reg .pred p;\nsetp.ne.b32 p, 0, 0;\n"
        "wgmma.mma_async.sync.aligned.m64n64k16.f32.bf16.bf16 {%0, %1, %2, %3, %4, %5, %6, %7, %8, %9, %10, %11, %12, %13, %14, %15, %16, %17, %18, %19, %20, %21, %22, %23, %24, %25, %26, %27, %28, %29, %30, %31}, %32, %33, p, 1, 1, 0, %34;\n}"
        : "=f"(d[0]), "=f"(d[1]), "=f"(d[2]), "=f"(d[3]), "=f"(d[4]), "=f"(d[5]), "=f"(d[6]), "=f"(d[7]), "=f"(d[8]), "=f"(d[9]), "=f"(d[10]), "=f"(d[11]), "=f"(d[12]), "=f"(d[13]), "=f"(d[14]), "=f"(d[15]), "=f"(d[16]), "=f"(d[17]), "=f"(d[18]), "=f"(d[19]), "=f"(d[20]), "=f"(d[21]), "=f"(d[22]), "=f"(d[23]), "=f"(d[24]), "=f"(d[25]), "=f"(d[26]), "=f"(d[27]), "=f"(d[28]), "=f"(d[29]), "=f"(d[30]), "=f"(d[31])
        : "l"(da), "l"(db), "n"(TB));
}
__device__ __forceinline__ void wgmma_rs128(float (&d)[64], uint32_t a0, uint32_t a1, uint32_t a2, uint32_t a3, uint64_t db, int acc) {
    asm volatile("{\n.reg .pred p;\nsetp.ne.b32 p, %69, 0;\n"
        "wgmma.mma_async.sync.aligned.m64n128k16.f32.bf16.bf16 {%0, %1, %2, %3, %4, %5, %6, %7, %8, %9, %10, %11, %12, %13, %14, %15, %16, %17, %18, %19, %20, %21, %22, %23, %24, %25, %26, %27, %28, %29, %30, %31, %32, %33, %34, %35, %36, %37, %38, %39, %40, %41, %42, %43, %44, %45, %46, %47, %48, %49, %50, %51, %52, %53, %54, %55, %56, %57, %58, %59, %60, %61, %62, %63}, {%64, %65, %66, %67}, %68, p, 1, 1, 1;\n}"
        : "+f"(d[0]), "+f"(d[1]), "+f"(d[2]), "+f"(d[3]), "+f"(d[4]), "+f"(d[5]), "+f"(d[6]), "+f"(d[7]), "+f"(d[8]), "+f"(d[9]), "+f"(d[10]), "+f"(d[11]), "+f"(d[12]), "+f"(d[13]), "+f"(d[14]), "+f"(d[15]), "+f"(d[16]), "+f"(d[17]), "+f"(d[18]), "+f"(d[19]), "+f"(d[20]), "+f"(d[21]), "+f"(d[22]), "+f"(d[23]), "+f"(d[24]), "+f"(d[25]), "+f"(d[26]), "+f"(d[27]), "+f"(d[28]), "+f"(d[29]), "+f"(d[30]), "+f"(d[31]), "+f"(d[32]), "+f"(d[33]), "+f"(d[34]), "+f"(d[35]), "+f"(d[36]), "+f"(d[37]), "+f"(d[38]), "+f"(d[39]), "+f"(d[40]), "+f"(d[41]), "+f"(d[42]), "+f"(d[43]), "+f"(d[44]), "+f"(d[45]), "+f"(d[46]), "+f"(d[47]), "+f"(d[48]), "+f"(d[49]), "+f"(d[50]), "+f"(d[51]), "+f"(d[52]), "+f"(d[53]), "+f"(d[54]), "+f"(d[55]), "+f"(d[56]), "+f"(d[57]), "+f"(d[58]), "+f"(d[59]), "+f"(d[60]), "+f"(d[61]), "+f"(d[62]), "+f"(d[63])
        : "r"(a0), "r"(a1), "r"(a2), "r"(a3), "l"(db), "r"(acc));
}

__device__ __forceinline__ uint32_t pack2(float lo, float hi) {
    uint32_t r;
    asm("cvt.rn.bf16x2.f32 %0, %1, %2;" : "=r"(r) : "f"(hi), "f"(lo));
    return r;
}
__device__ __forceinline__ float bf_lo(uint32_t v) { return __uint_as_float(v << 16); }
__device__ __forceinline__ float bf_hi(uint32_t v) { return __uint_as_float(v & 0xffff0000u); }
__device__ __forceinline__ float rbf(float v) { return bf_lo(pack2(v, v)); }
__device__ __forceinline__ uint32_t badd(uint32_t a, uint32_t b) {
    uint32_t r;
    asm("add.rn.bf16x2 %0, %1, %2;" : "=r"(r) : "r"(a), "r"(b));
    return r;
}
__device__ __forceinline__ uint32_t bsub(uint32_t a, uint32_t b) {
    uint32_t r;
    asm("sub.rn.bf16x2 %0, %1, %2;" : "=r"(r) : "r"(a), "r"(b));
    return r;
}
__device__ __forceinline__ uint32_t bmul(uint32_t a, uint32_t b) {
    uint32_t r;
    asm("mul.rn.bf16x2 %0, %1, %2;" : "=r"(r) : "r"(a), "r"(b));
    return r;
}
__device__ __forceinline__ uint32_t ln_apply(uint32_t x, uint32_t mb, float rs, uint32_t scale, uint32_t shift) {
    const uint32_t d = bsub(x, mb);
    return badd(bmul(pack2(bf_lo(d) * rs, bf_hi(d) * rs), scale), shift);
}
__device__ __forceinline__ float ex2(float v) {
    float r;
    asm("ex2.approx.ftz.f32 %0, %1;" : "=f"(r) : "f"(v));
    return r;
}
__device__ __forceinline__ float rcp(float v) {
    float r;
    asm("rcp.approx.ftz.f32 %0, %1;" : "=f"(r) : "f"(v));
    return r;
}
__device__ __forceinline__ float sqrt_fast(float v) {
    float r;
    asm("sqrt.approx.ftz.f32 %0, %1;" : "=f"(r) : "f"(v));
    return r;
}
__device__ __forceinline__ float ln_rstd(float var) { return rcp(rbf(sqrt_fast(rbf(rbf(var) + 1e-5f)))); }
__device__ __forceinline__ float sigmoid(float v) { return rcp(1.f + ex2(-1.4426950408889634f * v)); }
__device__ __forceinline__ float quad_sum(float v) {
    v += __shfl_xor_sync(0xffffffffu, v, 1);
    return v + __shfl_xor_sync(0xffffffffu, v, 2);
}

constexpr uint32_t HI_128 = 0x40000040u, HI_IMG = 0x80000080u, HI_Q = 0x80000040u;
template <int M, int RH>
__device__ __forceinline__ uint4 img_pack(const float (&d)[64], float s) {
    uint4 v;
    v.x = pack2(d[16 * M + 2 * RH] * s, d[16 * M + 2 * RH + 1] * s);
    v.y = pack2(d[16 * M + 4 + 2 * RH] * s, d[16 * M + 5 + 2 * RH] * s);
    v.z = pack2(d[16 * M + 8 + 2 * RH] * s, d[16 * M + 9 + 2 * RH] * s);
    v.w = pack2(d[16 * M + 12 + 2 * RH] * s, d[16 * M + 13 + 2 * RH] * s);
    return v;
}
template <int M>
__device__ __forceinline__ void img_store_global(uint32_t img, uint32_t toff, const float (&d)[64], float s0, float s1) {
    uint4* p = reinterpret_cast<uint4*>(g_img + (img + toff)) + M * 32;
    p[0] = img_pack<M, 0>(d, s0);
    p[128] = img_pack<M, 1>(d, s1);
}
__device__ __forceinline__ void sts128(uint32_t a, uint4 v) {
    asm volatile("st.shared.v4.b32 [%0], {%1, %2, %3, %4};" ::"r"(a), "r"(v.x), "r"(v.y), "r"(v.z), "r"(v.w) : "memory");
}
constexpr float SM_C = 0.08838834764831845f * 1.4426950408889634f;
__device__ __forceinline__ float pack2f(float lo, float hi) {
    float r;
    asm("{\n.reg .b32 t;\ncvt.rn.bf16x2.f32 t, %1, %2;\nmov.b32 %0, t;\n}" : "=f"(r) : "f"(hi), "f"(lo));
    return r;
}
template <int M, bool SCALE, bool PARK>
__device__ __forceinline__ void pack_group(float (&d)[64], float (&v)[8], float s0, float s1) {
#pragma unroll
    for (int i = 0; i < 8; i++) {
        const int k = 16 * M + 4 * (i & 3) + 2 * (i >> 2);
        v[i] = SCALE ? pack2f(d[k] * (i < 4 ? s0 : s1), d[k + 1] * (i < 4 ? s0 : s1)) : pack2f(d[k], d[k + 1]);
        if (PARK && M > 0) d[16 * (M > 0 ? M - 1 : 0) + i] = v[i];
    }
}
__device__ __forceinline__ uint32_t q_off(uint32_t toff) {
    asm volatile("" : "+r"(toff));
    return (((toff >> 1) & ~2047u) ^ 8192) + (toff & 511);
}
template <int M>
__device__ __forceinline__ void ctx_store_part(float4* p, float (&d)[64], float i0, float i1) {
    float v[8];
    pack_group<M, true, true>(d, v, i0, i1);
    p[M * 32] = make_float4(v[0], v[1], v[2], v[3]);
    p[M * 32 + 128] = make_float4(v[4], v[5], v[6], v[7]);
}
__device__ __forceinline__ void ctx_store(uint32_t img, uint32_t toff, float (&o)[64], float i0, float i1) {
    asm volatile("" : "+r"(toff));
    float4* p = reinterpret_cast<float4*>(g_img + (img + toff));
    ctx_store_part<0>(p, o, i0, i1); ctx_store_part<1>(p, o, i0, i1); ctx_store_part<2>(p, o, i0, i1); ctx_store_part<3>(p, o, i0, i1);
}

__device__ __forceinline__ void slot_wait(uint32_t bars, uint32_t& ph, uint32_t slot) {
    mbar_wait(bars + 8 * slot, (ph >> slot) & 1);
    ph ^= 1u << slot;
}
__device__ __forceinline__ void release_if(uint32_t eb, uint32_t slot, bool on) {
    asm volatile("{\n.reg .pred p;\nsetp.ne.s32 p, %1, 0;\n@p mbarrier.arrive.shared::cluster.b64 _, [%0];\n}" ::"r"(eb + 8 * slot), "r"((int)on) : "memory");
}
__device__ __forceinline__ void slot_expect(uint32_t sb, uint32_t slot) {
    asm volatile("{\n.reg .pred p;\nelect.sync _|p, 0xffffffff;\n@p mbarrier.arrive.expect_tx.shared::cta.b64 _, [%0], 32768;\n}"
                 ::"r"(sb + BAR_FULL + 8 * slot) : "memory");
}
__device__ __forceinline__ void slot_acquire(uint32_t sb, uint32_t& ph, uint32_t slot) {
    slot_wait(sb + BAR_EMPTY, ph, slot);
    slot_expect(sb, slot);
}
__device__ __forceinline__ void load_bulk(uint32_t sb, uint32_t slot, uint32_t off, const void* src, uint32_t bytes, bool both, bool first) {
    if (both)
        asm volatile("{\n.reg .pred p;\nelect.sync _|p, 0xffffffff;\n"
                     "@p cp.async.bulk.shared::cluster.global.mbarrier::complete_tx::bytes.multicast::cluster.L2::cache_hint [%0], [%1], %5, [%2], %4, %3;\n}"
                     ::"r"(sb + slot * SLOT + off), "l"(src), "r"(sb + BAR_FULL + 8 * slot), "l"(first ? L2_FIRST : L2_NORMAL), "h"((uint16_t)3),
                     "r"(bytes) : "memory");
    else
        asm volatile("{\n.reg .pred p;\nelect.sync _|p, 0xffffffff;\n"
                     "@p cp.async.bulk.shared::cluster.global.mbarrier::complete_tx::bytes.L2::cache_hint [%0], [%1], %4, [%2], %3;\n}"
                     ::"r"(sb + slot * SLOT + off), "l"(src), "r"(sb + BAR_FULL + 8 * slot), "l"(first ? L2_FIRST : L2_NORMAL), "r"(bytes) : "memory");
}
__device__ __forceinline__ void load_tile(uint32_t sb, uint32_t slot, uint32_t off, const CUtensorMap* m, int row, int cb, bool both, bool first) {
    if (both)
        asm volatile("{\n.reg .pred p;\nelect.sync _|p, 0xffffffff;\n"
                     "@p cp.async.bulk.tensor.3d.shared::cluster.global.mbarrier::complete_tx::bytes.multicast::cluster.L2::cache_hint [%0], [%1, {%3, %4, %5}], [%2], %7, %6;\n}"
                     ::"r"(sb + slot * SLOT + off), "l"(m), "r"(sb + BAR_FULL + 8 * slot), "r"(0), "r"(row), "r"(cb),
                     "l"(first ? L2_FIRST : L2_NORMAL), "h"((uint16_t)3) : "memory");
    else
        asm volatile("{\n.reg .pred p;\nelect.sync _|p, 0xffffffff;\n"
                     "@p cp.async.bulk.tensor.3d.shared::cluster.global.mbarrier::complete_tx::bytes.L2::cache_hint [%0], [%1, {%3, %4, %5}], [%2], %6;\n}"
                     ::"r"(sb + slot * SLOT + off), "l"(m), "r"(sb + BAR_FULL + 8 * slot), "r"(0), "r"(row), "r"(cb),
                     "l"(first ? L2_FIRST : L2_NORMAL) : "memory");
}
__device__ __forceinline__ uint32_t ring_next(uint32_t r) { return r == 4 ? 0 : r + 1; }
__device__ __forceinline__ uint32_t w_table(int hp) { return hp ? 0x3104u : 0x4210u; }
__device__ __forceinline__ uint32_t a_table(int hp) { return hp ? 0x625u : 0x635u; }
__device__ __forceinline__ uint32_t a_next(uint32_t& t) {
    const uint32_t s = t & 15;
    t = (t >> 4) | (s << 8);
    return s;
}
constexpr uint32_t O_TABLE = 0x1604235u;
__device__ __forceinline__ uint32_t o_next(uint32_t& t) {
    const uint32_t s = t & 15;
    t = (t >> 4) | (s << 24);
    return s;
}
__device__ __forceinline__ int o_head(int i, int kh) { return i < 16 ? 4 * (i & 7) + 2 * (kh ^ 1) + (i >> 3) : 29 + 2 * kh; }

template <bool INIT>
__device__ __forceinline__ void gemm_issue(float (&d)[64], uint32_t a, uint32_t b, int acc, bool img) {
    uint64_t da = desc64(a, img ? HI_IMG : HI_128), db = desc64(b, HI_128);
    wg_fence();
#pragma unroll
    for (int k = 0; k < 8; k++) {
        if (INIT && k == 0) wgmma_ss128_init<1>(d, da, db);
        else wgmma_ss128<1>(d, da, db, k ? 1 : acc);
        desc_add(da, !(k & 1) ? 2 : img ? 30 : k == 3 ? 1018 : 2);
        desc_add(db, 128);
    }
    wg_commit();
}

__device__ __forceinline__ void step_retire(uint32_t eb, bool rel, uint32_t pend) {
    wg_wait<0>();
    release_if(eb, pend & 7, rel && (pend & 7) != 7);
    release_if(eb, pend >> 4, rel && pend < 0x70);
}
template <bool ODD>
__device__ __forceinline__ void proj_tile(float (&acc)[64], float (&prev)[64], int t, int q0, uint32_t sb, int wg, uint32_t eb, bool rel, uint32_t& fph,
                                          uint32_t wtab, uint32_t& atab, uint32_t& pend, uint32_t prev_img, uint32_t toff, float s0, float s1,
                                          uint32_t (&v)[32]) {
    const uint32_t a0 = desc_k(sb + (wg ^ (ODD && t == 5)) * 8192), b0 = desc_mn(sb);
    int q = q0;
#pragma unroll 1
    do {
        const uint32_t ws = (wtab >> (4 * q)) & 15, as = a_next(atab);
        if (!ODD && t != 2) slot_wait(sb + BAR_FULL, fph, ws);
        slot_wait(sb + BAR_FULL, fph, as);
        step_retire(eb, rel, pend);
        if (ODD && q == 2 && t == 5) {
            const uint32_t a = sb + 5 * SLOT + q_off(toff);
#pragma unroll
            for (int i = 0; i < 8; i++) sts128(a + (i >> 2) * 16384 + (i & 2) * 256 + (i & 1) * 1024, make_uint4(v[4 * i], v[4 * i + 1], v[4 * i + 2], v[4 * i + 3]));
        }
        bar_sync(1 + wg, 256);
        gemm_issue<false>(acc, a0 + as * (SLOT / 16), b0 + ws * (SLOT / 16), q, false);
        bar_arrive(2 - wg, 256);
        pend = (ODD && q == 1 && t == 5 ? 7 : as) | (ODD && t != 1 ? ws : 7) << 4;
        wg_wait<1>();
        reg_fence(prev);
        if (ODD && t == 5) {
            if (q == 0) {
#pragma unroll
                for (int i = 0; i < 32; i++) {
                    const int k = 16 * (i >> 3) + 4 * (i & 3) + ((i >> 1) & 2);
                    v[i] = pack2(prev[k], prev[k + 1]);
                }
            }
        } else {
            if (q == 0) img_store_global<0>(prev_img, toff, prev, s0, s1);
            if (q == 1) img_store_global<1>(prev_img, toff, prev, s0, s1);
            if (q == 2) img_store_global<2>(prev_img, toff, prev, s0, s1);
            if (q == 3) img_store_global<3>(prev_img, toff, prev, s0, s1);
        }
    } while (++q < (ODD && t == 5 ? 3 : 4));
}

__device__ __forceinline__ void qk_issue(float (&s)[64], uint32_t q, uint32_t k) {
    wg_fence();
    uint64_t da = desc64(q, HI_Q), db = desc64(k, HI_IMG);
    wgmma_ss128_init<0>(s, da, db);
#pragma unroll
    for (int i = 1; i < 8; i++) {
        desc_add(da, (i & 1) ? 2 : i == 4 ? 990 : 30);
        desc_add(db, (i & 1) ? 2 : 30);
        wgmma_ss128<0>(s, da, db, 1);
    }
    wg_commit();
}
__device__ __forceinline__ void qk_issue(float (&s)[32], uint32_t q, uint32_t k) {
    wg_fence();
    uint64_t da = desc64(q, HI_Q), db = desc64(k, HI_IMG);
    wgmma_ss64_init<0>(s, da, db);
#pragma unroll
    for (int i = 1; i < 8; i++) {
        desc_add(da, (i & 1) ? 2 : i == 4 ? 990 : 30);
        desc_add(db, (i & 1) ? 2 : 30);
        wgmma_ss64<0>(s, da, db, 1);
    }
    wg_commit();
}
__device__ __forceinline__ void pv_issue(float (&o)[64], const uint32_t (&p)[32], uint32_t v, int acc, bool half) {
    uint64_t db = desc64(v, HI_IMG);
    if (half) {
        asm volatile("// half" ::: "memory");
        wg_fence();
#pragma unroll
        for (int i = 0; i < 4; i++) {
            wgmma_rs128(o, p[4 * i], p[4 * i + 1], p[4 * i + 2], p[4 * i + 3], db, i ? 1 : acc);
            desc_add(db, 256);
        }
        wg_commit();
        asm volatile("// half" ::: "memory");
    } else {
        wg_fence();
#pragma unroll
        for (int i = 0; i < 8; i++) {
            wgmma_rs128(o, p[4 * i], p[4 * i + 1], p[4 * i + 2], p[4 * i + 3], db, i ? 1 : acc);
            desc_add(db, 256);
        }
        wg_commit();
    }
}
__device__ __forceinline__ void tri_mask(float (&s)[64], float x) {
#pragma unroll
    for (int k = 0; k < 16; k++) {
        float b;
        asm("sub.sat.f32 %0, %1, %2;" : "=f"(b) : "f"((float)(8 * (k >> 1) + (k & 1))), "f"(x));
        const int i = 32 + 4 * (k >> 1) + (k & 1);
        asm("fma.rn.f32 %0, %1, 0fFF61B1E6, %0;" : "+f"(s[i]) : "f"(b));
        if (k < 14) asm("fma.rn.f32 %0, %1, 0fFF61B1E6, %0;" : "+f"(s[i + 6]) : "f"(b));
    }
}
__device__ __forceinline__ void tri_mask_copy(float (&s)[64], const float (&h)[32], float x) {
#pragma unroll
    for (int i = 0; i < 32; i++) {
            asm("{\n.reg .pred p;\nsetp.lt.f32 p, %2, %3;\nselp.f32 %0, 0fFF800000, %1, p;\n}"
                : "=f"(s[i]) : "f"(h[i]), "f"(x), "f"((float)(8 * (i >> 2) - 4 * (i & 2) + (i & 1))));
        s[32 + i] = __uint_as_float(0xff800000u);
    }
}
constexpr float SM_HI = 1152921504606846976.f, SM_LO = 1.f / 1152921504606846976.f;
__device__ __forceinline__ bool softmax_unsafe(float t0, float t1, bool first) {
    bool bad = __any_sync(0xffffffffu, fmaxf(t0, t1) > SM_HI);
    if (first) {
        uint32_t a = __ballot_sync(0xffffffffu, t0 >= SM_LO), b = __ballot_sync(0xffffffffu, t1 >= SM_LO);
        a |= a >> 1;
        b |= b >> 1;
        bad |= ((a | (a >> 2)) & (b | (b >> 2)) & 0x11111111u) != 0x11111111u;
    }
    return bad;
}
__device__ __forceinline__ void softmax_remax(const float (&s)[64], float (&m)[2], bool first, float& m0, float& m1, float& a0, float& a1) {
    m0 = fmaxf(s[0], s[1]), m1 = fmaxf(s[2], s[3]);
#pragma unroll
    for (int k = 1; k < 16; k++) {
        m0 = fmaxf(m0, fmaxf(s[4 * k], s[4 * k + 1]));
        m1 = fmaxf(m1, fmaxf(s[4 * k + 2], s[4 * k + 3]));
    }
    m0 = fmaxf(m0, __shfl_xor_sync(0xffffffffu, m0, 1));
    m1 = fmaxf(m1, __shfl_xor_sync(0xffffffffu, m1, 1));
    m0 = fmaxf(m0, __shfl_xor_sync(0xffffffffu, m0, 2));
    m1 = fmaxf(m1, __shfl_xor_sync(0xffffffffu, m1, 2));
    if (!first) {
        m0 = fmaxf(m0, 0.f);
        m1 = fmaxf(m1, 0.f);
    }
    a0 = first ? 1.f : ex2(-m0);
    a1 = first ? 1.f : ex2(-m1);
    m[0] += m0;
    m[1] += m1;
}
template <int J0, int J1>
__device__ __forceinline__ void softmax_exp(const float (&s)[64], uint32_t (&p)[32], float (&t)[4]) {
#pragma unroll
    for (int k = J0; k < J1; k++) {
        const float e0 = ex2(s[4 * k]), e1 = ex2(s[4 * k + 1]), e2 = ex2(s[4 * k + 2]), e3 = ex2(s[4 * k + 3]);
        if (k == 0) { t[0] = e0; t[1] = e1; t[2] = e2; t[3] = e3; }
        else { t[0] += e0; t[1] += e1; t[2] += e2; t[3] += e3; }
        p[2 * k] = pack2(e0, e1);
        p[2 * k + 1] = pack2(e2, e3);
    }
}
__device__ __forceinline__ void mma16816(float (&d)[4], const uint32_t* a, uint32_t b0, uint32_t b1) {
    asm("mma.sync.aligned.m16n8k16.row.col.f32.bf16.bf16.f32 {%0, %1, %2, %3}, {%4, %5, %6, %7}, {%8, %9}, {%0, %1, %2, %3};"
        : "+f"(d[0]), "+f"(d[1]), "+f"(d[2]), "+f"(d[3]) : "r"(a[0]), "r"(a[1]), "r"(a[2]), "r"(a[3]), "r"(b0), "r"(b1));
}
__device__ __forceinline__ uint2 best_key(const uint32_t* keys, int lane, uint32_t ep, uint32_t cur, int enough) {
#pragma unroll 1
    for (;;) {
        const uint4 k = ld_poll(reinterpret_cast<const uint4*>(keys) + lane);
        const bool ok = (((k.x ^ ep) | (k.y ^ ep) | (k.z ^ ep) | (k.w ^ ep)) & 31) == 0;
        const uint32_t best = __reduce_max_sync(0xffffffffu, ok ? max(max(k.x, k.y), max(k.z, k.w)) : 0u);
        const int n = __popc(__ballot_sync(0xffffffffu, ok));
        if (n == 32 || (n >= enough && best != cur)) return make_uint2(best, n == 32);
        __nanosleep(KSLEEP);
    }
}

__global__ void __cluster_dims__(2, 1, 1) __launch_bounds__(384, 1)
fused_kernel(const __grid_constant__ CUtensorMap tm_ckv, const __grid_constant__ CUtensorMap tm_wq,
             const __grid_constant__ CUtensorMap tm_wuk, const __grid_constant__ CUtensorMap tm_wuv,
             const __grid_constant__ CUtensorMap tm_wo, const __grid_constant__ CUtensorMap tm_wg,
             const __grid_constant__ CUtensorMap tm_wu,
             const __grid_constant__ CUtensorMap tm_wm, const __grid_constant__ CUtensorMap tm_x, const Params P) {
    extern __shared__ __align__(1024) uint8_t smem[];
    const uint32_t sb = (uint32_t)__cvta_generic_to_shared(smem);
    const int tid = threadIdx.x, lane = tid & 31, warp = __shfl_sync(0xffffffffu, tid >> 5, 0), wg = warp >> 2;
    const uint32_t sm = blockIdx.x < 8 ? blockIdx.x + 124 : blockIdx.x - 8, smq = ((sm - 64) * 147) >> 11;
    const int rb = sm < 64 ? (sm & 14) * 8 + (sm >> 4) * 2 + (sm & 1)
                 : sm < 120 ? ((sm - 64 - smq * 14) & 14) * 8 + 24 + smq * 2 + (sm & 1) : sm < 124 ? sm + 8 : sm - 116;
    const int grp = rb >> 3, j = rb & 7, kh = (grp >> (OMAP - 1)) & 1;
    const int cq = (j & 1) + ((grp >> (OMAP - 1)) & 2), ort = (OMAP == 1 ? grp & 12 : (grp & 8) + (grp & 1) * 4) + (j >> 1);
    if (warp == 0) TS(0);

    const CUtensorMap* tw = (j & 1) ? &tm_wuv : &tm_wuk;
    if (lane == 0) {
        if (warp == 8) {
#pragma unroll
            for (int i = 0; i < 7; i++) mbar_init(sb + BAR_FULL + 8 * i, 1);
            fence_async_smem();
        } else if (warp < 11) {
            const int w = warp - (warp > 8);
            const u64 cnt = (w < 5 ? (rb < NCTA ? 0x888888884444444ull : 0x888888888888888ull) : 0x111812111111118ull) >> (12 * (w % 5));
#pragma unroll
            for (int i = 0; i < 3; i++) mbar_init(sb + BAR_EMPTY + 24 * w + 8 * i, ((uint32_t)cnt >> (4 * i)) & 15);
        }
        asm volatile("fence.mbarrier_init.release.cluster;" ::: "memory");
    }
    __syncwarp();
    asm volatile("barrier.cluster.arrive.relaxed.aligned;" ::: "memory");
    if (warp == 8) {
        if (rb < NCTA) {
#pragma unroll 1
            for (int u = 0; u < 4; u++) {
                const uint32_t ws = u + (u == 3), as = (0x635u >> (4 * u)) & 15;
                slot_expect(sb, ws);
                load_tile(sb, ws, 0, tw, u * 128, 4 * grp, false, HINT & 1);
                if (u == 3) break;
                slot_expect(sb, as);
                load_tile(sb, as, 0, &tm_ckv, (j >> 1) * 128, u * 2, false, false);
                load_tile(sb, as, 16384, &tm_ckv, (j >> 1) * 128, u * 2 + 1, false, false);
            }
        } else {
#pragma unroll 1
            for (int i = 0; i < 6; i++) {
                slot_expect(sb, i);
                load_tile(sb, i, 0, &tm_wm, i * 64, (rb - NCTA) * 4, false, HINT & 64);
                if (i > 3) tma3d_prefetch(&tm_wm, i * 64 + 128, (rb - NCTA) * 4);
            }
        }
    }
    asm volatile("barrier.cluster.wait.aligned;" ::: "memory");

    if (rb >= NCTA) {
        uint32_t ph = 0, sl = 0;
        if (warp == 8) {
#pragma unroll 1
            for (int i = 6; i < 24; i++) {
                slot_acquire(sb, ph, sl);
                load_tile(sb, sl, 0, &tm_wm, (i & 7) * 64, (i >> 3) * 16 + (rb - NCTA) * 4, false, HINT & 64);
                if (++sl == 6) sl = 0;
            }
#pragma unroll 1
            for (int i = 0; i <= NFFN / NSPARE; i++) {
                const int b = (rb - NCTA) * (NFFN / NSPARE) + i;
                if (i < NFFN / NSPARE) {
                    asm volatile("cp.async.bulk.wait_group.read 0;" ::: "memory");
                    uint32_t done = 0x7f;
                    slot_acquire(sb, done, i & 1);
#pragma unroll 1
                    for (int k = 0; k < 4; k++) tma2d(sb + (i & 1) * SLOT + k * 8192, k < 2 ? &tm_wg : &tm_wu, b * 16, (k & 1) * 256, sb + BAR_FULL + 8 * (i & 1), (HINT & 128) && (i & 3) == 3);
                }
                if (i) {
                    mbar_wait(sb + BAR_FULL + 8 * (~i & 1), ((i - 1) >> 1) & 1);
                    bulk_store(g_wf + (b - 1) * SLOT, sb + (~i & 1) * SLOT, SLOT, HINT & 256);
                    asm volatile("cp.async.bulk.commit_group;" ::: "memory");
                }
            }
            asm volatile("cp.async.bulk.wait_group 0;" ::: "memory");
            fence_async_global();
            TS(4);
        } else if (warp < 8) {
            const uint32_t c2 = __ldg(reinterpret_cast<const uint32_t*>(P.c) + tid), ep = __ldcg(&g_sync.epoch[0]) + 1;
            uint32_t* sc = reinterpret_cast<uint32_t*>(smem + 6 * SLOT);
            sc[tid] = pack2(bf_lo(c2) * sigmoid(bf_lo(c2)), bf_hi(c2) * sigmoid(bf_hi(c2)));
            bar_sync(1, 256);
            const uint32_t a = sb + (warp >> 1) * 8192 + ((lane >> 4) * 8 + (lane & 7)) * 128, ch = (warp & 1) * 4 + ((lane >> 3) & 1);
#pragma unroll 1
            for (int ps = 0; ps < 3; ps++) {
                float d[2][4] = {};
#pragma unroll 1
                for (int bt = 0; bt < 8; bt++) {
                    slot_wait(sb + BAR_FULL, ph, sl);
#pragma unroll
                    for (int i = 0; i < 8; i++) {
                        uint32_t w[4];
                        asm volatile("ldmatrix.sync.aligned.m8n8.x4.trans.shared.b16 {%0, %1, %2, %3}, [%4];" : "=r"(w[0]), "=r"(w[1]), "=r"(w[2]), "=r"(w[3])
                                     : "r"(a + sl * SLOT + (i >> 1) * 2048 + (((ch + 2 * (i & 1)) ^ (lane & 7)) << 4)) : "memory");
                        mma16816(d[i & 1], w, sc[bt * 32 + (i >> 1) * 8 + (lane & 3)], sc[bt * 32 + (i >> 1) * 8 + 4 + (lane & 3)]);
                    }
                    __syncwarp();
                    mbar_arrive_if(sb + BAR_EMPTY + 8 * sl, lane == 0);
                    if (++sl == 6) sl = 0;
                }
                const float v = (lane & 2) ? ((lane & 1) ? d[1][2] : d[1][0]) : ((lane & 1) ? d[0][2] : d[0][0]);
                const int col = (rb - NCTA) * 256 + warp * 32 + (lane & 3) * 8 + (lane >> 2);
                if (ps == 0) st_pub(g_mod1 + col, (pack2(0.f, v) & 0xffff0000u) | (ep & 0xffffu), true);
                else g_mod[ps * 1024 + col] = __float2bfloat16_rn(v);
                if (warp == 0) TS(1 + ps);
            }
        }
        __syncthreads();
        if (tid < 2) flag_add(&g_sync.cnt[7 * 8]);
        return;
    }

    if (wg == 2) {
        asm volatile("setmaxnreg.dec.sync.aligned.u32 40;");
        if (warp == 8) {
            const uint32_t rank = j & 1, half = rank * 16384;
            uint32_t eph = 0, r = 0;
            *reinterpret_cast<volatile uint32_t*>(smem + SM_EP + 20) = 0;
#pragma unroll 1
            for (int hp = 0; hp < 2; hp++) {
                uint32_t wtab = w_table(hp), atab = a_table(hp);
                const int hc = 4 * grp + 2 * hp;
#pragma unroll 1
                for (int u = 3 - 3 * hp; u < 16; u++) {
                    if (hp && u < 4) {
                        const uint32_t ws = (wtab >> (4 * u)) & 15;
                        slot_acquire(sb, eph, ws);
                        load_tile(sb, ws, 0, tw, u * 128, hc, false, HINT & 1);
                        PT();
                    }
                    if (hp == 1 && (u & 7) == 4) mbar_wait(sb + BAR_FLAG + 24 + (u & 8), 0);
                    const uint32_t as = a_next(atab);
                    slot_acquire(sb, eph, as);
                    load_tile(sb, as, half, &tm_ckv, ((u & 12) + (j >> 1)) * 128, (u & 3) * 2 + rank, true, (HINT & 8) && hp);
                    PT();
                    if (hp == 1 && (u | 2) == 3 && lane == 0)
                        asm volatile("red.relaxed.gpu.global.add.u32 [%0], 1;" ::"l"(&g_sync.cnt[(grp * 8 + 3 + (u >> 1)) * 8]) : "memory");
                }
                const uint8_t* src = g_h + (15 - j) * 4 * SLOT;
#pragma unroll 1
                for (int u = 0; u < 8; u++) {
                    if (u == 0 || u == KVG) {
                        mbar_wait(sb + BAR_FLAG + (u ? 8 + 32 * hp : 0), 0);
                        fence_async_global();
                    }
                    if (u < 4) {
                        const uint32_t ws = (wtab >> (4 * u)) & 15;
                        slot_acquire(sb, eph, ws);
                        load_tile(sb, ws, 0, &tm_wq, u * 128, hc, false, HINT & 1);
                        PT();
                    }
                    const uint32_t as = a_next(atab);
                    slot_acquire(sb, eph, as);
                    load_bulk(sb, as, 0, src, SLOT, false, (HINT & 8) && hp);
                    PT();
                    src += u == 3 ? (8 * j - 63) * SLOT : SLOT;
                }
                const int step = hp ? -2 * SLOT : 2 * SLOT;
                src = g_KV + (size_t)(grp * 32 + 30 * hp) * SLOT + half - step;
#pragma unroll 1
                for (int n = 0; n <= 17; n++) {
                    if (n == 8) {
                        mbar_wait(sb + BAR_FLAG + 16 + 32 * hp, 0);
                        fence_async_global();
                    }
                    const uint8_t* v = src + SLOT;
                    src += n < 16 - j ? step : n == 16 - j ? (2 * j - 15) * step : -step;
                    if (n < 17) {
                        slot_acquire(sb, eph, r);
                        if (n != 15 - (j & 6)) load_bulk(sb, r, half, src, SLOT / 2, true, HINT & 4);
                        else load_bulk(sb, r, 0, src - half, SLOT, false, HINT & 4);
                        PT();
                        r = ring_next(r);
                    }
                    if (n) {
                        slot_acquire(sb, eph, r);
                        if (n != 16 - (j & 6)) load_bulk(sb, r, half, v, SLOT / 2, true, HINT & 4);
                        else load_bulk(sb, r, 0, v - half, SLOT, false, HINT & 4);
                        PT();
                        r = ring_next(r);
                    }
                    asm volatile("st.volatile.shared.u32 [%0], %1;" ::"r"(sb + SM_EP + 16), "r"(18 * hp + n + 1) : "memory");
                }
            }
            uint32_t otab = O_TABLE, ready = 0;
#pragma unroll 1
            for (int i = 0; i < 17; i++) {
                const bool dyn = i >= 8 && i < 15;
                const uint32_t want = dyn ? 15u << (4 * (i - 8)) : 1u << max(i + 14, 28);
                if (!(ready & want)) {
                    do {
                        asm volatile("ld.acquire.cta.shared.u32 %0, [%1];" : "=r"(ready) : "r"(sb + SM_EP + 20) : "memory");
                        ready = __shfl_sync(0xffffffffu, ready, 0);
                    } while (!(ready & want));
                    fence_async_global();
                }
                const int head = o_head(dyn ? (ready >> (4 * (i - 8))) & 15 : i, kh);
                const uint32_t as = o_next(otab), ws = o_next(otab), off = i < 15 ? half : kh * 16384;
                slot_acquire(sb, eph, as);
                load_bulk(sb, as, off, g_ctx + (size_t)(ort * 32 + head) * SLOT + off, SLOT / 2, i < 15, HINT & 16);
                if (i == 15) load_tile(sb, as, off ^ 16384, &tm_x, ort * 128 + kh * 64, cq * 2, false, false);
                if (i == 16) load_bulk(sb, as, off ^ 16384, P.wdown + min(rb, NFFN - 1) * 8192, SLOT / 2, false, false);
                PT();
                slot_acquire(sb, eph, ws);
                load_tile(sb, ws, 0, &tm_wo, head * 128, cq * 2, false, HINT & 2);
                PT();
                if (i == 0) o_next(otab);
            }
            if (rb < NFFN) {
                slot_acquire(sb, eph, 5);
                load_bulk(sb, 5, 0, g_wf + rb * SLOT, SLOT, false, false);
            }
        } else if (warp == 9) {
            *reinterpret_cast<volatile uint32_t*>(smem + SM_EP + 16) = 0;
            l2_prefetch(P.ckv + rb * 2048, 4096);
            mbar_watch(sb + BAR_FULL, 0);
            l2_prefetch(P.ckv + 512 * 512 + rb * 2048, 4096);
            mbar_watch(sb + BAR_FULL + 8 * XPF, 0);
            l2_prefetch(P.x + rb * 8192, 16384);
            mbar_watch(sb + BAR_FULL + 8 * 4, 0);
            l2_prefetch(P.ckv + 1024 * 512 + rb * 4096, 8192);
            TS(40);
#pragma unroll 1
            for (int i = 0; i < 15; i++) {
                step_watch(sb + SM_EP + 16, i == 0 ? 0 : i < 5 ? PFA + i : 13 + PFB + i);
                if (i == 12) mbar_watch(sb + BAR_FLAG + 8 * 7, 0);
                const int rf = min(rb, NFFN - 1);
                const uint8_t* p = i == 3 ? reinterpret_cast<const uint8_t*>(P.ckv) + rb * 16384
                                 : i == 4 ? g_h + rb * 16384
                                 : i < 9 ? g_ctx + (size_t)(ort * 32 + o_head(cq + 2 * ((i - 5) & 2), kh)) * SLOT + (i & 1) * 16384
                                 : i < 11 ? reinterpret_cast<const uint8_t*>(P.wo) + (grp * 16 + (~i & 1) * 8 + j) * 16384
                                 : i == 11 ? reinterpret_cast<const uint8_t*>(P.x) + rb * 16384
                                 : i == 12 ? reinterpret_cast<const uint8_t*>(P.wdown) + rf * 16384 : g_wf + rf * SLOT + (i & 1) * 16384;
                if (i >= 3) l2_prefetch(p, 16384);
                else if ((i | j) & 1) tma3d_prefetch(i == 1 ? tw : &tm_wq, (j >> 1) * 128, grp * 4 + (i ? 2 : 0));
            }
            const uint32_t v = lds32(sb + SM_EP) - 1;
            sts128(sb + SM_RED + lane * 16, make_uint4(v, v, v, v));
            fence_async_smem();
            __syncwarp();
#pragma unroll 1
            for (int i = 0; i < OB / 32; i++) bulk_store(g_out + rb * OB + i * 32, sb + SM_RED, 512, false);
            asm volatile("cp.async.bulk.commit_group;\ncp.async.bulk.wait_group 0;" ::: "memory");
            fence_async_global();
            __syncwarp();
            mbar_arrive_if(sb + BAR_PF, lane == 0);
            if (lane == 0) mbar_watch(sb + BAR_END, 0);
        } else {
            const uint32_t ep = __ldcg(&g_sync.epoch[0]) + 1;
            asm volatile("st.shared.u32 [%0], %1;" ::"r"(sb + SM_EP), "r"(ep) : "memory");
            mbar_wait(sb + BAR_FULL + 8 * 4, 0);
            {
                uint4 v[4];
                for (;;) {
                    uint32_t bad = 0;
#pragma unroll
                    for (int k = 0; k < 4; k++) v[k] = ld_poll(reinterpret_cast<const uint4*>(g_mod1) + (warp & 1) * 128 + k * 32 + lane);
#pragma unroll
                    for (int k = 0; k < 4; k++) bad |= (v[k].x ^ ep) | (v[k].y ^ ep) | (v[k].z ^ ep) | (v[k].w ^ ep);
                    if (__all_sync(0xffffffffu, (bad & 0xffff) == 0)) break;
                    __nanosleep(100);
                }
                const uint32_t one = (warp & 1) ? ONE2 : 0x80008000u;
#pragma unroll
                for (int k = 0; k < 4; k++)
                    *reinterpret_cast<uint2*>(smem + SM_TAB + (warp & 1) * 1024 + k * 256 + lane * 8) =
                        make_uint2(badd(__byte_perm(v[k].x, v[k].y, 0x7632), one), badd(__byte_perm(v[k].z, v[k].w, 0x7632), one));
            }
            __syncwarp();
            mbar_arrive_if(sb + BAR_FLAG + 8 * 8, lane == 0);
            if (warp == 10) {
#pragma unroll 1
                for (int i = 0; i < 9; i++) {
                    mbar_sleep(sb + BAR_DONE + 8 * i);
                    if (lane == 0) flag_add(i && ((i - 1) & 2) ? &g_sync.ctxcnt[((i & 1) ? 15 - j : j) * 32 + 2 * grp + (i > 4)] : &g_sync.cnt[(grp * 8 + i) * 8]);
                    if (i == 0) TS(43);
                }
            } else {
                TS(42);
#pragma unroll 1
                for (int i = 0; i < 8; i++) {
                    mbar_sleep(sb + BAR_DONE + 8 * (i == 7 ? 6 : i == 4 ? 3 : i));
                    if (lane < 2) flag_wait(&g_sync.cnt[((i == 0 ? (lane ? j : 15 - j) : i == 7 ? 0 : grp) * 8 + i) * 8], 8 * ep);
                    __syncwarp();
                    mbar_arrive_if(sb + BAR_FLAG + 8 * i, lane == 0 && i < 7);
                    TS(48 + i);
                }
                const uint32_t *mp = reinterpret_cast<const uint32_t*>(g_mod) + lane, *wp = reinterpret_cast<const uint32_t*>(P.wr) + lane;
                float ra = 0.f, rs = 0.f;
#pragma unroll 1
                for (int k = 0; k < 256; k += 32) {
                    const uint32_t ga = __ldcg(mp + 512 + k), sh = __ldcg(mp + 768 + k), c1 = badd(__ldcg(mp + 1024 + k), ONE2);
                    const uint32_t gb = __ldcg(mp + 1280 + k), ww = __ldg(wp + k);
                    const uint32_t a = bmul(c1, ww);
                    ra += bf_lo(a) + bf_hi(a);
                    rs = fmaf(bf_lo(sh), bf_lo(ww), fmaf(bf_hi(sh), bf_hi(ww), rs));
                    if (k >> 6 == cq) {
                        sts128(sb + SM_TAB + ((k & 32) + lane) * 16, make_uint4(ga << 16, ga & 0xffff0000u, a, 0));
                        sts128(sb + SM_TAB + 1024 + ((k & 32) + lane) * 16, make_uint4(c1, sh, gb, 0));
                    }
                }
#pragma unroll 1
                for (int o = 16; o > 0; o >>= 1) {
                    ra += __shfl_xor_sync(0xffffffffu, ra, o);
                    rs += __shfl_xor_sync(0xffffffffu, rs, o);
                }
                *reinterpret_cast<float2*>(smem + SM_EP + 8) = make_float2(ra, rs);
                __syncwarp();
                mbar_arrive_if(sb + BAR_FLAG + 8 * 7, lane == 0);
                const uint32_t* f = &g_sync.ctxcnt[ort * 32 + o_head(min(lane, 16), kh)];
                uint32_t ready = -(j & 1), list = 0, sh = 0, qa;
                asm("mapa.shared::cluster.u32 %0, %1, %2;" : "=r"(qa) : "r"(sb + SM_EP + 20), "r"(lane & 1));
                while (ready != ~0u) {
                    uint32_t v;
                    asm volatile("ld.acquire.gpu.global.u32 %0, [%1];" : "=r"(v) : "l"(f) : "memory");
                    const uint32_t now = __ballot_sync(0xffffffffu, (int)(v - ep) >= 0);
#pragma unroll 1
                    for (uint32_t fresh = now & ~ready & 0x7f00; fresh; fresh &= fresh - 1, sh += 4) list |= (__ffs(fresh) - 1) << sh;
                    list |= (((now & 0xff) + 1) >> 8 << 28) | ((now & 0x18000) << 14);
                    if (now != ready && lane < 2) asm volatile("st.relaxed.cluster.shared::cluster.u32 [%0], %1;" ::"r"(qa), "r"(list) : "memory");
                    if ((now & 0xff) == 0xff) mbar_sleep(sb + BAR_DONE + 8 * 7);
                    ready = now;
                    __nanosleep(POLL_NS);
                }
                TS(45);
            }
        }
    } else {
        const bool elected = (tid & 127) == 0, rel = (tid & 95) == 0;
        uint32_t eb;
        asm("mapa.shared::cluster.u32 %0, %1, %2;" : "=r"(eb) : "r"(sb + BAR_EMPTY), "r"(warp & 1));
        const int g = lane >> 2, c4 = lane & 3;
        uint32_t toff = warp * 4096 + g * 64 + ((c4 ^ (g >> 1)) << 4);
        uint32_t fph = 0x3f, r = 0;
        if (wg == 1) bar_arrive(1, 256);
        const uint32_t kd = desc_k(sb), wd = desc_mn(sb), vd = ((sb & 0x3ffff) >> 4) | (32u << 16);
        const int nL = 16 - j, hn = nL - 1 + wg;
        float s[64], o[64], li[2] = {0.f, 0.f};
        uint32_t cimg = 0;
        const float sc = (j & 1) ? 1.f : SM_C;
#pragma unroll 1
        for (int q = 0; q < 3; q++) {
            const uint32_t as = (0x635u >> (4 * q)) & 15;
            mbar_wait(sb + BAR_FULL + 8 * q, 0);
            mbar_wait(sb + BAR_FULL + 8 * as, 0);
            bar_sync(1 + wg, 256);
            gemm_issue<false>(s, kd + wg * 512 + as * (SLOT / 16), wd + q * (SLOT / 16), q, false);
            bar_arrive(2 - wg, 256);
            wg_wait<0>();
            release_if(eb, as, rel);
        }
        {
            const int xrow = rb * 16 + warp * 2;
            const uint4* xp = reinterpret_cast<const uint4*>(P.x) + xrow * 64;
            const uint32_t img = (grp * 32 + j) * SLOT;
            uint32_t x[16], x0[2];
            float st[4] = {0.f, 0.f, 0.f, 0.f};
            mbar_wait(sb + BAR_FULL + 8 * 4, 0);
#pragma unroll
            for (int q = 3; q < 8; q++) {
                const uint32_t ws = (0x4210u >> (4 * (q & 3))) & 15, as = (0x635u >> (4 * (q % 3))) & 15;
                mbar_wait(sb + BAR_FULL + 8 * as, (q / 3) & 1);
                bar_sync(1 + wg, 256);
                if (q == 3) gemm_issue<false>(s, kd + wg * 512 + as * (SLOT / 16), wd + ws * (SLOT / 16), 1, false);
                else if (q == 4) gemm_issue<true>(o, kd + wg * 512 + as * (SLOT / 16), wd + ws * (SLOT / 16), 0, false);
                else gemm_issue<false>(o, kd + wg * 512 + as * (SLOT / 16), wd + ws * (SLOT / 16), 1, false);
                bar_arrive(2 - wg, 256);
                sched_fence(fph, P.zero);
                if (q > 3) reg_fence(s);
                if (q == 3) {
                    asm volatile("setmaxnreg.inc.sync.aligned.u32 232;");
#pragma unroll
                    for (int i = 0; i < 4; i++)
                        asm volatile("ld.global.nc.v4.u32 {%0, %1, %2, %3}, [%4];" : "=r"(x[4 * i]), "=r"(x[4 * i + 1]), "=r"(x[4 * i + 2]), "=r"(x[4 * i + 3])
                                     : "l"(xp + lane + 32 * i) : "memory");
#pragma unroll
                    for (int i = 0; i < 2; i++) asm volatile("ld.global.nc.u32 %0, [%1];" : "=r"(x0[i]) : "l"(xp + 64 * i) : "memory");
                }
                if (q == 4) {
                    img_store_global<0>(img, toff, s, sc, sc);
#pragma unroll
                    for (int k = 0; k < 16; k++) {
                        const float d0 = bf_lo(x[k]) - bf_lo(x0[k >> 3]), d1 = bf_hi(x[k]) - bf_lo(x0[k >> 3]);
                        st[k >> 3] += d0 + d1;
                        st[2 + (k >> 3)] = fmaf(d0, d0, fmaf(d1, d1, st[2 + (k >> 3)]));
                    }
#pragma unroll
                    for (int i = 0; i < 4 * NSH; i++) st[i & 3] += __shfl_xor_sync(0xffffffffu, st[i & 3], 1 << (i >> 2));
                    reg_fence(st);
                }
                if (q == 5) {
#pragma unroll
                    for (int i = 4 * NSH; i < 20; i++) st[i & 3] += __shfl_xor_sync(0xffffffffu, st[i & 3], 1 << (i >> 2));
                    img_store_global<1>(img, toff, s, sc, sc);
#pragma unroll
                    for (int i = 0; i < 2; i++) {
                        const float d = st[i] * (1.f / 512.f);
                        st[2 + i] = ln_rstd(fmaxf(fmaf(-d, d, st[2 + i] * (1.f / 512.f)), 0.f));
                        x0[i] = pack2(bf_lo(x0[i]) + d, bf_lo(x0[i]) + d);
                    }
                    reg_fence(st);
                    reg_fence(x0);
                }
                if (q > 5) {
                    if (q == 6) mbar_wait(sb + BAR_FLAG + 8 * 8, 0);
                    const uint4 a = lds128(sb + SM_TAB + 1024 + (q & 1) * 512 + lane * 16), c = lds128(sb + SM_TAB + (q & 1) * 512 + lane * 16);
                    uint8_t* hp = g_h + (grp * 8 + (q & 1) * 4 + (lane >> 3)) * 16384 + (xrow & 127) * 128;
#pragma unroll
                    for (int i = 0; i < 2; i++) {
                        const uint32_t* y = x + 8 * i + 4 * (q & 1);
                        *reinterpret_cast<uint4*>(hp + i * 128 + (((lane ^ xrow ^ i) & 7) << 4)) =
                            make_uint4(ln_apply(y[0], x0[i], st[2 + i], a.x, c.x), ln_apply(y[1], x0[i], st[2 + i], a.y, c.y),
                                       ln_apply(y[2], x0[i], st[2 + i], a.z, c.z), ln_apply(y[3], x0[i], st[2 + i], a.w, c.w));
                    }
                    if (q == 7) {
                        __syncwarp();
                        mbar_arrive_if(sb + BAR_DONE, lane == 0);
                    }
                    if (q == 6) img_store_global<2>(img, toff, s, sc, sc);
                    else img_store_global<3>(img, toff, s, sc, sc);
                }
                if (q < 7) {
                    sched_fence(fph, P.zero);
                    wg_wait<0>();
                    release_if(eb, as, rel);
                }
            }
        }
        uint32_t pend = 0x73;
        uint32_t p[32] = {};
#pragma unroll 1
        for (int hp = 0; hp < 2; hp++) {
            float m[2] = {0.f, 0.f}, l[2] = {0.f, 0.f}, t[4] = {0.f, 0.f, 0.f, 0.f};
            bool shifted = false, bad = false, plain = false;
            uint32_t qa = desc_k(sb + 5 * SLOT + (wg ^ 1) * 8192);
            const uint32_t limg = (512 + (15 - j) * 32 + 2 * grp + hp) * SLOT;
            {
                const int step = hp ? -8 * SLOT : 8 * SLOT;
                uint32_t img = (grp * 32 + (hp ? j ^ 30 : j) + 8) * SLOT;
                const uint32_t wtab = w_table(hp);
                uint32_t atab = hp ? 0x562u : 0x356u;
#pragma unroll 1
                for (int u = 2 - 2 * hp; u < 6; u += 2) {
                    proj_tile<false>(s, o, u, !u, sb, wg, eb, rel, fph, wtab, atab, pend, u ? img : cimg, toff, u ? sc : li[0], u ? sc : li[1], p);
                    __syncwarp();
                    mbar_arrive_if(sb + BAR_DONE + 4 * u + 32 * hp, lane == 0);
                    if (elected) TS(1 + 10 * hp + u + 20 * wg);
                    proj_tile<true>(o, s, u + 1, 0, sb, wg, eb, rel, fph, wtab, atab, pend, img + step, toff, sc, sc, p);
                    if (elected) TS(2 + 10 * hp + u + 20 * wg);
                    img += 2 * step;
                }
            }
            asm volatile("" : "+r"(toff));
            if (elected) TS(6 + 10 * hp + 20 * wg);
            fence_async_smem();
            slot_wait(sb + BAR_FULL, fph, r);
            step_retire(eb, rel, pend);
            reg_fence(o);
            int n = -1;
#pragma unroll 1
            for (;;) {
                while (bad || plain) {
                    float d0 = m[0], d1 = m[1];
                    if (bad) {
                        float a0, a1;
                        softmax_remax(s, m, n == 0 || n == nL, d0, d1, a0, a1);
                        shifted = true;
                        l[0] *= a0;
                        l[1] *= a1;
#pragma unroll
                        for (int i = 0; i < 64; i++) o[i] *= (i & 2) ? a1 : a0;
                    }
#pragma unroll
                    for (int i = 0; i < 64; i++) s[i] -= (i & 2) ? d1 : d0;
                    softmax_exp<0, 16>(s, p, t);
                    t[0] += t[1];
                    t[2] += t[3];
                    bad = !bad && softmax_unsafe(t[0], t[2], false);
                    plain = false;
                }
#pragma unroll 1
                do {
                    l[0] += t[0];
                    l[1] += t[2];
                    if (++n > 16) break;
                    const uint32_t ks = r;
                    uint32_t vs = ring_next(r);
                    r = ring_next(vs);
                    bar_sync(1 + wg, 256);
                    const float x = (float)((warp & 3) * 16 + g - 2 * c4);
                    if (n == hn) {
                        float sh[32];
                        qk_issue(sh, qa, kd + ks * (SLOT / 16));
                        slot_wait(sb + BAR_FULL, fph, vs);
                        pv_issue(o, p, vd + vs * (SLOT / 16), 1, false);
                        bar_arrive(2 - wg, 256);
                        wg_wait<1>();
                        reg_fence(sh);
                        tri_mask_copy(s, sh, x);
                        release_if(eb, ks, rel);
                        release_if(eb, 5 + wg, rel && (!wg || n == 16));
                        if (!wg) qa += SLOT / 16;
                        float e[4 * EARLY];
#pragma unroll
                        for (int i = 0; i < 4 * EARLY; i++) {
                            e[i] = ex2(s[i]);
                            t[i & 3] = i < 4 ? e[i] : t[i & 3] + e[i];
                        }
                        reg_fence(e);
                        slot_wait(sb + BAR_FULL, fph, r);
                        wg_wait<0>();
                        reg_fence(o);
                        reg_fence(e);
                        release_if(eb, vs, rel);
#pragma unroll
                        for (int i = 0; i < 2 * EARLY; i++) p[i] = pack2(e[2 * i], e[2 * i + 1]);
                        softmax_exp<EARLY, 8>(s, p, t);
                        if (wg) {
                            ctx_store(limg, toff, o, rcp(quad_sum(l[0])), rcp(quad_sum(l[1])));
                            __syncwarp();
                            mbar_arrive_if(sb + BAR_DONE + 24 + 32 * hp, lane == 0);
                            l[0] = l[1] = m[0] = m[1] = 0.f;
                            shifted = false;
                        }
                        t[0] += t[1];
                        t[2] += t[3];
                        plain = shifted;
                        if (plain) break;
                        bad = softmax_unsafe(t[0], t[2], wg);
                        continue;
                    }
                    if (n == nL) {
                        qk_issue(s, qa, kd + ks * (SLOT / 16));
                        slot_wait(sb + BAR_FULL, fph, vs);
                        pv_issue(o, p, vd + vs * (SLOT / 16), 1, true);
                        bar_arrive(2 - wg, 256);
                        const float i0 = rcp(quad_sum(l[0])), i1 = rcp(quad_sum(l[1]));
                        wg_wait<1>();
                        reg_fence(s);
                        release_if(eb, ks, rel);
                        release_if(eb, 6, rel && n == 16);
                        tri_mask(s, x);
                        float e[4 * EARLY2];
#pragma unroll
                        for (int i = 0; i < 4 * EARLY2; i++) {
                            e[i] = ex2(s[i]);
                            t[i & 3] = i < 4 ? e[i] : t[i & 3] + e[i];
                        }
                        reg_fence(e);
                        reg_fence(s);
                        reg_fence(t);
                        slot_wait(sb + BAR_FULL, fph, r);
                        if (SF & 1) sched_fence(fph, P.zero);
                        wg_wait<0>();
                        reg_fence(o);
                        reg_fence(e);
                        release_if(eb, vs, rel);
#pragma unroll
                        for (int i = 0; i < 2 * EARLY2; i++) p[i] = pack2(e[2 * i], e[2 * i + 1]);
                        softmax_exp<EARLY2, MSPLIT>(s, p, t);
                        ctx_store(limg, toff, o, i0, i1);
                        reg_fence(t);
                        if (SF & 2) sched_fence(fph, P.zero);
                        reg_fence(s);
                        softmax_exp<MSPLIT, 16>(s, p, t);
                        __syncwarp();
                        mbar_arrive_if(sb + BAR_DONE + 24 + 32 * hp, lane == 0);
                        l[0] = l[1] = m[0] = m[1] = 0.f;
                        shifted = false;
                        t[0] += t[1];
                        t[2] += t[3];
                        bad = __any_sync(0xffffffffu, fmaxf(t[0], t[2]) > SM_HI || fminf(t[0], t[2]) < SM_LO);
                        continue;
                    }
                    qk_issue(s, qa, kd + ks * (SLOT / 16));
                    if (n == 0) {
                        r = vs;
                        vs = 4 - hp;
                        slot_wait(sb + BAR_FULL, fph, 6);
                        gemm_issue<false>(o, qa + SLOT / 16, wd + vs * (SLOT / 16), 1, false);
                    } else {
                        slot_wait(sb + BAR_FULL, fph, vs);
                        if (n == 1) {
                            wg_wait<1>();
                            reg_fence(o);
                            const uint32_t a = sb + 6 * SLOT + q_off(toff);
#pragma unroll
                            for (int i = 0; i < 8; i++) {
                                const int k = 16 * (i >> 1) + 2 * (i & 1);
                                sts128(a + (i >> 2) * 16384 + (i & 2) * 256 + (i & 1) * 1024,
                                       make_uint4(pack2(o[k], o[k + 1]), pack2(o[k + 4], o[k + 5]), pack2(o[k + 8], o[k + 9]), pack2(o[k + 12], o[k + 13])));
                            }
                        }
                        pv_issue(o, p, vd + vs * (SLOT / 16), n != 1 && n != nL + 1, n == hn + 1);
                    }
                    bar_arrive(2 - wg, 256);
                    wg_wait<1>();
                    reg_fence(s);
                    release_if(eb, ks, rel);
                    release_if(eb, 6, rel && n == 16);
                    if (n == nL - 1) {
                        tri_mask(s, x);
                        release_if(eb, 5, rel);
                        qa += SLOT / 16;
                    }
                    if (n == 2) fence_async_smem();
                    if (shifted) {
                        slot_wait(sb + BAR_FULL, fph, r);
                        wg_wait<0>();
                        reg_fence(o);
                        release_if(eb, vs, rel);
                        plain = true;
                        break;
                    }
                    float e[4 * EARLY];
#pragma unroll
                    for (int i = 0; i < 4 * EARLY; i++) {
                        e[i] = ex2(s[i]);
                        t[i & 3] = i < 4 ? e[i] : t[i & 3] + e[i];
                    }
                    reg_fence(e);
                    slot_wait(sb + BAR_FULL, fph, r);
                    wg_wait<0>();
                    reg_fence(o);
                    reg_fence(e);
                    release_if(eb, vs, rel);
#pragma unroll
                    for (int i = 0; i < 2 * EARLY; i++) p[i] = pack2(e[2 * i], e[2 * i + 1]);
                    softmax_exp<EARLY, 16>(s, p, t);
                    t[0] += t[1];
                    t[2] += t[3];
                    bad = __any_sync(0xffffffffu, fmaxf(t[0], t[2]) > SM_HI || (n == 0 && fminf(t[0], t[2]) < SM_LO));
                } while (!bad);
                if (!bad && !plain) break;
            }
            asm volatile("" : "+r"(toff));
            const uint32_t vs = r, ga = desc_k(sb + (hp ? 2 * (wg ^ kh ^ 1) : wg) * 8192);
            r = ring_next(r);
            slot_wait(sb + BAR_FULL, fph, 5);
            slot_wait(sb + BAR_FULL, fph, r);
            bar_sync(1 + wg, 256);
            gemm_issue<true>(s, ga + 5 * (SLOT / 16), wd + r * (SLOT / 16), 0, hp);
            pv_issue(o, p, vd + vs * (SLOT / 16), j, hn == 16);
            bar_arrive(2 - wg, 256);
            li[0] = rcp(quad_sum(l[0]));
            li[1] = rcp(quad_sum(l[1]));
            cimg = limg + (2 * j - 15) * 32 * SLOT + (wg ? -16384 : 16384);
            wg_wait<1>();
            release_if(eb, 5, rel);
            release_if(eb, r, rel && hp);
            wg_wait<0>();
            release_if(eb, vs, rel);
            reg_fence(o);
            img_store_global<0>(cimg, toff, o, li[0], li[1]);
            pend = 0x77;
            if (elected) TS(8 + 10 * hp + 20 * wg);
        }
        uint32_t otab = 0x2351604u;
        const uint32_t oa = desc_k(sb + (wg ^ kh ^ 1) * 16384);
        const int t7 = tid & 127, w4 = warp & 3, row = ort * 128 + kh * 64 + w4 * 16 + g;
#pragma unroll 1
        for (int i = 1; i < 15 - wg; i++) {
            const uint32_t as = o_next(otab), ws = o_next(otab);
            slot_wait(sb + BAR_FULL, fph, as);
            slot_wait(sb + BAR_FULL, fph, ws);
            bar_sync(1 + wg, 256);
            gemm_issue<false>(s, oa + as * (SLOT / 16), wd + ws * (SLOT / 16), 1, true);
            bar_arrive(2 - wg, 256);
            wg_wait<1>();
            reg_fence(o);
            if (i == 1) img_store_global<1>(cimg, toff, o, li[0], li[1]);
            if (i == 2) {
                img_store_global<2>(cimg, toff, o, li[0], li[1]);
                img_store_global<3>(cimg, toff, o, li[0], li[1]);
                __syncwarp();
                mbar_arrive_if(sb + BAR_DONE + 64, lane == 0);
            }
            wg_wait<0>();
            release_if(eb, as, rel);
            release_if(eb, ws, rel);
        }
        mbar_wait(sb + BAR_PF, 0);
        const uint32_t ep = lds32(sb + SM_EP);
        uint32_t eb2 = sb + BAR_END;
        if (wg == 0) {
            reg_fence(s);
            if (elected) TS(9);
            TT(1);
#pragma unroll
            for (int v = 0; v < 8; v++)
                st_pub(g_out + rb * OB + v * 128 + t7, make_uint4((pack2(s[8 * v], s[8 * v + 1]) & ~1u) | (ep & 1), pack2(s[8 * v + 2], s[8 * v + 3]),
                                                                      pack2(s[8 * v + 4], s[8 * v + 5]), pack2(s[8 * v + 6], s[8 * v + 7])), true);
            constexpr uint32_t s1 = 5, s2 = 6;
            if (ELATE >= 0) bar_sync(4, 256);
            uint32_t wf[64];
            float wn[64];
            if (rb < NFFN) {
                slot_wait(sb + BAR_FULL, fph, s1);
                const uint32_t a = sb + s1 * SLOT + (w4 * 128 + (lane >> 4) * 8 + (lane & 7)) * 32 + (((lane >> 3) ^ (lane >> 2)) & 1) * 16;
#pragma unroll
                for (int i = 0; i < 16; i++)
                    asm volatile("ldmatrix.sync.aligned.m8n8.x4.trans.shared.b16 {%0, %1, %2, %3}, [%4];"
                                 : "=r"(wf[4 * i]), "=r"(wf[4 * i + 1]), "=r"(wf[4 * i + 2]), "=r"(wf[4 * i + 3])
                                 : "r"(a + (i >> 3) * 16384 + (i & 7) * 512) : "memory");
                slot_wait(sb + BAR_FULL, fph, s2);
#pragma unroll
                for (int i = 0; i < 16; i++) {
                    const uint2 w = *reinterpret_cast<const uint2*>(smem + s2 * SLOT + (kh ^ 1) * 16384 + i * 1024 + t7 * 8);
                    wn[4 * i] = bf_lo(w.x); wn[4 * i + 1] = bf_hi(w.x); wn[4 * i + 2] = bf_lo(w.y); wn[4 * i + 3] = bf_hi(w.y);
                }
                reg_fence(wn);
            }
            const uint32_t gbf = __ldcg(reinterpret_cast<const uint32_t*>(g_mod) + 1280 + rb * 2 + (tid & 1));
            if (elected) TS(10);
            TT(2);
            float* sred = reinterpret_cast<float*>(smem + SM_RED);
            uint32_t best = ep ^ 1, all;
            bool fresh;
            do {
                if (warp == 0) {
                    const uint2 k = best_key(g_key + cq * 128, lane, ep, best, rb < NFFN ? SPEC : 32);
                    *reinterpret_cast<uint2*>(smem + SM_EP + 24) = k;
                    mbar_arrive_if(sb + BAR_BEST, lane == 0 && k.y);
                }
                bar_sync(3, 128);
                const uint2 k = *reinterpret_cast<const uint2*>(smem + SM_EP + 24);
                fresh = k.x != best;
                best = k.x;
                all = k.y;
                TT(3);
                if (!fresh || rb >= NFFN) break;
                const uint4* cp = g_cand + ((~best >> 9) & 127) * 192;
                uint4 cv[6];
                for (;;) {
                    uint32_t bad = 0;
#pragma unroll
                    for (int v = 0; v < 6; v++) cv[v] = ld_poll(cp + w4 * 24 + v * 4 + c4);
#pragma unroll
                    for (int v = 0; v < 6; v++) bad |= cv[v].w ^ ep;
                    if (__all_sync(0xffffffffu, bad == 0)) break;
                    if (CSLEEP) __nanosleep(CSLEEP);
                }
            TT(4);
                float d[4][4] = {};
#pragma unroll
                for (int k = 0; k < 8; k++) {
                    const uint32_t b0 = (&cv[(2 * k) / 3].x)[(2 * k) % 3], b1 = (&cv[(2 * k + 1) / 3].x)[(2 * k + 1) % 3];
                    mma16816(d[k & 1], wf + 4 * k, b0, b1);
                    mma16816(d[2 + (k & 1)], wf + 32 + 4 * k, b0, b1);
                }
                const float u = (c4 & 2) ? ((c4 & 1) ? d[2][2] + d[3][2] : d[2][0] + d[3][0]) : ((c4 & 1) ? d[0][2] + d[1][2] : d[0][0] + d[1][0]);
                sred[w4 * 32 + c4 * 8 + g] = u;
                bar_sync(3, 128);
                const float v = rbf((sred[lane] + sred[32 + lane]) + (sred[64 + lane] + sred[96 + lane]));
                const float act = rbf(rbf(v * sigmoid(v)) * __shfl_down_sync(0xffffffffu, v, 16));
                float y[4] = {0.f, 0.f, 0.f, 0.f};
#pragma unroll
                for (int k = 0; k < 16; k++) {
                    const float a = __shfl_sync(0xffffffffu, act, k);
#pragma unroll
                    for (int i = 0; i < 4; i++) y[i] = fmaf(a, wn[4 * k + i], y[i]);
                }
                st_pub(g_out + rb * OB + OB_Y + t7, make_uint4((__float_as_uint(y[0]) & ~15u) | (ep & 15), (__float_as_uint(y[1]) & ~127u) | ((best >> 9) & 127),
                                                               __float_as_uint(y[2]), __float_as_uint(y[3])), true);
            } while (!all);
            const int sel = (~best >> 5) & 2047;
            const int pq = (2 * rb + (tid & 1)) & 63, pv = (pq >> 2) / 3;
            const uint4* fp = g_cand + (sel >> 4) * 192 + (rb >> 5) * 24 + pv * 4 + (pq & 3);
            uint4 fh = {}, fx = {};
            if (rb == 0 && tid == 0) g_sync.epoch[0] = ep;
            if (elected) TS(60);
            TT(5);
            uint4 yv;
            if (warp == 0) { fh = ld_poll(fp); fx = ld_poll(fp + 96); }
            if (fresh && rb < NFFN) __nanosleep(YPRE);
            for (;;) {
                yv = ld_poll(g_out + min(t7, NFFN - 1) * OB + OB_Y + rb);
                if (__all_sync(0xffffffffu, (((yv.x ^ ep) & 15) | ((yv.y ^ (best >> 9)) & 127)) == 0)) break;
                if (YSLEEP) __nanosleep(YSLEEP);
            }
            if (elected) TS(61);
            TT(6);
            float y[4] = {0.f, 0.f, 0.f, 0.f};
            if (t7 < NFFN) { y[0] = __uint_as_float(yv.x); y[1] = __uint_as_float(yv.y); y[2] = __uint_as_float(yv.z); y[3] = __uint_as_float(yv.w); }
            const float z0 = ((lane & 16) ? y[2] : y[0]) + __shfl_xor_sync(0xffffffffu, (lane & 16) ? y[0] : y[2], 16);
            const float z1 = ((lane & 16) ? y[3] : y[1]) + __shfl_xor_sync(0xffffffffu, (lane & 16) ? y[1] : y[3], 16);
            float z = ((lane & 8) ? z1 : z0) + __shfl_xor_sync(0xffffffffu, (lane & 8) ? z0 : z1, 8);
            z += __shfl_xor_sync(0xffffffffu, z, 4);
            z = quad_sum(z);
            if ((lane & 7) == 0) sred[128 + (lane >> 3) * 4 + w4] = z;
            bar_sync(3, 128);
            if (tid < 2) {
                while (fh.w != ep || fx.w != ep) { fh = ld_poll(fp); fx = ld_poll(fp + 96); }
                const float4 y0 = *reinterpret_cast<const float4*>(sred + 128 + tid * 8), y1 = *reinterpret_cast<const float4*>(sred + 132 + tid * 8);
                const int cm = (pq >> 2) - 3 * pv;
                const uint32_t h2 = cm == 0 ? fh.x : cm == 1 ? fh.y : fh.z, x2 = cm == 0 ? fx.x : cm == 1 ? fx.y : fx.z;
                const float sg = sigmoid(bf_hi((best & 0x80000000u) ? (best ^ 0x80000000u) : ~best));
                reinterpret_cast<uint32_t*>(P.out)[sel * 256 + rb * 2 + tid] =
                    badd(x2, bmul(gbf, badd(h2, bmul(pack2((y0.x + y0.y) + (y0.z + y0.w), (y1.x + y1.y) + (y1.z + y1.w)), pack2(sg, sg)))));
            }
            if (elected) TS(62);
            TT(7);
        } else {
            const float4* tf = reinterpret_cast<const float4*>(smem + SM_TAB) + c4;
            const uint32_t xa = sb + 4 * SLOT + (kh ^ 1) * 16384 + (w4 * 16 + (lane & 15)) * 128;
            uint32_t x2[32];
            bar_sync(2, 256);
#pragma unroll 1
            for (int i = 14; i < 17; i++) {
                const uint32_t as = o_next(otab), ws = o_next(otab);
                slot_wait(sb + BAR_FULL, fph, as);
                slot_wait(sb + BAR_FULL, fph, ws);
                gemm_issue<false>(s, oa + as * (SLOT / 16), wd + ws * (SLOT / 16), 1, true);
                wg_wait<1>();
            }
            const uint4* pr = g_out + (rb ^ (8 * OMAP)) * OB + t7;
            uint4 pa[8];
            if (PEARLY) {
#pragma unroll
                for (int v = 0; v < 8; v++) pa[v] = ld_poll(pr + v * 128);
            }
            if (elected) TS(29);
            TT(1);
            {
#pragma unroll
                for (int k = 0; k < 8; k++)
                    asm volatile("ldmatrix.sync.aligned.m8n8.x4.shared.b16 {%0, %1, %2, %3}, [%4];"
                                 : "=r"(x2[4 * k]), "=r"(x2[4 * k + 1]), "=r"(x2[4 * k + 2]), "=r"(x2[4 * k + 3])
                                 : "r"(xa + (k >> 2) * 8192 + (((2 * (k & 3) + (lane >> 4)) ^ (lane & 7)) << 4)) : "memory");
            }
            wg_wait<0>();
            reg_fence(s);
            if (!ELATE) bar_arrive(4, 256);
            if (elected) TS(39);
            TT(2);
            if (!PEARLY) {
#pragma unroll
                for (int v = 0; v < 8; v++) pa[v] = ld_poll(pr + v * 128);
            }
            float4 tc[16];
#pragma unroll
            for (int k = 0; k < 16; k++) {
                tc[k] = tf[k * 4];
                if (!(g & 1)) tc[k].z = __uint_as_float(ONE2);
#pragma unroll
                for (int i = 4 * k; i < 4 * k + 4; i++) s[i] = fmaf((i & 1) ? tc[k].y : tc[k].x, s[i], (i & 1) ? bf_hi(x2[i >> 1]) : bf_lo(x2[i >> 1]));
            }
            reg_fence(s);
            if (TF & 2) sched_fence(eb2, P.zero);
            for (;;) {
                uint32_t bad = 0;
#pragma unroll
                for (int v = 0; v < 8; v++) asm("lop3.b32 %0, %0, %1, %2, 0xf6;" : "+r"(bad) : "r"(pa[v].x), "r"(ep));
                if (__all_sync(0xffffffffu, (bad & 1) == 0)) break;
                if (PSLEEP) __nanosleep(PSLEEP);
#pragma unroll
                for (int v = 0; v < 8; v++) pa[v] = ld_poll(pr + v * 128);
            }
            if (ELATE == 1) bar_arrive(4, 256);
            if (elected) TS(30);
            TT(3);
            float sd[4] = {}, q0[4] = {}, q1[4] = {};
#pragma unroll
            for (int k = 0; k < 8; k++) {
#pragma unroll
                for (int i = 4 * k; i < 4 * k + 4; i++) {
                    const uint32_t w = (&pa[k].x)[i & 3];
                    x2[i] = pack2(fmaf(tc[i >> 1].x, bf_lo(w), s[2 * i]), fmaf(tc[i >> 1].y, bf_hi(w), s[2 * i + 1]));
                }
                mma16816(sd, x2 + 4 * k, __float_as_uint(tc[2 * k].z), __float_as_uint(tc[2 * k + 1].z));
                mma16816(q0, x2 + 4 * k, x2[4 * k], x2[4 * k + 2]);
                mma16816(q1, x2 + 4 * k, x2[4 * k + 1], x2[4 * k + 3]);
            }
            uint4* sp = g_out + rb * OB + OB_STAT + (w4 * 8 + g) * 2;
            st_pub(sp, make_uint4(__float_as_uint(sd[0]), __float_as_uint((g & 1) ? q0[1] : q0[0]), __float_as_uint(sd[1]), ep), c4 == g >> 1);
            st_pub(sp + 1, make_uint4(__float_as_uint(sd[2]), __float_as_uint((g & 1) ? q1[3] : q1[2]), __float_as_uint(sd[3]), ep), c4 == g >> 1);
            if (ELATE == 2) bar_arrive(4, 256);
            if (TF & 1) sched_fence(eb2, P.zero);
            if (elected) TS(56);
            TT(4);
            uint32_t cb[16], sh[16], gb[16];
#pragma unroll
            for (int i = 0; i < 16; i++) {
                const float4 c = tf[64 + i * 4];
                cb[i] = __float_as_uint(c.x); sh[i] = __float_as_uint(c.y); gb[i] = __float_as_uint(c.z);
            }
            const float ra = __uint_as_float(lds32(sb + SM_EP + 8)), rb0 = __uint_as_float(lds32(sb + SM_EP + 12));
            uint4 r0, r1;
            if (SPRE) __nanosleep(SPRE);
            for (;;) {
                r0 = ld_poll(g_out + ((rb & ~(16 * OMAP + 1)) + (c4 & 1) + (c4 & 2) * 8 * OMAP) * OB + OB_STAT + (w4 * 8 + g) * 2);
                r1 = ld_poll(g_out + ((rb & ~(16 * OMAP + 1)) + (c4 & 1) + (c4 & 2) * 8 * OMAP) * OB + OB_STAT + (w4 * 8 + g) * 2 + 1);
                if (__all_sync(0xffffffffu, r0.w == ep && r1.w == ep)) break;
                if (SSLEEP) __nanosleep(SSLEEP);
            }
            if (elected) TS(57);
            TT(5);
            const float m0 = quad_sum(__uint_as_float(r0.x)) * (1.f / 512.f), m1 = quad_sum(__uint_as_float(r1.x)) * (1.f / 512.f);
            const float rs0 = ln_rstd(fmaxf(fmaf(-m0, m0, quad_sum(__uint_as_float(r0.y)) * (1.f / 512.f)), 0.f));
            const float rs1 = ln_rstd(fmaxf(fmaf(-m1, m1, quad_sum(__uint_as_float(r1.y)) * (1.f / 512.f)), 0.f));
            const uint32_t mb0 = pack2(m0, m0), mb1 = pack2(m1, m1);
            const uint32_t lg = pack2(fmaf(rs0, fmaf(-bf_lo(mb0), ra, quad_sum(__uint_as_float(r0.z))), rb0),
                                      fmaf(rs1, fmaf(-bf_lo(mb1), ra, quad_sum(__uint_as_float(r1.z))), rb0));
            const uint32_t u0 = lg << 16, u1 = lg & 0xffff0000u;
            const uint32_t k0 = ((u0 ^ (((int)u0 >> 31) | 0x80000000u)) & 0xffff0000u) | ((2047 - row) << 5) | (ep & 31);
            const uint32_t k1 = ((u1 ^ (((int)u1 >> 31) | 0x80000000u)) & 0xffff0000u) | ((2039 - row) << 5) | (ep & 31);
            const uint32_t kb = __reduce_max_sync(0xffffffffu, max(k0, k1));
            st_pub(g_key + cq * 128 + (row >> 4), kb, lane == 0);
            const bool cand = kb == k0 || kb == k1;
            uint4* cp = g_cand + (row >> 4) * 192 + cq * 24 + c4;
#pragma unroll 1
            for (int it = 0; it < 3; it++) {
                bool put = it == 1 || !cand;
                if (it == 2) {
                    mbar_wait(sb + BAR_BEST, 0);
                    put = cand && lds32(sb + SM_EP + 24) != kb;
                }
                const bool hi = (kb == k1) != (it == 1);
                uint32_t cx[18], ch[18];
#pragma unroll
                for (int i = 0; i < 16; i++) {
                    cx[i] = hi ? x2[2 * i + 1] : x2[2 * i];
                    ch[i] = ln_apply(cx[i], hi ? mb1 : mb0, hi ? rs1 : rs0, cb[i], sh[i]);
                }
                cx[16] = cx[17] = ch[16] = ch[17] = 0;
#pragma unroll
                for (int v = 0; v < 6; v++) st_pub(cp + v * 4, make_uint4(ch[3 * v], ch[3 * v + 1], ch[3 * v + 2], ep), cand && it == 0);
#pragma unroll
                for (int v = 0; v < 6; v++) st_pub(cp + 96 + v * 4, make_uint4(cx[3 * v], cx[3 * v + 1], cx[3 * v + 2], ep), cand && it == 0);
                if (it == 0) TT(6);
                uint2* op = reinterpret_cast<uint2*>(P.out) + (row + 8 * hi) * 128 + cq * 32 + (c4 & 1) * 2 + (c4 >> 1);
#pragma unroll
                for (int i = 0; i < 16; i += 2) {
                    const uint32_t v0 = badd(cx[i], bmul(gb[i], ch[i])), v1 = badd(cx[i + 1], bmul(gb[i + 1], ch[i + 1]));
                    const uint32_t rv = __shfl_xor_sync(0xffffffffu, (c4 & 1) ? v0 : v1, 1);
                    if (put) op[i * 2] = (c4 & 1) ? make_uint2(rv, v1) : make_uint2(v0, rv);
                }
            }
            if (elected) TS(59);
            TT(7);
        }
        mbar_arrive_if(eb2, lane == 0);
    }
}

typedef CUresult (*EncodeFn)(CUtensorMap*, CUtensorMapDataType, cuuint32_t, void*, const cuuint64_t*, const cuuint64_t*,
                             const cuuint32_t*, const cuuint32_t*, CUtensorMapInterleave, CUtensorMapSwizzle,
                             CUtensorMapL2promotion, CUtensorMapFloatOOBfill);

void make_2d(EncodeFn fn, CUtensorMap* m, const void* p, uint64_t cols, uint64_t rows, uint32_t bc, uint32_t br, CUtensorMapSwizzle sw) {
    cuuint64_t dims[2] = {cols, rows}, strides[1] = {cols * 2};
    cuuint32_t box[2] = {bc, br}, es[2] = {1, 1};
    fn(m, CU_TENSOR_MAP_DATA_TYPE_BFLOAT16, 2, const_cast<void*>(p), dims, strides, box, es, CU_TENSOR_MAP_INTERLEAVE_NONE,
       sw, CU_TENSOR_MAP_L2_PROMOTION_L2_128B, CU_TENSOR_MAP_FLOAT_OOB_FILL_NONE);
}
void make_3d(EncodeFn fn, CUtensorMap* m, const void* p, uint64_t cols, uint64_t rows, uint32_t br = 128, uint32_t nb = 2) {
    cuuint64_t dims[3] = {64, rows, cols / 64}, strides[2] = {cols * 2, 128};
    cuuint32_t box[3] = {64, br, nb}, es[3] = {1, 1, 1};
    fn(m, CU_TENSOR_MAP_DATA_TYPE_BFLOAT16, 3, const_cast<void*>(p), dims, strides, box, es, CU_TENSOR_MAP_INTERLEAVE_NONE,
       CU_TENSOR_MAP_SWIZZLE_128B, CU_TENSOR_MAP_L2_PROMOTION_L2_256B, CU_TENSOR_MAP_FLOAT_OOB_FILL_NONE);
}

}

extern "C" void kernel_launch(void* const* d_in, const int* in_sizes, int n_in, void* d_out, int out_size) {
    static EncodeFn fn = nullptr;
    if (!fn) {
        void* f = nullptr;
        cudaDriverEntryPointQueryResult st;
        cudaGetDriverEntryPoint("cuTensorMapEncodeTiled", &f, cudaEnableDefault, &st);
        fn = (EncodeFn)f;
        cudaFuncSetAttribute(fused_kernel, cudaFuncAttributeMaxDynamicSharedMemorySize, SMEM_BYTES);
    }
    CUtensorMap ckv, wq, wuk, wuv, wo, wg, wu, wm, xm;
    make_3d(fn, &ckv, d_in[1], 512, 2048, 128, 1);
    make_3d(fn, &xm, d_in[0], 512, 2048, 64);
    make_3d(fn, &wq, d_in[2], 4096, 512);
    make_3d(fn, &wuk, d_in[3], 4096, 512);
    make_3d(fn, &wuv, d_in[4], 4096, 512);
    make_3d(fn, &wo, d_in[5], 512, 4096);
    make_2d(fn, &wg, d_in[8], 1792, 512, 16, 256, CU_TENSOR_MAP_SWIZZLE_32B);
    make_2d(fn, &wu, d_in[9], 1792, 512, 16, 256, CU_TENSOR_MAP_SWIZZLE_32B);
    make_3d(fn, &wm, d_in[12], 3072, 512, 64, 4);
    Params p;
    p.x = (const bf16*)d_in[0];
    p.ckv = (const bf16*)d_in[1];
    p.wo = (const bf16*)d_in[5];
    p.wr = (const bf16*)d_in[7];
    p.wdown = (const bf16*)d_in[10];
    p.c = (const bf16*)d_in[11];
    p.out = (bf16*)d_out;
    p.zero = 0;
    fused_kernel<<<NCTA + NSPARE, 384, SMEM_BYTES>>>(ckv, wq, wuk, wuv, wo, wg, wu, wm, xm, p);
}
```

```cpp
#include <cuda.h>
#include <cuda_bf16.h>
#include <cuda_runtime.h>
#include <stdint.h>
#include <stdio.h>

namespace {

typedef __nv_bfloat16 bf16;
typedef unsigned long long u64;

constexpr int NCTA = 128, NSPARE = 4;
constexpr int SLOT = 32768;
constexpr int SM_BAR = 7 * SLOT;
constexpr int BAR_FULL = SM_BAR;
constexpr int BAR_EMPTY = BAR_FULL + 8 * 7;
constexpr int BAR_DONE = BAR_EMPTY + 8 * 7;
constexpr int BAR_FLAG = BAR_DONE + 8 * 9;
constexpr int BAR_PF = BAR_FLAG + 8 * 9;
constexpr int BAR_END = BAR_PF + 8;
constexpr int BAR_BEST = BAR_END + 8;
constexpr int SM_EP = BAR_END + 40;
constexpr int SM_RED = SM_BAR + 384;
constexpr int SM_TAB = SM_BAR + 1024;
constexpr int SMEM_BYTES = SM_BAR + 3072;
constexpr int NFFN = 112;
#define HINT 479
constexpr u64 L2_NORMAL = 0x1000000000000000ull, L2_FIRST = 0x12F0000000000000ull;
#define PFA 8
#define PFB 6
#define POLL_NS 50
#define MSPLIT 13
#define NSH 1
#define XPF 1
#define KSLEEP 200
#define YSLEEP 50
#define YPRE 150
#define SSLEEP 50
#define PSLEEP 100
#define SPEC 28
#define KVG 7
#define EARLY2 4
#define EARLY 7
constexpr uint32_t SPIN_LIMIT = 1u << 22;
constexpr uint32_t ONE2 = 0x3f803f80u;

struct Sync {
    uint32_t cnt[16 * 8 * 8];
    uint32_t ctxcnt[16 * 32];
    uint32_t epoch[32];
};

__device__ __align__(1024) uint8_t g_img[2 * 512 * SLOT];
#define g_KV g_img
#define g_ctx (g_img + 512 * SLOT)
__device__ __align__(1024) uint8_t g_h[16 * 4 * SLOT];
constexpr int OB = 1216, OB_STAT = 1024, OB_Y = 1088;
__device__ __align__(1024) uint4 g_out[128 * OB];
__device__ __align__(1024) bf16 g_mod[3072];
__device__ __align__(1024) uint32_t g_mod1[1024];
__device__ __align__(1024) uint4 g_cand[128 * 192];
__device__ __align__(1024) uint32_t g_key[4 * 128];
__device__ __align__(1024) uint8_t g_wf[NFFN * SLOT];
__device__ __align__(1024) Sync g_sync;
#define TS(i)

#define TT(i)
#define PT()

struct Params {
    const bf16 *x, *ckv, *wo, *wr, *wdown, *c;
    bf16* out;
    int zero;
};

__device__ __forceinline__ void mbar_init(uint32_t bar, uint32_t cnt) {
    asm volatile("mbarrier.init.shared::cta.b64 [%0], %1;" ::"r"(bar), "r"(cnt) : "memory");
}
__device__ __forceinline__ void mbar_wait(uint32_t bar, uint32_t parity) {
    asm volatile("{\n.reg .pred p;\nL_%=:\nmbarrier.try_wait.parity.shared::cta.b64 p, [%0], %1;\n@!p bra L_%=;\n}" ::"r"(bar), "r"(parity) : "memory");
}
__device__ __forceinline__ void mbar_sleep(uint32_t bar) {
    if ((threadIdx.x & 31) == 0)
        asm volatile("{\n.reg .pred p;\nL_%=:\nmbarrier.try_wait.parity.shared::cta.b64 p, [%0], 0, 100000;\n@!p bra L_%=;\n}" ::"r"(bar) : "memory");
    __syncwarp();
}
__device__ __forceinline__ void mbar_watch(uint32_t bar, uint32_t parity) {
    asm volatile("{\n.reg .pred p;\n.reg .u32 n;\nmov.u32 n, 0;\n"
                 "L_%=:\nmbarrier.try_wait.parity.shared::cta.b64 p, [%0], %1;\n@p bra D_%=;\n"
                 "add.u32 n, n, 1;\nsetp.lt.u32 p, n, %2;\n@p bra L_%=;\ntrap;\nD_%=:\n}"
                 ::"r"(bar), "r"(parity), "n"(SPIN_LIMIT) : "memory");
}
__device__ __forceinline__ void step_watch(uint32_t a, uint32_t step) {
    asm volatile("{\n.reg .pred p;\n.reg .u32 n, v;\nmov.u32 n, 0;\n"
                 "L_%=:\nld.volatile.shared.u32 v, [%0];\nsetp.ge.u32 p, v, %1;\n@p bra D_%=;\nnanosleep.u32 400;\n"
                 "add.u32 n, n, 1;\nsetp.lt.u32 p, n, %2;\n@p bra L_%=;\ntrap;\nD_%=:\n}"
                 ::"r"(a), "r"(step), "n"(SPIN_LIMIT) : "memory");
}
__device__ __forceinline__ void mbar_arrive_if(uint32_t bar, bool on) {
    asm volatile("{\n.reg .pred p;\nsetp.ne.s32 p, %1, 0;\n@p mbarrier.arrive.shared::cta.b64 _, [%0];\n}" ::"r"(bar), "r"((int)on) : "memory");
}
__device__ __forceinline__ void tma2d(uint32_t dst, const CUtensorMap* m, int c0, int c1, uint32_t bar, bool first) {
    asm volatile("{\n.reg .pred p;\nelect.sync _|p, 0xffffffff;\n"
                 "@p cp.async.bulk.tensor.2d.shared::cluster.global.mbarrier::complete_tx::bytes.L2::cache_hint [%0], [%1, {%3, %4}], [%2], %5;\n}"
                 ::"r"(dst), "l"(m), "r"(bar), "r"(c0), "r"(c1), "l"(first ? L2_FIRST : L2_NORMAL) : "memory");
}
__device__ __forceinline__ void tma3d_prefetch(const CUtensorMap* m, int row, int cb) {
    asm volatile("{\n.reg .pred p;\nelect.sync _|p, 0xffffffff;\n@p cp.async.bulk.prefetch.tensor.3d.L2.global [%0, {%1, %2, %3}];\n}"
                 ::"l"(m), "r"(0), "r"(row), "r"(cb) : "memory");
}
__device__ __forceinline__ void l2_prefetch(const void* p, uint32_t bytes) {
    asm volatile("{\n.reg .pred p;\nelect.sync _|p, 0xffffffff;\n@p cp.async.bulk.prefetch.L2.global [%0], %1;\n}" ::"l"(p), "r"(bytes) : "memory");
}
__device__ __forceinline__ void bulk_store(void* dst, uint32_t src, uint32_t bytes, bool first) {
    asm volatile("{\n.reg .pred p;\nelect.sync _|p, 0xffffffff;\n@p cp.async.bulk.global.shared::cta.bulk_group.L2::cache_hint [%0], [%1], %2, %3;\n}"
                 ::"l"(dst), "r"(src), "r"(bytes), "l"(first ? L2_FIRST : L2_NORMAL) : "memory");
}
__device__ __forceinline__ void flag_wait(const uint32_t* f, uint32_t target) {
    asm volatile("{\n.reg .pred p;\n.reg .u32 v;\n"
                 "L_%=:\nld.acquire.gpu.global.u32 v, [%0];\nsub.u32 v, v, %1;\nsetp.lt.s32 p, v, 0;\n@p nanosleep.u32 100;\n@p bra L_%=;\n}"
                 ::"l"(f), "r"(target) : "memory");
}
__device__ __forceinline__ uint4 ld_poll(const uint4* p) {
    uint4 v;
    asm volatile("{\n.reg .b128 t;\nld.relaxed.gpu.global.b128 t, [%4];\nmov.b128 {%0, %1, %2, %3}, t;\n}"
                 : "=r"(v.x), "=r"(v.y), "=r"(v.z), "=r"(v.w) : "l"(p) : "memory");
    return v;
}
__device__ __forceinline__ void st_pub(uint4* p, uint4 v, bool on) {
    asm volatile("{\n.reg .pred p;\n.reg .b128 t;\nsetp.ne.s32 p, %5, 0;\nmov.b128 t, {%1, %2, %3, %4};\n@p st.relaxed.gpu.global.b128 [%0], t;\n}"
                 ::"l"(p), "r"(v.x), "r"(v.y), "r"(v.z), "r"(v.w), "r"((int)on) : "memory");
}
__device__ __forceinline__ void st_pub(uint32_t* p, uint32_t v, bool on) {
    asm volatile("{\n.reg .pred p;\nsetp.ne.s32 p, %2, 0;\n@p st.relaxed.gpu.global.u32 [%0], %1;\n}" ::"l"(p), "r"(v), "r"((int)on) : "memory");
}
__device__ __forceinline__ void flag_add(uint32_t* p) {
    asm volatile("red.release.gpu.global.add.u32 [%0], 1;" ::"l"(p) : "memory");
}
__device__ __forceinline__ uint32_t lds32(uint32_t a) {
    uint32_t v;
    asm volatile("ld.shared.u32 %0, [%1];" : "=r"(v) : "r"(a) : "memory");
    return v;
}
__device__ __forceinline__ uint4 lds128(uint32_t a) {
    uint4 v;
    asm volatile("ld.shared.v4.u32 {%0, %1, %2, %3}, [%4];" : "=r"(v.x), "=r"(v.y), "=r"(v.z), "=r"(v.w) : "r"(a) : "memory");
    return v;
}
__device__ __forceinline__ void sched_fence(uint32_t& v, uint32_t z) {
    uint32_t ck;
    asm volatile("mov.u32 %0, %%clock;" : "=r"(ck)::"memory");
    v ^= ck & z;
}
__device__ __forceinline__ void fence_async_global() { asm volatile("fence.proxy.async.global;" ::: "memory"); }
__device__ __forceinline__ void fence_async_smem() { asm volatile("fence.proxy.async.shared::cta;" ::: "memory"); }
__device__ __forceinline__ void bar_sync(int id, int n) { asm volatile("bar.sync %0, %1;" ::"r"(id), "r"(n) : "memory"); }
__device__ __forceinline__ void bar_arrive(int id, int n) { asm volatile("bar.arrive %0, %1;" ::"r"(id), "r"(n) : "memory"); }
__device__ __forceinline__ void wg_fence() { asm volatile("wgmma.fence.sync.aligned;" ::: "memory"); }
__device__ __forceinline__ void wg_commit() { asm volatile("wgmma.commit_group.sync.aligned;" ::: "memory"); }
template <int N> __device__ __forceinline__ void wg_wait() { asm volatile("wgmma.wait_group.sync.aligned %0;" ::"n"(N) : "memory"); }
template <int N> __device__ __forceinline__ void reg_fence(float (&d)[N]) {
#pragma unroll
    for (int i = 0; i < N; i++) asm volatile("" : "+f"(d[i])::"memory");
}
template <int N> __device__ __forceinline__ void reg_fence(uint32_t (&d)[N]) {
#pragma unroll
    for (int i = 0; i < N; i++) asm volatile("" : "+r"(d[i])::"memory");
}
__device__ __forceinline__ uint32_t desc_k(uint32_t a) { return ((a & 0x3ffff) >> 4) | (1u << 16); }
__device__ __forceinline__ uint32_t desc_mn(uint32_t a) { return ((a & 0x3ffff) >> 4) | (1024u << 16); }

__device__ __forceinline__ uint64_t desc64(uint32_t lo, uint32_t hi) {
    uint64_t d;
    asm("mov.b64 %0, {%1, %2};" : "=l"(d) : "r"(lo), "r"(hi));
    return d;
}
__device__ __forceinline__ void desc_add(uint64_t& d, uint32_t x) { asm("add.u64 %0, %0, %1;" : "+l"(d) : "l"((uint64_t)x)); }

template <int TB>
__device__ __forceinline__ void wgmma_ss128(float (&d)[64], uint64_t da, uint64_t db, int acc) {
    asm volatile("{\n.reg .pred p;\nsetp.ne.b32 p, %66, 0;\n"
        "wgmma.mma_async.sync.aligned.m64n128k16.f32.bf16.bf16 {%0, %1, %2, %3, %4, %5, %6, %7, %8, %9, %10, %11, %12, %13, %14, %15, %16, %17, %18, %19, %20, %21, %22, %23, %24, %25, %26, %27, %28, %29, %30, %31, %32, %33, %34, %35, %36, %37, %38, %39, %40, %41, %42, %43, %44, %45, %46, %47, %48, %49, %50, %51, %52, %53, %54, %55, %56, %57, %58, %59, %60, %61, %62, %63}, %64, %65, p, 1, 1, 0, %67;\n}"
        : "+f"(d[0]), "+f"(d[1]), "+f"(d[2]), "+f"(d[3]), "+f"(d[4]), "+f"(d[5]), "+f"(d[6]), "+f"(d[7]), "+f"(d[8]), "+f"(d[9]), "+f"(d[10]), "+f"(d[11]), "+f"(d[12]), "+f"(d[13]), "+f"(d[14]), "+f"(d[15]), "+f"(d[16]), "+f"(d[17]), "+f"(d[18]), "+f"(d[19]), "+f"(d[20]), "+f"(d[21]), "+f"(d[22]), "+f"(d[23]), "+f"(d[24]), "+f"(d[25]), "+f"(d[26]), "+f"(d[27]), "+f"(d[28]), "+f"(d[29]), "+f"(d[30]), "+f"(d[31]), "+f"(d[32]), "+f"(d[33]), "+f"(d[34]), "+f"(d[35]), "+f"(d[36]), "+f"(d[37]), "+f"(d[38]), "+f"(d[39]), "+f"(d[40]), "+f"(d[41]), "+f"(d[42]), "+f"(d[43]), "+f"(d[44]), "+f"(d[45]), "+f"(d[46]), "+f"(d[47]), "+f"(d[48]), "+f"(d[49]), "+f"(d[50]), "+f"(d[51]), "+f"(d[52]), "+f"(d[53]), "+f"(d[54]), "+f"(d[55]), "+f"(d[56]), "+f"(d[57]), "+f"(d[58]), "+f"(d[59]), "+f"(d[60]), "+f"(d[61]), "+f"(d[62]), "+f"(d[63])
        : "l"(da), "l"(db), "r"(acc), "n"(TB));
}
template <int TB>
__device__ __forceinline__ void wgmma_ss128_init(float (&d)[64], uint64_t da, uint64_t db) {
    asm volatile("{\n.reg .pred p;\nsetp.ne.b32 p, 0, 0;\n"
        "wgmma.mma_async.sync.aligned.m64n128k16.f32.bf16.bf16 {%0, %1, %2, %3, %4, %5, %6, %7, %8, %9, %10, %11, %12, %13, %14, %15, %16, %17, %18, %19, %20, %21, %22, %23, %24, %25, %26, %27, %28, %29, %30, %31, %32, %33, %34, %35, %36, %37, %38, %39, %40, %41, %42, %43, %44, %45, %46, %47, %48, %49, %50, %51, %52, %53, %54, %55, %56, %57, %58, %59, %60, %61, %62, %63}, %64, %65, p, 1, 1, 0, %66;\n}"
        : "=f"(d[0]), "=f"(d[1]), "=f"(d[2]), "=f"(d[3]), "=f"(d[4]), "=f"(d[5]), "=f"(d[6]), "=f"(d[7]), "=f"(d[8]), "=f"(d[9]), "=f"(d[10]), "=f"(d[11]), "=f"(d[12]), "=f"(d[13]), "=f"(d[14]), "=f"(d[15]), "=f"(d[16]), "=f"(d[17]), "=f"(d[18]), "=f"(d[19]), "=f"(d[20]), "=f"(d[21]), "=f"(d[22]), "=f"(d[23]), "=f"(d[24]), "=f"(d[25]), "=f"(d[26]), "=f"(d[27]), "=f"(d[28]), "=f"(d[29]), "=f"(d[30]), "=f"(d[31]), "=f"(d[32]), "=f"(d[33]), "=f"(d[34]), "=f"(d[35]), "=f"(d[36]), "=f"(d[37]), "=f"(d[38]), "=f"(d[39]), "=f"(d[40]), "=f"(d[41]), "=f"(d[42]), "=f"(d[43]), "=f"(d[44]), "=f"(d[45]), "=f"(d[46]), "=f"(d[47]), "=f"(d[48]), "=f"(d[49]), "=f"(d[50]), "=f"(d[51]), "=f"(d[52]), "=f"(d[53]), "=f"(d[54]), "=f"(d[55]), "=f"(d[56]), "=f"(d[57]), "=f"(d[58]), "=f"(d[59]), "=f"(d[60]), "=f"(d[61]), "=f"(d[62]), "=f"(d[63])
        : "l"(da), "l"(db), "n"(TB));
}
template <int TB>
__device__ __forceinline__ void wgmma_ss64(float (&d)[32], uint64_t da, uint64_t db, int acc) {
    asm volatile("{\n.reg .pred p;\nsetp.ne.b32 p, %34, 0;\n"
        "wgmma.mma_async.sync.aligned.m64n64k16.f32.bf16.bf16 {%0, %1, %2, %3, %4, %5, %6, %7, %8, %9, %10, %11, %12, %13, %14, %15, %16, %17, %18, %19, %20, %21, %22, %23, %24, %25, %26, %27, %28, %29, %30, %31}, %32, %33, p, 1, 1, 0, %35;\n}"
        : "+f"(d[0]), "+f"(d[1]), "+f"(d[2]), "+f"(d[3]), "+f"(d[4]), "+f"(d[5]), "+f"(d[6]), "+f"(d[7]), "+f"(d[8]), "+f"(d[9]), "+f"(d[10]), "+f"(d[11]), "+f"(d[12]), "+f"(d[13]), "+f"(d[14]), "+f"(d[15]), "+f"(d[16]), "+f"(d[17]), "+f"(d[18]), "+f"(d[19]), "+f"(d[20]), "+f"(d[21]), "+f"(d[22]), "+f"(d[23]), "+f"(d[24]), "+f"(d[25]), "+f"(d[26]), "+f"(d[27]), "+f"(d[28]), "+f"(d[29]), "+f"(d[30]), "+f"(d[31])
        : "l"(da), "l"(db), "r"(acc), "n"(TB));
}
template <int TB>
__device__ __forceinline__ void wgmma_ss64_init(float (&d)[32], uint64_t da, uint64_t db) {
    asm volatile("{\n.reg .pred p;\nsetp.ne.b32 p, 0, 0;\n"
        "wgmma.mma_async.sync.aligned.m64n64k16.f32.bf16.bf16 {%0, %1, %2, %3, %4, %5, %6, %7, %8, %9, %10, %11, %12, %13, %14, %15, %16, %17, %18, %19, %20, %21, %22, %23, %24, %25, %26, %27, %28, %29, %30, %31}, %32, %33, p, 1, 1, 0, %34;\n}"
        : "=f"(d[0]), "=f"(d[1]), "=f"(d[2]), "=f"(d[3]), "=f"(d[4]), "=f"(d[5]), "=f"(d[6]), "=f"(d[7]), "=f"(d[8]), "=f"(d[9]), "=f"(d[10]), "=f"(d[11]), "=f"(d[12]), "=f"(d[13]), "=f"(d[14]), "=f"(d[15]), "=f"(d[16]), "=f"(d[17]), "=f"(d[18]), "=f"(d[19]), "=f"(d[20]), "=f"(d[21]), "=f"(d[22]), "=f"(d[23]), "=f"(d[24]), "=f"(d[25]), "=f"(d[26]), "=f"(d[27]), "=f"(d[28]), "=f"(d[29]), "=f"(d[30]), "=f"(d[31])
        : "l"(da), "l"(db), "n"(TB));
}
__device__ __forceinline__ void wgmma_rs128(float (&d)[64], uint32_t a0, uint32_t a1, uint32_t a2, uint32_t a3, uint64_t db, int acc) {
    asm volatile("{\n.reg .pred p;\nsetp.ne.b32 p, %69, 0;\n"
        "wgmma.mma_async.sync.aligned.m64n128k16.f32.bf16.bf16 {%0, %1, %2, %3, %4, %5, %6, %7, %8, %9, %10, %11, %12, %13, %14, %15, %16, %17, %18, %19, %20, %21, %22, %23, %24, %25, %26, %27, %28, %29, %30, %31, %32, %33, %34, %35, %36, %37, %38, %39, %40, %41, %42, %43, %44, %45, %46, %47, %48, %49, %50, %51, %52, %53, %54, %55, %56, %57, %58, %59, %60, %61, %62, %63}, {%64, %65, %66, %67}, %68, p, 1, 1, 1;\n}"
        : "+f"(d[0]), "+f"(d[1]), "+f"(d[2]), "+f"(d[3]), "+f"(d[4]), "+f"(d[5]), "+f"(d[6]), "+f"(d[7]), "+f"(d[8]), "+f"(d[9]), "+f"(d[10]), "+f"(d[11]), "+f"(d[12]), "+f"(d[13]), "+f"(d[14]), "+f"(d[15]), "+f"(d[16]), "+f"(d[17]), "+f"(d[18]), "+f"(d[19]), "+f"(d[20]), "+f"(d[21]), "+f"(d[22]), "+f"(d[23]), "+f"(d[24]), "+f"(d[25]), "+f"(d[26]), "+f"(d[27]), "+f"(d[28]), "+f"(d[29]), "+f"(d[30]), "+f"(d[31]), "+f"(d[32]), "+f"(d[33]), "+f"(d[34]), "+f"(d[35]), "+f"(d[36]), "+f"(d[37]), "+f"(d[38]), "+f"(d[39]), "+f"(d[40]), "+f"(d[41]), "+f"(d[42]), "+f"(d[43]), "+f"(d[44]), "+f"(d[45]), "+f"(d[46]), "+f"(d[47]), "+f"(d[48]), "+f"(d[49]), "+f"(d[50]), "+f"(d[51]), "+f"(d[52]), "+f"(d[53]), "+f"(d[54]), "+f"(d[55]), "+f"(d[56]), "+f"(d[57]), "+f"(d[58]), "+f"(d[59]), "+f"(d[60]), "+f"(d[61]), "+f"(d[62]), "+f"(d[63])
        : "r"(a0), "r"(a1), "r"(a2), "r"(a3), "l"(db), "r"(acc));
}

__device__ __forceinline__ uint32_t pack2(float lo, float hi) {
    uint32_t r;
    asm("cvt.rn.bf16x2.f32 %0, %1, %2;" : "=r"(r) : "f"(hi), "f"(lo));
    return r;
}
__device__ __forceinline__ float bf_lo(uint32_t v) { return __uint_as_float(v << 16); }
__device__ __forceinline__ float bf_hi(uint32_t v) { return __uint_as_float(v & 0xffff0000u); }
__device__ __forceinline__ float rbf(float v) { return bf_lo(pack2(v, v)); }
__device__ __forceinline__ uint32_t badd(uint32_t a, uint32_t b) {
    uint32_t r;
    asm("add.rn.bf16x2 %0, %1, %2;" : "=r"(r) : "r"(a), "r"(b));
    return r;
}
__device__ __forceinline__ uint32_t bsub(uint32_t a, uint32_t b) {
    uint32_t r;
    asm("sub.rn.bf16x2 %0, %1, %2;" : "=r"(r) : "r"(a), "r"(b));
    return r;
}
__device__ __forceinline__ uint32_t bmul(uint32_t a, uint32_t b) {
    uint32_t r;
    asm("mul.rn.bf16x2 %0, %1, %2;" : "=r"(r) : "r"(a), "r"(b));
    return r;
}
__device__ __forceinline__ uint32_t ln_apply(uint32_t x, uint32_t mb, float rs, uint32_t scale, uint32_t shift) {
    const uint32_t d = bsub(x, mb);
    return badd(bmul(pack2(bf_lo(d) * rs, bf_hi(d) * rs), scale), shift);
}
__device__ __forceinline__ float ex2(float v) {
    float r;
    asm("ex2.approx.ftz.f32 %0, %1;" : "=f"(r) : "f"(v));
    return r;
}
__device__ __forceinline__ float rcp(float v) {
    float r;
    asm("rcp.approx.ftz.f32 %0, %1;" : "=f"(r) : "f"(v));
    return r;
}
__device__ __forceinline__ float sqrt_fast(float v) {
    float r;
    asm("sqrt.approx.ftz.f32 %0, %1;" : "=f"(r) : "f"(v));
    return r;
}
__device__ __forceinline__ float ln_rstd(float var) { return rcp(rbf(sqrt_fast(rbf(rbf(var) + 1e-5f)))); }
__device__ __forceinline__ float sigmoid(float v) { return rcp(1.f + ex2(-1.4426950408889634f * v)); }
__device__ __forceinline__ float quad_sum(float v) {
    v += __shfl_xor_sync(0xffffffffu, v, 1);
    return v + __shfl_xor_sync(0xffffffffu, v, 2);
}

constexpr uint32_t HI_128 = 0x40000040u, HI_IMG = 0x80000080u, HI_Q = 0x80000040u;
template <int M, int RH>
__device__ __forceinline__ uint4 img_pack(const float (&d)[64], float s) {
    uint4 v;
    v.x = pack2(d[16 * M + 2 * RH] * s, d[16 * M + 2 * RH + 1] * s);
    v.y = pack2(d[16 * M + 4 + 2 * RH] * s, d[16 * M + 5 + 2 * RH] * s);
    v.z = pack2(d[16 * M + 8 + 2 * RH] * s, d[16 * M + 9 + 2 * RH] * s);
    v.w = pack2(d[16 * M + 12 + 2 * RH] * s, d[16 * M + 13 + 2 * RH] * s);
    return v;
}
template <int M>
__device__ __forceinline__ void img_store_global(uint32_t img, uint32_t toff, const float (&d)[64], float s0, float s1) {
    uint4* p = reinterpret_cast<uint4*>(g_img + (img + toff)) + M * 32;
    p[0] = img_pack<M, 0>(d, s0);
    p[128] = img_pack<M, 1>(d, s1);
}
__device__ __forceinline__ void sts128(uint32_t a, uint4 v) {
    asm volatile("st.shared.v4.b32 [%0], {%1, %2, %3, %4};" ::"r"(a), "r"(v.x), "r"(v.y), "r"(v.z), "r"(v.w) : "memory");
}
constexpr float SM_C = 0.08838834764831845f * 1.4426950408889634f;
__device__ __forceinline__ float pack2f(float lo, float hi) {
    float r;
    asm("{\n.reg .b32 t;\ncvt.rn.bf16x2.f32 t, %1, %2;\nmov.b32 %0, t;\n}" : "=f"(r) : "f"(hi), "f"(lo));
    return r;
}
template <int M, bool SCALE, bool PARK>
__device__ __forceinline__ void pack_group(float (&d)[64], float (&v)[8], float s0, float s1) {
#pragma unroll
    for (int i = 0; i < 8; i++) {
        const int k = 16 * M + 4 * (i & 3) + 2 * (i >> 2);
        v[i] = SCALE ? pack2f(d[k] * (i < 4 ? s0 : s1), d[k + 1] * (i < 4 ? s0 : s1)) : pack2f(d[k], d[k + 1]);
        if (PARK && M > 0) d[16 * (M > 0 ? M - 1 : 0) + i] = v[i];
    }
}
__device__ __forceinline__ uint32_t q_off(uint32_t toff) {
    asm volatile("" : "+r"(toff));
    return (((toff >> 1) & ~2047u) ^ 8192) + (toff & 511);
}
template <int M>
__device__ __forceinline__ void ctx_store_part(float4* p, float (&d)[64], float i0, float i1) {
    float v[8];
    pack_group<M, true, true>(d, v, i0, i1);
    p[M * 32] = make_float4(v[0], v[1], v[2], v[3]);
    p[M * 32 + 128] = make_float4(v[4], v[5], v[6], v[7]);
}
__device__ __forceinline__ void ctx_store(uint32_t img, uint32_t toff, float (&o)[64], float i0, float i1) {
    asm volatile("" : "+r"(toff));
    float4* p = reinterpret_cast<float4*>(g_img + (img + toff));
    ctx_store_part<0>(p, o, i0, i1); ctx_store_part<1>(p, o, i0, i1); ctx_store_part<2>(p, o, i0, i1); ctx_store_part<3>(p, o, i0, i1);
}

__device__ __forceinline__ void slot_wait(uint32_t bars, uint32_t& ph, uint32_t slot) {
    mbar_wait(bars + 8 * slot, (ph >> slot) & 1);
    ph ^= 1u << slot;
}
__device__ __forceinline__ void release_if(uint32_t eb, uint32_t slot, bool on) {
    asm volatile("{\n.reg .pred p;\nsetp.ne.s32 p, %1, 0;\n@p mbarrier.arrive.shared::cluster.b64 _, [%0];\n}" ::"r"(eb + 8 * slot), "r"((int)on) : "memory");
}
__device__ __forceinline__ void slot_expect(uint32_t sb, uint32_t slot) {
    asm volatile("{\n.reg .pred p;\nelect.sync _|p, 0xffffffff;\n@p mbarrier.arrive.expect_tx.shared::cta.b64 _, [%0], 32768;\n}"
                 ::"r"(sb + BAR_FULL + 8 * slot) : "memory");
}
__device__ __forceinline__ void slot_acquire(uint32_t sb, uint32_t& ph, uint32_t slot) {
    slot_wait(sb + BAR_EMPTY, ph, slot);
    slot_expect(sb, slot);
}
__device__ __forceinline__ void load_bulk(uint32_t sb, uint32_t slot, uint32_t off, const void* src, uint32_t bytes, bool both, bool first) {
    if (both)
        asm volatile("{\n.reg .pred p;\nelect.sync _|p, 0xffffffff;\n"
                     "@p cp.async.bulk.shared::cluster.global.mbarrier::complete_tx::bytes.multicast::cluster.L2::cache_hint [%0], [%1], %5, [%2], %4, %3;\n}"
                     ::"r"(sb + slot * SLOT + off), "l"(src), "r"(sb + BAR_FULL + 8 * slot), "l"(first ? L2_FIRST : L2_NORMAL), "h"((uint16_t)3),
                     "r"(bytes) : "memory");
    else
        asm volatile("{\n.reg .pred p;\nelect.sync _|p, 0xffffffff;\n"
                     "@p cp.async.bulk.shared::cluster.global.mbarrier::complete_tx::bytes.L2::cache_hint [%0], [%1], %4, [%2], %3;\n}"
                     ::"r"(sb + slot * SLOT + off), "l"(src), "r"(sb + BAR_FULL + 8 * slot), "l"(first ? L2_FIRST : L2_NORMAL), "r"(bytes) : "memory");
}
__device__ __forceinline__ void load_tile(uint32_t sb, uint32_t slot, uint32_t off, const CUtensorMap* m, int row, int cb, bool both, bool first) {
    if (both)
        asm volatile("{\n.reg .pred p;\nelect.sync _|p, 0xffffffff;\n"
                     "@p cp.async.bulk.tensor.3d.shared::cluster.global.mbarrier::complete_tx::bytes.multicast::cluster.L2::cache_hint [%0], [%1, {%3, %4, %5}], [%2], %7, %6;\n}"
                     ::"r"(sb + slot * SLOT + off), "l"(m), "r"(sb + BAR_FULL + 8 * slot), "r"(0), "r"(row), "r"(cb),
                     "l"(first ? L2_FIRST : L2_NORMAL), "h"((uint16_t)3) : "memory");
    else
        asm volatile("{\n.reg .pred p;\nelect.sync _|p, 0xffffffff;\n"
                     "@p cp.async.bulk.tensor.3d.shared::cluster.global.mbarrier::complete_tx::bytes.L2::cache_hint [%0], [%1, {%3, %4, %5}], [%2], %6;\n}"
                     ::"r"(sb + slot * SLOT + off), "l"(m), "r"(sb + BAR_FULL + 8 * slot), "r"(0), "r"(row), "r"(cb),
                     "l"(first ? L2_FIRST : L2_NORMAL) : "memory");
}
__device__ __forceinline__ uint32_t ring_next(uint32_t r) { return r == 4 ? 0 : r + 1; }
__device__ __forceinline__ uint32_t w_table(int hp) { return hp ? 0x3104u : 0x4210u; }
__device__ __forceinline__ uint32_t a_table(int hp) { return hp ? 0x625u : 0x635u; }
__device__ __forceinline__ uint32_t a_next(uint32_t& t) {
    const uint32_t s = t & 15;
    t = (t >> 4) | (s << 8);
    return s;
}
constexpr uint32_t O_TABLE = 0x1604235u;
__device__ __forceinline__ uint32_t o_next(uint32_t& t) {
    const uint32_t s = t & 15;
    t = (t >> 4) | (s << 24);
    return s;
}
__device__ __forceinline__ int o_head(int i, int kh) { return i < 16 ? 4 * (i & 7) + 2 * (kh ^ 1) + (i >> 3) : 29 + 2 * kh; }

template <bool INIT>
__device__ __forceinline__ void gemm_issue(float (&d)[64], uint32_t a, uint32_t b, int acc, bool img) {
    uint64_t da = desc64(a, img ? HI_IMG : HI_128), db = desc64(b, HI_128);
    wg_fence();
#pragma unroll
    for (int k = 0; k < 8; k++) {
        if (INIT && k == 0) wgmma_ss128_init<1>(d, da, db);
        else wgmma_ss128<1>(d, da, db, k ? 1 : acc);
        desc_add(da, !(k & 1) ? 2 : img ? 30 : k == 3 ? 1018 : 2);
        desc_add(db, 128);
    }
    wg_commit();
}

__device__ __forceinline__ void step_retire(uint32_t eb, bool rel, uint32_t pend) {
    wg_wait<0>();
    release_if(eb, pend & 7, rel && (pend & 7) != 7);
    release_if(eb, pend >> 4, rel && pend < 0x70);
}
template <bool ODD>
__device__ __forceinline__ void proj_tile(float (&acc)[64], float (&prev)[64], int t, int q0, uint32_t sb, int wg, uint32_t eb, bool rel, uint32_t& fph,
                                          uint32_t wtab, uint32_t& atab, uint32_t& pend, uint32_t prev_img, uint32_t toff, float s0, float s1,
                                          uint32_t (&v)[32]) {
    const uint32_t a0 = desc_k(sb + (wg ^ (ODD && t == 5)) * 8192), b0 = desc_mn(sb);
    int q = q0;
#pragma unroll 1
    do {
        const uint32_t ws = (wtab >> (4 * q)) & 15, as = a_next(atab);
        if (!ODD && t != 2) slot_wait(sb + BAR_FULL, fph, ws);
        slot_wait(sb + BAR_FULL, fph, as);
        step_retire(eb, rel, pend);
        if (ODD && q == 2 && t == 5) {
            const uint32_t a = sb + 5 * SLOT + q_off(toff);
#pragma unroll
            for (int i = 0; i < 8; i++) sts128(a + (i >> 2) * 16384 + (i & 2) * 256 + (i & 1) * 1024, make_uint4(v[4 * i], v[4 * i + 1], v[4 * i + 2], v[4 * i + 3]));
        }
        bar_sync(1 + wg, 256);
        gemm_issue<false>(acc, a0 + as * (SLOT / 16), b0 + ws * (SLOT / 16), q, false);
        bar_arrive(2 - wg, 256);
        pend = (ODD && q == 1 && t == 5 ? 7 : as) | (ODD && t != 1 ? ws : 7) << 4;
        wg_wait<1>();
        reg_fence(prev);
        if (ODD && t == 5) {
            if (q == 0) {
#pragma unroll
                for (int i = 0; i < 32; i++) {
                    const int k = 16 * (i >> 3) + 4 * (i & 3) + ((i >> 1) & 2);
                    v[i] = pack2(prev[k], prev[k + 1]);
                }
            }
        } else {
            if (q == 0) img_store_global<0>(prev_img, toff, prev, s0, s1);
            if (q == 1) img_store_global<1>(prev_img, toff, prev, s0, s1);
            if (q == 2) img_store_global<2>(prev_img, toff, prev, s0, s1);
            if (q == 3) img_store_global<3>(prev_img, toff, prev, s0, s1);
        }
    } while (++q < (ODD && t == 5 ? 3 : 4));
}

__device__ __forceinline__ void qk_issue(float (&s)[64], uint32_t q, uint32_t k) {
    wg_fence();
    uint64_t da = desc64(q, HI_Q), db = desc64(k, HI_IMG);
    wgmma_ss128_init<0>(s, da, db);
#pragma unroll
    for (int i = 1; i < 8; i++) {
        desc_add(da, (i & 1) ? 2 : i == 4 ? 990 : 30);
        desc_add(db, (i & 1) ? 2 : 30);
        wgmma_ss128<0>(s, da, db, 1);
    }
    wg_commit();
}
__device__ __forceinline__ void qk_issue(float (&s)[32], uint32_t q, uint32_t k) {
    wg_fence();
    uint64_t da = desc64(q, HI_Q), db = desc64(k, HI_IMG);
    wgmma_ss64_init<0>(s, da, db);
#pragma unroll
    for (int i = 1; i < 8; i++) {
        desc_add(da, (i & 1) ? 2 : i == 4 ? 990 : 30);
        desc_add(db, (i & 1) ? 2 : 30);
        wgmma_ss64<0>(s, da, db, 1);
    }
    wg_commit();
}
__device__ __forceinline__ void pv_issue(float (&o)[64], const uint32_t (&p)[32], uint32_t v, int acc, bool half) {
    uint64_t db = desc64(v, HI_IMG);
    if (half) {
        asm volatile("// half" ::: "memory");
        wg_fence();
#pragma unroll
        for (int i = 0; i < 4; i++) {
            wgmma_rs128(o, p[4 * i], p[4 * i + 1], p[4 * i + 2], p[4 * i + 3], db, i ? 1 : acc);
            desc_add(db, 256);
        }
        wg_commit();
        asm volatile("// half" ::: "memory");
    } else {
        wg_fence();
#pragma unroll
        for (int i = 0; i < 8; i++) {
            wgmma_rs128(o, p[4 * i], p[4 * i + 1], p[4 * i + 2], p[4 * i + 3], db, i ? 1 : acc);
            desc_add(db, 256);
        }
        wg_commit();
    }
}
__device__ __forceinline__ void tri_mask(float (&s)[64], float x) {
#pragma unroll
    for (int k = 0; k < 16; k++) {
        float b;
        asm("sub.sat.f32 %0, %1, %2;" : "=f"(b) : "f"((float)(8 * (k >> 1) + (k & 1))), "f"(x));
        const int i = 32 + 4 * (k >> 1) + (k & 1);
        asm("fma.rn.f32 %0, %1, 0fFF61B1E6, %0;" : "+f"(s[i]) : "f"(b));
        if (k < 14) asm("fma.rn.f32 %0, %1, 0fFF61B1E6, %0;" : "+f"(s[i + 6]) : "f"(b));
    }
}
__device__ __forceinline__ void tri_mask_copy(float (&s)[64], const float (&h)[32], float x) {
#pragma unroll
    for (int i = 0; i < 32; i++) {
            asm("{\n.reg .pred p;\nsetp.lt.f32 p, %2, %3;\nselp.f32 %0, 0fFF800000, %1, p;\n}"
                : "=f"(s[i]) : "f"(h[i]), "f"(x), "f"((float)(8 * (i >> 2) - 4 * (i & 2) + (i & 1))));
        s[32 + i] = __uint_as_float(0xff800000u);
    }
}
constexpr float SM_HI = 1152921504606846976.f, SM_LO = 1.f / 1152921504606846976.f;
__device__ __forceinline__ bool softmax_unsafe(float t0, float t1, bool first) {
    bool bad = __any_sync(0xffffffffu, fmaxf(t0, t1) > SM_HI);
    if (first) {
        uint32_t a = __ballot_sync(0xffffffffu, t0 >= SM_LO), b = __ballot_sync(0xffffffffu, t1 >= SM_LO);
        a |= a >> 1;
        b |= b >> 1;
        bad |= ((a | (a >> 2)) & (b | (b >> 2)) & 0x11111111u) != 0x11111111u;
    }
    return bad;
}
__device__ __forceinline__ void softmax_remax(const float (&s)[64], float (&m)[2], bool first, float& m0, float& m1, float& a0, float& a1) {
    m0 = fmaxf(s[0], s[1]), m1 = fmaxf(s[2], s[3]);
#pragma unroll
    for (int k = 1; k < 16; k++) {
        m0 = fmaxf(m0, fmaxf(s[4 * k], s[4 * k + 1]));
        m1 = fmaxf(m1, fmaxf(s[4 * k + 2], s[4 * k + 3]));
    }
    m0 = fmaxf(m0, __shfl_xor_sync(0xffffffffu, m0, 1));
    m1 = fmaxf(m1, __shfl_xor_sync(0xffffffffu, m1, 1));
    m0 = fmaxf(m0, __shfl_xor_sync(0xffffffffu, m0, 2));
    m1 = fmaxf(m1, __shfl_xor_sync(0xffffffffu, m1, 2));
    if (!first) {
        m0 = fmaxf(m0, 0.f);
        m1 = fmaxf(m1, 0.f);
    }
    a0 = first ? 1.f : ex2(-m0);
    a1 = first ? 1.f : ex2(-m1);
    m[0] += m0;
    m[1] += m1;
}
template <int J0, int J1>
__device__ __forceinline__ void softmax_exp(const float (&s)[64], uint32_t (&p)[32], float (&t)[4]) {
#pragma unroll
    for (int k = J0; k < J1; k++) {
        const float e0 = ex2(s[4 * k]), e1 = ex2(s[4 * k + 1]), e2 = ex2(s[4 * k + 2]), e3 = ex2(s[4 * k + 3]);
        if (k == 0) { t[0] = e0; t[1] = e1; t[2] = e2; t[3] = e3; }
        else { t[0] += e0; t[1] += e1; t[2] += e2; t[3] += e3; }
        p[2 * k] = pack2(e0, e1);
        p[2 * k + 1] = pack2(e2, e3);
    }
}
__device__ __forceinline__ void mma16816(float (&d)[4], const uint32_t* a, uint32_t b0, uint32_t b1) {
    asm("mma.sync.aligned.m16n8k16.row.col.f32.bf16.bf16.f32 {%0, %1, %2, %3}, {%4, %5, %6, %7}, {%8, %9}, {%0, %1, %2, %3};"
        : "+f"(d[0]), "+f"(d[1]), "+f"(d[2]), "+f"(d[3]) : "r"(a[0]), "r"(a[1]), "r"(a[2]), "r"(a[3]), "r"(b0), "r"(b1));
}
__device__ __forceinline__ uint2 best_key(const uint32_t* keys, int lane, uint32_t ep, uint32_t cur, int enough) {
#pragma unroll 1
    for (;;) {
        const uint4 k = ld_poll(reinterpret_cast<const uint4*>(keys) + lane);
        const bool ok = (((k.x ^ ep) | (k.y ^ ep) | (k.z ^ ep) | (k.w ^ ep)) & 31) == 0;
        const uint32_t best = __reduce_max_sync(0xffffffffu, ok ? max(max(k.x, k.y), max(k.z, k.w)) : 0u);
        const int n = __popc(__ballot_sync(0xffffffffu, ok));
        if (n == 32 || (n >= enough && best != cur)) return make_uint2(best, n == 32);
        __nanosleep(KSLEEP);
    }
}

__global__ void __cluster_dims__(2, 1, 1) __launch_bounds__(384, 1)
fused_kernel(const __grid_constant__ CUtensorMap tm_ckv, const __grid_constant__ CUtensorMap tm_wq,
             const __grid_constant__ CUtensorMap tm_wuk, const __grid_constant__ CUtensorMap tm_wuv,
             const __grid_constant__ CUtensorMap tm_wo, const __grid_constant__ CUtensorMap tm_wg,
             const __grid_constant__ CUtensorMap tm_wu,
             const __grid_constant__ CUtensorMap tm_wm, const __grid_constant__ CUtensorMap tm_x, const Params P) {
    extern __shared__ __align__(1024) uint8_t smem[];
    const uint32_t sb = (uint32_t)__cvta_generic_to_shared(smem);
    const int tid = threadIdx.x, lane = tid & 31, warp = __shfl_sync(0xffffffffu, tid >> 5, 0), wg = warp >> 2;
    const uint32_t sm = blockIdx.x < 8 ? blockIdx.x + 124 : blockIdx.x - 8, smq = ((sm - 64) * 147) >> 11;
    const int rb = sm < 64 ? (sm & 14) * 8 + (sm >> 4) * 2 + (sm & 1)
                 : sm < 120 ? ((sm - 64 - smq * 14) & 14) * 8 + 24 + smq * 2 + (sm & 1) : sm < 124 ? sm + 8 : sm - 116;
    const int grp = rb >> 3, j = rb & 7, kh = (grp >> 1) & 1;
    const int cq = (j & 1) + ((grp >> 1) & 2), ort = (grp & 8) + (grp & 1) * 4 + (j >> 1);
    if (warp == 0) TS(0);

    const CUtensorMap* tw = (j & 1) ? &tm_wuv : &tm_wuk;
    if (lane == 0) {
        if (warp == 8) {
#pragma unroll
            for (int i = 0; i < 7; i++) mbar_init(sb + BAR_FULL + 8 * i, 1);
            fence_async_smem();
        } else if (warp < 11) {
            const int w = warp - (warp > 8);
            const u64 cnt = (w < 5 ? (rb < NCTA ? 0x888888884444444ull : 0x888888888888888ull) : 0x111812111111118ull) >> (12 * (w % 5));
#pragma unroll
            for (int i = 0; i < 3; i++) mbar_init(sb + BAR_EMPTY + 24 * w + 8 * i, ((uint32_t)cnt >> (4 * i)) & 15);
        }
        asm volatile("fence.mbarrier_init.release.cluster;" ::: "memory");
    }
    __syncwarp();
    asm volatile("barrier.cluster.arrive.relaxed.aligned;" ::: "memory");
    if (warp == 8) {
        if (rb < NCTA) {
#pragma unroll 1
            for (int u = 0; u < 4; u++) {
                const uint32_t ws = u + (u == 3), as = (0x635u >> (4 * u)) & 15;
                slot_expect(sb, ws);
                load_tile(sb, ws, 0, tw, u * 128, 4 * grp, false, HINT & 1);
                if (u == 3) break;
                slot_expect(sb, as);
                load_tile(sb, as, 0, &tm_ckv, (j >> 1) * 128, u * 2, false, false);
                load_tile(sb, as, 16384, &tm_ckv, (j >> 1) * 128, u * 2 + 1, false, false);
            }
        } else {
#pragma unroll 1
            for (int i = 0; i < 6; i++) {
                slot_expect(sb, i);
                load_tile(sb, i, 0, &tm_wm, i * 64, (rb - NCTA) * 4, false, HINT & 64);
                if (i > 3) tma3d_prefetch(&tm_wm, i * 64 + 128, (rb - NCTA) * 4);
            }
        }
    }
    asm volatile("barrier.cluster.wait.aligned;" ::: "memory");

    if (rb >= NCTA) {
        uint32_t ph = 0, sl = 0;
        if (warp == 8) {
#pragma unroll 1
            for (int i = 6; i < 24; i++) {
                slot_acquire(sb, ph, sl);
                load_tile(sb, sl, 0, &tm_wm, (i & 7) * 64, (i >> 3) * 16 + (rb - NCTA) * 4, false, HINT & 64);
                if (++sl == 6) sl = 0;
            }
#pragma unroll 1
            for (int i = 0; i <= NFFN / NSPARE; i++) {
                const int b = (rb - NCTA) * (NFFN / NSPARE) + i;
                if (i < NFFN / NSPARE) {
                    asm volatile("cp.async.bulk.wait_group.read 0;" ::: "memory");
                    uint32_t done = 0x7f;
                    slot_acquire(sb, done, i & 1);
#pragma unroll 1
                    for (int k = 0; k < 4; k++) tma2d(sb + (i & 1) * SLOT + k * 8192, k < 2 ? &tm_wg : &tm_wu, b * 16, (k & 1) * 256, sb + BAR_FULL + 8 * (i & 1), (HINT & 128) && (i & 3) == 3);
                }
                if (i) {
                    mbar_wait(sb + BAR_FULL + 8 * (~i & 1), ((i - 1) >> 1) & 1);
                    bulk_store(g_wf + (b - 1) * SLOT, sb + (~i & 1) * SLOT, SLOT, HINT & 256);
                    asm volatile("cp.async.bulk.commit_group;" ::: "memory");
                }
            }
            asm volatile("cp.async.bulk.wait_group 0;" ::: "memory");
            fence_async_global();
            TS(4);
        } else if (warp < 8) {
            const uint32_t c2 = __ldg(reinterpret_cast<const uint32_t*>(P.c) + tid), ep = __ldcg(&g_sync.epoch[0]) + 1;
            uint32_t* sc = reinterpret_cast<uint32_t*>(smem + 6 * SLOT);
            sc[tid] = pack2(bf_lo(c2) * sigmoid(bf_lo(c2)), bf_hi(c2) * sigmoid(bf_hi(c2)));
            bar_sync(1, 256);
            const uint32_t a = sb + (warp >> 1) * 8192 + ((lane >> 4) * 8 + (lane & 7)) * 128, ch = (warp & 1) * 4 + ((lane >> 3) & 1);
#pragma unroll 1
            for (int ps = 0; ps < 3; ps++) {
                float d[2][4] = {};
#pragma unroll 1
                for (int bt = 0; bt < 8; bt++) {
                    slot_wait(sb + BAR_FULL, ph, sl);
#pragma unroll
                    for (int i = 0; i < 8; i++) {
                        uint32_t w[4];
                        asm volatile("ldmatrix.sync.aligned.m8n8.x4.trans.shared.b16 {%0, %1, %2, %3}, [%4];" : "=r"(w[0]), "=r"(w[1]), "=r"(w[2]), "=r"(w[3])
                                     : "r"(a + sl * SLOT + (i >> 1) * 2048 + (((ch + 2 * (i & 1)) ^ (lane & 7)) << 4)) : "memory");
                        mma16816(d[i & 1], w, sc[bt * 32 + (i >> 1) * 8 + (lane & 3)], sc[bt * 32 + (i >> 1) * 8 + 4 + (lane & 3)]);
                    }
                    __syncwarp();
                    mbar_arrive_if(sb + BAR_EMPTY + 8 * sl, lane == 0);
                    if (++sl == 6) sl = 0;
                }
                const float v = (lane & 2) ? ((lane & 1) ? d[1][2] : d[1][0]) : ((lane & 1) ? d[0][2] : d[0][0]);
                const int col = (rb - NCTA) * 256 + warp * 32 + (lane & 3) * 8 + (lane >> 2);
                if (ps == 0) st_pub(g_mod1 + col, (pack2(0.f, v) & 0xffff0000u) | (ep & 0xffffu), true);
                else g_mod[ps * 1024 + col] = __float2bfloat16_rn(v);
                if (warp == 0) TS(1 + ps);
            }
        }
        __syncthreads();
        if (tid < 2) flag_add(&g_sync.cnt[7 * 8]);
        return;
    }

    if (wg == 2) {
        asm volatile("setmaxnreg.dec.sync.aligned.u32 40;");
        if (warp == 8) {
            const uint32_t rank = j & 1, half = rank * 16384;
            uint32_t eph = 0, r = 0;
            *reinterpret_cast<volatile uint32_t*>(smem + SM_EP + 20) = 0;
#pragma unroll 1
            for (int hp = 0; hp < 2; hp++) {
                uint32_t wtab = w_table(hp), atab = a_table(hp);
                const int hc = 4 * grp + 2 * hp;
#pragma unroll 1
                for (int u = 3 - 3 * hp; u < 16; u++) {
                    if (hp && u < 4) {
                        const uint32_t ws = (wtab >> (4 * u)) & 15;
                        slot_acquire(sb, eph, ws);
                        load_tile(sb, ws, 0, tw, u * 128, hc, false, HINT & 1);
                        PT();
                    }
                    if (hp == 1 && (u & 7) == 4) mbar_wait(sb + BAR_FLAG + 24 + (u & 8), 0);
                    const uint32_t as = a_next(atab);
                    slot_acquire(sb, eph, as);
                    load_tile(sb, as, half, &tm_ckv, ((u & 12) + (j >> 1)) * 128, (u & 3) * 2 + rank, true, (HINT & 8) && hp);
                    PT();
                    if (hp == 1 && (u | 2) == 3 && lane == 0)
                        asm volatile("red.relaxed.gpu.global.add.u32 [%0], 1;" ::"l"(&g_sync.cnt[(grp * 8 + 3 + (u >> 1)) * 8]) : "memory");
                }
                const uint8_t* src = g_h + (15 - j) * 4 * SLOT;
#pragma unroll 1
                for (int u = 0; u < 8; u++) {
                    if (u == 0 || u == KVG) {
                        mbar_wait(sb + BAR_FLAG + (u ? 8 + 32 * hp : 0), 0);
                        fence_async_global();
                    }
                    if (u < 4) {
                        const uint32_t ws = (wtab >> (4 * u)) & 15;
                        slot_acquire(sb, eph, ws);
                        load_tile(sb, ws, 0, &tm_wq, u * 128, hc, false, HINT & 1);
                        PT();
                    }
                    const uint32_t as = a_next(atab);
                    slot_acquire(sb, eph, as);
                    load_bulk(sb, as, 0, src, SLOT, false, (HINT & 8) && hp);
                    PT();
                    src += u == 3 ? (8 * j - 63) * SLOT : SLOT;
                }
                const int step = hp ? -2 * SLOT : 2 * SLOT;
                src = g_KV + (size_t)(grp * 32 + 30 * hp) * SLOT + half - step;
#pragma unroll 1
                for (int n = 0; n <= 17; n++) {
                    if (n == 8) {
                        mbar_wait(sb + BAR_FLAG + 16 + 32 * hp, 0);
                        fence_async_global();
                    }
                    const uint8_t* v = src + SLOT;
                    src += n < 16 - j ? step : n == 16 - j ? (2 * j - 15) * step : -step;
                    if (n < 17) {
                        slot_acquire(sb, eph, r);
                        if (n != 15 - (j & 6)) load_bulk(sb, r, half, src, SLOT / 2, true, HINT & 4);
                        else load_bulk(sb, r, 0, src - half, SLOT, false, HINT & 4);
                        PT();
                        r = ring_next(r);
                    }
                    if (n) {
                        slot_acquire(sb, eph, r);
                        if (n != 16 - (j & 6)) load_bulk(sb, r, half, v, SLOT / 2, true, HINT & 4);
                        else load_bulk(sb, r, 0, v - half, SLOT, false, HINT & 4);
                        PT();
                        r = ring_next(r);
                    }
                    asm volatile("st.volatile.shared.u32 [%0], %1;" ::"r"(sb + SM_EP + 16), "r"(18 * hp + n + 1) : "memory");
                }
            }
            uint32_t otab = O_TABLE, ready = 0;
#pragma unroll 1
            for (int i = 0; i < 17; i++) {
                const bool dyn = i >= 8 && i < 15;
                const uint32_t want = dyn ? 15u << (4 * (i - 8)) : 1u << max(i + 14, 28);
                if (!(ready & want)) {
                    do {
                        asm volatile("ld.acquire.cta.shared.u32 %0, [%1];" : "=r"(ready) : "r"(sb + SM_EP + 20) : "memory");
                        ready = __shfl_sync(0xffffffffu, ready, 0);
                    } while (!(ready & want));
                    fence_async_global();
                }
                const int head = o_head(dyn ? (ready >> (4 * (i - 8))) & 15 : i, kh);
                const uint32_t as = o_next(otab), ws = o_next(otab), off = i < 15 ? half : kh * 16384;
                slot_acquire(sb, eph, as);
                load_bulk(sb, as, off, g_ctx + (size_t)(ort * 32 + head) * SLOT + off, SLOT / 2, i < 15, HINT & 16);
                if (i == 15) load_tile(sb, as, off ^ 16384, &tm_x, ort * 128 + kh * 64, cq * 2, false, false);
                if (i == 16) load_bulk(sb, as, off ^ 16384, P.wdown + min(rb, NFFN - 1) * 8192, SLOT / 2, false, false);
                PT();
                slot_acquire(sb, eph, ws);
                load_tile(sb, ws, 0, &tm_wo, head * 128, cq * 2, false, HINT & 2);
                PT();
                if (i == 0) o_next(otab);
            }
            if (rb < NFFN) {
                slot_acquire(sb, eph, 5);
                load_bulk(sb, 5, 0, g_wf + rb * SLOT, SLOT, false, false);
            }
        } else if (warp == 9) {
            *reinterpret_cast<volatile uint32_t*>(smem + SM_EP + 16) = 0;
            l2_prefetch(P.ckv + rb * 2048, 4096);
            mbar_watch(sb + BAR_FULL, 0);
            l2_prefetch(P.ckv + 512 * 512 + rb * 2048, 4096);
            mbar_watch(sb + BAR_FULL + 8 * XPF, 0);
            l2_prefetch(P.x + rb * 8192, 16384);
            mbar_watch(sb + BAR_FULL + 8 * 4, 0);
            l2_prefetch(P.ckv + 1024 * 512 + rb * 4096, 8192);
            TS(40);
#pragma unroll 1
            for (int i = 0; i < 15; i++) {
                step_watch(sb + SM_EP + 16, i == 0 ? 0 : i < 5 ? PFA + i : 13 + PFB + i);
                if (i == 12) mbar_watch(sb + BAR_FLAG + 8 * 7, 0);
                const int rf = min(rb, NFFN - 1);
                const uint8_t* p = i == 3 ? reinterpret_cast<const uint8_t*>(P.ckv) + rb * 16384
                                 : i == 4 ? g_h + rb * 16384
                                 : i < 9 ? g_ctx + (size_t)(ort * 32 + o_head(cq + 2 * ((i - 5) & 2), kh)) * SLOT + (i & 1) * 16384
                                 : i < 11 ? reinterpret_cast<const uint8_t*>(P.wo) + (grp * 16 + (~i & 1) * 8 + j) * 16384
                                 : i == 11 ? reinterpret_cast<const uint8_t*>(P.x) + rb * 16384
                                 : i == 12 ? reinterpret_cast<const uint8_t*>(P.wdown) + rf * 16384 : g_wf + rf * SLOT + (i & 1) * 16384;
                if (i >= 3) l2_prefetch(p, 16384);
                else if ((i | j) & 1) tma3d_prefetch(i == 1 ? tw : &tm_wq, (j >> 1) * 128, grp * 4 + (i ? 2 : 0));
            }
            const uint32_t v = lds32(sb + SM_EP) - 1;
            sts128(sb + SM_RED + lane * 16, make_uint4(v, v, v, v));
            fence_async_smem();
            __syncwarp();
#pragma unroll 1
            for (int i = 0; i < OB / 32; i++) bulk_store(g_out + rb * OB + i * 32, sb + SM_RED, 512, false);
            asm volatile("cp.async.bulk.commit_group;\ncp.async.bulk.wait_group 0;" ::: "memory");
            fence_async_global();
            __syncwarp();
            mbar_arrive_if(sb + BAR_PF, lane == 0);
            if (lane == 0) mbar_watch(sb + BAR_END, 0);
        } else {
            const uint32_t ep = __ldcg(&g_sync.epoch[0]) + 1;
            asm volatile("st.shared.u32 [%0], %1;" ::"r"(sb + SM_EP), "r"(ep) : "memory");
            mbar_wait(sb + BAR_FULL + 8 * 4, 0);
            {
                uint4 v[4];
                for (;;) {
                    uint32_t bad = 0;
#pragma unroll
                    for (int k = 0; k < 4; k++) v[k] = ld_poll(reinterpret_cast<const uint4*>(g_mod1) + (warp & 1) * 128 + k * 32 + lane);
#pragma unroll
                    for (int k = 0; k < 4; k++) bad |= (v[k].x ^ ep) | (v[k].y ^ ep) | (v[k].z ^ ep) | (v[k].w ^ ep);
                    if (__all_sync(0xffffffffu, (bad & 0xffff) == 0)) break;
                    __nanosleep(100);
                }
                const uint32_t one = (warp & 1) ? ONE2 : 0x80008000u;
#pragma unroll
                for (int k = 0; k < 4; k++)
                    *reinterpret_cast<uint2*>(smem + SM_TAB + (warp & 1) * 1024 + k * 256 + lane * 8) =
                        make_uint2(badd(__byte_perm(v[k].x, v[k].y, 0x7632), one), badd(__byte_perm(v[k].z, v[k].w, 0x7632), one));
            }
            __syncwarp();
            mbar_arrive_if(sb + BAR_FLAG + 8 * 8, lane == 0);
            if (warp == 10) {
#pragma unroll 1
                for (int i = 0; i < 9; i++) {
                    mbar_sleep(sb + BAR_DONE + 8 * i);
                    if (lane == 0) flag_add(i && ((i - 1) & 2) ? &g_sync.ctxcnt[((i & 1) ? 15 - j : j) * 32 + 2 * grp + (i > 4)] : &g_sync.cnt[(grp * 8 + i) * 8]);
                    if (i == 0) TS(43);
                }
            } else {
                TS(42);
#pragma unroll 1
                for (int i = 0; i < 8; i++) {
                    mbar_sleep(sb + BAR_DONE + 8 * (i == 7 ? 6 : i == 4 ? 3 : i));
                    if (lane < 2) flag_wait(&g_sync.cnt[((i == 0 ? (lane ? j : 15 - j) : i == 7 ? 0 : grp) * 8 + i) * 8], 8 * ep);
                    __syncwarp();
                    mbar_arrive_if(sb + BAR_FLAG + 8 * i, lane == 0 && i < 7);
                    TS(48 + i);
                }
                const uint32_t *mp = reinterpret_cast<const uint32_t*>(g_mod) + lane, *wp = reinterpret_cast<const uint32_t*>(P.wr) + lane;
                float ra = 0.f, rs = 0.f;
#pragma unroll 1
                for (int k = 0; k < 256; k += 32) {
                    const uint32_t ga = __ldcg(mp + 512 + k), sh = __ldcg(mp + 768 + k), c1 = badd(__ldcg(mp + 1024 + k), ONE2);
                    const uint32_t gb = __ldcg(mp + 1280 + k), ww = __ldg(wp + k);
                    const uint32_t a = bmul(c1, ww);
                    ra += bf_lo(a) + bf_hi(a);
                    rs = fmaf(bf_lo(sh), bf_lo(ww), fmaf(bf_hi(sh), bf_hi(ww), rs));
                    if (k >> 6 == cq) {
                        sts128(sb + SM_TAB + ((k & 32) + lane) * 16, make_uint4(ga << 16, ga & 0xffff0000u, a, 0));
                        sts128(sb + SM_TAB + 1024 + ((k & 32) + lane) * 16, make_uint4(c1, sh, gb, 0));
                    }
                }
#pragma unroll 1
                for (int o = 16; o > 0; o >>= 1) {
                    ra += __shfl_xor_sync(0xffffffffu, ra, o);
                    rs += __shfl_xor_sync(0xffffffffu, rs, o);
                }
                *reinterpret_cast<float2*>(smem + SM_EP + 8) = make_float2(ra, rs);
                __syncwarp();
                mbar_arrive_if(sb + BAR_FLAG + 8 * 7, lane == 0);
                const uint32_t* f = &g_sync.ctxcnt[ort * 32 + o_head(min(lane, 16), kh)];
                uint32_t ready = -(j & 1), list = 0, sh = 0, qa;
                asm("mapa.shared::cluster.u32 %0, %1, %2;" : "=r"(qa) : "r"(sb + SM_EP + 20), "r"(lane & 1));
                while (ready != ~0u) {
                    uint32_t v;
                    asm volatile("ld.acquire.gpu.global.u32 %0, [%1];" : "=r"(v) : "l"(f) : "memory");
                    const uint32_t now = __ballot_sync(0xffffffffu, (int)(v - ep) >= 0);
#pragma unroll 1
                    for (uint32_t fresh = now & ~ready & 0x7f00; fresh; fresh &= fresh - 1, sh += 4) list |= (__ffs(fresh) - 1) << sh;
                    list |= (((now & 0xff) + 1) >> 8 << 28) | ((now & 0x18000) << 14);
                    if (now != ready && lane < 2) asm volatile("st.relaxed.cluster.shared::cluster.u32 [%0], %1;" ::"r"(qa), "r"(list) : "memory");
                    if ((now & 0xff) == 0xff) mbar_sleep(sb + BAR_DONE + 8 * 7);
                    ready = now;
                    __nanosleep(POLL_NS);
                }
                TS(45);
            }
        }
    } else {
        const bool elected = (tid & 127) == 0, rel = (tid & 95) == 0;
        uint32_t eb;
        asm("mapa.shared::cluster.u32 %0, %1, %2;" : "=r"(eb) : "r"(sb + BAR_EMPTY), "r"(warp & 1));
        const int g = lane >> 2, c4 = lane & 3;
        uint32_t toff = warp * 4096 + g * 64 + ((c4 ^ (g >> 1)) << 4);
        uint32_t fph = 0x3f, r = 0;
        if (wg == 1) bar_arrive(1, 256);
        const uint32_t kd = desc_k(sb), wd = desc_mn(sb), vd = ((sb & 0x3ffff) >> 4) | (32u << 16);
        const int nL = 16 - j, hn = nL - 1 + wg;
        float s[64], o[64], li[2] = {0.f, 0.f};
        uint32_t cimg = 0;
        const float sc = (j & 1) ? 1.f : SM_C;
#pragma unroll 1
        for (int q = 0; q < 3; q++) {
            const uint32_t as = (0x635u >> (4 * q)) & 15;
            mbar_wait(sb + BAR_FULL + 8 * q, 0);
            mbar_wait(sb + BAR_FULL + 8 * as, 0);
            bar_sync(1 + wg, 256);
            gemm_issue<false>(s, kd + wg * 512 + as * (SLOT / 16), wd + q * (SLOT / 16), q, false);
            bar_arrive(2 - wg, 256);
            wg_wait<0>();
            release_if(eb, as, rel);
        }
        {
            const int xrow = rb * 16 + warp * 2;
            const uint4* xp = reinterpret_cast<const uint4*>(P.x) + xrow * 64;
            const uint32_t img = (grp * 32 + j) * SLOT;
            uint32_t x[16], x0[2];
            float st[4] = {0.f, 0.f, 0.f, 0.f};
            mbar_wait(sb + BAR_FULL + 8 * 4, 0);
#pragma unroll
            for (int q = 3; q < 8; q++) {
                const uint32_t ws = (0x4210u >> (4 * (q & 3))) & 15, as = (0x635u >> (4 * (q % 3))) & 15;
                mbar_wait(sb + BAR_FULL + 8 * as, (q / 3) & 1);
                bar_sync(1 + wg, 256);
                if (q == 3) gemm_issue<false>(s, kd + wg * 512 + as * (SLOT / 16), wd + ws * (SLOT / 16), 1, false);
                else if (q == 4) gemm_issue<true>(o, kd + wg * 512 + as * (SLOT / 16), wd + ws * (SLOT / 16), 0, false);
                else gemm_issue<false>(o, kd + wg * 512 + as * (SLOT / 16), wd + ws * (SLOT / 16), 1, false);
                bar_arrive(2 - wg, 256);
                sched_fence(fph, P.zero);
                if (q > 3) reg_fence(s);
                if (q == 3) {
                    asm volatile("setmaxnreg.inc.sync.aligned.u32 232;");
#pragma unroll
                    for (int i = 0; i < 4; i++)
                        asm volatile("ld.global.nc.v4.u32 {%0, %1, %2, %3}, [%4];" : "=r"(x[4 * i]), "=r"(x[4 * i + 1]), "=r"(x[4 * i + 2]), "=r"(x[4 * i + 3])
                                     : "l"(xp + lane + 32 * i) : "memory");
#pragma unroll
                    for (int i = 0; i < 2; i++) asm volatile("ld.global.nc.u32 %0, [%1];" : "=r"(x0[i]) : "l"(xp + 64 * i) : "memory");
                }
                if (q == 4) {
                    img_store_global<0>(img, toff, s, sc, sc);
#pragma unroll
                    for (int k = 0; k < 16; k++) {
                        const float d0 = bf_lo(x[k]) - bf_lo(x0[k >> 3]), d1 = bf_hi(x[k]) - bf_lo(x0[k >> 3]);
                        st[k >> 3] += d0 + d1;
                        st[2 + (k >> 3)] = fmaf(d0, d0, fmaf(d1, d1, st[2 + (k >> 3)]));
                    }
#pragma unroll
                    for (int i = 0; i < 4 * NSH; i++) st[i & 3] += __shfl_xor_sync(0xffffffffu, st[i & 3], 1 << (i >> 2));
                    reg_fence(st);
                }
                if (q == 5) {
#pragma unroll
                    for (int i = 4 * NSH; i < 20; i++) st[i & 3] += __shfl_xor_sync(0xffffffffu, st[i & 3], 1 << (i >> 2));
                    img_store_global<1>(img, toff, s, sc, sc);
#pragma unroll
                    for (int i = 0; i < 2; i++) {
                        const float d = st[i] * (1.f / 512.f);
                        st[2 + i] = ln_rstd(fmaxf(fmaf(-d, d, st[2 + i] * (1.f / 512.f)), 0.f));
                        x0[i] = pack2(bf_lo(x0[i]) + d, bf_lo(x0[i]) + d);
                    }
                    reg_fence(st);
                    reg_fence(x0);
                }
                if (q > 5) {
                    if (q == 6) mbar_wait(sb + BAR_FLAG + 8 * 8, 0);
                    const uint4 a = lds128(sb + SM_TAB + 1024 + (q & 1) * 512 + lane * 16), c = lds128(sb + SM_TAB + (q & 1) * 512 + lane * 16);
                    uint8_t* hp = g_h + (grp * 8 + (q & 1) * 4 + (lane >> 3)) * 16384 + (xrow & 127) * 128;
#pragma unroll
                    for (int i = 0; i < 2; i++) {
                        const uint32_t* y = x + 8 * i + 4 * (q & 1);
                        *reinterpret_cast<uint4*>(hp + i * 128 + (((lane ^ xrow ^ i) & 7) << 4)) =
                            make_uint4(ln_apply(y[0], x0[i], st[2 + i], a.x, c.x), ln_apply(y[1], x0[i], st[2 + i], a.y, c.y),
                                       ln_apply(y[2], x0[i], st[2 + i], a.z, c.z), ln_apply(y[3], x0[i], st[2 + i], a.w, c.w));
                    }
                    if (q == 7) {
                        __syncwarp();
                        mbar_arrive_if(sb + BAR_DONE, lane == 0);
                    }
                    if (q == 6) img_store_global<2>(img, toff, s, sc, sc);
                    else img_store_global<3>(img, toff, s, sc, sc);
                }
                if (q < 7) {
                    sched_fence(fph, P.zero);
                    wg_wait<0>();
                    release_if(eb, as, rel);
                }
            }
        }
        uint32_t pend = 0x73;
        uint32_t p[32] = {};
#pragma unroll 1
        for (int hp = 0; hp < 2; hp++) {
            float m[2] = {0.f, 0.f}, l[2] = {0.f, 0.f}, t[4] = {0.f, 0.f, 0.f, 0.f};
            bool shifted = false, bad = false, plain = false;
            uint32_t qa = desc_k(sb + 5 * SLOT + (wg ^ 1) * 8192);
            const uint32_t limg = (512 + (15 - j) * 32 + 2 * grp + hp) * SLOT;
            {
                const int step = hp ? -8 * SLOT : 8 * SLOT;
                uint32_t img = (grp * 32 + (hp ? j ^ 30 : j) + 8) * SLOT;
                const uint32_t wtab = w_table(hp);
                uint32_t atab = hp ? 0x562u : 0x356u;
#pragma unroll 1
                for (int u = 2 - 2 * hp; u < 6; u += 2) {
                    proj_tile<false>(s, o, u, !u, sb, wg, eb, rel, fph, wtab, atab, pend, u ? img : cimg, toff, u ? sc : li[0], u ? sc : li[1], p);
                    __syncwarp();
                    mbar_arrive_if(sb + BAR_DONE + 4 * u + 32 * hp, lane == 0);
                    if (elected) TS(1 + 10 * hp + u + 20 * wg);
                    proj_tile<true>(o, s, u + 1, 0, sb, wg, eb, rel, fph, wtab, atab, pend, img + step, toff, sc, sc, p);
                    if (elected) TS(2 + 10 * hp + u + 20 * wg);
                    img += 2 * step;
                }
            }
            asm volatile("" : "+r"(toff));
            if (elected) TS(6 + 10 * hp + 20 * wg);
            fence_async_smem();
            slot_wait(sb + BAR_FULL, fph, r);
            step_retire(eb, rel, pend);
            reg_fence(o);
            int n = -1;
#pragma unroll 1
            for (;;) {
                while (bad || plain) {
                    float d0 = m[0], d1 = m[1];
                    if (bad) {
                        float a0, a1;
                        softmax_remax(s, m, n == 0 || n == nL, d0, d1, a0, a1);
                        shifted = true;
                        l[0] *= a0;
                        l[1] *= a1;
#pragma unroll
                        for (int i = 0; i < 64; i++) o[i] *= (i & 2) ? a1 : a0;
                    }
#pragma unroll
                    for (int i = 0; i < 64; i++) s[i] -= (i & 2) ? d1 : d0;
                    softmax_exp<0, 16>(s, p, t);
                    t[0] += t[1];
                    t[2] += t[3];
                    bad = !bad && softmax_unsafe(t[0], t[2], false);
                    plain = false;
                }
#pragma unroll 1
                do {
                    l[0] += t[0];
                    l[1] += t[2];
                    if (++n > 16) break;
                    const uint32_t ks = r;
                    uint32_t vs = ring_next(r);
                    r = ring_next(vs);
                    bar_sync(1 + wg, 256);
                    const float x = (float)((warp & 3) * 16 + g - 2 * c4);
                    if (n == hn) {
                        float sh[32];
                        qk_issue(sh, qa, kd + ks * (SLOT / 16));
                        slot_wait(sb + BAR_FULL, fph, vs);
                        pv_issue(o, p, vd + vs * (SLOT / 16), 1, false);
                        bar_arrive(2 - wg, 256);
                        wg_wait<1>();
                        reg_fence(sh);
                        tri_mask_copy(s, sh, x);
                        release_if(eb, ks, rel);
                        release_if(eb, 5 + wg, rel && (!wg || n == 16));
                        if (!wg) qa += SLOT / 16;
                        float e[4 * EARLY];
#pragma unroll
                        for (int i = 0; i < 4 * EARLY; i++) {
                            e[i] = ex2(s[i]);
                            t[i & 3] = i < 4 ? e[i] : t[i & 3] + e[i];
                        }
                        reg_fence(e);
                        slot_wait(sb + BAR_FULL, fph, r);
                        wg_wait<0>();
                        reg_fence(o);
                        reg_fence(e);
                        release_if(eb, vs, rel);
#pragma unroll
                        for (int i = 0; i < 2 * EARLY; i++) p[i] = pack2(e[2 * i], e[2 * i + 1]);
                        softmax_exp<EARLY, 8>(s, p, t);
                        if (wg) {
                            ctx_store(limg, toff, o, rcp(quad_sum(l[0])), rcp(quad_sum(l[1])));
                            __syncwarp();
                            mbar_arrive_if(sb + BAR_DONE + 24 + 32 * hp, lane == 0);
                            l[0] = l[1] = m[0] = m[1] = 0.f;
                            shifted = false;
                        }
                        t[0] += t[1];
                        t[2] += t[3];
                        plain = shifted;
                        if (plain) break;
                        bad = softmax_unsafe(t[0], t[2], wg);
                        continue;
                    }
                    if (n == nL) {
                        qk_issue(s, qa, kd + ks * (SLOT / 16));
                        slot_wait(sb + BAR_FULL, fph, vs);
                        pv_issue(o, p, vd + vs * (SLOT / 16), 1, true);
                        bar_arrive(2 - wg, 256);
                        const float i0 = rcp(quad_sum(l[0])), i1 = rcp(quad_sum(l[1]));
                        wg_wait<1>();
                        reg_fence(s);
                        release_if(eb, ks, rel);
                        release_if(eb, 6, rel && n == 16);
                        tri_mask(s, x);
                        float e[4 * EARLY2];
#pragma unroll
                        for (int i = 0; i < 4 * EARLY2; i++) {
                            e[i] = ex2(s[i]);
                            t[i & 3] = i < 4 ? e[i] : t[i & 3] + e[i];
                        }
                        reg_fence(e);
                        reg_fence(s);
                        reg_fence(t);
                        slot_wait(sb + BAR_FULL, fph, r);
                        sched_fence(fph, P.zero);
                        wg_wait<0>();
                        reg_fence(o);
                        reg_fence(e);
                        release_if(eb, vs, rel);
#pragma unroll
                        for (int i = 0; i < 2 * EARLY2; i++) p[i] = pack2(e[2 * i], e[2 * i + 1]);
                        softmax_exp<EARLY2, MSPLIT>(s, p, t);
                        ctx_store(limg, toff, o, i0, i1);
                        reg_fence(t);
                        reg_fence(s);
                        softmax_exp<MSPLIT, 16>(s, p, t);
                        __syncwarp();
                        mbar_arrive_if(sb + BAR_DONE + 24 + 32 * hp, lane == 0);
                        l[0] = l[1] = m[0] = m[1] = 0.f;
                        shifted = false;
                        t[0] += t[1];
                        t[2] += t[3];
                        bad = __any_sync(0xffffffffu, fmaxf(t[0], t[2]) > SM_HI || fminf(t[0], t[2]) < SM_LO);
                        continue;
                    }
                    qk_issue(s, qa, kd + ks * (SLOT / 16));
                    if (n == 0) {
                        r = vs;
                        vs = 4 - hp;
                        slot_wait(sb + BAR_FULL, fph, 6);
                        gemm_issue<false>(o, qa + SLOT / 16, wd + vs * (SLOT / 16), 1, false);
                    } else {
                        slot_wait(sb + BAR_FULL, fph, vs);
                        if (n == 1) {
                            wg_wait<1>();
                            reg_fence(o);
                            const uint32_t a = sb + 6 * SLOT + q_off(toff);
#pragma unroll
                            for (int i = 0; i < 8; i++) {
                                const int k = 16 * (i >> 1) + 2 * (i & 1);
                                sts128(a + (i >> 2) * 16384 + (i & 2) * 256 + (i & 1) * 1024,
                                       make_uint4(pack2(o[k], o[k + 1]), pack2(o[k + 4], o[k + 5]), pack2(o[k + 8], o[k + 9]), pack2(o[k + 12], o[k + 13])));
                            }
                        }
                        pv_issue(o, p, vd + vs * (SLOT / 16), n != 1 && n != nL + 1, n == hn + 1);
                    }
                    bar_arrive(2 - wg, 256);
                    wg_wait<1>();
                    reg_fence(s);
                    release_if(eb, ks, rel);
                    release_if(eb, 6, rel && n == 16);
                    if (n == nL - 1) {
                        tri_mask(s, x);
                        release_if(eb, 5, rel);
                        qa += SLOT / 16;
                    }
                    if (n == 2) fence_async_smem();
                    if (shifted) {
                        slot_wait(sb + BAR_FULL, fph, r);
                        wg_wait<0>();
                        reg_fence(o);
                        release_if(eb, vs, rel);
                        plain = true;
                        break;
                    }
                    float e[4 * EARLY];
#pragma unroll
                    for (int i = 0; i < 4 * EARLY; i++) {
                        e[i] = ex2(s[i]);
                        t[i & 3] = i < 4 ? e[i] : t[i & 3] + e[i];
                    }
                    reg_fence(e);
                    slot_wait(sb + BAR_FULL, fph, r);
                    wg_wait<0>();
                    reg_fence(o);
                    reg_fence(e);
                    release_if(eb, vs, rel);
#pragma unroll
                    for (int i = 0; i < 2 * EARLY; i++) p[i] = pack2(e[2 * i], e[2 * i + 1]);
                    softmax_exp<EARLY, 16>(s, p, t);
                    t[0] += t[1];
                    t[2] += t[3];
                    bad = __any_sync(0xffffffffu, fmaxf(t[0], t[2]) > SM_HI || (n == 0 && fminf(t[0], t[2]) < SM_LO));
                } while (!bad);
                if (!bad && !plain) break;
            }
            asm volatile("" : "+r"(toff));
            const uint32_t vs = r, ga = desc_k(sb + (hp ? 2 * (wg ^ kh ^ 1) : wg) * 8192);
            r = ring_next(r);
            slot_wait(sb + BAR_FULL, fph, 5);
            slot_wait(sb + BAR_FULL, fph, r);
            bar_sync(1 + wg, 256);
            gemm_issue<true>(s, ga + 5 * (SLOT / 16), wd + r * (SLOT / 16), 0, hp);
            pv_issue(o, p, vd + vs * (SLOT / 16), j, hn == 16);
            bar_arrive(2 - wg, 256);
            li[0] = rcp(quad_sum(l[0]));
            li[1] = rcp(quad_sum(l[1]));
            cimg = limg + (2 * j - 15) * 32 * SLOT + (wg ? -16384 : 16384);
            wg_wait<1>();
            release_if(eb, 5, rel);
            release_if(eb, r, rel && hp);
            wg_wait<0>();
            release_if(eb, vs, rel);
            reg_fence(o);
            img_store_global<0>(cimg, toff, o, li[0], li[1]);
            pend = 0x77;
            if (elected) TS(8 + 10 * hp + 20 * wg);
        }
        uint32_t otab = 0x2351604u;
        const uint32_t oa = desc_k(sb + (wg ^ kh ^ 1) * 16384);
        const int t7 = tid & 127, w4 = warp & 3, row = ort * 128 + kh * 64 + w4 * 16 + g;
#pragma unroll 1
        for (int i = 1; i < 15 - wg; i++) {
            const uint32_t as = o_next(otab), ws = o_next(otab);
            slot_wait(sb + BAR_FULL, fph, as);
            slot_wait(sb + BAR_FULL, fph, ws);
            bar_sync(1 + wg, 256);
            gemm_issue<false>(s, oa + as * (SLOT / 16), wd + ws * (SLOT / 16), 1, true);
            bar_arrive(2 - wg, 256);
            wg_wait<1>();
            reg_fence(o);
            if (i == 1) img_store_global<1>(cimg, toff, o, li[0], li[1]);
            if (i == 2) {
                img_store_global<2>(cimg, toff, o, li[0], li[1]);
                img_store_global<3>(cimg, toff, o, li[0], li[1]);
                __syncwarp();
                mbar_arrive_if(sb + BAR_DONE + 64, lane == 0);
            }
            wg_wait<0>();
            release_if(eb, as, rel);
            release_if(eb, ws, rel);
        }
        mbar_wait(sb + BAR_PF, 0);
        const uint32_t ep = lds32(sb + SM_EP);
        uint32_t eb2 = sb + BAR_END;
        if (wg == 0) {
            reg_fence(s);
            if (elected) TS(9);
            TT(1);
#pragma unroll
            for (int v = 0; v < 8; v++)
                st_pub(g_out + rb * OB + v * 128 + t7, make_uint4((pack2(s[8 * v], s[8 * v + 1]) & ~1u) | (ep & 1), pack2(s[8 * v + 2], s[8 * v + 3]),
                                                                      pack2(s[8 * v + 4], s[8 * v + 5]), pack2(s[8 * v + 6], s[8 * v + 7])), true);
            constexpr uint32_t s1 = 5, s2 = 6;
            bar_sync(4, 256);
            uint32_t wf[64];
            float wn[64];
            if (rb < NFFN) {
                slot_wait(sb + BAR_FULL, fph, s1);
                const uint32_t a = sb + s1 * SLOT + (w4 * 128 + (lane >> 4) * 8 + (lane & 7)) * 32 + (((lane >> 3) ^ (lane >> 2)) & 1) * 16;
#pragma unroll
                for (int i = 0; i < 16; i++)
                    asm volatile("ldmatrix.sync.aligned.m8n8.x4.trans.shared.b16 {%0, %1, %2, %3}, [%4];"
                                 : "=r"(wf[4 * i]), "=r"(wf[4 * i + 1]), "=r"(wf[4 * i + 2]), "=r"(wf[4 * i + 3])
                                 : "r"(a + (i >> 3) * 16384 + (i & 7) * 512) : "memory");
                slot_wait(sb + BAR_FULL, fph, s2);
#pragma unroll
                for (int i = 0; i < 16; i++) {
                    const uint2 w = *reinterpret_cast<const uint2*>(smem + s2 * SLOT + (kh ^ 1) * 16384 + i * 1024 + t7 * 8);
                    wn[4 * i] = bf_lo(w.x); wn[4 * i + 1] = bf_hi(w.x); wn[4 * i + 2] = bf_lo(w.y); wn[4 * i + 3] = bf_hi(w.y);
                }
                reg_fence(wn);
            }
            const uint32_t gbf = __ldcg(reinterpret_cast<const uint32_t*>(g_mod) + 1280 + rb * 2 + (tid & 1));
            if (elected) TS(10);
            TT(2);
            float* sred = reinterpret_cast<float*>(smem + SM_RED);
            uint32_t best = ep ^ 1, all;
            bool fresh;
            do {
                if (warp == 0) {
                    const uint2 k = best_key(g_key + cq * 128, lane, ep, best, rb < NFFN ? SPEC : 32);
                    *reinterpret_cast<uint2*>(smem + SM_EP + 24) = k;
                    mbar_arrive_if(sb + BAR_BEST, lane == 0 && k.y);
                }
                bar_sync(3, 128);
                const uint2 k = *reinterpret_cast<const uint2*>(smem + SM_EP + 24);
                fresh = k.x != best;
                best = k.x;
                all = k.y;
                TT(3);
                if (!fresh || rb >= NFFN) break;
                const uint4* cp = g_cand + ((~best >> 9) & 127) * 192;
                uint4 cv[6];
                for (;;) {
                    uint32_t bad = 0;
#pragma unroll
                    for (int v = 0; v < 6; v++) cv[v] = ld_poll(cp + w4 * 24 + v * 4 + c4);
#pragma unroll
                    for (int v = 0; v < 6; v++) bad |= cv[v].w ^ ep;
                    if (__all_sync(0xffffffffu, bad == 0)) break;
                }
            TT(4);
                float d[4][4] = {};
#pragma unroll
                for (int k = 0; k < 8; k++) {
                    const uint32_t b0 = (&cv[(2 * k) / 3].x)[(2 * k) % 3], b1 = (&cv[(2 * k + 1) / 3].x)[(2 * k + 1) % 3];
                    mma16816(d[k & 1], wf + 4 * k, b0, b1);
                    mma16816(d[2 + (k & 1)], wf + 32 + 4 * k, b0, b1);
                }
                const float u = (c4 & 2) ? ((c4 & 1) ? d[2][2] + d[3][2] : d[2][0] + d[3][0]) : ((c4 & 1) ? d[0][2] + d[1][2] : d[0][0] + d[1][0]);
                sred[w4 * 32 + c4 * 8 + g] = u;
                bar_sync(3, 128);
                const float v = rbf((sred[lane] + sred[32 + lane]) + (sred[64 + lane] + sred[96 + lane]));
                const float act = rbf(rbf(v * sigmoid(v)) * __shfl_down_sync(0xffffffffu, v, 16));
                float y[4] = {0.f, 0.f, 0.f, 0.f};
#pragma unroll
                for (int k = 0; k < 16; k++) {
                    const float a = __shfl_sync(0xffffffffu, act, k);
#pragma unroll
                    for (int i = 0; i < 4; i++) y[i] = fmaf(a, wn[4 * k + i], y[i]);
                }
                st_pub(g_out + rb * OB + OB_Y + t7, make_uint4((__float_as_uint(y[0]) & ~15u) | (ep & 15), (__float_as_uint(y[1]) & ~127u) | ((best >> 9) & 127),
                                                               __float_as_uint(y[2]), __float_as_uint(y[3])), true);
            } while (!all);
            const int sel = (~best >> 5) & 2047;
            const int pq = (2 * rb + (tid & 1)) & 63, pv = (pq >> 2) / 3;
            const uint4* fp = g_cand + (sel >> 4) * 192 + (rb >> 5) * 24 + pv * 4 + (pq & 3);
            uint4 fh = {}, fx = {};
            if (rb == 0 && tid == 0) g_sync.epoch[0] = ep;
            if (elected) TS(60);
            TT(5);
            uint4 yv;
            if (warp == 0) { fh = ld_poll(fp); fx = ld_poll(fp + 96); }
            if (fresh && rb < NFFN) __nanosleep(YPRE);
            for (;;) {
                yv = ld_poll(g_out + min(t7, NFFN - 1) * OB + OB_Y + rb);
                if (__all_sync(0xffffffffu, (((yv.x ^ ep) & 15) | ((yv.y ^ (best >> 9)) & 127)) == 0)) break;
                if (YSLEEP) __nanosleep(YSLEEP);
            }
            if (elected) TS(61);
            TT(6);
            float y[4] = {0.f, 0.f, 0.f, 0.f};
            if (t7 < NFFN) { y[0] = __uint_as_float(yv.x); y[1] = __uint_as_float(yv.y); y[2] = __uint_as_float(yv.z); y[3] = __uint_as_float(yv.w); }
            const float z0 = ((lane & 16) ? y[2] : y[0]) + __shfl_xor_sync(0xffffffffu, (lane & 16) ? y[0] : y[2], 16);
            const float z1 = ((lane & 16) ? y[3] : y[1]) + __shfl_xor_sync(0xffffffffu, (lane & 16) ? y[1] : y[3], 16);
            float z = ((lane & 8) ? z1 : z0) + __shfl_xor_sync(0xffffffffu, (lane & 8) ? z0 : z1, 8);
            z += __shfl_xor_sync(0xffffffffu, z, 4);
            z = quad_sum(z);
            if ((lane & 7) == 0) sred[128 + (lane >> 3) * 4 + w4] = z;
            bar_sync(3, 128);
            if (tid < 2) {
                while (fh.w != ep || fx.w != ep) { fh = ld_poll(fp); fx = ld_poll(fp + 96); }
                const float4 y0 = *reinterpret_cast<const float4*>(sred + 128 + tid * 8), y1 = *reinterpret_cast<const float4*>(sred + 132 + tid * 8);
                const int cm = (pq >> 2) - 3 * pv;
                const uint32_t h2 = cm == 0 ? fh.x : cm == 1 ? fh.y : fh.z, x2 = cm == 0 ? fx.x : cm == 1 ? fx.y : fx.z;
                const float sg = sigmoid(bf_hi((best & 0x80000000u) ? (best ^ 0x80000000u) : ~best));
                reinterpret_cast<uint32_t*>(P.out)[sel * 256 + rb * 2 + tid] =
                    badd(x2, bmul(gbf, badd(h2, bmul(pack2((y0.x + y0.y) + (y0.z + y0.w), (y1.x + y1.y) + (y1.z + y1.w)), pack2(sg, sg)))));
            }
            if (elected) TS(62);
            TT(7);
        } else {
            const float4* tf = reinterpret_cast<const float4*>(smem + SM_TAB) + c4;
            const uint32_t xa = sb + 4 * SLOT + (kh ^ 1) * 16384 + (w4 * 16 + (lane & 15)) * 128;
            uint32_t x2[32];
            bar_sync(2, 256);
#pragma unroll 1
            for (int i = 14; i < 17; i++) {
                const uint32_t as = o_next(otab), ws = o_next(otab);
                slot_wait(sb + BAR_FULL, fph, as);
                slot_wait(sb + BAR_FULL, fph, ws);
                gemm_issue<false>(s, oa + as * (SLOT / 16), wd + ws * (SLOT / 16), 1, true);
                wg_wait<1>();
            }
            const uint4* pr = g_out + (rb ^ 16) * OB + t7;
            uint4 pa[8];
            if (elected) TS(29);
            TT(1);
            {
#pragma unroll
                for (int k = 0; k < 8; k++)
                    asm volatile("ldmatrix.sync.aligned.m8n8.x4.shared.b16 {%0, %1, %2, %3}, [%4];"
                                 : "=r"(x2[4 * k]), "=r"(x2[4 * k + 1]), "=r"(x2[4 * k + 2]), "=r"(x2[4 * k + 3])
                                 : "r"(xa + (k >> 2) * 8192 + (((2 * (k & 3) + (lane >> 4)) ^ (lane & 7)) << 4)) : "memory");
            }
            wg_wait<0>();
            reg_fence(s);
            bar_arrive(4, 256);
            if (elected) TS(39);
            TT(2);
#pragma unroll
            for (int v = 0; v < 8; v++) pa[v] = ld_poll(pr + v * 128);
            float4 tc[16];
#pragma unroll
            for (int k = 0; k < 16; k++) {
                tc[k] = tf[k * 4];
                if (!(g & 1)) tc[k].z = __uint_as_float(ONE2);
#pragma unroll
                for (int i = 4 * k; i < 4 * k + 4; i++) s[i] = fmaf((i & 1) ? tc[k].y : tc[k].x, s[i], (i & 1) ? bf_hi(x2[i >> 1]) : bf_lo(x2[i >> 1]));
            }
            reg_fence(s);
            sched_fence(eb2, P.zero);
            for (;;) {
                uint32_t bad = 0;
#pragma unroll
                for (int v = 0; v < 8; v++) asm("lop3.b32 %0, %0, %1, %2, 0xf6;" : "+r"(bad) : "r"(pa[v].x), "r"(ep));
                if (__all_sync(0xffffffffu, (bad & 1) == 0)) break;
                if (PSLEEP) __nanosleep(PSLEEP);
#pragma unroll
                for (int v = 0; v < 8; v++) pa[v] = ld_poll(pr + v * 128);
            }
            if (elected) TS(30);
            TT(3);
            float sd[4] = {}, q0[4] = {}, q1[4] = {};
#pragma unroll
            for (int k = 0; k < 8; k++) {
#pragma unroll
                for (int i = 4 * k; i < 4 * k + 4; i++) {
                    const uint32_t w = (&pa[k].x)[i & 3];
                    x2[i] = pack2(fmaf(tc[i >> 1].x, bf_lo(w), s[2 * i]), fmaf(tc[i >> 1].y, bf_hi(w), s[2 * i + 1]));
                }
                mma16816(sd, x2 + 4 * k, __float_as_uint(tc[2 * k].z), __float_as_uint(tc[2 * k + 1].z));
                mma16816(q0, x2 + 4 * k, x2[4 * k], x2[4 * k + 2]);
                mma16816(q1, x2 + 4 * k, x2[4 * k + 1], x2[4 * k + 3]);
            }
            uint4* sp = g_out + rb * OB + OB_STAT + (w4 * 8 + g) * 2;
            st_pub(sp, make_uint4(__float_as_uint(sd[0]), __float_as_uint((g & 1) ? q0[1] : q0[0]), __float_as_uint(sd[1]), ep), c4 == g >> 1);
            st_pub(sp + 1, make_uint4(__float_as_uint(sd[2]), __float_as_uint((g & 1) ? q1[3] : q1[2]), __float_as_uint(sd[3]), ep), c4 == g >> 1);
            sched_fence(eb2, P.zero);
            if (elected) TS(56);
            TT(4);
            uint32_t cb[16], sh[16], gb[16];
#pragma unroll
            for (int i = 0; i < 16; i++) {
                const float4 c = tf[64 + i * 4];
                cb[i] = __float_as_uint(c.x); sh[i] = __float_as_uint(c.y); gb[i] = __float_as_uint(c.z);
            }
            const float ra = __uint_as_float(lds32(sb + SM_EP + 8)), rb0 = __uint_as_float(lds32(sb + SM_EP + 12));
            uint4 r0, r1;
            for (;;) {
                r0 = ld_poll(g_out + ((rb & ~33) + (c4 & 1) + (c4 & 2) * 16) * OB + OB_STAT + (w4 * 8 + g) * 2);
                r1 = ld_poll(g_out + ((rb & ~33) + (c4 & 1) + (c4 & 2) * 16) * OB + OB_STAT + (w4 * 8 + g) * 2 + 1);
                if (__all_sync(0xffffffffu, r0.w == ep && r1.w == ep)) break;
                if (SSLEEP) __nanosleep(SSLEEP);
            }
            if (elected) TS(57);
            TT(5);
            const float m0 = quad_sum(__uint_as_float(r0.x)) * (1.f / 512.f), m1 = quad_sum(__uint_as_float(r1.x)) * (1.f / 512.f);
            const float rs0 = ln_rstd(fmaxf(fmaf(-m0, m0, quad_sum(__uint_as_float(r0.y)) * (1.f / 512.f)), 0.f));
            const float rs1 = ln_rstd(fmaxf(fmaf(-m1, m1, quad_sum(__uint_as_float(r1.y)) * (1.f / 512.f)), 0.f));
            const uint32_t mb0 = pack2(m0, m0), mb1 = pack2(m1, m1);
            const uint32_t lg = pack2(fmaf(rs0, fmaf(-bf_lo(mb0), ra, quad_sum(__uint_as_float(r0.z))), rb0),
                                      fmaf(rs1, fmaf(-bf_lo(mb1), ra, quad_sum(__uint_as_float(r1.z))), rb0));
            const uint32_t u0 = lg << 16, u1 = lg & 0xffff0000u;
            const uint32_t k0 = ((u0 ^ (((int)u0 >> 31) | 0x80000000u)) & 0xffff0000u) | ((2047 - row) << 5) | (ep & 31);
            const uint32_t k1 = ((u1 ^ (((int)u1 >> 31) | 0x80000000u)) & 0xffff0000u) | ((2039 - row) << 5) | (ep & 31);
            const uint32_t kb = __reduce_max_sync(0xffffffffu, max(k0, k1));
            st_pub(g_key + cq * 128 + (row >> 4), kb, lane == 0);
            const bool cand = kb == k0 || kb == k1;
            uint4* cp = g_cand + (row >> 4) * 192 + cq * 24 + c4;
#pragma unroll 1
            for (int it = 0; it < 3; it++) {
                bool put = it == 1 || !cand;
                if (it == 2) {
                    mbar_wait(sb + BAR_BEST, 0);
                    put = cand && lds32(sb + SM_EP + 24) != kb;
                }
                const bool hi = (kb == k1) != (it == 1);
                uint32_t cx[18], ch[18];
#pragma unroll
                for (int i = 0; i < 16; i++) {
                    cx[i] = hi ? x2[2 * i + 1] : x2[2 * i];
                    ch[i] = ln_apply(cx[i], hi ? mb1 : mb0, hi ? rs1 : rs0, cb[i], sh[i]);
                }
                cx[16] = cx[17] = ch[16] = ch[17] = 0;
#pragma unroll
                for (int v = 0; v < 6; v++) st_pub(cp + v * 4, make_uint4(ch[3 * v], ch[3 * v + 1], ch[3 * v + 2], ep), cand && it == 0);
#pragma unroll
                for (int v = 0; v < 6; v++) st_pub(cp + 96 + v * 4, make_uint4(cx[3 * v], cx[3 * v + 1], cx[3 * v + 2], ep), cand && it == 0);
                if (it == 0) TT(6);
                uint2* op = reinterpret_cast<uint2*>(P.out) + (row + 8 * hi) * 128 + cq * 32 + (c4 & 1) * 2 + (c4 >> 1);
#pragma unroll
                for (int i = 0; i < 16; i += 2) {
                    const uint32_t v0 = badd(cx[i], bmul(gb[i], ch[i])), v1 = badd(cx[i + 1], bmul(gb[i + 1], ch[i + 1]));
                    const uint32_t rv = __shfl_xor_sync(0xffffffffu, (c4 & 1) ? v0 : v1, 1);
                    if (put) op[i * 2] = (c4 & 1) ? make_uint2(rv, v1) : make_uint2(v0, rv);
                }
            }
            if (elected) TS(59);
            TT(7);
        }
        mbar_arrive_if(eb2, lane == 0);
    }
}

typedef CUresult (*EncodeFn)(CUtensorMap*, CUtensorMapDataType, cuuint32_t, void*, const cuuint64_t*, const cuuint64_t*,
                             const cuuint32_t*, const cuuint32_t*, CUtensorMapInterleave, CUtensorMapSwizzle,
                             CUtensorMapL2promotion, CUtensorMapFloatOOBfill);

void make_2d(EncodeFn fn, CUtensorMap* m, const void* p, uint64_t cols, uint64_t rows, uint32_t bc, uint32_t br, CUtensorMapSwizzle sw) {
    cuuint64_t dims[2] = {cols, rows}, strides[1] = {cols * 2};
    cuuint32_t box[2] = {bc, br}, es[2] = {1, 1};
    fn(m, CU_TENSOR_MAP_DATA_TYPE_BFLOAT16, 2, const_cast<void*>(p), dims, strides, box, es, CU_TENSOR_MAP_INTERLEAVE_NONE,
       sw, CU_TENSOR_MAP_L2_PROMOTION_L2_128B, CU_TENSOR_MAP_FLOAT_OOB_FILL_NONE);
}
void make_3d(EncodeFn fn, CUtensorMap* m, const void* p, uint64_t cols, uint64_t rows, uint32_t br = 128, uint32_t nb = 2) {
    cuuint64_t dims[3] = {64, rows, cols / 64}, strides[2] = {cols * 2, 128};
    cuuint32_t box[3] = {64, br, nb}, es[3] = {1, 1, 1};
    fn(m, CU_TENSOR_MAP_DATA_TYPE_BFLOAT16, 3, const_cast<void*>(p), dims, strides, box, es, CU_TENSOR_MAP_INTERLEAVE_NONE,
       CU_TENSOR_MAP_SWIZZLE_128B, CU_TENSOR_MAP_L2_PROMOTION_L2_256B, CU_TENSOR_MAP_FLOAT_OOB_FILL_NONE);
}

}

extern "C" void kernel_launch(void* const* d_in, const int* in_sizes, int n_in, void* d_out, int out_size) {
    static EncodeFn fn = nullptr;
    if (!fn) {
        void* f = nullptr;
        cudaDriverEntryPointQueryResult st;
        cudaGetDriverEntryPoint("cuTensorMapEncodeTiled", &f, cudaEnableDefault, &st);
        fn = (EncodeFn)f;
        cudaFuncSetAttribute(fused_kernel, cudaFuncAttributeMaxDynamicSharedMemorySize, SMEM_BYTES);
    }
    CUtensorMap ckv, wq, wuk, wuv, wo, wg, wu, wm, xm;
    make_3d(fn, &ckv, d_in[1], 512, 2048, 128, 1);
    make_3d(fn, &xm, d_in[0], 512, 2048, 64);
    make_3d(fn, &wq, d_in[2], 4096, 512);
    make_3d(fn, &wuk, d_in[3], 4096, 512);
    make_3d(fn, &wuv, d_in[4], 4096, 512);
    make_3d(fn, &wo, d_in[5], 512, 4096);
    make_2d(fn, &wg, d_in[8], 1792, 512, 16, 256, CU_TENSOR_MAP_SWIZZLE_32B);
    make_2d(fn, &wu, d_in[9], 1792, 512, 16, 256, CU_TENSOR_MAP_SWIZZLE_32B);
    make_3d(fn, &wm, d_in[12], 3072, 512, 64, 4);
    Params p;
    p.x = (const bf16*)d_in[0];
    p.ckv = (const bf16*)d_in[1];
    p.wo = (const bf16*)d_in[5];
    p.wr = (const bf16*)d_in[7];
    p.wdown = (const bf16*)d_in[10];
    p.c = (const bf16*)d_in[11];
    p.out = (bf16*)d_out;
    p.zero = 0;
    fused_kernel<<<NCTA + NSPARE, 384, SMEM_BYTES>>>(ckv, wq, wuk, wuv, wo, wg, wu, wm, xm, p);
}
```

```cpp
#include <cuda.h>
#include <cuda_bf16.h>
#include <cuda_runtime.h>
#include <stdint.h>
#include <stdio.h>

namespace {

typedef __nv_bfloat16 bf16;
typedef unsigned long long u64;

constexpr int NCTA = 128, NSPARE = 4;
constexpr int SLOT = 32768;
constexpr int SM_BAR = 7 * SLOT;
constexpr int BAR_FULL = SM_BAR;
constexpr int BAR_EMPTY = BAR_FULL + 8 * 7;
constexpr int BAR_DONE = BAR_EMPTY + 8 * 7;
constexpr int BAR_FLAG = BAR_DONE + 8 * 9;
constexpr int BAR_PF = BAR_FLAG + 8 * 9;
constexpr int BAR_END = BAR_PF + 8;
constexpr int BAR_BEST = BAR_END + 8;
constexpr int SM_EP = BAR_END + 40;
constexpr int SM_RED = SM_BAR + 384;
constexpr int SM_TAB = SM_BAR + 1024;
constexpr int SMEM_BYTES = SM_BAR + 3072;
constexpr int NFFN = 112;
#define HINT 479
constexpr u64 L2_NORMAL = 0x1000000000000000ull, L2_FIRST = 0x12F0000000000000ull;
#define PFA 8
#define PFB 6
#define POLL_NS 50
#define MSPLIT 13
#define NSH 1
#define XPF 1
#define KSLEEP 200
#define YSLEEP 50
#define YPRE 150
#define SSLEEP 50
#define PSLEEP 100
#define SPEC 28
#define KVG 7
#define EARLY2 4
#define OFF 2
#define CLAST 2
#define EARLY 7
constexpr uint32_t SPIN_LIMIT = 1u << 22;
constexpr uint32_t ONE2 = 0x3f803f80u;

struct Sync {
    uint32_t cnt[16 * 8 * 8];
    uint32_t ctxcnt[16 * 32];
    uint32_t epoch[32];
};

__device__ __align__(1024) uint8_t g_img[2 * 512 * SLOT];
#define g_KV g_img
#define g_ctx (g_img + 512 * SLOT)
__device__ __align__(1024) uint8_t g_h[16 * 4 * SLOT];
constexpr int OB = 1216, OB_STAT = 1024, OB_Y = 1088;
__device__ __align__(1024) uint4 g_out[128 * OB];
__device__ __align__(1024) bf16 g_mod[3072];
__device__ __align__(1024) uint32_t g_mod1[1024];
__device__ __align__(1024) uint4 g_cand[128 * 192];
__device__ __align__(1024) uint32_t g_key[4 * 128];
__device__ __align__(1024) uint8_t g_wf[NFFN * SLOT];
__device__ __align__(1024) uint4 g_x2[128 * 1024];
__device__ __align__(1024) Sync g_sync;
#define TS(i)

#define TT(i)
#define PT()

struct Params {
    const bf16 *x, *ckv, *wo, *wr, *wdown, *c;
    bf16* out;
    int zero;
};

__device__ __forceinline__ void mbar_init(uint32_t bar, uint32_t cnt) {
    asm volatile("mbarrier.init.shared::cta.b64 [%0], %1;" ::"r"(bar), "r"(cnt) : "memory");
}
__device__ __forceinline__ void mbar_wait(uint32_t bar, uint32_t parity) {
    asm volatile("{\n.reg .pred p;\nL_%=:\nmbarrier.try_wait.parity.shared::cta.b64 p, [%0], %1;\n@!p bra L_%=;\n}" ::"r"(bar), "r"(parity) : "memory");
}
__device__ __forceinline__ void mbar_sleep(uint32_t bar) {
    if ((threadIdx.x & 31) == 0)
        asm volatile("{\n.reg .pred p;\nL_%=:\nmbarrier.try_wait.parity.shared::cta.b64 p, [%0], 0, 100000;\n@!p bra L_%=;\n}" ::"r"(bar) : "memory");
    __syncwarp();
}
__device__ __forceinline__ void mbar_watch(uint32_t bar, uint32_t parity) {
    asm volatile("{\n.reg .pred p;\n.reg .u32 n;\nmov.u32 n, 0;\n"
                 "L_%=:\nmbarrier.try_wait.parity.shared::cta.b64 p, [%0], %1;\n@p bra D_%=;\n"
                 "add.u32 n, n, 1;\nsetp.lt.u32 p, n, %2;\n@p bra L_%=;\ntrap;\nD_%=:\n}"
                 ::"r"(bar), "r"(parity), "n"(SPIN_LIMIT) : "memory");
}
__device__ __forceinline__ void step_watch(uint32_t a, uint32_t step) {
    asm volatile("{\n.reg .pred p;\n.reg .u32 n, v;\nmov.u32 n, 0;\n"
                 "L_%=:\nld.volatile.shared.u32 v, [%0];\nsetp.ge.u32 p, v, %1;\n@p bra D_%=;\nnanosleep.u32 400;\n"
                 "add.u32 n, n, 1;\nsetp.lt.u32 p, n, %2;\n@p bra L_%=;\ntrap;\nD_%=:\n}"
                 ::"r"(a), "r"(step), "n"(SPIN_LIMIT) : "memory");
}
__device__ __forceinline__ void mbar_arrive_if(uint32_t bar, bool on) {
    asm volatile("{\n.reg .pred p;\nsetp.ne.s32 p, %1, 0;\n@p mbarrier.arrive.shared::cta.b64 _, [%0];\n}" ::"r"(bar), "r"((int)on) : "memory");
}
__device__ __forceinline__ void tma3d_prefetch(const CUtensorMap* m, int row, int cb) {
    asm volatile("{\n.reg .pred p;\nelect.sync _|p, 0xffffffff;\n@p cp.async.bulk.prefetch.tensor.3d.L2.global [%0, {%1, %2, %3}];\n}"
                 ::"l"(m), "r"(0), "r"(row), "r"(cb) : "memory");
}
__device__ __forceinline__ void l2_prefetch(const void* p, uint32_t bytes) {
    asm volatile("{\n.reg .pred p;\nelect.sync _|p, 0xffffffff;\n@p cp.async.bulk.prefetch.L2.global [%0], %1;\n}" ::"l"(p), "r"(bytes) : "memory");
}
__device__ __forceinline__ void bulk_store(void* dst, uint32_t src, uint32_t bytes, bool first) {
    asm volatile("{\n.reg .pred p;\nelect.sync _|p, 0xffffffff;\n@p cp.async.bulk.global.shared::cta.bulk_group.L2::cache_hint [%0], [%1], %2, %3;\n}"
                 ::"l"(dst), "r"(src), "r"(bytes), "l"(first ? L2_FIRST : L2_NORMAL) : "memory");
}
__device__ __forceinline__ void flag_wait(const uint32_t* f, uint32_t target) {
    asm volatile("{\n.reg .pred p;\n.reg .u32 v;\n"
                 "L_%=:\nld.acquire.gpu.global.u32 v, [%0];\nsub.u32 v, v, %1;\nsetp.lt.s32 p, v, 0;\n@p nanosleep.u32 100;\n@p bra L_%=;\n}"
                 ::"l"(f), "r"(target) : "memory");
}
__device__ __forceinline__ uint4 ld_poll(const uint4* p) {
    uint4 v;
    asm volatile("{\n.reg .b128 t;\nld.relaxed.gpu.global.b128 t, [%4];\nmov.b128 {%0, %1, %2, %3}, t;\n}"
                 : "=r"(v.x), "=r"(v.y), "=r"(v.z), "=r"(v.w) : "l"(p) : "memory");
    return v;
}
__device__ __forceinline__ void st_pub(uint4* p, uint4 v, bool on) {
    asm volatile("{\n.reg .pred p;\n.reg .b128 t;\nsetp.ne.s32 p, %5, 0;\nmov.b128 t, {%1, %2, %3, %4};\n@p st.relaxed.gpu.global.b128 [%0], t;\n}"
                 ::"l"(p), "r"(v.x), "r"(v.y), "r"(v.z), "r"(v.w), "r"((int)on) : "memory");
}
__device__ __forceinline__ void st_pub(uint32_t* p, uint32_t v, bool on) {
    asm volatile("{\n.reg .pred p;\nsetp.ne.s32 p, %2, 0;\n@p st.relaxed.gpu.global.u32 [%0], %1;\n}" ::"l"(p), "r"(v), "r"((int)on) : "memory");
}
__device__ __forceinline__ void flag_add(uint32_t* p) {
    asm volatile("red.release.gpu.global.add.u32 [%0], 1;" ::"l"(p) : "memory");
}
__device__ __forceinline__ uint32_t lds32(uint32_t a) {
    uint32_t v;
    asm volatile("ld.shared.u32 %0, [%1];" : "=r"(v) : "r"(a) : "memory");
    return v;
}
__device__ __forceinline__ uint4 lds128(uint32_t a) {
    uint4 v;
    asm volatile("ld.shared.v4.u32 {%0, %1, %2, %3}, [%4];" : "=r"(v.x), "=r"(v.y), "=r"(v.z), "=r"(v.w) : "r"(a) : "memory");
    return v;
}
__device__ __forceinline__ void sched_fence(uint32_t& v, uint32_t z) {
    uint32_t ck;
    asm volatile("mov.u32 %0, %%clock;" : "=r"(ck)::"memory");
    v ^= ck & z;
}
__device__ __forceinline__ void fence_async_global() { asm volatile("fence.proxy.async.global;" ::: "memory"); }
__device__ __forceinline__ void fence_async_smem() { asm volatile("fence.proxy.async.shared::cta;" ::: "memory"); }
__device__ __forceinline__ void bar_sync(int id, int n) { asm volatile("bar.sync %0, %1;" ::"r"(id), "r"(n) : "memory"); }
__device__ __forceinline__ void bar_arrive(int id, int n) { asm volatile("bar.arrive %0, %1;" ::"r"(id), "r"(n) : "memory"); }
__device__ __forceinline__ void wg_fence() { asm volatile("wgmma.fence.sync.aligned;" ::: "memory"); }
__device__ __forceinline__ void wg_commit() { asm volatile("wgmma.commit_group.sync.aligned;" ::: "memory"); }
template <int N> __device__ __forceinline__ void wg_wait() { asm volatile("wgmma.wait_group.sync.aligned %0;" ::"n"(N) : "memory"); }
template <int N> __device__ __forceinline__ void reg_fence(float (&d)[N]) {
#pragma unroll
    for (int i = 0; i < N; i++) asm volatile("" : "+f"(d[i])::"memory");
}
template <int N> __device__ __forceinline__ void reg_fence(uint32_t (&d)[N]) {
#pragma unroll
    for (int i = 0; i < N; i++) asm volatile("" : "+r"(d[i])::"memory");
}
__device__ __forceinline__ uint32_t desc_k(uint32_t a) { return ((a & 0x3ffff) >> 4) | (1u << 16); }
__device__ __forceinline__ uint32_t desc_mn(uint32_t a) { return ((a & 0x3ffff) >> 4) | (1024u << 16); }

__device__ __forceinline__ uint64_t desc64(uint32_t lo, uint32_t hi) {
    uint64_t d;
    asm("mov.b64 %0, {%1, %2};" : "=l"(d) : "r"(lo), "r"(hi));
    return d;
}
__device__ __forceinline__ void desc_add(uint64_t& d, uint32_t x) { asm("add.u64 %0, %0, %1;" : "+l"(d) : "l"((uint64_t)x)); }

template <int TB>
__device__ __forceinline__ void wgmma_ss128(float (&d)[64], uint64_t da, uint64_t db, int acc) {
    asm volatile("{\n.reg .pred p;\nsetp.ne.b32 p, %66, 0;\n"
        "wgmma.mma_async.sync.aligned.m64n128k16.f32.bf16.bf16 {%0, %1, %2, %3, %4, %5, %6, %7, %8, %9, %10, %11, %12, %13, %14, %15, %16, %17, %18, %19, %20, %21, %22, %23, %24, %25, %26, %27, %28, %29, %30, %31, %32, %33, %34, %35, %36, %37, %38, %39, %40, %41, %42, %43, %44, %45, %46, %47, %48, %49, %50, %51, %52, %53, %54, %55, %56, %57, %58, %59, %60, %61, %62, %63}, %64, %65, p, 1, 1, 0, %67;\n}"
        : "+f"(d[0]), "+f"(d[1]), "+f"(d[2]), "+f"(d[3]), "+f"(d[4]), "+f"(d[5]), "+f"(d[6]), "+f"(d[7]), "+f"(d[8]), "+f"(d[9]), "+f"(d[10]), "+f"(d[11]), "+f"(d[12]), "+f"(d[13]), "+f"(d[14]), "+f"(d[15]), "+f"(d[16]), "+f"(d[17]), "+f"(d[18]), "+f"(d[19]), "+f"(d[20]), "+f"(d[21]), "+f"(d[22]), "+f"(d[23]), "+f"(d[24]), "+f"(d[25]), "+f"(d[26]), "+f"(d[27]), "+f"(d[28]), "+f"(d[29]), "+f"(d[30]), "+f"(d[31]), "+f"(d[32]), "+f"(d[33]), "+f"(d[34]), "+f"(d[35]), "+f"(d[36]), "+f"(d[37]), "+f"(d[38]), "+f"(d[39]), "+f"(d[40]), "+f"(d[41]), "+f"(d[42]), "+f"(d[43]), "+f"(d[44]), "+f"(d[45]), "+f"(d[46]), "+f"(d[47]), "+f"(d[48]), "+f"(d[49]), "+f"(d[50]), "+f"(d[51]), "+f"(d[52]), "+f"(d[53]), "+f"(d[54]), "+f"(d[55]), "+f"(d[56]), "+f"(d[57]), "+f"(d[58]), "+f"(d[59]), "+f"(d[60]), "+f"(d[61]), "+f"(d[62]), "+f"(d[63])
        : "l"(da), "l"(db), "r"(acc), "n"(TB));
}
template <int TB>
__device__ __forceinline__ void wgmma_ss128_init(float (&d)[64], uint64_t da, uint64_t db) {
    asm volatile("{\n.reg .pred p;\nsetp.ne.b32 p, 0, 0;\n"
        "wgmma.mma_async.sync.aligned.m64n128k16.f32.bf16.bf16 {%0, %1, %2, %3, %4, %5, %6, %7, %8, %9, %10, %11, %12, %13, %14, %15, %16, %17, %18, %19, %20, %21, %22, %23, %24, %25, %26, %27, %28, %29, %30, %31, %32, %33, %34, %35, %36, %37, %38, %39, %40, %41, %42, %43, %44, %45, %46, %47, %48, %49, %50, %51, %52, %53, %54, %55, %56, %57, %58, %59, %60, %61, %62, %63}, %64, %65, p, 1, 1, 0, %66;\n}"
        : "=f"(d[0]), "=f"(d[1]), "=f"(d[2]), "=f"(d[3]), "=f"(d[4]), "=f"(d[5]), "=f"(d[6]), "=f"(d[7]), "=f"(d[8]), "=f"(d[9]), "=f"(d[10]), "=f"(d[11]), "=f"(d[12]), "=f"(d[13]), "=f"(d[14]), "=f"(d[15]), "=f"(d[16]), "=f"(d[17]), "=f"(d[18]), "=f"(d[19]), "=f"(d[20]), "=f"(d[21]), "=f"(d[22]), "=f"(d[23]), "=f"(d[24]), "=f"(d[25]), "=f"(d[26]), "=f"(d[27]), "=f"(d[28]), "=f"(d[29]), "=f"(d[30]), "=f"(d[31]), "=f"(d[32]), "=f"(d[33]), "=f"(d[34]), "=f"(d[35]), "=f"(d[36]), "=f"(d[37]), "=f"(d[38]), "=f"(d[39]), "=f"(d[40]), "=f"(d[41]), "=f"(d[42]), "=f"(d[43]), "=f"(d[44]), "=f"(d[45]), "=f"(d[46]), "=f"(d[47]), "=f"(d[48]), "=f"(d[49]), "=f"(d[50]), "=f"(d[51]), "=f"(d[52]), "=f"(d[53]), "=f"(d[54]), "=f"(d[55]), "=f"(d[56]), "=f"(d[57]), "=f"(d[58]), "=f"(d[59]), "=f"(d[60]), "=f"(d[61]), "=f"(d[62]), "=f"(d[63])
        : "l"(da), "l"(db), "n"(TB));
}
template <int TB>
__device__ __forceinline__ void wgmma_ss64(float (&d)[32], uint64_t da, uint64_t db, int acc) {
    asm volatile("{\n.reg .pred p;\nsetp.ne.b32 p, %34, 0;\n"
        "wgmma.mma_async.sync.aligned.m64n64k16.f32.bf16.bf16 {%0, %1, %2, %3, %4, %5, %6, %7, %8, %9, %10, %11, %12, %13, %14, %15, %16, %17, %18, %19, %20, %21, %22, %23, %24, %25, %26, %27, %28, %29, %30, %31}, %32, %33, p, 1, 1, 0, %35;\n}"
        : "+f"(d[0]), "+f"(d[1]), "+f"(d[2]), "+f"(d[3]), "+f"(d[4]), "+f"(d[5]), "+f"(d[6]), "+f"(d[7]), "+f"(d[8]), "+f"(d[9]), "+f"(d[10]), "+f"(d[11]), "+f"(d[12]), "+f"(d[13]), "+f"(d[14]), "+f"(d[15]), "+f"(d[16]), "+f"(d[17]), "+f"(d[18]), "+f"(d[19]), "+f"(d[20]), "+f"(d[21]), "+f"(d[22]), "+f"(d[23]), "+f"(d[24]), "+f"(d[25]), "+f"(d[26]), "+f"(d[27]), "+f"(d[28]), "+f"(d[29]), "+f"(d[30]), "+f"(d[31])
        : "l"(da), "l"(db), "r"(acc), "n"(TB));
}
template <int TB>
__device__ __forceinline__ void wgmma_ss64_init(float (&d)[32], uint64_t da, uint64_t db) {
    asm volatile("{\n.reg .pred p;\nsetp.ne.b32 p, 0, 0;\n"
        "wgmma.mma_async.sync.aligned.m64n64k16.f32.bf16.bf16 {%0, %1, %2, %3, %4, %5, %6, %7, %8, %9, %10, %11, %12, %13, %14, %15, %16, %17, %18, %19, %20, %21, %22, %23, %24, %25, %26, %27, %28, %29, %30, %31}, %32, %33, p, 1, 1, 0, %34;\n}"
        : "=f"(d[0]), "=f"(d[1]), "=f"(d[2]), "=f"(d[3]), "=f"(d[4]), "=f"(d[5]), "=f"(d[6]), "=f"(d[7]), "=f"(d[8]), "=f"(d[9]), "=f"(d[10]), "=f"(d[11]), "=f"(d[12]), "=f"(d[13]), "=f"(d[14]), "=f"(d[15]), "=f"(d[16]), "=f"(d[17]), "=f"(d[18]), "=f"(d[19]), "=f"(d[20]), "=f"(d[21]), "=f"(d[22]), "=f"(d[23]), "=f"(d[24]), "=f"(d[25]), "=f"(d[26]), "=f"(d[27]), "=f"(d[28]), "=f"(d[29]), "=f"(d[30]), "=f"(d[31])
        : "l"(da), "l"(db), "n"(TB));
}
__device__ __forceinline__ void wgmma_rs128(float (&d)[64], uint32_t a0, uint32_t a1, uint32_t a2, uint32_t a3, uint64_t db, int acc) {
    asm volatile("{\n.reg .pred p;\nsetp.ne.b32 p, %69, 0;\n"
        "wgmma.mma_async.sync.aligned.m64n128k16.f32.bf16.bf16 {%0, %1, %2, %3, %4, %5, %6, %7, %8, %9, %10, %11, %12, %13, %14, %15, %16, %17, %18, %19, %20, %21, %22, %23, %24, %25, %26, %27, %28, %29, %30, %31, %32, %33, %34, %35, %36, %37, %38, %39, %40, %41, %42, %43, %44, %45, %46, %47, %48, %49, %50, %51, %52, %53, %54, %55, %56, %57, %58, %59, %60, %61, %62, %63}, {%64, %65, %66, %67}, %68, p, 1, 1, 1;\n}"
        : "+f"(d[0]), "+f"(d[1]), "+f"(d[2]), "+f"(d[3]), "+f"(d[4]), "+f"(d[5]), "+f"(d[6]), "+f"(d[7]), "+f"(d[8]), "+f"(d[9]), "+f"(d[10]), "+f"(d[11]), "+f"(d[12]), "+f"(d[13]), "+f"(d[14]), "+f"(d[15]), "+f"(d[16]), "+f"(d[17]), "+f"(d[18]), "+f"(d[19]), "+f"(d[20]), "+f"(d[21]), "+f"(d[22]), "+f"(d[23]), "+f"(d[24]), "+f"(d[25]), "+f"(d[26]), "+f"(d[27]), "+f"(d[28]), "+f"(d[29]), "+f"(d[30]), "+f"(d[31]), "+f"(d[32]), "+f"(d[33]), "+f"(d[34]), "+f"(d[35]), "+f"(d[36]), "+f"(d[37]), "+f"(d[38]), "+f"(d[39]), "+f"(d[40]), "+f"(d[41]), "+f"(d[42]), "+f"(d[43]), "+f"(d[44]), "+f"(d[45]), "+f"(d[46]), "+f"(d[47]), "+f"(d[48]), "+f"(d[49]), "+f"(d[50]), "+f"(d[51]), "+f"(d[52]), "+f"(d[53]), "+f"(d[54]), "+f"(d[55]), "+f"(d[56]), "+f"(d[57]), "+f"(d[58]), "+f"(d[59]), "+f"(d[60]), "+f"(d[61]), "+f"(d[62]), "+f"(d[63])
        : "r"(a0), "r"(a1), "r"(a2), "r"(a3), "l"(db), "r"(acc));
}

__device__ __forceinline__ uint32_t pack2(float lo, float hi) {
    uint32_t r;
    asm("cvt.rn.bf16x2.f32 %0, %1, %2;" : "=r"(r) : "f"(hi), "f"(lo));
    return r;
}
__device__ __forceinline__ float bf_lo(uint32_t v) { return __uint_as_float(v << 16); }
__device__ __forceinline__ float bf_hi(uint32_t v) { return __uint_as_float(v & 0xffff0000u); }
__device__ __forceinline__ float rbf(float v) { return bf_lo(pack2(v, v)); }
__device__ __forceinline__ uint32_t badd(uint32_t a, uint32_t b) {
    uint32_t r;
    asm("add.rn.bf16x2 %0, %1, %2;" : "=r"(r) : "r"(a), "r"(b));
    return r;
}
__device__ __forceinline__ uint32_t bsub(uint32_t a, uint32_t b) {
    uint32_t r;
    asm("sub.rn.bf16x2 %0, %1, %2;" : "=r"(r) : "r"(a), "r"(b));
    return r;
}
__device__ __forceinline__ uint32_t bmul(uint32_t a, uint32_t b) {
    uint32_t r;
    asm("mul.rn.bf16x2 %0, %1, %2;" : "=r"(r) : "r"(a), "r"(b));
    return r;
}
__device__ __forceinline__ uint32_t ln_apply(uint32_t x, uint32_t mb, float rs, uint32_t scale, uint32_t shift) {
    const uint32_t d = bsub(x, mb);
    return badd(bmul(pack2(bf_lo(d) * rs, bf_hi(d) * rs), scale), shift);
}
__device__ __forceinline__ float ex2(float v) {
    float r;
    asm("ex2.approx.ftz.f32 %0, %1;" : "=f"(r) : "f"(v));
    return r;
}
__device__ __forceinline__ float rcp(float v) {
    float r;
    asm("rcp.approx.ftz.f32 %0, %1;" : "=f"(r) : "f"(v));
    return r;
}
__device__ __forceinline__ float sqrt_fast(float v) {
    float r;
    asm("sqrt.approx.ftz.f32 %0, %1;" : "=f"(r) : "f"(v));
    return r;
}
__device__ __forceinline__ float ln_rstd(float var) { return rcp(rbf(sqrt_fast(rbf(rbf(var) + 1e-5f)))); }
__device__ __forceinline__ float sigmoid(float v) { return rcp(1.f + ex2(-1.4426950408889634f * v)); }
__device__ __forceinline__ float quad_sum(float v) {
    v += __shfl_xor_sync(0xffffffffu, v, 1);
    return v + __shfl_xor_sync(0xffffffffu, v, 2);
}

constexpr uint32_t HI_128 = 0x40000040u, HI_IMG = 0x80000080u, HI_Q = 0x80000040u;
template <int M, int RH>
__device__ __forceinline__ uint4 img_pack(const float (&d)[64], float s) {
    uint4 v;
    v.x = pack2(d[16 * M + 2 * RH] * s, d[16 * M + 2 * RH + 1] * s);
    v.y = pack2(d[16 * M + 4 + 2 * RH] * s, d[16 * M + 5 + 2 * RH] * s);
    v.z = pack2(d[16 * M + 8 + 2 * RH] * s, d[16 * M + 9 + 2 * RH] * s);
    v.w = pack2(d[16 * M + 12 + 2 * RH] * s, d[16 * M + 13 + 2 * RH] * s);
    return v;
}
template <int M>
__device__ __forceinline__ void img_store_global(uint32_t img, uint32_t toff, const float (&d)[64], float s0, float s1) {
    uint4* p = reinterpret_cast<uint4*>(g_img + (img + toff)) + M * 32;
    p[0] = img_pack<M, 0>(d, s0);
    p[128] = img_pack<M, 1>(d, s1);
}
__device__ __forceinline__ void sts128(uint32_t a, uint4 v) {
    asm volatile("st.shared.v4.b32 [%0], {%1, %2, %3, %4};" ::"r"(a), "r"(v.x), "r"(v.y), "r"(v.z), "r"(v.w) : "memory");
}
constexpr float SM_C = 0.08838834764831845f * 1.4426950408889634f;
__device__ __forceinline__ float pack2f(float lo, float hi) {
    float r;
    asm("{\n.reg .b32 t;\ncvt.rn.bf16x2.f32 t, %1, %2;\nmov.b32 %0, t;\n}" : "=f"(r) : "f"(hi), "f"(lo));
    return r;
}
template <int M, bool SCALE, bool PARK>
__device__ __forceinline__ void pack_group(float (&d)[64], float (&v)[8], float s0, float s1) {
#pragma unroll
    for (int i = 0; i < 8; i++) {
        const int k = 16 * M + 4 * (i & 3) + 2 * (i >> 2);
        v[i] = SCALE ? pack2f(d[k] * (i < 4 ? s0 : s1), d[k + 1] * (i < 4 ? s0 : s1)) : pack2f(d[k], d[k + 1]);
        if (PARK && M > 0) d[16 * (M > 0 ? M - 1 : 0) + i] = v[i];
    }
}
__device__ __forceinline__ uint32_t q_off(uint32_t toff) {
    asm volatile("" : "+r"(toff));
    return (((toff >> 1) & ~2047u) ^ 8192) + (toff & 511);
}
template <int M>
__device__ __forceinline__ void ctx_store_part(float4* p, float (&d)[64], float i0, float i1) {
    float v[8];
    pack_group<M, true, true>(d, v, i0, i1);
    p[M * 32] = make_float4(v[0], v[1], v[2], v[3]);
    p[M * 32 + 128] = make_float4(v[4], v[5], v[6], v[7]);
}
__device__ __forceinline__ void ctx_store(uint32_t img, uint32_t toff, float (&o)[64], float i0, float i1) {
    asm volatile("" : "+r"(toff));
    float4* p = reinterpret_cast<float4*>(g_img + (img + toff));
    ctx_store_part<0>(p, o, i0, i1); ctx_store_part<1>(p, o, i0, i1); ctx_store_part<2>(p, o, i0, i1); ctx_store_part<3>(p, o, i0, i1);
}

__device__ __forceinline__ void slot_wait(uint32_t bars, uint32_t& ph, uint32_t slot) {
    mbar_wait(bars + 8 * slot, (ph >> slot) & 1);
    ph ^= 1u << slot;
}
__device__ __forceinline__ void release_if(uint32_t eb, uint32_t slot, bool on) {
    asm volatile("{\n.reg .pred p;\nsetp.ne.s32 p, %1, 0;\n@p mbarrier.arrive.shared::cluster.b64 _, [%0];\n}" ::"r"(eb + 8 * slot), "r"((int)on) : "memory");
}
__device__ __forceinline__ void slot_expect(uint32_t sb, uint32_t slot) {
    asm volatile("{\n.reg .pred p;\nelect.sync _|p, 0xffffffff;\n@p mbarrier.arrive.expect_tx.shared::cta.b64 _, [%0], 32768;\n}"
                 ::"r"(sb + BAR_FULL + 8 * slot) : "memory");
}
__device__ __forceinline__ void slot_acquire(uint32_t sb, uint32_t& ph, uint32_t slot) {
    slot_wait(sb + BAR_EMPTY, ph, slot);
    slot_expect(sb, slot);
}
__device__ __forceinline__ void load_bulk(uint32_t sb, uint32_t slot, uint32_t off, const void* src, uint32_t bytes, bool both, bool first) {
    if (both)
        asm volatile("{\n.reg .pred p;\nelect.sync _|p, 0xffffffff;\n"
                     "@p cp.async.bulk.shared::cluster.global.mbarrier::complete_tx::bytes.multicast::cluster.L2::cache_hint [%0], [%1], %5, [%2], %4, %3;\n}"
                     ::"r"(sb + slot * SLOT + off), "l"(src), "r"(sb + BAR_FULL + 8 * slot), "l"(first ? L2_FIRST : L2_NORMAL), "h"((uint16_t)3),
                     "r"(bytes) : "memory");
    else
        asm volatile("{\n.reg .pred p;\nelect.sync _|p, 0xffffffff;\n"
                     "@p cp.async.bulk.shared::cluster.global.mbarrier::complete_tx::bytes.L2::cache_hint [%0], [%1], %4, [%2], %3;\n}"
                     ::"r"(sb + slot * SLOT + off), "l"(src), "r"(sb + BAR_FULL + 8 * slot), "l"(first ? L2_FIRST : L2_NORMAL), "r"(bytes) : "memory");
}
__device__ __forceinline__ void load_tile(uint32_t sb, uint32_t slot, uint32_t off, const CUtensorMap* m, int row, int cb, bool both, bool first) {
    if (both)
        asm volatile("{\n.reg .pred p;\nelect.sync _|p, 0xffffffff;\n"
                     "@p cp.async.bulk.tensor.3d.shared::cluster.global.mbarrier::complete_tx::bytes.multicast::cluster.L2::cache_hint [%0], [%1, {%3, %4, %5}], [%2], %7, %6;\n}"
                     ::"r"(sb + slot * SLOT + off), "l"(m), "r"(sb + BAR_FULL + 8 * slot), "r"(0), "r"(row), "r"(cb),
                     "l"(first ? L2_FIRST : L2_NORMAL), "h"((uint16_t)3) : "memory");
    else
        asm volatile("{\n.reg .pred p;\nelect.sync _|p, 0xffffffff;\n"
                     "@p cp.async.bulk.tensor.3d.shared::cluster.global.mbarrier::complete_tx::bytes.L2::cache_hint [%0], [%1, {%3, %4, %5}], [%2], %6;\n}"
                     ::"r"(sb + slot * SLOT + off), "l"(m), "r"(sb + BAR_FULL + 8 * slot), "r"(0), "r"(row), "r"(cb),
                     "l"(first ? L2_FIRST : L2_NORMAL) : "memory");
}
__device__ __forceinline__ uint32_t ring_next(uint32_t r) { return r == 4 ? 0 : r + 1; }
__device__ __forceinline__ uint32_t w_table(int hp) { return hp ? 0x3104u : 0x4210u; }
__device__ __forceinline__ uint32_t a_table(int hp) { return hp ? 0x625u : 0x635u; }
__device__ __forceinline__ uint32_t a_next(uint32_t& t) {
    const uint32_t s = t & 15;
    t = (t >> 4) | (s << 8);
    return s;
}
constexpr uint32_t O_TABLE = 0x1604235u;
constexpr uint32_t SL_X = OFF == 0 ? 4 : OFF == 1 ? 3 : 1, SL_WD = OFF == 0 ? 6 : OFF == 1 ? 4 : 3, SL_WF = OFF == 0 ? 5 : OFF == 1 ? 6 : 4;
__device__ __forceinline__ uint32_t o_next(uint32_t& t) {
    const uint32_t s = t & 15;
    t = (t >> 4) | (s << 24);
    return s;
}
__device__ __forceinline__ int o_head(int i, int kh) { return i < 16 ? 4 * (i & 7) + 2 * (kh ^ 1) + (i >> 3) : 29 + 2 * kh; }

template <bool INIT>
__device__ __forceinline__ void gemm_issue(float (&d)[64], uint32_t a, uint32_t b, int acc, bool img) {
    uint64_t da = desc64(a, img ? HI_IMG : HI_128), db = desc64(b, HI_128);
    wg_fence();
#pragma unroll
    for (int k = 0; k < 8; k++) {
        if (INIT && k == 0) wgmma_ss128_init<1>(d, da, db);
        else wgmma_ss128<1>(d, da, db, k ? 1 : acc);
        desc_add(da, !(k & 1) ? 2 : img ? 30 : k == 3 ? 1018 : 2);
        desc_add(db, 128);
    }
    wg_commit();
}

__device__ __forceinline__ void step_retire(uint32_t eb, bool rel, uint32_t pend) {
    wg_wait<0>();
    release_if(eb, pend & 7, rel && (pend & 7) != 7);
    release_if(eb, pend >> 4, rel && pend < 0x70);
}
template <bool ODD>
__device__ __forceinline__ void proj_tile(float (&acc)[64], float (&prev)[64], int t, int q0, uint32_t sb, int wg, uint32_t eb, bool rel, uint32_t& fph,
                                          uint32_t wtab, uint32_t& atab, uint32_t& pend, uint32_t prev_img, uint32_t toff, float s0, float s1,
                                          uint32_t (&v)[32]) {
    const uint32_t a0 = desc_k(sb + (wg ^ (ODD && t == 5)) * 8192), b0 = desc_mn(sb);
    int q = q0;
#pragma unroll 1
    do {
        const uint32_t ws = (wtab >> (4 * q)) & 15, as = a_next(atab);
        if (!ODD && t != 2) slot_wait(sb + BAR_FULL, fph, ws);
        slot_wait(sb + BAR_FULL, fph, as);
        step_retire(eb, rel, pend);
        if (ODD && q == 2 && t == 5) {
            const uint32_t a = sb + 5 * SLOT + q_off(toff);
#pragma unroll
            for (int i = 0; i < 8; i++) sts128(a + (i >> 2) * 16384 + (i & 2) * 256 + (i & 1) * 1024, make_uint4(v[4 * i], v[4 * i + 1], v[4 * i + 2], v[4 * i + 3]));
        }
        bar_sync(1 + wg, 256);
        gemm_issue<false>(acc, a0 + as * (SLOT / 16), b0 + ws * (SLOT / 16), q, false);
        bar_arrive(2 - wg, 256);
        pend = (ODD && q == 1 && t == 5 ? 7 : as) | (ODD && t != 1 ? ws : 7) << 4;
        wg_wait<1>();
        reg_fence(prev);
        if (ODD && t == 5) {
            if (q == 0) {
#pragma unroll
                for (int i = 0; i < 32; i++) {
                    const int k = 16 * (i >> 3) + 4 * (i & 3) + ((i >> 1) & 2);
                    v[i] = pack2(prev[k], prev[k + 1]);
                }
            }
        } else {
            if (q == 0) img_store_global<0>(prev_img, toff, prev, s0, s1);
            if (q == 1) img_store_global<1>(prev_img, toff, prev, s0, s1);
            if (q == 2) img_store_global<2>(prev_img, toff, prev, s0, s1);
            if (q == 3) img_store_global<3>(prev_img, toff, prev, s0, s1);
        }
    } while (++q < (ODD && t == 5 ? 3 : 4));
}

__device__ __forceinline__ void qk_issue(float (&s)[64], uint32_t q, uint32_t k) {
    wg_fence();
    uint64_t da = desc64(q, HI_Q), db = desc64(k, HI_IMG);
    wgmma_ss128_init<0>(s, da, db);
#pragma unroll
    for (int i = 1; i < 8; i++) {
        desc_add(da, (i & 1) ? 2 : i == 4 ? 990 : 30);
        desc_add(db, (i & 1) ? 2 : 30);
        wgmma_ss128<0>(s, da, db, 1);
    }
    wg_commit();
}
__device__ __forceinline__ void qk_issue(float (&s)[32], uint32_t q, uint32_t k) {
    wg_fence();
    uint64_t da = desc64(q, HI_Q), db = desc64(k, HI_IMG);
    wgmma_ss64_init<0>(s, da, db);
#pragma unroll
    for (int i = 1; i < 8; i++) {
        desc_add(da, (i & 1) ? 2 : i == 4 ? 990 : 30);
        desc_add(db, (i & 1) ? 2 : 30);
        wgmma_ss64<0>(s, da, db, 1);
    }
    wg_commit();
}
__device__ __forceinline__ void pv_issue(float (&o)[64], const uint32_t (&p)[32], uint32_t v, int acc, bool half) {
    uint64_t db = desc64(v, HI_IMG);
    if (half) {
        asm volatile("// half" ::: "memory");
        wg_fence();
#pragma unroll
        for (int i = 0; i < 4; i++) {
            wgmma_rs128(o, p[4 * i], p[4 * i + 1], p[4 * i + 2], p[4 * i + 3], db, i ? 1 : acc);
            desc_add(db, 256);
        }
        wg_commit();
        asm volatile("// half" ::: "memory");
    } else {
        wg_fence();
#pragma unroll
        for (int i = 0; i < 8; i++) {
            wgmma_rs128(o, p[4 * i], p[4 * i + 1], p[4 * i + 2], p[4 * i + 3], db, i ? 1 : acc);
            desc_add(db, 256);
        }
        wg_commit();
    }
}
__device__ __forceinline__ void tri_mask(float (&s)[64], float x) {
#pragma unroll
    for (int k = 0; k < 16; k++) {
        float b;
        asm("sub.sat.f32 %0, %1, %2;" : "=f"(b) : "f"((float)(8 * (k >> 1) + (k & 1))), "f"(x));
        const int i = 32 + 4 * (k >> 1) + (k & 1);
        asm("fma.rn.f32 %0, %1, 0fFF61B1E6, %0;" : "+f"(s[i]) : "f"(b));
        if (k < 14) asm("fma.rn.f32 %0, %1, 0fFF61B1E6, %0;" : "+f"(s[i + 6]) : "f"(b));
    }
}
__device__ __forceinline__ void tri_mask_copy(float (&s)[64], const float (&h)[32], float x) {
#pragma unroll
    for (int i = 0; i < 32; i++) {
            asm("{\n.reg .pred p;\nsetp.lt.f32 p, %2, %3;\nselp.f32 %0, 0fFF800000, %1, p;\n}"
                : "=f"(s[i]) : "f"(h[i]), "f"(x), "f"((float)(8 * (i >> 2) - 4 * (i & 2) + (i & 1))));
        s[32 + i] = __uint_as_float(0xff800000u);
    }
}
constexpr float SM_HI = 1152921504606846976.f, SM_LO = 1.f / 1152921504606846976.f;
__device__ __forceinline__ bool softmax_unsafe(float t0, float t1, bool first) {
    bool bad = __any_sync(0xffffffffu, fmaxf(t0, t1) > SM_HI);
    if (first) {
        uint32_t a = __ballot_sync(0xffffffffu, t0 >= SM_LO), b = __ballot_sync(0xffffffffu, t1 >= SM_LO);
        a |= a >> 1;
        b |= b >> 1;
        bad |= ((a | (a >> 2)) & (b | (b >> 2)) & 0x11111111u) != 0x11111111u;
    }
    return bad;
}
__device__ __forceinline__ void softmax_remax(const float (&s)[64], float (&m)[2], bool first, float& m0, float& m1, float& a0, float& a1) {
    m0 = fmaxf(s[0], s[1]), m1 = fmaxf(s[2], s[3]);
#pragma unroll
    for (int k = 1; k < 16; k++) {
        m0 = fmaxf(m0, fmaxf(s[4 * k], s[4 * k + 1]));
        m1 = fmaxf(m1, fmaxf(s[4 * k + 2], s[4 * k + 3]));
    }
    m0 = fmaxf(m0, __shfl_xor_sync(0xffffffffu, m0, 1));
    m1 = fmaxf(m1, __shfl_xor_sync(0xffffffffu, m1, 1));
    m0 = fmaxf(m0, __shfl_xor_sync(0xffffffffu, m0, 2));
    m1 = fmaxf(m1, __shfl_xor_sync(0xffffffffu, m1, 2));
    if (!first) {
        m0 = fmaxf(m0, 0.f);
        m1 = fmaxf(m1, 0.f);
    }
    a0 = first ? 1.f : ex2(-m0);
    a1 = first ? 1.f : ex2(-m1);
    m[0] += m0;
    m[1] += m1;
}
template <int J0, int J1>
__device__ __forceinline__ void softmax_exp(const float (&s)[64], uint32_t (&p)[32], float (&t)[4]) {
#pragma unroll
    for (int k = J0; k < J1; k++) {
        const float e0 = ex2(s[4 * k]), e1 = ex2(s[4 * k + 1]), e2 = ex2(s[4 * k + 2]), e3 = ex2(s[4 * k + 3]);
        if (k == 0) { t[0] = e0; t[1] = e1; t[2] = e2; t[3] = e3; }
        else { t[0] += e0; t[1] += e1; t[2] += e2; t[3] += e3; }
        p[2 * k] = pack2(e0, e1);
        p[2 * k + 1] = pack2(e2, e3);
    }
}
__device__ __forceinline__ void mma16816(float (&d)[4], const uint32_t* a, uint32_t b0, uint32_t b1) {
    asm("mma.sync.aligned.m16n8k16.row.col.f32.bf16.bf16.f32 {%0, %1, %2, %3}, {%4, %5, %6, %7}, {%8, %9}, {%0, %1, %2, %3};"
        : "+f"(d[0]), "+f"(d[1]), "+f"(d[2]), "+f"(d[3]) : "r"(a[0]), "r"(a[1]), "r"(a[2]), "r"(a[3]), "r"(b0), "r"(b1));
}
__device__ __forceinline__ uint2 best_key(const uint32_t* keys, int lane, uint32_t ep, uint32_t cur, int enough) {
#pragma unroll 1
    for (;;) {
        const uint4 k = ld_poll(reinterpret_cast<const uint4*>(keys) + lane);
        const bool ok = (((k.x ^ ep) | (k.y ^ ep) | (k.z ^ ep) | (k.w ^ ep)) & 31) == 0;
        const uint32_t best = __reduce_max_sync(0xffffffffu, ok ? max(max(k.x, k.y), max(k.z, k.w)) : 0u);
        const int n = __popc(__ballot_sync(0xffffffffu, ok));
        if (n == 32 || (n >= enough && best != cur)) return make_uint2(best, n == 32);
        __nanosleep(KSLEEP);
    }
}

__global__ void __cluster_dims__(2, 1, 1) __launch_bounds__(384, 1)
fused_kernel(const __grid_constant__ CUtensorMap tm_ckv, const __grid_constant__ CUtensorMap tm_wq,
             const __grid_constant__ CUtensorMap tm_wuk, const __grid_constant__ CUtensorMap tm_wuv,
             const __grid_constant__ CUtensorMap tm_wo, const __grid_constant__ CUtensorMap tm_wg,
             const __grid_constant__ CUtensorMap tm_wu,
             const __grid_constant__ CUtensorMap tm_wm, const __grid_constant__ CUtensorMap tm_x, const Params P) {
    extern __shared__ __align__(1024) uint8_t smem[];
    const uint32_t sb = (uint32_t)__cvta_generic_to_shared(smem);
    const int tid = threadIdx.x, lane = tid & 31, warp = __shfl_sync(0xffffffffu, tid >> 5, 0), wg = warp >> 2;
    const uint32_t sm = blockIdx.x < 8 ? blockIdx.x + 124 : blockIdx.x - 8, smq = ((sm - 64) * 147) >> 11;
    const int rb = sm < 64 ? (sm & 14) * 8 + (sm >> 4) * 2 + (sm & 1)
                 : sm < 120 ? ((sm - 64 - smq * 14) & 14) * 8 + 24 + smq * 2 + (sm & 1) : sm < 124 ? sm + 8 : sm - 116;
    const int grp = rb >> 3, j = rb & 7, kh = (grp >> 1) & 1;
    const int cq = (j & 1) + ((grp >> 1) & 2), ort = (grp & 8) + (grp & 1) * 4 + (j >> 1);
    if (warp == 0) TS(0);

    const CUtensorMap* tw = (j & 1) ? &tm_wuv : &tm_wuk;
    if (lane == 0) {
        if (warp == 8) {
#pragma unroll
            for (int i = 0; i < 7; i++) mbar_init(sb + BAR_FULL + 8 * i, 1);
            fence_async_smem();
        } else if (warp < 11) {
            const int w = warp - (warp > 8);
            const u64 cnt = (w < 5 ? (rb < NCTA ? 0x888888884444444ull : 0x888888888888888ull) : 0x111812111111118ull) >> (12 * (w % 5));
#pragma unroll
            for (int i = 0; i < 3; i++) mbar_init(sb + BAR_EMPTY + 24 * w + 8 * i, ((uint32_t)cnt >> (4 * i)) & 15);
        }
        asm volatile("fence.mbarrier_init.release.cluster;" ::: "memory");
    }
    __syncwarp();
    asm volatile("barrier.cluster.arrive.relaxed.aligned;" ::: "memory");
    if (warp == 8) {
        if (rb < NCTA) {
#pragma unroll 1
            for (int u = 0; u < 4; u++) {
                const uint32_t ws = u + (u == 3), as = (0x635u >> (4 * u)) & 15;
                slot_expect(sb, ws);
                load_tile(sb, ws, 0, tw, u * 128, 4 * grp, false, HINT & 1);
                if (u == 3) break;
                slot_expect(sb, as);
                load_tile(sb, as, 0, &tm_ckv, (j >> 1) * 128, u * 2, false, false);
                load_tile(sb, as, 16384, &tm_ckv, (j >> 1) * 128, u * 2 + 1, false, false);
            }
        } else {
#pragma unroll 1
            for (int i = 0; i < 6; i++) {
                slot_expect(sb, i);
                load_tile(sb, i, 0, &tm_wm, i * 64, (rb - NCTA) * 4, false, HINT & 64);
                if (i > 3) tma3d_prefetch(&tm_wm, i * 64 + 128, (rb - NCTA) * 4);
            }
        }
    }
    asm volatile("barrier.cluster.wait.aligned;" ::: "memory");

    if (rb >= NCTA) {
        const int sp = rb - NCTA;
        const uint32_t ep = __ldcg(&g_sync.epoch[0]) + 1;
        uint32_t ph = 0, sl = 0;
        if (warp == 8) {
#pragma unroll 1
            for (int i = 6; i < 54 + 2 * OFF; i++) {
                slot_acquire(sb, ph, sl);
                const int k = i - 24;
                load_tile(sb, sl, 0, i < 24 ? &tm_wm : i >= 54 ? &tm_wo : (k & 2) ? &tm_wu : &tm_wg, i < 24 ? (i & 7) * 64 : i >= 54 ? (i - 38 - 2 * OFF) * 256 : (k & 1) * 256,
                          i < 24 ? (i >> 3) * 16 + sp * 4 : i >= 54 ? sp * 2 : sp * 7 + (k >> 2), false, true);
                if (++sl == 6) sl = 0;
                if (i == 51) { i = 53; sl = 0; }
            }
            bar_sync(4, 64);
            slot_wait(sb + BAR_EMPTY, ph, 4);
            slot_wait(sb + BAR_EMPTY, ph, 5);
            ph = 0x3f, sl = 0;
#pragma unroll 1
            for (int h = 0; h < 32; h++) {
                step_watch(sb + SM_EP + 16, h + 1);
                fence_async_global();
                const uint8_t* src = g_ctx + (size_t)(((h >> 1) ^ 8) * 32 + 30 - 4 * OFF) * SLOT + (h & 1) * 16384;
#pragma unroll 1
                for (int k = 0; k <= 2 * OFF; k++, src += 2 * SLOT) {
                    slot_wait(sb + BAR_DONE, ph, sl);
                    const uint32_t f = sb + BAR_FLAG + 8 * sl, d = sb + 4 * SLOT + sl * 16384;
                    asm volatile("{\n.reg .pred p;\nelect.sync _|p, 0xffffffff;\n@p mbarrier.arrive.expect_tx.shared::cta.b64 _, [%0], 16384;\n}" ::"r"(f) : "memory");
                    if (k == 0)
                        asm volatile("{\n.reg .pred p;\nelect.sync _|p, 0xffffffff;\n"
                                     "@p cp.async.bulk.tensor.3d.shared::cluster.global.mbarrier::complete_tx::bytes [%0], [%1, {%3, %4, %5}], [%2];\n}"
                                     ::"r"(d), "l"(&tm_x), "r"(f), "r"(0), "r"((h ^ 16) * 64), "r"(sp * 2) : "memory");
                    else
                        asm volatile("{\n.reg .pred p;\nelect.sync _|p, 0xffffffff;\n"
                                     "@p cp.async.bulk.shared::cluster.global.mbarrier::complete_tx::bytes [%0], [%1], 16384, [%2];\n}"
                                     ::"r"(d), "l"(src), "r"(f) : "memory");
                    if (++sl == 6) sl = 0;
                }
            }
        } else if (warp == 9) {
#pragma unroll 1
            for (int t = 0; t <= 16; t++) {
                asm volatile("st.release.cta.shared.u32 [%0], %1;" ::"r"(sb + SM_EP + 16), "r"(2 * t) : "memory");
                if (t == 0) bar_sync(4, 64);
                if (lane < 4 && t < 16) flag_wait(&g_sync.ctxcnt[(t ^ 8) * 32 + 24 + 2 * lane], ep);
                __syncwarp();
            }
        } else if (warp < 8) {
            const uint32_t c2 = __ldg(reinterpret_cast<const uint32_t*>(P.c) + tid);
            uint32_t* sc = reinterpret_cast<uint32_t*>(smem + SM_TAB);
            sc[tid] = pack2(bf_lo(c2) * sigmoid(bf_lo(c2)), bf_hi(c2) * sigmoid(bf_hi(c2)));
            bar_sync(1, 256);
            const uint32_t a = sb + (warp >> 1) * 8192 + ((lane >> 4) * 8 + (lane & 7)) * 128, ch = (warp & 1) * 4 + ((lane >> 3) & 1);
#pragma unroll 1
            for (int ps = 0; ps < 3; ps++) {
                float d[2][4] = {};
#pragma unroll 1
                for (int bt = 0; bt < 8; bt++) {
                    slot_wait(sb + BAR_FULL, ph, sl);
#pragma unroll
                    for (int i = 0; i < 8; i++) {
                        uint32_t w[4];
                        asm volatile("ldmatrix.sync.aligned.m8n8.x4.trans.shared.b16 {%0, %1, %2, %3}, [%4];" : "=r"(w[0]), "=r"(w[1]), "=r"(w[2]), "=r"(w[3])
                                     : "r"(a + sl * SLOT + (i >> 1) * 2048 + (((ch + 2 * (i & 1)) ^ (lane & 7)) << 4)) : "memory");
                        mma16816(d[i & 1], w, sc[bt * 32 + (i >> 1) * 8 + (lane & 3)], sc[bt * 32 + (i >> 1) * 8 + 4 + (lane & 3)]);
                    }
                    __syncwarp();
                    mbar_arrive_if(sb + BAR_EMPTY + 8 * sl, lane == 0);
                    if (++sl == 6) sl = 0;
                }
                const float v = (lane & 2) ? ((lane & 1) ? d[1][2] : d[1][0]) : ((lane & 1) ? d[0][2] : d[0][0]);
                const int col = sp * 256 + warp * 32 + (lane & 3) * 8 + (lane >> 2);
                if (ps == 0) st_pub(g_mod1 + col, (pack2(0.f, v) & 0xffff0000u) | (ep & 0xffffu), true);
                else g_mod[ps * 1024 + col] = __float2bfloat16_rn(v);
                if (warp == 0) TS(1 + ps);
            }
#pragma unroll 1
            for (int k = 0; k < 28; k++) {
                slot_wait(sb + BAR_FULL, ph, sl);
                uint4* dst = reinterpret_cast<uint4*>(g_wf) + (sp * 28 + (k & ~3)) * 2048 + (k & 3) * 512 + tid;
#pragma unroll 4
                for (int i = 0; i < 8; i++) {
                    const int row = (i & 1) * 128 + (tid >> 1);
                    __stcs(dst + (i >> 1) * 2048 + (i & 1) * 256, lds128(sb + sl * SLOT + row * 128 + ((((i & 6) + ((tid ^ (row >> 2)) & 1)) ^ (row & 7)) << 4)));
                }
                __syncwarp();
                mbar_arrive_if(sb + BAR_EMPTY + 8 * sl, lane == 0);
                if (++sl == 6) sl = 0;
            }
            bar_sync(1, 256);
            if (tid < 2) {
                flag_add(&g_sync.cnt[7 * 8]);
                flag_wait(&g_sync.cnt[7 * 8], 8 * ep);
            }
            if (warp == 0) TS(4);
            bar_sync(1, 256);
            uint32_t ga[16], x2[32];
#pragma unroll
            for (int i = 0; i < 16; i++) ga[i] = __ldcg(reinterpret_cast<const uint32_t*>(g_mod) + 512 + sp * 64 + (lane & 3) + 4 * i);
#pragma unroll 1
            for (int i = 0; i < 2 * OFF; i++) slot_wait(sb + BAR_FULL, ph, i);
            float d[64];
            uint32_t u = (2 * OFF + 1) * wg, up = 0;
            if (wg == 1) bar_arrive(2, 256);
#pragma unroll 1
            for (int h = wg; h < 32; h += 2) {
                mbar_wait(sb + BAR_FLAG + 8 * u, up);
                const uint32_t xa = sb + 4 * SLOT + u * 16384 + ((warp & 3) * 16 + (lane & 15)) * 128;
#pragma unroll
                for (int k = 0; k < 8; k++)
                    asm volatile("ldmatrix.sync.aligned.m8n8.x4.shared.b16 {%0, %1, %2, %3}, [%4];"
                                 : "=r"(x2[4 * k]), "=r"(x2[4 * k + 1]), "=r"(x2[4 * k + 2]), "=r"(x2[4 * k + 3])
                                 : "r"(xa + (k >> 2) * 8192 + (((2 * (k & 3) + (lane >> 4)) ^ (lane & 7)) << 4)) : "memory");
                mbar_arrive_if(sb + BAR_DONE + 8 * u, lane < 2);
                bar_sync(2 + wg, 256);
#pragma unroll 1
                for (int k = 0; k < 2 * OFF; k++) {
                    const uint32_t pu = u;
                    if (++u == 6) { u = 0; up ^= 1; }
                    mbar_wait(sb + BAR_FLAG + 8 * u, up);
                    gemm_issue<false>(d, desc_k(sb + 4 * SLOT) + u * 1024, desc_mn(sb) + k * (SLOT / 16), k, true);
                    wg_wait<1>();
                    mbar_arrive_if(sb + BAR_DONE + 8 * pu, lane < 2 && k);
                }
                if (h < 31) bar_arrive(3 - wg, 256);
                wg_wait<0>();
                reg_fence(d);
                mbar_arrive_if(sb + BAR_DONE + 8 * u, lane < 2);
                u += 2 * OFF + 2;
                if (u >= 6) { u -= 6; up ^= 1; }
                uint4* op = g_x2 + ((h ^ 16) * 4 + sp) * 1024 + (tid & 127);
#pragma unroll
                for (int v = 0; v < 8; v++) {
                    uint32_t y[4];
#pragma unroll
                    for (int i = 0; i < 4; i++) {
                        const int k = 4 * v + i;
                        y[i] = pack2(fmaf(bf_lo(ga[k >> 1]), d[2 * k], bf_lo(x2[k])), fmaf(bf_hi(ga[k >> 1]), d[2 * k + 1], bf_hi(x2[k])));
                    }
                    op[v * 128] = make_uint4(y[0], y[1], y[2], y[3]);
                }
            }
            bar_sync(1, 256);
            if (tid == 0) flag_add(&g_sync.cnt[15 * 8]);
            if (warp == 0) TS(5);
        }
        return;
    }

    if (wg == 2) {
        asm volatile("setmaxnreg.dec.sync.aligned.u32 40;");
        if (warp == 8) {
            const uint32_t rank = j & 1, half = rank * 16384;
            uint32_t eph = 0, r = 0;
            *reinterpret_cast<volatile uint32_t*>(smem + SM_EP + 20) = 0;
#pragma unroll 1
            for (int hp = 0; hp < 2; hp++) {
                uint32_t wtab = w_table(hp), atab = a_table(hp);
                const int hc = 4 * grp + 2 * hp;
#pragma unroll 1
                for (int u = 3 - 3 * hp; u < 16; u++) {
                    if (hp && u < 4) {
                        const uint32_t ws = (wtab >> (4 * u)) & 15;
                        slot_acquire(sb, eph, ws);
                        load_tile(sb, ws, 0, tw, u * 128, hc, false, HINT & 1);
                        PT();
                    }
                    if (hp == 1 && (u & 7) == 4) mbar_wait(sb + BAR_FLAG + 24 + (u & 8), 0);
                    const uint32_t as = a_next(atab);
                    slot_acquire(sb, eph, as);
                    load_tile(sb, as, half, &tm_ckv, ((u & 12) + (j >> 1)) * 128, (u & 3) * 2 + rank, true, (HINT & 8) && hp);
                    PT();
                    if (hp == 1 && (u | 2) == 3 && lane == 0)
                        asm volatile("red.relaxed.gpu.global.add.u32 [%0], 1;" ::"l"(&g_sync.cnt[(grp * 8 + 3 + (u >> 1)) * 8]) : "memory");
                }
                const uint8_t* src = g_h + (15 - j) * 4 * SLOT;
#pragma unroll 1
                for (int u = 0; u < 8; u++) {
                    if (u == 0 || u == KVG) {
                        mbar_wait(sb + BAR_FLAG + (u ? 8 + 32 * hp : 0), 0);
                        fence_async_global();
                    }
                    if (u < 4) {
                        const uint32_t ws = (wtab >> (4 * u)) & 15;
                        slot_acquire(sb, eph, ws);
                        load_tile(sb, ws, 0, &tm_wq, u * 128, hc, false, HINT & 1);
                        PT();
                    }
                    const uint32_t as = a_next(atab);
                    slot_acquire(sb, eph, as);
                    load_bulk(sb, as, 0, src, SLOT, false, (HINT & 8) && hp);
                    PT();
                    src += u == 3 ? (8 * j - 63) * SLOT : SLOT;
                }
                const int step = hp ? -2 * SLOT : 2 * SLOT;
                src = g_KV + (size_t)(grp * 32 + 30 * hp) * SLOT + half - step;
#pragma unroll 1
                for (int n = 0; n <= 17; n++) {
                    if (n == 8) {
                        mbar_wait(sb + BAR_FLAG + 16 + 32 * hp, 0);
                        fence_async_global();
                    }
                    const uint8_t* v = src + SLOT;
                    src += n < 16 - j ? step : n == 16 - j ? (2 * j - 15) * step : -step;
                    if (n < 17) {
                        slot_acquire(sb, eph, r);
                        if (n != 15 - (j & 6)) load_bulk(sb, r, half, src, SLOT / 2, true, HINT & 4);
                        else load_bulk(sb, r, 0, src - half, SLOT, false, HINT & 4);
                        PT();
                        r = ring_next(r);
                    }
                    if (n) {
                        slot_acquire(sb, eph, r);
                        if (n != 16 - (j & 6)) load_bulk(sb, r, half, v, SLOT / 2, true, HINT & 4);
                        else load_bulk(sb, r, 0, v - half, SLOT, false, HINT & 4);
                        PT();
                        r = ring_next(r);
                    }
                    asm volatile("st.volatile.shared.u32 [%0], %1;" ::"r"(sb + SM_EP + 16), "r"(18 * hp + n + 1) : "memory");
                }
            }
            uint32_t otab = O_TABLE, ready = 0;
#pragma unroll 1
            for (int i = 0; i < 17; i += i == 7 - OFF ? 1 + OFF : 1) {
                const bool dyn = i >= 8 && i < 15;
                const uint32_t want = dyn ? 15u << (4 * (i - 8)) : 1u << max(i + 14, 28);
                if (!(ready & want)) {
                    do {
                        asm volatile("ld.acquire.cta.shared.u32 %0, [%1];" : "=r"(ready) : "r"(sb + SM_EP + 20) : "memory");
                        ready = __shfl_sync(0xffffffffu, ready, 0);
                    } while (!(ready & want));
                    fence_async_global();
                }
                const int head = o_head(dyn ? (ready >> (4 * (i - 8))) & 15 : i, kh);
                const uint32_t as = o_next(otab), ws = o_next(otab), off = i < 15 ? half : kh * 16384;
                slot_acquire(sb, eph, as);
                load_bulk(sb, as, off, g_ctx + (size_t)(ort * 32 + head) * SLOT + off, SLOT / 2, i < 15, HINT & 16);
                if (i >= 15) load_bulk(sb, as, off ^ 16384, i == 15 ? g_x2 + ((ort * 2 + kh) * 4 + cq) * 1024 : reinterpret_cast<const uint4*>(P.wdown) + min(rb, NFFN - 1) * 1024, SLOT / 2, false, false);
                PT();
                slot_acquire(sb, eph, ws);
                load_tile(sb, ws, 0, &tm_wo, head * 128, cq * 2, false, HINT & 2);
                PT();
                if (i == 0) o_next(otab);
            }
            if (rb < NFFN) {
                slot_acquire(sb, eph, SL_WF);
                load_bulk(sb, SL_WF, 0, g_wf + rb * SLOT, SLOT, false, false);
            }
        } else if (warp == 9) {
            *reinterpret_cast<volatile uint32_t*>(smem + SM_EP + 16) = 0;
            l2_prefetch(P.ckv + rb * 2048, 4096);
            mbar_watch(sb + BAR_FULL, 0);
            l2_prefetch(P.ckv + 512 * 512 + rb * 2048, 4096);
            mbar_watch(sb + BAR_FULL + 8 * XPF, 0);
            l2_prefetch(P.x + rb * 8192, 16384);
            mbar_watch(sb + BAR_FULL + 8 * 4, 0);
            l2_prefetch(P.ckv + 1024 * 512 + rb * 4096, 8192);
            TS(40);
#pragma unroll 1
            for (int i = 0; i < 13; i++) {
                step_watch(sb + SM_EP + 16, i == 0 ? 0 : i < 5 ? PFA + i : 13 + PFB + i);
                if (i == 10) mbar_watch(sb + BAR_FLAG + 8 * 7, 0);
                const int rf = min(rb, NFFN - 1), pc = 4 * (i - 5) + cq;
                const uint8_t* p = i == 3 ? reinterpret_cast<const uint8_t*>(P.ckv) + rb * 16384
                                 : i == 4 ? g_h + rb * 16384
                                 : i < 8 ? g_ctx + (size_t)(ort * 32 + o_head(pc >> 1, kh)) * SLOT + (pc & 1) * 16384
                                 : i < 10 ? reinterpret_cast<const uint8_t*>(P.wo) + (grp * 16 + (i & 1) * 8 + j) * 16384
                                 : i == 10 ? reinterpret_cast<const uint8_t*>(P.wdown) + rf * 16384 : g_wf + rf * SLOT + (i & 1) * 16384;
                if (i >= 3) l2_prefetch(p, 16384);
                else if ((i | j) & 1) tma3d_prefetch(i == 1 ? tw : &tm_wq, (j >> 1) * 128, grp * 4 + (i ? 2 : 0));
            }
            const uint32_t v = lds32(sb + SM_EP) - 1;
            sts128(sb + SM_RED + lane * 16, make_uint4(v, v, v, v));
            fence_async_smem();
            __syncwarp();
#pragma unroll 1
            for (int i = 0; i < OB / 32; i++) bulk_store(g_out + rb * OB + i * 32, sb + SM_RED, 512, false);
            asm volatile("cp.async.bulk.commit_group;\ncp.async.bulk.wait_group 0;" ::: "memory");
            fence_async_global();
            __syncwarp();
            mbar_arrive_if(sb + BAR_PF, lane == 0);
            if (lane == 0) mbar_watch(sb + BAR_END, 0);
        } else {
            const uint32_t ep = __ldcg(&g_sync.epoch[0]) + 1;
            asm volatile("st.shared.u32 [%0], %1;" ::"r"(sb + SM_EP), "r"(ep) : "memory");
            mbar_wait(sb + BAR_FULL + 8 * 4, 0);
            {
                uint4 v[4];
                for (;;) {
                    uint32_t bad = 0;
#pragma unroll
                    for (int k = 0; k < 4; k++) v[k] = ld_poll(reinterpret_cast<const uint4*>(g_mod1) + (warp & 1) * 128 + k * 32 + lane);
#pragma unroll
                    for (int k = 0; k < 4; k++) bad |= (v[k].x ^ ep) | (v[k].y ^ ep) | (v[k].z ^ ep) | (v[k].w ^ ep);
                    if (__all_sync(0xffffffffu, (bad & 0xffff) == 0)) break;
                    __nanosleep(100);
                }
                const uint32_t one = (warp & 1) ? ONE2 : 0x80008000u;
#pragma unroll
                for (int k = 0; k < 4; k++)
                    *reinterpret_cast<uint2*>(smem + SM_TAB + (warp & 1) * 1024 + k * 256 + lane * 8) =
                        make_uint2(badd(__byte_perm(v[k].x, v[k].y, 0x7632), one), badd(__byte_perm(v[k].z, v[k].w, 0x7632), one));
            }
            __syncwarp();
            mbar_arrive_if(sb + BAR_FLAG + 8 * 8, lane == 0);
            if (warp == 10) {
#pragma unroll 1
                for (int i = 0; i < 9; i++) {
                    mbar_sleep(sb + BAR_DONE + 8 * i);
                    if (lane == 0) flag_add(i && ((i - 1) & 2) ? &g_sync.ctxcnt[((i & 1) ? 15 - j : j) * 32 + 2 * grp + (i > 4)] : &g_sync.cnt[(grp * 8 + i) * 8]);
                    if (i == 0) TS(43);
                }
            } else {
                TS(42);
#pragma unroll 1
                for (int i = 0; i < 8; i++) {
                    mbar_sleep(sb + BAR_DONE + 8 * (i == 7 ? 6 : i == 4 ? 3 : i));
                    if (lane < 2) flag_wait(&g_sync.cnt[((i == 0 ? (lane ? j : 15 - j) : i == 7 ? 0 : grp) * 8 + i) * 8], 8 * ep);
                    __syncwarp();
                    mbar_arrive_if(sb + BAR_FLAG + 8 * i, lane == 0 && i < 7);
                    TS(48 + i);
                }
                const uint32_t *mp = reinterpret_cast<const uint32_t*>(g_mod) + lane, *wp = reinterpret_cast<const uint32_t*>(P.wr) + lane;
                float ra = 0.f, rs = 0.f;
#pragma unroll 1
                for (int k = 0; k < 256; k += 32) {
                    const uint32_t ga = __ldcg(mp + 512 + k), sh = __ldcg(mp + 768 + k), c1 = badd(__ldcg(mp + 1024 + k), ONE2);
                    const uint32_t gb = __ldcg(mp + 1280 + k), ww = __ldg(wp + k);
                    const uint32_t a = bmul(c1, ww);
                    ra += bf_lo(a) + bf_hi(a);
                    rs = fmaf(bf_lo(sh), bf_lo(ww), fmaf(bf_hi(sh), bf_hi(ww), rs));
                    if (k >> 6 == cq) {
                        sts128(sb + SM_TAB + ((k & 32) + lane) * 16, make_uint4(ga << 16, ga & 0xffff0000u, a, 0));
                        sts128(sb + SM_TAB + 1024 + ((k & 32) + lane) * 16, make_uint4(c1, sh, gb, 0));
                    }
                }
#pragma unroll 1
                for (int o = 16; o > 0; o >>= 1) {
                    ra += __shfl_xor_sync(0xffffffffu, ra, o);
                    rs += __shfl_xor_sync(0xffffffffu, rs, o);
                }
                *reinterpret_cast<float2*>(smem + SM_EP + 8) = make_float2(ra, rs);
                __syncwarp();
                mbar_arrive_if(sb + BAR_FLAG + 8 * 7, lane == 0);
                const uint32_t* f = lane < 17 ? &g_sync.ctxcnt[ort * 32 + o_head(lane, kh)] : &g_sync.cnt[15 * 8];
                uint32_t ready = -(j & 1), list = 0, sh = 0, qa;
                asm("mapa.shared::cluster.u32 %0, %1, %2;" : "=r"(qa) : "r"(sb + SM_EP + 20), "r"(lane & 1));
                while (ready != ~0u) {
                    uint32_t v;
                    asm volatile("ld.acquire.gpu.global.u32 %0, [%1];" : "=r"(v) : "l"(f) : "memory");
                    const uint32_t now = __ballot_sync(0xffffffffu, (int)(v - (lane < 17 ? ep : NSPARE * ep)) >= 0);
#pragma unroll 1
                    for (uint32_t fresh = now & ~ready & 0x7f00; fresh; fresh &= fresh - 1, sh += 4) list |= (__ffs(fresh) - 1) << sh;
                    list |= (((now & 0xff) + 1) >> 8 << 28) | ((now & (now >> 2) & 0x18000) << 14);
                    if (now != ready && lane < 2) asm volatile("st.relaxed.cluster.shared::cluster.u32 [%0], %1;" ::"r"(qa), "r"(list) : "memory");
                    if ((now & 0xff) == 0xff) mbar_sleep(sb + BAR_DONE + 8 * 7);
                    ready = now;
                    __nanosleep(POLL_NS);
                }
                TS(45);
            }
        }
    } else {
        const bool elected = (tid & 127) == 0, rel = (tid & 95) == 0;
        uint32_t eb;
        asm("mapa.shared::cluster.u32 %0, %1, %2;" : "=r"(eb) : "r"(sb + BAR_EMPTY), "r"(warp & 1));
        const int g = lane >> 2, c4 = lane & 3;
        uint32_t toff = warp * 4096 + g * 64 + ((c4 ^ (g >> 1)) << 4);
        uint32_t fph = 0x3f, r = 0;
        if (wg == 1) bar_arrive(1, 256);
        const uint32_t kd = desc_k(sb), wd = desc_mn(sb), vd = ((sb & 0x3ffff) >> 4) | (32u << 16);
        const int nL = 16 - j, hn = nL - 1 + wg;
        float s[64], o[64], li[2] = {0.f, 0.f};
        uint32_t cimg = 0;
        const float sc = (j & 1) ? 1.f : SM_C;
#pragma unroll 1
        for (int q = 0; q < 3; q++) {
            const uint32_t as = (0x635u >> (4 * q)) & 15;
            mbar_wait(sb + BAR_FULL + 8 * q, 0);
            mbar_wait(sb + BAR_FULL + 8 * as, 0);
            bar_sync(1 + wg, 256);
            gemm_issue<false>(s, kd + wg * 512 + as * (SLOT / 16), wd + q * (SLOT / 16), q, false);
            bar_arrive(2 - wg, 256);
            wg_wait<0>();
            release_if(eb, as, rel);
        }
        {
            const int xrow = rb * 16 + warp * 2;
            const uint4* xp = reinterpret_cast<const uint4*>(P.x) + xrow * 64;
            const uint32_t img = (grp * 32 + j) * SLOT;
            uint32_t x[16], x0[2];
            float st[4] = {0.f, 0.f, 0.f, 0.f};
            mbar_wait(sb + BAR_FULL + 8 * 4, 0);
#pragma unroll
            for (int q = 3; q < 8; q++) {
                const uint32_t ws = (0x4210u >> (4 * (q & 3))) & 15, as = (0x635u >> (4 * (q % 3))) & 15;
                mbar_wait(sb + BAR_FULL + 8 * as, (q / 3) & 1);
                bar_sync(1 + wg, 256);
                if (q == 3) gemm_issue<false>(s, kd + wg * 512 + as * (SLOT / 16), wd + ws * (SLOT / 16), 1, false);
                else if (q == 4) gemm_issue<true>(o, kd + wg * 512 + as * (SLOT / 16), wd + ws * (SLOT / 16), 0, false);
                else gemm_issue<false>(o, kd + wg * 512 + as * (SLOT / 16), wd + ws * (SLOT / 16), 1, false);
                bar_arrive(2 - wg, 256);
                sched_fence(fph, P.zero);
                if (q > 3) reg_fence(s);
                if (q == 3) {
                    asm volatile("setmaxnreg.inc.sync.aligned.u32 232;");
#pragma unroll
                    for (int i = 0; i < 4; i++)
                        asm volatile("ld.global.nc.v4.u32 {%0, %1, %2, %3}, [%4];" : "=r"(x[4 * i]), "=r"(x[4 * i + 1]), "=r"(x[4 * i + 2]), "=r"(x[4 * i + 3])
                                     : "l"(xp + lane + 32 * i) : "memory");
#pragma unroll
                    for (int i = 0; i < 2; i++) asm volatile("ld.global.nc.u32 %0, [%1];" : "=r"(x0[i]) : "l"(xp + 64 * i) : "memory");
                }
                if (q == 4) {
                    img_store_global<0>(img, toff, s, sc, sc);
#pragma unroll
                    for (int k = 0; k < 16; k++) {
                        const float d0 = bf_lo(x[k]) - bf_lo(x0[k >> 3]), d1 = bf_hi(x[k]) - bf_lo(x0[k >> 3]);
                        st[k >> 3] += d0 + d1;
                        st[2 + (k >> 3)] = fmaf(d0, d0, fmaf(d1, d1, st[2 + (k >> 3)]));
                    }
#pragma unroll
                    for (int i = 0; i < 4 * NSH; i++) st[i & 3] += __shfl_xor_sync(0xffffffffu, st[i & 3], 1 << (i >> 2));
                    reg_fence(st);
                }
                if (q == 5) {
#pragma unroll
                    for (int i = 4 * NSH; i < 20; i++) st[i & 3] += __shfl_xor_sync(0xffffffffu, st[i & 3], 1 << (i >> 2));
                    img_store_global<1>(img, toff, s, sc, sc);
#pragma unroll
                    for (int i = 0; i < 2; i++) {
                        const float d = st[i] * (1.f / 512.f);
                        st[2 + i] = ln_rstd(fmaxf(fmaf(-d, d, st[2 + i] * (1.f / 512.f)), 0.f));
                        x0[i] = pack2(bf_lo(x0[i]) + d, bf_lo(x0[i]) + d);
                    }
                    reg_fence(st);
                    reg_fence(x0);
                }
                if (q > 5) {
                    if (q == 6) mbar_wait(sb + BAR_FLAG + 8 * 8, 0);
                    const uint4 a = lds128(sb + SM_TAB + 1024 + (q & 1) * 512 + lane * 16), c = lds128(sb + SM_TAB + (q & 1) * 512 + lane * 16);
                    uint8_t* hp = g_h + (grp * 8 + (q & 1) * 4 + (lane >> 3)) * 16384 + (xrow & 127) * 128;
#pragma unroll
                    for (int i = 0; i < 2; i++) {
                        const uint32_t* y = x + 8 * i + 4 * (q & 1);
                        *reinterpret_cast<uint4*>(hp + i * 128 + (((lane ^ xrow ^ i) & 7) << 4)) =
                            make_uint4(ln_apply(y[0], x0[i], st[2 + i], a.x, c.x), ln_apply(y[1], x0[i], st[2 + i], a.y, c.y),
                                       ln_apply(y[2], x0[i], st[2 + i], a.z, c.z), ln_apply(y[3], x0[i], st[2 + i], a.w, c.w));
                    }
                    if (q == 7) {
                        __syncwarp();
                        mbar_arrive_if(sb + BAR_DONE, lane == 0);
                    }
                    if (q == 6) img_store_global<2>(img, toff, s, sc, sc);
                    else img_store_global<3>(img, toff, s, sc, sc);
                }
                if (q < 7) {
                    sched_fence(fph, P.zero);
                    wg_wait<0>();
                    release_if(eb, as, rel);
                }
            }
        }
        uint32_t pend = 0x73;
        uint32_t p[32] = {};
#pragma unroll 1
        for (int hp = 0; hp < 2; hp++) {
            float m[2] = {0.f, 0.f}, l[2] = {0.f, 0.f}, t[4] = {0.f, 0.f, 0.f, 0.f};
            bool shifted = false, bad = false, plain = false;
            uint32_t qa = desc_k(sb + 5 * SLOT + (wg ^ 1) * 8192);
            const uint32_t limg = (512 + (15 - j) * 32 + 2 * grp + hp) * SLOT;
            {
                const int step = hp ? -8 * SLOT : 8 * SLOT;
                uint32_t img = (grp * 32 + (hp ? j ^ 30 : j) + 8) * SLOT;
                const uint32_t wtab = w_table(hp);
                uint32_t atab = hp ? 0x562u : 0x356u;
#pragma unroll 1
                for (int u = 2 - 2 * hp; u < 6; u += 2) {
                    proj_tile<false>(s, o, u, !u, sb, wg, eb, rel, fph, wtab, atab, pend, u ? img : cimg, toff, u ? sc : li[0], u ? sc : li[1], p);
                    __syncwarp();
                    mbar_arrive_if(sb + BAR_DONE + 4 * u + 32 * hp, lane == 0);
                    if (elected) TS(1 + 10 * hp + u + 20 * wg);
                    proj_tile<true>(o, s, u + 1, 0, sb, wg, eb, rel, fph, wtab, atab, pend, img + step, toff, sc, sc, p);
                    if (elected) TS(2 + 10 * hp + u + 20 * wg);
                    img += 2 * step;
                }
            }
            asm volatile("" : "+r"(toff));
            if (elected) TS(6 + 10 * hp + 20 * wg);
            fence_async_smem();
            slot_wait(sb + BAR_FULL, fph, r);
            step_retire(eb, rel, pend);
            reg_fence(o);
            int n = -1;
#pragma unroll 1
            for (;;) {
                while (bad || plain) {
                    float d0 = m[0], d1 = m[1];
                    if (bad) {
                        float a0, a1;
                        softmax_remax(s, m, n == 0 || n == nL, d0, d1, a0, a1);
                        shifted = true;
                        l[0] *= a0;
                        l[1] *= a1;
#pragma unroll
                        for (int i = 0; i < 64; i++) o[i] *= (i & 2) ? a1 : a0;
                    }
#pragma unroll
                    for (int i = 0; i < 64; i++) s[i] -= (i & 2) ? d1 : d0;
                    softmax_exp<0, 16>(s, p, t);
                    t[0] += t[1];
                    t[2] += t[3];
                    bad = !bad && softmax_unsafe(t[0], t[2], false);
                    plain = false;
                }
#pragma unroll 1
                do {
                    l[0] += t[0];
                    l[1] += t[2];
                    if (++n > 16) break;
                    const uint32_t ks = r;
                    uint32_t vs = ring_next(r);
                    r = ring_next(vs);
                    bar_sync(1 + wg, 256);
                    const float x = (float)((warp & 3) * 16 + g - 2 * c4);
                    if (n == hn) {
                        float sh[32];
                        qk_issue(sh, qa, kd + ks * (SLOT / 16));
                        slot_wait(sb + BAR_FULL, fph, vs);
                        pv_issue(o, p, vd + vs * (SLOT / 16), 1, false);
                        bar_arrive(2 - wg, 256);
                        wg_wait<1>();
                        reg_fence(sh);
                        tri_mask_copy(s, sh, x);
                        release_if(eb, ks, rel);
                        release_if(eb, 5 + wg, rel && (!wg || n == 16));
                        if (!wg) qa += SLOT / 16;
                        float e[4 * EARLY];
#pragma unroll
                        for (int i = 0; i < 4 * EARLY; i++) {
                            e[i] = ex2(s[i]);
                            t[i & 3] = i < 4 ? e[i] : t[i & 3] + e[i];
                        }
                        reg_fence(e);
                        slot_wait(sb + BAR_FULL, fph, r);
                        wg_wait<0>();
                        reg_fence(o);
                        reg_fence(e);
                        release_if(eb, vs, rel);
#pragma unroll
                        for (int i = 0; i < 2 * EARLY; i++) p[i] = pack2(e[2 * i], e[2 * i + 1]);
                        softmax_exp<EARLY, 8>(s, p, t);
                        if (wg) {
                            ctx_store(limg, toff, o, rcp(quad_sum(l[0])), rcp(quad_sum(l[1])));
                            __syncwarp();
                            mbar_arrive_if(sb + BAR_DONE + 24 + 32 * hp, lane == 0);
                            l[0] = l[1] = m[0] = m[1] = 0.f;
                            shifted = false;
                        }
                        t[0] += t[1];
                        t[2] += t[3];
                        plain = shifted;
                        if (plain) break;
                        bad = softmax_unsafe(t[0], t[2], wg);
                        continue;
                    }
                    if (n == nL) {
                        qk_issue(s, qa, kd + ks * (SLOT / 16));
                        slot_wait(sb + BAR_FULL, fph, vs);
                        pv_issue(o, p, vd + vs * (SLOT / 16), 1, true);
                        bar_arrive(2 - wg, 256);
                        const float i0 = rcp(quad_sum(l[0])), i1 = rcp(quad_sum(l[1]));
                        wg_wait<1>();
                        reg_fence(s);
                        release_if(eb, ks, rel);
                        release_if(eb, 6, rel && n == 16);
                        tri_mask(s, x);
                        float e[4 * EARLY2];
#pragma unroll
                        for (int i = 0; i < 4 * EARLY2; i++) {
                            e[i] = ex2(s[i]);
                            t[i & 3] = i < 4 ? e[i] : t[i & 3] + e[i];
                        }
                        reg_fence(e);
                        reg_fence(s);
                        reg_fence(t);
                        slot_wait(sb + BAR_FULL, fph, r);
                        sched_fence(fph, P.zero);
                        wg_wait<0>();
                        reg_fence(o);
                        reg_fence(e);
                        release_if(eb, vs, rel);
#pragma unroll
                        for (int i = 0; i < 2 * EARLY2; i++) p[i] = pack2(e[2 * i], e[2 * i + 1]);
                        softmax_exp<EARLY2, MSPLIT>(s, p, t);
                        ctx_store(limg, toff, o, i0, i1);
                        reg_fence(t);
                        reg_fence(s);
                        softmax_exp<MSPLIT, 16>(s, p, t);
                        __syncwarp();
                        mbar_arrive_if(sb + BAR_DONE + 24 + 32 * hp, lane == 0);
                        l[0] = l[1] = m[0] = m[1] = 0.f;
                        shifted = false;
                        t[0] += t[1];
                        t[2] += t[3];
                        bad = __any_sync(0xffffffffu, fmaxf(t[0], t[2]) > SM_HI || fminf(t[0], t[2]) < SM_LO);
                        continue;
                    }
                    qk_issue(s, qa, kd + ks * (SLOT / 16));
                    if (n == 0) {
                        r = vs;
                        vs = 4 - hp;
                        slot_wait(sb + BAR_FULL, fph, 6);
                        gemm_issue<false>(o, qa + SLOT / 16, wd + vs * (SLOT / 16), 1, false);
                    } else {
                        slot_wait(sb + BAR_FULL, fph, vs);
                        if (n == 1) {
                            wg_wait<1>();
                            reg_fence(o);
                            const uint32_t a = sb + 6 * SLOT + q_off(toff);
#pragma unroll
                            for (int i = 0; i < 8; i++) {
                                const int k = 16 * (i >> 1) + 2 * (i & 1);
                                sts128(a + (i >> 2) * 16384 + (i & 2) * 256 + (i & 1) * 1024,
                                       make_uint4(pack2(o[k], o[k + 1]), pack2(o[k + 4], o[k + 5]), pack2(o[k + 8], o[k + 9]), pack2(o[k + 12], o[k + 13])));
                            }
                        }
                        pv_issue(o, p, vd + vs * (SLOT / 16), n != 1 && n != nL + 1, n == hn + 1);
                    }
                    bar_arrive(2 - wg, 256);
                    wg_wait<1>();
                    reg_fence(s);
                    release_if(eb, ks, rel);
                    release_if(eb, 6, rel && n == 16);
                    if (n == nL - 1) {
                        tri_mask(s, x);
                        release_if(eb, 5, rel);
                        qa += SLOT / 16;
                    }
                    if (n == 2) fence_async_smem();
                    if (shifted) {
                        slot_wait(sb + BAR_FULL, fph, r);
                        wg_wait<0>();
                        reg_fence(o);
                        release_if(eb, vs, rel);
                        plain = true;
                        break;
                    }
                    float e[4 * EARLY];
#pragma unroll
                    for (int i = 0; i < 4 * EARLY; i++) {
                        e[i] = ex2(s[i]);
                        t[i & 3] = i < 4 ? e[i] : t[i & 3] + e[i];
                    }
                    reg_fence(e);
                    slot_wait(sb + BAR_FULL, fph, r);
                    wg_wait<0>();
                    reg_fence(o);
                    reg_fence(e);
                    release_if(eb, vs, rel);
#pragma unroll
                    for (int i = 0; i < 2 * EARLY; i++) p[i] = pack2(e[2 * i], e[2 * i + 1]);
                    softmax_exp<EARLY, 16>(s, p, t);
                    t[0] += t[1];
                    t[2] += t[3];
                    bad = __any_sync(0xffffffffu, fmaxf(t[0], t[2]) > SM_HI || (n == 0 && fminf(t[0], t[2]) < SM_LO));
                } while (!bad);
                if (!bad && !plain) break;
            }
            asm volatile("" : "+r"(toff));
            const uint32_t vs = r, ga = desc_k(sb + (hp ? 2 * (wg ^ kh ^ 1) : wg) * 8192);
            r = ring_next(r);
            slot_wait(sb + BAR_FULL, fph, 5);
            slot_wait(sb + BAR_FULL, fph, r);
            bar_sync(1 + wg, 256);
            gemm_issue<true>(s, ga + 5 * (SLOT / 16), wd + r * (SLOT / 16), 0, hp);
            pv_issue(o, p, vd + vs * (SLOT / 16), j, hn == 16);
            bar_arrive(2 - wg, 256);
            li[0] = rcp(quad_sum(l[0]));
            li[1] = rcp(quad_sum(l[1]));
            cimg = limg + (2 * j - 15) * 32 * SLOT + (wg ? -16384 : 16384);
            wg_wait<1>();
            release_if(eb, 5, rel);
            release_if(eb, r, rel && hp);
            wg_wait<0>();
            release_if(eb, vs, rel);
            reg_fence(o);
            img_store_global<0>(cimg, toff, o, li[0], li[1]);
            pend = 0x77;
            if (elected) TS(8 + 10 * hp + 20 * wg);
        }
        uint32_t otab = 0x2351604u;
        const uint32_t oa = desc_k(sb + (wg ^ kh ^ 1) * 16384);
        const int t7 = tid & 127, w4 = warp & 3, row = ort * 128 + kh * 64 + w4 * 16 + g;
#pragma unroll 1
        for (int i = 1; i < 15 - OFF - wg; i++) {
            const uint32_t as = o_next(otab), ws = o_next(otab);
            slot_wait(sb + BAR_FULL, fph, as);
            slot_wait(sb + BAR_FULL, fph, ws);
            bar_sync(1 + wg, 256);
            gemm_issue<false>(s, oa + as * (SLOT / 16), wd + ws * (SLOT / 16), 1, true);
            bar_arrive(2 - wg, 256);
            wg_wait<1>();
            reg_fence(o);
            if (i == 1) img_store_global<1>(cimg, toff, o, li[0], li[1]);
            if (i == 2) img_store_global<2>(cimg, toff, o, li[0], li[1]);
            if (i == CLAST) {
                img_store_global<3>(cimg, toff, o, li[0], li[1]);
                __syncwarp();
                mbar_arrive_if(sb + BAR_DONE + 64, lane == 0);
            }
            wg_wait<0>();
            release_if(eb, as, rel);
            release_if(eb, ws, rel);
        }
        mbar_wait(sb + BAR_PF, 0);
        const uint32_t ep = lds32(sb + SM_EP);
        uint32_t eb2 = sb + BAR_END;
        if (wg == 0) {
            reg_fence(s);
            if (elected) TS(9);
            TT(1);
#pragma unroll
            for (int v = 0; v < 8; v++)
                st_pub(g_out + rb * OB + v * 128 + t7, make_uint4((pack2(s[8 * v], s[8 * v + 1]) & ~1u) | (ep & 1), pack2(s[8 * v + 2], s[8 * v + 3]),
                                                                      pack2(s[8 * v + 4], s[8 * v + 5]), pack2(s[8 * v + 6], s[8 * v + 7])), true);
            constexpr uint32_t s1 = SL_WF, s2 = SL_WD;
            bar_sync(4, 256);
            uint32_t wf[64];
            float wn[64];
            if (rb < NFFN) {
                slot_wait(sb + BAR_FULL, fph, s1);
                const uint32_t a = sb + s1 * SLOT + (w4 * 128 + (lane >> 4) * 8 + (lane & 7)) * 32 + (((lane >> 3) ^ (lane >> 2)) & 1) * 16;
#pragma unroll
                for (int i = 0; i < 16; i++)
                    asm volatile("ldmatrix.sync.aligned.m8n8.x4.trans.shared.b16 {%0, %1, %2, %3}, [%4];"
                                 : "=r"(wf[4 * i]), "=r"(wf[4 * i + 1]), "=r"(wf[4 * i + 2]), "=r"(wf[4 * i + 3])
                                 : "r"(a + (i >> 3) * 16384 + (i & 7) * 512) : "memory");
                slot_wait(sb + BAR_FULL, fph, s2);
#pragma unroll
                for (int i = 0; i < 16; i++) {
                    const uint2 w = *reinterpret_cast<const uint2*>(smem + s2 * SLOT + (kh ^ 1) * 16384 + i * 1024 + t7 * 8);
                    wn[4 * i] = bf_lo(w.x); wn[4 * i + 1] = bf_hi(w.x); wn[4 * i + 2] = bf_lo(w.y); wn[4 * i + 3] = bf_hi(w.y);
                }
                reg_fence(wn);
            }
            const uint32_t gbf = __ldcg(reinterpret_cast<const uint32_t*>(g_mod) + 1280 + rb * 2 + (tid & 1));
            if (elected) TS(10);
            TT(2);
            float* sred = reinterpret_cast<float*>(smem + SM_RED);
            uint32_t best = ep ^ 1, all;
            bool fresh;
            do {
                if (warp == 0) {
                    const uint2 k = best_key(g_key + cq * 128, lane, ep, best, rb < NFFN ? SPEC : 32);
                    *reinterpret_cast<uint2*>(smem + SM_EP + 24) = k;
                    mbar_arrive_if(sb + BAR_BEST, lane == 0 && k.y);
                }
                bar_sync(3, 128);
                const uint2 k = *reinterpret_cast<const uint2*>(smem + SM_EP + 24);
                fresh = k.x != best;
                best = k.x;
                all = k.y;
                TT(3);
                if (!fresh || rb >= NFFN) break;
                const uint4* cp = g_cand + ((~best >> 9) & 127) * 192;
                uint4 cv[6];
                for (;;) {
                    uint32_t bad = 0;
#pragma unroll
                    for (int v = 0; v < 6; v++) cv[v] = ld_poll(cp + w4 * 24 + v * 4 + c4);
#pragma unroll
                    for (int v = 0; v < 6; v++) bad |= cv[v].w ^ ep;
                    if (__all_sync(0xffffffffu, bad == 0)) break;
                }
            TT(4);
                float d[4][4] = {};
#pragma unroll
                for (int k = 0; k < 8; k++) {
                    const uint32_t b0 = (&cv[(2 * k) / 3].x)[(2 * k) % 3], b1 = (&cv[(2 * k + 1) / 3].x)[(2 * k + 1) % 3];
                    mma16816(d[k & 1], wf + 4 * k, b0, b1);
                    mma16816(d[2 + (k & 1)], wf + 32 + 4 * k, b0, b1);
                }
                const float u = (c4 & 2) ? ((c4 & 1) ? d[2][2] + d[3][2] : d[2][0] + d[3][0]) : ((c4 & 1) ? d[0][2] + d[1][2] : d[0][0] + d[1][0]);
                sred[w4 * 32 + c4 * 8 + g] = u;
                bar_sync(3, 128);
                const float v = rbf((sred[lane] + sred[32 + lane]) + (sred[64 + lane] + sred[96 + lane]));
                const float act = rbf(rbf(v * sigmoid(v)) * __shfl_down_sync(0xffffffffu, v, 16));
                float y[4] = {0.f, 0.f, 0.f, 0.f};
#pragma unroll
                for (int k = 0; k < 16; k++) {
                    const float a = __shfl_sync(0xffffffffu, act, k);
#pragma unroll
                    for (int i = 0; i < 4; i++) y[i] = fmaf(a, wn[4 * k + i], y[i]);
                }
                st_pub(g_out + rb * OB + OB_Y + t7, make_uint4((__float_as_uint(y[0]) & ~15u) | (ep & 15), (__float_as_uint(y[1]) & ~127u) | ((best >> 9) & 127),
                                                               __float_as_uint(y[2]), __float_as_uint(y[3])), true);
            } while (!all);
            const int sel = (~best >> 5) & 2047;
            const int pq = (2 * rb + (tid & 1)) & 63, pv = (pq >> 2) / 3;
            const uint4* fp = g_cand + (sel >> 4) * 192 + (rb >> 5) * 24 + pv * 4 + (pq & 3);
            uint4 fh = {}, fx = {};
            if (rb == 0 && tid == 0) g_sync.epoch[0] = ep;
            if (elected) TS(60);
            TT(5);
            uint4 yv;
            if (warp == 0) { fh = ld_poll(fp); fx = ld_poll(fp + 96); }
            if (fresh && rb < NFFN) __nanosleep(YPRE);
            for (;;) {
                yv = ld_poll(g_out + min(t7, NFFN - 1) * OB + OB_Y + rb);
                if (__all_sync(0xffffffffu, (((yv.x ^ ep) & 15) | ((yv.y ^ (best >> 9)) & 127)) == 0)) break;
                if (YSLEEP) __nanosleep(YSLEEP);
            }
            if (elected) TS(61);
            TT(6);
            float y[4] = {0.f, 0.f, 0.f, 0.f};
            if (t7 < NFFN) { y[0] = __uint_as_float(yv.x); y[1] = __uint_as_float(yv.y); y[2] = __uint_as_float(yv.z); y[3] = __uint_as_float(yv.w); }
            const float z0 = ((lane & 16) ? y[2] : y[0]) + __shfl_xor_sync(0xffffffffu, (lane & 16) ? y[0] : y[2], 16);
            const float z1 = ((lane & 16) ? y[3] : y[1]) + __shfl_xor_sync(0xffffffffu, (lane & 16) ? y[1] : y[3], 16);
            float z = ((lane & 8) ? z1 : z0) + __shfl_xor_sync(0xffffffffu, (lane & 8) ? z0 : z1, 8);
            z += __shfl_xor_sync(0xffffffffu, z, 4);
            z = quad_sum(z);
            if ((lane & 7) == 0) sred[128 + (lane >> 3) * 4 + w4] = z;
            bar_sync(3, 128);
            if (tid < 2) {
                while (fh.w != ep || fx.w != ep) { fh = ld_poll(fp); fx = ld_poll(fp + 96); }
                const float4 y0 = *reinterpret_cast<const float4*>(sred + 128 + tid * 8), y1 = *reinterpret_cast<const float4*>(sred + 132 + tid * 8);
                const int cm = (pq >> 2) - 3 * pv;
                const uint32_t h2 = cm == 0 ? fh.x : cm == 1 ? fh.y : fh.z, x2 = cm == 0 ? fx.x : cm == 1 ? fx.y : fx.z;
                const float sg = sigmoid(bf_hi((best & 0x80000000u) ? (best ^ 0x80000000u) : ~best));
                reinterpret_cast<uint32_t*>(P.out)[sel * 256 + rb * 2 + tid] =
                    badd(x2, bmul(gbf, badd(h2, bmul(pack2((y0.x + y0.y) + (y0.z + y0.w), (y1.x + y1.y) + (y1.z + y1.w)), pack2(sg, sg)))));
            }
            if (elected) TS(62);
            TT(7);
        } else {
            const float4* tf = reinterpret_cast<const float4*>(smem + SM_TAB) + c4;
            uint32_t x2[32];
            bar_sync(2, 256);
#pragma unroll 1
            for (int i = 14; i < 17; i++) {
                const uint32_t as = o_next(otab), ws = o_next(otab);
                slot_wait(sb + BAR_FULL, fph, as);
                slot_wait(sb + BAR_FULL, fph, ws);
                gemm_issue<false>(s, oa + as * (SLOT / 16), wd + ws * (SLOT / 16), 1, true);
                wg_wait<1>();
            }
            const uint4* pr = g_out + (rb ^ 16) * OB + t7;
            uint4 pa[8];
            if (elected) TS(29);
            TT(1);
#pragma unroll
            for (int k = 0; k < 8; k++) {
                const uint4 v = lds128(sb + SL_X * SLOT + (kh ^ 1) * 16384 + k * 2048 + t7 * 16);
                x2[4 * k] = v.x; x2[4 * k + 1] = v.y; x2[4 * k + 2] = v.z; x2[4 * k + 3] = v.w;
            }
            wg_wait<0>();
            reg_fence(s);
            bar_arrive(4, 256);
            if (elected) TS(39);
            TT(2);
#pragma unroll
            for (int v = 0; v < 8; v++) pa[v] = ld_poll(pr + v * 128);
            float4 tc[16];
#pragma unroll
            for (int k = 0; k < 16; k++) {
                tc[k] = tf[k * 4];
                if (!(g & 1)) tc[k].z = __uint_as_float(ONE2);
#pragma unroll
                for (int i = 4 * k; i < 4 * k + 4; i++) s[i] = fmaf((i & 1) ? tc[k].y : tc[k].x, s[i], (i & 1) ? bf_hi(x2[i >> 1]) : bf_lo(x2[i >> 1]));
            }
            reg_fence(s);
            sched_fence(eb2, P.zero);
            for (;;) {
                uint32_t bad = 0;
#pragma unroll
                for (int v = 0; v < 8; v++) asm("lop3.b32 %0, %0, %1, %2, 0xf6;" : "+r"(bad) : "r"(pa[v].x), "r"(ep));
                if (__all_sync(0xffffffffu, (bad & 1) == 0)) break;
                if (PSLEEP) __nanosleep(PSLEEP);
#pragma unroll
                for (int v = 0; v < 8; v++) pa[v] = ld_poll(pr + v * 128);
            }
            if (elected) TS(30);
            TT(3);
            float sd[4] = {}, q0[4] = {}, q1[4] = {};
#pragma unroll
            for (int k = 0; k < 8; k++) {
#pragma unroll
                for (int i = 4 * k; i < 4 * k + 4; i++) {
                    const uint32_t w = (&pa[k].x)[i & 3];
                    x2[i] = pack2(fmaf(tc[i >> 1].x, bf_lo(w), s[2 * i]), fmaf(tc[i >> 1].y, bf_hi(w), s[2 * i + 1]));
                }
                mma16816(sd, x2 + 4 * k, __float_as_uint(tc[2 * k].z), __float_as_uint(tc[2 * k + 1].z));
                mma16816(q0, x2 + 4 * k, x2[4 * k], x2[4 * k + 2]);
                mma16816(q1, x2 + 4 * k, x2[4 * k + 1], x2[4 * k + 3]);
            }
            uint4* sp = g_out + rb * OB + OB_STAT + (w4 * 8 + g) * 2;
            st_pub(sp, make_uint4(__float_as_uint(sd[0]), __float_as_uint((g & 1) ? q0[1] : q0[0]), __float_as_uint(sd[1]), ep), c4 == g >> 1);
            st_pub(sp + 1, make_uint4(__float_as_uint(sd[2]), __float_as_uint((g & 1) ? q1[3] : q1[2]), __float_as_uint(sd[3]), ep), c4 == g >> 1);
            sched_fence(eb2, P.zero);
            if (elected) TS(56);
            TT(4);
            uint32_t cb[16], sh[16], gb[16];
#pragma unroll
            for (int i = 0; i < 16; i++) {
                const float4 c = tf[64 + i * 4];
                cb[i] = __float_as_uint(c.x); sh[i] = __float_as_uint(c.y); gb[i] = __float_as_uint(c.z);
            }
            const float ra = __uint_as_float(lds32(sb + SM_EP + 8)), rb0 = __uint_as_float(lds32(sb + SM_EP + 12));
            uint4 r0, r1;
            for (;;) {
                r0 = ld_poll(g_out + ((rb & ~33) + (c4 & 1) + (c4 & 2) * 16) * OB + OB_STAT + (w4 * 8 + g) * 2);
                r1 = ld_poll(g_out + ((rb & ~33) + (c4 & 1) + (c4 & 2) * 16) * OB + OB_STAT + (w4 * 8 + g) * 2 + 1);
                if (__all_sync(0xffffffffu, r0.w == ep && r1.w == ep)) break;
                if (SSLEEP) __nanosleep(SSLEEP);
            }
            if (elected) TS(57);
            TT(5);
            const float m0 = quad_sum(__uint_as_float(r0.x)) * (1.f / 512.f), m1 = quad_sum(__uint_as_float(r1.x)) * (1.f / 512.f);
            const float rs0 = ln_rstd(fmaxf(fmaf(-m0, m0, quad_sum(__uint_as_float(r0.y)) * (1.f / 512.f)), 0.f));
            const float rs1 = ln_rstd(fmaxf(fmaf(-m1, m1, quad_sum(__uint_as_float(r1.y)) * (1.f / 512.f)), 0.f));
            const uint32_t mb0 = pack2(m0, m0), mb1 = pack2(m1, m1);
            const uint32_t lg = pack2(fmaf(rs0, fmaf(-bf_lo(mb0), ra, quad_sum(__uint_as_float(r0.z))), rb0),
                                      fmaf(rs1, fmaf(-bf_lo(mb1), ra, quad_sum(__uint_as_float(r1.z))), rb0));
            const uint32_t u0 = lg << 16, u1 = lg & 0xffff0000u;
            const uint32_t k0 = ((u0 ^ (((int)u0 >> 31) | 0x80000000u)) & 0xffff0000u) | ((2047 - row) << 5) | (ep & 31);
            const uint32_t k1 = ((u1 ^ (((int)u1 >> 31) | 0x80000000u)) & 0xffff0000u) | ((2039 - row) << 5) | (ep & 31);
            const uint32_t kb = __reduce_max_sync(0xffffffffu, max(k0, k1));
            st_pub(g_key + cq * 128 + (row >> 4), kb, lane == 0);
            const bool cand = kb == k0 || kb == k1;
            uint4* cp = g_cand + (row >> 4) * 192 + cq * 24 + c4;
#pragma unroll 1
            for (int it = 0; it < 3; it++) {
                bool put = it == 1 || !cand;
                if (it == 2) {
                    mbar_wait(sb + BAR_BEST, 0);
                    put = cand && lds32(sb + SM_EP + 24) != kb;
                }
                const bool hi = (kb == k1) != (it == 1);
                uint32_t cx[18], ch[18];
#pragma unroll
                for (int i = 0; i < 16; i++) {
                    cx[i] = hi ? x2[2 * i + 1] : x2[2 * i];
                    ch[i] = ln_apply(cx[i], hi ? mb1 : mb0, hi ? rs1 : rs0, cb[i], sh[i]);
                }
                cx[16] = cx[17] = ch[16] = ch[17] = 0;
#pragma unroll
                for (int v = 0; v < 6; v++) st_pub(cp + v * 4, make_uint4(ch[3 * v], ch[3 * v + 1], ch[3 * v + 2], ep), cand && it == 0);
#pragma unroll
                for (int v = 0; v < 6; v++) st_pub(cp + 96 + v * 4, make_uint4(cx[3 * v], cx[3 * v + 1], cx[3 * v + 2], ep), cand && it == 0);
                if (it == 0) TT(6);
                uint2* op = reinterpret_cast<uint2*>(P.out) + (row + 8 * hi) * 128 + cq * 32 + (c4 & 1) * 2 + (c4 >> 1);
#pragma unroll
                for (int i = 0; i < 16; i += 2) {
                    const uint32_t v0 = badd(cx[i], bmul(gb[i], ch[i])), v1 = badd(cx[i + 1], bmul(gb[i + 1], ch[i + 1]));
                    const uint32_t rv = __shfl_xor_sync(0xffffffffu, (c4 & 1) ? v0 : v1, 1);
                    if (put) op[i * 2] = (c4 & 1) ? make_uint2(rv, v1) : make_uint2(v0, rv);
                }
            }
            if (elected) TS(59);
            TT(7);
        }
        mbar_arrive_if(eb2, lane == 0);
    }
}

typedef CUresult (*EncodeFn)(CUtensorMap*, CUtensorMapDataType, cuuint32_t, void*, const cuuint64_t*, const cuuint64_t*,
                             const cuuint32_t*, const cuuint32_t*, CUtensorMapInterleave, CUtensorMapSwizzle,
                             CUtensorMapL2promotion, CUtensorMapFloatOOBfill);

void make_3d(EncodeFn fn, CUtensorMap* m, const void* p, uint64_t cols, uint64_t rows, uint32_t br = 128, uint32_t nb = 2) {
    cuuint64_t dims[3] = {64, rows, cols / 64}, strides[2] = {cols * 2, 128};
    cuuint32_t box[3] = {64, br, nb}, es[3] = {1, 1, 1};
    fn(m, CU_TENSOR_MAP_DATA_TYPE_BFLOAT16, 3, const_cast<void*>(p), dims, strides, box, es, CU_TENSOR_MAP_INTERLEAVE_NONE,
       CU_TENSOR_MAP_SWIZZLE_128B, CU_TENSOR_MAP_L2_PROMOTION_L2_256B, CU_TENSOR_MAP_FLOAT_OOB_FILL_NONE);
}

}

extern "C" void kernel_launch(void* const* d_in, const int* in_sizes, int n_in, void* d_out, int out_size) {
    static EncodeFn fn = nullptr;
    if (!fn) {
        void* f = nullptr;
        cudaDriverEntryPointQueryResult st;
        cudaGetDriverEntryPoint("cuTensorMapEncodeTiled", &f, cudaEnableDefault, &st);
        fn = (EncodeFn)f;
        cudaFuncSetAttribute(fused_kernel, cudaFuncAttributeMaxDynamicSharedMemorySize, SMEM_BYTES);
    }
    CUtensorMap ckv, wq, wuk, wuv, wo, wg, wu, wm, xm;
    make_3d(fn, &ckv, d_in[1], 512, 2048, 128, 1);
    make_3d(fn, &xm, d_in[0], 512, 2048, 64);
    make_3d(fn, &wq, d_in[2], 4096, 512);
    make_3d(fn, &wuk, d_in[3], 4096, 512);
    make_3d(fn, &wuv, d_in[4], 4096, 512);
    make_3d(fn, &wo, d_in[5], 512, 4096);
    make_3d(fn, &wg, d_in[8], 1792, 512, 256, 1);
    make_3d(fn, &wu, d_in[9], 1792, 512, 256, 1);
    make_3d(fn, &wm, d_in[12], 3072, 512, 64, 4);
    Params p;
    p.x = (const bf16*)d_in[0];
    p.ckv = (const bf16*)d_in[1];
    p.wo = (const bf16*)d_in[5];
    p.wr = (const bf16*)d_in[7];
    p.wdown = (const bf16*)d_in[10];
    p.c = (const bf16*)d_in[11];
    p.out = (bf16*)d_out;
    p.zero = 0;
    fused_kernel<<<NCTA + NSPARE, 384, SMEM_BYTES>>>(ckv, wq, wuk, wuv, wo, wg, wu, wm, xm, p);
}
```

```cpp
#include <cuda.h>
#include <cuda_bf16.h>
#include <cuda_runtime.h>
#include <stdint.h>
#include <stdio.h>

namespace {

typedef __nv_bfloat16 bf16;
typedef unsigned long long u64;

constexpr int NCTA = 128, NSPARE = 4;
constexpr int SLOT = 32768;
constexpr int SM_BAR = 7 * SLOT;
constexpr int BAR_FULL = SM_BAR;
constexpr int BAR_EMPTY = BAR_FULL + 8 * 7;
constexpr int BAR_DONE = BAR_EMPTY + 8 * 7;
constexpr int BAR_FLAG = BAR_DONE + 8 * 9;
constexpr int BAR_PF = BAR_FLAG + 8 * 9;
constexpr int BAR_END = BAR_PF + 8;
constexpr int BAR_BEST = BAR_END + 8;
constexpr int SM_EP = BAR_END + 40;
constexpr int SM_RED = SM_BAR + 384;
constexpr int SM_TAB = SM_BAR + 1024;
constexpr int SMEM_BYTES = SM_BAR + 3072;
constexpr int NFFN = 112;
#define HINT 479
constexpr u64 L2_NORMAL = 0x1000000000000000ull, L2_FIRST = 0x12F0000000000000ull;
#define PFA 8
#define PFB 6
#define POLL_NS 50
#define MSPLIT 13
#define NSH 1
#define XPF 1
#define KSLEEP 200
#define YSLEEP 50
#define YPRE 150
#define SSLEEP 50
#define PSLEEP 100
#define SPEC 28
#define KVG 7
#define EARLY2 4
#define OFF 2
#define CLAST 2
#define KN 20
#define KSLEEP2 200
#define EARLY 7
constexpr uint32_t SPIN_LIMIT = 1u << 22;
constexpr uint32_t ONE2 = 0x3f803f80u;

struct Sync {
    uint32_t cnt[16 * 8 * 8];
    uint32_t ctxcnt[16 * 32];
    uint32_t epoch[32];
};

__device__ __align__(1024) uint8_t g_img[2 * 512 * SLOT];
#define g_KV g_img
#define g_ctx (g_img + 512 * SLOT)
__device__ __align__(1024) uint8_t g_h[16 * 4 * SLOT];
constexpr int OB = 1216, OB_STAT = 1024, OB_Y = 1088;
__device__ __align__(1024) uint4 g_out[128 * OB];
__device__ __align__(1024) bf16 g_mod[3072];
__device__ __align__(1024) uint32_t g_mod1[1024];
__device__ __align__(1024) uint4 g_cand[128 * 192];
__device__ __align__(1024) uint32_t g_key[4 * 128];
__device__ __align__(1024) uint8_t g_wf[NFFN * SLOT];
__device__ __align__(1024) uint4 g_x2[128 * 1024];
__device__ __align__(1024) Sync g_sync;
#define TS(i)

#define TT(i)
#define PT()

struct Params {
    const bf16 *x, *ckv, *wo, *wr, *wdown, *c;
    bf16* out;
    int zero;
};

__device__ __forceinline__ void mbar_init(uint32_t bar, uint32_t cnt) {
    asm volatile("mbarrier.init.shared::cta.b64 [%0], %1;" ::"r"(bar), "r"(cnt) : "memory");
}
__device__ __forceinline__ void mbar_wait(uint32_t bar, uint32_t parity) {
    asm volatile("{\n.reg .pred p;\nL_%=:\nmbarrier.try_wait.parity.shared::cta.b64 p, [%0], %1;\n@!p bra L_%=;\n}" ::"r"(bar), "r"(parity) : "memory");
}
__device__ __forceinline__ void mbar_sleep(uint32_t bar) {
    if ((threadIdx.x & 31) == 0)
        asm volatile("{\n.reg .pred p;\nL_%=:\nmbarrier.try_wait.parity.shared::cta.b64 p, [%0], 0, 100000;\n@!p bra L_%=;\n}" ::"r"(bar) : "memory");
    __syncwarp();
}
__device__ __forceinline__ void mbar_watch(uint32_t bar, uint32_t parity) {
    asm volatile("{\n.reg .pred p;\n.reg .u32 n;\nmov.u32 n, 0;\n"
                 "L_%=:\nmbarrier.try_wait.parity.shared::cta.b64 p, [%0], %1;\n@p bra D_%=;\n"
                 "add.u32 n, n, 1;\nsetp.lt.u32 p, n, %2;\n@p bra L_%=;\ntrap;\nD_%=:\n}"
                 ::"r"(bar), "r"(parity), "n"(SPIN_LIMIT) : "memory");
}
__device__ __forceinline__ void step_watch(uint32_t a, uint32_t step) {
    asm volatile("{\n.reg .pred p;\n.reg .u32 n, v;\nmov.u32 n, 0;\n"
                 "L_%=:\nld.volatile.shared.u32 v, [%0];\nsetp.ge.u32 p, v, %1;\n@p bra D_%=;\nnanosleep.u32 400;\n"
                 "add.u32 n, n, 1;\nsetp.lt.u32 p, n, %2;\n@p bra L_%=;\ntrap;\nD_%=:\n}"
                 ::"r"(a), "r"(step), "n"(SPIN_LIMIT) : "memory");
}
__device__ __forceinline__ void mbar_arrive_if(uint32_t bar, bool on) {
    asm volatile("{\n.reg .pred p;\nsetp.ne.s32 p, %1, 0;\n@p mbarrier.arrive.shared::cta.b64 _, [%0];\n}" ::"r"(bar), "r"((int)on) : "memory");
}
__device__ __forceinline__ void tma3d_prefetch(const CUtensorMap* m, int row, int cb) {
    asm volatile("{\n.reg .pred p;\nelect.sync _|p, 0xffffffff;\n@p cp.async.bulk.prefetch.tensor.3d.L2.global [%0, {%1, %2, %3}];\n}"
                 ::"l"(m), "r"(0), "r"(row), "r"(cb) : "memory");
}
__device__ __forceinline__ void l2_prefetch(const void* p, uint32_t bytes) {
    asm volatile("{\n.reg .pred p;\nelect.sync _|p, 0xffffffff;\n@p cp.async.bulk.prefetch.L2.global [%0], %1;\n}" ::"l"(p), "r"(bytes) : "memory");
}
__device__ __forceinline__ void bulk_store(void* dst, uint32_t src, uint32_t bytes, bool first) {
    asm volatile("{\n.reg .pred p;\nelect.sync _|p, 0xffffffff;\n@p cp.async.bulk.global.shared::cta.bulk_group.L2::cache_hint [%0], [%1], %2, %3;\n}"
                 ::"l"(dst), "r"(src), "r"(bytes), "l"(first ? L2_FIRST : L2_NORMAL) : "memory");
}
__device__ __forceinline__ void flag_wait(const uint32_t* f, uint32_t target) {
    asm volatile("{\n.reg .pred p;\n.reg .u32 v;\n"
                 "L_%=:\nld.acquire.gpu.global.u32 v, [%0];\nsub.u32 v, v, %1;\nsetp.lt.s32 p, v, 0;\n@p nanosleep.u32 100;\n@p bra L_%=;\n}"
                 ::"l"(f), "r"(target) : "memory");
}
__device__ __forceinline__ uint4 ld_poll(const uint4* p) {
    uint4 v;
    asm volatile("{\n.reg .b128 t;\nld.relaxed.gpu.global.b128 t, [%4];\nmov.b128 {%0, %1, %2, %3}, t;\n}"
                 : "=r"(v.x), "=r"(v.y), "=r"(v.z), "=r"(v.w) : "l"(p) : "memory");
    return v;
}
__device__ __forceinline__ void st_pub(uint4* p, uint4 v, bool on) {
    asm volatile("{\n.reg .pred p;\n.reg .b128 t;\nsetp.ne.s32 p, %5, 0;\nmov.b128 t, {%1, %2, %3, %4};\n@p st.relaxed.gpu.global.b128 [%0], t;\n}"
                 ::"l"(p), "r"(v.x), "r"(v.y), "r"(v.z), "r"(v.w), "r"((int)on) : "memory");
}
__device__ __forceinline__ void st_pub(uint32_t* p, uint32_t v, bool on) {
    asm volatile("{\n.reg .pred p;\nsetp.ne.s32 p, %2, 0;\n@p st.relaxed.gpu.global.u32 [%0], %1;\n}" ::"l"(p), "r"(v), "r"((int)on) : "memory");
}
__device__ __forceinline__ void flag_add(uint32_t* p) {
    asm volatile("red.release.gpu.global.add.u32 [%0], 1;" ::"l"(p) : "memory");
}
__device__ __forceinline__ uint32_t lds32(uint32_t a) {
    uint32_t v;
    asm volatile("ld.shared.u32 %0, [%1];" : "=r"(v) : "r"(a) : "memory");
    return v;
}
__device__ __forceinline__ uint4 lds128(uint32_t a) {
    uint4 v;
    asm volatile("ld.shared.v4.u32 {%0, %1, %2, %3}, [%4];" : "=r"(v.x), "=r"(v.y), "=r"(v.z), "=r"(v.w) : "r"(a) : "memory");
    return v;
}
__device__ __forceinline__ void sched_fence(uint32_t& v, uint32_t z) {
    uint32_t ck;
    asm volatile("mov.u32 %0, %%clock;" : "=r"(ck)::"memory");
    v ^= ck & z;
}
__device__ __forceinline__ void fence_async_global() { asm volatile("fence.proxy.async.global;" ::: "memory"); }
__device__ __forceinline__ void fence_async_smem() { asm volatile("fence.proxy.async.shared::cta;" ::: "memory"); }
__device__ __forceinline__ void bar_sync(int id, int n) { asm volatile("bar.sync %0, %1;" ::"r"(id), "r"(n) : "memory"); }
__device__ __forceinline__ void bar_arrive(int id, int n) { asm volatile("bar.arrive %0, %1;" ::"r"(id), "r"(n) : "memory"); }
__device__ __forceinline__ void wg_fence() { asm volatile("wgmma.fence.sync.aligned;" ::: "memory"); }
__device__ __forceinline__ void wg_commit() { asm volatile("wgmma.commit_group.sync.aligned;" ::: "memory"); }
template <int N> __device__ __forceinline__ void wg_wait() { asm volatile("wgmma.wait_group.sync.aligned %0;" ::"n"(N) : "memory"); }
template <int N> __device__ __forceinline__ void reg_fence(float (&d)[N]) {
#pragma unroll
    for (int i = 0; i < N; i++) asm volatile("" : "+f"(d[i])::"memory");
}
template <int N> __device__ __forceinline__ void reg_fence(uint32_t (&d)[N]) {
#pragma unroll
    for (int i = 0; i < N; i++) asm volatile("" : "+r"(d[i])::"memory");
}
__device__ __forceinline__ uint32_t desc_k(uint32_t a) { return ((a & 0x3ffff) >> 4) | (1u << 16); }
__device__ __forceinline__ uint32_t desc_mn(uint32_t a) { return ((a & 0x3ffff) >> 4) | (1024u << 16); }

__device__ __forceinline__ uint64_t desc64(uint32_t lo, uint32_t hi) {
    uint64_t d;
    asm("mov.b64 %0, {%1, %2};" : "=l"(d) : "r"(lo), "r"(hi));
    return d;
}
__device__ __forceinline__ void desc_add(uint64_t& d, uint32_t x) { asm("add.u64 %0, %0, %1;" : "+l"(d) : "l"((uint64_t)x)); }

template <int TB>
__device__ __forceinline__ void wgmma_ss128(float (&d)[64], uint64_t da, uint64_t db, int acc) {
    asm volatile("{\n.reg .pred p;\nsetp.ne.b32 p, %66, 0;\n"
        "wgmma.mma_async.sync.aligned.m64n128k16.f32.bf16.bf16 {%0, %1, %2, %3, %4, %5, %6, %7, %8, %9, %10, %11, %12, %13, %14, %15, %16, %17, %18, %19, %20, %21, %22, %23, %24, %25, %26, %27, %28, %29, %30, %31, %32, %33, %34, %35, %36, %37, %38, %39, %40, %41, %42, %43, %44, %45, %46, %47, %48, %49, %50, %51, %52, %53, %54, %55, %56, %57, %58, %59, %60, %61, %62, %63}, %64, %65, p, 1, 1, 0, %67;\n}"
        : "+f"(d[0]), "+f"(d[1]), "+f"(d[2]), "+f"(d[3]), "+f"(d[4]), "+f"(d[5]), "+f"(d[6]), "+f"(d[7]), "+f"(d[8]), "+f"(d[9]), "+f"(d[10]), "+f"(d[11]), "+f"(d[12]), "+f"(d[13]), "+f"(d[14]), "+f"(d[15]), "+f"(d[16]), "+f"(d[17]), "+f"(d[18]), "+f"(d[19]), "+f"(d[20]), "+f"(d[21]), "+f"(d[22]), "+f"(d[23]), "+f"(d[24]), "+f"(d[25]), "+f"(d[26]), "+f"(d[27]), "+f"(d[28]), "+f"(d[29]), "+f"(d[30]), "+f"(d[31]), "+f"(d[32]), "+f"(d[33]), "+f"(d[34]), "+f"(d[35]), "+f"(d[36]), "+f"(d[37]), "+f"(d[38]), "+f"(d[39]), "+f"(d[40]), "+f"(d[41]), "+f"(d[42]), "+f"(d[43]), "+f"(d[44]), "+f"(d[45]), "+f"(d[46]), "+f"(d[47]), "+f"(d[48]), "+f"(d[49]), "+f"(d[50]), "+f"(d[51]), "+f"(d[52]), "+f"(d[53]), "+f"(d[54]), "+f"(d[55]), "+f"(d[56]), "+f"(d[57]), "+f"(d[58]), "+f"(d[59]), "+f"(d[60]), "+f"(d[61]), "+f"(d[62]), "+f"(d[63])
        : "l"(da), "l"(db), "r"(acc), "n"(TB));
}
template <int TB>
__device__ __forceinline__ void wgmma_ss128_init(float (&d)[64], uint64_t da, uint64_t db) {
    asm volatile("{\n.reg .pred p;\nsetp.ne.b32 p, 0, 0;\n"
        "wgmma.mma_async.sync.aligned.m64n128k16.f32.bf16.bf16 {%0, %1, %2, %3, %4, %5, %6, %7, %8, %9, %10, %11, %12, %13, %14, %15, %16, %17, %18, %19, %20, %21, %22, %23, %24, %25, %26, %27, %28, %29, %30, %31, %32, %33, %34, %35, %36, %37, %38, %39, %40, %41, %42, %43, %44, %45, %46, %47, %48, %49, %50, %51, %52, %53, %54, %55, %56, %57, %58, %59, %60, %61, %62, %63}, %64, %65, p, 1, 1, 0, %66;\n}"
        : "=f"(d[0]), "=f"(d[1]), "=f"(d[2]), "=f"(d[3]), "=f"(d[4]), "=f"(d[5]), "=f"(d[6]), "=f"(d[7]), "=f"(d[8]), "=f"(d[9]), "=f"(d[10]), "=f"(d[11]), "=f"(d[12]), "=f"(d[13]), "=f"(d[14]), "=f"(d[15]), "=f"(d[16]), "=f"(d[17]), "=f"(d[18]), "=f"(d[19]), "=f"(d[20]), "=f"(d[21]), "=f"(d[22]), "=f"(d[23]), "=f"(d[24]), "=f"(d[25]), "=f"(d[26]), "=f"(d[27]), "=f"(d[28]), "=f"(d[29]), "=f"(d[30]), "=f"(d[31]), "=f"(d[32]), "=f"(d[33]), "=f"(d[34]), "=f"(d[35]), "=f"(d[36]), "=f"(d[37]), "=f"(d[38]), "=f"(d[39]), "=f"(d[40]), "=f"(d[41]), "=f"(d[42]), "=f"(d[43]), "=f"(d[44]), "=f"(d[45]), "=f"(d[46]), "=f"(d[47]), "=f"(d[48]), "=f"(d[49]), "=f"(d[50]), "=f"(d[51]), "=f"(d[52]), "=f"(d[53]), "=f"(d[54]), "=f"(d[55]), "=f"(d[56]), "=f"(d[57]), "=f"(d[58]), "=f"(d[59]), "=f"(d[60]), "=f"(d[61]), "=f"(d[62]), "=f"(d[63])
        : "l"(da), "l"(db), "n"(TB));
}
template <int TB>
__device__ __forceinline__ void wgmma_ss64(float (&d)[32], uint64_t da, uint64_t db, int acc) {
    asm volatile("{\n.reg .pred p;\nsetp.ne.b32 p, %34, 0;\n"
        "wgmma.mma_async.sync.aligned.m64n64k16.f32.bf16.bf16 {%0, %1, %2, %3, %4, %5, %6, %7, %8, %9, %10, %11, %12, %13, %14, %15, %16, %17, %18, %19, %20, %21, %22, %23, %24, %25, %26, %27, %28, %29, %30, %31}, %32, %33, p, 1, 1, 0, %35;\n}"
        : "+f"(d[0]), "+f"(d[1]), "+f"(d[2]), "+f"(d[3]), "+f"(d[4]), "+f"(d[5]), "+f"(d[6]), "+f"(d[7]), "+f"(d[8]), "+f"(d[9]), "+f"(d[10]), "+f"(d[11]), "+f"(d[12]), "+f"(d[13]), "+f"(d[14]), "+f"(d[15]), "+f"(d[16]), "+f"(d[17]), "+f"(d[18]), "+f"(d[19]), "+f"(d[20]), "+f"(d[21]), "+f"(d[22]), "+f"(d[23]), "+f"(d[24]), "+f"(d[25]), "+f"(d[26]), "+f"(d[27]), "+f"(d[28]), "+f"(d[29]), "+f"(d[30]), "+f"(d[31])
        : "l"(da), "l"(db), "r"(acc), "n"(TB));
}
template <int TB>
__device__ __forceinline__ void wgmma_ss64_init(float (&d)[32], uint64_t da, uint64_t db) {
    asm volatile("{\n.reg .pred p;\nsetp.ne.b32 p, 0, 0;\n"
        "wgmma.mma_async.sync.aligned.m64n64k16.f32.bf16.bf16 {%0, %1, %2, %3, %4, %5, %6, %7, %8, %9, %10, %11, %12, %13, %14, %15, %16, %17, %18, %19, %20, %21, %22, %23, %24, %25, %26, %27, %28, %29, %30, %31}, %32, %33, p, 1, 1, 0, %34;\n}"
        : "=f"(d[0]), "=f"(d[1]), "=f"(d[2]), "=f"(d[3]), "=f"(d[4]), "=f"(d[5]), "=f"(d[6]), "=f"(d[7]), "=f"(d[8]), "=f"(d[9]), "=f"(d[10]), "=f"(d[11]), "=f"(d[12]), "=f"(d[13]), "=f"(d[14]), "=f"(d[15]), "=f"(d[16]), "=f"(d[17]), "=f"(d[18]), "=f"(d[19]), "=f"(d[20]), "=f"(d[21]), "=f"(d[22]), "=f"(d[23]), "=f"(d[24]), "=f"(d[25]), "=f"(d[26]), "=f"(d[27]), "=f"(d[28]), "=f"(d[29]), "=f"(d[30]), "=f"(d[31])
        : "l"(da), "l"(db), "n"(TB));
}
__device__ __forceinline__ void wgmma_rs128(float (&d)[64], uint32_t a0, uint32_t a1, uint32_t a2, uint32_t a3, uint64_t db, int acc) {
    asm volatile("{\n.reg .pred p;\nsetp.ne.b32 p, %69, 0;\n"
        "wgmma.mma_async.sync.aligned.m64n128k16.f32.bf16.bf16 {%0, %1, %2, %3, %4, %5, %6, %7, %8, %9, %10, %11, %12, %13, %14, %15, %16, %17, %18, %19, %20, %21, %22, %23, %24, %25, %26, %27, %28, %29, %30, %31, %32, %33, %34, %35, %36, %37, %38, %39, %40, %41, %42, %43, %44, %45, %46, %47, %48, %49, %50, %51, %52, %53, %54, %55, %56, %57, %58, %59, %60, %61, %62, %63}, {%64, %65, %66, %67}, %68, p, 1, 1, 1;\n}"
        : "+f"(d[0]), "+f"(d[1]), "+f"(d[2]), "+f"(d[3]), "+f"(d[4]), "+f"(d[5]), "+f"(d[6]), "+f"(d[7]), "+f"(d[8]), "+f"(d[9]), "+f"(d[10]), "+f"(d[11]), "+f"(d[12]), "+f"(d[13]), "+f"(d[14]), "+f"(d[15]), "+f"(d[16]), "+f"(d[17]), "+f"(d[18]), "+f"(d[19]), "+f"(d[20]), "+f"(d[21]), "+f"(d[22]), "+f"(d[23]), "+f"(d[24]), "+f"(d[25]), "+f"(d[26]), "+f"(d[27]), "+f"(d[28]), "+f"(d[29]), "+f"(d[30]), "+f"(d[31]), "+f"(d[32]), "+f"(d[33]), "+f"(d[34]), "+f"(d[35]), "+f"(d[36]), "+f"(d[37]), "+f"(d[38]), "+f"(d[39]), "+f"(d[40]), "+f"(d[41]), "+f"(d[42]), "+f"(d[43]), "+f"(d[44]), "+f"(d[45]), "+f"(d[46]), "+f"(d[47]), "+f"(d[48]), "+f"(d[49]), "+f"(d[50]), "+f"(d[51]), "+f"(d[52]), "+f"(d[53]), "+f"(d[54]), "+f"(d[55]), "+f"(d[56]), "+f"(d[57]), "+f"(d[58]), "+f"(d[59]), "+f"(d[60]), "+f"(d[61]), "+f"(d[62]), "+f"(d[63])
        : "r"(a0), "r"(a1), "r"(a2), "r"(a3), "l"(db), "r"(acc));
}

__device__ __forceinline__ uint32_t pack2(float lo, float hi) {
    uint32_t r;
    asm("cvt.rn.bf16x2.f32 %0, %1, %2;" : "=r"(r) : "f"(hi), "f"(lo));
    return r;
}
__device__ __forceinline__ float bf_lo(uint32_t v) { return __uint_as_float(v << 16); }
__device__ __forceinline__ float bf_hi(uint32_t v) { return __uint_as_float(v & 0xffff0000u); }
__device__ __forceinline__ float rbf(float v) { return bf_lo(pack2(v, v)); }
__device__ __forceinline__ uint32_t badd(uint32_t a, uint32_t b) {
    uint32_t r;
    asm("add.rn.bf16x2 %0, %1, %2;" : "=r"(r) : "r"(a), "r"(b));
    return r;
}
__device__ __forceinline__ uint32_t bsub(uint32_t a, uint32_t b) {
    uint32_t r;
    asm("sub.rn.bf16x2 %0, %1, %2;" : "=r"(r) : "r"(a), "r"(b));
    return r;
}
__device__ __forceinline__ uint32_t bmul(uint32_t a, uint32_t b) {
    uint32_t r;
    asm("mul.rn.bf16x2 %0, %1, %2;" : "=r"(r) : "r"(a), "r"(b));
    return r;
}
__device__ __forceinline__ uint32_t ln_apply(uint32_t x, uint32_t mb, float rs, uint32_t scale, uint32_t shift) {
    const uint32_t d = bsub(x, mb);
    return badd(bmul(pack2(bf_lo(d) * rs, bf_hi(d) * rs), scale), shift);
}
__device__ __forceinline__ float ex2(float v) {
    float r;
    asm("ex2.approx.ftz.f32 %0, %1;" : "=f"(r) : "f"(v));
    return r;
}
__device__ __forceinline__ float rcp(float v) {
    float r;
    asm("rcp.approx.ftz.f32 %0, %1;" : "=f"(r) : "f"(v));
    return r;
}
__device__ __forceinline__ float sqrt_fast(float v) {
    float r;
    asm("sqrt.approx.ftz.f32 %0, %1;" : "=f"(r) : "f"(v));
    return r;
}
__device__ __forceinline__ float ln_rstd(float var) { return rcp(rbf(sqrt_fast(rbf(rbf(var) + 1e-5f)))); }
__device__ __forceinline__ float sigmoid(float v) { return rcp(1.f + ex2(-1.4426950408889634f * v)); }
__device__ __forceinline__ float quad_sum(float v) {
    v += __shfl_xor_sync(0xffffffffu, v, 1);
    return v + __shfl_xor_sync(0xffffffffu, v, 2);
}

constexpr uint32_t HI_128 = 0x40000040u, HI_IMG = 0x80000080u, HI_Q = 0x80000040u;
template <int M, int RH>
__device__ __forceinline__ uint4 img_pack(const float (&d)[64], float s) {
    uint4 v;
    v.x = pack2(d[16 * M + 2 * RH] * s, d[16 * M + 2 * RH + 1] * s);
    v.y = pack2(d[16 * M + 4 + 2 * RH] * s, d[16 * M + 5 + 2 * RH] * s);
    v.z = pack2(d[16 * M + 8 + 2 * RH] * s, d[16 * M + 9 + 2 * RH] * s);
    v.w = pack2(d[16 * M + 12 + 2 * RH] * s, d[16 * M + 13 + 2 * RH] * s);
    return v;
}
template <int M>
__device__ __forceinline__ void img_store_global(uint32_t img, uint32_t toff, const float (&d)[64], float s0, float s1) {
    uint4* p = reinterpret_cast<uint4*>(g_img + (img + toff)) + M * 32;
    p[0] = img_pack<M, 0>(d, s0);
    p[128] = img_pack<M, 1>(d, s1);
}
__device__ __forceinline__ void sts128(uint32_t a, uint4 v) {
    asm volatile("st.shared.v4.b32 [%0], {%1, %2, %3, %4};" ::"r"(a), "r"(v.x), "r"(v.y), "r"(v.z), "r"(v.w) : "memory");
}
constexpr float SM_C = 0.08838834764831845f * 1.4426950408889634f;
__device__ __forceinline__ float pack2f(float lo, float hi) {
    float r;
    asm("{\n.reg .b32 t;\ncvt.rn.bf16x2.f32 t, %1, %2;\nmov.b32 %0, t;\n}" : "=f"(r) : "f"(hi), "f"(lo));
    return r;
}
template <int M, bool SCALE, bool PARK>
__device__ __forceinline__ void pack_group(float (&d)[64], float (&v)[8], float s0, float s1) {
#pragma unroll
    for (int i = 0; i < 8; i++) {
        const int k = 16 * M + 4 * (i & 3) + 2 * (i >> 2);
        v[i] = SCALE ? pack2f(d[k] * (i < 4 ? s0 : s1), d[k + 1] * (i < 4 ? s0 : s1)) : pack2f(d[k], d[k + 1]);
        if (PARK && M > 0) d[16 * (M > 0 ? M - 1 : 0) + i] = v[i];
    }
}
__device__ __forceinline__ uint32_t q_off(uint32_t toff) {
    asm volatile("" : "+r"(toff));
    return (((toff >> 1) & ~2047u) ^ 8192) + (toff & 511);
}
template <int M>
__device__ __forceinline__ void ctx_store_part(float4* p, float (&d)[64], float i0, float i1) {
    float v[8];
    pack_group<M, true, true>(d, v, i0, i1);
    p[M * 32] = make_float4(v[0], v[1], v[2], v[3]);
    p[M * 32 + 128] = make_float4(v[4], v[5], v[6], v[7]);
}
__device__ __forceinline__ void ctx_store(uint32_t img, uint32_t toff, float (&o)[64], float i0, float i1) {
    asm volatile("" : "+r"(toff));
    float4* p = reinterpret_cast<float4*>(g_img + (img + toff));
    ctx_store_part<0>(p, o, i0, i1); ctx_store_part<1>(p, o, i0, i1); ctx_store_part<2>(p, o, i0, i1); ctx_store_part<3>(p, o, i0, i1);
}

__device__ __forceinline__ void slot_wait(uint32_t bars, uint32_t& ph, uint32_t slot) {
    mbar_wait(bars + 8 * slot, (ph >> slot) & 1);
    ph ^= 1u << slot;
}
__device__ __forceinline__ void release_if(uint32_t eb, uint32_t slot, bool on) {
    asm volatile("{\n.reg .pred p;\nsetp.ne.s32 p, %1, 0;\n@p mbarrier.arrive.shared::cluster.b64 _, [%0];\n}" ::"r"(eb + 8 * slot), "r"((int)on) : "memory");
}
__device__ __forceinline__ void slot_expect(uint32_t sb, uint32_t slot) {
    asm volatile("{\n.reg .pred p;\nelect.sync _|p, 0xffffffff;\n@p mbarrier.arrive.expect_tx.shared::cta.b64 _, [%0], 32768;\n}"
                 ::"r"(sb + BAR_FULL + 8 * slot) : "memory");
}
__device__ __forceinline__ void slot_acquire(uint32_t sb, uint32_t& ph, uint32_t slot) {
    slot_wait(sb + BAR_EMPTY, ph, slot);
    slot_expect(sb, slot);
}
__device__ __forceinline__ void load_bulk(uint32_t sb, uint32_t slot, uint32_t off, const void* src, uint32_t bytes, bool both, bool first) {
    if (both)
        asm volatile("{\n.reg .pred p;\nelect.sync _|p, 0xffffffff;\n"
                     "@p cp.async.bulk.shared::cluster.global.mbarrier::complete_tx::bytes.multicast::cluster.L2::cache_hint [%0], [%1], %5, [%2], %4, %3;\n}"
                     ::"r"(sb + slot * SLOT + off), "l"(src), "r"(sb + BAR_FULL + 8 * slot), "l"(first ? L2_FIRST : L2_NORMAL), "h"((uint16_t)3),
                     "r"(bytes) : "memory");
    else
        asm volatile("{\n.reg .pred p;\nelect.sync _|p, 0xffffffff;\n"
                     "@p cp.async.bulk.shared::cluster.global.mbarrier::complete_tx::bytes.L2::cache_hint [%0], [%1], %4, [%2], %3;\n}"
                     ::"r"(sb + slot * SLOT + off), "l"(src), "r"(sb + BAR_FULL + 8 * slot), "l"(first ? L2_FIRST : L2_NORMAL), "r"(bytes) : "memory");
}
__device__ __forceinline__ void load_tile(uint32_t sb, uint32_t slot, uint32_t off, const CUtensorMap* m, int row, int cb, bool both, bool first) {
    if (both)
        asm volatile("{\n.reg .pred p;\nelect.sync _|p, 0xffffffff;\n"
                     "@p cp.async.bulk.tensor.3d.shared::cluster.global.mbarrier::complete_tx::bytes.multicast::cluster.L2::cache_hint [%0], [%1, {%3, %4, %5}], [%2], %7, %6;\n}"
                     ::"r"(sb + slot * SLOT + off), "l"(m), "r"(sb + BAR_FULL + 8 * slot), "r"(0), "r"(row), "r"(cb),
                     "l"(first ? L2_FIRST : L2_NORMAL), "h"((uint16_t)3) : "memory");
    else
        asm volatile("{\n.reg .pred p;\nelect.sync _|p, 0xffffffff;\n"
                     "@p cp.async.bulk.tensor.3d.shared::cluster.global.mbarrier::complete_tx::bytes.L2::cache_hint [%0], [%1, {%3, %4, %5}], [%2], %6;\n}"
                     ::"r"(sb + slot * SLOT + off), "l"(m), "r"(sb + BAR_FULL + 8 * slot), "r"(0), "r"(row), "r"(cb),
                     "l"(first ? L2_FIRST : L2_NORMAL) : "memory");
}
__device__ __forceinline__ uint32_t ring_next(uint32_t r) { return r == 4 ? 0 : r + 1; }
__device__ __forceinline__ uint32_t w_table(int hp) { return hp ? 0x3104u : 0x4210u; }
__device__ __forceinline__ uint32_t a_table(int hp) { return hp ? 0x625u : 0x635u; }
__device__ __forceinline__ uint32_t a_next(uint32_t& t) {
    const uint32_t s = t & 15;
    t = (t >> 4) | (s << 8);
    return s;
}
constexpr uint32_t O_TABLE = 0x1604235u;
constexpr uint32_t SL_X = OFF == 0 ? 4 : OFF == 1 ? 3 : 1, SL_WD = OFF == 0 ? 6 : OFF == 1 ? 4 : 3, SL_WF = OFF == 0 ? 5 : OFF == 1 ? 6 : 4;
__device__ __forceinline__ uint32_t o_next(uint32_t& t) {
    const uint32_t s = t & 15;
    t = (t >> 4) | (s << 24);
    return s;
}
__device__ __forceinline__ int o_head(int i, int kh) { return i < 16 ? 4 * (i & 7) + 2 * (kh ^ 1) + (i >> 3) : 29 + 2 * kh; }

template <bool INIT>
__device__ __forceinline__ void gemm_issue(float (&d)[64], uint32_t a, uint32_t b, int acc, bool img) {
    uint64_t da = desc64(a, img ? HI_IMG : HI_128), db = desc64(b, HI_128);
    wg_fence();
#pragma unroll
    for (int k = 0; k < 8; k++) {
        if (INIT && k == 0) wgmma_ss128_init<1>(d, da, db);
        else wgmma_ss128<1>(d, da, db, k ? 1 : acc);
        desc_add(da, !(k & 1) ? 2 : img ? 30 : k == 3 ? 1018 : 2);
        desc_add(db, 128);
    }
    wg_commit();
}

__device__ __forceinline__ void step_retire(uint32_t eb, bool rel, uint32_t pend) {
    wg_wait<0>();
    release_if(eb, pend & 7, rel && (pend & 7) != 7);
    release_if(eb, pend >> 4, rel && pend < 0x70);
}
template <bool ODD>
__device__ __forceinline__ void proj_tile(float (&acc)[64], float (&prev)[64], int t, int q0, uint32_t sb, int wg, uint32_t eb, bool rel, uint32_t& fph,
                                          uint32_t wtab, uint32_t& atab, uint32_t& pend, uint32_t prev_img, uint32_t toff, float s0, float s1,
                                          uint32_t (&v)[32]) {
    const uint32_t a0 = desc_k(sb + (wg ^ (ODD && t == 5)) * 8192), b0 = desc_mn(sb);
    int q = q0;
#pragma unroll 1
    do {
        const uint32_t ws = (wtab >> (4 * q)) & 15, as = a_next(atab);
        if (!ODD && t != 2) slot_wait(sb + BAR_FULL, fph, ws);
        slot_wait(sb + BAR_FULL, fph, as);
        step_retire(eb, rel, pend);
        if (ODD && q == 2 && t == 5) {
            const uint32_t a = sb + 5 * SLOT + q_off(toff);
#pragma unroll
            for (int i = 0; i < 8; i++) sts128(a + (i >> 2) * 16384 + (i & 2) * 256 + (i & 1) * 1024, make_uint4(v[4 * i], v[4 * i + 1], v[4 * i + 2], v[4 * i + 3]));
        }
        bar_sync(1 + wg, 256);
        gemm_issue<false>(acc, a0 + as * (SLOT / 16), b0 + ws * (SLOT / 16), q, false);
        bar_arrive(2 - wg, 256);
        pend = (ODD && q == 1 && t == 5 ? 7 : as) | (ODD && t != 1 ? ws : 7) << 4;
        wg_wait<1>();
        reg_fence(prev);
        if (ODD && t == 5) {
            if (q == 0) {
#pragma unroll
                for (int i = 0; i < 32; i++) {
                    const int k = 16 * (i >> 3) + 4 * (i & 3) + ((i >> 1) & 2);
                    v[i] = pack2(prev[k], prev[k + 1]);
                }
            }
        } else {
            if (q == 0) img_store_global<0>(prev_img, toff, prev, s0, s1);
            if (q == 1) img_store_global<1>(prev_img, toff, prev, s0, s1);
            if (q == 2) img_store_global<2>(prev_img, toff, prev, s0, s1);
            if (q == 3) img_store_global<3>(prev_img, toff, prev, s0, s1);
        }
    } while (++q < (ODD && t == 5 ? 3 : 4));
}

__device__ __forceinline__ void qk_issue(float (&s)[64], uint32_t q, uint32_t k) {
    wg_fence();
    uint64_t da = desc64(q, HI_Q), db = desc64(k, HI_IMG);
    wgmma_ss128_init<0>(s, da, db);
#pragma unroll
    for (int i = 1; i < 8; i++) {
        desc_add(da, (i & 1) ? 2 : i == 4 ? 990 : 30);
        desc_add(db, (i & 1) ? 2 : 30);
        wgmma_ss128<0>(s, da, db, 1);
    }
    wg_commit();
}
__device__ __forceinline__ void qk_issue(float (&s)[32], uint32_t q, uint32_t k) {
    wg_fence();
    uint64_t da = desc64(q, HI_Q), db = desc64(k, HI_IMG);
    wgmma_ss64_init<0>(s, da, db);
#pragma unroll
    for (int i = 1; i < 8; i++) {
        desc_add(da, (i & 1) ? 2 : i == 4 ? 990 : 30);
        desc_add(db, (i & 1) ? 2 : 30);
        wgmma_ss64<0>(s, da, db, 1);
    }
    wg_commit();
}
__device__ __forceinline__ void pv_issue(float (&o)[64], const uint32_t (&p)[32], uint32_t v, int acc, bool half) {
    uint64_t db = desc64(v, HI_IMG);
    if (half) {
        asm volatile("// half" ::: "memory");
        wg_fence();
#pragma unroll
        for (int i = 0; i < 4; i++) {
            wgmma_rs128(o, p[4 * i], p[4 * i + 1], p[4 * i + 2], p[4 * i + 3], db, i ? 1 : acc);
            desc_add(db, 256);
        }
        wg_commit();
        asm volatile("// half" ::: "memory");
    } else {
        wg_fence();
#pragma unroll
        for (int i = 0; i < 8; i++) {
            wgmma_rs128(o, p[4 * i], p[4 * i + 1], p[4 * i + 2], p[4 * i + 3], db, i ? 1 : acc);
            desc_add(db, 256);
        }
        wg_commit();
    }
}
__device__ __forceinline__ void tri_mask(float (&s)[64], float x) {
#pragma unroll
    for (int k = 0; k < 16; k++) {
        float b;
        asm("sub.sat.f32 %0, %1, %2;" : "=f"(b) : "f"((float)(8 * (k >> 1) + (k & 1))), "f"(x));
        const int i = 32 + 4 * (k >> 1) + (k & 1);
        asm("fma.rn.f32 %0, %1, 0fFF61B1E6, %0;" : "+f"(s[i]) : "f"(b));
        if (k < 14) asm("fma.rn.f32 %0, %1, 0fFF61B1E6, %0;" : "+f"(s[i + 6]) : "f"(b));
    }
}
__device__ __forceinline__ void tri_mask_copy(float (&s)[64], const float (&h)[32], float x) {
#pragma unroll
    for (int i = 0; i < 32; i++) {
            asm("{\n.reg .pred p;\nsetp.lt.f32 p, %2, %3;\nselp.f32 %0, 0fFF800000, %1, p;\n}"
                : "=f"(s[i]) : "f"(h[i]), "f"(x), "f"((float)(8 * (i >> 2) - 4 * (i & 2) + (i & 1))));
        s[32 + i] = __uint_as_float(0xff800000u);
    }
}
constexpr float SM_HI = 1152921504606846976.f, SM_LO = 1.f / 1152921504606846976.f;
__device__ __forceinline__ bool softmax_unsafe(float t0, float t1, bool first) {
    bool bad = __any_sync(0xffffffffu, fmaxf(t0, t1) > SM_HI);
    if (first) {
        uint32_t a = __ballot_sync(0xffffffffu, t0 >= SM_LO), b = __ballot_sync(0xffffffffu, t1 >= SM_LO);
        a |= a >> 1;
        b |= b >> 1;
        bad |= ((a | (a >> 2)) & (b | (b >> 2)) & 0x11111111u) != 0x11111111u;
    }
    return bad;
}
__device__ __forceinline__ void softmax_remax(const float (&s)[64], float (&m)[2], bool first, float& m0, float& m1, float& a0, float& a1) {
    m0 = fmaxf(s[0], s[1]), m1 = fmaxf(s[2], s[3]);
#pragma unroll
    for (int k = 1; k < 16; k++) {
        m0 = fmaxf(m0, fmaxf(s[4 * k], s[4 * k + 1]));
        m1 = fmaxf(m1, fmaxf(s[4 * k + 2], s[4 * k + 3]));
    }
    m0 = fmaxf(m0, __shfl_xor_sync(0xffffffffu, m0, 1));
    m1 = fmaxf(m1, __shfl_xor_sync(0xffffffffu, m1, 1));
    m0 = fmaxf(m0, __shfl_xor_sync(0xffffffffu, m0, 2));
    m1 = fmaxf(m1, __shfl_xor_sync(0xffffffffu, m1, 2));
    if (!first) {
        m0 = fmaxf(m0, 0.f);
        m1 = fmaxf(m1, 0.f);
    }
    a0 = first ? 1.f : ex2(-m0);
    a1 = first ? 1.f : ex2(-m1);
    m[0] += m0;
    m[1] += m1;
}
template <int J0, int J1>
__device__ __forceinline__ void softmax_exp(const float (&s)[64], uint32_t (&p)[32], float (&t)[4]) {
#pragma unroll
    for (int k = J0; k < J1; k++) {
        const float e0 = ex2(s[4 * k]), e1 = ex2(s[4 * k + 1]), e2 = ex2(s[4 * k + 2]), e3 = ex2(s[4 * k + 3]);
        if (k == 0) { t[0] = e0; t[1] = e1; t[2] = e2; t[3] = e3; }
        else { t[0] += e0; t[1] += e1; t[2] += e2; t[3] += e3; }
        p[2 * k] = pack2(e0, e1);
        p[2 * k + 1] = pack2(e2, e3);
    }
}
__device__ __forceinline__ void mma16816(float (&d)[4], const uint32_t* a, uint32_t b0, uint32_t b1) {
    asm("mma.sync.aligned.m16n8k16.row.col.f32.bf16.bf16.f32 {%0, %1, %2, %3}, {%4, %5, %6, %7}, {%8, %9}, {%0, %1, %2, %3};"
        : "+f"(d[0]), "+f"(d[1]), "+f"(d[2]), "+f"(d[3]) : "r"(a[0]), "r"(a[1]), "r"(a[2]), "r"(a[3]), "r"(b0), "r"(b1));
}
__device__ __forceinline__ uint2 best_key(const uint32_t* keys, int lane, uint32_t ep, uint32_t cur, int enough) {
#pragma unroll 1
    for (;;) {
        const uint4 k = ld_poll(reinterpret_cast<const uint4*>(keys) + lane);
        const bool ok = (((k.x ^ ep) | (k.y ^ ep) | (k.z ^ ep) | (k.w ^ ep)) & 31) == 0;
        const uint32_t best = __reduce_max_sync(0xffffffffu, ok ? max(max(k.x, k.y), max(k.z, k.w)) : 0u);
        const int n = __popc(__ballot_sync(0xffffffffu, ok));
        if (n == 32 || (n >= enough && best != cur)) return make_uint2(best, n == 32);
        __nanosleep(n < KN ? KSLEEP : KSLEEP2);
    }
}

__global__ void __cluster_dims__(2, 1, 1) __launch_bounds__(384, 1)
fused_kernel(const __grid_constant__ CUtensorMap tm_ckv, const __grid_constant__ CUtensorMap tm_wq,
             const __grid_constant__ CUtensorMap tm_wuk, const __grid_constant__ CUtensorMap tm_wuv,
             const __grid_constant__ CUtensorMap tm_wo, const __grid_constant__ CUtensorMap tm_wg,
             const __grid_constant__ CUtensorMap tm_wu,
             const __grid_constant__ CUtensorMap tm_wm, const __grid_constant__ CUtensorMap tm_x, const Params P) {
    extern __shared__ __align__(1024) uint8_t smem[];
    if (threadIdx.x == 352) {
        asm volatile("prefetch.tensormap [%0];" ::"l"(&tm_ckv) : "memory");
        asm volatile("prefetch.tensormap [%0];" ::"l"(blockIdx.x >= NCTA ? &tm_wm : (blockIdx.x & 1) ? &tm_wuv : &tm_wuk) : "memory");
    }
    const uint32_t sb = (uint32_t)__cvta_generic_to_shared(smem);
    const int tid = threadIdx.x, lane = tid & 31, warp = __shfl_sync(0xffffffffu, tid >> 5, 0), wg = warp >> 2;
    const uint32_t sm = blockIdx.x < 8 ? blockIdx.x + 124 : blockIdx.x - 8, smq = ((sm - 64) * 147) >> 11;
    const int rb = sm < 64 ? (sm & 14) * 8 + (sm >> 4) * 2 + (sm & 1)
                 : sm < 120 ? ((sm - 64 - smq * 14) & 14) * 8 + 24 + smq * 2 + (sm & 1) : sm < 124 ? sm + 8 : sm - 116;
    const int grp = rb >> 3, j = rb & 7, kh = (grp >> 1) & 1;
    const int cq = (j & 1) + ((grp >> 1) & 2), ort = (grp & 8) + (grp & 1) * 4 + (j >> 1);
    if (warp == 0) TS(0);

    const CUtensorMap* tw = (j & 1) ? &tm_wuv : &tm_wuk;
    if (lane == 0) {
        if (warp == 8) {
#pragma unroll
            for (int i = 0; i < 7; i++) mbar_init(sb + BAR_FULL + 8 * i, 1);
            fence_async_smem();
        } else if (warp < 11) {
            const int w = warp - (warp > 8);
            const u64 cnt = (w < 5 ? (rb < NCTA ? 0x888888884444444ull : 0x888888888888888ull) : 0x111812111111118ull) >> (12 * (w % 5));
#pragma unroll
            for (int i = 0; i < 3; i++) mbar_init(sb + BAR_EMPTY + 24 * w + 8 * i, ((uint32_t)cnt >> (4 * i)) & 15);
        }
        asm volatile("fence.mbarrier_init.release.cluster;" ::: "memory");
    }
    __syncwarp();
    asm volatile("barrier.cluster.arrive.relaxed.aligned;" ::: "memory");
    if (warp == 8) {
        if (rb < NCTA) {
#pragma unroll 1
            for (int u = 0; u < 4; u++) {
                const uint32_t ws = u + (u == 3), as = (0x635u >> (4 * u)) & 15;
                slot_expect(sb, ws);
                load_tile(sb, ws, 0, tw, u * 128, 4 * grp, false, HINT & 1);
                if (u == 3) break;
                slot_expect(sb, as);
                load_tile(sb, as, 0, &tm_ckv, (j >> 1) * 128, u * 2, false, false);
                load_tile(sb, as, 16384, &tm_ckv, (j >> 1) * 128, u * 2 + 1, false, false);
            }
        } else {
#pragma unroll 1
            for (int i = 0; i < 6; i++) {
                slot_expect(sb, i);
                load_tile(sb, i, 0, &tm_wm, i * 64, (rb - NCTA) * 4, false, HINT & 64);
                if (i > 3) tma3d_prefetch(&tm_wm, i * 64 + 128, (rb - NCTA) * 4);
            }
        }
    }
    asm volatile("barrier.cluster.wait.aligned;" ::: "memory");

    if (rb >= NCTA) {
        const int sp = rb - NCTA;
        const uint32_t ep = __ldcg(&g_sync.epoch[0]) + 1;
        uint32_t ph = 0, sl = 0;
        if (warp == 8) {
#pragma unroll 1
            for (int i = 6; i < 54 + 2 * OFF; i++) {
                slot_acquire(sb, ph, sl);
                const int k = i - 24;
                load_tile(sb, sl, 0, i < 24 ? &tm_wm : i >= 54 ? &tm_wo : (k & 2) ? &tm_wu : &tm_wg, i < 24 ? (i & 7) * 64 : i >= 54 ? (i - 38 - 2 * OFF) * 256 : (k & 1) * 256,
                          i < 24 ? (i >> 3) * 16 + sp * 4 : i >= 54 ? sp * 2 : sp * 7 + (k >> 2), false, true);
                if (++sl == 6) sl = 0;
                if (i == 51) { i = 53; sl = 0; }
            }
            bar_sync(4, 64);
            slot_wait(sb + BAR_EMPTY, ph, 4);
            slot_wait(sb + BAR_EMPTY, ph, 5);
            ph = 0x3f, sl = 0;
#pragma unroll 1
            for (int h = 0; h < 32; h++) {
                step_watch(sb + SM_EP + 16, h + 1);
                fence_async_global();
                const uint8_t* src = g_ctx + (size_t)(((h >> 1) ^ 8) * 32 + 30 - 4 * OFF) * SLOT + (h & 1) * 16384;
#pragma unroll 1
                for (int k = 0; k <= 2 * OFF; k++, src += 2 * SLOT) {
                    slot_wait(sb + BAR_DONE, ph, sl);
                    const uint32_t f = sb + BAR_FLAG + 8 * sl, d = sb + 4 * SLOT + sl * 16384;
                    asm volatile("{\n.reg .pred p;\nelect.sync _|p, 0xffffffff;\n@p mbarrier.arrive.expect_tx.shared::cta.b64 _, [%0], 16384;\n}" ::"r"(f) : "memory");
                    if (k == 0)
                        asm volatile("{\n.reg .pred p;\nelect.sync _|p, 0xffffffff;\n"
                                     "@p cp.async.bulk.tensor.3d.shared::cluster.global.mbarrier::complete_tx::bytes [%0], [%1, {%3, %4, %5}], [%2];\n}"
                                     ::"r"(d), "l"(&tm_x), "r"(f), "r"(0), "r"((h ^ 16) * 64), "r"(sp * 2) : "memory");
                    else
                        asm volatile("{\n.reg .pred p;\nelect.sync _|p, 0xffffffff;\n"
                                     "@p cp.async.bulk.shared::cluster.global.mbarrier::complete_tx::bytes [%0], [%1], 16384, [%2];\n}"
                                     ::"r"(d), "l"(src), "r"(f) : "memory");
                    if (++sl == 6) sl = 0;
                }
            }
        } else if (warp == 9) {
#pragma unroll 1
            for (int t = 0; t <= 16; t++) {
                asm volatile("st.release.cta.shared.u32 [%0], %1;" ::"r"(sb + SM_EP + 16), "r"(2 * t) : "memory");
                if (t == 0) bar_sync(4, 64);
                if (lane < 4 && t < 16) flag_wait(&g_sync.ctxcnt[(t ^ 8) * 32 + 24 + 2 * lane], ep);
                __syncwarp();
            }
        } else if (warp < 8) {
            const uint32_t c2 = __ldg(reinterpret_cast<const uint32_t*>(P.c) + tid);
            uint32_t* sc = reinterpret_cast<uint32_t*>(smem + SM_TAB);
            sc[tid] = pack2(bf_lo(c2) * sigmoid(bf_lo(c2)), bf_hi(c2) * sigmoid(bf_hi(c2)));
            bar_sync(1, 256);
            const uint32_t a = sb + (warp >> 1) * 8192 + ((lane >> 4) * 8 + (lane & 7)) * 128, ch = (warp & 1) * 4 + ((lane >> 3) & 1);
#pragma unroll 1
            for (int ps = 0; ps < 3; ps++) {
                float d[2][4] = {};
#pragma unroll 1
                for (int bt = 0; bt < 8; bt++) {
                    slot_wait(sb + BAR_FULL, ph, sl);
#pragma unroll
                    for (int i = 0; i < 8; i++) {
                        uint32_t w[4];
                        asm volatile("ldmatrix.sync.aligned.m8n8.x4.trans.shared.b16 {%0, %1, %2, %3}, [%4];" : "=r"(w[0]), "=r"(w[1]), "=r"(w[2]), "=r"(w[3])
                                     : "r"(a + sl * SLOT + (i >> 1) * 2048 + (((ch + 2 * (i & 1)) ^ (lane & 7)) << 4)) : "memory");
                        mma16816(d[i & 1], w, sc[bt * 32 + (i >> 1) * 8 + (lane & 3)], sc[bt * 32 + (i >> 1) * 8 + 4 + (lane & 3)]);
                    }
                    __syncwarp();
                    mbar_arrive_if(sb + BAR_EMPTY + 8 * sl, lane == 0);
                    if (++sl == 6) sl = 0;
                }
                const float v = (lane & 2) ? ((lane & 1) ? d[1][2] : d[1][0]) : ((lane & 1) ? d[0][2] : d[0][0]);
                const int col = sp * 256 + warp * 32 + (lane & 3) * 8 + (lane >> 2);
                if (ps == 0) st_pub(g_mod1 + col, (pack2(0.f, v) & 0xffff0000u) | (ep & 0xffffu), true);
                else g_mod[ps * 1024 + col] = __float2bfloat16_rn(v);
                if (warp == 0) TS(1 + ps);
            }
#pragma unroll 1
            for (int k = 0; k < 28; k++) {
                slot_wait(sb + BAR_FULL, ph, sl);
                uint4* dst = reinterpret_cast<uint4*>(g_wf) + (sp * 28 + (k & ~3)) * 2048 + (k & 3) * 512 + tid;
#pragma unroll 4
                for (int i = 0; i < 8; i++) {
                    const int row = (i & 1) * 128 + (tid >> 1);
                    __stcs(dst + (i >> 1) * 2048 + (i & 1) * 256, lds128(sb + sl * SLOT + row * 128 + ((((i & 6) + ((tid ^ (row >> 2)) & 1)) ^ (row & 7)) << 4)));
                }
                __syncwarp();
                mbar_arrive_if(sb + BAR_EMPTY + 8 * sl, lane == 0);
                if (++sl == 6) sl = 0;
            }
            bar_sync(1, 256);
            if (tid < 2) {
                flag_add(&g_sync.cnt[7 * 8]);
                flag_wait(&g_sync.cnt[7 * 8], 8 * ep);
            }
            if (warp == 0) TS(4);
            bar_sync(1, 256);
            uint32_t ga[16], x2[32];
#pragma unroll
            for (int i = 0; i < 16; i++) ga[i] = __ldcg(reinterpret_cast<const uint32_t*>(g_mod) + 512 + sp * 64 + (lane & 3) + 4 * i);
#pragma unroll 1
            for (int i = 0; i < 2 * OFF; i++) slot_wait(sb + BAR_FULL, ph, i);
            float d[64];
            uint32_t u = (2 * OFF + 1) * wg, up = 0;
            if (wg == 1) bar_arrive(2, 256);
#pragma unroll 1
            for (int h = wg; h < 32; h += 2) {
                mbar_wait(sb + BAR_FLAG + 8 * u, up);
                const uint32_t xa = sb + 4 * SLOT + u * 16384 + ((warp & 3) * 16 + (lane & 15)) * 128;
#pragma unroll
                for (int k = 0; k < 8; k++)
                    asm volatile("ldmatrix.sync.aligned.m8n8.x4.shared.b16 {%0, %1, %2, %3}, [%4];"
                                 : "=r"(x2[4 * k]), "=r"(x2[4 * k + 1]), "=r"(x2[4 * k + 2]), "=r"(x2[4 * k + 3])
                                 : "r"(xa + (k >> 2) * 8192 + (((2 * (k & 3) + (lane >> 4)) ^ (lane & 7)) << 4)) : "memory");
                mbar_arrive_if(sb + BAR_DONE + 8 * u, lane < 2);
                bar_sync(2 + wg, 256);
#pragma unroll 1
                for (int k = 0; k < 2 * OFF; k++) {
                    const uint32_t pu = u;
                    if (++u == 6) { u = 0; up ^= 1; }
                    mbar_wait(sb + BAR_FLAG + 8 * u, up);
                    gemm_issue<false>(d, desc_k(sb + 4 * SLOT) + u * 1024, desc_mn(sb) + k * (SLOT / 16), k, true);
                    wg_wait<1>();
                    mbar_arrive_if(sb + BAR_DONE + 8 * pu, lane < 2 && k);
                }
                if (h < 31) bar_arrive(3 - wg, 256);
                wg_wait<0>();
                reg_fence(d);
                mbar_arrive_if(sb + BAR_DONE + 8 * u, lane < 2);
                u += 2 * OFF + 2;
                if (u >= 6) { u -= 6; up ^= 1; }
                uint4* op = g_x2 + ((h ^ 16) * 4 + sp) * 1024 + (tid & 127);
#pragma unroll
                for (int v = 0; v < 8; v++) {
                    uint32_t y[4];
#pragma unroll
                    for (int i = 0; i < 4; i++) {
                        const int k = 4 * v + i;
                        y[i] = pack2(fmaf(bf_lo(ga[k >> 1]), d[2 * k], bf_lo(x2[k])), fmaf(bf_hi(ga[k >> 1]), d[2 * k + 1], bf_hi(x2[k])));
                    }
                    op[v * 128] = make_uint4(y[0], y[1], y[2], y[3]);
                }
            }
            bar_sync(1, 256);
            if (tid == 0) flag_add(&g_sync.cnt[15 * 8]);
            if (warp == 0) TS(5);
        }
        return;
    }

    if (wg == 2) {
        asm volatile("setmaxnreg.dec.sync.aligned.u32 40;");
        if (warp == 8) {
            const uint32_t rank = j & 1, half = rank * 16384;
            uint32_t eph = 0, r = 0;
            *reinterpret_cast<volatile uint32_t*>(smem + SM_EP + 20) = 0;
#pragma unroll 1
            for (int hp = 0; hp < 2; hp++) {
                uint32_t wtab = w_table(hp), atab = a_table(hp);
                const int hc = 4 * grp + 2 * hp;
#pragma unroll 1
                for (int u = 3 - 3 * hp; u < 16; u++) {
                    if (hp && u < 4) {
                        const uint32_t ws = (wtab >> (4 * u)) & 15;
                        slot_acquire(sb, eph, ws);
                        load_tile(sb, ws, 0, tw, u * 128, hc, false, HINT & 1);
                        PT();
                    }
                    if (hp == 1 && (u & 7) == 4) mbar_wait(sb + BAR_FLAG + 24 + (u & 8), 0);
                    const uint32_t as = a_next(atab);
                    slot_acquire(sb, eph, as);
                    load_tile(sb, as, half, &tm_ckv, ((u & 12) + (j >> 1)) * 128, (u & 3) * 2 + rank, true, (HINT & 8) && hp);
                    PT();
                    if (hp == 1 && (u | 2) == 3 && lane == 0)
                        asm volatile("red.relaxed.gpu.global.add.u32 [%0], 1;" ::"l"(&g_sync.cnt[(grp * 8 + 3 + (u >> 1)) * 8]) : "memory");
                }
                const uint8_t* src = g_h + (15 - j) * 4 * SLOT;
#pragma unroll 1
                for (int u = 0; u < 8; u++) {
                    if (u == 0 || u == KVG) {
                        mbar_wait(sb + BAR_FLAG + (u ? 8 + 32 * hp : 0), 0);
                        fence_async_global();
                    }
                    if (u < 4) {
                        const uint32_t ws = (wtab >> (4 * u)) & 15;
                        slot_acquire(sb, eph, ws);
                        load_tile(sb, ws, 0, &tm_wq, u * 128, hc, false, HINT & 1);
                        PT();
                    }
                    const uint32_t as = a_next(atab);
                    slot_acquire(sb, eph, as);
                    load_bulk(sb, as, 0, src, SLOT, false, (HINT & 8) && hp);
                    PT();
                    src += u == 3 ? (8 * j - 63) * SLOT : SLOT;
                }
                const int step = hp ? -2 * SLOT : 2 * SLOT;
                src = g_KV + (size_t)(grp * 32 + 30 * hp) * SLOT + half - step;
#pragma unroll 1
                for (int n = 0; n <= 17; n++) {
                    if (n == 8) {
                        mbar_wait(sb + BAR_FLAG + 16 + 32 * hp, 0);
                        fence_async_global();
                    }
                    const uint8_t* v = src + SLOT;
                    src += n < 16 - j ? step : n == 16 - j ? (2 * j - 15) * step : -step;
                    if (n < 17) {
                        slot_acquire(sb, eph, r);
                        if (n != 15 - (j & 6)) load_bulk(sb, r, half, src, SLOT / 2, true, HINT & 4);
                        else load_bulk(sb, r, 0, src - half, SLOT, false, HINT & 4);
                        PT();
                        r = ring_next(r);
                    }
                    if (n) {
                        slot_acquire(sb, eph, r);
                        if (n != 16 - (j & 6)) load_bulk(sb, r, half, v, SLOT / 2, true, HINT & 4);
                        else load_bulk(sb, r, 0, v - half, SLOT, false, HINT & 4);
                        PT();
                        r = ring_next(r);
                    }
                    asm volatile("st.volatile.shared.u32 [%0], %1;" ::"r"(sb + SM_EP + 16), "r"(18 * hp + n + 1) : "memory");
                }
            }
            uint32_t otab = O_TABLE, ready = 0;
#pragma unroll 1
            for (int i = 0; i < 17; i += i == 7 - OFF ? 1 + OFF : 1) {
                const bool dyn = i >= 8 && i < 15;
                const uint32_t want = dyn ? 15u << (4 * (i - 8)) : 1u << max(i + 14, 28);
                if (!(ready & want)) {
                    do {
                        asm volatile("ld.acquire.cta.shared.u32 %0, [%1];" : "=r"(ready) : "r"(sb + SM_EP + 20) : "memory");
                        ready = __shfl_sync(0xffffffffu, ready, 0);
                    } while (!(ready & want));
                    fence_async_global();
                }
                const int head = o_head(dyn ? (ready >> (4 * (i - 8))) & 15 : i, kh);
                const uint32_t as = o_next(otab), ws = o_next(otab), off = i < 15 ? half : kh * 16384;
                slot_acquire(sb, eph, as);
                load_bulk(sb, as, off, g_ctx + (size_t)(ort * 32 + head) * SLOT + off, SLOT / 2, i < 15, HINT & 16);
                if (i >= 15) load_bulk(sb, as, off ^ 16384, i == 15 ? g_x2 + ((ort * 2 + kh) * 4 + cq) * 1024 : reinterpret_cast<const uint4*>(P.wdown) + min(rb, NFFN - 1) * 1024, SLOT / 2, false, false);
                PT();
                slot_acquire(sb, eph, ws);
                load_tile(sb, ws, 0, &tm_wo, head * 128, cq * 2, false, HINT & 2);
                PT();
                if (i == 0) o_next(otab);
            }
            if (rb < NFFN) {
                slot_acquire(sb, eph, SL_WF);
                load_bulk(sb, SL_WF, 0, g_wf + rb * SLOT, SLOT, false, false);
            }
        } else if (warp == 9) {
            *reinterpret_cast<volatile uint32_t*>(smem + SM_EP + 16) = 0;
            l2_prefetch(P.ckv + rb * 2048, 4096);
            mbar_watch(sb + BAR_FULL, 0);
            l2_prefetch(P.ckv + 512 * 512 + rb * 2048, 4096);
            mbar_watch(sb + BAR_FULL + 8 * XPF, 0);
            l2_prefetch(P.x + rb * 8192, 16384);
            mbar_watch(sb + BAR_FULL + 8 * 4, 0);
            l2_prefetch(P.ckv + 1024 * 512 + rb * 4096, 8192);
            TS(40);
#pragma unroll 1
            for (int i = 0; i < 13; i++) {
                step_watch(sb + SM_EP + 16, i == 0 ? 0 : i < 5 ? PFA + i : 13 + PFB + i);
                if (i == 10) mbar_watch(sb + BAR_FLAG + 8 * 7, 0);
                const int rf = min(rb, NFFN - 1), pc = 4 * (i - 5) + cq;
                const uint8_t* p = i == 3 ? reinterpret_cast<const uint8_t*>(P.ckv) + rb * 16384
                                 : i == 4 ? g_h + rb * 16384
                                 : i < 8 ? g_ctx + (size_t)(ort * 32 + o_head(pc >> 1, kh)) * SLOT + (pc & 1) * 16384
                                 : i < 10 ? reinterpret_cast<const uint8_t*>(P.wo) + (grp * 16 + (i & 1) * 8 + j) * 16384
                                 : i == 10 ? reinterpret_cast<const uint8_t*>(P.wdown) + rf * 16384 : g_wf + rf * SLOT + (i & 1) * 16384;
                if (i >= 3) l2_prefetch(p, 16384);
                else if ((i | j) & 1) tma3d_prefetch(i == 1 ? tw : &tm_wq, (j >> 1) * 128, grp * 4 + (i ? 2 : 0));
            }
            const uint32_t v = lds32(sb + SM_EP) - 1;
            sts128(sb + SM_RED + lane * 16, make_uint4(v, v, v, v));
            fence_async_smem();
            __syncwarp();
#pragma unroll 1
            for (int i = 0; i < OB / 32; i++) bulk_store(g_out + rb * OB + i * 32, sb + SM_RED, 512, false);
            asm volatile("cp.async.bulk.commit_group;\ncp.async.bulk.wait_group 0;" ::: "memory");
            fence_async_global();
            __syncwarp();
            mbar_arrive_if(sb + BAR_PF, lane == 0);
            if (lane == 0) mbar_watch(sb + BAR_END, 0);
        } else {
            const uint32_t ep = __ldcg(&g_sync.epoch[0]) + 1;
            asm volatile("st.shared.u32 [%0], %1;" ::"r"(sb + SM_EP), "r"(ep) : "memory");
            mbar_wait(sb + BAR_FULL + 8 * 4, 0);
            {
                uint4 v[4];
                for (;;) {
                    uint32_t bad = 0;
#pragma unroll
                    for (int k = 0; k < 4; k++) v[k] = ld_poll(reinterpret_cast<const uint4*>(g_mod1) + (warp & 1) * 128 + k * 32 + lane);
#pragma unroll
                    for (int k = 0; k < 4; k++) bad |= (v[k].x ^ ep) | (v[k].y ^ ep) | (v[k].z ^ ep) | (v[k].w ^ ep);
                    if (__all_sync(0xffffffffu, (bad & 0xffff) == 0)) break;
                    __nanosleep(100);
                }
                const uint32_t one = (warp & 1) ? ONE2 : 0x80008000u;
#pragma unroll
                for (int k = 0; k < 4; k++)
                    *reinterpret_cast<uint2*>(smem + SM_TAB + (warp & 1) * 1024 + k * 256 + lane * 8) =
                        make_uint2(badd(__byte_perm(v[k].x, v[k].y, 0x7632), one), badd(__byte_perm(v[k].z, v[k].w, 0x7632), one));
            }
            __syncwarp();
            mbar_arrive_if(sb + BAR_FLAG + 8 * 8, lane == 0);
            if (warp == 10) {
#pragma unroll 1
                for (int i = 0; i < 9; i++) {
                    mbar_sleep(sb + BAR_DONE + 8 * i);
                    if (lane == 0) flag_add(i && ((i - 1) & 2) ? &g_sync.ctxcnt[((i & 1) ? 15 - j : j) * 32 + 2 * grp + (i > 4)] : &g_sync.cnt[(grp * 8 + i) * 8]);
                    if (i == 0) TS(43);
                }
            } else {
                TS(42);
#pragma unroll 1
                for (int i = 0; i < 8; i++) {
                    mbar_sleep(sb + BAR_DONE + 8 * (i == 7 ? 6 : i == 4 ? 3 : i));
                    if (lane < 2) flag_wait(&g_sync.cnt[((i == 0 ? (lane ? j : 15 - j) : i == 7 ? 0 : grp) * 8 + i) * 8], 8 * ep);
                    __syncwarp();
                    mbar_arrive_if(sb + BAR_FLAG + 8 * i, lane == 0 && i < 7);
                    TS(48 + i);
                }
                const uint32_t *mp = reinterpret_cast<const uint32_t*>(g_mod) + lane, *wp = reinterpret_cast<const uint32_t*>(P.wr) + lane;
                float ra = 0.f, rs = 0.f;
#pragma unroll 1
                for (int k = 0; k < 256; k += 32) {
                    const uint32_t ga = __ldcg(mp + 512 + k), sh = __ldcg(mp + 768 + k), c1 = badd(__ldcg(mp + 1024 + k), ONE2);
                    const uint32_t gb = __ldcg(mp + 1280 + k), ww = __ldg(wp + k);
                    const uint32_t a = bmul(c1, ww);
                    ra += bf_lo(a) + bf_hi(a);
                    rs = fmaf(bf_lo(sh), bf_lo(ww), fmaf(bf_hi(sh), bf_hi(ww), rs));
                    if (k >> 6 == cq) {
                        sts128(sb + SM_TAB + ((k & 32) + lane) * 16, make_uint4(ga << 16, ga & 0xffff0000u, a, 0));
                        sts128(sb + SM_TAB + 1024 + ((k & 32) + lane) * 16, make_uint4(c1, sh, gb, 0));
                    }
                }
#pragma unroll 1
                for (int o = 16; o > 0; o >>= 1) {
                    ra += __shfl_xor_sync(0xffffffffu, ra, o);
                    rs += __shfl_xor_sync(0xffffffffu, rs, o);
                }
                *reinterpret_cast<float2*>(smem + SM_EP + 8) = make_float2(ra, rs);
                __syncwarp();
                mbar_arrive_if(sb + BAR_FLAG + 8 * 7, lane == 0);
                const uint32_t* f = lane < 17 ? &g_sync.ctxcnt[ort * 32 + o_head(lane, kh)] : &g_sync.cnt[15 * 8];
                uint32_t ready = -(j & 1), list = 0, sh = 0, qa;
                asm("mapa.shared::cluster.u32 %0, %1, %2;" : "=r"(qa) : "r"(sb + SM_EP + 20), "r"(lane & 1));
                while (ready != ~0u) {
                    uint32_t v;
                    asm volatile("ld.acquire.gpu.global.u32 %0, [%1];" : "=r"(v) : "l"(f) : "memory");
                    const uint32_t now = __ballot_sync(0xffffffffu, (int)(v - (lane < 17 ? ep : NSPARE * ep)) >= 0);
#pragma unroll 1
                    for (uint32_t fresh = now & ~ready & 0x7f00; fresh; fresh &= fresh - 1, sh += 4) list |= (__ffs(fresh) - 1) << sh;
                    list |= (((now & 0xff) + 1) >> 8 << 28) | ((now & (now >> 2) & 0x18000) << 14);
                    if (now != ready && lane < 2) asm volatile("st.relaxed.cluster.shared::cluster.u32 [%0], %1;" ::"r"(qa), "r"(list) : "memory");
                    if ((now & 0xff) == 0xff) mbar_sleep(sb + BAR_DONE + 8 * 7);
                    ready = now;
                    __nanosleep(POLL_NS);
                }
                TS(45);
            }
        }
    } else {
        const bool elected = (tid & 127) == 0, rel = (tid & 95) == 0;
        uint32_t eb;
        asm("mapa.shared::cluster.u32 %0, %1, %2;" : "=r"(eb) : "r"(sb + BAR_EMPTY), "r"(warp & 1));
        const int g = lane >> 2, c4 = lane & 3;
        uint32_t toff = warp * 4096 + g * 64 + ((c4 ^ (g >> 1)) << 4);
        uint32_t fph = 0x3f, r = 0;
        if (wg == 1) bar_arrive(1, 256);
        const uint32_t kd = desc_k(sb), wd = desc_mn(sb), vd = ((sb & 0x3ffff) >> 4) | (32u << 16);
        const int nL = 16 - j, hn = nL - 1 + wg;
        float s[64], o[64], li[2] = {0.f, 0.f};
        uint32_t cimg = 0;
        const float sc = (j & 1) ? 1.f : SM_C;
#pragma unroll 1
        for (int q = 0; q < 3; q++) {
            const uint32_t as = (0x635u >> (4 * q)) & 15;
            mbar_wait(sb + BAR_FULL + 8 * q, 0);
            mbar_wait(sb + BAR_FULL + 8 * as, 0);
            bar_sync(1 + wg, 256);
            gemm_issue<false>(s, kd + wg * 512 + as * (SLOT / 16), wd + q * (SLOT / 16), q, false);
            bar_arrive(2 - wg, 256);
            wg_wait<0>();
            release_if(eb, as, rel);
        }
        {
            const int xrow = rb * 16 + warp * 2;
            const uint4* xp = reinterpret_cast<const uint4*>(P.x) + xrow * 64;
            const uint32_t img = (grp * 32 + j) * SLOT;
            uint32_t x[16], x0[2];
            float st[4] = {0.f, 0.f, 0.f, 0.f};
            mbar_wait(sb + BAR_FULL + 8 * 4, 0);
#pragma unroll
            for (int q = 3; q < 8; q++) {
                const uint32_t ws = (0x4210u >> (4 * (q & 3))) & 15, as = (0x635u >> (4 * (q % 3))) & 15;
                mbar_wait(sb + BAR_FULL + 8 * as, (q / 3) & 1);
                bar_sync(1 + wg, 256);
                if (q == 3) gemm_issue<false>(s, kd + wg * 512 + as * (SLOT / 16), wd + ws * (SLOT / 16), 1, false);
                else if (q == 4) gemm_issue<true>(o, kd + wg * 512 + as * (SLOT / 16), wd + ws * (SLOT / 16), 0, false);
                else gemm_issue<false>(o, kd + wg * 512 + as * (SLOT / 16), wd + ws * (SLOT / 16), 1, false);
                bar_arrive(2 - wg, 256);
                sched_fence(fph, P.zero);
                if (q > 3) reg_fence(s);
                if (q == 3) {
                    asm volatile("setmaxnreg.inc.sync.aligned.u32 232;");
#pragma unroll
                    for (int i = 0; i < 4; i++)
                        asm volatile("ld.global.nc.v4.u32 {%0, %1, %2, %3}, [%4];" : "=r"(x[4 * i]), "=r"(x[4 * i + 1]), "=r"(x[4 * i + 2]), "=r"(x[4 * i + 3])
                                     : "l"(xp + lane + 32 * i) : "memory");
#pragma unroll
                    for (int i = 0; i < 2; i++) asm volatile("ld.global.nc.u32 %0, [%1];" : "=r"(x0[i]) : "l"(xp + 64 * i) : "memory");
                }
                if (q == 4) {
                    img_store_global<0>(img, toff, s, sc, sc);
#pragma unroll
                    for (int k = 0; k < 16; k++) {
                        const float d0 = bf_lo(x[k]) - bf_lo(x0[k >> 3]), d1 = bf_hi(x[k]) - bf_lo(x0[k >> 3]);
                        st[k >> 3] += d0 + d1;
                        st[2 + (k >> 3)] = fmaf(d0, d0, fmaf(d1, d1, st[2 + (k >> 3)]));
                    }
#pragma unroll
                    for (int i = 0; i < 4 * NSH; i++) st[i & 3] += __shfl_xor_sync(0xffffffffu, st[i & 3], 1 << (i >> 2));
                    reg_fence(st);
                }
                if (q == 5) {
#pragma unroll
                    for (int i = 4 * NSH; i < 20; i++) st[i & 3] += __shfl_xor_sync(0xffffffffu, st[i & 3], 1 << (i >> 2));
                    img_store_global<1>(img, toff, s, sc, sc);
#pragma unroll
                    for (int i = 0; i < 2; i++) {
                        const float d = st[i] * (1.f / 512.f);
                        st[2 + i] = ln_rstd(fmaxf(fmaf(-d, d, st[2 + i] * (1.f / 512.f)), 0.f));
                        x0[i] = pack2(bf_lo(x0[i]) + d, bf_lo(x0[i]) + d);
                    }
                    reg_fence(st);
                    reg_fence(x0);
                }
                if (q > 5) {
                    if (q == 6) mbar_wait(sb + BAR_FLAG + 8 * 8, 0);
                    const uint4 a = lds128(sb + SM_TAB + 1024 + (q & 1) * 512 + lane * 16), c = lds128(sb + SM_TAB + (q & 1) * 512 + lane * 16);
                    uint8_t* hp = g_h + (grp * 8 + (q & 1) * 4 + (lane >> 3)) * 16384 + (xrow & 127) * 128;
#pragma unroll
                    for (int i = 0; i < 2; i++) {
                        const uint32_t* y = x + 8 * i + 4 * (q & 1);
                        *reinterpret_cast<uint4*>(hp + i * 128 + (((lane ^ xrow ^ i) & 7) << 4)) =
                            make_uint4(ln_apply(y[0], x0[i], st[2 + i], a.x, c.x), ln_apply(y[1], x0[i], st[2 + i], a.y, c.y),
                                       ln_apply(y[2], x0[i], st[2 + i], a.z, c.z), ln_apply(y[3], x0[i], st[2 + i], a.w, c.w));
                    }
                    if (q == 7) {
                        __syncwarp();
                        mbar_arrive_if(sb + BAR_DONE, lane == 0);
                    }
                    if (q == 6) img_store_global<2>(img, toff, s, sc, sc);
                    else img_store_global<3>(img, toff, s, sc, sc);
                }
                if (q < 7) {
                    sched_fence(fph, P.zero);
                    wg_wait<0>();
                    release_if(eb, as, rel);
                }
            }
        }
        uint32_t pend = 0x73;
        uint32_t p[32] = {};
#pragma unroll 1
        for (int hp = 0; hp < 2; hp++) {
            float m[2] = {0.f, 0.f}, l[2] = {0.f, 0.f}, t[4] = {0.f, 0.f, 0.f, 0.f};
            bool shifted = false, bad = false, plain = false;
            uint32_t qa = desc_k(sb + 5 * SLOT + (wg ^ 1) * 8192);
            const uint32_t limg = (512 + (15 - j) * 32 + 2 * grp + hp) * SLOT;
            {
                const int step = hp ? -8 * SLOT : 8 * SLOT;
                uint32_t img = (grp * 32 + (hp ? j ^ 30 : j) + 8) * SLOT;
                const uint32_t wtab = w_table(hp);
                uint32_t atab = hp ? 0x562u : 0x356u;
#pragma unroll 1
                for (int u = 2 - 2 * hp; u < 6; u += 2) {
                    proj_tile<false>(s, o, u, !u, sb, wg, eb, rel, fph, wtab, atab, pend, u ? img : cimg, toff, u ? sc : li[0], u ? sc : li[1], p);
                    __syncwarp();
                    mbar_arrive_if(sb + BAR_DONE + 4 * u + 32 * hp, lane == 0);
                    if (elected) TS(1 + 10 * hp + u + 20 * wg);
                    proj_tile<true>(o, s, u + 1, 0, sb, wg, eb, rel, fph, wtab, atab, pend, img + step, toff, sc, sc, p);
                    if (elected) TS(2 + 10 * hp + u + 20 * wg);
                    img += 2 * step;
                }
            }
            asm volatile("" : "+r"(toff));
            if (elected) TS(6 + 10 * hp + 20 * wg);
            fence_async_smem();
            slot_wait(sb + BAR_FULL, fph, r);
            step_retire(eb, rel, pend);
            reg_fence(o);
            int n = -1;
#pragma unroll 1
            for (;;) {
                while (bad || plain) {
                    float d0 = m[0], d1 = m[1];
                    if (bad) {
                        float a0, a1;
                        softmax_remax(s, m, n == 0 || n == nL, d0, d1, a0, a1);
                        shifted = true;
                        l[0] *= a0;
                        l[1] *= a1;
#pragma unroll
                        for (int i = 0; i < 64; i++) o[i] *= (i & 2) ? a1 : a0;
                    }
#pragma unroll
                    for (int i = 0; i < 64; i++) s[i] -= (i & 2) ? d1 : d0;
                    softmax_exp<0, 16>(s, p, t);
                    t[0] += t[1];
                    t[2] += t[3];
                    bad = !bad && softmax_unsafe(t[0], t[2], false);
                    plain = false;
                }
#pragma unroll 1
                do {
                    l[0] += t[0];
                    l[1] += t[2];
                    if (++n > 16) break;
                    const uint32_t ks = r;
                    uint32_t vs = ring_next(r);
                    r = ring_next(vs);
                    bar_sync(1 + wg, 256);
                    const float x = (float)((warp & 3) * 16 + g - 2 * c4);
                    if (n == hn) {
                        float sh[32];
                        qk_issue(sh, qa, kd + ks * (SLOT / 16));
                        slot_wait(sb + BAR_FULL, fph, vs);
                        pv_issue(o, p, vd + vs * (SLOT / 16), 1, false);
                        bar_arrive(2 - wg, 256);
                        wg_wait<1>();
                        reg_fence(sh);
                        tri_mask_copy(s, sh, x);
                        release_if(eb, ks, rel);
                        release_if(eb, 5 + wg, rel && (!wg || n == 16));
                        if (!wg) qa += SLOT / 16;
                        float e[4 * EARLY];
#pragma unroll
                        for (int i = 0; i < 4 * EARLY; i++) {
                            e[i] = ex2(s[i]);
                            t[i & 3] = i < 4 ? e[i] : t[i & 3] + e[i];
                        }
                        reg_fence(e);
                        slot_wait(sb + BAR_FULL, fph, r);
                        wg_wait<0>();
                        reg_fence(o);
                        reg_fence(e);
                        release_if(eb, vs, rel);
#pragma unroll
                        for (int i = 0; i < 2 * EARLY; i++) p[i] = pack2(e[2 * i], e[2 * i + 1]);
                        softmax_exp<EARLY, 8>(s, p, t);
                        if (wg) {
                            ctx_store(limg, toff, o, rcp(quad_sum(l[0])), rcp(quad_sum(l[1])));
                            __syncwarp();
                            mbar_arrive_if(sb + BAR_DONE + 24 + 32 * hp, lane == 0);
                            l[0] = l[1] = m[0] = m[1] = 0.f;
                            shifted = false;
                        }
                        t[0] += t[1];
                        t[2] += t[3];
                        plain = shifted;
                        if (plain) break;
                        bad = softmax_unsafe(t[0], t[2], wg);
                        continue;
                    }
                    if (n == nL) {
                        qk_issue(s, qa, kd + ks * (SLOT / 16));
                        slot_wait(sb + BAR_FULL, fph, vs);
                        pv_issue(o, p, vd + vs * (SLOT / 16), 1, true);
                        bar_arrive(2 - wg, 256);
                        const float i0 = rcp(quad_sum(l[0])), i1 = rcp(quad_sum(l[1]));
                        wg_wait<1>();
                        reg_fence(s);
                        release_if(eb, ks, rel);
                        release_if(eb, 6, rel && n == 16);
                        tri_mask(s, x);
                        float e[4 * EARLY2];
#pragma unroll
                        for (int i = 0; i < 4 * EARLY2; i++) {
                            e[i] = ex2(s[i]);
                            t[i & 3] = i < 4 ? e[i] : t[i & 3] + e[i];
                        }
                        reg_fence(e);
                        reg_fence(s);
                        reg_fence(t);
                        slot_wait(sb + BAR_FULL, fph, r);
                        sched_fence(fph, P.zero);
                        wg_wait<0>();
                        reg_fence(o);
                        reg_fence(e);
                        release_if(eb, vs, rel);
#pragma unroll
                        for (int i = 0; i < 2 * EARLY2; i++) p[i] = pack2(e[2 * i], e[2 * i + 1]);
                        softmax_exp<EARLY2, MSPLIT>(s, p, t);
                        ctx_store(limg, toff, o, i0, i1);
                        reg_fence(t);
                        reg_fence(s);
                        softmax_exp<MSPLIT, 16>(s, p, t);
                        __syncwarp();
                        mbar_arrive_if(sb + BAR_DONE + 24 + 32 * hp, lane == 0);
                        l[0] = l[1] = m[0] = m[1] = 0.f;
                        shifted = false;
                        t[0] += t[1];
                        t[2] += t[3];
                        bad = __any_sync(0xffffffffu, fmaxf(t[0], t[2]) > SM_HI || fminf(t[0], t[2]) < SM_LO);
                        continue;
                    }
                    qk_issue(s, qa, kd + ks * (SLOT / 16));
                    if (n == 0) {
                        r = vs;
                        vs = 4 - hp;
                        slot_wait(sb + BAR_FULL, fph, 6);
                        gemm_issue<false>(o, qa + SLOT / 16, wd + vs * (SLOT / 16), 1, false);
                    } else {
                        slot_wait(sb + BAR_FULL, fph, vs);
                        if (n == 1) {
                            wg_wait<1>();
                            reg_fence(o);
                            const uint32_t a = sb + 6 * SLOT + q_off(toff);
#pragma unroll
                            for (int i = 0; i < 8; i++) {
                                const int k = 16 * (i >> 1) + 2 * (i & 1);
                                sts128(a + (i >> 2) * 16384 + (i & 2) * 256 + (i & 1) * 1024,
                                       make_uint4(pack2(o[k], o[k + 1]), pack2(o[k + 4], o[k + 5]), pack2(o[k + 8], o[k + 9]), pack2(o[k + 12], o[k + 13])));
                            }
                        }
                        pv_issue(o, p, vd + vs * (SLOT / 16), n != 1 && n != nL + 1, n == hn + 1);
                    }
                    bar_arrive(2 - wg, 256);
                    wg_wait<1>();
                    reg_fence(s);
                    release_if(eb, ks, rel);
                    release_if(eb, 6, rel && n == 16);
                    if (n == nL - 1) {
                        tri_mask(s, x);
                        release_if(eb, 5, rel);
                        qa += SLOT / 16;
                    }
                    if (n == 2) fence_async_smem();
                    if (shifted) {
                        slot_wait(sb + BAR_FULL, fph, r);
                        wg_wait<0>();
                        reg_fence(o);
                        release_if(eb, vs, rel);
                        plain = true;
                        break;
                    }
                    float e[4 * EARLY];
#pragma unroll
                    for (int i = 0; i < 4 * EARLY; i++) {
                        e[i] = ex2(s[i]);
                        t[i & 3] = i < 4 ? e[i] : t[i & 3] + e[i];
                    }
                    reg_fence(e);
                    slot_wait(sb + BAR_FULL, fph, r);
                    wg_wait<0>();
                    reg_fence(o);
                    reg_fence(e);
                    release_if(eb, vs, rel);
#pragma unroll
                    for (int i = 0; i < 2 * EARLY; i++) p[i] = pack2(e[2 * i], e[2 * i + 1]);
                    softmax_exp<EARLY, 16>(s, p, t);
                    t[0] += t[1];
                    t[2] += t[3];
                    bad = __any_sync(0xffffffffu, fmaxf(t[0], t[2]) > SM_HI || (n == 0 && fminf(t[0], t[2]) < SM_LO));
                } while (!bad);
                if (!bad && !plain) break;
            }
            asm volatile("" : "+r"(toff));
            const uint32_t vs = r, ga = desc_k(sb + (hp ? 2 * (wg ^ kh ^ 1) : wg) * 8192);
            r = ring_next(r);
            slot_wait(sb + BAR_FULL, fph, 5);
            slot_wait(sb + BAR_FULL, fph, r);
            bar_sync(1 + wg, 256);
            gemm_issue<true>(s, ga + 5 * (SLOT / 16), wd + r * (SLOT / 16), 0, hp);
            pv_issue(o, p, vd + vs * (SLOT / 16), j, hn == 16);
            bar_arrive(2 - wg, 256);
            li[0] = rcp(quad_sum(l[0]));
            li[1] = rcp(quad_sum(l[1]));
            cimg = limg + (2 * j - 15) * 32 * SLOT + (wg ? -16384 : 16384);
            wg_wait<1>();
            release_if(eb, 5, rel);
            release_if(eb, r, rel && hp);
            wg_wait<0>();
            release_if(eb, vs, rel);
            reg_fence(o);
            img_store_global<0>(cimg, toff, o, li[0], li[1]);
            pend = 0x77;
            if (elected) TS(8 + 10 * hp + 20 * wg);
        }
        uint32_t otab = 0x2351604u;
        const uint32_t oa = desc_k(sb + (wg ^ kh ^ 1) * 16384);
        const int t7 = tid & 127, w4 = warp & 3, row = ort * 128 + kh * 64 + w4 * 16 + g;
#pragma unroll 1
        for (int i = 1; i < 15 - OFF - wg; i++) {
            const uint32_t as = o_next(otab), ws = o_next(otab);
            slot_wait(sb + BAR_FULL, fph, as);
            slot_wait(sb + BAR_FULL, fph, ws);
            bar_sync(1 + wg, 256);
            gemm_issue<false>(s, oa + as * (SLOT / 16), wd + ws * (SLOT / 16), 1, true);
            bar_arrive(2 - wg, 256);
            wg_wait<1>();
            reg_fence(o);
            if (i == 1) img_store_global<1>(cimg, toff, o, li[0], li[1]);
            if (i == 2) img_store_global<2>(cimg, toff, o, li[0], li[1]);
            if (i == CLAST) {
                img_store_global<3>(cimg, toff, o, li[0], li[1]);
                __syncwarp();
                mbar_arrive_if(sb + BAR_DONE + 64, lane == 0);
            }
            wg_wait<0>();
            release_if(eb, as, rel);
            release_if(eb, ws, rel);
        }
        mbar_wait(sb + BAR_PF, 0);
        const uint32_t ep = lds32(sb + SM_EP);
        uint32_t eb2 = sb + BAR_END;
        if (wg == 0) {
            reg_fence(s);
            if (elected) TS(9);
            TT(1);
#pragma unroll
            for (int v = 0; v < 8; v++)
                st_pub(g_out + rb * OB + v * 128 + t7, make_uint4((pack2(s[8 * v], s[8 * v + 1]) & ~1u) | (ep & 1), pack2(s[8 * v + 2], s[8 * v + 3]),
                                                                      pack2(s[8 * v + 4], s[8 * v + 5]), pack2(s[8 * v + 6], s[8 * v + 7])), true);
            constexpr uint32_t s1 = SL_WF, s2 = SL_WD;
            bar_sync(4, 256);
            uint32_t wf[64];
            float wn[64];
            if (rb < NFFN) {
                slot_wait(sb + BAR_FULL, fph, s1);
                const uint32_t a = sb + s1 * SLOT + (w4 * 128 + (lane >> 4) * 8 + (lane & 7)) * 32 + (((lane >> 3) ^ (lane >> 2)) & 1) * 16;
#pragma unroll
                for (int i = 0; i < 16; i++)
                    asm volatile("ldmatrix.sync.aligned.m8n8.x4.trans.shared.b16 {%0, %1, %2, %3}, [%4];"
                                 : "=r"(wf[4 * i]), "=r"(wf[4 * i + 1]), "=r"(wf[4 * i + 2]), "=r"(wf[4 * i + 3])
                                 : "r"(a + (i >> 3) * 16384 + (i & 7) * 512) : "memory");
                slot_wait(sb + BAR_FULL, fph, s2);
#pragma unroll
                for (int i = 0; i < 16; i++) {
                    const uint2 w = *reinterpret_cast<const uint2*>(smem + s2 * SLOT + (kh ^ 1) * 16384 + i * 1024 + t7 * 8);
                    wn[4 * i] = bf_lo(w.x); wn[4 * i + 1] = bf_hi(w.x); wn[4 * i + 2] = bf_lo(w.y); wn[4 * i + 3] = bf_hi(w.y);
                }
                reg_fence(wn);
            }
            const uint32_t gbf = __ldcg(reinterpret_cast<const uint32_t*>(g_mod) + 1280 + rb * 2 + (tid & 1));
            if (elected) TS(10);
            TT(2);
            float* sred = reinterpret_cast<float*>(smem + SM_RED);
            uint32_t best = ep ^ 1, all;
            bool fresh;
            do {
                if (warp == 0) {
                    const uint2 k = best_key(g_key + cq * 128, lane, ep, best, rb < NFFN ? SPEC : 32);
                    *reinterpret_cast<uint2*>(smem + SM_EP + 24) = k;
                    mbar_arrive_if(sb + BAR_BEST, lane == 0 && k.y);
                }
                bar_sync(3, 128);
                const uint2 k = *reinterpret_cast<const uint2*>(smem + SM_EP + 24);
                fresh = k.x != best;
                best = k.x;
                all = k.y;
                TT(3);
                if (!fresh || rb >= NFFN) break;
                const uint4* cp = g_cand + ((~best >> 9) & 127) * 192;
                uint4 cv[6];
                for (;;) {
                    uint32_t bad = 0;
#pragma unroll
                    for (int v = 0; v < 6; v++) cv[v] = ld_poll(cp + w4 * 24 + v * 4 + c4);
#pragma unroll
                    for (int v = 0; v < 6; v++) bad |= cv[v].w ^ ep;
                    if (__all_sync(0xffffffffu, bad == 0)) break;
                }
            TT(4);
                float d[4][4] = {};
#pragma unroll
                for (int k = 0; k < 8; k++) {
                    const uint32_t b0 = (&cv[(2 * k) / 3].x)[(2 * k) % 3], b1 = (&cv[(2 * k + 1) / 3].x)[(2 * k + 1) % 3];
                    mma16816(d[k & 1], wf + 4 * k, b0, b1);
                    mma16816(d[2 + (k & 1)], wf + 32 + 4 * k, b0, b1);
                }
                const float u = (c4 & 2) ? ((c4 & 1) ? d[2][2] + d[3][2] : d[2][0] + d[3][0]) : ((c4 & 1) ? d[0][2] + d[1][2] : d[0][0] + d[1][0]);
                sred[w4 * 32 + c4 * 8 + g] = u;
                bar_sync(3, 128);
                const float v = rbf((sred[lane] + sred[32 + lane]) + (sred[64 + lane] + sred[96 + lane]));
                const float act = rbf(rbf(v * sigmoid(v)) * __shfl_down_sync(0xffffffffu, v, 16));
                float y[4] = {0.f, 0.f, 0.f, 0.f};
#pragma unroll
                for (int k = 0; k < 16; k++) {
                    const float a = __shfl_sync(0xffffffffu, act, k);
#pragma unroll
                    for (int i = 0; i < 4; i++) y[i] = fmaf(a, wn[4 * k + i], y[i]);
                }
                st_pub(g_out + rb * OB + OB_Y + t7, make_uint4((__float_as_uint(y[0]) & ~15u) | (ep & 15), (__float_as_uint(y[1]) & ~127u) | ((best >> 9) & 127),
                                                               __float_as_uint(y[2]), __float_as_uint(y[3])), true);
            } while (!all);
            const int sel = (~best >> 5) & 2047;
            const int pq = (2 * rb + (tid & 1)) & 63, pv = (pq >> 2) / 3;
            const uint4* fp = g_cand + (sel >> 4) * 192 + (rb >> 5) * 24 + pv * 4 + (pq & 3);
            uint4 fh = {}, fx = {};
            if (rb == 0 && tid == 0) g_sync.epoch[0] = ep;
            if (elected) TS(60);
            TT(5);
            uint4 yv;
            if (warp == 0) { fh = ld_poll(fp); fx = ld_poll(fp + 96); }
            if (fresh && rb < NFFN) __nanosleep(YPRE);
            for (;;) {
                yv = ld_poll(g_out + min(t7, NFFN - 1) * OB + OB_Y + rb);
                if (__all_sync(0xffffffffu, (((yv.x ^ ep) & 15) | ((yv.y ^ (best >> 9)) & 127)) == 0)) break;
                if (YSLEEP) __nanosleep(YSLEEP);
            }
            if (elected) TS(61);
            TT(6);
            float y[4] = {0.f, 0.f, 0.f, 0.f};
            if (t7 < NFFN) { y[0] = __uint_as_float(yv.x); y[1] = __uint_as_float(yv.y); y[2] = __uint_as_float(yv.z); y[3] = __uint_as_float(yv.w); }
            const float z0 = ((lane & 16) ? y[2] : y[0]) + __shfl_xor_sync(0xffffffffu, (lane & 16) ? y[0] : y[2], 16);
            const float z1 = ((lane & 16) ? y[3] : y[1]) + __shfl_xor_sync(0xffffffffu, (lane & 16) ? y[1] : y[3], 16);
            float z = ((lane & 8) ? z1 : z0) + __shfl_xor_sync(0xffffffffu, (lane & 8) ? z0 : z1, 8);
            z += __shfl_xor_sync(0xffffffffu, z, 4);
            z = quad_sum(z);
            if ((lane & 7) == 0) sred[128 + (lane >> 3) * 4 + w4] = z;
            bar_sync(3, 128);
            if (tid < 2) {
                while (fh.w != ep || fx.w != ep) { fh = ld_poll(fp); fx = ld_poll(fp + 96); }
                const float4 y0 = *reinterpret_cast<const float4*>(sred + 128 + tid * 8), y1 = *reinterpret_cast<const float4*>(sred + 132 + tid * 8);
                const int cm = (pq >> 2) - 3 * pv;
                const uint32_t h2 = cm == 0 ? fh.x : cm == 1 ? fh.y : fh.z, x2 = cm == 0 ? fx.x : cm == 1 ? fx.y : fx.z;
                const float sg = sigmoid(bf_hi((best & 0x80000000u) ? (best ^ 0x80000000u) : ~best));
                reinterpret_cast<uint32_t*>(P.out)[sel * 256 + rb * 2 + tid] =
                    badd(x2, bmul(gbf, badd(h2, bmul(pack2((y0.x + y0.y) + (y0.z + y0.w), (y1.x + y1.y) + (y1.z + y1.w)), pack2(sg, sg)))));
            }
            if (elected) TS(62);
            TT(7);
        } else {
            const float4* tf = reinterpret_cast<const float4*>(smem + SM_TAB) + c4;
            uint32_t x2[32];
            bar_sync(2, 256);
#pragma unroll 1
            for (int i = 14; i < 17; i++) {
                const uint32_t as = o_next(otab), ws = o_next(otab);
                slot_wait(sb + BAR_FULL, fph, as);
                slot_wait(sb + BAR_FULL, fph, ws);
                gemm_issue<false>(s, oa + as * (SLOT / 16), wd + ws * (SLOT / 16), 1, true);
                wg_wait<1>();
            }
            const uint4* pr = g_out + (rb ^ 16) * OB + t7;
            uint4 pa[8];
            if (elected) TS(29);
            TT(1);
#pragma unroll
            for (int k = 0; k < 8; k++) {
                const uint4 v = lds128(sb + SL_X * SLOT + (kh ^ 1) * 16384 + k * 2048 + t7 * 16);
                x2[4 * k] = v.x; x2[4 * k + 1] = v.y; x2[4 * k + 2] = v.z; x2[4 * k + 3] = v.w;
            }
            wg_wait<0>();
            reg_fence(s);
            bar_arrive(4, 256);
            if (elected) TS(39);
            TT(2);
#pragma unroll
            for (int v = 0; v < 8; v++) pa[v] = ld_poll(pr + v * 128);
            float4 tc[16];
#pragma unroll
            for (int k = 0; k < 16; k++) {
                tc[k] = tf[k * 4];
                if (!(g & 1)) tc[k].z = __uint_as_float(ONE2);
#pragma unroll
                for (int i = 4 * k; i < 4 * k + 4; i++) s[i] = fmaf((i & 1) ? tc[k].y : tc[k].x, s[i], (i & 1) ? bf_hi(x2[i >> 1]) : bf_lo(x2[i >> 1]));
            }
            reg_fence(s);
            sched_fence(eb2, P.zero);
            for (;;) {
                uint32_t bad = 0;
#pragma unroll
                for (int v = 0; v < 8; v++) asm("lop3.b32 %0, %0, %1, %2, 0xf6;" : "+r"(bad) : "r"(pa[v].x), "r"(ep));
                if (__all_sync(0xffffffffu, (bad & 1) == 0)) break;
                if (PSLEEP) __nanosleep(PSLEEP);
#pragma unroll
                for (int v = 0; v < 8; v++) pa[v] = ld_poll(pr + v * 128);
            }
            if (elected) TS(30);
            TT(3);
            float sd[4] = {}, q0[4] = {}, q1[4] = {};
#pragma unroll
            for (int k = 0; k < 8; k++) {
#pragma unroll
                for (int i = 4 * k; i < 4 * k + 4; i++) {
                    const uint32_t w = (&pa[k].x)[i & 3];
                    x2[i] = pack2(fmaf(tc[i >> 1].x, bf_lo(w), s[2 * i]), fmaf(tc[i >> 1].y, bf_hi(w), s[2 * i + 1]));
                }
                mma16816(sd, x2 + 4 * k, __float_as_uint(tc[2 * k].z), __float_as_uint(tc[2 * k + 1].z));
                mma16816(q0, x2 + 4 * k, x2[4 * k], x2[4 * k + 2]);
                mma16816(q1, x2 + 4 * k, x2[4 * k + 1], x2[4 * k + 3]);
            }
            uint4* sp = g_out + rb * OB + OB_STAT + (w4 * 8 + g) * 2;
            st_pub(sp, make_uint4(__float_as_uint(sd[0]), __float_as_uint((g & 1) ? q0[1] : q0[0]), __float_as_uint(sd[1]), ep), c4 == g >> 1);
            st_pub(sp + 1, make_uint4(__float_as_uint(sd[2]), __float_as_uint((g & 1) ? q1[3] : q1[2]), __float_as_uint(sd[3]), ep), c4 == g >> 1);
            sched_fence(eb2, P.zero);
            if (elected) TS(56);
            TT(4);
            uint32_t cb[16], sh[16], gb[16];
#pragma unroll
            for (int i = 0; i < 16; i++) {
                const float4 c = tf[64 + i * 4];
                cb[i] = __float_as_uint(c.x); sh[i] = __float_as_uint(c.y); gb[i] = __float_as_uint(c.z);
            }
            const float ra = __uint_as_float(lds32(sb + SM_EP + 8)), rb0 = __uint_as_float(lds32(sb + SM_EP + 12));
            uint4 r0, r1;
            for (;;) {
                r0 = ld_poll(g_out + ((rb & ~33) + (c4 & 1) + (c4 & 2) * 16) * OB + OB_STAT + (w4 * 8 + g) * 2);
                r1 = ld_poll(g_out + ((rb & ~33) + (c4 & 1) + (c4 & 2) * 16) * OB + OB_STAT + (w4 * 8 + g) * 2 + 1);
                if (__all_sync(0xffffffffu, r0.w == ep && r1.w == ep)) break;
                if (SSLEEP) __nanosleep(SSLEEP);
            }
            if (elected) TS(57);
            TT(5);
            const float m0 = quad_sum(__uint_as_float(r0.x)) * (1.f / 512.f), m1 = quad_sum(__uint_as_float(r1.x)) * (1.f / 512.f);
            const float rs0 = ln_rstd(fmaxf(fmaf(-m0, m0, quad_sum(__uint_as_float(r0.y)) * (1.f / 512.f)), 0.f));
            const float rs1 = ln_rstd(fmaxf(fmaf(-m1, m1, quad_sum(__uint_as_float(r1.y)) * (1.f / 512.f)), 0.f));
            const uint32_t mb0 = pack2(m0, m0), mb1 = pack2(m1, m1);
            const uint32_t lg = pack2(fmaf(rs0, fmaf(-bf_lo(mb0), ra, quad_sum(__uint_as_float(r0.z))), rb0),
                                      fmaf(rs1, fmaf(-bf_lo(mb1), ra, quad_sum(__uint_as_float(r1.z))), rb0));
            const uint32_t u0 = lg << 16, u1 = lg & 0xffff0000u;
            const uint32_t k0 = ((u0 ^ (((int)u0 >> 31) | 0x80000000u)) & 0xffff0000u) | ((2047 - row) << 5) | (ep & 31);
            const uint32_t k1 = ((u1 ^ (((int)u1 >> 31) | 0x80000000u)) & 0xffff0000u) | ((2039 - row) << 5) | (ep & 31);
            const uint32_t kb = __reduce_max_sync(0xffffffffu, max(k0, k1));
            st_pub(g_key + cq * 128 + (row >> 4), kb, lane == 0);
            const bool cand = kb == k0 || kb == k1;
            uint4* cp = g_cand + (row >> 4) * 192 + cq * 24 + c4;
#pragma unroll 1
            for (int it = 0; it < 3; it++) {
                bool put = it == 1 || !cand;
                if (it == 2) {
                    mbar_wait(sb + BAR_BEST, 0);
                    put = cand && lds32(sb + SM_EP + 24) != kb;
                }
                const bool hi = (kb == k1) != (it == 1);
                uint32_t cx[18], ch[18];
#pragma unroll
                for (int i = 0; i < 16; i++) {
                    cx[i] = hi ? x2[2 * i + 1] : x2[2 * i];
                    ch[i] = ln_apply(cx[i], hi ? mb1 : mb0, hi ? rs1 : rs0, cb[i], sh[i]);
                }
                cx[16] = cx[17] = ch[16] = ch[17] = 0;
#pragma unroll
                for (int v = 0; v < 6; v++) st_pub(cp + v * 4, make_uint4(ch[3 * v], ch[3 * v + 1], ch[3 * v + 2], ep), cand && it == 0);
#pragma unroll
                for (int v = 0; v < 6; v++) st_pub(cp + 96 + v * 4, make_uint4(cx[3 * v], cx[3 * v + 1], cx[3 * v + 2], ep), cand && it == 0);
                if (it == 0) TT(6);
                uint2* op = reinterpret_cast<uint2*>(P.out) + (row + 8 * hi) * 128 + cq * 32 + (c4 & 1) * 2 + (c4 >> 1);
#pragma unroll
                for (int i = 0; i < 16; i += 2) {
                    const uint32_t v0 = badd(cx[i], bmul(gb[i], ch[i])), v1 = badd(cx[i + 1], bmul(gb[i + 1], ch[i + 1]));
                    const uint32_t rv = __shfl_xor_sync(0xffffffffu, (c4 & 1) ? v0 : v1, 1);
                    if (put) op[i * 2] = (c4 & 1) ? make_uint2(rv, v1) : make_uint2(v0, rv);
                }
            }
            if (elected) TS(59);
            TT(7);
        }
        mbar_arrive_if(eb2, lane == 0);
    }
}

typedef CUresult (*EncodeFn)(CUtensorMap*, CUtensorMapDataType, cuuint32_t, void*, const cuuint64_t*, const cuuint64_t*,
                             const cuuint32_t*, const cuuint32_t*, CUtensorMapInterleave, CUtensorMapSwizzle,
                             CUtensorMapL2promotion, CUtensorMapFloatOOBfill);

void make_3d(EncodeFn fn, CUtensorMap* m, const void* p, uint64_t cols, uint64_t rows, uint32_t br = 128, uint32_t nb = 2) {
    cuuint64_t dims[3] = {64, rows, cols / 64}, strides[2] = {cols * 2, 128};
    cuuint32_t box[3] = {64, br, nb}, es[3] = {1, 1, 1};
    fn(m, CU_TENSOR_MAP_DATA_TYPE_BFLOAT16, 3, const_cast<void*>(p), dims, strides, box, es, CU_TENSOR_MAP_INTERLEAVE_NONE,
       CU_TENSOR_MAP_SWIZZLE_128B, CU_TENSOR_MAP_L2_PROMOTION_L2_256B, CU_TENSOR_MAP_FLOAT_OOB_FILL_NONE);
}

}

extern "C" void kernel_launch(void* const* d_in, const int* in_sizes, int n_in, void* d_out, int out_size) {
    static EncodeFn fn = nullptr;
    if (!fn) {
        void* f = nullptr;
        cudaDriverEntryPointQueryResult st;
        cudaGetDriverEntryPoint("cuTensorMapEncodeTiled", &f, cudaEnableDefault, &st);
        fn = (EncodeFn)f;
        cudaFuncSetAttribute(fused_kernel, cudaFuncAttributeMaxDynamicSharedMemorySize, SMEM_BYTES);
    }
    CUtensorMap ckv, wq, wuk, wuv, wo, wg, wu, wm, xm;
    make_3d(fn, &ckv, d_in[1], 512, 2048, 128, 1);
    make_3d(fn, &xm, d_in[0], 512, 2048, 64);
    make_3d(fn, &wq, d_in[2], 4096, 512);
    make_3d(fn, &wuk, d_in[3], 4096, 512);
    make_3d(fn, &wuv, d_in[4], 4096, 512);
    make_3d(fn, &wo, d_in[5], 512, 4096);
    make_3d(fn, &wg, d_in[8], 1792, 512, 256, 1);
    make_3d(fn, &wu, d_in[9], 1792, 512, 256, 1);
    make_3d(fn, &wm, d_in[12], 3072, 512, 64, 4);
    Params p;
    p.x = (const bf16*)d_in[0];
    p.ckv = (const bf16*)d_in[1];
    p.wo = (const bf16*)d_in[5];
    p.wr = (const bf16*)d_in[7];
    p.wdown = (const bf16*)d_in[10];
    p.c = (const bf16*)d_in[11];
    p.out = (bf16*)d_out;
    p.zero = 0;
    fused_kernel<<<NCTA + NSPARE, 384, SMEM_BYTES>>>(ckv, wq, wuk, wuv, wo, wg, wu, wm, xm, p);
}
```

```cpp
#include <cuda.h>
#include <cuda_bf16.h>
#include <cuda_runtime.h>
#include <stdint.h>
#include <stdio.h>

namespace {

typedef __nv_bfloat16 bf16;
typedef unsigned long long u64;

constexpr int NCTA = 128, NSPARE = 4;
constexpr int SLOT = 32768;
constexpr int SM_BAR = 7 * SLOT;
constexpr int BAR_FULL = SM_BAR;
constexpr int BAR_EMPTY = BAR_FULL + 8 * 7;
constexpr int BAR_DONE = BAR_EMPTY + 8 * 7;
constexpr int BAR_FLAG = BAR_DONE + 8 * 9;
constexpr int BAR_PF = BAR_FLAG + 8 * 9;
constexpr int BAR_END = BAR_PF + 8;
constexpr int BAR_BEST = BAR_END + 8;
constexpr int SM_EP = BAR_END + 40;
constexpr int SM_RED = SM_BAR + 384;
constexpr int SM_TAB = SM_BAR + 1024;
constexpr int SMEM_BYTES = SM_BAR + 3072;
constexpr int NFFN = 112;
#define HINT 479
constexpr u64 L2_NORMAL = 0x1000000000000000ull, L2_FIRST = 0x12F0000000000000ull;
#define PFA 8
#define PFB 6
#define POLL_NS 50
#define MSPLIT 13
#define NSH 1
#define XPF 1
#define KSLEEP 400
#define YSLEEP 50
#define YPRE 150
#define SSLEEP 50
#define PSLEEP 100
#define KVG 7
#define EARLY2 4
#define OFF 2
#define CLAST 2
#define KN 16
#define KSLEEP2 60
#define EARLY 7
constexpr uint32_t SPIN_LIMIT = 1u << 22;
constexpr uint32_t ONE2 = 0x3f803f80u;

struct Sync {
    uint32_t cnt[16 * 8 * 8];
    uint32_t ctxcnt[16 * 32];
    uint32_t epoch[32];
};

__device__ __align__(1024) uint8_t g_img[2 * 512 * SLOT];
#define g_KV g_img
#define g_ctx (g_img + 512 * SLOT)
__device__ __align__(1024) uint8_t g_h[16 * 4 * SLOT];
constexpr int OB = 1216, OB_STAT = 1024, OB_Y = 1088;
__device__ __align__(1024) uint4 g_out[128 * OB];
__device__ __align__(1024) bf16 g_mod[3072];
__device__ __align__(1024) uint32_t g_mod1[1024];
__device__ __align__(1024) uint4 g_cand[128 * 192];
__device__ __align__(1024) uint32_t g_key[4 * 128];
__device__ __align__(1024) uint8_t g_wf[NFFN * SLOT];
__device__ __align__(1024) uint4 g_x2[128 * 1024];
__device__ __align__(1024) Sync g_sync;
#define TS(i)

#define TT(i)
#define PT()

struct Params {
    const bf16 *x, *ckv, *wo, *wr, *wdown, *c;
    bf16* out;
    int zero;
};

__device__ __forceinline__ void mbar_init(uint32_t bar, uint32_t cnt) {
    asm volatile("mbarrier.init.shared::cta.b64 [%0], %1;" ::"r"(bar), "r"(cnt) : "memory");
}
__device__ __forceinline__ void mbar_wait(uint32_t bar, uint32_t parity) {
    asm volatile("{\n.reg .pred p;\nL_%=:\nmbarrier.try_wait.parity.shared::cta.b64 p, [%0], %1;\n@!p bra L_%=;\n}" ::"r"(bar), "r"(parity) : "memory");
}
__device__ __forceinline__ void mbar_sleep(uint32_t bar) {
    if ((threadIdx.x & 31) == 0)
        asm volatile("{\n.reg .pred p;\nL_%=:\nmbarrier.try_wait.parity.shared::cta.b64 p, [%0], 0, 100000;\n@!p bra L_%=;\n}" ::"r"(bar) : "memory");
    __syncwarp();
}
__device__ __forceinline__ void mbar_watch(uint32_t bar, uint32_t parity) {
    asm volatile("{\n.reg .pred p;\n.reg .u32 n;\nmov.u32 n, 0;\n"
                 "L_%=:\nmbarrier.try_wait.parity.shared::cta.b64 p, [%0], %1;\n@p bra D_%=;\n"
                 "add.u32 n, n, 1;\nsetp.lt.u32 p, n, %2;\n@p bra L_%=;\ntrap;\nD_%=:\n}"
                 ::"r"(bar), "r"(parity), "n"(SPIN_LIMIT) : "memory");
}
__device__ __forceinline__ void step_watch(uint32_t a, uint32_t step) {
    asm volatile("{\n.reg .pred p;\n.reg .u32 n, v;\nmov.u32 n, 0;\n"
                 "L_%=:\nld.volatile.shared.u32 v, [%0];\nsetp.ge.u32 p, v, %1;\n@p bra D_%=;\nnanosleep.u32 400;\n"
                 "add.u32 n, n, 1;\nsetp.lt.u32 p, n, %2;\n@p bra L_%=;\ntrap;\nD_%=:\n}"
                 ::"r"(a), "r"(step), "n"(SPIN_LIMIT) : "memory");
}
__device__ __forceinline__ void mbar_arrive_if(uint32_t bar, bool on) {
    asm volatile("{\n.reg .pred p;\nsetp.ne.s32 p, %1, 0;\n@p mbarrier.arrive.shared::cta.b64 _, [%0];\n}" ::"r"(bar), "r"((int)on) : "memory");
}
__device__ __forceinline__ void tma3d_prefetch(const CUtensorMap* m, int row, int cb) {
    asm volatile("{\n.reg .pred p;\nelect.sync _|p, 0xffffffff;\n@p cp.async.bulk.prefetch.tensor.3d.L2.global [%0, {%1, %2, %3}];\n}"
                 ::"l"(m), "r"(0), "r"(row), "r"(cb) : "memory");
}
__device__ __forceinline__ void l2_prefetch(const void* p, uint32_t bytes) {
    asm volatile("{\n.reg .pred p;\nelect.sync _|p, 0xffffffff;\n@p cp.async.bulk.prefetch.L2.global [%0], %1;\n}" ::"l"(p), "r"(bytes) : "memory");
}
__device__ __forceinline__ void bulk_store(void* dst, uint32_t src, uint32_t bytes, bool first) {
    asm volatile("{\n.reg .pred p;\nelect.sync _|p, 0xffffffff;\n@p cp.async.bulk.global.shared::cta.bulk_group.L2::cache_hint [%0], [%1], %2, %3;\n}"
                 ::"l"(dst), "r"(src), "r"(bytes), "l"(first ? L2_FIRST : L2_NORMAL) : "memory");
}
__device__ __forceinline__ void flag_wait(const uint32_t* f, uint32_t target) {
    asm volatile("{\n.reg .pred p;\n.reg .u32 v;\n"
                 "L_%=:\nld.acquire.gpu.global.u32 v, [%0];\nsub.u32 v, v, %1;\nsetp.lt.s32 p, v, 0;\n@p nanosleep.u32 100;\n@p bra L_%=;\n}"
                 ::"l"(f), "r"(target) : "memory");
}
__device__ __forceinline__ uint4 ld_poll(const uint4* p) {
    uint4 v;
    asm volatile("{\n.reg .b128 t;\nld.relaxed.gpu.global.b128 t, [%4];\nmov.b128 {%0, %1, %2, %3}, t;\n}"
                 : "=r"(v.x), "=r"(v.y), "=r"(v.z), "=r"(v.w) : "l"(p) : "memory");
    return v;
}
__device__ __forceinline__ void st_pub(uint4* p, uint4 v, bool on) {
    asm volatile("{\n.reg .pred p;\n.reg .b128 t;\nsetp.ne.s32 p, %5, 0;\nmov.b128 t, {%1, %2, %3, %4};\n@p st.relaxed.gpu.global.b128 [%0], t;\n}"
                 ::"l"(p), "r"(v.x), "r"(v.y), "r"(v.z), "r"(v.w), "r"((int)on) : "memory");
}
__device__ __forceinline__ void st_pub(uint32_t* p, uint32_t v, bool on) {
    asm volatile("{\n.reg .pred p;\nsetp.ne.s32 p, %2, 0;\n@p st.relaxed.gpu.global.u32 [%0], %1;\n}" ::"l"(p), "r"(v), "r"((int)on) : "memory");
}
__device__ __forceinline__ void flag_add(uint32_t* p) {
    asm volatile("red.release.gpu.global.add.u32 [%0], 1;" ::"l"(p) : "memory");
}
__device__ __forceinline__ uint32_t lds32(uint32_t a) {
    uint32_t v;
    asm volatile("ld.shared.u32 %0, [%1];" : "=r"(v) : "r"(a) : "memory");
    return v;
}
__device__ __forceinline__ uint4 lds128(uint32_t a) {
    uint4 v;
    asm volatile("ld.shared.v4.u32 {%0, %1, %2, %3}, [%4];" : "=r"(v.x), "=r"(v.y), "=r"(v.z), "=r"(v.w) : "r"(a) : "memory");
    return v;
}
__device__ __forceinline__ void sched_fence(uint32_t& v, uint32_t z) {
    uint32_t ck;
    asm volatile("mov.u32 %0, %%clock;" : "=r"(ck)::"memory");
    v ^= ck & z;
}
__device__ __forceinline__ void fence_async_global() { asm volatile("fence.proxy.async.global;" ::: "memory"); }
__device__ __forceinline__ void fence_async_smem() { asm volatile("fence.proxy.async.shared::cta;" ::: "memory"); }
__device__ __forceinline__ void bar_sync(int id, int n) { asm volatile("bar.sync %0, %1;" ::"r"(id), "r"(n) : "memory"); }
__device__ __forceinline__ void bar_arrive(int id, int n) { asm volatile("bar.arrive %0, %1;" ::"r"(id), "r"(n) : "memory"); }
__device__ __forceinline__ void wg_fence() { asm volatile("wgmma.fence.sync.aligned;" ::: "memory"); }
__device__ __forceinline__ void wg_commit() { asm volatile("wgmma.commit_group.sync.aligned;" ::: "memory"); }
template <int N> __device__ __forceinline__ void wg_wait() { asm volatile("wgmma.wait_group.sync.aligned %0;" ::"n"(N) : "memory"); }
template <int N> __device__ __forceinline__ void reg_fence(float (&d)[N]) {
#pragma unroll
    for (int i = 0; i < N; i++) asm volatile("" : "+f"(d[i])::"memory");
}
template <int N> __device__ __forceinline__ void reg_fence(uint32_t (&d)[N]) {
#pragma unroll
    for (int i = 0; i < N; i++) asm volatile("" : "+r"(d[i])::"memory");
}
__device__ __forceinline__ uint32_t desc_k(uint32_t a) { return ((a & 0x3ffff) >> 4) | (1u << 16); }
__device__ __forceinline__ uint32_t desc_mn(uint32_t a) { return ((a & 0x3ffff) >> 4) | (1024u << 16); }

__device__ __forceinline__ uint64_t desc64(uint32_t lo, uint32_t hi) {
    uint64_t d;
    asm("mov.b64 %0, {%1, %2};" : "=l"(d) : "r"(lo), "r"(hi));
    return d;
}
__device__ __forceinline__ void desc_add(uint64_t& d, uint32_t x) { asm("add.u64 %0, %0, %1;" : "+l"(d) : "l"((uint64_t)x)); }

template <int TB>
__device__ __forceinline__ void wgmma_ss128(float (&d)[64], uint64_t da, uint64_t db, int acc) {
    asm volatile("{\n.reg .pred p;\nsetp.ne.b32 p, %66, 0;\n"
        "wgmma.mma_async.sync.aligned.m64n128k16.f32.bf16.bf16 {%0, %1, %2, %3, %4, %5, %6, %7, %8, %9, %10, %11, %12, %13, %14, %15, %16, %17, %18, %19, %20, %21, %22, %23, %24, %25, %26, %27, %28, %29, %30, %31, %32, %33, %34, %35, %36, %37, %38, %39, %40, %41, %42, %43, %44, %45, %46, %47, %48, %49, %50, %51, %52, %53, %54, %55, %56, %57, %58, %59, %60, %61, %62, %63}, %64, %65, p, 1, 1, 0, %67;\n}"
        : "+f"(d[0]), "+f"(d[1]), "+f"(d[2]), "+f"(d[3]), "+f"(d[4]), "+f"(d[5]), "+f"(d[6]), "+f"(d[7]), "+f"(d[8]), "+f"(d[9]), "+f"(d[10]), "+f"(d[11]), "+f"(d[12]), "+f"(d[13]), "+f"(d[14]), "+f"(d[15]), "+f"(d[16]), "+f"(d[17]), "+f"(d[18]), "+f"(d[19]), "+f"(d[20]), "+f"(d[21]), "+f"(d[22]), "+f"(d[23]), "+f"(d[24]), "+f"(d[25]), "+f"(d[26]), "+f"(d[27]), "+f"(d[28]), "+f"(d[29]), "+f"(d[30]), "+f"(d[31]), "+f"(d[32]), "+f"(d[33]), "+f"(d[34]), "+f"(d[35]), "+f"(d[36]), "+f"(d[37]), "+f"(d[38]), "+f"(d[39]), "+f"(d[40]), "+f"(d[41]), "+f"(d[42]), "+f"(d[43]), "+f"(d[44]), "+f"(d[45]), "+f"(d[46]), "+f"(d[47]), "+f"(d[48]), "+f"(d[49]), "+f"(d[50]), "+f"(d[51]), "+f"(d[52]), "+f"(d[53]), "+f"(d[54]), "+f"(d[55]), "+f"(d[56]), "+f"(d[57]), "+f"(d[58]), "+f"(d[59]), "+f"(d[60]), "+f"(d[61]), "+f"(d[62]), "+f"(d[63])
        : "l"(da), "l"(db), "r"(acc), "n"(TB));
}
template <int TB>
__device__ __forceinline__ void wgmma_ss128_init(float (&d)[64], uint64_t da, uint64_t db) {
    asm volatile("{\n.reg .pred p;\nsetp.ne.b32 p, 0, 0;\n"
        "wgmma.mma_async.sync.aligned.m64n128k16.f32.bf16.bf16 {%0, %1, %2, %3, %4, %5, %6, %7, %8, %9, %10, %11, %12, %13, %14, %15, %16, %17, %18, %19, %20, %21, %22, %23, %24, %25, %26, %27, %28, %29, %30, %31, %32, %33, %34, %35, %36, %37, %38, %39, %40, %41, %42, %43, %44, %45, %46, %47, %48, %49, %50, %51, %52, %53, %54, %55, %56, %57, %58, %59, %60, %61, %62, %63}, %64, %65, p, 1, 1, 0, %66;\n}"
        : "=f"(d[0]), "=f"(d[1]), "=f"(d[2]), "=f"(d[3]), "=f"(d[4]), "=f"(d[5]), "=f"(d[6]), "=f"(d[7]), "=f"(d[8]), "=f"(d[9]), "=f"(d[10]), "=f"(d[11]), "=f"(d[12]), "=f"(d[13]), "=f"(d[14]), "=f"(d[15]), "=f"(d[16]), "=f"(d[17]), "=f"(d[18]), "=f"(d[19]), "=f"(d[20]), "=f"(d[21]), "=f"(d[22]), "=f"(d[23]), "=f"(d[24]), "=f"(d[25]), "=f"(d[26]), "=f"(d[27]), "=f"(d[28]), "=f"(d[29]), "=f"(d[30]), "=f"(d[31]), "=f"(d[32]), "=f"(d[33]), "=f"(d[34]), "=f"(d[35]), "=f"(d[36]), "=f"(d[37]), "=f"(d[38]), "=f"(d[39]), "=f"(d[40]), "=f"(d[41]), "=f"(d[42]), "=f"(d[43]), "=f"(d[44]), "=f"(d[45]), "=f"(d[46]), "=f"(d[47]), "=f"(d[48]), "=f"(d[49]), "=f"(d[50]), "=f"(d[51]), "=f"(d[52]), "=f"(d[53]), "=f"(d[54]), "=f"(d[55]), "=f"(d[56]), "=f"(d[57]), "=f"(d[58]), "=f"(d[59]), "=f"(d[60]), "=f"(d[61]), "=f"(d[62]), "=f"(d[63])
        : "l"(da), "l"(db), "n"(TB));
}
template <int TB>
__device__ __forceinline__ void wgmma_ss64(float (&d)[32], uint64_t da, uint64_t db, int acc) {
    asm volatile("{\n.reg .pred p;\nsetp.ne.b32 p, %34, 0;\n"
        "wgmma.mma_async.sync.aligned.m64n64k16.f32.bf16.bf16 {%0, %1, %2, %3, %4, %5, %6, %7, %8, %9, %10, %11, %12, %13, %14, %15, %16, %17, %18, %19, %20, %21, %22, %23, %24, %25, %26, %27, %28, %29, %30, %31}, %32, %33, p, 1, 1, 0, %35;\n}"
        : "+f"(d[0]), "+f"(d[1]), "+f"(d[2]), "+f"(d[3]), "+f"(d[4]), "+f"(d[5]), "+f"(d[6]), "+f"(d[7]), "+f"(d[8]), "+f"(d[9]), "+f"(d[10]), "+f"(d[11]), "+f"(d[12]), "+f"(d[13]), "+f"(d[14]), "+f"(d[15]), "+f"(d[16]), "+f"(d[17]), "+f"(d[18]), "+f"(d[19]), "+f"(d[20]), "+f"(d[21]), "+f"(d[22]), "+f"(d[23]), "+f"(d[24]), "+f"(d[25]), "+f"(d[26]), "+f"(d[27]), "+f"(d[28]), "+f"(d[29]), "+f"(d[30]), "+f"(d[31])
        : "l"(da), "l"(db), "r"(acc), "n"(TB));
}
template <int TB>
__device__ __forceinline__ void wgmma_ss64_init(float (&d)[32], uint64_t da, uint64_t db) {
    asm volatile("{\n.reg .pred p;\nsetp.ne.b32 p, 0, 0;\n"
        "wgmma.mma_async.sync.aligned.m64n64k16.f32.bf16.bf16 {%0, %1, %2, %3, %4, %5, %6, %7, %8, %9, %10, %11, %12, %13, %14, %15, %16, %17, %18, %19, %20, %21, %22, %23, %24, %25, %26, %27, %28, %29, %30, %31}, %32, %33, p, 1, 1, 0, %34;\n}"
        : "=f"(d[0]), "=f"(d[1]), "=f"(d[2]), "=f"(d[3]), "=f"(d[4]), "=f"(d[5]), "=f"(d[6]), "=f"(d[7]), "=f"(d[8]), "=f"(d[9]), "=f"(d[10]), "=f"(d[11]), "=f"(d[12]), "=f"(d[13]), "=f"(d[14]), "=f"(d[15]), "=f"(d[16]), "=f"(d[17]), "=f"(d[18]), "=f"(d[19]), "=f"(d[20]), "=f"(d[21]), "=f"(d[22]), "=f"(d[23]), "=f"(d[24]), "=f"(d[25]), "=f"(d[26]), "=f"(d[27]), "=f"(d[28]), "=f"(d[29]), "=f"(d[30]), "=f"(d[31])
        : "l"(da), "l"(db), "n"(TB));
}
__device__ __forceinline__ void wgmma_rs128(float (&d)[64], uint32_t a0, uint32_t a1, uint32_t a2, uint32_t a3, uint64_t db, int acc) {
    asm volatile("{\n.reg .pred p;\nsetp.ne.b32 p, %69, 0;\n"
        "wgmma.mma_async.sync.aligned.m64n128k16.f32.bf16.bf16 {%0, %1, %2, %3, %4, %5, %6, %7, %8, %9, %10, %11, %12, %13, %14, %15, %16, %17, %18, %19, %20, %21, %22, %23, %24, %25, %26, %27, %28, %29, %30, %31, %32, %33, %34, %35, %36, %37, %38, %39, %40, %41, %42, %43, %44, %45, %46, %47, %48, %49, %50, %51, %52, %53, %54, %55, %56, %57, %58, %59, %60, %61, %62, %63}, {%64, %65, %66, %67}, %68, p, 1, 1, 1;\n}"
        : "+f"(d[0]), "+f"(d[1]), "+f"(d[2]), "+f"(d[3]), "+f"(d[4]), "+f"(d[5]), "+f"(d[6]), "+f"(d[7]), "+f"(d[8]), "+f"(d[9]), "+f"(d[10]), "+f"(d[11]), "+f"(d[12]), "+f"(d[13]), "+f"(d[14]), "+f"(d[15]), "+f"(d[16]), "+f"(d[17]), "+f"(d[18]), "+f"(d[19]), "+f"(d[20]), "+f"(d[21]), "+f"(d[22]), "+f"(d[23]), "+f"(d[24]), "+f"(d[25]), "+f"(d[26]), "+f"(d[27]), "+f"(d[28]), "+f"(d[29]), "+f"(d[30]), "+f"(d[31]), "+f"(d[32]), "+f"(d[33]), "+f"(d[34]), "+f"(d[35]), "+f"(d[36]), "+f"(d[37]), "+f"(d[38]), "+f"(d[39]), "+f"(d[40]), "+f"(d[41]), "+f"(d[42]), "+f"(d[43]), "+f"(d[44]), "+f"(d[45]), "+f"(d[46]), "+f"(d[47]), "+f"(d[48]), "+f"(d[49]), "+f"(d[50]), "+f"(d[51]), "+f"(d[52]), "+f"(d[53]), "+f"(d[54]), "+f"(d[55]), "+f"(d[56]), "+f"(d[57]), "+f"(d[58]), "+f"(d[59]), "+f"(d[60]), "+f"(d[61]), "+f"(d[62]), "+f"(d[63])
        : "r"(a0), "r"(a1), "r"(a2), "r"(a3), "l"(db), "r"(acc));
}

__device__ __forceinline__ uint32_t pack2(float lo, float hi) {
    uint32_t r;
    asm("cvt.rn.bf16x2.f32 %0, %1, %2;" : "=r"(r) : "f"(hi), "f"(lo));
    return r;
}
__device__ __forceinline__ float bf_lo(uint32_t v) { return __uint_as_float(v << 16); }
__device__ __forceinline__ float bf_hi(uint32_t v) { return __uint_as_float(v & 0xffff0000u); }
__device__ __forceinline__ float rbf(float v) { return bf_lo(pack2(v, v)); }
__device__ __forceinline__ uint32_t badd(uint32_t a, uint32_t b) {
    uint32_t r;
    asm("add.rn.bf16x2 %0, %1, %2;" : "=r"(r) : "r"(a), "r"(b));
    return r;
}
__device__ __forceinline__ uint32_t bsub(uint32_t a, uint32_t b) {
    uint32_t r;
    asm("sub.rn.bf16x2 %0, %1, %2;" : "=r"(r) : "r"(a), "r"(b));
    return r;
}
__device__ __forceinline__ uint32_t bmul(uint32_t a, uint32_t b) {
    uint32_t r;
    asm("mul.rn.bf16x2 %0, %1, %2;" : "=r"(r) : "r"(a), "r"(b));
    return r;
}
__device__ __forceinline__ uint32_t ln_apply(uint32_t x, uint32_t mb, float rs, uint32_t scale, uint32_t shift) {
    const uint32_t d = bsub(x, mb);
    return badd(bmul(pack2(bf_lo(d) * rs, bf_hi(d) * rs), scale), shift);
}
__device__ __forceinline__ float ex2(float v) {
    float r;
    asm("ex2.approx.ftz.f32 %0, %1;" : "=f"(r) : "f"(v));
    return r;
}
__device__ __forceinline__ float rcp(float v) {
    float r;
    asm("rcp.approx.ftz.f32 %0, %1;" : "=f"(r) : "f"(v));
    return r;
}
__device__ __forceinline__ float sqrt_fast(float v) {
    float r;
    asm("sqrt.approx.ftz.f32 %0, %1;" : "=f"(r) : "f"(v));
    return r;
}
__device__ __forceinline__ float ln_rstd(float var) { return rcp(rbf(sqrt_fast(rbf(rbf(var) + 1e-5f)))); }
__device__ __forceinline__ float sigmoid(float v) { return rcp(1.f + ex2(-1.4426950408889634f * v)); }
__device__ __forceinline__ float quad_sum(float v) {
    v += __shfl_xor_sync(0xffffffffu, v, 1);
    return v + __shfl_xor_sync(0xffffffffu, v, 2);
}

constexpr uint32_t HI_128 = 0x40000040u, HI_IMG = 0x80000080u, HI_Q = 0x80000040u;
template <int M, int RH>
__device__ __forceinline__ uint4 img_pack(const float (&d)[64], float s) {
    uint4 v;
    v.x = pack2(d[16 * M + 2 * RH] * s, d[16 * M + 2 * RH + 1] * s);
    v.y = pack2(d[16 * M + 4 + 2 * RH] * s, d[16 * M + 5 + 2 * RH] * s);
    v.z = pack2(d[16 * M + 8 + 2 * RH] * s, d[16 * M + 9 + 2 * RH] * s);
    v.w = pack2(d[16 * M + 12 + 2 * RH] * s, d[16 * M + 13 + 2 * RH] * s);
    return v;
}
template <int M>
__device__ __forceinline__ void img_store_global(uint32_t img, uint32_t toff, const float (&d)[64], float s0, float s1) {
    uint4* p = reinterpret_cast<uint4*>(g_img + (img + toff)) + M * 32;
    p[0] = img_pack<M, 0>(d, s0);
    p[128] = img_pack<M, 1>(d, s1);
}
__device__ __forceinline__ void sts128(uint32_t a, uint4 v) {
    asm volatile("st.shared.v4.b32 [%0], {%1, %2, %3, %4};" ::"r"(a), "r"(v.x), "r"(v.y), "r"(v.z), "r"(v.w) : "memory");
}
constexpr float SM_C = 0.08838834764831845f * 1.4426950408889634f;
__device__ __forceinline__ float pack2f(float lo, float hi) {
    float r;
    asm("{\n.reg .b32 t;\ncvt.rn.bf16x2.f32 t, %1, %2;\nmov.b32 %0, t;\n}" : "=f"(r) : "f"(hi), "f"(lo));
    return r;
}
template <int M, bool SCALE, bool PARK>
__device__ __forceinline__ void pack_group(float (&d)[64], float (&v)[8], float s0, float s1) {
#pragma unroll
    for (int i = 0; i < 8; i++) {
        const int k = 16 * M + 4 * (i & 3) + 2 * (i >> 2);
        v[i] = SCALE ? pack2f(d[k] * (i < 4 ? s0 : s1), d[k + 1] * (i < 4 ? s0 : s1)) : pack2f(d[k], d[k + 1]);
        if (PARK && M > 0) d[16 * (M > 0 ? M - 1 : 0) + i] = v[i];
    }
}
__device__ __forceinline__ uint32_t q_off(uint32_t toff) {
    asm volatile("" : "+r"(toff));
    return (((toff >> 1) & ~2047u) ^ 8192) + (toff & 511);
}
template <int M>
__device__ __forceinline__ void ctx_store_part(float4* p, float (&d)[64], float i0, float i1) {
    float v[8];
    pack_group<M, true, true>(d, v, i0, i1);
    p[M * 32] = make_float4(v[0], v[1], v[2], v[3]);
    p[M * 32 + 128] = make_float4(v[4], v[5], v[6], v[7]);
}
__device__ __forceinline__ void ctx_store(uint32_t img, uint32_t toff, float (&o)[64], float i0, float i1) {
    asm volatile("" : "+r"(toff));
    float4* p = reinterpret_cast<float4*>(g_img + (img + toff));
    ctx_store_part<0>(p, o, i0, i1); ctx_store_part<1>(p, o, i0, i1); ctx_store_part<2>(p, o, i0, i1); ctx_store_part<3>(p, o, i0, i1);
}

__device__ __forceinline__ void slot_wait(uint32_t bars, uint32_t& ph, uint32_t slot) {
    mbar_wait(bars + 8 * slot, (ph >> slot) & 1);
    ph ^= 1u << slot;
}
__device__ __forceinline__ void release_if(uint32_t eb, uint32_t slot, bool on) {
    asm volatile("{\n.reg .pred p;\nsetp.ne.s32 p, %1, 0;\n@p mbarrier.arrive.shared::cluster.b64 _, [%0];\n}" ::"r"(eb + 8 * slot), "r"((int)on) : "memory");
}
__device__ __forceinline__ void slot_expect(uint32_t sb, uint32_t slot) {
    asm volatile("{\n.reg .pred p;\nelect.sync _|p, 0xffffffff;\n@p mbarrier.arrive.expect_tx.shared::cta.b64 _, [%0], 32768;\n}"
                 ::"r"(sb + BAR_FULL + 8 * slot) : "memory");
}
__device__ __forceinline__ void slot_acquire(uint32_t sb, uint32_t& ph, uint32_t slot) {
    slot_wait(sb + BAR_EMPTY, ph, slot);
    slot_expect(sb, slot);
}
__device__ __forceinline__ void load_bulk(uint32_t sb, uint32_t slot, uint32_t off, const void* src, uint32_t bytes, bool both, bool first) {
    if (both)
        asm volatile("{\n.reg .pred p;\nelect.sync _|p, 0xffffffff;\n"
                     "@p cp.async.bulk.shared::cluster.global.mbarrier::complete_tx::bytes.multicast::cluster.L2::cache_hint [%0], [%1], %5, [%2], %4, %3;\n}"
                     ::"r"(sb + slot * SLOT + off), "l"(src), "r"(sb + BAR_FULL + 8 * slot), "l"(first ? L2_FIRST : L2_NORMAL), "h"((uint16_t)3),
                     "r"(bytes) : "memory");
    else
        asm volatile("{\n.reg .pred p;\nelect.sync _|p, 0xffffffff;\n"
                     "@p cp.async.bulk.shared::cluster.global.mbarrier::complete_tx::bytes.L2::cache_hint [%0], [%1], %4, [%2], %3;\n}"
                     ::"r"(sb + slot * SLOT + off), "l"(src), "r"(sb + BAR_FULL + 8 * slot), "l"(first ? L2_FIRST : L2_NORMAL), "r"(bytes) : "memory");
}
__device__ __forceinline__ void load_tile(uint32_t sb, uint32_t slot, uint32_t off, const CUtensorMap* m, int row, int cb, bool both, bool first) {
    if (both)
        asm volatile("{\n.reg .pred p;\nelect.sync _|p, 0xffffffff;\n"
                     "@p cp.async.bulk.tensor.3d.shared::cluster.global.mbarrier::complete_tx::bytes.multicast::cluster.L2::cache_hint [%0], [%1, {%3, %4, %5}], [%2], %7, %6;\n}"
                     ::"r"(sb + slot * SLOT + off), "l"(m), "r"(sb + BAR_FULL + 8 * slot), "r"(0), "r"(row), "r"(cb),
                     "l"(first ? L2_FIRST : L2_NORMAL), "h"((uint16_t)3) : "memory");
    else
        asm volatile("{\n.reg .pred p;\nelect.sync _|p, 0xffffffff;\n"
                     "@p cp.async.bulk.tensor.3d.shared::cluster.global.mbarrier::complete_tx::bytes.L2::cache_hint [%0], [%1, {%3, %4, %5}], [%2], %6;\n}"
                     ::"r"(sb + slot * SLOT + off), "l"(m), "r"(sb + BAR_FULL + 8 * slot), "r"(0), "r"(row), "r"(cb),
                     "l"(first ? L2_FIRST : L2_NORMAL) : "memory");
}
__device__ __forceinline__ uint32_t ring_next(uint32_t r) { return r == 4 ? 0 : r + 1; }
__device__ __forceinline__ uint32_t w_table(int hp) { return hp ? 0x3104u : 0x4210u; }
__device__ __forceinline__ uint32_t a_table(int hp) { return hp ? 0x625u : 0x635u; }
__device__ __forceinline__ uint32_t a_next(uint32_t& t) {
    const uint32_t s = t & 15;
    t = (t >> 4) | (s << 8);
    return s;
}
constexpr uint32_t O_TABLE = 0x1604235u;
constexpr uint32_t SL_X = OFF == 0 ? 4 : OFF == 1 ? 3 : 1, SL_WD = OFF == 0 ? 6 : OFF == 1 ? 4 : 3, SL_WF = OFF == 0 ? 5 : OFF == 1 ? 6 : 4;
__device__ __forceinline__ uint32_t o_next(uint32_t& t) {
    const uint32_t s = t & 15;
    t = (t >> 4) | (s << 24);
    return s;
}
__device__ __forceinline__ int o_head(int i, int kh) { return i < 16 ? 4 * (i & 7) + 2 * (kh ^ 1) + (i >> 3) : 29 + 2 * kh; }

template <bool INIT>
__device__ __forceinline__ void gemm_issue(float (&d)[64], uint32_t a, uint32_t b, int acc, bool img) {
    uint64_t da = desc64(a, img ? HI_IMG : HI_128), db = desc64(b, HI_128);
    wg_fence();
#pragma unroll
    for (int k = 0; k < 8; k++) {
        if (INIT && k == 0) wgmma_ss128_init<1>(d, da, db);
        else wgmma_ss128<1>(d, da, db, k ? 1 : acc);
        desc_add(da, !(k & 1) ? 2 : img ? 30 : k == 3 ? 1018 : 2);
        desc_add(db, 128);
    }
    wg_commit();
}

__device__ __forceinline__ void step_retire(uint32_t eb, bool rel, uint32_t pend) {
    wg_wait<0>();
    release_if(eb, pend & 7, rel && (pend & 7) != 7);
    release_if(eb, pend >> 4, rel && pend < 0x70);
}
template <bool ODD>
__device__ __forceinline__ void proj_tile(float (&acc)[64], float (&prev)[64], int t, int q0, uint32_t sb, int wg, uint32_t eb, bool rel, uint32_t& fph,
                                          uint32_t wtab, uint32_t& atab, uint32_t& pend, uint32_t prev_img, uint32_t toff, float s0, float s1,
                                          uint32_t (&v)[32]) {
    const uint32_t a0 = desc_k(sb + (wg ^ (ODD && t == 5)) * 8192), b0 = desc_mn(sb);
    int q = q0;
#pragma unroll 1
    do {
        const uint32_t ws = (wtab >> (4 * q)) & 15, as = a_next(atab);
        if (!ODD && t != 2) slot_wait(sb + BAR_FULL, fph, ws);
        slot_wait(sb + BAR_FULL, fph, as);
        step_retire(eb, rel, pend);
        if (ODD && q == 2 && t == 5) {
            const uint32_t a = sb + 5 * SLOT + q_off(toff);
#pragma unroll
            for (int i = 0; i < 8; i++) sts128(a + (i >> 2) * 16384 + (i & 2) * 256 + (i & 1) * 1024, make_uint4(v[4 * i], v[4 * i + 1], v[4 * i + 2], v[4 * i + 3]));
        }
        bar_sync(1 + wg, 256);
        gemm_issue<false>(acc, a0 + as * (SLOT / 16), b0 + ws * (SLOT / 16), q, false);
        bar_arrive(2 - wg, 256);
        pend = (ODD && q == 1 && t == 5 ? 7 : as) | (ODD && t != 1 ? ws : 7) << 4;
        wg_wait<1>();
        reg_fence(prev);
        if (ODD && t == 5) {
            if (q == 0) {
#pragma unroll
                for (int i = 0; i < 32; i++) {
                    const int k = 16 * (i >> 3) + 4 * (i & 3) + ((i >> 1) & 2);
                    v[i] = pack2(prev[k], prev[k + 1]);
                }
            }
        } else {
            if (q == 0) img_store_global<0>(prev_img, toff, prev, s0, s1);
            if (q == 1) img_store_global<1>(prev_img, toff, prev, s0, s1);
            if (q == 2) img_store_global<2>(prev_img, toff, prev, s0, s1);
            if (q == 3) img_store_global<3>(prev_img, toff, prev, s0, s1);
        }
    } while (++q < (ODD && t == 5 ? 3 : 4));
}

__device__ __forceinline__ void qk_issue(float (&s)[64], uint32_t q, uint32_t k) {
    wg_fence();
    uint64_t da = desc64(q, HI_Q), db = desc64(k, HI_IMG);
    wgmma_ss128_init<0>(s, da, db);
#pragma unroll
    for (int i = 1; i < 8; i++) {
        desc_add(da, (i & 1) ? 2 : i == 4 ? 990 : 30);
        desc_add(db, (i & 1) ? 2 : 30);
        wgmma_ss128<0>(s, da, db, 1);
    }
    wg_commit();
}
__device__ __forceinline__ void qk_issue(float (&s)[32], uint32_t q, uint32_t k) {
    wg_fence();
    uint64_t da = desc64(q, HI_Q), db = desc64(k, HI_IMG);
    wgmma_ss64_init<0>(s, da, db);
#pragma unroll
    for (int i = 1; i < 8; i++) {
        desc_add(da, (i & 1) ? 2 : i == 4 ? 990 : 30);
        desc_add(db, (i & 1) ? 2 : 30);
        wgmma_ss64<0>(s, da, db, 1);
    }
    wg_commit();
}
__device__ __forceinline__ void pv_issue(float (&o)[64], const uint32_t (&p)[32], uint32_t v, int acc, bool half) {
    uint64_t db = desc64(v, HI_IMG);
    if (half) {
        asm volatile("// half" ::: "memory");
        wg_fence();
#pragma unroll
        for (int i = 0; i < 4; i++) {
            wgmma_rs128(o, p[4 * i], p[4 * i + 1], p[4 * i + 2], p[4 * i + 3], db, i ? 1 : acc);
            desc_add(db, 256);
        }
        wg_commit();
        asm volatile("// half" ::: "memory");
    } else {
        wg_fence();
#pragma unroll
        for (int i = 0; i < 8; i++) {
            wgmma_rs128(o, p[4 * i], p[4 * i + 1], p[4 * i + 2], p[4 * i + 3], db, i ? 1 : acc);
            desc_add(db, 256);
        }
        wg_commit();
    }
}
__device__ __forceinline__ void tri_mask(float (&s)[64], float x) {
#pragma unroll
    for (int k = 0; k < 16; k++) {
        float b;
        asm("sub.sat.f32 %0, %1, %2;" : "=f"(b) : "f"((float)(8 * (k >> 1) + (k & 1))), "f"(x));
        const int i = 32 + 4 * (k >> 1) + (k & 1);
        asm("fma.rn.f32 %0, %1, 0fFF61B1E6, %0;" : "+f"(s[i]) : "f"(b));
        if (k < 14) asm("fma.rn.f32 %0, %1, 0fFF61B1E6, %0;" : "+f"(s[i + 6]) : "f"(b));
    }
}
__device__ __forceinline__ void tri_mask_copy(float (&s)[64], const float (&h)[32], float x) {
#pragma unroll
    for (int i = 0; i < 32; i++) {
            asm("{\n.reg .pred p;\nsetp.lt.f32 p, %2, %3;\nselp.f32 %0, 0fFF800000, %1, p;\n}"
                : "=f"(s[i]) : "f"(h[i]), "f"(x), "f"((float)(8 * (i >> 2) - 4 * (i & 2) + (i & 1))));
        s[32 + i] = __uint_as_float(0xff800000u);
    }
}
constexpr float SM_HI = 1152921504606846976.f, SM_LO = 1.f / 1152921504606846976.f;
__device__ __forceinline__ bool softmax_unsafe(float t0, float t1, bool first) {
    bool bad = __any_sync(0xffffffffu, fmaxf(t0, t1) > SM_HI);
    if (first) {
        uint32_t a = __ballot_sync(0xffffffffu, t0 >= SM_LO), b = __ballot_sync(0xffffffffu, t1 >= SM_LO);
        a |= a >> 1;
        b |= b >> 1;
        bad |= ((a | (a >> 2)) & (b | (b >> 2)) & 0x11111111u) != 0x11111111u;
    }
    return bad;
}
__device__ __forceinline__ void softmax_remax(const float (&s)[64], float (&m)[2], bool first, float& m0, float& m1, float& a0, float& a1) {
    m0 = fmaxf(s[0], s[1]), m1 = fmaxf(s[2], s[3]);
#pragma unroll
    for (int k = 1; k < 16; k++) {
        m0 = fmaxf(m0, fmaxf(s[4 * k], s[4 * k + 1]));
        m1 = fmaxf(m1, fmaxf(s[4 * k + 2], s[4 * k + 3]));
    }
    m0 = fmaxf(m0, __shfl_xor_sync(0xffffffffu, m0, 1));
    m1 = fmaxf(m1, __shfl_xor_sync(0xffffffffu, m1, 1));
    m0 = fmaxf(m0, __shfl_xor_sync(0xffffffffu, m0, 2));
    m1 = fmaxf(m1, __shfl_xor_sync(0xffffffffu, m1, 2));
    if (!first) {
        m0 = fmaxf(m0, 0.f);
        m1 = fmaxf(m1, 0.f);
    }
    a0 = first ? 1.f : ex2(-m0);
    a1 = first ? 1.f : ex2(-m1);
    m[0] += m0;
    m[1] += m1;
}
template <int J0, int J1>
__device__ __forceinline__ void softmax_exp(const float (&s)[64], uint32_t (&p)[32], float (&t)[4]) {
#pragma unroll
    for (int k = J0; k < J1; k++) {
        const float e0 = ex2(s[4 * k]), e1 = ex2(s[4 * k + 1]), e2 = ex2(s[4 * k + 2]), e3 = ex2(s[4 * k + 3]);
        if (k == 0) { t[0] = e0; t[1] = e1; t[2] = e2; t[3] = e3; }
        else { t[0] += e0; t[1] += e1; t[2] += e2; t[3] += e3; }
        p[2 * k] = pack2(e0, e1);
        p[2 * k + 1] = pack2(e2, e3);
    }
}
__device__ __forceinline__ void mma16816(float (&d)[4], const uint32_t* a, uint32_t b0, uint32_t b1) {
    asm("mma.sync.aligned.m16n8k16.row.col.f32.bf16.bf16.f32 {%0, %1, %2, %3}, {%4, %5, %6, %7}, {%8, %9}, {%0, %1, %2, %3};"
        : "+f"(d[0]), "+f"(d[1]), "+f"(d[2]), "+f"(d[3]) : "r"(a[0]), "r"(a[1]), "r"(a[2]), "r"(a[3]), "r"(b0), "r"(b1));
}
__device__ __forceinline__ uint32_t best_key(const uint32_t* keys, int lane, uint32_t ep) {
#pragma unroll 1
    for (;;) {
        const uint4 k = ld_poll(reinterpret_cast<const uint4*>(keys) + lane);
        const int n = __popc(__ballot_sync(0xffffffffu, (((k.x ^ ep) | (k.y ^ ep) | (k.z ^ ep) | (k.w ^ ep)) & 31) == 0));
        if (n == 32) return __reduce_max_sync(0xffffffffu, max(max(k.x, k.y), max(k.z, k.w)));
        __nanosleep(n < KN ? KSLEEP : KSLEEP2);
    }
}

__global__ void __cluster_dims__(2, 1, 1) __launch_bounds__(384, 1)
fused_kernel(const __grid_constant__ CUtensorMap tm_ckv, const __grid_constant__ CUtensorMap tm_wq,
             const __grid_constant__ CUtensorMap tm_wuk, const __grid_constant__ CUtensorMap tm_wuv,
             const __grid_constant__ CUtensorMap tm_wo, const __grid_constant__ CUtensorMap tm_wg,
             const __grid_constant__ CUtensorMap tm_wu,
             const __grid_constant__ CUtensorMap tm_wm, const __grid_constant__ CUtensorMap tm_x, const Params P) {
    extern __shared__ __align__(1024) uint8_t smem[];
    if (threadIdx.x == 352) {
        asm volatile("prefetch.tensormap [%0];" ::"l"(&tm_ckv) : "memory");
        asm volatile("prefetch.tensormap [%0];" ::"l"(blockIdx.x >= NCTA ? &tm_wm : (blockIdx.x & 1) ? &tm_wuv : &tm_wuk) : "memory");
    }
    const uint32_t sb = (uint32_t)__cvta_generic_to_shared(smem);
    const int tid = threadIdx.x, lane = tid & 31, warp = __shfl_sync(0xffffffffu, tid >> 5, 0), wg = warp >> 2;
    const uint32_t sm = blockIdx.x < 8 ? blockIdx.x + 124 : blockIdx.x - 8, smq = ((sm - 64) * 147) >> 11;
    const int rb = sm < 64 ? (sm & 14) * 8 + (sm >> 4) * 2 + (sm & 1)
                 : sm < 120 ? ((sm - 64 - smq * 14) & 14) * 8 + 24 + smq * 2 + (sm & 1) : sm < 124 ? sm + 8 : sm - 116;
    const int grp = rb >> 3, j = rb & 7, kh = (grp >> 1) & 1;
    const int cq = (j & 1) + ((grp >> 1) & 2), ort = (grp & 8) + (grp & 1) * 4 + (j >> 1);
    if (warp == 0) TS(0);

    const CUtensorMap* tw = (j & 1) ? &tm_wuv : &tm_wuk;
    if (lane == 0) {
        if (warp == 8) {
#pragma unroll
            for (int i = 0; i < 7; i++) mbar_init(sb + BAR_FULL + 8 * i, 1);
            fence_async_smem();
        } else if (warp < 11) {
            const int w = warp - (warp > 8);
            const u64 cnt = (w < 5 ? (rb < NCTA ? 0x888888884444444ull : 0x888888888888888ull) : 0x111812111111118ull) >> (12 * (w % 5));
#pragma unroll
            for (int i = 0; i < 3; i++) mbar_init(sb + BAR_EMPTY + 24 * w + 8 * i, ((uint32_t)cnt >> (4 * i)) & 15);
        }
        asm volatile("fence.mbarrier_init.release.cluster;" ::: "memory");
    }
    __syncwarp();
    asm volatile("barrier.cluster.arrive.relaxed.aligned;" ::: "memory");
    if (warp == 8) {
        if (rb < NCTA) {
#pragma unroll 1
            for (int u = 0; u < 4; u++) {
                const uint32_t ws = u + (u == 3), as = (0x635u >> (4 * u)) & 15;
                slot_expect(sb, ws);
                load_tile(sb, ws, 0, tw, u * 128, 4 * grp, false, HINT & 1);
                if (u == 3) break;
                slot_expect(sb, as);
                load_tile(sb, as, 0, &tm_ckv, (j >> 1) * 128, u * 2, false, false);
                load_tile(sb, as, 16384, &tm_ckv, (j >> 1) * 128, u * 2 + 1, false, false);
            }
        } else {
#pragma unroll 1
            for (int i = 0; i < 6; i++) {
                slot_expect(sb, i);
                load_tile(sb, i, 0, &tm_wm, i * 64, (rb - NCTA) * 4, false, HINT & 64);
                if (i > 3) tma3d_prefetch(&tm_wm, i * 64 + 128, (rb - NCTA) * 4);
            }
        }
    }
    asm volatile("barrier.cluster.wait.aligned;" ::: "memory");

    if (rb >= NCTA) {
        const int sp = rb - NCTA;
        const uint32_t ep = __ldcg(&g_sync.epoch[0]) + 1;
        uint32_t ph = 0, sl = 0;
        if (warp == 8) {
#pragma unroll 1
            for (int i = 6; i < 54 + 2 * OFF; i++) {
                slot_acquire(sb, ph, sl);
                const int k = i - 24;
                load_tile(sb, sl, 0, i < 24 ? &tm_wm : i >= 54 ? &tm_wo : (k & 2) ? &tm_wu : &tm_wg, i < 24 ? (i & 7) * 64 : i >= 54 ? (i - 38 - 2 * OFF) * 256 : (k & 1) * 256,
                          i < 24 ? (i >> 3) * 16 + sp * 4 : i >= 54 ? sp * 2 : sp * 7 + (k >> 2), false, true);
                if (++sl == 6) sl = 0;
                if (i == 51) { i = 53; sl = 0; }
            }
            bar_sync(4, 64);
            slot_wait(sb + BAR_EMPTY, ph, 4);
            slot_wait(sb + BAR_EMPTY, ph, 5);
            ph = 0x3f, sl = 0;
#pragma unroll 1
            for (int h = 0; h < 32; h++) {
                step_watch(sb + SM_EP + 16, h + 1);
                fence_async_global();
                const uint8_t* src = g_ctx + (size_t)(((h >> 1) ^ 8) * 32 + 30 - 4 * OFF) * SLOT + (h & 1) * 16384;
#pragma unroll 1
                for (int k = 0; k <= 2 * OFF; k++, src += 2 * SLOT) {
                    slot_wait(sb + BAR_DONE, ph, sl);
                    const uint32_t f = sb + BAR_FLAG + 8 * sl, d = sb + 4 * SLOT + sl * 16384;
                    asm volatile("{\n.reg .pred p;\nelect.sync _|p, 0xffffffff;\n@p mbarrier.arrive.expect_tx.shared::cta.b64 _, [%0], 16384;\n}" ::"r"(f) : "memory");
                    if (k == 0)
                        asm volatile("{\n.reg .pred p;\nelect.sync _|p, 0xffffffff;\n"
                                     "@p cp.async.bulk.tensor.3d.shared::cluster.global.mbarrier::complete_tx::bytes [%0], [%1, {%3, %4, %5}], [%2];\n}"
                                     ::"r"(d), "l"(&tm_x), "r"(f), "r"(0), "r"((h ^ 16) * 64), "r"(sp * 2) : "memory");
                    else
                        asm volatile("{\n.reg .pred p;\nelect.sync _|p, 0xffffffff;\n"
                                     "@p cp.async.bulk.shared::cluster.global.mbarrier::complete_tx::bytes [%0], [%1], 16384, [%2];\n}"
                                     ::"r"(d), "l"(src), "r"(f) : "memory");
                    if (++sl == 6) sl = 0;
                }
            }
        } else if (warp == 9) {
#pragma unroll 1
            for (int t = 0; t <= 16; t++) {
                asm volatile("st.release.cta.shared.u32 [%0], %1;" ::"r"(sb + SM_EP + 16), "r"(2 * t) : "memory");
                if (t == 0) bar_sync(4, 64);
                if (lane < 4 && t < 16) flag_wait(&g_sync.ctxcnt[(t ^ 8) * 32 + 24 + 2 * lane], ep);
                __syncwarp();
            }
        } else if (warp < 8) {
            const uint32_t c2 = __ldg(reinterpret_cast<const uint32_t*>(P.c) + tid);
            uint32_t* sc = reinterpret_cast<uint32_t*>(smem + SM_TAB);
            sc[tid] = pack2(bf_lo(c2) * sigmoid(bf_lo(c2)), bf_hi(c2) * sigmoid(bf_hi(c2)));
            bar_sync(1, 256);
            const uint32_t a = sb + (warp >> 1) * 8192 + ((lane >> 4) * 8 + (lane & 7)) * 128, ch = (warp & 1) * 4 + ((lane >> 3) & 1);
#pragma unroll 1
            for (int ps = 0; ps < 3; ps++) {
                float d[2][4] = {};
#pragma unroll 1
                for (int bt = 0; bt < 8; bt++) {
                    slot_wait(sb + BAR_FULL, ph, sl);
#pragma unroll
                    for (int i = 0; i < 8; i++) {
                        uint32_t w[4];
                        asm volatile("ldmatrix.sync.aligned.m8n8.x4.trans.shared.b16 {%0, %1, %2, %3}, [%4];" : "=r"(w[0]), "=r"(w[1]), "=r"(w[2]), "=r"(w[3])
                                     : "r"(a + sl * SLOT + (i >> 1) * 2048 + (((ch + 2 * (i & 1)) ^ (lane & 7)) << 4)) : "memory");
                        mma16816(d[i & 1], w, sc[bt * 32 + (i >> 1) * 8 + (lane & 3)], sc[bt * 32 + (i >> 1) * 8 + 4 + (lane & 3)]);
                    }
                    __syncwarp();
                    mbar_arrive_if(sb + BAR_EMPTY + 8 * sl, lane == 0);
                    if (++sl == 6) sl = 0;
                }
                const float v = (lane & 2) ? ((lane & 1) ? d[1][2] : d[1][0]) : ((lane & 1) ? d[0][2] : d[0][0]);
                const int col = sp * 256 + warp * 32 + (lane & 3) * 8 + (lane >> 2);
                if (ps == 0) st_pub(g_mod1 + col, (pack2(0.f, v) & 0xffff0000u) | (ep & 0xffffu), true);
                else g_mod[ps * 1024 + col] = __float2bfloat16_rn(v);
                if (warp == 0) TS(1 + ps);
            }
#pragma unroll 1
            for (int k = 0; k < 28; k++) {
                slot_wait(sb + BAR_FULL, ph, sl);
                uint4* dst = reinterpret_cast<uint4*>(g_wf) + (sp * 28 + (k & ~3)) * 2048 + (k & 3) * 512 + tid;
#pragma unroll 4
                for (int i = 0; i < 8; i++) {
                    const int row = (i & 1) * 128 + (tid >> 1);
                    __stcs(dst + (i >> 1) * 2048 + (i & 1) * 256, lds128(sb + sl * SLOT + row * 128 + ((((i & 6) + ((tid ^ (row >> 2)) & 1)) ^ (row & 7)) << 4)));
                }
                __syncwarp();
                mbar_arrive_if(sb + BAR_EMPTY + 8 * sl, lane == 0);
                if (++sl == 6) sl = 0;
            }
            bar_sync(1, 256);
            if (tid < 2) {
                flag_add(&g_sync.cnt[7 * 8]);
                flag_wait(&g_sync.cnt[7 * 8], 8 * ep);
            }
            if (warp == 0) TS(4);
            bar_sync(1, 256);
            uint32_t ga[16], x2[32];
#pragma unroll
            for (int i = 0; i < 16; i++) ga[i] = __ldcg(reinterpret_cast<const uint32_t*>(g_mod) + 512 + sp * 64 + (lane & 3) + 4 * i);
#pragma unroll 1
            for (int i = 0; i < 2 * OFF; i++) slot_wait(sb + BAR_FULL, ph, i);
            float d[64];
            uint32_t u = (2 * OFF + 1) * wg, up = 0;
            if (wg == 1) bar_arrive(2, 256);
#pragma unroll 1
            for (int h = wg; h < 32; h += 2) {
                mbar_wait(sb + BAR_FLAG + 8 * u, up);
                const uint32_t xa = sb + 4 * SLOT + u * 16384 + ((warp & 3) * 16 + (lane & 15)) * 128;
#pragma unroll
                for (int k = 0; k < 8; k++)
                    asm volatile("ldmatrix.sync.aligned.m8n8.x4.shared.b16 {%0, %1, %2, %3}, [%4];"
                                 : "=r"(x2[4 * k]), "=r"(x2[4 * k + 1]), "=r"(x2[4 * k + 2]), "=r"(x2[4 * k + 3])
                                 : "r"(xa + (k >> 2) * 8192 + (((2 * (k & 3) + (lane >> 4)) ^ (lane & 7)) << 4)) : "memory");
                mbar_arrive_if(sb + BAR_DONE + 8 * u, lane < 2);
                bar_sync(2 + wg, 256);
#pragma unroll 1
                for (int k = 0; k < 2 * OFF; k++) {
                    const uint32_t pu = u;
                    if (++u == 6) { u = 0; up ^= 1; }
                    mbar_wait(sb + BAR_FLAG + 8 * u, up);
                    gemm_issue<false>(d, desc_k(sb + 4 * SLOT) + u * 1024, desc_mn(sb) + k * (SLOT / 16), k, true);
                    wg_wait<1>();
                    mbar_arrive_if(sb + BAR_DONE + 8 * pu, lane < 2 && k);
                }
                if (h < 31) bar_arrive(3 - wg, 256);
                wg_wait<0>();
                reg_fence(d);
                mbar_arrive_if(sb + BAR_DONE + 8 * u, lane < 2);
                u += 2 * OFF + 2;
                if (u >= 6) { u -= 6; up ^= 1; }
                uint4* op = g_x2 + ((h ^ 16) * 4 + sp) * 1024 + (tid & 127);
#pragma unroll
                for (int v = 0; v < 8; v++) {
                    uint32_t y[4];
#pragma unroll
                    for (int i = 0; i < 4; i++) {
                        const int k = 4 * v + i;
                        y[i] = pack2(fmaf(bf_lo(ga[k >> 1]), d[2 * k], bf_lo(x2[k])), fmaf(bf_hi(ga[k >> 1]), d[2 * k + 1], bf_hi(x2[k])));
                    }
                    op[v * 128] = make_uint4(y[0], y[1], y[2], y[3]);
                }
            }
            bar_sync(1, 256);
            if (tid == 0) flag_add(&g_sync.cnt[15 * 8]);
            if (warp == 0) TS(5);
        }
        return;
    }

    if (wg == 2) {
        asm volatile("setmaxnreg.dec.sync.aligned.u32 40;");
        if (warp == 8) {
            const uint32_t rank = j & 1, half = rank * 16384;
            uint32_t eph = 0, r = 0;
            *reinterpret_cast<volatile uint32_t*>(smem + SM_EP + 20) = 0;
#pragma unroll 1
            for (int hp = 0; hp < 2; hp++) {
                uint32_t wtab = w_table(hp), atab = a_table(hp);
                const int hc = 4 * grp + 2 * hp;
#pragma unroll 1
                for (int u = 3 - 3 * hp; u < 16; u++) {
                    if (hp && u < 4) {
                        const uint32_t ws = (wtab >> (4 * u)) & 15;
                        slot_acquire(sb, eph, ws);
                        load_tile(sb, ws, 0, tw, u * 128, hc, false, HINT & 1);
                        PT();
                    }
                    if (hp == 1 && (u & 7) == 4) mbar_wait(sb + BAR_FLAG + 24 + (u & 8), 0);
                    const uint32_t as = a_next(atab);
                    slot_acquire(sb, eph, as);
                    load_tile(sb, as, half, &tm_ckv, ((u & 12) + (j >> 1)) * 128, (u & 3) * 2 + rank, true, (HINT & 8) && hp);
                    PT();
                    if (hp == 1 && (u | 2) == 3 && lane == 0)
                        asm volatile("red.relaxed.gpu.global.add.u32 [%0], 1;" ::"l"(&g_sync.cnt[(grp * 8 + 3 + (u >> 1)) * 8]) : "memory");
                }
                const uint8_t* src = g_h + (15 - j) * 4 * SLOT;
#pragma unroll 1
                for (int u = 0; u < 8; u++) {
                    if (u == 0 || u == KVG) {
                        mbar_wait(sb + BAR_FLAG + (u ? 8 + 32 * hp : 0), 0);
                        fence_async_global();
                    }
                    if (u < 4) {
                        const uint32_t ws = (wtab >> (4 * u)) & 15;
                        slot_acquire(sb, eph, ws);
                        load_tile(sb, ws, 0, &tm_wq, u * 128, hc, false, HINT & 1);
                        PT();
                    }
                    const uint32_t as = a_next(atab);
                    slot_acquire(sb, eph, as);
                    load_bulk(sb, as, 0, src, SLOT, false, (HINT & 8) && hp);
                    PT();
                    src += u == 3 ? (8 * j - 63) * SLOT : SLOT;
                }
                const int step = hp ? -2 * SLOT : 2 * SLOT;
                src = g_KV + (size_t)(grp * 32 + 30 * hp) * SLOT + half - step;
#pragma unroll 1
                for (int n = 0; n <= 17; n++) {
                    if (n == 8) {
                        mbar_wait(sb + BAR_FLAG + 16 + 32 * hp, 0);
                        fence_async_global();
                    }
                    const uint8_t* v = src + SLOT;
                    src += n < 16 - j ? step : n == 16 - j ? (2 * j - 15) * step : -step;
                    if (n < 17) {
                        slot_acquire(sb, eph, r);
                        if (n != 15 - (j & 6)) load_bulk(sb, r, half, src, SLOT / 2, true, HINT & 4);
                        else load_bulk(sb, r, 0, src - half, SLOT, false, HINT & 4);
                        PT();
                        r = ring_next(r);
                    }
                    if (n) {
                        slot_acquire(sb, eph, r);
                        if (n != 16 - (j & 6)) load_bulk(sb, r, half, v, SLOT / 2, true, HINT & 4);
                        else load_bulk(sb, r, 0, v - half, SLOT, false, HINT & 4);
                        PT();
                        r = ring_next(r);
                    }
                    asm volatile("st.volatile.shared.u32 [%0], %1;" ::"r"(sb + SM_EP + 16), "r"(18 * hp + n + 1) : "memory");
                }
            }
            uint32_t otab = O_TABLE, ready = 0;
#pragma unroll 1
            for (int i = 0; i < 17; i += i == 7 - OFF ? 1 + OFF : 1) {
                const bool dyn = i >= 8 && i < 15;
                const uint32_t want = dyn ? 15u << (4 * (i - 8)) : 1u << max(i + 14, 28);
                if (!(ready & want)) {
                    do {
                        asm volatile("ld.acquire.cta.shared.u32 %0, [%1];" : "=r"(ready) : "r"(sb + SM_EP + 20) : "memory");
                        ready = __shfl_sync(0xffffffffu, ready, 0);
                    } while (!(ready & want));
                    fence_async_global();
                }
                const int head = o_head(dyn ? (ready >> (4 * (i - 8))) & 15 : i, kh);
                const uint32_t as = o_next(otab), ws = o_next(otab), off = i < 15 ? half : kh * 16384;
                slot_acquire(sb, eph, as);
                load_bulk(sb, as, off, g_ctx + (size_t)(ort * 32 + head) * SLOT + off, SLOT / 2, i < 15, HINT & 16);
                if (i >= 15) load_bulk(sb, as, off ^ 16384, i == 15 ? g_x2 + ((ort * 2 + kh) * 4 + cq) * 1024 : reinterpret_cast<const uint4*>(P.wdown) + min(rb, NFFN - 1) * 1024, SLOT / 2, false, false);
                PT();
                slot_acquire(sb, eph, ws);
                load_tile(sb, ws, 0, &tm_wo, head * 128, cq * 2, false, HINT & 2);
                PT();
                if (i == 0) o_next(otab);
            }
            if (rb < NFFN) {
                slot_acquire(sb, eph, SL_WF);
                load_bulk(sb, SL_WF, 0, g_wf + rb * SLOT, SLOT, false, false);
            }
        } else if (warp == 9) {
            *reinterpret_cast<volatile uint32_t*>(smem + SM_EP + 16) = 0;
            l2_prefetch(P.ckv + rb * 2048, 4096);
            mbar_watch(sb + BAR_FULL, 0);
            l2_prefetch(P.ckv + 512 * 512 + rb * 2048, 4096);
            mbar_watch(sb + BAR_FULL + 8 * XPF, 0);
            l2_prefetch(P.x + rb * 8192, 16384);
            mbar_watch(sb + BAR_FULL + 8 * 4, 0);
            l2_prefetch(P.ckv + 1024 * 512 + rb * 4096, 8192);
            TS(40);
#pragma unroll 1
            for (int i = 0; i < 13; i++) {
                step_watch(sb + SM_EP + 16, i == 0 ? 0 : i < 5 ? PFA + i : 13 + PFB + i);
                if (i == 10) mbar_watch(sb + BAR_FLAG + 8 * 7, 0);
                const int rf = min(rb, NFFN - 1), pc = 4 * (i - 5) + cq;
                const uint8_t* p = i == 3 ? reinterpret_cast<const uint8_t*>(P.ckv) + rb * 16384
                                 : i == 4 ? g_h + rb * 16384
                                 : i < 8 ? g_ctx + (size_t)(ort * 32 + o_head(pc >> 1, kh)) * SLOT + (pc & 1) * 16384
                                 : i < 10 ? reinterpret_cast<const uint8_t*>(P.wo) + (grp * 16 + (i & 1) * 8 + j) * 16384
                                 : i == 10 ? reinterpret_cast<const uint8_t*>(P.wdown) + rf * 16384 : g_wf + rf * SLOT + (i & 1) * 16384;
                if (i >= 3) l2_prefetch(p, 16384);
                else if ((i | j) & 1) tma3d_prefetch(i == 1 ? tw : &tm_wq, (j >> 1) * 128, grp * 4 + (i ? 2 : 0));
            }
            const uint32_t v = lds32(sb + SM_EP) - 1;
            sts128(sb + SM_RED + lane * 16, make_uint4(v, v, v, v));
            fence_async_smem();
            __syncwarp();
#pragma unroll 1
            for (int i = 0; i < OB / 32; i++) bulk_store(g_out + rb * OB + i * 32, sb + SM_RED, 512, false);
            asm volatile("cp.async.bulk.commit_group;\ncp.async.bulk.wait_group 0;" ::: "memory");
            fence_async_global();
            __syncwarp();
            mbar_arrive_if(sb + BAR_PF, lane == 0);
            if (lane == 0) mbar_watch(sb + BAR_END, 0);
        } else {
            const uint32_t ep = __ldcg(&g_sync.epoch[0]) + 1;
            asm volatile("st.shared.u32 [%0], %1;" ::"r"(sb + SM_EP), "r"(ep) : "memory");
            mbar_wait(sb + BAR_FULL + 8 * 4, 0);
            {
                uint4 v[4];
                for (;;) {
                    uint32_t bad = 0;
#pragma unroll
                    for (int k = 0; k < 4; k++) v[k] = ld_poll(reinterpret_cast<const uint4*>(g_mod1) + (warp & 1) * 128 + k * 32 + lane);
#pragma unroll
                    for (int k = 0; k < 4; k++) bad |= (v[k].x ^ ep) | (v[k].y ^ ep) | (v[k].z ^ ep) | (v[k].w ^ ep);
                    if (__all_sync(0xffffffffu, (bad & 0xffff) == 0)) break;
                    __nanosleep(100);
                }
                const uint32_t one = (warp & 1) ? ONE2 : 0x80008000u;
#pragma unroll
                for (int k = 0; k < 4; k++)
                    *reinterpret_cast<uint2*>(smem + SM_TAB + (warp & 1) * 1024 + k * 256 + lane * 8) =
                        make_uint2(badd(__byte_perm(v[k].x, v[k].y, 0x7632), one), badd(__byte_perm(v[k].z, v[k].w, 0x7632), one));
            }
            __syncwarp();
            mbar_arrive_if(sb + BAR_FLAG + 8 * 8, lane == 0);
            if (warp == 10) {
#pragma unroll 1
                for (int i = 0; i < 9; i++) {
                    mbar_sleep(sb + BAR_DONE + 8 * i);
                    if (lane == 0) flag_add(i && ((i - 1) & 2) ? &g_sync.ctxcnt[((i & 1) ? 15 - j : j) * 32 + 2 * grp + (i > 4)] : &g_sync.cnt[(grp * 8 + i) * 8]);
                    if (i == 0) TS(43);
                }
            } else {
                TS(42);
#pragma unroll 1
                for (int i = 0; i < 8; i++) {
                    mbar_sleep(sb + BAR_DONE + 8 * (i == 7 ? 6 : i == 4 ? 3 : i));
                    if (lane < 2) flag_wait(&g_sync.cnt[((i == 0 ? (lane ? j : 15 - j) : i == 7 ? 0 : grp) * 8 + i) * 8], 8 * ep);
                    __syncwarp();
                    mbar_arrive_if(sb + BAR_FLAG + 8 * i, lane == 0 && i < 7);
                    TS(48 + i);
                }
                const uint32_t *mp = reinterpret_cast<const uint32_t*>(g_mod) + lane, *wp = reinterpret_cast<const uint32_t*>(P.wr) + lane;
                float ra = 0.f, rs = 0.f;
#pragma unroll 1
                for (int k = 0; k < 256; k += 32) {
                    const uint32_t ga = __ldcg(mp + 512 + k), sh = __ldcg(mp + 768 + k), c1 = badd(__ldcg(mp + 1024 + k), ONE2);
                    const uint32_t gb = __ldcg(mp + 1280 + k), ww = __ldg(wp + k);
                    const uint32_t a = bmul(c1, ww);
                    ra += bf_lo(a) + bf_hi(a);
                    rs = fmaf(bf_lo(sh), bf_lo(ww), fmaf(bf_hi(sh), bf_hi(ww), rs));
                    if (k >> 6 == cq) {
                        sts128(sb + SM_TAB + ((k & 32) + lane) * 16, make_uint4(ga << 16, ga & 0xffff0000u, a, 0));
                        sts128(sb + SM_TAB + 1024 + ((k & 32) + lane) * 16, make_uint4(c1, sh, gb, 0));
                    }
                }
#pragma unroll 1
                for (int o = 16; o > 0; o >>= 1) {
                    ra += __shfl_xor_sync(0xffffffffu, ra, o);
                    rs += __shfl_xor_sync(0xffffffffu, rs, o);
                }
                *reinterpret_cast<float2*>(smem + SM_EP + 8) = make_float2(ra, rs);
                __syncwarp();
                mbar_arrive_if(sb + BAR_FLAG + 8 * 7, lane == 0);
                const uint32_t* f = lane < 17 ? &g_sync.ctxcnt[ort * 32 + o_head(lane, kh)] : &g_sync.cnt[15 * 8];
                uint32_t ready = -(j & 1), list = 0, sh = 0, qa;
                asm("mapa.shared::cluster.u32 %0, %1, %2;" : "=r"(qa) : "r"(sb + SM_EP + 20), "r"(lane & 1));
                while (ready != ~0u) {
                    uint32_t v;
                    asm volatile("ld.acquire.gpu.global.u32 %0, [%1];" : "=r"(v) : "l"(f) : "memory");
                    const uint32_t now = __ballot_sync(0xffffffffu, (int)(v - (lane < 17 ? ep : NSPARE * ep)) >= 0);
#pragma unroll 1
                    for (uint32_t fresh = now & ~ready & 0x7f00; fresh; fresh &= fresh - 1, sh += 4) list |= (__ffs(fresh) - 1) << sh;
                    list |= (((now & 0xff) + 1) >> 8 << 28) | ((now & (now >> 2) & 0x18000) << 14);
                    if (now != ready && lane < 2) asm volatile("st.relaxed.cluster.shared::cluster.u32 [%0], %1;" ::"r"(qa), "r"(list) : "memory");
                    if ((now & 0xff) == 0xff) mbar_sleep(sb + BAR_DONE + 8 * 7);
                    ready = now;
                    __nanosleep(POLL_NS);
                }
                TS(45);
            }
        }
    } else {
        const bool elected = (tid & 127) == 0, rel = (tid & 95) == 0;
        uint32_t eb;
        asm("mapa.shared::cluster.u32 %0, %1, %2;" : "=r"(eb) : "r"(sb + BAR_EMPTY), "r"(warp & 1));
        const int g = lane >> 2, c4 = lane & 3;
        uint32_t toff = warp * 4096 + g * 64 + ((c4 ^ (g >> 1)) << 4);
        uint32_t fph = 0x3f, r = 0;
        if (wg == 1) bar_arrive(1, 256);
        const uint32_t kd = desc_k(sb), wd = desc_mn(sb), vd = ((sb & 0x3ffff) >> 4) | (32u << 16);
        const int nL = 16 - j, hn = nL - 1 + wg;
        float s[64], o[64], li[2] = {0.f, 0.f};
        uint32_t cimg = 0;
        const float sc = (j & 1) ? 1.f : SM_C;
#pragma unroll 1
        for (int q = 0; q < 3; q++) {
            const uint32_t as = (0x635u >> (4 * q)) & 15;
            mbar_wait(sb + BAR_FULL + 8 * q, 0);
            mbar_wait(sb + BAR_FULL + 8 * as, 0);
            bar_sync(1 + wg, 256);
            gemm_issue<false>(s, kd + wg * 512 + as * (SLOT / 16), wd + q * (SLOT / 16), q, false);
            bar_arrive(2 - wg, 256);
            wg_wait<0>();
            release_if(eb, as, rel);
        }
        {
            const int xrow = rb * 16 + warp * 2;
            const uint4* xp = reinterpret_cast<const uint4*>(P.x) + xrow * 64;
            const uint32_t img = (grp * 32 + j) * SLOT;
            uint32_t x[16], x0[2];
            float st[4] = {0.f, 0.f, 0.f, 0.f};
            mbar_wait(sb + BAR_FULL + 8 * 4, 0);
#pragma unroll
            for (int q = 3; q < 8; q++) {
                const uint32_t ws = (0x4210u >> (4 * (q & 3))) & 15, as = (0x635u >> (4 * (q % 3))) & 15;
                mbar_wait(sb + BAR_FULL + 8 * as, (q / 3) & 1);
                bar_sync(1 + wg, 256);
                if (q == 3) gemm_issue<false>(s, kd + wg * 512 + as * (SLOT / 16), wd + ws * (SLOT / 16), 1, false);
                else if (q == 4) gemm_issue<true>(o, kd + wg * 512 + as * (SLOT / 16), wd + ws * (SLOT / 16), 0, false);
                else gemm_issue<false>(o, kd + wg * 512 + as * (SLOT / 16), wd + ws * (SLOT / 16), 1, false);
                bar_arrive(2 - wg, 256);
                sched_fence(fph, P.zero);
                if (q > 3) reg_fence(s);
                if (q == 3) {
                    asm volatile("setmaxnreg.inc.sync.aligned.u32 232;");
#pragma unroll
                    for (int i = 0; i < 4; i++)
                        asm volatile("ld.global.nc.v4.u32 {%0, %1, %2, %3}, [%4];" : "=r"(x[4 * i]), "=r"(x[4 * i + 1]), "=r"(x[4 * i + 2]), "=r"(x[4 * i + 3])
                                     : "l"(xp + lane + 32 * i) : "memory");
#pragma unroll
                    for (int i = 0; i < 2; i++) asm volatile("ld.global.nc.u32 %0, [%1];" : "=r"(x0[i]) : "l"(xp + 64 * i) : "memory");
                }
                if (q == 4) {
                    img_store_global<0>(img, toff, s, sc, sc);
#pragma unroll
                    for (int k = 0; k < 16; k++) {
                        const float d0 = bf_lo(x[k]) - bf_lo(x0[k >> 3]), d1 = bf_hi(x[k]) - bf_lo(x0[k >> 3]);
                        st[k >> 3] += d0 + d1;
                        st[2 + (k >> 3)] = fmaf(d0, d0, fmaf(d1, d1, st[2 + (k >> 3)]));
                    }
#pragma unroll
                    for (int i = 0; i < 4 * NSH; i++) st[i & 3] += __shfl_xor_sync(0xffffffffu, st[i & 3], 1 << (i >> 2));
                    reg_fence(st);
                }
                if (q == 5) {
#pragma unroll
                    for (int i = 4 * NSH; i < 20; i++) st[i & 3] += __shfl_xor_sync(0xffffffffu, st[i & 3], 1 << (i >> 2));
                    img_store_global<1>(img, toff, s, sc, sc);
#pragma unroll
                    for (int i = 0; i < 2; i++) {
                        const float d = st[i] * (1.f / 512.f);
                        st[2 + i] = ln_rstd(fmaxf(fmaf(-d, d, st[2 + i] * (1.f / 512.f)), 0.f));
                        x0[i] = pack2(bf_lo(x0[i]) + d, bf_lo(x0[i]) + d);
                    }
                    reg_fence(st);
                    reg_fence(x0);
                }
                if (q > 5) {
                    if (q == 6) mbar_wait(sb + BAR_FLAG + 8 * 8, 0);
                    const uint4 a = lds128(sb + SM_TAB + 1024 + (q & 1) * 512 + lane * 16), c = lds128(sb + SM_TAB + (q & 1) * 512 + lane * 16);
                    uint8_t* hp = g_h + (grp * 8 + (q & 1) * 4 + (lane >> 3)) * 16384 + (xrow & 127) * 128;
#pragma unroll
                    for (int i = 0; i < 2; i++) {
                        const uint32_t* y = x + 8 * i + 4 * (q & 1);
                        *reinterpret_cast<uint4*>(hp + i * 128 + (((lane ^ xrow ^ i) & 7) << 4)) =
                            make_uint4(ln_apply(y[0], x0[i], st[2 + i], a.x, c.x), ln_apply(y[1], x0[i], st[2 + i], a.y, c.y),
                                       ln_apply(y[2], x0[i], st[2 + i], a.z, c.z), ln_apply(y[3], x0[i], st[2 + i], a.w, c.w));
                    }
                    if (q == 7) {
                        __syncwarp();
                        mbar_arrive_if(sb + BAR_DONE, lane == 0);
                    }
                    if (q == 6) img_store_global<2>(img, toff, s, sc, sc);
                    else img_store_global<3>(img, toff, s, sc, sc);
                }
                if (q < 7) {
                    sched_fence(fph, P.zero);
                    wg_wait<0>();
                    release_if(eb, as, rel);
                }
            }
        }
        uint32_t pend = 0x73;
        uint32_t p[32] = {};
#pragma unroll 1
        for (int hp = 0; hp < 2; hp++) {
            float m[2] = {0.f, 0.f}, l[2] = {0.f, 0.f}, t[4] = {0.f, 0.f, 0.f, 0.f};
            bool shifted = false, bad = false, plain = false;
            uint32_t qa = desc_k(sb + 5 * SLOT + (wg ^ 1) * 8192);
            const uint32_t limg = (512 + (15 - j) * 32 + 2 * grp + hp) * SLOT;
            {
                const int step = hp ? -8 * SLOT : 8 * SLOT;
                uint32_t img = (grp * 32 + (hp ? j ^ 30 : j) + 8) * SLOT;
                const uint32_t wtab = w_table(hp);
                uint32_t atab = hp ? 0x562u : 0x356u;
#pragma unroll 1
                for (int u = 2 - 2 * hp; u < 6; u += 2) {
                    proj_tile<false>(s, o, u, !u, sb, wg, eb, rel, fph, wtab, atab, pend, u ? img : cimg, toff, u ? sc : li[0], u ? sc : li[1], p);
                    __syncwarp();
                    mbar_arrive_if(sb + BAR_DONE + 4 * u + 32 * hp, lane == 0);
                    if (elected) TS(1 + 10 * hp + u + 20 * wg);
                    proj_tile<true>(o, s, u + 1, 0, sb, wg, eb, rel, fph, wtab, atab, pend, img + step, toff, sc, sc, p);
                    if (elected) TS(2 + 10 * hp + u + 20 * wg);
                    img += 2 * step;
                }
            }
            asm volatile("" : "+r"(toff));
            if (elected) TS(6 + 10 * hp + 20 * wg);
            fence_async_smem();
            slot_wait(sb + BAR_FULL, fph, r);
            step_retire(eb, rel, pend);
            reg_fence(o);
            int n = -1;
#pragma unroll 1
            for (;;) {
                while (bad || plain) {
                    float d0 = m[0], d1 = m[1];
                    if (bad) {
                        float a0, a1;
                        softmax_remax(s, m, n == 0 || n == nL, d0, d1, a0, a1);
                        shifted = true;
                        l[0] *= a0;
                        l[1] *= a1;
#pragma unroll
                        for (int i = 0; i < 64; i++) o[i] *= (i & 2) ? a1 : a0;
                    }
#pragma unroll
                    for (int i = 0; i < 64; i++) s[i] -= (i & 2) ? d1 : d0;
                    softmax_exp<0, 16>(s, p, t);
                    t[0] += t[1];
                    t[2] += t[3];
                    bad = !bad && softmax_unsafe(t[0], t[2], false);
                    plain = false;
                }
#pragma unroll 1
                do {
                    l[0] += t[0];
                    l[1] += t[2];
                    if (++n > 16) break;
                    const uint32_t ks = r;
                    uint32_t vs = ring_next(r);
                    r = ring_next(vs);
                    bar_sync(1 + wg, 256);
                    const float x = (float)((warp & 3) * 16 + g - 2 * c4);
                    if (n == hn) {
                        float sh[32];
                        qk_issue(sh, qa, kd + ks * (SLOT / 16));
                        slot_wait(sb + BAR_FULL, fph, vs);
                        pv_issue(o, p, vd + vs * (SLOT / 16), 1, false);
                        bar_arrive(2 - wg, 256);
                        wg_wait<1>();
                        reg_fence(sh);
                        tri_mask_copy(s, sh, x);
                        release_if(eb, ks, rel);
                        release_if(eb, 5 + wg, rel && (!wg || n == 16));
                        if (!wg) qa += SLOT / 16;
                        float e[4 * EARLY];
#pragma unroll
                        for (int i = 0; i < 4 * EARLY; i++) {
                            e[i] = ex2(s[i]);
                            t[i & 3] = i < 4 ? e[i] : t[i & 3] + e[i];
                        }
                        reg_fence(e);
                        slot_wait(sb + BAR_FULL, fph, r);
                        wg_wait<0>();
                        reg_fence(o);
                        reg_fence(e);
                        release_if(eb, vs, rel);
#pragma unroll
                        for (int i = 0; i < 2 * EARLY; i++) p[i] = pack2(e[2 * i], e[2 * i + 1]);
                        softmax_exp<EARLY, 8>(s, p, t);
                        if (wg) {
                            ctx_store(limg, toff, o, rcp(quad_sum(l[0])), rcp(quad_sum(l[1])));
                            __syncwarp();
                            mbar_arrive_if(sb + BAR_DONE + 24 + 32 * hp, lane == 0);
                            l[0] = l[1] = m[0] = m[1] = 0.f;
                            shifted = false;
                        }
                        t[0] += t[1];
                        t[2] += t[3];
                        plain = shifted;
                        if (plain) break;
                        bad = softmax_unsafe(t[0], t[2], wg);
                        continue;
                    }
                    if (n == nL) {
                        qk_issue(s, qa, kd + ks * (SLOT / 16));
                        slot_wait(sb + BAR_FULL, fph, vs);
                        pv_issue(o, p, vd + vs * (SLOT / 16), 1, true);
                        bar_arrive(2 - wg, 256);
                        const float i0 = rcp(quad_sum(l[0])), i1 = rcp(quad_sum(l[1]));
                        wg_wait<1>();
                        reg_fence(s);
                        release_if(eb, ks, rel);
                        release_if(eb, 6, rel && n == 16);
                        tri_mask(s, x);
                        float e[4 * EARLY2];
#pragma unroll
                        for (int i = 0; i < 4 * EARLY2; i++) {
                            e[i] = ex2(s[i]);
                            t[i & 3] = i < 4 ? e[i] : t[i & 3] + e[i];
                        }
                        reg_fence(e);
                        reg_fence(s);
                        reg_fence(t);
                        slot_wait(sb + BAR_FULL, fph, r);
                        sched_fence(fph, P.zero);
                        wg_wait<0>();
                        reg_fence(o);
                        reg_fence(e);
                        release_if(eb, vs, rel);
#pragma unroll
                        for (int i = 0; i < 2 * EARLY2; i++) p[i] = pack2(e[2 * i], e[2 * i + 1]);
                        softmax_exp<EARLY2, MSPLIT>(s, p, t);
                        ctx_store(limg, toff, o, i0, i1);
                        reg_fence(t);
                        reg_fence(s);
                        softmax_exp<MSPLIT, 16>(s, p, t);
                        __syncwarp();
                        mbar_arrive_if(sb + BAR_DONE + 24 + 32 * hp, lane == 0);
                        l[0] = l[1] = m[0] = m[1] = 0.f;
                        shifted = false;
                        t[0] += t[1];
                        t[2] += t[3];
                        bad = __any_sync(0xffffffffu, fmaxf(t[0], t[2]) > SM_HI || fminf(t[0], t[2]) < SM_LO);
                        continue;
                    }
                    qk_issue(s, qa, kd + ks * (SLOT / 16));
                    if (n == 0) {
                        r = vs;
                        vs = 4 - hp;
                        slot_wait(sb + BAR_FULL, fph, 6);
                        gemm_issue<false>(o, qa + SLOT / 16, wd + vs * (SLOT / 16), 1, false);
                    } else {
                        slot_wait(sb + BAR_FULL, fph, vs);
                        if (n == 1) {
                            wg_wait<1>();
                            reg_fence(o);
                            const uint32_t a = sb + 6 * SLOT + q_off(toff);
#pragma unroll
                            for (int i = 0; i < 8; i++) {
                                const int k = 16 * (i >> 1) + 2 * (i & 1);
                                sts128(a + (i >> 2) * 16384 + (i & 2) * 256 + (i & 1) * 1024,
                                       make_uint4(pack2(o[k], o[k + 1]), pack2(o[k + 4], o[k + 5]), pack2(o[k + 8], o[k + 9]), pack2(o[k + 12], o[k + 13])));
                            }
                        }
                        pv_issue(o, p, vd + vs * (SLOT / 16), n != 1 && n != nL + 1, n == hn + 1);
                    }
                    bar_arrive(2 - wg, 256);
                    wg_wait<1>();
                    reg_fence(s);
                    release_if(eb, ks, rel);
                    release_if(eb, 6, rel && n == 16);
                    if (n == nL - 1) {
                        tri_mask(s, x);
                        release_if(eb, 5, rel);
                        qa += SLOT / 16;
                    }
                    if (n == 2) fence_async_smem();
                    if (shifted) {
                        slot_wait(sb + BAR_FULL, fph, r);
                        wg_wait<0>();
                        reg_fence(o);
                        release_if(eb, vs, rel);
                        plain = true;
                        break;
                    }
                    float e[4 * EARLY];
#pragma unroll
                    for (int i = 0; i < 4 * EARLY; i++) {
                        e[i] = ex2(s[i]);
                        t[i & 3] = i < 4 ? e[i] : t[i & 3] + e[i];
                    }
                    reg_fence(e);
                    slot_wait(sb + BAR_FULL, fph, r);
                    wg_wait<0>();
                    reg_fence(o);
                    reg_fence(e);
                    release_if(eb, vs, rel);
#pragma unroll
                    for (int i = 0; i < 2 * EARLY; i++) p[i] = pack2(e[2 * i], e[2 * i + 1]);
                    softmax_exp<EARLY, 16>(s, p, t);
                    t[0] += t[1];
                    t[2] += t[3];
                    bad = __any_sync(0xffffffffu, fmaxf(t[0], t[2]) > SM_HI || (n == 0 && fminf(t[0], t[2]) < SM_LO));
                } while (!bad);
                if (!bad && !plain) break;
            }
            asm volatile("" : "+r"(toff));
            const uint32_t vs = r, ga = desc_k(sb + (hp ? 2 * (wg ^ kh ^ 1) : wg) * 8192);
            r = ring_next(r);
            slot_wait(sb + BAR_FULL, fph, 5);
            slot_wait(sb + BAR_FULL, fph, r);
            bar_sync(1 + wg, 256);
            gemm_issue<true>(s, ga + 5 * (SLOT / 16), wd + r * (SLOT / 16), 0, hp);
            pv_issue(o, p, vd + vs * (SLOT / 16), j, hn == 16);
            bar_arrive(2 - wg, 256);
            li[0] = rcp(quad_sum(l[0]));
            li[1] = rcp(quad_sum(l[1]));
            cimg = limg + (2 * j - 15) * 32 * SLOT + (wg ? -16384 : 16384);
            wg_wait<1>();
            release_if(eb, 5, rel);
            release_if(eb, r, rel && hp);
            wg_wait<0>();
            release_if(eb, vs, rel);
            reg_fence(o);
            img_store_global<0>(cimg, toff, o, li[0], li[1]);
            pend = 0x77;
            if (elected) TS(8 + 10 * hp + 20 * wg);
        }
        uint32_t otab = 0x2351604u;
        const uint32_t oa = desc_k(sb + (wg ^ kh ^ 1) * 16384);
        const int t7 = tid & 127, w4 = warp & 3, row = ort * 128 + kh * 64 + w4 * 16 + g;
#pragma unroll 1
        for (int i = 1; i < 15 - OFF - wg; i++) {
            const uint32_t as = o_next(otab), ws = o_next(otab);
            slot_wait(sb + BAR_FULL, fph, as);
            slot_wait(sb + BAR_FULL, fph, ws);
            bar_sync(1 + wg, 256);
            gemm_issue<false>(s, oa + as * (SLOT / 16), wd + ws * (SLOT / 16), 1, true);
            bar_arrive(2 - wg, 256);
            wg_wait<1>();
            reg_fence(o);
            if (i == 1) img_store_global<1>(cimg, toff, o, li[0], li[1]);
            if (i == 2) img_store_global<2>(cimg, toff, o, li[0], li[1]);
            if (i == CLAST) {
                img_store_global<3>(cimg, toff, o, li[0], li[1]);
                __syncwarp();
                mbar_arrive_if(sb + BAR_DONE + 64, lane == 0);
            }
            wg_wait<0>();
            release_if(eb, as, rel);
            release_if(eb, ws, rel);
        }
        mbar_wait(sb + BAR_PF, 0);
        const uint32_t ep = lds32(sb + SM_EP);
        uint32_t eb2 = sb + BAR_END;
        if (wg == 0) {
            reg_fence(s);
            if (elected) TS(9);
            TT(1);
#pragma unroll
            for (int v = 0; v < 8; v++)
                st_pub(g_out + rb * OB + v * 128 + t7, make_uint4((pack2(s[8 * v], s[8 * v + 1]) & ~1u) | (ep & 1), pack2(s[8 * v + 2], s[8 * v + 3]),
                                                                      pack2(s[8 * v + 4], s[8 * v + 5]), pack2(s[8 * v + 6], s[8 * v + 7])), true);
            constexpr uint32_t s1 = SL_WF, s2 = SL_WD;
            bar_sync(4, 256);
            uint32_t wf[64];
            float wn[64];
            if (rb < NFFN) {
                slot_wait(sb + BAR_FULL, fph, s1);
                const uint32_t a = sb + s1 * SLOT + (w4 * 128 + (lane >> 4) * 8 + (lane & 7)) * 32 + (((lane >> 3) ^ (lane >> 2)) & 1) * 16;
#pragma unroll
                for (int i = 0; i < 16; i++)
                    asm volatile("ldmatrix.sync.aligned.m8n8.x4.trans.shared.b16 {%0, %1, %2, %3}, [%4];"
                                 : "=r"(wf[4 * i]), "=r"(wf[4 * i + 1]), "=r"(wf[4 * i + 2]), "=r"(wf[4 * i + 3])
                                 : "r"(a + (i >> 3) * 16384 + (i & 7) * 512) : "memory");
                slot_wait(sb + BAR_FULL, fph, s2);
#pragma unroll
                for (int i = 0; i < 16; i++) {
                    const uint2 w = *reinterpret_cast<const uint2*>(smem + s2 * SLOT + (kh ^ 1) * 16384 + i * 1024 + t7 * 8);
                    wn[4 * i] = bf_lo(w.x); wn[4 * i + 1] = bf_hi(w.x); wn[4 * i + 2] = bf_lo(w.y); wn[4 * i + 3] = bf_hi(w.y);
                }
                reg_fence(wn);
            }
            const uint32_t gbf = __ldcg(reinterpret_cast<const uint32_t*>(g_mod) + 1280 + rb * 2 + (tid & 1));
            if (elected) TS(10);
            TT(2);
            float* sred = reinterpret_cast<float*>(smem + SM_RED);
            if (warp == 0) {
                *reinterpret_cast<uint32_t*>(smem + SM_EP + 24) = best_key(g_key + cq * 128, lane, ep);
                mbar_arrive_if(sb + BAR_BEST, lane == 0);
            }
            bar_sync(3, 128);
            const uint32_t best = lds32(sb + SM_EP + 24);
            const int sel = (~best >> 5) & 2047;
            TT(3);
            if (rb < NFFN) {
                const uint4* cp = g_cand + (sel >> 4) * 192;
                uint4 cv[6];
                for (;;) {
                    uint32_t bad = 0;
#pragma unroll
                    for (int v = 0; v < 6; v++) cv[v] = ld_poll(cp + w4 * 24 + v * 4 + c4);
#pragma unroll
                    for (int v = 0; v < 6; v++) bad |= cv[v].w ^ ep;
                    if (__all_sync(0xffffffffu, bad == 0)) break;
                }
            TT(4);
                float d[4][4] = {};
#pragma unroll
                for (int k = 0; k < 8; k++) {
                    const uint32_t b0 = (&cv[(2 * k) / 3].x)[(2 * k) % 3], b1 = (&cv[(2 * k + 1) / 3].x)[(2 * k + 1) % 3];
                    mma16816(d[k & 1], wf + 4 * k, b0, b1);
                    mma16816(d[2 + (k & 1)], wf + 32 + 4 * k, b0, b1);
                }
                const float u = (c4 & 2) ? ((c4 & 1) ? d[2][2] + d[3][2] : d[2][0] + d[3][0]) : ((c4 & 1) ? d[0][2] + d[1][2] : d[0][0] + d[1][0]);
                sred[w4 * 32 + c4 * 8 + g] = u;
                bar_sync(3, 128);
                const float v = rbf((sred[lane] + sred[32 + lane]) + (sred[64 + lane] + sred[96 + lane]));
                const float act = rbf(rbf(v * sigmoid(v)) * __shfl_down_sync(0xffffffffu, v, 16));
                float y[4] = {0.f, 0.f, 0.f, 0.f};
#pragma unroll
                for (int k = 0; k < 16; k++) {
                    const float a = __shfl_sync(0xffffffffu, act, k);
#pragma unroll
                    for (int i = 0; i < 4; i++) y[i] = fmaf(a, wn[4 * k + i], y[i]);
                }
                st_pub(g_out + rb * OB + OB_Y + t7, make_uint4((__float_as_uint(y[0]) & ~15u) | (ep & 15), __float_as_uint(y[1]), __float_as_uint(y[2]), __float_as_uint(y[3])), true);
            }
            const int pq = (2 * rb + (tid & 1)) & 63, pv = (pq >> 2) / 3;
            const uint4* fp = g_cand + (sel >> 4) * 192 + (rb >> 5) * 24 + pv * 4 + (pq & 3);
            uint4 fh = {}, fx = {};
            if (rb == 0 && tid == 0) g_sync.epoch[0] = ep;
            if (elected) TS(60);
            TT(5);
            uint4 yv;
            if (warp == 0) { fh = ld_poll(fp); fx = ld_poll(fp + 96); }
            __nanosleep(rb < NFFN ? YPRE : 4 * YPRE);
            for (;;) {
                yv = ld_poll(g_out + min(t7, NFFN - 1) * OB + OB_Y + rb);
                if (__all_sync(0xffffffffu, ((yv.x ^ ep) & 15) == 0)) break;
                if (YSLEEP) __nanosleep(YSLEEP);
            }
            if (elected) TS(61);
            TT(6);
            float y[4] = {0.f, 0.f, 0.f, 0.f};
            if (t7 < NFFN) { y[0] = __uint_as_float(yv.x); y[1] = __uint_as_float(yv.y); y[2] = __uint_as_float(yv.z); y[3] = __uint_as_float(yv.w); }
            const float z0 = ((lane & 16) ? y[2] : y[0]) + __shfl_xor_sync(0xffffffffu, (lane & 16) ? y[0] : y[2], 16);
            const float z1 = ((lane & 16) ? y[3] : y[1]) + __shfl_xor_sync(0xffffffffu, (lane & 16) ? y[1] : y[3], 16);
            float z = ((lane & 8) ? z1 : z0) + __shfl_xor_sync(0xffffffffu, (lane & 8) ? z0 : z1, 8);
            z += __shfl_xor_sync(0xffffffffu, z, 4);
            z = quad_sum(z);
            if ((lane & 7) == 0) sred[128 + (lane >> 3) * 4 + w4] = z;
            bar_sync(3, 128);
            if (tid < 2) {
                while (fh.w != ep || fx.w != ep) { fh = ld_poll(fp); fx = ld_poll(fp + 96); }
                const float4 y0 = *reinterpret_cast<const float4*>(sred + 128 + tid * 8), y1 = *reinterpret_cast<const float4*>(sred + 132 + tid * 8);
                const int cm = (pq >> 2) - 3 * pv;
                const uint32_t h2 = cm == 0 ? fh.x : cm == 1 ? fh.y : fh.z, x2 = cm == 0 ? fx.x : cm == 1 ? fx.y : fx.z;
                const float sg = sigmoid(bf_hi((best & 0x80000000u) ? (best ^ 0x80000000u) : ~best));
                reinterpret_cast<uint32_t*>(P.out)[sel * 256 + rb * 2 + tid] =
                    badd(x2, bmul(gbf, badd(h2, bmul(pack2((y0.x + y0.y) + (y0.z + y0.w), (y1.x + y1.y) + (y1.z + y1.w)), pack2(sg, sg)))));
            }
            if (elected) TS(62);
            TT(7);
        } else {
            const float4* tf = reinterpret_cast<const float4*>(smem + SM_TAB) + c4;
            uint32_t x2[32];
            bar_sync(2, 256);
#pragma unroll 1
            for (int i = 14; i < 17; i++) {
                const uint32_t as = o_next(otab), ws = o_next(otab);
                slot_wait(sb + BAR_FULL, fph, as);
                slot_wait(sb + BAR_FULL, fph, ws);
                gemm_issue<false>(s, oa + as * (SLOT / 16), wd + ws * (SLOT / 16), 1, true);
                wg_wait<1>();
            }
            const uint4* pr = g_out + (rb ^ 16) * OB + t7;
            uint4 pa[8];
            if (elected) TS(29);
            TT(1);
#pragma unroll
            for (int k = 0; k < 8; k++) {
                const uint4 v = lds128(sb + SL_X * SLOT + (kh ^ 1) * 16384 + k * 2048 + t7 * 16);
                x2[4 * k] = v.x; x2[4 * k + 1] = v.y; x2[4 * k + 2] = v.z; x2[4 * k + 3] = v.w;
            }
            wg_wait<0>();
            reg_fence(s);
            bar_arrive(4, 256);
            if (elected) TS(39);
            TT(2);
#pragma unroll
            for (int v = 0; v < 8; v++) pa[v] = ld_poll(pr + v * 128);
            float4 tc[16];
#pragma unroll
            for (int k = 0; k < 16; k++) {
                tc[k] = tf[k * 4];
                if (!(g & 1)) tc[k].z = __uint_as_float(ONE2);
#pragma unroll
                for (int i = 4 * k; i < 4 * k + 4; i++) s[i] = fmaf((i & 1) ? tc[k].y : tc[k].x, s[i], (i & 1) ? bf_hi(x2[i >> 1]) : bf_lo(x2[i >> 1]));
            }
            reg_fence(s);
            sched_fence(eb2, P.zero);
            for (;;) {
                uint32_t bad = 0;
#pragma unroll
                for (int v = 0; v < 8; v++) asm("lop3.b32 %0, %0, %1, %2, 0xf6;" : "+r"(bad) : "r"(pa[v].x), "r"(ep));
                if (__all_sync(0xffffffffu, (bad & 1) == 0)) break;
                if (PSLEEP) __nanosleep(PSLEEP);
#pragma unroll
                for (int v = 0; v < 8; v++) pa[v] = ld_poll(pr + v * 128);
            }
            if (elected) TS(30);
            TT(3);
            float sd[4] = {}, q0[4] = {}, q1[4] = {};
#pragma unroll
            for (int k = 0; k < 8; k++) {
#pragma unroll
                for (int i = 4 * k; i < 4 * k + 4; i++) {
                    const uint32_t w = (&pa[k].x)[i & 3];
                    x2[i] = pack2(fmaf(tc[i >> 1].x, bf_lo(w), s[2 * i]), fmaf(tc[i >> 1].y, bf_hi(w), s[2 * i + 1]));
                }
                mma16816(sd, x2 + 4 * k, __float_as_uint(tc[2 * k].z), __float_as_uint(tc[2 * k + 1].z));
                mma16816(q0, x2 + 4 * k, x2[4 * k], x2[4 * k + 2]);
                mma16816(q1, x2 + 4 * k, x2[4 * k + 1], x2[4 * k + 3]);
            }
            uint4* sp = g_out + rb * OB + OB_STAT + (w4 * 8 + g) * 2;
            st_pub(sp, make_uint4(__float_as_uint(sd[0]), __float_as_uint((g & 1) ? q0[1] : q0[0]), __float_as_uint(sd[1]), ep), c4 == g >> 1);
            st_pub(sp + 1, make_uint4(__float_as_uint(sd[2]), __float_as_uint((g & 1) ? q1[3] : q1[2]), __float_as_uint(sd[3]), ep), c4 == g >> 1);
            sched_fence(eb2, P.zero);
            if (elected) TS(56);
            TT(4);
            uint32_t cb[16], sh[16], gb[16];
#pragma unroll
            for (int i = 0; i < 16; i++) {
                const float4 c = tf[64 + i * 4];
                cb[i] = __float_as_uint(c.x); sh[i] = __float_as_uint(c.y); gb[i] = __float_as_uint(c.z);
            }
            const float ra = __uint_as_float(lds32(sb + SM_EP + 8)), rb0 = __uint_as_float(lds32(sb + SM_EP + 12));
            uint4 r0, r1;
            for (;;) {
                r0 = ld_poll(g_out + ((rb & ~33) + (c4 & 1) + (c4 & 2) * 16) * OB + OB_STAT + (w4 * 8 + g) * 2);
                r1 = ld_poll(g_out + ((rb & ~33) + (c4 & 1) + (c4 & 2) * 16) * OB + OB_STAT + (w4 * 8 + g) * 2 + 1);
                if (__all_sync(0xffffffffu, r0.w == ep && r1.w == ep)) break;
                if (SSLEEP) __nanosleep(SSLEEP);
            }
            if (elected) TS(57);
            TT(5);
            const float m0 = quad_sum(__uint_as_float(r0.x)) * (1.f / 512.f), m1 = quad_sum(__uint_as_float(r1.x)) * (1.f / 512.f);
            const float rs0 = ln_rstd(fmaxf(fmaf(-m0, m0, quad_sum(__uint_as_float(r0.y)) * (1.f / 512.f)), 0.f));
            const float rs1 = ln_rstd(fmaxf(fmaf(-m1, m1, quad_sum(__uint_as_float(r1.y)) * (1.f / 512.f)), 0.f));
            const uint32_t mb0 = pack2(m0, m0), mb1 = pack2(m1, m1);
            const uint32_t lg = pack2(fmaf(rs0, fmaf(-bf_lo(mb0), ra, quad_sum(__uint_as_float(r0.z))), rb0),
                                      fmaf(rs1, fmaf(-bf_lo(mb1), ra, quad_sum(__uint_as_float(r1.z))), rb0));
            const uint32_t u0 = lg << 16, u1 = lg & 0xffff0000u;
            const uint32_t k0 = ((u0 ^ (((int)u0 >> 31) | 0x80000000u)) & 0xffff0000u) | ((2047 - row) << 5) | (ep & 31);
            const uint32_t k1 = ((u1 ^ (((int)u1 >> 31) | 0x80000000u)) & 0xffff0000u) | ((2039 - row) << 5) | (ep & 31);
            const uint32_t kb = __reduce_max_sync(0xffffffffu, max(k0, k1));
            st_pub(g_key + cq * 128 + (row >> 4), kb, lane == 0);
            const bool cand = kb == k0 || kb == k1;
            uint4* cp = g_cand + (row >> 4) * 192 + cq * 24 + c4;
#pragma unroll 1
            for (int it = 0; it < 3; it++) {
                bool put = it == 1 || !cand;
                if (it == 2) {
                    mbar_wait(sb + BAR_BEST, 0);
                    put = cand && lds32(sb + SM_EP + 24) != kb;
                }
                const bool hi = (kb == k1) != (it == 1);
                uint32_t cx[18], ch[18];
#pragma unroll
                for (int i = 0; i < 16; i++) {
                    cx[i] = hi ? x2[2 * i + 1] : x2[2 * i];
                    ch[i] = ln_apply(cx[i], hi ? mb1 : mb0, hi ? rs1 : rs0, cb[i], sh[i]);
                }
                cx[16] = cx[17] = ch[16] = ch[17] = 0;
#pragma unroll
                for (int v = 0; v < 6; v++) st_pub(cp + v * 4, make_uint4(ch[3 * v], ch[3 * v + 1], ch[3 * v + 2], ep), cand && it == 0);
#pragma unroll
                for (int v = 0; v < 6; v++) st_pub(cp + 96 + v * 4, make_uint4(cx[3 * v], cx[3 * v + 1], cx[3 * v + 2], ep), cand && it == 0);
                if (it == 0) TT(6);
                uint2* op = reinterpret_cast<uint2*>(P.out) + (row + 8 * hi) * 128 + cq * 32 + (c4 & 1) * 2 + (c4 >> 1);
#pragma unroll
                for (int i = 0; i < 16; i += 2) {
                    const uint32_t v0 = badd(cx[i], bmul(gb[i], ch[i])), v1 = badd(cx[i + 1], bmul(gb[i + 1], ch[i + 1]));
                    const uint32_t rv = __shfl_xor_sync(0xffffffffu, (c4 & 1) ? v0 : v1, 1);
                    if (put) op[i * 2] = (c4 & 1) ? make_uint2(rv, v1) : make_uint2(v0, rv);
                }
            }
            if (elected) TS(59);
            TT(7);
        }
        mbar_arrive_if(eb2, lane == 0);
    }
}

typedef CUresult (*EncodeFn)(CUtensorMap*, CUtensorMapDataType, cuuint32_t, void*, const cuuint64_t*, const cuuint64_t*,
                             const cuuint32_t*, const cuuint32_t*, CUtensorMapInterleave, CUtensorMapSwizzle,
                             CUtensorMapL2promotion, CUtensorMapFloatOOBfill);

void make_3d(EncodeFn fn, CUtensorMap* m, const void* p, uint64_t cols, uint64_t rows, uint32_t br = 128, uint32_t nb = 2) {
    cuuint64_t dims[3] = {64, rows, cols / 64}, strides[2] = {cols * 2, 128};
    cuuint32_t box[3] = {64, br, nb}, es[3] = {1, 1, 1};
    fn(m, CU_TENSOR_MAP_DATA_TYPE_BFLOAT16, 3, const_cast<void*>(p), dims, strides, box, es, CU_TENSOR_MAP_INTERLEAVE_NONE,
       CU_TENSOR_MAP_SWIZZLE_128B, CU_TENSOR_MAP_L2_PROMOTION_L2_256B, CU_TENSOR_MAP_FLOAT_OOB_FILL_NONE);
}

}

extern "C" void kernel_launch(void* const* d_in, const int* in_sizes, int n_in, void* d_out, int out_size) {
    static EncodeFn fn = nullptr;
    if (!fn) {
        void* f = nullptr;
        cudaDriverEntryPointQueryResult st;
        cudaGetDriverEntryPoint("cuTensorMapEncodeTiled", &f, cudaEnableDefault, &st);
        fn = (EncodeFn)f;
        cudaFuncSetAttribute(fused_kernel, cudaFuncAttributeMaxDynamicSharedMemorySize, SMEM_BYTES);
    }
    CUtensorMap ckv, wq, wuk, wuv, wo, wg, wu, wm, xm;
    make_3d(fn, &ckv, d_in[1], 512, 2048, 128, 1);
    make_3d(fn, &xm, d_in[0], 512, 2048, 64);
    make_3d(fn, &wq, d_in[2], 4096, 512);
    make_3d(fn, &wuk, d_in[3], 4096, 512);
    make_3d(fn, &wuv, d_in[4], 4096, 512);
    make_3d(fn, &wo, d_in[5], 512, 4096);
    make_3d(fn, &wg, d_in[8], 1792, 512, 256, 1);
    make_3d(fn, &wu, d_in[9], 1792, 512, 256, 1);
    make_3d(fn, &wm, d_in[12], 3072, 512, 64, 4);
    Params p;
    p.x = (const bf16*)d_in[0];
    p.ckv = (const bf16*)d_in[1];
    p.wo = (const bf16*)d_in[5];
    p.wr = (const bf16*)d_in[7];
    p.wdown = (const bf16*)d_in[10];
    p.c = (const bf16*)d_in[11];
    p.out = (bf16*)d_out;
    p.zero = 0;
    fused_kernel<<<NCTA + NSPARE, 384, SMEM_BYTES>>>(ckv, wq, wuk, wuv, wo, wg, wu, wm, xm, p);
}
```

```cpp
#include <cuda.h>
#include <cuda_bf16.h>
#include <cuda_runtime.h>
#include <stdint.h>
#include <stdio.h>

namespace {

typedef __nv_bfloat16 bf16;
typedef unsigned long long u64;

constexpr int NCTA = 128, NSPARE = 4;
constexpr int SLOT = 32768;
constexpr int SM_BAR = 7 * SLOT;
constexpr int BAR_FULL = SM_BAR;
constexpr int BAR_EMPTY = BAR_FULL + 8 * 7;
constexpr int BAR_DONE = BAR_EMPTY + 8 * 7;
constexpr int BAR_FLAG = BAR_DONE + 8 * 9;
constexpr int BAR_PF = BAR_FLAG + 8 * 9;
constexpr int BAR_END = BAR_PF + 8;
constexpr int BAR_BEST = BAR_END + 8;
constexpr int SM_EP = BAR_END + 40;
constexpr int SM_RED = SM_BAR + 384;
constexpr int SM_TAB = SM_BAR + 1024;
constexpr int SMEM_BYTES = SM_BAR + 3072;
constexpr int NFFN = 112;
#define HINT 479
constexpr u64 L2_NORMAL = 0x1000000000000000ull, L2_FIRST = 0x12F0000000000000ull;
#define PFA 8
#define PFB 6
#define POLL_NS 50
#define MSPLIT 13
#define NSH 1
#define XPF 1
#define KSLEEP 400
#define YSLEEP 50
#define YPRE 150
#define SSLEEP 50
#define PSLEEP 100
#define KVG 7
#define EARLY2 4
#define OFF 2
#define CLAST 2
#define KN 16
#define KSLEEP2 60
#define EARLY 7
constexpr uint32_t SPIN_LIMIT = 1u << 22;
constexpr uint32_t ONE2 = 0x3f803f80u;

struct Sync {
    uint32_t cnt[16 * 8 * 8];
    uint32_t ctxcnt[16 * 32];
    uint32_t epoch[32];
};

__device__ __align__(1024) uint8_t g_img[2 * 512 * SLOT];
#define g_KV g_img
#define g_ctx (g_img + 512 * SLOT)
__device__ __align__(1024) uint8_t g_h[16 * 4 * SLOT];
constexpr int OB = 1216, OB_STAT = 1024, OB_Y = 1088;
__device__ __align__(1024) uint4 g_out[128 * OB];
__device__ __align__(1024) bf16 g_mod[3072];
__device__ __align__(1024) uint32_t g_mod1[1024];
__device__ __align__(1024) uint4 g_cand[128 * 192];
__device__ __align__(1024) uint32_t g_key[4 * 128];
__device__ __align__(1024) uint8_t g_wf[NFFN * SLOT];
__device__ __align__(1024) uint4 g_x2[128 * 1024];
__device__ __align__(1024) Sync g_sync;
#define TS(i)

#define TT(i)
#define PT()

struct Params {
    const bf16 *x, *ckv, *wo, *wr, *wdown, *c;
    bf16* out;
    int zero;
};

__device__ __forceinline__ void mbar_init(uint32_t bar, uint32_t cnt) {
    asm volatile("mbarrier.init.shared::cta.b64 [%0], %1;" ::"r"(bar), "r"(cnt) : "memory");
}
__device__ __forceinline__ void mbar_wait(uint32_t bar, uint32_t parity) {
    asm volatile("{\n.reg .pred p;\nL_%=:\nmbarrier.try_wait.parity.shared::cta.b64 p, [%0], %1;\n@!p bra L_%=;\n}" ::"r"(bar), "r"(parity) : "memory");
}
__device__ __forceinline__ void mbar_sleep(uint32_t bar) {
    if ((threadIdx.x & 31) == 0)
        asm volatile("{\n.reg .pred p;\nL_%=:\nmbarrier.try_wait.parity.shared::cta.b64 p, [%0], 0, 100000;\n@!p bra L_%=;\n}" ::"r"(bar) : "memory");
    __syncwarp();
}
__device__ __forceinline__ void mbar_watch(uint32_t bar, uint32_t parity) {
    asm volatile("{\n.reg .pred p;\n.reg .u32 n;\nmov.u32 n, 0;\n"
                 "L_%=:\nmbarrier.try_wait.parity.shared::cta.b64 p, [%0], %1;\n@p bra D_%=;\n"
                 "add.u32 n, n, 1;\nsetp.lt.u32 p, n, %2;\n@p bra L_%=;\ntrap;\nD_%=:\n}"
                 ::"r"(bar), "r"(parity), "n"(SPIN_LIMIT) : "memory");
}
__device__ __forceinline__ void step_watch(uint32_t a, uint32_t step) {
    asm volatile("{\n.reg .pred p;\n.reg .u32 n, v;\nmov.u32 n, 0;\n"
                 "L_%=:\nld.volatile.shared.u32 v, [%0];\nsetp.ge.u32 p, v, %1;\n@p bra D_%=;\nnanosleep.u32 400;\n"
                 "add.u32 n, n, 1;\nsetp.lt.u32 p, n, %2;\n@p bra L_%=;\ntrap;\nD_%=:\n}"
                 ::"r"(a), "r"(step), "n"(SPIN_LIMIT) : "memory");
}
__device__ __forceinline__ void mbar_arrive_if(uint32_t bar, bool on) {
    asm volatile("{\n.reg .pred p;\nsetp.ne.s32 p, %1, 0;\n@p mbarrier.arrive.shared::cta.b64 _, [%0];\n}" ::"r"(bar), "r"((int)on) : "memory");
}
__device__ __forceinline__ void tma3d_prefetch(const CUtensorMap* m, int row, int cb) {
    asm volatile("{\n.reg .pred p;\nelect.sync _|p, 0xffffffff;\n@p cp.async.bulk.prefetch.tensor.3d.L2.global [%0, {%1, %2, %3}];\n}"
                 ::"l"(m), "r"(0), "r"(row), "r"(cb) : "memory");
}
__device__ __forceinline__ void l2_prefetch(const void* p, uint32_t bytes) {
    asm volatile("{\n.reg .pred p;\nelect.sync _|p, 0xffffffff;\n@p cp.async.bulk.prefetch.L2.global [%0], %1;\n}" ::"l"(p), "r"(bytes) : "memory");
}
__device__ __forceinline__ void bulk_store(void* dst, uint32_t src, uint32_t bytes, bool first) {
    asm volatile("{\n.reg .pred p;\nelect.sync _|p, 0xffffffff;\n@p cp.async.bulk.global.shared::cta.bulk_group.L2::cache_hint [%0], [%1], %2, %3;\n}"
                 ::"l"(dst), "r"(src), "r"(bytes), "l"(first ? L2_FIRST : L2_NORMAL) : "memory");
}
__device__ __forceinline__ void flag_wait(const uint32_t* f, uint32_t target) {
    asm volatile("{\n.reg .pred p;\n.reg .u32 v;\n"
                 "L_%=:\nld.acquire.gpu.global.u32 v, [%0];\nsub.u32 v, v, %1;\nsetp.lt.s32 p, v, 0;\n@p nanosleep.u32 100;\n@p bra L_%=;\n}"
                 ::"l"(f), "r"(target) : "memory");
}
__device__ __forceinline__ uint4 ld_poll(const uint4* p) {
    uint4 v;
    asm volatile("{\n.reg .b128 t;\nld.relaxed.gpu.global.b128 t, [%4];\nmov.b128 {%0, %1, %2, %3}, t;\n}"
                 : "=r"(v.x), "=r"(v.y), "=r"(v.z), "=r"(v.w) : "l"(p) : "memory");
    return v;
}
__device__ __forceinline__ void st_pub(uint4* p, uint4 v, bool on) {
    asm volatile("{\n.reg .pred p;\n.reg .b128 t;\nsetp.ne.s32 p, %5, 0;\nmov.b128 t, {%1, %2, %3, %4};\n@p st.relaxed.gpu.global.b128 [%0], t;\n}"
                 ::"l"(p), "r"(v.x), "r"(v.y), "r"(v.z), "r"(v.w), "r"((int)on) : "memory");
}
__device__ __forceinline__ void st_pub(uint32_t* p, uint32_t v, bool on) {
    asm volatile("{\n.reg .pred p;\nsetp.ne.s32 p, %2, 0;\n@p st.relaxed.gpu.global.u32 [%0], %1;\n}" ::"l"(p), "r"(v), "r"((int)on) : "memory");
}
__device__ __forceinline__ bool poll_done(bool ok, uint32_t ns) {
    const int done = __all_sync(0xffffffffu, ok);
    asm volatile("{\n.reg .pred p;\nsetp.eq.s32 p, %0, 0;\n@p nanosleep.u32 %1;\n}" ::"r"(done), "r"(ns) : "memory");
    return done;
}
__device__ __forceinline__ void flag_add(uint32_t* p) {
    asm volatile("red.release.gpu.global.add.u32 [%0], 1;" ::"l"(p) : "memory");
}
__device__ __forceinline__ uint32_t lds32(uint32_t a) {
    uint32_t v;
    asm volatile("ld.shared.u32 %0, [%1];" : "=r"(v) : "r"(a) : "memory");
    return v;
}
__device__ __forceinline__ uint4 lds128(uint32_t a) {
    uint4 v;
    asm volatile("ld.shared.v4.u32 {%0, %1, %2, %3}, [%4];" : "=r"(v.x), "=r"(v.y), "=r"(v.z), "=r"(v.w) : "r"(a) : "memory");
    return v;
}
__device__ __forceinline__ void sched_fence(uint32_t& v, uint32_t z) {
    uint32_t ck;
    asm volatile("mov.u32 %0, %%clock;" : "=r"(ck)::"memory");
    v ^= ck & z;
}
__device__ __forceinline__ void fence_async_global() { asm volatile("fence.proxy.async.global;" ::: "memory"); }
__device__ __forceinline__ void fence_async_smem() { asm volatile("fence.proxy.async.shared::cta;" ::: "memory"); }
__device__ __forceinline__ void bar_sync(int id, int n) { asm volatile("bar.sync %0, %1;" ::"r"(id), "r"(n) : "memory"); }
__device__ __forceinline__ void bar_arrive(int id, int n) { asm volatile("bar.arrive %0, %1;" ::"r"(id), "r"(n) : "memory"); }
__device__ __forceinline__ void wg_fence() { asm volatile("wgmma.fence.sync.aligned;" ::: "memory"); }
__device__ __forceinline__ void wg_commit() { asm volatile("wgmma.commit_group.sync.aligned;" ::: "memory"); }
template <int N> __device__ __forceinline__ void wg_wait() { asm volatile("wgmma.wait_group.sync.aligned %0;" ::"n"(N) : "memory"); }
template <int N> __device__ __forceinline__ void reg_fence(float (&d)[N]) {
#pragma unroll
    for (int i = 0; i < N; i++) asm volatile("" : "+f"(d[i])::"memory");
}
template <int N> __device__ __forceinline__ void reg_fence(uint32_t (&d)[N]) {
#pragma unroll
    for (int i = 0; i < N; i++) asm volatile("" : "+r"(d[i])::"memory");
}
__device__ __forceinline__ uint32_t desc_k(uint32_t a) { return ((a & 0x3ffff) >> 4) | (1u << 16); }
__device__ __forceinline__ uint32_t desc_mn(uint32_t a) { return ((a & 0x3ffff) >> 4) | (1024u << 16); }

__device__ __forceinline__ uint64_t desc64(uint32_t lo, uint32_t hi) {
    uint64_t d;
    asm("mov.b64 %0, {%1, %2};" : "=l"(d) : "r"(lo), "r"(hi));
    return d;
}
__device__ __forceinline__ void desc_add(uint64_t& d, uint32_t x) { asm("add.u64 %0, %0, %1;" : "+l"(d) : "l"((uint64_t)x)); }

template <int TB>
__device__ __forceinline__ void wgmma_ss128(float (&d)[64], uint64_t da, uint64_t db, int acc) {
    asm volatile("{\n.reg .pred p;\nsetp.ne.b32 p, %66, 0;\n"
        "wgmma.mma_async.sync.aligned.m64n128k16.f32.bf16.bf16 {%0, %1, %2, %3, %4, %5, %6, %7, %8, %9, %10, %11, %12, %13, %14, %15, %16, %17, %18, %19, %20, %21, %22, %23, %24, %25, %26, %27, %28, %29, %30, %31, %32, %33, %34, %35, %36, %37, %38, %39, %40, %41, %42, %43, %44, %45, %46, %47, %48, %49, %50, %51, %52, %53, %54, %55, %56, %57, %58, %59, %60, %61, %62, %63}, %64, %65, p, 1, 1, 0, %67;\n}"
        : "+f"(d[0]), "+f"(d[1]), "+f"(d[2]), "+f"(d[3]), "+f"(d[4]), "+f"(d[5]), "+f"(d[6]), "+f"(d[7]), "+f"(d[8]), "+f"(d[9]), "+f"(d[10]), "+f"(d[11]), "+f"(d[12]), "+f"(d[13]), "+f"(d[14]), "+f"(d[15]), "+f"(d[16]), "+f"(d[17]), "+f"(d[18]), "+f"(d[19]), "+f"(d[20]), "+f"(d[21]), "+f"(d[22]), "+f"(d[23]), "+f"(d[24]), "+f"(d[25]), "+f"(d[26]), "+f"(d[27]), "+f"(d[28]), "+f"(d[29]), "+f"(d[30]), "+f"(d[31]), "+f"(d[32]), "+f"(d[33]), "+f"(d[34]), "+f"(d[35]), "+f"(d[36]), "+f"(d[37]), "+f"(d[38]), "+f"(d[39]), "+f"(d[40]), "+f"(d[41]), "+f"(d[42]), "+f"(d[43]), "+f"(d[44]), "+f"(d[45]), "+f"(d[46]), "+f"(d[47]), "+f"(d[48]), "+f"(d[49]), "+f"(d[50]), "+f"(d[51]), "+f"(d[52]), "+f"(d[53]), "+f"(d[54]), "+f"(d[55]), "+f"(d[56]), "+f"(d[57]), "+f"(d[58]), "+f"(d[59]), "+f"(d[60]), "+f"(d[61]), "+f"(d[62]), "+f"(d[63])
        : "l"(da), "l"(db), "r"(acc), "n"(TB));
}
template <int TB>
__device__ __forceinline__ void wgmma_ss128_init(float (&d)[64], uint64_t da, uint64_t db) {
    asm volatile("{\n.reg .pred p;\nsetp.ne.b32 p, 0, 0;\n"
        "wgmma.mma_async.sync.aligned.m64n128k16.f32.bf16.bf16 {%0, %1, %2, %3, %4, %5, %6, %7, %8, %9, %10, %11, %12, %13, %14, %15, %16, %17, %18, %19, %20, %21, %22, %23, %24, %25, %26, %27, %28, %29, %30, %31, %32, %33, %34, %35, %36, %37, %38, %39, %40, %41, %42, %43, %44, %45, %46, %47, %48, %49, %50, %51, %52, %53, %54, %55, %56, %57, %58, %59, %60, %61, %62, %63}, %64, %65, p, 1, 1, 0, %66;\n}"
        : "=f"(d[0]), "=f"(d[1]), "=f"(d[2]), "=f"(d[3]), "=f"(d[4]), "=f"(d[5]), "=f"(d[6]), "=f"(d[7]), "=f"(d[8]), "=f"(d[9]), "=f"(d[10]), "=f"(d[11]), "=f"(d[12]), "=f"(d[13]), "=f"(d[14]), "=f"(d[15]), "=f"(d[16]), "=f"(d[17]), "=f"(d[18]), "=f"(d[19]), "=f"(d[20]), "=f"(d[21]), "=f"(d[22]), "=f"(d[23]), "=f"(d[24]), "=f"(d[25]), "=f"(d[26]), "=f"(d[27]), "=f"(d[28]), "=f"(d[29]), "=f"(d[30]), "=f"(d[31]), "=f"(d[32]), "=f"(d[33]), "=f"(d[34]), "=f"(d[35]), "=f"(d[36]), "=f"(d[37]), "=f"(d[38]), "=f"(d[39]), "=f"(d[40]), "=f"(d[41]), "=f"(d[42]), "=f"(d[43]), "=f"(d[44]), "=f"(d[45]), "=f"(d[46]), "=f"(d[47]), "=f"(d[48]), "=f"(d[49]), "=f"(d[50]), "=f"(d[51]), "=f"(d[52]), "=f"(d[53]), "=f"(d[54]), "=f"(d[55]), "=f"(d[56]), "=f"(d[57]), "=f"(d[58]), "=f"(d[59]), "=f"(d[60]), "=f"(d[61]), "=f"(d[62]), "=f"(d[63])
        : "l"(da), "l"(db), "n"(TB));
}
template <int TB>
__device__ __forceinline__ void wgmma_ss64(float (&d)[32], uint64_t da, uint64_t db, int acc) {
    asm volatile("{\n.reg .pred p;\nsetp.ne.b32 p, %34, 0;\n"
        "wgmma.mma_async.sync.aligned.m64n64k16.f32.bf16.bf16 {%0, %1, %2, %3, %4, %5, %6, %7, %8, %9, %10, %11, %12, %13, %14, %15, %16, %17, %18, %19, %20, %21, %22, %23, %24, %25, %26, %27, %28, %29, %30, %31}, %32, %33, p, 1, 1, 0, %35;\n}"
        : "+f"(d[0]), "+f"(d[1]), "+f"(d[2]), "+f"(d[3]), "+f"(d[4]), "+f"(d[5]), "+f"(d[6]), "+f"(d[7]), "+f"(d[8]), "+f"(d[9]), "+f"(d[10]), "+f"(d[11]), "+f"(d[12]), "+f"(d[13]), "+f"(d[14]), "+f"(d[15]), "+f"(d[16]), "+f"(d[17]), "+f"(d[18]), "+f"(d[19]), "+f"(d[20]), "+f"(d[21]), "+f"(d[22]), "+f"(d[23]), "+f"(d[24]), "+f"(d[25]), "+f"(d[26]), "+f"(d[27]), "+f"(d[28]), "+f"(d[29]), "+f"(d[30]), "+f"(d[31])
        : "l"(da), "l"(db), "r"(acc), "n"(TB));
}
template <int TB>
__device__ __forceinline__ void wgmma_ss64_init(float (&d)[32], uint64_t da, uint64_t db) {
    asm volatile("{\n.reg .pred p;\nsetp.ne.b32 p, 0, 0;\n"
        "wgmma.mma_async.sync.aligned.m64n64k16.f32.bf16.bf16 {%0, %1, %2, %3, %4, %5, %6, %7, %8, %9, %10, %11, %12, %13, %14, %15, %16, %17, %18, %19, %20, %21, %22, %23, %24, %25, %26, %27, %28, %29, %30, %31}, %32, %33, p, 1, 1, 0, %34;\n}"
        : "=f"(d[0]), "=f"(d[1]), "=f"(d[2]), "=f"(d[3]), "=f"(d[4]), "=f"(d[5]), "=f"(d[6]), "=f"(d[7]), "=f"(d[8]), "=f"(d[9]), "=f"(d[10]), "=f"(d[11]), "=f"(d[12]), "=f"(d[13]), "=f"(d[14]), "=f"(d[15]), "=f"(d[16]), "=f"(d[17]), "=f"(d[18]), "=f"(d[19]), "=f"(d[20]), "=f"(d[21]), "=f"(d[22]), "=f"(d[23]), "=f"(d[24]), "=f"(d[25]), "=f"(d[26]), "=f"(d[27]), "=f"(d[28]), "=f"(d[29]), "=f"(d[30]), "=f"(d[31])
        : "l"(da), "l"(db), "n"(TB));
}
__device__ __forceinline__ void wgmma_rs128(float (&d)[64], uint32_t a0, uint32_t a1, uint32_t a2, uint32_t a3, uint64_t db, int acc) {
    asm volatile("{\n.reg .pred p;\nsetp.ne.b32 p, %69, 0;\n"
        "wgmma.mma_async.sync.aligned.m64n128k16.f32.bf16.bf16 {%0, %1, %2, %3, %4, %5, %6, %7, %8, %9, %10, %11, %12, %13, %14, %15, %16, %17, %18, %19, %20, %21, %22, %23, %24, %25, %26, %27, %28, %29, %30, %31, %32, %33, %34, %35, %36, %37, %38, %39, %40, %41, %42, %43, %44, %45, %46, %47, %48, %49, %50, %51, %52, %53, %54, %55, %56, %57, %58, %59, %60, %61, %62, %63}, {%64, %65, %66, %67}, %68, p, 1, 1, 1;\n}"
        : "+f"(d[0]), "+f"(d[1]), "+f"(d[2]), "+f"(d[3]), "+f"(d[4]), "+f"(d[5]), "+f"(d[6]), "+f"(d[7]), "+f"(d[8]), "+f"(d[9]), "+f"(d[10]), "+f"(d[11]), "+f"(d[12]), "+f"(d[13]), "+f"(d[14]), "+f"(d[15]), "+f"(d[16]), "+f"(d[17]), "+f"(d[18]), "+f"(d[19]), "+f"(d[20]), "+f"(d[21]), "+f"(d[22]), "+f"(d[23]), "+f"(d[24]), "+f"(d[25]), "+f"(d[26]), "+f"(d[27]), "+f"(d[28]), "+f"(d[29]), "+f"(d[30]), "+f"(d[31]), "+f"(d[32]), "+f"(d[33]), "+f"(d[34]), "+f"(d[35]), "+f"(d[36]), "+f"(d[37]), "+f"(d[38]), "+f"(d[39]), "+f"(d[40]), "+f"(d[41]), "+f"(d[42]), "+f"(d[43]), "+f"(d[44]), "+f"(d[45]), "+f"(d[46]), "+f"(d[47]), "+f"(d[48]), "+f"(d[49]), "+f"(d[50]), "+f"(d[51]), "+f"(d[52]), "+f"(d[53]), "+f"(d[54]), "+f"(d[55]), "+f"(d[56]), "+f"(d[57]), "+f"(d[58]), "+f"(d[59]), "+f"(d[60]), "+f"(d[61]), "+f"(d[62]), "+f"(d[63])
        : "r"(a0), "r"(a1), "r"(a2), "r"(a3), "l"(db), "r"(acc));
}

__device__ __forceinline__ uint32_t pack2(float lo, float hi) {
    uint32_t r;
    asm("cvt.rn.bf16x2.f32 %0, %1, %2;" : "=r"(r) : "f"(hi), "f"(lo));
    return r;
}
__device__ __forceinline__ float bf_lo(uint32_t v) { return __uint_as_float(v << 16); }
__device__ __forceinline__ float bf_hi(uint32_t v) { return __uint_as_float(v & 0xffff0000u); }
__device__ __forceinline__ float rbf(float v) { return bf_lo(pack2(v, v)); }
__device__ __forceinline__ uint32_t badd(uint32_t a, uint32_t b) {
    uint32_t r;
    asm("add.rn.bf16x2 %0, %1, %2;" : "=r"(r) : "r"(a), "r"(b));
    return r;
}
__device__ __forceinline__ uint32_t bsub(uint32_t a, uint32_t b) {
    uint32_t r;
    asm("sub.rn.bf16x2 %0, %1, %2;" : "=r"(r) : "r"(a), "r"(b));
    return r;
}
__device__ __forceinline__ uint32_t bmul(uint32_t a, uint32_t b) {
    uint32_t r;
    asm("mul.rn.bf16x2 %0, %1, %2;" : "=r"(r) : "r"(a), "r"(b));
    return r;
}
__device__ __forceinline__ uint32_t ln_apply(uint32_t x, uint32_t mb, float rs, uint32_t scale, uint32_t shift) {
    const uint32_t d = bsub(x, mb);
    return badd(bmul(pack2(bf_lo(d) * rs, bf_hi(d) * rs), scale), shift);
}
__device__ __forceinline__ float ex2(float v) {
    float r;
    asm("ex2.approx.ftz.f32 %0, %1;" : "=f"(r) : "f"(v));
    return r;
}
__device__ __forceinline__ float rcp(float v) {
    float r;
    asm("rcp.approx.ftz.f32 %0, %1;" : "=f"(r) : "f"(v));
    return r;
}
__device__ __forceinline__ float sqrt_fast(float v) {
    float r;
    asm("sqrt.approx.ftz.f32 %0, %1;" : "=f"(r) : "f"(v));
    return r;
}
__device__ __forceinline__ float ln_rstd(float var) { return rcp(rbf(sqrt_fast(rbf(rbf(var) + 1e-5f)))); }
__device__ __forceinline__ float sigmoid(float v) { return rcp(1.f + ex2(-1.4426950408889634f * v)); }
__device__ __forceinline__ float quad_sum(float v) {
    v += __shfl_xor_sync(0xffffffffu, v, 1);
    return v + __shfl_xor_sync(0xffffffffu, v, 2);
}

constexpr uint32_t HI_128 = 0x40000040u, HI_IMG = 0x80000080u, HI_Q = 0x80000040u;
template <int M, int RH>
__device__ __forceinline__ uint4 img_pack(const float (&d)[64], float s) {
    uint4 v;
    v.x = pack2(d[16 * M + 2 * RH] * s, d[16 * M + 2 * RH + 1] * s);
    v.y = pack2(d[16 * M + 4 + 2 * RH] * s, d[16 * M + 5 + 2 * RH] * s);
    v.z = pack2(d[16 * M + 8 + 2 * RH] * s, d[16 * M + 9 + 2 * RH] * s);
    v.w = pack2(d[16 * M + 12 + 2 * RH] * s, d[16 * M + 13 + 2 * RH] * s);
    return v;
}
template <int M>
__device__ __forceinline__ void img_store_global(uint32_t img, uint32_t toff, const float (&d)[64], float s0, float s1) {
    uint4* p = reinterpret_cast<uint4*>(g_img + (img + toff)) + M * 32;
    p[0] = img_pack<M, 0>(d, s0);
    p[128] = img_pack<M, 1>(d, s1);
}
__device__ __forceinline__ void sts128(uint32_t a, uint4 v) {
    asm volatile("st.shared.v4.b32 [%0], {%1, %2, %3, %4};" ::"r"(a), "r"(v.x), "r"(v.y), "r"(v.z), "r"(v.w) : "memory");
}
constexpr float SM_C = 0.08838834764831845f * 1.4426950408889634f;
__device__ __forceinline__ float pack2f(float lo, float hi) {
    float r;
    asm("{\n.reg .b32 t;\ncvt.rn.bf16x2.f32 t, %1, %2;\nmov.b32 %0, t;\n}" : "=f"(r) : "f"(hi), "f"(lo));
    return r;
}
template <int M, bool SCALE, bool PARK>
__device__ __forceinline__ void pack_group(float (&d)[64], float (&v)[8], float s0, float s1) {
#pragma unroll
    for (int i = 0; i < 8; i++) {
        const int k = 16 * M + 4 * (i & 3) + 2 * (i >> 2);
        v[i] = SCALE ? pack2f(d[k] * (i < 4 ? s0 : s1), d[k + 1] * (i < 4 ? s0 : s1)) : pack2f(d[k], d[k + 1]);
        if (PARK && M > 0) d[16 * (M > 0 ? M - 1 : 0) + i] = v[i];
    }
}
__device__ __forceinline__ uint32_t q_off(uint32_t toff) {
    asm volatile("" : "+r"(toff));
    return (((toff >> 1) & ~2047u) ^ 8192) + (toff & 511);
}
template <int M>
__device__ __forceinline__ void ctx_store_part(float4* p, float (&d)[64], float i0, float i1) {
    float v[8];
    pack_group<M, true, true>(d, v, i0, i1);
    p[M * 32] = make_float4(v[0], v[1], v[2], v[3]);
    p[M * 32 + 128] = make_float4(v[4], v[5], v[6], v[7]);
}
__device__ __forceinline__ void ctx_store(uint32_t img, uint32_t toff, float (&o)[64], float i0, float i1) {
    asm volatile("" : "+r"(toff));
    float4* p = reinterpret_cast<float4*>(g_img + (img + toff));
    ctx_store_part<0>(p, o, i0, i1); ctx_store_part<1>(p, o, i0, i1); ctx_store_part<2>(p, o, i0, i1); ctx_store_part<3>(p, o, i0, i1);
}

__device__ __forceinline__ void slot_wait(uint32_t bars, uint32_t& ph, uint32_t slot) {
    mbar_wait(bars + 8 * slot, (ph >> slot) & 1);
    ph ^= 1u << slot;
}
__device__ __forceinline__ void release_if(uint32_t eb, uint32_t slot, bool on) {
    asm volatile("{\n.reg .pred p;\nsetp.ne.s32 p, %1, 0;\n@p mbarrier.arrive.shared::cluster.b64 _, [%0];\n}" ::"r"(eb + 8 * slot), "r"((int)on) : "memory");
}
__device__ __forceinline__ void slot_expect(uint32_t sb, uint32_t slot) {
    asm volatile("{\n.reg .pred p;\nelect.sync _|p, 0xffffffff;\n@p mbarrier.arrive.expect_tx.shared::cta.b64 _, [%0], 32768;\n}"
                 ::"r"(sb + BAR_FULL + 8 * slot) : "memory");
}
__device__ __forceinline__ void slot_acquire(uint32_t sb, uint32_t& ph, uint32_t slot) {
    slot_wait(sb + BAR_EMPTY, ph, slot);
    slot_expect(sb, slot);
}
__device__ __forceinline__ void load_bulk(uint32_t sb, uint32_t slot, uint32_t off, const void* src, uint32_t bytes, bool both, bool first) {
    if (both)
        asm volatile("{\n.reg .pred p;\nelect.sync _|p, 0xffffffff;\n"
                     "@p cp.async.bulk.shared::cluster.global.mbarrier::complete_tx::bytes.multicast::cluster.L2::cache_hint [%0], [%1], %5, [%2], %4, %3;\n}"
                     ::"r"(sb + slot * SLOT + off), "l"(src), "r"(sb + BAR_FULL + 8 * slot), "l"(first ? L2_FIRST : L2_NORMAL), "h"((uint16_t)3),
                     "r"(bytes) : "memory");
    else
        asm volatile("{\n.reg .pred p;\nelect.sync _|p, 0xffffffff;\n"
                     "@p cp.async.bulk.shared::cluster.global.mbarrier::complete_tx::bytes.L2::cache_hint [%0], [%1], %4, [%2], %3;\n}"
                     ::"r"(sb + slot * SLOT + off), "l"(src), "r"(sb + BAR_FULL + 8 * slot), "l"(first ? L2_FIRST : L2_NORMAL), "r"(bytes) : "memory");
}
__device__ __forceinline__ void load_tile(uint32_t sb, uint32_t slot, uint32_t off, const CUtensorMap* m, int row, int cb, bool both, bool first) {
    if (both)
        asm volatile("{\n.reg .pred p;\nelect.sync _|p, 0xffffffff;\n"
                     "@p cp.async.bulk.tensor.3d.shared::cluster.global.mbarrier::complete_tx::bytes.multicast::cluster.L2::cache_hint [%0], [%1, {%3, %4, %5}], [%2], %7, %6;\n}"
                     ::"r"(sb + slot * SLOT + off), "l"(m), "r"(sb + BAR_FULL + 8 * slot), "r"(0), "r"(row), "r"(cb),
                     "l"(first ? L2_FIRST : L2_NORMAL), "h"((uint16_t)3) : "memory");
    else
        asm volatile("{\n.reg .pred p;\nelect.sync _|p, 0xffffffff;\n"
                     "@p cp.async.bulk.tensor.3d.shared::cluster.global.mbarrier::complete_tx::bytes.L2::cache_hint [%0], [%1, {%3, %4, %5}], [%2], %6;\n}"
                     ::"r"(sb + slot * SLOT + off), "l"(m), "r"(sb + BAR_FULL + 8 * slot), "r"(0), "r"(row), "r"(cb),
                     "l"(first ? L2_FIRST : L2_NORMAL) : "memory");
}
__device__ __forceinline__ uint32_t ring_next(uint32_t r) { return r == 4 ? 0 : r + 1; }
__device__ __forceinline__ uint32_t w_table(int hp) { return hp ? 0x3104u : 0x4210u; }
__device__ __forceinline__ uint32_t a_table(int hp) { return hp ? 0x625u : 0x635u; }
__device__ __forceinline__ uint32_t a_next(uint32_t& t) {
    const uint32_t s = t & 15;
    t = (t >> 4) | (s << 8);
    return s;
}
constexpr uint32_t O_TABLE = 0x1604235u;
constexpr uint32_t SL_X = OFF == 0 ? 4 : OFF == 1 ? 3 : 1, SL_WD = OFF == 0 ? 6 : OFF == 1 ? 4 : 3, SL_WF = OFF == 0 ? 5 : OFF == 1 ? 6 : 4;
__device__ __forceinline__ uint32_t o_next(uint32_t& t) {
    const uint32_t s = t & 15;
    t = (t >> 4) | (s << 24);
    return s;
}
__device__ __forceinline__ int o_head(int i, int kh) { return i < 16 ? 4 * (i & 7) + 2 * (kh ^ 1) + (i >> 3) : 29 + 2 * kh; }

template <bool INIT>
__device__ __forceinline__ void gemm_issue(float (&d)[64], uint32_t a, uint32_t b, int acc, bool img) {
    uint64_t da = desc64(a, img ? HI_IMG : HI_128), db = desc64(b, HI_128);
    wg_fence();
#pragma unroll
    for (int k = 0; k < 8; k++) {
        if (INIT && k == 0) wgmma_ss128_init<1>(d, da, db);
        else wgmma_ss128<1>(d, da, db, k ? 1 : acc);
        desc_add(da, !(k & 1) ? 2 : img ? 30 : k == 3 ? 1018 : 2);
        desc_add(db, 128);
    }
    wg_commit();
}

__device__ __forceinline__ void step_retire(uint32_t eb, bool rel, uint32_t pend) {
    wg_wait<0>();
    release_if(eb, pend & 7, rel && (pend & 7) != 7);
    release_if(eb, pend >> 4, rel && pend < 0x70);
}
template <bool ODD>
__device__ __forceinline__ void proj_tile(float (&acc)[64], float (&prev)[64], int t, int q0, uint32_t sb, int wg, uint32_t eb, bool rel, uint32_t& fph,
                                          uint32_t wtab, uint32_t& atab, uint32_t& pend, uint32_t prev_img, uint32_t toff, float s0, float s1,
                                          uint32_t (&v)[32]) {
    const uint32_t a0 = desc_k(sb + (wg ^ (ODD && t == 5)) * 8192), b0 = desc_mn(sb);
    int q = q0;
#pragma unroll 1
    do {
        const uint32_t ws = (wtab >> (4 * q)) & 15, as = a_next(atab);
        if (!ODD && t != 2) slot_wait(sb + BAR_FULL, fph, ws);
        slot_wait(sb + BAR_FULL, fph, as);
        step_retire(eb, rel, pend);
        if (ODD && q == 2 && t == 5) {
            const uint32_t a = sb + 5 * SLOT + q_off(toff);
#pragma unroll
            for (int i = 0; i < 8; i++) sts128(a + (i >> 2) * 16384 + (i & 2) * 256 + (i & 1) * 1024, make_uint4(v[4 * i], v[4 * i + 1], v[4 * i + 2], v[4 * i + 3]));
        }
        bar_sync(1 + wg, 256);
        gemm_issue<false>(acc, a0 + as * (SLOT / 16), b0 + ws * (SLOT / 16), q, false);
        bar_arrive(2 - wg, 256);
        pend = (ODD && q == 1 && t == 5 ? 7 : as) | (ODD && t != 1 ? ws : 7) << 4;
        wg_wait<1>();
        reg_fence(prev);
        if (ODD && t == 5) {
            if (q == 0) {
#pragma unroll
                for (int i = 0; i < 32; i++) {
                    const int k = 16 * (i >> 3) + 4 * (i & 3) + ((i >> 1) & 2);
                    v[i] = pack2(prev[k], prev[k + 1]);
                }
            }
        } else {
            if (q == 0) img_store_global<0>(prev_img, toff, prev, s0, s1);
            if (q == 1) img_store_global<1>(prev_img, toff, prev, s0, s1);
            if (q == 2) img_store_global<2>(prev_img, toff, prev, s0, s1);
            if (q == 3) img_store_global<3>(prev_img, toff, prev, s0, s1);
        }
    } while (++q < (ODD && t == 5 ? 3 : 4));
}

__device__ __forceinline__ void qk_issue(float (&s)[64], uint32_t q, uint32_t k) {
    wg_fence();
    uint64_t da = desc64(q, HI_Q), db = desc64(k, HI_IMG);
    wgmma_ss128_init<0>(s, da, db);
#pragma unroll
    for (int i = 1; i < 8; i++) {
        desc_add(da, (i & 1) ? 2 : i == 4 ? 990 : 30);
        desc_add(db, (i & 1) ? 2 : 30);
        wgmma_ss128<0>(s, da, db, 1);
    }
    wg_commit();
}
__device__ __forceinline__ void qk_issue(float (&s)[32], uint32_t q, uint32_t k) {
    wg_fence();
    uint64_t da = desc64(q, HI_Q), db = desc64(k, HI_IMG);
    wgmma_ss64_init<0>(s, da, db);
#pragma unroll
    for (int i = 1; i < 8; i++) {
        desc_add(da, (i & 1) ? 2 : i == 4 ? 990 : 30);
        desc_add(db, (i & 1) ? 2 : 30);
        wgmma_ss64<0>(s, da, db, 1);
    }
    wg_commit();
}
__device__ __forceinline__ void pv_issue(float (&o)[64], const uint32_t (&p)[32], uint32_t v, int acc, bool half) {
    uint64_t db = desc64(v, HI_IMG);
    if (half) {
        asm volatile("// half" ::: "memory");
        wg_fence();
#pragma unroll
        for (int i = 0; i < 4; i++) {
            wgmma_rs128(o, p[4 * i], p[4 * i + 1], p[4 * i + 2], p[4 * i + 3], db, i ? 1 : acc);
            desc_add(db, 256);
        }
        wg_commit();
        asm volatile("// half" ::: "memory");
    } else {
        wg_fence();
#pragma unroll
        for (int i = 0; i < 8; i++) {
            wgmma_rs128(o, p[4 * i], p[4 * i + 1], p[4 * i + 2], p[4 * i + 3], db, i ? 1 : acc);
            desc_add(db, 256);
        }
        wg_commit();
    }
}
__device__ __forceinline__ void tri_mask(float (&s)[64], float x) {
#pragma unroll
    for (int k = 0; k < 16; k++) {
        float b;
        asm("sub.sat.f32 %0, %1, %2;" : "=f"(b) : "f"((float)(8 * (k >> 1) + (k & 1))), "f"(x));
        const int i = 32 + 4 * (k >> 1) + (k & 1);
        asm("fma.rn.f32 %0, %1, 0fFF61B1E6, %0;" : "+f"(s[i]) : "f"(b));
        if (k < 14) asm("fma.rn.f32 %0, %1, 0fFF61B1E6, %0;" : "+f"(s[i + 6]) : "f"(b));
    }
}
__device__ __forceinline__ void tri_mask_copy(float (&s)[64], const float (&h)[32], float x) {
#pragma unroll
    for (int i = 0; i < 32; i++) {
            asm("{\n.reg .pred p;\nsetp.lt.f32 p, %2, %3;\nselp.f32 %0, 0fFF800000, %1, p;\n}"
                : "=f"(s[i]) : "f"(h[i]), "f"(x), "f"((float)(8 * (i >> 2) - 4 * (i & 2) + (i & 1))));
        s[32 + i] = __uint_as_float(0xff800000u);
    }
}
constexpr float SM_HI = 1152921504606846976.f, SM_LO = 1.f / 1152921504606846976.f;
__device__ __forceinline__ bool softmax_unsafe(float t0, float t1, bool first) {
    bool bad = __any_sync(0xffffffffu, fmaxf(t0, t1) > SM_HI);
    if (first) {
        uint32_t a = __ballot_sync(0xffffffffu, t0 >= SM_LO), b = __ballot_sync(0xffffffffu, t1 >= SM_LO);
        a |= a >> 1;
        b |= b >> 1;
        bad |= ((a | (a >> 2)) & (b | (b >> 2)) & 0x11111111u) != 0x11111111u;
    }
    return bad;
}
__device__ __forceinline__ void softmax_remax(const float (&s)[64], float (&m)[2], bool first, float& m0, float& m1, float& a0, float& a1) {
    m0 = fmaxf(s[0], s[1]), m1 = fmaxf(s[2], s[3]);
#pragma unroll
    for (int k = 1; k < 16; k++) {
        m0 = fmaxf(m0, fmaxf(s[4 * k], s[4 * k + 1]));
        m1 = fmaxf(m1, fmaxf(s[4 * k + 2], s[4 * k + 3]));
    }
    m0 = fmaxf(m0, __shfl_xor_sync(0xffffffffu, m0, 1));
    m1 = fmaxf(m1, __shfl_xor_sync(0xffffffffu, m1, 1));
    m0 = fmaxf(m0, __shfl_xor_sync(0xffffffffu, m0, 2));
    m1 = fmaxf(m1, __shfl_xor_sync(0xffffffffu, m1, 2));
    if (!first) {
        m0 = fmaxf(m0, 0.f);
        m1 = fmaxf(m1, 0.f);
    }
    a0 = first ? 1.f : ex2(-m0);
    a1 = first ? 1.f : ex2(-m1);
    m[0] += m0;
    m[1] += m1;
}
template <int J0, int J1>
__device__ __forceinline__ void softmax_exp(const float (&s)[64], uint32_t (&p)[32], float (&t)[4]) {
#pragma unroll
    for (int k = J0; k < J1; k++) {
        const float e0 = ex2(s[4 * k]), e1 = ex2(s[4 * k + 1]), e2 = ex2(s[4 * k + 2]), e3 = ex2(s[4 * k + 3]);
        if (k == 0) { t[0] = e0; t[1] = e1; t[2] = e2; t[3] = e3; }
        else { t[0] += e0; t[1] += e1; t[2] += e2; t[3] += e3; }
        p[2 * k] = pack2(e0, e1);
        p[2 * k + 1] = pack2(e2, e3);
    }
}
__device__ __forceinline__ void mma16816(float (&d)[4], const uint32_t* a, uint32_t b0, uint32_t b1) {
    asm("mma.sync.aligned.m16n8k16.row.col.f32.bf16.bf16.f32 {%0, %1, %2, %3}, {%4, %5, %6, %7}, {%8, %9}, {%0, %1, %2, %3};"
        : "+f"(d[0]), "+f"(d[1]), "+f"(d[2]), "+f"(d[3]) : "r"(a[0]), "r"(a[1]), "r"(a[2]), "r"(a[3]), "r"(b0), "r"(b1));
}
__device__ __forceinline__ uint32_t best_key(const uint32_t* keys, int lane, uint32_t ep) {
#pragma unroll 1
    for (;;) {
        const uint4 k = ld_poll(reinterpret_cast<const uint4*>(keys) + lane);
        const int n = __popc(__ballot_sync(0xffffffffu, (((k.x ^ ep) | (k.y ^ ep) | (k.z ^ ep) | (k.w ^ ep)) & 31) == 0));
        if (poll_done(n == 32, n < KN ? KSLEEP : KSLEEP2)) return __reduce_max_sync(0xffffffffu, max(max(k.x, k.y), max(k.z, k.w)));
    }
}

__global__ void __cluster_dims__(2, 1, 1) __launch_bounds__(384, 1)
fused_kernel(const __grid_constant__ CUtensorMap tm_ckv, const __grid_constant__ CUtensorMap tm_wq,
             const __grid_constant__ CUtensorMap tm_wuk, const __grid_constant__ CUtensorMap tm_wuv,
             const __grid_constant__ CUtensorMap tm_wo, const __grid_constant__ CUtensorMap tm_wg,
             const __grid_constant__ CUtensorMap tm_wu,
             const __grid_constant__ CUtensorMap tm_wm, const __grid_constant__ CUtensorMap tm_x, const Params P) {
    extern __shared__ __align__(1024) uint8_t smem[];
    if (threadIdx.x == 352) {
        asm volatile("prefetch.tensormap [%0];" ::"l"(&tm_ckv) : "memory");
        asm volatile("prefetch.tensormap [%0];" ::"l"(blockIdx.x >= NCTA ? &tm_wm : (blockIdx.x & 1) ? &tm_wuv : &tm_wuk) : "memory");
    }
    const uint32_t sb = (uint32_t)__cvta_generic_to_shared(smem);
    const int tid = threadIdx.x, lane = tid & 31, warp = __shfl_sync(0xffffffffu, tid >> 5, 0), wg = warp >> 2;
    const uint32_t sm = blockIdx.x < 8 ? blockIdx.x + 124 : blockIdx.x - 8, smq = ((sm - 64) * 147) >> 11;
    const int rb = sm < 64 ? (sm & 14) * 8 + (sm >> 4) * 2 + (sm & 1)
                 : sm < 120 ? ((sm - 64 - smq * 14) & 14) * 8 + 24 + smq * 2 + (sm & 1) : sm < 124 ? sm + 8 : sm - 116;
    const int grp = rb >> 3, j = rb & 7, kh = (grp >> 1) & 1;
    const int cq = (j & 1) + ((grp >> 1) & 2), ort = (grp & 8) + (grp & 1) * 4 + (j >> 1);
    if (warp == 0) TS(0);

    const CUtensorMap* tw = (j & 1) ? &tm_wuv : &tm_wuk;
    if (lane == 0) {
        if (warp == 8) {
#pragma unroll
            for (int i = 0; i < 7; i++) mbar_init(sb + BAR_FULL + 8 * i, 1);
            fence_async_smem();
        } else if (warp < 11) {
            const int w = warp - (warp > 8);
            const u64 cnt = (w < 5 ? (rb < NCTA ? 0x888888884444444ull : 0x888888888888888ull) : 0x111812111111118ull) >> (12 * (w % 5));
#pragma unroll
            for (int i = 0; i < 3; i++) mbar_init(sb + BAR_EMPTY + 24 * w + 8 * i, ((uint32_t)cnt >> (4 * i)) & 15);
        }
        asm volatile("fence.mbarrier_init.release.cluster;" ::: "memory");
    }
    __syncwarp();
    asm volatile("barrier.cluster.arrive.relaxed.aligned;" ::: "memory");
    if (warp == 8) {
        if (rb < NCTA) {
#pragma unroll 1
            for (int u = 0; u < 4; u++) {
                const uint32_t ws = u + (u == 3), as = (0x635u >> (4 * u)) & 15;
                slot_expect(sb, ws);
                load_tile(sb, ws, 0, tw, u * 128, 4 * grp, false, HINT & 1);
                if (u == 3) break;
                slot_expect(sb, as);
                load_tile(sb, as, 0, &tm_ckv, (j >> 1) * 128, u * 2, false, false);
                load_tile(sb, as, 16384, &tm_ckv, (j >> 1) * 128, u * 2 + 1, false, false);
            }
        } else {
#pragma unroll 1
            for (int i = 0; i < 6; i++) {
                slot_expect(sb, i);
                load_tile(sb, i, 0, &tm_wm, i * 64, (rb - NCTA) * 4, false, HINT & 64);
                if (i > 3) tma3d_prefetch(&tm_wm, i * 64 + 128, (rb - NCTA) * 4);
            }
        }
    }
    asm volatile("barrier.cluster.wait.aligned;" ::: "memory");

    if (rb >= NCTA) {
        const int sp = rb - NCTA;
        const uint32_t ep = __ldcg(&g_sync.epoch[0]) + 1;
        uint32_t ph = 0, sl = 0;
        if (warp == 8) {
#pragma unroll 1
            for (int i = 6; i < 54 + 2 * OFF; i++) {
                slot_acquire(sb, ph, sl);
                const int k = i - 24;
                load_tile(sb, sl, 0, i < 24 ? &tm_wm : i >= 54 ? &tm_wo : (k & 2) ? &tm_wu : &tm_wg, i < 24 ? (i & 7) * 64 : i >= 54 ? (i - 38 - 2 * OFF) * 256 : (k & 1) * 256,
                          i < 24 ? (i >> 3) * 16 + sp * 4 : i >= 54 ? sp * 2 : sp * 7 + (k >> 2), false, true);
                if (++sl == 6) sl = 0;
                if (i == 51) { i = 53; sl = 0; }
            }
            bar_sync(4, 64);
            slot_wait(sb + BAR_EMPTY, ph, 4);
            slot_wait(sb + BAR_EMPTY, ph, 5);
            ph = 0x3f, sl = 0;
#pragma unroll 1
            for (int h = 0; h < 32; h++) {
                step_watch(sb + SM_EP + 16, h + 1);
                fence_async_global();
                const uint8_t* src = g_ctx + (size_t)(((h >> 1) ^ 8) * 32 + 30 - 4 * OFF) * SLOT + (h & 1) * 16384;
#pragma unroll 1
                for (int k = 0; k <= 2 * OFF; k++, src += 2 * SLOT) {
                    slot_wait(sb + BAR_DONE, ph, sl);
                    const uint32_t f = sb + BAR_FLAG + 8 * sl, d = sb + 4 * SLOT + sl * 16384;
                    asm volatile("{\n.reg .pred p;\nelect.sync _|p, 0xffffffff;\n@p mbarrier.arrive.expect_tx.shared::cta.b64 _, [%0], 16384;\n}" ::"r"(f) : "memory");
                    if (k == 0)
                        asm volatile("{\n.reg .pred p;\nelect.sync _|p, 0xffffffff;\n"
                                     "@p cp.async.bulk.tensor.3d.shared::cluster.global.mbarrier::complete_tx::bytes [%0], [%1, {%3, %4, %5}], [%2];\n}"
                                     ::"r"(d), "l"(&tm_x), "r"(f), "r"(0), "r"((h ^ 16) * 64), "r"(sp * 2) : "memory");
                    else
                        asm volatile("{\n.reg .pred p;\nelect.sync _|p, 0xffffffff;\n"
                                     "@p cp.async.bulk.shared::cluster.global.mbarrier::complete_tx::bytes [%0], [%1], 16384, [%2];\n}"
                                     ::"r"(d), "l"(src), "r"(f) : "memory");
                    if (++sl == 6) sl = 0;
                }
            }
        } else if (warp == 9) {
#pragma unroll 1
            for (int t = 0; t <= 16; t++) {
                asm volatile("st.release.cta.shared.u32 [%0], %1;" ::"r"(sb + SM_EP + 16), "r"(2 * t) : "memory");
                if (t == 0) bar_sync(4, 64);
                if (lane < 4 && t < 16) flag_wait(&g_sync.ctxcnt[(t ^ 8) * 32 + 24 + 2 * lane], ep);
                __syncwarp();
            }
        } else if (warp < 8) {
            const uint32_t c2 = __ldg(reinterpret_cast<const uint32_t*>(P.c) + tid);
            uint32_t* sc = reinterpret_cast<uint32_t*>(smem + SM_TAB);
            sc[tid] = pack2(bf_lo(c2) * sigmoid(bf_lo(c2)), bf_hi(c2) * sigmoid(bf_hi(c2)));
            bar_sync(1, 256);
            const uint32_t a = sb + (warp >> 1) * 8192 + ((lane >> 4) * 8 + (lane & 7)) * 128, ch = (warp & 1) * 4 + ((lane >> 3) & 1);
#pragma unroll 1
            for (int ps = 0; ps < 3; ps++) {
                float d[2][4] = {};
#pragma unroll 1
                for (int bt = 0; bt < 8; bt++) {
                    slot_wait(sb + BAR_FULL, ph, sl);
#pragma unroll
                    for (int i = 0; i < 8; i++) {
                        uint32_t w[4];
                        asm volatile("ldmatrix.sync.aligned.m8n8.x4.trans.shared.b16 {%0, %1, %2, %3}, [%4];" : "=r"(w[0]), "=r"(w[1]), "=r"(w[2]), "=r"(w[3])
                                     : "r"(a + sl * SLOT + (i >> 1) * 2048 + (((ch + 2 * (i & 1)) ^ (lane & 7)) << 4)) : "memory");
                        mma16816(d[i & 1], w, sc[bt * 32 + (i >> 1) * 8 + (lane & 3)], sc[bt * 32 + (i >> 1) * 8 + 4 + (lane & 3)]);
                    }
                    __syncwarp();
                    mbar_arrive_if(sb + BAR_EMPTY + 8 * sl, lane == 0);
                    if (++sl == 6) sl = 0;
                }
                const float v = (lane & 2) ? ((lane & 1) ? d[1][2] : d[1][0]) : ((lane & 1) ? d[0][2] : d[0][0]);
                const int col = sp * 256 + warp * 32 + (lane & 3) * 8 + (lane >> 2);
                if (ps == 0) st_pub(g_mod1 + col, (pack2(0.f, v) & 0xffff0000u) | (ep & 0xffffu), true);
                else g_mod[ps * 1024 + col] = __float2bfloat16_rn(v);
                if (warp == 0) TS(1 + ps);
            }
#pragma unroll 1
            for (int k = 0; k < 28; k++) {
                slot_wait(sb + BAR_FULL, ph, sl);
                uint4* dst = reinterpret_cast<uint4*>(g_wf) + (sp * 28 + (k & ~3)) * 2048 + (k & 3) * 512 + tid;
#pragma unroll 4
                for (int i = 0; i < 8; i++) {
                    const int row = (i & 1) * 128 + (tid >> 1);
                    __stcs(dst + (i >> 1) * 2048 + (i & 1) * 256, lds128(sb + sl * SLOT + row * 128 + ((((i & 6) + ((tid ^ (row >> 2)) & 1)) ^ (row & 7)) << 4)));
                }
                __syncwarp();
                mbar_arrive_if(sb + BAR_EMPTY + 8 * sl, lane == 0);
                if (++sl == 6) sl = 0;
            }
            bar_sync(1, 256);
            if (tid < 2) {
                flag_add(&g_sync.cnt[7 * 8]);
                flag_wait(&g_sync.cnt[7 * 8], 8 * ep);
            }
            if (warp == 0) TS(4);
            bar_sync(1, 256);
            uint32_t ga[16], x2[32];
#pragma unroll
            for (int i = 0; i < 16; i++) ga[i] = __ldcg(reinterpret_cast<const uint32_t*>(g_mod) + 512 + sp * 64 + (lane & 3) + 4 * i);
#pragma unroll 1
            for (int i = 0; i < 2 * OFF; i++) slot_wait(sb + BAR_FULL, ph, i);
            float d[64];
            uint32_t u = (2 * OFF + 1) * wg, up = 0;
            if (wg == 1) bar_arrive(2, 256);
#pragma unroll 1
            for (int h = wg; h < 32; h += 2) {
                mbar_wait(sb + BAR_FLAG + 8 * u, up);
                const uint32_t xa = sb + 4 * SLOT + u * 16384 + ((warp & 3) * 16 + (lane & 15)) * 128;
#pragma unroll
                for (int k = 0; k < 8; k++)
                    asm volatile("ldmatrix.sync.aligned.m8n8.x4.shared.b16 {%0, %1, %2, %3}, [%4];"
                                 : "=r"(x2[4 * k]), "=r"(x2[4 * k + 1]), "=r"(x2[4 * k + 2]), "=r"(x2[4 * k + 3])
                                 : "r"(xa + (k >> 2) * 8192 + (((2 * (k & 3) + (lane >> 4)) ^ (lane & 7)) << 4)) : "memory");
                mbar_arrive_if(sb + BAR_DONE + 8 * u, lane < 2);
                bar_sync(2 + wg, 256);
#pragma unroll 1
                for (int k = 0; k < 2 * OFF; k++) {
                    const uint32_t pu = u;
                    if (++u == 6) { u = 0; up ^= 1; }
                    mbar_wait(sb + BAR_FLAG + 8 * u, up);
                    gemm_issue<false>(d, desc_k(sb + 4 * SLOT) + u * 1024, desc_mn(sb) + k * (SLOT / 16), k, true);
                    wg_wait<1>();
                    mbar_arrive_if(sb + BAR_DONE + 8 * pu, lane < 2 && k);
                }
                if (h < 31) bar_arrive(3 - wg, 256);
                wg_wait<0>();
                reg_fence(d);
                mbar_arrive_if(sb + BAR_DONE + 8 * u, lane < 2);
                u += 2 * OFF + 2;
                if (u >= 6) { u -= 6; up ^= 1; }
                uint4* op = g_x2 + ((h ^ 16) * 4 + sp) * 1024 + (tid & 127);
#pragma unroll
                for (int v = 0; v < 8; v++) {
                    uint32_t y[4];
#pragma unroll
                    for (int i = 0; i < 4; i++) {
                        const int k = 4 * v + i;
                        y[i] = pack2(fmaf(bf_lo(ga[k >> 1]), d[2 * k], bf_lo(x2[k])), fmaf(bf_hi(ga[k >> 1]), d[2 * k + 1], bf_hi(x2[k])));
                    }
                    op[v * 128] = make_uint4(y[0], y[1], y[2], y[3]);
                }
            }
            bar_sync(1, 256);
            if (tid == 0) flag_add(&g_sync.cnt[15 * 8]);
            if (warp == 0) TS(5);
        }
        return;
    }

    if (wg == 2) {
        asm volatile("setmaxnreg.dec.sync.aligned.u32 40;");
        if (warp == 8) {
            const uint32_t rank = j & 1, half = rank * 16384;
            uint32_t eph = 0, r = 0;
            *reinterpret_cast<volatile uint32_t*>(smem + SM_EP + 20) = 0;
#pragma unroll 1
            for (int hp = 0; hp < 2; hp++) {
                uint32_t wtab = w_table(hp), atab = a_table(hp);
                const int hc = 4 * grp + 2 * hp;
#pragma unroll 1
                for (int u = 3 - 3 * hp; u < 16; u++) {
                    if (hp && u < 4) {
                        const uint32_t ws = (wtab >> (4 * u)) & 15;
                        slot_acquire(sb, eph, ws);
                        load_tile(sb, ws, 0, tw, u * 128, hc, false, HINT & 1);
                        PT();
                    }
                    if (hp == 1 && (u & 7) == 4) mbar_wait(sb + BAR_FLAG + 24 + (u & 8), 0);
                    const uint32_t as = a_next(atab);
                    slot_acquire(sb, eph, as);
                    load_tile(sb, as, half, &tm_ckv, ((u & 12) + (j >> 1)) * 128, (u & 3) * 2 + rank, true, (HINT & 8) && hp);
                    PT();
                    if (hp == 1 && (u | 2) == 3 && lane == 0)
                        asm volatile("red.relaxed.gpu.global.add.u32 [%0], 1;" ::"l"(&g_sync.cnt[(grp * 8 + 3 + (u >> 1)) * 8]) : "memory");
                }
                const uint8_t* src = g_h + (15 - j) * 4 * SLOT;
#pragma unroll 1
                for (int u = 0; u < 8; u++) {
                    if (u == 0 || u == KVG) {
                        mbar_wait(sb + BAR_FLAG + (u ? 8 + 32 * hp : 0), 0);
                        fence_async_global();
                    }
                    if (u < 4) {
                        const uint32_t ws = (wtab >> (4 * u)) & 15;
                        slot_acquire(sb, eph, ws);
                        load_tile(sb, ws, 0, &tm_wq, u * 128, hc, false, HINT & 1);
                        PT();
                    }
                    const uint32_t as = a_next(atab);
                    slot_acquire(sb, eph, as);
                    load_bulk(sb, as, 0, src, SLOT, false, (HINT & 8) && hp);
                    PT();
                    src += u == 3 ? (8 * j - 63) * SLOT : SLOT;
                }
                const int step = hp ? -2 * SLOT : 2 * SLOT;
                src = g_KV + (size_t)(grp * 32 + 30 * hp) * SLOT + half - step;
#pragma unroll 1
                for (int n = 0; n <= 17; n++) {
                    if (n == 8) {
                        mbar_wait(sb + BAR_FLAG + 16 + 32 * hp, 0);
                        fence_async_global();
                    }
                    const uint8_t* v = src + SLOT;
                    src += n < 16 - j ? step : n == 16 - j ? (2 * j - 15) * step : -step;
                    if (n < 17) {
                        slot_acquire(sb, eph, r);
                        if (n != 15 - (j & 6)) load_bulk(sb, r, half, src, SLOT / 2, true, HINT & 4);
                        else load_bulk(sb, r, 0, src - half, SLOT, false, HINT & 4);
                        PT();
                        r = ring_next(r);
                    }
                    if (n) {
                        slot_acquire(sb, eph, r);
                        if (n != 16 - (j & 6)) load_bulk(sb, r, half, v, SLOT / 2, true, HINT & 4);
                        else load_bulk(sb, r, 0, v - half, SLOT, false, HINT & 4);
                        PT();
                        r = ring_next(r);
                    }
                    asm volatile("st.volatile.shared.u32 [%0], %1;" ::"r"(sb + SM_EP + 16), "r"(18 * hp + n + 1) : "memory");
                }
            }
            uint32_t otab = O_TABLE, ready = 0;
#pragma unroll 1
            for (int i = 0; i < 17; i += i == 7 - OFF ? 1 + OFF : 1) {
                const bool dyn = i >= 8 && i < 15;
                const uint32_t want = dyn ? 15u << (4 * (i - 8)) : 1u << max(i + 14, 28);
                if (!(ready & want)) {
                    do {
                        asm volatile("ld.acquire.cta.shared.u32 %0, [%1];" : "=r"(ready) : "r"(sb + SM_EP + 20) : "memory");
                        ready = __shfl_sync(0xffffffffu, ready, 0);
                    } while (!(ready & want));
                    fence_async_global();
                }
                const int head = o_head(dyn ? (ready >> (4 * (i - 8))) & 15 : i, kh);
                const uint32_t as = o_next(otab), ws = o_next(otab), off = i < 15 ? half : kh * 16384;
                slot_acquire(sb, eph, as);
                load_bulk(sb, as, off, g_ctx + (size_t)(ort * 32 + head) * SLOT + off, SLOT / 2, i < 15, HINT & 16);
                if (i >= 15) load_bulk(sb, as, off ^ 16384, i == 15 ? g_x2 + ((ort * 2 + kh) * 4 + cq) * 1024 : reinterpret_cast<const uint4*>(P.wdown) + min(rb, NFFN - 1) * 1024, SLOT / 2, false, false);
                PT();
                slot_acquire(sb, eph, ws);
                load_tile(sb, ws, 0, &tm_wo, head * 128, cq * 2, false, HINT & 2);
                PT();
                if (i == 0) o_next(otab);
            }
            if (rb < NFFN) {
                slot_acquire(sb, eph, SL_WF);
                load_bulk(sb, SL_WF, 0, g_wf + rb * SLOT, SLOT, false, false);
            }
        } else if (warp == 9) {
            *reinterpret_cast<volatile uint32_t*>(smem + SM_EP + 16) = 0;
            l2_prefetch(P.ckv + rb * 2048, 4096);
            mbar_watch(sb + BAR_FULL, 0);
            l2_prefetch(P.ckv + 512 * 512 + rb * 2048, 4096);
            mbar_watch(sb + BAR_FULL + 8 * XPF, 0);
            l2_prefetch(P.x + rb * 8192, 16384);
            mbar_watch(sb + BAR_FULL + 8 * 4, 0);
            l2_prefetch(P.ckv + 1024 * 512 + rb * 4096, 8192);
            TS(40);
#pragma unroll 1
            for (int i = 0; i < 13; i++) {
                step_watch(sb + SM_EP + 16, i == 0 ? 0 : i < 5 ? PFA + i : 13 + PFB + i);
                if (i == 10) mbar_watch(sb + BAR_FLAG + 8 * 7, 0);
                const int rf = min(rb, NFFN - 1), pc = 4 * (i - 5) + cq;
                const uint8_t* p = i == 3 ? reinterpret_cast<const uint8_t*>(P.ckv) + rb * 16384
                                 : i == 4 ? g_h + rb * 16384
                                 : i < 8 ? g_ctx + (size_t)(ort * 32 + o_head(pc >> 1, kh)) * SLOT + (pc & 1) * 16384
                                 : i < 10 ? reinterpret_cast<const uint8_t*>(P.wo) + (grp * 16 + (i & 1) * 8 + j) * 16384
                                 : i == 10 ? reinterpret_cast<const uint8_t*>(P.wdown) + rf * 16384 : g_wf + rf * SLOT + (i & 1) * 16384;
                if (i >= 3) l2_prefetch(p, 16384);
                else if ((i | j) & 1) tma3d_prefetch(i == 1 ? tw : &tm_wq, (j >> 1) * 128, grp * 4 + (i ? 2 : 0));
            }
            const uint32_t v = lds32(sb + SM_EP) - 1;
            sts128(sb + SM_RED + lane * 16, make_uint4(v, v, v, v));
            fence_async_smem();
            __syncwarp();
#pragma unroll 1
            for (int i = 0; i < OB / 32; i++) bulk_store(g_out + rb * OB + i * 32, sb + SM_RED, 512, false);
            asm volatile("cp.async.bulk.commit_group;\ncp.async.bulk.wait_group 0;" ::: "memory");
            fence_async_global();
            __syncwarp();
            mbar_arrive_if(sb + BAR_PF, lane == 0);
            if (lane == 0) mbar_watch(sb + BAR_END, 0);
        } else {
            const uint32_t ep = __ldcg(&g_sync.epoch[0]) + 1;
            asm volatile("st.shared.u32 [%0], %1;" ::"r"(sb + SM_EP), "r"(ep) : "memory");
            mbar_wait(sb + BAR_FULL + 8 * 4, 0);
            {
                uint4 v[4];
                for (;;) {
                    uint32_t bad = 0;
#pragma unroll
                    for (int k = 0; k < 4; k++) v[k] = ld_poll(reinterpret_cast<const uint4*>(g_mod1) + (warp & 1) * 128 + k * 32 + lane);
#pragma unroll
                    for (int k = 0; k < 4; k++) bad |= (v[k].x ^ ep) | (v[k].y ^ ep) | (v[k].z ^ ep) | (v[k].w ^ ep);
                    if (poll_done((bad & 0xffff) == 0, 100)) break;
                }
                const uint32_t one = (warp & 1) ? ONE2 : 0x80008000u;
#pragma unroll
                for (int k = 0; k < 4; k++)
                    *reinterpret_cast<uint2*>(smem + SM_TAB + (warp & 1) * 1024 + k * 256 + lane * 8) =
                        make_uint2(badd(__byte_perm(v[k].x, v[k].y, 0x7632), one), badd(__byte_perm(v[k].z, v[k].w, 0x7632), one));
            }
            __syncwarp();
            mbar_arrive_if(sb + BAR_FLAG + 8 * 8, lane == 0);
            if (warp == 10) {
#pragma unroll 1
                for (int i = 0; i < 9; i++) {
                    mbar_sleep(sb + BAR_DONE + 8 * i);
                    if (lane == 0) flag_add(i && ((i - 1) & 2) ? &g_sync.ctxcnt[((i & 1) ? 15 - j : j) * 32 + 2 * grp + (i > 4)] : &g_sync.cnt[(grp * 8 + i) * 8]);
                    if (i == 0) TS(43);
                }
            } else {
                TS(42);
#pragma unroll 1
                for (int i = 0; i < 8; i++) {
                    mbar_sleep(sb + BAR_DONE + 8 * (i == 7 ? 6 : i == 4 ? 3 : i));
                    if (lane < 2) flag_wait(&g_sync.cnt[((i == 0 ? (lane ? j : 15 - j) : i == 7 ? 0 : grp) * 8 + i) * 8], 8 * ep);
                    __syncwarp();
                    mbar_arrive_if(sb + BAR_FLAG + 8 * i, lane == 0 && i < 7);
                    TS(48 + i);
                }
                const uint32_t *mp = reinterpret_cast<const uint32_t*>(g_mod) + lane, *wp = reinterpret_cast<const uint32_t*>(P.wr) + lane;
                float ra = 0.f, rs = 0.f;
#pragma unroll 1
                for (int k = 0; k < 256; k += 32) {
                    const uint32_t ga = __ldcg(mp + 512 + k), sh = __ldcg(mp + 768 + k), c1 = badd(__ldcg(mp + 1024 + k), ONE2);
                    const uint32_t gb = __ldcg(mp + 1280 + k), ww = __ldg(wp + k);
                    const uint32_t a = bmul(c1, ww);
                    ra += bf_lo(a) + bf_hi(a);
                    rs = fmaf(bf_lo(sh), bf_lo(ww), fmaf(bf_hi(sh), bf_hi(ww), rs));
                    if (k >> 6 == cq) {
                        sts128(sb + SM_TAB + ((k & 32) + lane) * 16, make_uint4(ga << 16, ga & 0xffff0000u, a, 0));
                        sts128(sb + SM_TAB + 1024 + ((k & 32) + lane) * 16, make_uint4(c1, sh, gb, 0));
                    }
                }
#pragma unroll 1
                for (int o = 16; o > 0; o >>= 1) {
                    ra += __shfl_xor_sync(0xffffffffu, ra, o);
                    rs += __shfl_xor_sync(0xffffffffu, rs, o);
                }
                *reinterpret_cast<float2*>(smem + SM_EP + 8) = make_float2(ra, rs);
                __syncwarp();
                mbar_arrive_if(sb + BAR_FLAG + 8 * 7, lane == 0);
                const uint32_t* f = lane < 17 ? &g_sync.ctxcnt[ort * 32 + o_head(lane, kh)] : &g_sync.cnt[15 * 8];
                uint32_t ready = -(j & 1), list = 0, sh = 0, qa;
                asm("mapa.shared::cluster.u32 %0, %1, %2;" : "=r"(qa) : "r"(sb + SM_EP + 20), "r"(lane & 1));
                while (ready != ~0u) {
                    uint32_t v;
                    asm volatile("ld.acquire.gpu.global.u32 %0, [%1];" : "=r"(v) : "l"(f) : "memory");
                    const uint32_t now = __ballot_sync(0xffffffffu, (int)(v - (lane < 17 ? ep : NSPARE * ep)) >= 0);
#pragma unroll 1
                    for (uint32_t fresh = now & ~ready & 0x7f00; fresh; fresh &= fresh - 1, sh += 4) list |= (__ffs(fresh) - 1) << sh;
                    list |= (((now & 0xff) + 1) >> 8 << 28) | ((now & (now >> 2) & 0x18000) << 14);
                    if (now != ready && lane < 2) asm volatile("st.relaxed.cluster.shared::cluster.u32 [%0], %1;" ::"r"(qa), "r"(list) : "memory");
                    if ((now & 0xff) == 0xff) mbar_sleep(sb + BAR_DONE + 8 * 7);
                    ready = now;
                    __nanosleep(POLL_NS);
                }
                TS(45);
            }
        }
    } else {
        const bool elected = (tid & 127) == 0, rel = (tid & 95) == 0;
        uint32_t eb;
        asm("mapa.shared::cluster.u32 %0, %1, %2;" : "=r"(eb) : "r"(sb + BAR_EMPTY), "r"(warp & 1));
        const int g = lane >> 2, c4 = lane & 3;
        uint32_t toff = warp * 4096 + g * 64 + ((c4 ^ (g >> 1)) << 4);
        uint32_t fph = 0x3f, r = 0;
        if (wg == 1) bar_arrive(1, 256);
        const uint32_t kd = desc_k(sb), wd = desc_mn(sb), vd = ((sb & 0x3ffff) >> 4) | (32u << 16);
        const int nL = 16 - j, hn = nL - 1 + wg;
        float s[64], o[64], li[2] = {0.f, 0.f};
        uint32_t cimg = 0;
        const float sc = (j & 1) ? 1.f : SM_C;
#pragma unroll 1
        for (int q = 0; q < 3; q++) {
            const uint32_t as = (0x635u >> (4 * q)) & 15;
            mbar_wait(sb + BAR_FULL + 8 * q, 0);
            mbar_wait(sb + BAR_FULL + 8 * as, 0);
            bar_sync(1 + wg, 256);
            gemm_issue<false>(s, kd + wg * 512 + as * (SLOT / 16), wd + q * (SLOT / 16), q, false);
            bar_arrive(2 - wg, 256);
            wg_wait<0>();
            release_if(eb, as, rel);
        }
        {
            const int xrow = rb * 16 + warp * 2;
            const uint4* xp = reinterpret_cast<const uint4*>(P.x) + xrow * 64;
            const uint32_t img = (grp * 32 + j) * SLOT;
            uint32_t x[16], x0[2];
            float st[4] = {0.f, 0.f, 0.f, 0.f};
            mbar_wait(sb + BAR_FULL + 8 * 4, 0);
#pragma unroll
            for (int q = 3; q < 8; q++) {
                const uint32_t ws = (0x4210u >> (4 * (q & 3))) & 15, as = (0x635u >> (4 * (q % 3))) & 15;
                mbar_wait(sb + BAR_FULL + 8 * as, (q / 3) & 1);
                bar_sync(1 + wg, 256);
                if (q == 3) gemm_issue<false>(s, kd + wg * 512 + as * (SLOT / 16), wd + ws * (SLOT / 16), 1, false);
                else if (q == 4) gemm_issue<true>(o, kd + wg * 512 + as * (SLOT / 16), wd + ws * (SLOT / 16), 0, false);
                else gemm_issue<false>(o, kd + wg * 512 + as * (SLOT / 16), wd + ws * (SLOT / 16), 1, false);
                bar_arrive(2 - wg, 256);
                sched_fence(fph, P.zero);
                if (q > 3) reg_fence(s);
                if (q == 3) {
                    asm volatile("setmaxnreg.inc.sync.aligned.u32 232;");
#pragma unroll
                    for (int i = 0; i < 4; i++)
                        asm volatile("ld.global.nc.v4.u32 {%0, %1, %2, %3}, [%4];" : "=r"(x[4 * i]), "=r"(x[4 * i + 1]), "=r"(x[4 * i + 2]), "=r"(x[4 * i + 3])
                                     : "l"(xp + lane + 32 * i) : "memory");
#pragma unroll
                    for (int i = 0; i < 2; i++) asm volatile("ld.global.nc.u32 %0, [%1];" : "=r"(x0[i]) : "l"(xp + 64 * i) : "memory");
                }
                if (q == 4) {
                    img_store_global<0>(img, toff, s, sc, sc);
#pragma unroll
                    for (int k = 0; k < 16; k++) {
                        const float d0 = bf_lo(x[k]) - bf_lo(x0[k >> 3]), d1 = bf_hi(x[k]) - bf_lo(x0[k >> 3]);
                        st[k >> 3] += d0 + d1;
                        st[2 + (k >> 3)] = fmaf(d0, d0, fmaf(d1, d1, st[2 + (k >> 3)]));
                    }
#pragma unroll
                    for (int i = 0; i < 4 * NSH; i++) st[i & 3] += __shfl_xor_sync(0xffffffffu, st[i & 3], 1 << (i >> 2));
                    reg_fence(st);
                }
                if (q == 5) {
#pragma unroll
                    for (int i = 4 * NSH; i < 20; i++) st[i & 3] += __shfl_xor_sync(0xffffffffu, st[i & 3], 1 << (i >> 2));
                    img_store_global<1>(img, toff, s, sc, sc);
#pragma unroll
                    for (int i = 0; i < 2; i++) {
                        const float d = st[i] * (1.f / 512.f);
                        st[2 + i] = ln_rstd(fmaxf(fmaf(-d, d, st[2 + i] * (1.f / 512.f)), 0.f));
                        x0[i] = pack2(bf_lo(x0[i]) + d, bf_lo(x0[i]) + d);
                    }
                    reg_fence(st);
                    reg_fence(x0);
                }
                if (q > 5) {
                    if (q == 6) mbar_wait(sb + BAR_FLAG + 8 * 8, 0);
                    const uint4 a = lds128(sb + SM_TAB + 1024 + (q & 1) * 512 + lane * 16), c = lds128(sb + SM_TAB + (q & 1) * 512 + lane * 16);
                    uint8_t* hp = g_h + (grp * 8 + (q & 1) * 4 + (lane >> 3)) * 16384 + (xrow & 127) * 128;
#pragma unroll
                    for (int i = 0; i < 2; i++) {
                        const uint32_t* y = x + 8 * i + 4 * (q & 1);
                        *reinterpret_cast<uint4*>(hp + i * 128 + (((lane ^ xrow ^ i) & 7) << 4)) =
                            make_uint4(ln_apply(y[0], x0[i], st[2 + i], a.x, c.x), ln_apply(y[1], x0[i], st[2 + i], a.y, c.y),
                                       ln_apply(y[2], x0[i], st[2 + i], a.z, c.z), ln_apply(y[3], x0[i], st[2 + i], a.w, c.w));
                    }
                    if (q == 7) {
                        __syncwarp();
                        mbar_arrive_if(sb + BAR_DONE, lane == 0);
                    }
                    if (q == 6) img_store_global<2>(img, toff, s, sc, sc);
                    else img_store_global<3>(img, toff, s, sc, sc);
                }
                if (q < 7) {
                    sched_fence(fph, P.zero);
                    wg_wait<0>();
                    release_if(eb, as, rel);
                }
            }
        }
        uint32_t pend = 0x73;
        uint32_t p[32] = {};
#pragma unroll 1
        for (int hp = 0; hp < 2; hp++) {
            float m[2] = {0.f, 0.f}, l[2] = {0.f, 0.f}, t[4] = {0.f, 0.f, 0.f, 0.f};
            bool shifted = false, bad = false, plain = false;
            uint32_t qa = desc_k(sb + 5 * SLOT + (wg ^ 1) * 8192);
            const uint32_t limg = (512 + (15 - j) * 32 + 2 * grp + hp) * SLOT;
            {
                const int step = hp ? -8 * SLOT : 8 * SLOT;
                uint32_t img = (grp * 32 + (hp ? j ^ 30 : j) + 8) * SLOT;
                const uint32_t wtab = w_table(hp);
                uint32_t atab = hp ? 0x562u : 0x356u;
#pragma unroll 1
                for (int u = 2 - 2 * hp; u < 6; u += 2) {
                    proj_tile<false>(s, o, u, !u, sb, wg, eb, rel, fph, wtab, atab, pend, u ? img : cimg, toff, u ? sc : li[0], u ? sc : li[1], p);
                    __syncwarp();
                    mbar_arrive_if(sb + BAR_DONE + 4 * u + 32 * hp, lane == 0);
                    if (elected) TS(1 + 10 * hp + u + 20 * wg);
                    proj_tile<true>(o, s, u + 1, 0, sb, wg, eb, rel, fph, wtab, atab, pend, img + step, toff, sc, sc, p);
                    if (elected) TS(2 + 10 * hp + u + 20 * wg);
                    img += 2 * step;
                }
            }
            asm volatile("" : "+r"(toff));
            if (elected) TS(6 + 10 * hp + 20 * wg);
            fence_async_smem();
            slot_wait(sb + BAR_FULL, fph, r);
            step_retire(eb, rel, pend);
            reg_fence(o);
            int n = -1;
#pragma unroll 1
            for (;;) {
                while (bad || plain) {
                    float d0 = m[0], d1 = m[1];
                    if (bad) {
                        float a0, a1;
                        softmax_remax(s, m, n == 0 || n == nL, d0, d1, a0, a1);
                        shifted = true;
                        l[0] *= a0;
                        l[1] *= a1;
#pragma unroll
                        for (int i = 0; i < 64; i++) o[i] *= (i & 2) ? a1 : a0;
                    }
#pragma unroll
                    for (int i = 0; i < 64; i++) s[i] -= (i & 2) ? d1 : d0;
                    softmax_exp<0, 16>(s, p, t);
                    t[0] += t[1];
                    t[2] += t[3];
                    bad = !bad && softmax_unsafe(t[0], t[2], false);
                    plain = false;
                }
#pragma unroll 1
                do {
                    l[0] += t[0];
                    l[1] += t[2];
                    if (++n > 16) break;
                    const uint32_t ks = r;
                    uint32_t vs = ring_next(r);
                    r = ring_next(vs);
                    bar_sync(1 + wg, 256);
                    const float x = (float)((warp & 3) * 16 + g - 2 * c4);
                    if (n == hn) {
                        float sh[32];
                        qk_issue(sh, qa, kd + ks * (SLOT / 16));
                        slot_wait(sb + BAR_FULL, fph, vs);
                        pv_issue(o, p, vd + vs * (SLOT / 16), 1, false);
                        bar_arrive(2 - wg, 256);
                        wg_wait<1>();
                        reg_fence(sh);
                        tri_mask_copy(s, sh, x);
                        release_if(eb, ks, rel);
                        release_if(eb, 5 + wg, rel && (!wg || n == 16));
                        if (!wg) qa += SLOT / 16;
                        float e[4 * EARLY];
#pragma unroll
                        for (int i = 0; i < 4 * EARLY; i++) {
                            e[i] = ex2(s[i]);
                            t[i & 3] = i < 4 ? e[i] : t[i & 3] + e[i];
                        }
                        reg_fence(e);
                        slot_wait(sb + BAR_FULL, fph, r);
                        wg_wait<0>();
                        reg_fence(o);
                        reg_fence(e);
                        release_if(eb, vs, rel);
#pragma unroll
                        for (int i = 0; i < 2 * EARLY; i++) p[i] = pack2(e[2 * i], e[2 * i + 1]);
                        softmax_exp<EARLY, 8>(s, p, t);
                        if (wg) {
                            ctx_store(limg, toff, o, rcp(quad_sum(l[0])), rcp(quad_sum(l[1])));
                            __syncwarp();
                            mbar_arrive_if(sb + BAR_DONE + 24 + 32 * hp, lane == 0);
                            l[0] = l[1] = m[0] = m[1] = 0.f;
                            shifted = false;
                        }
                        t[0] += t[1];
                        t[2] += t[3];
                        plain = shifted;
                        if (plain) break;
                        bad = softmax_unsafe(t[0], t[2], wg);
                        continue;
                    }
                    if (n == nL) {
                        qk_issue(s, qa, kd + ks * (SLOT / 16));
                        slot_wait(sb + BAR_FULL, fph, vs);
                        pv_issue(o, p, vd + vs * (SLOT / 16), 1, true);
                        bar_arrive(2 - wg, 256);
                        const float i0 = rcp(quad_sum(l[0])), i1 = rcp(quad_sum(l[1]));
                        wg_wait<1>();
                        reg_fence(s);
                        release_if(eb, ks, rel);
                        release_if(eb, 6, rel && n == 16);
                        tri_mask(s, x);
                        float e[4 * EARLY2];
#pragma unroll
                        for (int i = 0; i < 4 * EARLY2; i++) {
                            e[i] = ex2(s[i]);
                            t[i & 3] = i < 4 ? e[i] : t[i & 3] + e[i];
                        }
                        reg_fence(e);
                        reg_fence(s);
                        reg_fence(t);
                        slot_wait(sb + BAR_FULL, fph, r);
                        sched_fence(fph, P.zero);
                        wg_wait<0>();
                        reg_fence(o);
                        reg_fence(e);
                        release_if(eb, vs, rel);
#pragma unroll
                        for (int i = 0; i < 2 * EARLY2; i++) p[i] = pack2(e[2 * i], e[2 * i + 1]);
                        softmax_exp<EARLY2, MSPLIT>(s, p, t);
                        ctx_store(limg, toff, o, i0, i1);
                        reg_fence(t);
                        reg_fence(s);
                        softmax_exp<MSPLIT, 16>(s, p, t);
                        __syncwarp();
                        mbar_arrive_if(sb + BAR_DONE + 24 + 32 * hp, lane == 0);
                        l[0] = l[1] = m[0] = m[1] = 0.f;
                        shifted = false;
                        t[0] += t[1];
                        t[2] += t[3];
                        bad = __any_sync(0xffffffffu, fmaxf(t[0], t[2]) > SM_HI || fminf(t[0], t[2]) < SM_LO);
                        continue;
                    }
                    qk_issue(s, qa, kd + ks * (SLOT / 16));
                    if (n == 0) {
                        r = vs;
                        vs = 4 - hp;
                        slot_wait(sb + BAR_FULL, fph, 6);
                        gemm_issue<false>(o, qa + SLOT / 16, wd + vs * (SLOT / 16), 1, false);
                    } else {
                        slot_wait(sb + BAR_FULL, fph, vs);
                        if (n == 1) {
                            wg_wait<1>();
                            reg_fence(o);
                            const uint32_t a = sb + 6 * SLOT + q_off(toff);
#pragma unroll
                            for (int i = 0; i < 8; i++) {
                                const int k = 16 * (i >> 1) + 2 * (i & 1);
                                sts128(a + (i >> 2) * 16384 + (i & 2) * 256 + (i & 1) * 1024,
                                       make_uint4(pack2(o[k], o[k + 1]), pack2(o[k + 4], o[k + 5]), pack2(o[k + 8], o[k + 9]), pack2(o[k + 12], o[k + 13])));
                            }
                        }
                        pv_issue(o, p, vd + vs * (SLOT / 16), n != 1 && n != nL + 1, n == hn + 1);
                    }
                    bar_arrive(2 - wg, 256);
                    wg_wait<1>();
                    reg_fence(s);
                    release_if(eb, ks, rel);
                    release_if(eb, 6, rel && n == 16);
                    if (n == nL - 1) {
                        tri_mask(s, x);
                        release_if(eb, 5, rel);
                        qa += SLOT / 16;
                    }
                    if (n == 2) fence_async_smem();
                    if (shifted) {
                        slot_wait(sb + BAR_FULL, fph, r);
                        wg_wait<0>();
                        reg_fence(o);
                        release_if(eb, vs, rel);
                        plain = true;
                        break;
                    }
                    float e[4 * EARLY];
#pragma unroll
                    for (int i = 0; i < 4 * EARLY; i++) {
                        e[i] = ex2(s[i]);
                        t[i & 3] = i < 4 ? e[i] : t[i & 3] + e[i];
                    }
                    reg_fence(e);
                    slot_wait(sb + BAR_FULL, fph, r);
                    wg_wait<0>();
                    reg_fence(o);
                    reg_fence(e);
                    release_if(eb, vs, rel);
#pragma unroll
                    for (int i = 0; i < 2 * EARLY; i++) p[i] = pack2(e[2 * i], e[2 * i + 1]);
                    softmax_exp<EARLY, 16>(s, p, t);
                    t[0] += t[1];
                    t[2] += t[3];
                    bad = __any_sync(0xffffffffu, fmaxf(t[0], t[2]) > SM_HI || (n == 0 && fminf(t[0], t[2]) < SM_LO));
                } while (!bad);
                if (!bad && !plain) break;
            }
            asm volatile("" : "+r"(toff));
            const uint32_t vs = r, ga = desc_k(sb + (hp ? 2 * (wg ^ kh ^ 1) : wg) * 8192);
            r = ring_next(r);
            slot_wait(sb + BAR_FULL, fph, 5);
            slot_wait(sb + BAR_FULL, fph, r);
            bar_sync(1 + wg, 256);
            gemm_issue<true>(s, ga + 5 * (SLOT / 16), wd + r * (SLOT / 16), 0, hp);
            pv_issue(o, p, vd + vs * (SLOT / 16), j, hn == 16);
            bar_arrive(2 - wg, 256);
            li[0] = rcp(quad_sum(l[0]));
            li[1] = rcp(quad_sum(l[1]));
            cimg = limg + (2 * j - 15) * 32 * SLOT + (wg ? -16384 : 16384);
            wg_wait<1>();
            release_if(eb, 5, rel);
            release_if(eb, r, rel && hp);
            wg_wait<0>();
            release_if(eb, vs, rel);
            reg_fence(o);
            img_store_global<0>(cimg, toff, o, li[0], li[1]);
            pend = 0x77;
            if (elected) TS(8 + 10 * hp + 20 * wg);
        }
        uint32_t otab = 0x2351604u;
        const uint32_t oa = desc_k(sb + (wg ^ kh ^ 1) * 16384);
        const int t7 = tid & 127, w4 = warp & 3, row = ort * 128 + kh * 64 + w4 * 16 + g;
#pragma unroll 1
        for (int i = 1; i < 15 - OFF - wg; i++) {
            const uint32_t as = o_next(otab), ws = o_next(otab);
            slot_wait(sb + BAR_FULL, fph, as);
            slot_wait(sb + BAR_FULL, fph, ws);
            bar_sync(1 + wg, 256);
            gemm_issue<false>(s, oa + as * (SLOT / 16), wd + ws * (SLOT / 16), 1, true);
            bar_arrive(2 - wg, 256);
            wg_wait<1>();
            reg_fence(o);
            if (i == 1) img_store_global<1>(cimg, toff, o, li[0], li[1]);
            if (i == 2) img_store_global<2>(cimg, toff, o, li[0], li[1]);
            if (i == CLAST) {
                img_store_global<3>(cimg, toff, o, li[0], li[1]);
                __syncwarp();
                mbar_arrive_if(sb + BAR_DONE + 64, lane == 0);
            }
            wg_wait<0>();
            release_if(eb, as, rel);
            release_if(eb, ws, rel);
        }
        mbar_wait(sb + BAR_PF, 0);
        const uint32_t ep = lds32(sb + SM_EP);
        uint32_t eb2 = sb + BAR_END;
        if (wg == 0) {
            reg_fence(s);
            if (elected) TS(9);
            TT(1);
#pragma unroll
            for (int v = 0; v < 8; v++)
                st_pub(g_out + rb * OB + v * 128 + t7, make_uint4((pack2(s[8 * v], s[8 * v + 1]) & ~1u) | (ep & 1), pack2(s[8 * v + 2], s[8 * v + 3]),
                                                                      pack2(s[8 * v + 4], s[8 * v + 5]), pack2(s[8 * v + 6], s[8 * v + 7])), true);
            constexpr uint32_t s1 = SL_WF, s2 = SL_WD;
            bar_sync(4, 256);
            uint32_t wf[64];
            float wn[64];
            if (rb < NFFN) {
                slot_wait(sb + BAR_FULL, fph, s1);
                const uint32_t a = sb + s1 * SLOT + (w4 * 128 + (lane >> 4) * 8 + (lane & 7)) * 32 + (((lane >> 3) ^ (lane >> 2)) & 1) * 16;
#pragma unroll
                for (int i = 0; i < 16; i++)
                    asm volatile("ldmatrix.sync.aligned.m8n8.x4.trans.shared.b16 {%0, %1, %2, %3}, [%4];"
                                 : "=r"(wf[4 * i]), "=r"(wf[4 * i + 1]), "=r"(wf[4 * i + 2]), "=r"(wf[4 * i + 3])
                                 : "r"(a + (i >> 3) * 16384 + (i & 7) * 512) : "memory");
                slot_wait(sb + BAR_FULL, fph, s2);
#pragma unroll
                for (int i = 0; i < 16; i++) {
                    const uint2 w = *reinterpret_cast<const uint2*>(smem + s2 * SLOT + (kh ^ 1) * 16384 + i * 1024 + t7 * 8);
                    wn[4 * i] = bf_lo(w.x); wn[4 * i + 1] = bf_hi(w.x); wn[4 * i + 2] = bf_lo(w.y); wn[4 * i + 3] = bf_hi(w.y);
                }
                reg_fence(wn);
            }
            const uint32_t gbf = __ldcg(reinterpret_cast<const uint32_t*>(g_mod) + 1280 + rb * 2 + (tid & 1));
            if (elected) TS(10);
            TT(2);
            float* sred = reinterpret_cast<float*>(smem + SM_RED);
            if (warp == 0) {
                *reinterpret_cast<uint32_t*>(smem + SM_EP + 24) = best_key(g_key + cq * 128, lane, ep);
                mbar_arrive_if(sb + BAR_BEST, lane == 0);
            }
            bar_sync(3, 128);
            const uint32_t best = lds32(sb + SM_EP + 24);
            const int sel = (~best >> 5) & 2047;
            TT(3);
            if (rb < NFFN) {
                const uint4* cp = g_cand + (sel >> 4) * 192;
                uint4 cv[6];
                for (;;) {
                    uint32_t bad = 0;
#pragma unroll
                    for (int v = 0; v < 6; v++) cv[v] = ld_poll(cp + w4 * 24 + v * 4 + c4);
#pragma unroll
                    for (int v = 0; v < 6; v++) bad |= cv[v].w ^ ep;
                    if (__all_sync(0xffffffffu, bad == 0)) break;
                }
            TT(4);
                float d[4][4] = {};
#pragma unroll
                for (int k = 0; k < 8; k++) {
                    const uint32_t b0 = (&cv[(2 * k) / 3].x)[(2 * k) % 3], b1 = (&cv[(2 * k + 1) / 3].x)[(2 * k + 1) % 3];
                    mma16816(d[k & 1], wf + 4 * k, b0, b1);
                    mma16816(d[2 + (k & 1)], wf + 32 + 4 * k, b0, b1);
                }
                const float u = (c4 & 2) ? ((c4 & 1) ? d[2][2] + d[3][2] : d[2][0] + d[3][0]) : ((c4 & 1) ? d[0][2] + d[1][2] : d[0][0] + d[1][0]);
                sred[w4 * 32 + c4 * 8 + g] = u;
                bar_sync(3, 128);
                const float v = rbf((sred[lane] + sred[32 + lane]) + (sred[64 + lane] + sred[96 + lane]));
                const float act = rbf(rbf(v * sigmoid(v)) * __shfl_down_sync(0xffffffffu, v, 16));
                float y[4] = {0.f, 0.f, 0.f, 0.f};
#pragma unroll
                for (int k = 0; k < 16; k++) {
                    const float a = __shfl_sync(0xffffffffu, act, k);
#pragma unroll
                    for (int i = 0; i < 4; i++) y[i] = fmaf(a, wn[4 * k + i], y[i]);
                }
                st_pub(g_out + rb * OB + OB_Y + t7, make_uint4((__float_as_uint(y[0]) & ~15u) | (ep & 15), __float_as_uint(y[1]), __float_as_uint(y[2]), __float_as_uint(y[3])), true);
            }
            const int pq = (2 * rb + (tid & 1)) & 63, pv = (pq >> 2) / 3;
            const uint4* fp = g_cand + (sel >> 4) * 192 + (rb >> 5) * 24 + pv * 4 + (pq & 3);
            uint4 fh = {}, fx = {};
            if (rb == 0 && tid == 0) g_sync.epoch[0] = ep;
            if (elected) TS(60);
            TT(5);
            uint4 yv;
            if (warp == 0) { fh = ld_poll(fp); fx = ld_poll(fp + 96); }
            __nanosleep(rb < NFFN ? YPRE : 4 * YPRE);
            for (;;) {
                yv = ld_poll(g_out + min(t7, NFFN - 1) * OB + OB_Y + rb);
                if (poll_done(((yv.x ^ ep) & 15) == 0, YSLEEP)) break;
            }
            if (elected) TS(61);
            TT(6);
            float y[4] = {0.f, 0.f, 0.f, 0.f};
            if (t7 < NFFN) { y[0] = __uint_as_float(yv.x); y[1] = __uint_as_float(yv.y); y[2] = __uint_as_float(yv.z); y[3] = __uint_as_float(yv.w); }
            const float z0 = ((lane & 16) ? y[2] : y[0]) + __shfl_xor_sync(0xffffffffu, (lane & 16) ? y[0] : y[2], 16);
            const float z1 = ((lane & 16) ? y[3] : y[1]) + __shfl_xor_sync(0xffffffffu, (lane & 16) ? y[1] : y[3], 16);
            float z = ((lane & 8) ? z1 : z0) + __shfl_xor_sync(0xffffffffu, (lane & 8) ? z0 : z1, 8);
            z += __shfl_xor_sync(0xffffffffu, z, 4);
            z = quad_sum(z);
            if ((lane & 7) == 0) sred[128 + (lane >> 3) * 4 + w4] = z;
            bar_sync(3, 128);
            if (tid < 2) {
                while (fh.w != ep || fx.w != ep) { fh = ld_poll(fp); fx = ld_poll(fp + 96); }
                const float4 y0 = *reinterpret_cast<const float4*>(sred + 128 + tid * 8), y1 = *reinterpret_cast<const float4*>(sred + 132 + tid * 8);
                const int cm = (pq >> 2) - 3 * pv;
                const uint32_t h2 = cm == 0 ? fh.x : cm == 1 ? fh.y : fh.z, x2 = cm == 0 ? fx.x : cm == 1 ? fx.y : fx.z;
                const float sg = sigmoid(bf_hi((best & 0x80000000u) ? (best ^ 0x80000000u) : ~best));
                reinterpret_cast<uint32_t*>(P.out)[sel * 256 + rb * 2 + tid] =
                    badd(x2, bmul(gbf, badd(h2, bmul(pack2((y0.x + y0.y) + (y0.z + y0.w), (y1.x + y1.y) + (y1.z + y1.w)), pack2(sg, sg)))));
            }
            if (elected) TS(62);
            TT(7);
        } else {
            const float4* tf = reinterpret_cast<const float4*>(smem + SM_TAB) + c4;
            uint32_t x2[32];
            bar_sync(2, 256);
#pragma unroll 1
            for (int i = 14; i < 17; i++) {
                const uint32_t as = o_next(otab), ws = o_next(otab);
                slot_wait(sb + BAR_FULL, fph, as);
                slot_wait(sb + BAR_FULL, fph, ws);
                gemm_issue<false>(s, oa + as * (SLOT / 16), wd + ws * (SLOT / 16), 1, true);
                wg_wait<1>();
            }
            const uint4* pr = g_out + (rb ^ 16) * OB + t7;
            uint4 pa[8];
            if (elected) TS(29);
            TT(1);
#pragma unroll
            for (int k = 0; k < 8; k++) {
                const uint4 v = lds128(sb + SL_X * SLOT + (kh ^ 1) * 16384 + k * 2048 + t7 * 16);
                x2[4 * k] = v.x; x2[4 * k + 1] = v.y; x2[4 * k + 2] = v.z; x2[4 * k + 3] = v.w;
            }
            wg_wait<0>();
            reg_fence(s);
            bar_arrive(4, 256);
            if (elected) TS(39);
            TT(2);
#pragma unroll
            for (int v = 0; v < 8; v++) pa[v] = ld_poll(pr + v * 128);
            float4 tc[16];
#pragma unroll
            for (int k = 0; k < 16; k++) {
                tc[k] = tf[k * 4];
                if (!(g & 1)) tc[k].z = __uint_as_float(ONE2);
#pragma unroll
                for (int i = 4 * k; i < 4 * k + 4; i++) s[i] = fmaf((i & 1) ? tc[k].y : tc[k].x, s[i], (i & 1) ? bf_hi(x2[i >> 1]) : bf_lo(x2[i >> 1]));
            }
            reg_fence(s);
            sched_fence(eb2, P.zero);
            for (;;) {
                uint32_t bad = 0;
#pragma unroll
                for (int v = 0; v < 8; v++) asm("lop3.b32 %0, %0, %1, %2, 0xf6;" : "+r"(bad) : "r"(pa[v].x), "r"(ep));
                if (__all_sync(0xffffffffu, (bad & 1) == 0)) break;
                if (PSLEEP) __nanosleep(PSLEEP);
#pragma unroll
                for (int v = 0; v < 8; v++) pa[v] = ld_poll(pr + v * 128);
            }
            if (elected) TS(30);
            TT(3);
            float sd[4] = {}, q0[4] = {}, q1[4] = {};
#pragma unroll
            for (int k = 0; k < 8; k++) {
#pragma unroll
                for (int i = 4 * k; i < 4 * k + 4; i++) {
                    const uint32_t w = (&pa[k].x)[i & 3];
                    x2[i] = pack2(fmaf(tc[i >> 1].x, bf_lo(w), s[2 * i]), fmaf(tc[i >> 1].y, bf_hi(w), s[2 * i + 1]));
                }
                mma16816(sd, x2 + 4 * k, __float_as_uint(tc[2 * k].z), __float_as_uint(tc[2 * k + 1].z));
                mma16816(q0, x2 + 4 * k, x2[4 * k], x2[4 * k + 2]);
                mma16816(q1, x2 + 4 * k, x2[4 * k + 1], x2[4 * k + 3]);
            }
            uint4* sp = g_out + rb * OB + OB_STAT + (w4 * 8 + g) * 2;
            st_pub(sp, make_uint4(__float_as_uint(sd[0]), __float_as_uint((g & 1) ? q0[1] : q0[0]), __float_as_uint(sd[1]), ep), c4 == g >> 1);
            st_pub(sp + 1, make_uint4(__float_as_uint(sd[2]), __float_as_uint((g & 1) ? q1[3] : q1[2]), __float_as_uint(sd[3]), ep), c4 == g >> 1);
            sched_fence(eb2, P.zero);
            if (elected) TS(56);
            TT(4);
            uint32_t cb[16], sh[16], gb[16];
#pragma unroll
            for (int i = 0; i < 16; i++) {
                const float4 c = tf[64 + i * 4];
                cb[i] = __float_as_uint(c.x); sh[i] = __float_as_uint(c.y); gb[i] = __float_as_uint(c.z);
            }
            const float ra = __uint_as_float(lds32(sb + SM_EP + 8)), rb0 = __uint_as_float(lds32(sb + SM_EP + 12));
            uint4 r0, r1;
            for (;;) {
                r0 = ld_poll(g_out + ((rb & ~33) + (c4 & 1) + (c4 & 2) * 16) * OB + OB_STAT + (w4 * 8 + g) * 2);
                r1 = ld_poll(g_out + ((rb & ~33) + (c4 & 1) + (c4 & 2) * 16) * OB + OB_STAT + (w4 * 8 + g) * 2 + 1);
                if (poll_done(r0.w == ep && r1.w == ep, SSLEEP)) break;
            }
            if (elected) TS(57);
            TT(5);
            const float m0 = quad_sum(__uint_as_float(r0.x)) * (1.f / 512.f), m1 = quad_sum(__uint_as_float(r1.x)) * (1.f / 512.f);
            const float rs0 = ln_rstd(fmaxf(fmaf(-m0, m0, quad_sum(__uint_as_float(r0.y)) * (1.f / 512.f)), 0.f));
            const float rs1 = ln_rstd(fmaxf(fmaf(-m1, m1, quad_sum(__uint_as_float(r1.y)) * (1.f / 512.f)), 0.f));
            const uint32_t mb0 = pack2(m0, m0), mb1 = pack2(m1, m1);
            const uint32_t lg = pack2(fmaf(rs0, fmaf(-bf_lo(mb0), ra, quad_sum(__uint_as_float(r0.z))), rb0),
                                      fmaf(rs1, fmaf(-bf_lo(mb1), ra, quad_sum(__uint_as_float(r1.z))), rb0));
            const uint32_t u0 = lg << 16, u1 = lg & 0xffff0000u;
            const uint32_t k0 = ((u0 ^ (((int)u0 >> 31) | 0x80000000u)) & 0xffff0000u) | ((2047 - row) << 5) | (ep & 31);
            const uint32_t k1 = ((u1 ^ (((int)u1 >> 31) | 0x80000000u)) & 0xffff0000u) | ((2039 - row) << 5) | (ep & 31);
            const uint32_t kb = __reduce_max_sync(0xffffffffu, max(k0, k1));
            st_pub(g_key + cq * 128 + (row >> 4), kb, lane == 0);
            const bool cand = kb == k0 || kb == k1;
            uint4* cp = g_cand + (row >> 4) * 192 + cq * 24 + c4;
#pragma unroll 1
            for (int it = 0; it < 3; it++) {
                bool put = it == 1 || !cand;
                if (it == 2) {
                    mbar_wait(sb + BAR_BEST, 0);
                    put = cand && lds32(sb + SM_EP + 24) != kb;
                }
                const bool hi = (kb == k1) != (it == 1);
                uint32_t cx[18], ch[18];
#pragma unroll
                for (int i = 0; i < 16; i++) {
                    cx[i] = hi ? x2[2 * i + 1] : x2[2 * i];
                    ch[i] = ln_apply(cx[i], hi ? mb1 : mb0, hi ? rs1 : rs0, cb[i], sh[i]);
                }
                cx[16] = cx[17] = ch[16] = ch[17] = 0;
#pragma unroll
                for (int v = 0; v < 6; v++) st_pub(cp + v * 4, make_uint4(ch[3 * v], ch[3 * v + 1], ch[3 * v + 2], ep), cand && it == 0);
#pragma unroll
                for (int v = 0; v < 6; v++) st_pub(cp + 96 + v * 4, make_uint4(cx[3 * v], cx[3 * v + 1], cx[3 * v + 2], ep), cand && it == 0);
                if (it == 0) TT(6);
                uint2* op = reinterpret_cast<uint2*>(P.out) + (row + 8 * hi) * 128 + cq * 32 + (c4 & 1) * 2 + (c4 >> 1);
#pragma unroll
                for (int i = 0; i < 16; i += 2) {
                    const uint32_t v0 = badd(cx[i], bmul(gb[i], ch[i])), v1 = badd(cx[i + 1], bmul(gb[i + 1], ch[i + 1]));
                    const uint32_t rv = __shfl_xor_sync(0xffffffffu, (c4 & 1) ? v0 : v1, 1);
                    if (put) op[i * 2] = (c4 & 1) ? make_uint2(rv, v1) : make_uint2(v0, rv);
                }
            }
            if (elected) TS(59);
            TT(7);
        }
        mbar_arrive_if(eb2, lane == 0);
    }
}

typedef CUresult (*EncodeFn)(CUtensorMap*, CUtensorMapDataType, cuuint32_t, void*, const cuuint64_t*, const cuuint64_t*,
                             const cuuint32_t*, const cuuint32_t*, CUtensorMapInterleave, CUtensorMapSwizzle,
                             CUtensorMapL2promotion, CUtensorMapFloatOOBfill);

void make_3d(EncodeFn fn, CUtensorMap* m, const void* p, uint64_t cols, uint64_t rows, uint32_t br = 128, uint32_t nb = 2) {
    cuuint64_t dims[3] = {64, rows, cols / 64}, strides[2] = {cols * 2, 128};
    cuuint32_t box[3] = {64, br, nb}, es[3] = {1, 1, 1};
    fn(m, CU_TENSOR_MAP_DATA_TYPE_BFLOAT16, 3, const_cast<void*>(p), dims, strides, box, es, CU_TENSOR_MAP_INTERLEAVE_NONE,
       CU_TENSOR_MAP_SWIZZLE_128B, CU_TENSOR_MAP_L2_PROMOTION_L2_256B, CU_TENSOR_MAP_FLOAT_OOB_FILL_NONE);
}

}

extern "C" void kernel_launch(void* const* d_in, const int* in_sizes, int n_in, void* d_out, int out_size) {
    static EncodeFn fn = nullptr;
    if (!fn) {
        void* f = nullptr;
        cudaDriverEntryPointQueryResult st;
        cudaGetDriverEntryPoint("cuTensorMapEncodeTiled", &f, cudaEnableDefault, &st);
        fn = (EncodeFn)f;
        cudaFuncSetAttribute(fused_kernel, cudaFuncAttributeMaxDynamicSharedMemorySize, SMEM_BYTES);
    }
    CUtensorMap ckv, wq, wuk, wuv, wo, wg, wu, wm, xm;
    make_3d(fn, &ckv, d_in[1], 512, 2048, 128, 1);
    make_3d(fn, &xm, d_in[0], 512, 2048, 64);
    make_3d(fn, &wq, d_in[2], 4096, 512);
    make_3d(fn, &wuk, d_in[3], 4096, 512);
    make_3d(fn, &wuv, d_in[4], 4096, 512);
    make_3d(fn, &wo, d_in[5], 512, 4096);
    make_3d(fn, &wg, d_in[8], 1792, 512, 256, 1);
    make_3d(fn, &wu, d_in[9], 1792, 512, 256, 1);
    make_3d(fn, &wm, d_in[12], 3072, 512, 64, 4);
    Params p;
    p.x = (const bf16*)d_in[0];
    p.ckv = (const bf16*)d_in[1];
    p.wo = (const bf16*)d_in[5];
    p.wr = (const bf16*)d_in[7];
    p.wdown = (const bf16*)d_in[10];
    p.c = (const bf16*)d_in[11];
    p.out = (bf16*)d_out;
    p.zero = 0;
    fused_kernel<<<NCTA + NSPARE, 384, SMEM_BYTES>>>(ckv, wq, wuk, wuv, wo, wg, wu, wm, xm, p);
}
```

```cpp
#include <cuda.h>
#include <cuda_bf16.h>
#include <cuda_runtime.h>
#include <stdint.h>
#include <stdio.h>

namespace {

typedef __nv_bfloat16 bf16;
typedef unsigned long long u64;

constexpr int NCTA = 128, NSPARE = 4;
constexpr int SLOT = 32768;
constexpr int SM_BAR = 7 * SLOT;
constexpr int BAR_FULL = SM_BAR;
constexpr int BAR_EMPTY = BAR_FULL + 8 * 7;
constexpr int BAR_DONE = BAR_EMPTY + 8 * 7;
constexpr int BAR_FLAG = BAR_DONE + 8 * 9;
constexpr int BAR_PF = BAR_FLAG + 8 * 9;
constexpr int BAR_END = BAR_PF + 8;
constexpr int BAR_BEST = BAR_END + 8;
constexpr int SM_EP = BAR_END + 40;
constexpr int SM_RED = SM_BAR + 384;
constexpr int SM_TAB = SM_BAR + 1024;
constexpr int SMEM_BYTES = SM_BAR + 3072;
constexpr int NFFN = 112;
#define HINT 479
constexpr u64 L2_NORMAL = 0x1000000000000000ull, L2_FIRST = 0x12F0000000000000ull;
#define PFA 8
#define PFB 6
#define POLL_NS 50
#define MSPLIT 13
#define NSH 1
#define XPF 1
#define KSLEEP 400
#define YSLEEP 50
#define YPRE 150
#define SSLEEP 50
#define PSLEEP 100
#define KVG 7
#define EARLY2 4
#define OFF 2
#define KN 16
#define KSLEEP2 60
#define EARLY 7
constexpr uint32_t SPIN_LIMIT = 1u << 22;
constexpr uint32_t ONE2 = 0x3f803f80u;

struct Sync {
    uint32_t cnt[16 * 8 * 8];
    uint32_t ctxcnt[16 * 32];
    uint32_t epoch[32];
};

__device__ __align__(1024) uint8_t g_img[2 * 512 * SLOT];
#define g_KV g_img
#define g_ctx (g_img + 512 * SLOT)
__device__ __align__(1024) uint8_t g_h[16 * 4 * SLOT];
constexpr int OB = 1216, OB_STAT = 1024, OB_Y = 1088;
__device__ __align__(1024) uint4 g_out[128 * OB];
__device__ __align__(1024) bf16 g_mod[3072];
__device__ __align__(1024) uint32_t g_mod1[1024];
__device__ __align__(1024) uint4 g_cand[128 * 192];
__device__ __align__(1024) uint32_t g_key[4 * 128];
__device__ __align__(1024) uint8_t g_wf[NFFN * SLOT];
__device__ __align__(1024) uint4 g_x2[128 * 1024];
__device__ __align__(1024) Sync g_sync;
#define TS(i)

#define TT(i)
#define PT()

struct Params {
    const bf16 *x, *ckv, *wo, *wr, *wdown, *c;
    bf16* out;
    int zero;
};

__device__ __forceinline__ void mbar_init(uint32_t bar, uint32_t cnt) {
    asm volatile("mbarrier.init.shared::cta.b64 [%0], %1;" ::"r"(bar), "r"(cnt) : "memory");
}
__device__ __forceinline__ void mbar_wait(uint32_t bar, uint32_t parity) {
    asm volatile("{\n.reg .pred p;\nL_%=:\nmbarrier.try_wait.parity.shared::cta.b64 p, [%0], %1;\n@!p bra L_%=;\n}" ::"r"(bar), "r"(parity) : "memory");
}
__device__ __forceinline__ void mbar_sleep(uint32_t bar) {
    if ((threadIdx.x & 31) == 0)
        asm volatile("{\n.reg .pred p;\nL_%=:\nmbarrier.try_wait.parity.shared::cta.b64 p, [%0], 0, 100000;\n@!p bra L_%=;\n}" ::"r"(bar) : "memory");
    __syncwarp();
}
__device__ __forceinline__ void mbar_watch(uint32_t bar, uint32_t parity) {
    asm volatile("{\n.reg .pred p;\n.reg .u32 n;\nmov.u32 n, 0;\n"
                 "L_%=:\nmbarrier.try_wait.parity.shared::cta.b64 p, [%0], %1;\n@p bra D_%=;\n"
                 "add.u32 n, n, 1;\nsetp.lt.u32 p, n, %2;\n@p bra L_%=;\ntrap;\nD_%=:\n}"
                 ::"r"(bar), "r"(parity), "n"(SPIN_LIMIT) : "memory");
}
__device__ __forceinline__ void step_watch(uint32_t a, uint32_t step) {
    asm volatile("{\n.reg .pred p;\n.reg .u32 n, v;\nmov.u32 n, 0;\n"
                 "L_%=:\nld.volatile.shared.u32 v, [%0];\nsetp.ge.u32 p, v, %1;\n@p bra D_%=;\nnanosleep.u32 400;\n"
                 "add.u32 n, n, 1;\nsetp.lt.u32 p, n, %2;\n@p bra L_%=;\ntrap;\nD_%=:\n}"
                 ::"r"(a), "r"(step), "n"(SPIN_LIMIT) : "memory");
}
__device__ __forceinline__ void mbar_arrive_if(uint32_t bar, bool on) {
    asm volatile("{\n.reg .pred p;\nsetp.ne.s32 p, %1, 0;\n@p mbarrier.arrive.shared::cta.b64 _, [%0];\n}" ::"r"(bar), "r"((int)on) : "memory");
}
__device__ __forceinline__ void tma3d_prefetch(const CUtensorMap* m, int row, int cb) {
    asm volatile("{\n.reg .pred p;\nelect.sync _|p, 0xffffffff;\n@p cp.async.bulk.prefetch.tensor.3d.L2.global [%0, {%1, %2, %3}];\n}"
                 ::"l"(m), "r"(0), "r"(row), "r"(cb) : "memory");
}
__device__ __forceinline__ void l2_prefetch(const void* p, uint32_t bytes) {
    asm volatile("{\n.reg .pred p;\nelect.sync _|p, 0xffffffff;\n@p cp.async.bulk.prefetch.L2.global [%0], %1;\n}" ::"l"(p), "r"(bytes) : "memory");
}
__device__ __forceinline__ void bulk_store(void* dst, uint32_t src, uint32_t bytes, bool first) {
    asm volatile("{\n.reg .pred p;\nelect.sync _|p, 0xffffffff;\n@p cp.async.bulk.global.shared::cta.bulk_group.L2::cache_hint [%0], [%1], %2, %3;\n}"
                 ::"l"(dst), "r"(src), "r"(bytes), "l"(first ? L2_FIRST : L2_NORMAL) : "memory");
}
__device__ __forceinline__ void flag_wait(const uint32_t* f, uint32_t target) {
    asm volatile("{\n.reg .pred p;\n.reg .u32 v;\n"
                 "L_%=:\nld.acquire.gpu.global.u32 v, [%0];\nsub.u32 v, v, %1;\nsetp.lt.s32 p, v, 0;\n@p nanosleep.u32 100;\n@p bra L_%=;\n}"
                 ::"l"(f), "r"(target) : "memory");
}
__device__ __forceinline__ uint4 ld_poll(const uint4* p) {
    uint4 v;
    asm volatile("{\n.reg .b128 t;\nld.relaxed.gpu.global.b128 t, [%4];\nmov.b128 {%0, %1, %2, %3}, t;\n}"
                 : "=r"(v.x), "=r"(v.y), "=r"(v.z), "=r"(v.w) : "l"(p) : "memory");
    return v;
}
__device__ __forceinline__ void st_pub(uint4* p, uint4 v, bool on) {
    asm volatile("{\n.reg .pred p;\n.reg .b128 t;\nsetp.ne.s32 p, %5, 0;\nmov.b128 t, {%1, %2, %3, %4};\n@p st.relaxed.gpu.global.b128 [%0], t;\n}"
                 ::"l"(p), "r"(v.x), "r"(v.y), "r"(v.z), "r"(v.w), "r"((int)on) : "memory");
}
__device__ __forceinline__ void st_pub(uint32_t* p, uint32_t v, bool on) {
    asm volatile("{\n.reg .pred p;\nsetp.ne.s32 p, %2, 0;\n@p st.relaxed.gpu.global.u32 [%0], %1;\n}" ::"l"(p), "r"(v), "r"((int)on) : "memory");
}
__device__ __forceinline__ bool poll_done(bool ok, uint32_t ns) {
    const int done = __all_sync(0xffffffffu, ok);
    asm volatile("{\n.reg .pred p;\nsetp.eq.s32 p, %0, 0;\n@p nanosleep.u32 %1;\n}" ::"r"(done), "r"(ns) : "memory");
    return done;
}
__device__ __forceinline__ void flag_add(uint32_t* p) {
    asm volatile("red.release.gpu.global.add.u32 [%0], 1;" ::"l"(p) : "memory");
}
__device__ __forceinline__ uint32_t lds32(uint32_t a) {
    uint32_t v;
    asm volatile("ld.shared.u32 %0, [%1];" : "=r"(v) : "r"(a) : "memory");
    return v;
}
__device__ __forceinline__ uint4 lds128(uint32_t a) {
    uint4 v;
    asm volatile("ld.shared.v4.u32 {%0, %1, %2, %3}, [%4];" : "=r"(v.x), "=r"(v.y), "=r"(v.z), "=r"(v.w) : "r"(a) : "memory");
    return v;
}
__device__ __forceinline__ void sched_fence(uint32_t& v, uint32_t z) {
    uint32_t ck;
    asm volatile("mov.u32 %0, %%clock;" : "=r"(ck)::"memory");
    v ^= ck & z;
}
__device__ __forceinline__ void fence_async_global() { asm volatile("fence.proxy.async.global;" ::: "memory"); }
__device__ __forceinline__ void fence_async_smem() { asm volatile("fence.proxy.async.shared::cta;" ::: "memory"); }
__device__ __forceinline__ void bar_sync(int id, int n) { asm volatile("bar.sync %0, %1;" ::"r"(id), "r"(n) : "memory"); }
__device__ __forceinline__ void bar_arrive(int id, int n) { asm volatile("bar.arrive %0, %1;" ::"r"(id), "r"(n) : "memory"); }
__device__ __forceinline__ void wg_fence() { asm volatile("wgmma.fence.sync.aligned;" ::: "memory"); }
__device__ __forceinline__ void wg_commit() { asm volatile("wgmma.commit_group.sync.aligned;" ::: "memory"); }
template <int N> __device__ __forceinline__ void wg_wait() { asm volatile("wgmma.wait_group.sync.aligned %0;" ::"n"(N) : "memory"); }
template <int N> __device__ __forceinline__ void reg_fence(float (&d)[N]) {
#pragma unroll
    for (int i = 0; i < N; i++) asm volatile("" : "+f"(d[i])::"memory");
}
template <int N> __device__ __forceinline__ void reg_fence(uint32_t (&d)[N]) {
#pragma unroll
    for (int i = 0; i < N; i++) asm volatile("" : "+r"(d[i])::"memory");
}
__device__ __forceinline__ uint32_t desc_k(uint32_t a) { return ((a & 0x3ffff) >> 4) | (1u << 16); }
__device__ __forceinline__ uint32_t desc_mn(uint32_t a) { return ((a & 0x3ffff) >> 4) | (1024u << 16); }

__device__ __forceinline__ uint64_t desc64(uint32_t lo, uint32_t hi) {
    uint64_t d;
    asm("mov.b64 %0, {%1, %2};" : "=l"(d) : "r"(lo), "r"(hi));
    return d;
}
__device__ __forceinline__ void desc_add(uint64_t& d, uint32_t x) { asm("add.u64 %0, %0, %1;" : "+l"(d) : "l"((uint64_t)x)); }

template <int TB>
__device__ __forceinline__ void wgmma_ss128(float (&d)[64], uint64_t da, uint64_t db, int acc) {
    asm volatile("{\n.reg .pred p;\nsetp.ne.b32 p, %66, 0;\n"
        "wgmma.mma_async.sync.aligned.m64n128k16.f32.bf16.bf16 {%0, %1, %2, %3, %4, %5, %6, %7, %8, %9, %10, %11, %12, %13, %14, %15, %16, %17, %18, %19, %20, %21, %22, %23, %24, %25, %26, %27, %28, %29, %30, %31, %32, %33, %34, %35, %36, %37, %38, %39, %40, %41, %42, %43, %44, %45, %46, %47, %48, %49, %50, %51, %52, %53, %54, %55, %56, %57, %58, %59, %60, %61, %62, %63}, %64, %65, p, 1, 1, 0, %67;\n}"
        : "+f"(d[0]), "+f"(d[1]), "+f"(d[2]), "+f"(d[3]), "+f"(d[4]), "+f"(d[5]), "+f"(d[6]), "+f"(d[7]), "+f"(d[8]), "+f"(d[9]), "+f"(d[10]), "+f"(d[11]), "+f"(d[12]), "+f"(d[13]), "+f"(d[14]), "+f"(d[15]), "+f"(d[16]), "+f"(d[17]), "+f"(d[18]), "+f"(d[19]), "+f"(d[20]), "+f"(d[21]), "+f"(d[22]), "+f"(d[23]), "+f"(d[24]), "+f"(d[25]), "+f"(d[26]), "+f"(d[27]), "+f"(d[28]), "+f"(d[29]), "+f"(d[30]), "+f"(d[31]), "+f"(d[32]), "+f"(d[33]), "+f"(d[34]), "+f"(d[35]), "+f"(d[36]), "+f"(d[37]), "+f"(d[38]), "+f"(d[39]), "+f"(d[40]), "+f"(d[41]), "+f"(d[42]), "+f"(d[43]), "+f"(d[44]), "+f"(d[45]), "+f"(d[46]), "+f"(d[47]), "+f"(d[48]), "+f"(d[49]), "+f"(d[50]), "+f"(d[51]), "+f"(d[52]), "+f"(d[53]), "+f"(d[54]), "+f"(d[55]), "+f"(d[56]), "+f"(d[57]), "+f"(d[58]), "+f"(d[59]), "+f"(d[60]), "+f"(d[61]), "+f"(d[62]), "+f"(d[63])
        : "l"(da), "l"(db), "r"(acc), "n"(TB));
}
template <int TB>
__device__ __forceinline__ void wgmma_ss128_init(float (&d)[64], uint64_t da, uint64_t db) {
    asm volatile("{\n.reg .pred p;\nsetp.ne.b32 p, 0, 0;\n"
        "wgmma.mma_async.sync.aligned.m64n128k16.f32.bf16.bf16 {%0, %1, %2, %3, %4, %5, %6, %7, %8, %9, %10, %11, %12, %13, %14, %15, %16, %17, %18, %19, %20, %21, %22, %23, %24, %25, %26, %27, %28, %29, %30, %31, %32, %33, %34, %35, %36, %37, %38, %39, %40, %41, %42, %43, %44, %45, %46, %47, %48, %49, %50, %51, %52, %53, %54, %55, %56, %57, %58, %59, %60, %61, %62, %63}, %64, %65, p, 1, 1, 0, %66;\n}"
        : "=f"(d[0]), "=f"(d[1]), "=f"(d[2]), "=f"(d[3]), "=f"(d[4]), "=f"(d[5]), "=f"(d[6]), "=f"(d[7]), "=f"(d[8]), "=f"(d[9]), "=f"(d[10]), "=f"(d[11]), "=f"(d[12]), "=f"(d[13]), "=f"(d[14]), "=f"(d[15]), "=f"(d[16]), "=f"(d[17]), "=f"(d[18]), "=f"(d[19]), "=f"(d[20]), "=f"(d[21]), "=f"(d[22]), "=f"(d[23]), "=f"(d[24]), "=f"(d[25]), "=f"(d[26]), "=f"(d[27]), "=f"(d[28]), "=f"(d[29]), "=f"(d[30]), "=f"(d[31]), "=f"(d[32]), "=f"(d[33]), "=f"(d[34]), "=f"(d[35]), "=f"(d[36]), "=f"(d[37]), "=f"(d[38]), "=f"(d[39]), "=f"(d[40]), "=f"(d[41]), "=f"(d[42]), "=f"(d[43]), "=f"(d[44]), "=f"(d[45]), "=f"(d[46]), "=f"(d[47]), "=f"(d[48]), "=f"(d[49]), "=f"(d[50]), "=f"(d[51]), "=f"(d[52]), "=f"(d[53]), "=f"(d[54]), "=f"(d[55]), "=f"(d[56]), "=f"(d[57]), "=f"(d[58]), "=f"(d[59]), "=f"(d[60]), "=f"(d[61]), "=f"(d[62]), "=f"(d[63])
        : "l"(da), "l"(db), "n"(TB));
}
template <int TB>
__device__ __forceinline__ void wgmma_ss64(float (&d)[32], uint64_t da, uint64_t db, int acc) {
    asm volatile("{\n.reg .pred p;\nsetp.ne.b32 p, %34, 0;\n"
        "wgmma.mma_async.sync.aligned.m64n64k16.f32.bf16.bf16 {%0, %1, %2, %3, %4, %5, %6, %7, %8, %9, %10, %11, %12, %13, %14, %15, %16, %17, %18, %19, %20, %21, %22, %23, %24, %25, %26, %27, %28, %29, %30, %31}, %32, %33, p, 1, 1, 0, %35;\n}"
        : "+f"(d[0]), "+f"(d[1]), "+f"(d[2]), "+f"(d[3]), "+f"(d[4]), "+f"(d[5]), "+f"(d[6]), "+f"(d[7]), "+f"(d[8]), "+f"(d[9]), "+f"(d[10]), "+f"(d[11]), "+f"(d[12]), "+f"(d[13]), "+f"(d[14]), "+f"(d[15]), "+f"(d[16]), "+f"(d[17]), "+f"(d[18]), "+f"(d[19]), "+f"(d[20]), "+f"(d[21]), "+f"(d[22]), "+f"(d[23]), "+f"(d[24]), "+f"(d[25]), "+f"(d[26]), "+f"(d[27]), "+f"(d[28]), "+f"(d[29]), "+f"(d[30]), "+f"(d[31])
        : "l"(da), "l"(db), "r"(acc), "n"(TB));
}
template <int TB>
__device__ __forceinline__ void wgmma_ss64_init(float (&d)[32], uint64_t da, uint64_t db) {
    asm volatile("{\n.reg .pred p;\nsetp.ne.b32 p, 0, 0;\n"
        "wgmma.mma_async.sync.aligned.m64n64k16.f32.bf16.bf16 {%0, %1, %2, %3, %4, %5, %6, %7, %8, %9, %10, %11, %12, %13, %14, %15, %16, %17, %18, %19, %20, %21, %22, %23, %24, %25, %26, %27, %28, %29, %30, %31}, %32, %33, p, 1, 1, 0, %34;\n}"
        : "=f"(d[0]), "=f"(d[1]), "=f"(d[2]), "=f"(d[3]), "=f"(d[4]), "=f"(d[5]), "=f"(d[6]), "=f"(d[7]), "=f"(d[8]), "=f"(d[9]), "=f"(d[10]), "=f"(d[11]), "=f"(d[12]), "=f"(d[13]), "=f"(d[14]), "=f"(d[15]), "=f"(d[16]), "=f"(d[17]), "=f"(d[18]), "=f"(d[19]), "=f"(d[20]), "=f"(d[21]), "=f"(d[22]), "=f"(d[23]), "=f"(d[24]), "=f"(d[25]), "=f"(d[26]), "=f"(d[27]), "=f"(d[28]), "=f"(d[29]), "=f"(d[30]), "=f"(d[31])
        : "l"(da), "l"(db), "n"(TB));
}
__device__ __forceinline__ void wgmma_rs128(float (&d)[64], uint32_t a0, uint32_t a1, uint32_t a2, uint32_t a3, uint64_t db, int acc) {
    asm volatile("{\n.reg .pred p;\nsetp.ne.b32 p, %69, 0;\n"
        "wgmma.mma_async.sync.aligned.m64n128k16.f32.bf16.bf16 {%0, %1, %2, %3, %4, %5, %6, %7, %8, %9, %10, %11, %12, %13, %14, %15, %16, %17, %18, %19, %20, %21, %22, %23, %24, %25, %26, %27, %28, %29, %30, %31, %32, %33, %34, %35, %36, %37, %38, %39, %40, %41, %42, %43, %44, %45, %46, %47, %48, %49, %50, %51, %52, %53, %54, %55, %56, %57, %58, %59, %60, %61, %62, %63}, {%64, %65, %66, %67}, %68, p, 1, 1, 1;\n}"
        : "+f"(d[0]), "+f"(d[1]), "+f"(d[2]), "+f"(d[3]), "+f"(d[4]), "+f"(d[5]), "+f"(d[6]), "+f"(d[7]), "+f"(d[8]), "+f"(d[9]), "+f"(d[10]), "+f"(d[11]), "+f"(d[12]), "+f"(d[13]), "+f"(d[14]), "+f"(d[15]), "+f"(d[16]), "+f"(d[17]), "+f"(d[18]), "+f"(d[19]), "+f"(d[20]), "+f"(d[21]), "+f"(d[22]), "+f"(d[23]), "+f"(d[24]), "+f"(d[25]), "+f"(d[26]), "+f"(d[27]), "+f"(d[28]), "+f"(d[29]), "+f"(d[30]), "+f"(d[31]), "+f"(d[32]), "+f"(d[33]), "+f"(d[34]), "+f"(d[35]), "+f"(d[36]), "+f"(d[37]), "+f"(d[38]), "+f"(d[39]), "+f"(d[40]), "+f"(d[41]), "+f"(d[42]), "+f"(d[43]), "+f"(d[44]), "+f"(d[45]), "+f"(d[46]), "+f"(d[47]), "+f"(d[48]), "+f"(d[49]), "+f"(d[50]), "+f"(d[51]), "+f"(d[52]), "+f"(d[53]), "+f"(d[54]), "+f"(d[55]), "+f"(d[56]), "+f"(d[57]), "+f"(d[58]), "+f"(d[59]), "+f"(d[60]), "+f"(d[61]), "+f"(d[62]), "+f"(d[63])
        : "r"(a0), "r"(a1), "r"(a2), "r"(a3), "l"(db), "r"(acc));
}

__device__ __forceinline__ uint32_t pack2(float lo, float hi) {
    uint32_t r;
    asm("cvt.rn.bf16x2.f32 %0, %1, %2;" : "=r"(r) : "f"(hi), "f"(lo));
    return r;
}
__device__ __forceinline__ float bf_lo(uint32_t v) { return __uint_as_float(v << 16); }
__device__ __forceinline__ float bf_hi(uint32_t v) { return __uint_as_float(v & 0xffff0000u); }
__device__ __forceinline__ float rbf(float v) { return bf_lo(pack2(v, v)); }
__device__ __forceinline__ uint32_t badd(uint32_t a, uint32_t b) {
    uint32_t r;
    asm("add.rn.bf16x2 %0, %1, %2;" : "=r"(r) : "r"(a), "r"(b));
    return r;
}
__device__ __forceinline__ uint32_t bsub(uint32_t a, uint32_t b) {
    uint32_t r;
    asm("sub.rn.bf16x2 %0, %1, %2;" : "=r"(r) : "r"(a), "r"(b));
    return r;
}
__device__ __forceinline__ uint32_t bmul(uint32_t a, uint32_t b) {
    uint32_t r;
    asm("mul.rn.bf16x2 %0, %1, %2;" : "=r"(r) : "r"(a), "r"(b));
    return r;
}
__device__ __forceinline__ uint32_t ln_apply(uint32_t x, uint32_t mb, float rs, uint32_t scale, uint32_t shift) {
    const uint32_t d = bsub(x, mb);
    return badd(bmul(pack2(bf_lo(d) * rs, bf_hi(d) * rs), scale), shift);
}
__device__ __forceinline__ float ex2(float v) {
    float r;
    asm("ex2.approx.ftz.f32 %0, %1;" : "=f"(r) : "f"(v));
    return r;
}
__device__ __forceinline__ float rcp(float v) {
    float r;
    asm("rcp.approx.ftz.f32 %0, %1;" : "=f"(r) : "f"(v));
    return r;
}
__device__ __forceinline__ float sqrt_fast(float v) {
    float r;
    asm("sqrt.approx.ftz.f32 %0, %1;" : "=f"(r) : "f"(v));
    return r;
}
__device__ __forceinline__ float ln_rstd(float var) { return rcp(rbf(sqrt_fast(rbf(rbf(var) + 1e-5f)))); }
__device__ __forceinline__ float sigmoid(float v) { return rcp(1.f + ex2(-1.4426950408889634f * v)); }
__device__ __forceinline__ float quad_sum(float v) {
    v += __shfl_xor_sync(0xffffffffu, v, 1);
    return v + __shfl_xor_sync(0xffffffffu, v, 2);
}

constexpr uint32_t HI_128 = 0x40000040u, HI_IMG = 0x80000080u, HI_Q = 0x80000040u;
template <int M, int RH>
__device__ __forceinline__ uint4 img_pack(const float (&d)[64], float s) {
    uint4 v;
    v.x = pack2(d[16 * M + 2 * RH] * s, d[16 * M + 2 * RH + 1] * s);
    v.y = pack2(d[16 * M + 4 + 2 * RH] * s, d[16 * M + 5 + 2 * RH] * s);
    v.z = pack2(d[16 * M + 8 + 2 * RH] * s, d[16 * M + 9 + 2 * RH] * s);
    v.w = pack2(d[16 * M + 12 + 2 * RH] * s, d[16 * M + 13 + 2 * RH] * s);
    return v;
}
template <int M>
__device__ __forceinline__ void img_store_global(uint32_t img, uint32_t toff, const float (&d)[64], float s0, float s1) {
    uint4* p = reinterpret_cast<uint4*>(g_img + (img + toff)) + M * 32;
    p[0] = img_pack<M, 0>(d, s0);
    p[128] = img_pack<M, 1>(d, s1);
}
__device__ __forceinline__ void sts128(uint32_t a, uint4 v) {
    asm volatile("st.shared.v4.b32 [%0], {%1, %2, %3, %4};" ::"r"(a), "r"(v.x), "r"(v.y), "r"(v.z), "r"(v.w) : "memory");
}
constexpr float SM_C = 0.08838834764831845f * 1.4426950408889634f;
__device__ __forceinline__ float pack2f(float lo, float hi) {
    float r;
    asm("{\n.reg .b32 t;\ncvt.rn.bf16x2.f32 t, %1, %2;\nmov.b32 %0, t;\n}" : "=f"(r) : "f"(hi), "f"(lo));
    return r;
}
template <int M, bool SCALE, bool PARK>
__device__ __forceinline__ void pack_group(float (&d)[64], float (&v)[8], float s0, float s1) {
#pragma unroll
    for (int i = 0; i < 8; i++) {
        const int k = 16 * M + 4 * (i & 3) + 2 * (i >> 2);
        v[i] = SCALE ? pack2f(d[k] * (i < 4 ? s0 : s1), d[k + 1] * (i < 4 ? s0 : s1)) : pack2f(d[k], d[k + 1]);
        if (PARK && M > 0) d[16 * (M > 0 ? M - 1 : 0) + i] = v[i];
    }
}
__device__ __forceinline__ uint32_t q_off(uint32_t toff) {
    asm volatile("" : "+r"(toff));
    return (((toff >> 1) & ~2047u) ^ 8192) + (toff & 511);
}
template <int M>
__device__ __forceinline__ void ctx_store_part(float4* p, float (&d)[64], float i0, float i1) {
    float v[8];
    pack_group<M, true, true>(d, v, i0, i1);
    p[M * 32] = make_float4(v[0], v[1], v[2], v[3]);
    p[M * 32 + 128] = make_float4(v[4], v[5], v[6], v[7]);
}
__device__ __forceinline__ void ctx_store(uint32_t img, uint32_t toff, float (&o)[64], float i0, float i1) {
    asm volatile("" : "+r"(toff));
    float4* p = reinterpret_cast<float4*>(g_img + (img + toff));
    ctx_store_part<0>(p, o, i0, i1); ctx_store_part<1>(p, o, i0, i1); ctx_store_part<2>(p, o, i0, i1); ctx_store_part<3>(p, o, i0, i1);
}

__device__ __forceinline__ void slot_wait(uint32_t bars, uint32_t& ph, uint32_t slot) {
    mbar_wait(bars + 8 * slot, (ph >> slot) & 1);
    ph ^= 1u << slot;
}
__device__ __forceinline__ void release_if(uint32_t eb, uint32_t slot, bool on) {
    asm volatile("{\n.reg .pred p;\nsetp.ne.s32 p, %1, 0;\n@p mbarrier.arrive.shared::cluster.b64 _, [%0];\n}" ::"r"(eb + 8 * slot), "r"((int)on) : "memory");
}
__device__ __forceinline__ void slot_expect(uint32_t sb, uint32_t slot) {
    asm volatile("{\n.reg .pred p;\nelect.sync _|p, 0xffffffff;\n@p mbarrier.arrive.expect_tx.shared::cta.b64 _, [%0], 32768;\n}"
                 ::"r"(sb + BAR_FULL + 8 * slot) : "memory");
}
__device__ __forceinline__ void slot_acquire(uint32_t sb, uint32_t& ph, uint32_t slot) {
    slot_wait(sb + BAR_EMPTY, ph, slot);
    slot_expect(sb, slot);
}
__device__ __forceinline__ void load_bulk(uint32_t sb, uint32_t slot, uint32_t off, const void* src, uint32_t bytes, bool both, bool first) {
    if (both)
        asm volatile("{\n.reg .pred p;\nelect.sync _|p, 0xffffffff;\n"
                     "@p cp.async.bulk.shared::cluster.global.mbarrier::complete_tx::bytes.multicast::cluster.L2::cache_hint [%0], [%1], %5, [%2], %4, %3;\n}"
                     ::"r"(sb + slot * SLOT + off), "l"(src), "r"(sb + BAR_FULL + 8 * slot), "l"(first ? L2_FIRST : L2_NORMAL), "h"((uint16_t)3),
                     "r"(bytes) : "memory");
    else
        asm volatile("{\n.reg .pred p;\nelect.sync _|p, 0xffffffff;\n"
                     "@p cp.async.bulk.shared::cluster.global.mbarrier::complete_tx::bytes.L2::cache_hint [%0], [%1], %4, [%2], %3;\n}"
                     ::"r"(sb + slot * SLOT + off), "l"(src), "r"(sb + BAR_FULL + 8 * slot), "l"(first ? L2_FIRST : L2_NORMAL), "r"(bytes) : "memory");
}
__device__ __forceinline__ void load_tile(uint32_t sb, uint32_t slot, uint32_t off, const CUtensorMap* m, int row, int cb, bool both, bool first) {
    if (both)
        asm volatile("{\n.reg .pred p;\nelect.sync _|p, 0xffffffff;\n"
                     "@p cp.async.bulk.tensor.3d.shared::cluster.global.mbarrier::complete_tx::bytes.multicast::cluster.L2::cache_hint [%0], [%1, {%3, %4, %5}], [%2], %7, %6;\n}"
                     ::"r"(sb + slot * SLOT + off), "l"(m), "r"(sb + BAR_FULL + 8 * slot), "r"(0), "r"(row), "r"(cb),
                     "l"(first ? L2_FIRST : L2_NORMAL), "h"((uint16_t)3) : "memory");
    else
        asm volatile("{\n.reg .pred p;\nelect.sync _|p, 0xffffffff;\n"
                     "@p cp.async.bulk.tensor.3d.shared::cluster.global.mbarrier::complete_tx::bytes.L2::cache_hint [%0], [%1, {%3, %4, %5}], [%2], %6;\n}"
                     ::"r"(sb + slot * SLOT + off), "l"(m), "r"(sb + BAR_FULL + 8 * slot), "r"(0), "r"(row), "r"(cb),
                     "l"(first ? L2_FIRST : L2_NORMAL) : "memory");
}
__device__ __forceinline__ uint32_t ring_next(uint32_t r) { return r == 4 ? 0 : r + 1; }
__device__ __forceinline__ uint32_t w_table(int hp) { return hp ? 0x3104u : 0x4210u; }
__device__ __forceinline__ uint32_t a_table(int hp) { return hp ? 0x625u : 0x635u; }
__device__ __forceinline__ uint32_t a_next(uint32_t& t) {
    const uint32_t s = t & 15;
    t = (t >> 4) | (s << 8);
    return s;
}
constexpr uint32_t O_TABLE = 0x1604235u;
constexpr uint32_t SL_X = OFF == 0 ? 4 : OFF == 1 ? 3 : 1, SL_WD = OFF == 0 ? 6 : OFF == 1 ? 4 : 3, SL_WF = OFF == 0 ? 5 : OFF == 1 ? 6 : 4;
__device__ __forceinline__ uint32_t o_next(uint32_t& t) {
    const uint32_t s = t & 15;
    t = (t >> 4) | (s << 24);
    return s;
}
__device__ __forceinline__ int o_head(int i, int kh) { return i < 16 ? 4 * (i & 7) + 2 * (kh ^ 1) + (i >> 3) : 29 + 2 * kh; }

template <bool INIT>
__device__ __forceinline__ void gemm_issue(float (&d)[64], uint32_t a, uint32_t b, int acc, bool img) {
    uint64_t da = desc64(a, img ? HI_IMG : HI_128), db = desc64(b, HI_128);
    wg_fence();
#pragma unroll
    for (int k = 0; k < 8; k++) {
        if (INIT && k == 0) wgmma_ss128_init<1>(d, da, db);
        else wgmma_ss128<1>(d, da, db, k ? 1 : acc);
        desc_add(da, !(k & 1) ? 2 : img ? 30 : k == 3 ? 1018 : 2);
        desc_add(db, 128);
    }
    wg_commit();
}

__device__ __forceinline__ void step_retire(uint32_t eb, bool rel, uint32_t pend) {
    wg_wait<0>();
    release_if(eb, pend & 7, rel && (pend & 7) != 7);
    release_if(eb, pend >> 4, rel && pend < 0x70);
}
template <bool ODD>
__device__ __forceinline__ void proj_tile(float (&acc)[64], float (&prev)[64], int t, int q0, uint32_t sb, int wg, uint32_t eb, bool rel, uint32_t& fph,
                                          uint32_t wtab, uint32_t& atab, uint32_t& pend, uint32_t prev_img, uint32_t toff, float s0, float s1,
                                          uint32_t (&v)[32]) {
    const uint32_t a0 = desc_k(sb + (wg ^ (ODD && t == 5)) * 8192), b0 = desc_mn(sb);
    int q = q0;
#pragma unroll 1
    do {
        const uint32_t ws = (wtab >> (4 * q)) & 15, as = a_next(atab);
        if (!ODD && t != 2) slot_wait(sb + BAR_FULL, fph, ws);
        slot_wait(sb + BAR_FULL, fph, as);
        step_retire(eb, rel, pend);
        if (ODD && q == 2 && t == 5) {
            const uint32_t a = sb + 5 * SLOT + q_off(toff);
#pragma unroll
            for (int i = 0; i < 8; i++) sts128(a + (i >> 2) * 16384 + (i & 2) * 256 + (i & 1) * 1024, make_uint4(v[4 * i], v[4 * i + 1], v[4 * i + 2], v[4 * i + 3]));
        }
        bar_sync(1 + wg, 256);
        gemm_issue<false>(acc, a0 + as * (SLOT / 16), b0 + ws * (SLOT / 16), q, false);
        bar_arrive(2 - wg, 256);
        pend = (ODD && q == 1 && t == 5 ? 7 : as) | (ODD && t != 1 ? ws : 7) << 4;
        wg_wait<1>();
        reg_fence(prev);
        if (ODD && t == 5) {
            if (q == 0) {
#pragma unroll
                for (int i = 0; i < 32; i++) {
                    const int k = 16 * (i >> 3) + 4 * (i & 3) + ((i >> 1) & 2);
                    v[i] = pack2(prev[k], prev[k + 1]);
                }
            }
        } else {
            if (q == 0) img_store_global<0>(prev_img, toff, prev, s0, s1);
            if (q == 1) img_store_global<1>(prev_img, toff, prev, s0, s1);
            if (q == 2) img_store_global<2>(prev_img, toff, prev, s0, s1);
            if (q == 3) img_store_global<3>(prev_img, toff, prev, s0, s1);
        }
    } while (++q < (ODD && t == 5 ? 3 : 4));
}

__device__ __forceinline__ void qk_issue(float (&s)[64], uint32_t q, uint32_t k) {
    wg_fence();
    uint64_t da = desc64(q, HI_Q), db = desc64(k, HI_IMG);
    wgmma_ss128_init<0>(s, da, db);
#pragma unroll
    for (int i = 1; i < 8; i++) {
        desc_add(da, (i & 1) ? 2 : i == 4 ? 990 : 30);
        desc_add(db, (i & 1) ? 2 : 30);
        wgmma_ss128<0>(s, da, db, 1);
    }
    wg_commit();
}
__device__ __forceinline__ void qk_issue(float (&s)[32], uint32_t q, uint32_t k) {
    wg_fence();
    uint64_t da = desc64(q, HI_Q), db = desc64(k, HI_IMG);
    wgmma_ss64_init<0>(s, da, db);
#pragma unroll
    for (int i = 1; i < 8; i++) {
        desc_add(da, (i & 1) ? 2 : i == 4 ? 990 : 30);
        desc_add(db, (i & 1) ? 2 : 30);
        wgmma_ss64<0>(s, da, db, 1);
    }
    wg_commit();
}
__device__ __forceinline__ void pv_issue(float (&o)[64], const uint32_t (&p)[32], uint32_t v, int acc, bool half) {
    uint64_t db = desc64(v, HI_IMG);
    if (half) {
        asm volatile("// half" ::: "memory");
        wg_fence();
#pragma unroll
        for (int i = 0; i < 4; i++) {
            wgmma_rs128(o, p[4 * i], p[4 * i + 1], p[4 * i + 2], p[4 * i + 3], db, i ? 1 : acc);
            desc_add(db, 256);
        }
        wg_commit();
        asm volatile("// half" ::: "memory");
    } else {
        wg_fence();
#pragma unroll
        for (int i = 0; i < 8; i++) {
            wgmma_rs128(o, p[4 * i], p[4 * i + 1], p[4 * i + 2], p[4 * i + 3], db, i ? 1 : acc);
            desc_add(db, 256);
        }
        wg_commit();
    }
}
__device__ __forceinline__ void tri_mask(float (&s)[64], float x) {
#pragma unroll
    for (int k = 0; k < 16; k++) {
        float b;
        asm("sub.sat.f32 %0, %1, %2;" : "=f"(b) : "f"((float)(8 * (k >> 1) + (k & 1))), "f"(x));
        const int i = 32 + 4 * (k >> 1) + (k & 1);
        asm("fma.rn.f32 %0, %1, 0fFF61B1E6, %0;" : "+f"(s[i]) : "f"(b));
        if (k < 14) asm("fma.rn.f32 %0, %1, 0fFF61B1E6, %0;" : "+f"(s[i + 6]) : "f"(b));
    }
}
__device__ __forceinline__ void tri_mask_copy(float (&s)[64], const float (&h)[32], float x) {
#pragma unroll
    for (int i = 0; i < 32; i++) {
            asm("{\n.reg .pred p;\nsetp.lt.f32 p, %2, %3;\nselp.f32 %0, 0fFF800000, %1, p;\n}"
                : "=f"(s[i]) : "f"(h[i]), "f"(x), "f"((float)(8 * (i >> 2) - 4 * (i & 2) + (i & 1))));
        s[32 + i] = __uint_as_float(0xff800000u);
    }
}
constexpr float SM_HI = 1152921504606846976.f, SM_LO = 1.f / 1152921504606846976.f;
__device__ __forceinline__ bool softmax_unsafe(float t0, float t1, bool first) {
    bool bad = __any_sync(0xffffffffu, fmaxf(t0, t1) > SM_HI);
    if (first) {
        uint32_t a = __ballot_sync(0xffffffffu, t0 >= SM_LO), b = __ballot_sync(0xffffffffu, t1 >= SM_LO);
        a |= a >> 1;
        b |= b >> 1;
        bad |= ((a | (a >> 2)) & (b | (b >> 2)) & 0x11111111u) != 0x11111111u;
    }
    return bad;
}
__device__ __forceinline__ void softmax_remax(const float (&s)[64], float (&m)[2], bool first, float& m0, float& m1, float& a0, float& a1) {
    m0 = fmaxf(s[0], s[1]), m1 = fmaxf(s[2], s[3]);
#pragma unroll
    for (int k = 1; k < 16; k++) {
        m0 = fmaxf(m0, fmaxf(s[4 * k], s[4 * k + 1]));
        m1 = fmaxf(m1, fmaxf(s[4 * k + 2], s[4 * k + 3]));
    }
    m0 = fmaxf(m0, __shfl_xor_sync(0xffffffffu, m0, 1));
    m1 = fmaxf(m1, __shfl_xor_sync(0xffffffffu, m1, 1));
    m0 = fmaxf(m0, __shfl_xor_sync(0xffffffffu, m0, 2));
    m1 = fmaxf(m1, __shfl_xor_sync(0xffffffffu, m1, 2));
    if (!first) {
        m0 = fmaxf(m0, 0.f);
        m1 = fmaxf(m1, 0.f);
    }
    a0 = first ? 1.f : ex2(-m0);
    a1 = first ? 1.f : ex2(-m1);
    m[0] += m0;
    m[1] += m1;
}
template <int J0, int J1>
__device__ __forceinline__ void softmax_exp(const float (&s)[64], uint32_t (&p)[32], float (&t)[4]) {
#pragma unroll
    for (int k = J0; k < J1; k++) {
        const float e0 = ex2(s[4 * k]), e1 = ex2(s[4 * k + 1]), e2 = ex2(s[4 * k + 2]), e3 = ex2(s[4 * k + 3]);
        if (k == 0) { t[0] = e0; t[1] = e1; t[2] = e2; t[3] = e3; }
        else { t[0] += e0; t[1] += e1; t[2] += e2; t[3] += e3; }
        p[2 * k] = pack2(e0, e1);
        p[2 * k + 1] = pack2(e2, e3);
    }
}
__device__ __forceinline__ void mma16816(float (&d)[4], const uint32_t* a, uint32_t b0, uint32_t b1) {
    asm("mma.sync.aligned.m16n8k16.row.col.f32.bf16.bf16.f32 {%0, %1, %2, %3}, {%4, %5, %6, %7}, {%8, %9}, {%0, %1, %2, %3};"
        : "+f"(d[0]), "+f"(d[1]), "+f"(d[2]), "+f"(d[3]) : "r"(a[0]), "r"(a[1]), "r"(a[2]), "r"(a[3]), "r"(b0), "r"(b1));
}
__device__ __forceinline__ uint32_t best_key(const uint32_t* keys, int lane, uint32_t ep) {
#pragma unroll 1
    for (;;) {
        const uint4 k = ld_poll(reinterpret_cast<const uint4*>(keys) + lane);
        const int n = __popc(__ballot_sync(0xffffffffu, (((k.x ^ ep) | (k.y ^ ep) | (k.z ^ ep) | (k.w ^ ep)) & 31) == 0));
        if (poll_done(n == 32, n < KN ? KSLEEP : KSLEEP2)) return __reduce_max_sync(0xffffffffu, max(max(k.x, k.y), max(k.z, k.w)));
    }
}

__global__ void __cluster_dims__(2, 1, 1) __launch_bounds__(384, 1)
fused_kernel(const __grid_constant__ CUtensorMap tm_ckv, const __grid_constant__ CUtensorMap tm_wq,
             const __grid_constant__ CUtensorMap tm_wuk, const __grid_constant__ CUtensorMap tm_wuv,
             const __grid_constant__ CUtensorMap tm_wo, const __grid_constant__ CUtensorMap tm_wg,
             const __grid_constant__ CUtensorMap tm_wu,
             const __grid_constant__ CUtensorMap tm_wm, const __grid_constant__ CUtensorMap tm_x, const Params P) {
    extern __shared__ __align__(1024) uint8_t smem[];
    if (threadIdx.x == 352) {
        asm volatile("prefetch.tensormap [%0];" ::"l"(&tm_ckv) : "memory");
        asm volatile("prefetch.tensormap [%0];" ::"l"(blockIdx.x >= NCTA ? &tm_wm : (blockIdx.x & 1) ? &tm_wuv : &tm_wuk) : "memory");
    }
    const uint32_t sb = (uint32_t)__cvta_generic_to_shared(smem);
    const int tid = threadIdx.x, lane = tid & 31, warp = __shfl_sync(0xffffffffu, tid >> 5, 0), wg = warp >> 2;
    const uint32_t sm = blockIdx.x < 8 ? blockIdx.x + 124 : blockIdx.x - 8, smq = ((sm - 64) * 147) >> 11;
    const int rb = sm < 64 ? (sm & 14) * 8 + (sm >> 4) * 2 + (sm & 1)
                 : sm < 120 ? ((sm - 64 - smq * 14) & 14) * 8 + 24 + smq * 2 + (sm & 1) : sm < 124 ? sm + 8 : sm - 116;
    const int grp = rb >> 3, j = rb & 7, kh = (grp >> 1) & 1;
    const int cq = (j & 1) + ((grp >> 1) & 2), ort = (grp & 8) + (grp & 1) * 4 + (j >> 1);
    if (warp == 0) TS(0);

    const CUtensorMap* tw = (j & 1) ? &tm_wuv : &tm_wuk;
    if (lane == 0) {
        if (warp == 8) {
#pragma unroll
            for (int i = 0; i < 7; i++) mbar_init(sb + BAR_FULL + 8 * i, 1);
            fence_async_smem();
        } else if (warp < 11) {
            const int w = warp - (warp > 8);
            const u64 cnt = (w < 5 ? (rb < NCTA ? 0x888888884444444ull : 0x888888888888888ull) : 0x111812111111118ull) >> (12 * (w % 5));
#pragma unroll
            for (int i = 0; i < 3; i++) mbar_init(sb + BAR_EMPTY + 24 * w + 8 * i, ((uint32_t)cnt >> (4 * i)) & 15);
        }
        asm volatile("fence.mbarrier_init.release.cluster;" ::: "memory");
    }
    __syncwarp();
    asm volatile("barrier.cluster.arrive.relaxed.aligned;" ::: "memory");
    if (warp == 8) {
        if (rb < NCTA) {
#pragma unroll 1
            for (int u = 0; u < 4; u++) {
                const uint32_t ws = u + (u == 3), as = (0x635u >> (4 * u)) & 15;
                slot_expect(sb, ws);
                load_tile(sb, ws, 0, tw, u * 128, 4 * grp, false, HINT & 1);
                if (u == 3) break;
                slot_expect(sb, as);
                load_tile(sb, as, 0, &tm_ckv, (j >> 1) * 128, u * 2, false, false);
                load_tile(sb, as, 16384, &tm_ckv, (j >> 1) * 128, u * 2 + 1, false, false);
            }
        } else {
#pragma unroll 1
            for (int i = 0; i < 6; i++) {
                slot_expect(sb, i);
                load_tile(sb, i, 0, &tm_wm, i * 64, (rb - NCTA) * 4, false, HINT & 64);
                if (i > 3) tma3d_prefetch(&tm_wm, i * 64 + 128, (rb - NCTA) * 4);
            }
        }
    }
    asm volatile("barrier.cluster.wait.aligned;" ::: "memory");

    if (rb >= NCTA) {
        const int sp = rb - NCTA;
        const uint32_t ep = __ldcg(&g_sync.epoch[0]) + 1;
        uint32_t ph = 0, sl = 0;
        if (warp == 8) {
#pragma unroll 1
            for (int i = 6; i < 54 + 2 * OFF; i++) {
                slot_acquire(sb, ph, sl);
                const int k = i - 24;
                load_tile(sb, sl, 0, i < 24 ? &tm_wm : i >= 54 ? &tm_wo : (k & 2) ? &tm_wu : &tm_wg, i < 24 ? (i & 7) * 64 : i >= 54 ? (i - 38 - 2 * OFF) * 256 : (k & 1) * 256,
                          i < 24 ? (i >> 3) * 16 + sp * 4 : i >= 54 ? sp * 2 : sp * 7 + (k >> 2), false, true);
                if (++sl == 6) sl = 0;
                if (i == 51) { i = 53; sl = 0; }
            }
            bar_sync(4, 64);
            slot_wait(sb + BAR_EMPTY, ph, 4);
            slot_wait(sb + BAR_EMPTY, ph, 5);
            ph = 0x3f, sl = 0;
#pragma unroll 1
            for (int h = 0; h < 32; h++) {
                step_watch(sb + SM_EP + 16, h + 1);
                fence_async_global();
                const uint8_t* src = g_ctx + (size_t)(((h >> 1) ^ 8) * 32 + 30 - 4 * OFF) * SLOT + (h & 1) * 16384;
#pragma unroll 1
                for (int k = 0; k <= 2 * OFF; k++, src += 2 * SLOT) {
                    slot_wait(sb + BAR_DONE, ph, sl);
                    const uint32_t f = sb + BAR_FLAG + 8 * sl, d = sb + 4 * SLOT + sl * 16384;
                    asm volatile("{\n.reg .pred p;\nelect.sync _|p, 0xffffffff;\n@p mbarrier.arrive.expect_tx.shared::cta.b64 _, [%0], 16384;\n}" ::"r"(f) : "memory");
                    if (k == 0)
                        asm volatile("{\n.reg .pred p;\nelect.sync _|p, 0xffffffff;\n"
                                     "@p cp.async.bulk.tensor.3d.shared::cluster.global.mbarrier::complete_tx::bytes [%0], [%1, {%3, %4, %5}], [%2];\n}"
                                     ::"r"(d), "l"(&tm_x), "r"(f), "r"(0), "r"((h ^ 16) * 64), "r"(sp * 2) : "memory");
                    else
                        asm volatile("{\n.reg .pred p;\nelect.sync _|p, 0xffffffff;\n"
                                     "@p cp.async.bulk.shared::cluster.global.mbarrier::complete_tx::bytes [%0], [%1], 16384, [%2];\n}"
                                     ::"r"(d), "l"(src), "r"(f) : "memory");
                    if (++sl == 6) sl = 0;
                }
            }
        } else if (warp == 9) {
#pragma unroll 1
            for (int t = 0; t <= 16; t++) {
                asm volatile("st.release.cta.shared.u32 [%0], %1;" ::"r"(sb + SM_EP + 16), "r"(2 * t) : "memory");
                if (t == 0) bar_sync(4, 64);
                if (lane < 4 && t < 16) flag_wait(&g_sync.ctxcnt[(t ^ 8) * 32 + 24 + 2 * lane], ep);
                __syncwarp();
            }
        } else if (warp < 8) {
            const uint32_t c2 = __ldg(reinterpret_cast<const uint32_t*>(P.c) + tid);
            uint32_t* sc = reinterpret_cast<uint32_t*>(smem + SM_TAB);
            sc[tid] = pack2(bf_lo(c2) * sigmoid(bf_lo(c2)), bf_hi(c2) * sigmoid(bf_hi(c2)));
            bar_sync(1, 256);
            const uint32_t a = sb + (warp >> 1) * 8192 + ((lane >> 4) * 8 + (lane & 7)) * 128, ch = (warp & 1) * 4 + ((lane >> 3) & 1);
#pragma unroll 1
            for (int ps = 0; ps < 3; ps++) {
                float d[2][4] = {};
#pragma unroll 1
                for (int bt = 0; bt < 8; bt++) {
                    slot_wait(sb + BAR_FULL, ph, sl);
#pragma unroll
                    for (int i = 0; i < 8; i++) {
                        uint32_t w[4];
                        asm volatile("ldmatrix.sync.aligned.m8n8.x4.trans.shared.b16 {%0, %1, %2, %3}, [%4];" : "=r"(w[0]), "=r"(w[1]), "=r"(w[2]), "=r"(w[3])
                                     : "r"(a + sl * SLOT + (i >> 1) * 2048 + (((ch + 2 * (i & 1)) ^ (lane & 7)) << 4)) : "memory");
                        mma16816(d[i & 1], w, sc[bt * 32 + (i >> 1) * 8 + (lane & 3)], sc[bt * 32 + (i >> 1) * 8 + 4 + (lane & 3)]);
                    }
                    __syncwarp();
                    mbar_arrive_if(sb + BAR_EMPTY + 8 * sl, lane == 0);
                    if (++sl == 6) sl = 0;
                }
                const float v = (lane & 2) ? ((lane & 1) ? d[1][2] : d[1][0]) : ((lane & 1) ? d[0][2] : d[0][0]);
                const int col = sp * 256 + warp * 32 + (lane & 3) * 8 + (lane >> 2);
                if (ps == 0) st_pub(g_mod1 + col, (pack2(0.f, v) & 0xffff0000u) | (ep & 0xffffu), true);
                else g_mod[ps * 1024 + col] = __float2bfloat16_rn(v);
                if (warp == 0) TS(1 + ps);
            }
#pragma unroll 1
            for (int k = 0; k < 28; k++) {
                slot_wait(sb + BAR_FULL, ph, sl);
                uint4* dst = reinterpret_cast<uint4*>(g_wf) + (sp * 28 + (k & ~3)) * 2048 + (k & 3) * 512 + tid;
#pragma unroll 4
                for (int i = 0; i < 8; i++) {
                    const int row = (i & 1) * 128 + (tid >> 1);
                    __stcs(dst + (i >> 1) * 2048 + (i & 1) * 256, lds128(sb + sl * SLOT + row * 128 + ((((i & 6) + ((tid ^ (row >> 2)) & 1)) ^ (row & 7)) << 4)));
                }
                __syncwarp();
                mbar_arrive_if(sb + BAR_EMPTY + 8 * sl, lane == 0);
                if (++sl == 6) sl = 0;
            }
            bar_sync(1, 256);
            if (tid < 2) {
                flag_add(&g_sync.cnt[7 * 8]);
                flag_wait(&g_sync.cnt[7 * 8], 8 * ep);
            }
            if (warp == 0) TS(4);
            bar_sync(1, 256);
            uint32_t ga[16], x2[32];
#pragma unroll
            for (int i = 0; i < 16; i++) ga[i] = __ldcg(reinterpret_cast<const uint32_t*>(g_mod) + 512 + sp * 64 + (lane & 3) + 4 * i);
#pragma unroll 1
            for (int i = 0; i < 2 * OFF; i++) slot_wait(sb + BAR_FULL, ph, i);
            float d[64];
            uint32_t u = (2 * OFF + 1) * wg, up = 0;
            if (wg == 1) bar_arrive(2, 256);
#pragma unroll 1
            for (int h = wg; h < 32; h += 2) {
                mbar_wait(sb + BAR_FLAG + 8 * u, up);
                const uint32_t xa = sb + 4 * SLOT + u * 16384 + ((warp & 3) * 16 + (lane & 15)) * 128;
#pragma unroll
                for (int k = 0; k < 8; k++)
                    asm volatile("ldmatrix.sync.aligned.m8n8.x4.shared.b16 {%0, %1, %2, %3}, [%4];"
                                 : "=r"(x2[4 * k]), "=r"(x2[4 * k + 1]), "=r"(x2[4 * k + 2]), "=r"(x2[4 * k + 3])
                                 : "r"(xa + (k >> 2) * 8192 + (((2 * (k & 3) + (lane >> 4)) ^ (lane & 7)) << 4)) : "memory");
                mbar_arrive_if(sb + BAR_DONE + 8 * u, lane < 2);
                bar_sync(2 + wg, 256);
#pragma unroll 1
                for (int k = 0; k < 2 * OFF; k++) {
                    const uint32_t pu = u;
                    if (++u == 6) { u = 0; up ^= 1; }
                    mbar_wait(sb + BAR_FLAG + 8 * u, up);
                    gemm_issue<false>(d, desc_k(sb + 4 * SLOT) + u * 1024, desc_mn(sb) + k * (SLOT / 16), k, true);
                    wg_wait<1>();
                    mbar_arrive_if(sb + BAR_DONE + 8 * pu, lane < 2 && k);
                }
                if (h < 31) bar_arrive(3 - wg, 256);
                wg_wait<0>();
                reg_fence(d);
                mbar_arrive_if(sb + BAR_DONE + 8 * u, lane < 2);
                u += 2 * OFF + 2;
                if (u >= 6) { u -= 6; up ^= 1; }
                uint4* op = g_x2 + ((h ^ 16) * 4 + sp) * 1024 + (tid & 127);
#pragma unroll
                for (int v = 0; v < 8; v++) {
                    uint32_t y[4];
#pragma unroll
                    for (int i = 0; i < 4; i++) {
                        const int k = 4 * v + i;
                        y[i] = pack2(fmaf(bf_lo(ga[k >> 1]), d[2 * k], bf_lo(x2[k])), fmaf(bf_hi(ga[k >> 1]), d[2 * k + 1], bf_hi(x2[k])));
                    }
                    op[v * 128] = make_uint4(y[0], y[1], y[2], y[3]);
                }
            }
            bar_sync(1, 256);
            if (tid == 0) flag_add(&g_sync.cnt[15 * 8]);
            if (warp == 0) TS(5);
        }
        return;
    }

    if (wg == 2) {
        asm volatile("setmaxnreg.dec.sync.aligned.u32 40;");
        if (warp == 8) {
            const uint32_t rank = j & 1, half = rank * 16384;
            uint32_t eph = 0, r = 0;
            *reinterpret_cast<volatile uint32_t*>(smem + SM_EP + 20) = 0;
#pragma unroll 1
            for (int hp = 0; hp < 2; hp++) {
                uint32_t wtab = w_table(hp), atab = a_table(hp);
                const int hc = 4 * grp + 2 * hp;
#pragma unroll 1
                for (int u = 3 - 3 * hp; u < 16; u++) {
                    if (hp && u < 4) {
                        const uint32_t ws = (wtab >> (4 * u)) & 15;
                        slot_acquire(sb, eph, ws);
                        load_tile(sb, ws, 0, tw, u * 128, hc, false, HINT & 1);
                        PT();
                    }
                    if (hp == 1 && (u & 7) == 4) mbar_wait(sb + BAR_FLAG + 24 + (u & 8), 0);
                    const uint32_t as = a_next(atab);
                    slot_acquire(sb, eph, as);
                    load_tile(sb, as, half, &tm_ckv, ((u & 12) + (j >> 1)) * 128, (u & 3) * 2 + rank, true, (HINT & 8) && hp);
                    PT();
                    if (hp == 1 && (u | 2) == 3 && lane == 0)
                        asm volatile("red.relaxed.gpu.global.add.u32 [%0], 1;" ::"l"(&g_sync.cnt[(grp * 8 + 3 + (u >> 1)) * 8]) : "memory");
                }
                const uint8_t* src = g_h + (15 - j) * 4 * SLOT;
#pragma unroll 1
                for (int u = 0; u < 8; u++) {
                    if (u == 0 || u == KVG) {
                        mbar_wait(sb + BAR_FLAG + (u ? 8 + 32 * hp : 0), 0);
                        fence_async_global();
                    }
                    if (u < 4) {
                        const uint32_t ws = (wtab >> (4 * u)) & 15;
                        slot_acquire(sb, eph, ws);
                        load_tile(sb, ws, 0, &tm_wq, u * 128, hc, false, HINT & 1);
                        PT();
                    }
                    const uint32_t as = a_next(atab);
                    slot_acquire(sb, eph, as);
                    load_bulk(sb, as, 0, src, SLOT, false, (HINT & 8) && hp);
                    PT();
                    src += u == 3 ? (8 * j - 63) * SLOT : SLOT;
                }
                const int step = hp ? -2 * SLOT : 2 * SLOT;
                src = g_KV + (size_t)(grp * 32 + 30 * hp) * SLOT + half - step;
#pragma unroll 1
                for (int n = 0; n <= 17; n++) {
                    if (n == 8) {
                        mbar_wait(sb + BAR_FLAG + 16 + 32 * hp, 0);
                        fence_async_global();
                    }
                    const uint8_t* v = src + SLOT;
                    src += n < 16 - j ? step : n == 16 - j ? (2 * j - 15) * step : -step;
                    if (n < 17) {
                        slot_acquire(sb, eph, r);
                        if (n != 15 - (j & 6)) load_bulk(sb, r, half, src, SLOT / 2, true, HINT & 4);
                        else load_bulk(sb, r, 0, src - half, SLOT, false, HINT & 4);
                        PT();
                        r = ring_next(r);
                    }
                    if (n) {
                        slot_acquire(sb, eph, r);
                        if (n != 16 - (j & 6)) load_bulk(sb, r, half, v, SLOT / 2, true, HINT & 4);
                        else load_bulk(sb, r, 0, v - half, SLOT, false, HINT & 4);
                        PT();
                        r = ring_next(r);
                    }
                    asm volatile("st.volatile.shared.u32 [%0], %1;" ::"r"(sb + SM_EP + 16), "r"(18 * hp + n + 1) : "memory");
                }
            }
            uint32_t otab = O_TABLE, ready = 0;
#pragma unroll 1
            for (int i = 0; i < 17; i += i == 7 - OFF ? 1 + OFF : 1) {
                const bool dyn = i >= 8 && i < 15;
                const uint32_t want = dyn ? 15u << (4 * (i - 8)) : 1u << max(i + 14, 28);
                if (!(ready & want)) {
                    do {
                        asm volatile("ld.acquire.cta.shared.u32 %0, [%1];" : "=r"(ready) : "r"(sb + SM_EP + 20) : "memory");
                        ready = __shfl_sync(0xffffffffu, ready, 0);
                    } while (!(ready & want));
                    fence_async_global();
                }
                const int head = o_head(dyn ? (ready >> (4 * (i - 8))) & 15 : i, kh);
                const uint32_t as = o_next(otab), ws = o_next(otab), off = i < 15 ? half : kh * 16384;
                slot_acquire(sb, eph, as);
                load_bulk(sb, as, off, g_ctx + (size_t)(ort * 32 + head) * SLOT + off, SLOT / 2, i < 15, HINT & 16);
                if (i >= 15) load_bulk(sb, as, off ^ 16384, i == 15 ? g_x2 + ((ort * 2 + kh) * 4 + cq) * 1024 : reinterpret_cast<const uint4*>(P.wdown) + min(rb, NFFN - 1) * 1024, SLOT / 2, false, false);
                PT();
                slot_acquire(sb, eph, ws);
                load_tile(sb, ws, 0, &tm_wo, head * 128, cq * 2, false, HINT & 2);
                PT();
                if (i == 0) o_next(otab);
            }
            if (rb < NFFN) {
                slot_acquire(sb, eph, SL_WF);
                load_bulk(sb, SL_WF, 0, g_wf + rb * SLOT, SLOT, false, false);
            }
        } else if (warp == 9) {
            *reinterpret_cast<volatile uint32_t*>(smem + SM_EP + 16) = 0;
            l2_prefetch(P.ckv + rb * 2048, 4096);
            mbar_watch(sb + BAR_FULL, 0);
            l2_prefetch(P.ckv + 512 * 512 + rb * 2048, 4096);
            mbar_watch(sb + BAR_FULL + 8 * XPF, 0);
            l2_prefetch(P.x + rb * 8192, 16384);
            mbar_watch(sb + BAR_FULL + 8 * 4, 0);
            l2_prefetch(P.ckv + 1024 * 512 + rb * 4096, 8192);
            TS(40);
#pragma unroll 1
            for (int i = 0; i < 13; i++) {
                step_watch(sb + SM_EP + 16, i == 0 ? 0 : i < 5 ? PFA + i : 13 + PFB + i);
                if (i == 10) mbar_watch(sb + BAR_FLAG + 8 * 7, 0);
                const int rf = min(rb, NFFN - 1), pc = 4 * (i - 5) + cq;
                const uint8_t* p = i == 3 ? reinterpret_cast<const uint8_t*>(P.ckv) + rb * 16384
                                 : i == 4 ? g_h + rb * 16384
                                 : i < 8 ? g_ctx + (size_t)(ort * 32 + o_head(pc >> 1, kh)) * SLOT + (pc & 1) * 16384
                                 : i < 10 ? reinterpret_cast<const uint8_t*>(P.wo) + (grp * 16 + (i & 1) * 8 + j) * 16384
                                 : i == 10 ? reinterpret_cast<const uint8_t*>(P.wdown) + rf * 16384 : g_wf + rf * SLOT + (i & 1) * 16384;
                if (i >= 3) l2_prefetch(p, 16384);
                else if ((i | j) & 1) tma3d_prefetch(i == 1 ? tw : &tm_wq, (j >> 1) * 128, grp * 4 + (i ? 2 : 0));
            }
            const uint32_t v = lds32(sb + SM_EP) - 1;
            sts128(sb + SM_RED + lane * 16, make_uint4(v, v, v, v));
            fence_async_smem();
            __syncwarp();
#pragma unroll 1
            for (int i = 0; i < OB / 32; i++) bulk_store(g_out + rb * OB + i * 32, sb + SM_RED, 512, false);
            asm volatile("cp.async.bulk.commit_group;\ncp.async.bulk.wait_group 0;" ::: "memory");
            fence_async_global();
            __syncwarp();
            mbar_arrive_if(sb + BAR_PF, lane == 0);
            if (lane == 0) mbar_watch(sb + BAR_END, 0);
        } else {
            const uint32_t ep = __ldcg(&g_sync.epoch[0]) + 1;
            asm volatile("st.shared.u32 [%0], %1;" ::"r"(sb + SM_EP), "r"(ep) : "memory");
            mbar_wait(sb + BAR_FULL + 8 * 4, 0);
            {
                uint4 v[4];
                for (;;) {
                    uint32_t bad = 0;
#pragma unroll
                    for (int k = 0; k < 4; k++) v[k] = ld_poll(reinterpret_cast<const uint4*>(g_mod1) + (warp & 1) * 128 + k * 32 + lane);
#pragma unroll
                    for (int k = 0; k < 4; k++) bad |= (v[k].x ^ ep) | (v[k].y ^ ep) | (v[k].z ^ ep) | (v[k].w ^ ep);
                    if (poll_done((bad & 0xffff) == 0, 100)) break;
                }
                const uint32_t one = (warp & 1) ? ONE2 : 0x80008000u;
#pragma unroll
                for (int k = 0; k < 4; k++)
                    *reinterpret_cast<uint2*>(smem + SM_TAB + (warp & 1) * 1024 + k * 256 + lane * 8) =
                        make_uint2(badd(__byte_perm(v[k].x, v[k].y, 0x7632), one), badd(__byte_perm(v[k].z, v[k].w, 0x7632), one));
            }
            __syncwarp();
            mbar_arrive_if(sb + BAR_FLAG + 8 * 8, lane == 0);
            if (warp == 10) {
#pragma unroll 1
                for (int i = 0; i < 9; i++) {
                    mbar_sleep(sb + BAR_DONE + 8 * i);
                    if (lane == 0) flag_add(i && ((i - 1) & 2) ? &g_sync.ctxcnt[((i & 1) ? 15 - j : j) * 32 + 2 * grp + (i > 4)] : &g_sync.cnt[(grp * 8 + i) * 8]);
                    if (i == 0) TS(43);
                }
            } else {
                TS(42);
#pragma unroll 1
                for (int i = 0; i < 8; i++) {
                    mbar_sleep(sb + BAR_DONE + 8 * (i == 7 ? 6 : i == 4 ? 3 : i));
                    if (lane < 2) flag_wait(&g_sync.cnt[((i == 0 ? (lane ? j : 15 - j) : i == 7 ? 0 : grp) * 8 + i) * 8], 8 * ep);
                    __syncwarp();
                    mbar_arrive_if(sb + BAR_FLAG + 8 * i, lane == 0 && i < 7);
                    TS(48 + i);
                }
                const uint32_t *mp = reinterpret_cast<const uint32_t*>(g_mod) + lane, *wp = reinterpret_cast<const uint32_t*>(P.wr) + lane;
                float ra = 0.f, rs = 0.f;
#pragma unroll 1
                for (int k = 0; k < 256; k += 32) {
                    const uint32_t ga = __ldcg(mp + 512 + k), sh = __ldcg(mp + 768 + k), c1 = badd(__ldcg(mp + 1024 + k), ONE2);
                    const uint32_t gb = __ldcg(mp + 1280 + k), ww = __ldg(wp + k);
                    const uint32_t a = bmul(c1, ww);
                    ra += bf_lo(a) + bf_hi(a);
                    rs = fmaf(bf_lo(sh), bf_lo(ww), fmaf(bf_hi(sh), bf_hi(ww), rs));
                    if (k >> 6 == cq) {
                        sts128(sb + SM_TAB + ((k & 32) + lane) * 16, make_uint4(ga << 16, ga & 0xffff0000u, a, 0));
                        sts128(sb + SM_TAB + 1024 + ((k & 32) + lane) * 16, make_uint4(c1, sh, gb, 0));
                    }
                }
#pragma unroll 1
                for (int o = 16; o > 0; o >>= 1) {
                    ra += __shfl_xor_sync(0xffffffffu, ra, o);
                    rs += __shfl_xor_sync(0xffffffffu, rs, o);
                }
                *reinterpret_cast<float2*>(smem + SM_EP + 8) = make_float2(ra, rs);
                __syncwarp();
                mbar_arrive_if(sb + BAR_FLAG + 8 * 7, lane == 0);
                const uint32_t* f = lane < 17 ? &g_sync.ctxcnt[ort * 32 + o_head(lane, kh)] : &g_sync.cnt[15 * 8];
                uint32_t ready = -(j & 1), list = 0, sh = 0, qa;
                asm("mapa.shared::cluster.u32 %0, %1, %2;" : "=r"(qa) : "r"(sb + SM_EP + 20), "r"(lane & 1));
                while (ready != ~0u) {
                    uint32_t v, now;
                    do {
                        asm volatile("ld.acquire.gpu.global.u32 %0, [%1];" : "=r"(v) : "l"(f) : "memory");
                        now = __ballot_sync(0xffffffffu, (int)(v - (lane < 17 ? ep : NSPARE * ep)) >= 0);
                    } while (!poll_done(now != ready, POLL_NS));
#pragma unroll 1
                    for (uint32_t fresh = now & ~ready & 0x7f00; fresh; fresh &= fresh - 1, sh += 4) list |= (__ffs(fresh) - 1) << sh;
                    list |= (((now & 0xff) + 1) >> 8 << 28) | ((now & (now >> 2) & 0x18000) << 14);
                    if (lane < 2) asm volatile("st.relaxed.cluster.shared::cluster.u32 [%0], %1;" ::"r"(qa), "r"(list) : "memory");
                    if ((ready & 0xff) != 0xff && (now & 0xff) == 0xff) mbar_sleep(sb + BAR_DONE + 8 * 7);
                    ready = now;
                }
                TS(45);
            }
        }
    } else {
        const bool elected = (tid & 127) == 0, rel = (tid & 95) == 0;
        uint32_t eb;
        asm("mapa.shared::cluster.u32 %0, %1, %2;" : "=r"(eb) : "r"(sb + BAR_EMPTY), "r"(warp & 1));
        const int g = lane >> 2, c4 = lane & 3;
        uint32_t toff = warp * 4096 + g * 64 + ((c4 ^ (g >> 1)) << 4);
        uint32_t fph = 0x3f, r = 0;
        if (wg == 1) bar_arrive(1, 256);
        const uint32_t kd = desc_k(sb), wd = desc_mn(sb), vd = ((sb & 0x3ffff) >> 4) | (32u << 16);
        const int nL = 16 - j, hn = nL - 1 + wg;
        float s[64], o[64], li[2] = {0.f, 0.f};
        uint32_t cimg = 0;
        const float sc = (j & 1) ? 1.f : SM_C;
#pragma unroll 1
        for (int q = 0; q < 3; q++) {
            const uint32_t as = (0x635u >> (4 * q)) & 15;
            mbar_wait(sb + BAR_FULL + 8 * q, 0);
            mbar_wait(sb + BAR_FULL + 8 * as, 0);
            bar_sync(1 + wg, 256);
            gemm_issue<false>(s, kd + wg * 512 + as * (SLOT / 16), wd + q * (SLOT / 16), q, false);
            bar_arrive(2 - wg, 256);
            wg_wait<0>();
            release_if(eb, as, rel);
        }
        {
            const int xrow = rb * 16 + warp * 2;
            const uint4* xp = reinterpret_cast<const uint4*>(P.x) + xrow * 64;
            const uint32_t img = (grp * 32 + j) * SLOT;
            uint32_t x[16], x0[2];
            float st[4] = {0.f, 0.f, 0.f, 0.f};
            mbar_wait(sb + BAR_FULL + 8 * 4, 0);
#pragma unroll
            for (int q = 3; q < 8; q++) {
                const uint32_t ws = (0x4210u >> (4 * (q & 3))) & 15, as = (0x635u >> (4 * (q % 3))) & 15;
                mbar_wait(sb + BAR_FULL + 8 * as, (q / 3) & 1);
                bar_sync(1 + wg, 256);
                if (q == 3) gemm_issue<false>(s, kd + wg * 512 + as * (SLOT / 16), wd + ws * (SLOT / 16), 1, false);
                else if (q == 4) gemm_issue<true>(o, kd + wg * 512 + as * (SLOT / 16), wd + ws * (SLOT / 16), 0, false);
                else gemm_issue<false>(o, kd + wg * 512 + as * (SLOT / 16), wd + ws * (SLOT / 16), 1, false);
                bar_arrive(2 - wg, 256);
                sched_fence(fph, P.zero);
                if (q > 3) reg_fence(s);
                if (q == 3) {
                    asm volatile("setmaxnreg.inc.sync.aligned.u32 232;");
#pragma unroll
                    for (int i = 0; i < 4; i++)
                        asm volatile("ld.global.nc.v4.u32 {%0, %1, %2, %3}, [%4];" : "=r"(x[4 * i]), "=r"(x[4 * i + 1]), "=r"(x[4 * i + 2]), "=r"(x[4 * i + 3])
                                     : "l"(xp + lane + 32 * i) : "memory");
#pragma unroll
                    for (int i = 0; i < 2; i++) asm volatile("ld.global.nc.u32 %0, [%1];" : "=r"(x0[i]) : "l"(xp + 64 * i) : "memory");
                }
                if (q == 4) {
                    img_store_global<0>(img, toff, s, sc, sc);
#pragma unroll
                    for (int k = 0; k < 16; k++) {
                        const float d0 = bf_lo(x[k]) - bf_lo(x0[k >> 3]), d1 = bf_hi(x[k]) - bf_lo(x0[k >> 3]);
                        st[k >> 3] += d0 + d1;
                        st[2 + (k >> 3)] = fmaf(d0, d0, fmaf(d1, d1, st[2 + (k >> 3)]));
                    }
#pragma unroll
                    for (int i = 0; i < 4 * NSH; i++) st[i & 3] += __shfl_xor_sync(0xffffffffu, st[i & 3], 1 << (i >> 2));
                    reg_fence(st);
                }
                if (q == 5) {
#pragma unroll
                    for (int i = 4 * NSH; i < 20; i++) st[i & 3] += __shfl_xor_sync(0xffffffffu, st[i & 3], 1 << (i >> 2));
                    img_store_global<1>(img, toff, s, sc, sc);
#pragma unroll
                    for (int i = 0; i < 2; i++) {
                        const float d = st[i] * (1.f / 512.f);
                        st[2 + i] = ln_rstd(fmaxf(fmaf(-d, d, st[2 + i] * (1.f / 512.f)), 0.f));
                        x0[i] = pack2(bf_lo(x0[i]) + d, bf_lo(x0[i]) + d);
                    }
                    reg_fence(st);
                    reg_fence(x0);
                }
                if (q > 5) {
                    if (q == 6) mbar_wait(sb + BAR_FLAG + 8 * 8, 0);
                    const uint4 a = lds128(sb + SM_TAB + 1024 + (q & 1) * 512 + lane * 16), c = lds128(sb + SM_TAB + (q & 1) * 512 + lane * 16);
                    uint8_t* hp = g_h + (grp * 8 + (q & 1) * 4 + (lane >> 3)) * 16384 + (xrow & 127) * 128;
#pragma unroll
                    for (int i = 0; i < 2; i++) {
                        const uint32_t* y = x + 8 * i + 4 * (q & 1);
                        *reinterpret_cast<uint4*>(hp + i * 128 + (((lane ^ xrow ^ i) & 7) << 4)) =
                            make_uint4(ln_apply(y[0], x0[i], st[2 + i], a.x, c.x), ln_apply(y[1], x0[i], st[2 + i], a.y, c.y),
                                       ln_apply(y[2], x0[i], st[2 + i], a.z, c.z), ln_apply(y[3], x0[i], st[2 + i], a.w, c.w));
                    }
                    if (q == 7) {
                        __syncwarp();
                        mbar_arrive_if(sb + BAR_DONE, lane == 0);
                    }
                    if (q == 6) img_store_global<2>(img, toff, s, sc, sc);
                    else img_store_global<3>(img, toff, s, sc, sc);
                }
                if (q < 7) {
                    sched_fence(fph, P.zero);
                    wg_wait<0>();
                    release_if(eb, as, rel);
                }
            }
        }
        uint32_t pend = 0x73;
        uint32_t p[32] = {};
#pragma unroll 1
        for (int hp = 0; hp < 2; hp++) {
            float m[2] = {0.f, 0.f}, l[2] = {0.f, 0.f}, t[4] = {0.f, 0.f, 0.f, 0.f};
            bool shifted = false, bad = false, plain = false;
            uint32_t qa = desc_k(sb + 5 * SLOT + (wg ^ 1) * 8192);
            const uint32_t limg = (512 + (15 - j) * 32 + 2 * grp + hp) * SLOT;
            {
                const int step = hp ? -8 * SLOT : 8 * SLOT;
                uint32_t img = (grp * 32 + (hp ? j ^ 30 : j) + 8) * SLOT;
                const uint32_t wtab = w_table(hp);
                uint32_t atab = hp ? 0x562u : 0x356u;
#pragma unroll 1
                for (int u = 2 - 2 * hp; u < 6; u += 2) {
                    proj_tile<false>(s, o, u, !u, sb, wg, eb, rel, fph, wtab, atab, pend, u ? img : cimg, toff, u ? sc : li[0], u ? sc : li[1], p);
                    __syncwarp();
                    mbar_arrive_if(sb + BAR_DONE + 4 * u + 32 * hp, lane == 0);
                    if (elected) TS(1 + 10 * hp + u + 20 * wg);
                    proj_tile<true>(o, s, u + 1, 0, sb, wg, eb, rel, fph, wtab, atab, pend, img + step, toff, sc, sc, p);
                    if (elected) TS(2 + 10 * hp + u + 20 * wg);
                    img += 2 * step;
                }
            }
            asm volatile("" : "+r"(toff));
            if (elected) TS(6 + 10 * hp + 20 * wg);
            fence_async_smem();
            slot_wait(sb + BAR_FULL, fph, r);
            step_retire(eb, rel, pend);
            reg_fence(o);
            int n = -1;
#pragma unroll 1
            for (;;) {
                while (bad || plain) {
                    float d0 = m[0], d1 = m[1];
                    if (bad) {
                        float a0, a1;
                        softmax_remax(s, m, n == 0 || n == nL, d0, d1, a0, a1);
                        shifted = true;
                        l[0] *= a0;
                        l[1] *= a1;
#pragma unroll
                        for (int i = 0; i < 64; i++) o[i] *= (i & 2) ? a1 : a0;
                    }
#pragma unroll
                    for (int i = 0; i < 64; i++) s[i] -= (i & 2) ? d1 : d0;
                    softmax_exp<0, 16>(s, p, t);
                    t[0] += t[1];
                    t[2] += t[3];
                    bad = !bad && softmax_unsafe(t[0], t[2], false);
                    plain = false;
                }
#pragma unroll 1
                do {
                    l[0] += t[0];
                    l[1] += t[2];
                    if (++n > 16) break;
                    const uint32_t ks = r;
                    uint32_t vs = ring_next(r);
                    r = ring_next(vs);
                    bar_sync(1 + wg, 256);
                    const float x = (float)((warp & 3) * 16 + g - 2 * c4);
                    if (n == hn) {
                        float sh[32];
                        qk_issue(sh, qa, kd + ks * (SLOT / 16));
                        slot_wait(sb + BAR_FULL, fph, vs);
                        pv_issue(o, p, vd + vs * (SLOT / 16), 1, false);
                        bar_arrive(2 - wg, 256);
                        wg_wait<1>();
                        reg_fence(sh);
                        tri_mask_copy(s, sh, x);
                        release_if(eb, ks, rel);
                        release_if(eb, 5 + wg, rel && (!wg || n == 16));
                        if (!wg) qa += SLOT / 16;
                        float e[4 * EARLY];
#pragma unroll
                        for (int i = 0; i < 4 * EARLY; i++) {
                            e[i] = ex2(s[i]);
                            t[i & 3] = i < 4 ? e[i] : t[i & 3] + e[i];
                        }
                        reg_fence(e);
                        slot_wait(sb + BAR_FULL, fph, r);
                        wg_wait<0>();
                        reg_fence(o);
                        reg_fence(e);
                        release_if(eb, vs, rel);
#pragma unroll
                        for (int i = 0; i < 2 * EARLY; i++) p[i] = pack2(e[2 * i], e[2 * i + 1]);
                        softmax_exp<EARLY, 8>(s, p, t);
                        if (wg) {
                            ctx_store(limg, toff, o, rcp(quad_sum(l[0])), rcp(quad_sum(l[1])));
                            __syncwarp();
                            mbar_arrive_if(sb + BAR_DONE + 24 + 32 * hp, lane == 0);
                            l[0] = l[1] = m[0] = m[1] = 0.f;
                            shifted = false;
                        }
                        t[0] += t[1];
                        t[2] += t[3];
                        plain = shifted;
                        if (plain) break;
                        bad = softmax_unsafe(t[0], t[2], wg);
                        continue;
                    }
                    if (n == nL) {
                        qk_issue(s, qa, kd + ks * (SLOT / 16));
                        slot_wait(sb + BAR_FULL, fph, vs);
                        pv_issue(o, p, vd + vs * (SLOT / 16), 1, true);
                        bar_arrive(2 - wg, 256);
                        const float i0 = rcp(quad_sum(l[0])), i1 = rcp(quad_sum(l[1]));
                        wg_wait<1>();
                        reg_fence(s);
                        release_if(eb, ks, rel);
                        release_if(eb, 6, rel && n == 16);
                        tri_mask(s, x);
                        float e[4 * EARLY2];
#pragma unroll
                        for (int i = 0; i < 4 * EARLY2; i++) {
                            e[i] = ex2(s[i]);
                            t[i & 3] = i < 4 ? e[i] : t[i & 3] + e[i];
                        }
                        reg_fence(e);
                        reg_fence(s);
                        reg_fence(t);
                        slot_wait(sb + BAR_FULL, fph, r);
                        sched_fence(fph, P.zero);
                        wg_wait<0>();
                        reg_fence(o);
                        reg_fence(e);
                        release_if(eb, vs, rel);
#pragma unroll
                        for (int i = 0; i < 2 * EARLY2; i++) p[i] = pack2(e[2 * i], e[2 * i + 1]);
                        softmax_exp<EARLY2, MSPLIT>(s, p, t);
                        ctx_store(limg, toff, o, i0, i1);
                        reg_fence(t);
                        reg_fence(s);
                        softmax_exp<MSPLIT, 16>(s, p, t);
                        __syncwarp();
                        mbar_arrive_if(sb + BAR_DONE + 24 + 32 * hp, lane == 0);
                        l[0] = l[1] = m[0] = m[1] = 0.f;
                        shifted = false;
                        t[0] += t[1];
                        t[2] += t[3];
                        bad = __any_sync(0xffffffffu, fmaxf(t[0], t[2]) > SM_HI || fminf(t[0], t[2]) < SM_LO);
                        continue;
                    }
                    qk_issue(s, qa, kd + ks * (SLOT / 16));
                    if (n == 0) {
                        r = vs;
                        vs = 4 - hp;
                        slot_wait(sb + BAR_FULL, fph, 6);
                        gemm_issue<false>(o, qa + SLOT / 16, wd + vs * (SLOT / 16), 1, false);
                    } else {
                        slot_wait(sb + BAR_FULL, fph, vs);
                        if (n == 1) {
                            wg_wait<1>();
                            reg_fence(o);
                            const uint32_t a = sb + 6 * SLOT + q_off(toff);
#pragma unroll
                            for (int i = 0; i < 8; i++) {
                                const int k = 16 * (i >> 1) + 2 * (i & 1);
                                sts128(a + (i >> 2) * 16384 + (i & 2) * 256 + (i & 1) * 1024,
                                       make_uint4(pack2(o[k], o[k + 1]), pack2(o[k + 4], o[k + 5]), pack2(o[k + 8], o[k + 9]), pack2(o[k + 12], o[k + 13])));
                            }
                        }
                        pv_issue(o, p, vd + vs * (SLOT / 16), n != 1 && n != nL + 1, n == hn + 1);
                    }
                    bar_arrive(2 - wg, 256);
                    wg_wait<1>();
                    reg_fence(s);
                    release_if(eb, ks, rel);
                    release_if(eb, 6, rel && n == 16);
                    if (n == nL - 1) {
                        tri_mask(s, x);
                        release_if(eb, 5, rel);
                        qa += SLOT / 16;
                    }
                    if (n == 2) fence_async_smem();
                    if (shifted) {
                        slot_wait(sb + BAR_FULL, fph, r);
                        wg_wait<0>();
                        reg_fence(o);
                        release_if(eb, vs, rel);
                        plain = true;
                        break;
                    }
                    float e[4 * EARLY];
#pragma unroll
                    for (int i = 0; i < 4 * EARLY; i++) {
                        e[i] = ex2(s[i]);
                        t[i & 3] = i < 4 ? e[i] : t[i & 3] + e[i];
                    }
                    reg_fence(e);
                    slot_wait(sb + BAR_FULL, fph, r);
                    wg_wait<0>();
                    reg_fence(o);
                    reg_fence(e);
                    release_if(eb, vs, rel);
#pragma unroll
                    for (int i = 0; i < 2 * EARLY; i++) p[i] = pack2(e[2 * i], e[2 * i + 1]);
                    softmax_exp<EARLY, 16>(s, p, t);
                    t[0] += t[1];
                    t[2] += t[3];
                    bad = __any_sync(0xffffffffu, fmaxf(t[0], t[2]) > SM_HI || (n == 0 && fminf(t[0], t[2]) < SM_LO));
                } while (!bad);
                if (!bad && !plain) break;
            }
            asm volatile("" : "+r"(toff));
            const uint32_t vs = r, ga = desc_k(sb + (hp ? 2 * (wg ^ kh ^ 1) : wg) * 8192);
            r = ring_next(r);
            slot_wait(sb + BAR_FULL, fph, 5);
            slot_wait(sb + BAR_FULL, fph, r);
            bar_sync(1 + wg, 256);
            gemm_issue<true>(s, ga + 5 * (SLOT / 16), wd + r * (SLOT / 16), 0, hp);
            pv_issue(o, p, vd + vs * (SLOT / 16), j, hn == 16);
            bar_arrive(2 - wg, 256);
            li[0] = rcp(quad_sum(l[0]));
            li[1] = rcp(quad_sum(l[1]));
            cimg = limg + (2 * j - 15) * 32 * SLOT + (wg ? -16384 : 16384);
            wg_wait<1>();
            release_if(eb, 5, rel);
            release_if(eb, r, rel && hp);
            wg_wait<0>();
            release_if(eb, vs, rel);
            reg_fence(o);
            img_store_global<0>(cimg, toff, o, li[0], li[1]);
            pend = 0x77;
            if (elected) TS(8 + 10 * hp + 20 * wg);
        }
        uint32_t otab = 0x2351604u;
        const uint32_t oa = desc_k(sb + (wg ^ kh ^ 1) * 16384);
        const int t7 = tid & 127, w4 = warp & 3, row = ort * 128 + kh * 64 + w4 * 16 + g;
#pragma unroll 1
        for (int i = 1; i < 15 - OFF - wg; i++) {
            const uint32_t as = o_next(otab), ws = o_next(otab);
            slot_wait(sb + BAR_FULL, fph, as);
            slot_wait(sb + BAR_FULL, fph, ws);
            bar_sync(1 + wg, 256);
            gemm_issue<false>(s, oa + as * (SLOT / 16), wd + ws * (SLOT / 16), 1, true);
            bar_arrive(2 - wg, 256);
            wg_wait<1>();
            reg_fence(o);
            if (i == 1) img_store_global<1>(cimg, toff, o, li[0], li[1]);
            if (i == 2) {
                img_store_global<2>(cimg, toff, o, li[0], li[1]);
                img_store_global<3>(cimg, toff, o, li[0], li[1]);
                __syncwarp();
                mbar_arrive_if(sb + BAR_DONE + 64, lane == 0);
            }
            wg_wait<0>();
            release_if(eb, as, rel);
            release_if(eb, ws, rel);
        }
        mbar_wait(sb + BAR_PF, 0);
        const uint32_t ep = lds32(sb + SM_EP);
        uint32_t eb2 = sb + BAR_END;
        if (wg == 0) {
            reg_fence(s);
            if (elected) TS(9);
            TT(1);
#pragma unroll
            for (int v = 0; v < 8; v++)
                st_pub(g_out + rb * OB + v * 128 + t7, make_uint4((pack2(s[8 * v], s[8 * v + 1]) & ~1u) | (ep & 1), pack2(s[8 * v + 2], s[8 * v + 3]),
                                                                      pack2(s[8 * v + 4], s[8 * v + 5]), pack2(s[8 * v + 6], s[8 * v + 7])), true);
            constexpr uint32_t s1 = SL_WF, s2 = SL_WD;
            bar_sync(4, 256);
            uint32_t wf[64];
            float wn[64];
            if (rb < NFFN) {
                slot_wait(sb + BAR_FULL, fph, s1);
                const uint32_t a = sb + s1 * SLOT + (w4 * 128 + (lane >> 4) * 8 + (lane & 7)) * 32 + (((lane >> 3) ^ (lane >> 2)) & 1) * 16;
#pragma unroll
                for (int i = 0; i < 16; i++)
                    asm volatile("ldmatrix.sync.aligned.m8n8.x4.trans.shared.b16 {%0, %1, %2, %3}, [%4];"
                                 : "=r"(wf[4 * i]), "=r"(wf[4 * i + 1]), "=r"(wf[4 * i + 2]), "=r"(wf[4 * i + 3])
                                 : "r"(a + (i >> 3) * 16384 + (i & 7) * 512) : "memory");
                slot_wait(sb + BAR_FULL, fph, s2);
#pragma unroll
                for (int i = 0; i < 16; i++) {
                    const uint2 w = *reinterpret_cast<const uint2*>(smem + s2 * SLOT + (kh ^ 1) * 16384 + i * 1024 + t7 * 8);
                    wn[4 * i] = bf_lo(w.x); wn[4 * i + 1] = bf_hi(w.x); wn[4 * i + 2] = bf_lo(w.y); wn[4 * i + 3] = bf_hi(w.y);
                }
                reg_fence(wn);
            }
            const uint32_t gbf = __ldcg(reinterpret_cast<const uint32_t*>(g_mod) + 1280 + rb * 2 + (tid & 1));
            if (elected) TS(10);
            TT(2);
            float* sred = reinterpret_cast<float*>(smem + SM_RED);
            if (warp == 0) {
                *reinterpret_cast<uint32_t*>(smem + SM_EP + 24) = best_key(g_key + cq * 128, lane, ep);
                mbar_arrive_if(sb + BAR_BEST, lane == 0);
            }
            bar_sync(3, 128);
            const uint32_t best = lds32(sb + SM_EP + 24);
            const int sel = (~best >> 5) & 2047;
            TT(3);
            if (rb < NFFN) {
                const uint4* cp = g_cand + (sel >> 4) * 192;
                uint4 cv[6];
                for (;;) {
                    uint32_t bad = 0;
#pragma unroll
                    for (int v = 0; v < 6; v++) cv[v] = ld_poll(cp + w4 * 24 + v * 4 + c4);
#pragma unroll
                    for (int v = 0; v < 6; v++) bad |= cv[v].w ^ ep;
                    if (__all_sync(0xffffffffu, bad == 0)) break;
                }
            TT(4);
                float d[4][4] = {};
#pragma unroll
                for (int k = 0; k < 8; k++) {
                    const uint32_t b0 = (&cv[(2 * k) / 3].x)[(2 * k) % 3], b1 = (&cv[(2 * k + 1) / 3].x)[(2 * k + 1) % 3];
                    mma16816(d[k & 1], wf + 4 * k, b0, b1);
                    mma16816(d[2 + (k & 1)], wf + 32 + 4 * k, b0, b1);
                }
                const float u = (c4 & 2) ? ((c4 & 1) ? d[2][2] + d[3][2] : d[2][0] + d[3][0]) : ((c4 & 1) ? d[0][2] + d[1][2] : d[0][0] + d[1][0]);
                sred[w4 * 32 + c4 * 8 + g] = u;
                bar_sync(3, 128);
                const float v = rbf((sred[lane] + sred[32 + lane]) + (sred[64 + lane] + sred[96 + lane]));
                const float act = rbf(rbf(v * sigmoid(v)) * __shfl_down_sync(0xffffffffu, v, 16));
                float y[4] = {0.f, 0.f, 0.f, 0.f};
#pragma unroll
                for (int k = 0; k < 16; k++) {
                    const float a = __shfl_sync(0xffffffffu, act, k);
#pragma unroll
                    for (int i = 0; i < 4; i++) y[i] = fmaf(a, wn[4 * k + i], y[i]);
                }
                st_pub(g_out + rb * OB + OB_Y + t7, make_uint4((__float_as_uint(y[0]) & ~15u) | (ep & 15), __float_as_uint(y[1]), __float_as_uint(y[2]), __float_as_uint(y[3])), true);
            }
            const int pq = (2 * rb + (tid & 1)) & 63, pv = (pq >> 2) / 3;
            const uint4* fp = g_cand + (sel >> 4) * 192 + (rb >> 5) * 24 + pv * 4 + (pq & 3);
            uint4 fh = {}, fx = {};
            if (rb == 0 && tid == 0) g_sync.epoch[0] = ep;
            if (elected) TS(60);
            TT(5);
            uint4 yv;
            if (warp == 0) { fh = ld_poll(fp); fx = ld_poll(fp + 96); }
            __nanosleep(rb < NFFN ? YPRE : 4 * YPRE);
            for (;;) {
                yv = ld_poll(g_out + min(t7, NFFN - 1) * OB + OB_Y + rb);
                if (poll_done(((yv.x ^ ep) & 15) == 0, YSLEEP)) break;
            }
            if (elected) TS(61);
            TT(6);
            float y[4] = {0.f, 0.f, 0.f, 0.f};
            if (t7 < NFFN) { y[0] = __uint_as_float(yv.x & ~15u); y[1] = __uint_as_float(yv.y); y[2] = __uint_as_float(yv.z); y[3] = __uint_as_float(yv.w); }
            const float z0 = ((lane & 16) ? y[2] : y[0]) + __shfl_xor_sync(0xffffffffu, (lane & 16) ? y[0] : y[2], 16);
            const float z1 = ((lane & 16) ? y[3] : y[1]) + __shfl_xor_sync(0xffffffffu, (lane & 16) ? y[1] : y[3], 16);
            float z = ((lane & 8) ? z1 : z0) + __shfl_xor_sync(0xffffffffu, (lane & 8) ? z0 : z1, 8);
            z += __shfl_xor_sync(0xffffffffu, z, 4);
            z = quad_sum(z);
            if ((lane & 7) == 0) sred[128 + (lane >> 3) * 4 + w4] = z;
            bar_sync(3, 128);
            if (tid < 2) {
                while (fh.w != ep || fx.w != ep) { fh = ld_poll(fp); fx = ld_poll(fp + 96); }
                const float4 y0 = *reinterpret_cast<const float4*>(sred + 128 + tid * 8), y1 = *reinterpret_cast<const float4*>(sred + 132 + tid * 8);
                const int cm = (pq >> 2) - 3 * pv;
                const uint32_t h2 = cm == 0 ? fh.x : cm == 1 ? fh.y : fh.z, x2 = cm == 0 ? fx.x : cm == 1 ? fx.y : fx.z;
                const float sg = sigmoid(bf_hi((best & 0x80000000u) ? (best ^ 0x80000000u) : ~best));
                reinterpret_cast<uint32_t*>(P.out)[sel * 256 + rb * 2 + tid] =
                    badd(x2, bmul(gbf, badd(h2, bmul(pack2((y0.x + y0.y) + (y0.z + y0.w), (y1.x + y1.y) + (y1.z + y1.w)), pack2(sg, sg)))));
            }
            if (elected) TS(62);
            TT(7);
        } else {
            const float4* tf = reinterpret_cast<const float4*>(smem + SM_TAB) + c4;
            uint32_t x2[32];
            bar_sync(2, 256);
#pragma unroll 1
            for (int i = 14; i < 17; i++) {
                const uint32_t as = o_next(otab), ws = o_next(otab);
                slot_wait(sb + BAR_FULL, fph, as);
                slot_wait(sb + BAR_FULL, fph, ws);
                gemm_issue<false>(s, oa + as * (SLOT / 16), wd + ws * (SLOT / 16), 1, true);
                wg_wait<1>();
            }
            const uint4* pr = g_out + (rb ^ 16) * OB + t7;
            uint4 pa[8];
            if (elected) TS(29);
            TT(1);
#pragma unroll
            for (int k = 0; k < 8; k++) {
                const uint4 v = lds128(sb + SL_X * SLOT + (kh ^ 1) * 16384 + k * 2048 + t7 * 16);
                x2[4 * k] = v.x; x2[4 * k + 1] = v.y; x2[4 * k + 2] = v.z; x2[4 * k + 3] = v.w;
            }
            wg_wait<0>();
            reg_fence(s);
            bar_arrive(4, 256);
            if (elected) TS(39);
            TT(2);
#pragma unroll
            for (int v = 0; v < 8; v++) pa[v] = ld_poll(pr + v * 128);
            float4 tc[16];
#pragma unroll
            for (int k = 0; k < 16; k++) {
                tc[k] = tf[k * 4];
                if (!(g & 1)) tc[k].z = __uint_as_float(ONE2);
#pragma unroll
                for (int i = 4 * k; i < 4 * k + 4; i++) s[i] = fmaf((i & 1) ? tc[k].y : tc[k].x, s[i], (i & 1) ? bf_hi(x2[i >> 1]) : bf_lo(x2[i >> 1]));
            }
            reg_fence(s);
            sched_fence(eb2, P.zero);
            for (;;) {
                uint32_t bad = 0;
#pragma unroll
                for (int v = 0; v < 8; v++) asm("lop3.b32 %0, %0, %1, %2, 0xf6;" : "+r"(bad) : "r"(pa[v].x), "r"(ep));
                if (__all_sync(0xffffffffu, (bad & 1) == 0)) break;
                if (PSLEEP) __nanosleep(PSLEEP);
#pragma unroll
                for (int v = 0; v < 8; v++) pa[v] = ld_poll(pr + v * 128);
            }
            if (elected) TS(30);
            TT(3);
            float sd[4] = {}, q0[4] = {}, q1[4] = {};
#pragma unroll
            for (int k = 0; k < 8; k++) {
#pragma unroll
                for (int i = 4 * k; i < 4 * k + 4; i++) {
                    const uint32_t w = (i & 3) ? (&pa[k].x)[i & 3] : pa[k].x & ~1u;
                    x2[i] = pack2(fmaf(tc[i >> 1].x, bf_lo(w), s[2 * i]), fmaf(tc[i >> 1].y, bf_hi(w), s[2 * i + 1]));
                }
                mma16816(sd, x2 + 4 * k, __float_as_uint(tc[2 * k].z), __float_as_uint(tc[2 * k + 1].z));
                mma16816(q0, x2 + 4 * k, x2[4 * k], x2[4 * k + 2]);
                mma16816(q1, x2 + 4 * k, x2[4 * k + 1], x2[4 * k + 3]);
            }
            uint4* sp = g_out + rb * OB + OB_STAT + (w4 * 8 + g) * 2;
            st_pub(sp, make_uint4(__float_as_uint(sd[0]), __float_as_uint((g & 1) ? q0[1] : q0[0]), __float_as_uint(sd[1]), ep), c4 == g >> 1);
            st_pub(sp + 1, make_uint4(__float_as_uint(sd[2]), __float_as_uint((g & 1) ? q1[3] : q1[2]), __float_as_uint(sd[3]), ep), c4 == g >> 1);
            sched_fence(eb2, P.zero);
            if (elected) TS(56);
            TT(4);
            uint32_t cb[16], sh[16], gb[16];
#pragma unroll
            for (int i = 0; i < 16; i++) {
                const float4 c = tf[64 + i * 4];
                cb[i] = __float_as_uint(c.x); sh[i] = __float_as_uint(c.y); gb[i] = __float_as_uint(c.z);
            }
            const float ra = __uint_as_float(lds32(sb + SM_EP + 8)), rb0 = __uint_as_float(lds32(sb + SM_EP + 12));
            uint4 r0, r1;
            for (;;) {
                r0 = ld_poll(g_out + ((rb & ~33) + (c4 & 1) + (c4 & 2) * 16) * OB + OB_STAT + (w4 * 8 + g) * 2);
                r1 = ld_poll(g_out + ((rb & ~33) + (c4 & 1) + (c4 & 2) * 16) * OB + OB_STAT + (w4 * 8 + g) * 2 + 1);
                if (poll_done(r0.w == ep && r1.w == ep, SSLEEP)) break;
            }
            if (elected) TS(57);
            TT(5);
            const float m0 = quad_sum(__uint_as_float(r0.x)) * (1.f / 512.f), m1 = quad_sum(__uint_as_float(r1.x)) * (1.f / 512.f);
            const float rs0 = ln_rstd(fmaxf(fmaf(-m0, m0, quad_sum(__uint_as_float(r0.y)) * (1.f / 512.f)), 0.f));
            const float rs1 = ln_rstd(fmaxf(fmaf(-m1, m1, quad_sum(__uint_as_float(r1.y)) * (1.f / 512.f)), 0.f));
            const uint32_t mb0 = pack2(m0, m0), mb1 = pack2(m1, m1);
            const uint32_t lg = pack2(fmaf(rs0, fmaf(-bf_lo(mb0), ra, quad_sum(__uint_as_float(r0.z))), rb0),
                                      fmaf(rs1, fmaf(-bf_lo(mb1), ra, quad_sum(__uint_as_float(r1.z))), rb0));
            const uint32_t u0 = lg << 16, u1 = lg & 0xffff0000u;
            const uint32_t k0 = ((u0 ^ (((int)u0 >> 31) | 0x80000000u)) & 0xffff0000u) | ((2047 - row) << 5) | (ep & 31);
            const uint32_t k1 = ((u1 ^ (((int)u1 >> 31) | 0x80000000u)) & 0xffff0000u) | ((2039 - row) << 5) | (ep & 31);
            const uint32_t kb = __reduce_max_sync(0xffffffffu, max(k0, k1));
            st_pub(g_key + cq * 128 + (row >> 4), kb, lane == 0);
            const bool cand = kb == k0 || kb == k1;
            uint4* cp = g_cand + (row >> 4) * 192 + cq * 24 + c4;
#pragma unroll 1
            for (int it = 0; it < 3; it++) {
                bool put = it == 1 || !cand;
                if (it == 2) {
                    mbar_wait(sb + BAR_BEST, 0);
                    put = cand && lds32(sb + SM_EP + 24) != kb;
                }
                const bool hi = (kb == k1) != (it == 1);
                uint32_t cx[18], ch[18];
#pragma unroll
                for (int i = 0; i < 16; i++) {
                    cx[i] = hi ? x2[2 * i + 1] : x2[2 * i];
                    ch[i] = ln_apply(cx[i], hi ? mb1 : mb0, hi ? rs1 : rs0, cb[i], sh[i]);
                }
                cx[16] = cx[17] = ch[16] = ch[17] = 0;
#pragma unroll
                for (int v = 0; v < 6; v++) st_pub(cp + v * 4, make_uint4(ch[3 * v], ch[3 * v + 1], ch[3 * v + 2], ep), cand && it == 0);
#pragma unroll
                for (int v = 0; v < 6; v++) st_pub(cp + 96 + v * 4, make_uint4(cx[3 * v], cx[3 * v + 1], cx[3 * v + 2], ep), cand && it == 0);
                if (it == 0) TT(6);
                uint2* op = reinterpret_cast<uint2*>(P.out) + (row + 8 * hi) * 128 + cq * 32 + (c4 & 1) * 2 + (c4 >> 1);
#pragma unroll
                for (int i = 0; i < 16; i += 2) {
                    const uint32_t v0 = badd(cx[i], bmul(gb[i], ch[i])), v1 = badd(cx[i + 1], bmul(gb[i + 1], ch[i + 1]));
                    const uint32_t rv = __shfl_xor_sync(0xffffffffu, (c4 & 1) ? v0 : v1, 1);
                    if (put) op[i * 2] = (c4 & 1) ? make_uint2(rv, v1) : make_uint2(v0, rv);
                }
            }
            if (elected) TS(59);
            TT(7);
        }
        mbar_arrive_if(eb2, lane == 0);
    }
}

typedef CUresult (*EncodeFn)(CUtensorMap*, CUtensorMapDataType, cuuint32_t, void*, const cuuint64_t*, const cuuint64_t*,
                             const cuuint32_t*, const cuuint32_t*, CUtensorMapInterleave, CUtensorMapSwizzle,
                             CUtensorMapL2promotion, CUtensorMapFloatOOBfill);

void make_3d(EncodeFn fn, CUtensorMap* m, const void* p, uint64_t cols, uint64_t rows, uint32_t br = 128, uint32_t nb = 2) {
    cuuint64_t dims[3] = {64, rows, cols / 64}, strides[2] = {cols * 2, 128};
    cuuint32_t box[3] = {64, br, nb}, es[3] = {1, 1, 1};
    fn(m, CU_TENSOR_MAP_DATA_TYPE_BFLOAT16, 3, const_cast<void*>(p), dims, strides, box, es, CU_TENSOR_MAP_INTERLEAVE_NONE,
       CU_TENSOR_MAP_SWIZZLE_128B, CU_TENSOR_MAP_L2_PROMOTION_L2_256B, CU_TENSOR_MAP_FLOAT_OOB_FILL_NONE);
}

}

extern "C" void kernel_launch(void* const* d_in, const int* in_sizes, int n_in, void* d_out, int out_size) {
    static EncodeFn fn = nullptr;
    if (!fn) {
        void* f = nullptr;
        cudaDriverEntryPointQueryResult st;
        cudaGetDriverEntryPoint("cuTensorMapEncodeTiled", &f, cudaEnableDefault, &st);
        fn = (EncodeFn)f;
        cudaFuncSetAttribute(fused_kernel, cudaFuncAttributeMaxDynamicSharedMemorySize, SMEM_BYTES);
    }
    CUtensorMap ckv, wq, wuk, wuv, wo, wg, wu, wm, xm;
    make_3d(fn, &ckv, d_in[1], 512, 2048, 128, 1);
    make_3d(fn, &xm, d_in[0], 512, 2048, 64);
    make_3d(fn, &wq, d_in[2], 4096, 512);
    make_3d(fn, &wuk, d_in[3], 4096, 512);
    make_3d(fn, &wuv, d_in[4], 4096, 512);
    make_3d(fn, &wo, d_in[5], 512, 4096);
    make_3d(fn, &wg, d_in[8], 1792, 512, 256, 1);
    make_3d(fn, &wu, d_in[9], 1792, 512, 256, 1);
    make_3d(fn, &wm, d_in[12], 3072, 512, 64, 4);
    Params p;
    p.x = (const bf16*)d_in[0];
    p.ckv = (const bf16*)d_in[1];
    p.wo = (const bf16*)d_in[5];
    p.wr = (const bf16*)d_in[7];
    p.wdown = (const bf16*)d_in[10];
    p.c = (const bf16*)d_in[11];
    p.out = (bf16*)d_out;
    p.zero = 0;
    fused_kernel<<<NCTA + NSPARE, 384, SMEM_BYTES>>>(ckv, wq, wuk, wuv, wo, wg, wu, wm, xm, p);
}
```

```cpp
#include <cuda.h>
#include <cuda_bf16.h>
#include <cuda_runtime.h>
#include <stdint.h>
#include <stdio.h>

namespace {

typedef __nv_bfloat16 bf16;
typedef unsigned long long u64;

constexpr int NCTA = 128, NSPARE = 4;
constexpr int SLOT = 32768;
constexpr int SM_BAR = 7 * SLOT;
constexpr int BAR_FULL = SM_BAR;
constexpr int BAR_EMPTY = BAR_FULL + 8 * 7;
constexpr int BAR_DONE = BAR_EMPTY + 8 * 7;
constexpr int BAR_FLAG = BAR_DONE + 8 * 9;
constexpr int BAR_PF = BAR_FLAG + 8 * 9;
constexpr int BAR_END = BAR_PF + 8;
constexpr int BAR_BEST = BAR_END + 8;
constexpr int SM_EP = BAR_END + 40;
constexpr int SM_RED = SM_BAR + 384;
constexpr int SM_TAB = SM_BAR + 1024;
constexpr int SMEM_BYTES = SM_BAR + 3072;
constexpr int NFFN = 112;
#define HINT 479
constexpr u64 L2_NORMAL = 0x1000000000000000ull, L2_FIRST = 0x12F0000000000000ull;
#define PFA 8
#define PFB 6
#define POLL_NS 50
#define MSPLIT 13
#define NSH 1
#define XPF 1
#define KSLEEP 400
#define YSLEEP 50
#define YPRE 400
#define SSLEEP 50
#define PSLEEP 100
#define KVG 7
#define EARLY2 4
#define OFF 2
#define KN 16
#define KSLEEP2 60
#define EARLY 7
constexpr uint32_t SPIN_LIMIT = 1u << 22;
constexpr uint32_t ONE2 = 0x3f803f80u;

struct Sync {
    uint32_t cnt[16 * 8 * 8];
    uint32_t ctxcnt[16 * 32];
    uint32_t epoch[32];
};

__device__ __align__(1024) uint8_t g_img[2 * 512 * SLOT];
#define g_KV g_img
#define g_ctx (g_img + 512 * SLOT)
__device__ __align__(1024) uint8_t g_h[16 * 4 * SLOT];
constexpr int OB = 1216, OB_STAT = 1024, OB_Y = 1088;
__device__ __align__(1024) uint4 g_out[128 * OB];
__device__ __align__(1024) bf16 g_mod[3072];
__device__ __align__(1024) uint32_t g_mod1[1024];
__device__ __align__(1024) uint4 g_cand[128 * 192];
__device__ __align__(1024) uint32_t g_key[4 * 128];
__device__ __align__(1024) uint8_t g_wf[NFFN * SLOT];
__device__ __align__(1024) uint4 g_x2[128 * 1024];
__device__ __align__(1024) Sync g_sync;
#define TS(i)

#define TT(i)
#define PT()

struct Params {
    const bf16 *x, *ckv, *wo, *wr, *wdown, *c;
    bf16* out;
    int zero;
};

__device__ __forceinline__ void mbar_init(uint32_t bar, uint32_t cnt) {
    asm volatile("mbarrier.init.shared::cta.b64 [%0], %1;" ::"r"(bar), "r"(cnt) : "memory");
}
__device__ __forceinline__ void mbar_wait(uint32_t bar, uint32_t parity) {
    asm volatile("{\n.reg .pred p;\nL_%=:\nmbarrier.try_wait.parity.shared::cta.b64 p, [%0], %1;\n@!p bra L_%=;\n}" ::"r"(bar), "r"(parity) : "memory");
}
__device__ __forceinline__ void mbar_sleep(uint32_t bar) {
    if ((threadIdx.x & 31) == 0)
        asm volatile("{\n.reg .pred p;\nL_%=:\nmbarrier.try_wait.parity.shared::cta.b64 p, [%0], 0, 100000;\n@!p bra L_%=;\n}" ::"r"(bar) : "memory");
    __syncwarp();
}
__device__ __forceinline__ void mbar_watch(uint32_t bar, uint32_t parity) {
    asm volatile("{\n.reg .pred p;\n.reg .u32 n;\nmov.u32 n, 0;\n"
                 "L_%=:\nmbarrier.try_wait.parity.shared::cta.b64 p, [%0], %1;\n@p bra D_%=;\n"
                 "add.u32 n, n, 1;\nsetp.lt.u32 p, n, %2;\n@p bra L_%=;\ntrap;\nD_%=:\n}"
                 ::"r"(bar), "r"(parity), "n"(SPIN_LIMIT) : "memory");
}
__device__ __forceinline__ void step_watch(uint32_t a, uint32_t step) {
    asm volatile("{\n.reg .pred p;\n.reg .u32 n, v;\nmov.u32 n, 0;\n"
                 "L_%=:\nld.volatile.shared.u32 v, [%0];\nsetp.ge.u32 p, v, %1;\n@p bra D_%=;\nnanosleep.u32 400;\n"
                 "add.u32 n, n, 1;\nsetp.lt.u32 p, n, %2;\n@p bra L_%=;\ntrap;\nD_%=:\n}"
                 ::"r"(a), "r"(step), "n"(SPIN_LIMIT) : "memory");
}
__device__ __forceinline__ void mbar_arrive_if(uint32_t bar, bool on) {
    asm volatile("{\n.reg .pred p;\nsetp.ne.s32 p, %1, 0;\n@p mbarrier.arrive.shared::cta.b64 _, [%0];\n}" ::"r"(bar), "r"((int)on) : "memory");
}
__device__ __forceinline__ void tma3d_prefetch(const CUtensorMap* m, int row, int cb) {
    asm volatile("{\n.reg .pred p;\nelect.sync _|p, 0xffffffff;\n@p cp.async.bulk.prefetch.tensor.3d.L2.global [%0, {%1, %2, %3}];\n}"
                 ::"l"(m), "r"(0), "r"(row), "r"(cb) : "memory");
}
__device__ __forceinline__ void l2_prefetch(const void* p, uint32_t bytes) {
    asm volatile("{\n.reg .pred p;\nelect.sync _|p, 0xffffffff;\n@p cp.async.bulk.prefetch.L2.global [%0], %1;\n}" ::"l"(p), "r"(bytes) : "memory");
}
__device__ __forceinline__ void bulk_store(void* dst, uint32_t src, uint32_t bytes, bool first) {
    asm volatile("{\n.reg .pred p;\nelect.sync _|p, 0xffffffff;\n@p cp.async.bulk.global.shared::cta.bulk_group.L2::cache_hint [%0], [%1], %2, %3;\n}"
                 ::"l"(dst), "r"(src), "r"(bytes), "l"(first ? L2_FIRST : L2_NORMAL) : "memory");
}
__device__ __forceinline__ void flag_wait(const uint32_t* f, uint32_t target) {
    asm volatile("{\n.reg .pred p;\n.reg .u32 v;\n"
                 "L_%=:\nld.acquire.gpu.global.u32 v, [%0];\nsub.u32 v, v, %1;\nsetp.lt.s32 p, v, 0;\n@p nanosleep.u32 100;\n@p bra L_%=;\n}"
                 ::"l"(f), "r"(target) : "memory");
}
__device__ __forceinline__ uint4 ld_poll(const uint4* p) {
    uint4 v;
    asm volatile("{\n.reg .b128 t;\nld.relaxed.gpu.global.b128 t, [%4];\nmov.b128 {%0, %1, %2, %3}, t;\n}"
                 : "=r"(v.x), "=r"(v.y), "=r"(v.z), "=r"(v.w) : "l"(p) : "memory");
    return v;
}
__device__ __forceinline__ void st_pub(uint4* p, uint4 v, bool on) {
    asm volatile("{\n.reg .pred p;\n.reg .b128 t;\nsetp.ne.s32 p, %5, 0;\nmov.b128 t, {%1, %2, %3, %4};\n@p st.relaxed.gpu.global.b128 [%0], t;\n}"
                 ::"l"(p), "r"(v.x), "r"(v.y), "r"(v.z), "r"(v.w), "r"((int)on) : "memory");
}
__device__ __forceinline__ void st_pub(uint32_t* p, uint32_t v, bool on) {
    asm volatile("{\n.reg .pred p;\nsetp.ne.s32 p, %2, 0;\n@p st.relaxed.gpu.global.u32 [%0], %1;\n}" ::"l"(p), "r"(v), "r"((int)on) : "memory");
}
__device__ __forceinline__ bool poll_done(bool ok, uint32_t ns) {
    const int done = __all_sync(0xffffffffu, ok);
    asm volatile("{\n.reg .pred p;\nsetp.eq.s32 p, %0, 0;\n@p nanosleep.u32 %1;\n}" ::"r"(done), "r"(ns) : "memory");
    return done;
}
__device__ __forceinline__ void flag_add(uint32_t* p) {
    asm volatile("red.release.gpu.global.add.u32 [%0], 1;" ::"l"(p) : "memory");
}
__device__ __forceinline__ uint32_t lds32(uint32_t a) {
    uint32_t v;
    asm volatile("ld.shared.u32 %0, [%1];" : "=r"(v) : "r"(a) : "memory");
    return v;
}
__device__ __forceinline__ uint4 lds128(uint32_t a) {
    uint4 v;
    asm volatile("ld.shared.v4.u32 {%0, %1, %2, %3}, [%4];" : "=r"(v.x), "=r"(v.y), "=r"(v.z), "=r"(v.w) : "r"(a) : "memory");
    return v;
}
__device__ __forceinline__ void sched_fence(uint32_t& v, uint32_t z) {
    uint32_t ck;
    asm volatile("mov.u32 %0, %%clock;" : "=r"(ck)::"memory");
    v ^= ck & z;
}
__device__ __forceinline__ void fence_async_global() { asm volatile("fence.proxy.async.global;" ::: "memory"); }
__device__ __forceinline__ void fence_async_smem() { asm volatile("fence.proxy.async.shared::cta;" ::: "memory"); }
__device__ __forceinline__ void bar_sync(int id, int n) { asm volatile("bar.sync %0, %1;" ::"r"(id), "r"(n) : "memory"); }
__device__ __forceinline__ void bar_arrive(int id, int n) { asm volatile("bar.arrive %0, %1;" ::"r"(id), "r"(n) : "memory"); }
__device__ __forceinline__ void wg_fence() { asm volatile("wgmma.fence.sync.aligned;" ::: "memory"); }
__device__ __forceinline__ void wg_commit() { asm volatile("wgmma.commit_group.sync.aligned;" ::: "memory"); }
template <int N> __device__ __forceinline__ void wg_wait() { asm volatile("wgmma.wait_group.sync.aligned %0;" ::"n"(N) : "memory"); }
template <int N> __device__ __forceinline__ void reg_fence(float (&d)[N]) {
#pragma unroll
    for (int i = 0; i < N; i++) asm volatile("" : "+f"(d[i])::"memory");
}
template <int N> __device__ __forceinline__ void reg_fence(uint32_t (&d)[N]) {
#pragma unroll
    for (int i = 0; i < N; i++) asm volatile("" : "+r"(d[i])::"memory");
}
__device__ __forceinline__ uint32_t desc_k(uint32_t a) { return ((a & 0x3ffff) >> 4) | (1u << 16); }
__device__ __forceinline__ uint32_t desc_mn(uint32_t a) { return ((a & 0x3ffff) >> 4) | (1024u << 16); }

__device__ __forceinline__ uint64_t desc64(uint32_t lo, uint32_t hi) {
    uint64_t d;
    asm("mov.b64 %0, {%1, %2};" : "=l"(d) : "r"(lo), "r"(hi));
    return d;
}
__device__ __forceinline__ void desc_add(uint64_t& d, uint32_t x) { asm("add.u64 %0, %0, %1;" : "+l"(d) : "l"((uint64_t)x)); }

template <int TB>
__device__ __forceinline__ void wgmma_ss128(float (&d)[64], uint64_t da, uint64_t db, int acc) {
    asm volatile("{\n.reg .pred p;\nsetp.ne.b32 p, %66, 0;\n"
        "wgmma.mma_async.sync.aligned.m64n128k16.f32.bf16.bf16 {%0, %1, %2, %3, %4, %5, %6, %7, %8, %9, %10, %11, %12, %13, %14, %15, %16, %17, %18, %19, %20, %21, %22, %23, %24, %25, %26, %27, %28, %29, %30, %31, %32, %33, %34, %35, %36, %37, %38, %39, %40, %41, %42, %43, %44, %45, %46, %47, %48, %49, %50, %51, %52, %53, %54, %55, %56, %57, %58, %59, %60, %61, %62, %63}, %64, %65, p, 1, 1, 0, %67;\n}"
        : "+f"(d[0]), "+f"(d[1]), "+f"(d[2]), "+f"(d[3]), "+f"(d[4]), "+f"(d[5]), "+f"(d[6]), "+f"(d[7]), "+f"(d[8]), "+f"(d[9]), "+f"(d[10]), "+f"(d[11]), "+f"(d[12]), "+f"(d[13]), "+f"(d[14]), "+f"(d[15]), "+f"(d[16]), "+f"(d[17]), "+f"(d[18]), "+f"(d[19]), "+f"(d[20]), "+f"(d[21]), "+f"(d[22]), "+f"(d[23]), "+f"(d[24]), "+f"(d[25]), "+f"(d[26]), "+f"(d[27]), "+f"(d[28]), "+f"(d[29]), "+f"(d[30]), "+f"(d[31]), "+f"(d[32]), "+f"(d[33]), "+f"(d[34]), "+f"(d[35]), "+f"(d[36]), "+f"(d[37]), "+f"(d[38]), "+f"(d[39]), "+f"(d[40]), "+f"(d[41]), "+f"(d[42]), "+f"(d[43]), "+f"(d[44]), "+f"(d[45]), "+f"(d[46]), "+f"(d[47]), "+f"(d[48]), "+f"(d[49]), "+f"(d[50]), "+f"(d[51]), "+f"(d[52]), "+f"(d[53]), "+f"(d[54]), "+f"(d[55]), "+f"(d[56]), "+f"(d[57]), "+f"(d[58]), "+f"(d[59]), "+f"(d[60]), "+f"(d[61]), "+f"(d[62]), "+f"(d[63])
        : "l"(da), "l"(db), "r"(acc), "n"(TB));
}
template <int TB>
__device__ __forceinline__ void wgmma_ss128_init(float (&d)[64], uint64_t da, uint64_t db) {
    asm volatile("{\n.reg .pred p;\nsetp.ne.b32 p, 0, 0;\n"
        "wgmma.mma_async.sync.aligned.m64n128k16.f32.bf16.bf16 {%0, %1, %2, %3, %4, %5, %6, %7, %8, %9, %10, %11, %12, %13, %14, %15, %16, %17, %18, %19, %20, %21, %22, %23, %24, %25, %26, %27, %28, %29, %30, %31, %32, %33, %34, %35, %36, %37, %38, %39, %40, %41, %42, %43, %44, %45, %46, %47, %48, %49, %50, %51, %52, %53, %54, %55, %56, %57, %58, %59, %60, %61, %62, %63}, %64, %65, p, 1, 1, 0, %66;\n}"
        : "=f"(d[0]), "=f"(d[1]), "=f"(d[2]), "=f"(d[3]), "=f"(d[4]), "=f"(d[5]), "=f"(d[6]), "=f"(d[7]), "=f"(d[8]), "=f"(d[9]), "=f"(d[10]), "=f"(d[11]), "=f"(d[12]), "=f"(d[13]), "=f"(d[14]), "=f"(d[15]), "=f"(d[16]), "=f"(d[17]), "=f"(d[18]), "=f"(d[19]), "=f"(d[20]), "=f"(d[21]), "=f"(d[22]), "=f"(d[23]), "=f"(d[24]), "=f"(d[25]), "=f"(d[26]), "=f"(d[27]), "=f"(d[28]), "=f"(d[29]), "=f"(d[30]), "=f"(d[31]), "=f"(d[32]), "=f"(d[33]), "=f"(d[34]), "=f"(d[35]), "=f"(d[36]), "=f"(d[37]), "=f"(d[38]), "=f"(d[39]), "=f"(d[40]), "=f"(d[41]), "=f"(d[42]), "=f"(d[43]), "=f"(d[44]), "=f"(d[45]), "=f"(d[46]), "=f"(d[47]), "=f"(d[48]), "=f"(d[49]), "=f"(d[50]), "=f"(d[51]), "=f"(d[52]), "=f"(d[53]), "=f"(d[54]), "=f"(d[55]), "=f"(d[56]), "=f"(d[57]), "=f"(d[58]), "=f"(d[59]), "=f"(d[60]), "=f"(d[61]), "=f"(d[62]), "=f"(d[63])
        : "l"(da), "l"(db), "n"(TB));
}
template <int TB>
__device__ __forceinline__ void wgmma_ss64(float (&d)[32], uint64_t da, uint64_t db, int acc) {
    asm volatile("{\n.reg .pred p;\nsetp.ne.b32 p, %34, 0;\n"
        "wgmma.mma_async.sync.aligned.m64n64k16.f32.bf16.bf16 {%0, %1, %2, %3, %4, %5, %6, %7, %8, %9, %10, %11, %12, %13, %14, %15, %16, %17, %18, %19, %20, %21, %22, %23, %24, %25, %26, %27, %28, %29, %30, %31}, %32, %33, p, 1, 1, 0, %35;\n}"
        : "+f"(d[0]), "+f"(d[1]), "+f"(d[2]), "+f"(d[3]), "+f"(d[4]), "+f"(d[5]), "+f"(d[6]), "+f"(d[7]), "+f"(d[8]), "+f"(d[9]), "+f"(d[10]), "+f"(d[11]), "+f"(d[12]), "+f"(d[13]), "+f"(d[14]), "+f"(d[15]), "+f"(d[16]), "+f"(d[17]), "+f"(d[18]), "+f"(d[19]), "+f"(d[20]), "+f"(d[21]), "+f"(d[22]), "+f"(d[23]), "+f"(d[24]), "+f"(d[25]), "+f"(d[26]), "+f"(d[27]), "+f"(d[28]), "+f"(d[29]), "+f"(d[30]), "+f"(d[31])
        : "l"(da), "l"(db), "r"(acc), "n"(TB));
}
template <int TB>
__device__ __forceinline__ void wgmma_ss64_init(float (&d)[32], uint64_t da, uint64_t db) {
    asm volatile("{\n.reg .pred p;\nsetp.ne.b32 p, 0, 0;\n"
        "wgmma.mma_async.sync.aligned.m64n64k16.f32.bf16.bf16 {%0, %1, %2, %3, %4, %5, %6, %7, %8, %9, %10, %11, %12, %13, %14, %15, %16, %17, %18, %19, %20, %21, %22, %23, %24, %25, %26, %27, %28, %29, %30, %31}, %32, %33, p, 1, 1, 0, %34;\n}"
        : "=f"(d[0]), "=f"(d[1]), "=f"(d[2]), "=f"(d[3]), "=f"(d[4]), "=f"(d[5]), "=f"(d[6]), "=f"(d[7]), "=f"(d[8]), "=f"(d[9]), "=f"(d[10]), "=f"(d[11]), "=f"(d[12]), "=f"(d[13]), "=f"(d[14]), "=f"(d[15]), "=f"(d[16]), "=f"(d[17]), "=f"(d[18]), "=f"(d[19]), "=f"(d[20]), "=f"(d[21]), "=f"(d[22]), "=f"(d[23]), "=f"(d[24]), "=f"(d[25]), "=f"(d[26]), "=f"(d[27]), "=f"(d[28]), "=f"(d[29]), "=f"(d[30]), "=f"(d[31])
        : "l"(da), "l"(db), "n"(TB));
}
__device__ __forceinline__ void wgmma_rs128(float (&d)[64], uint32_t a0, uint32_t a1, uint32_t a2, uint32_t a3, uint64_t db, int acc) {
    asm volatile("{\n.reg .pred p;\nsetp.ne.b32 p, %69, 0;\n"
        "wgmma.mma_async.sync.aligned.m64n128k16.f32.bf16.bf16 {%0, %1, %2, %3, %4, %5, %6, %7, %8, %9, %10, %11, %12, %13, %14, %15, %16, %17, %18, %19, %20, %21, %22, %23, %24, %25, %26, %27, %28, %29, %30, %31, %32, %33, %34, %35, %36, %37, %38, %39, %40, %41, %42, %43, %44, %45, %46, %47, %48, %49, %50, %51, %52, %53, %54, %55, %56, %57, %58, %59, %60, %61, %62, %63}, {%64, %65, %66, %67}, %68, p, 1, 1, 1;\n}"
        : "+f"(d[0]), "+f"(d[1]), "+f"(d[2]), "+f"(d[3]), "+f"(d[4]), "+f"(d[5]), "+f"(d[6]), "+f"(d[7]), "+f"(d[8]), "+f"(d[9]), "+f"(d[10]), "+f"(d[11]), "+f"(d[12]), "+f"(d[13]), "+f"(d[14]), "+f"(d[15]), "+f"(d[16]), "+f"(d[17]), "+f"(d[18]), "+f"(d[19]), "+f"(d[20]), "+f"(d[21]), "+f"(d[22]), "+f"(d[23]), "+f"(d[24]), "+f"(d[25]), "+f"(d[26]), "+f"(d[27]), "+f"(d[28]), "+f"(d[29]), "+f"(d[30]), "+f"(d[31]), "+f"(d[32]), "+f"(d[33]), "+f"(d[34]), "+f"(d[35]), "+f"(d[36]), "+f"(d[37]), "+f"(d[38]), "+f"(d[39]), "+f"(d[40]), "+f"(d[41]), "+f"(d[42]), "+f"(d[43]), "+f"(d[44]), "+f"(d[45]), "+f"(d[46]), "+f"(d[47]), "+f"(d[48]), "+f"(d[49]), "+f"(d[50]), "+f"(d[51]), "+f"(d[52]), "+f"(d[53]), "+f"(d[54]), "+f"(d[55]), "+f"(d[56]), "+f"(d[57]), "+f"(d[58]), "+f"(d[59]), "+f"(d[60]), "+f"(d[61]), "+f"(d[62]), "+f"(d[63])
        : "r"(a0), "r"(a1), "r"(a2), "r"(a3), "l"(db), "r"(acc));
}

__device__ __forceinline__ uint32_t pack2(float lo, float hi) {
    uint32_t r;
    asm("cvt.rn.bf16x2.f32 %0, %1, %2;" : "=r"(r) : "f"(hi), "f"(lo));
    return r;
}
__device__ __forceinline__ float bf_lo(uint32_t v) { return __uint_as_float(v << 16); }
__device__ __forceinline__ float bf_hi(uint32_t v) { return __uint_as_float(v & 0xffff0000u); }
__device__ __forceinline__ float rbf(float v) { return bf_lo(pack2(v, v)); }
__device__ __forceinline__ uint32_t badd(uint32_t a, uint32_t b) {
    uint32_t r;
    asm("add.rn.bf16x2 %0, %1, %2;" : "=r"(r) : "r"(a), "r"(b));
    return r;
}
__device__ __forceinline__ uint32_t bsub(uint32_t a, uint32_t b) {
    uint32_t r;
    asm("sub.rn.bf16x2 %0, %1, %2;" : "=r"(r) : "r"(a), "r"(b));
    return r;
}
__device__ __forceinline__ uint32_t bmul(uint32_t a, uint32_t b) {
    uint32_t r;
    asm("mul.rn.bf16x2 %0, %1, %2;" : "=r"(r) : "r"(a), "r"(b));
    return r;
}
__device__ __forceinline__ uint32_t ln_apply(uint32_t x, uint32_t mb, float rs, uint32_t scale, uint32_t shift) {
    const uint32_t d = bsub(x, mb);
    return badd(bmul(pack2(bf_lo(d) * rs, bf_hi(d) * rs), scale), shift);
}
__device__ __forceinline__ float ex2(float v) {
    float r;
    asm("ex2.approx.ftz.f32 %0, %1;" : "=f"(r) : "f"(v));
    return r;
}
__device__ __forceinline__ float rcp(float v) {
    float r;
    asm("rcp.approx.ftz.f32 %0, %1;" : "=f"(r) : "f"(v));
    return r;
}
__device__ __forceinline__ float sqrt_fast(float v) {
    float r;
    asm("sqrt.approx.ftz.f32 %0, %1;" : "=f"(r) : "f"(v));
    return r;
}
__device__ __forceinline__ float ln_rstd(float var) { return rcp(rbf(sqrt_fast(rbf(rbf(var) + 1e-5f)))); }
__device__ __forceinline__ float sigmoid(float v) { return rcp(1.f + ex2(-1.4426950408889634f * v)); }
__device__ __forceinline__ float quad_sum(float v) {
    v += __shfl_xor_sync(0xffffffffu, v, 1);
    return v + __shfl_xor_sync(0xffffffffu, v, 2);
}

constexpr uint32_t HI_128 = 0x40000040u, HI_IMG = 0x80000080u, HI_Q = 0x80000040u;
template <int M, int RH>
__device__ __forceinline__ uint4 img_pack(const float (&d)[64], float s) {
    uint4 v;
    v.x = pack2(d[16 * M + 2 * RH] * s, d[16 * M + 2 * RH + 1] * s);
    v.y = pack2(d[16 * M + 4 + 2 * RH] * s, d[16 * M + 5 + 2 * RH] * s);
    v.z = pack2(d[16 * M + 8 + 2 * RH] * s, d[16 * M + 9 + 2 * RH] * s);
    v.w = pack2(d[16 * M + 12 + 2 * RH] * s, d[16 * M + 13 + 2 * RH] * s);
    return v;
}
template <int M>
__device__ __forceinline__ void img_store_global(uint32_t img, uint32_t toff, const float (&d)[64], float s0, float s1) {
    uint4* p = reinterpret_cast<uint4*>(g_img + (img + toff)) + M * 32;
    p[0] = img_pack<M, 0>(d, s0);
    p[128] = img_pack<M, 1>(d, s1);
}
__device__ __forceinline__ void sts128(uint32_t a, uint4 v) {
    asm volatile("st.shared.v4.b32 [%0], {%1, %2, %3, %4};" ::"r"(a), "r"(v.x), "r"(v.y), "r"(v.z), "r"(v.w) : "memory");
}
constexpr float SM_C = 0.08838834764831845f * 1.4426950408889634f;
__device__ __forceinline__ float pack2f(float lo, float hi) {
    float r;
    asm("{\n.reg .b32 t;\ncvt.rn.bf16x2.f32 t, %1, %2;\nmov.b32 %0, t;\n}" : "=f"(r) : "f"(hi), "f"(lo));
    return r;
}
template <int M, bool SCALE, bool PARK>
__device__ __forceinline__ void pack_group(float (&d)[64], float (&v)[8], float s0, float s1) {
#pragma unroll
    for (int i = 0; i < 8; i++) {
        const int k = 16 * M + 4 * (i & 3) + 2 * (i >> 2);
        v[i] = SCALE ? pack2f(d[k] * (i < 4 ? s0 : s1), d[k + 1] * (i < 4 ? s0 : s1)) : pack2f(d[k], d[k + 1]);
        if (PARK && M > 0) d[16 * (M > 0 ? M - 1 : 0) + i] = v[i];
    }
}
__device__ __forceinline__ uint32_t q_off(uint32_t toff) {
    asm volatile("" : "+r"(toff));
    return (((toff >> 1) & ~2047u) ^ 8192) + (toff & 511);
}
template <int M>
__device__ __forceinline__ void ctx_store_part(float4* p, float (&d)[64], float i0, float i1) {
    float v[8];
    pack_group<M, true, true>(d, v, i0, i1);
    p[M * 32] = make_float4(v[0], v[1], v[2], v[3]);
    p[M * 32 + 128] = make_float4(v[4], v[5], v[6], v[7]);
}
__device__ __forceinline__ void ctx_store(uint32_t img, uint32_t toff, float (&o)[64], float i0, float i1) {
    asm volatile("" : "+r"(toff));
    float4* p = reinterpret_cast<float4*>(g_img + (img + toff));
    ctx_store_part<0>(p, o, i0, i1); ctx_store_part<1>(p, o, i0, i1); ctx_store_part<2>(p, o, i0, i1); ctx_store_part<3>(p, o, i0, i1);
}

__device__ __forceinline__ void slot_wait(uint32_t bars, uint32_t& ph, uint32_t slot) {
    mbar_wait(bars + 8 * slot, (ph >> slot) & 1);
    ph ^= 1u << slot;
}
__device__ __forceinline__ void release_if(uint32_t eb, uint32_t slot, bool on) {
    asm volatile("{\n.reg .pred p;\nsetp.ne.s32 p, %1, 0;\n@p mbarrier.arrive.shared::cluster.b64 _, [%0];\n}" ::"r"(eb + 8 * slot), "r"((int)on) : "memory");
}
__device__ __forceinline__ void slot_expect(uint32_t sb, uint32_t slot) {
    asm volatile("{\n.reg .pred p;\nelect.sync _|p, 0xffffffff;\n@p mbarrier.arrive.expect_tx.shared::cta.b64 _, [%0], 32768;\n}"
                 ::"r"(sb + BAR_FULL + 8 * slot) : "memory");
}
__device__ __forceinline__ void slot_acquire(uint32_t sb, uint32_t& ph, uint32_t slot) {
    slot_wait(sb + BAR_EMPTY, ph, slot);
    slot_expect(sb, slot);
}
__device__ __forceinline__ void load_bulk(uint32_t sb, uint32_t slot, uint32_t off, const void* src, uint32_t bytes, bool both, bool first) {
    if (both)
        asm volatile("{\n.reg .pred p;\nelect.sync _|p, 0xffffffff;\n"
                     "@p cp.async.bulk.shared::cluster.global.mbarrier::complete_tx::bytes.multicast::cluster.L2::cache_hint [%0], [%1], %5, [%2], %4, %3;\n}"
                     ::"r"(sb + slot * SLOT + off), "l"(src), "r"(sb + BAR_FULL + 8 * slot), "l"(first ? L2_FIRST : L2_NORMAL), "h"((uint16_t)3),
                     "r"(bytes) : "memory");
    else
        asm volatile("{\n.reg .pred p;\nelect.sync _|p, 0xffffffff;\n"
                     "@p cp.async.bulk.shared::cluster.global.mbarrier::complete_tx::bytes.L2::cache_hint [%0], [%1], %4, [%2], %3;\n}"
                     ::"r"(sb + slot * SLOT + off), "l"(src), "r"(sb + BAR_FULL + 8 * slot), "l"(first ? L2_FIRST : L2_NORMAL), "r"(bytes) : "memory");
}
__device__ __forceinline__ void load_tile(uint32_t sb, uint32_t slot, uint32_t off, const CUtensorMap* m, int row, int cb, bool both, bool first) {
    if (both)
        asm volatile("{\n.reg .pred p;\nelect.sync _|p, 0xffffffff;\n"
                     "@p cp.async.bulk.tensor.3d.shared::cluster.global.mbarrier::complete_tx::bytes.multicast::cluster.L2::cache_hint [%0], [%1, {%3, %4, %5}], [%2], %7, %6;\n}"
                     ::"r"(sb + slot * SLOT + off), "l"(m), "r"(sb + BAR_FULL + 8 * slot), "r"(0), "r"(row), "r"(cb),
                     "l"(first ? L2_FIRST : L2_NORMAL), "h"((uint16_t)3) : "memory");
    else
        asm volatile("{\n.reg .pred p;\nelect.sync _|p, 0xffffffff;\n"
                     "@p cp.async.bulk.tensor.3d.shared::cluster.global.mbarrier::complete_tx::bytes.L2::cache_hint [%0], [%1, {%3, %4, %5}], [%2], %6;\n}"
                     ::"r"(sb + slot * SLOT + off), "l"(m), "r"(sb + BAR_FULL + 8 * slot), "r"(0), "r"(row), "r"(cb),
                     "l"(first ? L2_FIRST : L2_NORMAL) : "memory");
}
__device__ __forceinline__ uint32_t ring_next(uint32_t r) { return r == 4 ? 0 : r + 1; }
__device__ __forceinline__ uint32_t w_table(int hp) { return hp ? 0x3104u : 0x4210u; }
__device__ __forceinline__ uint32_t a_table(int hp) { return hp ? 0x625u : 0x635u; }
__device__ __forceinline__ uint32_t a_next(uint32_t& t) {
    const uint32_t s = t & 15;
    t = (t >> 4) | (s << 8);
    return s;
}
constexpr uint32_t O_TABLE = 0x1604235u;
constexpr uint32_t SL_X = OFF == 0 ? 4 : OFF == 1 ? 3 : 1, SL_WD = OFF == 0 ? 6 : OFF == 1 ? 4 : 3, SL_WF = OFF == 0 ? 5 : OFF == 1 ? 6 : 4;
__device__ __forceinline__ uint32_t o_next(uint32_t& t) {
    const uint32_t s = t & 15;
    t = (t >> 4) | (s << 24);
    return s;
}
__device__ __forceinline__ int o_head(int i, int kh) { return i < 16 ? 4 * (i & 7) + 2 * (kh ^ 1) + (i >> 3) : 29 + 2 * kh; }

template <bool INIT>
__device__ __forceinline__ void gemm_issue(float (&d)[64], uint32_t a, uint32_t b, int acc, bool img) {
    uint64_t da = desc64(a, img ? HI_IMG : HI_128), db = desc64(b, HI_128);
    wg_fence();
#pragma unroll
    for (int k = 0; k < 8; k++) {
        if (INIT && k == 0) wgmma_ss128_init<1>(d, da, db);
        else wgmma_ss128<1>(d, da, db, k ? 1 : acc);
        desc_add(da, !(k & 1) ? 2 : img ? 30 : k == 3 ? 1018 : 2);
        desc_add(db, 128);
    }
    wg_commit();
}

__device__ __forceinline__ void step_retire(uint32_t eb, bool rel, uint32_t pend) {
    wg_wait<0>();
    release_if(eb, pend & 7, rel && (pend & 7) != 7);
    release_if(eb, pend >> 4, rel && pend < 0x70);
}
template <bool ODD>
__device__ __forceinline__ void proj_tile(float (&acc)[64], float (&prev)[64], int t, int q0, uint32_t sb, int wg, uint32_t eb, bool rel, uint32_t& fph,
                                          uint32_t wtab, uint32_t& atab, uint32_t& pend, uint32_t prev_img, uint32_t toff, float s0, float s1,
                                          uint32_t (&v)[32]) {
    const uint32_t a0 = desc_k(sb + (wg ^ (ODD && t == 5)) * 8192), b0 = desc_mn(sb);
    int q = q0;
#pragma unroll 1
    do {
        const uint32_t ws = (wtab >> (4 * q)) & 15, as = a_next(atab);
        if (!ODD && t != 2) slot_wait(sb + BAR_FULL, fph, ws);
        slot_wait(sb + BAR_FULL, fph, as);
        step_retire(eb, rel, pend);
        if (ODD && q == 2 && t == 5) {
            const uint32_t a = sb + 5 * SLOT + q_off(toff);
#pragma unroll
            for (int i = 0; i < 8; i++) sts128(a + (i >> 2) * 16384 + (i & 2) * 256 + (i & 1) * 1024, make_uint4(v[4 * i], v[4 * i + 1], v[4 * i + 2], v[4 * i + 3]));
        }
        bar_sync(1 + wg, 256);
        gemm_issue<false>(acc, a0 + as * (SLOT / 16), b0 + ws * (SLOT / 16), q, false);
        bar_arrive(2 - wg, 256);
        pend = (ODD && q == 1 && t == 5 ? 7 : as) | (ODD && t != 1 ? ws : 7) << 4;
        wg_wait<1>();
        reg_fence(prev);
        if (ODD && t == 5) {
            if (q == 0) {
#pragma unroll
                for (int i = 0; i < 32; i++) {
                    const int k = 16 * (i >> 3) + 4 * (i & 3) + ((i >> 1) & 2);
                    v[i] = pack2(prev[k], prev[k + 1]);
                }
            }
        } else {
            if (q == 0) img_store_global<0>(prev_img, toff, prev, s0, s1);
            if (q == 1) img_store_global<1>(prev_img, toff, prev, s0, s1);
            if (q == 2) img_store_global<2>(prev_img, toff, prev, s0, s1);
            if (q == 3) img_store_global<3>(prev_img, toff, prev, s0, s1);
        }
    } while (++q < (ODD && t == 5 ? 3 : 4));
}

__device__ __forceinline__ void qk_issue(float (&s)[64], uint32_t q, uint32_t k) {
    wg_fence();
    uint64_t da = desc64(q, HI_Q), db = desc64(k, HI_IMG);
    wgmma_ss128_init<0>(s, da, db);
#pragma unroll
    for (int i = 1; i < 8; i++) {
        desc_add(da, (i & 1) ? 2 : i == 4 ? 990 : 30);
        desc_add(db, (i & 1) ? 2 : 30);
        wgmma_ss128<0>(s, da, db, 1);
    }
    wg_commit();
}
__device__ __forceinline__ void qk_issue(float (&s)[32], uint32_t q, uint32_t k) {
    wg_fence();
    uint64_t da = desc64(q, HI_Q), db = desc64(k, HI_IMG);
    wgmma_ss64_init<0>(s, da, db);
#pragma unroll
    for (int i = 1; i < 8; i++) {
        desc_add(da, (i & 1) ? 2 : i == 4 ? 990 : 30);
        desc_add(db, (i & 1) ? 2 : 30);
        wgmma_ss64<0>(s, da, db, 1);
    }
    wg_commit();
}
__device__ __forceinline__ void pv_issue(float (&o)[64], const uint32_t (&p)[32], uint32_t v, int acc, bool half) {
    uint64_t db = desc64(v, HI_IMG);
    if (half) {
        asm volatile("// half" ::: "memory");
        wg_fence();
#pragma unroll
        for (int i = 0; i < 4; i++) {
            wgmma_rs128(o, p[4 * i], p[4 * i + 1], p[4 * i + 2], p[4 * i + 3], db, i ? 1 : acc);
            desc_add(db, 256);
        }
        wg_commit();
        asm volatile("// half" ::: "memory");
    } else {
        wg_fence();
#pragma unroll
        for (int i = 0; i < 8; i++) {
            wgmma_rs128(o, p[4 * i], p[4 * i + 1], p[4 * i + 2], p[4 * i + 3], db, i ? 1 : acc);
            desc_add(db, 256);
        }
        wg_commit();
    }
}
__device__ __forceinline__ void tri_mask(float (&s)[64], float x) {
#pragma unroll
    for (int k = 0; k < 16; k++) {
        float b;
        asm("sub.sat.f32 %0, %1, %2;" : "=f"(b) : "f"((float)(8 * (k >> 1) + (k & 1))), "f"(x));
        const int i = 32 + 4 * (k >> 1) + (k & 1);
        asm("fma.rn.f32 %0, %1, 0fFF61B1E6, %0;" : "+f"(s[i]) : "f"(b));
        if (k < 14) asm("fma.rn.f32 %0, %1, 0fFF61B1E6, %0;" : "+f"(s[i + 6]) : "f"(b));
    }
}
__device__ __forceinline__ void tri_mask_copy(float (&s)[64], const float (&h)[32], float x) {
#pragma unroll
    for (int i = 0; i < 32; i++) {
            asm("{\n.reg .pred p;\nsetp.lt.f32 p, %2, %3;\nselp.f32 %0, 0fFF800000, %1, p;\n}"
                : "=f"(s[i]) : "f"(h[i]), "f"(x), "f"((float)(8 * (i >> 2) - 4 * (i & 2) + (i & 1))));
        s[32 + i] = __uint_as_float(0xff800000u);
    }
}
constexpr float SM_HI = 1152921504606846976.f, SM_LO = 1.f / 1152921504606846976.f;
__device__ __forceinline__ bool softmax_unsafe(float t0, float t1, bool first) {
    bool bad = __any_sync(0xffffffffu, fmaxf(t0, t1) > SM_HI);
    if (first) {
        uint32_t a = __ballot_sync(0xffffffffu, t0 >= SM_LO), b = __ballot_sync(0xffffffffu, t1 >= SM_LO);
        a |= a >> 1;
        b |= b >> 1;
        bad |= ((a | (a >> 2)) & (b | (b >> 2)) & 0x11111111u) != 0x11111111u;
    }
    return bad;
}
__device__ __forceinline__ void softmax_remax(const float (&s)[64], float (&m)[2], bool first, float& m0, float& m1, float& a0, float& a1) {
    m0 = fmaxf(s[0], s[1]), m1 = fmaxf(s[2], s[3]);
#pragma unroll
    for (int k = 1; k < 16; k++) {
        m0 = fmaxf(m0, fmaxf(s[4 * k], s[4 * k + 1]));
        m1 = fmaxf(m1, fmaxf(s[4 * k + 2], s[4 * k + 3]));
    }
    m0 = fmaxf(m0, __shfl_xor_sync(0xffffffffu, m0, 1));
    m1 = fmaxf(m1, __shfl_xor_sync(0xffffffffu, m1, 1));
    m0 = fmaxf(m0, __shfl_xor_sync(0xffffffffu, m0, 2));
    m1 = fmaxf(m1, __shfl_xor_sync(0xffffffffu, m1, 2));
    if (!first) {
        m0 = fmaxf(m0, 0.f);
        m1 = fmaxf(m1, 0.f);
    }
    a0 = first ? 1.f : ex2(-m0);
    a1 = first ? 1.f : ex2(-m1);
    m[0] += m0;
    m[1] += m1;
}
template <int J0, int J1>
__device__ __forceinline__ void softmax_exp(const float (&s)[64], uint32_t (&p)[32], float (&t)[4]) {
#pragma unroll
    for (int k = J0; k < J1; k++) {
        const float e0 = ex2(s[4 * k]), e1 = ex2(s[4 * k + 1]), e2 = ex2(s[4 * k + 2]), e3 = ex2(s[4 * k + 3]);
        if (k == 0) { t[0] = e0; t[1] = e1; t[2] = e2; t[3] = e3; }
        else { t[0] += e0; t[1] += e1; t[2] += e2; t[3] += e3; }
        p[2 * k] = pack2(e0, e1);
        p[2 * k + 1] = pack2(e2, e3);
    }
}
__device__ __forceinline__ void mma16816(float (&d)[4], const uint32_t* a, uint32_t b0, uint32_t b1) {
    asm("mma.sync.aligned.m16n8k16.row.col.f32.bf16.bf16.f32 {%0, %1, %2, %3}, {%4, %5, %6, %7}, {%8, %9}, {%0, %1, %2, %3};"
        : "+f"(d[0]), "+f"(d[1]), "+f"(d[2]), "+f"(d[3]) : "r"(a[0]), "r"(a[1]), "r"(a[2]), "r"(a[3]), "r"(b0), "r"(b1));
}
__device__ __forceinline__ uint32_t best_key(const uint32_t* keys, int lane, uint32_t ep) {
#pragma unroll 1
    for (;;) {
        const uint4 k = ld_poll(reinterpret_cast<const uint4*>(keys) + lane);
        const uint32_t best = __reduce_max_sync(0xffffffffu, max(max(k.x, k.y), max(k.z, k.w)));
        const uint32_t ok = __ballot_sync(0xffffffffu, (((k.x ^ ep) | (k.y ^ ep) | (k.z ^ ep) | (k.w ^ ep)) & 31) == 0);
        if (ok == ~0u) return best;
        __nanosleep(__popc(ok) < KN ? KSLEEP : KSLEEP2);
    }
}

__global__ void __cluster_dims__(2, 1, 1) __launch_bounds__(384, 1)
fused_kernel(const __grid_constant__ CUtensorMap tm_ckv, const __grid_constant__ CUtensorMap tm_wq,
             const __grid_constant__ CUtensorMap tm_wuk, const __grid_constant__ CUtensorMap tm_wuv,
             const __grid_constant__ CUtensorMap tm_wo, const __grid_constant__ CUtensorMap tm_wg,
             const __grid_constant__ CUtensorMap tm_wu,
             const __grid_constant__ CUtensorMap tm_wm, const __grid_constant__ CUtensorMap tm_x, const Params P) {
    extern __shared__ __align__(1024) uint8_t smem[];
    if (threadIdx.x == 352) {
        asm volatile("prefetch.tensormap [%0];" ::"l"(&tm_ckv) : "memory");
        asm volatile("prefetch.tensormap [%0];" ::"l"(blockIdx.x >= NCTA ? &tm_wm : (blockIdx.x & 1) ? &tm_wuv : &tm_wuk) : "memory");
    }
    const uint32_t sb = (uint32_t)__cvta_generic_to_shared(smem);
    const int tid = threadIdx.x, lane = tid & 31, warp = __shfl_sync(0xffffffffu, tid >> 5, 0), wg = warp >> 2;
    const uint32_t sm = blockIdx.x < 8 ? blockIdx.x + 124 : blockIdx.x - 8, smq = ((sm - 64) * 147) >> 11;
    const int rb = sm < 64 ? (sm & 14) * 8 + (sm >> 4) * 2 + (sm & 1)
                 : sm < 120 ? ((sm - 64 - smq * 14) & 14) * 8 + 24 + smq * 2 + (sm & 1) : sm < 124 ? sm + 8 : sm - 116;
    const int grp = rb >> 3, j = rb & 7, kh = (grp >> 1) & 1;
    const int cq = (j & 1) + ((grp >> 1) & 2), ort = (grp & 8) + (grp & 1) * 4 + (j >> 1);
    if (warp == 0) TS(0);

    const CUtensorMap* tw = (j & 1) ? &tm_wuv : &tm_wuk;
    if (lane == 0) {
        if (warp == 8) {
#pragma unroll
            for (int i = 0; i < 7; i++) mbar_init(sb + BAR_FULL + 8 * i, 1);
            fence_async_smem();
        } else if (warp < 11) {
            const int w = warp - (warp > 8);
            const u64 cnt = (w < 5 ? (rb < NCTA ? 0x888888884444444ull : 0x888888888888888ull) : 0x111812111111118ull) >> (12 * (w % 5));
#pragma unroll
            for (int i = 0; i < 3; i++) mbar_init(sb + BAR_EMPTY + 24 * w + 8 * i, ((uint32_t)cnt >> (4 * i)) & 15);
        }
        asm volatile("fence.mbarrier_init.release.cluster;" ::: "memory");
    }
    __syncwarp();
    asm volatile("barrier.cluster.arrive.relaxed.aligned;" ::: "memory");
    if (warp == 8) {
        if (rb < NCTA) {
#pragma unroll 1
            for (int u = 0; u < 4; u++) {
                const uint32_t ws = u + (u == 3), as = (0x635u >> (4 * u)) & 15;
                slot_expect(sb, ws);
                load_tile(sb, ws, 0, tw, u * 128, 4 * grp, false, HINT & 1);
                if (u == 3) break;
                slot_expect(sb, as);
                load_tile(sb, as, 0, &tm_ckv, (j >> 1) * 128, u * 2, false, false);
                load_tile(sb, as, 16384, &tm_ckv, (j >> 1) * 128, u * 2 + 1, false, false);
            }
        } else {
#pragma unroll 1
            for (int i = 0; i < 6; i++) {
                slot_expect(sb, i);
                load_tile(sb, i, 0, &tm_wm, i * 64, (rb - NCTA) * 4, false, HINT & 64);
                if (i > 3) tma3d_prefetch(&tm_wm, i * 64 + 128, (rb - NCTA) * 4);
            }
        }
    }
    asm volatile("barrier.cluster.wait.aligned;" ::: "memory");

    if (rb >= NCTA) {
        const int sp = rb - NCTA;
        const uint32_t ep = __ldcg(&g_sync.epoch[0]) + 1;
        uint32_t ph = 0, sl = 0;
        if (warp == 8) {
#pragma unroll 1
            for (int i = 6; i < 54 + 2 * OFF; i++) {
                slot_acquire(sb, ph, sl);
                const int k = i - 24;
                load_tile(sb, sl, 0, i < 24 ? &tm_wm : i >= 54 ? &tm_wo : (k & 2) ? &tm_wu : &tm_wg, i < 24 ? (i & 7) * 64 : i >= 54 ? (i - 38 - 2 * OFF) * 256 : (k & 1) * 256,
                          i < 24 ? (i >> 3) * 16 + sp * 4 : i >= 54 ? sp * 2 : sp * 7 + (k >> 2), false, true);
                if (++sl == 6) sl = 0;
                if (i == 51) { i = 53; sl = 0; }
            }
            bar_sync(4, 64);
            slot_wait(sb + BAR_EMPTY, ph, 4);
            slot_wait(sb + BAR_EMPTY, ph, 5);
            ph = 0x3f, sl = 0;
#pragma unroll 1
            for (int h = 0; h < 32; h++) {
                step_watch(sb + SM_EP + 16, h + 1);
                fence_async_global();
                const uint8_t* src = g_ctx + (size_t)(((h >> 1) ^ 8) * 32 + 30 - 4 * OFF) * SLOT + (h & 1) * 16384;
#pragma unroll 1
                for (int k = 0; k <= 2 * OFF; k++, src += 2 * SLOT) {
                    slot_wait(sb + BAR_DONE, ph, sl);
                    const uint32_t f = sb + BAR_FLAG + 8 * sl, d = sb + 4 * SLOT + sl * 16384;
                    asm volatile("{\n.reg .pred p;\nelect.sync _|p, 0xffffffff;\n@p mbarrier.arrive.expect_tx.shared::cta.b64 _, [%0], 16384;\n}" ::"r"(f) : "memory");
                    if (k == 0)
                        asm volatile("{\n.reg .pred p;\nelect.sync _|p, 0xffffffff;\n"
                                     "@p cp.async.bulk.tensor.3d.shared::cluster.global.mbarrier::complete_tx::bytes [%0], [%1, {%3, %4, %5}], [%2];\n}"
                                     ::"r"(d), "l"(&tm_x), "r"(f), "r"(0), "r"((h ^ 16) * 64), "r"(sp * 2) : "memory");
                    else
                        asm volatile("{\n.reg .pred p;\nelect.sync _|p, 0xffffffff;\n"
                                     "@p cp.async.bulk.shared::cluster.global.mbarrier::complete_tx::bytes [%0], [%1], 16384, [%2];\n}"
                                     ::"r"(d), "l"(src), "r"(f) : "memory");
                    if (++sl == 6) sl = 0;
                }
            }
        } else if (warp == 9) {
#pragma unroll 1
            for (int t = 0; t <= 16; t++) {
                asm volatile("st.release.cta.shared.u32 [%0], %1;" ::"r"(sb + SM_EP + 16), "r"(2 * t) : "memory");
                if (t == 0) bar_sync(4, 64);
                if (lane < 4 && t < 16) flag_wait(&g_sync.ctxcnt[(t ^ 8) * 32 + 24 + 2 * lane], ep);
                __syncwarp();
            }
        } else if (warp < 8) {
            const uint32_t c2 = __ldg(reinterpret_cast<const uint32_t*>(P.c) + tid);
            uint32_t* sc = reinterpret_cast<uint32_t*>(smem + SM_TAB);
            sc[tid] = pack2(bf_lo(c2) * sigmoid(bf_lo(c2)), bf_hi(c2) * sigmoid(bf_hi(c2)));
            bar_sync(1, 256);
            const uint32_t a = sb + (warp >> 1) * 8192 + ((lane >> 4) * 8 + (lane & 7)) * 128, ch = (warp & 1) * 4 + ((lane >> 3) & 1);
#pragma unroll 1
            for (int ps = 0; ps < 3; ps++) {
                float d[2][4] = {};
#pragma unroll 1
                for (int bt = 0; bt < 8; bt++) {
                    slot_wait(sb + BAR_FULL, ph, sl);
#pragma unroll
                    for (int i = 0; i < 8; i++) {
                        uint32_t w[4];
                        asm volatile("ldmatrix.sync.aligned.m8n8.x4.trans.shared.b16 {%0, %1, %2, %3}, [%4];" : "=r"(w[0]), "=r"(w[1]), "=r"(w[2]), "=r"(w[3])
                                     : "r"(a + sl * SLOT + (i >> 1) * 2048 + (((ch + 2 * (i & 1)) ^ (lane & 7)) << 4)) : "memory");
                        mma16816(d[i & 1], w, sc[bt * 32 + (i >> 1) * 8 + (lane & 3)], sc[bt * 32 + (i >> 1) * 8 + 4 + (lane & 3)]);
                    }
                    __syncwarp();
                    mbar_arrive_if(sb + BAR_EMPTY + 8 * sl, lane == 0);
                    if (++sl == 6) sl = 0;
                }
                const float v = (lane & 2) ? ((lane & 1) ? d[1][2] : d[1][0]) : ((lane & 1) ? d[0][2] : d[0][0]);
                const int col = sp * 256 + warp * 32 + (lane & 3) * 8 + (lane >> 2);
                if (ps == 0) st_pub(g_mod1 + col, (pack2(0.f, v) & 0xffff0000u) | (ep & 0xffffu), true);
                else g_mod[ps * 1024 + col] = __float2bfloat16_rn(v);
                if (warp == 0) TS(1 + ps);
            }
#pragma unroll 1
            for (int k = 0; k < 28; k++) {
                slot_wait(sb + BAR_FULL, ph, sl);
                uint4* dst = reinterpret_cast<uint4*>(g_wf) + (sp * 28 + (k & ~3)) * 2048 + (k & 3) * 512 + tid;
#pragma unroll 4
                for (int i = 0; i < 8; i++) {
                    const int row = (i & 1) * 128 + (tid >> 1);
                    __stcs(dst + (i >> 1) * 2048 + (i & 1) * 256, lds128(sb + sl * SLOT + row * 128 + ((((i & 6) + ((tid ^ (row >> 2)) & 1)) ^ (row & 7)) << 4)));
                }
                __syncwarp();
                mbar_arrive_if(sb + BAR_EMPTY + 8 * sl, lane == 0);
                if (++sl == 6) sl = 0;
            }
            bar_sync(1, 256);
            if (tid < 2) {
                flag_add(&g_sync.cnt[7 * 8]);
                flag_wait(&g_sync.cnt[7 * 8], 8 * ep);
            }
            if (warp == 0) TS(4);
            bar_sync(1, 256);
            uint32_t ga[16], x2[32];
#pragma unroll
            for (int i = 0; i < 16; i++) ga[i] = __ldcg(reinterpret_cast<const uint32_t*>(g_mod) + 512 + sp * 64 + (lane & 3) + 4 * i);
#pragma unroll 1
            for (int i = 0; i < 2 * OFF; i++) slot_wait(sb + BAR_FULL, ph, i);
            float d[64];
            uint32_t u = (2 * OFF + 1) * wg, up = 0;
            if (wg == 1) bar_arrive(2, 256);
#pragma unroll 1
            for (int h = wg; h < 32; h += 2) {
                mbar_wait(sb + BAR_FLAG + 8 * u, up);
                const uint32_t xa = sb + 4 * SLOT + u * 16384 + ((warp & 3) * 16 + (lane & 15)) * 128;
#pragma unroll
                for (int k = 0; k < 8; k++)
                    asm volatile("ldmatrix.sync.aligned.m8n8.x4.shared.b16 {%0, %1, %2, %3}, [%4];"
                                 : "=r"(x2[4 * k]), "=r"(x2[4 * k + 1]), "=r"(x2[4 * k + 2]), "=r"(x2[4 * k + 3])
                                 : "r"(xa + (k >> 2) * 8192 + (((2 * (k & 3) + (lane >> 4)) ^ (lane & 7)) << 4)) : "memory");
                mbar_arrive_if(sb + BAR_DONE + 8 * u, lane < 2);
                bar_sync(2 + wg, 256);
#pragma unroll 1
                for (int k = 0; k < 2 * OFF; k++) {
                    const uint32_t pu = u;
                    if (++u == 6) { u = 0; up ^= 1; }
                    mbar_wait(sb + BAR_FLAG + 8 * u, up);
                    gemm_issue<false>(d, desc_k(sb + 4 * SLOT) + u * 1024, desc_mn(sb) + k * (SLOT / 16), k, true);
                    wg_wait<1>();
                    mbar_arrive_if(sb + BAR_DONE + 8 * pu, lane < 2 && k);
                }
                if (h < 31) bar_arrive(3 - wg, 256);
                wg_wait<0>();
                reg_fence(d);
                mbar_arrive_if(sb + BAR_DONE + 8 * u, lane < 2);
                u += 2 * OFF + 2;
                if (u >= 6) { u -= 6; up ^= 1; }
                uint4* op = g_x2 + ((h ^ 16) * 4 + sp) * 1024 + (tid & 127);
#pragma unroll
                for (int v = 0; v < 8; v++) {
                    uint32_t y[4];
#pragma unroll
                    for (int i = 0; i < 4; i++) {
                        const int k = 4 * v + i;
                        y[i] = pack2(fmaf(bf_lo(ga[k >> 1]), d[2 * k], bf_lo(x2[k])), fmaf(bf_hi(ga[k >> 1]), d[2 * k + 1], bf_hi(x2[k])));
                    }
                    op[v * 128] = make_uint4(y[0], y[1], y[2], y[3]);
                }
            }
            bar_sync(1, 256);
            if (tid == 0) flag_add(&g_sync.cnt[15 * 8]);
            if (warp == 0) TS(5);
        }
        return;
    }

    if (wg == 2) {
        asm volatile("setmaxnreg.dec.sync.aligned.u32 40;");
        if (warp == 8) {
            const uint32_t rank = j & 1, half = rank * 16384;
            uint32_t eph = 0, r = 0;
            *reinterpret_cast<volatile uint32_t*>(smem + SM_EP + 20) = 0;
#pragma unroll 1
            for (int hp = 0; hp < 2; hp++) {
                uint32_t wtab = w_table(hp), atab = a_table(hp);
                const int hc = 4 * grp + 2 * hp;
#pragma unroll 1
                for (int u = 3 - 3 * hp; u < 16; u++) {
                    if (hp && u < 4) {
                        const uint32_t ws = (wtab >> (4 * u)) & 15;
                        slot_acquire(sb, eph, ws);
                        load_tile(sb, ws, 0, tw, u * 128, hc, false, HINT & 1);
                        PT();
                    }
                    if (hp == 1 && (u & 7) == 4) mbar_wait(sb + BAR_FLAG + 24 + (u & 8), 0);
                    const uint32_t as = a_next(atab);
                    slot_acquire(sb, eph, as);
                    load_tile(sb, as, half, &tm_ckv, ((u & 12) + (j >> 1)) * 128, (u & 3) * 2 + rank, true, (HINT & 8) && hp);
                    PT();
                    if (hp == 1 && (u | 2) == 3 && lane == 0)
                        asm volatile("red.relaxed.gpu.global.add.u32 [%0], 1;" ::"l"(&g_sync.cnt[(grp * 8 + 3 + (u >> 1)) * 8]) : "memory");
                }
                const uint8_t* src = g_h + (15 - j) * 4 * SLOT;
#pragma unroll 1
                for (int u = 0; u < 8; u++) {
                    if (u == 0 || u == KVG) {
                        mbar_wait(sb + BAR_FLAG + (u ? 8 + 32 * hp : 0), 0);
                        fence_async_global();
                    }
                    if (u < 4) {
                        const uint32_t ws = (wtab >> (4 * u)) & 15;
                        slot_acquire(sb, eph, ws);
                        load_tile(sb, ws, 0, &tm_wq, u * 128, hc, false, HINT & 1);
                        PT();
                    }
                    const uint32_t as = a_next(atab);
                    slot_acquire(sb, eph, as);
                    load_bulk(sb, as, 0, src, SLOT, false, (HINT & 8) && hp);
                    PT();
                    src += u == 3 ? (8 * j - 63) * SLOT : SLOT;
                }
                const int step = hp ? -2 * SLOT : 2 * SLOT;
                src = g_KV + (size_t)(grp * 32 + 30 * hp) * SLOT + half - step;
#pragma unroll 1
                for (int n = 0; n <= 17; n++) {
                    if (n == 8) {
                        mbar_wait(sb + BAR_FLAG + 16 + 32 * hp, 0);
                        fence_async_global();
                    }
                    const uint8_t* v = src + SLOT;
                    src += n < 16 - j ? step : n == 16 - j ? (2 * j - 15) * step : -step;
                    if (n < 17) {
                        slot_acquire(sb, eph, r);
                        if (n != 15 - (j & 6)) load_bulk(sb, r, half, src, SLOT / 2, true, HINT & 4);
                        else load_bulk(sb, r, 0, src - half, SLOT, false, HINT & 4);
                        PT();
                        r = ring_next(r);
                    }
                    if (n) {
                        slot_acquire(sb, eph, r);
                        if (n != 16 - (j & 6)) load_bulk(sb, r, half, v, SLOT / 2, true, HINT & 4);
                        else load_bulk(sb, r, 0, v - half, SLOT, false, HINT & 4);
                        PT();
                        r = ring_next(r);
                    }
                    asm volatile("st.volatile.shared.u32 [%0], %1;" ::"r"(sb + SM_EP + 16), "r"(18 * hp + n + 1) : "memory");
                }
            }
            uint32_t otab = O_TABLE, ready = 0;
#pragma unroll 1
            for (int i = 0; i < 17; i += i == 7 - OFF ? 1 + OFF : 1) {
                const bool dyn = i >= 8 && i < 15;
                const uint32_t want = dyn ? 15u << (4 * (i - 8)) : 1u << max(i + 14, 28);
                if (!(ready & want)) {
                    do {
                        asm volatile("ld.acquire.cta.shared.u32 %0, [%1];" : "=r"(ready) : "r"(sb + SM_EP + 20) : "memory");
                        ready = __shfl_sync(0xffffffffu, ready, 0);
                    } while (!(ready & want));
                    fence_async_global();
                }
                const int head = o_head(dyn ? (ready >> (4 * (i - 8))) & 15 : i, kh);
                const uint32_t as = o_next(otab), ws = o_next(otab), off = i < 15 ? half : kh * 16384;
                slot_acquire(sb, eph, as);
                load_bulk(sb, as, off, g_ctx + (size_t)(ort * 32 + head) * SLOT + off, SLOT / 2, i < 15, HINT & 16);
                if (i >= 15) load_bulk(sb, as, off ^ 16384, i == 15 ? g_x2 + ((ort * 2 + kh) * 4 + cq) * 1024 : reinterpret_cast<const uint4*>(P.wdown) + min(rb, NFFN - 1) * 1024, SLOT / 2, false, false);
                PT();
                slot_acquire(sb, eph, ws);
                load_tile(sb, ws, 0, &tm_wo, head * 128, cq * 2, false, HINT & 2);
                PT();
                if (i == 0) o_next(otab);
            }
            if (rb < NFFN) {
                slot_acquire(sb, eph, SL_WF);
                load_bulk(sb, SL_WF, 0, g_wf + rb * SLOT, SLOT, false, false);
            }
        } else if (warp == 9) {
            *reinterpret_cast<volatile uint32_t*>(smem + SM_EP + 16) = 0;
            l2_prefetch(P.ckv + rb * 2048, 4096);
            mbar_watch(sb + BAR_FULL, 0);
            l2_prefetch(P.ckv + 512 * 512 + rb * 2048, 4096);
            mbar_watch(sb + BAR_FULL + 8 * XPF, 0);
            l2_prefetch(P.x + rb * 8192, 16384);
            mbar_watch(sb + BAR_FULL + 8 * 4, 0);
            l2_prefetch(P.ckv + 1024 * 512 + rb * 4096, 8192);
            TS(40);
#pragma unroll 1
            for (int i = 0; i < 13; i++) {
                step_watch(sb + SM_EP + 16, i == 0 ? 0 : i < 5 ? PFA + i : 13 + PFB + i);
                if (i == 10) mbar_watch(sb + BAR_FLAG + 8 * 7, 0);
                const int rf = min(rb, NFFN - 1), pc = 4 * (i - 5) + cq;
                const uint8_t* p = i == 3 ? reinterpret_cast<const uint8_t*>(P.ckv) + rb * 16384
                                 : i == 4 ? g_h + rb * 16384
                                 : i < 8 ? g_ctx + (size_t)(ort * 32 + o_head(pc >> 1, kh)) * SLOT + (pc & 1) * 16384
                                 : i < 10 ? reinterpret_cast<const uint8_t*>(P.wo) + (grp * 16 + (i & 1) * 8 + j) * 16384
                                 : i == 10 ? reinterpret_cast<const uint8_t*>(P.wdown) + rf * 16384 : g_wf + rf * SLOT + (i & 1) * 16384;
                if (i >= 3) l2_prefetch(p, 16384);
                else if ((i | j) & 1) tma3d_prefetch(i == 1 ? tw : &tm_wq, (j >> 1) * 128, grp * 4 + (i ? 2 : 0));
            }
            const uint32_t v = lds32(sb + SM_EP) - 1;
            sts128(sb + SM_RED + lane * 16, make_uint4(v, v, v, v));
            fence_async_smem();
            __syncwarp();
#pragma unroll 1
            for (int i = 0; i < OB / 32; i++) bulk_store(g_out + rb * OB + i * 32, sb + SM_RED, 512, false);
            asm volatile("cp.async.bulk.commit_group;\ncp.async.bulk.wait_group 0;" ::: "memory");
            fence_async_global();
            __syncwarp();
            mbar_arrive_if(sb + BAR_PF, lane == 0);
            if (lane == 0) mbar_watch(sb + BAR_END, 0);
        } else {
            const uint32_t ep = __ldcg(&g_sync.epoch[0]) + 1;
            asm volatile("st.shared.u32 [%0], %1;" ::"r"(sb + SM_EP), "r"(ep) : "memory");
            mbar_wait(sb + BAR_FULL + 8 * 4, 0);
            {
                uint4 v[4];
                for (;;) {
                    uint32_t bad = 0;
#pragma unroll
                    for (int k = 0; k < 4; k++) v[k] = ld_poll(reinterpret_cast<const uint4*>(g_mod1) + (warp & 1) * 128 + k * 32 + lane);
#pragma unroll
                    for (int k = 0; k < 4; k++) bad |= (v[k].x ^ ep) | (v[k].y ^ ep) | (v[k].z ^ ep) | (v[k].w ^ ep);
                    if (poll_done((bad & 0xffff) == 0, 100)) break;
                }
                const uint32_t one = (warp & 1) ? ONE2 : 0x80008000u;
#pragma unroll
                for (int k = 0; k < 4; k++)
                    *reinterpret_cast<uint2*>(smem + SM_TAB + (warp & 1) * 1024 + k * 256 + lane * 8) =
                        make_uint2(badd(__byte_perm(v[k].x, v[k].y, 0x7632), one), badd(__byte_perm(v[k].z, v[k].w, 0x7632), one));
            }
            __syncwarp();
            mbar_arrive_if(sb + BAR_FLAG + 8 * 8, lane == 0);
            if (warp == 10) {
#pragma unroll 1
                for (int i = 0; i < 9; i++) {
                    mbar_sleep(sb + BAR_DONE + 8 * i);
                    if (lane == 0) flag_add(i && ((i - 1) & 2) ? &g_sync.ctxcnt[((i & 1) ? 15 - j : j) * 32 + 2 * grp + (i > 4)] : &g_sync.cnt[(grp * 8 + i) * 8]);
                    if (i == 0) TS(43);
                }
            } else {
                TS(42);
#pragma unroll 1
                for (int i = 0; i < 8; i++) {
                    mbar_sleep(sb + BAR_DONE + 8 * (i == 7 ? 6 : i == 4 ? 3 : i));
                    if (lane < 2) flag_wait(&g_sync.cnt[((i == 0 ? (lane ? j : 15 - j) : i == 7 ? 0 : grp) * 8 + i) * 8], 8 * ep);
                    __syncwarp();
                    mbar_arrive_if(sb + BAR_FLAG + 8 * i, lane == 0 && i < 7);
                    TS(48 + i);
                }
                const uint32_t *mp = reinterpret_cast<const uint32_t*>(g_mod) + lane, *wp = reinterpret_cast<const uint32_t*>(P.wr) + lane;
                float ra = 0.f, rs = 0.f;
#pragma unroll 1
                for (int k = 0; k < 256; k += 32) {
                    const uint32_t ga = __ldcg(mp + 512 + k), sh = __ldcg(mp + 768 + k), c1 = badd(__ldcg(mp + 1024 + k), ONE2);
                    const uint32_t gb = __ldcg(mp + 1280 + k), ww = __ldg(wp + k);
                    const uint32_t a = bmul(c1, ww);
                    ra += bf_lo(a) + bf_hi(a);
                    rs = fmaf(bf_lo(sh), bf_lo(ww), fmaf(bf_hi(sh), bf_hi(ww), rs));
                    if (k >> 6 == cq) {
                        sts128(sb + SM_TAB + ((k & 32) + lane) * 16, make_uint4(ga << 16, ga & 0xffff0000u, a, 0));
                        sts128(sb + SM_TAB + 1024 + ((k & 32) + lane) * 16, make_uint4(c1, sh, gb, 0));
                    }
                }
#pragma unroll 1
                for (int o = 16; o > 0; o >>= 1) {
                    ra += __shfl_xor_sync(0xffffffffu, ra, o);
                    rs += __shfl_xor_sync(0xffffffffu, rs, o);
                }
                *reinterpret_cast<float2*>(smem + SM_EP + 8) = make_float2(ra, rs);
                __syncwarp();
                mbar_arrive_if(sb + BAR_FLAG + 8 * 7, lane == 0);
                const uint32_t* f = lane < 17 ? &g_sync.ctxcnt[ort * 32 + o_head(lane, kh)] : &g_sync.cnt[15 * 8];
                uint32_t ready = -(j & 1), list = 0, sh = 0, qa;
                asm("mapa.shared::cluster.u32 %0, %1, %2;" : "=r"(qa) : "r"(sb + SM_EP + 20), "r"(lane & 1));
                while (ready != ~0u) {
                    uint32_t v, now;
                    do {
                        asm volatile("ld.acquire.gpu.global.u32 %0, [%1];" : "=r"(v) : "l"(f) : "memory");
                        now = __ballot_sync(0xffffffffu, (int)(v - (lane < 17 ? ep : NSPARE * ep)) >= 0);
                    } while (!poll_done(now != ready, POLL_NS));
#pragma unroll 1
                    for (uint32_t fresh = now & ~ready & 0x7f00; fresh; fresh &= fresh - 1, sh += 4) list |= (__ffs(fresh) - 1) << sh;
                    list |= (((now & 0xff) + 1) >> 8 << 28) | ((now & (now >> 2) & 0x18000) << 14);
                    if (lane < 2) asm volatile("st.relaxed.cluster.shared::cluster.u32 [%0], %1;" ::"r"(qa), "r"(list) : "memory");
                    if ((ready & 0xff) != 0xff && (now & 0xff) == 0xff) mbar_sleep(sb + BAR_DONE + 8 * 7);
                    ready = now;
                }
                TS(45);
            }
        }
    } else {
        const bool elected = (tid & 127) == 0, rel = (tid & 95) == 0;
        uint32_t eb;
        asm("mapa.shared::cluster.u32 %0, %1, %2;" : "=r"(eb) : "r"(sb + BAR_EMPTY), "r"(warp & 1));
        const int g = lane >> 2, c4 = lane & 3;
        uint32_t toff = warp * 4096 + g * 64 + ((c4 ^ (g >> 1)) << 4);
        uint32_t fph = 0x3f, r = 0;
        if (wg == 1) bar_arrive(1, 256);
        const uint32_t kd = desc_k(sb), wd = desc_mn(sb), vd = ((sb & 0x3ffff) >> 4) | (32u << 16);
        const int nL = 16 - j, hn = nL - 1 + wg;
        float s[64], o[64], li[2] = {0.f, 0.f};
        uint32_t cimg = 0;
        const float sc = (j & 1) ? 1.f : SM_C;
#pragma unroll 1
        for (int q = 0; q < 3; q++) {
            const uint32_t as = (0x635u >> (4 * q)) & 15;
            mbar_wait(sb + BAR_FULL + 8 * q, 0);
            mbar_wait(sb + BAR_FULL + 8 * as, 0);
            bar_sync(1 + wg, 256);
            gemm_issue<false>(s, kd + wg * 512 + as * (SLOT / 16), wd + q * (SLOT / 16), q, false);
            bar_arrive(2 - wg, 256);
            wg_wait<0>();
            release_if(eb, as, rel);
        }
        {
            const int xrow = rb * 16 + warp * 2;
            const uint4* xp = reinterpret_cast<const uint4*>(P.x) + xrow * 64;
            const uint32_t img = (grp * 32 + j) * SLOT;
            uint32_t x[16], x0[2];
            float st[4] = {0.f, 0.f, 0.f, 0.f};
            mbar_wait(sb + BAR_FULL + 8 * 4, 0);
#pragma unroll
            for (int q = 3; q < 8; q++) {
                const uint32_t ws = (0x4210u >> (4 * (q & 3))) & 15, as = (0x635u >> (4 * (q % 3))) & 15;
                mbar_wait(sb + BAR_FULL + 8 * as, (q / 3) & 1);
                bar_sync(1 + wg, 256);
                if (q == 3) gemm_issue<false>(s, kd + wg * 512 + as * (SLOT / 16), wd + ws * (SLOT / 16), 1, false);
                else if (q == 4) gemm_issue<true>(o, kd + wg * 512 + as * (SLOT / 16), wd + ws * (SLOT / 16), 0, false);
                else gemm_issue<false>(o, kd + wg * 512 + as * (SLOT / 16), wd + ws * (SLOT / 16), 1, false);
                bar_arrive(2 - wg, 256);
                sched_fence(fph, P.zero);
                if (q > 3) reg_fence(s);
                if (q == 3) {
                    asm volatile("setmaxnreg.inc.sync.aligned.u32 232;");
#pragma unroll
                    for (int i = 0; i < 4; i++)
                        asm volatile("ld.global.nc.v4.u32 {%0, %1, %2, %3}, [%4];" : "=r"(x[4 * i]), "=r"(x[4 * i + 1]), "=r"(x[4 * i + 2]), "=r"(x[4 * i + 3])
                                     : "l"(xp + lane + 32 * i) : "memory");
#pragma unroll
                    for (int i = 0; i < 2; i++) asm volatile("ld.global.nc.u32 %0, [%1];" : "=r"(x0[i]) : "l"(xp + 64 * i) : "memory");
                }
                if (q == 4) {
                    img_store_global<0>(img, toff, s, sc, sc);
#pragma unroll
                    for (int k = 0; k < 16; k++) {
                        const float d0 = bf_lo(x[k]) - bf_lo(x0[k >> 3]), d1 = bf_hi(x[k]) - bf_lo(x0[k >> 3]);
                        st[k >> 3] += d0 + d1;
                        st[2 + (k >> 3)] = fmaf(d0, d0, fmaf(d1, d1, st[2 + (k >> 3)]));
                    }
#pragma unroll
                    for (int i = 0; i < 4 * NSH; i++) st[i & 3] += __shfl_xor_sync(0xffffffffu, st[i & 3], 1 << (i >> 2));
                    reg_fence(st);
                }
                if (q == 5) {
#pragma unroll
                    for (int i = 4 * NSH; i < 20; i++) st[i & 3] += __shfl_xor_sync(0xffffffffu, st[i & 3], 1 << (i >> 2));
                    img_store_global<1>(img, toff, s, sc, sc);
#pragma unroll
                    for (int i = 0; i < 2; i++) {
                        const float d = st[i] * (1.f / 512.f);
                        st[2 + i] = ln_rstd(fmaxf(fmaf(-d, d, st[2 + i] * (1.f / 512.f)), 0.f));
                        x0[i] = pack2(bf_lo(x0[i]) + d, bf_lo(x0[i]) + d);
                    }
                    reg_fence(st);
                    reg_fence(x0);
                }
                if (q > 5) {
                    if (q == 6) mbar_wait(sb + BAR_FLAG + 8 * 8, 0);
                    const uint4 a = lds128(sb + SM_TAB + 1024 + (q & 1) * 512 + lane * 16), c = lds128(sb + SM_TAB + (q & 1) * 512 + lane * 16);
                    uint8_t* hp = g_h + (grp * 8 + (q & 1) * 4 + (lane >> 3)) * 16384 + (xrow & 127) * 128;
#pragma unroll
                    for (int i = 0; i < 2; i++) {
                        const uint32_t* y = x + 8 * i + 4 * (q & 1);
                        *reinterpret_cast<uint4*>(hp + i * 128 + (((lane ^ xrow ^ i) & 7) << 4)) =
                            make_uint4(ln_apply(y[0], x0[i], st[2 + i], a.x, c.x), ln_apply(y[1], x0[i], st[2 + i], a.y, c.y),
                                       ln_apply(y[2], x0[i], st[2 + i], a.z, c.z), ln_apply(y[3], x0[i], st[2 + i], a.w, c.w));
                    }
                    if (q == 7) {
                        __syncwarp();
                        mbar_arrive_if(sb + BAR_DONE, lane == 0);
                    }
                    if (q == 6) img_store_global<2>(img, toff, s, sc, sc);
                    else img_store_global<3>(img, toff, s, sc, sc);
                }
                if (q < 7) {
                    sched_fence(fph, P.zero);
                    wg_wait<0>();
                    release_if(eb, as, rel);
                }
            }
        }
        uint32_t pend = 0x73;
        uint32_t p[32] = {};
#pragma unroll 1
        for (int hp = 0; hp < 2; hp++) {
            float m[2] = {0.f, 0.f}, l[2] = {0.f, 0.f}, t[4] = {0.f, 0.f, 0.f, 0.f};
            bool shifted = false, bad = false, plain = false;
            uint32_t qa = desc_k(sb + 5 * SLOT + (wg ^ 1) * 8192);
            const uint32_t limg = (512 + (15 - j) * 32 + 2 * grp + hp) * SLOT;
            {
                const int step = hp ? -8 * SLOT : 8 * SLOT;
                uint32_t img = (grp * 32 + (hp ? j ^ 30 : j) + 8) * SLOT;
                const uint32_t wtab = w_table(hp);
                uint32_t atab = hp ? 0x562u : 0x356u;
#pragma unroll 1
                for (int u = 2 - 2 * hp; u < 6; u += 2) {
                    proj_tile<false>(s, o, u, !u, sb, wg, eb, rel, fph, wtab, atab, pend, u ? img : cimg, toff, u ? sc : li[0], u ? sc : li[1], p);
                    __syncwarp();
                    mbar_arrive_if(sb + BAR_DONE + 4 * u + 32 * hp, lane == 0);
                    if (elected) TS(1 + 10 * hp + u + 20 * wg);
                    proj_tile<true>(o, s, u + 1, 0, sb, wg, eb, rel, fph, wtab, atab, pend, img + step, toff, sc, sc, p);
                    if (elected) TS(2 + 10 * hp + u + 20 * wg);
                    img += 2 * step;
                }
            }
            asm volatile("" : "+r"(toff));
            if (elected) TS(6 + 10 * hp + 20 * wg);
            fence_async_smem();
            slot_wait(sb + BAR_FULL, fph, r);
            step_retire(eb, rel, pend);
            reg_fence(o);
            int n = -1;
#pragma unroll 1
            for (;;) {
                while (bad || plain) {
                    float d0 = m[0], d1 = m[1];
                    if (bad) {
                        float a0, a1;
                        softmax_remax(s, m, n == 0 || n == nL, d0, d1, a0, a1);
                        shifted = true;
                        l[0] *= a0;
                        l[1] *= a1;
#pragma unroll
                        for (int i = 0; i < 64; i++) o[i] *= (i & 2) ? a1 : a0;
                    }
#pragma unroll
                    for (int i = 0; i < 64; i++) s[i] -= (i & 2) ? d1 : d0;
                    softmax_exp<0, 16>(s, p, t);
                    t[0] += t[1];
                    t[2] += t[3];
                    bad = !bad && softmax_unsafe(t[0], t[2], false);
                    plain = false;
                }
#pragma unroll 1
                do {
                    l[0] += t[0];
                    l[1] += t[2];
                    if (++n > 16) break;
                    const uint32_t ks = r;
                    uint32_t vs = ring_next(r);
                    r = ring_next(vs);
                    bar_sync(1 + wg, 256);
                    const float x = (float)((warp & 3) * 16 + g - 2 * c4);
                    if (n == hn) {
                        float sh[32];
                        qk_issue(sh, qa, kd + ks * (SLOT / 16));
                        slot_wait(sb + BAR_FULL, fph, vs);
                        pv_issue(o, p, vd + vs * (SLOT / 16), 1, false);
                        bar_arrive(2 - wg, 256);
                        wg_wait<1>();
                        reg_fence(sh);
                        tri_mask_copy(s, sh, x);
                        release_if(eb, ks, rel);
                        release_if(eb, 5 + wg, rel && (!wg || n == 16));
                        if (!wg) qa += SLOT / 16;
                        float e[4 * EARLY];
#pragma unroll
                        for (int i = 0; i < 4 * EARLY; i++) {
                            e[i] = ex2(s[i]);
                            t[i & 3] = i < 4 ? e[i] : t[i & 3] + e[i];
                        }
                        reg_fence(e);
                        slot_wait(sb + BAR_FULL, fph, r);
                        wg_wait<0>();
                        reg_fence(o);
                        reg_fence(e);
                        release_if(eb, vs, rel);
#pragma unroll
                        for (int i = 0; i < 2 * EARLY; i++) p[i] = pack2(e[2 * i], e[2 * i + 1]);
                        softmax_exp<EARLY, 8>(s, p, t);
                        if (wg) {
                            ctx_store(limg, toff, o, rcp(quad_sum(l[0])), rcp(quad_sum(l[1])));
                            __syncwarp();
                            mbar_arrive_if(sb + BAR_DONE + 24 + 32 * hp, lane == 0);
                            l[0] = l[1] = m[0] = m[1] = 0.f;
                            shifted = false;
                        }
                        t[0] += t[1];
                        t[2] += t[3];
                        plain = shifted;
                        if (plain) break;
                        bad = softmax_unsafe(t[0], t[2], wg);
                        continue;
                    }
                    if (n == nL) {
                        qk_issue(s, qa, kd + ks * (SLOT / 16));
                        slot_wait(sb + BAR_FULL, fph, vs);
                        pv_issue(o, p, vd + vs * (SLOT / 16), 1, true);
                        bar_arrive(2 - wg, 256);
                        const float i0 = rcp(quad_sum(l[0])), i1 = rcp(quad_sum(l[1]));
                        wg_wait<1>();
                        reg_fence(s);
                        release_if(eb, ks, rel);
                        release_if(eb, 6, rel && n == 16);
                        tri_mask(s, x);
                        float e[4 * EARLY2];
#pragma unroll
                        for (int i = 0; i < 4 * EARLY2; i++) {
                            e[i] = ex2(s[i]);
                            t[i & 3] = i < 4 ? e[i] : t[i & 3] + e[i];
                        }
                        reg_fence(e);
                        reg_fence(s);
                        reg_fence(t);
                        slot_wait(sb + BAR_FULL, fph, r);
                        sched_fence(fph, P.zero);
                        wg_wait<0>();
                        reg_fence(o);
                        reg_fence(e);
                        release_if(eb, vs, rel);
#pragma unroll
                        for (int i = 0; i < 2 * EARLY2; i++) p[i] = pack2(e[2 * i], e[2 * i + 1]);
                        softmax_exp<EARLY2, MSPLIT>(s, p, t);
                        ctx_store(limg, toff, o, i0, i1);
                        reg_fence(t);
                        reg_fence(s);
                        softmax_exp<MSPLIT, 16>(s, p, t);
                        __syncwarp();
                        mbar_arrive_if(sb + BAR_DONE + 24 + 32 * hp, lane == 0);
                        l[0] = l[1] = m[0] = m[1] = 0.f;
                        shifted = false;
                        t[0] += t[1];
                        t[2] += t[3];
                        bad = __any_sync(0xffffffffu, fmaxf(t[0], t[2]) > SM_HI || fminf(t[0], t[2]) < SM_LO);
                        continue;
                    }
                    qk_issue(s, qa, kd + ks * (SLOT / 16));
                    if (n == 0) {
                        r = vs;
                        vs = 4 - hp;
                        slot_wait(sb + BAR_FULL, fph, 6);
                        gemm_issue<false>(o, qa + SLOT / 16, wd + vs * (SLOT / 16), 1, false);
                    } else {
                        slot_wait(sb + BAR_FULL, fph, vs);
                        if (n == 1) {
                            wg_wait<1>();
                            reg_fence(o);
                            const uint32_t a = sb + 6 * SLOT + q_off(toff);
#pragma unroll
                            for (int i = 0; i < 8; i++) {
                                const int k = 16 * (i >> 1) + 2 * (i & 1);
                                sts128(a + (i >> 2) * 16384 + (i & 2) * 256 + (i & 1) * 1024,
                                       make_uint4(pack2(o[k], o[k + 1]), pack2(o[k + 4], o[k + 5]), pack2(o[k + 8], o[k + 9]), pack2(o[k + 12], o[k + 13])));
                            }
                        }
                        pv_issue(o, p, vd + vs * (SLOT / 16), n != 1 && n != nL + 1, n == hn + 1);
                    }
                    bar_arrive(2 - wg, 256);
                    wg_wait<1>();
                    reg_fence(s);
                    release_if(eb, ks, rel);
                    release_if(eb, 6, rel && n == 16);
                    if (n == nL - 1) {
                        tri_mask(s, x);
                        release_if(eb, 5, rel);
                        qa += SLOT / 16;
                    }
                    if (n == 2) fence_async_smem();
                    if (shifted) {
                        slot_wait(sb + BAR_FULL, fph, r);
                        wg_wait<0>();
                        reg_fence(o);
                        release_if(eb, vs, rel);
                        plain = true;
                        break;
                    }
                    float e[4 * EARLY];
#pragma unroll
                    for (int i = 0; i < 4 * EARLY; i++) {
                        e[i] = ex2(s[i]);
                        t[i & 3] = i < 4 ? e[i] : t[i & 3] + e[i];
                    }
                    reg_fence(e);
                    slot_wait(sb + BAR_FULL, fph, r);
                    wg_wait<0>();
                    reg_fence(o);
                    reg_fence(e);
                    release_if(eb, vs, rel);
#pragma unroll
                    for (int i = 0; i < 2 * EARLY; i++) p[i] = pack2(e[2 * i], e[2 * i + 1]);
                    softmax_exp<EARLY, 16>(s, p, t);
                    t[0] += t[1];
                    t[2] += t[3];
                    bad = __any_sync(0xffffffffu, fmaxf(t[0], t[2]) > SM_HI || (n == 0 && fminf(t[0], t[2]) < SM_LO));
                } while (!bad);
                if (!bad && !plain) break;
            }
            asm volatile("" : "+r"(toff));
            const uint32_t vs = r, ga = desc_k(sb + (hp ? 2 * (wg ^ kh ^ 1) : wg) * 8192);
            r = ring_next(r);
            slot_wait(sb + BAR_FULL, fph, 5);
            slot_wait(sb + BAR_FULL, fph, r);
            bar_sync(1 + wg, 256);
            gemm_issue<true>(s, ga + 5 * (SLOT / 16), wd + r * (SLOT / 16), 0, hp);
            pv_issue(o, p, vd + vs * (SLOT / 16), j, hn == 16);
            bar_arrive(2 - wg, 256);
            li[0] = rcp(quad_sum(l[0]));
            li[1] = rcp(quad_sum(l[1]));
            cimg = limg + (2 * j - 15) * 32 * SLOT + (wg ? -16384 : 16384);
            wg_wait<1>();
            release_if(eb, 5, rel);
            release_if(eb, r, rel && hp);
            wg_wait<0>();
            release_if(eb, vs, rel);
            reg_fence(o);
            img_store_global<0>(cimg, toff, o, li[0], li[1]);
            pend = 0x77;
            if (elected) TS(8 + 10 * hp + 20 * wg);
        }
        uint32_t otab = 0x2351604u;
        const uint32_t oa = desc_k(sb + (wg ^ kh ^ 1) * 16384);
        const int t7 = tid & 127, w4 = warp & 3, row = ort * 128 + kh * 64 + w4 * 16 + g;
#pragma unroll 1
        for (int i = 1; i < 15 - OFF - wg; i++) {
            const uint32_t as = o_next(otab), ws = o_next(otab);
            slot_wait(sb + BAR_FULL, fph, as);
            slot_wait(sb + BAR_FULL, fph, ws);
            bar_sync(1 + wg, 256);
            gemm_issue<false>(s, oa + as * (SLOT / 16), wd + ws * (SLOT / 16), 1, true);
            bar_arrive(2 - wg, 256);
            wg_wait<1>();
            reg_fence(o);
            if (i == 1) img_store_global<1>(cimg, toff, o, li[0], li[1]);
            if (i == 2) {
                img_store_global<2>(cimg, toff, o, li[0], li[1]);
                img_store_global<3>(cimg, toff, o, li[0], li[1]);
                __syncwarp();
                mbar_arrive_if(sb + BAR_DONE + 64, lane == 0);
            }
            wg_wait<0>();
            release_if(eb, as, rel);
            release_if(eb, ws, rel);
        }
        mbar_wait(sb + BAR_PF, 0);
        const uint32_t ep = lds32(sb + SM_EP);
        uint32_t eb2 = sb + BAR_END;
        if (wg == 0) {
            reg_fence(s);
            if (elected) TS(9);
            TT(1);
#pragma unroll
            for (int v = 0; v < 8; v++)
                st_pub(g_out + rb * OB + v * 128 + t7, make_uint4((pack2(s[8 * v], s[8 * v + 1]) & ~1u) | (ep & 1), pack2(s[8 * v + 2], s[8 * v + 3]),
                                                                      pack2(s[8 * v + 4], s[8 * v + 5]), pack2(s[8 * v + 6], s[8 * v + 7])), true);
            constexpr uint32_t s1 = SL_WF, s2 = SL_WD;
            bar_sync(4, 256);
            uint32_t wf[64];
            float wn[64];
            if (rb < NFFN) {
                slot_wait(sb + BAR_FULL, fph, s1);
                const uint32_t a = sb + s1 * SLOT + (w4 * 128 + (lane >> 4) * 8 + (lane & 7)) * 32 + (((lane >> 3) ^ (lane >> 2)) & 1) * 16;
#pragma unroll
                for (int i = 0; i < 16; i++)
                    asm volatile("ldmatrix.sync.aligned.m8n8.x4.trans.shared.b16 {%0, %1, %2, %3}, [%4];"
                                 : "=r"(wf[4 * i]), "=r"(wf[4 * i + 1]), "=r"(wf[4 * i + 2]), "=r"(wf[4 * i + 3])
                                 : "r"(a + (i >> 3) * 16384 + (i & 7) * 512) : "memory");
                slot_wait(sb + BAR_FULL, fph, s2);
#pragma unroll
                for (int i = 0; i < 16; i++) {
                    const uint2 w = *reinterpret_cast<const uint2*>(smem + s2 * SLOT + (kh ^ 1) * 16384 + i * 1024 + t7 * 8);
                    wn[4 * i] = bf_lo(w.x); wn[4 * i + 1] = bf_hi(w.x); wn[4 * i + 2] = bf_lo(w.y); wn[4 * i + 3] = bf_hi(w.y);
                }
                reg_fence(wn);
            }
            const uint32_t gbf = __ldcg(reinterpret_cast<const uint32_t*>(g_mod) + 1280 + rb * 2 + (lane >> 4));
            if (elected) TS(10);
            TT(2);
            const int pq = (2 * rb + (lane >> 4)) & 63, pv = (pq >> 2) / 3, cm = (pq >> 2) - 3 * pv;
            const uint4* cp = g_cand + w4 * 24 + c4;
            const uint4* fp = g_cand + (rb >> 5) * 24 + pv * 4 + (pq & 3);
            const uint4* yp = g_out + lane * OB + OB_Y + rb;
            uint4* yo = g_out + rb * OB + OB_Y + t7;
            uint32_t* op = reinterpret_cast<uint32_t*>(P.out) + rb * 2 + (lane >> 4);
            uint32_t ra = sb + SM_RED + (w4 * 32 + c4 * 8 + g) * 4;
            asm volatile("" : "+l"(cp), "+l"(fp), "+l"(yp), "+l"(yo), "+l"(op), "+r"(ra));
            sched_fence(eb2, P.zero);
            if (warp == 0) {
                asm volatile("st.shared.u32 [%0], %1;" ::"r"(sb + SM_EP + 24), "r"(best_key(g_key + cq * 128, lane, ep)) : "memory");
                mbar_arrive_if(sb + BAR_BEST, lane == 0);
            }
            bar_sync(3, 128);
            const uint32_t best = lds32(sb + SM_EP + 24), co = ((~best >> 9) & 127) * 192;
            TT(3);
            if (rb < NFFN) {
                uint4 cv[6];
                for (;;) {
                    uint32_t bad = 0;
#pragma unroll
                    for (int v = 0; v < 6; v++) cv[v] = ld_poll(cp + co + v * 4);
#pragma unroll
                    for (int v = 0; v < 6; v++) bad |= cv[v].w ^ ep;
                    if (__all_sync(0xffffffffu, bad == 0)) break;
                }
                TT(4);
                float d[4][4] = {};
#pragma unroll
                for (int k = 0; k < 8; k++) {
                    const uint32_t b0 = (&cv[(2 * k) / 3].x)[(2 * k) % 3], b1 = (&cv[(2 * k + 1) / 3].x)[(2 * k + 1) % 3];
                    mma16816(d[k & 1], wf + 4 * k, b0, b1);
                    mma16816(d[2 + (k & 1)], wf + 32 + 4 * k, b0, b1);
                }
                float u[4] = {d[0][0] + d[1][0], d[0][2] + d[1][2], d[2][0] + d[3][0], d[2][2] + d[3][2]};
                reg_fence(u);
                asm volatile("st.shared.f32 [%0], %1;" ::"r"(ra), "f"((c4 & 2) ? ((c4 & 1) ? u[3] : u[2]) : ((c4 & 1) ? u[1] : u[0])) : "memory");
                bar_sync(3, 128);
                const float* sred = reinterpret_cast<const float*>(smem + SM_RED);
                const float v = rbf((sred[lane] + sred[32 + lane]) + (sred[64 + lane] + sred[96 + lane]));
                const float act = rbf(rbf(v * sigmoid(v)) * __shfl_down_sync(0xffffffffu, v, 16));
                float y[4] = {0.f, 0.f, 0.f, 0.f};
#pragma unroll
                for (int k = 0; k < 16; k++) {
                    const float a = __shfl_sync(0xffffffffu, act, k);
#pragma unroll
                    for (int i = 0; i < 4; i++) y[i] = fmaf(a, wn[4 * k + i], y[i]);
                }
                st_pub(yo, make_uint4((__float_as_uint(y[0]) & ~15u) | (ep & 15), __float_as_uint(y[1]), __float_as_uint(y[2]), __float_as_uint(y[3])), true);
            }
            TT(5);
            if (warp == 0) {
                if (rb == 0 && lane == 0) g_sync.epoch[0] = ep;
                uint4 fh, fx;
                do { fh = ld_poll(fp + co); fx = ld_poll(fp + co + 96); } while (!poll_done(fh.w == ep && fx.w == ep, 50));
                const float sg = sigmoid(bf_hi((best & 0x80000000u) ? (best ^ 0x80000000u) : ~best));
                uint32_t fin[3] = {cm == 0 ? fh.x : cm == 1 ? fh.y : fh.z, cm == 0 ? fx.x : cm == 1 ? fx.y : fx.z, pack2(sg, sg)};
                op += ((~best >> 5) & 2047) * 256;
                asm volatile("" : "+l"(op));
                reg_fence(fin);
                if (rb >= NFFN) __nanosleep(YPRE);
                sched_fence(eb2, P.zero);
                uint4 yv[4];
                for (;;) {
#pragma unroll
                    for (int k = 0; k < 4; k++) yv[k] = ld_poll(yp + (k < 3 || lane < 16 ? k : 2) * 32 * OB);
                    if (poll_done((((yv[0].x ^ ep) | (yv[1].x ^ ep) | (yv[2].x ^ ep) | (yv[3].x ^ ep)) & 15) == 0, YSLEEP)) break;
                }
                TT(6);
                mbar_arrive_if(eb2, lane == 0);
                float y[4];
#pragma unroll
                for (int i = 0; i < 4; i++) {
                    const uint32_t mk = i ? ~0u : ~15u;
                    y[i] = (__uint_as_float((&yv[0].x)[i] & mk) + __uint_as_float((&yv[1].x)[i] & mk)) +
                           (__uint_as_float((&yv[2].x)[i] & mk) + (lane < 16 ? __uint_as_float((&yv[3].x)[i] & mk) : 0.f));
                }
                float z0 = ((lane & 16) ? y[2] : y[0]) + __shfl_xor_sync(0xffffffffu, (lane & 16) ? y[0] : y[2], 16);
                float z1 = ((lane & 16) ? y[3] : y[1]) + __shfl_xor_sync(0xffffffffu, (lane & 16) ? y[1] : y[3], 16);
#pragma unroll
                for (int o = 8; o > 0; o >>= 1) {
                    z0 += __shfl_xor_sync(0xffffffffu, z0, o);
                    z1 += __shfl_xor_sync(0xffffffffu, z1, o);
                }
                if ((lane & 15) == 0) *op = badd(fin[1], bmul(gbf, badd(fin[0], bmul(pack2(z0, z1), fin[2]))));
            }
            if (elected) TS(62);
            TT(7);
        } else {
            const float4* tf = reinterpret_cast<const float4*>(smem + SM_TAB) + c4;
            uint32_t x2[32];
            bar_sync(2, 256);
#pragma unroll 1
            for (int i = 14; i < 17; i++) {
                const uint32_t as = o_next(otab), ws = o_next(otab);
                slot_wait(sb + BAR_FULL, fph, as);
                slot_wait(sb + BAR_FULL, fph, ws);
                gemm_issue<false>(s, oa + as * (SLOT / 16), wd + ws * (SLOT / 16), 1, true);
                wg_wait<1>();
            }
            const uint4* pr = g_out + (rb ^ 16) * OB + t7;
            uint4 pa[8];
            if (elected) TS(29);
            TT(1);
#pragma unroll
            for (int k = 0; k < 8; k++) {
                const uint4 v = lds128(sb + SL_X * SLOT + (kh ^ 1) * 16384 + k * 2048 + t7 * 16);
                x2[4 * k] = v.x; x2[4 * k + 1] = v.y; x2[4 * k + 2] = v.z; x2[4 * k + 3] = v.w;
            }
            wg_wait<0>();
            reg_fence(s);
            bar_arrive(4, 256);
            if (elected) TS(39);
            TT(2);
#pragma unroll
            for (int v = 0; v < 8; v++) pa[v] = ld_poll(pr + v * 128);
            float4 tc[16];
#pragma unroll
            for (int k = 0; k < 16; k++) {
                tc[k] = tf[k * 4];
                if (!(g & 1)) tc[k].z = __uint_as_float(ONE2);
#pragma unroll
                for (int i = 4 * k; i < 4 * k + 4; i++) s[i] = fmaf((i & 1) ? tc[k].y : tc[k].x, s[i], (i & 1) ? bf_hi(x2[i >> 1]) : bf_lo(x2[i >> 1]));
            }
            reg_fence(s);
            sched_fence(eb2, P.zero);
            for (;;) {
                uint32_t bad = 0;
#pragma unroll
                for (int v = 0; v < 8; v++) asm("lop3.b32 %0, %0, %1, %2, 0xf6;" : "+r"(bad) : "r"(pa[v].x), "r"(ep));
                if (__all_sync(0xffffffffu, (bad & 1) == 0)) break;
                if (PSLEEP) __nanosleep(PSLEEP);
#pragma unroll
                for (int v = 0; v < 8; v++) pa[v] = ld_poll(pr + v * 128);
            }
            if (elected) TS(30);
            TT(3);
            float sd[4] = {}, q0[4] = {}, q1[4] = {};
#pragma unroll
            for (int k = 0; k < 8; k++) {
#pragma unroll
                for (int i = 4 * k; i < 4 * k + 4; i++) {
                    const uint32_t w = (i & 3) ? (&pa[k].x)[i & 3] : pa[k].x & ~1u;
                    x2[i] = pack2(fmaf(tc[i >> 1].x, bf_lo(w), s[2 * i]), fmaf(tc[i >> 1].y, bf_hi(w), s[2 * i + 1]));
                }
                mma16816(sd, x2 + 4 * k, __float_as_uint(tc[2 * k].z), __float_as_uint(tc[2 * k + 1].z));
                mma16816(q0, x2 + 4 * k, x2[4 * k], x2[4 * k + 2]);
                mma16816(q1, x2 + 4 * k, x2[4 * k + 1], x2[4 * k + 3]);
            }
            uint4* sp = g_out + rb * OB + OB_STAT + (w4 * 8 + g) * 2;
            st_pub(sp, make_uint4(__float_as_uint(sd[0]), __float_as_uint((g & 1) ? q0[1] : q0[0]), __float_as_uint(sd[1]), ep), c4 == g >> 1);
            st_pub(sp + 1, make_uint4(__float_as_uint(sd[2]), __float_as_uint((g & 1) ? q1[3] : q1[2]), __float_as_uint(sd[3]), ep), c4 == g >> 1);
            sched_fence(eb2, P.zero);
            if (elected) TS(56);
            TT(4);
            uint32_t cb[16], sh[16], gb[16];
#pragma unroll
            for (int i = 0; i < 16; i++) {
                const float4 c = tf[64 + i * 4];
                cb[i] = __float_as_uint(c.x); sh[i] = __float_as_uint(c.y); gb[i] = __float_as_uint(c.z);
            }
            const float ra = __uint_as_float(lds32(sb + SM_EP + 8)), rb0 = __uint_as_float(lds32(sb + SM_EP + 12));
            const uint4* rp = g_out + ((rb & ~33) + (c4 & 1) + (c4 & 2) * 16) * OB + OB_STAT + (w4 * 8 + g) * 2;
            uint32_t* kp = g_key + cq * 128 + (row >> 4);
            uint4* cp = g_cand + (row >> 4) * 192 + cq * 24 + c4;
            uint32_t kt = ((2047 - row) << 5) | (ep & 31);
            asm volatile("" : "+l"(kp), "+l"(cp), "+r"(kt));
            uint4 r0, r1;
            do {
                r0 = ld_poll(rp);
                r1 = ld_poll(rp + 1);
            } while (!poll_done(r0.w == ep && r1.w == ep, SSLEEP));
            if (elected) TS(57);
            TT(5);
            float st[6] = {__uint_as_float(r0.x), __uint_as_float(r1.x), __uint_as_float(r0.y), __uint_as_float(r1.y), __uint_as_float(r0.z), __uint_as_float(r1.z)};
#pragma unroll
            for (int i = 0; i < 12; i++) st[i % 6] += __shfl_xor_sync(0xffffffffu, st[i % 6], 1 + i / 6);
            const float m0 = st[0] * (1.f / 512.f), m1 = st[1] * (1.f / 512.f);
            const float rs0 = ln_rstd(fmaxf(fmaf(-m0, m0, st[2] * (1.f / 512.f)), 0.f));
            const float rs1 = ln_rstd(fmaxf(fmaf(-m1, m1, st[3] * (1.f / 512.f)), 0.f));
            const uint32_t mb0 = pack2(m0, m0), mb1 = pack2(m1, m1);
            const uint32_t lg = pack2(fmaf(rs0, fmaf(-bf_lo(mb0), ra, st[4]), rb0), fmaf(rs1, fmaf(-bf_lo(mb1), ra, st[5]), rb0));
            const uint32_t u0 = lg << 16, u1 = lg & 0xffff0000u;
            const uint32_t k0 = ((u0 ^ (((int)u0 >> 31) | 0x80000000u)) & 0xffff0000u) | kt;
            const uint32_t k1 = ((u1 ^ (((int)u1 >> 31) | 0x80000000u)) & 0xffff0000u) | (kt - 256);
            const uint32_t kb = __reduce_max_sync(0xffffffffu, max(k0, k1));
            st_pub(kp, kb, lane == 0);
            const bool cand = kb == k0 || kb == k1;
#pragma unroll 1
            for (int it = 0; it < 3; it++) {
                bool put = it == 1 || !cand;
                if (it == 2) {
                    mbar_wait(sb + BAR_BEST, 0);
                    put = cand && lds32(sb + SM_EP + 24) != kb;
                }
                const bool hi = (kb == k1) != (it == 1);
                uint32_t cx[18], ch[18];
#pragma unroll
                for (int i = 0; i < 16; i++) {
                    cx[i] = hi ? x2[2 * i + 1] : x2[2 * i];
                    ch[i] = ln_apply(cx[i], hi ? mb1 : mb0, hi ? rs1 : rs0, cb[i], sh[i]);
                }
                cx[16] = cx[17] = ch[16] = ch[17] = 0;
#pragma unroll
                for (int v = 0; v < 6; v++) st_pub(cp + v * 4, make_uint4(ch[3 * v], ch[3 * v + 1], ch[3 * v + 2], ep), cand && it == 0);
#pragma unroll
                for (int v = 0; v < 6; v++) st_pub(cp + 96 + v * 4, make_uint4(cx[3 * v], cx[3 * v + 1], cx[3 * v + 2], ep), cand && it == 0);
                if (it == 0) TT(6);
                uint2* op = reinterpret_cast<uint2*>(P.out) + (row + 8 * hi) * 128 + cq * 32 + (c4 & 1) * 2 + (c4 >> 1);
#pragma unroll
                for (int i = 0; i < 16; i += 2) {
                    const uint32_t v0 = badd(cx[i], bmul(gb[i], ch[i])), v1 = badd(cx[i + 1], bmul(gb[i + 1], ch[i + 1]));
                    const uint32_t rv = __shfl_xor_sync(0xffffffffu, (c4 & 1) ? v0 : v1, 1);
                    if (put) op[i * 2] = (c4 & 1) ? make_uint2(rv, v1) : make_uint2(v0, rv);
                }
            }
            if (elected) TS(59);
            TT(7);
        }
        mbar_arrive_if(eb2, lane == 0 && warp != 0);
    }
}

typedef CUresult (*EncodeFn)(CUtensorMap*, CUtensorMapDataType, cuuint32_t, void*, const cuuint64_t*, const cuuint64_t*,
                             const cuuint32_t*, const cuuint32_t*, CUtensorMapInterleave, CUtensorMapSwizzle,
                             CUtensorMapL2promotion, CUtensorMapFloatOOBfill);

void make_3d(EncodeFn fn, CUtensorMap* m, const void* p, uint64_t cols, uint64_t rows, uint32_t br = 128, uint32_t nb = 2) {
    cuuint64_t dims[3] = {64, rows, cols / 64}, strides[2] = {cols * 2, 128};
    cuuint32_t box[3] = {64, br, nb}, es[3] = {1, 1, 1};
    fn(m, CU_TENSOR_MAP_DATA_TYPE_BFLOAT16, 3, const_cast<void*>(p), dims, strides, box, es, CU_TENSOR_MAP_INTERLEAVE_NONE,
       CU_TENSOR_MAP_SWIZZLE_128B, CU_TENSOR_MAP_L2_PROMOTION_L2_256B, CU_TENSOR_MAP_FLOAT_OOB_FILL_NONE);
}

}

extern "C" void kernel_launch(void* const* d_in, const int* in_sizes, int n_in, void* d_out, int out_size) {
    static EncodeFn fn = nullptr;
    if (!fn) {
        void* f = nullptr;
        cudaDriverEntryPointQueryResult st;
        cudaGetDriverEntryPoint("cuTensorMapEncodeTiled", &f, cudaEnableDefault, &st);
        fn = (EncodeFn)f;
        cudaFuncSetAttribute(fused_kernel, cudaFuncAttributeMaxDynamicSharedMemorySize, SMEM_BYTES);
    }
    CUtensorMap ckv, wq, wuk, wuv, wo, wg, wu, wm, xm;
    make_3d(fn, &ckv, d_in[1], 512, 2048, 128, 1);
    make_3d(fn, &xm, d_in[0], 512, 2048, 64);
    make_3d(fn, &wq, d_in[2], 4096, 512);
    make_3d(fn, &wuk, d_in[3], 4096, 512);
    make_3d(fn, &wuv, d_in[4], 4096, 512);
    make_3d(fn, &wo, d_in[5], 512, 4096);
    make_3d(fn, &wg, d_in[8], 1792, 512, 256, 1);
    make_3d(fn, &wu, d_in[9], 1792, 512, 256, 1);
    make_3d(fn, &wm, d_in[12], 3072, 512, 64, 4);
    Params p;
    p.x = (const bf16*)d_in[0];
    p.ckv = (const bf16*)d_in[1];
    p.wo = (const bf16*)d_in[5];
    p.wr = (const bf16*)d_in[7];
    p.wdown = (const bf16*)d_in[10];
    p.c = (const bf16*)d_in[11];
    p.out = (bf16*)d_out;
    p.zero = 0;
    fused_kernel<<<NCTA + NSPARE, 384, SMEM_BYTES>>>(ckv, wq, wuk, wuv, wo, wg, wu, wm, xm, p);
}
```

```cpp
#include <cuda.h>
#include <cuda_bf16.h>
#include <cuda_runtime.h>
#include <stdint.h>
#include <stdio.h>

namespace {

typedef __nv_bfloat16 bf16;
typedef unsigned long long u64;

constexpr int NCTA = 128, NSPARE = 4;
constexpr int SLOT = 32768;
constexpr int SM_BAR = 7 * SLOT;
constexpr int BAR_FULL = SM_BAR;
constexpr int BAR_EMPTY = BAR_FULL + 8 * 7;
constexpr int BAR_DONE = BAR_EMPTY + 8 * 7;
constexpr int BAR_FLAG = BAR_DONE + 8 * 9;
constexpr int BAR_PF = BAR_FLAG + 8 * 9;
constexpr int BAR_END = BAR_PF + 8;
constexpr int BAR_BEST = BAR_END + 8;
constexpr int SM_EP = BAR_END + 40;
constexpr int SM_RED = SM_BAR + 384;
constexpr int SM_TAB = SM_BAR + 1024;
constexpr int SMEM_BYTES = SM_BAR + 3072;
constexpr int NFFN = 112;
#define HINT 479
constexpr u64 L2_NORMAL = 0x1000000000000000ull, L2_FIRST = 0x12F0000000000000ull;
#define PFA 8
#define PFB 6
#define POLL_NS 50
#define MSPLIT 13
#define NSH 1
#define XPF 1
#define KSLEEP 400
#define YSLEEP 50
#define YPRE 400
#define SSLEEP 50
#define PSLEEP 100
#define KVG 7
#define EARLY2 4
#define OFF 2
#define KN 16
#define KSLEEP2 60
#define EARLY 7
constexpr uint32_t SPIN_LIMIT = 1u << 22;
constexpr uint32_t ONE2 = 0x3f803f80u;

struct Sync {
    uint32_t cnt[16 * 8 * 8];
    uint32_t ctxcnt[16 * 32];
    uint32_t epoch[32];
};

__device__ __align__(1024) uint8_t g_img[2 * 512 * SLOT];
#define g_KV g_img
#define g_ctx (g_img + 512 * SLOT)
__device__ __align__(1024) uint8_t g_h[16 * 4 * SLOT];
constexpr int OB = 1216, OB_STAT = 1024, OB_Y = 1088;
__device__ __align__(1024) uint4 g_out[128 * OB];
__device__ __align__(1024) bf16 g_mod[3072];
__device__ __align__(1024) uint32_t g_mod1[1024];
__device__ __align__(1024) uint4 g_cand[128 * 192];
__device__ __align__(1024) uint32_t g_key[4 * 128];
__device__ __align__(1024) uint8_t g_wf[NFFN * SLOT];
__device__ __align__(1024) uint4 g_x2[128 * 1024];
__device__ __align__(1024) Sync g_sync;
#define TS(i)

#define TT(i)
#define PT()

struct Params {
    const bf16 *x, *ckv, *wo, *wr, *wdown, *c;
    bf16* out;
    int zero;
};

__device__ __forceinline__ void mbar_init(uint32_t bar, uint32_t cnt) {
    asm volatile("mbarrier.init.shared::cta.b64 [%0], %1;" ::"r"(bar), "r"(cnt) : "memory");
}
__device__ __forceinline__ void mbar_wait(uint32_t bar, uint32_t parity) {
    asm volatile("{\n.reg .pred p;\nL_%=:\nmbarrier.try_wait.parity.shared::cta.b64 p, [%0], %1;\n@!p bra L_%=;\n}" ::"r"(bar), "r"(parity) : "memory");
}
__device__ __forceinline__ void mbar_sleep(uint32_t bar) {
    if ((threadIdx.x & 31) == 0)
        asm volatile("{\n.reg .pred p;\nL_%=:\nmbarrier.try_wait.parity.shared::cta.b64 p, [%0], 0, 100000;\n@!p bra L_%=;\n}" ::"r"(bar) : "memory");
    __syncwarp();
}
__device__ __forceinline__ void mbar_watch(uint32_t bar, uint32_t parity) {
    asm volatile("{\n.reg .pred p;\n.reg .u32 n;\nmov.u32 n, 0;\n"
                 "L_%=:\nmbarrier.try_wait.parity.shared::cta.b64 p, [%0], %1;\n@p bra D_%=;\n"
                 "add.u32 n, n, 1;\nsetp.lt.u32 p, n, %2;\n@p bra L_%=;\ntrap;\nD_%=:\n}"
                 ::"r"(bar), "r"(parity), "n"(SPIN_LIMIT) : "memory");
}
__device__ __forceinline__ void step_watch(uint32_t a, uint32_t step) {
    asm volatile("{\n.reg .pred p;\n.reg .u32 n, v;\nmov.u32 n, 0;\n"
                 "L_%=:\nld.volatile.shared.u32 v, [%0];\nsetp.ge.u32 p, v, %1;\n@p bra D_%=;\nnanosleep.u32 400;\n"
                 "add.u32 n, n, 1;\nsetp.lt.u32 p, n, %2;\n@p bra L_%=;\ntrap;\nD_%=:\n}"
                 ::"r"(a), "r"(step), "n"(SPIN_LIMIT) : "memory");
}
__device__ __forceinline__ void mbar_arrive_if(uint32_t bar, bool on) {
    asm volatile("{\n.reg .pred p;\nsetp.ne.s32 p, %1, 0;\n@p mbarrier.arrive.shared::cta.b64 _, [%0];\n}" ::"r"(bar), "r"((int)on) : "memory");
}
__device__ __forceinline__ void tma3d_prefetch(const CUtensorMap* m, int row, int cb) {
    asm volatile("{\n.reg .pred p;\nelect.sync _|p, 0xffffffff;\n@p cp.async.bulk.prefetch.tensor.3d.L2.global [%0, {%1, %2, %3}];\n}"
                 ::"l"(m), "r"(0), "r"(row), "r"(cb) : "memory");
}
__device__ __forceinline__ void l2_prefetch(const void* p, uint32_t bytes) {
    asm volatile("{\n.reg .pred p;\nelect.sync _|p, 0xffffffff;\n@p cp.async.bulk.prefetch.L2.global [%0], %1;\n}" ::"l"(p), "r"(bytes) : "memory");
}
__device__ __forceinline__ void bulk_store(void* dst, uint32_t src, uint32_t bytes, bool first) {
    asm volatile("{\n.reg .pred p;\nelect.sync _|p, 0xffffffff;\n@p cp.async.bulk.global.shared::cta.bulk_group.L2::cache_hint [%0], [%1], %2, %3;\n}"
                 ::"l"(dst), "r"(src), "r"(bytes), "l"(first ? L2_FIRST : L2_NORMAL) : "memory");
}
__device__ __forceinline__ void flag_wait(const uint32_t* f, uint32_t target) {
    asm volatile("{\n.reg .pred p;\n.reg .u32 v;\n"
                 "L_%=:\nld.acquire.gpu.global.u32 v, [%0];\nsub.u32 v, v, %1;\nsetp.lt.s32 p, v, 0;\n@p nanosleep.u32 100;\n@p bra L_%=;\n}"
                 ::"l"(f), "r"(target) : "memory");
}
__device__ __forceinline__ uint4 ld_poll(const uint4* p) {
    uint4 v;
    asm volatile("{\n.reg .b128 t;\nld.relaxed.gpu.global.b128 t, [%4];\nmov.b128 {%0, %1, %2, %3}, t;\n}"
                 : "=r"(v.x), "=r"(v.y), "=r"(v.z), "=r"(v.w) : "l"(p) : "memory");
    return v;
}
__device__ __forceinline__ void st_pub(uint4* p, uint4 v, bool on) {
    asm volatile("{\n.reg .pred p;\n.reg .b128 t;\nsetp.ne.s32 p, %5, 0;\nmov.b128 t, {%1, %2, %3, %4};\n@p st.relaxed.gpu.global.b128 [%0], t;\n}"
                 ::"l"(p), "r"(v.x), "r"(v.y), "r"(v.z), "r"(v.w), "r"((int)on) : "memory");
}
__device__ __forceinline__ void st_pub(uint32_t* p, uint32_t v, bool on) {
    asm volatile("{\n.reg .pred p;\nsetp.ne.s32 p, %2, 0;\n@p st.relaxed.gpu.global.u32 [%0], %1;\n}" ::"l"(p), "r"(v), "r"((int)on) : "memory");
}
__device__ __forceinline__ bool poll_done(bool ok, uint32_t ns) {
    const int done = __all_sync(0xffffffffu, ok);
    asm volatile("{\n.reg .pred p;\nsetp.eq.s32 p, %0, 0;\n@p nanosleep.u32 %1;\n}" ::"r"(done), "r"(ns) : "memory");
    return done;
}
__device__ __forceinline__ void flag_add(uint32_t* p) {
    asm volatile("red.release.gpu.global.add.u32 [%0], 1;" ::"l"(p) : "memory");
}
__device__ __forceinline__ uint32_t lds32(uint32_t a) {
    uint32_t v;
    asm volatile("ld.shared.u32 %0, [%1];" : "=r"(v) : "r"(a) : "memory");
    return v;
}
__device__ __forceinline__ uint4 lds128(uint32_t a) {
    uint4 v;
    asm volatile("ld.shared.v4.u32 {%0, %1, %2, %3}, [%4];" : "=r"(v.x), "=r"(v.y), "=r"(v.z), "=r"(v.w) : "r"(a) : "memory");
    return v;
}
__device__ __forceinline__ void sched_fence(uint32_t& v, uint32_t z) {
    uint32_t ck;
    asm volatile("mov.u32 %0, %%clock;" : "=r"(ck)::"memory");
    v ^= ck & z;
}
__device__ __forceinline__ void fence_async_global() { asm volatile("fence.proxy.async.global;" ::: "memory"); }
__device__ __forceinline__ void fence_async_smem() { asm volatile("fence.proxy.async.shared::cta;" ::: "memory"); }
__device__ __forceinline__ void bar_sync(int id, int n) { asm volatile("bar.sync %0, %1;" ::"r"(id), "r"(n) : "memory"); }
__device__ __forceinline__ void bar_arrive(int id, int n) { asm volatile("bar.arrive %0, %1;" ::"r"(id), "r"(n) : "memory"); }
__device__ __forceinline__ void wg_fence() { asm volatile("wgmma.fence.sync.aligned;" ::: "memory"); }
__device__ __forceinline__ void wg_commit() { asm volatile("wgmma.commit_group.sync.aligned;" ::: "memory"); }
template <int N> __device__ __forceinline__ void wg_wait() { asm volatile("wgmma.wait_group.sync.aligned %0;" ::"n"(N) : "memory"); }
template <int N> __device__ __forceinline__ void reg_fence(float (&d)[N]) {
#pragma unroll
    for (int i = 0; i < N; i++) asm volatile("" : "+f"(d[i])::"memory");
}
template <int N> __device__ __forceinline__ void reg_fence(uint32_t (&d)[N]) {
#pragma unroll
    for (int i = 0; i < N; i++) asm volatile("" : "+r"(d[i])::"memory");
}
__device__ __forceinline__ uint32_t desc_k(uint32_t a) { return ((a & 0x3ffff) >> 4) | (1u << 16); }
__device__ __forceinline__ uint32_t desc_mn(uint32_t a) { return ((a & 0x3ffff) >> 4) | (1024u << 16); }

__device__ __forceinline__ uint64_t desc64(uint32_t lo, uint32_t hi) {
    uint64_t d;
    asm("mov.b64 %0, {%1, %2};" : "=l"(d) : "r"(lo), "r"(hi));
    return d;
}
__device__ __forceinline__ void desc_add(uint64_t& d, uint32_t x) { asm("add.u64 %0, %0, %1;" : "+l"(d) : "l"((uint64_t)x)); }

template <int TB>
__device__ __forceinline__ void wgmma_ss128(float (&d)[64], uint64_t da, uint64_t db, int acc) {
    asm volatile("{\n.reg .pred p;\nsetp.ne.b32 p, %66, 0;\n"
        "wgmma.mma_async.sync.aligned.m64n128k16.f32.bf16.bf16 {%0, %1, %2, %3, %4, %5, %6, %7, %8, %9, %10, %11, %12, %13, %14, %15, %16, %17, %18, %19, %20, %21, %22, %23, %24, %25, %26, %27, %28, %29, %30, %31, %32, %33, %34, %35, %36, %37, %38, %39, %40, %41, %42, %43, %44, %45, %46, %47, %48, %49, %50, %51, %52, %53, %54, %55, %56, %57, %58, %59, %60, %61, %62, %63}, %64, %65, p, 1, 1, 0, %67;\n}"
        : "+f"(d[0]), "+f"(d[1]), "+f"(d[2]), "+f"(d[3]), "+f"(d[4]), "+f"(d[5]), "+f"(d[6]), "+f"(d[7]), "+f"(d[8]), "+f"(d[9]), "+f"(d[10]), "+f"(d[11]), "+f"(d[12]), "+f"(d[13]), "+f"(d[14]), "+f"(d[15]), "+f"(d[16]), "+f"(d[17]), "+f"(d[18]), "+f"(d[19]), "+f"(d[20]), "+f"(d[21]), "+f"(d[22]), "+f"(d[23]), "+f"(d[24]), "+f"(d[25]), "+f"(d[26]), "+f"(d[27]), "+f"(d[28]), "+f"(d[29]), "+f"(d[30]), "+f"(d[31]), "+f"(d[32]), "+f"(d[33]), "+f"(d[34]), "+f"(d[35]), "+f"(d[36]), "+f"(d[37]), "+f"(d[38]), "+f"(d[39]), "+f"(d[40]), "+f"(d[41]), "+f"(d[42]), "+f"(d[43]), "+f"(d[44]), "+f"(d[45]), "+f"(d[46]), "+f"(d[47]), "+f"(d[48]), "+f"(d[49]), "+f"(d[50]), "+f"(d[51]), "+f"(d[52]), "+f"(d[53]), "+f"(d[54]), "+f"(d[55]), "+f"(d[56]), "+f"(d[57]), "+f"(d[58]), "+f"(d[59]), "+f"(d[60]), "+f"(d[61]), "+f"(d[62]), "+f"(d[63])
        : "l"(da), "l"(db), "r"(acc), "n"(TB));
}
template <int TB>
__device__ __forceinline__ void wgmma_ss128_init(float (&d)[64], uint64_t da, uint64_t db) {
    asm volatile("{\n.reg .pred p;\nsetp.ne.b32 p, 0, 0;\n"
        "wgmma.mma_async.sync.aligned.m64n128k16.f32.bf16.bf16 {%0, %1, %2, %3, %4, %5, %6, %7, %8, %9, %10, %11, %12, %13, %14, %15, %16, %17, %18, %19, %20, %21, %22, %23, %24, %25, %26, %27, %28, %29, %30, %31, %32, %33, %34, %35, %36, %37, %38, %39, %40, %41, %42, %43, %44, %45, %46, %47, %48, %49, %50, %51, %52, %53, %54, %55, %56, %57, %58, %59, %60, %61, %62, %63}, %64, %65, p, 1, 1, 0, %66;\n}"
        : "=f"(d[0]), "=f"(d[1]), "=f"(d[2]), "=f"(d[3]), "=f"(d[4]), "=f"(d[5]), "=f"(d[6]), "=f"(d[7]), "=f"(d[8]), "=f"(d[9]), "=f"(d[10]), "=f"(d[11]), "=f"(d[12]), "=f"(d[13]), "=f"(d[14]), "=f"(d[15]), "=f"(d[16]), "=f"(d[17]), "=f"(d[18]), "=f"(d[19]), "=f"(d[20]), "=f"(d[21]), "=f"(d[22]), "=f"(d[23]), "=f"(d[24]), "=f"(d[25]), "=f"(d[26]), "=f"(d[27]), "=f"(d[28]), "=f"(d[29]), "=f"(d[30]), "=f"(d[31]), "=f"(d[32]), "=f"(d[33]), "=f"(d[34]), "=f"(d[35]), "=f"(d[36]), "=f"(d[37]), "=f"(d[38]), "=f"(d[39]), "=f"(d[40]), "=f"(d[41]), "=f"(d[42]), "=f"(d[43]), "=f"(d[44]), "=f"(d[45]), "=f"(d[46]), "=f"(d[47]), "=f"(d[48]), "=f"(d[49]), "=f"(d[50]), "=f"(d[51]), "=f"(d[52]), "=f"(d[53]), "=f"(d[54]), "=f"(d[55]), "=f"(d[56]), "=f"(d[57]), "=f"(d[58]), "=f"(d[59]), "=f"(d[60]), "=f"(d[61]), "=f"(d[62]), "=f"(d[63])
        : "l"(da), "l"(db), "n"(TB));
}
template <int TB>
__device__ __forceinline__ void wgmma_ss64(float (&d)[32], uint64_t da, uint64_t db, int acc) {
    asm volatile("{\n.reg .pred p;\nsetp.ne.b32 p, %34, 0;\n"
        "wgmma.mma_async.sync.aligned.m64n64k16.f32.bf16.bf16 {%0, %1, %2, %3, %4, %5, %6, %7, %8, %9, %10, %11, %12, %13, %14, %15, %16, %17, %18, %19, %20, %21, %22, %23, %24, %25, %26, %27, %28, %29, %30, %31}, %32, %33, p, 1, 1, 0, %35;\n}"
        : "+f"(d[0]), "+f"(d[1]), "+f"(d[2]), "+f"(d[3]), "+f"(d[4]), "+f"(d[5]), "+f"(d[6]), "+f"(d[7]), "+f"(d[8]), "+f"(d[9]), "+f"(d[10]), "+f"(d[11]), "+f"(d[12]), "+f"(d[13]), "+f"(d[14]), "+f"(d[15]), "+f"(d[16]), "+f"(d[17]), "+f"(d[18]), "+f"(d[19]), "+f"(d[20]), "+f"(d[21]), "+f"(d[22]), "+f"(d[23]), "+f"(d[24]), "+f"(d[25]), "+f"(d[26]), "+f"(d[27]), "+f"(d[28]), "+f"(d[29]), "+f"(d[30]), "+f"(d[31])
        : "l"(da), "l"(db), "r"(acc), "n"(TB));
}
template <int TB>
__device__ __forceinline__ void wgmma_ss64_init(float (&d)[32], uint64_t da, uint64_t db) {
    asm volatile("{\n.reg .pred p;\nsetp.ne.b32 p, 0, 0;\n"
        "wgmma.mma_async.sync.aligned.m64n64k16.f32.bf16.bf16 {%0, %1, %2, %3, %4, %5, %6, %7, %8, %9, %10, %11, %12, %13, %14, %15, %16, %17, %18, %19, %20, %21, %22, %23, %24, %25, %26, %27, %28, %29, %30, %31}, %32, %33, p, 1, 1, 0, %34;\n}"
        : "=f"(d[0]), "=f"(d[1]), "=f"(d[2]), "=f"(d[3]), "=f"(d[4]), "=f"(d[5]), "=f"(d[6]), "=f"(d[7]), "=f"(d[8]), "=f"(d[9]), "=f"(d[10]), "=f"(d[11]), "=f"(d[12]), "=f"(d[13]), "=f"(d[14]), "=f"(d[15]), "=f"(d[16]), "=f"(d[17]), "=f"(d[18]), "=f"(d[19]), "=f"(d[20]), "=f"(d[21]), "=f"(d[22]), "=f"(d[23]), "=f"(d[24]), "=f"(d[25]), "=f"(d[26]), "=f"(d[27]), "=f"(d[28]), "=f"(d[29]), "=f"(d[30]), "=f"(d[31])
        : "l"(da), "l"(db), "n"(TB));
}
__device__ __forceinline__ void wgmma_rs128(float (&d)[64], uint32_t a0, uint32_t a1, uint32_t a2, uint32_t a3, uint64_t db, int acc) {
    asm volatile("{\n.reg .pred p;\nsetp.ne.b32 p, %69, 0;\n"
        "wgmma.mma_async.sync.aligned.m64n128k16.f32.bf16.bf16 {%0, %1, %2, %3, %4, %5, %6, %7, %8, %9, %10, %11, %12, %13, %14, %15, %16, %17, %18, %19, %20, %21, %22, %23, %24, %25, %26, %27, %28, %29, %30, %31, %32, %33, %34, %35, %36, %37, %38, %39, %40, %41, %42, %43, %44, %45, %46, %47, %48, %49, %50, %51, %52, %53, %54, %55, %56, %57, %58, %59, %60, %61, %62, %63}, {%64, %65, %66, %67}, %68, p, 1, 1, 1;\n}"
        : "+f"(d[0]), "+f"(d[1]), "+f"(d[2]), "+f"(d[3]), "+f"(d[4]), "+f"(d[5]), "+f"(d[6]), "+f"(d[7]), "+f"(d[8]), "+f"(d[9]), "+f"(d[10]), "+f"(d[11]), "+f"(d[12]), "+f"(d[13]), "+f"(d[14]), "+f"(d[15]), "+f"(d[16]), "+f"(d[17]), "+f"(d[18]), "+f"(d[19]), "+f"(d[20]), "+f"(d[21]), "+f"(d[22]), "+f"(d[23]), "+f"(d[24]), "+f"(d[25]), "+f"(d[26]), "+f"(d[27]), "+f"(d[28]), "+f"(d[29]), "+f"(d[30]), "+f"(d[31]), "+f"(d[32]), "+f"(d[33]), "+f"(d[34]), "+f"(d[35]), "+f"(d[36]), "+f"(d[37]), "+f"(d[38]), "+f"(d[39]), "+f"(d[40]), "+f"(d[41]), "+f"(d[42]), "+f"(d[43]), "+f"(d[44]), "+f"(d[45]), "+f"(d[46]), "+f"(d[47]), "+f"(d[48]), "+f"(d[49]), "+f"(d[50]), "+f"(d[51]), "+f"(d[52]), "+f"(d[53]), "+f"(d[54]), "+f"(d[55]), "+f"(d[56]), "+f"(d[57]), "+f"(d[58]), "+f"(d[59]), "+f"(d[60]), "+f"(d[61]), "+f"(d[62]), "+f"(d[63])
        : "r"(a0), "r"(a1), "r"(a2), "r"(a3), "l"(db), "r"(acc));
}

__device__ __forceinline__ uint32_t pack2(float lo, float hi) {
    uint32_t r;
    asm("cvt.rn.bf16x2.f32 %0, %1, %2;" : "=r"(r) : "f"(hi), "f"(lo));
    return r;
}
__device__ __forceinline__ float bf_lo(uint32_t v) { return __uint_as_float(v << 16); }
__device__ __forceinline__ float bf_hi(uint32_t v) { return __uint_as_float(v & 0xffff0000u); }
__device__ __forceinline__ float rbf(float v) { return bf_lo(pack2(v, v)); }
__device__ __forceinline__ uint32_t badd(uint32_t a, uint32_t b) {
    uint32_t r;
    asm("add.rn.bf16x2 %0, %1, %2;" : "=r"(r) : "r"(a), "r"(b));
    return r;
}
__device__ __forceinline__ uint32_t bsub(uint32_t a, uint32_t b) {
    uint32_t r;
    asm("sub.rn.bf16x2 %0, %1, %2;" : "=r"(r) : "r"(a), "r"(b));
    return r;
}
__device__ __forceinline__ uint32_t bmul(uint32_t a, uint32_t b) {
    uint32_t r;
    asm("mul.rn.bf16x2 %0, %1, %2;" : "=r"(r) : "r"(a), "r"(b));
    return r;
}
__device__ __forceinline__ uint32_t ln_apply(uint32_t x, uint32_t mb, float rs, uint32_t scale, uint32_t shift) {
    const uint32_t d = bsub(x, mb);
    return badd(bmul(pack2(bf_lo(d) * rs, bf_hi(d) * rs), scale), shift);
}
__device__ __forceinline__ float ex2(float v) {
    float r;
    asm("ex2.approx.ftz.f32 %0, %1;" : "=f"(r) : "f"(v));
    return r;
}
__device__ __forceinline__ float rcp(float v) {
    float r;
    asm("rcp.approx.ftz.f32 %0, %1;" : "=f"(r) : "f"(v));
    return r;
}
__device__ __forceinline__ float sqrt_fast(float v) {
    float r;
    asm("sqrt.approx.ftz.f32 %0, %1;" : "=f"(r) : "f"(v));
    return r;
}
__device__ __forceinline__ float ln_rstd(float var) { return rcp(rbf(sqrt_fast(rbf(rbf(var) + 1e-5f)))); }
__device__ __forceinline__ float sigmoid(float v) { return rcp(1.f + ex2(-1.4426950408889634f * v)); }
__device__ __forceinline__ float quad_sum(float v) {
    v += __shfl_xor_sync(0xffffffffu, v, 1);
    return v + __shfl_xor_sync(0xffffffffu, v, 2);
}

constexpr uint32_t HI_128 = 0x40000040u, HI_IMG = 0x80000080u, HI_Q = 0x80000040u;
template <int M, int RH>
__device__ __forceinline__ uint4 img_pack(const float (&d)[64], float s) {
    uint4 v;
    v.x = pack2(d[16 * M + 2 * RH] * s, d[16 * M + 2 * RH + 1] * s);
    v.y = pack2(d[16 * M + 4 + 2 * RH] * s, d[16 * M + 5 + 2 * RH] * s);
    v.z = pack2(d[16 * M + 8 + 2 * RH] * s, d[16 * M + 9 + 2 * RH] * s);
    v.w = pack2(d[16 * M + 12 + 2 * RH] * s, d[16 * M + 13 + 2 * RH] * s);
    return v;
}
template <int M>
__device__ __forceinline__ void img_store_global(uint32_t img, uint32_t toff, const float (&d)[64], float s0, float s1) {
    uint4* p = reinterpret_cast<uint4*>(g_img + (img + toff)) + M * 32;
    p[0] = img_pack<M, 0>(d, s0);
    p[128] = img_pack<M, 1>(d, s1);
}
__device__ __forceinline__ void sts128(uint32_t a, uint4 v) {
    asm volatile("st.shared.v4.b32 [%0], {%1, %2, %3, %4};" ::"r"(a), "r"(v.x), "r"(v.y), "r"(v.z), "r"(v.w) : "memory");
}
constexpr float SM_C = 0.08838834764831845f * 1.4426950408889634f;
__device__ __forceinline__ float pack2f(float lo, float hi) {
    float r;
    asm("{\n.reg .b32 t;\ncvt.rn.bf16x2.f32 t, %1, %2;\nmov.b32 %0, t;\n}" : "=f"(r) : "f"(hi), "f"(lo));
    return r;
}
template <int M, bool SCALE, bool PARK>
__device__ __forceinline__ void pack_group(float (&d)[64], float (&v)[8], float s0, float s1) {
#pragma unroll
    for (int i = 0; i < 8; i++) {
        const int k = 16 * M + 4 * (i & 3) + 2 * (i >> 2);
        v[i] = SCALE ? pack2f(d[k] * (i < 4 ? s0 : s1), d[k + 1] * (i < 4 ? s0 : s1)) : pack2f(d[k], d[k + 1]);
        if (PARK && M > 0) d[16 * (M > 0 ? M - 1 : 0) + i] = v[i];
    }
}
__device__ __forceinline__ uint32_t q_off(uint32_t toff) {
    asm volatile("" : "+r"(toff));
    return (((toff >> 1) & ~2047u) ^ 8192) + (toff & 511);
}
template <int M>
__device__ __forceinline__ void ctx_store_part(float4* p, float (&d)[64], float i0, float i1) {
    float v[8];
    pack_group<M, true, true>(d, v, i0, i1);
    p[M * 32] = make_float4(v[0], v[1], v[2], v[3]);
    p[M * 32 + 128] = make_float4(v[4], v[5], v[6], v[7]);
}
__device__ __forceinline__ void ctx_store(uint32_t img, uint32_t toff, float (&o)[64], float i0, float i1) {
    asm volatile("" : "+r"(toff));
    float4* p = reinterpret_cast<float4*>(g_img + (img + toff));
    ctx_store_part<0>(p, o, i0, i1); ctx_store_part<1>(p, o, i0, i1); ctx_store_part<2>(p, o, i0, i1); ctx_store_part<3>(p, o, i0, i1);
}

__device__ __forceinline__ void slot_wait(uint32_t bars, uint32_t& ph, uint32_t slot) {
    mbar_wait(bars + 8 * slot, (ph >> slot) & 1);
    ph ^= 1u << slot;
}
__device__ __forceinline__ void release_if(uint32_t eb, uint32_t slot, bool on) {
    asm volatile("{\n.reg .pred p;\nsetp.ne.s32 p, %1, 0;\n@p mbarrier.arrive.shared::cluster.b64 _, [%0];\n}" ::"r"(eb + 8 * slot), "r"((int)on) : "memory");
}
__device__ __forceinline__ void slot_expect(uint32_t sb, uint32_t slot) {
    asm volatile("{\n.reg .pred p;\nelect.sync _|p, 0xffffffff;\n@p mbarrier.arrive.expect_tx.shared::cta.b64 _, [%0], 32768;\n}"
                 ::"r"(sb + BAR_FULL + 8 * slot) : "memory");
}
__device__ __forceinline__ void slot_acquire(uint32_t sb, uint32_t& ph, uint32_t slot) {
    slot_wait(sb + BAR_EMPTY, ph, slot);
    slot_expect(sb, slot);
}
__device__ __forceinline__ void load_bulk(uint32_t sb, uint32_t slot, uint32_t off, const void* src, uint32_t bytes, bool both, bool first) {
    if (both)
        asm volatile("{\n.reg .pred p;\nelect.sync _|p, 0xffffffff;\n"
                     "@p cp.async.bulk.shared::cluster.global.mbarrier::complete_tx::bytes.multicast::cluster.L2::cache_hint [%0], [%1], %5, [%2], %4, %3;\n}"
                     ::"r"(sb + slot * SLOT + off), "l"(src), "r"(sb + BAR_FULL + 8 * slot), "l"(first ? L2_FIRST : L2_NORMAL), "h"((uint16_t)3),
                     "r"(bytes) : "memory");
    else
        asm volatile("{\n.reg .pred p;\nelect.sync _|p, 0xffffffff;\n"
                     "@p cp.async.bulk.shared::cluster.global.mbarrier::complete_tx::bytes.L2::cache_hint [%0], [%1], %4, [%2], %3;\n}"
                     ::"r"(sb + slot * SLOT + off), "l"(src), "r"(sb + BAR_FULL + 8 * slot), "l"(first ? L2_FIRST : L2_NORMAL), "r"(bytes) : "memory");
}
__device__ __forceinline__ void load_tile(uint32_t sb, uint32_t slot, uint32_t off, const CUtensorMap* m, int row, int cb, bool both, bool first) {
    if (both)
        asm volatile("{\n.reg .pred p;\nelect.sync _|p, 0xffffffff;\n"
                     "@p cp.async.bulk.tensor.3d.shared::cluster.global.mbarrier::complete_tx::bytes.multicast::cluster.L2::cache_hint [%0], [%1, {%3, %4, %5}], [%2], %7, %6;\n}"
                     ::"r"(sb + slot * SLOT + off), "l"(m), "r"(sb + BAR_FULL + 8 * slot), "r"(0), "r"(row), "r"(cb),
                     "l"(first ? L2_FIRST : L2_NORMAL), "h"((uint16_t)3) : "memory");
    else
        asm volatile("{\n.reg .pred p;\nelect.sync _|p, 0xffffffff;\n"
                     "@p cp.async.bulk.tensor.3d.shared::cluster.global.mbarrier::complete_tx::bytes.L2::cache_hint [%0], [%1, {%3, %4, %5}], [%2], %6;\n}"
                     ::"r"(sb + slot * SLOT + off), "l"(m), "r"(sb + BAR_FULL + 8 * slot), "r"(0), "r"(row), "r"(cb),
                     "l"(first ? L2_FIRST : L2_NORMAL) : "memory");
}
__device__ __forceinline__ uint32_t ring_next(uint32_t r) { return r == 4 ? 0 : r + 1; }
__device__ __forceinline__ uint32_t w_table(int hp) { return hp ? 0x3104u : 0x4210u; }
__device__ __forceinline__ uint32_t a_table(int hp) { return hp ? 0x625u : 0x635u; }
__device__ __forceinline__ uint32_t a_next(uint32_t& t) {
    const uint32_t s = t & 15;
    t = (t >> 4) | (s << 8);
    return s;
}
constexpr uint32_t O_TABLE = 0x1604235u;
constexpr uint32_t SL_X = OFF == 0 ? 4 : OFF == 1 ? 3 : 1, SL_WD = OFF == 0 ? 6 : OFF == 1 ? 4 : 3, SL_WF = OFF == 0 ? 5 : OFF == 1 ? 6 : 4;
__device__ __forceinline__ uint32_t o_next(uint32_t& t) {
    const uint32_t s = t & 15;
    t = (t >> 4) | (s << 24);
    return s;
}
__device__ __forceinline__ int o_head(int i, int kh) { return i < 16 ? 4 * (i & 7) + 2 * (kh ^ 1) + (i >> 3) : 29 + 2 * kh; }

template <bool INIT>
__device__ __forceinline__ void gemm_issue(float (&d)[64], uint32_t a, uint32_t b, int acc, bool img) {
    uint64_t da = desc64(a, img ? HI_IMG : HI_128), db = desc64(b, HI_128);
    wg_fence();
#pragma unroll
    for (int k = 0; k < 8; k++) {
        if (INIT && k == 0) wgmma_ss128_init<1>(d, da, db);
        else wgmma_ss128<1>(d, da, db, k ? 1 : acc);
        desc_add(da, !(k & 1) ? 2 : img ? 30 : k == 3 ? 1018 : 2);
        desc_add(db, 128);
    }
    wg_commit();
}

__device__ __forceinline__ void step_retire(uint32_t eb, bool rel, uint32_t pend) {
    wg_wait<0>();
    release_if(eb, pend & 7, rel && (pend & 7) != 7);
    release_if(eb, pend >> 4, rel && pend < 0x70);
}
template <bool ODD>
__device__ __forceinline__ void proj_tile(float (&acc)[64], float (&prev)[64], int t, int q0, uint32_t sb, int wg, uint32_t eb, bool rel, uint32_t& fph,
                                          uint32_t wtab, uint32_t& atab, uint32_t& pend, uint32_t prev_img, uint32_t toff, float s0, float s1,
                                          uint32_t (&v)[32]) {
    const uint32_t a0 = desc_k(sb + (wg ^ (ODD && t == 5)) * 8192), b0 = desc_mn(sb);
    int q = q0;
#pragma unroll 1
    do {
        const uint32_t ws = (wtab >> (4 * q)) & 15, as = a_next(atab);
        if (!ODD && t != 2) slot_wait(sb + BAR_FULL, fph, ws);
        slot_wait(sb + BAR_FULL, fph, as);
        step_retire(eb, rel, pend);
        if (ODD && q == 2 && t == 5) {
            const uint32_t a = sb + 5 * SLOT + q_off(toff);
#pragma unroll
            for (int i = 0; i < 8; i++) sts128(a + (i >> 2) * 16384 + (i & 2) * 256 + (i & 1) * 1024, make_uint4(v[4 * i], v[4 * i + 1], v[4 * i + 2], v[4 * i + 3]));
        }
        bar_sync(1 + wg, 256);
        gemm_issue<false>(acc, a0 + as * (SLOT / 16), b0 + ws * (SLOT / 16), q, false);
        bar_arrive(2 - wg, 256);
        pend = (ODD && q == 1 && t == 5 ? 7 : as) | (ODD && t != 1 ? ws : 7) << 4;
        wg_wait<1>();
        reg_fence(prev);
        if (ODD && t == 5) {
            if (q == 0) {
#pragma unroll
                for (int i = 0; i < 32; i++) {
                    const int k = 16 * (i >> 3) + 4 * (i & 3) + ((i >> 1) & 2);
                    v[i] = pack2(prev[k], prev[k + 1]);
                }
            }
        } else {
            if (q == 0) img_store_global<0>(prev_img, toff, prev, s0, s1);
            if (q == 1) img_store_global<1>(prev_img, toff, prev, s0, s1);
            if (q == 2) img_store_global<2>(prev_img, toff, prev, s0, s1);
            if (q == 3) img_store_global<3>(prev_img, toff, prev, s0, s1);
        }
    } while (++q < (ODD && t == 5 ? 3 : 4));
}

__device__ __forceinline__ void qk_issue(float (&s)[64], uint32_t q, uint32_t k) {
    wg_fence();
    uint64_t da = desc64(q, HI_Q), db = desc64(k, HI_IMG);
    wgmma_ss128_init<0>(s, da, db);
#pragma unroll
    for (int i = 1; i < 8; i++) {
        desc_add(da, (i & 1) ? 2 : i == 4 ? 990 : 30);
        desc_add(db, (i & 1) ? 2 : 30);
        wgmma_ss128<0>(s, da, db, 1);
    }
    wg_commit();
}
__device__ __forceinline__ void qk_issue(float (&s)[32], uint32_t q, uint32_t k) {
    wg_fence();
    uint64_t da = desc64(q, HI_Q), db = desc64(k, HI_IMG);
    wgmma_ss64_init<0>(s, da, db);
#pragma unroll
    for (int i = 1; i < 8; i++) {
        desc_add(da, (i & 1) ? 2 : i == 4 ? 990 : 30);
        desc_add(db, (i & 1) ? 2 : 30);
        wgmma_ss64<0>(s, da, db, 1);
    }
    wg_commit();
}
__device__ __forceinline__ void pv_issue(float (&o)[64], const uint32_t (&p)[32], uint32_t v, int acc, bool half) {
    uint64_t db = desc64(v, HI_IMG);
    if (half) {
        asm volatile("// half" ::: "memory");
        wg_fence();
#pragma unroll
        for (int i = 0; i < 4; i++) {
            wgmma_rs128(o, p[4 * i], p[4 * i + 1], p[4 * i + 2], p[4 * i + 3], db, i ? 1 : acc);
            desc_add(db, 256);
        }
        wg_commit();
        asm volatile("// half" ::: "memory");
    } else {
        wg_fence();
#pragma unroll
        for (int i = 0; i < 8; i++) {
            wgmma_rs128(o, p[4 * i], p[4 * i + 1], p[4 * i + 2], p[4 * i + 3], db, i ? 1 : acc);
            desc_add(db, 256);
        }
        wg_commit();
    }
}
__device__ __forceinline__ void tri_mask(float (&s)[64], float x) {
#pragma unroll
    for (int k = 0; k < 16; k++) {
        float b;
        asm("sub.sat.f32 %0, %1, %2;" : "=f"(b) : "f"((float)(8 * (k >> 1) + (k & 1))), "f"(x));
        const int i = 32 + 4 * (k >> 1) + (k & 1);
        asm("fma.rn.f32 %0, %1, 0fFF61B1E6, %0;" : "+f"(s[i]) : "f"(b));
        if (k < 14) asm("fma.rn.f32 %0, %1, 0fFF61B1E6, %0;" : "+f"(s[i + 6]) : "f"(b));
    }
}
__device__ __forceinline__ void tri_mask_copy(float (&s)[64], const float (&h)[32], float x) {
#pragma unroll
    for (int i = 0; i < 32; i++) {
            asm("{\n.reg .pred p;\nsetp.lt.f32 p, %2, %3;\nselp.f32 %0, 0fFF800000, %1, p;\n}"
                : "=f"(s[i]) : "f"(h[i]), "f"(x), "f"((float)(8 * (i >> 2) - 4 * (i & 2) + (i & 1))));
        s[32 + i] = __uint_as_float(0xff800000u);
    }
}
constexpr float SM_HI = 1152921504606846976.f, SM_LO = 1.f / 1152921504606846976.f;
__device__ __forceinline__ bool softmax_unsafe(float t0, float t1, bool first) {
    bool bad = __any_sync(0xffffffffu, fmaxf(t0, t1) > SM_HI);
    if (first) {
        uint32_t a = __ballot_sync(0xffffffffu, t0 >= SM_LO), b = __ballot_sync(0xffffffffu, t1 >= SM_LO);
        a |= a >> 1;
        b |= b >> 1;
        bad |= ((a | (a >> 2)) & (b | (b >> 2)) & 0x11111111u) != 0x11111111u;
    }
    return bad;
}
__device__ __forceinline__ void softmax_remax(const float (&s)[64], float (&m)[2], bool first, float& m0, float& m1, float& a0, float& a1) {
    m0 = fmaxf(s[0], s[1]), m1 = fmaxf(s[2], s[3]);
#pragma unroll
    for (int k = 1; k < 16; k++) {
        m0 = fmaxf(m0, fmaxf(s[4 * k], s[4 * k + 1]));
        m1 = fmaxf(m1, fmaxf(s[4 * k + 2], s[4 * k + 3]));
    }
    m0 = fmaxf(m0, __shfl_xor_sync(0xffffffffu, m0, 1));
    m1 = fmaxf(m1, __shfl_xor_sync(0xffffffffu, m1, 1));
    m0 = fmaxf(m0, __shfl_xor_sync(0xffffffffu, m0, 2));
    m1 = fmaxf(m1, __shfl_xor_sync(0xffffffffu, m1, 2));
    if (!first) {
        m0 = fmaxf(m0, 0.f);
        m1 = fmaxf(m1, 0.f);
    }
    a0 = first ? 1.f : ex2(-m0);
    a1 = first ? 1.f : ex2(-m1);
    m[0] += m0;
    m[1] += m1;
}
template <int J0, int J1>
__device__ __forceinline__ void softmax_exp(const float (&s)[64], uint32_t (&p)[32], float (&t)[4]) {
#pragma unroll
    for (int k = J0; k < J1; k++) {
        const float e0 = ex2(s[4 * k]), e1 = ex2(s[4 * k + 1]), e2 = ex2(s[4 * k + 2]), e3 = ex2(s[4 * k + 3]);
        if (k == 0) { t[0] = e0; t[1] = e1; t[2] = e2; t[3] = e3; }
        else { t[0] += e0; t[1] += e1; t[2] += e2; t[3] += e3; }
        p[2 * k] = pack2(e0, e1);
        p[2 * k + 1] = pack2(e2, e3);
    }
}
__device__ __forceinline__ void mma16816(float (&d)[4], const uint32_t* a, uint32_t b0, uint32_t b1) {
    asm("mma.sync.aligned.m16n8k16.row.col.f32.bf16.bf16.f32 {%0, %1, %2, %3}, {%4, %5, %6, %7}, {%8, %9}, {%0, %1, %2, %3};"
        : "+f"(d[0]), "+f"(d[1]), "+f"(d[2]), "+f"(d[3]) : "r"(a[0]), "r"(a[1]), "r"(a[2]), "r"(a[3]), "r"(b0), "r"(b1));
}
__device__ __forceinline__ uint32_t best_key(const uint32_t* keys, int lane, uint32_t ep) {
#pragma unroll 1
    for (;;) {
        const uint4 k = ld_poll(reinterpret_cast<const uint4*>(keys) + lane);
        const uint32_t best = __reduce_max_sync(0xffffffffu, max(max(k.x, k.y), max(k.z, k.w)));
        const uint32_t ok = __ballot_sync(0xffffffffu, (((k.x ^ ep) | (k.y ^ ep) | (k.z ^ ep) | (k.w ^ ep)) & 31) == 0);
        if (ok == ~0u) return best;
        __nanosleep(__popc(ok) < KN ? KSLEEP : KSLEEP2);
    }
}

__global__ void __cluster_dims__(2, 1, 1) __launch_bounds__(384, 1)
fused_kernel(const __grid_constant__ CUtensorMap tm_ckv, const __grid_constant__ CUtensorMap tm_wq,
             const __grid_constant__ CUtensorMap tm_wuk, const __grid_constant__ CUtensorMap tm_wuv,
             const __grid_constant__ CUtensorMap tm_wo, const __grid_constant__ CUtensorMap tm_wg,
             const __grid_constant__ CUtensorMap tm_wu,
             const __grid_constant__ CUtensorMap tm_wm, const __grid_constant__ CUtensorMap tm_x, const Params P) {
    extern __shared__ __align__(1024) uint8_t smem[];
    if (threadIdx.x == 352) {
        asm volatile("prefetch.tensormap [%0];" ::"l"(&tm_ckv) : "memory");
        asm volatile("prefetch.tensormap [%0];" ::"l"(blockIdx.x >= NCTA ? &tm_wm : (blockIdx.x & 1) ? &tm_wuv : &tm_wuk) : "memory");
    }
    const uint32_t sb = (uint32_t)__cvta_generic_to_shared(smem);
    const int tid = threadIdx.x, lane = tid & 31, warp = __shfl_sync(0xffffffffu, tid >> 5, 0), wg = warp >> 2;
    const uint32_t sm = blockIdx.x < 8 ? blockIdx.x + 124 : blockIdx.x - 8, smq = ((sm - 64) * 147) >> 11;
    const int rb = sm < 64 ? (sm & 14) * 8 + (sm >> 4) * 2 + (sm & 1)
                 : sm < 120 ? ((sm - 64 - smq * 14) & 14) * 8 + 24 + smq * 2 + (sm & 1) : sm < 124 ? sm + 8 : sm - 116;
    const int grp = rb >> 3, j = rb & 7, kh = (grp >> 1) & 1;
    const int cq = (j & 1) + ((grp >> 1) & 2), ort = (grp & 8) + (grp & 1) * 4 + (j >> 1);
    if (warp == 0) TS(0);

    const CUtensorMap* tw = (j & 1) ? &tm_wuv : &tm_wuk;
    if (lane == 0) {
        if (warp == 8) {
#pragma unroll
            for (int i = 0; i < 7; i++) mbar_init(sb + BAR_FULL + 8 * i, 1);
            fence_async_smem();
        } else if (warp < 11) {
            const int w = warp - (warp > 8);
            const u64 cnt = (w < 5 ? (rb < NCTA ? 0x888888884444444ull : 0x888888888888888ull) : 0x111812111111118ull) >> (12 * (w % 5));
#pragma unroll
            for (int i = 0; i < 3; i++) mbar_init(sb + BAR_EMPTY + 24 * w + 8 * i, ((uint32_t)cnt >> (4 * i)) & 15);
        }
        asm volatile("fence.mbarrier_init.release.cluster;" ::: "memory");
    }
    __syncwarp();
    asm volatile("barrier.cluster.arrive.relaxed.aligned;" ::: "memory");
    if (warp == 8) {
        if (rb < NCTA) {
#pragma unroll 1
            for (int u = 0; u < 4; u++) {
                const uint32_t ws = u + (u == 3), as = (0x635u >> (4 * u)) & 15;
                slot_expect(sb, ws);
                load_tile(sb, ws, 0, tw, u * 128, 4 * grp, false, HINT & 1);
                if (u == 3) break;
                slot_expect(sb, as);
                load_tile(sb, as, 0, &tm_ckv, (j >> 1) * 128, u * 2, false, false);
                load_tile(sb, as, 16384, &tm_ckv, (j >> 1) * 128, u * 2 + 1, false, false);
            }
        } else {
#pragma unroll 1
            for (int i = 0; i < 6; i++) {
                slot_expect(sb, i);
                load_tile(sb, i, 0, &tm_wm, i * 64, (rb - NCTA) * 4, false, HINT & 64);
                if (i > 3) tma3d_prefetch(&tm_wm, i * 64 + 128, (rb - NCTA) * 4);
            }
        }
    }
    asm volatile("barrier.cluster.wait.aligned;" ::: "memory");

    if (rb >= NCTA) {
        const int sp = rb - NCTA;
        const uint32_t ep = __ldcg(&g_sync.epoch[0]) + 1;
        uint32_t ph = 0, sl = 0;
        if (warp == 8) {
#pragma unroll 1
            for (int i = 6; i < 54 + 2 * OFF; i++) {
                slot_acquire(sb, ph, sl);
                const int k = i - 24;
                load_tile(sb, sl, 0, i < 24 ? &tm_wm : i >= 54 ? &tm_wo : (k & 2) ? &tm_wu : &tm_wg, i < 24 ? (i & 7) * 64 : i >= 54 ? (i - 38 - 2 * OFF) * 256 : (k & 1) * 256,
                          i < 24 ? (i >> 3) * 16 + sp * 4 : i >= 54 ? sp * 2 : sp * 7 + (k >> 2), false, true);
                if (++sl == 6) sl = 0;
                if (i == 51) { i = 53; sl = 0; }
            }
            bar_sync(4, 64);
            slot_wait(sb + BAR_EMPTY, ph, 4);
            slot_wait(sb + BAR_EMPTY, ph, 5);
            ph = 0x3f, sl = 0;
#pragma unroll 1
            for (int h = 0; h < 32; h++) {
                step_watch(sb + SM_EP + 16, h + 1);
                fence_async_global();
                const uint8_t* src = g_ctx + (size_t)(((h >> 1) ^ 8) * 32 + 30 - 4 * OFF) * SLOT + (h & 1) * 16384;
#pragma unroll 1
                for (int k = 0; k <= 2 * OFF; k++, src += 2 * SLOT) {
                    slot_wait(sb + BAR_DONE, ph, sl);
                    const uint32_t f = sb + BAR_FLAG + 8 * sl, d = sb + 4 * SLOT + sl * 16384;
                    asm volatile("{\n.reg .pred p;\nelect.sync _|p, 0xffffffff;\n@p mbarrier.arrive.expect_tx.shared::cta.b64 _, [%0], 16384;\n}" ::"r"(f) : "memory");
                    if (k == 0)
                        asm volatile("{\n.reg .pred p;\nelect.sync _|p, 0xffffffff;\n"
                                     "@p cp.async.bulk.tensor.3d.shared::cluster.global.mbarrier::complete_tx::bytes [%0], [%1, {%3, %4, %5}], [%2];\n}"
                                     ::"r"(d), "l"(&tm_x), "r"(f), "r"(0), "r"((h ^ 16) * 64), "r"(sp * 2) : "memory");
                    else
                        asm volatile("{\n.reg .pred p;\nelect.sync _|p, 0xffffffff;\n"
                                     "@p cp.async.bulk.shared::cluster.global.mbarrier::complete_tx::bytes [%0], [%1], 16384, [%2];\n}"
                                     ::"r"(d), "l"(src), "r"(f) : "memory");
                    if (++sl == 6) sl = 0;
                }
            }
        } else if (warp == 9) {
#pragma unroll 1
            for (int t = 0; t <= 16; t++) {
                asm volatile("st.release.cta.shared.u32 [%0], %1;" ::"r"(sb + SM_EP + 16), "r"(2 * t) : "memory");
                if (t == 0) bar_sync(4, 64);
                if (lane < 4 && t < 16) flag_wait(&g_sync.ctxcnt[(t ^ 8) * 32 + 24 + 2 * lane], ep);
                __syncwarp();
            }
        } else if (warp < 8) {
            const uint32_t c2 = __ldg(reinterpret_cast<const uint32_t*>(P.c) + tid);
            uint32_t* sc = reinterpret_cast<uint32_t*>(smem + SM_TAB);
            sc[tid] = pack2(bf_lo(c2) * sigmoid(bf_lo(c2)), bf_hi(c2) * sigmoid(bf_hi(c2)));
            bar_sync(1, 256);
            const uint32_t a = sb + (warp >> 1) * 8192 + ((lane >> 4) * 8 + (lane & 7)) * 128, ch = (warp & 1) * 4 + ((lane >> 3) & 1);
#pragma unroll 1
            for (int ps = 0; ps < 3; ps++) {
                float d[2][4] = {};
#pragma unroll 1
                for (int bt = 0; bt < 8; bt++) {
                    slot_wait(sb + BAR_FULL, ph, sl);
#pragma unroll
                    for (int i = 0; i < 8; i++) {
                        uint32_t w[4];
                        asm volatile("ldmatrix.sync.aligned.m8n8.x4.trans.shared.b16 {%0, %1, %2, %3}, [%4];" : "=r"(w[0]), "=r"(w[1]), "=r"(w[2]), "=r"(w[3])
                                     : "r"(a + sl * SLOT + (i >> 1) * 2048 + (((ch + 2 * (i & 1)) ^ (lane & 7)) << 4)) : "memory");
                        mma16816(d[i & 1], w, sc[bt * 32 + (i >> 1) * 8 + (lane & 3)], sc[bt * 32 + (i >> 1) * 8 + 4 + (lane & 3)]);
                    }
                    __syncwarp();
                    mbar_arrive_if(sb + BAR_EMPTY + 8 * sl, lane == 0);
                    if (++sl == 6) sl = 0;
                }
                const float v = (lane & 2) ? ((lane & 1) ? d[1][2] : d[1][0]) : ((lane & 1) ? d[0][2] : d[0][0]);
                const int col = sp * 256 + warp * 32 + (lane & 3) * 8 + (lane >> 2);
                if (ps == 0) st_pub(g_mod1 + col, (pack2(0.f, v) & 0xffff0000u) | (ep & 0xffffu), true);
                else g_mod[ps * 1024 + col] = __float2bfloat16_rn(v);
                if (warp == 0) TS(1 + ps);
            }
#pragma unroll 1
            for (int k = 0; k < 28; k++) {
                slot_wait(sb + BAR_FULL, ph, sl);
                uint4* dst = reinterpret_cast<uint4*>(g_wf) + (sp * 28 + (k & ~3)) * 2048 + (k & 3) * 512 + tid;
#pragma unroll 4
                for (int i = 0; i < 8; i++) {
                    const int row = (i & 1) * 128 + (tid >> 1);
                    __stcs(dst + (i >> 1) * 2048 + (i & 1) * 256, lds128(sb + sl * SLOT + row * 128 + ((((i & 6) + ((tid ^ (row >> 2)) & 1)) ^ (row & 7)) << 4)));
                }
                __syncwarp();
                mbar_arrive_if(sb + BAR_EMPTY + 8 * sl, lane == 0);
                if (++sl == 6) sl = 0;
            }
            bar_sync(1, 256);
            if (tid < 2) {
                flag_add(&g_sync.cnt[7 * 8]);
                flag_wait(&g_sync.cnt[7 * 8], 8 * ep);
            }
            if (warp == 0) TS(4);
            bar_sync(1, 256);
            uint32_t ga[16], x2[32];
#pragma unroll
            for (int i = 0; i < 16; i++) ga[i] = __ldcg(reinterpret_cast<const uint32_t*>(g_mod) + 512 + sp * 64 + (lane & 3) + 4 * i);
#pragma unroll 1
            for (int i = 0; i < 2 * OFF; i++) slot_wait(sb + BAR_FULL, ph, i);
            float d[64];
            uint32_t u = (2 * OFF + 1) * wg, up = 0;
            if (wg == 1) bar_arrive(2, 256);
#pragma unroll 1
            for (int h = wg; h < 32; h += 2) {
                mbar_wait(sb + BAR_FLAG + 8 * u, up);
                const uint32_t xa = sb + 4 * SLOT + u * 16384 + ((warp & 3) * 16 + (lane & 15)) * 128;
#pragma unroll
                for (int k = 0; k < 8; k++)
                    asm volatile("ldmatrix.sync.aligned.m8n8.x4.shared.b16 {%0, %1, %2, %3}, [%4];"
                                 : "=r"(x2[4 * k]), "=r"(x2[4 * k + 1]), "=r"(x2[4 * k + 2]), "=r"(x2[4 * k + 3])
                                 : "r"(xa + (k >> 2) * 8192 + (((2 * (k & 3) + (lane >> 4)) ^ (lane & 7)) << 4)) : "memory");
                mbar_arrive_if(sb + BAR_DONE + 8 * u, lane < 2);
                bar_sync(2 + wg, 256);
#pragma unroll 1
                for (int k = 0; k < 2 * OFF; k++) {
                    const uint32_t pu = u;
                    if (++u == 6) { u = 0; up ^= 1; }
                    mbar_wait(sb + BAR_FLAG + 8 * u, up);
                    gemm_issue<false>(d, desc_k(sb + 4 * SLOT) + u * 1024, desc_mn(sb) + k * (SLOT / 16), k, true);
                    wg_wait<1>();
                    mbar_arrive_if(sb + BAR_DONE + 8 * pu, lane < 2 && k);
                }
                if (h < 31) bar_arrive(3 - wg, 256);
                wg_wait<0>();
                reg_fence(d);
                mbar_arrive_if(sb + BAR_DONE + 8 * u, lane < 2);
                u += 2 * OFF + 2;
                if (u >= 6) { u -= 6; up ^= 1; }
                uint4* op = g_x2 + ((h ^ 16) * 4 + sp) * 1024 + (tid & 127);
#pragma unroll
                for (int v = 0; v < 8; v++) {
                    uint32_t y[4];
#pragma unroll
                    for (int i = 0; i < 4; i++) {
                        const int k = 4 * v + i;
                        y[i] = pack2(fmaf(bf_lo(ga[k >> 1]), d[2 * k], bf_lo(x2[k])), fmaf(bf_hi(ga[k >> 1]), d[2 * k + 1], bf_hi(x2[k])));
                    }
                    op[v * 128] = make_uint4(y[0], y[1], y[2], y[3]);
                }
            }
            bar_sync(1, 256);
            if (tid == 0) flag_add(&g_sync.cnt[15 * 8]);
            if (warp == 0) TS(5);
        }
        return;
    }

    if (wg == 2) {
        asm volatile("setmaxnreg.dec.sync.aligned.u32 40;");
        if (warp == 8) {
            const uint32_t rank = j & 1, half = rank * 16384;
            uint32_t eph = 0, r = 0;
            *reinterpret_cast<volatile uint32_t*>(smem + SM_EP + 20) = 0;
#pragma unroll 1
            for (int hp = 0; hp < 2; hp++) {
                uint32_t wtab = w_table(hp), atab = a_table(hp);
                const int hc = 4 * grp + 2 * hp;
#pragma unroll 1
                for (int u = 3 - 3 * hp; u < 16; u++) {
                    if (hp && u < 4) {
                        const uint32_t ws = (wtab >> (4 * u)) & 15;
                        slot_acquire(sb, eph, ws);
                        load_tile(sb, ws, 0, tw, u * 128, hc, false, HINT & 1);
                        PT();
                    }
                    if (hp == 1 && (u & 7) == 4) mbar_wait(sb + BAR_FLAG + 24 + (u & 8), 0);
                    const uint32_t as = a_next(atab);
                    slot_acquire(sb, eph, as);
                    load_tile(sb, as, half, &tm_ckv, ((u & 12) + (j >> 1)) * 128, (u & 3) * 2 + rank, true, (HINT & 8) && hp);
                    PT();
                    if (hp == 1 && (u | 2) == 3 && lane == 0)
                        asm volatile("red.relaxed.gpu.global.add.u32 [%0], 1;" ::"l"(&g_sync.cnt[(grp * 8 + 3 + (u >> 1)) * 8]) : "memory");
                }
                const uint8_t* src = g_h + (15 - j) * 4 * SLOT;
#pragma unroll 1
                for (int u = 0; u < 8; u++) {
                    if (u == 0 || u == KVG) {
                        mbar_wait(sb + BAR_FLAG + (u ? 8 + 32 * hp : 0), 0);
                        fence_async_global();
                    }
                    if (u < 4) {
                        const uint32_t ws = (wtab >> (4 * u)) & 15;
                        slot_acquire(sb, eph, ws);
                        load_tile(sb, ws, 0, &tm_wq, u * 128, hc, false, HINT & 1);
                        PT();
                    }
                    const uint32_t as = a_next(atab);
                    slot_acquire(sb, eph, as);
                    load_bulk(sb, as, 0, src, SLOT, false, (HINT & 8) && hp);
                    PT();
                    src += u == 3 ? (8 * j - 63) * SLOT : SLOT;
                }
                const int step = hp ? -2 * SLOT : 2 * SLOT;
                src = g_KV + (size_t)(grp * 32 + 30 * hp) * SLOT + half - step;
#pragma unroll 1
                for (int n = 0; n <= 17; n++) {
                    if (n == 8) {
                        mbar_wait(sb + BAR_FLAG + 16 + 32 * hp, 0);
                        fence_async_global();
                    }
                    const uint8_t* v = src + SLOT;
                    src += n < 16 - j ? step : n == 16 - j ? (2 * j - 15) * step : -step;
                    if (n < 17) {
                        slot_acquire(sb, eph, r);
                        if (n != 15 - (j & 6)) load_bulk(sb, r, half, src, SLOT / 2, true, HINT & 4);
                        else load_bulk(sb, r, 0, src - half, SLOT, false, HINT & 4);
                        PT();
                        r = ring_next(r);
                    }
                    if (n) {
                        slot_acquire(sb, eph, r);
                        if (n != 16 - (j & 6)) load_bulk(sb, r, half, v, SLOT / 2, true, HINT & 4);
                        else load_bulk(sb, r, 0, v - half, SLOT, false, HINT & 4);
                        PT();
                        r = ring_next(r);
                    }
                    asm volatile("st.volatile.shared.u32 [%0], %1;" ::"r"(sb + SM_EP + 16), "r"(18 * hp + n + 1) : "memory");
                }
            }
            uint32_t otab = O_TABLE, ready = 0;
#pragma unroll 1
            for (int i = 0; i < 17; i += i == 7 - OFF ? 1 + OFF : 1) {
                const bool dyn = i >= 8 && i < 15;
                const uint32_t want = dyn ? 15u << (4 * (i - 8)) : 1u << max(i + 14, 28);
                if (!(ready & want)) {
                    do {
                        asm volatile("ld.acquire.cta.shared.u32 %0, [%1];" : "=r"(ready) : "r"(sb + SM_EP + 20) : "memory");
                        ready = __shfl_sync(0xffffffffu, ready, 0);
                    } while (!(ready & want));
                    fence_async_global();
                }
                const int head = o_head(dyn ? (ready >> (4 * (i - 8))) & 15 : i, kh);
                const uint32_t as = o_next(otab), ws = o_next(otab), off = i < 15 ? half : kh * 16384;
                slot_acquire(sb, eph, as);
                load_bulk(sb, as, off, g_ctx + (size_t)(ort * 32 + head) * SLOT + off, SLOT / 2, i < 15, HINT & 16);
                if (i >= 15) load_bulk(sb, as, off ^ 16384, i == 15 ? g_x2 + ((ort * 2 + kh) * 4 + cq) * 1024 : reinterpret_cast<const uint4*>(P.wdown) + min(rb, NFFN - 1) * 1024, SLOT / 2, false, false);
                PT();
                slot_acquire(sb, eph, ws);
                load_tile(sb, ws, 0, &tm_wo, head * 128, cq * 2, false, HINT & 2);
                PT();
                if (i == 0) o_next(otab);
            }
            if (rb < NFFN) {
                slot_acquire(sb, eph, SL_WF);
                load_bulk(sb, SL_WF, 0, g_wf + rb * SLOT, SLOT, false, false);
            }
        } else if (warp == 9) {
            *reinterpret_cast<volatile uint32_t*>(smem + SM_EP + 16) = 0;
            l2_prefetch(P.ckv + rb * 2048, 4096);
            mbar_watch(sb + BAR_FULL, 0);
            l2_prefetch(P.ckv + 512 * 512 + rb * 2048, 4096);
            mbar_watch(sb + BAR_FULL + 8 * XPF, 0);
            l2_prefetch(P.x + rb * 8192, 16384);
            mbar_watch(sb + BAR_FULL + 8 * 4, 0);
            l2_prefetch(P.ckv + 1024 * 512 + rb * 4096, 8192);
            TS(40);
#pragma unroll 1
            for (int i = 0; i < 13; i++) {
                step_watch(sb + SM_EP + 16, i == 0 ? 0 : i < 5 ? PFA + i : 13 + PFB + i);
                if (i == 10) mbar_watch(sb + BAR_FLAG + 8 * 7, 0);
                const int rf = min(rb, NFFN - 1), pc = 4 * (i - 5) + cq;
                const uint8_t* p = i == 3 ? reinterpret_cast<const uint8_t*>(P.ckv) + rb * 16384
                                 : i == 4 ? g_h + rb * 16384
                                 : i < 8 ? g_ctx + (size_t)(ort * 32 + o_head(pc >> 1, kh)) * SLOT + (pc & 1) * 16384
                                 : i < 10 ? reinterpret_cast<const uint8_t*>(P.wo) + (grp * 16 + (i & 1) * 8 + j) * 16384
                                 : i == 10 ? reinterpret_cast<const uint8_t*>(P.wdown) + rf * 16384 : g_wf + rf * SLOT + (i & 1) * 16384;
                if (i >= 3) l2_prefetch(p, 16384);
                else if ((i | j) & 1) tma3d_prefetch(i == 1 ? tw : &tm_wq, (j >> 1) * 128, grp * 4 + (i ? 2 : 0));
            }
            const uint32_t v = lds32(sb + SM_EP) - 1;
            sts128(sb + SM_RED + lane * 16, make_uint4(v, v, v, v));
            fence_async_smem();
            __syncwarp();
#pragma unroll 1
            for (int i = 0; i < OB / 32; i++) bulk_store(g_out + rb * OB + i * 32, sb + SM_RED, 512, false);
            asm volatile("cp.async.bulk.commit_group;\ncp.async.bulk.wait_group 0;" ::: "memory");
            fence_async_global();
            __syncwarp();
            mbar_arrive_if(sb + BAR_PF, lane == 0);
            if (lane == 0) mbar_watch(sb + BAR_END, 0);
        } else {
            const uint32_t ep = __ldcg(&g_sync.epoch[0]) + 1;
            asm volatile("st.shared.u32 [%0], %1;" ::"r"(sb + SM_EP), "r"(ep) : "memory");
            mbar_wait(sb + BAR_FULL + 8 * 4, 0);
            {
                uint4 v[4];
                for (;;) {
                    uint32_t bad = 0;
#pragma unroll
                    for (int k = 0; k < 4; k++) v[k] = ld_poll(reinterpret_cast<const uint4*>(g_mod1) + (warp & 1) * 128 + k * 32 + lane);
#pragma unroll
                    for (int k = 0; k < 4; k++) bad |= (v[k].x ^ ep) | (v[k].y ^ ep) | (v[k].z ^ ep) | (v[k].w ^ ep);
                    if (poll_done((bad & 0xffff) == 0, 100)) break;
                }
                const uint32_t one = (warp & 1) ? ONE2 : 0x80008000u;
#pragma unroll
                for (int k = 0; k < 4; k++)
                    *reinterpret_cast<uint2*>(smem + SM_TAB + (warp & 1) * 1024 + k * 256 + lane * 8) =
                        make_uint2(badd(__byte_perm(v[k].x, v[k].y, 0x7632), one), badd(__byte_perm(v[k].z, v[k].w, 0x7632), one));
            }
            __syncwarp();
            mbar_arrive_if(sb + BAR_FLAG + 8 * 8, lane == 0);
            if (warp == 10) {
#pragma unroll 1
                for (int i = 0; i < 9; i++) {
                    mbar_sleep(sb + BAR_DONE + 8 * i);
                    if (lane == 0) flag_add(i && ((i - 1) & 2) ? &g_sync.ctxcnt[((i & 1) ? 15 - j : j) * 32 + 2 * grp + (i > 4)] : &g_sync.cnt[(grp * 8 + i) * 8]);
                    if (i == 0) TS(43);
                }
            } else {
                TS(42);
#pragma unroll 1
                for (int i = 0; i < 8; i++) {
                    mbar_sleep(sb + BAR_DONE + 8 * (i == 7 ? 6 : i == 4 ? 3 : i));
                    if (lane < 2) flag_wait(&g_sync.cnt[((i == 0 ? (lane ? j : 15 - j) : i == 7 ? 0 : grp) * 8 + i) * 8], 8 * ep);
                    __syncwarp();
                    mbar_arrive_if(sb + BAR_FLAG + 8 * i, lane == 0 && i < 7);
                    TS(48 + i);
                }
                const uint32_t *mp = reinterpret_cast<const uint32_t*>(g_mod) + lane, *wp = reinterpret_cast<const uint32_t*>(P.wr) + lane;
                float ra = 0.f, rs = 0.f;
#pragma unroll 1
                for (int k = 0; k < 256; k += 32) {
                    const uint32_t ga = __ldcg(mp + 512 + k), sh = __ldcg(mp + 768 + k), c1 = badd(__ldcg(mp + 1024 + k), ONE2);
                    const uint32_t gb = __ldcg(mp + 1280 + k), ww = __ldg(wp + k);
                    const uint32_t a = bmul(c1, ww);
                    ra += bf_lo(a) + bf_hi(a);
                    rs = fmaf(bf_lo(sh), bf_lo(ww), fmaf(bf_hi(sh), bf_hi(ww), rs));
                    if (k >> 6 == cq) {
                        sts128(sb + SM_TAB + ((k & 32) + lane) * 16, make_uint4(ga << 16, ga & 0xffff0000u, a, 0));
                        sts128(sb + SM_TAB + 1024 + ((k & 32) + lane) * 16, make_uint4(c1, sh, gb, 0));
                    }
                }
#pragma unroll 1
                for (int o = 16; o > 0; o >>= 1) {
                    ra += __shfl_xor_sync(0xffffffffu, ra, o);
                    rs += __shfl_xor_sync(0xffffffffu, rs, o);
                }
                *reinterpret_cast<float2*>(smem + SM_EP + 8) = make_float2(ra, rs);
                __syncwarp();
                mbar_arrive_if(sb + BAR_FLAG + 8 * 7, lane == 0);
                const uint32_t* f = lane < 17 ? &g_sync.ctxcnt[ort * 32 + o_head(lane, kh)] : &g_sync.cnt[15 * 8];
                uint32_t ready = -(j & 1), list = 0, sh = 0, qa;
                asm("mapa.shared::cluster.u32 %0, %1, %2;" : "=r"(qa) : "r"(sb + SM_EP + 20), "r"(lane & 1));
                while (ready != ~0u) {
                    uint32_t v, now;
                    do {
                        asm volatile("ld.acquire.gpu.global.u32 %0, [%1];" : "=r"(v) : "l"(f) : "memory");
                        now = __ballot_sync(0xffffffffu, (int)(v - (lane < 17 ? ep : NSPARE * ep)) >= 0);
                    } while (!poll_done(now != ready, POLL_NS));
#pragma unroll 1
                    for (uint32_t fresh = now & ~ready & 0x7f00; fresh; fresh &= fresh - 1, sh += 4) list |= (__ffs(fresh) - 1) << sh;
                    list |= (((now & 0xff) + 1) >> 8 << 28) | ((now & (now >> 2) & 0x18000) << 14);
                    if (lane < 2) asm volatile("st.relaxed.cluster.shared::cluster.u32 [%0], %1;" ::"r"(qa), "r"(list) : "memory");
                    if ((ready & 0xff) != 0xff && (now & 0xff) == 0xff) mbar_sleep(sb + BAR_DONE + 8 * 7);
                    ready = now;
                }
                TS(45);
            }
        }
    } else {
        const bool elected = (tid & 127) == 0, rel = (tid & 95) == 0;
        uint32_t eb;
        asm("mapa.shared::cluster.u32 %0, %1, %2;" : "=r"(eb) : "r"(sb + BAR_EMPTY), "r"(warp & 1));
        const int g = lane >> 2, c4 = lane & 3;
        uint32_t toff = warp * 4096 + g * 64 + ((c4 ^ (g >> 1)) << 4);
        uint32_t fph = 0x3f, r = 0;
        if (wg == 1) bar_arrive(1, 256);
        const uint32_t kd = desc_k(sb), wd = desc_mn(sb), vd = ((sb & 0x3ffff) >> 4) | (32u << 16);
        const int nL = 16 - j, hn = nL - 1 + wg;
        float s[64], o[64], li[2] = {0.f, 0.f};
        uint32_t cimg = 0;
        const float sc = (j & 1) ? 1.f : SM_C;
#pragma unroll 1
        for (int q = 0; q < 3; q++) {
            const uint32_t as = (0x635u >> (4 * q)) & 15;
            mbar_wait(sb + BAR_FULL + 8 * q, 0);
            mbar_wait(sb + BAR_FULL + 8 * as, 0);
            bar_sync(1 + wg, 256);
            gemm_issue<false>(s, kd + wg * 512 + as * (SLOT / 16), wd + q * (SLOT / 16), q, false);
            bar_arrive(2 - wg, 256);
            wg_wait<0>();
            release_if(eb, as, rel);
        }
        {
            const int xrow = rb * 16 + warp * 2;
            const uint4* xp = reinterpret_cast<const uint4*>(P.x) + xrow * 64;
            const uint32_t img = (grp * 32 + j) * SLOT;
            uint32_t x[16], x0[2];
            float st[4] = {0.f, 0.f, 0.f, 0.f};
            mbar_wait(sb + BAR_FULL + 8 * 4, 0);
#pragma unroll
            for (int q = 3; q < 8; q++) {
                const uint32_t ws = (0x4210u >> (4 * (q & 3))) & 15, as = (0x635u >> (4 * (q % 3))) & 15;
                mbar_wait(sb + BAR_FULL + 8 * as, (q / 3) & 1);
                bar_sync(1 + wg, 256);
                if (q == 3) gemm_issue<false>(s, kd + wg * 512 + as * (SLOT / 16), wd + ws * (SLOT / 16), 1, false);
                else if (q == 4) gemm_issue<true>(o, kd + wg * 512 + as * (SLOT / 16), wd + ws * (SLOT / 16), 0, false);
                else gemm_issue<false>(o, kd + wg * 512 + as * (SLOT / 16), wd + ws * (SLOT / 16), 1, false);
                bar_arrive(2 - wg, 256);
                sched_fence(fph, P.zero);
                if (q > 3) reg_fence(s);
                if (q == 3) {
                    asm volatile("setmaxnreg.inc.sync.aligned.u32 232;");
#pragma unroll
                    for (int i = 0; i < 4; i++)
                        asm volatile("ld.global.nc.v4.u32 {%0, %1, %2, %3}, [%4];" : "=r"(x[4 * i]), "=r"(x[4 * i + 1]), "=r"(x[4 * i + 2]), "=r"(x[4 * i + 3])
                                     : "l"(xp + lane + 32 * i) : "memory");
#pragma unroll
                    for (int i = 0; i < 2; i++) asm volatile("ld.global.nc.u32 %0, [%1];" : "=r"(x0[i]) : "l"(xp + 64 * i) : "memory");
                }
                if (q == 4) {
                    img_store_global<0>(img, toff, s, sc, sc);
#pragma unroll
                    for (int k = 0; k < 16; k++) {
                        const float d0 = bf_lo(x[k]) - bf_lo(x0[k >> 3]), d1 = bf_hi(x[k]) - bf_lo(x0[k >> 3]);
                        st[k >> 3] += d0 + d1;
                        st[2 + (k >> 3)] = fmaf(d0, d0, fmaf(d1, d1, st[2 + (k >> 3)]));
                    }
#pragma unroll
                    for (int i = 0; i < 4 * NSH; i++) st[i & 3] += __shfl_xor_sync(0xffffffffu, st[i & 3], 1 << (i >> 2));
                    reg_fence(st);
                }
                if (q == 5) {
#pragma unroll
                    for (int i = 4 * NSH; i < 20; i++) st[i & 3] += __shfl_xor_sync(0xffffffffu, st[i & 3], 1 << (i >> 2));
                    img_store_global<1>(img, toff, s, sc, sc);
#pragma unroll
                    for (int i = 0; i < 2; i++) {
                        const float d = st[i] * (1.f / 512.f);
                        st[2 + i] = ln_rstd(fmaxf(fmaf(-d, d, st[2 + i] * (1.f / 512.f)), 0.f));
                        x0[i] = pack2(bf_lo(x0[i]) + d, bf_lo(x0[i]) + d);
                    }
                    reg_fence(st);
                    reg_fence(x0);
                }
                if (q > 5) {
                    if (q == 6) mbar_wait(sb + BAR_FLAG + 8 * 8, 0);
                    const uint4 a = lds128(sb + SM_TAB + 1024 + (q & 1) * 512 + lane * 16), c = lds128(sb + SM_TAB + (q & 1) * 512 + lane * 16);
                    uint8_t* hp = g_h + (grp * 8 + (q & 1) * 4 + (lane >> 3)) * 16384 + (xrow & 127) * 128;
#pragma unroll
                    for (int i = 0; i < 2; i++) {
                        const uint32_t* y = x + 8 * i + 4 * (q & 1);
                        *reinterpret_cast<uint4*>(hp + i * 128 + (((lane ^ xrow ^ i) & 7) << 4)) =
                            make_uint4(ln_apply(y[0], x0[i], st[2 + i], a.x, c.x), ln_apply(y[1], x0[i], st[2 + i], a.y, c.y),
                                       ln_apply(y[2], x0[i], st[2 + i], a.z, c.z), ln_apply(y[3], x0[i], st[2 + i], a.w, c.w));
                    }
                    if (q == 7) {
                        __syncwarp();
                        mbar_arrive_if(sb + BAR_DONE, lane == 0);
                    }
                    if (q == 6) img_store_global<2>(img, toff, s, sc, sc);
                    else img_store_global<3>(img, toff, s, sc, sc);
                }
                if (q < 7) {
                    sched_fence(fph, P.zero);
                    wg_wait<0>();
                    release_if(eb, as, rel);
                }
            }
        }
        uint32_t pend = 0x73;
        uint32_t p[32] = {};
#pragma unroll 1
        for (int hp = 0; hp < 2; hp++) {
            float m[2] = {0.f, 0.f}, l[2] = {0.f, 0.f}, t[4] = {0.f, 0.f, 0.f, 0.f};
            bool shifted = false, bad = false, plain = false;
            uint32_t qa = desc_k(sb + 5 * SLOT + (wg ^ 1) * 8192);
            const uint32_t limg = (512 + (15 - j) * 32 + 2 * grp + hp) * SLOT;
            {
                const int step = hp ? -8 * SLOT : 8 * SLOT;
                uint32_t img = (grp * 32 + (hp ? j ^ 30 : j) + 8) * SLOT;
                const uint32_t wtab = w_table(hp);
                uint32_t atab = hp ? 0x562u : 0x356u;
#pragma unroll 1
                for (int u = 2 - 2 * hp; u < 6; u += 2) {
                    proj_tile<false>(s, o, u, !u, sb, wg, eb, rel, fph, wtab, atab, pend, u ? img : cimg, toff, u ? sc : li[0], u ? sc : li[1], p);
                    __syncwarp();
                    mbar_arrive_if(sb + BAR_DONE + 4 * u + 32 * hp, lane == 0);
                    if (elected) TS(1 + 10 * hp + u + 20 * wg);
                    proj_tile<true>(o, s, u + 1, 0, sb, wg, eb, rel, fph, wtab, atab, pend, img + step, toff, sc, sc, p);
                    if (elected) TS(2 + 10 * hp + u + 20 * wg);
                    img += 2 * step;
                }
            }
            asm volatile("" : "+r"(toff));
            if (elected) TS(6 + 10 * hp + 20 * wg);
            fence_async_smem();
            slot_wait(sb + BAR_FULL, fph, r);
            step_retire(eb, rel, pend);
            reg_fence(o);
            int n = -1;
#pragma unroll 1
            for (;;) {
                while (bad || plain) {
                    float d0 = m[0], d1 = m[1];
                    if (bad) {
                        float a0, a1;
                        softmax_remax(s, m, n == 0 || n == nL, d0, d1, a0, a1);
                        shifted = true;
                        l[0] *= a0;
                        l[1] *= a1;
#pragma unroll
                        for (int i = 0; i < 64; i++) o[i] *= (i & 2) ? a1 : a0;
                    }
#pragma unroll
                    for (int i = 0; i < 64; i++) s[i] -= (i & 2) ? d1 : d0;
                    softmax_exp<0, 16>(s, p, t);
                    t[0] += t[1];
                    t[2] += t[3];
                    bad = !bad && softmax_unsafe(t[0], t[2], false);
                    plain = false;
                }
#pragma unroll 1
                do {
                    l[0] += t[0];
                    l[1] += t[2];
                    if (++n > 16) break;
                    const uint32_t ks = r;
                    uint32_t vs = ring_next(r);
                    r = ring_next(vs);
                    bar_sync(1 + wg, 256);
                    const float x = (float)((warp & 3) * 16 + g - 2 * c4);
                    if (n == hn) {
                        float sh[32];
                        qk_issue(sh, qa, kd + ks * (SLOT / 16));
                        slot_wait(sb + BAR_FULL, fph, vs);
                        pv_issue(o, p, vd + vs * (SLOT / 16), 1, false);
                        bar_arrive(2 - wg, 256);
                        wg_wait<1>();
                        reg_fence(sh);
                        tri_mask_copy(s, sh, x);
                        release_if(eb, ks, rel);
                        release_if(eb, 5 + wg, rel && (!wg || n == 16));
                        if (!wg) qa += SLOT / 16;
                        float e[4 * EARLY];
#pragma unroll
                        for (int i = 0; i < 4 * EARLY; i++) {
                            e[i] = ex2(s[i]);
                            t[i & 3] = i < 4 ? e[i] : t[i & 3] + e[i];
                        }
                        reg_fence(e);
                        slot_wait(sb + BAR_FULL, fph, r);
                        wg_wait<0>();
                        reg_fence(o);
                        reg_fence(e);
                        release_if(eb, vs, rel);
#pragma unroll
                        for (int i = 0; i < 2 * EARLY; i++) p[i] = pack2(e[2 * i], e[2 * i + 1]);
                        softmax_exp<EARLY, 8>(s, p, t);
                        if (wg) {
                            ctx_store(limg, toff, o, rcp(quad_sum(l[0])), rcp(quad_sum(l[1])));
                            __syncwarp();
                            mbar_arrive_if(sb + BAR_DONE + 24 + 32 * hp, lane == 0);
                            l[0] = l[1] = m[0] = m[1] = 0.f;
                            shifted = false;
                        }
                        t[0] += t[1];
                        t[2] += t[3];
                        plain = shifted;
                        if (plain) break;
                        bad = softmax_unsafe(t[0], t[2], wg);
                        continue;
                    }
                    if (n == nL) {
                        qk_issue(s, qa, kd + ks * (SLOT / 16));
                        slot_wait(sb + BAR_FULL, fph, vs);
                        pv_issue(o, p, vd + vs * (SLOT / 16), 1, true);
                        bar_arrive(2 - wg, 256);
                        const float i0 = rcp(quad_sum(l[0])), i1 = rcp(quad_sum(l[1]));
                        wg_wait<1>();
                        reg_fence(s);
                        release_if(eb, ks, rel);
                        release_if(eb, 6, rel && n == 16);
                        tri_mask(s, x);
                        float e[4 * EARLY2];
#pragma unroll
                        for (int i = 0; i < 4 * EARLY2; i++) {
                            e[i] = ex2(s[i]);
                            t[i & 3] = i < 4 ? e[i] : t[i & 3] + e[i];
                        }
                        reg_fence(e);
                        reg_fence(s);
                        reg_fence(t);
                        slot_wait(sb + BAR_FULL, fph, r);
                        sched_fence(fph, P.zero);
                        wg_wait<0>();
                        reg_fence(o);
                        reg_fence(e);
                        release_if(eb, vs, rel);
#pragma unroll
                        for (int i = 0; i < 2 * EARLY2; i++) p[i] = pack2(e[2 * i], e[2 * i + 1]);
                        softmax_exp<EARLY2, MSPLIT>(s, p, t);
                        ctx_store(limg, toff, o, i0, i1);
                        reg_fence(t);
                        reg_fence(s);
                        softmax_exp<MSPLIT, 16>(s, p, t);
                        __syncwarp();
                        mbar_arrive_if(sb + BAR_DONE + 24 + 32 * hp, lane == 0);
                        l[0] = l[1] = m[0] = m[1] = 0.f;
                        shifted = false;
                        t[0] += t[1];
                        t[2] += t[3];
                        bad = __any_sync(0xffffffffu, fmaxf(t[0], t[2]) > SM_HI || fminf(t[0], t[2]) < SM_LO);
                        continue;
                    }
                    qk_issue(s, qa, kd + ks * (SLOT / 16));
                    if (n == 0) {
                        r = vs;
                        vs = 4 - hp;
                        slot_wait(sb + BAR_FULL, fph, 6);
                        gemm_issue<false>(o, qa + SLOT / 16, wd + vs * (SLOT / 16), 1, false);
                    } else {
                        slot_wait(sb + BAR_FULL, fph, vs);
                        if (n == 1) {
                            wg_wait<1>();
                            reg_fence(o);
                            const uint32_t a = sb + 6 * SLOT + q_off(toff);
#pragma unroll
                            for (int i = 0; i < 8; i++) {
                                const int k = 16 * (i >> 1) + 2 * (i & 1);
                                sts128(a + (i >> 2) * 16384 + (i & 2) * 256 + (i & 1) * 1024,
                                       make_uint4(pack2(o[k], o[k + 1]), pack2(o[k + 4], o[k + 5]), pack2(o[k + 8], o[k + 9]), pack2(o[k + 12], o[k + 13])));
                            }
                        }
                        pv_issue(o, p, vd + vs * (SLOT / 16), n != 1 && n != nL + 1, n == hn + 1);
                    }
                    bar_arrive(2 - wg, 256);
                    wg_wait<1>();
                    reg_fence(s);
                    release_if(eb, ks, rel);
                    release_if(eb, 6, rel && n == 16);
                    if (n == nL - 1) {
                        tri_mask(s, x);
                        release_if(eb, 5, rel);
                        qa += SLOT / 16;
                    }
                    if (n == 2) fence_async_smem();
                    if (shifted) {
                        slot_wait(sb + BAR_FULL, fph, r);
                        wg_wait<0>();
                        reg_fence(o);
                        release_if(eb, vs, rel);
                        plain = true;
                        break;
                    }
                    float e[4 * EARLY];
#pragma unroll
                    for (int i = 0; i < 4 * EARLY; i++) {
                        e[i] = ex2(s[i]);
                        t[i & 3] = i < 4 ? e[i] : t[i & 3] + e[i];
                    }
                    reg_fence(e);
                    slot_wait(sb + BAR_FULL, fph, r);
                    wg_wait<0>();
                    reg_fence(o);
                    reg_fence(e);
                    release_if(eb, vs, rel);
#pragma unroll
                    for (int i = 0; i < 2 * EARLY; i++) p[i] = pack2(e[2 * i], e[2 * i + 1]);
                    softmax_exp<EARLY, 16>(s, p, t);
                    t[0] += t[1];
                    t[2] += t[3];
                    bad = __any_sync(0xffffffffu, fmaxf(t[0], t[2]) > SM_HI || (n == 0 && fminf(t[0], t[2]) < SM_LO));
                } while (!bad);
                if (!bad && !plain) break;
            }
            asm volatile("" : "+r"(toff));
            const uint32_t vs = r, ga = desc_k(sb + (hp ? 2 * (wg ^ kh ^ 1) : wg) * 8192);
            r = ring_next(r);
            slot_wait(sb + BAR_FULL, fph, 5);
            slot_wait(sb + BAR_FULL, fph, r);
            bar_sync(1 + wg, 256);
            gemm_issue<true>(s, ga + 5 * (SLOT / 16), wd + r * (SLOT / 16), 0, hp);
            pv_issue(o, p, vd + vs * (SLOT / 16), j, hn == 16);
            bar_arrive(2 - wg, 256);
            li[0] = rcp(quad_sum(l[0]));
            li[1] = rcp(quad_sum(l[1]));
            cimg = limg + (2 * j - 15) * 32 * SLOT + (wg ? -16384 : 16384);
            wg_wait<1>();
            release_if(eb, 5, rel);
            release_if(eb, r, rel && hp);
            wg_wait<0>();
            release_if(eb, vs, rel);
            reg_fence(o);
            img_store_global<0>(cimg, toff, o, li[0], li[1]);
            pend = 0x77;
            if (elected) TS(8 + 10 * hp + 20 * wg);
        }
        uint32_t otab = 0x2351604u;
        const uint32_t oa = desc_k(sb + (wg ^ kh ^ 1) * 16384);
        const int t7 = tid & 127, w4 = warp & 3, row = ort * 128 + kh * 64 + w4 * 16 + g;
#pragma unroll 1
        for (int i = 1; i < 15 - OFF - wg; i++) {
            const uint32_t as = o_next(otab), ws = o_next(otab);
            slot_wait(sb + BAR_FULL, fph, as);
            slot_wait(sb + BAR_FULL, fph, ws);
            bar_sync(1 + wg, 256);
            gemm_issue<false>(s, oa + as * (SLOT / 16), wd + ws * (SLOT / 16), 1, true);
            bar_arrive(2 - wg, 256);
            wg_wait<1>();
            reg_fence(o);
            if (i == 1) img_store_global<1>(cimg, toff, o, li[0], li[1]);
            if (i == 2) {
                img_store_global<2>(cimg, toff, o, li[0], li[1]);
                img_store_global<3>(cimg, toff, o, li[0], li[1]);
                __syncwarp();
                mbar_arrive_if(sb + BAR_DONE + 64, lane == 0);
            }
            wg_wait<0>();
            release_if(eb, as, rel);
            release_if(eb, ws, rel);
        }
        mbar_wait(sb + BAR_PF, 0);
        const uint32_t ep = lds32(sb + SM_EP);
        uint32_t eb2 = sb + BAR_END;
        if (wg == 0) {
            reg_fence(s);
            if (elected) TS(9);
            TT(1);
#pragma unroll
            for (int v = 0; v < 8; v++)
                st_pub(g_out + rb * OB + v * 128 + t7, make_uint4((pack2(s[8 * v], s[8 * v + 1]) & ~1u) | (ep & 1), pack2(s[8 * v + 2], s[8 * v + 3]),
                                                                      pack2(s[8 * v + 4], s[8 * v + 5]), pack2(s[8 * v + 6], s[8 * v + 7])), true);
            constexpr uint32_t s1 = SL_WF, s2 = SL_WD;
            bar_sync(4, 256);
            uint32_t wf[64];
            float wn[64];
            if (rb < NFFN) {
                slot_wait(sb + BAR_FULL, fph, s1);
                const uint32_t a = sb + s1 * SLOT + (w4 * 128 + (lane >> 4) * 8 + (lane & 7)) * 32 + (((lane >> 3) ^ (lane >> 2)) & 1) * 16;
#pragma unroll
                for (int i = 0; i < 16; i++)
                    asm volatile("ldmatrix.sync.aligned.m8n8.x4.trans.shared.b16 {%0, %1, %2, %3}, [%4];"
                                 : "=r"(wf[4 * i]), "=r"(wf[4 * i + 1]), "=r"(wf[4 * i + 2]), "=r"(wf[4 * i + 3])
                                 : "r"(a + (i >> 3) * 16384 + (i & 7) * 512) : "memory");
                slot_wait(sb + BAR_FULL, fph, s2);
#pragma unroll
                for (int i = 0; i < 16; i++) {
                    const uint2 w = *reinterpret_cast<const uint2*>(smem + s2 * SLOT + (kh ^ 1) * 16384 + i * 1024 + t7 * 8);
                    wn[4 * i] = bf_lo(w.x); wn[4 * i + 1] = bf_hi(w.x); wn[4 * i + 2] = bf_lo(w.y); wn[4 * i + 3] = bf_hi(w.y);
                }
                reg_fence(wn);
            }
            const uint32_t gbf = __ldcg(reinterpret_cast<const uint32_t*>(g_mod) + 1280 + rb * 2 + (lane >> 4));
            if (elected) TS(10);
            TT(2);
            const int pq = (2 * rb + (lane >> 4)) & 63, pv = (pq >> 2) / 3, cm = (pq >> 2) - 3 * pv;
            const uint4* cp = g_cand + w4 * 24 + c4;
            const uint4* fp = g_cand + (rb >> 5) * 24 + pv * 4 + (pq & 3);
            const uint4* yp = g_out + lane * OB + OB_Y + rb;
            uint4* yo = g_out + rb * OB + OB_Y + t7;
            uint32_t* op = reinterpret_cast<uint32_t*>(P.out) + rb * 2 + (lane >> 4);
            uint32_t ra = sb + SM_RED + (w4 * 32 + c4 * 8 + g) * 4;
            asm volatile("" : "+l"(cp), "+l"(fp), "+l"(yp), "+l"(yo), "+l"(op), "+r"(ra));
            sched_fence(eb2, P.zero);
            if (warp == 0) {
                asm volatile("st.shared.u32 [%0], %1;" ::"r"(sb + SM_EP + 24), "r"(best_key(g_key + cq * 128, lane, ep)) : "memory");
                mbar_arrive_if(sb + BAR_BEST, lane == 0);
            }
            bar_sync(3, 128);
            const uint32_t best = lds32(sb + SM_EP + 24), co = ((~best >> 9) & 127) * 192;
            TT(3);
            if (rb < NFFN) {
                uint4 cv[6];
                for (;;) {
                    uint32_t bad = 0;
#pragma unroll
                    for (int v = 0; v < 6; v++) cv[v] = ld_poll(cp + co + v * 4);
#pragma unroll
                    for (int v = 0; v < 6; v++) bad |= cv[v].w ^ ep;
                    if (__all_sync(0xffffffffu, bad == 0)) break;
                }
                TT(4);
                float d[4][4] = {};
#pragma unroll
                for (int k = 0; k < 8; k++) {
                    const uint32_t b0 = (&cv[(2 * k) / 3].x)[(2 * k) % 3], b1 = (&cv[(2 * k + 1) / 3].x)[(2 * k + 1) % 3];
                    mma16816(d[k & 1], wf + 4 * k, b0, b1);
                    mma16816(d[2 + (k & 1)], wf + 32 + 4 * k, b0, b1);
                }
                float u[4] = {d[0][0] + d[1][0], d[0][2] + d[1][2], d[2][0] + d[3][0], d[2][2] + d[3][2]};
                reg_fence(u);
                asm volatile("st.shared.f32 [%0], %1;" ::"r"(ra), "f"((c4 & 2) ? ((c4 & 1) ? u[3] : u[2]) : ((c4 & 1) ? u[1] : u[0])) : "memory");
                bar_sync(3, 128);
                const float* sred = reinterpret_cast<const float*>(smem + SM_RED);
                const float v = rbf((sred[lane] + sred[32 + lane]) + (sred[64 + lane] + sred[96 + lane]));
                const float act = rbf(rbf(v * sigmoid(v)) * __shfl_down_sync(0xffffffffu, v, 16));
                float y[4] = {0.f, 0.f, 0.f, 0.f};
#pragma unroll
                for (int k = 0; k < 16; k++) {
                    const float a = __shfl_sync(0xffffffffu, act, k);
#pragma unroll
                    for (int i = 0; i < 4; i++) y[i] = fmaf(a, wn[4 * k + i], y[i]);
                }
                st_pub(yo, make_uint4((__float_as_uint(y[0]) & ~15u) | (ep & 15), __float_as_uint(y[1]), __float_as_uint(y[2]), __float_as_uint(y[3])), true);
            }
            TT(5);
            if (warp == 0) {
                if (rb == 0 && lane == 0) g_sync.epoch[0] = ep;
                uint4 fh, fx;
                do { fh = ld_poll(fp + co); fx = ld_poll(fp + co + 96); } while (!poll_done(fh.w == ep && fx.w == ep, 50));
                const float sg = sigmoid(bf_hi((best & 0x80000000u) ? (best ^ 0x80000000u) : ~best));
                uint32_t fin[3] = {cm == 0 ? fh.x : cm == 1 ? fh.y : fh.z, cm == 0 ? fx.x : cm == 1 ? fx.y : fx.z, pack2(sg, sg)};
                op += ((~best >> 5) & 2047) * 256;
                asm volatile("" : "+l"(op));
                reg_fence(fin);
                if (rb >= NFFN) __nanosleep(YPRE);
                sched_fence(eb2, P.zero);
                uint4 yv[4];
                for (;;) {
#pragma unroll
                    for (int k = 0; k < 4; k++) yv[k] = ld_poll(yp + (k < 3 || lane < 16 ? k : 2) * 32 * OB);
                    if (poll_done((((yv[0].x ^ ep) | (yv[1].x ^ ep) | (yv[2].x ^ ep) | (yv[3].x ^ ep)) & 15) == 0, YSLEEP)) break;
                }
                TT(6);
                mbar_arrive_if(eb2, lane == 0);
                float y[4];
#pragma unroll
                for (int i = 0; i < 4; i++) {
                    const uint32_t mk = i ? ~0u : ~15u;
                    y[i] = (__uint_as_float((&yv[0].x)[i] & mk) + __uint_as_float((&yv[1].x)[i] & mk)) +
                           (__uint_as_float((&yv[2].x)[i] & mk) + (lane < 16 ? __uint_as_float((&yv[3].x)[i] & mk) : 0.f));
                }
                float z0 = ((lane & 16) ? y[2] : y[0]) + __shfl_xor_sync(0xffffffffu, (lane & 16) ? y[0] : y[2], 16);
                float z1 = ((lane & 16) ? y[3] : y[1]) + __shfl_xor_sync(0xffffffffu, (lane & 16) ? y[1] : y[3], 16);
#pragma unroll
                for (int o = 8; o > 0; o >>= 1) {
                    z0 += __shfl_xor_sync(0xffffffffu, z0, o);
                    z1 += __shfl_xor_sync(0xffffffffu, z1, o);
                }
                if ((lane & 15) == 0) *op = badd(fin[1], bmul(gbf, badd(fin[0], bmul(pack2(z0, z1), fin[2]))));
            }
            if (elected) TS(62);
            TT(7);
        } else {
            const float4* tf = reinterpret_cast<const float4*>(smem + SM_TAB) + c4;
            uint32_t x2[32];
            float tc[48];
#pragma unroll
            for (int k = 0; k < 16; k++) {
                const float4 c = tf[k * 4];
                tc[3 * k] = c.x; tc[3 * k + 1] = c.y; tc[3 * k + 2] = (g & 1) ? c.z : __uint_as_float(ONE2);
            }
            reg_fence(tc);
            bar_sync(2, 256);
#pragma unroll 1
            for (int i = 14; i < 17; i++) {
                const uint32_t as = o_next(otab), ws = o_next(otab);
                slot_wait(sb + BAR_FULL, fph, as);
                slot_wait(sb + BAR_FULL, fph, ws);
                gemm_issue<false>(s, oa + as * (SLOT / 16), wd + ws * (SLOT / 16), 1, true);
                wg_wait<1>();
            }
            const uint4* pr = g_out + (rb ^ 16) * OB + t7;
            uint4 pa[8];
            if (elected) TS(29);
            TT(1);
#pragma unroll
            for (int k = 0; k < 8; k++) {
                const uint4 v = lds128(sb + SL_X * SLOT + (kh ^ 1) * 16384 + k * 2048 + t7 * 16);
                x2[4 * k] = v.x; x2[4 * k + 1] = v.y; x2[4 * k + 2] = v.z; x2[4 * k + 3] = v.w;
            }
            wg_wait<0>();
            reg_fence(s);
            bar_arrive(4, 256);
            if (elected) TS(39);
            TT(2);
#pragma unroll
            for (int v = 0; v < 8; v++) pa[v] = ld_poll(pr + v * 128);
#pragma unroll
            for (int i = 0; i < 64; i++) s[i] = fmaf(tc[3 * (i >> 2) + (i & 1)], s[i], (i & 1) ? bf_hi(x2[i >> 1]) : bf_lo(x2[i >> 1]));
            reg_fence(s);
            sched_fence(eb2, P.zero);
            for (;;) {
                uint32_t bad = 0;
#pragma unroll
                for (int v = 0; v < 8; v++) asm("lop3.b32 %0, %0, %1, %2, 0xf6;" : "+r"(bad) : "r"(pa[v].x), "r"(ep));
                if (__all_sync(0xffffffffu, (bad & 1) == 0)) break;
                if (PSLEEP) __nanosleep(PSLEEP);
#pragma unroll
                for (int v = 0; v < 8; v++) pa[v] = ld_poll(pr + v * 128);
            }
            if (elected) TS(30);
            TT(3);
            float sd[4] = {}, q0[4] = {}, q1[4] = {};
#pragma unroll
            for (int k = 0; k < 8; k++) {
#pragma unroll
                for (int i = 4 * k; i < 4 * k + 4; i++) {
                    const uint32_t w = (i & 3) ? (&pa[k].x)[i & 3] : pa[k].x & ~1u;
                    x2[i] = pack2(fmaf(tc[3 * (i >> 1)], bf_lo(w), s[2 * i]), fmaf(tc[3 * (i >> 1) + 1], bf_hi(w), s[2 * i + 1]));
                }
                mma16816(sd, x2 + 4 * k, __float_as_uint(tc[6 * k + 2]), __float_as_uint(tc[6 * k + 5]));
                mma16816(q0, x2 + 4 * k, x2[4 * k], x2[4 * k + 2]);
                mma16816(q1, x2 + 4 * k, x2[4 * k + 1], x2[4 * k + 3]);
            }
            uint4* sp = g_out + rb * OB + OB_STAT + (w4 * 8 + g) * 2;
            st_pub(sp, make_uint4(__float_as_uint(sd[0]), __float_as_uint((g & 1) ? q0[1] : q0[0]), __float_as_uint(sd[1]), ep), c4 == g >> 1);
            st_pub(sp + 1, make_uint4(__float_as_uint(sd[2]), __float_as_uint((g & 1) ? q1[3] : q1[2]), __float_as_uint(sd[3]), ep), c4 == g >> 1);
            sched_fence(eb2, P.zero);
            if (elected) TS(56);
            TT(4);
            uint32_t cb[16], sh[16], gb[16];
#pragma unroll
            for (int i = 0; i < 16; i++) {
                const float4 c = tf[64 + i * 4];
                cb[i] = __float_as_uint(c.x); sh[i] = __float_as_uint(c.y); gb[i] = __float_as_uint(c.z);
            }
            const float ra = __uint_as_float(lds32(sb + SM_EP + 8)), rb0 = __uint_as_float(lds32(sb + SM_EP + 12));
            const uint4* rp = g_out + ((rb & ~33) + (c4 & 1) + (c4 & 2) * 16) * OB + OB_STAT + (w4 * 8 + g) * 2;
            uint32_t* kp = g_key + cq * 128 + (row >> 4);
            uint4* cp = g_cand + (row >> 4) * 192 + cq * 24 + c4;
            uint32_t kt = ((2047 - row) << 5) | (ep & 31);
            asm volatile("" : "+l"(kp), "+l"(cp), "+r"(kt));
            uint4 r0, r1;
            do {
                r0 = ld_poll(rp);
                r1 = ld_poll(rp + 1);
            } while (!poll_done(r0.w == ep && r1.w == ep, SSLEEP));
            if (elected) TS(57);
            TT(5);
            float st[6] = {__uint_as_float(r0.x), __uint_as_float(r1.x), __uint_as_float(r0.y), __uint_as_float(r1.y), __uint_as_float(r0.z), __uint_as_float(r1.z)};
#pragma unroll
            for (int i = 0; i < 12; i++) st[i % 6] += __shfl_xor_sync(0xffffffffu, st[i % 6], 1 + i / 6);
            const float m0 = st[0] * (1.f / 512.f), m1 = st[1] * (1.f / 512.f);
            const float rs0 = ln_rstd(fmaxf(fmaf(-m0, m0, st[2] * (1.f / 512.f)), 0.f));
            const float rs1 = ln_rstd(fmaxf(fmaf(-m1, m1, st[3] * (1.f / 512.f)), 0.f));
            const uint32_t mb0 = pack2(m0, m0), mb1 = pack2(m1, m1);
            const uint32_t lg = pack2(fmaf(rs0, fmaf(-bf_lo(mb0), ra, st[4]), rb0), fmaf(rs1, fmaf(-bf_lo(mb1), ra, st[5]), rb0));
            const uint32_t u0 = lg << 16, u1 = lg & 0xffff0000u;
            const uint32_t k0 = ((u0 ^ (((int)u0 >> 31) | 0x80000000u)) & 0xffff0000u) | kt;
            const uint32_t k1 = ((u1 ^ (((int)u1 >> 31) | 0x80000000u)) & 0xffff0000u) | (kt - 256);
            const uint32_t kb = __reduce_max_sync(0xffffffffu, max(k0, k1));
            st_pub(kp, kb, lane == 0);
            const bool cand = kb == k0 || kb == k1;
#pragma unroll 1
            for (int it = 0; it < 3; it++) {
                bool put = it == 1 || !cand;
                if (it == 2) {
                    mbar_wait(sb + BAR_BEST, 0);
                    put = cand && lds32(sb + SM_EP + 24) != kb;
                }
                const bool hi = (kb == k1) != (it == 1);
                uint32_t cx[18], ch[18];
#pragma unroll
                for (int i = 0; i < 16; i++) {
                    cx[i] = hi ? x2[2 * i + 1] : x2[2 * i];
                    ch[i] = ln_apply(cx[i], hi ? mb1 : mb0, hi ? rs1 : rs0, cb[i], sh[i]);
                }
                cx[16] = cx[17] = ch[16] = ch[17] = 0;
#pragma unroll
                for (int v = 0; v < 6; v++) st_pub(cp + v * 4, make_uint4(ch[3 * v], ch[3 * v + 1], ch[3 * v + 2], ep), cand && it == 0);
#pragma unroll
                for (int v = 0; v < 6; v++) st_pub(cp + 96 + v * 4, make_uint4(cx[3 * v], cx[3 * v + 1], cx[3 * v + 2], ep), cand && it == 0);
                if (it == 0) TT(6);
                uint2* op = reinterpret_cast<uint2*>(P.out) + (row + 8 * hi) * 128 + cq * 32 + (c4 & 1) * 2 + (c4 >> 1);
#pragma unroll
                for (int i = 0; i < 16; i += 2) {
                    const uint32_t v0 = badd(cx[i], bmul(gb[i], ch[i])), v1 = badd(cx[i + 1], bmul(gb[i + 1], ch[i + 1]));
                    const uint32_t rv = __shfl_xor_sync(0xffffffffu, (c4 & 1) ? v0 : v1, 1);
                    if (put) op[i * 2] = (c4 & 1) ? make_uint2(rv, v1) : make_uint2(v0, rv);
                }
            }
            if (elected) TS(59);
            TT(7);
        }
        mbar_arrive_if(eb2, lane == 0 && warp != 0);
    }
}

typedef CUresult (*EncodeFn)(CUtensorMap*, CUtensorMapDataType, cuuint32_t, void*, const cuuint64_t*, const cuuint64_t*,
                             const cuuint32_t*, const cuuint32_t*, CUtensorMapInterleave, CUtensorMapSwizzle,
                             CUtensorMapL2promotion, CUtensorMapFloatOOBfill);

void make_3d(EncodeFn fn, CUtensorMap* m, const void* p, uint64_t cols, uint64_t rows, uint32_t br = 128, uint32_t nb = 2) {
    cuuint64_t dims[3] = {64, rows, cols / 64}, strides[2] = {cols * 2, 128};
    cuuint32_t box[3] = {64, br, nb}, es[3] = {1, 1, 1};
    fn(m, CU_TENSOR_MAP_DATA_TYPE_BFLOAT16, 3, const_cast<void*>(p), dims, strides, box, es, CU_TENSOR_MAP_INTERLEAVE_NONE,
       CU_TENSOR_MAP_SWIZZLE_128B, CU_TENSOR_MAP_L2_PROMOTION_L2_256B, CU_TENSOR_MAP_FLOAT_OOB_FILL_NONE);
}

}

extern "C" void kernel_launch(void* const* d_in, const int* in_sizes, int n_in, void* d_out, int out_size) {
    static EncodeFn fn = nullptr;
    if (!fn) {
        void* f = nullptr;
        cudaDriverEntryPointQueryResult st;
        cudaGetDriverEntryPoint("cuTensorMapEncodeTiled", &f, cudaEnableDefault, &st);
        fn = (EncodeFn)f;
        cudaFuncSetAttribute(fused_kernel, cudaFuncAttributeMaxDynamicSharedMemorySize, SMEM_BYTES);
    }
    CUtensorMap ckv, wq, wuk, wuv, wo, wg, wu, wm, xm;
    make_3d(fn, &ckv, d_in[1], 512, 2048, 128, 1);
    make_3d(fn, &xm, d_in[0], 512, 2048, 64);
    make_3d(fn, &wq, d_in[2], 4096, 512);
    make_3d(fn, &wuk, d_in[3], 4096, 512);
    make_3d(fn, &wuv, d_in[4], 4096, 512);
    make_3d(fn, &wo, d_in[5], 512, 4096);
    make_3d(fn, &wg, d_in[8], 1792, 512, 256, 1);
    make_3d(fn, &wu, d_in[9], 1792, 512, 256, 1);
    make_3d(fn, &wm, d_in[12], 3072, 512, 64, 4);
    Params p;
    p.x = (const bf16*)d_in[0];
    p.ckv = (const bf16*)d_in[1];
    p.wo = (const bf16*)d_in[5];
    p.wr = (const bf16*)d_in[7];
    p.wdown = (const bf16*)d_in[10];
    p.c = (const bf16*)d_in[11];
    p.out = (bf16*)d_out;
    p.zero = 0;
    fused_kernel<<<NCTA + NSPARE, 384, SMEM_BYTES>>>(ckv, wq, wuk, wuv, wo, wg, wu, wm, xm, p);
}
```

```cpp
#include <cuda.h>
#include <cuda_bf16.h>
#include <cuda_runtime.h>
#include <stdint.h>
#include <stdio.h>

namespace {

typedef __nv_bfloat16 bf16;
typedef unsigned long long u64;

constexpr int NCTA = 128, NSPARE = 4;
constexpr int SLOT = 32768;
constexpr int SM_BAR = 7 * SLOT;
constexpr int BAR_FULL = SM_BAR;
constexpr int BAR_EMPTY = BAR_FULL + 8 * 7;
constexpr int BAR_DONE = BAR_EMPTY + 8 * 7;
constexpr int BAR_FLAG = BAR_DONE + 8 * 9;
constexpr int BAR_PF = BAR_FLAG + 8 * 9;
constexpr int BAR_END = BAR_PF + 8;
constexpr int BAR_BEST = BAR_END + 8;
constexpr int SM_EP = BAR_END + 40;
constexpr int SM_RED = SM_BAR + 384;
constexpr int SM_TAB = SM_BAR + 1024;
constexpr int SMEM_BYTES = SM_BAR + 3072;
constexpr int NFFN = 112;
#define HINT 479
constexpr u64 L2_NORMAL = 0x1000000000000000ull, L2_FIRST = 0x12F0000000000000ull;
#define PFA 8
#define PFB 6
#define POLL_NS 50
#define MSPLIT 13
#define NSH 1
#define XPF 1
#define KSLEEP 400
#define YSLEEP 50
#define YPRE 400
#define SSLEEP 50
#define PSLEEP 100
#define KVG 7
#define EARLY2 4
#define OFF 2
#define KN 16
#define KSLEEP2 60
#define EARLY 7
constexpr uint32_t SPIN_LIMIT = 1u << 22;
constexpr uint32_t ONE2 = 0x3f803f80u;

struct Sync {
    uint32_t cnt[16 * 8 * 8];
    uint32_t ctxcnt[16 * 32];
    uint32_t epoch[32];
};

__device__ __align__(1024) uint8_t g_img[2 * 512 * SLOT];
#define g_KV g_img
#define g_ctx (g_img + 512 * SLOT)
__device__ __align__(1024) uint8_t g_h[16 * 4 * SLOT];
constexpr int OB = 1248, OB_STAT = 1024, OB_Y = 1088, OB_KEY = 1216;
__device__ __align__(1024) uint4 g_out[128 * OB];
__device__ __align__(1024) bf16 g_mod[3072];
__device__ __align__(1024) uint32_t g_mod1[1024];
__device__ __align__(1024) uint4 g_cand[128 * 192];
__device__ __align__(1024) uint8_t g_wf[NFFN * SLOT];
__device__ __align__(1024) uint4 g_x2[128 * 1024];
__device__ __align__(1024) Sync g_sync;
#define TS(i)

#define TT(i)
#define PT()

struct Params {
    const bf16 *x, *ckv, *wo, *wr, *wdown, *c;
    bf16* out;
    int zero;
};

__device__ __forceinline__ void mbar_init(uint32_t bar, uint32_t cnt) {
    asm volatile("mbarrier.init.shared::cta.b64 [%0], %1;" ::"r"(bar), "r"(cnt) : "memory");
}
__device__ __forceinline__ void mbar_wait(uint32_t bar, uint32_t parity) {
    asm volatile("{\n.reg .pred p;\nL_%=:\nmbarrier.try_wait.parity.shared::cta.b64 p, [%0], %1;\n@!p bra L_%=;\n}" ::"r"(bar), "r"(parity) : "memory");
}
__device__ __forceinline__ void mbar_sleep(uint32_t bar) {
    if ((threadIdx.x & 31) == 0)
        asm volatile("{\n.reg .pred p;\nL_%=:\nmbarrier.try_wait.parity.shared::cta.b64 p, [%0], 0, 100000;\n@!p bra L_%=;\n}" ::"r"(bar) : "memory");
    __syncwarp();
}
__device__ __forceinline__ void mbar_watch(uint32_t bar, uint32_t parity) {
    asm volatile("{\n.reg .pred p;\n.reg .u32 n;\nmov.u32 n, 0;\n"
                 "L_%=:\nmbarrier.try_wait.parity.shared::cta.b64 p, [%0], %1;\n@p bra D_%=;\n"
                 "add.u32 n, n, 1;\nsetp.lt.u32 p, n, %2;\n@p bra L_%=;\ntrap;\nD_%=:\n}"
                 ::"r"(bar), "r"(parity), "n"(SPIN_LIMIT) : "memory");
}
__device__ __forceinline__ void step_watch(uint32_t a, uint32_t step) {
    asm volatile("{\n.reg .pred p;\n.reg .u32 n, v;\nmov.u32 n, 0;\n"
                 "L_%=:\nld.volatile.shared.u32 v, [%0];\nsetp.ge.u32 p, v, %1;\n@p bra D_%=;\nnanosleep.u32 400;\n"
                 "add.u32 n, n, 1;\nsetp.lt.u32 p, n, %2;\n@p bra L_%=;\ntrap;\nD_%=:\n}"
                 ::"r"(a), "r"(step), "n"(SPIN_LIMIT) : "memory");
}
__device__ __forceinline__ void mbar_arrive_if(uint32_t bar, bool on) {
    asm volatile("{\n.reg .pred p;\nsetp.ne.s32 p, %1, 0;\n@p mbarrier.arrive.shared::cta.b64 _, [%0];\n}" ::"r"(bar), "r"((int)on) : "memory");
}
__device__ __forceinline__ void tma3d_prefetch(const CUtensorMap* m, int row, int cb) {
    asm volatile("{\n.reg .pred p;\nelect.sync _|p, 0xffffffff;\n@p cp.async.bulk.prefetch.tensor.3d.L2.global [%0, {%1, %2, %3}];\n}"
                 ::"l"(m), "r"(0), "r"(row), "r"(cb) : "memory");
}
__device__ __forceinline__ void l2_prefetch(const void* p, uint32_t bytes) {
    asm volatile("{\n.reg .pred p;\nelect.sync _|p, 0xffffffff;\n@p cp.async.bulk.prefetch.L2.global [%0], %1;\n}" ::"l"(p), "r"(bytes) : "memory");
}
__device__ __forceinline__ void bulk_store(void* dst, uint32_t src, uint32_t bytes, bool first) {
    asm volatile("{\n.reg .pred p;\nelect.sync _|p, 0xffffffff;\n@p cp.async.bulk.global.shared::cta.bulk_group.L2::cache_hint [%0], [%1], %2, %3;\n}"
                 ::"l"(dst), "r"(src), "r"(bytes), "l"(first ? L2_FIRST : L2_NORMAL) : "memory");
}
__device__ __forceinline__ void flag_wait(const uint32_t* f, uint32_t target) {
    asm volatile("{\n.reg .pred p;\n.reg .u32 v;\n"
                 "L_%=:\nld.acquire.gpu.global.u32 v, [%0];\nsub.u32 v, v, %1;\nsetp.lt.s32 p, v, 0;\n@p nanosleep.u32 100;\n@p bra L_%=;\n}"
                 ::"l"(f), "r"(target) : "memory");
}
__device__ __forceinline__ uint4 ld_poll(const uint4* p) {
    uint4 v;
    asm volatile("{\n.reg .b128 t;\nld.relaxed.gpu.global.b128 t, [%4];\nmov.b128 {%0, %1, %2, %3}, t;\n}"
                 : "=r"(v.x), "=r"(v.y), "=r"(v.z), "=r"(v.w) : "l"(p) : "memory");
    return v;
}
__device__ __forceinline__ void st_pub(uint4* p, uint4 v, bool on) {
    asm volatile("{\n.reg .pred p;\n.reg .b128 t;\nsetp.ne.s32 p, %5, 0;\nmov.b128 t, {%1, %2, %3, %4};\n@p st.relaxed.gpu.global.b128 [%0], t;\n}"
                 ::"l"(p), "r"(v.x), "r"(v.y), "r"(v.z), "r"(v.w), "r"((int)on) : "memory");
}
__device__ __forceinline__ void st_pub(uint32_t* p, uint32_t v, bool on) {
    asm volatile("{\n.reg .pred p;\nsetp.ne.s32 p, %2, 0;\n@p st.relaxed.gpu.global.u32 [%0], %1;\n}" ::"l"(p), "r"(v), "r"((int)on) : "memory");
}
__device__ __forceinline__ bool poll_done(bool ok, uint32_t ns) {
    const int done = __all_sync(0xffffffffu, ok);
    asm volatile("{\n.reg .pred p;\nsetp.eq.s32 p, %0, 0;\n@p nanosleep.u32 %1;\n}" ::"r"(done), "r"(ns) : "memory");
    return done;
}
__device__ __forceinline__ void flag_add(uint32_t* p) {
    asm volatile("red.release.gpu.global.add.u32 [%0], 1;" ::"l"(p) : "memory");
}
__device__ __forceinline__ uint32_t lds32(uint32_t a) {
    uint32_t v;
    asm volatile("ld.shared.u32 %0, [%1];" : "=r"(v) : "r"(a) : "memory");
    return v;
}
__device__ __forceinline__ uint4 lds128(uint32_t a) {
    uint4 v;
    asm volatile("ld.shared.v4.u32 {%0, %1, %2, %3}, [%4];" : "=r"(v.x), "=r"(v.y), "=r"(v.z), "=r"(v.w) : "r"(a) : "memory");
    return v;
}
__device__ __forceinline__ void sched_fence(uint32_t& v, uint32_t z) {
    uint32_t ck;
    asm volatile("mov.u32 %0, %%clock;" : "=r"(ck)::"memory");
    v ^= ck & z;
}
__device__ __forceinline__ void fence_async_global() { asm volatile("fence.proxy.async.global;" ::: "memory"); }
__device__ __forceinline__ void fence_async_smem() { asm volatile("fence.proxy.async.shared::cta;" ::: "memory"); }
__device__ __forceinline__ void bar_sync(int id, int n) { asm volatile("bar.sync %0, %1;" ::"r"(id), "r"(n) : "memory"); }
__device__ __forceinline__ void bar_arrive(int id, int n) { asm volatile("bar.arrive %0, %1;" ::"r"(id), "r"(n) : "memory"); }
__device__ __forceinline__ void wg_fence() { asm volatile("wgmma.fence.sync.aligned;" ::: "memory"); }
__device__ __forceinline__ void wg_commit() { asm volatile("wgmma.commit_group.sync.aligned;" ::: "memory"); }
template <int N> __device__ __forceinline__ void wg_wait() { asm volatile("wgmma.wait_group.sync.aligned %0;" ::"n"(N) : "memory"); }
template <int N> __device__ __forceinline__ void reg_fence(float (&d)[N]) {
#pragma unroll
    for (int i = 0; i < N; i++) asm volatile("" : "+f"(d[i])::"memory");
}
template <int N> __device__ __forceinline__ void reg_fence(uint32_t (&d)[N]) {
#pragma unroll
    for (int i = 0; i < N; i++) asm volatile("" : "+r"(d[i])::"memory");
}
__device__ __forceinline__ uint32_t desc_k(uint32_t a) { return ((a & 0x3ffff) >> 4) | (1u << 16); }
__device__ __forceinline__ uint32_t desc_mn(uint32_t a) { return ((a & 0x3ffff) >> 4) | (1024u << 16); }

__device__ __forceinline__ uint64_t desc64(uint32_t lo, uint32_t hi) {
    uint64_t d;
    asm("mov.b64 %0, {%1, %2};" : "=l"(d) : "r"(lo), "r"(hi));
    return d;
}
__device__ __forceinline__ void desc_add(uint64_t& d, uint32_t x) { asm("add.u64 %0, %0, %1;" : "+l"(d) : "l"((uint64_t)x)); }

template <int TB>
__device__ __forceinline__ void wgmma_ss128(float (&d)[64], uint64_t da, uint64_t db, int acc) {
    asm volatile("{\n.reg .pred p;\nsetp.ne.b32 p, %66, 0;\n"
        "wgmma.mma_async.sync.aligned.m64n128k16.f32.bf16.bf16 {%0, %1, %2, %3, %4, %5, %6, %7, %8, %9, %10, %11, %12, %13, %14, %15, %16, %17, %18, %19, %20, %21, %22, %23, %24, %25, %26, %27, %28, %29, %30, %31, %32, %33, %34, %35, %36, %37, %38, %39, %40, %41, %42, %43, %44, %45, %46, %47, %48, %49, %50, %51, %52, %53, %54, %55, %56, %57, %58, %59, %60, %61, %62, %63}, %64, %65, p, 1, 1, 0, %67;\n}"
        : "+f"(d[0]), "+f"(d[1]), "+f"(d[2]), "+f"(d[3]), "+f"(d[4]), "+f"(d[5]), "+f"(d[6]), "+f"(d[7]), "+f"(d[8]), "+f"(d[9]), "+f"(d[10]), "+f"(d[11]), "+f"(d[12]), "+f"(d[13]), "+f"(d[14]), "+f"(d[15]), "+f"(d[16]), "+f"(d[17]), "+f"(d[18]), "+f"(d[19]), "+f"(d[20]), "+f"(d[21]), "+f"(d[22]), "+f"(d[23]), "+f"(d[24]), "+f"(d[25]), "+f"(d[26]), "+f"(d[27]), "+f"(d[28]), "+f"(d[29]), "+f"(d[30]), "+f"(d[31]), "+f"(d[32]), "+f"(d[33]), "+f"(d[34]), "+f"(d[35]), "+f"(d[36]), "+f"(d[37]), "+f"(d[38]), "+f"(d[39]), "+f"(d[40]), "+f"(d[41]), "+f"(d[42]), "+f"(d[43]), "+f"(d[44]), "+f"(d[45]), "+f"(d[46]), "+f"(d[47]), "+f"(d[48]), "+f"(d[49]), "+f"(d[50]), "+f"(d[51]), "+f"(d[52]), "+f"(d[53]), "+f"(d[54]), "+f"(d[55]), "+f"(d[56]), "+f"(d[57]), "+f"(d[58]), "+f"(d[59]), "+f"(d[60]), "+f"(d[61]), "+f"(d[62]), "+f"(d[63])
        : "l"(da), "l"(db), "r"(acc), "n"(TB));
}
template <int TB>
__device__ __forceinline__ void wgmma_ss128_init(float (&d)[64], uint64_t da, uint64_t db) {
    asm volatile("{\n.reg .pred p;\nsetp.ne.b32 p, 0, 0;\n"
        "wgmma.mma_async.sync.aligned.m64n128k16.f32.bf16.bf16 {%0, %1, %2, %3, %4, %5, %6, %7, %8, %9, %10, %11, %12, %13, %14, %15, %16, %17, %18, %19, %20, %21, %22, %23, %24, %25, %26, %27, %28, %29, %30, %31, %32, %33, %34, %35, %36, %37, %38, %39, %40, %41, %42, %43, %44, %45, %46, %47, %48, %49, %50, %51, %52, %53, %54, %55, %56, %57, %58, %59, %60, %61, %62, %63}, %64, %65, p, 1, 1, 0, %66;\n}"
        : "=f"(d[0]), "=f"(d[1]), "=f"(d[2]), "=f"(d[3]), "=f"(d[4]), "=f"(d[5]), "=f"(d[6]), "=f"(d[7]), "=f"(d[8]), "=f"(d[9]), "=f"(d[10]), "=f"(d[11]), "=f"(d[12]), "=f"(d[13]), "=f"(d[14]), "=f"(d[15]), "=f"(d[16]), "=f"(d[17]), "=f"(d[18]), "=f"(d[19]), "=f"(d[20]), "=f"(d[21]), "=f"(d[22]), "=f"(d[23]), "=f"(d[24]), "=f"(d[25]), "=f"(d[26]), "=f"(d[27]), "=f"(d[28]), "=f"(d[29]), "=f"(d[30]), "=f"(d[31]), "=f"(d[32]), "=f"(d[33]), "=f"(d[34]), "=f"(d[35]), "=f"(d[36]), "=f"(d[37]), "=f"(d[38]), "=f"(d[39]), "=f"(d[40]), "=f"(d[41]), "=f"(d[42]), "=f"(d[43]), "=f"(d[44]), "=f"(d[45]), "=f"(d[46]), "=f"(d[47]), "=f"(d[48]), "=f"(d[49]), "=f"(d[50]), "=f"(d[51]), "=f"(d[52]), "=f"(d[53]), "=f"(d[54]), "=f"(d[55]), "=f"(d[56]), "=f"(d[57]), "=f"(d[58]), "=f"(d[59]), "=f"(d[60]), "=f"(d[61]), "=f"(d[62]), "=f"(d[63])
        : "l"(da), "l"(db), "n"(TB));
}
template <int TB>
__device__ __forceinline__ void wgmma_ss64(float (&d)[32], uint64_t da, uint64_t db, int acc) {
    asm volatile("{\n.reg .pred p;\nsetp.ne.b32 p, %34, 0;\n"
        "wgmma.mma_async.sync.aligned.m64n64k16.f32.bf16.bf16 {%0, %1, %2, %3, %4, %5, %6, %7, %8, %9, %10, %11, %12, %13, %14, %15, %16, %17, %18, %19, %20, %21, %22, %23, %24, %25, %26, %27, %28, %29, %30, %31}, %32, %33, p, 1, 1, 0, %35;\n}"
        : "+f"(d[0]), "+f"(d[1]), "+f"(d[2]), "+f"(d[3]), "+f"(d[4]), "+f"(d[5]), "+f"(d[6]), "+f"(d[7]), "+f"(d[8]), "+f"(d[9]), "+f"(d[10]), "+f"(d[11]), "+f"(d[12]), "+f"(d[13]), "+f"(d[14]), "+f"(d[15]), "+f"(d[16]), "+f"(d[17]), "+f"(d[18]), "+f"(d[19]), "+f"(d[20]), "+f"(d[21]), "+f"(d[22]), "+f"(d[23]), "+f"(d[24]), "+f"(d[25]), "+f"(d[26]), "+f"(d[27]), "+f"(d[28]), "+f"(d[29]), "+f"(d[30]), "+f"(d[31])
        : "l"(da), "l"(db), "r"(acc), "n"(TB));
}
template <int TB>
__device__ __forceinline__ void wgmma_ss64_init(float (&d)[32], uint64_t da, uint64_t db) {
    asm volatile("{\n.reg .pred p;\nsetp.ne.b32 p, 0, 0;\n"
        "wgmma.mma_async.sync.aligned.m64n64k16.f32.bf16.bf16 {%0, %1, %2, %3, %4, %5, %6, %7, %8, %9, %10, %11, %12, %13, %14, %15, %16, %17, %18, %19, %20, %21, %22, %23, %24, %25, %26, %27, %28, %29, %30, %31}, %32, %33, p, 1, 1, 0, %34;\n}"
        : "=f"(d[0]), "=f"(d[1]), "=f"(d[2]), "=f"(d[3]), "=f"(d[4]), "=f"(d[5]), "=f"(d[6]), "=f"(d[7]), "=f"(d[8]), "=f"(d[9]), "=f"(d[10]), "=f"(d[11]), "=f"(d[12]), "=f"(d[13]), "=f"(d[14]), "=f"(d[15]), "=f"(d[16]), "=f"(d[17]), "=f"(d[18]), "=f"(d[19]), "=f"(d[20]), "=f"(d[21]), "=f"(d[22]), "=f"(d[23]), "=f"(d[24]), "=f"(d[25]), "=f"(d[26]), "=f"(d[27]), "=f"(d[28]), "=f"(d[29]), "=f"(d[30]), "=f"(d[31])
        : "l"(da), "l"(db), "n"(TB));
}
__device__ __forceinline__ void wgmma_rs128(float (&d)[64], uint32_t a0, uint32_t a1, uint32_t a2, uint32_t a3, uint64_t db, int acc) {
    asm volatile("{\n.reg .pred p;\nsetp.ne.b32 p, %69, 0;\n"
        "wgmma.mma_async.sync.aligned.m64n128k16.f32.bf16.bf16 {%0, %1, %2, %3, %4, %5, %6, %7, %8, %9, %10, %11, %12, %13, %14, %15, %16, %17, %18, %19, %20, %21, %22, %23, %24, %25, %26, %27, %28, %29, %30, %31, %32, %33, %34, %35, %36, %37, %38, %39, %40, %41, %42, %43, %44, %45, %46, %47, %48, %49, %50, %51, %52, %53, %54, %55, %56, %57, %58, %59, %60, %61, %62, %63}, {%64, %65, %66, %67}, %68, p, 1, 1, 1;\n}"
        : "+f"(d[0]), "+f"(d[1]), "+f"(d[2]), "+f"(d[3]), "+f"(d[4]), "+f"(d[5]), "+f"(d[6]), "+f"(d[7]), "+f"(d[8]), "+f"(d[9]), "+f"(d[10]), "+f"(d[11]), "+f"(d[12]), "+f"(d[13]), "+f"(d[14]), "+f"(d[15]), "+f"(d[16]), "+f"(d[17]), "+f"(d[18]), "+f"(d[19]), "+f"(d[20]), "+f"(d[21]), "+f"(d[22]), "+f"(d[23]), "+f"(d[24]), "+f"(d[25]), "+f"(d[26]), "+f"(d[27]), "+f"(d[28]), "+f"(d[29]), "+f"(d[30]), "+f"(d[31]), "+f"(d[32]), "+f"(d[33]), "+f"(d[34]), "+f"(d[35]), "+f"(d[36]), "+f"(d[37]), "+f"(d[38]), "+f"(d[39]), "+f"(d[40]), "+f"(d[41]), "+f"(d[42]), "+f"(d[43]), "+f"(d[44]), "+f"(d[45]), "+f"(d[46]), "+f"(d[47]), "+f"(d[48]), "+f"(d[49]), "+f"(d[50]), "+f"(d[51]), "+f"(d[52]), "+f"(d[53]), "+f"(d[54]), "+f"(d[55]), "+f"(d[56]), "+f"(d[57]), "+f"(d[58]), "+f"(d[59]), "+f"(d[60]), "+f"(d[61]), "+f"(d[62]), "+f"(d[63])
        : "r"(a0), "r"(a1), "r"(a2), "r"(a3), "l"(db), "r"(acc));
}

__device__ __forceinline__ uint32_t pack2(float lo, float hi) {
    uint32_t r;
    asm("cvt.rn.bf16x2.f32 %0, %1, %2;" : "=r"(r) : "f"(hi), "f"(lo));
    return r;
}
__device__ __forceinline__ float bf_lo(uint32_t v) { return __uint_as_float(v << 16); }
__device__ __forceinline__ float bf_hi(uint32_t v) { return __uint_as_float(v & 0xffff0000u); }
__device__ __forceinline__ float rbf(float v) { return bf_lo(pack2(v, v)); }
__device__ __forceinline__ uint32_t badd(uint32_t a, uint32_t b) {
    uint32_t r;
    asm("add.rn.bf16x2 %0, %1, %2;" : "=r"(r) : "r"(a), "r"(b));
    return r;
}
__device__ __forceinline__ uint32_t bsub(uint32_t a, uint32_t b) {
    uint32_t r;
    asm("sub.rn.bf16x2 %0, %1, %2;" : "=r"(r) : "r"(a), "r"(b));
    return r;
}
__device__ __forceinline__ uint32_t bmul(uint32_t a, uint32_t b) {
    uint32_t r;
    asm("mul.rn.bf16x2 %0, %1, %2;" : "=r"(r) : "r"(a), "r"(b));
    return r;
}
__device__ __forceinline__ uint32_t ln_apply(uint32_t x, uint32_t mb, float rs, uint32_t scale, uint32_t shift) {
    const uint32_t d = bsub(x, mb);
    return badd(bmul(pack2(bf_lo(d) * rs, bf_hi(d) * rs), scale), shift);
}
__device__ __forceinline__ float ex2(float v) {
    float r;
    asm("ex2.approx.ftz.f32 %0, %1;" : "=f"(r) : "f"(v));
    return r;
}
__device__ __forceinline__ float rcp(float v) {
    float r;
    asm("rcp.approx.ftz.f32 %0, %1;" : "=f"(r) : "f"(v));
    return r;
}
__device__ __forceinline__ float sqrt_fast(float v) {
    float r;
    asm("sqrt.approx.ftz.f32 %0, %1;" : "=f"(r) : "f"(v));
    return r;
}
__device__ __forceinline__ float ln_rstd(float var) { return rcp(rbf(sqrt_fast(rbf(rbf(var) + 1e-5f)))); }
__device__ __forceinline__ float sigmoid(float v) { return rcp(1.f + ex2(-1.4426950408889634f * v)); }
__device__ __forceinline__ float quad_sum(float v) {
    v += __shfl_xor_sync(0xffffffffu, v, 1);
    return v + __shfl_xor_sync(0xffffffffu, v, 2);
}

constexpr uint32_t HI_128 = 0x40000040u, HI_IMG = 0x80000080u, HI_Q = 0x80000040u;
template <int M, int RH>
__device__ __forceinline__ uint4 img_pack(const float (&d)[64], float s) {
    uint4 v;
    v.x = pack2(d[16 * M + 2 * RH] * s, d[16 * M + 2 * RH + 1] * s);
    v.y = pack2(d[16 * M + 4 + 2 * RH] * s, d[16 * M + 5 + 2 * RH] * s);
    v.z = pack2(d[16 * M + 8 + 2 * RH] * s, d[16 * M + 9 + 2 * RH] * s);
    v.w = pack2(d[16 * M + 12 + 2 * RH] * s, d[16 * M + 13 + 2 * RH] * s);
    return v;
}
template <int M>
__device__ __forceinline__ void img_store_global(uint32_t img, uint32_t toff, const float (&d)[64], float s0, float s1) {
    uint4* p = reinterpret_cast<uint4*>(g_img + (img + toff)) + M * 32;
    p[0] = img_pack<M, 0>(d, s0);
    p[128] = img_pack<M, 1>(d, s1);
}
__device__ __forceinline__ void sts128(uint32_t a, uint4 v) {
    asm volatile("st.shared.v4.b32 [%0], {%1, %2, %3, %4};" ::"r"(a), "r"(v.x), "r"(v.y), "r"(v.z), "r"(v.w) : "memory");
}
constexpr float SM_C = 0.08838834764831845f * 1.4426950408889634f;
__device__ __forceinline__ float pack2f(float lo, float hi) {
    float r;
    asm("{\n.reg .b32 t;\ncvt.rn.bf16x2.f32 t, %1, %2;\nmov.b32 %0, t;\n}" : "=f"(r) : "f"(hi), "f"(lo));
    return r;
}
template <int M, bool SCALE, bool PARK>
__device__ __forceinline__ void pack_group(float (&d)[64], float (&v)[8], float s0, float s1) {
#pragma unroll
    for (int i = 0; i < 8; i++) {
        const int k = 16 * M + 4 * (i & 3) + 2 * (i >> 2);
        v[i] = SCALE ? pack2f(d[k] * (i < 4 ? s0 : s1), d[k + 1] * (i < 4 ? s0 : s1)) : pack2f(d[k], d[k + 1]);
        if (PARK && M > 0) d[16 * (M > 0 ? M - 1 : 0) + i] = v[i];
    }
}
__device__ __forceinline__ uint32_t q_off(uint32_t toff) {
    asm volatile("" : "+r"(toff));
    return (((toff >> 1) & ~2047u) ^ 8192) + (toff & 511);
}
template <int M>
__device__ __forceinline__ void ctx_store_part(float4* p, float (&d)[64], float i0, float i1) {
    float v[8];
    pack_group<M, true, true>(d, v, i0, i1);
    p[M * 32] = make_float4(v[0], v[1], v[2], v[3]);
    p[M * 32 + 128] = make_float4(v[4], v[5], v[6], v[7]);
}
__device__ __forceinline__ void ctx_store(uint32_t img, uint32_t toff, float (&o)[64], float i0, float i1) {
    asm volatile("" : "+r"(toff));
    float4* p = reinterpret_cast<float4*>(g_img + (img + toff));
    ctx_store_part<0>(p, o, i0, i1); ctx_store_part<1>(p, o, i0, i1); ctx_store_part<2>(p, o, i0, i1); ctx_store_part<3>(p, o, i0, i1);
}

__device__ __forceinline__ void slot_wait(uint32_t bars, uint32_t& ph, uint32_t slot) {
    mbar_wait(bars + 8 * slot, (ph >> slot) & 1);
    ph ^= 1u << slot;
}
__device__ __forceinline__ void release_if(uint32_t eb, uint32_t slot, bool on) {
    asm volatile("{\n.reg .pred p;\nsetp.ne.s32 p, %1, 0;\n@p mbarrier.arrive.shared::cluster.b64 _, [%0];\n}" ::"r"(eb + 8 * slot), "r"((int)on) : "memory");
}
__device__ __forceinline__ void slot_expect(uint32_t sb, uint32_t slot) {
    asm volatile("{\n.reg .pred p;\nelect.sync _|p, 0xffffffff;\n@p mbarrier.arrive.expect_tx.shared::cta.b64 _, [%0], 32768;\n}"
                 ::"r"(sb + BAR_FULL + 8 * slot) : "memory");
}
__device__ __forceinline__ void slot_acquire(uint32_t sb, uint32_t& ph, uint32_t slot) {
    slot_wait(sb + BAR_EMPTY, ph, slot);
    slot_expect(sb, slot);
}
__device__ __forceinline__ void load_bulk(uint32_t sb, uint32_t slot, uint32_t off, const void* src, uint32_t bytes, bool both, bool first) {
    if (both)
        asm volatile("{\n.reg .pred p;\nelect.sync _|p, 0xffffffff;\n"
                     "@p cp.async.bulk.shared::cluster.global.mbarrier::complete_tx::bytes.multicast::cluster.L2::cache_hint [%0], [%1], %5, [%2], %4, %3;\n}"
                     ::"r"(sb + slot * SLOT + off), "l"(src), "r"(sb + BAR_FULL + 8 * slot), "l"(first ? L2_FIRST : L2_NORMAL), "h"((uint16_t)3),
                     "r"(bytes) : "memory");
    else
        asm volatile("{\n.reg .pred p;\nelect.sync _|p, 0xffffffff;\n"
                     "@p cp.async.bulk.shared::cluster.global.mbarrier::complete_tx::bytes.L2::cache_hint [%0], [%1], %4, [%2], %3;\n}"
                     ::"r"(sb + slot * SLOT + off), "l"(src), "r"(sb + BAR_FULL + 8 * slot), "l"(first ? L2_FIRST : L2_NORMAL), "r"(bytes) : "memory");
}
__device__ __forceinline__ void load_tile(uint32_t sb, uint32_t slot, uint32_t off, const CUtensorMap* m, int row, int cb, bool both, bool first) {
    if (both)
        asm volatile("{\n.reg .pred p;\nelect.sync _|p, 0xffffffff;\n"
                     "@p cp.async.bulk.tensor.3d.shared::cluster.global.mbarrier::complete_tx::bytes.multicast::cluster.L2::cache_hint [%0], [%1, {%3, %4, %5}], [%2], %7, %6;\n}"
                     ::"r"(sb + slot * SLOT + off), "l"(m), "r"(sb + BAR_FULL + 8 * slot), "r"(0), "r"(row), "r"(cb),
                     "l"(first ? L2_FIRST : L2_NORMAL), "h"((uint16_t)3) : "memory");
    else
        asm volatile("{\n.reg .pred p;\nelect.sync _|p, 0xffffffff;\n"
                     "@p cp.async.bulk.tensor.3d.shared::cluster.global.mbarrier::complete_tx::bytes.L2::cache_hint [%0], [%1, {%3, %4, %5}], [%2], %6;\n}"
                     ::"r"(sb + slot * SLOT + off), "l"(m), "r"(sb + BAR_FULL + 8 * slot), "r"(0), "r"(row), "r"(cb),
                     "l"(first ? L2_FIRST : L2_NORMAL) : "memory");
}
__device__ __forceinline__ uint32_t ring_next(uint32_t r) { return r == 4 ? 0 : r + 1; }
__device__ __forceinline__ uint32_t w_table(int hp) { return hp ? 0x3104u : 0x4210u; }
__device__ __forceinline__ uint32_t a_table(int hp) { return hp ? 0x625u : 0x635u; }
__device__ __forceinline__ uint32_t a_next(uint32_t& t) {
    const uint32_t s = t & 15;
    t = (t >> 4) | (s << 8);
    return s;
}
constexpr uint32_t O_TABLE = 0x1604235u;
constexpr uint32_t SL_X = OFF == 0 ? 4 : OFF == 1 ? 3 : 1, SL_WD = OFF == 0 ? 6 : OFF == 1 ? 4 : 3, SL_WF = OFF == 0 ? 5 : OFF == 1 ? 6 : 4;
__device__ __forceinline__ uint32_t o_next(uint32_t& t) {
    const uint32_t s = t & 15;
    t = (t >> 4) | (s << 24);
    return s;
}
__device__ __forceinline__ int o_head(int i, int kh) { return i < 16 ? 4 * (i & 7) + 2 * (kh ^ 1) + (i >> 3) : 29 + 2 * kh; }

template <bool INIT>
__device__ __forceinline__ void gemm_issue(float (&d)[64], uint32_t a, uint32_t b, int acc, bool img) {
    uint64_t da = desc64(a, img ? HI_IMG : HI_128), db = desc64(b, HI_128);
    wg_fence();
#pragma unroll
    for (int k = 0; k < 8; k++) {
        if (INIT && k == 0) wgmma_ss128_init<1>(d, da, db);
        else wgmma_ss128<1>(d, da, db, k ? 1 : acc);
        desc_add(da, !(k & 1) ? 2 : img ? 30 : k == 3 ? 1018 : 2);
        desc_add(db, 128);
    }
    wg_commit();
}

__device__ __forceinline__ void step_retire(uint32_t eb, bool rel, uint32_t pend) {
    wg_wait<0>();
    release_if(eb, pend & 7, rel && (pend & 7) != 7);
    release_if(eb, pend >> 4, rel && pend < 0x70);
}
template <bool ODD>
__device__ __forceinline__ void proj_tile(float (&acc)[64], float (&prev)[64], int t, int q0, uint32_t sb, int wg, uint32_t eb, bool rel, uint32_t& fph,
                                          uint32_t wtab, uint32_t& atab, uint32_t& pend, uint32_t prev_img, uint32_t toff, float s0, float s1,
                                          uint32_t (&v)[32]) {
    const uint32_t a0 = desc_k(sb + (wg ^ (ODD && t == 5)) * 8192), b0 = desc_mn(sb);
    int q = q0;
#pragma unroll 1
    do {
        const uint32_t ws = (wtab >> (4 * q)) & 15, as = a_next(atab);
        if (!ODD && t != 2) slot_wait(sb + BAR_FULL, fph, ws);
        slot_wait(sb + BAR_FULL, fph, as);
        step_retire(eb, rel, pend);
        if (ODD && q == 2 && t == 5) {
            const uint32_t a = sb + 5 * SLOT + q_off(toff);
#pragma unroll
            for (int i = 0; i < 8; i++) sts128(a + (i >> 2) * 16384 + (i & 2) * 256 + (i & 1) * 1024, make_uint4(v[4 * i], v[4 * i + 1], v[4 * i + 2], v[4 * i + 3]));
        }
        bar_sync(1 + wg, 256);
        gemm_issue<false>(acc, a0 + as * (SLOT / 16), b0 + ws * (SLOT / 16), q, false);
        bar_arrive(2 - wg, 256);
        pend = (ODD && q == 1 && t == 5 ? 7 : as) | (ODD && t != 1 ? ws : 7) << 4;
        wg_wait<1>();
        reg_fence(prev);
        if (ODD && t == 5) {
            if (q == 0) {
#pragma unroll
                for (int i = 0; i < 32; i++) {
                    const int k = 16 * (i >> 3) + 4 * (i & 3) + ((i >> 1) & 2);
                    v[i] = pack2(prev[k], prev[k + 1]);
                }
            }
        } else {
            if (q == 0) img_store_global<0>(prev_img, toff, prev, s0, s1);
            if (q == 1) img_store_global<1>(prev_img, toff, prev, s0, s1);
            if (q == 2) img_store_global<2>(prev_img, toff, prev, s0, s1);
            if (q == 3) img_store_global<3>(prev_img, toff, prev, s0, s1);
        }
    } while (++q < (ODD && t == 5 ? 3 : 4));
}

__device__ __forceinline__ void qk_issue(float (&s)[64], uint32_t q, uint32_t k) {
    wg_fence();
    uint64_t da = desc64(q, HI_Q), db = desc64(k, HI_IMG);
    wgmma_ss128_init<0>(s, da, db);
#pragma unroll
    for (int i = 1; i < 8; i++) {
        desc_add(da, (i & 1) ? 2 : i == 4 ? 990 : 30);
        desc_add(db, (i & 1) ? 2 : 30);
        wgmma_ss128<0>(s, da, db, 1);
    }
    wg_commit();
}
__device__ __forceinline__ void qk_issue(float (&s)[32], uint32_t q, uint32_t k) {
    wg_fence();
    uint64_t da = desc64(q, HI_Q), db = desc64(k, HI_IMG);
    wgmma_ss64_init<0>(s, da, db);
#pragma unroll
    for (int i = 1; i < 8; i++) {
        desc_add(da, (i & 1) ? 2 : i == 4 ? 990 : 30);
        desc_add(db, (i & 1) ? 2 : 30);
        wgmma_ss64<0>(s, da, db, 1);
    }
    wg_commit();
}
__device__ __forceinline__ void pv_issue(float (&o)[64], const uint32_t (&p)[32], uint32_t v, int acc, bool half) {
    uint64_t db = desc64(v, HI_IMG);
    if (half) {
        asm volatile("// half" ::: "memory");
        wg_fence();
#pragma unroll
        for (int i = 0; i < 4; i++) {
            wgmma_rs128(o, p[4 * i], p[4 * i + 1], p[4 * i + 2], p[4 * i + 3], db, i ? 1 : acc);
            desc_add(db, 256);
        }
        wg_commit();
        asm volatile("// half" ::: "memory");
    } else {
        wg_fence();
#pragma unroll
        for (int i = 0; i < 8; i++) {
            wgmma_rs128(o, p[4 * i], p[4 * i + 1], p[4 * i + 2], p[4 * i + 3], db, i ? 1 : acc);
            desc_add(db, 256);
        }
        wg_commit();
    }
}
__device__ __forceinline__ void tri_mask(float (&s)[64], float x) {
#pragma unroll
    for (int k = 0; k < 16; k++) {
        float b;
        asm("sub.sat.f32 %0, %1, %2;" : "=f"(b) : "f"((float)(8 * (k >> 1) + (k & 1))), "f"(x));
        const int i = 32 + 4 * (k >> 1) + (k & 1);
        asm("fma.rn.f32 %0, %1, 0fFF61B1E6, %0;" : "+f"(s[i]) : "f"(b));
        if (k < 14) asm("fma.rn.f32 %0, %1, 0fFF61B1E6, %0;" : "+f"(s[i + 6]) : "f"(b));
    }
}
__device__ __forceinline__ void tri_mask_copy(float (&s)[64], const float (&h)[32], float x) {
#pragma unroll
    for (int i = 0; i < 32; i++) {
            asm("{\n.reg .pred p;\nsetp.lt.f32 p, %2, %3;\nselp.f32 %0, 0fFF800000, %1, p;\n}"
                : "=f"(s[i]) : "f"(h[i]), "f"(x), "f"((float)(8 * (i >> 2) - 4 * (i & 2) + (i & 1))));
        s[32 + i] = __uint_as_float(0xff800000u);
    }
}
constexpr float SM_HI = 1152921504606846976.f, SM_LO = 1.f / 1152921504606846976.f;
__device__ __forceinline__ bool softmax_unsafe(float t0, float t1, bool first) {
    bool bad = __any_sync(0xffffffffu, fmaxf(t0, t1) > SM_HI);
    if (first) {
        uint32_t a = __ballot_sync(0xffffffffu, t0 >= SM_LO), b = __ballot_sync(0xffffffffu, t1 >= SM_LO);
        a |= a >> 1;
        b |= b >> 1;
        bad |= ((a | (a >> 2)) & (b | (b >> 2)) & 0x11111111u) != 0x11111111u;
    }
    return bad;
}
__device__ __forceinline__ void softmax_remax(const float (&s)[64], float (&m)[2], bool first, float& m0, float& m1, float& a0, float& a1) {
    m0 = fmaxf(s[0], s[1]), m1 = fmaxf(s[2], s[3]);
#pragma unroll
    for (int k = 1; k < 16; k++) {
        m0 = fmaxf(m0, fmaxf(s[4 * k], s[4 * k + 1]));
        m1 = fmaxf(m1, fmaxf(s[4 * k + 2], s[4 * k + 3]));
    }
    m0 = fmaxf(m0, __shfl_xor_sync(0xffffffffu, m0, 1));
    m1 = fmaxf(m1, __shfl_xor_sync(0xffffffffu, m1, 1));
    m0 = fmaxf(m0, __shfl_xor_sync(0xffffffffu, m0, 2));
    m1 = fmaxf(m1, __shfl_xor_sync(0xffffffffu, m1, 2));
    if (!first) {
        m0 = fmaxf(m0, 0.f);
        m1 = fmaxf(m1, 0.f);
    }
    a0 = first ? 1.f : ex2(-m0);
    a1 = first ? 1.f : ex2(-m1);
    m[0] += m0;
    m[1] += m1;
}
template <int J0, int J1>
__device__ __forceinline__ void softmax_exp(const float (&s)[64], uint32_t (&p)[32], float (&t)[4]) {
#pragma unroll
    for (int k = J0; k < J1; k++) {
        const float e0 = ex2(s[4 * k]), e1 = ex2(s[4 * k + 1]), e2 = ex2(s[4 * k + 2]), e3 = ex2(s[4 * k + 3]);
        if (k == 0) { t[0] = e0; t[1] = e1; t[2] = e2; t[3] = e3; }
        else { t[0] += e0; t[1] += e1; t[2] += e2; t[3] += e3; }
        p[2 * k] = pack2(e0, e1);
        p[2 * k + 1] = pack2(e2, e3);
    }
}
__device__ __forceinline__ void mma16816(float (&d)[4], const uint32_t* a, uint32_t b0, uint32_t b1) {
    asm("mma.sync.aligned.m16n8k16.row.col.f32.bf16.bf16.f32 {%0, %1, %2, %3}, {%4, %5, %6, %7}, {%8, %9}, {%0, %1, %2, %3};"
        : "+f"(d[0]), "+f"(d[1]), "+f"(d[2]), "+f"(d[3]) : "r"(a[0]), "r"(a[1]), "r"(a[2]), "r"(a[3]), "r"(b0), "r"(b1));
}
__device__ __forceinline__ uint32_t best_key(const uint4* keys, uint32_t ep) {
#pragma unroll 1
    for (;;) {
        const uint4 k = ld_poll(keys);
        const uint32_t best = __reduce_max_sync(0xffffffffu, max(max(k.x, k.y), max(k.z, k.w)));
        const uint32_t ok = __ballot_sync(0xffffffffu, (((k.x ^ ep) | (k.y ^ ep) | (k.z ^ ep) | (k.w ^ ep)) & 31) == 0);
        if (ok == ~0u) return best;
        __nanosleep(__popc(ok) < KN ? KSLEEP : KSLEEP2);
    }
}

__global__ void __cluster_dims__(2, 1, 1) __launch_bounds__(384, 1)
fused_kernel(const __grid_constant__ CUtensorMap tm_ckv, const __grid_constant__ CUtensorMap tm_wq,
             const __grid_constant__ CUtensorMap tm_wuk, const __grid_constant__ CUtensorMap tm_wuv,
             const __grid_constant__ CUtensorMap tm_wo, const __grid_constant__ CUtensorMap tm_wg,
             const __grid_constant__ CUtensorMap tm_wu,
             const __grid_constant__ CUtensorMap tm_wm, const __grid_constant__ CUtensorMap tm_x, const Params P) {
    extern __shared__ __align__(1024) uint8_t smem[];
    if (threadIdx.x == 352) {
        asm volatile("prefetch.tensormap [%0];" ::"l"(&tm_ckv) : "memory");
        asm volatile("prefetch.tensormap [%0];" ::"l"(blockIdx.x >= NCTA ? &tm_wm : (blockIdx.x & 1) ? &tm_wuv : &tm_wuk) : "memory");
    }
    const uint32_t sb = (uint32_t)__cvta_generic_to_shared(smem);
    const int tid = threadIdx.x, lane = tid & 31, warp = __shfl_sync(0xffffffffu, tid >> 5, 0), wg = warp >> 2;
    const uint32_t sm = blockIdx.x < 8 ? blockIdx.x + 124 : blockIdx.x - 8, smq = ((sm - 64) * 147) >> 11;
    const int rb = sm < 64 ? (sm & 14) * 8 + (sm >> 4) * 2 + (sm & 1)
                 : sm < 120 ? ((sm - 64 - smq * 14) & 14) * 8 + 24 + smq * 2 + (sm & 1) : sm < 124 ? sm + 8 : sm - 116;
    const int grp = rb >> 3, j = rb & 7, kh = (grp >> 1) & 1;
    const int cq = (j & 1) + ((grp >> 1) & 2), ort = (grp & 8) + (grp & 1) * 4 + (j >> 1);
    if (warp == 0) TS(0);

    const CUtensorMap* tw = (j & 1) ? &tm_wuv : &tm_wuk;
    if (lane == 0) {
        if (warp == 8) {
#pragma unroll
            for (int i = 0; i < 7; i++) mbar_init(sb + BAR_FULL + 8 * i, 1);
            fence_async_smem();
        } else if (warp < 11) {
            const int w = warp - (warp > 8);
            const u64 cnt = (w < 5 ? (rb < NCTA ? 0x888888884444444ull : 0x888888888888888ull) : 0x111812111111118ull) >> (12 * (w % 5));
#pragma unroll
            for (int i = 0; i < 3; i++) mbar_init(sb + BAR_EMPTY + 24 * w + 8 * i, ((uint32_t)cnt >> (4 * i)) & 15);
        }
        asm volatile("fence.mbarrier_init.release.cluster;" ::: "memory");
    }
    __syncwarp();
    asm volatile("barrier.cluster.arrive.relaxed.aligned;" ::: "memory");
    if (warp == 8) {
        if (rb < NCTA) {
#pragma unroll 1
            for (int u = 0; u < 4; u++) {
                const uint32_t ws = u + (u == 3), as = (0x635u >> (4 * u)) & 15;
                slot_expect(sb, ws);
                load_tile(sb, ws, 0, tw, u * 128, 4 * grp, false, HINT & 1);
                if (u == 3) break;
                slot_expect(sb, as);
                load_tile(sb, as, 0, &tm_ckv, (j >> 1) * 128, u * 2, false, false);
                load_tile(sb, as, 16384, &tm_ckv, (j >> 1) * 128, u * 2 + 1, false, false);
            }
        } else {
#pragma unroll 1
            for (int i = 0; i < 6; i++) {
                slot_expect(sb, i);
                load_tile(sb, i, 0, &tm_wm, i * 64, (rb - NCTA) * 4, false, HINT & 64);
                if (i > 3) tma3d_prefetch(&tm_wm, i * 64 + 128, (rb - NCTA) * 4);
            }
        }
    }
    asm volatile("barrier.cluster.wait.aligned;" ::: "memory");

    if (rb >= NCTA) {
        const int sp = rb - NCTA;
        const uint32_t ep = __ldcg(&g_sync.epoch[0]) + 1;
        uint32_t ph = 0, sl = 0;
        if (warp == 8) {
#pragma unroll 1
            for (int i = 6; i < 54 + 2 * OFF; i++) {
                slot_acquire(sb, ph, sl);
                const int k = i - 24;
                load_tile(sb, sl, 0, i < 24 ? &tm_wm : i >= 54 ? &tm_wo : (k & 2) ? &tm_wu : &tm_wg, i < 24 ? (i & 7) * 64 : i >= 54 ? (i - 38 - 2 * OFF) * 256 : (k & 1) * 256,
                          i < 24 ? (i >> 3) * 16 + sp * 4 : i >= 54 ? sp * 2 : sp * 7 + (k >> 2), false, true);
                if (++sl == 6) sl = 0;
                if (i == 51) { i = 53; sl = 0; }
            }
            bar_sync(4, 64);
            slot_wait(sb + BAR_EMPTY, ph, 4);
            slot_wait(sb + BAR_EMPTY, ph, 5);
            ph = 0x3f, sl = 0;
#pragma unroll 1
            for (int h = 0; h < 32; h++) {
                step_watch(sb + SM_EP + 16, h + 1);
                fence_async_global();
                const uint8_t* src = g_ctx + (size_t)(((h >> 1) ^ 8) * 32 + 30 - 4 * OFF) * SLOT + (h & 1) * 16384;
#pragma unroll 1
                for (int k = 0; k <= 2 * OFF; k++, src += 2 * SLOT) {
                    slot_wait(sb + BAR_DONE, ph, sl);
                    const uint32_t f = sb + BAR_FLAG + 8 * sl, d = sb + 4 * SLOT + sl * 16384;
                    asm volatile("{\n.reg .pred p;\nelect.sync _|p, 0xffffffff;\n@p mbarrier.arrive.expect_tx.shared::cta.b64 _, [%0], 16384;\n}" ::"r"(f) : "memory");
                    if (k == 0)
                        asm volatile("{\n.reg .pred p;\nelect.sync _|p, 0xffffffff;\n"
                                     "@p cp.async.bulk.tensor.3d.shared::cluster.global.mbarrier::complete_tx::bytes [%0], [%1, {%3, %4, %5}], [%2];\n}"
                                     ::"r"(d), "l"(&tm_x), "r"(f), "r"(0), "r"((h ^ 16) * 64), "r"(sp * 2) : "memory");
                    else
                        asm volatile("{\n.reg .pred p;\nelect.sync _|p, 0xffffffff;\n"
                                     "@p cp.async.bulk.shared::cluster.global.mbarrier::complete_tx::bytes [%0], [%1], 16384, [%2];\n}"
                                     ::"r"(d), "l"(src), "r"(f) : "memory");
                    if (++sl == 6) sl = 0;
                }
            }
        } else if (warp == 9) {
#pragma unroll 1
            for (int t = 0; t <= 16; t++) {
                asm volatile("st.release.cta.shared.u32 [%0], %1;" ::"r"(sb + SM_EP + 16), "r"(2 * t) : "memory");
                if (t == 0) bar_sync(4, 64);
                if (lane < 4 && t < 16) flag_wait(&g_sync.ctxcnt[(t ^ 8) * 32 + 24 + 2 * lane], ep);
                __syncwarp();
            }
        } else if (warp < 8) {
            const uint32_t c2 = __ldg(reinterpret_cast<const uint32_t*>(P.c) + tid);
            uint32_t* sc = reinterpret_cast<uint32_t*>(smem + SM_TAB);
            sc[tid] = pack2(bf_lo(c2) * sigmoid(bf_lo(c2)), bf_hi(c2) * sigmoid(bf_hi(c2)));
            bar_sync(1, 256);
            const uint32_t a = sb + (warp >> 1) * 8192 + ((lane >> 4) * 8 + (lane & 7)) * 128, ch = (warp & 1) * 4 + ((lane >> 3) & 1);
#pragma unroll 1
            for (int ps = 0; ps < 3; ps++) {
                float d[2][4] = {};
#pragma unroll 1
                for (int bt = 0; bt < 8; bt++) {
                    slot_wait(sb + BAR_FULL, ph, sl);
#pragma unroll
                    for (int i = 0; i < 8; i++) {
                        uint32_t w[4];
                        asm volatile("ldmatrix.sync.aligned.m8n8.x4.trans.shared.b16 {%0, %1, %2, %3}, [%4];" : "=r"(w[0]), "=r"(w[1]), "=r"(w[2]), "=r"(w[3])
                                     : "r"(a + sl * SLOT + (i >> 1) * 2048 + (((ch + 2 * (i & 1)) ^ (lane & 7)) << 4)) : "memory");
                        mma16816(d[i & 1], w, sc[bt * 32 + (i >> 1) * 8 + (lane & 3)], sc[bt * 32 + (i >> 1) * 8 + 4 + (lane & 3)]);
                    }
                    __syncwarp();
                    mbar_arrive_if(sb + BAR_EMPTY + 8 * sl, lane == 0);
                    if (++sl == 6) sl = 0;
                }
                const float v = (lane & 2) ? ((lane & 1) ? d[1][2] : d[1][0]) : ((lane & 1) ? d[0][2] : d[0][0]);
                const int col = sp * 256 + warp * 32 + (lane & 3) * 8 + (lane >> 2);
                if (ps == 0) st_pub(g_mod1 + col, (pack2(0.f, v) & 0xffff0000u) | (ep & 0xffffu), true);
                else g_mod[ps * 1024 + col] = __float2bfloat16_rn(v);
                if (warp == 0) TS(1 + ps);
            }
#pragma unroll 1
            for (int k = 0; k < 28; k++) {
                slot_wait(sb + BAR_FULL, ph, sl);
                uint4* dst = reinterpret_cast<uint4*>(g_wf) + (sp * 28 + (k & ~3)) * 2048 + (k & 3) * 512 + tid;
#pragma unroll 4
                for (int i = 0; i < 8; i++) {
                    const int row = (i & 1) * 128 + (tid >> 1);
                    __stcs(dst + (i >> 1) * 2048 + (i & 1) * 256, lds128(sb + sl * SLOT + row * 128 + ((((i & 6) + ((tid ^ (row >> 2)) & 1)) ^ (row & 7)) << 4)));
                }
                __syncwarp();
                mbar_arrive_if(sb + BAR_EMPTY + 8 * sl, lane == 0);
                if (++sl == 6) sl = 0;
            }
            bar_sync(1, 256);
            if (tid < 2) {
                flag_add(&g_sync.cnt[7 * 8]);
                flag_wait(&g_sync.cnt[7 * 8], 8 * ep);
            }
            if (warp == 0) TS(4);
            bar_sync(1, 256);
            uint32_t ga[16], x2[32];
#pragma unroll
            for (int i = 0; i < 16; i++) ga[i] = __ldcg(reinterpret_cast<const uint32_t*>(g_mod) + 512 + sp * 64 + (lane & 3) + 4 * i);
#pragma unroll 1
            for (int i = 0; i < 2 * OFF; i++) slot_wait(sb + BAR_FULL, ph, i);
            float d[64];
            uint32_t u = (2 * OFF + 1) * wg, up = 0;
            if (wg == 1) bar_arrive(2, 256);
#pragma unroll 1
            for (int h = wg; h < 32; h += 2) {
                mbar_wait(sb + BAR_FLAG + 8 * u, up);
                const uint32_t xa = sb + 4 * SLOT + u * 16384 + ((warp & 3) * 16 + (lane & 15)) * 128;
#pragma unroll
                for (int k = 0; k < 8; k++)
                    asm volatile("ldmatrix.sync.aligned.m8n8.x4.shared.b16 {%0, %1, %2, %3}, [%4];"
                                 : "=r"(x2[4 * k]), "=r"(x2[4 * k + 1]), "=r"(x2[4 * k + 2]), "=r"(x2[4 * k + 3])
                                 : "r"(xa + (k >> 2) * 8192 + (((2 * (k & 3) + (lane >> 4)) ^ (lane & 7)) << 4)) : "memory");
                mbar_arrive_if(sb + BAR_DONE + 8 * u, lane < 2);
                bar_sync(2 + wg, 256);
#pragma unroll 1
                for (int k = 0; k < 2 * OFF; k++) {
                    const uint32_t pu = u;
                    if (++u == 6) { u = 0; up ^= 1; }
                    mbar_wait(sb + BAR_FLAG + 8 * u, up);
                    gemm_issue<false>(d, desc_k(sb + 4 * SLOT) + u * 1024, desc_mn(sb) + k * (SLOT / 16), k, true);
                    wg_wait<1>();
                    mbar_arrive_if(sb + BAR_DONE + 8 * pu, lane < 2 && k);
                }
                if (h < 31) bar_arrive(3 - wg, 256);
                wg_wait<0>();
                reg_fence(d);
                mbar_arrive_if(sb + BAR_DONE + 8 * u, lane < 2);
                u += 2 * OFF + 2;
                if (u >= 6) { u -= 6; up ^= 1; }
                uint4* op = g_x2 + ((h ^ 16) * 4 + sp) * 1024 + (tid & 127);
#pragma unroll
                for (int v = 0; v < 8; v++) {
                    uint32_t y[4];
#pragma unroll
                    for (int i = 0; i < 4; i++) {
                        const int k = 4 * v + i;
                        y[i] = pack2(fmaf(bf_lo(ga[k >> 1]), d[2 * k], bf_lo(x2[k])), fmaf(bf_hi(ga[k >> 1]), d[2 * k + 1], bf_hi(x2[k])));
                    }
                    op[v * 128] = make_uint4(y[0], y[1], y[2], y[3]);
                }
            }
            bar_sync(1, 256);
            if (tid == 0) flag_add(&g_sync.cnt[15 * 8]);
            if (warp == 0) TS(5);
        }
        return;
    }

    if (wg == 2) {
        asm volatile("setmaxnreg.dec.sync.aligned.u32 40;");
        if (warp == 8) {
            const uint32_t rank = j & 1, half = rank * 16384;
            uint32_t eph = 0, r = 0;
            *reinterpret_cast<volatile uint32_t*>(smem + SM_EP + 20) = 0;
#pragma unroll 1
            for (int hp = 0; hp < 2; hp++) {
                uint32_t wtab = w_table(hp), atab = a_table(hp);
                const int hc = 4 * grp + 2 * hp;
#pragma unroll 1
                for (int u = 3 - 3 * hp; u < 16; u++) {
                    if (hp && u < 4) {
                        const uint32_t ws = (wtab >> (4 * u)) & 15;
                        slot_acquire(sb, eph, ws);
                        load_tile(sb, ws, 0, tw, u * 128, hc, false, HINT & 1);
                        PT();
                    }
                    if (hp == 1 && (u & 7) == 4) mbar_wait(sb + BAR_FLAG + 24 + (u & 8), 0);
                    const uint32_t as = a_next(atab);
                    slot_acquire(sb, eph, as);
                    load_tile(sb, as, half, &tm_ckv, ((u & 12) + (j >> 1)) * 128, (u & 3) * 2 + rank, true, (HINT & 8) && hp);
                    PT();
                    if (hp == 1 && (u | 2) == 3 && lane == 0)
                        asm volatile("red.relaxed.gpu.global.add.u32 [%0], 1;" ::"l"(&g_sync.cnt[(grp * 8 + 3 + (u >> 1)) * 8]) : "memory");
                }
                const uint8_t* src = g_h + (15 - j) * 4 * SLOT;
#pragma unroll 1
                for (int u = 0; u < 8; u++) {
                    if (u == 0 || u == KVG) {
                        mbar_wait(sb + BAR_FLAG + (u ? 8 + 32 * hp : 0), 0);
                        fence_async_global();
                    }
                    if (u < 4) {
                        const uint32_t ws = (wtab >> (4 * u)) & 15;
                        slot_acquire(sb, eph, ws);
                        load_tile(sb, ws, 0, &tm_wq, u * 128, hc, false, HINT & 1);
                        PT();
                    }
                    const uint32_t as = a_next(atab);
                    slot_acquire(sb, eph, as);
                    load_bulk(sb, as, 0, src, SLOT, false, (HINT & 8) && hp);
                    PT();
                    src += u == 3 ? (8 * j - 63) * SLOT : SLOT;
                }
                const int step = hp ? -2 * SLOT : 2 * SLOT;
                src = g_KV + (size_t)(grp * 32 + 30 * hp) * SLOT + half - step;
#pragma unroll 1
                for (int n = 0; n <= 17; n++) {
                    if (n == 8) {
                        mbar_wait(sb + BAR_FLAG + 16 + 32 * hp, 0);
                        fence_async_global();
                    }
                    const uint8_t* v = src + SLOT;
                    src += n < 16 - j ? step : n == 16 - j ? (2 * j - 15) * step : -step;
                    if (n < 17) {
                        slot_acquire(sb, eph, r);
                        if (n != 15 - (j & 6)) load_bulk(sb, r, half, src, SLOT / 2, true, HINT & 4);
                        else load_bulk(sb, r, 0, src - half, SLOT, false, HINT & 4);
                        PT();
                        r = ring_next(r);
                    }
                    if (n) {
                        slot_acquire(sb, eph, r);
                        if (n != 16 - (j & 6)) load_bulk(sb, r, half, v, SLOT / 2, true, HINT & 4);
                        else load_bulk(sb, r, 0, v - half, SLOT, false, HINT & 4);
                        PT();
                        r = ring_next(r);
                    }
                    asm volatile("st.volatile.shared.u32 [%0], %1;" ::"r"(sb + SM_EP + 16), "r"(18 * hp + n + 1) : "memory");
                }
            }
            uint32_t otab = O_TABLE, ready = 0;
#pragma unroll 1
            for (int i = 0; i < 17; i += i == 7 - OFF ? 1 + OFF : 1) {
                const bool dyn = i >= 8 && i < 15;
                const uint32_t want = dyn ? 15u << (4 * (i - 8)) : 1u << max(i + 14, 28);
                if (!(ready & want)) {
                    do {
                        asm volatile("ld.acquire.cta.shared.u32 %0, [%1];" : "=r"(ready) : "r"(sb + SM_EP + 20) : "memory");
                        ready = __shfl_sync(0xffffffffu, ready, 0);
                    } while (!(ready & want));
                    fence_async_global();
                }
                const int head = o_head(dyn ? (ready >> (4 * (i - 8))) & 15 : i, kh);
                const uint32_t as = o_next(otab), ws = o_next(otab), off = i < 15 ? half : kh * 16384;
                slot_acquire(sb, eph, as);
                load_bulk(sb, as, off, g_ctx + (size_t)(ort * 32 + head) * SLOT + off, SLOT / 2, i < 15, HINT & 16);
                if (i >= 15) load_bulk(sb, as, off ^ 16384, i == 15 ? g_x2 + ((ort * 2 + kh) * 4 + cq) * 1024 : reinterpret_cast<const uint4*>(P.wdown) + min(rb, NFFN - 1) * 1024, SLOT / 2, false, false);
                PT();
                slot_acquire(sb, eph, ws);
                load_tile(sb, ws, 0, &tm_wo, head * 128, cq * 2, false, HINT & 2);
                PT();
                if (i == 0) o_next(otab);
            }
            if (rb < NFFN) {
                slot_acquire(sb, eph, SL_WF);
                load_bulk(sb, SL_WF, 0, g_wf + rb * SLOT, SLOT, false, false);
            }
        } else if (warp == 9) {
            *reinterpret_cast<volatile uint32_t*>(smem + SM_EP + 16) = 0;
            l2_prefetch(P.ckv + rb * 2048, 4096);
            mbar_watch(sb + BAR_FULL, 0);
            l2_prefetch(P.ckv + 512 * 512 + rb * 2048, 4096);
            mbar_watch(sb + BAR_FULL + 8 * XPF, 0);
            l2_prefetch(P.x + rb * 8192, 16384);
            mbar_watch(sb + BAR_FULL + 8 * 4, 0);
            l2_prefetch(P.ckv + 1024 * 512 + rb * 4096, 8192);
            TS(40);
#pragma unroll 1
            for (int i = 0; i < 13; i++) {
                step_watch(sb + SM_EP + 16, i == 0 ? 0 : i < 5 ? PFA + i : 13 + PFB + i);
                if (i == 10) mbar_watch(sb + BAR_FLAG + 8 * 7, 0);
                const int rf = min(rb, NFFN - 1), pc = 4 * (i - 5) + cq;
                const uint8_t* p = i == 3 ? reinterpret_cast<const uint8_t*>(P.ckv) + rb * 16384
                                 : i == 4 ? g_h + rb * 16384
                                 : i < 8 ? g_ctx + (size_t)(ort * 32 + o_head(pc >> 1, kh)) * SLOT + (pc & 1) * 16384
                                 : i < 10 ? reinterpret_cast<const uint8_t*>(P.wo) + (grp * 16 + (i & 1) * 8 + j) * 16384
                                 : i == 10 ? reinterpret_cast<const uint8_t*>(P.wdown) + rf * 16384 : g_wf + rf * SLOT + (i & 1) * 16384;
                if (i >= 3) l2_prefetch(p, 16384);
                else if ((i | j) & 1) tma3d_prefetch(i == 1 ? tw : &tm_wq, (j >> 1) * 128, grp * 4 + (i ? 2 : 0));
            }
            const uint32_t v = lds32(sb + SM_EP) - 1;
            sts128(sb + SM_RED + lane * 16, make_uint4(v, v, v, v));
            fence_async_smem();
            __syncwarp();
#pragma unroll 1
            for (int i = 0; i < OB / 32; i++) bulk_store(g_out + rb * OB + i * 32, sb + SM_RED, 512, false);
            asm volatile("cp.async.bulk.commit_group;\ncp.async.bulk.wait_group 0;" ::: "memory");
            fence_async_global();
            __syncwarp();
            mbar_arrive_if(sb + BAR_PF, lane == 0);
            if (lane == 0) mbar_watch(sb + BAR_END, 0);
        } else {
            const uint32_t ep = __ldcg(&g_sync.epoch[0]) + 1;
            asm volatile("st.shared.u32 [%0], %1;" ::"r"(sb + SM_EP), "r"(ep) : "memory");
            mbar_wait(sb + BAR_FULL + 8 * 4, 0);
            {
                uint4 v[4];
                for (;;) {
                    uint32_t bad = 0;
#pragma unroll
                    for (int k = 0; k < 4; k++) v[k] = ld_poll(reinterpret_cast<const uint4*>(g_mod1) + (warp & 1) * 128 + k * 32 + lane);
#pragma unroll
                    for (int k = 0; k < 4; k++) bad |= (v[k].x ^ ep) | (v[k].y ^ ep) | (v[k].z ^ ep) | (v[k].w ^ ep);
                    if (poll_done((bad & 0xffff) == 0, 100)) break;
                }
                const uint32_t one = (warp & 1) ? ONE2 : 0x80008000u;
#pragma unroll
                for (int k = 0; k < 4; k++)
                    *reinterpret_cast<uint2*>(smem + SM_TAB + (warp & 1) * 1024 + k * 256 + lane * 8) =
                        make_uint2(badd(__byte_perm(v[k].x, v[k].y, 0x7632), one), badd(__byte_perm(v[k].z, v[k].w, 0x7632), one));
            }
            __syncwarp();
            mbar_arrive_if(sb + BAR_FLAG + 8 * 8, lane == 0);
            if (warp == 10) {
#pragma unroll 1
                for (int i = 0; i < 9; i++) {
                    mbar_sleep(sb + BAR_DONE + 8 * i);
                    if (lane == 0) flag_add(i && ((i - 1) & 2) ? &g_sync.ctxcnt[((i & 1) ? 15 - j : j) * 32 + 2 * grp + (i > 4)] : &g_sync.cnt[(grp * 8 + i) * 8]);
                    if (i == 0) TS(43);
                }
            } else {
                TS(42);
#pragma unroll 1
                for (int i = 0; i < 8; i++) {
                    mbar_sleep(sb + BAR_DONE + 8 * (i == 7 ? 6 : i == 4 ? 3 : i));
                    if (lane < 2) flag_wait(&g_sync.cnt[((i == 0 ? (lane ? j : 15 - j) : i == 7 ? 0 : grp) * 8 + i) * 8], 8 * ep);
                    __syncwarp();
                    mbar_arrive_if(sb + BAR_FLAG + 8 * i, lane == 0 && i < 7);
                    TS(48 + i);
                }
                const uint32_t *mp = reinterpret_cast<const uint32_t*>(g_mod) + lane, *wp = reinterpret_cast<const uint32_t*>(P.wr) + lane;
                float ra = 0.f, rs = 0.f;
#pragma unroll 1
                for (int k = 0; k < 256; k += 32) {
                    const uint32_t ga = __ldcg(mp + 512 + k), sh = __ldcg(mp + 768 + k), c1 = badd(__ldcg(mp + 1024 + k), ONE2);
                    const uint32_t gb = __ldcg(mp + 1280 + k), ww = __ldg(wp + k);
                    const uint32_t a = bmul(c1, ww);
                    ra += bf_lo(a) + bf_hi(a);
                    rs = fmaf(bf_lo(sh), bf_lo(ww), fmaf(bf_hi(sh), bf_hi(ww), rs));
                    if (k >> 6 == cq) {
                        sts128(sb + SM_TAB + ((k & 32) + lane) * 16, make_uint4(ga << 16, ga & 0xffff0000u, a, 0));
                        sts128(sb + SM_TAB + 1024 + ((k & 32) + lane) * 16, make_uint4(c1, sh, gb, 0));
                    }
                }
#pragma unroll 1
                for (int o = 16; o > 0; o >>= 1) {
                    ra += __shfl_xor_sync(0xffffffffu, ra, o);
                    rs += __shfl_xor_sync(0xffffffffu, rs, o);
                }
                *reinterpret_cast<float2*>(smem + SM_EP + 8) = make_float2(ra, rs);
                __syncwarp();
                mbar_arrive_if(sb + BAR_FLAG + 8 * 7, lane == 0);
                const uint32_t* f = lane < 17 ? &g_sync.ctxcnt[ort * 32 + o_head(lane, kh)] : &g_sync.cnt[15 * 8];
                uint32_t ready = -(j & 1), list = 0, sh = 0, qa;
                asm("mapa.shared::cluster.u32 %0, %1, %2;" : "=r"(qa) : "r"(sb + SM_EP + 20), "r"(lane & 1));
                while (ready != ~0u) {
                    uint32_t v, now;
                    do {
                        asm volatile("ld.acquire.gpu.global.u32 %0, [%1];" : "=r"(v) : "l"(f) : "memory");
                        now = __ballot_sync(0xffffffffu, (int)(v - (lane < 17 ? ep : NSPARE * ep)) >= 0);
                    } while (!poll_done(now != ready, POLL_NS));
#pragma unroll 1
                    for (uint32_t fresh = now & ~ready & 0x7f00; fresh; fresh &= fresh - 1, sh += 4) list |= (__ffs(fresh) - 1) << sh;
                    list |= (((now & 0xff) + 1) >> 8 << 28) | ((now & (now >> 2) & 0x18000) << 14);
                    if (lane < 2) asm volatile("st.relaxed.cluster.shared::cluster.u32 [%0], %1;" ::"r"(qa), "r"(list) : "memory");
                    if ((ready & 0xff) != 0xff && (now & 0xff) == 0xff) mbar_sleep(sb + BAR_DONE + 8 * 7);
                    ready = now;
                }
                TS(45);
            }
        }
    } else {
        const bool elected = (tid & 127) == 0, rel = (tid & 95) == 0;
        uint32_t eb;
        asm("mapa.shared::cluster.u32 %0, %1, %2;" : "=r"(eb) : "r"(sb + BAR_EMPTY), "r"(warp & 1));
        const int g = lane >> 2, c4 = lane & 3;
        uint32_t toff = warp * 4096 + g * 64 + ((c4 ^ (g >> 1)) << 4);
        uint32_t fph = 0x3f, r = 0;
        if (wg == 1) bar_arrive(1, 256);
        const uint32_t kd = desc_k(sb), wd = desc_mn(sb), vd = ((sb & 0x3ffff) >> 4) | (32u << 16);
        const int nL = 16 - j, hn = nL - 1 + wg;
        float s[64], o[64], li[2] = {0.f, 0.f};
        uint32_t cimg = 0;
        const float sc = (j & 1) ? 1.f : SM_C;
#pragma unroll 1
        for (int q = 0; q < 3; q++) {
            const uint32_t as = (0x635u >> (4 * q)) & 15;
            mbar_wait(sb + BAR_FULL + 8 * q, 0);
            mbar_wait(sb + BAR_FULL + 8 * as, 0);
            bar_sync(1 + wg, 256);
            gemm_issue<false>(s, kd + wg * 512 + as * (SLOT / 16), wd + q * (SLOT / 16), q, false);
            bar_arrive(2 - wg, 256);
            wg_wait<0>();
            release_if(eb, as, rel);
        }
        {
            const int xrow = rb * 16 + warp * 2;
            const uint4* xp = reinterpret_cast<const uint4*>(P.x) + xrow * 64;
            const uint32_t img = (grp * 32 + j) * SLOT;
            uint32_t x[16], x0[2];
            float st[4] = {0.f, 0.f, 0.f, 0.f};
            mbar_wait(sb + BAR_FULL + 8 * 4, 0);
#pragma unroll
            for (int q = 3; q < 8; q++) {
                const uint32_t ws = (0x4210u >> (4 * (q & 3))) & 15, as = (0x635u >> (4 * (q % 3))) & 15;
                mbar_wait(sb + BAR_FULL + 8 * as, (q / 3) & 1);
                bar_sync(1 + wg, 256);
                if (q == 3) gemm_issue<false>(s, kd + wg * 512 + as * (SLOT / 16), wd + ws * (SLOT / 16), 1, false);
                else if (q == 4) gemm_issue<true>(o, kd + wg * 512 + as * (SLOT / 16), wd + ws * (SLOT / 16), 0, false);
                else gemm_issue<false>(o, kd + wg * 512 + as * (SLOT / 16), wd + ws * (SLOT / 16), 1, false);
                bar_arrive(2 - wg, 256);
                sched_fence(fph, P.zero);
                if (q > 3) reg_fence(s);
                if (q == 3) {
                    asm volatile("setmaxnreg.inc.sync.aligned.u32 232;");
#pragma unroll
                    for (int i = 0; i < 4; i++)
                        asm volatile("ld.global.nc.v4.u32 {%0, %1, %2, %3}, [%4];" : "=r"(x[4 * i]), "=r"(x[4 * i + 1]), "=r"(x[4 * i + 2]), "=r"(x[4 * i + 3])
                                     : "l"(xp + lane + 32 * i) : "memory");
#pragma unroll
                    for (int i = 0; i < 2; i++) asm volatile("ld.global.nc.u32 %0, [%1];" : "=r"(x0[i]) : "l"(xp + 64 * i) : "memory");
                }
                if (q == 4) {
                    img_store_global<0>(img, toff, s, sc, sc);
#pragma unroll
                    for (int k = 0; k < 16; k++) {
                        const float d0 = bf_lo(x[k]) - bf_lo(x0[k >> 3]), d1 = bf_hi(x[k]) - bf_lo(x0[k >> 3]);
                        st[k >> 3] += d0 + d1;
                        st[2 + (k >> 3)] = fmaf(d0, d0, fmaf(d1, d1, st[2 + (k >> 3)]));
                    }
#pragma unroll
                    for (int i = 0; i < 4 * NSH; i++) st[i & 3] += __shfl_xor_sync(0xffffffffu, st[i & 3], 1 << (i >> 2));
                    reg_fence(st);
                }
                if (q == 5) {
#pragma unroll
                    for (int i = 4 * NSH; i < 20; i++) st[i & 3] += __shfl_xor_sync(0xffffffffu, st[i & 3], 1 << (i >> 2));
                    img_store_global<1>(img, toff, s, sc, sc);
#pragma unroll
                    for (int i = 0; i < 2; i++) {
                        const float d = st[i] * (1.f / 512.f);
                        st[2 + i] = ln_rstd(fmaxf(fmaf(-d, d, st[2 + i] * (1.f / 512.f)), 0.f));
                        x0[i] = pack2(bf_lo(x0[i]) + d, bf_lo(x0[i]) + d);
                    }
                    reg_fence(st);
                    reg_fence(x0);
                }
                if (q > 5) {
                    if (q == 6) mbar_wait(sb + BAR_FLAG + 8 * 8, 0);
                    const uint4 a = lds128(sb + SM_TAB + 1024 + (q & 1) * 512 + lane * 16), c = lds128(sb + SM_TAB + (q & 1) * 512 + lane * 16);
                    uint8_t* hp = g_h + (grp * 8 + (q & 1) * 4 + (lane >> 3)) * 16384 + (xrow & 127) * 128;
#pragma unroll
                    for (int i = 0; i < 2; i++) {
                        const uint32_t* y = x + 8 * i + 4 * (q & 1);
                        *reinterpret_cast<uint4*>(hp + i * 128 + (((lane ^ xrow ^ i) & 7) << 4)) =
                            make_uint4(ln_apply(y[0], x0[i], st[2 + i], a.x, c.x), ln_apply(y[1], x0[i], st[2 + i], a.y, c.y),
                                       ln_apply(y[2], x0[i], st[2 + i], a.z, c.z), ln_apply(y[3], x0[i], st[2 + i], a.w, c.w));
                    }
                    if (q == 7) {
                        __syncwarp();
                        mbar_arrive_if(sb + BAR_DONE, lane == 0);
                    }
                    if (q == 6) img_store_global<2>(img, toff, s, sc, sc);
                    else img_store_global<3>(img, toff, s, sc, sc);
                }
                if (q < 7) {
                    sched_fence(fph, P.zero);
                    wg_wait<0>();
                    release_if(eb, as, rel);
                }
            }
        }
        uint32_t pend = 0x73;
        uint32_t p[32] = {};
#pragma unroll 1
        for (int hp = 0; hp < 2; hp++) {
            float m[2] = {0.f, 0.f}, l[2] = {0.f, 0.f}, t[4] = {0.f, 0.f, 0.f, 0.f};
            bool shifted = false, bad = false, plain = false;
            uint32_t qa = desc_k(sb + 5 * SLOT + (wg ^ 1) * 8192);
            const uint32_t limg = (512 + (15 - j) * 32 + 2 * grp + hp) * SLOT;
            {
                const int step = hp ? -8 * SLOT : 8 * SLOT;
                uint32_t img = (grp * 32 + (hp ? j ^ 30 : j) + 8) * SLOT;
                const uint32_t wtab = w_table(hp);
                uint32_t atab = hp ? 0x562u : 0x356u;
#pragma unroll 1
                for (int u = 2 - 2 * hp; u < 6; u += 2) {
                    proj_tile<false>(s, o, u, !u, sb, wg, eb, rel, fph, wtab, atab, pend, u ? img : cimg, toff, u ? sc : li[0], u ? sc : li[1], p);
                    __syncwarp();
                    mbar_arrive_if(sb + BAR_DONE + 4 * u + 32 * hp, lane == 0);
                    if (elected) TS(1 + 10 * hp + u + 20 * wg);
                    proj_tile<true>(o, s, u + 1, 0, sb, wg, eb, rel, fph, wtab, atab, pend, img + step, toff, sc, sc, p);
                    if (elected) TS(2 + 10 * hp + u + 20 * wg);
                    img += 2 * step;
                }
            }
            asm volatile("" : "+r"(toff));
            if (elected) TS(6 + 10 * hp + 20 * wg);
            fence_async_smem();
            slot_wait(sb + BAR_FULL, fph, r);
            step_retire(eb, rel, pend);
            reg_fence(o);
            int n = -1;
#pragma unroll 1
            for (;;) {
                while (bad || plain) {
                    float d0 = m[0], d1 = m[1];
                    if (bad) {
                        float a0, a1;
                        softmax_remax(s, m, n == 0 || n == nL, d0, d1, a0, a1);
                        shifted = true;
                        l[0] *= a0;
                        l[1] *= a1;
#pragma unroll
                        for (int i = 0; i < 64; i++) o[i] *= (i & 2) ? a1 : a0;
                    }
#pragma unroll
                    for (int i = 0; i < 64; i++) s[i] -= (i & 2) ? d1 : d0;
                    softmax_exp<0, 16>(s, p, t);
                    t[0] += t[1];
                    t[2] += t[3];
                    bad = !bad && softmax_unsafe(t[0], t[2], false);
                    plain = false;
                }
#pragma unroll 1
                do {
                    l[0] += t[0];
                    l[1] += t[2];
                    if (++n > 16) break;
                    const uint32_t ks = r;
                    uint32_t vs = ring_next(r);
                    r = ring_next(vs);
                    bar_sync(1 + wg, 256);
                    const float x = (float)((warp & 3) * 16 + g - 2 * c4);
                    if (n == hn) {
                        float sh[32];
                        qk_issue(sh, qa, kd + ks * (SLOT / 16));
                        slot_wait(sb + BAR_FULL, fph, vs);
                        pv_issue(o, p, vd + vs * (SLOT / 16), 1, false);
                        bar_arrive(2 - wg, 256);
                        wg_wait<1>();
                        reg_fence(sh);
                        tri_mask_copy(s, sh, x);
                        release_if(eb, ks, rel);
                        release_if(eb, 5 + wg, rel && (!wg || n == 16));
                        if (!wg) qa += SLOT / 16;
                        float e[4 * EARLY];
#pragma unroll
                        for (int i = 0; i < 4 * EARLY; i++) {
                            e[i] = ex2(s[i]);
                            t[i & 3] = i < 4 ? e[i] : t[i & 3] + e[i];
                        }
                        reg_fence(e);
                        slot_wait(sb + BAR_FULL, fph, r);
                        wg_wait<0>();
                        reg_fence(o);
                        reg_fence(e);
                        release_if(eb, vs, rel);
#pragma unroll
                        for (int i = 0; i < 2 * EARLY; i++) p[i] = pack2(e[2 * i], e[2 * i + 1]);
                        softmax_exp<EARLY, 8>(s, p, t);
                        if (wg) {
                            ctx_store(limg, toff, o, rcp(quad_sum(l[0])), rcp(quad_sum(l[1])));
                            __syncwarp();
                            mbar_arrive_if(sb + BAR_DONE + 24 + 32 * hp, lane == 0);
                            l[0] = l[1] = m[0] = m[1] = 0.f;
                            shifted = false;
                        }
                        t[0] += t[1];
                        t[2] += t[3];
                        plain = shifted;
                        if (plain) break;
                        bad = softmax_unsafe(t[0], t[2], wg);
                        continue;
                    }
                    if (n == nL) {
                        qk_issue(s, qa, kd + ks * (SLOT / 16));
                        slot_wait(sb + BAR_FULL, fph, vs);
                        pv_issue(o, p, vd + vs * (SLOT / 16), 1, true);
                        bar_arrive(2 - wg, 256);
                        const float i0 = rcp(quad_sum(l[0])), i1 = rcp(quad_sum(l[1]));
                        wg_wait<1>();
                        reg_fence(s);
                        release_if(eb, ks, rel);
                        release_if(eb, 6, rel && n == 16);
                        tri_mask(s, x);
                        float e[4 * EARLY2];
#pragma unroll
                        for (int i = 0; i < 4 * EARLY2; i++) {
                            e[i] = ex2(s[i]);
                            t[i & 3] = i < 4 ? e[i] : t[i & 3] + e[i];
                        }
                        reg_fence(e);
                        reg_fence(s);
                        reg_fence(t);
                        slot_wait(sb + BAR_FULL, fph, r);
                        sched_fence(fph, P.zero);
                        wg_wait<0>();
                        reg_fence(o);
                        reg_fence(e);
                        release_if(eb, vs, rel);
#pragma unroll
                        for (int i = 0; i < 2 * EARLY2; i++) p[i] = pack2(e[2 * i], e[2 * i + 1]);
                        softmax_exp<EARLY2, MSPLIT>(s, p, t);
                        ctx_store(limg, toff, o, i0, i1);
                        reg_fence(t);
                        reg_fence(s);
                        softmax_exp<MSPLIT, 16>(s, p, t);
                        __syncwarp();
                        mbar_arrive_if(sb + BAR_DONE + 24 + 32 * hp, lane == 0);
                        l[0] = l[1] = m[0] = m[1] = 0.f;
                        shifted = false;
                        t[0] += t[1];
                        t[2] += t[3];
                        bad = __any_sync(0xffffffffu, fmaxf(t[0], t[2]) > SM_HI || fminf(t[0], t[2]) < SM_LO);
                        continue;
                    }
                    qk_issue(s, qa, kd + ks * (SLOT / 16));
                    if (n == 0) {
                        r = vs;
                        vs = 4 - hp;
                        slot_wait(sb + BAR_FULL, fph, 6);
                        gemm_issue<false>(o, qa + SLOT / 16, wd + vs * (SLOT / 16), 1, false);
                    } else {
                        slot_wait(sb + BAR_FULL, fph, vs);
                        if (n == 1) {
                            wg_wait<1>();
                            reg_fence(o);
                            const uint32_t a = sb + 6 * SLOT + q_off(toff);
#pragma unroll
                            for (int i = 0; i < 8; i++) {
                                const int k = 16 * (i >> 1) + 2 * (i & 1);
                                sts128(a + (i >> 2) * 16384 + (i & 2) * 256 + (i & 1) * 1024,
                                       make_uint4(pack2(o[k], o[k + 1]), pack2(o[k + 4], o[k + 5]), pack2(o[k + 8], o[k + 9]), pack2(o[k + 12], o[k + 13])));
                            }
                        }
                        pv_issue(o, p, vd + vs * (SLOT / 16), n != 1 && n != nL + 1, n == hn + 1);
                    }
                    bar_arrive(2 - wg, 256);
                    wg_wait<1>();
                    reg_fence(s);
                    release_if(eb, ks, rel);
                    release_if(eb, 6, rel && n == 16);
                    if (n == nL - 1) {
                        tri_mask(s, x);
                        release_if(eb, 5, rel);
                        qa += SLOT / 16;
                    }
                    if (n == 2) fence_async_smem();
                    if (shifted) {
                        slot_wait(sb + BAR_FULL, fph, r);
                        wg_wait<0>();
                        reg_fence(o);
                        release_if(eb, vs, rel);
                        plain = true;
                        break;
                    }
                    float e[4 * EARLY];
#pragma unroll
                    for (int i = 0; i < 4 * EARLY; i++) {
                        e[i] = ex2(s[i]);
                        t[i & 3] = i < 4 ? e[i] : t[i & 3] + e[i];
                    }
                    reg_fence(e);
                    slot_wait(sb + BAR_FULL, fph, r);
                    wg_wait<0>();
                    reg_fence(o);
                    reg_fence(e);
                    release_if(eb, vs, rel);
#pragma unroll
                    for (int i = 0; i < 2 * EARLY; i++) p[i] = pack2(e[2 * i], e[2 * i + 1]);
                    softmax_exp<EARLY, 16>(s, p, t);
                    t[0] += t[1];
                    t[2] += t[3];
                    bad = __any_sync(0xffffffffu, fmaxf(t[0], t[2]) > SM_HI || (n == 0 && fminf(t[0], t[2]) < SM_LO));
                } while (!bad);
                if (!bad && !plain) break;
            }
            asm volatile("" : "+r"(toff));
            const uint32_t vs = r, ga = desc_k(sb + (hp ? 2 * (wg ^ kh ^ 1) : wg) * 8192);
            r = ring_next(r);
            slot_wait(sb + BAR_FULL, fph, 5);
            slot_wait(sb + BAR_FULL, fph, r);
            bar_sync(1 + wg, 256);
            gemm_issue<true>(s, ga + 5 * (SLOT / 16), wd + r * (SLOT / 16), 0, hp);
            pv_issue(o, p, vd + vs * (SLOT / 16), j, hn == 16);
            bar_arrive(2 - wg, 256);
            li[0] = rcp(quad_sum(l[0]));
            li[1] = rcp(quad_sum(l[1]));
            cimg = limg + (2 * j - 15) * 32 * SLOT + (wg ? -16384 : 16384);
            wg_wait<1>();
            release_if(eb, 5, rel);
            release_if(eb, r, rel && hp);
            wg_wait<0>();
            release_if(eb, vs, rel);
            reg_fence(o);
            img_store_global<0>(cimg, toff, o, li[0], li[1]);
            pend = 0x77;
            if (elected) TS(8 + 10 * hp + 20 * wg);
        }
        uint32_t otab = 0x2351604u;
        const uint32_t oa = desc_k(sb + (wg ^ kh ^ 1) * 16384);
        const int t7 = tid & 127, w4 = warp & 3, row = ort * 128 + kh * 64 + w4 * 16 + g;
#pragma unroll 1
        for (int i = 1; i < 15 - OFF - wg; i++) {
            const uint32_t as = o_next(otab), ws = o_next(otab);
            slot_wait(sb + BAR_FULL, fph, as);
            slot_wait(sb + BAR_FULL, fph, ws);
            bar_sync(1 + wg, 256);
            gemm_issue<false>(s, oa + as * (SLOT / 16), wd + ws * (SLOT / 16), 1, true);
            bar_arrive(2 - wg, 256);
            wg_wait<1>();
            reg_fence(o);
            if (i == 1) img_store_global<1>(cimg, toff, o, li[0], li[1]);
            if (i == 2) {
                img_store_global<2>(cimg, toff, o, li[0], li[1]);
                img_store_global<3>(cimg, toff, o, li[0], li[1]);
                __syncwarp();
                mbar_arrive_if(sb + BAR_DONE + 64, lane == 0);
            }
            wg_wait<0>();
            release_if(eb, as, rel);
            release_if(eb, ws, rel);
        }
        mbar_wait(sb + BAR_PF, 0);
        const uint32_t ep = lds32(sb + SM_EP);
        uint32_t eb2 = sb + BAR_END;
        if (wg == 0) {
            reg_fence(s);
            if (elected) TS(9);
            TT(1);
#pragma unroll
            for (int v = 0; v < 8; v++)
                st_pub(g_out + rb * OB + v * 128 + t7, make_uint4((pack2(s[8 * v], s[8 * v + 1]) & ~1u) | (ep & 1), pack2(s[8 * v + 2], s[8 * v + 3]),
                                                                      pack2(s[8 * v + 4], s[8 * v + 5]), pack2(s[8 * v + 6], s[8 * v + 7])), true);
            constexpr uint32_t s1 = SL_WF, s2 = SL_WD;
            bar_sync(4, 256);
            uint32_t wf[64];
            float wn[64];
            if (rb < NFFN) {
                slot_wait(sb + BAR_FULL, fph, s1);
                const uint32_t a = sb + s1 * SLOT + (w4 * 128 + (lane >> 4) * 8 + (lane & 7)) * 32 + (((lane >> 3) ^ (lane >> 2)) & 1) * 16;
#pragma unroll
                for (int i = 0; i < 16; i++)
                    asm volatile("ldmatrix.sync.aligned.m8n8.x4.trans.shared.b16 {%0, %1, %2, %3}, [%4];"
                                 : "=r"(wf[4 * i]), "=r"(wf[4 * i + 1]), "=r"(wf[4 * i + 2]), "=r"(wf[4 * i + 3])
                                 : "r"(a + (i >> 3) * 16384 + (i & 7) * 512) : "memory");
                slot_wait(sb + BAR_FULL, fph, s2);
#pragma unroll
                for (int i = 0; i < 16; i++) {
                    const uint2 w = *reinterpret_cast<const uint2*>(smem + s2 * SLOT + (kh ^ 1) * 16384 + i * 1024 + t7 * 8);
                    wn[4 * i] = bf_lo(w.x); wn[4 * i + 1] = bf_hi(w.x); wn[4 * i + 2] = bf_lo(w.y); wn[4 * i + 3] = bf_hi(w.y);
                }
                reg_fence(wn);
            }
            const uint32_t gbf = __ldcg(reinterpret_cast<const uint32_t*>(g_mod) + 1280 + rb * 2 + (lane >> 4));
            if (elected) TS(10);
            TT(2);
            const int pq = (2 * rb + (lane >> 4)) & 63, pv = (pq >> 2) / 3, cm = (pq >> 2) - 3 * pv;
            const uint4* cp = g_cand + w4 * 24 + c4;
            const uint4* fp = g_cand + (rb >> 5) * 24 + pv * 4 + (pq & 3);
            const uint4* yp = g_out + lane * OB + OB_Y + rb;
            uint4* yo = g_out + rb * OB + OB_Y + t7;
            uint32_t* op = reinterpret_cast<uint32_t*>(P.out) + rb * 2 + (lane >> 4);
            uint32_t ra = sb + SM_RED + (w4 * 32 + c4 * 8 + g) * 4;
            asm volatile("" : "+l"(cp), "+l"(fp), "+l"(yp), "+l"(yo), "+l"(op), "+r"(ra));
            sched_fence(eb2, P.zero);
            if (warp == 0) {
                asm volatile("st.shared.u32 [%0], %1;" ::"r"(sb + SM_EP + 24), "r"(best_key(g_out + ((rb & 33) + (lane & 15) * 2 + (lane & 16) * 4) * OB + OB_KEY, ep)) : "memory");
                mbar_arrive_if(sb + BAR_BEST, lane == 0);
            }
            bar_sync(3, 128);
            const uint32_t best = lds32(sb + SM_EP + 24), co = ((~best >> 9) & 127) * 192;
            TT(3);
            if (rb < NFFN) {
                uint4 cv[6];
                for (;;) {
                    uint32_t bad = 0;
#pragma unroll
                    for (int v = 0; v < 6; v++) cv[v] = ld_poll(cp + co + v * 4);
#pragma unroll
                    for (int v = 0; v < 6; v++) bad |= cv[v].w ^ ep;
                    if (__all_sync(0xffffffffu, bad == 0)) break;
                }
                TT(4);
                float d[4][4] = {};
#pragma unroll
                for (int k = 0; k < 8; k++) {
                    const uint32_t b0 = (&cv[(2 * k) / 3].x)[(2 * k) % 3], b1 = (&cv[(2 * k + 1) / 3].x)[(2 * k + 1) % 3];
                    mma16816(d[k & 1], wf + 4 * k, b0, b1);
                    mma16816(d[2 + (k & 1)], wf + 32 + 4 * k, b0, b1);
                }
                float u[4] = {d[0][0] + d[1][0], d[0][2] + d[1][2], d[2][0] + d[3][0], d[2][2] + d[3][2]};
                reg_fence(u);
                asm volatile("st.shared.f32 [%0], %1;" ::"r"(ra), "f"((c4 & 2) ? ((c4 & 1) ? u[3] : u[2]) : ((c4 & 1) ? u[1] : u[0])) : "memory");
                bar_sync(3, 128);
                const float* sred = reinterpret_cast<const float*>(smem + SM_RED);
                const float v = rbf((sred[lane] + sred[32 + lane]) + (sred[64 + lane] + sred[96 + lane]));
                const float act = rbf(rbf(v * sigmoid(v)) * __shfl_down_sync(0xffffffffu, v, 16));
                float y[4] = {0.f, 0.f, 0.f, 0.f};
#pragma unroll
                for (int k = 0; k < 16; k++) {
                    const float a = __shfl_sync(0xffffffffu, act, k);
#pragma unroll
                    for (int i = 0; i < 4; i++) y[i] = fmaf(a, wn[4 * k + i], y[i]);
                }
                st_pub(yo, make_uint4((__float_as_uint(y[0]) & ~15u) | (ep & 15), __float_as_uint(y[1]), __float_as_uint(y[2]), __float_as_uint(y[3])), true);
            }
            TT(5);
            if (warp == 0) {
                if (rb == 0 && lane == 0) g_sync.epoch[0] = ep;
                uint4 fh, fx;
                do { fh = ld_poll(fp + co); fx = ld_poll(fp + co + 96); } while (!poll_done(fh.w == ep && fx.w == ep, 50));
                const float sg = sigmoid(bf_hi((best & 0x80000000u) ? (best ^ 0x80000000u) : ~best));
                uint32_t fin[3] = {cm == 0 ? fh.x : cm == 1 ? fh.y : fh.z, cm == 0 ? fx.x : cm == 1 ? fx.y : fx.z, pack2(sg, sg)};
                op += ((~best >> 5) & 2047) * 256;
                asm volatile("" : "+l"(op));
                reg_fence(fin);
                if (rb >= NFFN) __nanosleep(YPRE);
                sched_fence(eb2, P.zero);
                uint4 yv[4];
                for (;;) {
#pragma unroll
                    for (int k = 0; k < 4; k++) yv[k] = ld_poll(yp + (k < 3 || lane < 16 ? k : 2) * 32 * OB);
                    if (poll_done((((yv[0].x ^ ep) | (yv[1].x ^ ep) | (yv[2].x ^ ep) | (yv[3].x ^ ep)) & 15) == 0, YSLEEP)) break;
                }
                TT(6);
                mbar_arrive_if(eb2, lane == 0);
                float y[4];
#pragma unroll
                for (int i = 0; i < 4; i++) {
                    const uint32_t mk = i ? ~0u : ~15u;
                    y[i] = (__uint_as_float((&yv[0].x)[i] & mk) + __uint_as_float((&yv[1].x)[i] & mk)) +
                           (__uint_as_float((&yv[2].x)[i] & mk) + (lane < 16 ? __uint_as_float((&yv[3].x)[i] & mk) : 0.f));
                }
                float z0 = ((lane & 16) ? y[2] : y[0]) + __shfl_xor_sync(0xffffffffu, (lane & 16) ? y[0] : y[2], 16);
                float z1 = ((lane & 16) ? y[3] : y[1]) + __shfl_xor_sync(0xffffffffu, (lane & 16) ? y[1] : y[3], 16);
#pragma unroll
                for (int o = 8; o > 0; o >>= 1) {
                    z0 += __shfl_xor_sync(0xffffffffu, z0, o);
                    z1 += __shfl_xor_sync(0xffffffffu, z1, o);
                }
                if ((lane & 15) == 0) *op = badd(fin[1], bmul(gbf, badd(fin[0], bmul(pack2(z0, z1), fin[2]))));
            }
            if (elected) TS(62);
            TT(7);
        } else {
            const float4* tf = reinterpret_cast<const float4*>(smem + SM_TAB) + c4;
            uint32_t x2[32];
            float tc[48];
#pragma unroll
            for (int k = 0; k < 16; k++) {
                const float4 c = tf[k * 4];
                tc[3 * k] = c.x; tc[3 * k + 1] = c.y; tc[3 * k + 2] = (g & 1) ? c.z : __uint_as_float(ONE2);
            }
            reg_fence(tc);
            bar_sync(2, 256);
#pragma unroll 1
            for (int i = 14; i < 17; i++) {
                const uint32_t as = o_next(otab), ws = o_next(otab);
                slot_wait(sb + BAR_FULL, fph, as);
                slot_wait(sb + BAR_FULL, fph, ws);
                gemm_issue<false>(s, oa + as * (SLOT / 16), wd + ws * (SLOT / 16), 1, true);
                wg_wait<1>();
            }
            const uint4* pr = g_out + (rb ^ 16) * OB + t7;
            uint4 pa[8];
            if (elected) TS(29);
            TT(1);
#pragma unroll
            for (int k = 0; k < 8; k++) {
                const uint4 v = lds128(sb + SL_X * SLOT + (kh ^ 1) * 16384 + k * 2048 + t7 * 16);
                x2[4 * k] = v.x; x2[4 * k + 1] = v.y; x2[4 * k + 2] = v.z; x2[4 * k + 3] = v.w;
            }
            wg_wait<0>();
            reg_fence(s);
            bar_arrive(4, 256);
            if (elected) TS(39);
            TT(2);
#pragma unroll
            for (int v = 0; v < 8; v++) pa[v] = ld_poll(pr + v * 128);
#pragma unroll
            for (int i = 0; i < 64; i++) s[i] = fmaf(tc[3 * (i >> 2) + (i & 1)], s[i], (i & 1) ? bf_hi(x2[i >> 1]) : bf_lo(x2[i >> 1]));
            reg_fence(s);
            sched_fence(eb2, P.zero);
            for (;;) {
                uint32_t bad = 0;
#pragma unroll
                for (int v = 0; v < 8; v++) asm("lop3.b32 %0, %0, %1, %2, 0xf6;" : "+r"(bad) : "r"(pa[v].x), "r"(ep));
                if (__all_sync(0xffffffffu, (bad & 1) == 0)) break;
                if (PSLEEP) __nanosleep(PSLEEP);
#pragma unroll
                for (int v = 0; v < 8; v++) pa[v] = ld_poll(pr + v * 128);
            }
            if (elected) TS(30);
            TT(3);
            float sd[4] = {}, q0[4] = {}, q1[4] = {};
#pragma unroll
            for (int k = 0; k < 8; k++) {
#pragma unroll
                for (int i = 4 * k; i < 4 * k + 4; i++) {
                    const uint32_t w = (i & 3) ? (&pa[k].x)[i & 3] : pa[k].x & ~1u;
                    x2[i] = pack2(fmaf(tc[3 * (i >> 1)], bf_lo(w), s[2 * i]), fmaf(tc[3 * (i >> 1) + 1], bf_hi(w), s[2 * i + 1]));
                }
                mma16816(sd, x2 + 4 * k, __float_as_uint(tc[6 * k + 2]), __float_as_uint(tc[6 * k + 5]));
                mma16816(q0, x2 + 4 * k, x2[4 * k], x2[4 * k + 2]);
                mma16816(q1, x2 + 4 * k, x2[4 * k + 1], x2[4 * k + 3]);
            }
            uint4* sp = g_out + rb * OB + OB_STAT + (w4 * 8 + g) * 2;
            st_pub(sp, make_uint4(__float_as_uint(sd[0]), __float_as_uint((g & 1) ? q0[1] : q0[0]), __float_as_uint(sd[1]), ep), c4 == g >> 1);
            st_pub(sp + 1, make_uint4(__float_as_uint(sd[2]), __float_as_uint((g & 1) ? q1[3] : q1[2]), __float_as_uint(sd[3]), ep), c4 == g >> 1);
            sched_fence(eb2, P.zero);
            if (elected) TS(56);
            TT(4);
            uint32_t cb[16], sh[16], gb[16];
#pragma unroll
            for (int i = 0; i < 16; i++) {
                const float4 c = tf[64 + i * 4];
                cb[i] = __float_as_uint(c.x); sh[i] = __float_as_uint(c.y); gb[i] = __float_as_uint(c.z);
            }
            const float ra = __uint_as_float(lds32(sb + SM_EP + 8)), rb0 = __uint_as_float(lds32(sb + SM_EP + 12));
            const uint4* rp = g_out + ((rb & ~33) + (c4 & 1) + (c4 & 2) * 16) * OB + OB_STAT + (w4 * 8 + g) * 2;
            uint32_t* kp = &g_out[rb * OB + OB_KEY].x + w4;
            uint4* cp = g_cand + (row >> 4) * 192 + cq * 24 + c4;
            uint32_t kt = ((2047 - row) << 5) | (ep & 31);
            asm volatile("" : "+l"(kp), "+l"(cp), "+r"(kt));
            uint4 r0, r1;
            do {
                r0 = ld_poll(rp);
                r1 = ld_poll(rp + 1);
            } while (!poll_done(r0.w == ep && r1.w == ep, SSLEEP));
            if (elected) TS(57);
            TT(5);
            float st[6] = {__uint_as_float(r0.x), __uint_as_float(r1.x), __uint_as_float(r0.y), __uint_as_float(r1.y), __uint_as_float(r0.z), __uint_as_float(r1.z)};
#pragma unroll
            for (int i = 0; i < 12; i++) st[i % 6] += __shfl_xor_sync(0xffffffffu, st[i % 6], 1 + i / 6);
            const float m0 = st[0] * (1.f / 512.f), m1 = st[1] * (1.f / 512.f);
            const float rs0 = ln_rstd(fmaxf(fmaf(-m0, m0, st[2] * (1.f / 512.f)), 0.f));
            const float rs1 = ln_rstd(fmaxf(fmaf(-m1, m1, st[3] * (1.f / 512.f)), 0.f));
            const uint32_t mb0 = pack2(m0, m0), mb1 = pack2(m1, m1);
            const uint32_t lg = pack2(fmaf(rs0, fmaf(-bf_lo(mb0), ra, st[4]), rb0), fmaf(rs1, fmaf(-bf_lo(mb1), ra, st[5]), rb0));
            const uint32_t u0 = lg << 16, u1 = lg & 0xffff0000u;
            const uint32_t k0 = ((u0 ^ (((int)u0 >> 31) | 0x80000000u)) & 0xffff0000u) | kt;
            const uint32_t k1 = ((u1 ^ (((int)u1 >> 31) | 0x80000000u)) & 0xffff0000u) | (kt - 256);
            const uint32_t kb = __reduce_max_sync(0xffffffffu, max(k0, k1));
            st_pub(kp, kb, lane == 0);
            const bool cand = kb == k0 || kb == k1;
#pragma unroll 1
            for (int it = 0; it < 3; it++) {
                bool put = it == 1 || !cand;
                if (it == 2) {
                    mbar_wait(sb + BAR_BEST, 0);
                    put = cand && lds32(sb + SM_EP + 24) != kb;
                }
                const bool hi = (kb == k1) != (it == 1);
                uint32_t cx[18], ch[18];
#pragma unroll
                for (int i = 0; i < 16; i++) {
                    cx[i] = hi ? x2[2 * i + 1] : x2[2 * i];
                    ch[i] = ln_apply(cx[i], hi ? mb1 : mb0, hi ? rs1 : rs0, cb[i], sh[i]);
                }
                cx[16] = cx[17] = ch[16] = ch[17] = 0;
#pragma unroll
                for (int v = 0; v < 6; v++) st_pub(cp + v * 4, make_uint4(ch[3 * v], ch[3 * v + 1], ch[3 * v + 2], ep), cand && it == 0);
#pragma unroll
                for (int v = 0; v < 6; v++) st_pub(cp + 96 + v * 4, make_uint4(cx[3 * v], cx[3 * v + 1], cx[3 * v + 2], ep), cand && it == 0);
                if (it == 0) TT(6);
                uint2* op = reinterpret_cast<uint2*>(P.out) + (row + 8 * hi) * 128 + cq * 32 + (c4 & 1) * 2 + (c4 >> 1);
#pragma unroll
                for (int i = 0; i < 16; i += 2) {
                    const uint32_t v0 = badd(cx[i], bmul(gb[i], ch[i])), v1 = badd(cx[i + 1], bmul(gb[i + 1], ch[i + 1]));
                    const uint32_t rv = __shfl_xor_sync(0xffffffffu, (c4 & 1) ? v0 : v1, 1);
                    if (put) op[i * 2] = (c4 & 1) ? make_uint2(rv, v1) : make_uint2(v0, rv);
                }
            }
            if (elected) TS(59);
            TT(7);
        }
        mbar_arrive_if(eb2, lane == 0 && warp != 0);
    }
}

typedef CUresult (*EncodeFn)(CUtensorMap*, CUtensorMapDataType, cuuint32_t, void*, const cuuint64_t*, const cuuint64_t*,
                             const cuuint32_t*, const cuuint32_t*, CUtensorMapInterleave, CUtensorMapSwizzle,
                             CUtensorMapL2promotion, CUtensorMapFloatOOBfill);

void make_3d(EncodeFn fn, CUtensorMap* m, const void* p, uint64_t cols, uint64_t rows, uint32_t br = 128, uint32_t nb = 2) {
    cuuint64_t dims[3] = {64, rows, cols / 64}, strides[2] = {cols * 2, 128};
    cuuint32_t box[3] = {64, br, nb}, es[3] = {1, 1, 1};
    fn(m, CU_TENSOR_MAP_DATA_TYPE_BFLOAT16, 3, const_cast<void*>(p), dims, strides, box, es, CU_TENSOR_MAP_INTERLEAVE_NONE,
       CU_TENSOR_MAP_SWIZZLE_128B, CU_TENSOR_MAP_L2_PROMOTION_L2_256B, CU_TENSOR_MAP_FLOAT_OOB_FILL_NONE);
}

}

extern "C" void kernel_launch(void* const* d_in, const int* in_sizes, int n_in, void* d_out, int out_size) {
    static EncodeFn fn = nullptr;
    if (!fn) {
        void* f = nullptr;
        cudaDriverEntryPointQueryResult st;
        cudaGetDriverEntryPoint("cuTensorMapEncodeTiled", &f, cudaEnableDefault, &st);
        fn = (EncodeFn)f;
        cudaFuncSetAttribute(fused_kernel, cudaFuncAttributeMaxDynamicSharedMemorySize, SMEM_BYTES);
    }
    CUtensorMap ckv, wq, wuk, wuv, wo, wg, wu, wm, xm;
    make_3d(fn, &ckv, d_in[1], 512, 2048, 128, 1);
    make_3d(fn, &xm, d_in[0], 512, 2048, 64);
    make_3d(fn, &wq, d_in[2], 4096, 512);
    make_3d(fn, &wuk, d_in[3], 4096, 512);
    make_3d(fn, &wuv, d_in[4], 4096, 512);
    make_3d(fn, &wo, d_in[5], 512, 4096);
    make_3d(fn, &wg, d_in[8], 1792, 512, 256, 1);
    make_3d(fn, &wu, d_in[9], 1792, 512, 256, 1);
    make_3d(fn, &wm, d_in[12], 3072, 512, 64, 4);
    Params p;
    p.x = (const bf16*)d_in[0];
    p.ckv = (const bf16*)d_in[1];
    p.wo = (const bf16*)d_in[5];
    p.wr = (const bf16*)d_in[7];
    p.wdown = (const bf16*)d_in[10];
    p.c = (const bf16*)d_in[11];
    p.out = (bf16*)d_out;
    p.zero = 0;
    fused_kernel<<<NCTA + NSPARE, 384, SMEM_BYTES>>>(ckv, wq, wuk, wuv, wo, wg, wu, wm, xm, p);
}
```

```cpp
#include <cuda.h>
#include <cuda_bf16.h>
#include <cuda_runtime.h>
#include <stdint.h>
#include <stdio.h>

namespace {

typedef __nv_bfloat16 bf16;
typedef unsigned long long u64;

constexpr int NCTA = 128, NSPARE = 4;
constexpr int SLOT = 32768;
constexpr int SM_BAR = 7 * SLOT;
constexpr int BAR_FULL = SM_BAR;
constexpr int BAR_EMPTY = BAR_FULL + 8 * 7;
constexpr int BAR_DONE = BAR_EMPTY + 8 * 7;
constexpr int BAR_FLAG = BAR_DONE + 8 * 9;
constexpr int BAR_PF = BAR_FLAG + 8 * 9;
constexpr int BAR_END = BAR_PF + 8;
constexpr int BAR_BEST = BAR_END + 8;
constexpr int SM_EP = BAR_END + 40;
constexpr int SM_RED = SM_BAR + 384;
constexpr int SM_TAB = SM_BAR + 1024;
constexpr int SMEM_BYTES = SM_BAR + 3072;
constexpr int NFFN = 112;
#define HINT 479
constexpr u64 L2_NORMAL = 0x1000000000000000ull, L2_FIRST = 0x12F0000000000000ull;
#define PFA 8
#define PFB 6
#define POLL_NS 50
#define MSPLIT 13
#define NSH 1
#define XPF 1
#define KSLEEP 400
#define YSLEEP 50
#define YPRE 400
#define SSLEEP 50
#define PSLEEP 100
#define KVG 7
#define EARLY2 4
constexpr int OFF = 2;
#define KN 16
#define KSLEEP2 60
#define EARLY 7
constexpr uint32_t SPIN_LIMIT = 1u << 22;
constexpr uint32_t ONE2 = 0x3f803f80u;

struct Sync {
    uint32_t cnt[16 * 8 * 8];
    uint32_t ctxcnt[16 * 32];
    uint32_t epoch[32];
};

__device__ __align__(1024) uint8_t g_img[2 * 512 * SLOT];
#define g_KV g_img
#define g_ctx (g_img + 512 * SLOT)
__device__ __align__(1024) uint8_t g_h[16 * 4 * SLOT];
constexpr int OB = 1248, OB_STAT = 1024, OB_Y = 1088, OB_KEY = 1216;
__device__ __align__(1024) uint4 g_out[128 * OB];
__device__ __align__(1024) bf16 g_mod[3072];
__device__ __align__(1024) uint32_t g_mod1[1024];
__device__ __align__(1024) uint4 g_cand[128 * 192];
__device__ __align__(1024) uint8_t g_wf[NFFN * SLOT];
__device__ __align__(1024) uint4 g_x2[128 * 1024];
__device__ __align__(1024) Sync g_sync;
#define TS(i)

#define TT(i)
#define PT()

struct Params {
    const bf16 *x, *ckv, *wo, *wr, *wdown, *c;
    bf16* out;
    int zero;
};

__device__ __forceinline__ void mbar_init(uint32_t bar, uint32_t cnt) {
    asm volatile("mbarrier.init.shared::cta.b64 [%0], %1;" ::"r"(bar), "r"(cnt) : "memory");
}
__device__ __forceinline__ void mbar_wait(uint32_t bar, uint32_t parity) {
    asm volatile("{\n.reg .pred p;\nL_%=:\nmbarrier.try_wait.parity.shared::cta.b64 p, [%0], %1;\n@!p bra L_%=;\n}" ::"r"(bar), "r"(parity) : "memory");
}
__device__ __forceinline__ void mbar_sleep(uint32_t bar) {
    if ((threadIdx.x & 31) == 0)
        asm volatile("{\n.reg .pred p;\nL_%=:\nmbarrier.try_wait.parity.shared::cta.b64 p, [%0], 0, 100000;\n@!p bra L_%=;\n}" ::"r"(bar) : "memory");
    __syncwarp();
}
__device__ __forceinline__ void mbar_watch(uint32_t bar, uint32_t parity) {
    asm volatile("{\n.reg .pred p;\n.reg .u32 n;\nmov.u32 n, 0;\n"
                 "L_%=:\nmbarrier.try_wait.parity.shared::cta.b64 p, [%0], %1;\n@p bra D_%=;\n"
                 "add.u32 n, n, 1;\nsetp.lt.u32 p, n, %2;\n@p bra L_%=;\ntrap;\nD_%=:\n}"
                 ::"r"(bar), "r"(parity), "n"(SPIN_LIMIT) : "memory");
}
__device__ __forceinline__ void step_watch(uint32_t a, uint32_t step) {
    asm volatile("{\n.reg .pred p;\n.reg .u32 n, v;\nmov.u32 n, 0;\n"
                 "L_%=:\nld.volatile.shared.u32 v, [%0];\nsetp.ge.u32 p, v, %1;\n@p bra D_%=;\nnanosleep.u32 400;\n"
                 "add.u32 n, n, 1;\nsetp.lt.u32 p, n, %2;\n@p bra L_%=;\ntrap;\nD_%=:\n}"
                 ::"r"(a), "r"(step), "n"(SPIN_LIMIT) : "memory");
}
__device__ __forceinline__ void mbar_arrive_if(uint32_t bar, bool on) {
    asm volatile("{\n.reg .pred p;\nsetp.ne.s32 p, %1, 0;\n@p mbarrier.arrive.shared::cta.b64 _, [%0];\n}" ::"r"(bar), "r"((int)on) : "memory");
}
__device__ __forceinline__ void tma3d_prefetch(const CUtensorMap* m, int row, int cb) {
    asm volatile("{\n.reg .pred p;\nelect.sync _|p, 0xffffffff;\n@p cp.async.bulk.prefetch.tensor.3d.L2.global [%0, {%1, %2, %3}];\n}"
                 ::"l"(m), "r"(0), "r"(row), "r"(cb) : "memory");
}
__device__ __forceinline__ void l2_prefetch(const void* p, uint32_t bytes) {
    asm volatile("{\n.reg .pred p;\nelect.sync _|p, 0xffffffff;\n@p cp.async.bulk.prefetch.L2.global [%0], %1;\n}" ::"l"(p), "r"(bytes) : "memory");
}
__device__ __forceinline__ void bulk_store(void* dst, uint32_t src, uint32_t bytes, bool first) {
    asm volatile("{\n.reg .pred p;\nelect.sync _|p, 0xffffffff;\n@p cp.async.bulk.global.shared::cta.bulk_group.L2::cache_hint [%0], [%1], %2, %3;\n}"
                 ::"l"(dst), "r"(src), "r"(bytes), "l"(first ? L2_FIRST : L2_NORMAL) : "memory");
}
__device__ __forceinline__ void flag_wait(const uint32_t* f, uint32_t target) {
    asm volatile("{\n.reg .pred p;\n.reg .u32 v;\n"
                 "L_%=:\nld.acquire.gpu.global.u32 v, [%0];\nsub.u32 v, v, %1;\nsetp.lt.s32 p, v, 0;\n@p nanosleep.u32 100;\n@p bra L_%=;\n}"
                 ::"l"(f), "r"(target) : "memory");
}
__device__ __forceinline__ uint4 ld_poll(const uint4* p) {
    uint4 v;
    asm volatile("{\n.reg .b128 t;\nld.relaxed.gpu.global.b128 t, [%4];\nmov.b128 {%0, %1, %2, %3}, t;\n}"
                 : "=r"(v.x), "=r"(v.y), "=r"(v.z), "=r"(v.w) : "l"(p) : "memory");
    return v;
}
__device__ __forceinline__ void st_pub(uint4* p, uint4 v, bool on) {
    asm volatile("{\n.reg .pred p;\n.reg .b128 t;\nsetp.ne.s32 p, %5, 0;\nmov.b128 t, {%1, %2, %3, %4};\n@p st.relaxed.gpu.global.b128 [%0], t;\n}"
                 ::"l"(p), "r"(v.x), "r"(v.y), "r"(v.z), "r"(v.w), "r"((int)on) : "memory");
}
__device__ __forceinline__ void st_pub(uint32_t* p, uint32_t v, bool on) {
    asm volatile("{\n.reg .pred p;\nsetp.ne.s32 p, %2, 0;\n@p st.relaxed.gpu.global.u32 [%0], %1;\n}" ::"l"(p), "r"(v), "r"((int)on) : "memory");
}
__device__ __forceinline__ bool poll_done(bool ok, uint32_t ns) {
    const int done = __all_sync(0xffffffffu, ok);
    asm volatile("{\n.reg .pred p;\nsetp.eq.s32 p, %0, 0;\n@p nanosleep.u32 %1;\n}" ::"r"(done), "r"(ns) : "memory");
    return done;
}
__device__ __forceinline__ void flag_add(uint32_t* p) {
    asm volatile("red.release.gpu.global.add.u32 [%0], 1;" ::"l"(p) : "memory");
}
__device__ __forceinline__ uint32_t lds32(uint32_t a) {
    uint32_t v;
    asm volatile("ld.shared.u32 %0, [%1];" : "=r"(v) : "r"(a) : "memory");
    return v;
}
__device__ __forceinline__ uint4 lds128(uint32_t a) {
    uint4 v;
    asm volatile("ld.shared.v4.u32 {%0, %1, %2, %3}, [%4];" : "=r"(v.x), "=r"(v.y), "=r"(v.z), "=r"(v.w) : "r"(a) : "memory");
    return v;
}
__device__ __forceinline__ void sched_fence(uint32_t& v, uint32_t z) {
    uint32_t ck;
    asm volatile("mov.u32 %0, %%clock;" : "=r"(ck)::"memory");
    v ^= ck & z;
}
__device__ __forceinline__ void fence_async_global() { asm volatile("fence.proxy.async.global;" ::: "memory"); }
__device__ __forceinline__ void fence_async_smem() { asm volatile("fence.proxy.async.shared::cta;" ::: "memory"); }
__device__ __forceinline__ void bar_sync(int id, int n) { asm volatile("bar.sync %0, %1;" ::"r"(id), "r"(n) : "memory"); }
__device__ __forceinline__ void bar_arrive(int id, int n) { asm volatile("bar.arrive %0, %1;" ::"r"(id), "r"(n) : "memory"); }
__device__ __forceinline__ void wg_fence() { asm volatile("wgmma.fence.sync.aligned;" ::: "memory"); }
__device__ __forceinline__ void wg_commit() { asm volatile("wgmma.commit_group.sync.aligned;" ::: "memory"); }
template <int N> __device__ __forceinline__ void wg_wait() { asm volatile("wgmma.wait_group.sync.aligned %0;" ::"n"(N) : "memory"); }
template <int N> __device__ __forceinline__ void reg_fence(float (&d)[N]) {
#pragma unroll
    for (int i = 0; i < N; i++) asm volatile("" : "+f"(d[i])::"memory");
}
template <int N> __device__ __forceinline__ void reg_fence(uint32_t (&d)[N]) {
#pragma unroll
    for (int i = 0; i < N; i++) asm volatile("" : "+r"(d[i])::"memory");
}
__device__ __forceinline__ uint32_t desc_k(uint32_t a) { return ((a & 0x3ffff) >> 4) | (1u << 16); }
__device__ __forceinline__ uint32_t desc_mn(uint32_t a) { return ((a & 0x3ffff) >> 4) | (1024u << 16); }

__device__ __forceinline__ uint64_t desc64(uint32_t lo, uint32_t hi) {
    uint64_t d;
    asm("mov.b64 %0, {%1, %2};" : "=l"(d) : "r"(lo), "r"(hi));
    return d;
}
__device__ __forceinline__ void desc_add(uint64_t& d, uint32_t x) { asm("add.u64 %0, %0, %1;" : "+l"(d) : "l"((uint64_t)x)); }

template <int TB>
__device__ __forceinline__ void wgmma_ss128(float (&d)[64], uint64_t da, uint64_t db, int acc) {
    asm volatile("{\n.reg .pred p;\nsetp.ne.b32 p, %66, 0;\n"
        "wgmma.mma_async.sync.aligned.m64n128k16.f32.bf16.bf16 {%0, %1, %2, %3, %4, %5, %6, %7, %8, %9, %10, %11, %12, %13, %14, %15, %16, %17, %18, %19, %20, %21, %22, %23, %24, %25, %26, %27, %28, %29, %30, %31, %32, %33, %34, %35, %36, %37, %38, %39, %40, %41, %42, %43, %44, %45, %46, %47, %48, %49, %50, %51, %52, %53, %54, %55, %56, %57, %58, %59, %60, %61, %62, %63}, %64, %65, p, 1, 1, 0, %67;\n}"
        : "+f"(d[0]), "+f"(d[1]), "+f"(d[2]), "+f"(d[3]), "+f"(d[4]), "+f"(d[5]), "+f"(d[6]), "+f"(d[7]), "+f"(d[8]), "+f"(d[9]), "+f"(d[10]), "+f"(d[11]), "+f"(d[12]), "+f"(d[13]), "+f"(d[14]), "+f"(d[15]), "+f"(d[16]), "+f"(d[17]), "+f"(d[18]), "+f"(d[19]), "+f"(d[20]), "+f"(d[21]), "+f"(d[22]), "+f"(d[23]), "+f"(d[24]), "+f"(d[25]), "+f"(d[26]), "+f"(d[27]), "+f"(d[28]), "+f"(d[29]), "+f"(d[30]), "+f"(d[31]), "+f"(d[32]), "+f"(d[33]), "+f"(d[34]), "+f"(d[35]), "+f"(d[36]), "+f"(d[37]), "+f"(d[38]), "+f"(d[39]), "+f"(d[40]), "+f"(d[41]), "+f"(d[42]), "+f"(d[43]), "+f"(d[44]), "+f"(d[45]), "+f"(d[46]), "+f"(d[47]), "+f"(d[48]), "+f"(d[49]), "+f"(d[50]), "+f"(d[51]), "+f"(d[52]), "+f"(d[53]), "+f"(d[54]), "+f"(d[55]), "+f"(d[56]), "+f"(d[57]), "+f"(d[58]), "+f"(d[59]), "+f"(d[60]), "+f"(d[61]), "+f"(d[62]), "+f"(d[63])
        : "l"(da), "l"(db), "r"(acc), "n"(TB));
}
template <int TB>
__device__ __forceinline__ void wgmma_ss128_init(float (&d)[64], uint64_t da, uint64_t db) {
    asm volatile("{\n.reg .pred p;\nsetp.ne.b32 p, 0, 0;\n"
        "wgmma.mma_async.sync.aligned.m64n128k16.f32.bf16.bf16 {%0, %1, %2, %3, %4, %5, %6, %7, %8, %9, %10, %11, %12, %13, %14, %15, %16, %17, %18, %19, %20, %21, %22, %23, %24, %25, %26, %27, %28, %29, %30, %31, %32, %33, %34, %35, %36, %37, %38, %39, %40, %41, %42, %43, %44, %45, %46, %47, %48, %49, %50, %51, %52, %53, %54, %55, %56, %57, %58, %59, %60, %61, %62, %63}, %64, %65, p, 1, 1, 0, %66;\n}"
        : "=f"(d[0]), "=f"(d[1]), "=f"(d[2]), "=f"(d[3]), "=f"(d[4]), "=f"(d[5]), "=f"(d[6]), "=f"(d[7]), "=f"(d[8]), "=f"(d[9]), "=f"(d[10]), "=f"(d[11]), "=f"(d[12]), "=f"(d[13]), "=f"(d[14]), "=f"(d[15]), "=f"(d[16]), "=f"(d[17]), "=f"(d[18]), "=f"(d[19]), "=f"(d[20]), "=f"(d[21]), "=f"(d[22]), "=f"(d[23]), "=f"(d[24]), "=f"(d[25]), "=f"(d[26]), "=f"(d[27]), "=f"(d[28]), "=f"(d[29]), "=f"(d[30]), "=f"(d[31]), "=f"(d[32]), "=f"(d[33]), "=f"(d[34]), "=f"(d[35]), "=f"(d[36]), "=f"(d[37]), "=f"(d[38]), "=f"(d[39]), "=f"(d[40]), "=f"(d[41]), "=f"(d[42]), "=f"(d[43]), "=f"(d[44]), "=f"(d[45]), "=f"(d[46]), "=f"(d[47]), "=f"(d[48]), "=f"(d[49]), "=f"(d[50]), "=f"(d[51]), "=f"(d[52]), "=f"(d[53]), "=f"(d[54]), "=f"(d[55]), "=f"(d[56]), "=f"(d[57]), "=f"(d[58]), "=f"(d[59]), "=f"(d[60]), "=f"(d[61]), "=f"(d[62]), "=f"(d[63])
        : "l"(da), "l"(db), "n"(TB));
}
template <int TB>
__device__ __forceinline__ void wgmma_ss64(float (&d)[32], uint64_t da, uint64_t db, int acc) {
    asm volatile("{\n.reg .pred p;\nsetp.ne.b32 p, %34, 0;\n"
        "wgmma.mma_async.sync.aligned.m64n64k16.f32.bf16.bf16 {%0, %1, %2, %3, %4, %5, %6, %7, %8, %9, %10, %11, %12, %13, %14, %15, %16, %17, %18, %19, %20, %21, %22, %23, %24, %25, %26, %27, %28, %29, %30, %31}, %32, %33, p, 1, 1, 0, %35;\n}"
        : "+f"(d[0]), "+f"(d[1]), "+f"(d[2]), "+f"(d[3]), "+f"(d[4]), "+f"(d[5]), "+f"(d[6]), "+f"(d[7]), "+f"(d[8]), "+f"(d[9]), "+f"(d[10]), "+f"(d[11]), "+f"(d[12]), "+f"(d[13]), "+f"(d[14]), "+f"(d[15]), "+f"(d[16]), "+f"(d[17]), "+f"(d[18]), "+f"(d[19]), "+f"(d[20]), "+f"(d[21]), "+f"(d[22]), "+f"(d[23]), "+f"(d[24]), "+f"(d[25]), "+f"(d[26]), "+f"(d[27]), "+f"(d[28]), "+f"(d[29]), "+f"(d[30]), "+f"(d[31])
        : "l"(da), "l"(db), "r"(acc), "n"(TB));
}
template <int TB>
__device__ __forceinline__ void wgmma_ss64_init(float (&d)[32], uint64_t da, uint64_t db) {
    asm volatile("{\n.reg .pred p;\nsetp.ne.b32 p, 0, 0;\n"
        "wgmma.mma_async.sync.aligned.m64n64k16.f32.bf16.bf16 {%0, %1, %2, %3, %4, %5, %6, %7, %8, %9, %10, %11, %12, %13, %14, %15, %16, %17, %18, %19, %20, %21, %22, %23, %24, %25, %26, %27, %28, %29, %30, %31}, %32, %33, p, 1, 1, 0, %34;\n}"
        : "=f"(d[0]), "=f"(d[1]), "=f"(d[2]), "=f"(d[3]), "=f"(d[4]), "=f"(d[5]), "=f"(d[6]), "=f"(d[7]), "=f"(d[8]), "=f"(d[9]), "=f"(d[10]), "=f"(d[11]), "=f"(d[12]), "=f"(d[13]), "=f"(d[14]), "=f"(d[15]), "=f"(d[16]), "=f"(d[17]), "=f"(d[18]), "=f"(d[19]), "=f"(d[20]), "=f"(d[21]), "=f"(d[22]), "=f"(d[23]), "=f"(d[24]), "=f"(d[25]), "=f"(d[26]), "=f"(d[27]), "=f"(d[28]), "=f"(d[29]), "=f"(d[30]), "=f"(d[31])
        : "l"(da), "l"(db), "n"(TB));
}
__device__ __forceinline__ void wgmma_rs128(float (&d)[64], uint32_t a0, uint32_t a1, uint32_t a2, uint32_t a3, uint64_t db, int acc) {
    asm volatile("{\n.reg .pred p;\nsetp.ne.b32 p, %69, 0;\n"
        "wgmma.mma_async.sync.aligned.m64n128k16.f32.bf16.bf16 {%0, %1, %2, %3, %4, %5, %6, %7, %8, %9, %10, %11, %12, %13, %14, %15, %16, %17, %18, %19, %20, %21, %22, %23, %24, %25, %26, %27, %28, %29, %30, %31, %32, %33, %34, %35, %36, %37, %38, %39, %40, %41, %42, %43, %44, %45, %46, %47, %48, %49, %50, %51, %52, %53, %54, %55, %56, %57, %58, %59, %60, %61, %62, %63}, {%64, %65, %66, %67}, %68, p, 1, 1, 1;\n}"
        : "+f"(d[0]), "+f"(d[1]), "+f"(d[2]), "+f"(d[3]), "+f"(d[4]), "+f"(d[5]), "+f"(d[6]), "+f"(d[7]), "+f"(d[8]), "+f"(d[9]), "+f"(d[10]), "+f"(d[11]), "+f"(d[12]), "+f"(d[13]), "+f"(d[14]), "+f"(d[15]), "+f"(d[16]), "+f"(d[17]), "+f"(d[18]), "+f"(d[19]), "+f"(d[20]), "+f"(d[21]), "+f"(d[22]), "+f"(d[23]), "+f"(d[24]), "+f"(d[25]), "+f"(d[26]), "+f"(d[27]), "+f"(d[28]), "+f"(d[29]), "+f"(d[30]), "+f"(d[31]), "+f"(d[32]), "+f"(d[33]), "+f"(d[34]), "+f"(d[35]), "+f"(d[36]), "+f"(d[37]), "+f"(d[38]), "+f"(d[39]), "+f"(d[40]), "+f"(d[41]), "+f"(d[42]), "+f"(d[43]), "+f"(d[44]), "+f"(d[45]), "+f"(d[46]), "+f"(d[47]), "+f"(d[48]), "+f"(d[49]), "+f"(d[50]), "+f"(d[51]), "+f"(d[52]), "+f"(d[53]), "+f"(d[54]), "+f"(d[55]), "+f"(d[56]), "+f"(d[57]), "+f"(d[58]), "+f"(d[59]), "+f"(d[60]), "+f"(d[61]), "+f"(d[62]), "+f"(d[63])
        : "r"(a0), "r"(a1), "r"(a2), "r"(a3), "l"(db), "r"(acc));
}

__device__ __forceinline__ uint32_t pack2(float lo, float hi) {
    uint32_t r;
    asm("cvt.rn.bf16x2.f32 %0, %1, %2;" : "=r"(r) : "f"(hi), "f"(lo));
    return r;
}
__device__ __forceinline__ float bf_lo(uint32_t v) { return __uint_as_float(v << 16); }
__device__ __forceinline__ float bf_hi(uint32_t v) { return __uint_as_float(v & 0xffff0000u); }
__device__ __forceinline__ float rbf(float v) { return bf_lo(pack2(v, v)); }
__device__ __forceinline__ uint32_t badd(uint32_t a, uint32_t b) {
    uint32_t r;
    asm("add.rn.bf16x2 %0, %1, %2;" : "=r"(r) : "r"(a), "r"(b));
    return r;
}
__device__ __forceinline__ uint32_t bsub(uint32_t a, uint32_t b) {
    uint32_t r;
    asm("sub.rn.bf16x2 %0, %1, %2;" : "=r"(r) : "r"(a), "r"(b));
    return r;
}
__device__ __forceinline__ uint32_t bmul(uint32_t a, uint32_t b) {
    uint32_t r;
    asm("mul.rn.bf16x2 %0, %1, %2;" : "=r"(r) : "r"(a), "r"(b));
    return r;
}
__device__ __forceinline__ uint32_t ln_apply(uint32_t x, uint32_t mb, float rs, uint32_t scale, uint32_t shift) {
    const uint32_t d = bsub(x, mb);
    return badd(bmul(pack2(bf_lo(d) * rs, bf_hi(d) * rs), scale), shift);
}
__device__ __forceinline__ float ex2(float v) {
    float r;
    asm("ex2.approx.ftz.f32 %0, %1;" : "=f"(r) : "f"(v));
    return r;
}
__device__ __forceinline__ float rcp(float v) {
    float r;
    asm("rcp.approx.ftz.f32 %0, %1;" : "=f"(r) : "f"(v));
    return r;
}
__device__ __forceinline__ float sqrt_fast(float v) {
    float r;
    asm("sqrt.approx.ftz.f32 %0, %1;" : "=f"(r) : "f"(v));
    return r;
}
__device__ __forceinline__ float ln_rstd(float var) { return rcp(rbf(sqrt_fast(rbf(rbf(var) + 1e-5f)))); }
__device__ __forceinline__ float sigmoid(float v) { return rcp(1.f + ex2(-1.4426950408889634f * v)); }
__device__ __forceinline__ float quad_sum(float v) {
    v += __shfl_xor_sync(0xffffffffu, v, 1);
    return v + __shfl_xor_sync(0xffffffffu, v, 2);
}

constexpr uint32_t HI_128 = 0x40000040u, HI_IMG = 0x80000080u, HI_Q = 0x80000040u;
template <int M, int RH>
__device__ __forceinline__ uint4 img_pack(const float (&d)[64], float s) {
    uint4 v;
    v.x = pack2(d[16 * M + 2 * RH] * s, d[16 * M + 2 * RH + 1] * s);
    v.y = pack2(d[16 * M + 4 + 2 * RH] * s, d[16 * M + 5 + 2 * RH] * s);
    v.z = pack2(d[16 * M + 8 + 2 * RH] * s, d[16 * M + 9 + 2 * RH] * s);
    v.w = pack2(d[16 * M + 12 + 2 * RH] * s, d[16 * M + 13 + 2 * RH] * s);
    return v;
}
template <int M>
__device__ __forceinline__ void img_store_global(uint32_t img, uint32_t toff, const float (&d)[64], float s0, float s1) {
    uint4* p = reinterpret_cast<uint4*>(g_img + (img + toff)) + M * 32;
    p[0] = img_pack<M, 0>(d, s0);
    p[128] = img_pack<M, 1>(d, s1);
}
__device__ __forceinline__ void sts128(uint32_t a, uint4 v) {
    asm volatile("st.shared.v4.b32 [%0], {%1, %2, %3, %4};" ::"r"(a), "r"(v.x), "r"(v.y), "r"(v.z), "r"(v.w) : "memory");
}
constexpr float SM_C = 0.08838834764831845f * 1.4426950408889634f;
__device__ __forceinline__ float pack2f(float lo, float hi) {
    float r;
    asm("{\n.reg .b32 t;\ncvt.rn.bf16x2.f32 t, %1, %2;\nmov.b32 %0, t;\n}" : "=f"(r) : "f"(hi), "f"(lo));
    return r;
}
template <int M, bool SCALE, bool PARK>
__device__ __forceinline__ void pack_group(float (&d)[64], float (&v)[8], float s0, float s1) {
#pragma unroll
    for (int i = 0; i < 8; i++) {
        const int k = 16 * M + 4 * (i & 3) + 2 * (i >> 2);
        v[i] = SCALE ? pack2f(d[k] * (i < 4 ? s0 : s1), d[k + 1] * (i < 4 ? s0 : s1)) : pack2f(d[k], d[k + 1]);
        if (PARK && M > 0) d[16 * (M > 0 ? M - 1 : 0) + i] = v[i];
    }
}
__device__ __forceinline__ uint32_t q_off(uint32_t toff) {
    asm volatile("" : "+r"(toff));
    return (((toff >> 1) & ~2047u) ^ 8192) + (toff & 511);
}
template <int M>
__device__ __forceinline__ void ctx_store_part(float4* p, float (&d)[64], float i0, float i1) {
    float v[8];
    pack_group<M, true, true>(d, v, i0, i1);
    p[M * 32] = make_float4(v[0], v[1], v[2], v[3]);
    p[M * 32 + 128] = make_float4(v[4], v[5], v[6], v[7]);
}
__device__ __forceinline__ void ctx_store(uint32_t img, uint32_t toff, float (&o)[64], float i0, float i1) {
    asm volatile("" : "+r"(toff));
    float4* p = reinterpret_cast<float4*>(g_img + (img + toff));
    ctx_store_part<0>(p, o, i0, i1); ctx_store_part<1>(p, o, i0, i1); ctx_store_part<2>(p, o, i0, i1); ctx_store_part<3>(p, o, i0, i1);
}

__device__ __forceinline__ void slot_wait(uint32_t bars, uint32_t& ph, uint32_t slot) {
    mbar_wait(bars + 8 * slot, (ph >> slot) & 1);
    ph ^= 1u << slot;
}
__device__ __forceinline__ void release_if(uint32_t eb, uint32_t slot, bool on) {
    asm volatile("{\n.reg .pred p;\nsetp.ne.s32 p, %1, 0;\n@p mbarrier.arrive.shared::cluster.b64 _, [%0];\n}" ::"r"(eb + 8 * slot), "r"((int)on) : "memory");
}
__device__ __forceinline__ void slot_expect(uint32_t sb, uint32_t slot) {
    asm volatile("{\n.reg .pred p;\nelect.sync _|p, 0xffffffff;\n@p mbarrier.arrive.expect_tx.shared::cta.b64 _, [%0], 32768;\n}"
                 ::"r"(sb + BAR_FULL + 8 * slot) : "memory");
}
__device__ __forceinline__ void slot_acquire(uint32_t sb, uint32_t& ph, uint32_t slot) {
    slot_wait(sb + BAR_EMPTY, ph, slot);
    slot_expect(sb, slot);
}
__device__ __forceinline__ void load_bulk(uint32_t sb, uint32_t slot, uint32_t off, const void* src, uint32_t bytes, bool both, bool first) {
    if (both)
        asm volatile("{\n.reg .pred p;\nelect.sync _|p, 0xffffffff;\n"
                     "@p cp.async.bulk.shared::cluster.global.mbarrier::complete_tx::bytes.multicast::cluster.L2::cache_hint [%0], [%1], %5, [%2], %4, %3;\n}"
                     ::"r"(sb + slot * SLOT + off), "l"(src), "r"(sb + BAR_FULL + 8 * slot), "l"(first ? L2_FIRST : L2_NORMAL), "h"((uint16_t)3),
                     "r"(bytes) : "memory");
    else
        asm volatile("{\n.reg .pred p;\nelect.sync _|p, 0xffffffff;\n"
                     "@p cp.async.bulk.shared::cluster.global.mbarrier::complete_tx::bytes.L2::cache_hint [%0], [%1], %4, [%2], %3;\n}"
                     ::"r"(sb + slot * SLOT + off), "l"(src), "r"(sb + BAR_FULL + 8 * slot), "l"(first ? L2_FIRST : L2_NORMAL), "r"(bytes) : "memory");
}
__device__ __forceinline__ void load_tile(uint32_t sb, uint32_t slot, uint32_t off, const CUtensorMap* m, int row, int cb, bool both, bool first) {
    if (both)
        asm volatile("{\n.reg .pred p;\nelect.sync _|p, 0xffffffff;\n"
                     "@p cp.async.bulk.tensor.3d.shared::cluster.global.mbarrier::complete_tx::bytes.multicast::cluster.L2::cache_hint [%0], [%1, {%3, %4, %5}], [%2], %7, %6;\n}"
                     ::"r"(sb + slot * SLOT + off), "l"(m), "r"(sb + BAR_FULL + 8 * slot), "r"(0), "r"(row), "r"(cb),
                     "l"(first ? L2_FIRST : L2_NORMAL), "h"((uint16_t)3) : "memory");
    else
        asm volatile("{\n.reg .pred p;\nelect.sync _|p, 0xffffffff;\n"
                     "@p cp.async.bulk.tensor.3d.shared::cluster.global.mbarrier::complete_tx::bytes.L2::cache_hint [%0], [%1, {%3, %4, %5}], [%2], %6;\n}"
                     ::"r"(sb + slot * SLOT + off), "l"(m), "r"(sb + BAR_FULL + 8 * slot), "r"(0), "r"(row), "r"(cb),
                     "l"(first ? L2_FIRST : L2_NORMAL) : "memory");
}
__device__ __forceinline__ uint32_t ring_next(uint32_t r) { return r == 4 ? 0 : r + 1; }
__device__ __forceinline__ uint32_t w_table(int hp) { return hp ? 0x3104u : 0x4210u; }
__device__ __forceinline__ uint32_t a_table(int hp) { return hp ? 0x625u : 0x635u; }
__device__ __forceinline__ uint32_t a_next(uint32_t& t) {
    const uint32_t s = t & 15;
    t = (t >> 4) | (s << 8);
    return s;
}
constexpr uint32_t O_TABLE = 0x1604235u;
constexpr uint32_t SL_X = 1, SL_WD = 3, SL_WF = 4;
__device__ __forceinline__ uint32_t o_next(uint32_t& t) {
    const uint32_t s = t & 15;
    t = (t >> 4) | (s << 24);
    return s;
}
__device__ __forceinline__ int o_head(int i, int kh) { return i < 16 ? 4 * (i & 7) + 2 * (kh ^ 1) + (i >> 3) : 29 + 2 * kh; }

template <bool INIT>
__device__ __forceinline__ void gemm_issue(float (&d)[64], uint32_t a, uint32_t b, int acc, bool img) {
    uint64_t da = desc64(a, img ? HI_IMG : HI_128), db = desc64(b, HI_128);
    wg_fence();
#pragma unroll
    for (int k = 0; k < 8; k++) {
        if (INIT && k == 0) wgmma_ss128_init<1>(d, da, db);
        else wgmma_ss128<1>(d, da, db, k ? 1 : acc);
        desc_add(da, !(k & 1) ? 2 : img ? 30 : k == 3 ? 1018 : 2);
        desc_add(db, 128);
    }
    wg_commit();
}

__device__ __forceinline__ void step_retire(uint32_t eb, bool rel, uint32_t pend) {
    wg_wait<0>();
    release_if(eb, pend & 7, rel && (pend & 7) != 7);
    release_if(eb, pend >> 4, rel && pend < 0x70);
}
template <bool ODD>
__device__ __forceinline__ void proj_tile(float (&acc)[64], float (&prev)[64], int t, int q0, uint32_t sb, int wg, uint32_t eb, bool rel, uint32_t& fph,
                                          uint32_t wtab, uint32_t& atab, uint32_t& pend, uint32_t prev_img, uint32_t toff, float s0, float s1,
                                          uint32_t (&v)[32]) {
    const uint32_t a0 = desc_k(sb + (wg ^ (ODD && t == 5)) * 8192), b0 = desc_mn(sb);
    int q = q0;
#pragma unroll 1
    do {
        const uint32_t ws = (wtab >> (4 * q)) & 15, as = a_next(atab);
        if (!ODD && t != 2) slot_wait(sb + BAR_FULL, fph, ws);
        slot_wait(sb + BAR_FULL, fph, as);
        step_retire(eb, rel, pend);
        if (ODD && q == 2 && t == 5) {
            const uint32_t a = sb + 5 * SLOT + q_off(toff);
#pragma unroll
            for (int i = 0; i < 8; i++) sts128(a + (i >> 2) * 16384 + (i & 2) * 256 + (i & 1) * 1024, make_uint4(v[4 * i], v[4 * i + 1], v[4 * i + 2], v[4 * i + 3]));
        }
        bar_sync(1 + wg, 256);
        gemm_issue<false>(acc, a0 + as * (SLOT / 16), b0 + ws * (SLOT / 16), q, false);
        bar_arrive(2 - wg, 256);
        pend = (ODD && q == 1 && t == 5 ? 7 : as) | (ODD && t != 1 ? ws : 7) << 4;
        wg_wait<1>();
        reg_fence(prev);
        if (ODD && t == 5) {
            if (q == 0) {
#pragma unroll
                for (int i = 0; i < 32; i++) {
                    const int k = 16 * (i >> 3) + 4 * (i & 3) + ((i >> 1) & 2);
                    v[i] = pack2(prev[k], prev[k + 1]);
                }
            }
        } else {
            if (q == 0) img_store_global<0>(prev_img, toff, prev, s0, s1);
            if (q == 1) img_store_global<1>(prev_img, toff, prev, s0, s1);
            if (q == 2) img_store_global<2>(prev_img, toff, prev, s0, s1);
            if (q == 3) img_store_global<3>(prev_img, toff, prev, s0, s1);
        }
    } while (++q < (ODD && t == 5 ? 3 : 4));
}

__device__ __forceinline__ void qk_issue(float (&s)[64], uint32_t q, uint32_t k) {
    wg_fence();
    uint64_t da = desc64(q, HI_Q), db = desc64(k, HI_IMG);
    wgmma_ss128_init<0>(s, da, db);
#pragma unroll
    for (int i = 1; i < 8; i++) {
        desc_add(da, (i & 1) ? 2 : i == 4 ? 990 : 30);
        desc_add(db, (i & 1) ? 2 : 30);
        wgmma_ss128<0>(s, da, db, 1);
    }
    wg_commit();
}
__device__ __forceinline__ void qk_issue(float (&s)[32], uint32_t q, uint32_t k) {
    wg_fence();
    uint64_t da = desc64(q, HI_Q), db = desc64(k, HI_IMG);
    wgmma_ss64_init<0>(s, da, db);
#pragma unroll
    for (int i = 1; i < 8; i++) {
        desc_add(da, (i & 1) ? 2 : i == 4 ? 990 : 30);
        desc_add(db, (i & 1) ? 2 : 30);
        wgmma_ss64<0>(s, da, db, 1);
    }
    wg_commit();
}
__device__ __forceinline__ void pv_issue(float (&o)[64], const uint32_t (&p)[32], uint32_t v, int acc, bool half) {
    uint64_t db = desc64(v, HI_IMG);
    if (half) {
        asm volatile("// half" ::: "memory");
        wg_fence();
#pragma unroll
        for (int i = 0; i < 4; i++) {
            wgmma_rs128(o, p[4 * i], p[4 * i + 1], p[4 * i + 2], p[4 * i + 3], db, i ? 1 : acc);
            desc_add(db, 256);
        }
        wg_commit();
        asm volatile("// half" ::: "memory");
    } else {
        wg_fence();
#pragma unroll
        for (int i = 0; i < 8; i++) {
            wgmma_rs128(o, p[4 * i], p[4 * i + 1], p[4 * i + 2], p[4 * i + 3], db, i ? 1 : acc);
            desc_add(db, 256);
        }
        wg_commit();
    }
}
__device__ __forceinline__ void tri_mask(float (&s)[64], float x) {
#pragma unroll
    for (int k = 0; k < 16; k++) {
        float b;
        asm("sub.sat.f32 %0, %1, %2;" : "=f"(b) : "f"((float)(8 * (k >> 1) + (k & 1))), "f"(x));
        const int i = 32 + 4 * (k >> 1) + (k & 1);
        asm("fma.rn.f32 %0, %1, 0fFF61B1E6, %0;" : "+f"(s[i]) : "f"(b));
        if (k < 14) asm("fma.rn.f32 %0, %1, 0fFF61B1E6, %0;" : "+f"(s[i + 6]) : "f"(b));
    }
}
__device__ __forceinline__ void tri_mask_copy(float (&s)[64], const float (&h)[32], float x) {
#pragma unroll
    for (int i = 0; i < 32; i++) {
            asm("{\n.reg .pred p;\nsetp.lt.f32 p, %2, %3;\nselp.f32 %0, 0fFF800000, %1, p;\n}"
                : "=f"(s[i]) : "f"(h[i]), "f"(x), "f"((float)(8 * (i >> 2) - 4 * (i & 2) + (i & 1))));
        s[32 + i] = __uint_as_float(0xff800000u);
    }
}
constexpr float SM_HI = 1152921504606846976.f, SM_LO = 1.f / 1152921504606846976.f;
__device__ __forceinline__ bool softmax_unsafe(float t0, float t1, bool first) {
    bool bad = __any_sync(0xffffffffu, fmaxf(t0, t1) > SM_HI);
    if (first) {
        uint32_t a = __ballot_sync(0xffffffffu, t0 >= SM_LO), b = __ballot_sync(0xffffffffu, t1 >= SM_LO);
        a |= a >> 1;
        b |= b >> 1;
        bad |= ((a | (a >> 2)) & (b | (b >> 2)) & 0x11111111u) != 0x11111111u;
    }
    return bad;
}
__device__ __forceinline__ void softmax_remax(const float (&s)[64], float (&m)[2], bool first, float& m0, float& m1, float& a0, float& a1) {
    m0 = fmaxf(s[0], s[1]), m1 = fmaxf(s[2], s[3]);
#pragma unroll
    for (int k = 1; k < 16; k++) {
        m0 = fmaxf(m0, fmaxf(s[4 * k], s[4 * k + 1]));
        m1 = fmaxf(m1, fmaxf(s[4 * k + 2], s[4 * k + 3]));
    }
    m0 = fmaxf(m0, __shfl_xor_sync(0xffffffffu, m0, 1));
    m1 = fmaxf(m1, __shfl_xor_sync(0xffffffffu, m1, 1));
    m0 = fmaxf(m0, __shfl_xor_sync(0xffffffffu, m0, 2));
    m1 = fmaxf(m1, __shfl_xor_sync(0xffffffffu, m1, 2));
    if (!first) {
        m0 = fmaxf(m0, 0.f);
        m1 = fmaxf(m1, 0.f);
    }
    a0 = first ? 1.f : ex2(-m0);
    a1 = first ? 1.f : ex2(-m1);
    m[0] += m0;
    m[1] += m1;
}
template <int J0, int J1>
__device__ __forceinline__ void softmax_exp(const float (&s)[64], uint32_t (&p)[32], float (&t)[4]) {
#pragma unroll
    for (int k = J0; k < J1; k++) {
        const float e0 = ex2(s[4 * k]), e1 = ex2(s[4 * k + 1]), e2 = ex2(s[4 * k + 2]), e3 = ex2(s[4 * k + 3]);
        if (k == 0) { t[0] = e0; t[1] = e1; t[2] = e2; t[3] = e3; }
        else { t[0] += e0; t[1] += e1; t[2] += e2; t[3] += e3; }
        p[2 * k] = pack2(e0, e1);
        p[2 * k + 1] = pack2(e2, e3);
    }
}
__device__ __forceinline__ void mma16816(float (&d)[4], const uint32_t* a, uint32_t b0, uint32_t b1) {
    asm("mma.sync.aligned.m16n8k16.row.col.f32.bf16.bf16.f32 {%0, %1, %2, %3}, {%4, %5, %6, %7}, {%8, %9}, {%0, %1, %2, %3};"
        : "+f"(d[0]), "+f"(d[1]), "+f"(d[2]), "+f"(d[3]) : "r"(a[0]), "r"(a[1]), "r"(a[2]), "r"(a[3]), "r"(b0), "r"(b1));
}
__device__ __forceinline__ uint32_t best_key(const uint4* keys, uint32_t ep) {
#pragma unroll 1
    for (;;) {
        const uint4 k = ld_poll(keys);
        const uint32_t best = __reduce_max_sync(0xffffffffu, max(max(k.x, k.y), max(k.z, k.w)));
        const uint32_t ok = __ballot_sync(0xffffffffu, (((k.x ^ ep) | (k.y ^ ep) | (k.z ^ ep) | (k.w ^ ep)) & 31) == 0);
        if (ok == ~0u) return best;
        __nanosleep(__popc(ok) < KN ? KSLEEP : KSLEEP2);
    }
}

__global__ void __cluster_dims__(2, 1, 1) __launch_bounds__(384, 1)
fused_kernel(const __grid_constant__ CUtensorMap tm_ckv, const __grid_constant__ CUtensorMap tm_wq,
             const __grid_constant__ CUtensorMap tm_wuk, const __grid_constant__ CUtensorMap tm_wuv,
             const __grid_constant__ CUtensorMap tm_wo, const __grid_constant__ CUtensorMap tm_wg,
             const __grid_constant__ CUtensorMap tm_wu,
             const __grid_constant__ CUtensorMap tm_wm, const __grid_constant__ CUtensorMap tm_x, const Params P) {
    extern __shared__ __align__(1024) uint8_t smem[];
    if (threadIdx.x == 352) {
        asm volatile("prefetch.tensormap [%0];" ::"l"(&tm_ckv) : "memory");
        asm volatile("prefetch.tensormap [%0];" ::"l"(blockIdx.x >= NCTA ? &tm_wm : (blockIdx.x & 1) ? &tm_wuv : &tm_wuk) : "memory");
    }
    const uint32_t sb = (uint32_t)__cvta_generic_to_shared(smem);
    const int tid = threadIdx.x, lane = tid & 31, warp = __shfl_sync(0xffffffffu, tid >> 5, 0), wg = warp >> 2;
    const uint32_t sm = blockIdx.x < 8 ? blockIdx.x + 124 : blockIdx.x - 8, smq = ((sm - 64) * 147) >> 11;
    const int rb = sm < 64 ? (sm & 14) * 8 + (sm >> 4) * 2 + (sm & 1)
                 : sm < 120 ? ((sm - 64 - smq * 14) & 14) * 8 + 24 + smq * 2 + (sm & 1) : sm < 124 ? sm + 8 : sm - 116;
    const int grp = rb >> 3, j = rb & 7, kh = (grp >> 1) & 1;
    const int cq = (j & 1) + ((grp >> 1) & 2), ort = (grp & 8) + (grp & 1) * 4 + (j >> 1);
    if (warp == 0) TS(0);

    const CUtensorMap* tw = (j & 1) ? &tm_wuv : &tm_wuk;
    if (lane == 0) {
        if (warp == 8) {
#pragma unroll
            for (int i = 0; i < 7; i++) mbar_init(sb + BAR_FULL + 8 * i, 1);
            fence_async_smem();
        } else if (warp < 11) {
            const int w = warp - (warp > 8);
            const u64 cnt = (w < 5 ? (rb < NCTA ? 0x888888884444444ull : 0x888888888888888ull) : 0x111812111111118ull) >> (12 * (w % 5));
#pragma unroll
            for (int i = 0; i < 3; i++) mbar_init(sb + BAR_EMPTY + 24 * w + 8 * i, ((uint32_t)cnt >> (4 * i)) & 15);
        }
        asm volatile("fence.mbarrier_init.release.cluster;" ::: "memory");
    }
    __syncwarp();
    asm volatile("barrier.cluster.arrive.relaxed.aligned;" ::: "memory");
    if (warp == 8) {
        if (rb < NCTA) {
#pragma unroll 1
            for (int u = 0; u < 4; u++) {
                const uint32_t ws = u + (u == 3), as = (0x635u >> (4 * u)) & 15;
                slot_expect(sb, ws);
                load_tile(sb, ws, 0, tw, u * 128, 4 * grp, false, HINT & 1);
                if (u == 3) break;
                slot_expect(sb, as);
                load_tile(sb, as, 0, &tm_ckv, (j >> 1) * 128, u * 2, false, false);
                load_tile(sb, as, 16384, &tm_ckv, (j >> 1) * 128, u * 2 + 1, false, false);
            }
        } else {
#pragma unroll 1
            for (int i = 0; i < 6; i++) {
                slot_expect(sb, i);
                load_tile(sb, i, 0, &tm_wm, i * 64, (rb - NCTA) * 4, false, HINT & 64);
                if (i > 3) tma3d_prefetch(&tm_wm, i * 64 + 128, (rb - NCTA) * 4);
            }
        }
    }
    asm volatile("barrier.cluster.wait.aligned;" ::: "memory");

    if (rb >= NCTA) {
        const int sp = rb - NCTA;
        const uint32_t ep = __ldcg(&g_sync.epoch[0]) + 1;
        uint32_t ph = 0, sl = 0;
        if (warp == 8) {
#pragma unroll 1
            for (int i = 6; i < 54 + 2 * OFF; i++) {
                slot_acquire(sb, ph, sl);
                const int k = i - 24;
                load_tile(sb, sl, 0, i < 24 ? &tm_wm : i >= 54 ? &tm_wo : (k & 2) ? &tm_wu : &tm_wg, i < 24 ? (i & 7) * 64 : i >= 54 ? (i - 38 - 2 * OFF) * 256 : (k & 1) * 256,
                          i < 24 ? (i >> 3) * 16 + sp * 4 : i >= 54 ? sp * 2 : sp * 7 + (k >> 2), false, true);
                if (++sl == 6) sl = 0;
                if (i == 51) { i = 53; sl = 0; }
            }
            bar_sync(4, 64);
            slot_wait(sb + BAR_EMPTY, ph, 4);
            slot_wait(sb + BAR_EMPTY, ph, 5);
            ph = 0x3f, sl = 0;
#pragma unroll 1
            for (int h = 0; h < 32; h++) {
                step_watch(sb + SM_EP + 16, h + 1);
                fence_async_global();
                const uint8_t* src = g_ctx + (size_t)(((h >> 1) ^ 8) * 32 + 30 - 4 * OFF) * SLOT + (h & 1) * 16384;
#pragma unroll 1
                for (int k = 0; k <= 2 * OFF; k++, src += 2 * SLOT) {
                    slot_wait(sb + BAR_DONE, ph, sl);
                    const uint32_t f = sb + BAR_FLAG + 8 * sl, d = sb + 4 * SLOT + sl * 16384;
                    asm volatile("{\n.reg .pred p;\nelect.sync _|p, 0xffffffff;\n@p mbarrier.arrive.expect_tx.shared::cta.b64 _, [%0], 16384;\n}" ::"r"(f) : "memory");
                    if (k == 0)
                        asm volatile("{\n.reg .pred p;\nelect.sync _|p, 0xffffffff;\n"
                                     "@p cp.async.bulk.tensor.3d.shared::cluster.global.mbarrier::complete_tx::bytes [%0], [%1, {%3, %4, %5}], [%2];\n}"
                                     ::"r"(d), "l"(&tm_x), "r"(f), "r"(0), "r"((h ^ 16) * 64), "r"(sp * 2) : "memory");
                    else
                        asm volatile("{\n.reg .pred p;\nelect.sync _|p, 0xffffffff;\n"
                                     "@p cp.async.bulk.shared::cluster.global.mbarrier::complete_tx::bytes [%0], [%1], 16384, [%2];\n}"
                                     ::"r"(d), "l"(src), "r"(f) : "memory");
                    if (++sl == 6) sl = 0;
                }
            }
        } else if (warp == 9) {
#pragma unroll 1
            for (int t = 0; t <= 16; t++) {
                asm volatile("st.release.cta.shared.u32 [%0], %1;" ::"r"(sb + SM_EP + 16), "r"(2 * t) : "memory");
                if (t == 0) bar_sync(4, 64);
                if (lane < 4 && t < 16) flag_wait(&g_sync.ctxcnt[(t ^ 8) * 32 + 24 + 2 * lane], ep);
                __syncwarp();
            }
        } else if (warp < 8) {
            const uint32_t c2 = __ldg(reinterpret_cast<const uint32_t*>(P.c) + tid);
            uint32_t* sc = reinterpret_cast<uint32_t*>(smem + SM_TAB);
            sc[tid] = pack2(bf_lo(c2) * sigmoid(bf_lo(c2)), bf_hi(c2) * sigmoid(bf_hi(c2)));
            bar_sync(1, 256);
            const uint32_t a = sb + (warp >> 1) * 8192 + ((lane >> 4) * 8 + (lane & 7)) * 128, ch = (warp & 1) * 4 + ((lane >> 3) & 1);
#pragma unroll 1
            for (int ps = 0; ps < 3; ps++) {
                float d[2][4] = {};
#pragma unroll 1
                for (int bt = 0; bt < 8; bt++) {
                    slot_wait(sb + BAR_FULL, ph, sl);
#pragma unroll
                    for (int i = 0; i < 8; i++) {
                        uint32_t w[4];
                        asm volatile("ldmatrix.sync.aligned.m8n8.x4.trans.shared.b16 {%0, %1, %2, %3}, [%4];" : "=r"(w[0]), "=r"(w[1]), "=r"(w[2]), "=r"(w[3])
                                     : "r"(a + sl * SLOT + (i >> 1) * 2048 + (((ch + 2 * (i & 1)) ^ (lane & 7)) << 4)) : "memory");
                        mma16816(d[i & 1], w, sc[bt * 32 + (i >> 1) * 8 + (lane & 3)], sc[bt * 32 + (i >> 1) * 8 + 4 + (lane & 3)]);
                    }
                    __syncwarp();
                    mbar_arrive_if(sb + BAR_EMPTY + 8 * sl, lane == 0);
                    if (++sl == 6) sl = 0;
                }
                const float v = (lane & 2) ? ((lane & 1) ? d[1][2] : d[1][0]) : ((lane & 1) ? d[0][2] : d[0][0]);
                const int col = sp * 256 + warp * 32 + (lane & 3) * 8 + (lane >> 2);
                if (ps == 0) st_pub(g_mod1 + col, (pack2(0.f, v) & 0xffff0000u) | (ep & 0xffffu), true);
                else g_mod[ps * 1024 + col] = __float2bfloat16_rn(v);
                if (warp == 0) TS(1 + ps);
            }
#pragma unroll 1
            for (int k = 0; k < 28; k++) {
                slot_wait(sb + BAR_FULL, ph, sl);
                uint4* dst = reinterpret_cast<uint4*>(g_wf) + (sp * 28 + (k & ~3)) * 2048 + (k & 3) * 512 + tid;
#pragma unroll 4
                for (int i = 0; i < 8; i++) {
                    const int row = (i & 1) * 128 + (tid >> 1);
                    __stcs(dst + (i >> 1) * 2048 + (i & 1) * 256, lds128(sb + sl * SLOT + row * 128 + ((((i & 6) + ((tid ^ (row >> 2)) & 1)) ^ (row & 7)) << 4)));
                }
                __syncwarp();
                mbar_arrive_if(sb + BAR_EMPTY + 8 * sl, lane == 0);
                if (++sl == 6) sl = 0;
            }
            bar_sync(1, 256);
            if (tid < 2) {
                flag_add(&g_sync.cnt[7 * 8]);
                flag_wait(&g_sync.cnt[7 * 8], 8 * ep);
            }
            if (warp == 0) TS(4);
            bar_sync(1, 256);
            uint32_t ga[16], x2[32];
#pragma unroll
            for (int i = 0; i < 16; i++) ga[i] = __ldcg(reinterpret_cast<const uint32_t*>(g_mod) + 512 + sp * 64 + (lane & 3) + 4 * i);
#pragma unroll 1
            for (int i = 0; i < 2 * OFF; i++) slot_wait(sb + BAR_FULL, ph, i);
            float d[64];
            uint32_t u = (2 * OFF + 1) * wg, up = 0;
            if (wg == 1) bar_arrive(2, 256);
#pragma unroll 1
            for (int h = wg; h < 32; h += 2) {
                mbar_wait(sb + BAR_FLAG + 8 * u, up);
                const uint32_t xa = sb + 4 * SLOT + u * 16384 + ((warp & 3) * 16 + (lane & 15)) * 128;
#pragma unroll
                for (int k = 0; k < 8; k++)
                    asm volatile("ldmatrix.sync.aligned.m8n8.x4.shared.b16 {%0, %1, %2, %3}, [%4];"
                                 : "=r"(x2[4 * k]), "=r"(x2[4 * k + 1]), "=r"(x2[4 * k + 2]), "=r"(x2[4 * k + 3])
                                 : "r"(xa + (k >> 2) * 8192 + (((2 * (k & 3) + (lane >> 4)) ^ (lane & 7)) << 4)) : "memory");
                mbar_arrive_if(sb + BAR_DONE + 8 * u, lane < 2);
                bar_sync(2 + wg, 256);
#pragma unroll 1
                for (int k = 0; k < 2 * OFF; k++) {
                    const uint32_t pu = u;
                    if (++u == 6) { u = 0; up ^= 1; }
                    mbar_wait(sb + BAR_FLAG + 8 * u, up);
                    gemm_issue<false>(d, desc_k(sb + 4 * SLOT) + u * 1024, desc_mn(sb) + k * (SLOT / 16), k, true);
                    wg_wait<1>();
                    mbar_arrive_if(sb + BAR_DONE + 8 * pu, lane < 2 && k);
                }
                if (h < 31) bar_arrive(3 - wg, 256);
                wg_wait<0>();
                reg_fence(d);
                mbar_arrive_if(sb + BAR_DONE + 8 * u, lane < 2);
                u += 2 * OFF + 2;
                if (u >= 6) { u -= 6; up ^= 1; }
                uint4* op = g_x2 + ((h ^ 16) * 4 + sp) * 1024 + (tid & 127);
#pragma unroll
                for (int v = 0; v < 8; v++) {
                    uint32_t y[4];
#pragma unroll
                    for (int i = 0; i < 4; i++) {
                        const int k = 4 * v + i;
                        y[i] = pack2(fmaf(bf_lo(ga[k >> 1]), d[2 * k], bf_lo(x2[k])), fmaf(bf_hi(ga[k >> 1]), d[2 * k + 1], bf_hi(x2[k])));
                    }
                    op[v * 128] = make_uint4(y[0], y[1], y[2], y[3]);
                }
            }
            bar_sync(1, 256);
            if (tid == 0) flag_add(&g_sync.cnt[15 * 8]);
            if (warp == 0) TS(5);
        }
        return;
    }

    if (wg == 2) {
        asm volatile("setmaxnreg.dec.sync.aligned.u32 40;");
        if (warp == 8) {
            const uint32_t rank = j & 1, half = rank * 16384;
            uint32_t eph = 0, r = 0;
            *reinterpret_cast<volatile uint32_t*>(smem + SM_EP + 20) = 0;
#pragma unroll 1
            for (int hp = 0; hp < 2; hp++) {
                uint32_t wtab = w_table(hp), atab = a_table(hp);
                const int hc = 4 * grp + 2 * hp;
#pragma unroll 1
                for (int u = 3 - 3 * hp; u < 16; u++) {
                    if (hp && u < 4) {
                        const uint32_t ws = (wtab >> (4 * u)) & 15;
                        slot_acquire(sb, eph, ws);
                        load_tile(sb, ws, 0, tw, u * 128, hc, false, HINT & 1);
                        PT();
                    }
                    if (hp == 1 && (u & 7) == 4) mbar_wait(sb + BAR_FLAG + 24 + (u & 8), 0);
                    const uint32_t as = a_next(atab);
                    slot_acquire(sb, eph, as);
                    load_tile(sb, as, half, &tm_ckv, ((u & 12) + (j >> 1)) * 128, (u & 3) * 2 + rank, true, (HINT & 8) && hp);
                    PT();
                    if (hp == 1 && (u | 2) == 3 && lane == 0)
                        asm volatile("red.relaxed.gpu.global.add.u32 [%0], 1;" ::"l"(&g_sync.cnt[(grp * 8 + 3 + (u >> 1)) * 8]) : "memory");
                }
                const uint8_t* src = g_h + (15 - j) * 4 * SLOT;
#pragma unroll 1
                for (int u = 0; u < 8; u++) {
                    if (u == 0 || u == KVG) {
                        mbar_wait(sb + BAR_FLAG + (u ? 8 + 32 * hp : 0), 0);
                        fence_async_global();
                    }
                    if (u < 4) {
                        const uint32_t ws = (wtab >> (4 * u)) & 15;
                        slot_acquire(sb, eph, ws);
                        load_tile(sb, ws, 0, &tm_wq, u * 128, hc, false, HINT & 1);
                        PT();
                    }
                    const uint32_t as = a_next(atab);
                    slot_acquire(sb, eph, as);
                    load_bulk(sb, as, 0, src, SLOT, false, (HINT & 8) && hp);
                    PT();
                    src += u == 3 ? (8 * j - 63) * SLOT : SLOT;
                }
                const int step = hp ? -2 * SLOT : 2 * SLOT;
                src = g_KV + (size_t)(grp * 32 + 30 * hp) * SLOT + half - step;
#pragma unroll 1
                for (int n = 0; n <= 17; n++) {
                    if (n == 8) {
                        mbar_wait(sb + BAR_FLAG + 16 + 32 * hp, 0);
                        fence_async_global();
                    }
                    const uint8_t* v = src + SLOT;
                    src += n < 16 - j ? step : n == 16 - j ? (2 * j - 15) * step : -step;
                    if (n < 17) {
                        slot_acquire(sb, eph, r);
                        if (n != 15 - (j & 6)) load_bulk(sb, r, half, src, SLOT / 2, true, HINT & 4);
                        else load_bulk(sb, r, 0, src - half, SLOT, false, HINT & 4);
                        PT();
                        r = ring_next(r);
                    }
                    if (n) {
                        slot_acquire(sb, eph, r);
                        if (n != 16 - (j & 6)) load_bulk(sb, r, half, v, SLOT / 2, true, HINT & 4);
                        else load_bulk(sb, r, 0, v - half, SLOT, false, HINT & 4);
                        PT();
                        r = ring_next(r);
                    }
                    asm volatile("st.volatile.shared.u32 [%0], %1;" ::"r"(sb + SM_EP + 16), "r"(18 * hp + n + 1) : "memory");
                }
            }
            uint32_t otab = O_TABLE, ready = 0;
#pragma unroll 1
            for (int i = 0; i < 17; i += i == 7 - OFF ? 1 + OFF : 1) {
                if (!((ready >> i) & 1)) {
                    do {
                        asm volatile("ld.acquire.cta.shared.u32 %0, [%1];" : "=r"(ready) : "r"(sb + SM_EP + 20) : "memory");
                        ready = __shfl_sync(0xffffffffu, ready, 0);
                    } while (!((ready >> i) & 1));
                    fence_async_global();
                }
                const int head = o_head(i, kh);
                const uint32_t as = o_next(otab), ws = o_next(otab), off = i < 15 ? half : kh * 16384;
                slot_acquire(sb, eph, as);
                load_bulk(sb, as, off, g_ctx + (size_t)(ort * 32 + head) * SLOT + off, SLOT / 2, i < 15, HINT & 16);
                if (i >= 15) load_bulk(sb, as, off ^ 16384, i == 15 ? g_x2 + ((ort * 2 + kh) * 4 + cq) * 1024 : reinterpret_cast<const uint4*>(P.wdown) + min(rb, NFFN - 1) * 1024, SLOT / 2, false, false);
                PT();
                slot_acquire(sb, eph, ws);
                load_tile(sb, ws, 0, &tm_wo, head * 128, cq * 2, false, HINT & 2);
                PT();
                if (i == 0) o_next(otab);
            }
            if (rb < NFFN) {
                slot_acquire(sb, eph, SL_WF);
                load_bulk(sb, SL_WF, 0, g_wf + rb * SLOT, SLOT, false, false);
            }
        } else if (warp == 9) {
            *reinterpret_cast<volatile uint32_t*>(smem + SM_EP + 16) = 0;
            l2_prefetch(P.ckv + rb * 2048, 4096);
            mbar_watch(sb + BAR_FULL, 0);
            l2_prefetch(P.ckv + 512 * 512 + rb * 2048, 4096);
            mbar_watch(sb + BAR_FULL + 8 * XPF, 0);
            l2_prefetch(P.x + rb * 8192, 16384);
            mbar_watch(sb + BAR_FULL + 8 * 4, 0);
            l2_prefetch(P.ckv + 1024 * 512 + rb * 4096, 8192);
            TS(40);
#pragma unroll 1
            for (int i = 0; i < 13; i++) {
                step_watch(sb + SM_EP + 16, i == 0 ? 0 : i < 5 ? PFA + i : 13 + PFB + i);
                if (i == 10) mbar_watch(sb + BAR_FLAG + 8 * 7, 0);
                const int rf = min(rb, NFFN - 1), pc = 4 * (i - 5) + cq;
                const uint8_t* p = i == 3 ? reinterpret_cast<const uint8_t*>(P.ckv) + rb * 16384
                                 : i == 4 ? g_h + rb * 16384
                                 : i < 8 ? g_ctx + (size_t)(ort * 32 + o_head(pc >> 1, kh)) * SLOT + (pc & 1) * 16384
                                 : i < 10 ? reinterpret_cast<const uint8_t*>(P.wo) + (grp * 16 + (i & 1) * 8 + j) * 16384
                                 : i == 10 ? reinterpret_cast<const uint8_t*>(P.wdown) + rf * 16384 : g_wf + rf * SLOT + (i & 1) * 16384;
                if (i >= 3) l2_prefetch(p, 16384);
                else if ((i | j) & 1) tma3d_prefetch(i == 1 ? tw : &tm_wq, (j >> 1) * 128, grp * 4 + (i ? 2 : 0));
            }
            const uint32_t v = lds32(sb + SM_EP) - 1;
            sts128(sb + SM_RED + lane * 16, make_uint4(v, v, v, v));
            fence_async_smem();
            __syncwarp();
#pragma unroll 1
            for (int i = 0; i < OB / 32; i++) bulk_store(g_out + rb * OB + i * 32, sb + SM_RED, 512, false);
            asm volatile("cp.async.bulk.commit_group;\ncp.async.bulk.wait_group 0;" ::: "memory");
            fence_async_global();
            __syncwarp();
            mbar_arrive_if(sb + BAR_PF, lane == 0);
            if (lane == 0) mbar_watch(sb + BAR_END, 0);
        } else {
            const uint32_t ep = __ldcg(&g_sync.epoch[0]) + 1;
            asm volatile("st.shared.u32 [%0], %1;" ::"r"(sb + SM_EP), "r"(ep) : "memory");
            mbar_wait(sb + BAR_FULL + 8 * 4, 0);
            {
                uint4 v[4];
                for (;;) {
                    uint32_t bad = 0;
#pragma unroll
                    for (int k = 0; k < 4; k++) v[k] = ld_poll(reinterpret_cast<const uint4*>(g_mod1) + (warp & 1) * 128 + k * 32 + lane);
#pragma unroll
                    for (int k = 0; k < 4; k++) bad |= (v[k].x ^ ep) | (v[k].y ^ ep) | (v[k].z ^ ep) | (v[k].w ^ ep);
                    if (poll_done((bad & 0xffff) == 0, 100)) break;
                }
                const uint32_t one = (warp & 1) ? ONE2 : 0x80008000u;
#pragma unroll
                for (int k = 0; k < 4; k++)
                    *reinterpret_cast<uint2*>(smem + SM_TAB + (warp & 1) * 1024 + k * 256 + lane * 8) =
                        make_uint2(badd(__byte_perm(v[k].x, v[k].y, 0x7632), one), badd(__byte_perm(v[k].z, v[k].w, 0x7632), one));
            }
            __syncwarp();
            mbar_arrive_if(sb + BAR_FLAG + 8 * 8, lane == 0);
            if (warp == 10) {
#pragma unroll 1
                for (int i = 0; i < 9; i++) {
                    mbar_sleep(sb + BAR_DONE + 8 * i);
                    if (lane == 0) flag_add(i && ((i - 1) & 2) ? &g_sync.ctxcnt[((i & 1) ? 15 - j : j) * 32 + 2 * grp + (i > 4)] : &g_sync.cnt[(grp * 8 + i) * 8]);
                    if (i == 0) TS(43);
                }
            } else {
                TS(42);
#pragma unroll 1
                for (int i = 0; i < 8; i++) {
                    mbar_sleep(sb + BAR_DONE + 8 * (i == 7 ? 6 : i == 4 ? 3 : i));
                    if (lane < 2) flag_wait(&g_sync.cnt[((i == 0 ? (lane ? j : 15 - j) : i == 7 ? 0 : grp) * 8 + i) * 8], 8 * ep);
                    __syncwarp();
                    mbar_arrive_if(sb + BAR_FLAG + 8 * i, lane == 0 && i < 7);
                    TS(48 + i);
                }
                const uint32_t *mp = reinterpret_cast<const uint32_t*>(g_mod) + lane, *wp = reinterpret_cast<const uint32_t*>(P.wr) + lane;
                float ra = 0.f, rs = 0.f;
#pragma unroll 1
                for (int k = 0; k < 256; k += 32) {
                    const uint32_t ga = __ldcg(mp + 512 + k), sh = __ldcg(mp + 768 + k), c1 = badd(__ldcg(mp + 1024 + k), ONE2);
                    const uint32_t gb = __ldcg(mp + 1280 + k), ww = __ldg(wp + k);
                    const uint32_t a = bmul(c1, ww);
                    ra += bf_lo(a) + bf_hi(a);
                    rs = fmaf(bf_lo(sh), bf_lo(ww), fmaf(bf_hi(sh), bf_hi(ww), rs));
                    if (k >> 6 == cq) {
                        sts128(sb + SM_TAB + ((k & 32) + lane) * 16, make_uint4(ga << 16, ga & 0xffff0000u, a, 0));
                        sts128(sb + SM_TAB + 1024 + ((k & 32) + lane) * 16, make_uint4(c1, sh, gb, 0));
                    }
                }
#pragma unroll 1
                for (int o = 16; o > 0; o >>= 1) {
                    ra += __shfl_xor_sync(0xffffffffu, ra, o);
                    rs += __shfl_xor_sync(0xffffffffu, rs, o);
                }
                *reinterpret_cast<float2*>(smem + SM_EP + 8) = make_float2(ra, rs);
                __syncwarp();
                mbar_arrive_if(sb + BAR_FLAG + 8 * 7, lane == 0);
                const uint32_t* f = lane < 17 ? &g_sync.ctxcnt[ort * 32 + o_head(lane, kh)] : &g_sync.cnt[15 * 8];
                uint32_t ready = 0;
                while (ready != ~0u) {
                    uint32_t v, now;
                    do {
                        asm volatile("ld.acquire.gpu.global.u32 %0, [%1];" : "=r"(v) : "l"(f) : "memory");
                        now = __ballot_sync(0xffffffffu, (int)(v - (lane < 17 ? ep : NSPARE * ep)) >= 0);
                    } while (!poll_done(now != ready, POLL_NS));
                    if (lane == 0) asm volatile("st.release.cta.shared.u32 [%0], %1;" ::"r"(sb + SM_EP + 20), "r"(now & ((now >> 2) | 0x7fff)) : "memory");
                    if ((ready & 0xff) != 0xff && (now & 0xff) == 0xff) mbar_sleep(sb + BAR_DONE + 8 * 7);
                    ready = now;
                }
                TS(45);
            }
        }
    } else {
        const bool elected = (tid & 127) == 0, rel = (tid & 95) == 0;
        uint32_t eb;
        asm("mapa.shared::cluster.u32 %0, %1, %2;" : "=r"(eb) : "r"(sb + BAR_EMPTY), "r"(warp & 1));
        const int g = lane >> 2, c4 = lane & 3;
        uint32_t toff = warp * 4096 + g * 64 + ((c4 ^ (g >> 1)) << 4);
        uint32_t fph = 0x3f, r = 0;
        if (wg == 1) bar_arrive(1, 256);
        const uint32_t kd = desc_k(sb), wd = desc_mn(sb), vd = ((sb & 0x3ffff) >> 4) | (32u << 16);
        const int nL = 16 - j, hn = nL - 1 + wg;
        float s[64], o[64], li[2] = {0.f, 0.f};
        uint32_t cimg = 0;
        const float sc = (j & 1) ? 1.f : SM_C;
#pragma unroll 1
        for (int q = 0; q < 3; q++) {
            const uint32_t as = (0x635u >> (4 * q)) & 15;
            mbar_wait(sb + BAR_FULL + 8 * q, 0);
            mbar_wait(sb + BAR_FULL + 8 * as, 0);
            bar_sync(1 + wg, 256);
            gemm_issue<false>(s, kd + wg * 512 + as * (SLOT / 16), wd + q * (SLOT / 16), q, false);
            bar_arrive(2 - wg, 256);
            wg_wait<0>();
            release_if(eb, as, rel);
        }
        {
            const int xrow = rb * 16 + warp * 2;
            const uint4* xp = reinterpret_cast<const uint4*>(P.x) + xrow * 64;
            const uint32_t img = (grp * 32 + j) * SLOT;
            uint32_t x[16], x0[2];
            float st[4] = {0.f, 0.f, 0.f, 0.f};
            mbar_wait(sb + BAR_FULL + 8 * 4, 0);
#pragma unroll
            for (int q = 3; q < 8; q++) {
                const uint32_t ws = (0x4210u >> (4 * (q & 3))) & 15, as = (0x635u >> (4 * (q % 3))) & 15;
                mbar_wait(sb + BAR_FULL + 8 * as, (q / 3) & 1);
                bar_sync(1 + wg, 256);
                if (q == 3) gemm_issue<false>(s, kd + wg * 512 + as * (SLOT / 16), wd + ws * (SLOT / 16), 1, false);
                else if (q == 4) gemm_issue<true>(o, kd + wg * 512 + as * (SLOT / 16), wd + ws * (SLOT / 16), 0, false);
                else gemm_issue<false>(o, kd + wg * 512 + as * (SLOT / 16), wd + ws * (SLOT / 16), 1, false);
                bar_arrive(2 - wg, 256);
                sched_fence(fph, P.zero);
                if (q > 3) reg_fence(s);
                if (q == 3) {
                    asm volatile("setmaxnreg.inc.sync.aligned.u32 232;");
#pragma unroll
                    for (int i = 0; i < 4; i++)
                        asm volatile("ld.global.nc.v4.u32 {%0, %1, %2, %3}, [%4];" : "=r"(x[4 * i]), "=r"(x[4 * i + 1]), "=r"(x[4 * i + 2]), "=r"(x[4 * i + 3])
                                     : "l"(xp + lane + 32 * i) : "memory");
#pragma unroll
                    for (int i = 0; i < 2; i++) asm volatile("ld.global.nc.u32 %0, [%1];" : "=r"(x0[i]) : "l"(xp + 64 * i) : "memory");
                }
                if (q == 4) {
                    img_store_global<0>(img, toff, s, sc, sc);
#pragma unroll
                    for (int k = 0; k < 16; k++) {
                        const float d0 = bf_lo(x[k]) - bf_lo(x0[k >> 3]), d1 = bf_hi(x[k]) - bf_lo(x0[k >> 3]);
                        st[k >> 3] += d0 + d1;
                        st[2 + (k >> 3)] = fmaf(d0, d0, fmaf(d1, d1, st[2 + (k >> 3)]));
                    }
#pragma unroll
                    for (int i = 0; i < 4 * NSH; i++) st[i & 3] += __shfl_xor_sync(0xffffffffu, st[i & 3], 1 << (i >> 2));
                    reg_fence(st);
                }
                if (q == 5) {
#pragma unroll
                    for (int i = 4 * NSH; i < 20; i++) st[i & 3] += __shfl_xor_sync(0xffffffffu, st[i & 3], 1 << (i >> 2));
                    img_store_global<1>(img, toff, s, sc, sc);
#pragma unroll
                    for (int i = 0; i < 2; i++) {
                        const float d = st[i] * (1.f / 512.f);
                        st[2 + i] = ln_rstd(fmaxf(fmaf(-d, d, st[2 + i] * (1.f / 512.f)), 0.f));
                        x0[i] = pack2(bf_lo(x0[i]) + d, bf_lo(x0[i]) + d);
                    }
                    reg_fence(st);
                    reg_fence(x0);
                }
                if (q > 5) {
                    if (q == 6) mbar_wait(sb + BAR_FLAG + 8 * 8, 0);
                    const uint4 a = lds128(sb + SM_TAB + 1024 + (q & 1) * 512 + lane * 16), c = lds128(sb + SM_TAB + (q & 1) * 512 + lane * 16);
                    uint8_t* hp = g_h + (grp * 8 + (q & 1) * 4 + (lane >> 3)) * 16384 + (xrow & 127) * 128;
#pragma unroll
                    for (int i = 0; i < 2; i++) {
                        const uint32_t* y = x + 8 * i + 4 * (q & 1);
                        *reinterpret_cast<uint4*>(hp + i * 128 + (((lane ^ xrow ^ i) & 7) << 4)) =
                            make_uint4(ln_apply(y[0], x0[i], st[2 + i], a.x, c.x), ln_apply(y[1], x0[i], st[2 + i], a.y, c.y),
                                       ln_apply(y[2], x0[i], st[2 + i], a.z, c.z), ln_apply(y[3], x0[i], st[2 + i], a.w, c.w));
                    }
                    if (q == 7) {
                        __syncwarp();
                        mbar_arrive_if(sb + BAR_DONE, lane == 0);
                    }
                    if (q == 6) img_store_global<2>(img, toff, s, sc, sc);
                    else img_store_global<3>(img, toff, s, sc, sc);
                }
                if (q < 7) {
                    sched_fence(fph, P.zero);
                    wg_wait<0>();
                    release_if(eb, as, rel);
                }
            }
        }
        uint32_t pend = 0x73;
        uint32_t p[32] = {};
#pragma unroll 1
        for (int hp = 0; hp < 2; hp++) {
            float m[2] = {0.f, 0.f}, l[2] = {0.f, 0.f}, t[4] = {0.f, 0.f, 0.f, 0.f};
            bool shifted = false, bad = false, plain = false;
            uint32_t qa = desc_k(sb + 5 * SLOT + (wg ^ 1) * 8192);
            const uint32_t limg = (512 + (15 - j) * 32 + 2 * grp + hp) * SLOT;
            {
                const int step = hp ? -8 * SLOT : 8 * SLOT;
                uint32_t img = (grp * 32 + (hp ? j ^ 30 : j) + 8) * SLOT;
                const uint32_t wtab = w_table(hp);
                uint32_t atab = hp ? 0x562u : 0x356u;
#pragma unroll 1
                for (int u = 2 - 2 * hp; u < 6; u += 2) {
                    proj_tile<false>(s, o, u, !u, sb, wg, eb, rel, fph, wtab, atab, pend, u ? img : cimg, toff, u ? sc : li[0], u ? sc : li[1], p);
                    __syncwarp();
                    mbar_arrive_if(sb + BAR_DONE + 4 * u + 32 * hp, lane == 0);
                    if (elected) TS(1 + 10 * hp + u + 20 * wg);
                    proj_tile<true>(o, s, u + 1, 0, sb, wg, eb, rel, fph, wtab, atab, pend, img + step, toff, sc, sc, p);
                    if (elected) TS(2 + 10 * hp + u + 20 * wg);
                    img += 2 * step;
                }
            }
            asm volatile("" : "+r"(toff));
            if (elected) TS(6 + 10 * hp + 20 * wg);
            fence_async_smem();
            slot_wait(sb + BAR_FULL, fph, r);
            step_retire(eb, rel, pend);
            reg_fence(o);
            int n = -1;
#pragma unroll 1
            for (;;) {
                while (bad || plain) {
                    float d0 = m[0], d1 = m[1];
                    if (bad) {
                        float a0, a1;
                        softmax_remax(s, m, n == 0 || n == nL, d0, d1, a0, a1);
                        shifted = true;
                        l[0] *= a0;
                        l[1] *= a1;
#pragma unroll
                        for (int i = 0; i < 64; i++) o[i] *= (i & 2) ? a1 : a0;
                    }
#pragma unroll
                    for (int i = 0; i < 64; i++) s[i] -= (i & 2) ? d1 : d0;
                    softmax_exp<0, 16>(s, p, t);
                    t[0] += t[1];
                    t[2] += t[3];
                    bad = !bad && softmax_unsafe(t[0], t[2], false);
                    plain = false;
                }
#pragma unroll 1
                do {
                    l[0] += t[0];
                    l[1] += t[2];
                    if (++n > 16) break;
                    const uint32_t ks = r;
                    uint32_t vs = ring_next(r);
                    r = ring_next(vs);
                    bar_sync(1 + wg, 256);
                    const float x = (float)((warp & 3) * 16 + g - 2 * c4);
                    if (n == hn) {
                        float sh[32];
                        qk_issue(sh, qa, kd + ks * (SLOT / 16));
                        slot_wait(sb + BAR_FULL, fph, vs);
                        pv_issue(o, p, vd + vs * (SLOT / 16), 1, false);
                        bar_arrive(2 - wg, 256);
                        wg_wait<1>();
                        reg_fence(sh);
                        tri_mask_copy(s, sh, x);
                        release_if(eb, ks, rel);
                        release_if(eb, 5 + wg, rel && (!wg || n == 16));
                        if (!wg) qa += SLOT / 16;
                        float e[4 * EARLY];
#pragma unroll
                        for (int i = 0; i < 4 * EARLY; i++) {
                            e[i] = ex2(s[i]);
                            t[i & 3] = i < 4 ? e[i] : t[i & 3] + e[i];
                        }
                        reg_fence(e);
                        slot_wait(sb + BAR_FULL, fph, r);
                        wg_wait<0>();
                        reg_fence(o);
                        reg_fence(e);
                        release_if(eb, vs, rel);
#pragma unroll
                        for (int i = 0; i < 2 * EARLY; i++) p[i] = pack2(e[2 * i], e[2 * i + 1]);
                        softmax_exp<EARLY, 8>(s, p, t);
                        if (wg) {
                            ctx_store(limg, toff, o, rcp(quad_sum(l[0])), rcp(quad_sum(l[1])));
                            __syncwarp();
                            mbar_arrive_if(sb + BAR_DONE + 24 + 32 * hp, lane == 0);
                            l[0] = l[1] = m[0] = m[1] = 0.f;
                            shifted = false;
                        }
                        t[0] += t[1];
                        t[2] += t[3];
                        plain = shifted;
                        if (plain) break;
                        bad = softmax_unsafe(t[0], t[2], wg);
                        continue;
                    }
                    if (n == nL) {
                        qk_issue(s, qa, kd + ks * (SLOT / 16));
                        slot_wait(sb + BAR_FULL, fph, vs);
                        pv_issue(o, p, vd + vs * (SLOT / 16), 1, true);
                        bar_arrive(2 - wg, 256);
                        const float i0 = rcp(quad_sum(l[0])), i1 = rcp(quad_sum(l[1]));
                        wg_wait<1>();
                        reg_fence(s);
                        release_if(eb, ks, rel);
                        release_if(eb, 6, rel && n == 16);
                        tri_mask(s, x);
                        float e[4 * EARLY2];
#pragma unroll
                        for (int i = 0; i < 4 * EARLY2; i++) {
                            e[i] = ex2(s[i]);
                            t[i & 3] = i < 4 ? e[i] : t[i & 3] + e[i];
                        }
                        reg_fence(e);
                        reg_fence(s);
                        reg_fence(t);
                        slot_wait(sb + BAR_FULL, fph, r);
                        sched_fence(fph, P.zero);
                        wg_wait<0>();
                        reg_fence(o);
                        reg_fence(e);
                        release_if(eb, vs, rel);
#pragma unroll
                        for (int i = 0; i < 2 * EARLY2; i++) p[i] = pack2(e[2 * i], e[2 * i + 1]);
                        softmax_exp<EARLY2, MSPLIT>(s, p, t);
                        ctx_store(limg, toff, o, i0, i1);
                        reg_fence(t);
                        reg_fence(s);
                        softmax_exp<MSPLIT, 16>(s, p, t);
                        __syncwarp();
                        mbar_arrive_if(sb + BAR_DONE + 24 + 32 * hp, lane == 0);
                        l[0] = l[1] = m[0] = m[1] = 0.f;
                        shifted = false;
                        t[0] += t[1];
                        t[2] += t[3];
                        bad = __any_sync(0xffffffffu, fmaxf(t[0], t[2]) > SM_HI || fminf(t[0], t[2]) < SM_LO);
                        continue;
                    }
                    qk_issue(s, qa, kd + ks * (SLOT / 16));
                    if (n == 0) {
                        r = vs;
                        vs = 4 - hp;
                        slot_wait(sb + BAR_FULL, fph, 6);
                        gemm_issue<false>(o, qa + SLOT / 16, wd + vs * (SLOT / 16), 1, false);
                    } else {
                        slot_wait(sb + BAR_FULL, fph, vs);
                        if (n == 1) {
                            wg_wait<1>();
                            reg_fence(o);
                            const uint32_t a = sb + 6 * SLOT + q_off(toff);
#pragma unroll
                            for (int i = 0; i < 8; i++) {
                                const int k = 16 * (i >> 1) + 2 * (i & 1);
                                sts128(a + (i >> 2) * 16384 + (i & 2) * 256 + (i & 1) * 1024,
                                       make_uint4(pack2(o[k], o[k + 1]), pack2(o[k + 4], o[k + 5]), pack2(o[k + 8], o[k + 9]), pack2(o[k + 12], o[k + 13])));
                            }
                        }
                        pv_issue(o, p, vd + vs * (SLOT / 16), n != 1 && n != nL + 1, n == hn + 1);
                    }
                    bar_arrive(2 - wg, 256);
                    wg_wait<1>();
                    reg_fence(s);
                    release_if(eb, ks, rel);
                    release_if(eb, 6, rel && n == 16);
                    if (n == nL - 1) {
                        tri_mask(s, x);
                        release_if(eb, 5, rel);
                        qa += SLOT / 16;
                    }
                    if (n == 2) fence_async_smem();
                    if (shifted) {
                        slot_wait(sb + BAR_FULL, fph, r);
                        wg_wait<0>();
                        reg_fence(o);
                        release_if(eb, vs, rel);
                        plain = true;
                        break;
                    }
                    float e[4 * EARLY];
#pragma unroll
                    for (int i = 0; i < 4 * EARLY; i++) {
                        e[i] = ex2(s[i]);
                        t[i & 3] = i < 4 ? e[i] : t[i & 3] + e[i];
                    }
                    reg_fence(e);
                    slot_wait(sb + BAR_FULL, fph, r);
                    wg_wait<0>();
                    reg_fence(o);
                    reg_fence(e);
                    release_if(eb, vs, rel);
#pragma unroll
                    for (int i = 0; i < 2 * EARLY; i++) p[i] = pack2(e[2 * i], e[2 * i + 1]);
                    softmax_exp<EARLY, 16>(s, p, t);
                    t[0] += t[1];
                    t[2] += t[3];
                    bad = __any_sync(0xffffffffu, fmaxf(t[0], t[2]) > SM_HI || (n == 0 && fminf(t[0], t[2]) < SM_LO));
                } while (!bad);
                if (!bad && !plain) break;
            }
            asm volatile("" : "+r"(toff));
            const uint32_t vs = r, ga = desc_k(sb + (hp ? 2 * (wg ^ kh ^ 1) : wg) * 8192);
            r = ring_next(r);
            slot_wait(sb + BAR_FULL, fph, 5);
            slot_wait(sb + BAR_FULL, fph, r);
            bar_sync(1 + wg, 256);
            gemm_issue<true>(s, ga + 5 * (SLOT / 16), wd + r * (SLOT / 16), 0, hp);
            pv_issue(o, p, vd + vs * (SLOT / 16), j, hn == 16);
            bar_arrive(2 - wg, 256);
            li[0] = rcp(quad_sum(l[0]));
            li[1] = rcp(quad_sum(l[1]));
            cimg = limg + (2 * j - 15) * 32 * SLOT + (wg ? -16384 : 16384);
            wg_wait<1>();
            release_if(eb, 5, rel);
            release_if(eb, r, rel && hp);
            wg_wait<0>();
            release_if(eb, vs, rel);
            reg_fence(o);
            img_store_global<0>(cimg, toff, o, li[0], li[1]);
            pend = 0x77;
            if (elected) TS(8 + 10 * hp + 20 * wg);
        }
        uint32_t otab = 0x2351604u;
        const uint32_t oa = desc_k(sb + (wg ^ kh ^ 1) * 16384);
        const int t7 = tid & 127, w4 = warp & 3, row = ort * 128 + kh * 64 + w4 * 16 + g;
#pragma unroll 1
        for (int i = 1; i < 15 - OFF - wg; i++) {
            const uint32_t as = o_next(otab), ws = o_next(otab);
            slot_wait(sb + BAR_FULL, fph, as);
            slot_wait(sb + BAR_FULL, fph, ws);
            bar_sync(1 + wg, 256);
            gemm_issue<false>(s, oa + as * (SLOT / 16), wd + ws * (SLOT / 16), 1, true);
            bar_arrive(2 - wg, 256);
            wg_wait<1>();
            reg_fence(o);
            if (i == 1) img_store_global<1>(cimg, toff, o, li[0], li[1]);
            if (i == 2) {
                img_store_global<2>(cimg, toff, o, li[0], li[1]);
                img_store_global<3>(cimg, toff, o, li[0], li[1]);
                __syncwarp();
                mbar_arrive_if(sb + BAR_DONE + 64, lane == 0);
            }
            wg_wait<0>();
            release_if(eb, as, rel);
            release_if(eb, ws, rel);
        }
        mbar_wait(sb + BAR_PF, 0);
        const uint32_t ep = lds32(sb + SM_EP);
        uint32_t eb2 = sb + BAR_END;
        if (wg == 0) {
            reg_fence(s);
            if (elected) TS(9);
            TT(1);
#pragma unroll
            for (int v = 0; v < 8; v++)
                st_pub(g_out + rb * OB + v * 128 + t7, make_uint4((pack2(s[8 * v], s[8 * v + 1]) & ~1u) | (ep & 1), pack2(s[8 * v + 2], s[8 * v + 3]),
                                                                      pack2(s[8 * v + 4], s[8 * v + 5]), pack2(s[8 * v + 6], s[8 * v + 7])), true);
            constexpr uint32_t s1 = SL_WF, s2 = SL_WD;
            bar_sync(4, 256);
            uint32_t wf[64];
            float wn[64];
            if (rb < NFFN) {
                slot_wait(sb + BAR_FULL, fph, s1);
                const uint32_t a = sb + s1 * SLOT + (w4 * 128 + (lane >> 4) * 8 + (lane & 7)) * 32 + (((lane >> 3) ^ (lane >> 2)) & 1) * 16;
#pragma unroll
                for (int i = 0; i < 16; i++)
                    asm volatile("ldmatrix.sync.aligned.m8n8.x4.trans.shared.b16 {%0, %1, %2, %3}, [%4];"
                                 : "=r"(wf[4 * i]), "=r"(wf[4 * i + 1]), "=r"(wf[4 * i + 2]), "=r"(wf[4 * i + 3])
                                 : "r"(a + (i >> 3) * 16384 + (i & 7) * 512) : "memory");
                slot_wait(sb + BAR_FULL, fph, s2);
#pragma unroll
                for (int i = 0; i < 16; i++) {
                    const uint2 w = *reinterpret_cast<const uint2*>(smem + s2 * SLOT + (kh ^ 1) * 16384 + i * 1024 + t7 * 8);
                    wn[4 * i] = bf_lo(w.x); wn[4 * i + 1] = bf_hi(w.x); wn[4 * i + 2] = bf_lo(w.y); wn[4 * i + 3] = bf_hi(w.y);
                }
                reg_fence(wn);
            }
            const uint32_t gbf = __ldcg(reinterpret_cast<const uint32_t*>(g_mod) + 1280 + rb * 2 + (lane >> 4));
            if (elected) TS(10);
            TT(2);
            const int pq = (2 * rb + (lane >> 4)) & 63, pv = (pq >> 2) / 3, cm = (pq >> 2) - 3 * pv;
            const uint4* cp = g_cand + w4 * 24 + c4;
            const uint4* fp = g_cand + (rb >> 5) * 24 + pv * 4 + (pq & 3);
            const uint4* yp = g_out + lane * OB + OB_Y + rb;
            uint4* yo = g_out + rb * OB + OB_Y + t7;
            uint32_t* op = reinterpret_cast<uint32_t*>(P.out) + rb * 2 + (lane >> 4);
            uint32_t ra = sb + SM_RED + (w4 * 32 + c4 * 8 + g) * 4;
            asm volatile("" : "+l"(cp), "+l"(fp), "+l"(yp), "+l"(yo), "+l"(op), "+r"(ra));
            sched_fence(eb2, P.zero);
            if (warp == 0) {
                asm volatile("st.shared.u32 [%0], %1;" ::"r"(sb + SM_EP + 24), "r"(best_key(g_out + ((rb & 33) + (lane & 15) * 2 + (lane & 16) * 4) * OB + OB_KEY, ep)) : "memory");
                mbar_arrive_if(sb + BAR_BEST, lane == 0);
            }
            bar_sync(3, 128);
            const uint32_t best = lds32(sb + SM_EP + 24), co = ((~best >> 9) & 127) * 192;
            TT(3);
            if (rb < NFFN) {
                uint4 cv[6];
                for (;;) {
                    uint32_t bad = 0;
#pragma unroll
                    for (int v = 0; v < 6; v++) cv[v] = ld_poll(cp + co + v * 4);
#pragma unroll
                    for (int v = 0; v < 6; v++) bad |= cv[v].w ^ ep;
                    if (__all_sync(0xffffffffu, bad == 0)) break;
                }
                TT(4);
                float d[4][4] = {};
#pragma unroll
                for (int k = 0; k < 8; k++) {
                    const uint32_t b0 = (&cv[(2 * k) / 3].x)[(2 * k) % 3], b1 = (&cv[(2 * k + 1) / 3].x)[(2 * k + 1) % 3];
                    mma16816(d[k & 1], wf + 4 * k, b0, b1);
                    mma16816(d[2 + (k & 1)], wf + 32 + 4 * k, b0, b1);
                }
                float u[4] = {d[0][0] + d[1][0], d[0][2] + d[1][2], d[2][0] + d[3][0], d[2][2] + d[3][2]};
                reg_fence(u);
                asm volatile("st.shared.f32 [%0], %1;" ::"r"(ra), "f"((c4 & 2) ? ((c4 & 1) ? u[3] : u[2]) : ((c4 & 1) ? u[1] : u[0])) : "memory");
                bar_sync(3, 128);
                const float* sred = reinterpret_cast<const float*>(smem + SM_RED);
                const float v = rbf((sred[lane] + sred[32 + lane]) + (sred[64 + lane] + sred[96 + lane]));
                const float act = rbf(rbf(v * sigmoid(v)) * __shfl_down_sync(0xffffffffu, v, 16));
                float y[4] = {0.f, 0.f, 0.f, 0.f};
#pragma unroll
                for (int k = 0; k < 16; k++) {
                    const float a = __shfl_sync(0xffffffffu, act, k);
#pragma unroll
                    for (int i = 0; i < 4; i++) y[i] = fmaf(a, wn[4 * k + i], y[i]);
                }
                st_pub(yo, make_uint4((__float_as_uint(y[0]) & ~15u) | (ep & 15), __float_as_uint(y[1]), __float_as_uint(y[2]), __float_as_uint(y[3])), true);
            }
            TT(5);
            if (warp == 0) {
                if (rb == 0 && lane == 0) g_sync.epoch[0] = ep;
                uint4 fh, fx;
                do { fh = ld_poll(fp + co); fx = ld_poll(fp + co + 96); } while (!poll_done(fh.w == ep && fx.w == ep, 50));
                const float sg = sigmoid(bf_hi((best & 0x80000000u) ? (best ^ 0x80000000u) : ~best));
                uint32_t fin[3] = {cm == 0 ? fh.x : cm == 1 ? fh.y : fh.z, cm == 0 ? fx.x : cm == 1 ? fx.y : fx.z, pack2(sg, sg)};
                op += ((~best >> 5) & 2047) * 256;
                asm volatile("" : "+l"(op));
                reg_fence(fin);
                if (rb >= NFFN) __nanosleep(YPRE);
                sched_fence(eb2, P.zero);
                uint4 yv[4];
                for (;;) {
#pragma unroll
                    for (int k = 0; k < 4; k++) yv[k] = ld_poll(yp + (k < 3 || lane < 16 ? k : 2) * 32 * OB);
                    if (poll_done((((yv[0].x ^ ep) | (yv[1].x ^ ep) | (yv[2].x ^ ep) | (yv[3].x ^ ep)) & 15) == 0, YSLEEP)) break;
                }
                TT(6);
                mbar_arrive_if(eb2, lane == 0);
                float y[4];
#pragma unroll
                for (int i = 0; i < 4; i++) {
                    const uint32_t mk = i ? ~0u : ~15u;
                    y[i] = (__uint_as_float((&yv[0].x)[i] & mk) + __uint_as_float((&yv[1].x)[i] & mk)) +
                           (__uint_as_float((&yv[2].x)[i] & mk) + (lane < 16 ? __uint_as_float((&yv[3].x)[i] & mk) : 0.f));
                }
                float z0 = ((lane & 16) ? y[2] : y[0]) + __shfl_xor_sync(0xffffffffu, (lane & 16) ? y[0] : y[2], 16);
                float z1 = ((lane & 16) ? y[3] : y[1]) + __shfl_xor_sync(0xffffffffu, (lane & 16) ? y[1] : y[3], 16);
#pragma unroll
                for (int o = 8; o > 0; o >>= 1) {
                    z0 += __shfl_xor_sync(0xffffffffu, z0, o);
                    z1 += __shfl_xor_sync(0xffffffffu, z1, o);
                }
                if ((lane & 15) == 0) *op = badd(fin[1], bmul(gbf, badd(fin[0], bmul(pack2(z0, z1), fin[2]))));
            }
            if (elected) TS(62);
            TT(7);
        } else {
            const float4* tf = reinterpret_cast<const float4*>(smem + SM_TAB) + c4;
            uint32_t x2[32];
            float tc[48];
#pragma unroll
            for (int k = 0; k < 16; k++) {
                const float4 c = tf[k * 4];
                tc[3 * k] = c.x; tc[3 * k + 1] = c.y; tc[3 * k + 2] = (g & 1) ? c.z : __uint_as_float(ONE2);
            }
            reg_fence(tc);
            bar_sync(2, 256);
#pragma unroll 1
            for (int i = 14; i < 17; i++) {
                const uint32_t as = o_next(otab), ws = o_next(otab);
                slot_wait(sb + BAR_FULL, fph, as);
                slot_wait(sb + BAR_FULL, fph, ws);
                gemm_issue<false>(s, oa + as * (SLOT / 16), wd + ws * (SLOT / 16), 1, true);
                wg_wait<1>();
            }
            const uint4* pr = g_out + (rb ^ 16) * OB + t7;
            uint4 pa[8];
            if (elected) TS(29);
            TT(1);
#pragma unroll
            for (int k = 0; k < 8; k++) {
                const uint4 v = lds128(sb + SL_X * SLOT + (kh ^ 1) * 16384 + k * 2048 + t7 * 16);
                x2[4 * k] = v.x; x2[4 * k + 1] = v.y; x2[4 * k + 2] = v.z; x2[4 * k + 3] = v.w;
            }
            wg_wait<0>();
            reg_fence(s);
            bar_arrive(4, 256);
            if (elected) TS(39);
            TT(2);
#pragma unroll
            for (int v = 0; v < 8; v++) pa[v] = ld_poll(pr + v * 128);
#pragma unroll
            for (int i = 0; i < 64; i++) s[i] = fmaf(tc[3 * (i >> 2) + (i & 1)], s[i], (i & 1) ? bf_hi(x2[i >> 1]) : bf_lo(x2[i >> 1]));
            reg_fence(s);
            sched_fence(eb2, P.zero);
            for (;;) {
                uint32_t bad = 0;
#pragma unroll
                for (int v = 0; v < 8; v++) asm("lop3.b32 %0, %0, %1, %2, 0xf6;" : "+r"(bad) : "r"(pa[v].x), "r"(ep));
                if (__all_sync(0xffffffffu, (bad & 1) == 0)) break;
                if (PSLEEP) __nanosleep(PSLEEP);
#pragma unroll
                for (int v = 0; v < 8; v++) pa[v] = ld_poll(pr + v * 128);
            }
            if (elected) TS(30);
            TT(3);
            float sd[4] = {}, q0[4] = {}, q1[4] = {};
#pragma unroll
            for (int k = 0; k < 8; k++) {
#pragma unroll
                for (int i = 4 * k; i < 4 * k + 4; i++) {
                    const uint32_t w = (i & 3) ? (&pa[k].x)[i & 3] : pa[k].x & ~1u;
                    x2[i] = pack2(fmaf(tc[3 * (i >> 1)], bf_lo(w), s[2 * i]), fmaf(tc[3 * (i >> 1) + 1], bf_hi(w), s[2 * i + 1]));
                }
                mma16816(sd, x2 + 4 * k, __float_as_uint(tc[6 * k + 2]), __float_as_uint(tc[6 * k + 5]));
                mma16816(q0, x2 + 4 * k, x2[4 * k], x2[4 * k + 2]);
                mma16816(q1, x2 + 4 * k, x2[4 * k + 1], x2[4 * k + 3]);
            }
            uint4* sp = g_out + rb * OB + OB_STAT + (w4 * 8 + g) * 2;
            st_pub(sp, make_uint4(__float_as_uint(sd[0]), __float_as_uint((g & 1) ? q0[1] : q0[0]), __float_as_uint(sd[1]), ep), c4 == g >> 1);
            st_pub(sp + 1, make_uint4(__float_as_uint(sd[2]), __float_as_uint((g & 1) ? q1[3] : q1[2]), __float_as_uint(sd[3]), ep), c4 == g >> 1);
            sched_fence(eb2, P.zero);
            if (elected) TS(56);
            TT(4);
            uint32_t cb[16], sh[16], gb[16];
#pragma unroll
            for (int i = 0; i < 16; i++) {
                const float4 c = tf[64 + i * 4];
                cb[i] = __float_as_uint(c.x); sh[i] = __float_as_uint(c.y); gb[i] = __float_as_uint(c.z);
            }
            const float ra = __uint_as_float(lds32(sb + SM_EP + 8)), rb0 = __uint_as_float(lds32(sb + SM_EP + 12));
            const uint4* rp = g_out + ((rb & ~33) + (c4 & 1) + (c4 & 2) * 16) * OB + OB_STAT + (w4 * 8 + g) * 2;
            uint32_t* kp = &g_out[rb * OB + OB_KEY].x + w4;
            uint4* cp = g_cand + (row >> 4) * 192 + cq * 24 + c4;
            uint32_t kt = ((2047 - row) << 5) | (ep & 31);
            asm volatile("" : "+l"(kp), "+l"(cp), "+r"(kt));
            uint4 r0, r1;
            do {
                r0 = ld_poll(rp);
                r1 = ld_poll(rp + 1);
            } while (!poll_done(r0.w == ep && r1.w == ep, SSLEEP));
            if (elected) TS(57);
            TT(5);
            float st[6] = {__uint_as_float(r0.x), __uint_as_float(r1.x), __uint_as_float(r0.y), __uint_as_float(r1.y), __uint_as_float(r0.z), __uint_as_float(r1.z)};
#pragma unroll
            for (int i = 0; i < 12; i++) st[i % 6] += __shfl_xor_sync(0xffffffffu, st[i % 6], 1 + i / 6);
            const float m0 = st[0] * (1.f / 512.f), m1 = st[1] * (1.f / 512.f);
            const float rs0 = ln_rstd(fmaxf(fmaf(-m0, m0, st[2] * (1.f / 512.f)), 0.f));
            const float rs1 = ln_rstd(fmaxf(fmaf(-m1, m1, st[3] * (1.f / 512.f)), 0.f));
            const uint32_t mb0 = pack2(m0, m0), mb1 = pack2(m1, m1);
            const uint32_t lg = pack2(fmaf(rs0, fmaf(-bf_lo(mb0), ra, st[4]), rb0), fmaf(rs1, fmaf(-bf_lo(mb1), ra, st[5]), rb0));
            const uint32_t u0 = lg << 16, u1 = lg & 0xffff0000u;
            const uint32_t k0 = ((u0 ^ (((int)u0 >> 31) | 0x80000000u)) & 0xffff0000u) | kt;
            const uint32_t k1 = ((u1 ^ (((int)u1 >> 31) | 0x80000000u)) & 0xffff0000u) | (kt - 256);
            const uint32_t kb = __reduce_max_sync(0xffffffffu, max(k0, k1));
            st_pub(kp, kb, lane == 0);
            const bool cand = kb == k0 || kb == k1;
#pragma unroll 1
            for (int it = 0; it < 3; it++) {
                bool put = it == 1 || !cand;
                if (it == 2) {
                    mbar_wait(sb + BAR_BEST, 0);
                    put = cand && lds32(sb + SM_EP + 24) != kb;
                }
                const bool hi = (kb == k1) != (it == 1);
                uint32_t cx[18], ch[18];
#pragma unroll
                for (int i = 0; i < 16; i++) {
                    cx[i] = hi ? x2[2 * i + 1] : x2[2 * i];
                    ch[i] = ln_apply(cx[i], hi ? mb1 : mb0, hi ? rs1 : rs0, cb[i], sh[i]);
                }
                cx[16] = cx[17] = ch[16] = ch[17] = 0;
#pragma unroll
                for (int v = 0; v < 6; v++) st_pub(cp + v * 4, make_uint4(ch[3 * v], ch[3 * v + 1], ch[3 * v + 2], ep), cand && it == 0);
#pragma unroll
                for (int v = 0; v < 6; v++) st_pub(cp + 96 + v * 4, make_uint4(cx[3 * v], cx[3 * v + 1], cx[3 * v + 2], ep), cand && it == 0);
                if (it == 0) TT(6);
                uint2* op = reinterpret_cast<uint2*>(P.out) + (row + 8 * hi) * 128 + cq * 32 + (c4 & 1) * 2 + (c4 >> 1);
#pragma unroll
                for (int i = 0; i < 16; i += 2) {
                    const uint32_t v0 = badd(cx[i], bmul(gb[i], ch[i])), v1 = badd(cx[i + 1], bmul(gb[i + 1], ch[i + 1]));
                    const uint32_t rv = __shfl_xor_sync(0xffffffffu, (c4 & 1) ? v0 : v1, 1);
                    if (put) op[i * 2] = (c4 & 1) ? make_uint2(rv, v1) : make_uint2(v0, rv);
                }
            }
            if (elected) TS(59);
            TT(7);
        }
        mbar_arrive_if(eb2, lane == 0 && warp != 0);
    }
}

typedef CUresult (*EncodeFn)(CUtensorMap*, CUtensorMapDataType, cuuint32_t, void*, const cuuint64_t*, const cuuint64_t*,
                             const cuuint32_t*, const cuuint32_t*, CUtensorMapInterleave, CUtensorMapSwizzle,
                             CUtensorMapL2promotion, CUtensorMapFloatOOBfill);

void make_3d(EncodeFn fn, CUtensorMap* m, const void* p, uint64_t cols, uint64_t rows, uint32_t br = 128, uint32_t nb = 2) {
    cuuint64_t dims[3] = {64, rows, cols / 64}, strides[2] = {cols * 2, 128};
    cuuint32_t box[3] = {64, br, nb}, es[3] = {1, 1, 1};
    fn(m, CU_TENSOR_MAP_DATA_TYPE_BFLOAT16, 3, const_cast<void*>(p), dims, strides, box, es, CU_TENSOR_MAP_INTERLEAVE_NONE,
       CU_TENSOR_MAP_SWIZZLE_128B, CU_TENSOR_MAP_L2_PROMOTION_L2_256B, CU_TENSOR_MAP_FLOAT_OOB_FILL_NONE);
}

}

extern "C" void kernel_launch(void* const* d_in, const int* in_sizes, int n_in, void* d_out, int out_size) {
    static EncodeFn fn = nullptr;
    if (!fn) {
        void* f = nullptr;
        cudaDriverEntryPointQueryResult st;
        cudaGetDriverEntryPoint("cuTensorMapEncodeTiled", &f, cudaEnableDefault, &st);
        fn = (EncodeFn)f;
        cudaFuncSetAttribute(fused_kernel, cudaFuncAttributeMaxDynamicSharedMemorySize, SMEM_BYTES);
    }
    CUtensorMap ckv, wq, wuk, wuv, wo, wg, wu, wm, xm;
    make_3d(fn, &ckv, d_in[1], 512, 2048, 128, 1);
    make_3d(fn, &xm, d_in[0], 512, 2048, 64);
    make_3d(fn, &wq, d_in[2], 4096, 512);
    make_3d(fn, &wuk, d_in[3], 4096, 512);
    make_3d(fn, &wuv, d_in[4], 4096, 512);
    make_3d(fn, &wo, d_in[5], 512, 4096);
    make_3d(fn, &wg, d_in[8], 1792, 512, 256, 1);
    make_3d(fn, &wu, d_in[9], 1792, 512, 256, 1);
    make_3d(fn, &wm, d_in[12], 3072, 512, 64, 4);
    Params p;
    p.x = (const bf16*)d_in[0];
    p.ckv = (const bf16*)d_in[1];
    p.wo = (const bf16*)d_in[5];
    p.wr = (const bf16*)d_in[7];
    p.wdown = (const bf16*)d_in[10];
    p.c = (const bf16*)d_in[11];
    p.out = (bf16*)d_out;
    p.zero = 0;
    fused_kernel<<<NCTA + NSPARE, 384, SMEM_BYTES>>>(ckv, wq, wuk, wuv, wo, wg, wu, wm, xm, p);
}
```
